```python
import torch

def _softmax(x, axis=-1):
    return torch.softmax(x, dim=axis)

def _gelu(x):
    return torch.nn.functional.gelu(x, approximate='tanh')

def _silu(x):
    return torch.nn.functional.silu(x)

def _sigmoid(x):
    return torch.sigmoid(x)

def _layernorm(x, axis=-1, eps=1e-05):
    m = x.mean(dim=axis, keepdim=True)
    v = x.var(dim=axis, keepdim=True, unbiased=False)
    return (x - m) / torch.sqrt(v + eps)

def _scatter_add(tgt, idx, src, axis=0):
    return tgt.clone().index_add_(axis, idx, src)

def _segment_sum(src, seg, n):
    out = torch.zeros((n,) + src.shape[1:], dtype=src.dtype)
    return out.index_add_(0, seg, src)

def _pad(x, pw):
    flat = tuple((v for pair in reversed(pw) for v in pair))
    return torch.nn.functional.pad(x, flat)
kernel_name = 'adaLN_cond__memory_aug_recurrent_mem_tr__glu_gated_geglu__prompt'

def setup_inputs():

    _w = lambda a: (lambda t: t.to(torch.bfloat16) if t.is_floating_point() else t)(torch.as_tensor(a))

    def _A_setup():
        B, S, Dm = (1, 2048, 512)
        H, Dh = (32, 128)
        M, seg = (8, 32)
        seg = min(seg, S)
        S = S // seg * seg
        return {'x': _w((lambda *s: torch.randn(*s, dtype=torch.bfloat16) * 0.05)(B, S, Dm)), 'mem0': _w((lambda *s: torch.randn(*s, dtype=torch.bfloat16) * 0.8)(B, M, Dm)), 'Wq': _w((lambda *s: torch.randn(*s, dtype=torch.bfloat16) * 1.6)(Dm, H, Dh) * Dm ** (-0.5)), 'Wk': _w((lambda *s: torch.randn(*s, dtype=torch.bfloat16) * 1.6)(Dm, H, Dh) * Dm ** (-0.5)), 'Wv': _w((lambda *s: torch.randn(*s, dtype=torch.bfloat16) * 0.8)(Dm, H, Dh) * Dm ** (-0.5)), 'Wo': _w((lambda *s: torch.randn(*s, dtype=torch.bfloat16) * 0.8)(H, Dh, Dm) * (H * Dh) ** (-0.5)), 'seg_len': seg}
    _A_in = _A_setup()

    def _B_setup():
        B, S, Dm, Df = (1, 2048, 512, 1792)
        return {'x': _w((lambda *s: torch.randn(*s, dtype=torch.bfloat16) * 0.05)(B, S, Dm)), 'w_gate': _w((lambda *s: torch.randn(*s, dtype=torch.bfloat16) * 0.8)(Dm, Df) * Dm ** (-0.5)), 'w_up': _w((lambda *s: torch.randn(*s, dtype=torch.bfloat16) * 0.8)(Dm, Df) * Dm ** (-0.5)), 'w_down': _w((lambda *s: torch.randn(*s, dtype=torch.bfloat16) * 0.8)(Df, Dm) * Df ** (-0.5))}
    _B_in = _B_setup()
    return {'A_x': _A_in['x'], 'A_mem0': _A_in['mem0'], 'A_Wq': _A_in['Wq'], 'A_Wk': _A_in['Wk'], 'A_Wv': _A_in['Wv'], 'A_Wo': _A_in['Wo'], 'A_seg_len': _A_in['seg_len'], 'B_x': _B_in['x'], 'B_w_gate': _B_in['w_gate'], 'B_w_up': _B_in['w_up'], 'B_w_down': _B_in['w_down'], 'c': _w((lambda *s: torch.randn(*s, dtype=torch.bfloat16) * 0.1)(1, 512) * 8.0), 'w_mod': _w((lambda *s: torch.randn(*s, dtype=torch.bfloat16) * 0.1)(512, 6 * 512) * 512 ** (-0.5) * 8.0)}

def reference(A_x, A_mem0, A_Wq, A_Wk, A_Wv, A_Wo, A_seg_len, B_x, B_w_gate, B_w_up, B_w_down, c, w_mod):

    def _A_ref(x, mem0, Wq, Wk, Wv, Wo, seg_len):
        B, S, Dm = x.shape
        H, Dh = (Wq.shape[1], Wq.shape[2])
        M = mem0.shape[1]
        scale = Dh ** (-0.5)
        n_seg = S // seg_len
        L = M + seg_len
        idx = torch.arange(L)
        mask = (idx[:, None] < M) | (idx[:, None] >= idx[None, :])
        mem = mem0
        outs = []
        for s in range(n_seg):
            xs = x[:, s * seg_len:(s + 1) * seg_len, :].clone()
            h = torch.concatenate([mem, xs], axis=1)
            q = torch.einsum('btd,dhe->bhte', h, Wq)
            k = torch.einsum('btd,dhe->bhte', h, Wk)
            v = torch.einsum('btd,dhe->bhte', h, Wv)
            scores = torch.einsum('bhqe,bhke->bhqk', q, k) * scale
            scores = torch.where(mask[None, None], scores, -1000000000.0)
            p = _softmax(scores, axis=-1)
            o = torch.einsum('bhqk,bhke->bhqe', p, v)
            o = torch.einsum('bhte,hed->btd', o, Wo)
            mem = o[:, :M, :].clone()
            outs.append(o[:, M:, :])
        return torch.concatenate(outs, axis=1)

    def _B_ref(x, w_gate, w_up, w_down):
        g = torch.einsum('bsd,df->bsf', x, w_gate)
        u = torch.einsum('bsd,df->bsf', x, w_up)
        h = _gelu(g) * u
        return torch.einsum('bsf,fd->bsd', h, w_down)
    x = A_x
    mod = (_silu(c) @ w_mod).reshape(c.shape[0], 6, 1, -1)
    sa, ca, ga, sb, cb, gb = (mod[:, 0].clone(), mod[:, 1].clone(), mod[:, 2].clone(), mod[:, 3].clone(), mod[:, 4].clone(), mod[:, 5].clone())
    h = _layernorm(x, axis=-1) * (1 + ca) + sa
    x = x + ga * _A_ref(h, A_mem0, A_Wq, A_Wk, A_Wv, A_Wo, A_seg_len)
    h = _layernorm(x, axis=-1) * (1 + cb) + sb
    x = x + gb * _B_ref(h, B_w_gate, B_w_up, B_w_down)
    return x
```

```cpp
#include <cuda_runtime.h>
#include <cuda_bf16.h>
#include <cuda.h>
#include <stdint.h>

typedef __nv_bfloat16 bf16;

constexpr int S_ = 2048, D_ = 512, H_ = 32, DH_ = 128, HD_ = 4096, NSEG = 64, DF_ = 1792;
constexpr int NRB = 16;
constexpr int OSPLIT = 4;

__device__ __align__(1024) bf16 g_h[S_ * D_];
__device__ __align__(1024) bf16 g_kv[S_ * 2 * HD_];
__device__ __align__(1024) bf16 g_kvm[NSEG * 8 * 2 * HD_];
__device__ __align__(1024) bf16 g_o[S_ * HD_];
__device__ __align__(1024) bf16 g_op[OSPLIT * S_ * D_];
__device__ __align__(1024) bf16 g_x1[S_ * D_];
__device__ __align__(1024) bf16 g_h2[S_ * D_];
__device__ __align__(1024) bf16 g_act[S_ * DF_];
__device__ __align__(1024) float g_mod[6 * D_];
__device__ uint32_t g_Fraw[131072 + 65536 + 2048];
#define g_F ((uint32_t*)(((uint64_t)g_Fraw + 0x7FFFFull) & ~0x7FFFFull))
constexpr int F_KV = 0, F_MEM = 16, F_O = 80, F_OP = 96, F_H2 = 112, F_ACT = 128, F_JOB = 144, F_SIDE = 145  , F_TOTAL = 160;
__device__ __align__(128) unsigned int g_flags[F_TOTAL * 32];
#define TR(j, i) do {} while (0)

__device__ __forceinline__ uint32_t smem_u32(const void* p) { return (uint32_t)__cvta_generic_to_shared(p); }
__device__ __forceinline__ uint32_t clk32() { uint32_t c; asm volatile("mov.u32 %0, %%clock;" : "=r"(c)); return c; }
__device__ __forceinline__ uint32_t mapa_u32(uint32_t addr, uint32_t rank) {
    uint32_t r; asm volatile("mapa.shared::cluster.u32 %0, %1, %2;" : "=r"(r) : "r"(addr), "r"(rank)); return r;
}
__device__ __forceinline__ void mbar_init(uint32_t bar, uint32_t cnt) {
    asm volatile("mbarrier.init.shared::cta.b64 [%0], %1;" :: "r"(bar), "r"(cnt) : "memory");
}
__device__ __forceinline__ void mbar_inval(uint32_t bar) {
    asm volatile("mbarrier.inval.shared::cta.b64 [%0];" :: "r"(bar) : "memory");
}
__device__ __forceinline__ void mbar_expect_tx(uint32_t bar, uint32_t bytes) {
    asm volatile("mbarrier.arrive.expect_tx.shared::cta.b64 _, [%0], %1;" :: "r"(bar), "r"(bytes) : "memory");
}
__device__ __forceinline__ void mbar_arrive(uint32_t bar) {
    asm volatile("mbarrier.arrive.shared::cta.b64 _, [%0];" :: "r"(bar) : "memory");
}
__device__ __forceinline__ bool mbar_try_wait(uint32_t bar, uint32_t parity) {
    uint32_t ok;
    asm volatile("{\n.reg .pred p;\nmbarrier.try_wait.parity.shared::cta.b64 p, [%1], %2;\nselp.u32 %0, 1, 0, p;\n}"
                 : "=r"(ok) : "r"(bar), "r"(parity) : "memory");
    return ok;
}
__device__ __forceinline__ bool mbar_try_wait_cluster(uint32_t bar, uint32_t parity) {
    uint32_t ok;
    asm volatile("{\n.reg .pred p;\nmbarrier.try_wait.parity.acquire.cluster.shared::cta.b64 p, [%1], %2;\nselp.u32 %0, 1, 0, p;\n}"
                 : "=r"(ok) : "r"(bar), "r"(parity) : "memory");
    return ok;
}
constexpr int SPIN_LIMIT = 1 << 18;
#define TIMEOUT(code, info) do {} while (0)
__device__ __forceinline__ void mbar_wait(uint32_t bar, uint32_t parity) {
    int g = 0;
#pragma unroll 1
    while (!mbar_try_wait(bar, parity)) { if (++g >= SPIN_LIMIT) { TIMEOUT(0, bar & 255); break; } }
}
__device__ __forceinline__ void mbar_wait_cluster(uint32_t bar, uint32_t parity) {
    int g = 0;
#pragma unroll 1
    while (!mbar_try_wait_cluster(bar, parity)) { if (++g >= SPIN_LIMIT) { TIMEOUT(1, bar & 255); break; } }
}
__device__ __forceinline__ void bar_sync(int id, int n) { asm volatile("bar.sync %0, %1;" :: "r"(id), "r"(n) : "memory"); }
__device__ __forceinline__ void bar_arrive(int id, int n) { asm volatile("bar.arrive %0, %1;" :: "r"(id), "r"(n) : "memory"); }
__device__ __forceinline__ void cluster_sync_all() {
    asm volatile("barrier.cluster.arrive.aligned;\nbarrier.cluster.wait.aligned;" ::: "memory");
}
__device__ __forceinline__ void st_async_v2(uint32_t addr, float a, float b, uint32_t bar) {
    asm volatile("st.async.weak.shared::cluster.mbarrier::complete_tx::bytes.v2.f32 [%0], {%1,%2}, [%3];"
                 :: "r"(addr), "f"(a), "f"(b), "r"(bar) : "memory");
}
__device__ __forceinline__ void st_async_v4(uint32_t addr, uint4 v, uint32_t bar) {
    asm volatile("st.async.weak.shared::cluster.mbarrier::complete_tx::bytes.v4.b32 [%0], {%1,%2,%3,%4}, [%5];"
                 :: "r"(addr), "r"(v.x), "r"(v.y), "r"(v.z), "r"(v.w), "r"(bar) : "memory");
}
__device__ __forceinline__ uint2 ldg_relaxed2(const uint2* p) {
    uint2 v;
    asm volatile("ld.relaxed.gpu.global.v2.b32 {%0,%1}, [%2];" : "=r"(v.x), "=r"(v.y) : "l"(p) : "memory");
    return v;
}
__device__ __forceinline__ void stg_relaxed2(uint2* p, uint2 v) {
    asm volatile("st.relaxed.gpu.global.v2.b32 [%0], {%1,%2};" :: "l"(p), "r"(v.x), "r"(v.y) : "memory");
}
__device__ __forceinline__ uint4 ldg_relaxed(const uint4* p) {
    uint4 v;
    asm volatile("ld.relaxed.gpu.global.v4.b32 {%0,%1,%2,%3}, [%4];" : "=r"(v.x), "=r"(v.y), "=r"(v.z), "=r"(v.w) : "l"(p) : "memory");
    return v;
}
__device__ __forceinline__ void stg_relaxed(uint4* p, uint4 v) {
    asm volatile("st.relaxed.gpu.global.v4.b32 [%0], {%1,%2,%3,%4};" :: "l"(p), "r"(v.x), "r"(v.y), "r"(v.z), "r"(v.w) : "memory");
}
__device__ __forceinline__ void stg_relaxed32(uint32_t* p, uint32_t v) {
    asm volatile("st.relaxed.gpu.global.b32 [%0], %1;" :: "l"(p), "r"(v) : "memory");
}
__device__ __forceinline__ uint32_t ldg_relaxed32(const uint32_t* p) {
    uint32_t v; asm volatile("ld.relaxed.gpu.global.b32 %0, [%1];" : "=r"(v) : "l"(p) : "memory"); return v;
}
__device__ __forceinline__ unsigned int ld_acquire(const unsigned int* p) {
    unsigned int v; asm volatile("ld.acquire.gpu.global.u32 %0, [%1];" : "=r"(v) : "l"(p) : "memory"); return v;
}
__device__ __forceinline__ void red_release(unsigned int* p, unsigned int v) {
    asm volatile("red.release.gpu.global.add.u32 [%0], %1;" :: "l"(p), "r"(v) : "memory");
}
__device__ __forceinline__ void wait_flag(int idx, unsigned int target) {
    const unsigned int* p = &g_flags[idx * 32];
    int g = 0;
#pragma unroll 1
    while (ld_acquire(p) < target) { __nanosleep(64); if (++g >= 64 * SPIN_LIMIT) { TIMEOUT(2, idx); break; } }
}
__device__ __forceinline__ void cp_async16(uint32_t dst, const void* src) {
    asm volatile("cp.async.cg.shared.global [%0], [%1], 16;" :: "r"(dst), "l"(src) : "memory");
}
__device__ __forceinline__ void cp_async_commit() { asm volatile("cp.async.commit_group;" ::: "memory"); }
template <int N> __device__ __forceinline__ void cp_async_wait() { asm volatile("cp.async.wait_group %0;" :: "n"(N) : "memory"); }
__device__ __forceinline__ void ldsm4(uint32_t& r0, uint32_t& r1, uint32_t& r2, uint32_t& r3, uint32_t addr) {
    asm volatile("ldmatrix.sync.aligned.m8n8.x4.shared.b16 {%0,%1,%2,%3}, [%4];" : "=r"(r0), "=r"(r1), "=r"(r2), "=r"(r3) : "r"(addr) : "memory");
}
__device__ __forceinline__ void ldsm4t(uint32_t& r0, uint32_t& r1, uint32_t& r2, uint32_t& r3, uint32_t addr) {
    asm volatile("ldmatrix.sync.aligned.m8n8.x4.trans.shared.b16 {%0,%1,%2,%3}, [%4];" : "=r"(r0), "=r"(r1), "=r"(r2), "=r"(r3) : "r"(addr) : "memory");
}
__device__ __forceinline__ void ldsm2t(uint32_t& r0, uint32_t& r1, uint32_t addr) {
    asm volatile("ldmatrix.sync.aligned.m8n8.x2.trans.shared.b16 {%0,%1}, [%2];" : "=r"(r0), "=r"(r1) : "r"(addr) : "memory");
}
__device__ __forceinline__ void stsm4(uint32_t addr, uint32_t r0, uint32_t r1, uint32_t r2, uint32_t r3) {
    asm volatile("stmatrix.sync.aligned.m8n8.x4.shared.b16 [%0], {%1,%2,%3,%4};" :: "r"(addr), "r"(r0), "r"(r1), "r"(r2), "r"(r3) : "memory");
}
__device__ __forceinline__ void stsm2t(uint32_t addr, uint32_t r0, uint32_t r1) {
    asm volatile("stmatrix.sync.aligned.m8n8.x2.trans.shared.b16 [%0], {%1,%2};" :: "r"(addr), "r"(r0), "r"(r1) : "memory");
}
__device__ __forceinline__ void mma16816(float* d, uint32_t a0, uint32_t a1, uint32_t a2, uint32_t a3, uint32_t b0, uint32_t b1) {
    asm volatile("mma.sync.aligned.m16n8k16.row.col.f32.bf16.bf16.f32 {%0,%1,%2,%3}, {%4,%5,%6,%7}, {%8,%9}, {%0,%1,%2,%3};"
                 : "+f"(d[0]), "+f"(d[1]), "+f"(d[2]), "+f"(d[3]) : "r"(a0), "r"(a1), "r"(a2), "r"(a3), "r"(b0), "r"(b1));
}
__device__ __forceinline__ void mma1688(float* d, uint32_t a0, uint32_t a1, uint32_t b0) {
    asm volatile("mma.sync.aligned.m16n8k8.row.col.f32.bf16.bf16.f32 {%0,%1,%2,%3}, {%4,%5}, {%6}, {%0,%1,%2,%3};"
                 : "+f"(d[0]), "+f"(d[1]), "+f"(d[2]), "+f"(d[3]) : "r"(a0), "r"(a1), "r"(b0));
}
__device__ __forceinline__ uint32_t pack2(float lo, float hi) {
    uint32_t r; asm("cvt.rn.bf16x2.f32 %0, %1, %2;" : "=r"(r) : "f"(hi), "f"(lo)); return r;
}
__device__ __forceinline__ float bflo(uint32_t w) { return __uint_as_float(w << 16); }
__device__ __forceinline__ float bfhi(uint32_t w) { return __uint_as_float(w & 0xffff0000u); }
__device__ __forceinline__ float rbf(float x) { return __bfloat162float(__float2bfloat16_rn(x)); }
__device__ __forceinline__ float ex2(float x) { float y; asm("ex2.approx.ftz.f32 %0, %1;" : "=f"(y) : "f"(x)); return y; }
__device__ __forceinline__ void sts128(uint32_t addr, uint4 v) {
    asm volatile("st.shared.v4.b32 [%0], {%1,%2,%3,%4};" :: "r"(addr), "r"(v.x), "r"(v.y), "r"(v.z), "r"(v.w) : "memory");
}
__device__ __forceinline__ uint4 lds128(uint32_t addr) {
    uint4 v; asm volatile("ld.shared.v4.b32 {%0,%1,%2,%3}, [%4];" : "=r"(v.x), "=r"(v.y), "=r"(v.z), "=r"(v.w) : "r"(addr) : "memory"); return v;
}
__device__ __forceinline__ float2 lds64f(uint32_t addr) {
    float2 v; asm volatile("ld.shared.v2.f32 {%0,%1}, [%2];" : "=f"(v.x), "=f"(v.y) : "r"(addr) : "memory"); return v;
}
__device__ __forceinline__ float lds32f(uint32_t addr) {
    float v; asm volatile("ld.shared.f32 %0, [%1];" : "=f"(v) : "r"(addr) : "memory"); return v;
}
__device__ __forceinline__ uint32_t lds32(uint32_t addr) {
    uint32_t v; asm volatile("ld.shared.b32 %0, [%1];" : "=r"(v) : "r"(addr) : "memory"); return v;
}
__device__ __forceinline__ void sts32(uint32_t addr, uint32_t v) { asm volatile("st.shared.b32 [%0], %1;" :: "r"(addr), "r"(v) : "memory"); }
__device__ __forceinline__ void sts64f(uint32_t addr, float a, float b) { asm volatile("st.shared.v2.f32 [%0], {%1,%2};" :: "r"(addr), "f"(a), "f"(b) : "memory"); }

__device__ __forceinline__ void tma_load2d(uint32_t dst, const CUtensorMap* tm, int c0, int c1, uint32_t bar) {
    asm volatile("cp.async.bulk.tensor.2d.shared::cluster.global.mbarrier::complete_tx::bytes [%0], [%1, {%3, %4}], [%2];"
                 :: "r"(dst), "l"(tm), "r"(bar), "r"(c0), "r"(c1) : "memory");
}
__device__ __forceinline__ void tma_store2d(const CUtensorMap* tm, uint32_t src, int c0, int c1) {
    asm volatile("cp.async.bulk.tensor.2d.global.shared::cta.bulk_group [%0, {%2, %3}], [%1];"
                 :: "l"(tm), "r"(src), "r"(c0), "r"(c1) : "memory");
}
__device__ __forceinline__ void bulk_commit() { asm volatile("cp.async.bulk.commit_group;" ::: "memory"); }
__device__ __forceinline__ void bulk_wait0() { asm volatile("cp.async.bulk.wait_group 0;" ::: "memory"); }
__device__ __forceinline__ void fence_async_smem() { asm volatile("fence.proxy.async.shared::cta;" ::: "memory"); }
__device__ __forceinline__ void fence_async_all() { asm volatile("fence.proxy.async;" ::: "memory"); }

__device__ __forceinline__ void wg_fence() { asm volatile("wgmma.fence.sync.aligned;" ::: "memory"); }
__device__ __forceinline__ void wg_commit() { asm volatile("wgmma.commit_group.sync.aligned;" ::: "memory"); }
__device__ __forceinline__ void wg_wait0() { asm volatile("wgmma.wait_group.sync.aligned 0;" ::: "memory"); }
__device__ __forceinline__ uint64_t mkdesc(uint32_t saddr, uint32_t lbo, uint32_t sbo) {
    return (uint64_t)((saddr & 0x3FFFF) >> 4) | ((uint64_t)(lbo >> 4) << 16) | ((uint64_t)(sbo >> 4) << 32) | (1ull << 62);
}
#define ACC8(i) "+f"(d[i]), "+f"(d[i + 1]), "+f"(d[i + 2]), "+f"(d[i + 3]), "+f"(d[i + 4]), "+f"(d[i + 5]), "+f"(d[i + 6]), "+f"(d[i + 7])
__device__ __forceinline__ void wgmma_n256(float* d, uint64_t da, uint64_t db, int scale_d) {
    asm volatile(
        "{\n.reg .pred p;\nsetp.ne.b32 p, %130, 0;\n"
        "wgmma.mma_async.sync.aligned.m64n256k16.f32.bf16.bf16 "
        "{%0,%1,%2,%3,%4,%5,%6,%7,%8,%9,%10,%11,%12,%13,%14,%15,%16,%17,%18,%19,%20,%21,%22,%23,%24,%25,%26,%27,%28,%29,%30,%31,"
        "%32,%33,%34,%35,%36,%37,%38,%39,%40,%41,%42,%43,%44,%45,%46,%47,%48,%49,%50,%51,%52,%53,%54,%55,%56,%57,%58,%59,%60,%61,%62,%63,"
        "%64,%65,%66,%67,%68,%69,%70,%71,%72,%73,%74,%75,%76,%77,%78,%79,%80,%81,%82,%83,%84,%85,%86,%87,%88,%89,%90,%91,%92,%93,%94,%95,"
        "%96,%97,%98,%99,%100,%101,%102,%103,%104,%105,%106,%107,%108,%109,%110,%111,%112,%113,%114,%115,%116,%117,%118,%119,%120,%121,%122,%123,%124,%125,%126,%127}, "
        "%128, %129, p, 1, 1, 0, 1;\n}"
        : ACC8(0), ACC8(8), ACC8(16), ACC8(24), ACC8(32), ACC8(40), ACC8(48), ACC8(56),
          ACC8(64), ACC8(72), ACC8(80), ACC8(88), ACC8(96), ACC8(104), ACC8(112), ACC8(120)
        : "l"(da), "l"(db), "r"(scale_d));
}
__device__ __forceinline__ void wgmma_n128(float* d, uint64_t da, uint64_t db, int scale_d) {
    asm volatile(
        "{\n.reg .pred p;\nsetp.ne.b32 p, %66, 0;\n"
        "wgmma.mma_async.sync.aligned.m64n128k16.f32.bf16.bf16 "
        "{%0,%1,%2,%3,%4,%5,%6,%7,%8,%9,%10,%11,%12,%13,%14,%15,%16,%17,%18,%19,%20,%21,%22,%23,%24,%25,%26,%27,%28,%29,%30,%31,"
        "%32,%33,%34,%35,%36,%37,%38,%39,%40,%41,%42,%43,%44,%45,%46,%47,%48,%49,%50,%51,%52,%53,%54,%55,%56,%57,%58,%59,%60,%61,%62,%63}, "
        "%64, %65, p, 1, 1, 0, 1;\n}"
        : ACC8(0), ACC8(8), ACC8(16), ACC8(24), ACC8(32), ACC8(40), ACC8(48), ACC8(56)
        : "l"(da), "l"(db), "r"(scale_d));
}

__device__ __forceinline__ void wgmma_n8_ta(float* d, uint64_t da, uint64_t db, int scale_d) {
    asm volatile(
        "{\n.reg .pred p;\nsetp.ne.b32 p, %6, 0;\n"
        "wgmma.mma_async.sync.aligned.m64n8k16.f32.bf16.bf16 {%0,%1,%2,%3}, %4, %5, p, 1, 1, 1, 0;\n}"
        : "+f"(d[0]), "+f"(d[1]), "+f"(d[2]), "+f"(d[3]) : "l"(da), "l"(db), "r"(scale_d));
}

__global__ void __launch_bounds__(256) k_mod(const bf16* __restrict__ c, const bf16* __restrict__ w_mod) {
    __shared__ float s_c[D_];
    __shared__ float s_red[64][33];
    const int tid = threadIdx.x;
    const int cq = tid & 3, rg = tid >> 2;
    uint4 w[8];
#pragma unroll
    for (int i = 0; i < 8; i++)
        w[i] = __ldg((const uint4*)(w_mod + (size_t)(rg * 8 + i) * (6 * D_) + blockIdx.x * 32 + cq * 8));
    for (int i = tid; i < D_; i += 256) {
        float v = __bfloat162float(c[i]);
        s_c[i] = rbf(v / (1.f + __expf(-v)));
    }
    {
        const int gt = blockIdx.x * 256 + tid, nt = gridDim.x * 256;
        for (int i = gt; i < F_TOTAL * 32; i += nt) g_flags[i] = 0;
        for (int i = gt; i < 65536; i += nt) g_F[i] = 0;
    }
    __syncthreads();
    float a[8];
#pragma unroll
    for (int j = 0; j < 8; j++) a[j] = 0.f;
#pragma unroll
    for (int i = 0; i < 8; i++) {
        float cv = s_c[rg * 8 + i];
        a[0] += cv * bflo(w[i].x); a[1] += cv * bfhi(w[i].x); a[2] += cv * bflo(w[i].y); a[3] += cv * bfhi(w[i].y);
        a[4] += cv * bflo(w[i].z); a[5] += cv * bfhi(w[i].z); a[6] += cv * bflo(w[i].w); a[7] += cv * bfhi(w[i].w);
    }
#pragma unroll
    for (int j = 0; j < 8; j++) s_red[rg][cq * 8 + j] = a[j];
    __syncthreads();
    if (tid < 32) {
        float s = 0.f;
#pragma unroll 8
        for (int r = 0; r < 64; r++) s += s_red[r][tid];
        g_mod[blockIdx.x * 32 + tid] = rbf(s);
    }
}

__device__ __forceinline__ void load_mod16(const float* __restrict__ m, int lane, float* v) {
    const float4* q = (const float4*)m;
    const float4 a = __ldg(q + lane * 2), b = __ldg(q + lane * 2 + 1), c = __ldg(q + 64 + lane * 2), d = __ldg(q + 64 + lane * 2 + 1);
    v[0] = a.x; v[1] = a.y; v[2] = a.z; v[3] = a.w; v[4] = b.x; v[5] = b.y; v[6] = b.z; v[7] = b.w;
    v[8] = c.x; v[9] = c.y; v[10] = c.z; v[11] = c.w; v[12] = d.x; v[13] = d.y; v[14] = d.z; v[15] = d.w;
}
__device__ __forceinline__ void ln_mod_row(const float* v, const float* c1, const float* sm, uint4& o0, uint4& o1) {
    float s = 0.f;
#pragma unroll
    for (int i = 0; i < 16; i++) s += v[i];
#pragma unroll
    for (int o = 16; o > 0; o >>= 1) s += __shfl_xor_sync(~0u, s, o);
    const float mean = s * (1.f / D_);
    float q = 0.f;
#pragma unroll
    for (int i = 0; i < 16; i++) { float d = v[i] - mean; q += d * d; }
#pragma unroll
    for (int o = 16; o > 0; o >>= 1) q += __shfl_xor_sync(~0u, q, o);
    const float var = rbf(q * (1.f / D_));
    const float mu = rbf(mean);
    const float den = rbf(sqrtf(rbf(var + 1e-5f)));
    const float rden = 1.f / den;
    float r[16];
#pragma unroll
    for (int i = 0; i < 16; i++) {
        const float y = rbf(rbf(v[i] - mu) * rden);
        r[i] = rbf(y * c1[i]) + sm[i];
    }
    o0 = make_uint4(pack2(r[0], r[1]), pack2(r[2], r[3]), pack2(r[4], r[5]), pack2(r[6], r[7]));
    o1 = make_uint4(pack2(r[8], r[9]), pack2(r[10], r[11]), pack2(r[12], r[13]), pack2(r[14], r[15]));
}
__device__ __forceinline__ void unpack8(uint4 u, float* v) {
    v[0] = bflo(u.x); v[1] = bfhi(u.x); v[2] = bflo(u.y); v[3] = bfhi(u.y);
    v[4] = bflo(u.z); v[5] = bfhi(u.z); v[6] = bflo(u.w); v[7] = bfhi(u.w);
}

__global__ void __launch_bounds__(256) k_ln1(const bf16* __restrict__ x) {
    const int lane = threadIdx.x & 31, row = blockIdx.x * 8 + (threadIdx.x >> 5);
    const uint4* xr = (const uint4*)(x + (size_t)row * D_);
    float v[16], c1[16], sm[16];
    unpack8(__ldg(xr + lane), v);
    unpack8(__ldg(xr + 32 + lane), v + 8);
    load_mod16(g_mod + D_, lane, c1);
    load_mod16(g_mod, lane, sm);
#pragma unroll
    for (int i = 0; i < 16; i++) c1[i] = rbf(1.f + c1[i]);
    uint4 o0, o1;
    ln_mod_row(v, c1, sm, o0, o1);
    uint4* hr = (uint4*)(g_h + (size_t)row * D_);
    hr[lane] = o0; hr[32 + lane] = o1;
}

struct __align__(64) Params {
    CUtensorMap tm_h, tm_kv, tm_kvm, tm_o, tm_op, tm_h2, tm_act, tm_x1, tm_out;
    CUtensorMap tm_wq, tm_wk, tm_wv, tm_wo, tm_wg, tm_wu, tm_wd;
    const bf16* x;
    int job_begin, job_end;
};

constexpr int R_NST = 3;
constexpr uint32_t R_WV = 0, R_MEM = 65536, R_KX = 73728, R_VX = R_KX + R_NST * 4096, R_QS = R_VX + R_NST * 4096,
                   R_KMS = R_QS + 1024, R_VMS = R_KMS + 1024, R_OS = R_VMS + 1024, R_SX = R_OS + 1024, R_BAR = R_SX + 2560,
                   R_RS = 105472  , R_VP = R_RS + 8192  ,
                   R_STG = R_VP + 8192  , R_SMEM = R_STG + 98304;
static_assert(R_BAR + 64 <= R_RS, "smem");
constexpr uint32_t RB_SX = R_BAR, RB_V = R_BAR + 8, RB_E = R_BAR + 16, RB_A = R_BAR + 24, RB_ROLE = R_BAR + 32;
constexpr int W_NST = 3;
constexpr uint32_t W_STAGE = 49152, W_STG = W_NST * W_STAGE, W_END = W_STG + 65536;
constexpr uint32_t SM_BAR = W_END;
constexpr uint32_t SMEM_BYTES = W_END + 1024;
constexpr uint32_t B_FULL = 0, B_EMPTY = 32, B_STGFREE = 64, B_RING = 128;

constexpr int NB_X = 11  , NB_B = 2, NB_C = 3, NB_D = 4, NB_W0 = 6  , NB_ST = 9  ;

__device__ __forceinline__ int pos_of_d(int d) {
    const int rem = d & 31;
    return (d & ~31) + ((rem & 7) >> 1) * 8 + (rem & 1) * 4 + (rem >> 3);
}

#define PROF(i) do {} while (0)
#define PROFG(i) do {} while (0)
#define OPAQUE(x) asm volatile("" : "+r"(x))
#define FENCE_SCHED(x) do { if ((x) == 0u) asm volatile("trap;"); } while (0)
constexpr int VK0 = 12;
#define VDELAY -1
#define POLL_GAP 100

struct RecParams { const bf16 *mem0, *wq, *wk, *wv, *wo; int ncl; };

__device__ __forceinline__ void rec_qk(const RecParams& p, const uint32_t sb, const int cta, const int warp, int lane, const int sel) {
    const int crank = cta & 15, cl = cta >> 4, rank = cta & 1;
    const int wg = warp >> 2, tile = warp & 3;
    uint32_t wa[32][4];
    const uint32_t stg = sb + R_STG + wg * 32768;
    {
        const int t128 = tile * 32 + lane;
        const int row = (lane >> 4) * 8 + (lane & 7);
        const uint32_t fo = row * 128 + (((2 * tile + ((lane >> 3) & 1)) ^ (row & 7)) << 4);
        const bf16* W = (wg == 0 ? p.wq : p.wk) + cta * 64;
        const bf16* Wv = p.wv + cta * 64;
        const int ch = t128 & 7;
#pragma unroll 4
        for (int dd = 0; dd < 16; dd++) {
            const int d = dd * 16 + (t128 >> 3), pp = pos_of_d(d);
            cp_async16(sb + R_WV + wg * 32768 + pp * 128 + ((ch ^ (pp & 7)) << 4), Wv + (size_t)(wg * 256 + d) * HD_ + ch * 8);
        }
        cp_async_commit();
#pragma unroll 4
        for (int dd = 0; dd < 16; dd++) {
            const int d = dd * 16 + (t128 >> 3), pp = pos_of_d(d);
            cp_async16(stg + pp * 128 + ((ch ^ (pp & 7)) << 4), W + (size_t)d * HD_ + ch * 8);
        }
        cp_async_commit();
        {
            const int i0 = (warp * 32 + lane) * 16, tok = i0 >> 9;
            const uint4 m0 = __ldg((const uint4*)(p.mem0 + i0)), m1 = __ldg((const uint4*)(p.mem0 + i0 + 8));
            const uint32_t mw[8] = {m0.x, m0.y, m0.z, m0.w, m1.x, m1.y, m1.z, m1.w};
#pragma unroll
            for (int e = 0; e < 16; e++) {
                const int pp = pos_of_d((i0 & 511) + e);
                const unsigned short v = (unsigned short)(mw[e >> 1] >> ((e & 1) * 16));
                asm volatile("st.shared.u16 [%0], %1;" :: "r"(sb + R_MEM + (pp >> 3) * 128 + tok * 16 + (pp & 7) * 2), "h"(v) : "memory");
            }
        }
        cp_async_wait<1>();
        bar_sync(NB_W0 + wg, 128);
#pragma unroll
        for (int ks = 0; ks < 16; ks++) ldsm4t(wa[ks][0], wa[ks][1], wa[ks][2], wa[ks][3], sb + R_WV + wg * 32768 + fo + ks * 2048);
        bar_sync(NB_W0 + wg, 128);
#pragma unroll
        for (int ks = 0; ks < 16; ks++)
            sts128(sb + R_WV + wg * 32768 + (tile * 16 + ks) * 512 + lane * 16, make_uint4(wa[ks][0], wa[ks][1], wa[ks][2], wa[ks][3]));
        cp_async_wait<0>();
        bar_sync(NB_W0 + wg, 128);
#pragma unroll
        for (int ks = 0; ks < 16; ks++) ldsm4t(wa[ks][0], wa[ks][1], wa[ks][2], wa[ks][3], stg + fo + ks * 2048);
        bar_sync(NB_W0 + wg, 128);
#pragma unroll 4
        for (int dd = 0; dd < 16; dd++) {
            const int d = dd * 16 + (t128 >> 3), pp = pos_of_d(d);
            cp_async16(stg + pp * 128 + ((ch ^ (pp & 7)) << 4), W + (size_t)(256 + d) * HD_ + ch * 8);
        }
        cp_async_commit();
        cp_async_wait<0>();
        bar_sync(NB_W0 + wg, 128);
#pragma unroll
        for (int ks = 0; ks < 16; ks++) ldsm4t(wa[16 + ks][0], wa[16 + ks][1], wa[16 + ks][2], wa[16 + ks][3], stg + fo + ks * 2048);
        bar_sync(NB_W0 + wg, 128);
    }
    const uint32_t tab = stg + (tile * 32 + lane) * 16;
    {
        const uint32_t l7 = lane & 7, l8 = lane >> 3, g = lane >> 2, t = lane & 3;
        const uint32_t t0 = l7 * 128 + ((l8 ^ l7) << 4);
        const uint32_t tq = l7 * 128 + (((l8 >> 1) ^ l7) << 4);
        const uint32_t bq = warp >> 1, tp = warp & 1;
        uint4 v;
        v.x = sb + (wg == 0 ? R_QS : R_KMS) + l7 * 128 + (((2 * tile + (l8 & 1)) ^ l7) << 4);
        v.y = sb + R_QS + tq;
        v.z = sb + (warp == 0 ? R_KMS : R_KX + (warp - 1) * 1024) + t0;
        v.w = mapa_u32(sb + R_SX + (rank * 5 + warp) * 256 + lane * 8, crank ^ 1);
        sts128(tab, v);
        const uint32_t vp = (0x9Cu >> warp) & 1;
        const uint32_t vk = warp <= 2 ? 12 : (warp == 3 || warp == 6 ? 24 : (warp == 4 ? 28 : 16));
        const uint32_t vs = warp <= 2 ? 0 : (warp == 3 || warp == 6 ? 2 : (warp == 4 ? 3 : 1));
        sts128(tab + 2048, make_uint4(sb + lane * 16 + R_MEM, sb + lane * 16 + R_MEM + vk * 256,
                                      sb + lane * 16 + R_WV + (vk >> 4) * 32768 + (2 * vp * 16 + (vk & 15)) * 512,
                                      sb + lane * 16 + R_VP + (vs * 4 + 2 * vp) * 512));
        if (warp == 0) { sts128(sb + lane * 16 + R_VP + 12 * 512, make_uint4(0, 0, 0, 0)); sts128(sb + lane * 16 + R_VP + 13 * 512, make_uint4(0, 0, 0, 0)); }
        const uint32_t src = (l8 >> 1) * 8 + l7;
        const uint32_t L = bq * 8 + 2 * tp + (l8 & 1);
        const uint32_t d0 = (crank + ((t >> 1) | (g & 6))) & 15;
        v.x = sb + R_RS + src * 512 + ((L ^ (src & 7)) << 4);
        v.y = mapa_u32(sb + R_MEM + (crank * 4 + bq) * 128 + (4 * tp + 2 * (t & 1) + (g & 1)) * 16, d0);
        v.z = mapa_u32(sb + RB_A, d0);
        v.w = lane;
        sts128(tab + 4096, v);
        const uint64_t wr = (uint64_t)(g_F + ((crank * 2 + ((crank ^ (crank >> 3) ^ sel) & 1)) * 1024 + warp * 128 + cl * 32 + lane));
        sts128(tab + 6144, make_uint4((uint32_t)wr, (uint32_t)(wr >> 32), (uint32_t)((((cl + 1) & 3) - cl) * 128), (uint32_t)((((cl + 2) & 3) - cl) * 128)));
        sts32(tab + 8192, (uint32_t)((((cl + 3) & 3) - cl) * 128));
#pragma unroll
        for (int i = 0; i < 4; i++)
            sts128(tab + 10240 + i * 2048, make_uint4(wa[i][0], wa[i][1], wa[i][2], wa[i][3]));
    }
    bar_sync(NB_D, 384);
    uint32_t slot_off = 0;
    const uint32_t slot_inc = warp == 0 ? 0 : 4096;
    const uint32_t sx_bar_rem = (sb + RB_SX) ^ (1u << 24);
    uint4 ta = lds128(tab), tb = lds128(tab + 2048);
#pragma unroll 1
    for (int s = 0; s < NSEG; s++) {
        if (s > 0) mbar_wait(sb + RB_A, (s - 1) & 1);
        if (warp == 0) { PROF(0); PROFG(13); }
        {
            float acc[4][4];
#pragma unroll
            for (int c = 0; c < 4; c++) { acc[c][0] = acc[c][1] = acc[c][2] = acc[c][3] = 0.f; }
#pragma unroll
            for (int k2 = 0; k2 < 16; k2++) {
                uint32_t b0, b1, b2, b3;
                ldsm4(b0, b1, b2, b3, tb.x + k2 * 512);
                mma16816(acc[(2 * k2) & 3], wa[2 * k2][0], wa[2 * k2][1], wa[2 * k2][2], wa[2 * k2][3], b0, b1);
                mma16816(acc[(2 * k2 + 1) & 3], wa[2 * k2 + 1][0], wa[2 * k2 + 1][1], wa[2 * k2 + 1][2], wa[2 * k2 + 1][3], b2, b3);
            }
            stsm2t(ta.x, pack2((acc[0][0] + acc[1][0]) + (acc[2][0] + acc[3][0]), (acc[0][1] + acc[1][1]) + (acc[2][1] + acc[3][1])),
                   pack2((acc[0][2] + acc[1][2]) + (acc[2][2] + acc[3][2]), (acc[0][3] + acc[1][3]) + (acc[2][3] + acc[3][3])));
        }
        const uint32_t kb = ta.z + slot_off;
        if (warp == 0) PROF(1);
        bar_sync(NB_B, 256);
        if (warp < 5 && s != NSEG - 1) {
            uint32_t q[16], k0, k1, k2, k3, k4, k5, k6, k7;
            float sa[4] = {0.f, 0.f, 0.f, 0.f}, sc[4] = {0.f, 0.f, 0.f, 0.f};
            ldsm4(q[0], q[1], q[2], q[3], ta.y);
            ldsm4(k0, k1, k2, k3, kb);
            ldsm4(q[4], q[5], q[6], q[7], ta.y ^ 32);
            ldsm4(q[8], q[9], q[10], q[11], ta.y ^ 64);
            ldsm4(k4, k5, k6, k7, kb ^ 64);
            ldsm4(q[12], q[13], q[14], q[15], ta.y ^ 96);
            mma16816(sa, q[0], q[1], q[2], q[3], k0, k1);
            mma16816(sc, q[4], q[5], q[6], q[7], k2, k3);
            mma16816(sa, q[8], q[9], q[10], q[11], k4, k5);
            mma16816(sc, q[12], q[13], q[14], q[15], k6, k7);
            const float r0 = sa[0] + sc[0], r1 = sa[1] + sc[1];
            st_async_v2(ta.w, r0, r1, sx_bar_rem);
            st_async_v2(ta.w ^ (1u << 24), r0, r1, sx_bar_rem ^ (1u << 24));
            if (warp == 0) PROF(2);
        }
        if (warp != 0) {
            float v0[4] = {0.f, 0.f, 0.f, 0.f}, v1[4] = {0.f, 0.f, 0.f, 0.f};
            uint32_t off = 0;
            if (warp >= 5) {
                if (s > 0 && warp == 7 && lane == 0) mbar_expect_tx(sb + RB_A, 8192);
                const uint32_t t0 = clk32();
                while ((int)(clk32() - t0) < 30) {}
                uint32_t b[8];
                uint4 a[8];
                ldsm4(b[0], b[1], b[2], b[3], tb.y);
#pragma unroll
                for (int i = 0; i < 4; i++) {
                    a[2 * i] = lds128(tb.z + i * 512); a[2 * i + 1] = lds128(tb.z + 8192 + i * 512);
                    if (i == 1) ldsm4(b[4], b[5], b[6], b[7], tb.y + 512);
                }
#pragma unroll
                for (int i = 0; i < 4; i++) {
                    mma16816(v0, a[2 * i].x, a[2 * i].y, a[2 * i].z, a[2 * i].w, b[2 * i], b[2 * i + 1]);
                    mma16816(v1, a[2 * i + 1].x, a[2 * i + 1].y, a[2 * i + 1].z, a[2 * i + 1].w, b[2 * i], b[2 * i + 1]);
                }
                off = 1024;
            }
            {
                uint32_t b[8];
                uint4 a[8];
                ldsm4(b[0], b[1], b[2], b[3], tb.y + off);
#pragma unroll
                for (int i = 0; i < 4; i++) {
                    a[2 * i] = lds128(tb.z + 2 * off + i * 512); a[2 * i + 1] = lds128(tb.z + 2 * off + 8192 + i * 512);
                    if (i == 1) ldsm4(b[4], b[5], b[6], b[7], tb.y + off + 512);
                }
#pragma unroll
                for (int i = 0; i < 4; i++) {
                    mma16816(v0, a[2 * i].x, a[2 * i].y, a[2 * i].z, a[2 * i].w, b[2 * i], b[2 * i + 1]);
                    mma16816(v1, a[2 * i + 1].x, a[2 * i + 1].y, a[2 * i + 1].z, a[2 * i + 1].w, b[2 * i], b[2 * i + 1]);
                }
            }
            sts128(tb.w, make_uint4(__float_as_uint(v0[0]), __float_as_uint(v0[1]), __float_as_uint(v0[2]), __float_as_uint(v0[3])));
            sts128(tb.w + 512, make_uint4(__float_as_uint(v1[0]), __float_as_uint(v1[1]), __float_as_uint(v1[2]), __float_as_uint(v1[3])));
            __syncwarp();
            if (lane == 0) mbar_arrive(sb + RB_V);
            if (warp == 1) PROF(3);
            if (warp == 5) PROF(14);
        }
        if (s == NSEG - 1) break;
        slot_off = slot_off == (R_NST - 1) * 4096 ? 0 : slot_off + slot_inc;
        const uint4 tc = lds128(tab + 4096), td = lds128(tab + 6144);
        const uint32_t te = lds32(tab + 8192);
        uint32_t* wr = (uint32_t*)(((uint64_t)td.y << 32) | (td.x ^ ((s & 1) * 0x21000)));
        const uint32_t* r1p = (const uint32_t*)((const char*)wr + (int)td.z);
        const uint32_t* r2p = (const uint32_t*)((const char*)wr + (int)td.w);
        const uint32_t* r3p = (const uint32_t*)((const char*)wr + (int)te);
        const uint32_t tag = ((s >> 1) + 1) & 1;
        mbar_wait(sb + RB_E, s & 1);
        if (warp == 0) PROF(7);
        {
            uint32_t a0, a1, a2, a3, a4, a5, a6, a7;
            ldsm4t(a0, a1, a2, a3, tc.x);
            ldsm4t(a4, a5, a6, a7, tc.x ^ 64);
            const uint32_t one = 0x3F803F80u;
            float d0_[4] = {0.f, 0.f, 0.f, 0.f}, d1_[4] = {0.f, 0.f, 0.f, 0.f};
            mma16816(d0_, a0, a1, a2, a3, one, one);
            mma16816(d1_, a4, a5, a6, a7, one, one);
            const bool t1 = tc.w & 1, t2 = tc.w & 2;
            const float x = t2 ? (t1 ? d1_[2] : d1_[0]) : (t1 ? d0_[2] : d0_[0]);
            const uint32_t own = (__float_as_uint(x) & ~1u) | tag;
            stg_relaxed32(wr, own);
            const uint32_t tq = clk32();
            if (warp == 0) PROF(8);
            PROFG(16 + warp);
#pragma unroll
            for (int i = 0; i < 4; i++) {
                const uint4 f0 = lds128(tab + 10240 + i * 2048);
                wa[i][0] = f0.x; wa[i][1] = f0.y; wa[i][2] = f0.z; wa[i][3] = f0.w;
            }
            ta = lds128(tab); tb = lds128(tab + 2048);
            while ((int)(clk32() - tq) < POLL_GAP) {}
            uint32_t f1, f2, f3;
            int gg = 0;
#pragma unroll 1
            while (true) {
                f1 = ldg_relaxed32(r1p); f2 = ldg_relaxed32(r2p); f3 = ldg_relaxed32(r3p);
                if (__all_sync(~0u, (((f1 ^ tag) | (f2 ^ tag) | (f3 ^ tag)) & 1) == 0)) break;
                if (++gg > 16 * SPIN_LIMIT) { TIMEOUT(3, s); break; }
            }
            if (warp == 0) PROF(9);
            PROFG(32 + warp);
            const float v = (__uint_as_float(own) + __uint_as_float(f2)) + (__uint_as_float(f1) + __uint_as_float(f3));
            const bool b8 = tc.w & 8, b16 = tc.w & 16;
            const float recv = __shfl_xor_sync(~0u, v, 8);
            const uint32_t word = b8 ? pack2(recv, v) : pack2(v, recv);
            const uint32_t oth = __shfl_xor_sync(~0u, word, 16);
            const uint32_t wl = b16 ? oth : word, wh = b16 ? word : oth;
            const uint32_t p0 = __shfl_xor_sync(~0u, wl, 2), p1 = __shfl_xor_sync(~0u, wh, 2);
            const uint4 item = t2 ? make_uint4(p0, p1, wl, wh) : make_uint4(wl, wh, p0, p1);
            st_async_v4(tc.y, item, tc.z);
            st_async_v4(tc.y ^ (8u << 24), item, tc.z ^ (8u << 24));
            if (tc.w == 0 && warp == 7) mbar_expect_tx(sb + RB_E, 8192);
            if (warp == 0) PROF(10);
            PROF(40 + warp);
        }
        bar_sync(NB_D, 384);
    }
}

__device__ __forceinline__ void rec_load_kv(uint32_t sb, int col0, int s, uint32_t slot_off, int t128) {
    const int row = t128 >> 2, c2 = (t128 & 3) * 2;
    const bf16* src = g_kv + ((size_t)(s * 32 + row) * (2 * HD_) + col0 + c2 * 8);
    const uint32_t d0 = sb + R_KX + slot_off + row * 128 + ((c2 ^ (row & 7)) << 4);
    cp_async16(d0, src);
    cp_async16(d0 ^ 16, src + 8);
    cp_async16(d0 + (R_VX - R_KX), src + HD_);
    cp_async16((d0 ^ 16) + (R_VX - R_KX), src + HD_ + 8);
}

__device__ __forceinline__ void rec_vo(const RecParams& p, const uint32_t sb, const int cta, const int warp, int lane) {
    const int w = warp - 8, crank = cta & 15;
    const int col0 = cta * 64;
    uint32_t wo[8][4][4];
    {
        const int t128 = w * 32 + lane;
        const bf16* Wo = p.wo + (size_t)col0 * D_;
        const uint32_t stg = sb + R_STG + 2 * 32768;
#pragma unroll
        for (int half = 0; half < 2; half++) {
#pragma unroll 4
            for (int i = t128; i < 2048; i += 128) {
                const int e = i >> 6, ch = i & 63;
                cp_async16(stg + e * 1024 + ((ch ^ (e & 7)) << 4), Wo + (size_t)(half * 32 + e) * D_ + ch * 8);
            }
            cp_async_commit();
            cp_async_wait<0>();
            bar_sync(NB_W0 + 2, 128);
#pragma unroll
            for (int j = 0; j < 8; j++)
#pragma unroll
                for (int kk = 0; kk < 2; kk++) {
                    const int e = kk * 16 + (lane >> 4) * 8 + (lane & 7);
                    const int ch = (w * 8 + j) * 2 + ((lane >> 3) & 1);
                    ldsm4t(wo[j][half * 2 + kk][0], wo[j][half * 2 + kk][1], wo[j][half * 2 + kk][2], wo[j][half * 2 + kk][3],
                           stg + e * 1024 + ((ch ^ (e & 7)) << 4));
                }
            bar_sync(NB_W0 + 2, 128);
        }
        if (lane == 0) wait_flag(F_KV + 0, 64);
        __syncwarp();
        rec_load_kv(sb, col0, 0, 0, t128); cp_async_commit();
        rec_load_kv(sb, col0, 1, 4096, t128); cp_async_commit();
        cp_async_wait<1>();
    }
    const uint32_t tab = sb + R_STG + 2 * 32768 + (w * 32 + lane) * 16;
    {
        const uint32_t l7 = lane & 7, l8 = lane >> 3, g = lane >> 2;
        uint4 v;
        v.x = sb + R_VX + ((l8 >> 1) * 8 + l7) * 128 + (((2 * w + (l8 & 1)) ^ l7) << 4);
        v.y = sb + R_OS + g * 128 + (((2 * w) ^ g) << 4) + (lane & 3) * 4;
        v.z = sb + R_VMS + l7 * 128 + (((2 * w + (l8 & 1)) ^ l7) << 4);
        v.w = sb + R_OS + l7 * 128 + ((l8 ^ l7) << 4);
        sts128(tab, v);
        v.x = mapa_u32(sb + R_RS + crank * 512 + ((lane ^ (crank & 7)) << 4), w * 4);
        v.y = mapa_u32(sb + RB_E, w * 4);
        v.z = sb + R_VP + w * 512 + lane * 16;
        v.w = sb + R_SX + lane * 8;
        sts128(tab + 2048, v);
#pragma unroll
        for (int i = 0; i < 8; i++) sts128(tab + 4096 + i * 2048, make_uint4(wo[i][0][0], wo[i][0][1], wo[i][0][2], wo[i][0][3]));
        sts32(tab + 20480, sb + lane * 16);
    }
    bar_sync(NB_D, 384);
    const uint32_t lane16 = lds32(tab + 20480);
    uint4 av[VK0];
#pragma unroll
    for (int i = 0; i < VK0; i++) av[i] = lds128(lane16 + R_WV + (w * 16 + i) * 512);
    const float sc = 0.08838834764831845f * 1.4426950408889634f;
    uint32_t slot_off = 0;
#pragma unroll 1
    for (int s = 0; s < NSEG; s++) {
        if (s > 0) mbar_wait(sb + RB_A, (s - 1) & 1);
        float va[4] = {0.f, 0.f, 0.f, 0.f}, vc[4] = {0.f, 0.f, 0.f, 0.f};
#pragma unroll
        for (int k2 = 0; k2 < VK0 / 2; k2++) {
            uint32_t b0, b1, b2, b3;
            ldsm4(b0, b1, b2, b3, lane16 + R_MEM + k2 * 512);
            mma16816(va, av[2 * k2].x, av[2 * k2].y, av[2 * k2].z, av[2 * k2].w, b0, b1);
            mma16816(vc, av[2 * k2 + 1].x, av[2 * k2 + 1].y, av[2 * k2 + 1].z, av[2 * k2 + 1].w, b2, b3);
        }
        va[0] += vc[0]; va[1] += vc[1]; va[2] += vc[2]; va[3] += vc[3];
        const uint4 ta = lds128(tab), tb = lds128(tab + 2048);
        const uint32_t os2 = ta.y ^ 16, oa2 = ta.w ^ 64;
        float oa[2][4] = {{0.f, 0.f, 0.f, 0.f}, {0.f, 0.f, 0.f, 0.f}};
        float inv = 0.f;
        uint32_t vx[8];
        ldsm4t(vx[0], vx[1], vx[2], vx[3], ta.x + slot_off);
        ldsm4t(vx[4], vx[5], vx[6], vx[7], ta.x + slot_off + 2048);
        uint32_t vb0, vb1;
        uint32_t pf[5];
        if (s != NSEG - 1) {
            mbar_wait(sb + RB_SX, s & 1);
            if (w == 0) PROF(4);
            float sv[10];
#pragma unroll
            for (int n = 0; n < 5; n++) {
                const float2 a = lds64f(tb.w + n * 256), b = lds64f(tb.w + (5 + n) * 256);
                sv[2 * n] = a.x + b.x; sv[2 * n + 1] = a.y + b.y;
            }
            float mx = fmaxf(fmaxf(fmaxf(sv[0], sv[1]), fmaxf(sv[2], sv[3])), fmaxf(fmaxf(sv[4], sv[5]), fmaxf(sv[6], sv[7])));
            mx = fmaxf(mx, fmaxf(sv[8], sv[9]));
            mx = fmaxf(mx, __shfl_xor_sync(~0u, mx, 1));
            mx = fmaxf(mx, __shfl_xor_sync(~0u, mx, 2));
            const float mxs = -mx * sc;
#pragma unroll
            for (int n = 0; n < 5; n++) pf[n] = pack2(ex2(fmaf(sv[2 * n], sc, mxs)), ex2(fmaf(sv[2 * n + 1], sc, mxs)));
            if (w == 0) PROF(12);
        }
        {
            mbar_wait(sb + RB_V, s & 1);
            if (w == 0) PROF(11);
            const uint4 a = lds128(tb.z), b = lds128(tb.z + 2048), c = lds128(tb.z + 4096), d = lds128(tb.z + 6144);
            vb0 = pack2(va[0] + (__uint_as_float(a.x) + __uint_as_float(b.x)) + (__uint_as_float(c.x) + __uint_as_float(d.x)),
                        va[1] + (__uint_as_float(a.y) + __uint_as_float(b.y)) + (__uint_as_float(c.y) + __uint_as_float(d.y)));
            vb1 = pack2(va[2] + (__uint_as_float(a.z) + __uint_as_float(b.z)) + (__uint_as_float(c.z) + __uint_as_float(d.z)),
                        va[3] + (__uint_as_float(a.w) + __uint_as_float(b.w)) + (__uint_as_float(c.w) + __uint_as_float(d.w)));
        }
        if (s != NSEG - 1) {
            float ob_[2][4] = {{0.f, 0.f, 0.f, 0.f}, {0.f, 0.f, 0.f, 0.f}}, sm0[4] = {0.f, 0.f, 0.f, 0.f}, sm1[4] = {0.f, 0.f, 0.f, 0.f};
            const uint32_t one = 0x3F803F80u;
            mma16816(sm0, pf[1], 0u, pf[2], 0u, one, one);
            mma16816(sm1, pf[3], 0u, pf[4], 0u, one, one);
            mma16816(oa[0], pf[1], 0u, pf[2], 0u, vx[0], vx[2]);
            mma16816(oa[1], pf[1], 0u, pf[2], 0u, vx[1], vx[3]);
            mma16816(ob_[0], pf[3], 0u, pf[4], 0u, vx[4], vx[6]);
            mma16816(ob_[1], pf[3], 0u, pf[4], 0u, vx[5], vx[7]);
            mma1688(sm0, pf[0], 0u, one);
            mma1688(oa[0], pf[0], 0u, vb0);
            mma1688(oa[1], pf[0], 0u, vb1);
            asm("rcp.approx.ftz.f32 %0, %1;" : "=f"(inv) : "f"(sm0[0] + sm1[0]));
            oa[0][0] += ob_[0][0]; oa[0][1] += ob_[0][1]; oa[1][0] += ob_[1][0]; oa[1][1] += ob_[1][1];
            sts32(ta.y, pack2(oa[0][0] * inv, oa[0][1] * inv));
            sts32(os2, pack2(oa[1][0] * inv, oa[1][1] * inv));
#pragma unroll
            for (int i = 0; i < 4; i++) {
                const uint4 f0 = lds128(tab + 4096 + i * 2048);
                wo[i][0][0] = f0.x; wo[i][0][1] = f0.y; wo[i][0][2] = f0.z; wo[i][0][3] = f0.w;
            }
            bar_sync(NB_C, 128);
            if (w == 0) PROF(5);
            uint32_t ob[8];
            ldsm4(ob[0], ob[1], ob[2], ob[3], ta.w);
            ldsm4(ob[4], ob[5], ob[6], ob[7], oa2);
#pragma unroll
            for (int i = 4; i < 8; i++) {
                const uint4 f0 = lds128(tab + 4096 + i * 2048);
                wo[i][0][0] = f0.x; wo[i][0][1] = f0.y; wo[i][0][2] = f0.z; wo[i][0][3] = f0.w;
            }
#pragma unroll
            for (int jj = 0; jj < 2; jj++) {
                if (jj == 1 && tb.w == 0) break;
                float acc[4][4];
#pragma unroll
                for (int c = 0; c < 4; c++) { acc[c][0] = acc[c][1] = acc[c][2] = acc[c][3] = 0.f; }
#pragma unroll
                for (int ks = 0; ks < 4; ks++)
#pragma unroll
                    for (int c = 0; c < 4; c++)
                        mma16816(acc[c], wo[jj * 4 + c][ks][0], wo[jj * 4 + c][ks][1], wo[jj * 4 + c][ks][2], wo[jj * 4 + c][ks][3], ob[2 * ks], ob[2 * ks + 1]);
#pragma unroll
                for (int pr = 0; pr < 2; pr++) {
                    uint4 v;
                    v.x = pack2(acc[2 * pr][0], acc[2 * pr][1]);
                    v.y = pack2(acc[2 * pr][2], acc[2 * pr][3]);
                    v.z = pack2(acc[2 * pr + 1][0], acc[2 * pr + 1][1]);
                    v.w = pack2(acc[2 * pr + 1][2], acc[2 * pr + 1][3]);
                    st_async_v4(tb.x + ((jj * 2 + pr) << 24), v, tb.y + ((jj * 2 + pr) << 24));
                }
            }
            if (w == 0) PROF(6);
        }
        {
            stsm2t(ta.z, vb0, vb1);
            cp_async_wait<0>();
            bar_sync(NB_C, 128);
            if (w == 0 && lane == 0 && s != NSEG - 1) mbar_expect_tx(sb + RB_SX, 2560);
            const int omat = w >> 1, otok = (w & 1) * 4 + (lane >> 3), och = lane & 7;
            const uint4 v = lds128(sb + (omat ? R_VMS : R_KMS) + otok * 128 + ((och ^ otok) << 4));
            *(uint4*)(g_kvm + ((s * 8 + otok) * (2 * HD_) + omat * HD_ + col0 + och * 8)) = v;
            if (s != NSEG - 1) bar_arrive(NB_D, 384);
#pragma unroll
            for (int i = 0; i < VK0; i++) av[i] = lds128(lane16 + R_WV + (w * 16 + i) * 512);
            if (s + 2 < NSEG - 1) {
                if (((s + 2) & 3) == 0) { if (lane == 0) wait_flag(F_KV + ((s + 2) >> 2), 64); __syncwarp(); }
                rec_load_kv(sb, col0, s + 2, slot_off == 0 ? (R_NST - 1) * 4096 : slot_off - 4096, w * 32 + lane);
            }
            cp_async_commit();
            if ((s & 3) == 3) {
                bar_sync(NB_C, 128);
                if (w == 0 && lane == 0) red_release(&g_flags[(F_MEM + (s >> 2)) * 32], 1);
            }
        }
        slot_off = slot_off == (R_NST - 1) * 4096 ? 0 : slot_off + 4096;
    }
}

__global__ void __launch_bounds__(384, 1) k_rec(const RecParams p) {
    extern __shared__ __align__(1024) unsigned char smem_raw[];
    const uint32_t sb = __shfl_sync(~0u, smem_u32(smem_raw), 0);
    const int warp = __shfl_sync(~0u, threadIdx.x >> 5, 0);
    int lane; asm volatile("mov.u32 %0, %%laneid;" : "=r"(lane));
    const int crank = blockIdx.x & 15, slot = blockIdx.x >> 4;
    asm volatile("griddepcontrol.launch_dependents;");
    if (threadIdx.x == 0) {
        mbar_init(sb + RB_SX, 1); mbar_init(sb + RB_V, 7); mbar_init(sb + RB_E, 1); mbar_init(sb + RB_A, 1); mbar_init(sb + RB_ROLE, 1);
        asm volatile("fence.mbarrier_init.release.cluster;" ::: "memory");
        mbar_expect_tx(sb + RB_SX, 2560);
        mbar_expect_tx(sb + RB_E, 8192);
        mbar_expect_tx(sb + RB_A, 8192);
        mbar_expect_tx(sb + RB_ROLE, 4);
    }
    if (threadIdx.x == 32) {
        const int nct = p.ncl * 16;
        for (int i = blockIdx.x; i < 1024; i += nct) {
            const bf16* W = (i & 3) == 0 ? p.wq : ((i & 3) == 1 ? p.wk : ((i & 3) == 2 ? p.wo : p.wv));
            asm volatile("cp.async.bulk.prefetch.L2.global [%0], %1;" :: "l"(W + (size_t)(i >> 2) * 8192), "r"(16384) : "memory");
        }
    }
    unsigned role = 0;
    if (crank == 0 && threadIdx.x == 0) {
        unsigned x = 0;
        int tm[2] = {0x7fffffff, 0x7fffffff};
#pragma unroll 1
        for (int i = 0; i < 8; i++) {
            const uint32_t t0 = clk32();
            x = atomicAdd(&g_F[65536 + (i & 1) * 1024 + slot * 64 + (x >> 31)], 0u) & 0x7fffffffu;
            if (x == 0x7654321u) sts32(sb + R_BAR + 56, x);
            const int dt = (int)(clk32() - t0);
            if (i >= 2) { if (i & 1) tm[1] = min(tm[1], dt); else tm[0] = min(tm[0], dt); }
        }
        const int side = tm[1] > tm[0];
        const unsigned old = atomicAdd(&g_flags[(F_SIDE + side) * 32], 1u);
        unsigned c0, c1; int gd = 0;
#pragma unroll 1
        do { c0 = ldg_relaxed32(&g_flags[F_SIDE * 32]); c1 = ldg_relaxed32(&g_flags[(F_SIDE + 1) * 32]); } while ((int)(c0 + c1) < p.ncl && ++gd < 64 * SPIN_LIMIT);
        const int big = c1 > c0;
        role = side == big ? old : (big ? c1 : c0) + old;
        role |= (big ^ 1) << 8;
    }
    __syncwarp();
    asm volatile("barrier.cluster.arrive.relaxed.aligned;\nbarrier.cluster.wait.aligned;" ::: "memory");
    if (crank == 0 && warp == 0) {
        role = __shfl_sync(~0u, role, 0);
        if (lane < 16)
            asm volatile("st.async.weak.shared::cluster.mbarrier::complete_tx::bytes.u32 [%0], %1, [%2];"
                         :: "r"(mapa_u32(sb + R_BAR + 48, lane)), "r"(role), "r"(mapa_u32(sb + RB_ROLE, lane)) : "memory");
    }
    mbar_wait(sb + RB_ROLE, 0);
    const int rolew = __shfl_sync(~0u, lds32(sb + R_BAR + 48), 0);
    const int cl = rolew & 255;
    if (cl >= 4) return;
    const int cta = cl * 16 + crank;
    if (warp < 8) rec_qk(p, sb, cta, warp, lane, rolew >> 8);
    else rec_vo(p, sb, cta, warp, lane);
}

enum { J_KV = 0, J_QA = 1, J_O = 2, J_LN = 3, J_UP = 4, J_DN = 5, J_END = 6 };
constexpr int N_KV = NRB * 32;
constexpr int GRP = 16 + 8 + 4 + 14 + 4;
constexpr int LAG_O = 2, LAG_LN = 4, LAG_UP = 5, LAG_DN = 7;
constexpr int N_GRP = NRB + LAG_DN;
constexpr int N_JOBS = N_KV + N_GRP * GRP;
__device__ __forceinline__ int decode_job(int j) {
    if (j < N_KV) return J_KV | ((j >> 5) << 8) | ((j & 31) << 16);
    j -= N_KV;
    const int grp = j / GRP; int r = j % GRP;
    int type, rb;
    if (r < 4) { type = J_DN; rb = grp - LAG_DN; }
    else if (r < 18) { type = J_UP; rb = grp - LAG_UP; r -= 4; }
    else if (r < 22) { type = J_LN; rb = grp - LAG_LN; r -= 18; }
    else if (r < 30) { type = J_O; rb = grp - LAG_O; r -= 22; }
    else { type = J_QA; rb = grp; r -= 30; }
    if (rb < 0 || rb >= NRB) return J_END + 1;
    return type | (rb << 8) | (r << 16);
}

struct Pipe { uint32_t stage, phase; };
__device__ __forceinline__ void pipe_next(Pipe& p) { if (++p.stage == W_NST) { p.stage = 0; p.phase ^= 1; } }

__device__ __forceinline__ void producer(const Params& p, uint32_t sb) {
    Pipe pp{0, 1};
    const uint32_t bars = sb + SM_BAR;
    uint32_t seq = 0;
    while (true) {
        int jd, j;
        while (true) {
            j = p.job_begin + (int)atomicAdd(&g_flags[F_JOB * 32], 1u);
            if (j >= p.job_end) { jd = J_END; j = 2047; break; }
            jd = decode_job(j);
            if ((jd & 255) <= J_END) break;
        }
        TR(j, 1);
        const int type = jd & 255, rb = (jd >> 8) & 255, cb = jd >> 16;
        switch (type) {
            case J_QA: break;
            case J_O: wait_flag(F_O + rb, 32); break;
            case J_LN: wait_flag(F_OP + rb, 16); break;
            case J_UP: wait_flag(F_H2 + rb, 8); break;
            case J_DN: wait_flag(F_ACT + rb, 28); break;
            default: break;
        }
        if (type == J_UP || type == J_DN) fence_async_all();
        TR(j, 2);
        bool first = true;
        auto begin_stage = [&](uint32_t bytes) -> uint32_t {
            mbar_wait(bars + B_EMPTY + pp.stage * 8, pp.phase);
            if (first) { sts32(bars + B_RING + (seq & 7) * 4, (uint32_t)jd); sts32(bars + B_RING + 32 + (seq & 7) * 4, (uint32_t)j); first = false; }
            const uint32_t fb = bars + B_FULL + pp.stage * 8;
            if (bytes) mbar_expect_tx(fb, bytes); else mbar_arrive(fb);
            return fb;
        };
        if (type == J_END || type == J_LN) {
            begin_stage(0); pipe_next(pp);
            seq++;
            if (type == J_END) break;
            continue;
        }
        const CUtensorMap *ta, *tb0, *tb1;
        int k0 = 0, nk = 8, n0 = cb * 256, n1 = n0 + 128, nb = 4;
        switch (type) {
            case J_KV: ta = &p.tm_h; tb0 = tb1 = cb < 16 ? &p.tm_wk : &p.tm_wv; n0 = (cb & 15) * 256; n1 = n0 + 128; break;
            case J_QA: ta = &p.tm_h; tb0 = tb1 = &p.tm_wq; break;
            case J_O: ta = &p.tm_o; tb0 = tb1 = &p.tm_wo; n0 = (cb & 1) * 256; n1 = n0 + 128; k0 = (cb >> 1) * 1024; nk = 16; break;
            case J_UP: ta = &p.tm_h2; tb0 = &p.tm_wg; tb1 = &p.tm_wu; n0 = n1 = cb * 128; break;
            default: ta = &p.tm_act; tb0 = tb1 = &p.tm_wd; n0 = cb * 128; nk = 28; nb = 2; break;
        }
        const int m0 = rb * 128;
        for (int kb = 0; kb < nk; kb++) {
            const uint32_t fb = begin_stage(16384 + nb * 8192);
            const uint32_t st = sb + pp.stage * W_STAGE;
            const int k = k0 + kb * 64;
            tma_load2d(st, ta, k, m0, fb);
            tma_load2d(st + 8192, ta, k, m0 + 64, fb);
            tma_load2d(st + 16384, tb0, n0, k, fb);
            tma_load2d(st + 16384 + 8192, tb0, n0 + 64, k, fb);
            if (nb == 4) {
                tma_load2d(st + 16384 + 16384, tb1, n1, k, fb);
                tma_load2d(st + 16384 + 24576, tb1, n1 + 64, k, fb);
            }
            pipe_next(pp);
        }
        if (type == J_QA) {
            wait_flag(F_KV + rb, 64);
            wait_flag(F_MEM + rb, 64);
            fence_async_all();
            for (int i = 0; i < 4; i++) {
                const uint32_t fb = begin_stage(40960);
                const uint32_t st = sb + pp.stage * W_STAGE;
                const int col = (i & 1) * HD_ + (cb * 2 + (i >> 1)) * DH_;
                tma_load2d(st, &p.tm_kv, col, m0, fb);
                tma_load2d(st + 8192, &p.tm_kv, col, m0 + 64, fb);
                tma_load2d(st + 16384, &p.tm_kv, col + 64, m0, fb);
                tma_load2d(st + 24576, &p.tm_kv, col + 64, m0 + 64, fb);
                tma_load2d(st + 32768, &p.tm_kvm, col, rb * 32, fb);
                tma_load2d(st + 36864, &p.tm_kvm, col + 64, rb * 32, fb);
                pipe_next(pp);
            }
        } else if (type == J_DN) {
            const uint32_t fb = begin_stage(32768);
            const uint32_t st = sb + pp.stage * W_STAGE;
            tma_load2d(st, &p.tm_x1, n0, m0, fb);
            tma_load2d(st + 8192, &p.tm_x1, n0, m0 + 64, fb);
            tma_load2d(st + 16384, &p.tm_x1, n0 + 64, m0, fb);
            tma_load2d(st + 24576, &p.tm_x1, n0 + 64, m0 + 64, fb);
            pipe_next(pp);
        }
        seq++;
    }
}

__device__ __forceinline__ void store_warp(const Params& p, uint32_t sb, int wg, int lane) {
    const uint32_t bars = sb + SM_BAR;
    uint32_t seq = 0;
    while (true) {
        bar_sync(NB_ST + wg, 160);
        const uint32_t jd = lds32(bars + B_RING + (seq & 7) * 4);
        seq++;
        const int type = jd & 255, rb = (jd >> 8) & 255, cb = jd >> 16;
        if (type == J_END) break;
        if (lane == 0) {
            const uint32_t src = sb + W_STG + wg * 32768;
            const int m0 = rb * 128 + wg * 64;
            const CUtensorMap* tm = nullptr; int n0 = cb * 256, nbox = 4, mrow = m0, flag = 0;
            switch (type) {
                case J_KV: tm = &p.tm_kv; flag = F_KV + rb; break;
                case J_QA: tm = &p.tm_o; flag = F_O + rb; break;
                case J_O: tm = &p.tm_op; n0 = (cb & 1) * 256; mrow = (cb >> 1) * S_ + m0; flag = F_OP + rb; break;
                case J_LN: flag = F_H2 + rb; nbox = 0; break;
                case J_UP: tm = &p.tm_act; n0 = cb * 128; nbox = 2; flag = F_ACT + rb; break;
                default: tm = &p.tm_out; n0 = cb * 128; nbox = 2; flag = -1; break;
            }
            for (int b = 0; b < nbox; b++) tma_store2d(tm, src + b * 8192, n0 + b * 64, mrow);
            bulk_commit();
            bulk_wait0();
            mbar_arrive(bars + B_STGFREE + wg * 8);
            if (flag >= 0) { fence_async_all(); red_release(&g_flags[flag * 32], 1); }
        }
        __syncwarp();
    }
}

__device__ __forceinline__ float gelu_tanh(float x) {
    const float t = x * fmaf(-0.10294324397f, x * x, -2.30220819814f);
    float r; asm("rcp.approx.ftz.f32 %0, %1;" : "=f"(r) : "f"(1.f + ex2(t)));
    return x * r;
}

#define CTR(i) do {} while (0)

__device__ __forceinline__ void ln2_job(const Params& p, int row0, int lane) {
    float ga[16], c1[16], sm[16];
    uint4 u[4][2 * OSPLIT + 2];
#pragma unroll
    for (int rr = 0; rr < 4; rr++) {
        const int row = row0 + rr;
#pragma unroll
        for (int sp = 0; sp < OSPLIT; sp++) {
            const uint4* src = (const uint4*)(g_op + ((size_t)sp * S_ + row) * D_);
            u[rr][2 * sp] = __ldcg(src + lane); u[rr][2 * sp + 1] = __ldcg(src + 32 + lane);
        }
        const uint4* xr = (const uint4*)(p.x + (size_t)row * D_);
        u[rr][2 * OSPLIT] = __ldg(xr + lane); u[rr][2 * OSPLIT + 1] = __ldg(xr + 32 + lane);
    }
    load_mod16(g_mod + 2 * D_, lane, ga);
    float v[4][16];
#pragma unroll
    for (int rr = 0; rr < 4; rr++) {
        float a[16], t[16];
        unpack8(u[rr][0], a); unpack8(u[rr][1], a + 8);
#pragma unroll
        for (int sp = 1; sp < OSPLIT; sp++) {
            unpack8(u[rr][2 * sp], t); unpack8(u[rr][2 * sp + 1], t + 8);
#pragma unroll
            for (int i = 0; i < 16; i++) a[i] += t[i];
        }
        unpack8(u[rr][2 * OSPLIT], t); unpack8(u[rr][2 * OSPLIT + 1], t + 8);
#pragma unroll
        for (int i = 0; i < 16; i++) v[rr][i] = rbf(t[i] + rbf(ga[i] * rbf(a[i])));
        uint4* x1r = (uint4*)(g_x1 + (size_t)(row0 + rr) * D_);
        x1r[lane] = make_uint4(pack2(v[rr][0], v[rr][1]), pack2(v[rr][2], v[rr][3]), pack2(v[rr][4], v[rr][5]), pack2(v[rr][6], v[rr][7]));
        x1r[32 + lane] = make_uint4(pack2(v[rr][8], v[rr][9]), pack2(v[rr][10], v[rr][11]), pack2(v[rr][12], v[rr][13]), pack2(v[rr][14], v[rr][15]));
    }
    load_mod16(g_mod + 4 * D_, lane, c1);
    load_mod16(g_mod + 3 * D_, lane, sm);
#pragma unroll
    for (int i = 0; i < 16; i++) c1[i] = rbf(1.f + c1[i]);
#pragma unroll
    for (int rr = 0; rr < 4; rr++) {
        uint4 o0, o1;
        ln_mod_row(v[rr], c1, sm, o0, o1);
        uint4* hr = (uint4*)(g_h2 + (size_t)(row0 + rr) * D_);
        hr[lane] = o0; hr[32 + lane] = o1;
    }
}

__device__ __forceinline__ void consumer(const Params& p, uint32_t sb, int warp, int lane) {
    const uint32_t bars = sb + SM_BAR;
    const int wg = warp >> 2, wl = warp & 3;
    const uint32_t l7 = lane & 7, l8 = lane >> 3, g = lane >> 2, t = lane & 3;
    Pipe pp{0, 0};
    uint32_t seq = 0, stg_phase = 1;
    const int srow = wl * 16 + l7 + (l8 & 1) * 8;
    const uint32_t stg_base = sb + W_STG + wg * 32768 + srow * 128;
    const uint32_t sx = ((lane >> 4) ^ (srow & 7)) << 4;
#pragma unroll 1
    while (true) {
        mbar_wait(bars + B_FULL + pp.stage * 8, pp.phase);
        const uint32_t jd = lds32(bars + B_RING + (seq & 7) * 4);
        CTR(3);
        seq++;
        const int type = jd & 255, rb = (jd >> 8) & 255, cb = jd >> 16;
        if (type == J_END) { mbar_wait(bars + B_STGFREE + wg * 8, stg_phase); bar_arrive(NB_ST + wg, 160); break; }
        if (type == J_LN) {
            __syncwarp();
            if (lane == 0) mbar_arrive(bars + B_EMPTY + pp.stage * 8);
            pipe_next(pp);
            ln2_job(p, rb * 128 + cb * 32 + warp * 4, lane);
            mbar_wait(bars + B_STGFREE + wg * 8, stg_phase); stg_phase ^= 1;
            CTR(4); CTR(5);
            bar_arrive(NB_ST + wg, 160);
            continue;
        }
        if (type == J_DN) {
            float acc[64];
#pragma unroll
            for (int i = 0; i < 64; i++) acc[i] = 0.f;
#pragma unroll 1
            for (int kb = 0; kb < 28; kb++) {
                if (kb) mbar_wait(bars + B_FULL + pp.stage * 8, pp.phase);
                const uint32_t st = sb + pp.stage * W_STAGE;
                const uint64_t da = mkdesc(st + wg * 8192, 16, 1024), db = mkdesc(st + 16384, 8192, 1024);
                wg_fence();
#pragma unroll
                for (int ks = 0; ks < 4; ks++) wgmma_n128(acc, da + ks * 2, db + ks * 128, 1);
                wg_commit();
                wg_wait0();
                if (lane == 0) mbar_arrive(bars + B_EMPTY + pp.stage * 8);
                pipe_next(pp);
            }
            CTR(4);
            mbar_wait(bars + B_FULL + pp.stage * 8, pp.phase);
            const uint32_t st = sb + pp.stage * W_STAGE;
            mbar_wait(bars + B_STGFREE + wg * 8, stg_phase); stg_phase ^= 1;
            const float* gb = g_mod + 5 * D_ + cb * 128;
            const uint32_t xa = st + wg * 8192 + (wl * 16 + g) * 128 + (g << 4) + t * 4;
#pragma unroll
            for (int j = 0; j < 8; j++) {
                uint32_t r[4];
#pragma unroll
                for (int q = 0; q < 4; q++) {
                    const int nt = 2 * j + (q >> 1);
                    const uint32_t xw = lds32((xa ^ ((nt & 7) << 4)) + (nt >> 3) * 16384 + (q & 1) * 1024);
                    const float2 gv = __ldg((const float2*)(gb + nt * 8 + 2 * t));
                    const uint32_t dw = pack2(acc[8 * j + 2 * q], acc[8 * j + 2 * q + 1]);
                    const uint32_t mw = pack2(gv.x * bflo(dw), gv.y * bfhi(dw));
                    r[q] = pack2(bflo(xw) + bflo(mw), bfhi(xw) + bfhi(mw));
                }
                stsm4(stg_base + (j >> 2) * 8192 + (sx ^ ((2 * j & 7) << 4)), r[0], r[1], r[2], r[3]);
            }
            __syncwarp();
            if (lane == 0) mbar_arrive(bars + B_EMPTY + pp.stage * 8);
            pipe_next(pp);
            fence_async_smem();
            CTR(5);
            bar_arrive(NB_ST + wg, 160);
            continue;
        }
        float acc[128];
#pragma unroll
        for (int i = 0; i < 128; i++) acc[i] = 0.f;
        const int nk = type == J_O ? 16 : 8;
#pragma unroll 1
        for (int kb = 0; kb < nk; kb++) {
            if (kb) mbar_wait(bars + B_FULL + pp.stage * 8, pp.phase);
            const uint32_t st = sb + pp.stage * W_STAGE;
            const uint64_t da = mkdesc(st + wg * 8192, 16, 1024), db = mkdesc(st + 16384, 8192, 1024);
            wg_fence();
#pragma unroll
            for (int ks = 0; ks < 4; ks++) wgmma_n256(acc, da + ks * 2, db + ks * 128, 1);
            wg_commit();
            wg_wait0();
            if (lane == 0) mbar_arrive(bars + B_EMPTY + pp.stage * 8);
            pipe_next(pp);
        }
        CTR(4);
        if (type == J_QA) {
            uint32_t qf[64];
#pragma unroll
            for (int i = 0; i < 64; i++) qf[i] = pack2(acc[2 * i], acc[2 * i + 1]);
            const int sg = warp >> 1, half = warp & 1;
            const float sc = 0.08838834764831845f * 1.4426950408889634f;
            const uint32_t xoff = (sg >> 1) * 8192 + ((sg & 1) * 32 + l7) * 128;
            const uint32_t moff = 32768 + (sg * 8 + l7) * 128;
            const uint32_t kch = (l8 ^ l7) << 4;
            const uint32_t vch = ((l8 & 1) ^ l7) << 4;
            mbar_wait(bars + B_STGFREE + wg * 8, stg_phase); stg_phase ^= 1;
#pragma unroll
            for (int hh = 0; hh < 2; hh++) {
                mbar_wait(bars + B_FULL + pp.stage * 8, pp.phase);
                uint32_t st = sb + pp.stage * W_STAGE;
                float sa[5][4];
#pragma unroll
                for (int n = 0; n < 5; n++) sa[n][0] = sa[n][1] = sa[n][2] = sa[n][3] = 0.f;
#pragma unroll
                for (int i = 0; i < 4; i++) {
                    const uint32_t* q = qf + hh * 32 + i * 8;
                    uint32_t kk[5][4];
                    ldsm4(kk[0][0], kk[0][1], kk[0][2], kk[0][3], st + moff + (i >> 1) * 4096 + (kch ^ ((i & 1) * 64)));
#pragma unroll
                    for (int n = 1; n < 5; n++)
                        ldsm4(kk[n][0], kk[n][1], kk[n][2], kk[n][3], st + xoff + (n - 1) * 1024 + (i >> 1) * 16384 + (kch ^ ((i & 1) * 64)));
#pragma unroll
                    for (int n = 0; n < 5; n++) mma16816(sa[n], q[0], q[1], q[2], q[3], kk[n][0], kk[n][1]);
#pragma unroll
                    for (int n = 0; n < 5; n++) mma16816(sa[n], q[4], q[5], q[6], q[7], kk[n][2], kk[n][3]);
                }
                __syncwarp();
                if (lane == 0) mbar_arrive(bars + B_EMPTY + pp.stage * 8);
                pipe_next(pp);
                const int iq0 = half * 16 + g - 2 * t, iq1 = iq0 + 8;
                float m0 = fmaxf(sa[0][0], sa[0][1]), m1 = fmaxf(sa[0][2], sa[0][3]);
#pragma unroll
                for (int n = 1; n < 5; n++) {
#pragma unroll
                    for (int e = 0; e < 2; e++) {
                        const int jx = (n - 1) * 8 + e;
                        if (jx > iq0) sa[n][e] = -3.0e38f;
                        if (jx > iq1) sa[n][2 + e] = -3.0e38f;
                        m0 = fmaxf(m0, sa[n][e]); m1 = fmaxf(m1, sa[n][2 + e]);
                    }
                }
                m0 = fmaxf(m0, __shfl_xor_sync(~0u, m0, 1)); m1 = fmaxf(m1, __shfl_xor_sync(~0u, m1, 1));
                m0 = fmaxf(m0, __shfl_xor_sync(~0u, m0, 2)); m1 = fmaxf(m1, __shfl_xor_sync(~0u, m1, 2));
                m0 *= -sc; m1 *= -sc;
                float l0 = 0.f, l1 = 0.f;
                uint32_t p0[5], p1[5];
#pragma unroll
                for (int n = 0; n < 5; n++) {
                    const float e0 = ex2(fmaf(sa[n][0], sc, m0)), e1 = ex2(fmaf(sa[n][1], sc, m0));
                    const float e2 = ex2(fmaf(sa[n][2], sc, m1)), e3 = ex2(fmaf(sa[n][3], sc, m1));
                    l0 += e0 + e1; l1 += e2 + e3;
                    p0[n] = pack2(e0, e1); p1[n] = pack2(e2, e3);
                }
                l0 += __shfl_xor_sync(~0u, l0, 1); l1 += __shfl_xor_sync(~0u, l1, 1);
                l0 += __shfl_xor_sync(~0u, l0, 2); l1 += __shfl_xor_sync(~0u, l1, 2);
                const float i0 = __fdividef(1.f, l0), i1 = __fdividef(1.f, l1);
                mbar_wait(bars + B_FULL + pp.stage * 8, pp.phase);
                st = sb + pp.stage * W_STAGE;
#pragma unroll
                for (int bx = 0; bx < 2; bx++) {
                    float o[8][4];
                    uint32_t vm[8], v0[4][4], v1[4][4];
#pragma unroll
                    for (int ep = 0; ep < 4; ep++) {
                        ldsm2t(vm[2 * ep], vm[2 * ep + 1], st + moff + bx * 4096 + (vch ^ (ep << 5)));
                        const uint32_t va = st + xoff + (l8 >> 1) * 1024 + bx * 16384 + (vch ^ (ep << 5));
                        ldsm4t(v0[ep][0], v0[ep][1], v0[ep][2], v0[ep][3], va);
                        ldsm4t(v1[ep][0], v1[ep][1], v1[ep][2], v1[ep][3], va + 2048);
                    }
#pragma unroll
                    for (int n = 0; n < 8; n++) { o[n][0] = o[n][1] = o[n][2] = o[n][3] = 0.f; mma16816(o[n], p0[0], p1[0], p0[1], p1[1], vm[n], v0[n >> 1][n & 1]); }
#pragma unroll
                    for (int n = 0; n < 8; n++) mma16816(o[n], p0[2], p1[2], p0[3], p1[3], v0[n >> 1][2 + (n & 1)], v1[n >> 1][n & 1]);
#pragma unroll
                    for (int n = 0; n < 8; n++) mma1688(o[n], p0[4], p1[4], v1[n >> 1][2 + (n & 1)]);
#pragma unroll
                    for (int ep = 0; ep < 4; ep++)
                        stsm4(stg_base + (hh * 2 + bx) * 8192 + (sx ^ (ep << 5)),
                              pack2(o[2 * ep][0] * i0, o[2 * ep][1] * i0), pack2(o[2 * ep][2] * i1, o[2 * ep][3] * i1),
                              pack2(o[2 * ep + 1][0] * i0, o[2 * ep + 1][1] * i0), pack2(o[2 * ep + 1][2] * i1, o[2 * ep + 1][3] * i1));
                }
                __syncwarp();
                if (lane == 0) mbar_arrive(bars + B_EMPTY + pp.stage * 8);
                pipe_next(pp);
            }
        } else if (type == J_UP) {
            mbar_wait(bars + B_STGFREE + wg * 8, stg_phase); stg_phase ^= 1;
#pragma unroll
            for (int j = 0; j < 8; j++) {
                uint32_t r[4];
#pragma unroll
                for (int q = 0; q < 4; q++) {
                    const uint32_t gw = pack2(acc[8 * j + 2 * q], acc[8 * j + 2 * q + 1]);
                    const uint32_t uw = pack2(acc[64 + 8 * j + 2 * q], acc[64 + 8 * j + 2 * q + 1]);
                    const uint32_t aw = pack2(gelu_tanh(bflo(gw)), gelu_tanh(bfhi(gw)));
                    r[q] = pack2(bflo(aw) * bflo(uw), bfhi(aw) * bfhi(uw));
                }
                stsm4(stg_base + (j >> 2) * 8192 + (sx ^ ((2 * j & 7) << 4)), r[0], r[1], r[2], r[3]);
            }
        } else {
            mbar_wait(bars + B_STGFREE + wg * 8, stg_phase); stg_phase ^= 1;
#pragma unroll
            for (int j = 0; j < 16; j++)
                stsm4(stg_base + (j >> 2) * 8192 + (sx ^ ((2 * j & 7) << 4)),
                      pack2(acc[8 * j], acc[8 * j + 1]), pack2(acc[8 * j + 2], acc[8 * j + 3]),
                      pack2(acc[8 * j + 4], acc[8 * j + 5]), pack2(acc[8 * j + 6], acc[8 * j + 7]));
        }
        fence_async_smem();
        CTR(5);
        bar_arrive(NB_ST + wg, 160);
    }
}

__global__ void __launch_bounds__(384, 1) k_work(const __grid_constant__ Params p) {
    extern __shared__ __align__(1024) unsigned char smem_raw[];
    const uint32_t sb = smem_u32(smem_raw);
    if (sb & 1023) __trap();
    const int warp = __shfl_sync(~0u, threadIdx.x >> 5, 0);
    int lane; asm volatile("mov.u32 %0, %%laneid;" : "=r"(lane));
    if (threadIdx.x == 0) {
        const uint32_t bars = sb + SM_BAR;
        for (int i = 0; i < W_NST; i++) { mbar_init(bars + B_FULL + i * 8, 1); mbar_init(bars + B_EMPTY + i * 8, 8); }
        mbar_init(bars + B_STGFREE, 1); mbar_init(bars + B_STGFREE + 8, 1);
        asm volatile("fence.mbarrier_init.release.cluster;" ::: "memory");
    }
    __syncthreads();
    if (warp < 8) {
        asm volatile("setmaxnreg.inc.sync.aligned.u32 232;");
        consumer(p, sb, warp, lane);
    } else {
        asm volatile("setmaxnreg.dec.sync.aligned.u32 40;");
        if (warp == 8) { if (lane == 0) producer(p, sb); }
        else if (warp < 11) store_warp(p, sb, warp - 9, lane);
    }
}

typedef CUresult (*EncodeFn)(CUtensorMap*, CUtensorMapDataType, cuuint32_t, void*, const cuuint64_t*, const cuuint64_t*,
                             const cuuint32_t*, const cuuint32_t*, CUtensorMapInterleave, CUtensorMapSwizzle,
                             CUtensorMapL2promotion, CUtensorMapFloatOOBfill);

static void make_map(EncodeFn enc, CUtensorMap* m, const void* ptr, uint64_t rows, uint64_t cols, uint32_t box_rows) {
    cuuint64_t dims[2] = {cols, rows};
    cuuint64_t strides[1] = {cols * 2};
    cuuint32_t box[2] = {64, box_rows};
    cuuint32_t es[2] = {1, 1};
    enc(m, CU_TENSOR_MAP_DATA_TYPE_BFLOAT16, 2, const_cast<void*>(ptr), dims, strides, box, es, CU_TENSOR_MAP_INTERLEAVE_NONE,
        CU_TENSOR_MAP_SWIZZLE_128B, CU_TENSOR_MAP_L2_PROMOTION_L2_256B, CU_TENSOR_MAP_FLOAT_OOB_FILL_NONE);
}
template <typename T> static void* sym_addr(T& sym) { void* p = nullptr; cudaGetSymbolAddress(&p, sym); return p; }

extern "C" void kernel_launch(void* const* d_in, const int* in_sizes, int n_in, void* d_out, int out_size) {
    static Params prm;
    static RecParams rp;
    static bool ready = false;
    static const void* key[14];
    bool same = ready;
    for (int i = 0; i < 13 && same; i++) same = key[i] == d_in[i];
    same = same && key[13] == d_out;
    if (!same) {
        void* fn = nullptr;
        cudaDriverEntryPointQueryResult qr;
        cudaGetDriverEntryPoint("cuTensorMapEncodeTiled", &fn, cudaEnableDefault, &qr);
        EncodeFn enc = (EncodeFn)fn;
        make_map(enc, &prm.tm_h, sym_addr(g_h), S_, D_, 64);
        make_map(enc, &prm.tm_kv, sym_addr(g_kv), S_, 2 * HD_, 64);
        make_map(enc, &prm.tm_kvm, sym_addr(g_kvm), NSEG * 8, 2 * HD_, 32);
        make_map(enc, &prm.tm_o, sym_addr(g_o), S_, HD_, 64);
        make_map(enc, &prm.tm_op, sym_addr(g_op), OSPLIT * S_, D_, 64);
        make_map(enc, &prm.tm_h2, sym_addr(g_h2), S_, D_, 64);
        make_map(enc, &prm.tm_act, sym_addr(g_act), S_, DF_, 64);
        make_map(enc, &prm.tm_x1, sym_addr(g_x1), S_, D_, 64);
        make_map(enc, &prm.tm_out, d_out, S_, D_, 64);
        make_map(enc, &prm.tm_wq, d_in[2], D_, HD_, 64);
        make_map(enc, &prm.tm_wk, d_in[3], D_, HD_, 64);
        make_map(enc, &prm.tm_wv, d_in[4], D_, HD_, 64);
        make_map(enc, &prm.tm_wo, d_in[5], HD_, D_, 64);
        make_map(enc, &prm.tm_wg, d_in[8], D_, DF_, 64);
        make_map(enc, &prm.tm_wu, d_in[9], D_, DF_, 64);
        make_map(enc, &prm.tm_wd, d_in[10], DF_, D_, 64);
        prm.x = (const bf16*)d_in[0];
        rp.mem0 = (const bf16*)d_in[1];
        rp.wq = (const bf16*)d_in[2]; rp.wk = (const bf16*)d_in[3]; rp.wv = (const bf16*)d_in[4]; rp.wo = (const bf16*)d_in[5];
        cudaFuncSetAttribute(k_work, cudaFuncAttributeMaxDynamicSharedMemorySize, SMEM_BYTES);
        cudaFuncSetAttribute(k_rec, cudaFuncAttributeMaxDynamicSharedMemorySize, R_SMEM);
        cudaFuncSetAttribute(k_rec, cudaFuncAttributeNonPortableClusterSizeAllowed, 1);
        {
            cudaLaunchConfig_t cfg = {};
            cfg.gridDim = dim3(128); cfg.blockDim = dim3(384); cfg.dynamicSmemBytes = R_SMEM;
            cudaLaunchAttribute at[1];
            at[0].id = cudaLaunchAttributeClusterDimension; at[0].val.clusterDim.x = 16; at[0].val.clusterDim.y = 1; at[0].val.clusterDim.z = 1;
            cfg.attrs = at; cfg.numAttrs = 1;
            int n = 0;
            cudaOccupancyMaxActiveClusters(&n, k_rec, &cfg);
            rp.ncl = n < 4 ? 4 : (n > 8 ? 8 : n);
        }
        for (int i = 0; i < 13; i++) key[i] = d_in[i];
        key[13] = d_out;
        ready = true;
    }
    cudaStream_t st = cudaStreamPerThread;
    k_mod<<<96, 256, 0, st>>>((const bf16*)d_in[11], (const bf16*)d_in[12]);
    k_ln1<<<S_ / 8, 256, 0, st>>>((const bf16*)d_in[0]);
    auto launch_rec = [&]() {
        cudaLaunchConfig_t cfg = {};
        cfg.gridDim = dim3(16 * rp.ncl); cfg.blockDim = dim3(384); cfg.dynamicSmemBytes = R_SMEM; cfg.stream = st;
        cudaLaunchAttribute at[1];
        at[0].id = cudaLaunchAttributeClusterDimension; at[0].val.clusterDim.x = 16; at[0].val.clusterDim.y = 1; at[0].val.clusterDim.z = 1;
        cfg.attrs = at; cfg.numAttrs = 1;
        cudaLaunchKernelEx(&cfg, k_rec, rp);
    };
    auto launch_work = [&](int j0, int j1, int pdl) {
        prm.job_begin = j0; prm.job_end = j1;
        cudaLaunchConfig_t cfg = {};
        cfg.gridDim = dim3(132); cfg.blockDim = dim3(384); cfg.dynamicSmemBytes = SMEM_BYTES; cfg.stream = st;
        cudaLaunchAttribute at[1];
        at[0].id = cudaLaunchAttributeProgrammaticStreamSerialization; at[0].val.programmaticStreamSerializationAllowed = 1;
        cfg.attrs = at; cfg.numAttrs = pdl;
        cudaLaunchKernelEx(&cfg, k_work, prm);
    };
    launch_rec();
    launch_work(0, N_JOBS, 1);
}
```

```cpp
#include <cuda_runtime.h>
#include <cuda_bf16.h>
#include <cuda.h>
#include <stdint.h>

typedef __nv_bfloat16 bf16;

constexpr int S_ = 2048, D_ = 512, H_ = 32, DH_ = 128, HD_ = 4096, NSEG = 64, DF_ = 1792;
constexpr int NRB = 16;
constexpr int OSPLIT = 4;

__device__ __align__(1024) bf16 g_h[S_ * D_];
__device__ __align__(1024) bf16 g_kv[S_ * 2 * HD_];
__device__ __align__(1024) bf16 g_kvm[NSEG * 8 * 2 * HD_];
__device__ __align__(1024) bf16 g_o[S_ * HD_];
constexpr int FINE_RB = 15;
constexpr int OSPLIT2 = 16;
constexpr int OP_ROWS = OSPLIT * S_ + OSPLIT2 * (NRB - FINE_RB) * 128;
__device__ __align__(1024) bf16 g_op[OP_ROWS * D_];
__device__ __align__(1024) bf16 g_x1[S_ * D_];
__device__ __align__(1024) bf16 g_h2[S_ * D_];
__device__ __align__(1024) bf16 g_act[S_ * DF_];
__device__ __align__(1024) bf16 g_mod[6 * D_];
__device__ uint32_t g_Fraw[131072 + 65536 + 2048];
#define g_F ((uint32_t*)(((uint64_t)g_Fraw + 0x7FFFFull) & ~0x7FFFFull))
constexpr int F_KV = 0, F_MEM = 16, F_O = 80, F_OP = 96, F_H2 = 112, F_ACT = 128, F_JOB = 144, F_SIDE = 145  , F_TOTAL = 160;
__device__ __align__(128) unsigned int g_flags[F_TOTAL * 32];
#define TR(j, i) do {} while (0)

__device__ __forceinline__ uint32_t smem_u32(const void* p) { return (uint32_t)__cvta_generic_to_shared(p); }
__device__ __forceinline__ uint32_t clk32() { uint32_t c; asm volatile("mov.u32 %0, %%clock;" : "=r"(c)); return c; }
__device__ __forceinline__ uint32_t mapa_u32(uint32_t addr, uint32_t rank) {
    uint32_t r; asm volatile("mapa.shared::cluster.u32 %0, %1, %2;" : "=r"(r) : "r"(addr), "r"(rank)); return r;
}
__device__ __forceinline__ void mbar_init(uint32_t bar, uint32_t cnt) {
    asm volatile("mbarrier.init.shared::cta.b64 [%0], %1;" :: "r"(bar), "r"(cnt) : "memory");
}
__device__ __forceinline__ void mbar_inval(uint32_t bar) {
    asm volatile("mbarrier.inval.shared::cta.b64 [%0];" :: "r"(bar) : "memory");
}
__device__ __forceinline__ void mbar_expect_tx(uint32_t bar, uint32_t bytes) {
    asm volatile("mbarrier.arrive.expect_tx.shared::cta.b64 _, [%0], %1;" :: "r"(bar), "r"(bytes) : "memory");
}
__device__ __forceinline__ void mbar_arrive(uint32_t bar) {
    asm volatile("mbarrier.arrive.shared::cta.b64 _, [%0];" :: "r"(bar) : "memory");
}
__device__ __forceinline__ bool mbar_try_wait(uint32_t bar, uint32_t parity) {
    uint32_t ok;
    asm volatile("{\n.reg .pred p;\nmbarrier.try_wait.parity.shared::cta.b64 p, [%1], %2;\nselp.u32 %0, 1, 0, p;\n}"
                 : "=r"(ok) : "r"(bar), "r"(parity) : "memory");
    return ok;
}
__device__ __forceinline__ bool mbar_try_wait_cluster(uint32_t bar, uint32_t parity) {
    uint32_t ok;
    asm volatile("{\n.reg .pred p;\nmbarrier.try_wait.parity.acquire.cluster.shared::cta.b64 p, [%1], %2;\nselp.u32 %0, 1, 0, p;\n}"
                 : "=r"(ok) : "r"(bar), "r"(parity) : "memory");
    return ok;
}
constexpr int SPIN_LIMIT = 1 << 18;
#define TIMEOUT(code, info) do {} while (0)
__device__ __forceinline__ void mbar_wait(uint32_t bar, uint32_t parity) {
    int g = 0;
#pragma unroll 1
    while (!mbar_try_wait(bar, parity)) { if (++g >= SPIN_LIMIT) { TIMEOUT(0, bar & 255); break; } }
}
__device__ __forceinline__ void mbar_wait_cluster(uint32_t bar, uint32_t parity) {
    int g = 0;
#pragma unroll 1
    while (!mbar_try_wait_cluster(bar, parity)) { if (++g >= SPIN_LIMIT) { TIMEOUT(1, bar & 255); break; } }
}
__device__ __forceinline__ void bar_sync(int id, int n) { asm volatile("bar.sync %0, %1;" :: "r"(id), "r"(n) : "memory"); }
__device__ __forceinline__ void bar_arrive(int id, int n) { asm volatile("bar.arrive %0, %1;" :: "r"(id), "r"(n) : "memory"); }
__device__ __forceinline__ void cluster_sync_all() {
    asm volatile("barrier.cluster.arrive.aligned;\nbarrier.cluster.wait.aligned;" ::: "memory");
}
__device__ __forceinline__ void st_async_v2(uint32_t addr, float a, float b, uint32_t bar) {
    asm volatile("st.async.weak.shared::cluster.mbarrier::complete_tx::bytes.v2.f32 [%0], {%1,%2}, [%3];"
                 :: "r"(addr), "f"(a), "f"(b), "r"(bar) : "memory");
}
__device__ __forceinline__ void st_async_v4(uint32_t addr, uint4 v, uint32_t bar) {
    asm volatile("st.async.weak.shared::cluster.mbarrier::complete_tx::bytes.v4.b32 [%0], {%1,%2,%3,%4}, [%5];"
                 :: "r"(addr), "r"(v.x), "r"(v.y), "r"(v.z), "r"(v.w), "r"(bar) : "memory");
}
__device__ __forceinline__ uint2 ldg_relaxed2(const uint2* p) {
    uint2 v;
    asm volatile("ld.relaxed.gpu.global.v2.b32 {%0,%1}, [%2];" : "=r"(v.x), "=r"(v.y) : "l"(p) : "memory");
    return v;
}
__device__ __forceinline__ void stg_relaxed2(uint2* p, uint2 v) {
    asm volatile("st.relaxed.gpu.global.v2.b32 [%0], {%1,%2};" :: "l"(p), "r"(v.x), "r"(v.y) : "memory");
}
__device__ __forceinline__ uint4 ldg_relaxed(const uint4* p) {
    uint4 v;
    asm volatile("ld.relaxed.gpu.global.v4.b32 {%0,%1,%2,%3}, [%4];" : "=r"(v.x), "=r"(v.y), "=r"(v.z), "=r"(v.w) : "l"(p) : "memory");
    return v;
}
__device__ __forceinline__ void stg_relaxed(uint4* p, uint4 v) {
    asm volatile("st.relaxed.gpu.global.v4.b32 [%0], {%1,%2,%3,%4};" :: "l"(p), "r"(v.x), "r"(v.y), "r"(v.z), "r"(v.w) : "memory");
}
__device__ __forceinline__ void stg_relaxed32(uint32_t* p, uint32_t v) {
    asm volatile("st.relaxed.gpu.global.b32 [%0], %1;" :: "l"(p), "r"(v) : "memory");
}
__device__ __forceinline__ uint32_t ldg_relaxed32(const uint32_t* p) {
    uint32_t v; asm volatile("ld.relaxed.gpu.global.b32 %0, [%1];" : "=r"(v) : "l"(p) : "memory"); return v;
}
__device__ __forceinline__ unsigned int ld_acquire(const unsigned int* p) {
    unsigned int v; asm volatile("ld.acquire.gpu.global.u32 %0, [%1];" : "=r"(v) : "l"(p) : "memory"); return v;
}
__device__ __forceinline__ void red_release(unsigned int* p, unsigned int v) {
    asm volatile("red.release.gpu.global.add.u32 [%0], %1;" :: "l"(p), "r"(v) : "memory");
}
__device__ __forceinline__ void wait_flag(int idx, unsigned int target) {
    const unsigned int* p = &g_flags[idx * 32];
    int g = 0;
#pragma unroll 1
    while (ld_acquire(p) < target) { __nanosleep(20); if (++g >= 64 * SPIN_LIMIT) { TIMEOUT(2, idx); break; } }
}
__device__ __forceinline__ void cp_async16(uint32_t dst, const void* src) {
    asm volatile("cp.async.cg.shared.global [%0], [%1], 16;" :: "r"(dst), "l"(src) : "memory");
}
__device__ __forceinline__ void cp_async_commit() { asm volatile("cp.async.commit_group;" ::: "memory"); }
template <int N> __device__ __forceinline__ void cp_async_wait() { asm volatile("cp.async.wait_group %0;" :: "n"(N) : "memory"); }
__device__ __forceinline__ void ldsm4(uint32_t& r0, uint32_t& r1, uint32_t& r2, uint32_t& r3, uint32_t addr) {
    asm volatile("ldmatrix.sync.aligned.m8n8.x4.shared.b16 {%0,%1,%2,%3}, [%4];" : "=r"(r0), "=r"(r1), "=r"(r2), "=r"(r3) : "r"(addr) : "memory");
}
__device__ __forceinline__ void ldsm4t(uint32_t& r0, uint32_t& r1, uint32_t& r2, uint32_t& r3, uint32_t addr) {
    asm volatile("ldmatrix.sync.aligned.m8n8.x4.trans.shared.b16 {%0,%1,%2,%3}, [%4];" : "=r"(r0), "=r"(r1), "=r"(r2), "=r"(r3) : "r"(addr) : "memory");
}
__device__ __forceinline__ void ldsm2t(uint32_t& r0, uint32_t& r1, uint32_t addr) {
    asm volatile("ldmatrix.sync.aligned.m8n8.x2.trans.shared.b16 {%0,%1}, [%2];" : "=r"(r0), "=r"(r1) : "r"(addr) : "memory");
}
__device__ __forceinline__ void stsm4(uint32_t addr, uint32_t r0, uint32_t r1, uint32_t r2, uint32_t r3) {
    asm volatile("stmatrix.sync.aligned.m8n8.x4.shared.b16 [%0], {%1,%2,%3,%4};" :: "r"(addr), "r"(r0), "r"(r1), "r"(r2), "r"(r3) : "memory");
}
__device__ __forceinline__ void stsm2t(uint32_t addr, uint32_t r0, uint32_t r1) {
    asm volatile("stmatrix.sync.aligned.m8n8.x2.trans.shared.b16 [%0], {%1,%2};" :: "r"(addr), "r"(r0), "r"(r1) : "memory");
}
__device__ __forceinline__ void mma16816(float* d, uint32_t a0, uint32_t a1, uint32_t a2, uint32_t a3, uint32_t b0, uint32_t b1) {
    asm volatile("mma.sync.aligned.m16n8k16.row.col.f32.bf16.bf16.f32 {%0,%1,%2,%3}, {%4,%5,%6,%7}, {%8,%9}, {%0,%1,%2,%3};"
                 : "+f"(d[0]), "+f"(d[1]), "+f"(d[2]), "+f"(d[3]) : "r"(a0), "r"(a1), "r"(a2), "r"(a3), "r"(b0), "r"(b1));
}
__device__ __forceinline__ void mma1688(float* d, uint32_t a0, uint32_t a1, uint32_t b0) {
    asm volatile("mma.sync.aligned.m16n8k8.row.col.f32.bf16.bf16.f32 {%0,%1,%2,%3}, {%4,%5}, {%6}, {%0,%1,%2,%3};"
                 : "+f"(d[0]), "+f"(d[1]), "+f"(d[2]), "+f"(d[3]) : "r"(a0), "r"(a1), "r"(b0));
}
__device__ __forceinline__ void mma16816h(float* d, uint32_t a0, uint32_t a2, uint32_t b0, uint32_t b1) {
    asm volatile("{\n.reg .b32 ju, jv;\nmma.sync.aligned.m16n8k16.row.col.f32.bf16.bf16.f32 {%0,%1,%2,%3}, {%4,ju,%5,jv}, {%6,%7}, {%0,%1,%2,%3};\n}"
                 : "+f"(d[0]), "+f"(d[1]), "+f"(d[2]), "+f"(d[3]) : "r"(a0), "r"(a2), "r"(b0), "r"(b1));
}
__device__ __forceinline__ void mma1688h(float* d, uint32_t a0, uint32_t b0) {
    asm volatile("{\n.reg .b32 ju;\nmma.sync.aligned.m16n8k8.row.col.f32.bf16.bf16.f32 {%0,%1,%2,%3}, {%4,ju}, {%5}, {%0,%1,%2,%3};\n}"
                 : "+f"(d[0]), "+f"(d[1]), "+f"(d[2]), "+f"(d[3]) : "r"(a0), "r"(b0));
}
__device__ __forceinline__ uint32_t pack2(float lo, float hi) {
    uint32_t r; asm("cvt.rn.bf16x2.f32 %0, %1, %2;" : "=r"(r) : "f"(hi), "f"(lo)); return r;
}
__device__ __forceinline__ float bflo(uint32_t w) { return __uint_as_float(w << 16); }
__device__ __forceinline__ float bfhi(uint32_t w) { return __uint_as_float(w & 0xffff0000u); }
__device__ __forceinline__ float rbf(float x) { return __bfloat162float(__float2bfloat16_rn(x)); }
__device__ __forceinline__ float ex2(float x) { float y; asm("ex2.approx.ftz.f32 %0, %1;" : "=f"(y) : "f"(x)); return y; }
__device__ __forceinline__ void sts128(uint32_t addr, uint4 v) {
    asm volatile("st.shared.v4.b32 [%0], {%1,%2,%3,%4};" :: "r"(addr), "r"(v.x), "r"(v.y), "r"(v.z), "r"(v.w) : "memory");
}
__device__ __forceinline__ uint4 lds128(uint32_t addr) {
    uint4 v; asm volatile("ld.shared.v4.b32 {%0,%1,%2,%3}, [%4];" : "=r"(v.x), "=r"(v.y), "=r"(v.z), "=r"(v.w) : "r"(addr) : "memory"); return v;
}
__device__ __forceinline__ float2 lds64f(uint32_t addr) {
    float2 v; asm volatile("ld.shared.v2.f32 {%0,%1}, [%2];" : "=f"(v.x), "=f"(v.y) : "r"(addr) : "memory"); return v;
}
__device__ __forceinline__ float lds32f(uint32_t addr) {
    float v; asm volatile("ld.shared.f32 %0, [%1];" : "=f"(v) : "r"(addr) : "memory"); return v;
}
__device__ __forceinline__ uint32_t lds32(uint32_t addr) {
    uint32_t v; asm volatile("ld.shared.b32 %0, [%1];" : "=r"(v) : "r"(addr) : "memory"); return v;
}
__device__ __forceinline__ void sts32(uint32_t addr, uint32_t v) { asm volatile("st.shared.b32 [%0], %1;" :: "r"(addr), "r"(v) : "memory"); }
__device__ __forceinline__ void sts64f(uint32_t addr, float a, float b) { asm volatile("st.shared.v2.f32 [%0], {%1,%2};" :: "r"(addr), "f"(a), "f"(b) : "memory"); }

__device__ __forceinline__ void tma_load2d(uint32_t dst, const CUtensorMap* tm, int c0, int c1, uint32_t bar) {
    asm volatile("cp.async.bulk.tensor.2d.shared::cluster.global.mbarrier::complete_tx::bytes [%0], [%1, {%3, %4}], [%2];"
                 :: "r"(dst), "l"(tm), "r"(bar), "r"(c0), "r"(c1) : "memory");
}
__device__ __forceinline__ void tma_store2d(const CUtensorMap* tm, uint32_t src, int c0, int c1) {
    asm volatile("cp.async.bulk.tensor.2d.global.shared::cta.bulk_group [%0, {%2, %3}], [%1];"
                 :: "l"(tm), "r"(src), "r"(c0), "r"(c1) : "memory");
}
__device__ __forceinline__ void bulk_commit() { asm volatile("cp.async.bulk.commit_group;" ::: "memory"); }
__device__ __forceinline__ void bulk_wait0() { asm volatile("cp.async.bulk.wait_group 0;" ::: "memory"); }
__device__ __forceinline__ void fence_async_smem() { asm volatile("fence.proxy.async.shared::cta;" ::: "memory"); }
__device__ __forceinline__ void fence_async_all() { asm volatile("fence.proxy.async;" ::: "memory"); }

__device__ __forceinline__ void wg_fence() { asm volatile("wgmma.fence.sync.aligned;" ::: "memory"); }
__device__ __forceinline__ void wg_commit() { asm volatile("wgmma.commit_group.sync.aligned;" ::: "memory"); }
__device__ __forceinline__ void wg_wait0() { asm volatile("wgmma.wait_group.sync.aligned 0;" ::: "memory"); }
__device__ __forceinline__ uint64_t mkdesc(uint32_t saddr, uint32_t lbo, uint32_t sbo) {
    return (uint64_t)((saddr & 0x3FFFF) >> 4) | ((uint64_t)(lbo >> 4) << 16) | ((uint64_t)(sbo >> 4) << 32) | (1ull << 62);
}
#define ACC8(i) "+f"(d[i]), "+f"(d[i + 1]), "+f"(d[i + 2]), "+f"(d[i + 3]), "+f"(d[i + 4]), "+f"(d[i + 5]), "+f"(d[i + 6]), "+f"(d[i + 7])
__device__ __forceinline__ void wgmma_n256(float* d, uint64_t da, uint64_t db, int scale_d) {
    asm volatile(
        "{\n.reg .pred p;\nsetp.ne.b32 p, %130, 0;\n"
        "wgmma.mma_async.sync.aligned.m64n256k16.f32.bf16.bf16 "
        "{%0,%1,%2,%3,%4,%5,%6,%7,%8,%9,%10,%11,%12,%13,%14,%15,%16,%17,%18,%19,%20,%21,%22,%23,%24,%25,%26,%27,%28,%29,%30,%31,"
        "%32,%33,%34,%35,%36,%37,%38,%39,%40,%41,%42,%43,%44,%45,%46,%47,%48,%49,%50,%51,%52,%53,%54,%55,%56,%57,%58,%59,%60,%61,%62,%63,"
        "%64,%65,%66,%67,%68,%69,%70,%71,%72,%73,%74,%75,%76,%77,%78,%79,%80,%81,%82,%83,%84,%85,%86,%87,%88,%89,%90,%91,%92,%93,%94,%95,"
        "%96,%97,%98,%99,%100,%101,%102,%103,%104,%105,%106,%107,%108,%109,%110,%111,%112,%113,%114,%115,%116,%117,%118,%119,%120,%121,%122,%123,%124,%125,%126,%127}, "
        "%128, %129, p, 1, 1, 0, 1;\n}"
        : ACC8(0), ACC8(8), ACC8(16), ACC8(24), ACC8(32), ACC8(40), ACC8(48), ACC8(56),
          ACC8(64), ACC8(72), ACC8(80), ACC8(88), ACC8(96), ACC8(104), ACC8(112), ACC8(120)
        : "l"(da), "l"(db), "r"(scale_d));
}
__device__ __forceinline__ void wgmma_n128(float* d, uint64_t da, uint64_t db, int scale_d) {
    asm volatile(
        "{\n.reg .pred p;\nsetp.ne.b32 p, %66, 0;\n"
        "wgmma.mma_async.sync.aligned.m64n128k16.f32.bf16.bf16 "
        "{%0,%1,%2,%3,%4,%5,%6,%7,%8,%9,%10,%11,%12,%13,%14,%15,%16,%17,%18,%19,%20,%21,%22,%23,%24,%25,%26,%27,%28,%29,%30,%31,"
        "%32,%33,%34,%35,%36,%37,%38,%39,%40,%41,%42,%43,%44,%45,%46,%47,%48,%49,%50,%51,%52,%53,%54,%55,%56,%57,%58,%59,%60,%61,%62,%63}, "
        "%64, %65, p, 1, 1, 0, 1;\n}"
        : ACC8(0), ACC8(8), ACC8(16), ACC8(24), ACC8(32), ACC8(40), ACC8(48), ACC8(56)
        : "l"(da), "l"(db), "r"(scale_d));
}

__device__ __forceinline__ void wgmma_n64(float* d, uint64_t da, uint64_t db) {
    asm volatile(
        "wgmma.mma_async.sync.aligned.m64n64k16.f32.bf16.bf16 "
        "{%0,%1,%2,%3,%4,%5,%6,%7,%8,%9,%10,%11,%12,%13,%14,%15,%16,%17,%18,%19,%20,%21,%22,%23,%24,%25,%26,%27,%28,%29,%30,%31}, "
        "%32, %33, 1, 1, 1, 0, 1;"
        : ACC8(0), ACC8(8), ACC8(16), ACC8(24)
        : "l"(da), "l"(db));
}
__device__ __forceinline__ void wgmma_n8_ta(float* d, uint64_t da, uint64_t db, int scale_d) {
    asm volatile(
        "{\n.reg .pred p;\nsetp.ne.b32 p, %6, 0;\n"
        "wgmma.mma_async.sync.aligned.m64n8k16.f32.bf16.bf16 {%0,%1,%2,%3}, %4, %5, p, 1, 1, 1, 0;\n}"
        : "+f"(d[0]), "+f"(d[1]), "+f"(d[2]), "+f"(d[3]) : "l"(da), "l"(db), "r"(scale_d));
}

struct PrefetchList { const bf16* p[5]; };
__global__ void __launch_bounds__(256) k_mod(const bf16* __restrict__ c, const bf16* __restrict__ w_mod, const PrefetchList pf) {
    asm volatile("griddepcontrol.launch_dependents;");
    __shared__ float s_c[D_];
    __shared__ float s_red[64][33];
    const int tid = threadIdx.x;
    const int cq = tid & 3, rg = tid >> 2;
    uint4 w[8];
#pragma unroll
    for (int i = 0; i < 8; i++)
        w[i] = __ldg((const uint4*)(w_mod + (size_t)(rg * 8 + i) * (6 * D_) + blockIdx.x * 32 + cq * 8));
    for (int i = tid; i < D_; i += 256) {
        float v = __bfloat162float(c[i]);
        s_c[i] = rbf(v / (1.f + __expf(-v)));
    }
    {
        const int gt = blockIdx.x * 256 + tid, nt = gridDim.x * 256;
        for (int i = gt; i < F_TOTAL * 32; i += nt) g_flags[i] = 0;
        for (int i = gt; i < 65536 + 2048; i += nt) g_F[i] = 0;
        if (tid < 11) {
            const int i = tid * gridDim.x + blockIdx.x;
            if (i < 1024) asm volatile("cp.async.bulk.prefetch.L2.global [%0], %1;" :: "l"(pf.p[i >> 8] + (size_t)(i & 255) * 8192), "r"(16384) : "memory");
        }
    }
    __syncthreads();
    float a[8];
#pragma unroll
    for (int j = 0; j < 8; j++) a[j] = 0.f;
#pragma unroll
    for (int i = 0; i < 8; i++) {
        float cv = s_c[rg * 8 + i];
        a[0] += cv * bflo(w[i].x); a[1] += cv * bfhi(w[i].x); a[2] += cv * bflo(w[i].y); a[3] += cv * bfhi(w[i].y);
        a[4] += cv * bflo(w[i].z); a[5] += cv * bfhi(w[i].z); a[6] += cv * bflo(w[i].w); a[7] += cv * bfhi(w[i].w);
    }
#pragma unroll
    for (int j = 0; j < 8; j++) s_red[rg][cq * 8 + j] = a[j];
    __syncthreads();
    if (tid < 32) {
        float s = 0.f;
#pragma unroll 8
        for (int r = 0; r < 64; r++) s += s_red[r][tid];
        g_mod[blockIdx.x * 32 + tid] = __float2bfloat16_rn(s);
    }
}

__device__ __forceinline__ uint32_t hadd2(uint32_t a, uint32_t b) { uint32_t r; asm("add.rn.bf16x2 %0, %1, %2;" : "=r"(r) : "r"(a), "r"(b)); return r; }
__device__ __forceinline__ uint32_t hsub2(uint32_t a, uint32_t b) { uint32_t r; asm("sub.rn.bf16x2 %0, %1, %2;" : "=r"(r) : "r"(a), "r"(b)); return r; }
__device__ __forceinline__ uint32_t hmul2(uint32_t a, uint32_t b) { uint32_t r; asm("mul.rn.bf16x2 %0, %1, %2;" : "=r"(r) : "r"(a), "r"(b)); return r; }
__device__ __forceinline__ void load_mod8(const bf16* m, int lane, uint32_t* v) {
    const uint4 a = __ldcg((const uint4*)m + lane), b = __ldcg((const uint4*)m + 32 + lane);
    v[0] = a.x; v[1] = a.y; v[2] = a.z; v[3] = a.w; v[4] = b.x; v[5] = b.y; v[6] = b.z; v[7] = b.w;
}
__device__ __forceinline__ void ln_stats(const uint32_t* x, uint32_t& mu2, float& rden) {
    float s = 0.f;
#pragma unroll
    for (int i = 0; i < 8; i++) s += bflo(x[i]) + bfhi(x[i]);
#pragma unroll
    for (int o = 16; o > 0; o >>= 1) s += __shfl_xor_sync(~0u, s, o);
    const float mean = s * (1.f / D_);
    float q = 0.f;
#pragma unroll
    for (int i = 0; i < 8; i++) { const float d0 = bflo(x[i]) - mean, d1 = bfhi(x[i]) - mean; q = fmaf(d0, d0, q); q = fmaf(d1, d1, q); }
#pragma unroll
    for (int o = 16; o > 0; o >>= 1) q += __shfl_xor_sync(~0u, q, o);
    mu2 = pack2(mean, mean);
    rden = __frcp_rn(rbf(__fsqrt_rn(rbf(rbf(q * (1.f / D_)) + 1e-5f))));
}
__device__ __forceinline__ void ln_apply(const uint32_t* x, uint32_t mu2, float rden, const uint32_t* c1, const uint32_t* sm, uint32_t* r) {
#pragma unroll
    for (int i = 0; i < 8; i++) {
        const uint32_t d = hsub2(x[i], mu2);
        r[i] = hadd2(hmul2(pack2(bflo(d) * rden, bfhi(d) * rden), c1[i]), sm[i]);
    }
}

__global__ void __launch_bounds__(256) k_ln1(const bf16* __restrict__ x) {
    const int lane = threadIdx.x & 31, row = blockIdx.x * 8 + (threadIdx.x >> 5);
    const uint4* xr = (const uint4*)(x + (size_t)row * D_);
    const uint4 a = __ldg(xr + lane), b = __ldg(xr + 32 + lane);
    const uint32_t v[8] = {a.x, a.y, a.z, a.w, b.x, b.y, b.z, b.w};
    uint32_t mu2; float rden;
    ln_stats(v, mu2, rden);
    asm volatile("griddepcontrol.wait;" ::: "memory");
    uint32_t c1[8], sm[8], r[8];
    load_mod8(g_mod + D_, lane, c1);
    load_mod8(g_mod, lane, sm);
#pragma unroll
    for (int i = 0; i < 8; i++) c1[i] = hadd2(c1[i], 0x3F803F80u);
    ln_apply(v, mu2, rden, c1, sm, r);
    uint4* hr = (uint4*)(g_h + (size_t)row * D_);
    hr[lane] = make_uint4(r[0], r[1], r[2], r[3]); hr[32 + lane] = make_uint4(r[4], r[5], r[6], r[7]);
}

struct __align__(64) Params {
    CUtensorMap tm_h, tm_kv, tm_kvm, tm_o, tm_op, tm_h2, tm_act, tm_x1, tm_out;
    CUtensorMap tm_wq, tm_wk, tm_wv, tm_wo, tm_wg, tm_wu, tm_wd;
    const bf16* x;
    int job_begin, job_end;
};

constexpr int R_NST = 3;
constexpr uint32_t R_WV = 0, R_MEM = 65536, R_KX = 73728, R_VX = R_KX + R_NST * 4096, R_QS = R_VX + R_NST * 4096,
                   R_KMS = R_QS + 1024, R_VMS = R_KMS + 1024, R_OS = R_VMS + 1024, R_SX = R_OS + 1024, R_BAR = R_SX + 2560,
                   R_RS = 105472  , R_VP = R_RS + 8192  ,
                   R_STG = R_VP + 8192  , R_SMEM = R_STG + 98304;
static_assert(R_BAR + 64 <= R_RS, "smem");
constexpr uint32_t RB_SX = R_BAR, RB_V = R_BAR + 8, RB_E = R_BAR + 16, RB_A = R_BAR + 24, RB_ROLE = R_BAR + 32;
constexpr int W_NST = 3;
constexpr uint32_t W_STAGE = 49152, W_STG = W_NST * W_STAGE, W_END = W_STG + 65536;
constexpr uint32_t SM_BAR = W_END;
constexpr uint32_t SMEM_BYTES = W_END + 1024;
constexpr uint32_t B_FULL = 0, B_EMPTY = 32, B_STGFREE = 64, B_RING = 128;

constexpr int NB_X = 11  , NB_Y = 1, NB_B = 2, NB_C = 3, NB_D = 4, NB_W0 = 6  , NB_ST = 9  ;

__device__ __forceinline__ int pos_of_d(int d) {
    const int rem = d & 31;
    return (d & ~31) + ((rem & 7) >> 1) * 8 + (rem & 1) * 4 + (rem >> 3);
}

#define PROF(i) do {} while (0)
#define PROFG(i) do {} while (0)
#define OPAQUE(x) asm volatile("" : "+r"(x))
#define FENCE_SCHED(x) do { if ((x) == 0u) asm volatile("trap;"); } while (0)
#define VK0_ 4
constexpr int VK0 = VK0_;
constexpr int NOFF = 8;
#define VDELAY -1
#define POLL_GAP 100

struct RecParams { const bf16 *mem0, *wq, *wk, *wv, *wo; int ncl; };

__device__ __forceinline__ void rec_qk(const RecParams& p, const uint32_t sb, const int cta, const int warp, int lane, const int sel) {
    const int crank = cta & 15, cl = cta >> 4, rank = cta & 1;
    const int kh = warp >> 2, aa = warp & 3;
    uint32_t wa[2][16][4];
    const uint32_t stg = sb + R_STG + kh * 32768;
    {
        const int t128 = aa * 32 + lane;
        const int row = (lane >> 4) * 8 + (lane & 7);
        const int ch = t128 & 7;
        const size_t goff = (size_t)kh * 256 * HD_ + cta * 64 + ch * 8;
#pragma unroll 4
        for (int dd = 0; dd < 16; dd++) {
            const int d = dd * 16 + (t128 >> 3), pp = pos_of_d(d);
            cp_async16(sb + R_WV + kh * 32768 + pp * 128 + ((ch ^ (pp & 7)) << 4), p.wv + goff + (size_t)d * HD_);
        }
        cp_async_commit();
#pragma unroll 4
        for (int dd = 0; dd < 16; dd++) {
            const int d = dd * 16 + (t128 >> 3), pp = pos_of_d(d);
            cp_async16(stg + pp * 128 + ((ch ^ (pp & 7)) << 4), p.wq + goff + (size_t)d * HD_);
        }
        cp_async_commit();
        {
            const int i0 = (warp * 32 + lane) * 16, tok = i0 >> 9;
            const uint4 m0 = __ldg((const uint4*)(p.mem0 + i0)), m1 = __ldg((const uint4*)(p.mem0 + i0 + 8));
            const uint32_t mw[8] = {m0.x, m0.y, m0.z, m0.w, m1.x, m1.y, m1.z, m1.w};
#pragma unroll
            for (int e = 0; e < 16; e++) {
                const int pp = pos_of_d((i0 & 511) + e);
                const unsigned short v = (unsigned short)(mw[e >> 1] >> ((e & 1) * 16));
                asm volatile("st.shared.u16 [%0], %1;" :: "r"(sb + R_MEM + (pp >> 3) * 128 + tok * 16 + (pp & 7) * 2), "h"(v) : "memory");
            }
        }
        cp_async_wait<1>();
        bar_sync(NB_W0 + kh, 128);
        const uint32_t fv = row * 128 + (((2 * aa + ((lane >> 3) & 1)) ^ (row & 7)) << 4);
#pragma unroll
        for (int ks = 0; ks < 16; ks++) ldsm4t(wa[0][ks][0], wa[0][ks][1], wa[0][ks][2], wa[0][ks][3], sb + R_WV + kh * 32768 + fv + ks * 2048);
        bar_sync(NB_W0 + kh, 128);
#pragma unroll
        for (int ks = 0; ks < 16; ks++)
            sts128(sb + R_WV + kh * 32768 + (aa * 16 + ks) * 512 + lane * 16, make_uint4(wa[0][ks][0], wa[0][ks][1], wa[0][ks][2], wa[0][ks][3]));
        const uint32_t fo = stg + row * 128 + (((4 * (aa & 1) + ((lane >> 3) & 1)) ^ (row & 7)) << 4);
#pragma unroll 1
        for (int m = 0; m < 2; m++) {
            cp_async_wait<0>();
            bar_sync(NB_W0 + kh, 128);
            if ((aa >> 1) == m) {
#pragma unroll
                for (int ks = 0; ks < 16; ks++) {
                    ldsm4t(wa[0][ks][0], wa[0][ks][1], wa[0][ks][2], wa[0][ks][3], fo + ks * 2048);
                    ldsm4t(wa[1][ks][0], wa[1][ks][1], wa[1][ks][2], wa[1][ks][3], (fo ^ 32) + ks * 2048);
                }
            }
            bar_sync(NB_W0 + kh, 128);
            if (m == 0) {
#pragma unroll 4
                for (int dd = 0; dd < 16; dd++) {
                    const int d = dd * 16 + (t128 >> 3), pp = pos_of_d(d);
                    cp_async16(stg + pp * 128 + ((ch ^ (pp & 7)) << 4), p.wk + goff + (size_t)d * HD_);
                }
                cp_async_commit();
            }
        }
    }
    const uint32_t tab = stg + (aa * 32 + lane) * 16;
    {
        const uint32_t l7 = lane & 7, l8 = lane >> 3, g = lane >> 2, t = lane & 3;
        const uint32_t t0 = l7 * 128 + ((l8 ^ l7) << 4);
        const uint32_t tq = l7 * 128 + (((l8 >> 1) ^ l7) << 4);
        const uint32_t bq = warp >> 1, tp = warp & 1;
        uint4 v;
        v.x = sb + (aa < 2 ? R_QS : R_KMS) + l7 * 128 + (((4 * (aa & 1) + 2 * kh + (l8 & 1)) ^ l7) << 4);
        v.y = sb + R_QS + tq;
        v.z = sb + (warp == 0 ? R_KMS : R_KX + (warp - 1) * 1024) + t0;
        v.w = mapa_u32(sb + R_SX + (rank * 5 + warp) * 256 + lane * 8, crank ^ 1);
        sts128(tab, v);
        sts128(tab + 2048, make_uint4(sb + lane * 16 + R_MEM + kh * 4096, sb + lane * 16 + R_WV + warp * 8192,
                                      sb + lane * 16 + R_VP + warp * 512, sb + lane * 16 + R_VP + 4096 + (warp ^ 4) * 512));
        const uint32_t src = (l8 >> 1) * 8 + l7;
        const uint32_t L = bq * 8 + 2 * tp + (l8 & 1);
        const uint32_t d0 = (crank + ((t >> 1) | (g & 6))) & 15;
        v.x = sb + R_RS + src * 512 + ((L ^ (src & 7)) << 4);
        v.y = mapa_u32(sb + R_MEM + (crank * 4 + bq) * 128 + (4 * tp + 2 * (t & 1) + (g & 1)) * 16, d0);
        v.z = mapa_u32(sb + RB_A, d0);
        v.w = lane;
        sts128(tab + 4096, v);
        const uint64_t wr = (uint64_t)(g_F + ((crank * 2 + ((crank ^ (crank >> 3) ^ sel) & 1)) * 1024 + warp * 128 + cl * 32 + lane));
        sts128(tab + 6144, make_uint4((uint32_t)wr, (uint32_t)(wr >> 32), (uint32_t)((((cl + 1) & 3) - cl) * 128), (uint32_t)((((cl + 2) & 3) - cl) * 128)));
        sts32(tab + 8192, (uint32_t)((((cl + 3) & 3) - cl) * 128));
#pragma unroll
        for (int i = 0; i < NOFF; i++)
            sts128(tab + 10240 + i * 2048, make_uint4(wa[i & 1][i >> 1][0], wa[i & 1][i >> 1][1], wa[i & 1][i >> 1][2], wa[i & 1][i >> 1][3]));
    }
    bar_sync(NB_D, 384);
    uint32_t slot_off = 0;
    const uint32_t slot_inc = warp == 0 ? 0 : 4096;
    const uint32_t sx_bar_rem = (sb + RB_SX) ^ (1u << 24);
    uint4 tb = lds128(tab + 2048);
#pragma unroll 1
    for (int s = 0; s < NSEG; s++) {
        if (s > 0) mbar_wait(sb + RB_A, (s - 1) & 1);
        if (warp == 0) { PROF(0); PROFG(13); }
        uint4 ta;
        {
            float acc[5][4];
#pragma unroll
            for (int c = 0; c < 5; c++) { acc[c][0] = acc[c][1] = acc[c][2] = acc[c][3] = 0.f; }
            uint32_t b[8][4];
            uint4 av[16];
            ldsm4(b[0][0], b[0][1], b[0][2], b[0][3], tb.x);
            ldsm4(b[1][0], b[1][1], b[1][2], b[1][3], tb.x + 512);
            ldsm4(b[2][0], b[2][1], b[2][2], b[2][3], tb.x + 1024);
#pragma unroll
            for (int k2 = 0; k2 < 8; k2++) {
                mma16816(acc[0], wa[0][2 * k2][0], wa[0][2 * k2][1], wa[0][2 * k2][2], wa[0][2 * k2][3], b[k2][0], b[k2][1]);
                mma16816(acc[1], wa[1][2 * k2][0], wa[1][2 * k2][1], wa[1][2 * k2][2], wa[1][2 * k2][3], b[k2][0], b[k2][1]);
                if (2 * k2 >= VK0) mma16816(acc[2], av[2 * k2].x, av[2 * k2].y, av[2 * k2].z, av[2 * k2].w, b[k2][0], b[k2][1]);
                mma16816(acc[3], wa[0][2 * k2 + 1][0], wa[0][2 * k2 + 1][1], wa[0][2 * k2 + 1][2], wa[0][2 * k2 + 1][3], b[k2][2], b[k2][3]);
                mma16816(acc[4], wa[1][2 * k2 + 1][0], wa[1][2 * k2 + 1][1], wa[1][2 * k2 + 1][2], wa[1][2 * k2 + 1][3], b[k2][2], b[k2][3]);
                if (2 * k2 >= VK0) mma16816(acc[2], av[2 * k2 + 1].x, av[2 * k2 + 1].y, av[2 * k2 + 1].z, av[2 * k2 + 1].w, b[k2][2], b[k2][3]);
                if (k2 + 3 < 8) ldsm4(b[k2 + 3][0], b[k2 + 3][1], b[k2 + 3][2], b[k2 + 3][3], tb.x + (k2 + 3) * 512);
                if (VK0 + 2 * k2 < 16) { av[VK0 + 2 * k2] = lds128(tb.y + (VK0 + 2 * k2) * 512); av[VK0 + 2 * k2 + 1] = lds128(tb.y + (VK0 + 2 * k2 + 1) * 512); }
                if (k2 == 5) ta = lds128(tab);
            }
#pragma unroll
            for (int i = 0; i < 4; i++) { acc[0][i] += acc[3][i]; acc[1][i] += acc[4][i]; }
            const float g0 = kh ? acc[0][0] : acc[1][0], g1 = kh ? acc[0][1] : acc[1][1], g2 = kh ? acc[0][2] : acc[1][2], g3 = kh ? acc[0][3] : acc[1][3];
            sts128(tb.w, make_uint4(__float_as_uint(g0), __float_as_uint(g1), __float_as_uint(g2), __float_as_uint(g3)));
            const float k0 = kh ? acc[1][0] : acc[0][0], k1 = kh ? acc[1][1] : acc[0][1], k2_ = kh ? acc[1][2] : acc[0][2], k3 = kh ? acc[1][3] : acc[0][3];
            if (warp == 0) PROF(1);
            bar_sync(NB_X + aa, 64);
            const uint4 o = lds128(tb.z + 4096);
            stsm2t(ta.x, pack2(k0 + __uint_as_float(o.x), k1 + __uint_as_float(o.y)), pack2(k2_ + __uint_as_float(o.z), k3 + __uint_as_float(o.w)));
            sts128(tb.z, make_uint4(__float_as_uint(acc[2][0]), __float_as_uint(acc[2][1]), __float_as_uint(acc[2][2]), __float_as_uint(acc[2][3])));
        }
        const uint32_t kb = ta.z + slot_off;
        if (warp == 0) PROF(14);
        bar_sync(NB_B, 256);
        if (warp < 5) {
            uint32_t q[16], k0, k1, k2, k3, k4, k5, k6, k7;
            float sa[4] = {0.f, 0.f, 0.f, 0.f}, sc[4] = {0.f, 0.f, 0.f, 0.f};
            ldsm4(q[0], q[1], q[2], q[3], ta.y);
            ldsm4(k0, k1, k2, k3, kb);
            ldsm4(q[4], q[5], q[6], q[7], ta.y ^ 32);
            ldsm4(q[8], q[9], q[10], q[11], ta.y ^ 64);
            ldsm4(k4, k5, k6, k7, kb ^ 64);
            ldsm4(q[12], q[13], q[14], q[15], ta.y ^ 96);
            mma16816(sa, q[0], q[1], q[2], q[3], k0, k1);
            bar_arrive(NB_Y, 288);
            mma16816(sc, q[4], q[5], q[6], q[7], k2, k3);
            mma16816(sa, q[8], q[9], q[10], q[11], k4, k5);
            mma16816(sc, q[12], q[13], q[14], q[15], k6, k7);
            const float scl = 0.08838834764831845f * 1.4426950408889634f;
            const float r0 = (sa[0] + sc[0]) * scl, r1 = (sa[1] + sc[1]) * scl;
            if (s != NSEG - 1) {
                st_async_v2(ta.w, r0, r1, sx_bar_rem);
                st_async_v2(ta.w ^ (1u << 24), r0, r1, sx_bar_rem ^ (1u << 24));
            }
            if (warp == 0) PROF(2);
        } else if (s > 0 && warp == 7 && lane == 0) {
            mbar_expect_tx(sb + RB_A, 8192);
        }
        if (s == NSEG - 1) break;
        slot_off = slot_off == (R_NST - 1) * 4096 ? 0 : slot_off + slot_inc;
        const uint4 tc = lds128(tab + 4096), td = lds128(tab + 6144);
        const uint32_t te = lds32(tab + 8192);
        uint32_t* wr = (uint32_t*)(((uint64_t)td.y << 32) | (td.x ^ ((s & 1) * 0x21000)));
        const uint32_t* r1p = (const uint32_t*)((const char*)wr + (int)td.z);
        const uint32_t* r2p = (const uint32_t*)((const char*)wr + (int)td.w);
        const uint32_t* r3p = (const uint32_t*)((const char*)wr + (int)te);
        const uint32_t tag = ((s >> 1) + 1) & 1;
        mbar_wait(sb + RB_E, s & 1);
        if (warp == 0) PROF(7);
        {
            uint32_t a0, a1, a2, a3, a4, a5, a6, a7;
            ldsm4t(a0, a1, a2, a3, tc.x);
            ldsm4t(a4, a5, a6, a7, tc.x ^ 64);
            const uint32_t one = 0x3F803F80u;
            float d0_[4] = {0.f, 0.f, 0.f, 0.f}, d1_[4] = {0.f, 0.f, 0.f, 0.f};
            mma16816(d0_, a0, a1, a2, a3, one, one);
            mma16816(d1_, a4, a5, a6, a7, one, one);
            const bool t1 = tc.w & 1, t2 = tc.w & 2;
            const float x = t2 ? (t1 ? d1_[2] : d1_[0]) : (t1 ? d0_[2] : d0_[0]);
            const uint32_t own = (__float_as_uint(x) & ~1u) | tag;
            stg_relaxed32(wr, own);
            const uint32_t tq = clk32();
            if (warp == 0) PROF(8);
            PROFG(16 + warp);
#pragma unroll
            for (int i = 0; i < NOFF; i++) {
                const uint4 f0 = lds128(tab + 10240 + i * 2048);
                wa[i & 1][i >> 1][0] = f0.x; wa[i & 1][i >> 1][1] = f0.y; wa[i & 1][i >> 1][2] = f0.z; wa[i & 1][i >> 1][3] = f0.w;
            }
            tb = lds128(tab + 2048);
            while ((int)(clk32() - tq) < POLL_GAP) {}
            uint32_t f1, f2, f3;
            int gg = 0;
#pragma unroll 1
            while (true) {
                f1 = ldg_relaxed32(r1p); f2 = ldg_relaxed32(r2p); f3 = ldg_relaxed32(r3p);
                if (__all_sync(~0u, (((f1 ^ tag) | (f2 ^ tag) | (f3 ^ tag)) & 1) == 0)) break;
                if (++gg > 16 * SPIN_LIMIT) { TIMEOUT(3, s); break; }
            }
            if (warp == 0) PROF(9);
            PROFG(32 + warp);
            const float v = (__uint_as_float(own) + __uint_as_float(f2)) + (__uint_as_float(f1) + __uint_as_float(f3));
            const bool b8 = tc.w & 8, b16 = tc.w & 16;
            const float recv = __shfl_xor_sync(~0u, v, 8);
            const uint32_t word = b8 ? pack2(recv, v) : pack2(v, recv);
            const uint32_t oth = __shfl_xor_sync(~0u, word, 16);
            const uint32_t wl = b16 ? oth : word, wh = b16 ? word : oth;
            const uint32_t p0 = __shfl_xor_sync(~0u, wl, 2), p1 = __shfl_xor_sync(~0u, wh, 2);
            const uint4 item = t2 ? make_uint4(p0, p1, wl, wh) : make_uint4(wl, wh, p0, p1);
            st_async_v4(tc.y, item, tc.z);
            st_async_v4(tc.y ^ (8u << 24), item, tc.z ^ (8u << 24));
            if (tc.w == 0 && warp == 7) mbar_expect_tx(sb + RB_E, 8192);
            if (warp == 0) PROF(10);
            PROF(40 + warp);
        }
        bar_sync(NB_D, 384);
    }
}

__device__ __forceinline__ void rec_load_kv(uint32_t sb, int col0, int s, uint32_t slot_off, int t128) {
    const int row = t128 >> 2, c2 = (t128 & 3) * 2;
    const bf16* src = g_kv + ((size_t)(s * 32 + row) * (2 * HD_) + col0 + c2 * 8);
    const uint32_t d0 = sb + R_KX + slot_off + row * 128 + ((c2 ^ (row & 7)) << 4);
    cp_async16(d0, src);
    cp_async16(d0 ^ 16, src + 8);
    cp_async16(d0 + (R_VX - R_KX), src + HD_);
    cp_async16((d0 ^ 16) + (R_VX - R_KX), src + HD_ + 8);
}

__device__ __forceinline__ void rec_vo(const RecParams& p, const uint32_t sb, const int cta, const int warp, int lane) {
    const int w = warp - 8, crank = cta & 15;
    const int col0 = cta * 64;
    uint32_t wo[8][4][4];
    {
        const int t128 = w * 32 + lane;
        const bf16* Wo = p.wo + (size_t)col0 * D_;
        const uint32_t stg = sb + R_STG + 2 * 32768;
#pragma unroll
        for (int half = 0; half < 2; half++) {
#pragma unroll 4
            for (int i = t128; i < 2048; i += 128) {
                const int e = i >> 6, ch = i & 63;
                cp_async16(stg + e * 1024 + ((ch ^ (e & 7)) << 4), Wo + (size_t)(half * 32 + e) * D_ + ch * 8);
            }
            cp_async_commit();
            cp_async_wait<0>();
            bar_sync(NB_W0 + 2, 128);
#pragma unroll
            for (int j = 0; j < 8; j++)
#pragma unroll
                for (int kk = 0; kk < 2; kk++) {
                    const int e = kk * 16 + (lane >> 4) * 8 + (lane & 7);
                    const int ch = (w * 8 + j) * 2 + ((lane >> 3) & 1);
                    ldsm4t(wo[j][half * 2 + kk][0], wo[j][half * 2 + kk][1], wo[j][half * 2 + kk][2], wo[j][half * 2 + kk][3],
                           stg + e * 1024 + ((ch ^ (e & 7)) << 4));
                }
            bar_sync(NB_W0 + 2, 128);
        }
        if (lane == 0) wait_flag(F_KV + 0, 64);
        __syncwarp();
        rec_load_kv(sb, col0, 0, 0, t128); cp_async_commit();
        rec_load_kv(sb, col0, 1, 4096, t128); cp_async_commit();
        cp_async_wait<1>();
    }
    const uint32_t tab = sb + R_STG + 2 * 32768 + (w * 32 + lane) * 16;
    {
        const uint32_t l7 = lane & 7, l8 = lane >> 3, g = lane >> 2;
        uint4 v;
        v.x = sb + R_VX + ((l8 & 1) * 8 + l7) * 128 + (((2 * w + (l8 >> 1)) ^ l7) << 4);
        v.y = sb + R_OS + g * 128 + (((2 * w) ^ g) << 4) + (lane & 3) * 4;
        v.z = sb + R_VMS + l7 * 128 + (((2 * w + (l8 & 1)) ^ l7) << 4);
        v.w = sb + R_OS + l7 * 128 + ((l8 ^ l7) << 4);
        sts128(tab, v);
        v.x = mapa_u32(sb + R_RS + crank * 512 + ((lane ^ (crank & 7)) << 4), w * 4);
        v.y = mapa_u32(sb + RB_E, w * 4);
        v.z = sb + R_VP + w * 512 + lane * 16;
        v.w = sb + R_SX + lane * 8;
        sts128(tab + 2048, v);
#pragma unroll
        for (int i = 0; i < 8; i++) sts128(tab + 4096 + i * 2048, make_uint4(wo[i][0][0], wo[i][0][1], wo[i][0][2], wo[i][0][3]));
    }
    bar_sync(NB_D, 384);
    const uint32_t lane16 = lds32(tab + 2048 + 8) - R_VP - w * 512;
    uint4 av[2 * VK0];
#pragma unroll
    for (int i = 0; i < 2 * VK0; i++) av[i] = lds128(lane16 + R_WV + (i / VK0) * 32768 + (w * 16 + i % VK0) * 512);
    uint32_t slot_off = 0;
#pragma unroll 1
    for (int s = 0; s < NSEG; s++) {
        bar_sync(NB_Y, 288);
        uint32_t vb0, vb1;
        {
            float va[4] = {0.f, 0.f, 0.f, 0.f}, vc[4] = {0.f, 0.f, 0.f, 0.f};
            uint32_t bb[VK0][4];
#pragma unroll
            for (int k2 = 0; k2 < VK0; k2++) ldsm4(bb[k2][0], bb[k2][1], bb[k2][2], bb[k2][3], lane16 + R_MEM + (k2 / (VK0 / 2)) * 4096 + (k2 % (VK0 / 2)) * 512);
#pragma unroll
            for (int k2 = 0; k2 < VK0; k2++) {
                mma16816(va, av[2 * k2].x, av[2 * k2].y, av[2 * k2].z, av[2 * k2].w, bb[k2][0], bb[k2][1]);
                mma16816(vc, av[2 * k2 + 1].x, av[2 * k2 + 1].y, av[2 * k2 + 1].z, av[2 * k2 + 1].w, bb[k2][2], bb[k2][3]);
            }
            const uint4 a = lds128(lane16 + R_VP + w * 512), b = lds128(lane16 + R_VP + 2048 + w * 512);
            vb0 = pack2((va[0] + vc[0]) + (__uint_as_float(a.x) + __uint_as_float(b.x)), (va[1] + vc[1]) + (__uint_as_float(a.y) + __uint_as_float(b.y)));
            vb1 = pack2((va[2] + vc[2]) + (__uint_as_float(a.z) + __uint_as_float(b.z)), (va[3] + vc[3]) + (__uint_as_float(a.w) + __uint_as_float(b.w)));
        }
        const uint4 ta = lds128(tab), tb = lds128(tab + 2048);
        uint32_t vx[8];
        ldsm4t(vx[0], vx[1], vx[2], vx[3], ta.x + slot_off);
        ldsm4t(vx[4], vx[5], vx[6], vx[7], ta.x + slot_off + 2048);
#pragma unroll
        for (int i = 0; i < 4; i++) {
            const uint4 f0 = lds128(tab + 4096 + i * 2048);
            wo[i][0][0] = f0.x; wo[i][0][1] = f0.y; wo[i][0][2] = f0.z; wo[i][0][3] = f0.w;
        }
        if (w == 0) PROF(11);
        uint32_t pf[5];
        float oa[2][4] = {{0.f, 0.f, 0.f, 0.f}, {0.f, 0.f, 0.f, 0.f}}, ob_[2][4] = {{0.f, 0.f, 0.f, 0.f}, {0.f, 0.f, 0.f, 0.f}};
        float sm0[4] = {0.f, 0.f, 0.f, 0.f}, sm1[4] = {0.f, 0.f, 0.f, 0.f};
        if (s != NSEG - 1) {
            mbar_wait(sb + RB_SX, s & 1);
            if (w == 0) PROF(4);
            float sv[10];
#pragma unroll
            for (int n = 0; n < 5; n++) {
                const float2 a = lds64f(tb.w + n * 256), b = lds64f(tb.w + (5 + n) * 256);
                sv[2 * n] = a.x + b.x; sv[2 * n + 1] = a.y + b.y;
            }
            float mx = fmaxf(fmaxf(fmaxf(sv[0], sv[1]), fmaxf(sv[2], sv[3])), fmaxf(fmaxf(sv[4], sv[5]), fmaxf(sv[6], sv[7])));
            mx = fmaxf(mx, fmaxf(sv[8], sv[9]));
            mx = fmaxf(mx, __shfl_xor_sync(~0u, mx, 1));
            mx = fmaxf(mx, __shfl_xor_sync(~0u, mx, 2));
#pragma unroll
            for (int n = 1; n < 5; n++) pf[n] = pack2(ex2(sv[2 * n] - mx), ex2(sv[2 * n + 1] - mx));
            pf[0] = pack2(ex2(sv[0] - mx), ex2(sv[1] - mx));
            if (w == 0) PROF(12);
            const uint32_t one = 0x3F803F80u;
            mma16816h(sm0, pf[1], pf[2], one, one);
            mma16816h(oa[0], pf[1], pf[2], vx[0], vx[1]);
            mma16816h(oa[1], pf[1], pf[2], vx[2], vx[3]);
            mma16816h(sm1, pf[3], pf[4], one, one);
            mma16816h(ob_[0], pf[3], pf[4], vx[4], vx[5]);
            mma16816h(ob_[1], pf[3], pf[4], vx[6], vx[7]);
            mma1688h(sm0, pf[0], one);
            mma1688h(oa[0], pf[0], vb0);
            mma1688h(oa[1], pf[0], vb1);
            float inv;
            asm("rcp.approx.ftz.f32 %0, %1;" : "=f"(inv) : "f"(sm0[0] + sm1[0]));
            oa[0][0] += ob_[0][0]; oa[0][1] += ob_[0][1]; oa[1][0] += ob_[1][0]; oa[1][1] += ob_[1][1];
            sts32(ta.y, pack2(oa[0][0] * inv, oa[0][1] * inv));
            sts32(ta.y ^ 16, pack2(oa[1][0] * inv, oa[1][1] * inv));
            const uint32_t oa2 = ta.w ^ 64;
            bar_sync(NB_C, 128);
            if (w == 0) PROF(5);
            uint32_t ob[8];
            ldsm4(ob[0], ob[1], ob[2], ob[3], ta.w);
            ldsm4(ob[4], ob[5], ob[6], ob[7], oa2);
#pragma unroll
            for (int i = 4; i < 8; i++) {
                const uint4 f0 = lds128(tab + 4096 + i * 2048);
                wo[i][0][0] = f0.x; wo[i][0][1] = f0.y; wo[i][0][2] = f0.z; wo[i][0][3] = f0.w;
            }
#pragma unroll
            for (int jj = 0; jj < 2; jj++) {
                if (jj == 1 && tb.w == 0) break;
                float acc[4][4];
#pragma unroll
                for (int c = 0; c < 4; c++) { acc[c][0] = acc[c][1] = acc[c][2] = acc[c][3] = 0.f; }
#pragma unroll
                for (int ks = 0; ks < 4; ks++)
#pragma unroll
                    for (int c = 0; c < 4; c++)
                        mma16816(acc[c], wo[jj * 4 + c][ks][0], wo[jj * 4 + c][ks][1], wo[jj * 4 + c][ks][2], wo[jj * 4 + c][ks][3], ob[2 * ks], ob[2 * ks + 1]);
#pragma unroll
                for (int pr = 0; pr < 2; pr++) {
                    uint4 v;
                    v.x = pack2(acc[2 * pr][0], acc[2 * pr][1]);
                    v.y = pack2(acc[2 * pr][2], acc[2 * pr][3]);
                    v.z = pack2(acc[2 * pr + 1][0], acc[2 * pr + 1][1]);
                    v.w = pack2(acc[2 * pr + 1][2], acc[2 * pr + 1][3]);
                    st_async_v4(tb.x + ((jj * 2 + pr) << 24), v, tb.y + ((jj * 2 + pr) << 24));
                }
            }
            if (w == 0) PROF(6);
        }
        {
            stsm2t(ta.z, vb0, vb1);
            cp_async_wait<0>();
            bar_sync(NB_C, 128);
            if (w == 0 && lane == 0 && s != NSEG - 1) mbar_expect_tx(sb + RB_SX, 2560);
            const int omat = w >> 1, otok = (w & 1) * 4 + (lane >> 3), och = lane & 7;
            const uint4 v = lds128(sb + (omat ? R_VMS : R_KMS) + otok * 128 + ((och ^ otok) << 4));
            *(uint4*)(g_kvm + ((s * 8 + otok) * (2 * HD_) + omat * HD_ + col0 + och * 8)) = v;
            if (s != NSEG - 1) bar_arrive(NB_D, 384);
#pragma unroll
            for (int i = 0; i < 2 * VK0; i++) av[i] = lds128(lane16 + R_WV + (i / VK0) * 32768 + (w * 16 + i % VK0) * 512);
            if (s + 2 < NSEG - 1) {
                if (((s + 2) & 3) == 0) { if (lane == 0) wait_flag(F_KV + ((s + 2) >> 2), 64); __syncwarp(); }
                rec_load_kv(sb, col0, s + 2, slot_off == 0 ? (R_NST - 1) * 4096 : slot_off - 4096, w * 32 + lane);
            }
            cp_async_commit();
            if ((s & 3) == 3) {
                bar_sync(NB_C, 128);
                if (w == 0 && lane == 0) red_release(&g_flags[(F_MEM + (s >> 2)) * 32], 1);
            }
        }
        slot_off = slot_off == (R_NST - 1) * 4096 ? 0 : slot_off + 4096;
    }
}

__global__ void __launch_bounds__(384, 1) k_rec(const RecParams p) {
    extern __shared__ __align__(1024) unsigned char smem_raw[];
    const uint32_t sb = __shfl_sync(~0u, smem_u32(smem_raw), 0);
    const int warp = __shfl_sync(~0u, threadIdx.x >> 5, 0);
    int lane; asm volatile("mov.u32 %0, %%laneid;" : "=r"(lane));
    const int crank = blockIdx.x & 15, slot = blockIdx.x >> 4;
    asm volatile("griddepcontrol.launch_dependents;");
    if (threadIdx.x == 0) {
        mbar_init(sb + RB_SX, 1); mbar_init(sb + RB_E, 1); mbar_init(sb + RB_A, 1); mbar_init(sb + RB_ROLE, 1);
        asm volatile("fence.mbarrier_init.release.cluster;" ::: "memory");
        mbar_expect_tx(sb + RB_SX, 2560);
        mbar_expect_tx(sb + RB_E, 8192);
        mbar_expect_tx(sb + RB_A, 8192);
        mbar_expect_tx(sb + RB_ROLE, 4);
    }
    unsigned role = 0;
    if (crank == 0 && threadIdx.x == 0) {
        unsigned x = 0;
        int tm[2] = {0x7fffffff, 0x7fffffff};
#pragma unroll 1
        for (int i = 0; i < 6; i++) {
            const uint32_t t0 = clk32();
            x = atomicAdd(&g_F[65536 + (i & 1) * 1024 + slot * 64 + (x >> 31)], 0u) & 0x7fffffffu;
            if (x == 0x7654321u) sts32(sb + R_BAR + 56, x);
            const int dt = (int)(clk32() - t0);
            if (i >= 2) { if (i & 1) tm[1] = min(tm[1], dt); else tm[0] = min(tm[0], dt); }
        }
        const int side = tm[1] > tm[0];
        const unsigned old = atomicAdd(&g_flags[(F_SIDE + side) * 32], 1u);
        unsigned c0, c1; int gd = 0;
#pragma unroll 1
        do { c0 = ldg_relaxed32(&g_flags[F_SIDE * 32]); c1 = ldg_relaxed32(&g_flags[(F_SIDE + 1) * 32]); } while ((int)(c0 + c1) < p.ncl && ++gd < 64 * SPIN_LIMIT);
        const int big = c1 > c0;
        role = side == big ? old : (big ? c1 : c0) + old;
        role |= (big ^ 1) << 8;
    }
    __syncwarp();
    asm volatile("barrier.cluster.arrive.relaxed.aligned;\nbarrier.cluster.wait.aligned;" ::: "memory");
    if (crank == 0 && warp == 0) {
        role = __shfl_sync(~0u, role, 0);
        if (lane < 16)
            asm volatile("st.async.weak.shared::cluster.mbarrier::complete_tx::bytes.u32 [%0], %1, [%2];"
                         :: "r"(mapa_u32(sb + R_BAR + 48, lane)), "r"(role), "r"(mapa_u32(sb + RB_ROLE, lane)) : "memory");
    }
    mbar_wait(sb + RB_ROLE, 0);
    const int rolew = __shfl_sync(~0u, lds32(sb + R_BAR + 48), 0);
    const int cl = rolew & 255;
    if (cl >= 4) return;
    const int cta = cl * 16 + crank;
    if (warp < 8) rec_qk(p, sb, cta, warp, lane, rolew >> 8);
    else rec_vo(p, sb, cta, warp, lane);
}

enum { J_KV = 0, J_QA = 1, J_O = 2, J_LN = 3, J_UP = 4, J_DN = 5, J_UP2 = 6, J_DN2 = 7, J_END = 8 };
constexpr int N_KV = NRB * 32;
constexpr int NJ_O = 2 * OSPLIT, NJ_O2 = 2 * OSPLIT2, NJ_LN = 8, NJ_LN2 = 16, NJ_UP = 14, NJ_UP2 = 28, NJ_DN = 4, NJ_DN2 = 8;
constexpr int GRP = 16 + NJ_O2 + NJ_LN2 + NJ_UP2 + NJ_DN2;
constexpr int LAG_O = 1, LAG_LN = 2, LAG_UP = 2, LAG_DN = 3;
constexpr int N_GRP = NRB + LAG_DN;
constexpr int N_JOBS = N_KV + N_GRP * GRP;
__device__ __forceinline__ int decode_job(int j) {
    if (j < N_KV) return J_KV | ((j >> 5) << 8) | ((j & 31) << 16);
    j -= N_KV;
    const int grp = j / GRP; int r = j % GRP;
    int type, rb, n, n2;
    if (r < NJ_LN2) { type = J_LN; rb = grp - LAG_LN; n = NJ_LN; n2 = NJ_LN2; }
    else if ((r -= NJ_LN2) < NJ_O2) { type = J_O; rb = grp - LAG_O; n = NJ_O; n2 = NJ_O2; }
    else if ((r -= NJ_O2) < NJ_DN2) { type = J_DN; rb = grp - LAG_DN; n = NJ_DN; n2 = NJ_DN2; }
    else if ((r -= NJ_DN2) < NJ_UP2) { type = J_UP; rb = grp - LAG_UP; n = NJ_UP; n2 = NJ_UP2; }
    else { r -= NJ_UP2; type = J_QA; rb = grp; n = n2 = 16; }
    if (rb < 0 || rb >= NRB || r >= (rb >= FINE_RB ? n2 : n)) return J_END + 1;
    if (rb >= FINE_RB && (type == J_UP || type == J_DN)) type += 2;
    return type | (rb << 8) | (r << 16);
}
__device__ __forceinline__ int op_row(int rb, int split) {
    return rb < FINE_RB ? split * S_ + rb * 128 : OSPLIT * S_ + (split * (NRB - FINE_RB) + rb - FINE_RB) * 128;
}

struct Pipe { uint32_t stage, phase; };
__device__ __forceinline__ void pipe_next(Pipe& p) { if (++p.stage == W_NST) { p.stage = 0; p.phase ^= 1; } }

__device__ __forceinline__ void producer(const Params& p, uint32_t sb) {
    Pipe pp{0, 1};
    const uint32_t bars = sb + SM_BAR;
    uint32_t seq = 0;
#pragma unroll 1
    while (true) {
        int jd, j;
#pragma unroll 1
        while (true) {
            j = p.job_begin + (int)atomicAdd(&g_flags[F_JOB * 32], 1u);
            if (j >= p.job_end) { jd = J_END; j = 4095; break; }
            jd = decode_job(j);
            if ((jd & 255) <= J_END) break;
        }
        TR(j, 1);
        const int type = jd & 255, rb = (jd >> 8) & 255, cb = jd >> 16;
        const bool fine = rb >= FINE_RB;
        bool first = true;
        auto begin_stage = [&](uint32_t bytes) -> uint32_t {
            mbar_wait(bars + B_EMPTY + pp.stage * 8, pp.phase);
            if (first) { sts32(bars + B_RING + (seq & 7) * 4, (uint32_t)jd); sts32(bars + B_RING + 32 + (seq & 7) * 4, (uint32_t)j); first = false; }
            const uint32_t fb = bars + B_FULL + pp.stage * 8;
            if (bytes) mbar_expect_tx(fb, bytes); else mbar_arrive(fb);
            return fb;
        };
        if (type == J_END || type == J_LN) {
            if (type == J_LN) wait_flag(F_OP + rb, 2 * (fine ? NJ_O2 : NJ_O));
            TR(j, 2);
            begin_stage(0); pipe_next(pp);
            seq++;
            if (type == J_END) break;
            continue;
        }
        const CUtensorMap *ta, *tb0, *tb1;
        int k0 = 0, nk = 8, n0 = cb * 256, n1 = n0 + 128, nb = 4, dep = -1;
        unsigned tgt = 0;
        switch (type) {
            case J_KV: ta = &p.tm_h; tb0 = tb1 = cb < 16 ? &p.tm_wk : &p.tm_wv; n0 = (cb & 15) * 256; n1 = n0 + 128; break;
            case J_QA: ta = &p.tm_h; tb0 = tb1 = &p.tm_wq; break;
            case J_O: ta = &p.tm_o; tb0 = tb1 = &p.tm_wo; n0 = (cb & 1) * 256; n1 = n0 + 128; nk = fine ? 64 / OSPLIT2 : 64 / OSPLIT; k0 = (cb >> 1) * nk * 64;
                      dep = F_O + rb; tgt = 32; break;
            case J_UP: ta = &p.tm_h2; tb0 = &p.tm_wg; tb1 = &p.tm_wu; n0 = n1 = cb * 128; dep = F_H2 + rb; tgt = 2 * NJ_LN; break;
            case J_UP2: ta = &p.tm_h2; tb0 = &p.tm_wg; tb1 = &p.tm_wu; n0 = n1 = cb * 64; nb = 2; dep = F_H2 + rb; tgt = 2 * NJ_LN2; break;
            case J_DN: ta = &p.tm_act; tb0 = tb1 = &p.tm_wd; n0 = cb * 128; n1 = n0 + 64; nk = 28; nb = 2; dep = F_ACT + rb; tgt = 2 * NJ_UP; break;
            default: ta = &p.tm_act; tb0 = tb1 = &p.tm_wd; n0 = cb * 64; nk = 28; nb = 1; dep = F_ACT + rb; tgt = 2 * NJ_UP2; break;
        }
        const int m0 = rb * 128;
#pragma unroll 1
        for (int kb = 0; kb < nk; kb++) {
            const uint32_t fb = begin_stage(16384 + nb * 8192);
            const uint32_t st = sb + pp.stage * W_STAGE;
            const int k = k0 + kb * 64;
            tma_load2d(st + 16384, tb0, n0, k, fb);
            if (nb == 4) {
                tma_load2d(st + 16384 + 8192, tb0, n0 + 64, k, fb);
                tma_load2d(st + 16384 + 16384, tb1, n1, k, fb);
                tma_load2d(st + 16384 + 24576, tb1, n1 + 64, k, fb);
            } else if (nb == 2) {
                tma_load2d(st + 16384 + 8192, tb1, n1, k, fb);
            }
            if (kb == 0) {
                if (dep >= 0) { wait_flag(dep, tgt); if (type >= J_UP) fence_async_all(); }
                TR(j, 2);
            }
            tma_load2d(st, ta, k, m0, fb);
            tma_load2d(st + 8192, ta, k, m0 + 64, fb);
            pipe_next(pp);
        }
        if (type == J_QA) {
            wait_flag(F_KV + rb, 64);
#pragma unroll 1
            for (int i = 0; i < 4; i++) {
                const uint32_t fb = begin_stage(40960);
                const uint32_t st = sb + pp.stage * W_STAGE;
                const int col = (i & 1) * HD_ + (cb * 2 + (i >> 1)) * DH_;
                tma_load2d(st, &p.tm_kv, col, m0, fb);
                tma_load2d(st + 8192, &p.tm_kv, col, m0 + 64, fb);
                tma_load2d(st + 16384, &p.tm_kv, col + 64, m0, fb);
                tma_load2d(st + 24576, &p.tm_kv, col + 64, m0 + 64, fb);
                if (i == 0) { wait_flag(F_MEM + rb, 64); fence_async_all(); }
                tma_load2d(st + 32768, &p.tm_kvm, col, rb * 32, fb);
                tma_load2d(st + 36864, &p.tm_kvm, col + 64, rb * 32, fb);
                pipe_next(pp);
            }
        } else if (type == J_DN || type == J_DN2) {
            const uint32_t fb = begin_stage(type == J_DN ? 32768 : 16384);
            const uint32_t st = sb + pp.stage * W_STAGE;
            tma_load2d(st, &p.tm_x1, n0, m0, fb);
            tma_load2d(st + 8192, &p.tm_x1, n0, m0 + 64, fb);
            if (type == J_DN) {
                tma_load2d(st + 16384, &p.tm_x1, n0 + 64, m0, fb);
                tma_load2d(st + 24576, &p.tm_x1, n0 + 64, m0 + 64, fb);
            }
            pipe_next(pp);
        }
        seq++;
    }
}

__device__ __forceinline__ void store_warp(const Params& p, uint32_t sb, int wg, int lane) {
    const uint32_t bars = sb + SM_BAR;
    uint32_t seq = 0;
#pragma unroll 1
    while (true) {
        bar_sync(NB_ST + wg, 160);
        const uint32_t jd = lds32(bars + B_RING + (seq & 7) * 4);
        seq++;
        const int type = jd & 255, rb = (jd >> 8) & 255, cb = jd >> 16;
        if (type == J_END) break;
        if (lane == 0) {
            const uint32_t src = sb + W_STG + wg * 32768;
            const CUtensorMap* tm = nullptr; int n0 = cb * 256, nbox = 4, mrow = rb * 128 + wg * 64, flag = 0;
            switch (type) {
                case J_KV: tm = &p.tm_kv; flag = F_KV + rb; break;
                case J_QA: tm = &p.tm_o; flag = F_O + rb; break;
                case J_O: tm = &p.tm_op; n0 = (cb & 1) * 256; mrow = op_row(rb, cb >> 1) + wg * 64; flag = F_OP + rb; break;
                case J_LN: flag = F_H2 + rb; nbox = 0; break;
                case J_UP: tm = &p.tm_act; n0 = cb * 128; nbox = 2; flag = F_ACT + rb; break;
                case J_UP2: tm = &p.tm_act; n0 = cb * 64; nbox = 1; flag = F_ACT + rb; break;
                case J_DN: tm = &p.tm_out; n0 = cb * 128; nbox = 2; flag = -1; break;
                default: tm = &p.tm_out; n0 = cb * 64; nbox = 1; flag = -1; break;
            }
#pragma unroll 1
            for (int b = 0; b < nbox; b++) tma_store2d(tm, src + b * 8192, n0 + b * 64, mrow);
            bulk_commit();
            bulk_wait0();
            mbar_arrive(bars + B_STGFREE + wg * 8);
            if (flag >= 0) red_release(&g_flags[flag * 32], 1);
        }
        __syncwarp();
    }
}

__device__ __forceinline__ float gelu_tanh(float x) {
    const float t = x * fmaf(-0.10294324397f, x * x, -2.30220819814f);
    float r; asm("rcp.approx.ftz.f32 %0, %1;" : "=f"(r) : "f"(1.f + ex2(t)));
    return x * r;
}

#define CTR(i) do {} while (0)

template <int NSPLIT>
__device__ __forceinline__ void ln2_row(const Params& p, int rb, int r, int lane) {
    const int row = rb * 128 + r;
    uint4 u[2 * NSPLIT];
#pragma unroll
    for (int sp = 0; sp < NSPLIT; sp++) {
        const uint4* src = (const uint4*)(g_op + (size_t)(op_row(rb, sp) + r) * D_);
        u[2 * sp] = __ldcg(src + lane); u[2 * sp + 1] = __ldcg(src + 32 + lane);
    }
    const uint4* xr = (const uint4*)(p.x + (size_t)row * D_);
    const uint4 xa = __ldg(xr + lane), xb = __ldg(xr + 32 + lane);
    uint32_t ga[8], c1[8], sm[8];
    load_mod8(g_mod + 2 * D_, lane, ga);
    load_mod8(g_mod + 4 * D_, lane, c1);
    load_mod8(g_mod + 3 * D_, lane, sm);
    float a[16];
#pragma unroll
    for (int i = 0; i < 16; i++) a[i] = 0.f;
#pragma unroll
    for (int sp = 0; sp < 2 * NSPLIT; sp++) {
        float* q = a + (sp & 1) * 8;
        q[0] += bflo(u[sp].x); q[1] += bfhi(u[sp].x); q[2] += bflo(u[sp].y); q[3] += bfhi(u[sp].y);
        q[4] += bflo(u[sp].z); q[5] += bfhi(u[sp].z); q[6] += bflo(u[sp].w); q[7] += bfhi(u[sp].w);
    }
    const uint32_t xv[8] = {xa.x, xa.y, xa.z, xa.w, xb.x, xb.y, xb.z, xb.w};
    uint32_t v[8], r8[8];
#pragma unroll
    for (int i = 0; i < 8; i++) v[i] = hadd2(xv[i], hmul2(ga[i], pack2(a[2 * i], a[2 * i + 1])));
    uint4* x1r = (uint4*)(g_x1 + (size_t)row * D_);
    x1r[lane] = make_uint4(v[0], v[1], v[2], v[3]); x1r[32 + lane] = make_uint4(v[4], v[5], v[6], v[7]);
    uint32_t mu2; float rden;
    ln_stats(v, mu2, rden);
#pragma unroll
    for (int i = 0; i < 8; i++) c1[i] = hadd2(c1[i], 0x3F803F80u);
    ln_apply(v, mu2, rden, c1, sm, r8);
    uint4* hr = (uint4*)(g_h2 + (size_t)row * D_);
    hr[lane] = make_uint4(r8[0], r8[1], r8[2], r8[3]); hr[32 + lane] = make_uint4(r8[4], r8[5], r8[6], r8[7]);
}

__device__ __forceinline__ void consumer(const Params& p, uint32_t sb, int warp, int lane) {
    const uint32_t bars = sb + SM_BAR;
    const int wg = warp >> 2, wl = warp & 3;
    const uint32_t l7 = lane & 7, l8 = lane >> 3, g = lane >> 2, t = lane & 3;
    Pipe pp{0, 0};
    uint32_t seq = 0, stg_phase = 1;
    const int srow = wl * 16 + l7 + (l8 & 1) * 8;
    const uint32_t stg_base = sb + W_STG + wg * 32768 + srow * 128;
    const uint32_t sx = ((lane >> 4) ^ (srow & 7)) << 4;
#pragma unroll 1
    while (true) {
        mbar_wait(bars + B_FULL + pp.stage * 8, pp.phase);
        const uint32_t jd = lds32(bars + B_RING + (seq & 7) * 4);
        CTR(3);
        seq++;
        const int type = jd & 255, rb = (jd >> 8) & 255, cb = jd >> 16;
        if (type == J_END) { mbar_wait(bars + B_STGFREE + wg * 8, stg_phase); bar_arrive(NB_ST + wg, 160); break; }
        if (type == J_LN) {
            __syncwarp();
            if (lane == 0) mbar_arrive(bars + B_EMPTY + pp.stage * 8);
            pipe_next(pp);
            if (rb >= FINE_RB) ln2_row<OSPLIT2>(p, rb, cb * 8 + warp, lane);
            else {
#pragma unroll 1
                for (int rr = 0; rr < 2; rr++) ln2_row<OSPLIT>(p, rb, cb * 16 + warp * 2 + rr, lane);
            }
            mbar_wait(bars + B_STGFREE + wg * 8, stg_phase); stg_phase ^= 1;
            CTR(4); CTR(5);
            bar_arrive(NB_ST + wg, 160);
            continue;
        }
        if (type >= J_DN) {
            float acc[64];
#pragma unroll
            for (int i = 0; i < 64; i++) acc[i] = 0.f;
            if (type == J_DN2) {
#pragma unroll 1
                for (int kb = 0; kb < 28; kb++) {
                    if (kb) mbar_wait(bars + B_FULL + pp.stage * 8, pp.phase);
                    const uint32_t st = sb + pp.stage * W_STAGE;
                    const uint64_t da = mkdesc(st + wg * 8192, 16, 1024), db = mkdesc(st + 16384, 8192, 1024);
                    wg_fence();
#pragma unroll
                    for (int ks = 0; ks < 4; ks++) wgmma_n64(acc, da + ks * 2, db + ks * 128);
                    wg_commit();
                    wg_wait0();
                    if (lane == 0) mbar_arrive(bars + B_EMPTY + pp.stage * 8);
                    pipe_next(pp);
                }
            } else {
                const int nk = type == J_DN ? 28 : 8;
#pragma unroll 1
                for (int kb = 0; kb < nk; kb++) {
                    if (kb) mbar_wait(bars + B_FULL + pp.stage * 8, pp.phase);
                    const uint32_t st = sb + pp.stage * W_STAGE;
                    const uint64_t da = mkdesc(st + wg * 8192, 16, 1024), db = mkdesc(st + 16384, 8192, 1024);
                    wg_fence();
#pragma unroll
                    for (int ks = 0; ks < 4; ks++) wgmma_n128(acc, da + ks * 2, db + ks * 128, 1);
                    wg_commit();
                    wg_wait0();
                    if (lane == 0) mbar_arrive(bars + B_EMPTY + pp.stage * 8);
                    pipe_next(pp);
                }
            }
            CTR(4);
            if (type == J_UP2) {
                mbar_wait(bars + B_STGFREE + wg * 8, stg_phase); stg_phase ^= 1;
#pragma unroll
                for (int j = 0; j < 4; j++) {
                    uint32_t r[4];
#pragma unroll
                    for (int q = 0; q < 4; q++) {
                        const uint32_t gw = pack2(acc[8 * j + 2 * q], acc[8 * j + 2 * q + 1]);
                        const uint32_t uw = pack2(acc[32 + 8 * j + 2 * q], acc[32 + 8 * j + 2 * q + 1]);
                        r[q] = hmul2(pack2(gelu_tanh(bflo(gw)), gelu_tanh(bfhi(gw))), uw);
                    }
                    stsm4(stg_base + (sx ^ (j << 5)), r[0], r[1], r[2], r[3]);
                }
            } else {
                mbar_wait(bars + B_FULL + pp.stage * 8, pp.phase);
                const uint32_t st = sb + pp.stage * W_STAGE;
                mbar_wait(bars + B_STGFREE + wg * 8, stg_phase); stg_phase ^= 1;
                const uint32_t* gb = (const uint32_t*)(g_mod + 5 * D_ + cb * (type == J_DN ? 128 : 64)) + t;
                const uint32_t xa = st + wg * 8192 + (wl * 16 + g) * 128 + (g << 4) + t * 4;
#pragma unroll
                for (int j = 0; j < 8; j++) {
                    if (j == 4 && type == J_DN2) break;
                    uint32_t r[4];
#pragma unroll
                    for (int q = 0; q < 4; q++) {
                        const int nt = 2 * j + (q >> 1);
                        const uint32_t xw = lds32((xa ^ ((nt & 7) << 4)) + (nt >> 3) * 16384 + (q & 1) * 1024);
                        r[q] = hadd2(xw, hmul2(__ldcg(gb + nt * 4), pack2(acc[8 * j + 2 * q], acc[8 * j + 2 * q + 1])));
                    }
                    stsm4(stg_base + (j >> 2) * 8192 + (sx ^ ((2 * j & 7) << 4)), r[0], r[1], r[2], r[3]);
                }
                __syncwarp();
                if (lane == 0) mbar_arrive(bars + B_EMPTY + pp.stage * 8);
                pipe_next(pp);
            }
            fence_async_smem();
            CTR(5);
            bar_arrive(NB_ST + wg, 160);
            continue;
        }
        float acc[128];
#pragma unroll
        for (int i = 0; i < 128; i++) acc[i] = 0.f;
        const int nk = type == J_O ? (rb >= FINE_RB ? 64 / OSPLIT2 : 64 / OSPLIT) : 8;
#pragma unroll 1
        for (int kb = 0; kb < nk; kb++) {
            if (kb) mbar_wait(bars + B_FULL + pp.stage * 8, pp.phase);
            const uint32_t st = sb + pp.stage * W_STAGE;
            const uint64_t da = mkdesc(st + wg * 8192, 16, 1024), db = mkdesc(st + 16384, 8192, 1024);
            wg_fence();
#pragma unroll
            for (int ks = 0; ks < 4; ks++) wgmma_n256(acc, da + ks * 2, db + ks * 128, 1);
            wg_commit();
            wg_wait0();
            if (lane == 0) mbar_arrive(bars + B_EMPTY + pp.stage * 8);
            pipe_next(pp);
        }
        CTR(4);
        if (type == J_QA) {
            uint32_t qf[64];
#pragma unroll
            for (int i = 0; i < 64; i++) qf[i] = pack2(acc[2 * i], acc[2 * i + 1]);
            const int sg = warp >> 1, half = warp & 1;
            const float sc = 0.08838834764831845f * 1.4426950408889634f;
            const uint32_t xoff = (sg >> 1) * 8192 + ((sg & 1) * 32 + l7) * 128;
            const uint32_t moff = 32768 + (sg * 8 + l7) * 128;
            const uint32_t kch = (l8 ^ l7) << 4;
            const uint32_t vch = ((l8 & 1) ^ l7) << 4;
            mbar_wait(bars + B_STGFREE + wg * 8, stg_phase); stg_phase ^= 1;
#pragma unroll
            for (int hh = 0; hh < 2; hh++) {
                mbar_wait(bars + B_FULL + pp.stage * 8, pp.phase);
                uint32_t st = sb + pp.stage * W_STAGE;
                float sa[5][4];
#pragma unroll
                for (int n = 0; n < 5; n++) sa[n][0] = sa[n][1] = sa[n][2] = sa[n][3] = 0.f;
#pragma unroll
                for (int i = 0; i < 4; i++) {
                    const uint32_t* q = qf + hh * 32 + i * 8;
                    uint32_t kk[5][4];
                    ldsm4(kk[0][0], kk[0][1], kk[0][2], kk[0][3], st + moff + (i >> 1) * 4096 + (kch ^ ((i & 1) * 64)));
#pragma unroll
                    for (int n = 1; n < 5; n++)
                        ldsm4(kk[n][0], kk[n][1], kk[n][2], kk[n][3], st + xoff + (n - 1) * 1024 + (i >> 1) * 16384 + (kch ^ ((i & 1) * 64)));
#pragma unroll
                    for (int n = 0; n < 5; n++) mma16816(sa[n], q[0], q[1], q[2], q[3], kk[n][0], kk[n][1]);
#pragma unroll
                    for (int n = 0; n < 5; n++) mma16816(sa[n], q[4], q[5], q[6], q[7], kk[n][2], kk[n][3]);
                }
                __syncwarp();
                if (lane == 0) mbar_arrive(bars + B_EMPTY + pp.stage * 8);
                pipe_next(pp);
                const int iq0 = half * 16 + g - 2 * t, iq1 = iq0 + 8;
                float m0 = fmaxf(sa[0][0], sa[0][1]), m1 = fmaxf(sa[0][2], sa[0][3]);
#pragma unroll
                for (int n = 1; n < 5; n++) {
#pragma unroll
                    for (int e = 0; e < 2; e++) {
                        const int jx = (n - 1) * 8 + e;
                        if (jx > iq0) sa[n][e] = -3.0e38f;
                        if (jx > iq1) sa[n][2 + e] = -3.0e38f;
                        m0 = fmaxf(m0, sa[n][e]); m1 = fmaxf(m1, sa[n][2 + e]);
                    }
                }
                m0 = fmaxf(m0, __shfl_xor_sync(~0u, m0, 1)); m1 = fmaxf(m1, __shfl_xor_sync(~0u, m1, 1));
                m0 = fmaxf(m0, __shfl_xor_sync(~0u, m0, 2)); m1 = fmaxf(m1, __shfl_xor_sync(~0u, m1, 2));
                m0 *= -sc; m1 *= -sc;
                float l0 = 0.f, l1 = 0.f;
                uint32_t p0[5], p1[5];
#pragma unroll
                for (int n = 0; n < 5; n++) {
                    const float e0 = ex2(fmaf(sa[n][0], sc, m0)), e1 = ex2(fmaf(sa[n][1], sc, m0));
                    const float e2 = ex2(fmaf(sa[n][2], sc, m1)), e3 = ex2(fmaf(sa[n][3], sc, m1));
                    l0 += e0 + e1; l1 += e2 + e3;
                    p0[n] = pack2(e0, e1); p1[n] = pack2(e2, e3);
                }
                l0 += __shfl_xor_sync(~0u, l0, 1); l1 += __shfl_xor_sync(~0u, l1, 1);
                l0 += __shfl_xor_sync(~0u, l0, 2); l1 += __shfl_xor_sync(~0u, l1, 2);
                const float i0 = __fdividef(1.f, l0), i1 = __fdividef(1.f, l1);
                mbar_wait(bars + B_FULL + pp.stage * 8, pp.phase);
                st = sb + pp.stage * W_STAGE;
#pragma unroll
                for (int bx = 0; bx < 2; bx++) {
                    float o[8][4];
                    uint32_t vm[8], v0[4][4], v1[4][4];
#pragma unroll
                    for (int ep = 0; ep < 4; ep++) {
                        ldsm2t(vm[2 * ep], vm[2 * ep + 1], st + moff + bx * 4096 + (vch ^ (ep << 5)));
                        const uint32_t va = st + xoff + (l8 >> 1) * 1024 + bx * 16384 + (vch ^ (ep << 5));
                        ldsm4t(v0[ep][0], v0[ep][1], v0[ep][2], v0[ep][3], va);
                        ldsm4t(v1[ep][0], v1[ep][1], v1[ep][2], v1[ep][3], va + 2048);
                    }
#pragma unroll
                    for (int n = 0; n < 8; n++) { o[n][0] = o[n][1] = o[n][2] = o[n][3] = 0.f; mma16816(o[n], p0[0], p1[0], p0[1], p1[1], vm[n], v0[n >> 1][n & 1]); }
#pragma unroll
                    for (int n = 0; n < 8; n++) mma16816(o[n], p0[2], p1[2], p0[3], p1[3], v0[n >> 1][2 + (n & 1)], v1[n >> 1][n & 1]);
#pragma unroll
                    for (int n = 0; n < 8; n++) mma1688(o[n], p0[4], p1[4], v1[n >> 1][2 + (n & 1)]);
#pragma unroll
                    for (int ep = 0; ep < 4; ep++)
                        stsm4(stg_base + (hh * 2 + bx) * 8192 + (sx ^ (ep << 5)),
                              pack2(o[2 * ep][0] * i0, o[2 * ep][1] * i0), pack2(o[2 * ep][2] * i1, o[2 * ep][3] * i1),
                              pack2(o[2 * ep + 1][0] * i0, o[2 * ep + 1][1] * i0), pack2(o[2 * ep + 1][2] * i1, o[2 * ep + 1][3] * i1));
                }
                __syncwarp();
                if (lane == 0) mbar_arrive(bars + B_EMPTY + pp.stage * 8);
                pipe_next(pp);
            }
        } else if (type == J_UP) {
            mbar_wait(bars + B_STGFREE + wg * 8, stg_phase); stg_phase ^= 1;
#pragma unroll
            for (int j = 0; j < 8; j++) {
                uint32_t r[4];
#pragma unroll
                for (int q = 0; q < 4; q++) {
                    const uint32_t gw = pack2(acc[8 * j + 2 * q], acc[8 * j + 2 * q + 1]);
                    const uint32_t uw = pack2(acc[64 + 8 * j + 2 * q], acc[64 + 8 * j + 2 * q + 1]);
                    r[q] = hmul2(pack2(gelu_tanh(bflo(gw)), gelu_tanh(bfhi(gw))), uw);
                }
                stsm4(stg_base + (j >> 2) * 8192 + (sx ^ ((2 * j & 7) << 4)), r[0], r[1], r[2], r[3]);
            }
        } else {
            mbar_wait(bars + B_STGFREE + wg * 8, stg_phase); stg_phase ^= 1;
#pragma unroll
            for (int j = 0; j < 16; j++)
                stsm4(stg_base + (j >> 2) * 8192 + (sx ^ ((2 * j & 7) << 4)),
                      pack2(acc[8 * j], acc[8 * j + 1]), pack2(acc[8 * j + 2], acc[8 * j + 3]),
                      pack2(acc[8 * j + 4], acc[8 * j + 5]), pack2(acc[8 * j + 6], acc[8 * j + 7]));
        }
        fence_async_smem();
        CTR(5);
        bar_arrive(NB_ST + wg, 160);
    }
}

__global__ void __launch_bounds__(384, 1) k_work(const __grid_constant__ Params p) {
    extern __shared__ __align__(1024) unsigned char smem_raw[];
    const uint32_t sb = smem_u32(smem_raw);
    if (sb & 1023) __trap();
    const int warp = __shfl_sync(~0u, threadIdx.x >> 5, 0);
    int lane; asm volatile("mov.u32 %0, %%laneid;" : "=r"(lane));
    if (threadIdx.x == 0) {
        const uint32_t bars = sb + SM_BAR;
        for (int i = 0; i < W_NST; i++) { mbar_init(bars + B_FULL + i * 8, 1); mbar_init(bars + B_EMPTY + i * 8, 8); }
        mbar_init(bars + B_STGFREE, 1); mbar_init(bars + B_STGFREE + 8, 1);
        asm volatile("fence.mbarrier_init.release.cluster;" ::: "memory");
    }
    __syncthreads();
    if (warp < 8) {
        asm volatile("setmaxnreg.inc.sync.aligned.u32 232;");
        consumer(p, sb, warp, lane);
    } else {
        asm volatile("setmaxnreg.dec.sync.aligned.u32 40;");
        if (warp == 8) { if (lane == 0) producer(p, sb); }
        else if (warp < 11) store_warp(p, sb, warp - 9, lane);
    }
}

typedef CUresult (*EncodeFn)(CUtensorMap*, CUtensorMapDataType, cuuint32_t, void*, const cuuint64_t*, const cuuint64_t*,
                             const cuuint32_t*, const cuuint32_t*, CUtensorMapInterleave, CUtensorMapSwizzle,
                             CUtensorMapL2promotion, CUtensorMapFloatOOBfill);

static void make_map(EncodeFn enc, CUtensorMap* m, const void* ptr, uint64_t rows, uint64_t cols, uint32_t box_rows) {
    cuuint64_t dims[2] = {cols, rows};
    cuuint64_t strides[1] = {cols * 2};
    cuuint32_t box[2] = {64, box_rows};
    cuuint32_t es[2] = {1, 1};
    enc(m, CU_TENSOR_MAP_DATA_TYPE_BFLOAT16, 2, const_cast<void*>(ptr), dims, strides, box, es, CU_TENSOR_MAP_INTERLEAVE_NONE,
        CU_TENSOR_MAP_SWIZZLE_128B, CU_TENSOR_MAP_L2_PROMOTION_L2_256B, CU_TENSOR_MAP_FLOAT_OOB_FILL_NONE);
}
template <typename T> static void* sym_addr(T& sym) { void* p = nullptr; cudaGetSymbolAddress(&p, sym); return p; }

extern "C" void kernel_launch(void* const* d_in, const int* in_sizes, int n_in, void* d_out, int out_size) {
    static Params prm;
    static RecParams rp;
    static bool ready = false;
    static const void* key[14];
    bool same = ready;
    for (int i = 0; i < 13 && same; i++) same = key[i] == d_in[i];
    same = same && key[13] == d_out;
    if (!same) {
        void* fn = nullptr;
        cudaDriverEntryPointQueryResult qr;
        cudaGetDriverEntryPoint("cuTensorMapEncodeTiled", &fn, cudaEnableDefault, &qr);
        EncodeFn enc = (EncodeFn)fn;
        make_map(enc, &prm.tm_h, sym_addr(g_h), S_, D_, 64);
        make_map(enc, &prm.tm_kv, sym_addr(g_kv), S_, 2 * HD_, 64);
        make_map(enc, &prm.tm_kvm, sym_addr(g_kvm), NSEG * 8, 2 * HD_, 32);
        make_map(enc, &prm.tm_o, sym_addr(g_o), S_, HD_, 64);
        make_map(enc, &prm.tm_op, sym_addr(g_op), OP_ROWS, D_, 64);
        make_map(enc, &prm.tm_h2, sym_addr(g_h2), S_, D_, 64);
        make_map(enc, &prm.tm_act, sym_addr(g_act), S_, DF_, 64);
        make_map(enc, &prm.tm_x1, sym_addr(g_x1), S_, D_, 64);
        make_map(enc, &prm.tm_out, d_out, S_, D_, 64);
        make_map(enc, &prm.tm_wq, d_in[2], D_, HD_, 64);
        make_map(enc, &prm.tm_wk, d_in[3], D_, HD_, 64);
        make_map(enc, &prm.tm_wv, d_in[4], D_, HD_, 64);
        make_map(enc, &prm.tm_wo, d_in[5], HD_, D_, 64);
        make_map(enc, &prm.tm_wg, d_in[8], D_, DF_, 64);
        make_map(enc, &prm.tm_wu, d_in[9], D_, DF_, 64);
        make_map(enc, &prm.tm_wd, d_in[10], DF_, D_, 64);
        prm.x = (const bf16*)d_in[0];
        rp.mem0 = (const bf16*)d_in[1];
        rp.wq = (const bf16*)d_in[2]; rp.wk = (const bf16*)d_in[3]; rp.wv = (const bf16*)d_in[4]; rp.wo = (const bf16*)d_in[5];
        cudaFuncSetAttribute(k_work, cudaFuncAttributeMaxDynamicSharedMemorySize, SMEM_BYTES);
        cudaFuncSetAttribute(k_rec, cudaFuncAttributeMaxDynamicSharedMemorySize, R_SMEM);
        cudaFuncSetAttribute(k_rec, cudaFuncAttributeNonPortableClusterSizeAllowed, 1);
        {
            cudaLaunchConfig_t cfg = {};
            cfg.gridDim = dim3(128); cfg.blockDim = dim3(384); cfg.dynamicSmemBytes = R_SMEM;
            cudaLaunchAttribute at[1];
            at[0].id = cudaLaunchAttributeClusterDimension; at[0].val.clusterDim.x = 16; at[0].val.clusterDim.y = 1; at[0].val.clusterDim.z = 1;
            cfg.attrs = at; cfg.numAttrs = 1;
            int n = 0;
            cudaOccupancyMaxActiveClusters(&n, k_rec, &cfg);
            rp.ncl = n < 4 ? 4 : (n > 8 ? 8 : n);
        }
        for (int i = 0; i < 13; i++) key[i] = d_in[i];
        key[13] = d_out;
        ready = true;
    }
    cudaStream_t st = cudaStreamPerThread;
    PrefetchList pf;
    pf.p[0] = (const bf16*)d_in[3]; pf.p[1] = (const bf16*)d_in[4]; pf.p[2] = (const bf16*)d_in[2]; pf.p[3] = (const bf16*)d_in[5]; pf.p[4] = nullptr;
    k_mod<<<96, 256, 0, st>>>((const bf16*)d_in[11], (const bf16*)d_in[12], pf);
    {
        cudaLaunchConfig_t cfg = {};
        cfg.gridDim = dim3(S_ / 8); cfg.blockDim = dim3(256); cfg.stream = st;
        cudaLaunchAttribute at[1];
        at[0].id = cudaLaunchAttributeProgrammaticStreamSerialization; at[0].val.programmaticStreamSerializationAllowed = 1;
        cfg.attrs = at; cfg.numAttrs = 1;
        cudaLaunchKernelEx(&cfg, k_ln1, (const bf16*)d_in[0]);
    }
    auto launch_rec = [&]() {
        cudaLaunchConfig_t cfg = {};
        cfg.gridDim = dim3(16 * rp.ncl); cfg.blockDim = dim3(384); cfg.dynamicSmemBytes = R_SMEM; cfg.stream = st;
        cudaLaunchAttribute at[1];
        at[0].id = cudaLaunchAttributeClusterDimension; at[0].val.clusterDim.x = 16; at[0].val.clusterDim.y = 1; at[0].val.clusterDim.z = 1;
        cfg.attrs = at; cfg.numAttrs = 1;
        cudaLaunchKernelEx(&cfg, k_rec, rp);
    };
    auto launch_work = [&](int j0, int j1, int pdl) {
        prm.job_begin = j0; prm.job_end = j1;
        cudaLaunchConfig_t cfg = {};
        cfg.gridDim = dim3(132); cfg.blockDim = dim3(384); cfg.dynamicSmemBytes = SMEM_BYTES; cfg.stream = st;
        cudaLaunchAttribute at[1];
        at[0].id = cudaLaunchAttributeProgrammaticStreamSerialization; at[0].val.programmaticStreamSerializationAllowed = 1;
        cfg.attrs = at; cfg.numAttrs = pdl;
        cudaLaunchKernelEx(&cfg, k_work, prm);
    };
    launch_rec();
    launch_work(0, N_JOBS, 1);
}
```

```cpp
#include <cuda_runtime.h>
#include <cuda_bf16.h>
#include <cuda.h>
#include <stdint.h>

typedef __nv_bfloat16 bf16;

constexpr int S_ = 2048, D_ = 512, H_ = 32, DH_ = 128, HD_ = 4096, NSEG = 64, DF_ = 1792;
constexpr int NRB = 16;
constexpr int OSPLIT = 4;

__device__ __align__(1024) bf16 g_h[S_ * D_];
__device__ __align__(1024) bf16 g_kv[S_ * 2 * HD_];
__device__ __align__(1024) bf16 g_kvm[NSEG * 8 * 2 * HD_];
__device__ __align__(1024) bf16 g_o[S_ * HD_];
constexpr int FINE_RB = 15;
constexpr int OSPLIT2 = 16;
constexpr int OP_ROWS = OSPLIT * S_ + OSPLIT2 * (NRB - FINE_RB) * 128;
__device__ __align__(1024) bf16 g_op[OP_ROWS * D_];
__device__ __align__(1024) bf16 g_x1[S_ * D_];
__device__ __align__(1024) bf16 g_h2[S_ * D_];
__device__ __align__(1024) bf16 g_act[S_ * DF_];
__device__ __align__(1024) bf16 g_mod[6 * D_];
__device__ uint32_t g_Fraw[131072 + 65536 + 2048];
#define g_F ((uint32_t*)(((uint64_t)g_Fraw + 0x7FFFFull) & ~0x7FFFFull))
constexpr int F_KV = 0, F_MEM = 16, F_O = 80, F_OP = 96, F_H2 = 112, F_ACT = 128, F_HEAD = 144  , F_SIDE = 150  , F_TOTAL = 160;
__device__ __align__(128) unsigned int g_flags[F_TOTAL * 32];
#define TR(j, i) do {} while (0)

__device__ __forceinline__ uint32_t smem_u32(const void* p) { return (uint32_t)__cvta_generic_to_shared(p); }
__device__ __forceinline__ uint32_t clk32() { uint32_t c; asm volatile("mov.u32 %0, %%clock;" : "=r"(c)); return c; }
__device__ __forceinline__ uint32_t mapa_u32(uint32_t addr, uint32_t rank) {
    uint32_t r; asm volatile("mapa.shared::cluster.u32 %0, %1, %2;" : "=r"(r) : "r"(addr), "r"(rank)); return r;
}
__device__ __forceinline__ void mbar_init(uint32_t bar, uint32_t cnt) {
    asm volatile("mbarrier.init.shared::cta.b64 [%0], %1;" :: "r"(bar), "r"(cnt) : "memory");
}
__device__ __forceinline__ void mbar_inval(uint32_t bar) {
    asm volatile("mbarrier.inval.shared::cta.b64 [%0];" :: "r"(bar) : "memory");
}
__device__ __forceinline__ void mbar_expect_tx(uint32_t bar, uint32_t bytes) {
    asm volatile("mbarrier.arrive.expect_tx.shared::cta.b64 _, [%0], %1;" :: "r"(bar), "r"(bytes) : "memory");
}
__device__ __forceinline__ void mbar_arrive(uint32_t bar) {
    asm volatile("mbarrier.arrive.shared::cta.b64 _, [%0];" :: "r"(bar) : "memory");
}
__device__ __forceinline__ bool mbar_try_wait(uint32_t bar, uint32_t parity) {
    uint32_t ok;
    asm volatile("{\n.reg .pred p;\nmbarrier.try_wait.parity.shared::cta.b64 p, [%1], %2;\nselp.u32 %0, 1, 0, p;\n}"
                 : "=r"(ok) : "r"(bar), "r"(parity) : "memory");
    return ok;
}
__device__ __forceinline__ bool mbar_try_wait_cluster(uint32_t bar, uint32_t parity) {
    uint32_t ok;
    asm volatile("{\n.reg .pred p;\nmbarrier.try_wait.parity.acquire.cluster.shared::cta.b64 p, [%1], %2;\nselp.u32 %0, 1, 0, p;\n}"
                 : "=r"(ok) : "r"(bar), "r"(parity) : "memory");
    return ok;
}
constexpr int SPIN_LIMIT = 1 << 18;
#define TIMEOUT(code, info) do {} while (0)
__device__ __forceinline__ void mbar_wait(uint32_t bar, uint32_t parity) {
    int g = 0;
#pragma unroll 1
    while (!mbar_try_wait(bar, parity)) { if (++g >= SPIN_LIMIT) { TIMEOUT(0, bar & 255); break; } }
}
__device__ __forceinline__ void mbar_wait_cluster(uint32_t bar, uint32_t parity) {
    int g = 0;
#pragma unroll 1
    while (!mbar_try_wait_cluster(bar, parity)) { if (++g >= SPIN_LIMIT) { TIMEOUT(1, bar & 255); break; } }
}
__device__ __forceinline__ void bar_sync(int id, int n) { asm volatile("bar.sync %0, %1;" :: "r"(id), "r"(n) : "memory"); }
__device__ __forceinline__ void bar_arrive(int id, int n) { asm volatile("bar.arrive %0, %1;" :: "r"(id), "r"(n) : "memory"); }
__device__ __forceinline__ void cluster_sync_all() {
    asm volatile("barrier.cluster.arrive.aligned;\nbarrier.cluster.wait.aligned;" ::: "memory");
}
__device__ __forceinline__ void st_async_v2(uint32_t addr, float a, float b, uint32_t bar) {
    asm volatile("st.async.weak.shared::cluster.mbarrier::complete_tx::bytes.v2.f32 [%0], {%1,%2}, [%3];"
                 :: "r"(addr), "f"(a), "f"(b), "r"(bar) : "memory");
}
__device__ __forceinline__ void st_async_v4(uint32_t addr, uint4 v, uint32_t bar) {
    asm volatile("st.async.weak.shared::cluster.mbarrier::complete_tx::bytes.v4.b32 [%0], {%1,%2,%3,%4}, [%5];"
                 :: "r"(addr), "r"(v.x), "r"(v.y), "r"(v.z), "r"(v.w), "r"(bar) : "memory");
}
__device__ __forceinline__ uint2 ldg_relaxed2(const uint2* p) {
    uint2 v;
    asm volatile("ld.relaxed.gpu.global.v2.b32 {%0,%1}, [%2];" : "=r"(v.x), "=r"(v.y) : "l"(p) : "memory");
    return v;
}
__device__ __forceinline__ void stg_relaxed2(uint2* p, uint2 v) {
    asm volatile("st.relaxed.gpu.global.v2.b32 [%0], {%1,%2};" :: "l"(p), "r"(v.x), "r"(v.y) : "memory");
}
__device__ __forceinline__ uint4 ldg_relaxed(const uint4* p) {
    uint4 v;
    asm volatile("ld.relaxed.gpu.global.v4.b32 {%0,%1,%2,%3}, [%4];" : "=r"(v.x), "=r"(v.y), "=r"(v.z), "=r"(v.w) : "l"(p) : "memory");
    return v;
}
__device__ __forceinline__ void stg_relaxed(uint4* p, uint4 v) {
    asm volatile("st.relaxed.gpu.global.v4.b32 [%0], {%1,%2,%3,%4};" :: "l"(p), "r"(v.x), "r"(v.y), "r"(v.z), "r"(v.w) : "memory");
}
__device__ __forceinline__ void stg_relaxed32(uint32_t* p, uint32_t v) {
    asm volatile("st.relaxed.gpu.global.b32 [%0], %1;" :: "l"(p), "r"(v) : "memory");
}
__device__ __forceinline__ uint32_t ldg_relaxed32(const uint32_t* p) {
    uint32_t v; asm volatile("ld.relaxed.gpu.global.b32 %0, [%1];" : "=r"(v) : "l"(p) : "memory"); return v;
}
__device__ __forceinline__ unsigned int ld_acquire(const unsigned int* p) {
    unsigned int v; asm volatile("ld.acquire.gpu.global.u32 %0, [%1];" : "=r"(v) : "l"(p) : "memory"); return v;
}
__device__ __forceinline__ void red_release(unsigned int* p, unsigned int v) {
    asm volatile("red.release.gpu.global.add.u32 [%0], %1;" :: "l"(p), "r"(v) : "memory");
}
__device__ __forceinline__ void wait_flag(int idx, unsigned int target) {
    const unsigned int* p = &g_flags[idx * 32];
    int g = 0;
#pragma unroll 1
    while (ld_acquire(p) < target) { __nanosleep(20); if (++g >= 64 * SPIN_LIMIT) { TIMEOUT(2, idx); break; } }
}
__device__ __forceinline__ void cp_async16(uint32_t dst, const void* src) {
    asm volatile("cp.async.cg.shared.global [%0], [%1], 16;" :: "r"(dst), "l"(src) : "memory");
}
__device__ __forceinline__ void cp_async_commit() { asm volatile("cp.async.commit_group;" ::: "memory"); }
template <int N> __device__ __forceinline__ void cp_async_wait() { asm volatile("cp.async.wait_group %0;" :: "n"(N) : "memory"); }
__device__ __forceinline__ void ldsm4(uint32_t& r0, uint32_t& r1, uint32_t& r2, uint32_t& r3, uint32_t addr) {
    asm volatile("ldmatrix.sync.aligned.m8n8.x4.shared.b16 {%0,%1,%2,%3}, [%4];" : "=r"(r0), "=r"(r1), "=r"(r2), "=r"(r3) : "r"(addr) : "memory");
}
__device__ __forceinline__ void ldsm4t(uint32_t& r0, uint32_t& r1, uint32_t& r2, uint32_t& r3, uint32_t addr) {
    asm volatile("ldmatrix.sync.aligned.m8n8.x4.trans.shared.b16 {%0,%1,%2,%3}, [%4];" : "=r"(r0), "=r"(r1), "=r"(r2), "=r"(r3) : "r"(addr) : "memory");
}
__device__ __forceinline__ void ldsm2t(uint32_t& r0, uint32_t& r1, uint32_t addr) {
    asm volatile("ldmatrix.sync.aligned.m8n8.x2.trans.shared.b16 {%0,%1}, [%2];" : "=r"(r0), "=r"(r1) : "r"(addr) : "memory");
}
__device__ __forceinline__ void stsm4(uint32_t addr, uint32_t r0, uint32_t r1, uint32_t r2, uint32_t r3) {
    asm volatile("stmatrix.sync.aligned.m8n8.x4.shared.b16 [%0], {%1,%2,%3,%4};" :: "r"(addr), "r"(r0), "r"(r1), "r"(r2), "r"(r3) : "memory");
}
__device__ __forceinline__ void stsm2t(uint32_t addr, uint32_t r0, uint32_t r1) {
    asm volatile("stmatrix.sync.aligned.m8n8.x2.trans.shared.b16 [%0], {%1,%2};" :: "r"(addr), "r"(r0), "r"(r1) : "memory");
}
__device__ __forceinline__ void mma16816(float* d, uint32_t a0, uint32_t a1, uint32_t a2, uint32_t a3, uint32_t b0, uint32_t b1) {
    asm volatile("mma.sync.aligned.m16n8k16.row.col.f32.bf16.bf16.f32 {%0,%1,%2,%3}, {%4,%5,%6,%7}, {%8,%9}, {%0,%1,%2,%3};"
                 : "+f"(d[0]), "+f"(d[1]), "+f"(d[2]), "+f"(d[3]) : "r"(a0), "r"(a1), "r"(a2), "r"(a3), "r"(b0), "r"(b1));
}
__device__ __forceinline__ void mma1688(float* d, uint32_t a0, uint32_t a1, uint32_t b0) {
    asm volatile("mma.sync.aligned.m16n8k8.row.col.f32.bf16.bf16.f32 {%0,%1,%2,%3}, {%4,%5}, {%6}, {%0,%1,%2,%3};"
                 : "+f"(d[0]), "+f"(d[1]), "+f"(d[2]), "+f"(d[3]) : "r"(a0), "r"(a1), "r"(b0));
}
__device__ __forceinline__ void mma16816h(float* d, uint32_t a0, uint32_t a2, uint32_t b0, uint32_t b1) {
    asm volatile("{\n.reg .b32 ju, jv;\nmma.sync.aligned.m16n8k16.row.col.f32.bf16.bf16.f32 {%0,%1,%2,%3}, {%4,ju,%5,jv}, {%6,%7}, {%0,%1,%2,%3};\n}"
                 : "+f"(d[0]), "+f"(d[1]), "+f"(d[2]), "+f"(d[3]) : "r"(a0), "r"(a2), "r"(b0), "r"(b1));
}
__device__ __forceinline__ void mma1688h(float* d, uint32_t a0, uint32_t b0) {
    asm volatile("{\n.reg .b32 ju;\nmma.sync.aligned.m16n8k8.row.col.f32.bf16.bf16.f32 {%0,%1,%2,%3}, {%4,ju}, {%5}, {%0,%1,%2,%3};\n}"
                 : "+f"(d[0]), "+f"(d[1]), "+f"(d[2]), "+f"(d[3]) : "r"(a0), "r"(b0));
}
__device__ __forceinline__ uint32_t pack2(float lo, float hi) {
    uint32_t r; asm("cvt.rn.bf16x2.f32 %0, %1, %2;" : "=r"(r) : "f"(hi), "f"(lo)); return r;
}
__device__ __forceinline__ float bflo(uint32_t w) { return __uint_as_float(w << 16); }
__device__ __forceinline__ float bfhi(uint32_t w) { return __uint_as_float(w & 0xffff0000u); }
__device__ __forceinline__ float rbf(float x) { return __bfloat162float(__float2bfloat16_rn(x)); }
__device__ __forceinline__ float ex2(float x) { float y; asm("ex2.approx.ftz.f32 %0, %1;" : "=f"(y) : "f"(x)); return y; }
__device__ __forceinline__ void sts128(uint32_t addr, uint4 v) {
    asm volatile("st.shared.v4.b32 [%0], {%1,%2,%3,%4};" :: "r"(addr), "r"(v.x), "r"(v.y), "r"(v.z), "r"(v.w) : "memory");
}
__device__ __forceinline__ uint4 lds128(uint32_t addr) {
    uint4 v; asm volatile("ld.shared.v4.b32 {%0,%1,%2,%3}, [%4];" : "=r"(v.x), "=r"(v.y), "=r"(v.z), "=r"(v.w) : "r"(addr) : "memory"); return v;
}
__device__ __forceinline__ float2 lds64f(uint32_t addr) {
    float2 v; asm volatile("ld.shared.v2.f32 {%0,%1}, [%2];" : "=f"(v.x), "=f"(v.y) : "r"(addr) : "memory"); return v;
}
__device__ __forceinline__ float lds32f(uint32_t addr) {
    float v; asm volatile("ld.shared.f32 %0, [%1];" : "=f"(v) : "r"(addr) : "memory"); return v;
}
__device__ __forceinline__ uint32_t lds32(uint32_t addr) {
    uint32_t v; asm volatile("ld.shared.b32 %0, [%1];" : "=r"(v) : "r"(addr) : "memory"); return v;
}
__device__ __forceinline__ void sts32(uint32_t addr, uint32_t v) { asm volatile("st.shared.b32 [%0], %1;" :: "r"(addr), "r"(v) : "memory"); }
__device__ __forceinline__ void sts64f(uint32_t addr, float a, float b) { asm volatile("st.shared.v2.f32 [%0], {%1,%2};" :: "r"(addr), "f"(a), "f"(b) : "memory"); }

__device__ __forceinline__ void tma_load2d(uint32_t dst, const CUtensorMap* tm, int c0, int c1, uint32_t bar) {
    asm volatile("cp.async.bulk.tensor.2d.shared::cluster.global.mbarrier::complete_tx::bytes [%0], [%1, {%3, %4}], [%2];"
                 :: "r"(dst), "l"(tm), "r"(bar), "r"(c0), "r"(c1) : "memory");
}
__device__ __forceinline__ void tma_store2d(const CUtensorMap* tm, uint32_t src, int c0, int c1) {
    asm volatile("cp.async.bulk.tensor.2d.global.shared::cta.bulk_group [%0, {%2, %3}], [%1];"
                 :: "l"(tm), "r"(src), "r"(c0), "r"(c1) : "memory");
}
__device__ __forceinline__ void bulk_commit() { asm volatile("cp.async.bulk.commit_group;" ::: "memory"); }
__device__ __forceinline__ void bulk_wait0() { asm volatile("cp.async.bulk.wait_group 0;" ::: "memory"); }
__device__ __forceinline__ void fence_async_smem() { asm volatile("fence.proxy.async.shared::cta;" ::: "memory"); }
__device__ __forceinline__ void fence_async_all() { asm volatile("fence.proxy.async;" ::: "memory"); }

__device__ __forceinline__ void wg_fence() { asm volatile("wgmma.fence.sync.aligned;" ::: "memory"); }
__device__ __forceinline__ void wg_commit() { asm volatile("wgmma.commit_group.sync.aligned;" ::: "memory"); }
__device__ __forceinline__ void wg_wait0() { asm volatile("wgmma.wait_group.sync.aligned 0;" ::: "memory"); }
__device__ __forceinline__ uint64_t mkdesc(uint32_t saddr, uint32_t lbo, uint32_t sbo) {
    return (uint64_t)((saddr & 0x3FFFF) >> 4) | ((uint64_t)(lbo >> 4) << 16) | ((uint64_t)(sbo >> 4) << 32) | (1ull << 62);
}
#define ACC8(i) "+f"(d[i]), "+f"(d[i + 1]), "+f"(d[i + 2]), "+f"(d[i + 3]), "+f"(d[i + 4]), "+f"(d[i + 5]), "+f"(d[i + 6]), "+f"(d[i + 7])
__device__ __forceinline__ void wgmma_n256(float* d, uint64_t da, uint64_t db, int scale_d) {
    asm volatile(
        "{\n.reg .pred p;\nsetp.ne.b32 p, %130, 0;\n"
        "wgmma.mma_async.sync.aligned.m64n256k16.f32.bf16.bf16 "
        "{%0,%1,%2,%3,%4,%5,%6,%7,%8,%9,%10,%11,%12,%13,%14,%15,%16,%17,%18,%19,%20,%21,%22,%23,%24,%25,%26,%27,%28,%29,%30,%31,"
        "%32,%33,%34,%35,%36,%37,%38,%39,%40,%41,%42,%43,%44,%45,%46,%47,%48,%49,%50,%51,%52,%53,%54,%55,%56,%57,%58,%59,%60,%61,%62,%63,"
        "%64,%65,%66,%67,%68,%69,%70,%71,%72,%73,%74,%75,%76,%77,%78,%79,%80,%81,%82,%83,%84,%85,%86,%87,%88,%89,%90,%91,%92,%93,%94,%95,"
        "%96,%97,%98,%99,%100,%101,%102,%103,%104,%105,%106,%107,%108,%109,%110,%111,%112,%113,%114,%115,%116,%117,%118,%119,%120,%121,%122,%123,%124,%125,%126,%127}, "
        "%128, %129, p, 1, 1, 0, 1;\n}"
        : ACC8(0), ACC8(8), ACC8(16), ACC8(24), ACC8(32), ACC8(40), ACC8(48), ACC8(56),
          ACC8(64), ACC8(72), ACC8(80), ACC8(88), ACC8(96), ACC8(104), ACC8(112), ACC8(120)
        : "l"(da), "l"(db), "r"(scale_d));
}
__device__ __forceinline__ void wgmma_n128(float* d, uint64_t da, uint64_t db, int scale_d) {
    asm volatile(
        "{\n.reg .pred p;\nsetp.ne.b32 p, %66, 0;\n"
        "wgmma.mma_async.sync.aligned.m64n128k16.f32.bf16.bf16 "
        "{%0,%1,%2,%3,%4,%5,%6,%7,%8,%9,%10,%11,%12,%13,%14,%15,%16,%17,%18,%19,%20,%21,%22,%23,%24,%25,%26,%27,%28,%29,%30,%31,"
        "%32,%33,%34,%35,%36,%37,%38,%39,%40,%41,%42,%43,%44,%45,%46,%47,%48,%49,%50,%51,%52,%53,%54,%55,%56,%57,%58,%59,%60,%61,%62,%63}, "
        "%64, %65, p, 1, 1, 0, 1;\n}"
        : ACC8(0), ACC8(8), ACC8(16), ACC8(24), ACC8(32), ACC8(40), ACC8(48), ACC8(56)
        : "l"(da), "l"(db), "r"(scale_d));
}

__device__ __forceinline__ void wgmma_n64(float* d, uint64_t da, uint64_t db) {
    asm volatile(
        "wgmma.mma_async.sync.aligned.m64n64k16.f32.bf16.bf16 "
        "{%0,%1,%2,%3,%4,%5,%6,%7,%8,%9,%10,%11,%12,%13,%14,%15,%16,%17,%18,%19,%20,%21,%22,%23,%24,%25,%26,%27,%28,%29,%30,%31}, "
        "%32, %33, 1, 1, 1, 0, 1;"
        : ACC8(0), ACC8(8), ACC8(16), ACC8(24)
        : "l"(da), "l"(db));
}
__device__ __forceinline__ void wgmma_n8_ta(float* d, uint64_t da, uint64_t db, int scale_d) {
    asm volatile(
        "{\n.reg .pred p;\nsetp.ne.b32 p, %6, 0;\n"
        "wgmma.mma_async.sync.aligned.m64n8k16.f32.bf16.bf16 {%0,%1,%2,%3}, %4, %5, p, 1, 1, 1, 0;\n}"
        : "+f"(d[0]), "+f"(d[1]), "+f"(d[2]), "+f"(d[3]) : "l"(da), "l"(db), "r"(scale_d));
}

struct PrefetchList { const bf16* p[5]; };
__global__ void __launch_bounds__(256) k_mod(const bf16* __restrict__ c, const bf16* __restrict__ w_mod, const PrefetchList pf) {
    asm volatile("griddepcontrol.launch_dependents;");
    __shared__ float s_c[D_];
    __shared__ float s_red[64][33];
    const int tid = threadIdx.x;
    const int cq = tid & 3, rg = tid >> 2;
    uint4 w[8];
#pragma unroll
    for (int i = 0; i < 8; i++)
        w[i] = __ldg((const uint4*)(w_mod + (size_t)(rg * 8 + i) * (6 * D_) + blockIdx.x * 32 + cq * 8));
    for (int i = tid; i < D_; i += 256) {
        float v = __bfloat162float(c[i]);
        s_c[i] = rbf(v / (1.f + __expf(-v)));
    }
    {
        const int gt = blockIdx.x * 256 + tid, nt = gridDim.x * 256;
        for (int i = gt; i < F_TOTAL * 32; i += nt) g_flags[i] = 0;
        for (int i = gt; i < 65536 + 2048; i += nt) g_F[i] = 0;
        if (tid < 11) {
            const int i = tid * gridDim.x + blockIdx.x;
            if (i < 1024) asm volatile("cp.async.bulk.prefetch.L2.global [%0], %1;" :: "l"(pf.p[i >> 8] + (size_t)(i & 255) * 8192), "r"(16384) : "memory");
        }
    }
    __syncthreads();
    float a[8];
#pragma unroll
    for (int j = 0; j < 8; j++) a[j] = 0.f;
#pragma unroll
    for (int i = 0; i < 8; i++) {
        float cv = s_c[rg * 8 + i];
        a[0] += cv * bflo(w[i].x); a[1] += cv * bfhi(w[i].x); a[2] += cv * bflo(w[i].y); a[3] += cv * bfhi(w[i].y);
        a[4] += cv * bflo(w[i].z); a[5] += cv * bfhi(w[i].z); a[6] += cv * bflo(w[i].w); a[7] += cv * bfhi(w[i].w);
    }
#pragma unroll
    for (int j = 0; j < 8; j++) s_red[rg][cq * 8 + j] = a[j];
    __syncthreads();
    if (tid < 32) {
        float s = 0.f;
#pragma unroll 8
        for (int r = 0; r < 64; r++) s += s_red[r][tid];
        g_mod[blockIdx.x * 32 + tid] = __float2bfloat16_rn(s);
    }
}

__device__ __forceinline__ uint32_t hadd2(uint32_t a, uint32_t b) { uint32_t r; asm("add.rn.bf16x2 %0, %1, %2;" : "=r"(r) : "r"(a), "r"(b)); return r; }
__device__ __forceinline__ uint32_t hsub2(uint32_t a, uint32_t b) { uint32_t r; asm("sub.rn.bf16x2 %0, %1, %2;" : "=r"(r) : "r"(a), "r"(b)); return r; }
__device__ __forceinline__ uint32_t hmul2(uint32_t a, uint32_t b) { uint32_t r; asm("mul.rn.bf16x2 %0, %1, %2;" : "=r"(r) : "r"(a), "r"(b)); return r; }
__device__ __forceinline__ void load_mod8(const bf16* m, int lane, uint32_t* v) {
    const uint4 a = __ldcg((const uint4*)m + lane), b = __ldcg((const uint4*)m + 32 + lane);
    v[0] = a.x; v[1] = a.y; v[2] = a.z; v[3] = a.w; v[4] = b.x; v[5] = b.y; v[6] = b.z; v[7] = b.w;
}
__device__ __forceinline__ void ln_stats(const uint32_t* x, uint32_t& mu2, float& rden) {
    float s = 0.f;
#pragma unroll
    for (int i = 0; i < 8; i++) s += bflo(x[i]) + bfhi(x[i]);
#pragma unroll
    for (int o = 16; o > 0; o >>= 1) s += __shfl_xor_sync(~0u, s, o);
    const float mean = s * (1.f / D_);
    float q = 0.f;
#pragma unroll
    for (int i = 0; i < 8; i++) { const float d0 = bflo(x[i]) - mean, d1 = bfhi(x[i]) - mean; q = fmaf(d0, d0, q); q = fmaf(d1, d1, q); }
#pragma unroll
    for (int o = 16; o > 0; o >>= 1) q += __shfl_xor_sync(~0u, q, o);
    mu2 = pack2(mean, mean);
    rden = __frcp_rn(rbf(__fsqrt_rn(rbf(rbf(q * (1.f / D_)) + 1e-5f))));
}
__device__ __forceinline__ void ln_apply(const uint32_t* x, uint32_t mu2, float rden, const uint32_t* c1, const uint32_t* sm, uint32_t* r) {
#pragma unroll
    for (int i = 0; i < 8; i++) {
        const uint32_t d = hsub2(x[i], mu2);
        r[i] = hadd2(hmul2(pack2(bflo(d) * rden, bfhi(d) * rden), c1[i]), sm[i]);
    }
}

__global__ void __launch_bounds__(256) k_ln1(const bf16* __restrict__ x) {
    const int lane = threadIdx.x & 31, row = blockIdx.x * 8 + (threadIdx.x >> 5);
    const uint4* xr = (const uint4*)(x + (size_t)row * D_);
    const uint4 a = __ldg(xr + lane), b = __ldg(xr + 32 + lane);
    const uint32_t v[8] = {a.x, a.y, a.z, a.w, b.x, b.y, b.z, b.w};
    uint32_t mu2; float rden;
    ln_stats(v, mu2, rden);
    asm volatile("griddepcontrol.wait;" ::: "memory");
    uint32_t c1[8], sm[8], r[8];
    load_mod8(g_mod + D_, lane, c1);
    load_mod8(g_mod, lane, sm);
#pragma unroll
    for (int i = 0; i < 8; i++) c1[i] = hadd2(c1[i], 0x3F803F80u);
    ln_apply(v, mu2, rden, c1, sm, r);
    uint4* hr = (uint4*)(g_h + (size_t)row * D_);
    hr[lane] = make_uint4(r[0], r[1], r[2], r[3]); hr[32 + lane] = make_uint4(r[4], r[5], r[6], r[7]);
}

struct __align__(64) Params {
    CUtensorMap tm_h, tm_kv, tm_kvm, tm_o, tm_op, tm_h2, tm_act, tm_x1, tm_out;
    CUtensorMap tm_wq, tm_wk, tm_wv, tm_wo, tm_wg, tm_wu, tm_wd;
    const bf16* x;
    int qmask;
};

constexpr int R_NST = 3;
constexpr uint32_t R_WV = 0, R_MEM = 65536, R_KX = 73728, R_VX = R_KX + R_NST * 4096, R_QS = R_VX + R_NST * 4096,
                   R_KMS = R_QS + 1024, R_VMS = R_KMS + 1024, R_OS = R_VMS + 1024, R_SX = R_OS + 1024, R_BAR = R_SX + 2560,
                   R_RS = 105472  , R_VP = R_RS + 8192  ,
                   R_STG = R_VP + 8192  , R_SMEM = R_STG + 98304;
static_assert(R_BAR + 64 <= R_RS, "smem");
constexpr uint32_t RB_SX = R_BAR, RB_V = R_BAR + 8, RB_E = R_BAR + 16, RB_A = R_BAR + 24, RB_ROLE = R_BAR + 32;
constexpr int W_NST = 3;
constexpr uint32_t W_STAGE = 49152, W_STG = W_NST * W_STAGE, W_END = W_STG + 65536;
constexpr uint32_t SM_BAR = W_END;
constexpr uint32_t SMEM_BYTES = W_END + 1024;
constexpr uint32_t B_FULL = 0, B_EMPTY = 32, B_STGFREE = 64, B_RING = 128;

constexpr int NB_X = 11  , NB_Y = 1, NB_B = 2, NB_C = 3, NB_D = 4, NB_W0 = 6  , NB_ST = 9  ;

__device__ __forceinline__ int pos_of_d(int d) {
    const int rem = d & 31;
    return (d & ~31) + ((rem & 7) >> 1) * 8 + (rem & 1) * 4 + (rem >> 3);
}

#define PROF(i) do {} while (0)
#define PROFG(i) do {} while (0)
#define OPAQUE(x) asm volatile("" : "+r"(x))
#define FENCE_SCHED(x) do { if ((x) == 0u) asm volatile("trap;"); } while (0)
#define VK0_ 4
constexpr int VK0 = VK0_;
constexpr int NOFF = 8;
#define VDELAY -1
#define POLL_GAP 100

struct RecParams { const bf16 *mem0, *wq, *wk, *wv, *wo; int ncl; };

__device__ __forceinline__ void rec_qk(const RecParams& p, const uint32_t sb, const int cta, const int warp, int lane, const int sel) {
    const int crank = cta & 15, cl = cta >> 4, rank = cta & 1;
    const int kh = warp >> 2, aa = warp & 3;
    uint32_t wa[2][16][4];
    const uint32_t stg = sb + R_STG + kh * 32768;
    {
        const int t128 = aa * 32 + lane;
        const int row = (lane >> 4) * 8 + (lane & 7);
        const int ch = t128 & 7;
        const size_t goff = (size_t)kh * 256 * HD_ + cta * 64 + ch * 8;
#pragma unroll 4
        for (int dd = 0; dd < 16; dd++) {
            const int d = dd * 16 + (t128 >> 3), pp = pos_of_d(d);
            cp_async16(sb + R_WV + kh * 32768 + pp * 128 + ((ch ^ (pp & 7)) << 4), p.wv + goff + (size_t)d * HD_);
        }
        cp_async_commit();
#pragma unroll 4
        for (int dd = 0; dd < 16; dd++) {
            const int d = dd * 16 + (t128 >> 3), pp = pos_of_d(d);
            cp_async16(stg + pp * 128 + ((ch ^ (pp & 7)) << 4), p.wq + goff + (size_t)d * HD_);
        }
        cp_async_commit();
        {
            const int i0 = (warp * 32 + lane) * 16, tok = i0 >> 9;
            const uint4 m0 = __ldg((const uint4*)(p.mem0 + i0)), m1 = __ldg((const uint4*)(p.mem0 + i0 + 8));
            const uint32_t mw[8] = {m0.x, m0.y, m0.z, m0.w, m1.x, m1.y, m1.z, m1.w};
#pragma unroll
            for (int e = 0; e < 16; e++) {
                const int pp = pos_of_d((i0 & 511) + e);
                const unsigned short v = (unsigned short)(mw[e >> 1] >> ((e & 1) * 16));
                asm volatile("st.shared.u16 [%0], %1;" :: "r"(sb + R_MEM + (pp >> 3) * 128 + tok * 16 + (pp & 7) * 2), "h"(v) : "memory");
            }
        }
        cp_async_wait<1>();
        bar_sync(NB_W0 + kh, 128);
        const uint32_t fv = row * 128 + (((2 * aa + ((lane >> 3) & 1)) ^ (row & 7)) << 4);
#pragma unroll
        for (int ks = 0; ks < 16; ks++) ldsm4t(wa[0][ks][0], wa[0][ks][1], wa[0][ks][2], wa[0][ks][3], sb + R_WV + kh * 32768 + fv + ks * 2048);
        bar_sync(NB_W0 + kh, 128);
#pragma unroll
        for (int ks = 0; ks < 16; ks++)
            sts128(sb + R_WV + kh * 32768 + (aa * 16 + ks) * 512 + lane * 16, make_uint4(wa[0][ks][0], wa[0][ks][1], wa[0][ks][2], wa[0][ks][3]));
        const uint32_t fo = stg + row * 128 + (((4 * (aa & 1) + ((lane >> 3) & 1)) ^ (row & 7)) << 4);
#pragma unroll 1
        for (int m = 0; m < 2; m++) {
            cp_async_wait<0>();
            bar_sync(NB_W0 + kh, 128);
            if ((aa >> 1) == m) {
#pragma unroll
                for (int ks = 0; ks < 16; ks++) {
                    ldsm4t(wa[0][ks][0], wa[0][ks][1], wa[0][ks][2], wa[0][ks][3], fo + ks * 2048);
                    ldsm4t(wa[1][ks][0], wa[1][ks][1], wa[1][ks][2], wa[1][ks][3], (fo ^ 32) + ks * 2048);
                }
            }
            bar_sync(NB_W0 + kh, 128);
            if (m == 0) {
#pragma unroll 4
                for (int dd = 0; dd < 16; dd++) {
                    const int d = dd * 16 + (t128 >> 3), pp = pos_of_d(d);
                    cp_async16(stg + pp * 128 + ((ch ^ (pp & 7)) << 4), p.wk + goff + (size_t)d * HD_);
                }
                cp_async_commit();
            }
        }
    }
    const uint32_t tab = stg + (aa * 32 + lane) * 16;
    {
        const uint32_t l7 = lane & 7, l8 = lane >> 3, g = lane >> 2, t = lane & 3;
        const uint32_t t0 = l7 * 128 + ((l8 ^ l7) << 4);
        const uint32_t tq = l7 * 128 + (((l8 >> 1) ^ l7) << 4);
        const uint32_t bq = warp >> 1, tp = warp & 1;
        uint4 v;
        v.x = sb + (aa < 2 ? R_QS : R_KMS) + l7 * 128 + (((4 * (aa & 1) + 2 * kh + (l8 & 1)) ^ l7) << 4);
        v.y = sb + R_QS + tq;
        v.z = sb + (warp == 0 ? R_KMS : R_KX + (warp - 1) * 1024) + t0;
        v.w = mapa_u32(sb + R_SX + (rank * 5 + warp) * 256 + lane * 8, crank ^ 1);
        sts128(tab, v);
        sts128(tab + 2048, make_uint4(sb + lane * 16 + R_MEM + kh * 4096, sb + lane * 16 + R_WV + warp * 8192,
                                      sb + lane * 16 + R_VP + warp * 512, sb + lane * 16 + R_VP + 4096 + (warp ^ 4) * 512));
        const uint32_t src = (l8 >> 1) * 8 + l7;
        const uint32_t L = bq * 8 + 2 * tp + (l8 & 1);
        const uint32_t d0 = (crank + ((t >> 1) | (g & 6))) & 15;
        v.x = sb + R_RS + src * 512 + ((L ^ (src & 7)) << 4);
        v.y = mapa_u32(sb + R_MEM + (crank * 4 + bq) * 128 + (4 * tp + 2 * (t & 1) + (g & 1)) * 16, d0);
        v.z = mapa_u32(sb + RB_A, d0);
        v.w = lane;
        sts128(tab + 4096, v);
        const uint64_t wr = (uint64_t)(g_F + ((crank * 2 + ((crank ^ (crank >> 3) ^ sel) & 1)) * 1024 + warp * 128 + cl * 32 + lane));
        sts128(tab + 6144, make_uint4((uint32_t)wr, (uint32_t)(wr >> 32), (uint32_t)((((cl + 1) & 3) - cl) * 128), (uint32_t)((((cl + 2) & 3) - cl) * 128)));
        sts32(tab + 8192, (uint32_t)((((cl + 3) & 3) - cl) * 128));
#pragma unroll
        for (int i = 0; i < NOFF; i++)
            sts128(tab + 10240 + i * 2048, make_uint4(wa[i & 1][i >> 1][0], wa[i & 1][i >> 1][1], wa[i & 1][i >> 1][2], wa[i & 1][i >> 1][3]));
    }
    bar_sync(NB_D, 384);
    uint32_t slot_off = 0;
    const uint32_t slot_inc = warp == 0 ? 0 : 4096;
    const uint32_t sx_bar_rem = (sb + RB_SX) ^ (1u << 24);
    uint4 tb = lds128(tab + 2048);
#pragma unroll 1
    for (int s = 0; s < NSEG; s++) {
        if (s > 0) mbar_wait(sb + RB_A, (s - 1) & 1);
        if (warp == 0) { PROF(0); PROFG(13); }
        uint4 ta;
        {
            float acc[5][4];
#pragma unroll
            for (int c = 0; c < 5; c++) { acc[c][0] = acc[c][1] = acc[c][2] = acc[c][3] = 0.f; }
            uint32_t b[8][4];
            uint4 av[16];
            ldsm4(b[0][0], b[0][1], b[0][2], b[0][3], tb.x);
            ldsm4(b[1][0], b[1][1], b[1][2], b[1][3], tb.x + 512);
            ldsm4(b[2][0], b[2][1], b[2][2], b[2][3], tb.x + 1024);
#pragma unroll
            for (int k2 = 0; k2 < 8; k2++) {
                mma16816(acc[0], wa[0][2 * k2][0], wa[0][2 * k2][1], wa[0][2 * k2][2], wa[0][2 * k2][3], b[k2][0], b[k2][1]);
                mma16816(acc[1], wa[1][2 * k2][0], wa[1][2 * k2][1], wa[1][2 * k2][2], wa[1][2 * k2][3], b[k2][0], b[k2][1]);
                if (2 * k2 >= VK0) mma16816(acc[2], av[2 * k2].x, av[2 * k2].y, av[2 * k2].z, av[2 * k2].w, b[k2][0], b[k2][1]);
                mma16816(acc[3], wa[0][2 * k2 + 1][0], wa[0][2 * k2 + 1][1], wa[0][2 * k2 + 1][2], wa[0][2 * k2 + 1][3], b[k2][2], b[k2][3]);
                mma16816(acc[4], wa[1][2 * k2 + 1][0], wa[1][2 * k2 + 1][1], wa[1][2 * k2 + 1][2], wa[1][2 * k2 + 1][3], b[k2][2], b[k2][3]);
                if (2 * k2 >= VK0) mma16816(acc[2], av[2 * k2 + 1].x, av[2 * k2 + 1].y, av[2 * k2 + 1].z, av[2 * k2 + 1].w, b[k2][2], b[k2][3]);
                if (k2 + 3 < 8) ldsm4(b[k2 + 3][0], b[k2 + 3][1], b[k2 + 3][2], b[k2 + 3][3], tb.x + (k2 + 3) * 512);
                if (VK0 + 2 * k2 < 16) { av[VK0 + 2 * k2] = lds128(tb.y + (VK0 + 2 * k2) * 512); av[VK0 + 2 * k2 + 1] = lds128(tb.y + (VK0 + 2 * k2 + 1) * 512); }
                if (k2 == 5) ta = lds128(tab);
            }
#pragma unroll
            for (int i = 0; i < 4; i++) { acc[0][i] += acc[3][i]; acc[1][i] += acc[4][i]; }
            const float g0 = kh ? acc[0][0] : acc[1][0], g1 = kh ? acc[0][1] : acc[1][1], g2 = kh ? acc[0][2] : acc[1][2], g3 = kh ? acc[0][3] : acc[1][3];
            sts128(tb.w, make_uint4(__float_as_uint(g0), __float_as_uint(g1), __float_as_uint(g2), __float_as_uint(g3)));
            const float k0 = kh ? acc[1][0] : acc[0][0], k1 = kh ? acc[1][1] : acc[0][1], k2_ = kh ? acc[1][2] : acc[0][2], k3 = kh ? acc[1][3] : acc[0][3];
            if (warp == 0) PROF(1);
            bar_sync(NB_X + aa, 64);
            const uint4 o = lds128(tb.z + 4096);
            stsm2t(ta.x, pack2(k0 + __uint_as_float(o.x), k1 + __uint_as_float(o.y)), pack2(k2_ + __uint_as_float(o.z), k3 + __uint_as_float(o.w)));
            sts128(tb.z, make_uint4(__float_as_uint(acc[2][0]), __float_as_uint(acc[2][1]), __float_as_uint(acc[2][2]), __float_as_uint(acc[2][3])));
        }
        const uint32_t kb = ta.z + slot_off;
        if (warp == 0) PROF(14);
        bar_sync(NB_B, 256);
        if (warp < 5) {
            uint32_t q[16], k0, k1, k2, k3, k4, k5, k6, k7;
            float sa[4] = {0.f, 0.f, 0.f, 0.f}, sc[4] = {0.f, 0.f, 0.f, 0.f};
            ldsm4(q[0], q[1], q[2], q[3], ta.y);
            ldsm4(k0, k1, k2, k3, kb);
            ldsm4(q[4], q[5], q[6], q[7], ta.y ^ 32);
            ldsm4(q[8], q[9], q[10], q[11], ta.y ^ 64);
            ldsm4(k4, k5, k6, k7, kb ^ 64);
            ldsm4(q[12], q[13], q[14], q[15], ta.y ^ 96);
            mma16816(sa, q[0], q[1], q[2], q[3], k0, k1);
            bar_arrive(NB_Y, 288);
            mma16816(sc, q[4], q[5], q[6], q[7], k2, k3);
            mma16816(sa, q[8], q[9], q[10], q[11], k4, k5);
            mma16816(sc, q[12], q[13], q[14], q[15], k6, k7);
            const float scl = 0.08838834764831845f * 1.4426950408889634f;
            const float r0 = (sa[0] + sc[0]) * scl, r1 = (sa[1] + sc[1]) * scl;
            if (s != NSEG - 1) {
                st_async_v2(ta.w, r0, r1, sx_bar_rem);
                st_async_v2(ta.w ^ (1u << 24), r0, r1, sx_bar_rem ^ (1u << 24));
            }
            if (warp == 0) PROF(2);
        } else if (s > 0 && warp == 7 && lane == 0) {
            mbar_expect_tx(sb + RB_A, 8192);
        }
        if (s == NSEG - 1) break;
        slot_off = slot_off == (R_NST - 1) * 4096 ? 0 : slot_off + slot_inc;
        const uint4 tc = lds128(tab + 4096), td = lds128(tab + 6144);
        const uint32_t te = lds32(tab + 8192);
        uint32_t* wr = (uint32_t*)(((uint64_t)td.y << 32) | (td.x ^ ((s & 1) * 0x21000)));
        const uint32_t* r1p = (const uint32_t*)((const char*)wr + (int)td.z);
        const uint32_t* r2p = (const uint32_t*)((const char*)wr + (int)td.w);
        const uint32_t* r3p = (const uint32_t*)((const char*)wr + (int)te);
        const uint32_t tag = ((s >> 1) + 1) & 1;
        mbar_wait(sb + RB_E, s & 1);
        if (warp == 0) PROF(7);
        {
            uint32_t a0, a1, a2, a3, a4, a5, a6, a7;
            ldsm4t(a0, a1, a2, a3, tc.x);
            ldsm4t(a4, a5, a6, a7, tc.x ^ 64);
            const uint32_t one = 0x3F803F80u;
            float d0_[4] = {0.f, 0.f, 0.f, 0.f}, d1_[4] = {0.f, 0.f, 0.f, 0.f};
            mma16816(d0_, a0, a1, a2, a3, one, one);
            mma16816(d1_, a4, a5, a6, a7, one, one);
            const bool t1 = tc.w & 1, t2 = tc.w & 2;
            const float x = t2 ? (t1 ? d1_[2] : d1_[0]) : (t1 ? d0_[2] : d0_[0]);
            const uint32_t own = (__float_as_uint(x) & ~1u) | tag;
            stg_relaxed32(wr, own);
            const uint32_t tq = clk32();
            if (warp == 0) PROF(8);
            PROFG(16 + warp);
#pragma unroll
            for (int i = 0; i < NOFF; i++) {
                const uint4 f0 = lds128(tab + 10240 + i * 2048);
                wa[i & 1][i >> 1][0] = f0.x; wa[i & 1][i >> 1][1] = f0.y; wa[i & 1][i >> 1][2] = f0.z; wa[i & 1][i >> 1][3] = f0.w;
            }
            tb = lds128(tab + 2048);
            while ((int)(clk32() - tq) < POLL_GAP) {}
            uint32_t f1, f2, f3;
            int gg = 0;
#pragma unroll 1
            while (true) {
                f1 = ldg_relaxed32(r1p); f2 = ldg_relaxed32(r2p); f3 = ldg_relaxed32(r3p);
                if (__all_sync(~0u, (((f1 ^ tag) | (f2 ^ tag) | (f3 ^ tag)) & 1) == 0)) break;
                if (++gg > 16 * SPIN_LIMIT) { TIMEOUT(3, s); break; }
            }
            if (warp == 0) PROF(9);
            PROFG(32 + warp);
            const float v = (__uint_as_float(own) + __uint_as_float(f2)) + (__uint_as_float(f1) + __uint_as_float(f3));
            const bool b8 = tc.w & 8, b16 = tc.w & 16;
            const float recv = __shfl_xor_sync(~0u, v, 8);
            const uint32_t word = b8 ? pack2(recv, v) : pack2(v, recv);
            const uint32_t oth = __shfl_xor_sync(~0u, word, 16);
            const uint32_t wl = b16 ? oth : word, wh = b16 ? word : oth;
            const uint32_t p0 = __shfl_xor_sync(~0u, wl, 2), p1 = __shfl_xor_sync(~0u, wh, 2);
            const uint4 item = t2 ? make_uint4(p0, p1, wl, wh) : make_uint4(wl, wh, p0, p1);
            st_async_v4(tc.y, item, tc.z);
            st_async_v4(tc.y ^ (8u << 24), item, tc.z ^ (8u << 24));
            if (tc.w == 0 && warp == 7) mbar_expect_tx(sb + RB_E, 8192);
            if (warp == 0) PROF(10);
            PROF(40 + warp);
        }
        bar_sync(NB_D, 384);
    }
}

__device__ __forceinline__ void rec_load_kv(uint32_t sb, int col0, int s, uint32_t slot_off, int t128) {
    const int row = t128 >> 2, c2 = (t128 & 3) * 2;
    const bf16* src = g_kv + ((size_t)(s * 32 + row) * (2 * HD_) + col0 + c2 * 8);
    const uint32_t d0 = sb + R_KX + slot_off + row * 128 + ((c2 ^ (row & 7)) << 4);
    cp_async16(d0, src);
    cp_async16(d0 ^ 16, src + 8);
    cp_async16(d0 + (R_VX - R_KX), src + HD_);
    cp_async16((d0 ^ 16) + (R_VX - R_KX), src + HD_ + 8);
}

__device__ __forceinline__ void rec_vo(const RecParams& p, const uint32_t sb, const int cta, const int warp, int lane) {
    const int w = warp - 8, crank = cta & 15;
    const int col0 = cta * 64;
    uint32_t wo[8][4][4];
    {
        const int t128 = w * 32 + lane;
        const bf16* Wo = p.wo + (size_t)col0 * D_;
        const uint32_t stg = sb + R_STG + 2 * 32768;
#pragma unroll
        for (int half = 0; half < 2; half++) {
#pragma unroll 4
            for (int i = t128; i < 2048; i += 128) {
                const int e = i >> 6, ch = i & 63;
                cp_async16(stg + e * 1024 + ((ch ^ (e & 7)) << 4), Wo + (size_t)(half * 32 + e) * D_ + ch * 8);
            }
            cp_async_commit();
            cp_async_wait<0>();
            bar_sync(NB_W0 + 2, 128);
#pragma unroll
            for (int j = 0; j < 8; j++)
#pragma unroll
                for (int kk = 0; kk < 2; kk++) {
                    const int e = kk * 16 + (lane >> 4) * 8 + (lane & 7);
                    const int ch = (w * 8 + j) * 2 + ((lane >> 3) & 1);
                    ldsm4t(wo[j][half * 2 + kk][0], wo[j][half * 2 + kk][1], wo[j][half * 2 + kk][2], wo[j][half * 2 + kk][3],
                           stg + e * 1024 + ((ch ^ (e & 7)) << 4));
                }
            bar_sync(NB_W0 + 2, 128);
        }
        if (lane == 0) wait_flag(F_KV + 0, 64);
        __syncwarp();
        rec_load_kv(sb, col0, 0, 0, t128); cp_async_commit();
        rec_load_kv(sb, col0, 1, 4096, t128); cp_async_commit();
        cp_async_wait<1>();
    }
    const uint32_t tab = sb + R_STG + 2 * 32768 + (w * 32 + lane) * 16;
    {
        const uint32_t l7 = lane & 7, l8 = lane >> 3, g = lane >> 2;
        uint4 v;
        v.x = sb + R_VX + ((l8 & 1) * 8 + l7) * 128 + (((2 * w + (l8 >> 1)) ^ l7) << 4);
        v.y = sb + R_OS + g * 128 + (((2 * w) ^ g) << 4) + (lane & 3) * 4;
        v.z = sb + R_VMS + l7 * 128 + (((2 * w + (l8 & 1)) ^ l7) << 4);
        v.w = sb + R_OS + l7 * 128 + ((l8 ^ l7) << 4);
        sts128(tab, v);
        v.x = mapa_u32(sb + R_RS + crank * 512 + ((lane ^ (crank & 7)) << 4), w * 4);
        v.y = mapa_u32(sb + RB_E, w * 4);
        v.z = sb + R_VP + w * 512 + lane * 16;
        v.w = sb + R_SX + lane * 8;
        sts128(tab + 2048, v);
#pragma unroll
        for (int i = 0; i < 8; i++) sts128(tab + 4096 + i * 2048, make_uint4(wo[i][0][0], wo[i][0][1], wo[i][0][2], wo[i][0][3]));
    }
    bar_sync(NB_D, 384);
    const uint32_t lane16 = lds32(tab + 2048 + 8) - R_VP - w * 512;
    uint4 av[2 * VK0];
#pragma unroll
    for (int i = 0; i < 2 * VK0; i++) av[i] = lds128(lane16 + R_WV + (i / VK0) * 32768 + (w * 16 + i % VK0) * 512);
    uint32_t slot_off = 0;
#pragma unroll 1
    for (int s = 0; s < NSEG; s++) {
        bar_sync(NB_Y, 288);
        uint32_t vb0, vb1;
        {
            float va[4] = {0.f, 0.f, 0.f, 0.f}, vc[4] = {0.f, 0.f, 0.f, 0.f};
            uint32_t bb[VK0][4];
#pragma unroll
            for (int k2 = 0; k2 < VK0; k2++) ldsm4(bb[k2][0], bb[k2][1], bb[k2][2], bb[k2][3], lane16 + R_MEM + (k2 / (VK0 / 2)) * 4096 + (k2 % (VK0 / 2)) * 512);
#pragma unroll
            for (int k2 = 0; k2 < VK0; k2++) {
                mma16816(va, av[2 * k2].x, av[2 * k2].y, av[2 * k2].z, av[2 * k2].w, bb[k2][0], bb[k2][1]);
                mma16816(vc, av[2 * k2 + 1].x, av[2 * k2 + 1].y, av[2 * k2 + 1].z, av[2 * k2 + 1].w, bb[k2][2], bb[k2][3]);
            }
            const uint4 a = lds128(lane16 + R_VP + w * 512), b = lds128(lane16 + R_VP + 2048 + w * 512);
            vb0 = pack2((va[0] + vc[0]) + (__uint_as_float(a.x) + __uint_as_float(b.x)), (va[1] + vc[1]) + (__uint_as_float(a.y) + __uint_as_float(b.y)));
            vb1 = pack2((va[2] + vc[2]) + (__uint_as_float(a.z) + __uint_as_float(b.z)), (va[3] + vc[3]) + (__uint_as_float(a.w) + __uint_as_float(b.w)));
        }
        const uint4 ta = lds128(tab), tb = lds128(tab + 2048);
        uint32_t vx[8];
        ldsm4t(vx[0], vx[1], vx[2], vx[3], ta.x + slot_off);
        ldsm4t(vx[4], vx[5], vx[6], vx[7], ta.x + slot_off + 2048);
#pragma unroll
        for (int i = 0; i < 4; i++) {
            const uint4 f0 = lds128(tab + 4096 + i * 2048);
            wo[i][0][0] = f0.x; wo[i][0][1] = f0.y; wo[i][0][2] = f0.z; wo[i][0][3] = f0.w;
        }
        if (w == 0) PROF(11);
        uint32_t pf[5];
        float oa[2][4] = {{0.f, 0.f, 0.f, 0.f}, {0.f, 0.f, 0.f, 0.f}}, ob_[2][4] = {{0.f, 0.f, 0.f, 0.f}, {0.f, 0.f, 0.f, 0.f}};
        float sm0[4] = {0.f, 0.f, 0.f, 0.f}, sm1[4] = {0.f, 0.f, 0.f, 0.f};
        if (s != NSEG - 1) {
            mbar_wait(sb + RB_SX, s & 1);
            if (w == 0) PROF(4);
            float sv[10];
#pragma unroll
            for (int n = 0; n < 5; n++) {
                const float2 a = lds64f(tb.w + n * 256), b = lds64f(tb.w + (5 + n) * 256);
                sv[2 * n] = a.x + b.x; sv[2 * n + 1] = a.y + b.y;
            }
            float mx = fmaxf(fmaxf(fmaxf(sv[0], sv[1]), fmaxf(sv[2], sv[3])), fmaxf(fmaxf(sv[4], sv[5]), fmaxf(sv[6], sv[7])));
            mx = fmaxf(mx, fmaxf(sv[8], sv[9]));
            mx = fmaxf(mx, __shfl_xor_sync(~0u, mx, 1));
            mx = fmaxf(mx, __shfl_xor_sync(~0u, mx, 2));
#pragma unroll
            for (int n = 1; n < 5; n++) pf[n] = pack2(ex2(sv[2 * n] - mx), ex2(sv[2 * n + 1] - mx));
            pf[0] = pack2(ex2(sv[0] - mx), ex2(sv[1] - mx));
            if (w == 0) PROF(12);
            const uint32_t one = 0x3F803F80u;
            mma16816h(sm0, pf[1], pf[2], one, one);
            mma16816h(oa[0], pf[1], pf[2], vx[0], vx[1]);
            mma16816h(oa[1], pf[1], pf[2], vx[2], vx[3]);
            mma16816h(sm1, pf[3], pf[4], one, one);
            mma16816h(ob_[0], pf[3], pf[4], vx[4], vx[5]);
            mma16816h(ob_[1], pf[3], pf[4], vx[6], vx[7]);
            mma1688h(sm0, pf[0], one);
            mma1688h(oa[0], pf[0], vb0);
            mma1688h(oa[1], pf[0], vb1);
            float inv;
            asm("rcp.approx.ftz.f32 %0, %1;" : "=f"(inv) : "f"(sm0[0] + sm1[0]));
            oa[0][0] += ob_[0][0]; oa[0][1] += ob_[0][1]; oa[1][0] += ob_[1][0]; oa[1][1] += ob_[1][1];
            sts32(ta.y, pack2(oa[0][0] * inv, oa[0][1] * inv));
            sts32(ta.y ^ 16, pack2(oa[1][0] * inv, oa[1][1] * inv));
            const uint32_t oa2 = ta.w ^ 64;
            bar_sync(NB_C, 128);
            if (w == 0) PROF(5);
            uint32_t ob[8];
            ldsm4(ob[0], ob[1], ob[2], ob[3], ta.w);
            ldsm4(ob[4], ob[5], ob[6], ob[7], oa2);
#pragma unroll
            for (int i = 4; i < 8; i++) {
                const uint4 f0 = lds128(tab + 4096 + i * 2048);
                wo[i][0][0] = f0.x; wo[i][0][1] = f0.y; wo[i][0][2] = f0.z; wo[i][0][3] = f0.w;
            }
#pragma unroll
            for (int jj = 0; jj < 2; jj++) {
                if (jj == 1 && tb.w == 0) break;
                float acc[4][4];
#pragma unroll
                for (int c = 0; c < 4; c++) { acc[c][0] = acc[c][1] = acc[c][2] = acc[c][3] = 0.f; }
#pragma unroll
                for (int ks = 0; ks < 4; ks++)
#pragma unroll
                    for (int c = 0; c < 4; c++)
                        mma16816(acc[c], wo[jj * 4 + c][ks][0], wo[jj * 4 + c][ks][1], wo[jj * 4 + c][ks][2], wo[jj * 4 + c][ks][3], ob[2 * ks], ob[2 * ks + 1]);
#pragma unroll
                for (int pr = 0; pr < 2; pr++) {
                    uint4 v;
                    v.x = pack2(acc[2 * pr][0], acc[2 * pr][1]);
                    v.y = pack2(acc[2 * pr][2], acc[2 * pr][3]);
                    v.z = pack2(acc[2 * pr + 1][0], acc[2 * pr + 1][1]);
                    v.w = pack2(acc[2 * pr + 1][2], acc[2 * pr + 1][3]);
                    st_async_v4(tb.x + ((jj * 2 + pr) << 24), v, tb.y + ((jj * 2 + pr) << 24));
                }
            }
            if (w == 0) PROF(6);
        }
        {
            stsm2t(ta.z, vb0, vb1);
            cp_async_wait<0>();
            bar_sync(NB_C, 128);
            if (w == 0 && lane == 0 && s != NSEG - 1) mbar_expect_tx(sb + RB_SX, 2560);
            const int omat = w >> 1, otok = (w & 1) * 4 + (lane >> 3), och = lane & 7;
            const uint4 v = lds128(sb + (omat ? R_VMS : R_KMS) + otok * 128 + ((och ^ otok) << 4));
            *(uint4*)(g_kvm + ((s * 8 + otok) * (2 * HD_) + omat * HD_ + col0 + och * 8)) = v;
            if (s != NSEG - 1) bar_arrive(NB_D, 384);
#pragma unroll
            for (int i = 0; i < 2 * VK0; i++) av[i] = lds128(lane16 + R_WV + (i / VK0) * 32768 + (w * 16 + i % VK0) * 512);
            if (s + 2 < NSEG - 1) {
                if (((s + 2) & 3) == 0) { if (lane == 0) wait_flag(F_KV + ((s + 2) >> 2), 64); __syncwarp(); }
                rec_load_kv(sb, col0, s + 2, slot_off == 0 ? (R_NST - 1) * 4096 : slot_off - 4096, w * 32 + lane);
            }
            cp_async_commit();
            if ((s & 3) == 3) {
                bar_sync(NB_C, 128);
                if (w == 0 && lane == 0) red_release(&g_flags[(F_MEM + (s >> 2)) * 32], 1);
            }
        }
        slot_off = slot_off == (R_NST - 1) * 4096 ? 0 : slot_off + 4096;
    }
}

__global__ void __launch_bounds__(384, 1) k_rec(const RecParams p) {
    extern __shared__ __align__(1024) unsigned char smem_raw[];
    const uint32_t sb = __shfl_sync(~0u, smem_u32(smem_raw), 0);
    const int warp = __shfl_sync(~0u, threadIdx.x >> 5, 0);
    int lane; asm volatile("mov.u32 %0, %%laneid;" : "=r"(lane));
    const int crank = blockIdx.x & 15, slot = blockIdx.x >> 4;
    asm volatile("griddepcontrol.launch_dependents;");
    if (threadIdx.x == 0) {
        mbar_init(sb + RB_SX, 1); mbar_init(sb + RB_E, 1); mbar_init(sb + RB_A, 1); mbar_init(sb + RB_ROLE, 1);
        asm volatile("fence.mbarrier_init.release.cluster;" ::: "memory");
        mbar_expect_tx(sb + RB_SX, 2560);
        mbar_expect_tx(sb + RB_E, 8192);
        mbar_expect_tx(sb + RB_A, 8192);
        mbar_expect_tx(sb + RB_ROLE, 4);
    }
    unsigned role = 0;
    if (crank == 0 && threadIdx.x == 0) {
        unsigned x = 0;
        int tm[2] = {0x7fffffff, 0x7fffffff};
#pragma unroll 1
        for (int i = 0; i < 6; i++) {
            const uint32_t t0 = clk32();
            x = atomicAdd(&g_F[65536 + (i & 1) * 1024 + slot * 64 + (x >> 31)], 0u) & 0x7fffffffu;
            if (x == 0x7654321u) sts32(sb + R_BAR + 56, x);
            const int dt = (int)(clk32() - t0);
            if (i >= 2) { if (i & 1) tm[1] = min(tm[1], dt); else tm[0] = min(tm[0], dt); }
        }
        const int side = tm[1] > tm[0];
        const unsigned old = atomicAdd(&g_flags[(F_SIDE + side) * 32], 1u);
        unsigned c0, c1; int gd = 0;
#pragma unroll 1
        do { c0 = ldg_relaxed32(&g_flags[F_SIDE * 32]); c1 = ldg_relaxed32(&g_flags[(F_SIDE + 1) * 32]); } while ((int)(c0 + c1) < p.ncl && ++gd < 64 * SPIN_LIMIT);
        const int big = c1 > c0;
        role = side == big ? old : (big ? c1 : c0) + old;
        role |= (big ^ 1) << 8;
    }
    __syncwarp();
    asm volatile("barrier.cluster.arrive.relaxed.aligned;\nbarrier.cluster.wait.aligned;" ::: "memory");
    if (crank == 0 && warp == 0) {
        role = __shfl_sync(~0u, role, 0);
        if (lane < 16)
            asm volatile("st.async.weak.shared::cluster.mbarrier::complete_tx::bytes.u32 [%0], %1, [%2];"
                         :: "r"(mapa_u32(sb + R_BAR + 48, lane)), "r"(role), "r"(mapa_u32(sb + RB_ROLE, lane)) : "memory");
    }
    mbar_wait(sb + RB_ROLE, 0);
    const int rolew = __shfl_sync(~0u, lds32(sb + R_BAR + 48), 0);
    const int cl = rolew & 255;
    if (cl >= 4) return;
    const int cta = cl * 16 + crank;
    if (warp < 8) rec_qk(p, sb, cta, warp, lane, rolew >> 8);
    else rec_vo(p, sb, cta, warp, lane);
}

enum { J_KV = 0, J_QA = 1, J_O = 2, J_LN = 3, J_UP = 4, J_DN = 5, J_UP2 = 6, J_END = 8 };
constexpr int NJ_O = 2 * OSPLIT, NJ_O2 = 2 * OSPLIT2, NJ_LN = 8, NJ_LN2 = 16, NJ_UP = 14, NJ_UP2 = 28, NJ_DN = 8;
__device__ __forceinline__ int nj_coarse(int q) { return q == J_KV ? 32 : (q == J_QA ? 16 : (q == J_O ? NJ_O : (q == J_LN ? NJ_LN : (q == J_UP ? NJ_UP : NJ_DN)))); }
__device__ __forceinline__ int nj_fine(int q) { return q == J_KV ? 32 : (q == J_QA ? 16 : (q == J_O ? NJ_O2 : (q == J_LN ? NJ_LN2 : (q == J_UP ? NJ_UP2 : NJ_DN)))); }
__device__ __forceinline__ int pick_job(int lane, int qmask, int& idx) {
    const int q = lane < 6 ? lane : 0;
    const int nc = nj_coarse(q), nf = nj_fine(q), total = FINE_RB * nc + (NRB - FINE_RB) * nf;
    int gd = 0;
#pragma unroll 1
    while (true) {
        const int h = (int)ldg_relaxed32(&g_flags[(F_HEAD + q) * 32]);
        const bool have = lane < 6 && ((qmask >> q) & 1) && h < total;
        const int rb = h < FINE_RB * nc ? h / nc : FINE_RB + (h - FINE_RB * nc) / nf;
        const int cb = h < FINE_RB * nc ? h - rb * nc : h - FINE_RB * nc - (rb - FINE_RB) * nf;
        const bool fine = rb >= FINE_RB;
        bool ready = have;
        if (have && q != J_KV && !(q == J_QA && rb == 0)) {
            const int f = q == J_QA ? F_MEM + rb - 1 : (q == J_O ? F_O + rb : (q == J_LN ? F_OP + rb : (q == J_UP ? F_H2 + rb : F_ACT + rb)));
            const unsigned tgt = q == J_QA ? 64 : 2 * (fine ? nj_fine(q - 1) : nj_coarse(q - 1));
            ready = ldg_relaxed32(&g_flags[f * 32]) >= tgt;
        }
        const unsigned mh = __ballot_sync(~0u, have), mr = __ballot_sync(~0u, ready), mf = __ballot_sync(~0u, have && fine && q >= J_O);
        if (mh == 0) return J_END;
        int pick = -1;
        if (mr) pick = (mr & 1) ? 0 : 31 - __clz(mr);
        else if (mf) pick = __ffs(mf) - 1;
        if (pick >= 0) {
            int ok = 0;
            if (lane == pick) ok = atomicCAS(&g_flags[(F_HEAD + q) * 32], (unsigned)h, (unsigned)h + 1) == (unsigned)h;
            if (__shfl_sync(~0u, ok, pick)) {
                idx = __shfl_sync(~0u, q * 600 + h, pick);
                return __shfl_sync(~0u, (q == J_UP && fine ? J_UP2 : q) | (rb << 8) | (cb << 16), pick);
            }
        } else {
            __nanosleep(200);
            if (++gd > 16 * SPIN_LIMIT) { TIMEOUT(5, 0); return J_END; }
        }
    }
}
__device__ __forceinline__ int op_row(int rb, int split) {
    return rb < FINE_RB ? split * S_ + rb * 128 : OSPLIT * S_ + (split * (NRB - FINE_RB) + rb - FINE_RB) * 128;
}

struct Pipe { uint32_t stage, phase; };
__device__ __forceinline__ void pipe_next(Pipe& p) { if (++p.stage == W_NST) { p.stage = 0; p.phase ^= 1; } }

__device__ __forceinline__ void producer(const Params& p, uint32_t sb, int lane) {
    Pipe pp{0, 1};
    const uint32_t bars = sb + SM_BAR;
    uint32_t seq = 0;
#pragma unroll 1
    while (true) {
        __syncwarp();
        int j = 4095;
        const int jd = pick_job(lane, p.qmask, j);
        if (lane != 0) { if (jd == J_END) break; continue; }
        TR(j, 1);
        const int type = jd & 255, rb = (jd >> 8) & 255, cb = jd >> 16;
        const bool fine = rb >= FINE_RB;
        bool first = true;
        auto begin_stage = [&](uint32_t bytes) -> uint32_t {
            mbar_wait(bars + B_EMPTY + pp.stage * 8, pp.phase);
            if (first) { sts32(bars + B_RING + (seq & 7) * 4, (uint32_t)jd); sts32(bars + B_RING + 32 + (seq & 7) * 4, (uint32_t)j); first = false; }
            const uint32_t fb = bars + B_FULL + pp.stage * 8;
            if (bytes) mbar_expect_tx(fb, bytes); else mbar_arrive(fb);
            return fb;
        };
        if (type == J_END || type == J_LN) {
            if (type == J_LN) wait_flag(F_OP + rb, 2 * (fine ? NJ_O2 : NJ_O));
            TR(j, 2);
            begin_stage(0); pipe_next(pp);
            seq++;
            if (type == J_END) break;
            continue;
        }
        const CUtensorMap *ta, *tb0, *tb1;
        int k0 = 0, nk = 8, n0 = cb * 256, n1 = n0 + 128, nb = 4, dep = -1;
        unsigned tgt = 0;
        switch (type) {
            case J_KV: ta = &p.tm_h; tb0 = tb1 = cb < 16 ? &p.tm_wk : &p.tm_wv; n0 = (cb & 15) * 256; n1 = n0 + 128; break;
            case J_QA: ta = &p.tm_h; tb0 = tb1 = &p.tm_wq; break;
            case J_O: ta = &p.tm_o; tb0 = tb1 = &p.tm_wo; n0 = (cb & 1) * 256; n1 = n0 + 128; nk = fine ? 64 / OSPLIT2 : 64 / OSPLIT; k0 = (cb >> 1) * nk * 64;
                      dep = F_O + rb; tgt = 32; break;
            case J_UP: ta = &p.tm_h2; tb0 = &p.tm_wg; tb1 = &p.tm_wu; n0 = n1 = cb * 128; dep = F_H2 + rb; tgt = 2 * NJ_LN; break;
            case J_UP2: ta = &p.tm_h2; tb0 = &p.tm_wg; tb1 = &p.tm_wu; n0 = n1 = cb * 64; nb = 2; dep = F_H2 + rb; tgt = 2 * NJ_LN2; break;
            default: ta = &p.tm_act; tb0 = tb1 = &p.tm_wd; n0 = cb * 64; nk = 0; break;
        }
        const int m0 = rb * 128;
        if (type == J_DN) {
#pragma unroll 1
            for (int kb = 0; kb < 14; kb++) {
                const uint32_t fb = begin_stage(49152);
                const uint32_t st = sb + pp.stage * W_STAGE;
                const int k = kb * 128;
                tma_load2d(st + 32768, tb0, n0, k, fb);
                tma_load2d(st + 40960, tb0, n0, k + 64, fb);
                if (kb == 0) { wait_flag(F_ACT + rb, 2 * (fine ? NJ_UP2 : NJ_UP)); fence_async_all(); TR(j, 2); }
                tma_load2d(st, ta, k, m0, fb);
                tma_load2d(st + 8192, ta, k, m0 + 64, fb);
                tma_load2d(st + 16384, ta, k + 64, m0, fb);
                tma_load2d(st + 24576, ta, k + 64, m0 + 64, fb);
                pipe_next(pp);
            }
        }
#pragma unroll 1
        for (int kb = 0; kb < nk; kb++) {
            const uint32_t fb = begin_stage(16384 + nb * 8192);
            const uint32_t st = sb + pp.stage * W_STAGE;
            const int k = k0 + kb * 64;
            tma_load2d(st + 16384, tb0, n0, k, fb);
            if (nb == 4) {
                tma_load2d(st + 16384 + 8192, tb0, n0 + 64, k, fb);
                tma_load2d(st + 16384 + 16384, tb1, n1, k, fb);
                tma_load2d(st + 16384 + 24576, tb1, n1 + 64, k, fb);
            } else if (nb == 2) {
                tma_load2d(st + 16384 + 8192, tb1, n1, k, fb);
            }
            if (kb == 0) {
                if (dep >= 0) { wait_flag(dep, tgt); if (type >= J_UP) fence_async_all(); }
                TR(j, 2);
            }
            tma_load2d(st, ta, k, m0, fb);
            tma_load2d(st + 8192, ta, k, m0 + 64, fb);
            pipe_next(pp);
        }
        if (type == J_QA) {
            wait_flag(F_KV + rb, 64);
#pragma unroll 1
            for (int i = 0; i < 4; i++) {
                const uint32_t fb = begin_stage(40960);
                const uint32_t st = sb + pp.stage * W_STAGE;
                const int col = (i & 1) * HD_ + (cb * 2 + (i >> 1)) * DH_;
                tma_load2d(st, &p.tm_kv, col, m0, fb);
                tma_load2d(st + 8192, &p.tm_kv, col, m0 + 64, fb);
                tma_load2d(st + 16384, &p.tm_kv, col + 64, m0, fb);
                tma_load2d(st + 24576, &p.tm_kv, col + 64, m0 + 64, fb);
                if (i == 0) { wait_flag(F_MEM + rb, 64); fence_async_all(); }
                tma_load2d(st + 32768, &p.tm_kvm, col, rb * 32, fb);
                tma_load2d(st + 36864, &p.tm_kvm, col + 64, rb * 32, fb);
                pipe_next(pp);
            }
        } else if (type == J_DN) {
            const uint32_t fb = begin_stage(16384);
            const uint32_t st = sb + pp.stage * W_STAGE;
            tma_load2d(st, &p.tm_x1, n0, m0, fb);
            tma_load2d(st + 8192, &p.tm_x1, n0, m0 + 64, fb);
            pipe_next(pp);
        }
        seq++;
    }
}

__device__ __forceinline__ void store_warp(const Params& p, uint32_t sb, int wg, int lane) {
    const uint32_t bars = sb + SM_BAR;
    uint32_t seq = 0;
#pragma unroll 1
    while (true) {
        bar_sync(NB_ST + wg, 160);
        const uint32_t jd = lds32(bars + B_RING + (seq & 7) * 4);
        seq++;
        const int type = jd & 255, rb = (jd >> 8) & 255, cb = jd >> 16;
        if (type == J_END) break;
        if (lane == 0) {
            const uint32_t src = sb + W_STG + wg * 32768;
            const CUtensorMap* tm = nullptr; int n0 = cb * 256, nbox = 4, mrow = rb * 128 + wg * 64, flag = 0;
            switch (type) {
                case J_KV: tm = &p.tm_kv; flag = F_KV + rb; break;
                case J_QA: tm = &p.tm_o; flag = F_O + rb; break;
                case J_O: tm = &p.tm_op; n0 = (cb & 1) * 256; mrow = op_row(rb, cb >> 1) + wg * 64; flag = F_OP + rb; break;
                case J_LN: flag = F_H2 + rb; nbox = 0; break;
                case J_UP: tm = &p.tm_act; n0 = cb * 128; nbox = 2; flag = F_ACT + rb; break;
                case J_UP2: tm = &p.tm_act; n0 = cb * 64; nbox = 1; flag = F_ACT + rb; break;
                default: tm = &p.tm_out; n0 = cb * 64; nbox = 1; flag = -1; break;
            }
#pragma unroll 1
            for (int b = 0; b < nbox; b++) tma_store2d(tm, src + b * 8192, n0 + b * 64, mrow);
            bulk_commit();
            bulk_wait0();
            mbar_arrive(bars + B_STGFREE + wg * 8);
            if (flag >= 0) red_release(&g_flags[flag * 32], 1);
        }
        __syncwarp();
    }
}

__device__ __forceinline__ float gelu_tanh(float x) {
    const float t = x * fmaf(-0.10294324397f, x * x, -2.30220819814f);
    float r; asm("rcp.approx.ftz.f32 %0, %1;" : "=f"(r) : "f"(1.f + ex2(t)));
    return x * r;
}

#define CTR(i) do {} while (0)

template <int NSPLIT>
__device__ __forceinline__ void ln2_row(const Params& p, int rb, int r, int lane) {
    const int row = rb * 128 + r;
    uint4 u[2 * NSPLIT];
#pragma unroll
    for (int sp = 0; sp < NSPLIT; sp++) {
        const uint4* src = (const uint4*)(g_op + (size_t)(op_row(rb, sp) + r) * D_);
        u[2 * sp] = __ldcg(src + lane); u[2 * sp + 1] = __ldcg(src + 32 + lane);
    }
    const uint4* xr = (const uint4*)(p.x + (size_t)row * D_);
    const uint4 xa = __ldg(xr + lane), xb = __ldg(xr + 32 + lane);
    uint32_t ga[8], c1[8], sm[8];
    load_mod8(g_mod + 2 * D_, lane, ga);
    load_mod8(g_mod + 4 * D_, lane, c1);
    load_mod8(g_mod + 3 * D_, lane, sm);
    float a[16];
#pragma unroll
    for (int i = 0; i < 16; i++) a[i] = 0.f;
#pragma unroll
    for (int sp = 0; sp < 2 * NSPLIT; sp++) {
        float* q = a + (sp & 1) * 8;
        q[0] += bflo(u[sp].x); q[1] += bfhi(u[sp].x); q[2] += bflo(u[sp].y); q[3] += bfhi(u[sp].y);
        q[4] += bflo(u[sp].z); q[5] += bfhi(u[sp].z); q[6] += bflo(u[sp].w); q[7] += bfhi(u[sp].w);
    }
    const uint32_t xv[8] = {xa.x, xa.y, xa.z, xa.w, xb.x, xb.y, xb.z, xb.w};
    uint32_t v[8], r8[8];
#pragma unroll
    for (int i = 0; i < 8; i++) v[i] = hadd2(xv[i], hmul2(ga[i], pack2(a[2 * i], a[2 * i + 1])));
    uint4* x1r = (uint4*)(g_x1 + (size_t)row * D_);
    x1r[lane] = make_uint4(v[0], v[1], v[2], v[3]); x1r[32 + lane] = make_uint4(v[4], v[5], v[6], v[7]);
    uint32_t mu2; float rden;
    ln_stats(v, mu2, rden);
#pragma unroll
    for (int i = 0; i < 8; i++) c1[i] = hadd2(c1[i], 0x3F803F80u);
    ln_apply(v, mu2, rden, c1, sm, r8);
    uint4* hr = (uint4*)(g_h2 + (size_t)row * D_);
    hr[lane] = make_uint4(r8[0], r8[1], r8[2], r8[3]); hr[32 + lane] = make_uint4(r8[4], r8[5], r8[6], r8[7]);
}

__device__ __forceinline__ void consumer(const Params& p, uint32_t sb, int warp, int lane) {
    const uint32_t bars = sb + SM_BAR;
    const int wg = warp >> 2, wl = warp & 3;
    const uint32_t l7 = lane & 7, l8 = lane >> 3, g = lane >> 2, t = lane & 3;
    Pipe pp{0, 0};
    uint32_t seq = 0, stg_phase = 1;
    const int srow = wl * 16 + l7 + (l8 & 1) * 8;
    const uint32_t stg_base = sb + W_STG + wg * 32768 + srow * 128;
    const uint32_t sx = ((lane >> 4) ^ (srow & 7)) << 4;
#pragma unroll 1
    while (true) {
        mbar_wait(bars + B_FULL + pp.stage * 8, pp.phase);
        const uint32_t jd = lds32(bars + B_RING + (seq & 7) * 4);
        CTR(3);
        seq++;
        const int type = jd & 255, rb = (jd >> 8) & 255, cb = jd >> 16;
        if (type == J_END) { mbar_wait(bars + B_STGFREE + wg * 8, stg_phase); bar_arrive(NB_ST + wg, 160); break; }
        if (type == J_LN) {
            __syncwarp();
            if (lane == 0) mbar_arrive(bars + B_EMPTY + pp.stage * 8);
            pipe_next(pp);
            if (rb >= FINE_RB) ln2_row<OSPLIT2>(p, rb, cb * 8 + warp, lane);
            else {
#pragma unroll 1
                for (int rr = 0; rr < 2; rr++) ln2_row<OSPLIT>(p, rb, cb * 16 + warp * 2 + rr, lane);
            }
            mbar_wait(bars + B_STGFREE + wg * 8, stg_phase); stg_phase ^= 1;
            CTR(4); CTR(5);
            bar_arrive(NB_ST + wg, 160);
            continue;
        }
        if (type >= J_DN) {
            float acc[64];
#pragma unroll
            for (int i = 0; i < 64; i++) acc[i] = 0.f;
            if (type == J_DN) {
#pragma unroll 1
                for (int kb = 0; kb < 14; kb++) {
                    if (kb) mbar_wait(bars + B_FULL + pp.stage * 8, pp.phase);
                    const uint32_t st = sb + pp.stage * W_STAGE;
                    const uint64_t da = mkdesc(st + wg * 8192, 16, 1024), db = mkdesc(st + 32768, 8192, 1024);
                    wg_fence();
#pragma unroll
                    for (int ks = 0; ks < 8; ks++) wgmma_n64(acc, da + (ks >> 2) * 1024 + (ks & 3) * 2, db + ks * 128);
                    wg_commit();
                    wg_wait0();
                    if (lane == 0) mbar_arrive(bars + B_EMPTY + pp.stage * 8);
                    pipe_next(pp);
                }
            } else {
#pragma unroll 1
                for (int kb = 0; kb < 8; kb++) {
                    if (kb) mbar_wait(bars + B_FULL + pp.stage * 8, pp.phase);
                    const uint32_t st = sb + pp.stage * W_STAGE;
                    const uint64_t da = mkdesc(st + wg * 8192, 16, 1024), db = mkdesc(st + 16384, 8192, 1024);
                    wg_fence();
#pragma unroll
                    for (int ks = 0; ks < 4; ks++) wgmma_n128(acc, da + ks * 2, db + ks * 128, 1);
                    wg_commit();
                    wg_wait0();
                    if (lane == 0) mbar_arrive(bars + B_EMPTY + pp.stage * 8);
                    pipe_next(pp);
                }
            }
            CTR(4);
            if (type == J_UP2) {
                mbar_wait(bars + B_STGFREE + wg * 8, stg_phase); stg_phase ^= 1;
#pragma unroll
                for (int j = 0; j < 4; j++) {
                    uint32_t r[4];
#pragma unroll
                    for (int q = 0; q < 4; q++) {
                        const uint32_t gw = pack2(acc[8 * j + 2 * q], acc[8 * j + 2 * q + 1]);
                        const uint32_t uw = pack2(acc[32 + 8 * j + 2 * q], acc[32 + 8 * j + 2 * q + 1]);
                        r[q] = hmul2(pack2(gelu_tanh(bflo(gw)), gelu_tanh(bfhi(gw))), uw);
                    }
                    stsm4(stg_base + (sx ^ (j << 5)), r[0], r[1], r[2], r[3]);
                }
            } else {
                mbar_wait(bars + B_FULL + pp.stage * 8, pp.phase);
                const uint32_t st = sb + pp.stage * W_STAGE;
                mbar_wait(bars + B_STGFREE + wg * 8, stg_phase); stg_phase ^= 1;
                const uint32_t* gb = (const uint32_t*)(g_mod + 5 * D_ + cb * 64) + t;
                const uint32_t xa = st + wg * 8192 + (wl * 16 + g) * 128 + (g << 4) + t * 4;
#pragma unroll
                for (int j = 0; j < 4; j++) {
                    uint32_t r[4];
#pragma unroll
                    for (int q = 0; q < 4; q++) {
                        const int nt = 2 * j + (q >> 1);
                        const uint32_t xw = lds32((xa ^ ((nt & 7) << 4)) + (nt >> 3) * 16384 + (q & 1) * 1024);
                        r[q] = hadd2(xw, hmul2(__ldcg(gb + nt * 4), pack2(acc[8 * j + 2 * q], acc[8 * j + 2 * q + 1])));
                    }
                    stsm4(stg_base + (j >> 2) * 8192 + (sx ^ ((2 * j & 7) << 4)), r[0], r[1], r[2], r[3]);
                }
                __syncwarp();
                if (lane == 0) mbar_arrive(bars + B_EMPTY + pp.stage * 8);
                pipe_next(pp);
            }
            fence_async_smem();
            CTR(5);
            bar_arrive(NB_ST + wg, 160);
            continue;
        }
        float acc[128];
#pragma unroll
        for (int i = 0; i < 128; i++) acc[i] = 0.f;
        const int nk = type == J_O ? (rb >= FINE_RB ? 64 / OSPLIT2 : 64 / OSPLIT) : 8;
#pragma unroll 1
        for (int kb = 0; kb < nk; kb++) {
            if (kb) mbar_wait(bars + B_FULL + pp.stage * 8, pp.phase);
            const uint32_t st = sb + pp.stage * W_STAGE;
            const uint64_t da = mkdesc(st + wg * 8192, 16, 1024), db = mkdesc(st + 16384, 8192, 1024);
            wg_fence();
#pragma unroll
            for (int ks = 0; ks < 4; ks++) wgmma_n256(acc, da + ks * 2, db + ks * 128, 1);
            wg_commit();
            wg_wait0();
            if (lane == 0) mbar_arrive(bars + B_EMPTY + pp.stage * 8);
            pipe_next(pp);
        }
        CTR(4);
        if (type == J_QA) {
            uint32_t qf[64];
#pragma unroll
            for (int i = 0; i < 64; i++) qf[i] = pack2(acc[2 * i], acc[2 * i + 1]);
            const int sg = warp >> 1, half = warp & 1;
            const float sc = 0.08838834764831845f * 1.4426950408889634f;
            const uint32_t xoff = (sg >> 1) * 8192 + ((sg & 1) * 32 + l7) * 128;
            const uint32_t moff = 32768 + (sg * 8 + l7) * 128;
            const uint32_t kch = (l8 ^ l7) << 4;
            const uint32_t vch = ((l8 & 1) ^ l7) << 4;
            mbar_wait(bars + B_STGFREE + wg * 8, stg_phase); stg_phase ^= 1;
#pragma unroll
            for (int hh = 0; hh < 2; hh++) {
                mbar_wait(bars + B_FULL + pp.stage * 8, pp.phase);
                uint32_t st = sb + pp.stage * W_STAGE;
                float sa[5][4];
#pragma unroll
                for (int n = 0; n < 5; n++) sa[n][0] = sa[n][1] = sa[n][2] = sa[n][3] = 0.f;
#pragma unroll
                for (int i = 0; i < 4; i++) {
                    const uint32_t* q = qf + hh * 32 + i * 8;
                    uint32_t kk[5][4];
                    ldsm4(kk[0][0], kk[0][1], kk[0][2], kk[0][3], st + moff + (i >> 1) * 4096 + (kch ^ ((i & 1) * 64)));
#pragma unroll
                    for (int n = 1; n < 5; n++)
                        ldsm4(kk[n][0], kk[n][1], kk[n][2], kk[n][3], st + xoff + (n - 1) * 1024 + (i >> 1) * 16384 + (kch ^ ((i & 1) * 64)));
#pragma unroll
                    for (int n = 0; n < 5; n++) mma16816(sa[n], q[0], q[1], q[2], q[3], kk[n][0], kk[n][1]);
#pragma unroll
                    for (int n = 0; n < 5; n++) mma16816(sa[n], q[4], q[5], q[6], q[7], kk[n][2], kk[n][3]);
                }
                __syncwarp();
                if (lane == 0) mbar_arrive(bars + B_EMPTY + pp.stage * 8);
                pipe_next(pp);
                const int iq0 = half * 16 + g - 2 * t, iq1 = iq0 + 8;
                float m0 = fmaxf(sa[0][0], sa[0][1]), m1 = fmaxf(sa[0][2], sa[0][3]);
#pragma unroll
                for (int n = 1; n < 5; n++) {
#pragma unroll
                    for (int e = 0; e < 2; e++) {
                        const int jx = (n - 1) * 8 + e;
                        if (jx > iq0) sa[n][e] = -3.0e38f;
                        if (jx > iq1) sa[n][2 + e] = -3.0e38f;
                        m0 = fmaxf(m0, sa[n][e]); m1 = fmaxf(m1, sa[n][2 + e]);
                    }
                }
                m0 = fmaxf(m0, __shfl_xor_sync(~0u, m0, 1)); m1 = fmaxf(m1, __shfl_xor_sync(~0u, m1, 1));
                m0 = fmaxf(m0, __shfl_xor_sync(~0u, m0, 2)); m1 = fmaxf(m1, __shfl_xor_sync(~0u, m1, 2));
                m0 *= -sc; m1 *= -sc;
                float l0 = 0.f, l1 = 0.f;
                uint32_t p0[5], p1[5];
#pragma unroll
                for (int n = 0; n < 5; n++) {
                    const float e0 = ex2(fmaf(sa[n][0], sc, m0)), e1 = ex2(fmaf(sa[n][1], sc, m0));
                    const float e2 = ex2(fmaf(sa[n][2], sc, m1)), e3 = ex2(fmaf(sa[n][3], sc, m1));
                    l0 += e0 + e1; l1 += e2 + e3;
                    p0[n] = pack2(e0, e1); p1[n] = pack2(e2, e3);
                }
                l0 += __shfl_xor_sync(~0u, l0, 1); l1 += __shfl_xor_sync(~0u, l1, 1);
                l0 += __shfl_xor_sync(~0u, l0, 2); l1 += __shfl_xor_sync(~0u, l1, 2);
                const float i0 = __fdividef(1.f, l0), i1 = __fdividef(1.f, l1);
                mbar_wait(bars + B_FULL + pp.stage * 8, pp.phase);
                st = sb + pp.stage * W_STAGE;
#pragma unroll
                for (int bx = 0; bx < 2; bx++) {
                    float o[8][4];
                    uint32_t vm[8], v0[4][4], v1[4][4];
#pragma unroll
                    for (int ep = 0; ep < 4; ep++) {
                        ldsm2t(vm[2 * ep], vm[2 * ep + 1], st + moff + bx * 4096 + (vch ^ (ep << 5)));
                        const uint32_t va = st + xoff + (l8 >> 1) * 1024 + bx * 16384 + (vch ^ (ep << 5));
                        ldsm4t(v0[ep][0], v0[ep][1], v0[ep][2], v0[ep][3], va);
                        ldsm4t(v1[ep][0], v1[ep][1], v1[ep][2], v1[ep][3], va + 2048);
                    }
#pragma unroll
                    for (int n = 0; n < 8; n++) { o[n][0] = o[n][1] = o[n][2] = o[n][3] = 0.f; mma16816(o[n], p0[0], p1[0], p0[1], p1[1], vm[n], v0[n >> 1][n & 1]); }
#pragma unroll
                    for (int n = 0; n < 8; n++) mma16816(o[n], p0[2], p1[2], p0[3], p1[3], v0[n >> 1][2 + (n & 1)], v1[n >> 1][n & 1]);
#pragma unroll
                    for (int n = 0; n < 8; n++) mma1688(o[n], p0[4], p1[4], v1[n >> 1][2 + (n & 1)]);
#pragma unroll
                    for (int ep = 0; ep < 4; ep++)
                        stsm4(stg_base + (hh * 2 + bx) * 8192 + (sx ^ (ep << 5)),
                              pack2(o[2 * ep][0] * i0, o[2 * ep][1] * i0), pack2(o[2 * ep][2] * i1, o[2 * ep][3] * i1),
                              pack2(o[2 * ep + 1][0] * i0, o[2 * ep + 1][1] * i0), pack2(o[2 * ep + 1][2] * i1, o[2 * ep + 1][3] * i1));
                }
                __syncwarp();
                if (lane == 0) mbar_arrive(bars + B_EMPTY + pp.stage * 8);
                pipe_next(pp);
            }
        } else if (type == J_UP) {
            mbar_wait(bars + B_STGFREE + wg * 8, stg_phase); stg_phase ^= 1;
#pragma unroll
            for (int j = 0; j < 8; j++) {
                uint32_t r[4];
#pragma unroll
                for (int q = 0; q < 4; q++) {
                    const uint32_t gw = pack2(acc[8 * j + 2 * q], acc[8 * j + 2 * q + 1]);
                    const uint32_t uw = pack2(acc[64 + 8 * j + 2 * q], acc[64 + 8 * j + 2 * q + 1]);
                    r[q] = hmul2(pack2(gelu_tanh(bflo(gw)), gelu_tanh(bfhi(gw))), uw);
                }
                stsm4(stg_base + (j >> 2) * 8192 + (sx ^ ((2 * j & 7) << 4)), r[0], r[1], r[2], r[3]);
            }
        } else {
            mbar_wait(bars + B_STGFREE + wg * 8, stg_phase); stg_phase ^= 1;
#pragma unroll
            for (int j = 0; j < 16; j++)
                stsm4(stg_base + (j >> 2) * 8192 + (sx ^ ((2 * j & 7) << 4)),
                      pack2(acc[8 * j], acc[8 * j + 1]), pack2(acc[8 * j + 2], acc[8 * j + 3]),
                      pack2(acc[8 * j + 4], acc[8 * j + 5]), pack2(acc[8 * j + 6], acc[8 * j + 7]));
        }
        fence_async_smem();
        CTR(5);
        bar_arrive(NB_ST + wg, 160);
    }
}

__global__ void __launch_bounds__(384, 1) k_work(const __grid_constant__ Params p) {
    extern __shared__ __align__(1024) unsigned char smem_raw[];
    const uint32_t sb = smem_u32(smem_raw);
    if (sb & 1023) __trap();
    const int warp = __shfl_sync(~0u, threadIdx.x >> 5, 0);
    int lane; asm volatile("mov.u32 %0, %%laneid;" : "=r"(lane));
    if (threadIdx.x == 0) {
        const uint32_t bars = sb + SM_BAR;
        for (int i = 0; i < W_NST; i++) { mbar_init(bars + B_FULL + i * 8, 1); mbar_init(bars + B_EMPTY + i * 8, 8); }
        mbar_init(bars + B_STGFREE, 1); mbar_init(bars + B_STGFREE + 8, 1);
        asm volatile("fence.mbarrier_init.release.cluster;" ::: "memory");
    }
    __syncthreads();
    if (warp < 8) {
        asm volatile("setmaxnreg.inc.sync.aligned.u32 232;");
        consumer(p, sb, warp, lane);
    } else {
        asm volatile("setmaxnreg.dec.sync.aligned.u32 40;");
        if (warp == 8) producer(p, sb, lane);
        else if (warp < 11) store_warp(p, sb, warp - 9, lane);
    }
}

typedef CUresult (*EncodeFn)(CUtensorMap*, CUtensorMapDataType, cuuint32_t, void*, const cuuint64_t*, const cuuint64_t*,
                             const cuuint32_t*, const cuuint32_t*, CUtensorMapInterleave, CUtensorMapSwizzle,
                             CUtensorMapL2promotion, CUtensorMapFloatOOBfill);

static void make_map(EncodeFn enc, CUtensorMap* m, const void* ptr, uint64_t rows, uint64_t cols, uint32_t box_rows) {
    cuuint64_t dims[2] = {cols, rows};
    cuuint64_t strides[1] = {cols * 2};
    cuuint32_t box[2] = {64, box_rows};
    cuuint32_t es[2] = {1, 1};
    enc(m, CU_TENSOR_MAP_DATA_TYPE_BFLOAT16, 2, const_cast<void*>(ptr), dims, strides, box, es, CU_TENSOR_MAP_INTERLEAVE_NONE,
        CU_TENSOR_MAP_SWIZZLE_128B, CU_TENSOR_MAP_L2_PROMOTION_L2_256B, CU_TENSOR_MAP_FLOAT_OOB_FILL_NONE);
}
template <typename T> static void* sym_addr(T& sym) { void* p = nullptr; cudaGetSymbolAddress(&p, sym); return p; }

extern "C" void kernel_launch(void* const* d_in, const int* in_sizes, int n_in, void* d_out, int out_size) {
    static Params prm;
    static RecParams rp;
    static bool ready = false;
    static const void* key[14];
    bool same = ready;
    for (int i = 0; i < 13 && same; i++) same = key[i] == d_in[i];
    same = same && key[13] == d_out;
    if (!same) {
        void* fn = nullptr;
        cudaDriverEntryPointQueryResult qr;
        cudaGetDriverEntryPoint("cuTensorMapEncodeTiled", &fn, cudaEnableDefault, &qr);
        EncodeFn enc = (EncodeFn)fn;
        make_map(enc, &prm.tm_h, sym_addr(g_h), S_, D_, 64);
        make_map(enc, &prm.tm_kv, sym_addr(g_kv), S_, 2 * HD_, 64);
        make_map(enc, &prm.tm_kvm, sym_addr(g_kvm), NSEG * 8, 2 * HD_, 32);
        make_map(enc, &prm.tm_o, sym_addr(g_o), S_, HD_, 64);
        make_map(enc, &prm.tm_op, sym_addr(g_op), OP_ROWS, D_, 64);
        make_map(enc, &prm.tm_h2, sym_addr(g_h2), S_, D_, 64);
        make_map(enc, &prm.tm_act, sym_addr(g_act), S_, DF_, 64);
        make_map(enc, &prm.tm_x1, sym_addr(g_x1), S_, D_, 64);
        make_map(enc, &prm.tm_out, d_out, S_, D_, 64);
        make_map(enc, &prm.tm_wq, d_in[2], D_, HD_, 64);
        make_map(enc, &prm.tm_wk, d_in[3], D_, HD_, 64);
        make_map(enc, &prm.tm_wv, d_in[4], D_, HD_, 64);
        make_map(enc, &prm.tm_wo, d_in[5], HD_, D_, 64);
        make_map(enc, &prm.tm_wg, d_in[8], D_, DF_, 64);
        make_map(enc, &prm.tm_wu, d_in[9], D_, DF_, 64);
        make_map(enc, &prm.tm_wd, d_in[10], DF_, D_, 64);
        prm.x = (const bf16*)d_in[0];
        rp.mem0 = (const bf16*)d_in[1];
        rp.wq = (const bf16*)d_in[2]; rp.wk = (const bf16*)d_in[3]; rp.wv = (const bf16*)d_in[4]; rp.wo = (const bf16*)d_in[5];
        cudaFuncSetAttribute(k_work, cudaFuncAttributeMaxDynamicSharedMemorySize, SMEM_BYTES);
        cudaFuncSetAttribute(k_rec, cudaFuncAttributeMaxDynamicSharedMemorySize, R_SMEM);
        cudaFuncSetAttribute(k_rec, cudaFuncAttributeNonPortableClusterSizeAllowed, 1);
        {
            cudaLaunchConfig_t cfg = {};
            cfg.gridDim = dim3(128); cfg.blockDim = dim3(384); cfg.dynamicSmemBytes = R_SMEM;
            cudaLaunchAttribute at[1];
            at[0].id = cudaLaunchAttributeClusterDimension; at[0].val.clusterDim.x = 16; at[0].val.clusterDim.y = 1; at[0].val.clusterDim.z = 1;
            cfg.attrs = at; cfg.numAttrs = 1;
            int n = 0;
            cudaOccupancyMaxActiveClusters(&n, k_rec, &cfg);
            rp.ncl = n < 4 ? 4 : (n > 8 ? 8 : n);
        }
        for (int i = 0; i < 13; i++) key[i] = d_in[i];
        key[13] = d_out;
        ready = true;
    }
    cudaStream_t st = cudaStreamPerThread;
    PrefetchList pf;
    pf.p[0] = (const bf16*)d_in[3]; pf.p[1] = (const bf16*)d_in[4]; pf.p[2] = (const bf16*)d_in[2]; pf.p[3] = (const bf16*)d_in[5]; pf.p[4] = nullptr;
    k_mod<<<96, 256, 0, st>>>((const bf16*)d_in[11], (const bf16*)d_in[12], pf);
    {
        cudaLaunchConfig_t cfg = {};
        cfg.gridDim = dim3(S_ / 8); cfg.blockDim = dim3(256); cfg.stream = st;
        cudaLaunchAttribute at[1];
        at[0].id = cudaLaunchAttributeProgrammaticStreamSerialization; at[0].val.programmaticStreamSerializationAllowed = 1;
        cfg.attrs = at; cfg.numAttrs = 1;
        cudaLaunchKernelEx(&cfg, k_ln1, (const bf16*)d_in[0]);
    }
    auto launch_rec = [&]() {
        cudaLaunchConfig_t cfg = {};
        cfg.gridDim = dim3(16 * rp.ncl); cfg.blockDim = dim3(384); cfg.dynamicSmemBytes = R_SMEM; cfg.stream = st;
        cudaLaunchAttribute at[1];
        at[0].id = cudaLaunchAttributeClusterDimension; at[0].val.clusterDim.x = 16; at[0].val.clusterDim.y = 1; at[0].val.clusterDim.z = 1;
        cfg.attrs = at; cfg.numAttrs = 1;
        cudaLaunchKernelEx(&cfg, k_rec, rp);
    };
    auto launch_work = [&](int qmask, int pdl) {
        prm.qmask = qmask;
        cudaLaunchConfig_t cfg = {};
        cfg.gridDim = dim3(132); cfg.blockDim = dim3(384); cfg.dynamicSmemBytes = SMEM_BYTES; cfg.stream = st;
        cudaLaunchAttribute at[1];
        at[0].id = cudaLaunchAttributeProgrammaticStreamSerialization; at[0].val.programmaticStreamSerializationAllowed = 1;
        cfg.attrs = at; cfg.numAttrs = pdl;
        cudaLaunchKernelEx(&cfg, k_work, prm);
    };
    launch_rec();
    launch_work(0x3f, 1);
}
```

```cpp
#include <cuda_runtime.h>
#include <cuda_bf16.h>
#include <cuda.h>
#include <stdint.h>

typedef __nv_bfloat16 bf16;

constexpr int S_ = 2048, D_ = 512, H_ = 32, DH_ = 128, HD_ = 4096, NSEG = 64, DF_ = 1792;
constexpr int NRB = 16;
constexpr int OSPLIT = 4;

__device__ __align__(1024) bf16 g_h[S_ * D_];
__device__ __align__(1024) bf16 g_kv[S_ * 2 * HD_];
__device__ __align__(1024) bf16 g_kvm[NSEG * 8 * 2 * HD_];
__device__ __align__(1024) bf16 g_o[S_ * HD_];
constexpr int FINE_RB = 15;
constexpr int OSPLIT2 = 16;
constexpr int OP_ROWS = OSPLIT * S_ + OSPLIT2 * (NRB - FINE_RB) * 128;
__device__ __align__(1024) bf16 g_op[OP_ROWS * D_];
__device__ __align__(1024) bf16 g_x1[S_ * D_];
__device__ __align__(1024) bf16 g_h2[S_ * D_];
__device__ __align__(1024) bf16 g_act[S_ * DF_];
__device__ __align__(1024) bf16 g_mod[6 * D_];
__device__ uint32_t g_Fraw[131072 + 65536 + 2048];
#define g_F ((uint32_t*)(((uint64_t)g_Fraw + 0x7FFFFull) & ~0x7FFFFull))
constexpr int F_KV = 0, F_MEM = 32, F_O = 64, F_OP = 96, F_H2 = 128, F_ACT = 160, F_CLAIM = 192  , F_SIDE = 384  , F_TOTAL = 448;
__device__ __align__(128) unsigned int g_flags[F_TOTAL];
#define TR(j, i) do {} while (0)

__device__ __forceinline__ uint32_t smem_u32(const void* p) { return (uint32_t)__cvta_generic_to_shared(p); }
__device__ __forceinline__ uint32_t clk32() { uint32_t c; asm volatile("mov.u32 %0, %%clock;" : "=r"(c)); return c; }
__device__ __forceinline__ uint32_t mapa_u32(uint32_t addr, uint32_t rank) {
    uint32_t r; asm volatile("mapa.shared::cluster.u32 %0, %1, %2;" : "=r"(r) : "r"(addr), "r"(rank)); return r;
}
__device__ __forceinline__ void mbar_init(uint32_t bar, uint32_t cnt) {
    asm volatile("mbarrier.init.shared::cta.b64 [%0], %1;" :: "r"(bar), "r"(cnt) : "memory");
}
__device__ __forceinline__ void mbar_inval(uint32_t bar) {
    asm volatile("mbarrier.inval.shared::cta.b64 [%0];" :: "r"(bar) : "memory");
}
__device__ __forceinline__ void mbar_expect_tx(uint32_t bar, uint32_t bytes) {
    asm volatile("mbarrier.arrive.expect_tx.shared::cta.b64 _, [%0], %1;" :: "r"(bar), "r"(bytes) : "memory");
}
__device__ __forceinline__ void mbar_arrive(uint32_t bar) {
    asm volatile("mbarrier.arrive.shared::cta.b64 _, [%0];" :: "r"(bar) : "memory");
}
__device__ __forceinline__ bool mbar_try_wait(uint32_t bar, uint32_t parity) {
    uint32_t ok;
    asm volatile("{\n.reg .pred p;\nmbarrier.try_wait.parity.shared::cta.b64 p, [%1], %2;\nselp.u32 %0, 1, 0, p;\n}"
                 : "=r"(ok) : "r"(bar), "r"(parity) : "memory");
    return ok;
}
__device__ __forceinline__ bool mbar_try_wait_cluster(uint32_t bar, uint32_t parity) {
    uint32_t ok;
    asm volatile("{\n.reg .pred p;\nmbarrier.try_wait.parity.acquire.cluster.shared::cta.b64 p, [%1], %2;\nselp.u32 %0, 1, 0, p;\n}"
                 : "=r"(ok) : "r"(bar), "r"(parity) : "memory");
    return ok;
}
constexpr int SPIN_LIMIT = 1 << 18;
#define TIMEOUT(code, info) do {} while (0)
__device__ __forceinline__ void mbar_wait(uint32_t bar, uint32_t parity) {
    int g = 0;
#pragma unroll 1
    while (!mbar_try_wait(bar, parity)) { if (++g >= SPIN_LIMIT) { TIMEOUT(0, bar & 255); break; } }
}
__device__ __forceinline__ void mbar_wait_cluster(uint32_t bar, uint32_t parity) {
    int g = 0;
#pragma unroll 1
    while (!mbar_try_wait_cluster(bar, parity)) { if (++g >= SPIN_LIMIT) { TIMEOUT(1, bar & 255); break; } }
}
__device__ __forceinline__ void bar_sync(int id, int n) { asm volatile("bar.sync %0, %1;" :: "r"(id), "r"(n) : "memory"); }
__device__ __forceinline__ void bar_arrive(int id, int n) { asm volatile("bar.arrive %0, %1;" :: "r"(id), "r"(n) : "memory"); }
__device__ __forceinline__ void cluster_sync_all() {
    asm volatile("barrier.cluster.arrive.aligned;\nbarrier.cluster.wait.aligned;" ::: "memory");
}
__device__ __forceinline__ void st_async_v2(uint32_t addr, float a, float b, uint32_t bar) {
    asm volatile("st.async.weak.shared::cluster.mbarrier::complete_tx::bytes.v2.f32 [%0], {%1,%2}, [%3];"
                 :: "r"(addr), "f"(a), "f"(b), "r"(bar) : "memory");
}
__device__ __forceinline__ void st_async_v4(uint32_t addr, uint4 v, uint32_t bar) {
    asm volatile("st.async.weak.shared::cluster.mbarrier::complete_tx::bytes.v4.b32 [%0], {%1,%2,%3,%4}, [%5];"
                 :: "r"(addr), "r"(v.x), "r"(v.y), "r"(v.z), "r"(v.w), "r"(bar) : "memory");
}
__device__ __forceinline__ uint2 ldg_relaxed2(const uint2* p) {
    uint2 v;
    asm volatile("ld.relaxed.gpu.global.v2.b32 {%0,%1}, [%2];" : "=r"(v.x), "=r"(v.y) : "l"(p) : "memory");
    return v;
}
__device__ __forceinline__ void stg_relaxed2(uint2* p, uint2 v) {
    asm volatile("st.relaxed.gpu.global.v2.b32 [%0], {%1,%2};" :: "l"(p), "r"(v.x), "r"(v.y) : "memory");
}
__device__ __forceinline__ uint4 ldg_relaxed(const uint4* p) {
    uint4 v;
    asm volatile("ld.relaxed.gpu.global.v4.b32 {%0,%1,%2,%3}, [%4];" : "=r"(v.x), "=r"(v.y), "=r"(v.z), "=r"(v.w) : "l"(p) : "memory");
    return v;
}
__device__ __forceinline__ void stg_relaxed(uint4* p, uint4 v) {
    asm volatile("st.relaxed.gpu.global.v4.b32 [%0], {%1,%2,%3,%4};" :: "l"(p), "r"(v.x), "r"(v.y), "r"(v.z), "r"(v.w) : "memory");
}
__device__ __forceinline__ void stg_relaxed32(uint32_t* p, uint32_t v) {
    asm volatile("st.relaxed.gpu.global.b32 [%0], %1;" :: "l"(p), "r"(v) : "memory");
}
__device__ __forceinline__ uint32_t ldg_relaxed32(const uint32_t* p) {
    uint32_t v; asm volatile("ld.relaxed.gpu.global.b32 %0, [%1];" : "=r"(v) : "l"(p) : "memory"); return v;
}
__device__ __forceinline__ unsigned int ld_acquire(const unsigned int* p) {
    unsigned int v; asm volatile("ld.acquire.gpu.global.u32 %0, [%1];" : "=r"(v) : "l"(p) : "memory"); return v;
}
__device__ __forceinline__ void red_release(unsigned int* p, unsigned int v) {
    asm volatile("red.release.gpu.global.add.u32 [%0], %1;" :: "l"(p), "r"(v) : "memory");
}
__device__ __forceinline__ void wait_flag(int idx, unsigned int target) {
    const unsigned int* p = &g_flags[idx];
    int g = 0;
#pragma unroll 1
    while (ld_acquire(p) < target) { __nanosleep(20); if (++g >= 64 * SPIN_LIMIT) { TIMEOUT(2, idx); break; } }
}
__device__ __forceinline__ void cp_async16(uint32_t dst, const void* src) {
    asm volatile("cp.async.cg.shared.global [%0], [%1], 16;" :: "r"(dst), "l"(src) : "memory");
}
__device__ __forceinline__ void cp_async_commit() { asm volatile("cp.async.commit_group;" ::: "memory"); }
template <int N> __device__ __forceinline__ void cp_async_wait() { asm volatile("cp.async.wait_group %0;" :: "n"(N) : "memory"); }
__device__ __forceinline__ void ldsm4(uint32_t& r0, uint32_t& r1, uint32_t& r2, uint32_t& r3, uint32_t addr) {
    asm volatile("ldmatrix.sync.aligned.m8n8.x4.shared.b16 {%0,%1,%2,%3}, [%4];" : "=r"(r0), "=r"(r1), "=r"(r2), "=r"(r3) : "r"(addr) : "memory");
}
__device__ __forceinline__ void ldsm4t(uint32_t& r0, uint32_t& r1, uint32_t& r2, uint32_t& r3, uint32_t addr) {
    asm volatile("ldmatrix.sync.aligned.m8n8.x4.trans.shared.b16 {%0,%1,%2,%3}, [%4];" : "=r"(r0), "=r"(r1), "=r"(r2), "=r"(r3) : "r"(addr) : "memory");
}
__device__ __forceinline__ void ldsm2t(uint32_t& r0, uint32_t& r1, uint32_t addr) {
    asm volatile("ldmatrix.sync.aligned.m8n8.x2.trans.shared.b16 {%0,%1}, [%2];" : "=r"(r0), "=r"(r1) : "r"(addr) : "memory");
}
__device__ __forceinline__ void stsm4(uint32_t addr, uint32_t r0, uint32_t r1, uint32_t r2, uint32_t r3) {
    asm volatile("stmatrix.sync.aligned.m8n8.x4.shared.b16 [%0], {%1,%2,%3,%4};" :: "r"(addr), "r"(r0), "r"(r1), "r"(r2), "r"(r3) : "memory");
}
__device__ __forceinline__ void stsm2t(uint32_t addr, uint32_t r0, uint32_t r1) {
    asm volatile("stmatrix.sync.aligned.m8n8.x2.trans.shared.b16 [%0], {%1,%2};" :: "r"(addr), "r"(r0), "r"(r1) : "memory");
}
__device__ __forceinline__ void mma16816(float* d, uint32_t a0, uint32_t a1, uint32_t a2, uint32_t a3, uint32_t b0, uint32_t b1) {
    asm volatile("mma.sync.aligned.m16n8k16.row.col.f32.bf16.bf16.f32 {%0,%1,%2,%3}, {%4,%5,%6,%7}, {%8,%9}, {%0,%1,%2,%3};"
                 : "+f"(d[0]), "+f"(d[1]), "+f"(d[2]), "+f"(d[3]) : "r"(a0), "r"(a1), "r"(a2), "r"(a3), "r"(b0), "r"(b1));
}
__device__ __forceinline__ void mma1688(float* d, uint32_t a0, uint32_t a1, uint32_t b0) {
    asm volatile("mma.sync.aligned.m16n8k8.row.col.f32.bf16.bf16.f32 {%0,%1,%2,%3}, {%4,%5}, {%6}, {%0,%1,%2,%3};"
                 : "+f"(d[0]), "+f"(d[1]), "+f"(d[2]), "+f"(d[3]) : "r"(a0), "r"(a1), "r"(b0));
}
__device__ __forceinline__ void mma16816h(float* d, uint32_t a0, uint32_t a2, uint32_t b0, uint32_t b1) {
    asm volatile("{\n.reg .b32 ju, jv;\nmma.sync.aligned.m16n8k16.row.col.f32.bf16.bf16.f32 {%0,%1,%2,%3}, {%4,ju,%5,jv}, {%6,%7}, {%0,%1,%2,%3};\n}"
                 : "+f"(d[0]), "+f"(d[1]), "+f"(d[2]), "+f"(d[3]) : "r"(a0), "r"(a2), "r"(b0), "r"(b1));
}
__device__ __forceinline__ void mma1688h(float* d, uint32_t a0, uint32_t b0) {
    asm volatile("{\n.reg .b32 ju;\nmma.sync.aligned.m16n8k8.row.col.f32.bf16.bf16.f32 {%0,%1,%2,%3}, {%4,ju}, {%5}, {%0,%1,%2,%3};\n}"
                 : "+f"(d[0]), "+f"(d[1]), "+f"(d[2]), "+f"(d[3]) : "r"(a0), "r"(b0));
}
__device__ __forceinline__ uint32_t pack2(float lo, float hi) {
    uint32_t r; asm("cvt.rn.bf16x2.f32 %0, %1, %2;" : "=r"(r) : "f"(hi), "f"(lo)); return r;
}
__device__ __forceinline__ float bflo(uint32_t w) { return __uint_as_float(w << 16); }
__device__ __forceinline__ float bfhi(uint32_t w) { return __uint_as_float(w & 0xffff0000u); }
__device__ __forceinline__ float rbf(float x) { return __bfloat162float(__float2bfloat16_rn(x)); }
__device__ __forceinline__ float ex2(float x) { float y; asm("ex2.approx.ftz.f32 %0, %1;" : "=f"(y) : "f"(x)); return y; }
__device__ __forceinline__ void sts128(uint32_t addr, uint4 v) {
    asm volatile("st.shared.v4.b32 [%0], {%1,%2,%3,%4};" :: "r"(addr), "r"(v.x), "r"(v.y), "r"(v.z), "r"(v.w) : "memory");
}
__device__ __forceinline__ uint4 lds128(uint32_t addr) {
    uint4 v; asm volatile("ld.shared.v4.b32 {%0,%1,%2,%3}, [%4];" : "=r"(v.x), "=r"(v.y), "=r"(v.z), "=r"(v.w) : "r"(addr) : "memory"); return v;
}
__device__ __forceinline__ float2 lds64f(uint32_t addr) {
    float2 v; asm volatile("ld.shared.v2.f32 {%0,%1}, [%2];" : "=f"(v.x), "=f"(v.y) : "r"(addr) : "memory"); return v;
}
__device__ __forceinline__ float lds32f(uint32_t addr) {
    float v; asm volatile("ld.shared.f32 %0, [%1];" : "=f"(v) : "r"(addr) : "memory"); return v;
}
__device__ __forceinline__ uint32_t lds32(uint32_t addr) {
    uint32_t v; asm volatile("ld.shared.b32 %0, [%1];" : "=r"(v) : "r"(addr) : "memory"); return v;
}
__device__ __forceinline__ void sts32(uint32_t addr, uint32_t v) { asm volatile("st.shared.b32 [%0], %1;" :: "r"(addr), "r"(v) : "memory"); }
__device__ __forceinline__ void sts64f(uint32_t addr, float a, float b) { asm volatile("st.shared.v2.f32 [%0], {%1,%2};" :: "r"(addr), "f"(a), "f"(b) : "memory"); }

__device__ __forceinline__ void tma_load2d(uint32_t dst, const CUtensorMap* tm, int c0, int c1, uint32_t bar) {
    asm volatile("cp.async.bulk.tensor.2d.shared::cluster.global.mbarrier::complete_tx::bytes [%0], [%1, {%3, %4}], [%2];"
                 :: "r"(dst), "l"(tm), "r"(bar), "r"(c0), "r"(c1) : "memory");
}
__device__ __forceinline__ void tma_store2d(const CUtensorMap* tm, uint32_t src, int c0, int c1) {
    asm volatile("cp.async.bulk.tensor.2d.global.shared::cta.bulk_group [%0, {%2, %3}], [%1];"
                 :: "l"(tm), "r"(src), "r"(c0), "r"(c1) : "memory");
}
__device__ __forceinline__ void bulk_commit() { asm volatile("cp.async.bulk.commit_group;" ::: "memory"); }
__device__ __forceinline__ void bulk_wait0() { asm volatile("cp.async.bulk.wait_group 0;" ::: "memory"); }
__device__ __forceinline__ void fence_async_smem() { asm volatile("fence.proxy.async.shared::cta;" ::: "memory"); }
__device__ __forceinline__ void fence_async_all() { asm volatile("fence.proxy.async;" ::: "memory"); }

__device__ __forceinline__ void wg_fence() { asm volatile("wgmma.fence.sync.aligned;" ::: "memory"); }
__device__ __forceinline__ void wg_commit() { asm volatile("wgmma.commit_group.sync.aligned;" ::: "memory"); }
__device__ __forceinline__ void wg_wait0() { asm volatile("wgmma.wait_group.sync.aligned 0;" ::: "memory"); }
__device__ __forceinline__ uint64_t mkdesc(uint32_t saddr, uint32_t lbo, uint32_t sbo) {
    return (uint64_t)((saddr & 0x3FFFF) >> 4) | ((uint64_t)(lbo >> 4) << 16) | ((uint64_t)(sbo >> 4) << 32) | (1ull << 62);
}
#define ACC8(i) "+f"(d[i]), "+f"(d[i + 1]), "+f"(d[i + 2]), "+f"(d[i + 3]), "+f"(d[i + 4]), "+f"(d[i + 5]), "+f"(d[i + 6]), "+f"(d[i + 7])
__device__ __forceinline__ void wgmma_n256(float* d, uint64_t da, uint64_t db, int scale_d) {
    asm volatile(
        "{\n.reg .pred p;\nsetp.ne.b32 p, %130, 0;\n"
        "wgmma.mma_async.sync.aligned.m64n256k16.f32.bf16.bf16 "
        "{%0,%1,%2,%3,%4,%5,%6,%7,%8,%9,%10,%11,%12,%13,%14,%15,%16,%17,%18,%19,%20,%21,%22,%23,%24,%25,%26,%27,%28,%29,%30,%31,"
        "%32,%33,%34,%35,%36,%37,%38,%39,%40,%41,%42,%43,%44,%45,%46,%47,%48,%49,%50,%51,%52,%53,%54,%55,%56,%57,%58,%59,%60,%61,%62,%63,"
        "%64,%65,%66,%67,%68,%69,%70,%71,%72,%73,%74,%75,%76,%77,%78,%79,%80,%81,%82,%83,%84,%85,%86,%87,%88,%89,%90,%91,%92,%93,%94,%95,"
        "%96,%97,%98,%99,%100,%101,%102,%103,%104,%105,%106,%107,%108,%109,%110,%111,%112,%113,%114,%115,%116,%117,%118,%119,%120,%121,%122,%123,%124,%125,%126,%127}, "
        "%128, %129, p, 1, 1, 0, 1;\n}"
        : ACC8(0), ACC8(8), ACC8(16), ACC8(24), ACC8(32), ACC8(40), ACC8(48), ACC8(56),
          ACC8(64), ACC8(72), ACC8(80), ACC8(88), ACC8(96), ACC8(104), ACC8(112), ACC8(120)
        : "l"(da), "l"(db), "r"(scale_d));
}
__device__ __forceinline__ void wgmma_n128(float* d, uint64_t da, uint64_t db, int scale_d) {
    asm volatile(
        "{\n.reg .pred p;\nsetp.ne.b32 p, %66, 0;\n"
        "wgmma.mma_async.sync.aligned.m64n128k16.f32.bf16.bf16 "
        "{%0,%1,%2,%3,%4,%5,%6,%7,%8,%9,%10,%11,%12,%13,%14,%15,%16,%17,%18,%19,%20,%21,%22,%23,%24,%25,%26,%27,%28,%29,%30,%31,"
        "%32,%33,%34,%35,%36,%37,%38,%39,%40,%41,%42,%43,%44,%45,%46,%47,%48,%49,%50,%51,%52,%53,%54,%55,%56,%57,%58,%59,%60,%61,%62,%63}, "
        "%64, %65, p, 1, 1, 0, 1;\n}"
        : ACC8(0), ACC8(8), ACC8(16), ACC8(24), ACC8(32), ACC8(40), ACC8(48), ACC8(56)
        : "l"(da), "l"(db), "r"(scale_d));
}

__device__ __forceinline__ void wgmma_n64(float* d, uint64_t da, uint64_t db) {
    asm volatile(
        "wgmma.mma_async.sync.aligned.m64n64k16.f32.bf16.bf16 "
        "{%0,%1,%2,%3,%4,%5,%6,%7,%8,%9,%10,%11,%12,%13,%14,%15,%16,%17,%18,%19,%20,%21,%22,%23,%24,%25,%26,%27,%28,%29,%30,%31}, "
        "%32, %33, 1, 1, 1, 0, 1;"
        : ACC8(0), ACC8(8), ACC8(16), ACC8(24)
        : "l"(da), "l"(db));
}
__device__ __forceinline__ void wgmma_n8_ta(float* d, uint64_t da, uint64_t db, int scale_d) {
    asm volatile(
        "{\n.reg .pred p;\nsetp.ne.b32 p, %6, 0;\n"
        "wgmma.mma_async.sync.aligned.m64n8k16.f32.bf16.bf16 {%0,%1,%2,%3}, %4, %5, p, 1, 1, 1, 0;\n}"
        : "+f"(d[0]), "+f"(d[1]), "+f"(d[2]), "+f"(d[3]) : "l"(da), "l"(db), "r"(scale_d));
}

struct PrefetchList { const bf16* p[5]; };
__global__ void __launch_bounds__(256) k_mod(const bf16* __restrict__ c, const bf16* __restrict__ w_mod, const PrefetchList pf) {
    asm volatile("griddepcontrol.launch_dependents;");
    __shared__ float s_c[D_];
    __shared__ float s_red[64][33];
    const int tid = threadIdx.x;
    const int cq = tid & 3, rg = tid >> 2;
    uint4 w[8];
#pragma unroll
    for (int i = 0; i < 8; i++)
        w[i] = __ldg((const uint4*)(w_mod + (size_t)(rg * 8 + i) * (6 * D_) + blockIdx.x * 32 + cq * 8));
    for (int i = tid; i < D_; i += 256) {
        float v = __bfloat162float(c[i]);
        s_c[i] = rbf(v / (1.f + __expf(-v)));
    }
    {
        const int gt = blockIdx.x * 256 + tid, nt = gridDim.x * 256;
        for (int i = gt; i < F_TOTAL; i += nt) g_flags[i] = 0;
        for (int i = gt; i < 65536 + 2048; i += nt) g_F[i] = 0;
        if (tid < 11) {
            const int i = tid * gridDim.x + blockIdx.x;
            if (i < 1024) asm volatile("cp.async.bulk.prefetch.L2.global [%0], %1;" :: "l"(pf.p[i >> 8] + (size_t)(i & 255) * 8192), "r"(16384) : "memory");
        }
    }
    __syncthreads();
    float a[8];
#pragma unroll
    for (int j = 0; j < 8; j++) a[j] = 0.f;
#pragma unroll
    for (int i = 0; i < 8; i++) {
        float cv = s_c[rg * 8 + i];
        a[0] += cv * bflo(w[i].x); a[1] += cv * bfhi(w[i].x); a[2] += cv * bflo(w[i].y); a[3] += cv * bfhi(w[i].y);
        a[4] += cv * bflo(w[i].z); a[5] += cv * bfhi(w[i].z); a[6] += cv * bflo(w[i].w); a[7] += cv * bfhi(w[i].w);
    }
#pragma unroll
    for (int j = 0; j < 8; j++) s_red[rg][cq * 8 + j] = a[j];
    __syncthreads();
    if (tid < 32) {
        float s = 0.f;
#pragma unroll 8
        for (int r = 0; r < 64; r++) s += s_red[r][tid];
        g_mod[blockIdx.x * 32 + tid] = __float2bfloat16_rn(s);
    }
}

__device__ __forceinline__ uint32_t hadd2(uint32_t a, uint32_t b) { uint32_t r; asm("add.rn.bf16x2 %0, %1, %2;" : "=r"(r) : "r"(a), "r"(b)); return r; }
__device__ __forceinline__ uint32_t hsub2(uint32_t a, uint32_t b) { uint32_t r; asm("sub.rn.bf16x2 %0, %1, %2;" : "=r"(r) : "r"(a), "r"(b)); return r; }
__device__ __forceinline__ uint32_t hmul2(uint32_t a, uint32_t b) { uint32_t r; asm("mul.rn.bf16x2 %0, %1, %2;" : "=r"(r) : "r"(a), "r"(b)); return r; }
__device__ __forceinline__ void load_mod8(const bf16* m, int lane, uint32_t* v) {
    const uint4 a = __ldcg((const uint4*)m + lane), b = __ldcg((const uint4*)m + 32 + lane);
    v[0] = a.x; v[1] = a.y; v[2] = a.z; v[3] = a.w; v[4] = b.x; v[5] = b.y; v[6] = b.z; v[7] = b.w;
}
__device__ __forceinline__ void ln_stats(const uint32_t* x, uint32_t& mu2, float& rden) {
    float s = 0.f;
#pragma unroll
    for (int i = 0; i < 8; i++) s += bflo(x[i]) + bfhi(x[i]);
#pragma unroll
    for (int o = 16; o > 0; o >>= 1) s += __shfl_xor_sync(~0u, s, o);
    const float mean = s * (1.f / D_);
    float q = 0.f;
#pragma unroll
    for (int i = 0; i < 8; i++) { const float d0 = bflo(x[i]) - mean, d1 = bfhi(x[i]) - mean; q = fmaf(d0, d0, q); q = fmaf(d1, d1, q); }
#pragma unroll
    for (int o = 16; o > 0; o >>= 1) q += __shfl_xor_sync(~0u, q, o);
    mu2 = pack2(mean, mean);
    rden = __frcp_rn(rbf(__fsqrt_rn(rbf(rbf(q * (1.f / D_)) + 1e-5f))));
}
__device__ __forceinline__ void ln_apply(const uint32_t* x, uint32_t mu2, float rden, const uint32_t* c1, const uint32_t* sm, uint32_t* r) {
#pragma unroll
    for (int i = 0; i < 8; i++) {
        const uint32_t d = hsub2(x[i], mu2);
        r[i] = hadd2(hmul2(pack2(bflo(d) * rden, bfhi(d) * rden), c1[i]), sm[i]);
    }
}

__global__ void __launch_bounds__(256) k_ln1(const bf16* __restrict__ x) {
    const int lane = threadIdx.x & 31, row = blockIdx.x * 8 + (threadIdx.x >> 5);
    const uint4* xr = (const uint4*)(x + (size_t)row * D_);
    const uint4 a = __ldg(xr + lane), b = __ldg(xr + 32 + lane);
    const uint32_t v[8] = {a.x, a.y, a.z, a.w, b.x, b.y, b.z, b.w};
    uint32_t mu2; float rden;
    ln_stats(v, mu2, rden);
    asm volatile("griddepcontrol.wait;" ::: "memory");
    uint32_t c1[8], sm[8], r[8];
    load_mod8(g_mod + D_, lane, c1);
    load_mod8(g_mod, lane, sm);
#pragma unroll
    for (int i = 0; i < 8; i++) c1[i] = hadd2(c1[i], 0x3F803F80u);
    ln_apply(v, mu2, rden, c1, sm, r);
    uint4* hr = (uint4*)(g_h + (size_t)row * D_);
    hr[lane] = make_uint4(r[0], r[1], r[2], r[3]); hr[32 + lane] = make_uint4(r[4], r[5], r[6], r[7]);
}

struct __align__(64) Params {
    CUtensorMap tm_h, tm_kv, tm_kvm, tm_o, tm_op, tm_h2, tm_act, tm_x1, tm_out;
    CUtensorMap tm_wq, tm_wk, tm_wv, tm_wo, tm_wg, tm_wu, tm_wd;
    const bf16* x;
    int qmask;
};

constexpr int R_NST = 3;
constexpr uint32_t R_WV = 0, R_MEM = 65536, R_KX = 73728, R_VX = R_KX + R_NST * 4096, R_QS = R_VX + R_NST * 4096,
                   R_KMS = R_QS + 1024, R_VMS = R_KMS + 1024, R_OS = R_VMS + 1024, R_SX = R_OS + 1024, R_BAR = R_SX + 2560,
                   R_RS = 105472  , R_VP = R_RS + 8192  ,
                   R_STG = R_VP + 8192  , R_SMEM = R_STG + 98304;
static_assert(R_BAR + 64 <= R_RS, "smem");
constexpr uint32_t RB_SX = R_BAR, RB_V = R_BAR + 8, RB_E = R_BAR + 16, RB_A = R_BAR + 24, RB_ROLE = R_BAR + 32;
constexpr int W_NST = 3;
constexpr uint32_t W_STAGE = 49152, W_STG = W_NST * W_STAGE, W_END = W_STG + 65536;
constexpr uint32_t SM_BAR = W_END;
constexpr uint32_t SMEM_BYTES = W_END + 1024;
constexpr uint32_t B_FULL = 0, B_EMPTY = 32, B_STGFREE = 64, B_RING = 128;

constexpr int NB_X = 11  , NB_Y = 1, NB_B = 2, NB_C = 3, NB_D = 4, NB_W0 = 6  , NB_ST = 9  ;

__device__ __forceinline__ int pos_of_d(int d) {
    const int rem = d & 31;
    return (d & ~31) + ((rem & 7) >> 1) * 8 + (rem & 1) * 4 + (rem >> 3);
}

#define PROF(i) do {} while (0)
#define PROFG(i) do {} while (0)
#define OPAQUE(x) asm volatile("" : "+r"(x))
#define FENCE_SCHED(x) do { if ((x) == 0u) asm volatile("trap;"); } while (0)
#define VK0_ 4
constexpr int VK0 = VK0_;
constexpr int NOFF = 8;
#define VDELAY -1
#define POLL_GAP 100

struct RecParams { const bf16 *mem0, *wq, *wk, *wv, *wo; int ncl; };

__device__ __forceinline__ void rec_qk(const RecParams& p, const uint32_t sb, const int cta, const int warp, int lane, const int sel) {
    const int crank = cta & 15, cl = cta >> 4, rank = cta & 1;
    const int kh = warp >> 2, aa = warp & 3;
    uint32_t wa[2][16][4];
    const uint32_t stg = sb + R_STG + kh * 32768;
    {
        const int t128 = aa * 32 + lane;
        const int row = (lane >> 4) * 8 + (lane & 7);
        const int ch = t128 & 7;
        const size_t goff = (size_t)kh * 256 * HD_ + cta * 64 + ch * 8;
#pragma unroll 4
        for (int dd = 0; dd < 16; dd++) {
            const int d = dd * 16 + (t128 >> 3), pp = pos_of_d(d);
            cp_async16(sb + R_WV + kh * 32768 + pp * 128 + ((ch ^ (pp & 7)) << 4), p.wv + goff + (size_t)d * HD_);
        }
        cp_async_commit();
#pragma unroll 4
        for (int dd = 0; dd < 16; dd++) {
            const int d = dd * 16 + (t128 >> 3), pp = pos_of_d(d);
            cp_async16(stg + pp * 128 + ((ch ^ (pp & 7)) << 4), p.wq + goff + (size_t)d * HD_);
        }
        cp_async_commit();
        {
            const int i0 = (warp * 32 + lane) * 16, tok = i0 >> 9;
            const uint4 m0 = __ldg((const uint4*)(p.mem0 + i0)), m1 = __ldg((const uint4*)(p.mem0 + i0 + 8));
            const uint32_t mw[8] = {m0.x, m0.y, m0.z, m0.w, m1.x, m1.y, m1.z, m1.w};
#pragma unroll
            for (int e = 0; e < 16; e++) {
                const int pp = pos_of_d((i0 & 511) + e);
                const unsigned short v = (unsigned short)(mw[e >> 1] >> ((e & 1) * 16));
                asm volatile("st.shared.u16 [%0], %1;" :: "r"(sb + R_MEM + (pp >> 3) * 128 + tok * 16 + (pp & 7) * 2), "h"(v) : "memory");
            }
        }
        cp_async_wait<1>();
        bar_sync(NB_W0 + kh, 128);
        const uint32_t fv = row * 128 + (((2 * aa + ((lane >> 3) & 1)) ^ (row & 7)) << 4);
#pragma unroll
        for (int ks = 0; ks < 16; ks++) ldsm4t(wa[0][ks][0], wa[0][ks][1], wa[0][ks][2], wa[0][ks][3], sb + R_WV + kh * 32768 + fv + ks * 2048);
        bar_sync(NB_W0 + kh, 128);
#pragma unroll
        for (int ks = 0; ks < 16; ks++)
            sts128(sb + R_WV + kh * 32768 + (aa * 16 + ks) * 512 + lane * 16, make_uint4(wa[0][ks][0], wa[0][ks][1], wa[0][ks][2], wa[0][ks][3]));
        const uint32_t fo = stg + row * 128 + (((4 * (aa & 1) + ((lane >> 3) & 1)) ^ (row & 7)) << 4);
#pragma unroll 1
        for (int m = 0; m < 2; m++) {
            cp_async_wait<0>();
            bar_sync(NB_W0 + kh, 128);
            if ((aa >> 1) == m) {
#pragma unroll
                for (int ks = 0; ks < 16; ks++) {
                    ldsm4t(wa[0][ks][0], wa[0][ks][1], wa[0][ks][2], wa[0][ks][3], fo + ks * 2048);
                    ldsm4t(wa[1][ks][0], wa[1][ks][1], wa[1][ks][2], wa[1][ks][3], (fo ^ 32) + ks * 2048);
                }
            }
            bar_sync(NB_W0 + kh, 128);
            if (m == 0) {
#pragma unroll 4
                for (int dd = 0; dd < 16; dd++) {
                    const int d = dd * 16 + (t128 >> 3), pp = pos_of_d(d);
                    cp_async16(stg + pp * 128 + ((ch ^ (pp & 7)) << 4), p.wk + goff + (size_t)d * HD_);
                }
                cp_async_commit();
            }
        }
    }
    const uint32_t tab = stg + (aa * 32 + lane) * 16;
    {
        const uint32_t l7 = lane & 7, l8 = lane >> 3, g = lane >> 2, t = lane & 3;
        const uint32_t t0 = l7 * 128 + ((l8 ^ l7) << 4);
        const uint32_t tq = l7 * 128 + (((l8 >> 1) ^ l7) << 4);
        const uint32_t bq = warp >> 1, tp = warp & 1;
        uint4 v;
        v.x = sb + (aa < 2 ? R_QS : R_KMS) + l7 * 128 + (((4 * (aa & 1) + 2 * kh + (l8 & 1)) ^ l7) << 4);
        v.y = sb + R_QS + tq;
        v.z = sb + (warp == 0 ? R_KMS : R_KX + (warp - 1) * 1024) + t0;
        v.w = mapa_u32(sb + R_SX + (rank * 5 + warp) * 256 + lane * 8, crank ^ 1);
        sts128(tab, v);
        sts128(tab + 2048, make_uint4(sb + lane * 16 + R_MEM + kh * 4096, sb + lane * 16 + R_WV + warp * 8192,
                                      sb + lane * 16 + R_VP + warp * 512, sb + lane * 16 + R_VP + 4096 + (warp ^ 4) * 512));
        const uint32_t src = (l8 >> 1) * 8 + l7;
        const uint32_t L = bq * 8 + 2 * tp + (l8 & 1);
        const uint32_t d0 = (crank + ((t >> 1) | (g & 6))) & 15;
        v.x = sb + R_RS + src * 512 + ((L ^ (src & 7)) << 4);
        v.y = mapa_u32(sb + R_MEM + (crank * 4 + bq) * 128 + (4 * tp + 2 * (t & 1) + (g & 1)) * 16, d0);
        v.z = mapa_u32(sb + RB_A, d0);
        v.w = lane;
        sts128(tab + 4096, v);
        const uint64_t wr = (uint64_t)(g_F + ((crank * 2 + ((crank ^ (crank >> 3) ^ sel) & 1)) * 1024 + warp * 128 + cl * 32 + lane));
        sts128(tab + 6144, make_uint4((uint32_t)wr, (uint32_t)(wr >> 32), (uint32_t)((((cl + 1) & 3) - cl) * 128), (uint32_t)((((cl + 2) & 3) - cl) * 128)));
        sts32(tab + 8192, (uint32_t)((((cl + 3) & 3) - cl) * 128));
#pragma unroll
        for (int i = 0; i < NOFF; i++)
            sts128(tab + 10240 + i * 2048, make_uint4(wa[i & 1][i >> 1][0], wa[i & 1][i >> 1][1], wa[i & 1][i >> 1][2], wa[i & 1][i >> 1][3]));
    }
    bar_sync(NB_D, 384);
    uint32_t slot_off = 0;
    const uint32_t slot_inc = warp == 0 ? 0 : 4096;
    const uint32_t sx_bar_rem = (sb + RB_SX) ^ (1u << 24);
    uint4 tb = lds128(tab + 2048);
#pragma unroll 1
    for (int s = 0; s < NSEG; s++) {
        if (s > 0) mbar_wait(sb + RB_A, (s - 1) & 1);
        if (warp == 0) { PROF(0); PROFG(13); }
        uint4 ta;
        {
            float acc[5][4];
#pragma unroll
            for (int c = 0; c < 5; c++) { acc[c][0] = acc[c][1] = acc[c][2] = acc[c][3] = 0.f; }
            uint32_t b[8][4];
            uint4 av[16];
            ldsm4(b[0][0], b[0][1], b[0][2], b[0][3], tb.x);
            ldsm4(b[1][0], b[1][1], b[1][2], b[1][3], tb.x + 512);
            ldsm4(b[2][0], b[2][1], b[2][2], b[2][3], tb.x + 1024);
#pragma unroll
            for (int k2 = 0; k2 < 8; k2++) {
                mma16816(acc[0], wa[0][2 * k2][0], wa[0][2 * k2][1], wa[0][2 * k2][2], wa[0][2 * k2][3], b[k2][0], b[k2][1]);
                mma16816(acc[1], wa[1][2 * k2][0], wa[1][2 * k2][1], wa[1][2 * k2][2], wa[1][2 * k2][3], b[k2][0], b[k2][1]);
                if (2 * k2 >= VK0) mma16816(acc[2], av[2 * k2].x, av[2 * k2].y, av[2 * k2].z, av[2 * k2].w, b[k2][0], b[k2][1]);
                mma16816(acc[3], wa[0][2 * k2 + 1][0], wa[0][2 * k2 + 1][1], wa[0][2 * k2 + 1][2], wa[0][2 * k2 + 1][3], b[k2][2], b[k2][3]);
                mma16816(acc[4], wa[1][2 * k2 + 1][0], wa[1][2 * k2 + 1][1], wa[1][2 * k2 + 1][2], wa[1][2 * k2 + 1][3], b[k2][2], b[k2][3]);
                if (2 * k2 >= VK0) mma16816(acc[2], av[2 * k2 + 1].x, av[2 * k2 + 1].y, av[2 * k2 + 1].z, av[2 * k2 + 1].w, b[k2][2], b[k2][3]);
                if (k2 + 3 < 8) ldsm4(b[k2 + 3][0], b[k2 + 3][1], b[k2 + 3][2], b[k2 + 3][3], tb.x + (k2 + 3) * 512);
                if (VK0 + 2 * k2 < 16) { av[VK0 + 2 * k2] = lds128(tb.y + (VK0 + 2 * k2) * 512); av[VK0 + 2 * k2 + 1] = lds128(tb.y + (VK0 + 2 * k2 + 1) * 512); }
                if (k2 == 5) ta = lds128(tab);
            }
#pragma unroll
            for (int i = 0; i < 4; i++) { acc[0][i] += acc[3][i]; acc[1][i] += acc[4][i]; }
            const float g0 = kh ? acc[0][0] : acc[1][0], g1 = kh ? acc[0][1] : acc[1][1], g2 = kh ? acc[0][2] : acc[1][2], g3 = kh ? acc[0][3] : acc[1][3];
            sts128(tb.w, make_uint4(__float_as_uint(g0), __float_as_uint(g1), __float_as_uint(g2), __float_as_uint(g3)));
            const float k0 = kh ? acc[1][0] : acc[0][0], k1 = kh ? acc[1][1] : acc[0][1], k2_ = kh ? acc[1][2] : acc[0][2], k3 = kh ? acc[1][3] : acc[0][3];
            if (warp == 0) PROF(1);
            bar_sync(NB_X + aa, 64);
            const uint4 o = lds128(tb.z + 4096);
            stsm2t(ta.x, pack2(k0 + __uint_as_float(o.x), k1 + __uint_as_float(o.y)), pack2(k2_ + __uint_as_float(o.z), k3 + __uint_as_float(o.w)));
            sts128(tb.z, make_uint4(__float_as_uint(acc[2][0]), __float_as_uint(acc[2][1]), __float_as_uint(acc[2][2]), __float_as_uint(acc[2][3])));
        }
        const uint32_t kb = ta.z + slot_off;
        if (warp == 0) PROF(14);
        bar_sync(NB_B, 256);
        if (warp < 5) {
            uint32_t q[16], k0, k1, k2, k3, k4, k5, k6, k7;
            float sa[4] = {0.f, 0.f, 0.f, 0.f}, sc[4] = {0.f, 0.f, 0.f, 0.f};
            ldsm4(q[0], q[1], q[2], q[3], ta.y);
            ldsm4(k0, k1, k2, k3, kb);
            ldsm4(q[4], q[5], q[6], q[7], ta.y ^ 32);
            ldsm4(q[8], q[9], q[10], q[11], ta.y ^ 64);
            ldsm4(k4, k5, k6, k7, kb ^ 64);
            ldsm4(q[12], q[13], q[14], q[15], ta.y ^ 96);
            mma16816(sa, q[0], q[1], q[2], q[3], k0, k1);
            bar_arrive(NB_Y, 288);
            mma16816(sc, q[4], q[5], q[6], q[7], k2, k3);
            mma16816(sa, q[8], q[9], q[10], q[11], k4, k5);
            mma16816(sc, q[12], q[13], q[14], q[15], k6, k7);
            const float scl = 0.08838834764831845f * 1.4426950408889634f;
            const float r0 = (sa[0] + sc[0]) * scl, r1 = (sa[1] + sc[1]) * scl;
            if (s != NSEG - 1) {
                st_async_v2(ta.w, r0, r1, sx_bar_rem);
                st_async_v2(ta.w ^ (1u << 24), r0, r1, sx_bar_rem ^ (1u << 24));
            }
            if (warp == 0) PROF(2);
        } else if (s > 0 && warp == 7 && lane == 0) {
            mbar_expect_tx(sb + RB_A, 8192);
        }
        if (s == NSEG - 1) break;
        slot_off = slot_off == (R_NST - 1) * 4096 ? 0 : slot_off + slot_inc;
        const uint4 tc = lds128(tab + 4096), td = lds128(tab + 6144);
        const uint32_t te = lds32(tab + 8192);
        uint32_t* wr = (uint32_t*)(((uint64_t)td.y << 32) | (td.x ^ ((s & 1) * 0x21000)));
        const uint32_t* r1p = (const uint32_t*)((const char*)wr + (int)td.z);
        const uint32_t* r2p = (const uint32_t*)((const char*)wr + (int)td.w);
        const uint32_t* r3p = (const uint32_t*)((const char*)wr + (int)te);
        const uint32_t tag = ((s >> 1) + 1) & 1;
        mbar_wait(sb + RB_E, s & 1);
        if (warp == 0) PROF(7);
        {
            uint32_t a0, a1, a2, a3, a4, a5, a6, a7;
            ldsm4t(a0, a1, a2, a3, tc.x);
            ldsm4t(a4, a5, a6, a7, tc.x ^ 64);
            const uint32_t one = 0x3F803F80u;
            float d0_[4] = {0.f, 0.f, 0.f, 0.f}, d1_[4] = {0.f, 0.f, 0.f, 0.f};
            mma16816(d0_, a0, a1, a2, a3, one, one);
            mma16816(d1_, a4, a5, a6, a7, one, one);
            const bool t1 = tc.w & 1, t2 = tc.w & 2;
            const float x = t2 ? (t1 ? d1_[2] : d1_[0]) : (t1 ? d0_[2] : d0_[0]);
            const uint32_t own = (__float_as_uint(x) & ~1u) | tag;
            stg_relaxed32(wr, own);
            const uint32_t tq = clk32();
            if (warp == 0) PROF(8);
            PROFG(16 + warp);
#pragma unroll
            for (int i = 0; i < NOFF; i++) {
                const uint4 f0 = lds128(tab + 10240 + i * 2048);
                wa[i & 1][i >> 1][0] = f0.x; wa[i & 1][i >> 1][1] = f0.y; wa[i & 1][i >> 1][2] = f0.z; wa[i & 1][i >> 1][3] = f0.w;
            }
            tb = lds128(tab + 2048);
            while ((int)(clk32() - tq) < POLL_GAP) {}
            uint32_t f1, f2, f3;
            int gg = 0;
#pragma unroll 1
            while (true) {
                f1 = ldg_relaxed32(r1p); f2 = ldg_relaxed32(r2p); f3 = ldg_relaxed32(r3p);
                if (__all_sync(~0u, (((f1 ^ tag) | (f2 ^ tag) | (f3 ^ tag)) & 1) == 0)) break;
                if (++gg > 16 * SPIN_LIMIT) { TIMEOUT(3, s); break; }
            }
            if (warp == 0) PROF(9);
            PROFG(32 + warp);
            const float v = (__uint_as_float(own) + __uint_as_float(f2)) + (__uint_as_float(f1) + __uint_as_float(f3));
            const bool b8 = tc.w & 8, b16 = tc.w & 16;
            const float recv = __shfl_xor_sync(~0u, v, 8);
            const uint32_t word = b8 ? pack2(recv, v) : pack2(v, recv);
            const uint32_t oth = __shfl_xor_sync(~0u, word, 16);
            const uint32_t wl = b16 ? oth : word, wh = b16 ? word : oth;
            const uint32_t p0 = __shfl_xor_sync(~0u, wl, 2), p1 = __shfl_xor_sync(~0u, wh, 2);
            const uint4 item = t2 ? make_uint4(p0, p1, wl, wh) : make_uint4(wl, wh, p0, p1);
            st_async_v4(tc.y, item, tc.z);
            st_async_v4(tc.y ^ (8u << 24), item, tc.z ^ (8u << 24));
            if (tc.w == 0 && warp == 7) mbar_expect_tx(sb + RB_E, 8192);
            if (warp == 0) PROF(10);
            PROF(40 + warp);
        }
        bar_sync(NB_D, 384);
    }
}

__device__ __forceinline__ void rec_load_kv(uint32_t sb, int col0, int s, uint32_t slot_off, int t128) {
    const int row = t128 >> 2, c2 = (t128 & 3) * 2;
    const bf16* src = g_kv + ((size_t)(s * 32 + row) * (2 * HD_) + col0 + c2 * 8);
    const uint32_t d0 = sb + R_KX + slot_off + row * 128 + ((c2 ^ (row & 7)) << 4);
    cp_async16(d0, src);
    cp_async16(d0 ^ 16, src + 8);
    cp_async16(d0 + (R_VX - R_KX), src + HD_);
    cp_async16((d0 ^ 16) + (R_VX - R_KX), src + HD_ + 8);
}

__device__ __forceinline__ void rec_vo(const RecParams& p, const uint32_t sb, const int cta, const int warp, int lane) {
    const int w = warp - 8, crank = cta & 15;
    const int col0 = cta * 64;
    uint32_t wo[8][4][4];
    {
        const int t128 = w * 32 + lane;
        const bf16* Wo = p.wo + (size_t)col0 * D_;
        const uint32_t stg = sb + R_STG + 2 * 32768;
#pragma unroll
        for (int half = 0; half < 2; half++) {
#pragma unroll 4
            for (int i = t128; i < 2048; i += 128) {
                const int e = i >> 6, ch = i & 63;
                cp_async16(stg + e * 1024 + ((ch ^ (e & 7)) << 4), Wo + (size_t)(half * 32 + e) * D_ + ch * 8);
            }
            cp_async_commit();
            cp_async_wait<0>();
            bar_sync(NB_W0 + 2, 128);
#pragma unroll
            for (int j = 0; j < 8; j++)
#pragma unroll
                for (int kk = 0; kk < 2; kk++) {
                    const int e = kk * 16 + (lane >> 4) * 8 + (lane & 7);
                    const int ch = (w * 8 + j) * 2 + ((lane >> 3) & 1);
                    ldsm4t(wo[j][half * 2 + kk][0], wo[j][half * 2 + kk][1], wo[j][half * 2 + kk][2], wo[j][half * 2 + kk][3],
                           stg + e * 1024 + ((ch ^ (e & 7)) << 4));
                }
            bar_sync(NB_W0 + 2, 128);
        }
        if (lane == 0) wait_flag(F_KV + 0, 64);
        __syncwarp();
        rec_load_kv(sb, col0, 0, 0, t128); cp_async_commit();
        rec_load_kv(sb, col0, 1, 4096, t128); cp_async_commit();
        cp_async_wait<1>();
    }
    const uint32_t tab = sb + R_STG + 2 * 32768 + (w * 32 + lane) * 16;
    {
        const uint32_t l7 = lane & 7, l8 = lane >> 3, g = lane >> 2;
        uint4 v;
        v.x = sb + R_VX + ((l8 & 1) * 8 + l7) * 128 + (((2 * w + (l8 >> 1)) ^ l7) << 4);
        v.y = sb + R_OS + g * 128 + (((2 * w) ^ g) << 4) + (lane & 3) * 4;
        v.z = sb + R_VMS + l7 * 128 + (((2 * w + (l8 & 1)) ^ l7) << 4);
        v.w = sb + R_OS + l7 * 128 + ((l8 ^ l7) << 4);
        sts128(tab, v);
        v.x = mapa_u32(sb + R_RS + crank * 512 + ((lane ^ (crank & 7)) << 4), w * 4);
        v.y = mapa_u32(sb + RB_E, w * 4);
        v.z = sb + R_VP + w * 512 + lane * 16;
        v.w = sb + R_SX + lane * 8;
        sts128(tab + 2048, v);
#pragma unroll
        for (int i = 0; i < 8; i++) sts128(tab + 4096 + i * 2048, make_uint4(wo[i][0][0], wo[i][0][1], wo[i][0][2], wo[i][0][3]));
    }
    bar_sync(NB_D, 384);
    const uint32_t lane16 = lds32(tab + 2048 + 8) - R_VP - w * 512;
    uint4 av[2 * VK0];
#pragma unroll
    for (int i = 0; i < 2 * VK0; i++) av[i] = lds128(lane16 + R_WV + (i / VK0) * 32768 + (w * 16 + i % VK0) * 512);
    uint32_t slot_off = 0;
#pragma unroll 1
    for (int s = 0; s < NSEG; s++) {
        bar_sync(NB_Y, 288);
        uint32_t vb0, vb1;
        {
            float va[4] = {0.f, 0.f, 0.f, 0.f}, vc[4] = {0.f, 0.f, 0.f, 0.f};
            uint32_t bb[VK0][4];
#pragma unroll
            for (int k2 = 0; k2 < VK0; k2++) ldsm4(bb[k2][0], bb[k2][1], bb[k2][2], bb[k2][3], lane16 + R_MEM + (k2 / (VK0 / 2)) * 4096 + (k2 % (VK0 / 2)) * 512);
#pragma unroll
            for (int k2 = 0; k2 < VK0; k2++) {
                mma16816(va, av[2 * k2].x, av[2 * k2].y, av[2 * k2].z, av[2 * k2].w, bb[k2][0], bb[k2][1]);
                mma16816(vc, av[2 * k2 + 1].x, av[2 * k2 + 1].y, av[2 * k2 + 1].z, av[2 * k2 + 1].w, bb[k2][2], bb[k2][3]);
            }
            const uint4 a = lds128(lane16 + R_VP + w * 512), b = lds128(lane16 + R_VP + 2048 + w * 512);
            vb0 = pack2((va[0] + vc[0]) + (__uint_as_float(a.x) + __uint_as_float(b.x)), (va[1] + vc[1]) + (__uint_as_float(a.y) + __uint_as_float(b.y)));
            vb1 = pack2((va[2] + vc[2]) + (__uint_as_float(a.z) + __uint_as_float(b.z)), (va[3] + vc[3]) + (__uint_as_float(a.w) + __uint_as_float(b.w)));
        }
        const uint4 ta = lds128(tab), tb = lds128(tab + 2048);
        uint32_t vx[8];
        ldsm4t(vx[0], vx[1], vx[2], vx[3], ta.x + slot_off);
        ldsm4t(vx[4], vx[5], vx[6], vx[7], ta.x + slot_off + 2048);
#pragma unroll
        for (int i = 0; i < 4; i++) {
            const uint4 f0 = lds128(tab + 4096 + i * 2048);
            wo[i][0][0] = f0.x; wo[i][0][1] = f0.y; wo[i][0][2] = f0.z; wo[i][0][3] = f0.w;
        }
        if (w == 0) PROF(11);
        uint32_t pf[5];
        float oa[2][4] = {{0.f, 0.f, 0.f, 0.f}, {0.f, 0.f, 0.f, 0.f}}, ob_[2][4] = {{0.f, 0.f, 0.f, 0.f}, {0.f, 0.f, 0.f, 0.f}};
        float sm0[4] = {0.f, 0.f, 0.f, 0.f}, sm1[4] = {0.f, 0.f, 0.f, 0.f};
        if (s != NSEG - 1) {
            mbar_wait(sb + RB_SX, s & 1);
            if (w == 0) PROF(4);
            float sv[10];
#pragma unroll
            for (int n = 0; n < 5; n++) {
                const float2 a = lds64f(tb.w + n * 256), b = lds64f(tb.w + (5 + n) * 256);
                sv[2 * n] = a.x + b.x; sv[2 * n + 1] = a.y + b.y;
            }
            float mx = fmaxf(fmaxf(fmaxf(sv[0], sv[1]), fmaxf(sv[2], sv[3])), fmaxf(fmaxf(sv[4], sv[5]), fmaxf(sv[6], sv[7])));
            mx = fmaxf(mx, fmaxf(sv[8], sv[9]));
            mx = fmaxf(mx, __shfl_xor_sync(~0u, mx, 1));
            mx = fmaxf(mx, __shfl_xor_sync(~0u, mx, 2));
#pragma unroll
            for (int n = 1; n < 5; n++) pf[n] = pack2(ex2(sv[2 * n] - mx), ex2(sv[2 * n + 1] - mx));
            pf[0] = pack2(ex2(sv[0] - mx), ex2(sv[1] - mx));
            if (w == 0) PROF(12);
            const uint32_t one = 0x3F803F80u;
            mma16816h(sm0, pf[1], pf[2], one, one);
            mma16816h(oa[0], pf[1], pf[2], vx[0], vx[1]);
            mma16816h(oa[1], pf[1], pf[2], vx[2], vx[3]);
            mma16816h(sm1, pf[3], pf[4], one, one);
            mma16816h(ob_[0], pf[3], pf[4], vx[4], vx[5]);
            mma16816h(ob_[1], pf[3], pf[4], vx[6], vx[7]);
            mma1688h(sm0, pf[0], one);
            mma1688h(oa[0], pf[0], vb0);
            mma1688h(oa[1], pf[0], vb1);
            float inv;
            asm("rcp.approx.ftz.f32 %0, %1;" : "=f"(inv) : "f"(sm0[0] + sm1[0]));
            oa[0][0] += ob_[0][0]; oa[0][1] += ob_[0][1]; oa[1][0] += ob_[1][0]; oa[1][1] += ob_[1][1];
            sts32(ta.y, pack2(oa[0][0] * inv, oa[0][1] * inv));
            sts32(ta.y ^ 16, pack2(oa[1][0] * inv, oa[1][1] * inv));
            const uint32_t oa2 = ta.w ^ 64;
            bar_sync(NB_C, 128);
            if (w == 0) PROF(5);
            uint32_t ob[8];
            ldsm4(ob[0], ob[1], ob[2], ob[3], ta.w);
            ldsm4(ob[4], ob[5], ob[6], ob[7], oa2);
#pragma unroll
            for (int i = 4; i < 8; i++) {
                const uint4 f0 = lds128(tab + 4096 + i * 2048);
                wo[i][0][0] = f0.x; wo[i][0][1] = f0.y; wo[i][0][2] = f0.z; wo[i][0][3] = f0.w;
            }
#pragma unroll
            for (int jj = 0; jj < 2; jj++) {
                if (jj == 1 && tb.w == 0) break;
                float acc[4][4];
#pragma unroll
                for (int c = 0; c < 4; c++) { acc[c][0] = acc[c][1] = acc[c][2] = acc[c][3] = 0.f; }
#pragma unroll
                for (int ks = 0; ks < 4; ks++)
#pragma unroll
                    for (int c = 0; c < 4; c++)
                        mma16816(acc[c], wo[jj * 4 + c][ks][0], wo[jj * 4 + c][ks][1], wo[jj * 4 + c][ks][2], wo[jj * 4 + c][ks][3], ob[2 * ks], ob[2 * ks + 1]);
#pragma unroll
                for (int pr = 0; pr < 2; pr++) {
                    uint4 v;
                    v.x = pack2(acc[2 * pr][0], acc[2 * pr][1]);
                    v.y = pack2(acc[2 * pr][2], acc[2 * pr][3]);
                    v.z = pack2(acc[2 * pr + 1][0], acc[2 * pr + 1][1]);
                    v.w = pack2(acc[2 * pr + 1][2], acc[2 * pr + 1][3]);
                    st_async_v4(tb.x + ((jj * 2 + pr) << 24), v, tb.y + ((jj * 2 + pr) << 24));
                }
            }
            if (w == 0) PROF(6);
        }
        {
            stsm2t(ta.z, vb0, vb1);
            cp_async_wait<0>();
            bar_sync(NB_C, 128);
            if (w == 0 && lane == 0 && s != NSEG - 1) mbar_expect_tx(sb + RB_SX, 2560);
            const int omat = w >> 1, otok = (w & 1) * 4 + (lane >> 3), och = lane & 7;
            const uint4 v = lds128(sb + (omat ? R_VMS : R_KMS) + otok * 128 + ((och ^ otok) << 4));
            *(uint4*)(g_kvm + ((s * 8 + otok) * (2 * HD_) + omat * HD_ + col0 + och * 8)) = v;
            if (s != NSEG - 1) bar_arrive(NB_D, 384);
#pragma unroll
            for (int i = 0; i < 2 * VK0; i++) av[i] = lds128(lane16 + R_WV + (i / VK0) * 32768 + (w * 16 + i % VK0) * 512);
            if (s + 2 < NSEG - 1) {
                if (((s + 2) & 3) == 0) { if (lane == 0) wait_flag(F_KV + ((s + 2) >> 2), 64); __syncwarp(); }
                rec_load_kv(sb, col0, s + 2, slot_off == 0 ? (R_NST - 1) * 4096 : slot_off - 4096, w * 32 + lane);
            }
            cp_async_commit();
            if ((s & 3) == 3) {
                bar_sync(NB_C, 128);
                if (w == 0 && lane == 0) red_release(&g_flags[F_MEM + (s >> 2)], 1);
            }
        }
        slot_off = slot_off == (R_NST - 1) * 4096 ? 0 : slot_off + 4096;
    }
}

__global__ void __launch_bounds__(384, 1) k_rec(const RecParams p) {
    extern __shared__ __align__(1024) unsigned char smem_raw[];
    const uint32_t sb = __shfl_sync(~0u, smem_u32(smem_raw), 0);
    const int warp = __shfl_sync(~0u, threadIdx.x >> 5, 0);
    int lane; asm volatile("mov.u32 %0, %%laneid;" : "=r"(lane));
    const int crank = blockIdx.x & 15, slot = blockIdx.x >> 4;
    asm volatile("griddepcontrol.launch_dependents;");
    if (threadIdx.x == 0) {
        mbar_init(sb + RB_SX, 1); mbar_init(sb + RB_E, 1); mbar_init(sb + RB_A, 1); mbar_init(sb + RB_ROLE, 1);
        asm volatile("fence.mbarrier_init.release.cluster;" ::: "memory");
        mbar_expect_tx(sb + RB_SX, 2560);
        mbar_expect_tx(sb + RB_E, 8192);
        mbar_expect_tx(sb + RB_A, 8192);
        mbar_expect_tx(sb + RB_ROLE, 4);
    }
    unsigned role = 0;
    if (crank == 0 && threadIdx.x == 0) {
        unsigned x = 0;
        int tm[2] = {0x7fffffff, 0x7fffffff};
#pragma unroll 1
        for (int i = 0; i < 6; i++) {
            const uint32_t t0 = clk32();
            x = atomicAdd(&g_F[65536 + (i & 1) * 1024 + slot * 64 + (x >> 31)], 0u) & 0x7fffffffu;
            if (x == 0x7654321u) sts32(sb + R_BAR + 56, x);
            const int dt = (int)(clk32() - t0);
            if (i >= 2) { if (i & 1) tm[1] = min(tm[1], dt); else tm[0] = min(tm[0], dt); }
        }
        const int side = tm[1] > tm[0];
        const unsigned old = atomicAdd(&g_flags[F_SIDE + side * 32], 1u);
        unsigned c0, c1; int gd = 0;
#pragma unroll 1
        do { c0 = ldg_relaxed32(&g_flags[F_SIDE]); c1 = ldg_relaxed32(&g_flags[F_SIDE + 32]); } while ((int)(c0 + c1) < p.ncl && ++gd < 64 * SPIN_LIMIT);
        const int big = c1 > c0;
        role = side == big ? old : (big ? c1 : c0) + old;
        role |= (big ^ 1) << 8;
    }
    __syncwarp();
    asm volatile("barrier.cluster.arrive.relaxed.aligned;\nbarrier.cluster.wait.aligned;" ::: "memory");
    if (crank == 0 && warp == 0) {
        role = __shfl_sync(~0u, role, 0);
        if (lane < 16)
            asm volatile("st.async.weak.shared::cluster.mbarrier::complete_tx::bytes.u32 [%0], %1, [%2];"
                         :: "r"(mapa_u32(sb + R_BAR + 48, lane)), "r"(role), "r"(mapa_u32(sb + RB_ROLE, lane)) : "memory");
    }
    mbar_wait(sb + RB_ROLE, 0);
    const int rolew = __shfl_sync(~0u, lds32(sb + R_BAR + 48), 0);
    const int cl = rolew & 255;
    if (cl >= 4) return;
    const int cta = cl * 16 + crank;
    if (warp < 8) rec_qk(p, sb, cta, warp, lane, rolew >> 8);
    else rec_vo(p, sb, cta, warp, lane);
}

enum { J_KV = 0, J_QA = 1, J_O = 2, J_LN = 3, J_UP = 4, J_DN = 5, J_UP2 = 6, J_END = 8 };
constexpr int NJ_O = 2 * OSPLIT, NJ_O2 = 2 * OSPLIT2, NJ_LN = 8, NJ_LN2 = 16, NJ_UP = 14, NJ_UP2 = 28, NJ_DN = 8;
__device__ __forceinline__ int nj_coarse(int q) { return q == J_KV ? 32 : (q == J_QA ? 16 : (q == J_O ? NJ_O : (q == J_LN ? NJ_LN : (q == J_UP ? NJ_UP : NJ_DN)))); }
__device__ __forceinline__ int nj_fine(int q) { return q == J_KV ? 32 : (q == J_QA ? 16 : (q == J_O ? NJ_O2 : (q == J_LN ? NJ_LN2 : (q == J_UP ? NJ_UP2 : NJ_DN)))); }
__device__ __forceinline__ int pick_job(int lane, int qmask, int& idx) {
    const int rb = lane & 15, half = lane >> 4;
    const bool fine = rb >= FINE_RB;
    int gd = 0;
#pragma unroll 1
    while (true) {
        unsigned cl[3], dp[3];
#pragma unroll
        for (int i = 0; i < 3; i++) {
            const int q = half + 2 * i;
            cl[i] = ldg_relaxed32(&g_flags[F_CLAIM + q * 32 + rb]);
            dp[i] = ldg_relaxed32(&g_flags[q * 32 + (q == J_QA ? max(rb - 1, 0) : rb)]);
        }
        int pick_q = -1, pick_rb = 0, early_q = -1, early_rb = 0;
        bool any = false;
#pragma unroll
        for (int i = 0; i < 3; i++) {
            const int q = half + 2 * i;
            const bool have = ((qmask >> q) & 1) && (int)cl[i] < (fine ? nj_fine(q) : nj_coarse(q));
            const unsigned tgt = q == J_QA ? 64 : 2 * (fine ? nj_fine(q - 1) : nj_coarse(q - 1));
            const bool ready = have && (q == J_KV || (q == J_QA && rb == 0) || dp[i] >= tgt);
            const unsigned mh = __ballot_sync(~0u, have), mr = __ballot_sync(~0u, ready);
            any |= mh != 0;
#pragma unroll
            for (int hf = 0; hf < 2; hf++) {
                const int qq = hf + 2 * i;
                const unsigned r16 = (mr >> (16 * hf)) & 0xffffu, h16 = (mh >> (16 * hf)) & 0xffffu;
                if (r16 && pick_q != J_KV) { pick_q = qq; pick_rb = __ffs(r16) - 1; }
                if (qq >= J_O && early_q < 0 && h16 && __ffs(h16) - 1 >= FINE_RB) { early_q = qq; early_rb = __ffs(h16) - 1; }
            }
        }
        if (!any) return J_END;
        if (pick_q < 0) { pick_q = early_q; pick_rb = early_rb; }
        if (pick_q >= 0) {
            int c = 0;
            if (lane == 0) c = (int)atomicAdd(&g_flags[F_CLAIM + pick_q * 32 + pick_rb], 1u);
            c = __shfl_sync(~0u, c, 0);
            const bool f = pick_rb >= FINE_RB;
            if (c < (f ? nj_fine(pick_q) : nj_coarse(pick_q))) {
                idx = pick_q * 600 + pick_rb * 32 + c;
                return (pick_q == J_UP && f ? J_UP2 : pick_q) | (pick_rb << 8) | (c << 16);
            }
        } else {
            __nanosleep(200);
            if (++gd > 16 * SPIN_LIMIT) { TIMEOUT(5, 0); return J_END; }
        }
    }
}
__device__ __forceinline__ int op_row(int rb, int split) {
    return rb < FINE_RB ? split * S_ + rb * 128 : OSPLIT * S_ + (split * (NRB - FINE_RB) + rb - FINE_RB) * 128;
}

struct Pipe { uint32_t stage, phase; };
__device__ __forceinline__ void pipe_next(Pipe& p) { if (++p.stage == W_NST) { p.stage = 0; p.phase ^= 1; } }

__device__ __forceinline__ void producer(const Params& p, uint32_t sb, int lane) {
    Pipe pp{0, 1};
    const uint32_t bars = sb + SM_BAR;
    uint32_t seq = 0;
#pragma unroll 1
    while (true) {
        __syncwarp();
        int j = 4095;
        const int jd = pick_job(lane, p.qmask, j);
        if (lane != 0) { if (jd == J_END) break; continue; }
        TR(j, 1);
        const int type = jd & 255, rb = (jd >> 8) & 255, cb = jd >> 16;
        const bool fine = rb >= FINE_RB;
        bool first = true;
        auto begin_stage = [&](uint32_t bytes) -> uint32_t {
            mbar_wait(bars + B_EMPTY + pp.stage * 8, pp.phase);
            if (first) { sts32(bars + B_RING + (seq & 7) * 4, (uint32_t)jd); sts32(bars + B_RING + 32 + (seq & 7) * 4, (uint32_t)j); first = false; }
            const uint32_t fb = bars + B_FULL + pp.stage * 8;
            if (bytes) mbar_expect_tx(fb, bytes); else mbar_arrive(fb);
            return fb;
        };
        if (type == J_END || type == J_LN) {
            if (type == J_LN) wait_flag(F_OP + rb, 2 * (fine ? NJ_O2 : NJ_O));
            TR(j, 2);
            begin_stage(0); pipe_next(pp);
            seq++;
            if (type == J_END) break;
            continue;
        }
        const CUtensorMap *ta, *tb0, *tb1;
        int k0 = 0, nk = 8, n0 = cb * 256, n1 = n0 + 128, nb = 4, dep = -1;
        unsigned tgt = 0;
        switch (type) {
            case J_KV: ta = &p.tm_h; tb0 = tb1 = cb < 16 ? &p.tm_wk : &p.tm_wv; n0 = (cb & 15) * 256; n1 = n0 + 128; break;
            case J_QA: ta = &p.tm_h; tb0 = tb1 = &p.tm_wq; break;
            case J_O: ta = &p.tm_o; tb0 = tb1 = &p.tm_wo; n0 = (cb & 1) * 256; n1 = n0 + 128; nk = fine ? 64 / OSPLIT2 : 64 / OSPLIT; k0 = (cb >> 1) * nk * 64;
                      dep = F_O + rb; tgt = 32; break;
            case J_UP: ta = &p.tm_h2; tb0 = &p.tm_wg; tb1 = &p.tm_wu; n0 = n1 = cb * 128; dep = F_H2 + rb; tgt = 2 * NJ_LN; break;
            case J_UP2: ta = &p.tm_h2; tb0 = &p.tm_wg; tb1 = &p.tm_wu; n0 = n1 = cb * 64; nb = 2; dep = F_H2 + rb; tgt = 2 * NJ_LN2; break;
            default: ta = &p.tm_act; tb0 = tb1 = &p.tm_wd; n0 = cb * 64; nk = 0; break;
        }
        const int m0 = rb * 128;
        if (type == J_DN) {
#pragma unroll 1
            for (int kb = 0; kb < 14; kb++) {
                const uint32_t fb = begin_stage(49152);
                const uint32_t st = sb + pp.stage * W_STAGE;
                const int k = kb * 128;
                tma_load2d(st + 32768, tb0, n0, k, fb);
                tma_load2d(st + 40960, tb0, n0, k + 64, fb);
                if (kb == 0) { wait_flag(F_ACT + rb, 2 * (fine ? NJ_UP2 : NJ_UP)); fence_async_all(); TR(j, 2); }
                tma_load2d(st, ta, k, m0, fb);
                tma_load2d(st + 8192, ta, k, m0 + 64, fb);
                tma_load2d(st + 16384, ta, k + 64, m0, fb);
                tma_load2d(st + 24576, ta, k + 64, m0 + 64, fb);
                pipe_next(pp);
            }
        }
#pragma unroll 1
        for (int kb = 0; kb < nk; kb++) {
            const uint32_t fb = begin_stage(16384 + nb * 8192);
            const uint32_t st = sb + pp.stage * W_STAGE;
            const int k = k0 + kb * 64;
            tma_load2d(st + 16384, tb0, n0, k, fb);
            if (nb == 4) {
                tma_load2d(st + 16384 + 8192, tb0, n0 + 64, k, fb);
                tma_load2d(st + 16384 + 16384, tb1, n1, k, fb);
                tma_load2d(st + 16384 + 24576, tb1, n1 + 64, k, fb);
            } else if (nb == 2) {
                tma_load2d(st + 16384 + 8192, tb1, n1, k, fb);
            }
            if (kb == 0) {
                if (dep >= 0) { wait_flag(dep, tgt); if (type >= J_UP) fence_async_all(); }
                TR(j, 2);
            }
            tma_load2d(st, ta, k, m0, fb);
            tma_load2d(st + 8192, ta, k, m0 + 64, fb);
            pipe_next(pp);
        }
        if (type == J_QA) {
            wait_flag(F_KV + rb, 64);
#pragma unroll 1
            for (int i = 0; i < 4; i++) {
                const uint32_t fb = begin_stage(40960);
                const uint32_t st = sb + pp.stage * W_STAGE;
                const int col = (i & 1) * HD_ + (cb * 2 + (i >> 1)) * DH_;
                tma_load2d(st, &p.tm_kv, col, m0, fb);
                tma_load2d(st + 8192, &p.tm_kv, col, m0 + 64, fb);
                tma_load2d(st + 16384, &p.tm_kv, col + 64, m0, fb);
                tma_load2d(st + 24576, &p.tm_kv, col + 64, m0 + 64, fb);
                if (i == 0) { wait_flag(F_MEM + rb, 64); fence_async_all(); }
                tma_load2d(st + 32768, &p.tm_kvm, col, rb * 32, fb);
                tma_load2d(st + 36864, &p.tm_kvm, col + 64, rb * 32, fb);
                pipe_next(pp);
            }
        } else if (type == J_DN) {
            const uint32_t fb = begin_stage(16384);
            const uint32_t st = sb + pp.stage * W_STAGE;
            tma_load2d(st, &p.tm_x1, n0, m0, fb);
            tma_load2d(st + 8192, &p.tm_x1, n0, m0 + 64, fb);
            pipe_next(pp);
        }
        seq++;
    }
}

__device__ __forceinline__ void store_warp(const Params& p, uint32_t sb, int wg, int lane) {
    const uint32_t bars = sb + SM_BAR;
    uint32_t seq = 0;
#pragma unroll 1
    while (true) {
        bar_sync(NB_ST + wg, 160);
        const uint32_t jd = lds32(bars + B_RING + (seq & 7) * 4);
        seq++;
        const int type = jd & 255, rb = (jd >> 8) & 255, cb = jd >> 16;
        if (type == J_END) break;
        if (lane == 0) {
            const uint32_t src = sb + W_STG + wg * 32768;
            const CUtensorMap* tm = nullptr; int n0 = cb * 256, nbox = 4, mrow = rb * 128 + wg * 64, flag = 0;
            switch (type) {
                case J_KV: tm = &p.tm_kv; flag = F_KV + rb; break;
                case J_QA: tm = &p.tm_o; flag = F_O + rb; break;
                case J_O: tm = &p.tm_op; n0 = (cb & 1) * 256; mrow = op_row(rb, cb >> 1) + wg * 64; flag = F_OP + rb; break;
                case J_LN: flag = F_H2 + rb; nbox = 0; break;
                case J_UP: tm = &p.tm_act; n0 = cb * 128; nbox = 2; flag = F_ACT + rb; break;
                case J_UP2: tm = &p.tm_act; n0 = cb * 64; nbox = 1; flag = F_ACT + rb; break;
                default: tm = &p.tm_out; n0 = cb * 64; nbox = 1; flag = -1; break;
            }
#pragma unroll 1
            for (int b = 0; b < nbox; b++) tma_store2d(tm, src + b * 8192, n0 + b * 64, mrow);
            bulk_commit();
            bulk_wait0();
            mbar_arrive(bars + B_STGFREE + wg * 8);
            if (flag >= 0) red_release(&g_flags[flag], 1);
        }
        __syncwarp();
    }
}

__device__ __forceinline__ float gelu_tanh(float x) {
    const float t = x * fmaf(-0.10294324397f, x * x, -2.30220819814f);
    float r; asm("rcp.approx.ftz.f32 %0, %1;" : "=f"(r) : "f"(1.f + ex2(t)));
    return x * r;
}

#define CTR(i) do {} while (0)

template <int NSPLIT>
__device__ __forceinline__ void ln2_row(const Params& p, int rb, int r, int lane) {
    const int row = rb * 128 + r;
    uint4 u[2 * NSPLIT];
#pragma unroll
    for (int sp = 0; sp < NSPLIT; sp++) {
        const uint4* src = (const uint4*)(g_op + (size_t)(op_row(rb, sp) + r) * D_);
        u[2 * sp] = __ldcg(src + lane); u[2 * sp + 1] = __ldcg(src + 32 + lane);
    }
    const uint4* xr = (const uint4*)(p.x + (size_t)row * D_);
    const uint4 xa = __ldg(xr + lane), xb = __ldg(xr + 32 + lane);
    uint32_t ga[8], c1[8], sm[8];
    load_mod8(g_mod + 2 * D_, lane, ga);
    load_mod8(g_mod + 4 * D_, lane, c1);
    load_mod8(g_mod + 3 * D_, lane, sm);
    float a[16];
#pragma unroll
    for (int i = 0; i < 16; i++) a[i] = 0.f;
#pragma unroll
    for (int sp = 0; sp < 2 * NSPLIT; sp++) {
        float* q = a + (sp & 1) * 8;
        q[0] += bflo(u[sp].x); q[1] += bfhi(u[sp].x); q[2] += bflo(u[sp].y); q[3] += bfhi(u[sp].y);
        q[4] += bflo(u[sp].z); q[5] += bfhi(u[sp].z); q[6] += bflo(u[sp].w); q[7] += bfhi(u[sp].w);
    }
    const uint32_t xv[8] = {xa.x, xa.y, xa.z, xa.w, xb.x, xb.y, xb.z, xb.w};
    uint32_t v[8], r8[8];
#pragma unroll
    for (int i = 0; i < 8; i++) v[i] = hadd2(xv[i], hmul2(ga[i], pack2(a[2 * i], a[2 * i + 1])));
    uint4* x1r = (uint4*)(g_x1 + (size_t)row * D_);
    x1r[lane] = make_uint4(v[0], v[1], v[2], v[3]); x1r[32 + lane] = make_uint4(v[4], v[5], v[6], v[7]);
    uint32_t mu2; float rden;
    ln_stats(v, mu2, rden);
#pragma unroll
    for (int i = 0; i < 8; i++) c1[i] = hadd2(c1[i], 0x3F803F80u);
    ln_apply(v, mu2, rden, c1, sm, r8);
    uint4* hr = (uint4*)(g_h2 + (size_t)row * D_);
    hr[lane] = make_uint4(r8[0], r8[1], r8[2], r8[3]); hr[32 + lane] = make_uint4(r8[4], r8[5], r8[6], r8[7]);
}

__device__ __forceinline__ void consumer(const Params& p, uint32_t sb, int warp, int lane) {
    const uint32_t bars = sb + SM_BAR;
    const int wg = warp >> 2, wl = warp & 3;
    const uint32_t l7 = lane & 7, l8 = lane >> 3, g = lane >> 2, t = lane & 3;
    Pipe pp{0, 0};
    uint32_t seq = 0, stg_phase = 1;
    const int srow = wl * 16 + l7 + (l8 & 1) * 8;
    const uint32_t stg_base = sb + W_STG + wg * 32768 + srow * 128;
    const uint32_t sx = ((lane >> 4) ^ (srow & 7)) << 4;
#pragma unroll 1
    while (true) {
        mbar_wait(bars + B_FULL + pp.stage * 8, pp.phase);
        const uint32_t jd = lds32(bars + B_RING + (seq & 7) * 4);
        CTR(3);
        seq++;
        const int type = jd & 255, rb = (jd >> 8) & 255, cb = jd >> 16;
        if (type == J_END) { mbar_wait(bars + B_STGFREE + wg * 8, stg_phase); bar_arrive(NB_ST + wg, 160); break; }
        if (type == J_LN) {
            __syncwarp();
            if (lane == 0) mbar_arrive(bars + B_EMPTY + pp.stage * 8);
            pipe_next(pp);
            if (rb >= FINE_RB) ln2_row<OSPLIT2>(p, rb, cb * 8 + warp, lane);
            else {
#pragma unroll 1
                for (int rr = 0; rr < 2; rr++) ln2_row<OSPLIT>(p, rb, cb * 16 + warp * 2 + rr, lane);
            }
            mbar_wait(bars + B_STGFREE + wg * 8, stg_phase); stg_phase ^= 1;
            CTR(4); CTR(5);
            bar_arrive(NB_ST + wg, 160);
            continue;
        }
        if (type >= J_DN) {
            float acc[64];
#pragma unroll
            for (int i = 0; i < 64; i++) acc[i] = 0.f;
            if (type == J_DN) {
#pragma unroll 1
                for (int kb = 0; kb < 14; kb++) {
                    if (kb) mbar_wait(bars + B_FULL + pp.stage * 8, pp.phase);
                    const uint32_t st = sb + pp.stage * W_STAGE;
                    const uint64_t da = mkdesc(st + wg * 8192, 16, 1024), db = mkdesc(st + 32768, 8192, 1024);
                    wg_fence();
#pragma unroll
                    for (int ks = 0; ks < 8; ks++) wgmma_n64(acc, da + (ks >> 2) * 1024 + (ks & 3) * 2, db + ks * 128);
                    wg_commit();
                    wg_wait0();
                    if (lane == 0) mbar_arrive(bars + B_EMPTY + pp.stage * 8);
                    pipe_next(pp);
                }
            } else {
#pragma unroll 1
                for (int kb = 0; kb < 8; kb++) {
                    if (kb) mbar_wait(bars + B_FULL + pp.stage * 8, pp.phase);
                    const uint32_t st = sb + pp.stage * W_STAGE;
                    const uint64_t da = mkdesc(st + wg * 8192, 16, 1024), db = mkdesc(st + 16384, 8192, 1024);
                    wg_fence();
#pragma unroll
                    for (int ks = 0; ks < 4; ks++) wgmma_n128(acc, da + ks * 2, db + ks * 128, 1);
                    wg_commit();
                    wg_wait0();
                    if (lane == 0) mbar_arrive(bars + B_EMPTY + pp.stage * 8);
                    pipe_next(pp);
                }
            }
            CTR(4);
            if (type == J_UP2) {
                mbar_wait(bars + B_STGFREE + wg * 8, stg_phase); stg_phase ^= 1;
#pragma unroll
                for (int j = 0; j < 4; j++) {
                    uint32_t r[4];
#pragma unroll
                    for (int q = 0; q < 4; q++) {
                        const uint32_t gw = pack2(acc[8 * j + 2 * q], acc[8 * j + 2 * q + 1]);
                        const uint32_t uw = pack2(acc[32 + 8 * j + 2 * q], acc[32 + 8 * j + 2 * q + 1]);
                        r[q] = hmul2(pack2(gelu_tanh(bflo(gw)), gelu_tanh(bfhi(gw))), uw);
                    }
                    stsm4(stg_base + (sx ^ (j << 5)), r[0], r[1], r[2], r[3]);
                }
            } else {
                mbar_wait(bars + B_FULL + pp.stage * 8, pp.phase);
                const uint32_t st = sb + pp.stage * W_STAGE;
                mbar_wait(bars + B_STGFREE + wg * 8, stg_phase); stg_phase ^= 1;
                const uint32_t* gb = (const uint32_t*)(g_mod + 5 * D_ + cb * 64) + t;
                const uint32_t xa = st + wg * 8192 + (wl * 16 + g) * 128 + (g << 4) + t * 4;
#pragma unroll
                for (int j = 0; j < 4; j++) {
                    uint32_t r[4];
#pragma unroll
                    for (int q = 0; q < 4; q++) {
                        const int nt = 2 * j + (q >> 1);
                        const uint32_t xw = lds32((xa ^ ((nt & 7) << 4)) + (nt >> 3) * 16384 + (q & 1) * 1024);
                        r[q] = hadd2(xw, hmul2(__ldcg(gb + nt * 4), pack2(acc[8 * j + 2 * q], acc[8 * j + 2 * q + 1])));
                    }
                    stsm4(stg_base + (j >> 2) * 8192 + (sx ^ ((2 * j & 7) << 4)), r[0], r[1], r[2], r[3]);
                }
                __syncwarp();
                if (lane == 0) mbar_arrive(bars + B_EMPTY + pp.stage * 8);
                pipe_next(pp);
            }
            fence_async_smem();
            CTR(5);
            bar_arrive(NB_ST + wg, 160);
            continue;
        }
        float acc[128];
#pragma unroll
        for (int i = 0; i < 128; i++) acc[i] = 0.f;
        const int nk = type == J_O ? (rb >= FINE_RB ? 64 / OSPLIT2 : 64 / OSPLIT) : 8;
#pragma unroll 1
        for (int kb = 0; kb < nk; kb++) {
            if (kb) mbar_wait(bars + B_FULL + pp.stage * 8, pp.phase);
            const uint32_t st = sb + pp.stage * W_STAGE;
            const uint64_t da = mkdesc(st + wg * 8192, 16, 1024), db = mkdesc(st + 16384, 8192, 1024);
            wg_fence();
#pragma unroll
            for (int ks = 0; ks < 4; ks++) wgmma_n256(acc, da + ks * 2, db + ks * 128, 1);
            wg_commit();
            wg_wait0();
            if (lane == 0) mbar_arrive(bars + B_EMPTY + pp.stage * 8);
            pipe_next(pp);
        }
        CTR(4);
        if (type == J_QA) {
            uint32_t qf[64];
#pragma unroll
            for (int i = 0; i < 64; i++) qf[i] = pack2(acc[2 * i], acc[2 * i + 1]);
            const int sg = warp >> 1, half = warp & 1;
            const float sc = 0.08838834764831845f * 1.4426950408889634f;
            const uint32_t xoff = (sg >> 1) * 8192 + ((sg & 1) * 32 + l7) * 128;
            const uint32_t moff = 32768 + (sg * 8 + l7) * 128;
            const uint32_t kch = (l8 ^ l7) << 4;
            const uint32_t vch = ((l8 & 1) ^ l7) << 4;
            mbar_wait(bars + B_STGFREE + wg * 8, stg_phase); stg_phase ^= 1;
#pragma unroll
            for (int hh = 0; hh < 2; hh++) {
                mbar_wait(bars + B_FULL + pp.stage * 8, pp.phase);
                uint32_t st = sb + pp.stage * W_STAGE;
                float sa[5][4];
#pragma unroll
                for (int n = 0; n < 5; n++) sa[n][0] = sa[n][1] = sa[n][2] = sa[n][3] = 0.f;
#pragma unroll
                for (int i = 0; i < 4; i++) {
                    const uint32_t* q = qf + hh * 32 + i * 8;
                    uint32_t kk[5][4];
                    ldsm4(kk[0][0], kk[0][1], kk[0][2], kk[0][3], st + moff + (i >> 1) * 4096 + (kch ^ ((i & 1) * 64)));
#pragma unroll
                    for (int n = 1; n < 5; n++)
                        ldsm4(kk[n][0], kk[n][1], kk[n][2], kk[n][3], st + xoff + (n - 1) * 1024 + (i >> 1) * 16384 + (kch ^ ((i & 1) * 64)));
#pragma unroll
                    for (int n = 0; n < 5; n++) mma16816(sa[n], q[0], q[1], q[2], q[3], kk[n][0], kk[n][1]);
#pragma unroll
                    for (int n = 0; n < 5; n++) mma16816(sa[n], q[4], q[5], q[6], q[7], kk[n][2], kk[n][3]);
                }
                __syncwarp();
                if (lane == 0) mbar_arrive(bars + B_EMPTY + pp.stage * 8);
                pipe_next(pp);
                const int iq0 = half * 16 + g - 2 * t, iq1 = iq0 + 8;
                float m0 = fmaxf(sa[0][0], sa[0][1]), m1 = fmaxf(sa[0][2], sa[0][3]);
#pragma unroll
                for (int n = 1; n < 5; n++) {
#pragma unroll
                    for (int e = 0; e < 2; e++) {
                        const int jx = (n - 1) * 8 + e;
                        if (jx > iq0) sa[n][e] = -3.0e38f;
                        if (jx > iq1) sa[n][2 + e] = -3.0e38f;
                        m0 = fmaxf(m0, sa[n][e]); m1 = fmaxf(m1, sa[n][2 + e]);
                    }
                }
                m0 = fmaxf(m0, __shfl_xor_sync(~0u, m0, 1)); m1 = fmaxf(m1, __shfl_xor_sync(~0u, m1, 1));
                m0 = fmaxf(m0, __shfl_xor_sync(~0u, m0, 2)); m1 = fmaxf(m1, __shfl_xor_sync(~0u, m1, 2));
                m0 *= -sc; m1 *= -sc;
                float l0 = 0.f, l1 = 0.f;
                uint32_t p0[5], p1[5];
#pragma unroll
                for (int n = 0; n < 5; n++) {
                    const float e0 = ex2(fmaf(sa[n][0], sc, m0)), e1 = ex2(fmaf(sa[n][1], sc, m0));
                    const float e2 = ex2(fmaf(sa[n][2], sc, m1)), e3 = ex2(fmaf(sa[n][3], sc, m1));
                    l0 += e0 + e1; l1 += e2 + e3;
                    p0[n] = pack2(e0, e1); p1[n] = pack2(e2, e3);
                }
                l0 += __shfl_xor_sync(~0u, l0, 1); l1 += __shfl_xor_sync(~0u, l1, 1);
                l0 += __shfl_xor_sync(~0u, l0, 2); l1 += __shfl_xor_sync(~0u, l1, 2);
                const float i0 = __fdividef(1.f, l0), i1 = __fdividef(1.f, l1);
                mbar_wait(bars + B_FULL + pp.stage * 8, pp.phase);
                st = sb + pp.stage * W_STAGE;
#pragma unroll
                for (int bx = 0; bx < 2; bx++) {
                    float o[8][4];
                    uint32_t vm[8], v0[4][4], v1[4][4];
#pragma unroll
                    for (int ep = 0; ep < 4; ep++) {
                        ldsm2t(vm[2 * ep], vm[2 * ep + 1], st + moff + bx * 4096 + (vch ^ (ep << 5)));
                        const uint32_t va = st + xoff + (l8 >> 1) * 1024 + bx * 16384 + (vch ^ (ep << 5));
                        ldsm4t(v0[ep][0], v0[ep][1], v0[ep][2], v0[ep][3], va);
                        ldsm4t(v1[ep][0], v1[ep][1], v1[ep][2], v1[ep][3], va + 2048);
                    }
#pragma unroll
                    for (int n = 0; n < 8; n++) { o[n][0] = o[n][1] = o[n][2] = o[n][3] = 0.f; mma16816(o[n], p0[0], p1[0], p0[1], p1[1], vm[n], v0[n >> 1][n & 1]); }
#pragma unroll
                    for (int n = 0; n < 8; n++) mma16816(o[n], p0[2], p1[2], p0[3], p1[3], v0[n >> 1][2 + (n & 1)], v1[n >> 1][n & 1]);
#pragma unroll
                    for (int n = 0; n < 8; n++) mma1688(o[n], p0[4], p1[4], v1[n >> 1][2 + (n & 1)]);
#pragma unroll
                    for (int ep = 0; ep < 4; ep++)
                        stsm4(stg_base + (hh * 2 + bx) * 8192 + (sx ^ (ep << 5)),
                              pack2(o[2 * ep][0] * i0, o[2 * ep][1] * i0), pack2(o[2 * ep][2] * i1, o[2 * ep][3] * i1),
                              pack2(o[2 * ep + 1][0] * i0, o[2 * ep + 1][1] * i0), pack2(o[2 * ep + 1][2] * i1, o[2 * ep + 1][3] * i1));
                }
                __syncwarp();
                if (lane == 0) mbar_arrive(bars + B_EMPTY + pp.stage * 8);
                pipe_next(pp);
            }
        } else if (type == J_UP) {
            mbar_wait(bars + B_STGFREE + wg * 8, stg_phase); stg_phase ^= 1;
#pragma unroll
            for (int j = 0; j < 8; j++) {
                uint32_t r[4];
#pragma unroll
                for (int q = 0; q < 4; q++) {
                    const uint32_t gw = pack2(acc[8 * j + 2 * q], acc[8 * j + 2 * q + 1]);
                    const uint32_t uw = pack2(acc[64 + 8 * j + 2 * q], acc[64 + 8 * j + 2 * q + 1]);
                    r[q] = hmul2(pack2(gelu_tanh(bflo(gw)), gelu_tanh(bfhi(gw))), uw);
                }
                stsm4(stg_base + (j >> 2) * 8192 + (sx ^ ((2 * j & 7) << 4)), r[0], r[1], r[2], r[3]);
            }
        } else {
            mbar_wait(bars + B_STGFREE + wg * 8, stg_phase); stg_phase ^= 1;
#pragma unroll
            for (int j = 0; j < 16; j++)
                stsm4(stg_base + (j >> 2) * 8192 + (sx ^ ((2 * j & 7) << 4)),
                      pack2(acc[8 * j], acc[8 * j + 1]), pack2(acc[8 * j + 2], acc[8 * j + 3]),
                      pack2(acc[8 * j + 4], acc[8 * j + 5]), pack2(acc[8 * j + 6], acc[8 * j + 7]));
        }
        fence_async_smem();
        CTR(5);
        bar_arrive(NB_ST + wg, 160);
    }
}

__global__ void __launch_bounds__(384, 1) k_work(const __grid_constant__ Params p) {
    extern __shared__ __align__(1024) unsigned char smem_raw[];
    const uint32_t sb = smem_u32(smem_raw);
    if (sb & 1023) __trap();
    const int warp = __shfl_sync(~0u, threadIdx.x >> 5, 0);
    int lane; asm volatile("mov.u32 %0, %%laneid;" : "=r"(lane));
    if (threadIdx.x == 0) {
        const uint32_t bars = sb + SM_BAR;
        for (int i = 0; i < W_NST; i++) { mbar_init(bars + B_FULL + i * 8, 1); mbar_init(bars + B_EMPTY + i * 8, 8); }
        mbar_init(bars + B_STGFREE, 1); mbar_init(bars + B_STGFREE + 8, 1);
        asm volatile("fence.mbarrier_init.release.cluster;" ::: "memory");
    }
    __syncthreads();
    if (warp < 8) {
        asm volatile("setmaxnreg.inc.sync.aligned.u32 232;");
        consumer(p, sb, warp, lane);
    } else {
        asm volatile("setmaxnreg.dec.sync.aligned.u32 40;");
        if (warp == 8) producer(p, sb, lane);
        else if (warp < 11) store_warp(p, sb, warp - 9, lane);
    }
}

typedef CUresult (*EncodeFn)(CUtensorMap*, CUtensorMapDataType, cuuint32_t, void*, const cuuint64_t*, const cuuint64_t*,
                             const cuuint32_t*, const cuuint32_t*, CUtensorMapInterleave, CUtensorMapSwizzle,
                             CUtensorMapL2promotion, CUtensorMapFloatOOBfill);

static void make_map(EncodeFn enc, CUtensorMap* m, const void* ptr, uint64_t rows, uint64_t cols, uint32_t box_rows) {
    cuuint64_t dims[2] = {cols, rows};
    cuuint64_t strides[1] = {cols * 2};
    cuuint32_t box[2] = {64, box_rows};
    cuuint32_t es[2] = {1, 1};
    enc(m, CU_TENSOR_MAP_DATA_TYPE_BFLOAT16, 2, const_cast<void*>(ptr), dims, strides, box, es, CU_TENSOR_MAP_INTERLEAVE_NONE,
        CU_TENSOR_MAP_SWIZZLE_128B, CU_TENSOR_MAP_L2_PROMOTION_L2_256B, CU_TENSOR_MAP_FLOAT_OOB_FILL_NONE);
}
template <typename T> static void* sym_addr(T& sym) { void* p = nullptr; cudaGetSymbolAddress(&p, sym); return p; }

extern "C" void kernel_launch(void* const* d_in, const int* in_sizes, int n_in, void* d_out, int out_size) {
    static Params prm;
    static RecParams rp;
    static bool ready = false;
    static const void* key[14];
    bool same = ready;
    for (int i = 0; i < 13 && same; i++) same = key[i] == d_in[i];
    same = same && key[13] == d_out;
    if (!same) {
        void* fn = nullptr;
        cudaDriverEntryPointQueryResult qr;
        cudaGetDriverEntryPoint("cuTensorMapEncodeTiled", &fn, cudaEnableDefault, &qr);
        EncodeFn enc = (EncodeFn)fn;
        make_map(enc, &prm.tm_h, sym_addr(g_h), S_, D_, 64);
        make_map(enc, &prm.tm_kv, sym_addr(g_kv), S_, 2 * HD_, 64);
        make_map(enc, &prm.tm_kvm, sym_addr(g_kvm), NSEG * 8, 2 * HD_, 32);
        make_map(enc, &prm.tm_o, sym_addr(g_o), S_, HD_, 64);
        make_map(enc, &prm.tm_op, sym_addr(g_op), OP_ROWS, D_, 64);
        make_map(enc, &prm.tm_h2, sym_addr(g_h2), S_, D_, 64);
        make_map(enc, &prm.tm_act, sym_addr(g_act), S_, DF_, 64);
        make_map(enc, &prm.tm_x1, sym_addr(g_x1), S_, D_, 64);
        make_map(enc, &prm.tm_out, d_out, S_, D_, 64);
        make_map(enc, &prm.tm_wq, d_in[2], D_, HD_, 64);
        make_map(enc, &prm.tm_wk, d_in[3], D_, HD_, 64);
        make_map(enc, &prm.tm_wv, d_in[4], D_, HD_, 64);
        make_map(enc, &prm.tm_wo, d_in[5], HD_, D_, 64);
        make_map(enc, &prm.tm_wg, d_in[8], D_, DF_, 64);
        make_map(enc, &prm.tm_wu, d_in[9], D_, DF_, 64);
        make_map(enc, &prm.tm_wd, d_in[10], DF_, D_, 64);
        prm.x = (const bf16*)d_in[0];
        rp.mem0 = (const bf16*)d_in[1];
        rp.wq = (const bf16*)d_in[2]; rp.wk = (const bf16*)d_in[3]; rp.wv = (const bf16*)d_in[4]; rp.wo = (const bf16*)d_in[5];
        cudaFuncSetAttribute(k_work, cudaFuncAttributeMaxDynamicSharedMemorySize, SMEM_BYTES);
        cudaFuncSetAttribute(k_rec, cudaFuncAttributeMaxDynamicSharedMemorySize, R_SMEM);
        cudaFuncSetAttribute(k_rec, cudaFuncAttributeNonPortableClusterSizeAllowed, 1);
        {
            cudaLaunchConfig_t cfg = {};
            cfg.gridDim = dim3(128); cfg.blockDim = dim3(384); cfg.dynamicSmemBytes = R_SMEM;
            cudaLaunchAttribute at[1];
            at[0].id = cudaLaunchAttributeClusterDimension; at[0].val.clusterDim.x = 16; at[0].val.clusterDim.y = 1; at[0].val.clusterDim.z = 1;
            cfg.attrs = at; cfg.numAttrs = 1;
            int n = 0;
            cudaOccupancyMaxActiveClusters(&n, k_rec, &cfg);
            rp.ncl = n < 4 ? 4 : (n > 8 ? 8 : n);
        }
        for (int i = 0; i < 13; i++) key[i] = d_in[i];
        key[13] = d_out;
        ready = true;
    }
    cudaStream_t st = cudaStreamPerThread;
    PrefetchList pf;
    pf.p[0] = (const bf16*)d_in[3]; pf.p[1] = (const bf16*)d_in[4]; pf.p[2] = (const bf16*)d_in[2]; pf.p[3] = (const bf16*)d_in[5]; pf.p[4] = nullptr;
    k_mod<<<96, 256, 0, st>>>((const bf16*)d_in[11], (const bf16*)d_in[12], pf);
    {
        cudaLaunchConfig_t cfg = {};
        cfg.gridDim = dim3(S_ / 8); cfg.blockDim = dim3(256); cfg.stream = st;
        cudaLaunchAttribute at[1];
        at[0].id = cudaLaunchAttributeProgrammaticStreamSerialization; at[0].val.programmaticStreamSerializationAllowed = 1;
        cfg.attrs = at; cfg.numAttrs = 1;
        cudaLaunchKernelEx(&cfg, k_ln1, (const bf16*)d_in[0]);
    }
    auto launch_rec = [&]() {
        cudaLaunchConfig_t cfg = {};
        cfg.gridDim = dim3(16 * rp.ncl); cfg.blockDim = dim3(384); cfg.dynamicSmemBytes = R_SMEM; cfg.stream = st;
        cudaLaunchAttribute at[1];
        at[0].id = cudaLaunchAttributeClusterDimension; at[0].val.clusterDim.x = 16; at[0].val.clusterDim.y = 1; at[0].val.clusterDim.z = 1;
        cfg.attrs = at; cfg.numAttrs = 1;
        cudaLaunchKernelEx(&cfg, k_rec, rp);
    };
    auto launch_work = [&](int qmask, int pdl) {
        prm.qmask = qmask;
        cudaLaunchConfig_t cfg = {};
        cfg.gridDim = dim3(132); cfg.blockDim = dim3(384); cfg.dynamicSmemBytes = SMEM_BYTES; cfg.stream = st;
        cudaLaunchAttribute at[1];
        at[0].id = cudaLaunchAttributeProgrammaticStreamSerialization; at[0].val.programmaticStreamSerializationAllowed = 1;
        cfg.attrs = at; cfg.numAttrs = pdl;
        cudaLaunchKernelEx(&cfg, k_work, prm);
    };
    launch_rec();
    launch_work(0x3f, 1);
}
```

```cpp
#include <cuda_runtime.h>
#include <cuda_bf16.h>
#include <cuda.h>
#include <stdint.h>

typedef __nv_bfloat16 bf16;

constexpr int S_ = 2048, D_ = 512, H_ = 32, DH_ = 128, HD_ = 4096, NSEG = 64, DF_ = 1792;
constexpr int NRB = 16;
constexpr int OSPLIT = 4;

__device__ __align__(1024) bf16 g_h[S_ * D_];
__device__ __align__(1024) bf16 g_kv[S_ * 2 * HD_];
__device__ __align__(1024) bf16 g_kvm[NSEG * 8 * 2 * HD_];
__device__ __align__(1024) bf16 g_o[S_ * HD_];
#define FINE_RB_ 14
constexpr int FINE_RB = FINE_RB_;
constexpr int OSPLIT2 = 16;
constexpr int OP_ROWS = OSPLIT * S_ + OSPLIT2 * (NRB - FINE_RB) * 128;
__device__ __align__(1024) bf16 g_op[OP_ROWS * D_];
__device__ __align__(1024) bf16 g_x1[S_ * D_];
__device__ __align__(1024) bf16 g_h2[S_ * D_];
__device__ __align__(1024) bf16 g_act[S_ * DF_];
__device__ __align__(1024) bf16 g_mod[6 * D_];
__device__ uint32_t g_Fraw[131072 + 65536 + 2048];
#define g_F ((uint32_t*)(((uint64_t)g_Fraw + 0x7FFFFull) & ~0x7FFFFull))
constexpr int F_KV = 0, F_MEM = 32, F_O = 64, F_OP = 96, F_H2 = 128, F_ACT = 160, F_CLAIM = 192  , F_SIDE = 384  , F_TOTAL = 448;
__device__ __align__(128) unsigned int g_flags[F_TOTAL];
#define TR(j, i) do {} while (0)

__device__ __forceinline__ uint32_t smem_u32(const void* p) { return (uint32_t)__cvta_generic_to_shared(p); }
__device__ __forceinline__ uint32_t clk32() { uint32_t c; asm volatile("mov.u32 %0, %%clock;" : "=r"(c)); return c; }
__device__ __forceinline__ uint32_t mapa_u32(uint32_t addr, uint32_t rank) {
    uint32_t r; asm volatile("mapa.shared::cluster.u32 %0, %1, %2;" : "=r"(r) : "r"(addr), "r"(rank)); return r;
}
__device__ __forceinline__ void mbar_init(uint32_t bar, uint32_t cnt) {
    asm volatile("mbarrier.init.shared::cta.b64 [%0], %1;" :: "r"(bar), "r"(cnt) : "memory");
}
__device__ __forceinline__ void mbar_inval(uint32_t bar) {
    asm volatile("mbarrier.inval.shared::cta.b64 [%0];" :: "r"(bar) : "memory");
}
__device__ __forceinline__ void mbar_expect_tx(uint32_t bar, uint32_t bytes) {
    asm volatile("mbarrier.arrive.expect_tx.shared::cta.b64 _, [%0], %1;" :: "r"(bar), "r"(bytes) : "memory");
}
__device__ __forceinline__ void mbar_arrive(uint32_t bar) {
    asm volatile("mbarrier.arrive.shared::cta.b64 _, [%0];" :: "r"(bar) : "memory");
}
__device__ __forceinline__ bool mbar_try_wait(uint32_t bar, uint32_t parity) {
    uint32_t ok;
    asm volatile("{\n.reg .pred p;\nmbarrier.try_wait.parity.shared::cta.b64 p, [%1], %2;\nselp.u32 %0, 1, 0, p;\n}"
                 : "=r"(ok) : "r"(bar), "r"(parity) : "memory");
    return ok;
}
__device__ __forceinline__ bool mbar_try_wait_cluster(uint32_t bar, uint32_t parity) {
    uint32_t ok;
    asm volatile("{\n.reg .pred p;\nmbarrier.try_wait.parity.acquire.cluster.shared::cta.b64 p, [%1], %2;\nselp.u32 %0, 1, 0, p;\n}"
                 : "=r"(ok) : "r"(bar), "r"(parity) : "memory");
    return ok;
}
constexpr int SPIN_LIMIT = 1 << 18;
#define TIMEOUT(code, info) do {} while (0)
__device__ __forceinline__ void mbar_wait(uint32_t bar, uint32_t parity) {
    int g = 0;
#pragma unroll 1
    while (!mbar_try_wait(bar, parity)) { if (++g >= SPIN_LIMIT) { TIMEOUT(0, bar & 255); break; } }
}
__device__ __forceinline__ void mbar_wait_cluster(uint32_t bar, uint32_t parity) {
    int g = 0;
#pragma unroll 1
    while (!mbar_try_wait_cluster(bar, parity)) { if (++g >= SPIN_LIMIT) { TIMEOUT(1, bar & 255); break; } }
}
__device__ __forceinline__ void bar_sync(int id, int n) { asm volatile("bar.sync %0, %1;" :: "r"(id), "r"(n) : "memory"); }
__device__ __forceinline__ void bar_arrive(int id, int n) { asm volatile("bar.arrive %0, %1;" :: "r"(id), "r"(n) : "memory"); }
__device__ __forceinline__ void cluster_sync_all() {
    asm volatile("barrier.cluster.arrive.aligned;\nbarrier.cluster.wait.aligned;" ::: "memory");
}
__device__ __forceinline__ void st_async_v2(uint32_t addr, float a, float b, uint32_t bar) {
    asm volatile("st.async.weak.shared::cluster.mbarrier::complete_tx::bytes.v2.f32 [%0], {%1,%2}, [%3];"
                 :: "r"(addr), "f"(a), "f"(b), "r"(bar) : "memory");
}
__device__ __forceinline__ void st_async_v4(uint32_t addr, uint4 v, uint32_t bar) {
    asm volatile("st.async.weak.shared::cluster.mbarrier::complete_tx::bytes.v4.b32 [%0], {%1,%2,%3,%4}, [%5];"
                 :: "r"(addr), "r"(v.x), "r"(v.y), "r"(v.z), "r"(v.w), "r"(bar) : "memory");
}
__device__ __forceinline__ uint2 ldg_relaxed2(const uint2* p) {
    uint2 v;
    asm volatile("ld.relaxed.gpu.global.v2.b32 {%0,%1}, [%2];" : "=r"(v.x), "=r"(v.y) : "l"(p) : "memory");
    return v;
}
__device__ __forceinline__ void stg_relaxed2(uint2* p, uint2 v) {
    asm volatile("st.relaxed.gpu.global.v2.b32 [%0], {%1,%2};" :: "l"(p), "r"(v.x), "r"(v.y) : "memory");
}
__device__ __forceinline__ uint4 ldg_relaxed(const uint4* p) {
    uint4 v;
    asm volatile("ld.relaxed.gpu.global.v4.b32 {%0,%1,%2,%3}, [%4];" : "=r"(v.x), "=r"(v.y), "=r"(v.z), "=r"(v.w) : "l"(p) : "memory");
    return v;
}
__device__ __forceinline__ void stg_relaxed(uint4* p, uint4 v) {
    asm volatile("st.relaxed.gpu.global.v4.b32 [%0], {%1,%2,%3,%4};" :: "l"(p), "r"(v.x), "r"(v.y), "r"(v.z), "r"(v.w) : "memory");
}
__device__ __forceinline__ void stg_relaxed32(uint32_t* p, uint32_t v) {
    asm volatile("st.relaxed.gpu.global.b32 [%0], %1;" :: "l"(p), "r"(v) : "memory");
}
__device__ __forceinline__ uint32_t ldg_relaxed32(const uint32_t* p) {
    uint32_t v; asm volatile("ld.relaxed.gpu.global.b32 %0, [%1];" : "=r"(v) : "l"(p) : "memory"); return v;
}
__device__ __forceinline__ unsigned int ld_acquire(const unsigned int* p) {
    unsigned int v; asm volatile("ld.acquire.gpu.global.u32 %0, [%1];" : "=r"(v) : "l"(p) : "memory"); return v;
}
__device__ __forceinline__ void red_release(unsigned int* p, unsigned int v) {
    asm volatile("red.release.gpu.global.add.u32 [%0], %1;" :: "l"(p), "r"(v) : "memory");
}
__device__ __forceinline__ void wait_flag(int idx, unsigned int target) {
    const unsigned int* p = &g_flags[idx];
    int g = 0;
#pragma unroll 1
    while (ld_acquire(p) < target) { __nanosleep(20); if (++g >= 64 * SPIN_LIMIT) { TIMEOUT(2, idx); break; } }
}
__device__ __forceinline__ void cp_async16(uint32_t dst, const void* src) {
    asm volatile("cp.async.cg.shared.global [%0], [%1], 16;" :: "r"(dst), "l"(src) : "memory");
}
__device__ __forceinline__ void cp_async_commit() { asm volatile("cp.async.commit_group;" ::: "memory"); }
template <int N> __device__ __forceinline__ void cp_async_wait() { asm volatile("cp.async.wait_group %0;" :: "n"(N) : "memory"); }
__device__ __forceinline__ void ldsm4(uint32_t& r0, uint32_t& r1, uint32_t& r2, uint32_t& r3, uint32_t addr) {
    asm volatile("ldmatrix.sync.aligned.m8n8.x4.shared.b16 {%0,%1,%2,%3}, [%4];" : "=r"(r0), "=r"(r1), "=r"(r2), "=r"(r3) : "r"(addr) : "memory");
}
__device__ __forceinline__ void ldsm4t(uint32_t& r0, uint32_t& r1, uint32_t& r2, uint32_t& r3, uint32_t addr) {
    asm volatile("ldmatrix.sync.aligned.m8n8.x4.trans.shared.b16 {%0,%1,%2,%3}, [%4];" : "=r"(r0), "=r"(r1), "=r"(r2), "=r"(r3) : "r"(addr) : "memory");
}
__device__ __forceinline__ void ldsm2t(uint32_t& r0, uint32_t& r1, uint32_t addr) {
    asm volatile("ldmatrix.sync.aligned.m8n8.x2.trans.shared.b16 {%0,%1}, [%2];" : "=r"(r0), "=r"(r1) : "r"(addr) : "memory");
}
__device__ __forceinline__ void stsm4(uint32_t addr, uint32_t r0, uint32_t r1, uint32_t r2, uint32_t r3) {
    asm volatile("stmatrix.sync.aligned.m8n8.x4.shared.b16 [%0], {%1,%2,%3,%4};" :: "r"(addr), "r"(r0), "r"(r1), "r"(r2), "r"(r3) : "memory");
}
__device__ __forceinline__ void stsm2t(uint32_t addr, uint32_t r0, uint32_t r1) {
    asm volatile("stmatrix.sync.aligned.m8n8.x2.trans.shared.b16 [%0], {%1,%2};" :: "r"(addr), "r"(r0), "r"(r1) : "memory");
}
__device__ __forceinline__ void mma16816(float* d, uint32_t a0, uint32_t a1, uint32_t a2, uint32_t a3, uint32_t b0, uint32_t b1) {
    asm volatile("mma.sync.aligned.m16n8k16.row.col.f32.bf16.bf16.f32 {%0,%1,%2,%3}, {%4,%5,%6,%7}, {%8,%9}, {%0,%1,%2,%3};"
                 : "+f"(d[0]), "+f"(d[1]), "+f"(d[2]), "+f"(d[3]) : "r"(a0), "r"(a1), "r"(a2), "r"(a3), "r"(b0), "r"(b1));
}
__device__ __forceinline__ void mma1688(float* d, uint32_t a0, uint32_t a1, uint32_t b0) {
    asm volatile("mma.sync.aligned.m16n8k8.row.col.f32.bf16.bf16.f32 {%0,%1,%2,%3}, {%4,%5}, {%6}, {%0,%1,%2,%3};"
                 : "+f"(d[0]), "+f"(d[1]), "+f"(d[2]), "+f"(d[3]) : "r"(a0), "r"(a1), "r"(b0));
}
__device__ __forceinline__ void mma16816h(float* d, uint32_t a0, uint32_t a2, uint32_t b0, uint32_t b1) {
    asm volatile("{\n.reg .b32 ju, jv;\nmma.sync.aligned.m16n8k16.row.col.f32.bf16.bf16.f32 {%0,%1,%2,%3}, {%4,ju,%5,jv}, {%6,%7}, {%0,%1,%2,%3};\n}"
                 : "+f"(d[0]), "+f"(d[1]), "+f"(d[2]), "+f"(d[3]) : "r"(a0), "r"(a2), "r"(b0), "r"(b1));
}
__device__ __forceinline__ void mma1688h(float* d, uint32_t a0, uint32_t b0) {
    asm volatile("{\n.reg .b32 ju;\nmma.sync.aligned.m16n8k8.row.col.f32.bf16.bf16.f32 {%0,%1,%2,%3}, {%4,ju}, {%5}, {%0,%1,%2,%3};\n}"
                 : "+f"(d[0]), "+f"(d[1]), "+f"(d[2]), "+f"(d[3]) : "r"(a0), "r"(b0));
}
__device__ __forceinline__ uint32_t pack2(float lo, float hi) {
    uint32_t r; asm("cvt.rn.bf16x2.f32 %0, %1, %2;" : "=r"(r) : "f"(hi), "f"(lo)); return r;
}
__device__ __forceinline__ float bflo(uint32_t w) { return __uint_as_float(w << 16); }
__device__ __forceinline__ float bfhi(uint32_t w) { return __uint_as_float(w & 0xffff0000u); }
__device__ __forceinline__ float rbf(float x) { return __bfloat162float(__float2bfloat16_rn(x)); }
__device__ __forceinline__ float ex2(float x) { float y; asm("ex2.approx.ftz.f32 %0, %1;" : "=f"(y) : "f"(x)); return y; }
__device__ __forceinline__ void sts128(uint32_t addr, uint4 v) {
    asm volatile("st.shared.v4.b32 [%0], {%1,%2,%3,%4};" :: "r"(addr), "r"(v.x), "r"(v.y), "r"(v.z), "r"(v.w) : "memory");
}
__device__ __forceinline__ uint4 lds128(uint32_t addr) {
    uint4 v; asm volatile("ld.shared.v4.b32 {%0,%1,%2,%3}, [%4];" : "=r"(v.x), "=r"(v.y), "=r"(v.z), "=r"(v.w) : "r"(addr) : "memory"); return v;
}
__device__ __forceinline__ float2 lds64f(uint32_t addr) {
    float2 v; asm volatile("ld.shared.v2.f32 {%0,%1}, [%2];" : "=f"(v.x), "=f"(v.y) : "r"(addr) : "memory"); return v;
}
__device__ __forceinline__ float lds32f(uint32_t addr) {
    float v; asm volatile("ld.shared.f32 %0, [%1];" : "=f"(v) : "r"(addr) : "memory"); return v;
}
__device__ __forceinline__ uint32_t lds32(uint32_t addr) {
    uint32_t v; asm volatile("ld.shared.b32 %0, [%1];" : "=r"(v) : "r"(addr) : "memory"); return v;
}
__device__ __forceinline__ void sts32(uint32_t addr, uint32_t v) { asm volatile("st.shared.b32 [%0], %1;" :: "r"(addr), "r"(v) : "memory"); }
__device__ __forceinline__ void sts64f(uint32_t addr, float a, float b) { asm volatile("st.shared.v2.f32 [%0], {%1,%2};" :: "r"(addr), "f"(a), "f"(b) : "memory"); }

__device__ __forceinline__ void tma_load2d(uint32_t dst, const CUtensorMap* tm, int c0, int c1, uint32_t bar) {
    asm volatile("cp.async.bulk.tensor.2d.shared::cluster.global.mbarrier::complete_tx::bytes [%0], [%1, {%3, %4}], [%2];"
                 :: "r"(dst), "l"(tm), "r"(bar), "r"(c0), "r"(c1) : "memory");
}
__device__ __forceinline__ void tma_store2d(const CUtensorMap* tm, uint32_t src, int c0, int c1) {
    asm volatile("cp.async.bulk.tensor.2d.global.shared::cta.bulk_group [%0, {%2, %3}], [%1];"
                 :: "l"(tm), "r"(src), "r"(c0), "r"(c1) : "memory");
}
__device__ __forceinline__ void bulk_commit() { asm volatile("cp.async.bulk.commit_group;" ::: "memory"); }
__device__ __forceinline__ void bulk_wait0() { asm volatile("cp.async.bulk.wait_group 0;" ::: "memory"); }
__device__ __forceinline__ void fence_async_smem() { asm volatile("fence.proxy.async.shared::cta;" ::: "memory"); }
__device__ __forceinline__ void fence_async_all() { asm volatile("fence.proxy.async;" ::: "memory"); }

__device__ __forceinline__ void wg_fence() { asm volatile("wgmma.fence.sync.aligned;" ::: "memory"); }
__device__ __forceinline__ void wg_commit() { asm volatile("wgmma.commit_group.sync.aligned;" ::: "memory"); }
__device__ __forceinline__ void wg_wait0() { asm volatile("wgmma.wait_group.sync.aligned 0;" ::: "memory"); }
__device__ __forceinline__ uint64_t mkdesc(uint32_t saddr, uint32_t lbo, uint32_t sbo) {
    return (uint64_t)((saddr & 0x3FFFF) >> 4) | ((uint64_t)(lbo >> 4) << 16) | ((uint64_t)(sbo >> 4) << 32) | (1ull << 62);
}
#define ACC8(i) "+f"(d[i]), "+f"(d[i + 1]), "+f"(d[i + 2]), "+f"(d[i + 3]), "+f"(d[i + 4]), "+f"(d[i + 5]), "+f"(d[i + 6]), "+f"(d[i + 7])
__device__ __forceinline__ void wgmma_n256(float* d, uint64_t da, uint64_t db, int scale_d) {
    asm volatile(
        "{\n.reg .pred p;\nsetp.ne.b32 p, %130, 0;\n"
        "wgmma.mma_async.sync.aligned.m64n256k16.f32.bf16.bf16 "
        "{%0,%1,%2,%3,%4,%5,%6,%7,%8,%9,%10,%11,%12,%13,%14,%15,%16,%17,%18,%19,%20,%21,%22,%23,%24,%25,%26,%27,%28,%29,%30,%31,"
        "%32,%33,%34,%35,%36,%37,%38,%39,%40,%41,%42,%43,%44,%45,%46,%47,%48,%49,%50,%51,%52,%53,%54,%55,%56,%57,%58,%59,%60,%61,%62,%63,"
        "%64,%65,%66,%67,%68,%69,%70,%71,%72,%73,%74,%75,%76,%77,%78,%79,%80,%81,%82,%83,%84,%85,%86,%87,%88,%89,%90,%91,%92,%93,%94,%95,"
        "%96,%97,%98,%99,%100,%101,%102,%103,%104,%105,%106,%107,%108,%109,%110,%111,%112,%113,%114,%115,%116,%117,%118,%119,%120,%121,%122,%123,%124,%125,%126,%127}, "
        "%128, %129, p, 1, 1, 0, 1;\n}"
        : ACC8(0), ACC8(8), ACC8(16), ACC8(24), ACC8(32), ACC8(40), ACC8(48), ACC8(56),
          ACC8(64), ACC8(72), ACC8(80), ACC8(88), ACC8(96), ACC8(104), ACC8(112), ACC8(120)
        : "l"(da), "l"(db), "r"(scale_d));
}
__device__ __forceinline__ void wgmma_n128(float* d, uint64_t da, uint64_t db, int scale_d) {
    asm volatile(
        "{\n.reg .pred p;\nsetp.ne.b32 p, %66, 0;\n"
        "wgmma.mma_async.sync.aligned.m64n128k16.f32.bf16.bf16 "
        "{%0,%1,%2,%3,%4,%5,%6,%7,%8,%9,%10,%11,%12,%13,%14,%15,%16,%17,%18,%19,%20,%21,%22,%23,%24,%25,%26,%27,%28,%29,%30,%31,"
        "%32,%33,%34,%35,%36,%37,%38,%39,%40,%41,%42,%43,%44,%45,%46,%47,%48,%49,%50,%51,%52,%53,%54,%55,%56,%57,%58,%59,%60,%61,%62,%63}, "
        "%64, %65, p, 1, 1, 0, 1;\n}"
        : ACC8(0), ACC8(8), ACC8(16), ACC8(24), ACC8(32), ACC8(40), ACC8(48), ACC8(56)
        : "l"(da), "l"(db), "r"(scale_d));
}

__device__ __forceinline__ void wgmma_n64(float* d, uint64_t da, uint64_t db) {
    asm volatile(
        "wgmma.mma_async.sync.aligned.m64n64k16.f32.bf16.bf16 "
        "{%0,%1,%2,%3,%4,%5,%6,%7,%8,%9,%10,%11,%12,%13,%14,%15,%16,%17,%18,%19,%20,%21,%22,%23,%24,%25,%26,%27,%28,%29,%30,%31}, "
        "%32, %33, 1, 1, 1, 0, 1;"
        : ACC8(0), ACC8(8), ACC8(16), ACC8(24)
        : "l"(da), "l"(db));
}
__device__ __forceinline__ void wgmma_n8_ta(float* d, uint64_t da, uint64_t db, int scale_d) {
    asm volatile(
        "{\n.reg .pred p;\nsetp.ne.b32 p, %6, 0;\n"
        "wgmma.mma_async.sync.aligned.m64n8k16.f32.bf16.bf16 {%0,%1,%2,%3}, %4, %5, p, 1, 1, 1, 0;\n}"
        : "+f"(d[0]), "+f"(d[1]), "+f"(d[2]), "+f"(d[3]) : "l"(da), "l"(db), "r"(scale_d));
}

struct PrefetchList { const bf16* p[5]; };
__global__ void __launch_bounds__(256) k_mod(const bf16* __restrict__ c, const bf16* __restrict__ w_mod, const PrefetchList pf) {
    asm volatile("griddepcontrol.launch_dependents;");
    __shared__ float s_c[D_];
    __shared__ float s_red[64][33];
    const int tid = threadIdx.x;
    const int cq = tid & 3, rg = tid >> 2;
    uint4 w[8];
#pragma unroll
    for (int i = 0; i < 8; i++)
        w[i] = __ldg((const uint4*)(w_mod + (size_t)(rg * 8 + i) * (6 * D_) + blockIdx.x * 32 + cq * 8));
    for (int i = tid; i < D_; i += 256) {
        float v = __bfloat162float(c[i]);
        s_c[i] = rbf(v / (1.f + __expf(-v)));
    }
    {
        const int gt = blockIdx.x * 256 + tid, nt = gridDim.x * 256;
        for (int i = gt; i < F_TOTAL; i += nt) g_flags[i] = 0;
        for (int i = gt; i < 65536 + 2048; i += nt) g_F[i] = 0;
        if (tid < 11) {
            const int i = tid * gridDim.x + blockIdx.x;
            if (i < 1024) asm volatile("cp.async.bulk.prefetch.L2.global [%0], %1;" :: "l"(pf.p[i >> 8] + (size_t)(i & 255) * 8192), "r"(16384) : "memory");
        }
    }
    __syncthreads();
    float a[8];
#pragma unroll
    for (int j = 0; j < 8; j++) a[j] = 0.f;
#pragma unroll
    for (int i = 0; i < 8; i++) {
        float cv = s_c[rg * 8 + i];
        a[0] += cv * bflo(w[i].x); a[1] += cv * bfhi(w[i].x); a[2] += cv * bflo(w[i].y); a[3] += cv * bfhi(w[i].y);
        a[4] += cv * bflo(w[i].z); a[5] += cv * bfhi(w[i].z); a[6] += cv * bflo(w[i].w); a[7] += cv * bfhi(w[i].w);
    }
#pragma unroll
    for (int j = 0; j < 8; j++) s_red[rg][cq * 8 + j] = a[j];
    __syncthreads();
    if (tid < 32) {
        float s = 0.f;
#pragma unroll 8
        for (int r = 0; r < 64; r++) s += s_red[r][tid];
        g_mod[blockIdx.x * 32 + tid] = __float2bfloat16_rn(s);
    }
}

__device__ __forceinline__ uint32_t hadd2(uint32_t a, uint32_t b) { uint32_t r; asm("add.rn.bf16x2 %0, %1, %2;" : "=r"(r) : "r"(a), "r"(b)); return r; }
__device__ __forceinline__ uint32_t hsub2(uint32_t a, uint32_t b) { uint32_t r; asm("sub.rn.bf16x2 %0, %1, %2;" : "=r"(r) : "r"(a), "r"(b)); return r; }
__device__ __forceinline__ uint32_t hmul2(uint32_t a, uint32_t b) { uint32_t r; asm("mul.rn.bf16x2 %0, %1, %2;" : "=r"(r) : "r"(a), "r"(b)); return r; }
__device__ __forceinline__ void load_mod8(const bf16* m, int lane, uint32_t* v) {
    const uint4 a = __ldcg((const uint4*)m + lane), b = __ldcg((const uint4*)m + 32 + lane);
    v[0] = a.x; v[1] = a.y; v[2] = a.z; v[3] = a.w; v[4] = b.x; v[5] = b.y; v[6] = b.z; v[7] = b.w;
}
__device__ __forceinline__ void ln_stats(const uint32_t* x, uint32_t& mu2, float& rden) {
    float s = 0.f;
#pragma unroll
    for (int i = 0; i < 8; i++) s += bflo(x[i]) + bfhi(x[i]);
#pragma unroll
    for (int o = 16; o > 0; o >>= 1) s += __shfl_xor_sync(~0u, s, o);
    const float mean = s * (1.f / D_);
    float q = 0.f;
#pragma unroll
    for (int i = 0; i < 8; i++) { const float d0 = bflo(x[i]) - mean, d1 = bfhi(x[i]) - mean; q = fmaf(d0, d0, q); q = fmaf(d1, d1, q); }
#pragma unroll
    for (int o = 16; o > 0; o >>= 1) q += __shfl_xor_sync(~0u, q, o);
    mu2 = pack2(mean, mean);
    rden = __frcp_rn(rbf(__fsqrt_rn(rbf(rbf(q * (1.f / D_)) + 1e-5f))));
}
__device__ __forceinline__ void ln_apply(const uint32_t* x, uint32_t mu2, float rden, const uint32_t* c1, const uint32_t* sm, uint32_t* r) {
#pragma unroll
    for (int i = 0; i < 8; i++) {
        const uint32_t d = hsub2(x[i], mu2);
        r[i] = hadd2(hmul2(pack2(bflo(d) * rden, bfhi(d) * rden), c1[i]), sm[i]);
    }
}

__global__ void __launch_bounds__(256) k_ln1(const bf16* __restrict__ x) {
    const int lane = threadIdx.x & 31, row = blockIdx.x * 8 + (threadIdx.x >> 5);
    const uint4* xr = (const uint4*)(x + (size_t)row * D_);
    const uint4 a = __ldg(xr + lane), b = __ldg(xr + 32 + lane);
    const uint32_t v[8] = {a.x, a.y, a.z, a.w, b.x, b.y, b.z, b.w};
    uint32_t mu2; float rden;
    ln_stats(v, mu2, rden);
    asm volatile("griddepcontrol.wait;" ::: "memory");
    uint32_t c1[8], sm[8], r[8];
    load_mod8(g_mod + D_, lane, c1);
    load_mod8(g_mod, lane, sm);
#pragma unroll
    for (int i = 0; i < 8; i++) c1[i] = hadd2(c1[i], 0x3F803F80u);
    ln_apply(v, mu2, rden, c1, sm, r);
    uint4* hr = (uint4*)(g_h + (size_t)row * D_);
    hr[lane] = make_uint4(r[0], r[1], r[2], r[3]); hr[32 + lane] = make_uint4(r[4], r[5], r[6], r[7]);
}

struct __align__(64) Params {
    CUtensorMap tm_h, tm_kv, tm_kvm, tm_o, tm_op, tm_h2, tm_act, tm_x1, tm_out;
    CUtensorMap tm_wq, tm_wk, tm_wv, tm_wo, tm_wg, tm_wu, tm_wd;
    const bf16* x;
    int qmask;
};

constexpr int R_NST = 3;
constexpr uint32_t R_WV = 0, R_MEM = 65536, R_KX = 73728, R_VX = R_KX + R_NST * 4096, R_QS = R_VX + R_NST * 4096,
                   R_KMS = R_QS + 1024, R_VMS = R_KMS + 1024, R_OS = R_VMS + 1024, R_SX = R_OS + 1024, R_BAR = R_SX + 2560,
                   R_RS = 105472  , R_VP = R_RS + 8192  ,
                   R_STG = R_VP + 8192  , R_SMEM = R_STG + 98304;
static_assert(R_BAR + 64 <= R_RS, "smem");
constexpr uint32_t RB_SX = R_BAR, RB_V = R_BAR + 8, RB_E = R_BAR + 16, RB_A = R_BAR + 24, RB_ROLE = R_BAR + 32;
constexpr int W_NST = 3;
constexpr uint32_t W_STAGE = 49152, W_STG = W_NST * W_STAGE, W_END = W_STG + 65536;
constexpr uint32_t SM_BAR = W_END;
constexpr uint32_t SMEM_BYTES = W_END + 1024;
constexpr uint32_t B_FULL = 0, B_EMPTY = 32, B_STGFREE = 64, B_REQ = 80, B_RSP = 88, B_NEXT = 96, B_RING = 128;
#define PICK_AHEAD 2

constexpr int NB_X = 11  , NB_Y = 1, NB_B = 2, NB_C = 3, NB_D = 4, NB_W0 = 6  , NB_ST = 9  ;

__device__ __forceinline__ int pos_of_d(int d) {
    const int rem = d & 31;
    return (d & ~31) + ((rem & 7) >> 1) * 8 + (rem & 1) * 4 + (rem >> 3);
}

#define PROF(i) do {} while (0)
#define PROFG(i) do {} while (0)
#define OPAQUE(x) asm volatile("" : "+r"(x))
#define FENCE_SCHED(x) do { if ((x) == 0u) asm volatile("trap;"); } while (0)
#define VK0_ 4
constexpr int VK0 = VK0_;
constexpr int NOFF = 8;
#define VDELAY -1
#define POLL_GAP 100

struct RecParams { const bf16 *mem0, *wq, *wk, *wv, *wo; int ncl; };

__device__ __forceinline__ void rec_qk(const RecParams& p, const uint32_t sb, const int cta, const int warp, int lane, const int sel) {
    const int crank = cta & 15, cl = cta >> 4, rank = cta & 1;
    const int kh = warp >> 2, aa = warp & 3;
    uint32_t wa[2][16][4];
    const uint32_t stg = sb + R_STG + kh * 32768;
    {
        const int t128 = aa * 32 + lane;
        const int row = (lane >> 4) * 8 + (lane & 7);
        const int ch = t128 & 7;
        const size_t goff = (size_t)kh * 256 * HD_ + cta * 64 + ch * 8;
#pragma unroll 4
        for (int dd = 0; dd < 16; dd++) {
            const int d = dd * 16 + (t128 >> 3), pp = pos_of_d(d);
            cp_async16(sb + R_WV + kh * 32768 + pp * 128 + ((ch ^ (pp & 7)) << 4), p.wv + goff + (size_t)d * HD_);
        }
        cp_async_commit();
#pragma unroll 4
        for (int dd = 0; dd < 16; dd++) {
            const int d = dd * 16 + (t128 >> 3), pp = pos_of_d(d);
            cp_async16(stg + pp * 128 + ((ch ^ (pp & 7)) << 4), p.wq + goff + (size_t)d * HD_);
        }
        cp_async_commit();
        {
            const int i0 = (warp * 32 + lane) * 16, tok = i0 >> 9;
            const uint4 m0 = __ldg((const uint4*)(p.mem0 + i0)), m1 = __ldg((const uint4*)(p.mem0 + i0 + 8));
            const uint32_t mw[8] = {m0.x, m0.y, m0.z, m0.w, m1.x, m1.y, m1.z, m1.w};
#pragma unroll
            for (int e = 0; e < 16; e++) {
                const int pp = pos_of_d((i0 & 511) + e);
                const unsigned short v = (unsigned short)(mw[e >> 1] >> ((e & 1) * 16));
                asm volatile("st.shared.u16 [%0], %1;" :: "r"(sb + R_MEM + (pp >> 3) * 128 + tok * 16 + (pp & 7) * 2), "h"(v) : "memory");
            }
        }
        cp_async_wait<1>();
        bar_sync(NB_W0 + kh, 128);
        const uint32_t fv = row * 128 + (((2 * aa + ((lane >> 3) & 1)) ^ (row & 7)) << 4);
#pragma unroll
        for (int ks = 0; ks < 16; ks++) ldsm4t(wa[0][ks][0], wa[0][ks][1], wa[0][ks][2], wa[0][ks][3], sb + R_WV + kh * 32768 + fv + ks * 2048);
        bar_sync(NB_W0 + kh, 128);
#pragma unroll
        for (int ks = 0; ks < 16; ks++)
            sts128(sb + R_WV + kh * 32768 + (aa * 16 + ks) * 512 + lane * 16, make_uint4(wa[0][ks][0], wa[0][ks][1], wa[0][ks][2], wa[0][ks][3]));
        const uint32_t fo = stg + row * 128 + (((4 * (aa & 1) + ((lane >> 3) & 1)) ^ (row & 7)) << 4);
#pragma unroll 1
        for (int m = 0; m < 2; m++) {
            cp_async_wait<0>();
            bar_sync(NB_W0 + kh, 128);
            if ((aa >> 1) == m) {
#pragma unroll
                for (int ks = 0; ks < 16; ks++) {
                    ldsm4t(wa[0][ks][0], wa[0][ks][1], wa[0][ks][2], wa[0][ks][3], fo + ks * 2048);
                    ldsm4t(wa[1][ks][0], wa[1][ks][1], wa[1][ks][2], wa[1][ks][3], (fo ^ 32) + ks * 2048);
                }
            }
            bar_sync(NB_W0 + kh, 128);
            if (m == 0) {
#pragma unroll 4
                for (int dd = 0; dd < 16; dd++) {
                    const int d = dd * 16 + (t128 >> 3), pp = pos_of_d(d);
                    cp_async16(stg + pp * 128 + ((ch ^ (pp & 7)) << 4), p.wk + goff + (size_t)d * HD_);
                }
                cp_async_commit();
            }
        }
    }
    const uint32_t tab = stg + (aa * 32 + lane) * 16;
    {
        const uint32_t l7 = lane & 7, l8 = lane >> 3, g = lane >> 2, t = lane & 3;
        const uint32_t t0 = l7 * 128 + ((l8 ^ l7) << 4);
        const uint32_t tq = l7 * 128 + (((l8 >> 1) ^ l7) << 4);
        const uint32_t bq = warp >> 1, tp = warp & 1;
        uint4 v;
        v.x = sb + (aa < 2 ? R_QS : R_KMS) + l7 * 128 + (((4 * (aa & 1) + 2 * kh + (l8 & 1)) ^ l7) << 4);
        v.y = sb + R_QS + tq;
        v.z = sb + (warp == 0 ? R_KMS : R_KX + (warp - 1) * 1024) + t0;
        v.w = mapa_u32(sb + R_SX + (rank * 5 + warp) * 256 + lane * 8, crank ^ 1);
        sts128(tab, v);
        sts128(tab + 2048, make_uint4(sb + lane * 16 + R_MEM + kh * 4096, sb + lane * 16 + R_WV + warp * 8192,
                                      sb + lane * 16 + R_VP + warp * 512, sb + lane * 16 + R_VP + 4096 + (warp ^ 4) * 512));
        const uint32_t src = (l8 >> 1) * 8 + l7;
        const uint32_t L = bq * 8 + 2 * tp + (l8 & 1);
        const uint32_t d0 = (crank + ((t >> 1) | (g & 6))) & 15;
        v.x = sb + R_RS + src * 512 + ((L ^ (src & 7)) << 4);
        v.y = mapa_u32(sb + R_MEM + (crank * 4 + bq) * 128 + (4 * tp + 2 * (t & 1) + (g & 1)) * 16, d0);
        v.z = mapa_u32(sb + RB_A, d0);
        v.w = lane;
        sts128(tab + 4096, v);
        const uint64_t wr = (uint64_t)(g_F + ((crank * 2 + ((crank ^ (crank >> 3) ^ sel) & 1)) * 1024 + warp * 128 + cl * 32 + lane));
        sts128(tab + 6144, make_uint4((uint32_t)wr, (uint32_t)(wr >> 32), (uint32_t)((((cl + 1) & 3) - cl) * 128), (uint32_t)((((cl + 2) & 3) - cl) * 128)));
        sts32(tab + 8192, (uint32_t)((((cl + 3) & 3) - cl) * 128));
#pragma unroll
        for (int i = 0; i < NOFF; i++)
            sts128(tab + 10240 + i * 2048, make_uint4(wa[i & 1][i >> 1][0], wa[i & 1][i >> 1][1], wa[i & 1][i >> 1][2], wa[i & 1][i >> 1][3]));
    }
    bar_sync(NB_D, 384);
    uint32_t slot_off = 0;
    const uint32_t slot_inc = warp == 0 ? 0 : 4096;
    const uint32_t sx_bar_rem = (sb + RB_SX) ^ (1u << 24);
    uint4 tb = lds128(tab + 2048);
#pragma unroll 1
    for (int s = 0; s < NSEG; s++) {
        if (s > 0) mbar_wait(sb + RB_A, (s - 1) & 1);
        if (warp == 0) { PROF(0); PROFG(13); }
        uint4 ta;
        {
            float acc[5][4];
#pragma unroll
            for (int c = 0; c < 5; c++) { acc[c][0] = acc[c][1] = acc[c][2] = acc[c][3] = 0.f; }
            uint32_t b[8][4];
            uint4 av[16];
            ldsm4(b[0][0], b[0][1], b[0][2], b[0][3], tb.x);
            ldsm4(b[1][0], b[1][1], b[1][2], b[1][3], tb.x + 512);
            ldsm4(b[2][0], b[2][1], b[2][2], b[2][3], tb.x + 1024);
#pragma unroll
            for (int k2 = 0; k2 < 8; k2++) {
                mma16816(acc[0], wa[0][2 * k2][0], wa[0][2 * k2][1], wa[0][2 * k2][2], wa[0][2 * k2][3], b[k2][0], b[k2][1]);
                mma16816(acc[1], wa[1][2 * k2][0], wa[1][2 * k2][1], wa[1][2 * k2][2], wa[1][2 * k2][3], b[k2][0], b[k2][1]);
                if (2 * k2 >= VK0) mma16816(acc[2], av[2 * k2].x, av[2 * k2].y, av[2 * k2].z, av[2 * k2].w, b[k2][0], b[k2][1]);
                mma16816(acc[3], wa[0][2 * k2 + 1][0], wa[0][2 * k2 + 1][1], wa[0][2 * k2 + 1][2], wa[0][2 * k2 + 1][3], b[k2][2], b[k2][3]);
                mma16816(acc[4], wa[1][2 * k2 + 1][0], wa[1][2 * k2 + 1][1], wa[1][2 * k2 + 1][2], wa[1][2 * k2 + 1][3], b[k2][2], b[k2][3]);
                if (2 * k2 >= VK0) mma16816(acc[2], av[2 * k2 + 1].x, av[2 * k2 + 1].y, av[2 * k2 + 1].z, av[2 * k2 + 1].w, b[k2][2], b[k2][3]);
                if (k2 + 3 < 8) ldsm4(b[k2 + 3][0], b[k2 + 3][1], b[k2 + 3][2], b[k2 + 3][3], tb.x + (k2 + 3) * 512);
                if (VK0 + 2 * k2 < 16) { av[VK0 + 2 * k2] = lds128(tb.y + (VK0 + 2 * k2) * 512); av[VK0 + 2 * k2 + 1] = lds128(tb.y + (VK0 + 2 * k2 + 1) * 512); }
                if (k2 == 5) ta = lds128(tab);
            }
#pragma unroll
            for (int i = 0; i < 4; i++) { acc[0][i] += acc[3][i]; acc[1][i] += acc[4][i]; }
            const float g0 = kh ? acc[0][0] : acc[1][0], g1 = kh ? acc[0][1] : acc[1][1], g2 = kh ? acc[0][2] : acc[1][2], g3 = kh ? acc[0][3] : acc[1][3];
            sts128(tb.w, make_uint4(__float_as_uint(g0), __float_as_uint(g1), __float_as_uint(g2), __float_as_uint(g3)));
            const float k0 = kh ? acc[1][0] : acc[0][0], k1 = kh ? acc[1][1] : acc[0][1], k2_ = kh ? acc[1][2] : acc[0][2], k3 = kh ? acc[1][3] : acc[0][3];
            if (warp == 0) PROF(1);
            bar_sync(NB_X + aa, 64);
            const uint4 o = lds128(tb.z + 4096);
            stsm2t(ta.x, pack2(k0 + __uint_as_float(o.x), k1 + __uint_as_float(o.y)), pack2(k2_ + __uint_as_float(o.z), k3 + __uint_as_float(o.w)));
            sts128(tb.z, make_uint4(__float_as_uint(acc[2][0]), __float_as_uint(acc[2][1]), __float_as_uint(acc[2][2]), __float_as_uint(acc[2][3])));
        }
        const uint32_t kb = ta.z + slot_off;
        if (warp == 0) PROF(14);
        bar_sync(NB_B, 256);
        if (warp < 5) {
            uint32_t q[16], k0, k1, k2, k3, k4, k5, k6, k7;
            float sa[4] = {0.f, 0.f, 0.f, 0.f}, sc[4] = {0.f, 0.f, 0.f, 0.f};
            ldsm4(q[0], q[1], q[2], q[3], ta.y);
            ldsm4(k0, k1, k2, k3, kb);
            ldsm4(q[4], q[5], q[6], q[7], ta.y ^ 32);
            ldsm4(q[8], q[9], q[10], q[11], ta.y ^ 64);
            ldsm4(k4, k5, k6, k7, kb ^ 64);
            ldsm4(q[12], q[13], q[14], q[15], ta.y ^ 96);
            mma16816(sa, q[0], q[1], q[2], q[3], k0, k1);
            bar_arrive(NB_Y, 288);
            mma16816(sc, q[4], q[5], q[6], q[7], k2, k3);
            mma16816(sa, q[8], q[9], q[10], q[11], k4, k5);
            mma16816(sc, q[12], q[13], q[14], q[15], k6, k7);
            const float scl = 0.08838834764831845f * 1.4426950408889634f;
            const float r0 = (sa[0] + sc[0]) * scl, r1 = (sa[1] + sc[1]) * scl;
            if (s != NSEG - 1) {
                st_async_v2(ta.w, r0, r1, sx_bar_rem);
                st_async_v2(ta.w ^ (1u << 24), r0, r1, sx_bar_rem ^ (1u << 24));
            }
            if (warp == 0) PROF(2);
        } else if (s > 0 && warp == 7 && lane == 0) {
            mbar_expect_tx(sb + RB_A, 8192);
        }
        if (s == NSEG - 1) break;
        slot_off = slot_off == (R_NST - 1) * 4096 ? 0 : slot_off + slot_inc;
        const uint4 tc = lds128(tab + 4096), td = lds128(tab + 6144);
        const uint32_t te = lds32(tab + 8192);
        uint32_t* wr = (uint32_t*)(((uint64_t)td.y << 32) | (td.x ^ ((s & 1) * 0x21000)));
        const uint32_t* r1p = (const uint32_t*)((const char*)wr + (int)td.z);
        const uint32_t* r2p = (const uint32_t*)((const char*)wr + (int)td.w);
        const uint32_t* r3p = (const uint32_t*)((const char*)wr + (int)te);
        const uint32_t tag = ((s >> 1) + 1) & 1;
        mbar_wait(sb + RB_E, s & 1);
        if (warp == 0) PROF(7);
        {
            uint32_t a0, a1, a2, a3, a4, a5, a6, a7;
            ldsm4t(a0, a1, a2, a3, tc.x);
            ldsm4t(a4, a5, a6, a7, tc.x ^ 64);
            const uint32_t one = 0x3F803F80u;
            float d0_[4] = {0.f, 0.f, 0.f, 0.f}, d1_[4] = {0.f, 0.f, 0.f, 0.f};
            mma16816(d0_, a0, a1, a2, a3, one, one);
            mma16816(d1_, a4, a5, a6, a7, one, one);
            const bool t1 = tc.w & 1, t2 = tc.w & 2;
            const float x = t2 ? (t1 ? d1_[2] : d1_[0]) : (t1 ? d0_[2] : d0_[0]);
            const uint32_t own = (__float_as_uint(x) & ~1u) | tag;
            stg_relaxed32(wr, own);
            const uint32_t tq = clk32();
            if (warp == 0) PROF(8);
            PROFG(16 + warp);
#pragma unroll
            for (int i = 0; i < NOFF; i++) {
                const uint4 f0 = lds128(tab + 10240 + i * 2048);
                wa[i & 1][i >> 1][0] = f0.x; wa[i & 1][i >> 1][1] = f0.y; wa[i & 1][i >> 1][2] = f0.z; wa[i & 1][i >> 1][3] = f0.w;
            }
            tb = lds128(tab + 2048);
            while ((int)(clk32() - tq) < POLL_GAP) {}
            uint32_t f1, f2, f3;
            int gg = 0;
#pragma unroll 1
            while (true) {
                f1 = ldg_relaxed32(r1p); f2 = ldg_relaxed32(r2p); f3 = ldg_relaxed32(r3p);
                if (__all_sync(~0u, (((f1 ^ tag) | (f2 ^ tag) | (f3 ^ tag)) & 1) == 0)) break;
                if (++gg > 16 * SPIN_LIMIT) { TIMEOUT(3, s); break; }
            }
            if (warp == 0) PROF(9);
            PROFG(32 + warp);
            const float v = (__uint_as_float(own) + __uint_as_float(f2)) + (__uint_as_float(f1) + __uint_as_float(f3));
            const bool b8 = tc.w & 8, b16 = tc.w & 16;
            const float recv = __shfl_xor_sync(~0u, v, 8);
            const uint32_t word = b8 ? pack2(recv, v) : pack2(v, recv);
            const uint32_t oth = __shfl_xor_sync(~0u, word, 16);
            const uint32_t wl = b16 ? oth : word, wh = b16 ? word : oth;
            const uint32_t p0 = __shfl_xor_sync(~0u, wl, 2), p1 = __shfl_xor_sync(~0u, wh, 2);
            const uint4 item = t2 ? make_uint4(p0, p1, wl, wh) : make_uint4(wl, wh, p0, p1);
            st_async_v4(tc.y, item, tc.z);
            st_async_v4(tc.y ^ (8u << 24), item, tc.z ^ (8u << 24));
            if (tc.w == 0 && warp == 7) mbar_expect_tx(sb + RB_E, 8192);
            if (warp == 0) PROF(10);
            PROF(40 + warp);
        }
        bar_sync(NB_D, 384);
    }
}

__device__ __forceinline__ void rec_load_kv(uint32_t sb, int col0, int s, uint32_t slot_off, int t128) {
    const int row = t128 >> 2, c2 = (t128 & 3) * 2;
    const bf16* src = g_kv + ((size_t)(s * 32 + row) * (2 * HD_) + col0 + c2 * 8);
    const uint32_t d0 = sb + R_KX + slot_off + row * 128 + ((c2 ^ (row & 7)) << 4);
    cp_async16(d0, src);
    cp_async16(d0 ^ 16, src + 8);
    cp_async16(d0 + (R_VX - R_KX), src + HD_);
    cp_async16((d0 ^ 16) + (R_VX - R_KX), src + HD_ + 8);
}

__device__ __forceinline__ void rec_vo(const RecParams& p, const uint32_t sb, const int cta, const int warp, int lane) {
    const int w = warp - 8, crank = cta & 15;
    const int col0 = cta * 64;
    uint32_t wo[8][4][4];
    {
        const int t128 = w * 32 + lane;
        const bf16* Wo = p.wo + (size_t)col0 * D_;
        const uint32_t stg = sb + R_STG + 2 * 32768;
#pragma unroll
        for (int half = 0; half < 2; half++) {
#pragma unroll 4
            for (int i = t128; i < 2048; i += 128) {
                const int e = i >> 6, ch = i & 63;
                cp_async16(stg + e * 1024 + ((ch ^ (e & 7)) << 4), Wo + (size_t)(half * 32 + e) * D_ + ch * 8);
            }
            cp_async_commit();
            cp_async_wait<0>();
            bar_sync(NB_W0 + 2, 128);
#pragma unroll
            for (int j = 0; j < 8; j++)
#pragma unroll
                for (int kk = 0; kk < 2; kk++) {
                    const int e = kk * 16 + (lane >> 4) * 8 + (lane & 7);
                    const int ch = (w * 8 + j) * 2 + ((lane >> 3) & 1);
                    ldsm4t(wo[j][half * 2 + kk][0], wo[j][half * 2 + kk][1], wo[j][half * 2 + kk][2], wo[j][half * 2 + kk][3],
                           stg + e * 1024 + ((ch ^ (e & 7)) << 4));
                }
            bar_sync(NB_W0 + 2, 128);
        }
        if (lane == 0) wait_flag(F_KV + 0, 64);
        __syncwarp();
        rec_load_kv(sb, col0, 0, 0, t128); cp_async_commit();
        rec_load_kv(sb, col0, 1, 4096, t128); cp_async_commit();
        cp_async_wait<1>();
    }
    const uint32_t tab = sb + R_STG + 2 * 32768 + (w * 32 + lane) * 16;
    {
        const uint32_t l7 = lane & 7, l8 = lane >> 3, g = lane >> 2;
        uint4 v;
        v.x = sb + R_VX + ((l8 & 1) * 8 + l7) * 128 + (((2 * w + (l8 >> 1)) ^ l7) << 4);
        v.y = sb + R_OS + g * 128 + (((2 * w) ^ g) << 4) + (lane & 3) * 4;
        v.z = sb + R_VMS + l7 * 128 + (((2 * w + (l8 & 1)) ^ l7) << 4);
        v.w = sb + R_OS + l7 * 128 + ((l8 ^ l7) << 4);
        sts128(tab, v);
        v.x = mapa_u32(sb + R_RS + crank * 512 + ((lane ^ (crank & 7)) << 4), w * 4);
        v.y = mapa_u32(sb + RB_E, w * 4);
        v.z = sb + R_VP + w * 512 + lane * 16;
        v.w = sb + R_SX + lane * 8;
        sts128(tab + 2048, v);
#pragma unroll
        for (int i = 0; i < 8; i++) sts128(tab + 4096 + i * 2048, make_uint4(wo[i][0][0], wo[i][0][1], wo[i][0][2], wo[i][0][3]));
    }
    bar_sync(NB_D, 384);
    const uint32_t lane16 = lds32(tab + 2048 + 8) - R_VP - w * 512;
    uint4 av[2 * VK0];
#pragma unroll
    for (int i = 0; i < 2 * VK0; i++) av[i] = lds128(lane16 + R_WV + (i / VK0) * 32768 + (w * 16 + i % VK0) * 512);
    uint32_t slot_off = 0;
#pragma unroll 1
    for (int s = 0; s < NSEG; s++) {
        bar_sync(NB_Y, 288);
        uint32_t vb0, vb1;
        {
            float va[4] = {0.f, 0.f, 0.f, 0.f}, vc[4] = {0.f, 0.f, 0.f, 0.f};
            uint32_t bb[VK0][4];
#pragma unroll
            for (int k2 = 0; k2 < VK0; k2++) ldsm4(bb[k2][0], bb[k2][1], bb[k2][2], bb[k2][3], lane16 + R_MEM + (k2 / (VK0 / 2)) * 4096 + (k2 % (VK0 / 2)) * 512);
#pragma unroll
            for (int k2 = 0; k2 < VK0; k2++) {
                mma16816(va, av[2 * k2].x, av[2 * k2].y, av[2 * k2].z, av[2 * k2].w, bb[k2][0], bb[k2][1]);
                mma16816(vc, av[2 * k2 + 1].x, av[2 * k2 + 1].y, av[2 * k2 + 1].z, av[2 * k2 + 1].w, bb[k2][2], bb[k2][3]);
            }
            const uint4 a = lds128(lane16 + R_VP + w * 512), b = lds128(lane16 + R_VP + 2048 + w * 512);
            vb0 = pack2((va[0] + vc[0]) + (__uint_as_float(a.x) + __uint_as_float(b.x)), (va[1] + vc[1]) + (__uint_as_float(a.y) + __uint_as_float(b.y)));
            vb1 = pack2((va[2] + vc[2]) + (__uint_as_float(a.z) + __uint_as_float(b.z)), (va[3] + vc[3]) + (__uint_as_float(a.w) + __uint_as_float(b.w)));
        }
        const uint4 ta = lds128(tab), tb = lds128(tab + 2048);
        uint32_t vx[8];
        ldsm4t(vx[0], vx[1], vx[2], vx[3], ta.x + slot_off);
        ldsm4t(vx[4], vx[5], vx[6], vx[7], ta.x + slot_off + 2048);
#pragma unroll
        for (int i = 0; i < 4; i++) {
            const uint4 f0 = lds128(tab + 4096 + i * 2048);
            wo[i][0][0] = f0.x; wo[i][0][1] = f0.y; wo[i][0][2] = f0.z; wo[i][0][3] = f0.w;
        }
        if (w == 0) PROF(11);
        uint32_t pf[5];
        float oa[2][4] = {{0.f, 0.f, 0.f, 0.f}, {0.f, 0.f, 0.f, 0.f}}, ob_[2][4] = {{0.f, 0.f, 0.f, 0.f}, {0.f, 0.f, 0.f, 0.f}};
        float sm0[4] = {0.f, 0.f, 0.f, 0.f}, sm1[4] = {0.f, 0.f, 0.f, 0.f};
        if (s != NSEG - 1) {
            mbar_wait(sb + RB_SX, s & 1);
            if (w == 0) PROF(4);
            float sv[10];
#pragma unroll
            for (int n = 0; n < 5; n++) {
                const float2 a = lds64f(tb.w + n * 256), b = lds64f(tb.w + (5 + n) * 256);
                sv[2 * n] = a.x + b.x; sv[2 * n + 1] = a.y + b.y;
            }
            float mx = fmaxf(fmaxf(fmaxf(sv[0], sv[1]), fmaxf(sv[2], sv[3])), fmaxf(fmaxf(sv[4], sv[5]), fmaxf(sv[6], sv[7])));
            mx = fmaxf(mx, fmaxf(sv[8], sv[9]));
            mx = fmaxf(mx, __shfl_xor_sync(~0u, mx, 1));
            mx = fmaxf(mx, __shfl_xor_sync(~0u, mx, 2));
#pragma unroll
            for (int n = 1; n < 5; n++) pf[n] = pack2(ex2(sv[2 * n] - mx), ex2(sv[2 * n + 1] - mx));
            pf[0] = pack2(ex2(sv[0] - mx), ex2(sv[1] - mx));
            if (w == 0) PROF(12);
            const uint32_t one = 0x3F803F80u;
            mma16816h(sm0, pf[1], pf[2], one, one);
            mma16816h(oa[0], pf[1], pf[2], vx[0], vx[1]);
            mma16816h(oa[1], pf[1], pf[2], vx[2], vx[3]);
            mma16816h(sm1, pf[3], pf[4], one, one);
            mma16816h(ob_[0], pf[3], pf[4], vx[4], vx[5]);
            mma16816h(ob_[1], pf[3], pf[4], vx[6], vx[7]);
            mma1688h(sm0, pf[0], one);
            mma1688h(oa[0], pf[0], vb0);
            mma1688h(oa[1], pf[0], vb1);
            float inv;
            asm("rcp.approx.ftz.f32 %0, %1;" : "=f"(inv) : "f"(sm0[0] + sm1[0]));
            oa[0][0] += ob_[0][0]; oa[0][1] += ob_[0][1]; oa[1][0] += ob_[1][0]; oa[1][1] += ob_[1][1];
            sts32(ta.y, pack2(oa[0][0] * inv, oa[0][1] * inv));
            sts32(ta.y ^ 16, pack2(oa[1][0] * inv, oa[1][1] * inv));
            const uint32_t oa2 = ta.w ^ 64;
            bar_sync(NB_C, 128);
            if (w == 0) PROF(5);
            uint32_t ob[8];
            ldsm4(ob[0], ob[1], ob[2], ob[3], ta.w);
            ldsm4(ob[4], ob[5], ob[6], ob[7], oa2);
#pragma unroll
            for (int i = 4; i < 8; i++) {
                const uint4 f0 = lds128(tab + 4096 + i * 2048);
                wo[i][0][0] = f0.x; wo[i][0][1] = f0.y; wo[i][0][2] = f0.z; wo[i][0][3] = f0.w;
            }
#pragma unroll
            for (int jj = 0; jj < 2; jj++) {
                if (jj == 1 && tb.w == 0) break;
                float acc[4][4];
#pragma unroll
                for (int c = 0; c < 4; c++) { acc[c][0] = acc[c][1] = acc[c][2] = acc[c][3] = 0.f; }
#pragma unroll
                for (int ks = 0; ks < 4; ks++)
#pragma unroll
                    for (int c = 0; c < 4; c++)
                        mma16816(acc[c], wo[jj * 4 + c][ks][0], wo[jj * 4 + c][ks][1], wo[jj * 4 + c][ks][2], wo[jj * 4 + c][ks][3], ob[2 * ks], ob[2 * ks + 1]);
#pragma unroll
                for (int pr = 0; pr < 2; pr++) {
                    uint4 v;
                    v.x = pack2(acc[2 * pr][0], acc[2 * pr][1]);
                    v.y = pack2(acc[2 * pr][2], acc[2 * pr][3]);
                    v.z = pack2(acc[2 * pr + 1][0], acc[2 * pr + 1][1]);
                    v.w = pack2(acc[2 * pr + 1][2], acc[2 * pr + 1][3]);
                    st_async_v4(tb.x + ((jj * 2 + pr) << 24), v, tb.y + ((jj * 2 + pr) << 24));
                }
            }
            if (w == 0) PROF(6);
        }
        {
            stsm2t(ta.z, vb0, vb1);
            cp_async_wait<0>();
            bar_sync(NB_C, 128);
            if (w == 0 && lane == 0 && s != NSEG - 1) mbar_expect_tx(sb + RB_SX, 2560);
            const int omat = w >> 1, otok = (w & 1) * 4 + (lane >> 3), och = lane & 7;
            const uint4 v = lds128(sb + (omat ? R_VMS : R_KMS) + otok * 128 + ((och ^ otok) << 4));
            *(uint4*)(g_kvm + ((s * 8 + otok) * (2 * HD_) + omat * HD_ + col0 + och * 8)) = v;
            if (s != NSEG - 1) bar_arrive(NB_D, 384);
#pragma unroll
            for (int i = 0; i < 2 * VK0; i++) av[i] = lds128(lane16 + R_WV + (i / VK0) * 32768 + (w * 16 + i % VK0) * 512);
            if (s + 2 < NSEG - 1) {
                if (((s + 2) & 3) == 0) { if (lane == 0) wait_flag(F_KV + ((s + 2) >> 2), 64); __syncwarp(); }
                rec_load_kv(sb, col0, s + 2, slot_off == 0 ? (R_NST - 1) * 4096 : slot_off - 4096, w * 32 + lane);
            }
            cp_async_commit();
            if ((s & 3) == 3) {
                bar_sync(NB_C, 128);
                if (w == 0 && lane == 0) red_release(&g_flags[F_MEM + (s >> 2)], 1);
            }
        }
        slot_off = slot_off == (R_NST - 1) * 4096 ? 0 : slot_off + 4096;
    }
}

__global__ void __launch_bounds__(384, 1) k_rec(const RecParams p) {
    extern __shared__ __align__(1024) unsigned char smem_raw[];
    const uint32_t sb = __shfl_sync(~0u, smem_u32(smem_raw), 0);
    const int warp = __shfl_sync(~0u, threadIdx.x >> 5, 0);
    int lane; asm volatile("mov.u32 %0, %%laneid;" : "=r"(lane));
    const int crank = blockIdx.x & 15, slot = blockIdx.x >> 4;
    asm volatile("griddepcontrol.launch_dependents;");
    if (threadIdx.x == 0) {
        mbar_init(sb + RB_SX, 1); mbar_init(sb + RB_E, 1); mbar_init(sb + RB_A, 1); mbar_init(sb + RB_ROLE, 1);
        asm volatile("fence.mbarrier_init.release.cluster;" ::: "memory");
        mbar_expect_tx(sb + RB_SX, 2560);
        mbar_expect_tx(sb + RB_E, 8192);
        mbar_expect_tx(sb + RB_A, 8192);
        mbar_expect_tx(sb + RB_ROLE, 4);
    }
    unsigned role = 0;
    if (crank == 0 && threadIdx.x == 0) {
        unsigned x = 0;
        int tm[2] = {0x7fffffff, 0x7fffffff};
#pragma unroll 1
        for (int i = 0; i < 6; i++) {
            const uint32_t t0 = clk32();
            x = atomicAdd(&g_F[65536 + (i & 1) * 1024 + slot * 64 + (x >> 31)], 0u) & 0x7fffffffu;
            if (x == 0x7654321u) sts32(sb + R_BAR + 56, x);
            const int dt = (int)(clk32() - t0);
            if (i >= 2) { if (i & 1) tm[1] = min(tm[1], dt); else tm[0] = min(tm[0], dt); }
        }
        const int side = tm[1] > tm[0];
        const unsigned old = atomicAdd(&g_flags[F_SIDE + side * 32], 1u);
        unsigned c0, c1; int gd = 0;
#pragma unroll 1
        do { c0 = ldg_relaxed32(&g_flags[F_SIDE]); c1 = ldg_relaxed32(&g_flags[F_SIDE + 32]); } while ((int)(c0 + c1) < p.ncl && ++gd < 64 * SPIN_LIMIT);
        const int big = c1 > c0;
        role = side == big ? old : (big ? c1 : c0) + old;
        role |= (big ^ 1) << 8;
    }
    __syncwarp();
    asm volatile("barrier.cluster.arrive.relaxed.aligned;\nbarrier.cluster.wait.aligned;" ::: "memory");
    if (crank == 0 && warp == 0) {
        role = __shfl_sync(~0u, role, 0);
        if (lane < 16)
            asm volatile("st.async.weak.shared::cluster.mbarrier::complete_tx::bytes.u32 [%0], %1, [%2];"
                         :: "r"(mapa_u32(sb + R_BAR + 48, lane)), "r"(role), "r"(mapa_u32(sb + RB_ROLE, lane)) : "memory");
    }
    mbar_wait(sb + RB_ROLE, 0);
    const int rolew = __shfl_sync(~0u, lds32(sb + R_BAR + 48), 0);
    const int cl = rolew & 255;
    if (cl >= 4) return;
    const int cta = cl * 16 + crank;
    if (warp < 8) rec_qk(p, sb, cta, warp, lane, rolew >> 8);
    else rec_vo(p, sb, cta, warp, lane);
}

enum { J_KV = 0, J_QA = 1, J_O = 2, J_LN = 3, J_UP = 4, J_DN = 5, J_UP2 = 6, J_END = 8 };
constexpr int NJ_O = 2 * OSPLIT, NJ_O2 = 2 * OSPLIT2, NJ_LN = 8, NJ_LN2 = 16, NJ_UP = 14, NJ_UP2 = 28, NJ_DN = 8;
__device__ __forceinline__ int nj_coarse(int q) { return q == J_KV ? 32 : (q == J_QA ? 16 : (q == J_O ? NJ_O : (q == J_LN ? NJ_LN : (q == J_UP ? NJ_UP : NJ_DN)))); }
__device__ __forceinline__ int nj_fine(int q) { return q == J_KV ? 32 : (q == J_QA ? 16 : (q == J_O ? NJ_O2 : (q == J_LN ? NJ_LN2 : (q == J_UP ? NJ_UP2 : NJ_DN)))); }
__device__ __forceinline__ int pick_job(int lane, int qmask, int& idx) {
    const int rb = lane & 15, half = lane >> 4;
    const bool fine = rb >= FINE_RB;
    int gd = 0;
#pragma unroll 1
    while (true) {
        unsigned cl[3], dp[3];
#pragma unroll
        for (int i = 0; i < 3; i++) {
            const int q = half + 2 * i;
            cl[i] = ldg_relaxed32(&g_flags[F_CLAIM + q * 32 + rb]);
            dp[i] = ldg_relaxed32(&g_flags[q * 32 + (q == J_QA ? max(rb - 1, 0) : rb)]);
        }
        int pick_q = -1, pick_rb = 0, early_q = -1, early_rb = 0;
        bool any = false;
#pragma unroll
        for (int i = 0; i < 3; i++) {
            const int q = half + 2 * i;
            const bool have = ((qmask >> q) & 1) && (int)cl[i] < (fine ? nj_fine(q) : nj_coarse(q));
            const unsigned tgt = q == J_QA ? 64 : 2 * (fine ? nj_fine(q - 1) : nj_coarse(q - 1));
            const bool ready = have && (q == J_KV || (q == J_QA && rb == 0) || dp[i] >= tgt);
            const unsigned mh = __ballot_sync(~0u, have), mr = __ballot_sync(~0u, ready);
            any |= mh != 0;
#pragma unroll
            for (int hf = 0; hf < 2; hf++) {
                const int qq = hf + 2 * i;
                const unsigned r16 = (mr >> (16 * hf)) & 0xffffu, h16 = (mh >> (16 * hf)) & 0xffffu;
                if (r16 && pick_q != J_KV) { pick_q = qq; pick_rb = __ffs(r16) - 1; }
                if (qq >= J_O && early_q < 0 && h16 && __ffs(h16) - 1 >= FINE_RB) { early_q = qq; early_rb = __ffs(h16) - 1; }
            }
        }
        if (!any) return J_END;
        if (pick_q < 0) { pick_q = early_q; pick_rb = early_rb; }
        if (pick_q >= 0) {
            int c = 0;
            if (lane == 0) c = (int)atomicAdd(&g_flags[F_CLAIM + pick_q * 32 + pick_rb], 1u);
            c = __shfl_sync(~0u, c, 0);
            const bool f = pick_rb >= FINE_RB;
            if (c < (f ? nj_fine(pick_q) : nj_coarse(pick_q))) {
                idx = pick_q * 600 + pick_rb * 32 + c;
                return (pick_q == J_UP && f ? J_UP2 : pick_q) | (pick_rb << 8) | (c << 16);
            }
        } else {
            __nanosleep(200);
            if (++gd > 16 * SPIN_LIMIT) { TIMEOUT(5, 0); return J_END; }
        }
    }
}
__device__ __forceinline__ int op_row(int rb, int split) {
    return rb < FINE_RB ? split * S_ + rb * 128 : OSPLIT * S_ + (split * (NRB - FINE_RB) + rb - FINE_RB) * 128;
}

struct Pipe { uint32_t stage, phase; };
__device__ __forceinline__ void pipe_next(Pipe& p) { if (++p.stage == W_NST) { p.stage = 0; p.phase ^= 1; } }

__device__ __forceinline__ void scheduler(const Params& p, uint32_t sb, int lane) {
    const uint32_t bars = sb + SM_BAR;
    uint32_t ph = 0;
#pragma unroll 1
    while (true) {
        mbar_wait(bars + B_REQ, ph);
        int j = 4095;
        const int jd = pick_job(lane, p.qmask, j);
        if (lane == 0) { sts32(bars + B_NEXT, (uint32_t)jd); sts32(bars + B_NEXT + 4, (uint32_t)j); mbar_arrive(bars + B_RSP); }
        ph ^= 1;
        if (jd == J_END) break;
        __syncwarp();
    }
}

__device__ __forceinline__ void producer(const Params& p, uint32_t sb) {
    Pipe pp{0, 1};
    const uint32_t bars = sb + SM_BAR;
    uint32_t seq = 0;
    mbar_arrive(bars + B_REQ);
#pragma unroll 1
    while (true) {
        mbar_wait(bars + B_RSP, seq & 1);
        const int jd = (int)lds32(bars + B_NEXT), j = (int)lds32(bars + B_NEXT + 4);
        int left = (jd & 255) == J_DN ? 15 : ((jd & 255) == J_QA ? 12 : ((jd & 255) == J_O ? (((jd >> 8) & 255) >= FINE_RB ? 64 / OSPLIT2 : 64 / OSPLIT) : ((jd & 255) == J_LN ? 1 : 8)));
        left = max(left - PICK_AHEAD, 1);
        TR(j, 1);
        const int type = jd & 255, rb = (jd >> 8) & 255, cb = jd >> 16;
        const bool fine = rb >= FINE_RB;
        bool first = true;
        auto begin_stage = [&](uint32_t bytes) -> uint32_t {
            mbar_wait(bars + B_EMPTY + pp.stage * 8, pp.phase);
            if (first) { sts32(bars + B_RING + (seq & 7) * 4, (uint32_t)jd); sts32(bars + B_RING + 32 + (seq & 7) * 4, (uint32_t)j); first = false; }
            const uint32_t fb = bars + B_FULL + pp.stage * 8;
            if (bytes) mbar_expect_tx(fb, bytes); else mbar_arrive(fb);
            if (--left == 0 && type != J_END) mbar_arrive(bars + B_REQ);
            return fb;
        };
        if (type == J_END || type == J_LN) {
            if (type == J_LN) wait_flag(F_OP + rb, 2 * (fine ? NJ_O2 : NJ_O));
            TR(j, 2);
            begin_stage(0); pipe_next(pp);
            seq++;
            if (type == J_END) break;
            continue;
        }
        const CUtensorMap *ta, *tb0, *tb1;
        int k0 = 0, nk = 8, n0 = cb * 256, n1 = n0 + 128, nb = 4, dep = -1;
        unsigned tgt = 0;
        switch (type) {
            case J_KV: ta = &p.tm_h; tb0 = tb1 = cb < 16 ? &p.tm_wk : &p.tm_wv; n0 = (cb & 15) * 256; n1 = n0 + 128; break;
            case J_QA: ta = &p.tm_h; tb0 = tb1 = &p.tm_wq; break;
            case J_O: ta = &p.tm_o; tb0 = tb1 = &p.tm_wo; n0 = (cb & 1) * 256; n1 = n0 + 128; nk = fine ? 64 / OSPLIT2 : 64 / OSPLIT; k0 = (cb >> 1) * nk * 64;
                      dep = F_O + rb; tgt = 32; break;
            case J_UP: ta = &p.tm_h2; tb0 = &p.tm_wg; tb1 = &p.tm_wu; n0 = n1 = cb * 128; dep = F_H2 + rb; tgt = 2 * NJ_LN; break;
            case J_UP2: ta = &p.tm_h2; tb0 = &p.tm_wg; tb1 = &p.tm_wu; n0 = n1 = cb * 64; nb = 2; dep = F_H2 + rb; tgt = 2 * NJ_LN2; break;
            default: ta = &p.tm_act; tb0 = tb1 = &p.tm_wd; n0 = cb * 64; nk = 0; break;
        }
        const int m0 = rb * 128;
        if (type == J_DN) {
#pragma unroll 1
            for (int kb = 0; kb < 14; kb++) {
                const uint32_t fb = begin_stage(49152);
                const uint32_t st = sb + pp.stage * W_STAGE;
                const int k = kb * 128;
                tma_load2d(st + 32768, tb0, n0, k, fb);
                tma_load2d(st + 40960, tb0, n0, k + 64, fb);
                if (kb == 0) { wait_flag(F_ACT + rb, 2 * (fine ? NJ_UP2 : NJ_UP)); fence_async_all(); TR(j, 2); }
                tma_load2d(st, ta, k, m0, fb);
                tma_load2d(st + 8192, ta, k, m0 + 64, fb);
                tma_load2d(st + 16384, ta, k + 64, m0, fb);
                tma_load2d(st + 24576, ta, k + 64, m0 + 64, fb);
                pipe_next(pp);
            }
        }
#pragma unroll 1
        for (int kb = 0; kb < nk; kb++) {
            const uint32_t fb = begin_stage(16384 + nb * 8192);
            const uint32_t st = sb + pp.stage * W_STAGE;
            const int k = k0 + kb * 64;
            tma_load2d(st + 16384, tb0, n0, k, fb);
            if (nb == 4) {
                tma_load2d(st + 16384 + 8192, tb0, n0 + 64, k, fb);
                tma_load2d(st + 16384 + 16384, tb1, n1, k, fb);
                tma_load2d(st + 16384 + 24576, tb1, n1 + 64, k, fb);
            } else if (nb == 2) {
                tma_load2d(st + 16384 + 8192, tb1, n1, k, fb);
            }
            if (kb == 0) {
                if (dep >= 0) { wait_flag(dep, tgt); if (type >= J_UP) fence_async_all(); }
                TR(j, 2);
            }
            tma_load2d(st, ta, k, m0, fb);
            tma_load2d(st + 8192, ta, k, m0 + 64, fb);
            pipe_next(pp);
        }
        if (type == J_QA) {
            wait_flag(F_KV + rb, 64);
#pragma unroll 1
            for (int i = 0; i < 4; i++) {
                const uint32_t fb = begin_stage(40960);
                const uint32_t st = sb + pp.stage * W_STAGE;
                const int col = (i & 1) * HD_ + (cb * 2 + (i >> 1)) * DH_;
                tma_load2d(st, &p.tm_kv, col, m0, fb);
                tma_load2d(st + 8192, &p.tm_kv, col, m0 + 64, fb);
                tma_load2d(st + 16384, &p.tm_kv, col + 64, m0, fb);
                tma_load2d(st + 24576, &p.tm_kv, col + 64, m0 + 64, fb);
                if (i == 0) { wait_flag(F_MEM + rb, 64); fence_async_all(); }
                tma_load2d(st + 32768, &p.tm_kvm, col, rb * 32, fb);
                tma_load2d(st + 36864, &p.tm_kvm, col + 64, rb * 32, fb);
                pipe_next(pp);
            }
        } else if (type == J_DN) {
            const uint32_t fb = begin_stage(16384);
            const uint32_t st = sb + pp.stage * W_STAGE;
            tma_load2d(st, &p.tm_x1, n0, m0, fb);
            tma_load2d(st + 8192, &p.tm_x1, n0, m0 + 64, fb);
            pipe_next(pp);
        }
        seq++;
    }
}

__device__ __forceinline__ void store_warp(const Params& p, uint32_t sb, int wg, int lane) {
    const uint32_t bars = sb + SM_BAR;
    uint32_t seq = 0;
#pragma unroll 1
    while (true) {
        bar_sync(NB_ST + wg, 160);
        const uint32_t jd = lds32(bars + B_RING + (seq & 7) * 4);
        seq++;
        const int type = jd & 255, rb = (jd >> 8) & 255, cb = jd >> 16;
        if (type == J_END) break;
        if (lane == 0) {
            const uint32_t src = sb + W_STG + wg * 32768;
            const CUtensorMap* tm = nullptr; int n0 = cb * 256, nbox = 4, mrow = rb * 128 + wg * 64, flag = 0;
            switch (type) {
                case J_KV: tm = &p.tm_kv; flag = F_KV + rb; break;
                case J_QA: tm = &p.tm_o; flag = F_O + rb; break;
                case J_O: tm = &p.tm_op; n0 = (cb & 1) * 256; mrow = op_row(rb, cb >> 1) + wg * 64; flag = F_OP + rb; break;
                case J_LN: flag = F_H2 + rb; nbox = 0; break;
                case J_UP: tm = &p.tm_act; n0 = cb * 128; nbox = 2; flag = F_ACT + rb; break;
                case J_UP2: tm = &p.tm_act; n0 = cb * 64; nbox = 1; flag = F_ACT + rb; break;
                default: tm = &p.tm_out; n0 = cb * 64; nbox = 1; flag = -1; break;
            }
#pragma unroll 1
            for (int b = 0; b < nbox; b++) tma_store2d(tm, src + b * 8192, n0 + b * 64, mrow);
            bulk_commit();
            bulk_wait0();
            mbar_arrive(bars + B_STGFREE + wg * 8);
            if (flag >= 0) red_release(&g_flags[flag], 1);
        }
        __syncwarp();
    }
}

__device__ __forceinline__ float gelu_tanh(float x) {
    const float t = x * fmaf(-0.10294324397f, x * x, -2.30220819814f);
    float r; asm("rcp.approx.ftz.f32 %0, %1;" : "=f"(r) : "f"(1.f + ex2(t)));
    return x * r;
}

#define CTR(i) do {} while (0)

template <int NSPLIT>
__device__ __forceinline__ void ln2_row(const Params& p, int rb, int r, int lane) {
    const int row = rb * 128 + r;
    uint4 u[2 * NSPLIT];
#pragma unroll
    for (int sp = 0; sp < NSPLIT; sp++) {
        const uint4* src = (const uint4*)(g_op + (size_t)(op_row(rb, sp) + r) * D_);
        u[2 * sp] = __ldcg(src + lane); u[2 * sp + 1] = __ldcg(src + 32 + lane);
    }
    const uint4* xr = (const uint4*)(p.x + (size_t)row * D_);
    const uint4 xa = __ldg(xr + lane), xb = __ldg(xr + 32 + lane);
    uint32_t ga[8], c1[8], sm[8];
    load_mod8(g_mod + 2 * D_, lane, ga);
    load_mod8(g_mod + 4 * D_, lane, c1);
    load_mod8(g_mod + 3 * D_, lane, sm);
    float a[16];
#pragma unroll
    for (int i = 0; i < 16; i++) a[i] = 0.f;
#pragma unroll
    for (int sp = 0; sp < 2 * NSPLIT; sp++) {
        float* q = a + (sp & 1) * 8;
        q[0] += bflo(u[sp].x); q[1] += bfhi(u[sp].x); q[2] += bflo(u[sp].y); q[3] += bfhi(u[sp].y);
        q[4] += bflo(u[sp].z); q[5] += bfhi(u[sp].z); q[6] += bflo(u[sp].w); q[7] += bfhi(u[sp].w);
    }
    const uint32_t xv[8] = {xa.x, xa.y, xa.z, xa.w, xb.x, xb.y, xb.z, xb.w};
    uint32_t v[8], r8[8];
#pragma unroll
    for (int i = 0; i < 8; i++) v[i] = hadd2(xv[i], hmul2(ga[i], pack2(a[2 * i], a[2 * i + 1])));
    uint4* x1r = (uint4*)(g_x1 + (size_t)row * D_);
    x1r[lane] = make_uint4(v[0], v[1], v[2], v[3]); x1r[32 + lane] = make_uint4(v[4], v[5], v[6], v[7]);
    uint32_t mu2; float rden;
    ln_stats(v, mu2, rden);
#pragma unroll
    for (int i = 0; i < 8; i++) c1[i] = hadd2(c1[i], 0x3F803F80u);
    ln_apply(v, mu2, rden, c1, sm, r8);
    uint4* hr = (uint4*)(g_h2 + (size_t)row * D_);
    hr[lane] = make_uint4(r8[0], r8[1], r8[2], r8[3]); hr[32 + lane] = make_uint4(r8[4], r8[5], r8[6], r8[7]);
}

__device__ __forceinline__ void consumer(const Params& p, uint32_t sb, int warp, int lane) {
    const uint32_t bars = sb + SM_BAR;
    const int wg = warp >> 2, wl = warp & 3;
    const uint32_t l7 = lane & 7, l8 = lane >> 3, g = lane >> 2, t = lane & 3;
    Pipe pp{0, 0};
    uint32_t seq = 0, stg_phase = 1;
    const int srow = wl * 16 + l7 + (l8 & 1) * 8;
    const uint32_t stg_base = sb + W_STG + wg * 32768 + srow * 128;
    const uint32_t sx = ((lane >> 4) ^ (srow & 7)) << 4;
#pragma unroll 1
    while (true) {
        mbar_wait(bars + B_FULL + pp.stage * 8, pp.phase);
        const uint32_t jd = lds32(bars + B_RING + (seq & 7) * 4);
        CTR(3);
        seq++;
        const int type = jd & 255, rb = (jd >> 8) & 255, cb = jd >> 16;
        if (type == J_END) { mbar_wait(bars + B_STGFREE + wg * 8, stg_phase); bar_arrive(NB_ST + wg, 160); break; }
        if (type == J_LN) {
            __syncwarp();
            if (lane == 0) mbar_arrive(bars + B_EMPTY + pp.stage * 8);
            pipe_next(pp);
            if (rb >= FINE_RB) ln2_row<OSPLIT2>(p, rb, cb * 8 + warp, lane);
            else {
#pragma unroll 1
                for (int rr = 0; rr < 2; rr++) ln2_row<OSPLIT>(p, rb, cb * 16 + warp * 2 + rr, lane);
            }
            mbar_wait(bars + B_STGFREE + wg * 8, stg_phase); stg_phase ^= 1;
            CTR(4); CTR(5);
            bar_arrive(NB_ST + wg, 160);
            continue;
        }
        if (type >= J_DN) {
            float acc[64];
#pragma unroll
            for (int i = 0; i < 64; i++) acc[i] = 0.f;
            if (type == J_DN) {
#pragma unroll 1
                for (int kb = 0; kb < 14; kb++) {
                    if (kb) mbar_wait(bars + B_FULL + pp.stage * 8, pp.phase);
                    const uint32_t st = sb + pp.stage * W_STAGE;
                    const uint64_t da = mkdesc(st + wg * 8192, 16, 1024), db = mkdesc(st + 32768, 8192, 1024);
                    wg_fence();
#pragma unroll
                    for (int ks = 0; ks < 8; ks++) wgmma_n64(acc, da + (ks >> 2) * 1024 + (ks & 3) * 2, db + ks * 128);
                    wg_commit();
                    wg_wait0();
                    if (lane == 0) mbar_arrive(bars + B_EMPTY + pp.stage * 8);
                    pipe_next(pp);
                }
            } else {
#pragma unroll 1
                for (int kb = 0; kb < 8; kb++) {
                    if (kb) mbar_wait(bars + B_FULL + pp.stage * 8, pp.phase);
                    const uint32_t st = sb + pp.stage * W_STAGE;
                    const uint64_t da = mkdesc(st + wg * 8192, 16, 1024), db = mkdesc(st + 16384, 8192, 1024);
                    wg_fence();
#pragma unroll
                    for (int ks = 0; ks < 4; ks++) wgmma_n128(acc, da + ks * 2, db + ks * 128, 1);
                    wg_commit();
                    wg_wait0();
                    if (lane == 0) mbar_arrive(bars + B_EMPTY + pp.stage * 8);
                    pipe_next(pp);
                }
            }
            CTR(4);
            if (type == J_UP2) {
                mbar_wait(bars + B_STGFREE + wg * 8, stg_phase); stg_phase ^= 1;
#pragma unroll
                for (int j = 0; j < 4; j++) {
                    uint32_t r[4];
#pragma unroll
                    for (int q = 0; q < 4; q++) {
                        const uint32_t gw = pack2(acc[8 * j + 2 * q], acc[8 * j + 2 * q + 1]);
                        const uint32_t uw = pack2(acc[32 + 8 * j + 2 * q], acc[32 + 8 * j + 2 * q + 1]);
                        r[q] = hmul2(pack2(gelu_tanh(bflo(gw)), gelu_tanh(bfhi(gw))), uw);
                    }
                    stsm4(stg_base + (sx ^ (j << 5)), r[0], r[1], r[2], r[3]);
                }
            } else {
                mbar_wait(bars + B_FULL + pp.stage * 8, pp.phase);
                const uint32_t st = sb + pp.stage * W_STAGE;
                mbar_wait(bars + B_STGFREE + wg * 8, stg_phase); stg_phase ^= 1;
                const uint32_t* gb = (const uint32_t*)(g_mod + 5 * D_ + cb * 64) + t;
                const uint32_t xa = st + wg * 8192 + (wl * 16 + g) * 128 + (g << 4) + t * 4;
#pragma unroll
                for (int j = 0; j < 4; j++) {
                    uint32_t r[4];
#pragma unroll
                    for (int q = 0; q < 4; q++) {
                        const int nt = 2 * j + (q >> 1);
                        const uint32_t xw = lds32((xa ^ ((nt & 7) << 4)) + (nt >> 3) * 16384 + (q & 1) * 1024);
                        r[q] = hadd2(xw, hmul2(__ldcg(gb + nt * 4), pack2(acc[8 * j + 2 * q], acc[8 * j + 2 * q + 1])));
                    }
                    stsm4(stg_base + (j >> 2) * 8192 + (sx ^ ((2 * j & 7) << 4)), r[0], r[1], r[2], r[3]);
                }
                __syncwarp();
                if (lane == 0) mbar_arrive(bars + B_EMPTY + pp.stage * 8);
                pipe_next(pp);
            }
            fence_async_smem();
            CTR(5);
            bar_arrive(NB_ST + wg, 160);
            continue;
        }
        float acc[128];
#pragma unroll
        for (int i = 0; i < 128; i++) acc[i] = 0.f;
        const int nk = type == J_O ? (rb >= FINE_RB ? 64 / OSPLIT2 : 64 / OSPLIT) : 8;
#pragma unroll 1
        for (int kb = 0; kb < nk; kb++) {
            if (kb) mbar_wait(bars + B_FULL + pp.stage * 8, pp.phase);
            const uint32_t st = sb + pp.stage * W_STAGE;
            const uint64_t da = mkdesc(st + wg * 8192, 16, 1024), db = mkdesc(st + 16384, 8192, 1024);
            wg_fence();
#pragma unroll
            for (int ks = 0; ks < 4; ks++) wgmma_n256(acc, da + ks * 2, db + ks * 128, 1);
            wg_commit();
            wg_wait0();
            if (lane == 0) mbar_arrive(bars + B_EMPTY + pp.stage * 8);
            pipe_next(pp);
        }
        CTR(4);
        if (type == J_QA) {
            uint32_t qf[64];
#pragma unroll
            for (int i = 0; i < 64; i++) qf[i] = pack2(acc[2 * i], acc[2 * i + 1]);
            const int sg = warp >> 1, half = warp & 1;
            const float sc = 0.08838834764831845f * 1.4426950408889634f;
            const uint32_t xoff = (sg >> 1) * 8192 + ((sg & 1) * 32 + l7) * 128;
            const uint32_t moff = 32768 + (sg * 8 + l7) * 128;
            const uint32_t kch = (l8 ^ l7) << 4;
            const uint32_t vch = ((l8 & 1) ^ l7) << 4;
            mbar_wait(bars + B_STGFREE + wg * 8, stg_phase); stg_phase ^= 1;
#pragma unroll 1
            for (int hh = 0; hh < 2; hh++) {
                mbar_wait(bars + B_FULL + pp.stage * 8, pp.phase);
                uint32_t st = sb + pp.stage * W_STAGE;
                float sa[5][4];
#pragma unroll
                for (int n = 0; n < 5; n++) sa[n][0] = sa[n][1] = sa[n][2] = sa[n][3] = 0.f;
#pragma unroll
                for (int i = 0; i < 4; i++) {
                    const uint32_t* q = qf + i * 8;
                    uint32_t kk[5][4];
                    ldsm4(kk[0][0], kk[0][1], kk[0][2], kk[0][3], st + moff + (i >> 1) * 4096 + (kch ^ ((i & 1) * 64)));
#pragma unroll
                    for (int n = 1; n < 5; n++)
                        ldsm4(kk[n][0], kk[n][1], kk[n][2], kk[n][3], st + xoff + (n - 1) * 1024 + (i >> 1) * 16384 + (kch ^ ((i & 1) * 64)));
#pragma unroll
                    for (int n = 0; n < 5; n++) mma16816(sa[n], q[0], q[1], q[2], q[3], kk[n][0], kk[n][1]);
#pragma unroll
                    for (int n = 0; n < 5; n++) mma16816(sa[n], q[4], q[5], q[6], q[7], kk[n][2], kk[n][3]);
                }
                __syncwarp();
                if (lane == 0) mbar_arrive(bars + B_EMPTY + pp.stage * 8);
                pipe_next(pp);
                const int iq0 = half * 16 + g - 2 * t, iq1 = iq0 + 8;
                float m0 = fmaxf(sa[0][0], sa[0][1]), m1 = fmaxf(sa[0][2], sa[0][3]);
#pragma unroll
                for (int n = 1; n < 5; n++) {
#pragma unroll
                    for (int e = 0; e < 2; e++) {
                        const int jx = (n - 1) * 8 + e;
                        if (jx > iq0) sa[n][e] = -3.0e38f;
                        if (jx > iq1) sa[n][2 + e] = -3.0e38f;
                        m0 = fmaxf(m0, sa[n][e]); m1 = fmaxf(m1, sa[n][2 + e]);
                    }
                }
                m0 = fmaxf(m0, __shfl_xor_sync(~0u, m0, 1)); m1 = fmaxf(m1, __shfl_xor_sync(~0u, m1, 1));
                m0 = fmaxf(m0, __shfl_xor_sync(~0u, m0, 2)); m1 = fmaxf(m1, __shfl_xor_sync(~0u, m1, 2));
                m0 *= -sc; m1 *= -sc;
                float l0 = 0.f, l1 = 0.f;
                uint32_t p0[5], p1[5];
#pragma unroll
                for (int n = 0; n < 5; n++) {
                    const float e0 = ex2(fmaf(sa[n][0], sc, m0)), e1 = ex2(fmaf(sa[n][1], sc, m0));
                    const float e2 = ex2(fmaf(sa[n][2], sc, m1)), e3 = ex2(fmaf(sa[n][3], sc, m1));
                    l0 += e0 + e1; l1 += e2 + e3;
                    p0[n] = pack2(e0, e1); p1[n] = pack2(e2, e3);
                }
                l0 += __shfl_xor_sync(~0u, l0, 1); l1 += __shfl_xor_sync(~0u, l1, 1);
                l0 += __shfl_xor_sync(~0u, l0, 2); l1 += __shfl_xor_sync(~0u, l1, 2);
                const float i0 = __fdividef(1.f, l0), i1 = __fdividef(1.f, l1);
                mbar_wait(bars + B_FULL + pp.stage * 8, pp.phase);
                st = sb + pp.stage * W_STAGE;
#pragma unroll
                for (int i = 0; i < 32; i++) qf[i] = qf[32 + i];
#pragma unroll 1
                for (int bx = 0; bx < 2; bx++) {
                    float o[8][4];
                    uint32_t vm[8], v0[4][4], v1[4][4];
#pragma unroll
                    for (int ep = 0; ep < 4; ep++) {
                        ldsm2t(vm[2 * ep], vm[2 * ep + 1], st + moff + bx * 4096 + (vch ^ (ep << 5)));
                        const uint32_t va = st + xoff + (l8 >> 1) * 1024 + bx * 16384 + (vch ^ (ep << 5));
                        ldsm4t(v0[ep][0], v0[ep][1], v0[ep][2], v0[ep][3], va);
                        ldsm4t(v1[ep][0], v1[ep][1], v1[ep][2], v1[ep][3], va + 2048);
                    }
#pragma unroll
                    for (int n = 0; n < 8; n++) { o[n][0] = o[n][1] = o[n][2] = o[n][3] = 0.f; mma16816(o[n], p0[0], p1[0], p0[1], p1[1], vm[n], v0[n >> 1][n & 1]); }
#pragma unroll
                    for (int n = 0; n < 8; n++) mma16816(o[n], p0[2], p1[2], p0[3], p1[3], v0[n >> 1][2 + (n & 1)], v1[n >> 1][n & 1]);
#pragma unroll
                    for (int n = 0; n < 8; n++) mma1688(o[n], p0[4], p1[4], v1[n >> 1][2 + (n & 1)]);
#pragma unroll
                    for (int ep = 0; ep < 4; ep++)
                        stsm4(stg_base + (hh * 2 + bx) * 8192 + (sx ^ (ep << 5)),
                              pack2(o[2 * ep][0] * i0, o[2 * ep][1] * i0), pack2(o[2 * ep][2] * i1, o[2 * ep][3] * i1),
                              pack2(o[2 * ep + 1][0] * i0, o[2 * ep + 1][1] * i0), pack2(o[2 * ep + 1][2] * i1, o[2 * ep + 1][3] * i1));
                }
                __syncwarp();
                if (lane == 0) mbar_arrive(bars + B_EMPTY + pp.stage * 8);
                pipe_next(pp);
            }
        } else if (type == J_UP) {
            mbar_wait(bars + B_STGFREE + wg * 8, stg_phase); stg_phase ^= 1;
#pragma unroll
            for (int j = 0; j < 8; j++) {
                uint32_t r[4];
#pragma unroll
                for (int q = 0; q < 4; q++) {
                    const uint32_t gw = pack2(acc[8 * j + 2 * q], acc[8 * j + 2 * q + 1]);
                    const uint32_t uw = pack2(acc[64 + 8 * j + 2 * q], acc[64 + 8 * j + 2 * q + 1]);
                    r[q] = hmul2(pack2(gelu_tanh(bflo(gw)), gelu_tanh(bfhi(gw))), uw);
                }
                stsm4(stg_base + (j >> 2) * 8192 + (sx ^ ((2 * j & 7) << 4)), r[0], r[1], r[2], r[3]);
            }
        } else {
            mbar_wait(bars + B_STGFREE + wg * 8, stg_phase); stg_phase ^= 1;
#pragma unroll
            for (int j = 0; j < 16; j++)
                stsm4(stg_base + (j >> 2) * 8192 + (sx ^ ((2 * j & 7) << 4)),
                      pack2(acc[8 * j], acc[8 * j + 1]), pack2(acc[8 * j + 2], acc[8 * j + 3]),
                      pack2(acc[8 * j + 4], acc[8 * j + 5]), pack2(acc[8 * j + 6], acc[8 * j + 7]));
        }
        fence_async_smem();
        CTR(5);
        bar_arrive(NB_ST + wg, 160);
    }
}

__global__ void __launch_bounds__(384, 1) k_work(const __grid_constant__ Params p) {
    extern __shared__ __align__(1024) unsigned char smem_raw[];
    const uint32_t sb = smem_u32(smem_raw);
    if (sb & 1023) __trap();
    const int warp = __shfl_sync(~0u, threadIdx.x >> 5, 0);
    int lane; asm volatile("mov.u32 %0, %%laneid;" : "=r"(lane));
    if (threadIdx.x == 0) {
        const uint32_t bars = sb + SM_BAR;
        for (int i = 0; i < W_NST; i++) { mbar_init(bars + B_FULL + i * 8, 1); mbar_init(bars + B_EMPTY + i * 8, 8); }
        mbar_init(bars + B_STGFREE, 1); mbar_init(bars + B_STGFREE + 8, 1); mbar_init(bars + B_REQ, 1); mbar_init(bars + B_RSP, 1);
        asm volatile("fence.mbarrier_init.release.cluster;" ::: "memory");
    }
    __syncthreads();
    if (warp < 8) {
        asm volatile("setmaxnreg.inc.sync.aligned.u32 232;");
        consumer(p, sb, warp, lane);
    } else {
        asm volatile("setmaxnreg.dec.sync.aligned.u32 40;");
        if (warp == 8) { if (lane == 0) producer(p, sb); }
        else if (warp < 11) store_warp(p, sb, warp - 9, lane);
        else scheduler(p, sb, lane);
    }
}

typedef CUresult (*EncodeFn)(CUtensorMap*, CUtensorMapDataType, cuuint32_t, void*, const cuuint64_t*, const cuuint64_t*,
                             const cuuint32_t*, const cuuint32_t*, CUtensorMapInterleave, CUtensorMapSwizzle,
                             CUtensorMapL2promotion, CUtensorMapFloatOOBfill);

static void make_map(EncodeFn enc, CUtensorMap* m, const void* ptr, uint64_t rows, uint64_t cols, uint32_t box_rows) {
    cuuint64_t dims[2] = {cols, rows};
    cuuint64_t strides[1] = {cols * 2};
    cuuint32_t box[2] = {64, box_rows};
    cuuint32_t es[2] = {1, 1};
    enc(m, CU_TENSOR_MAP_DATA_TYPE_BFLOAT16, 2, const_cast<void*>(ptr), dims, strides, box, es, CU_TENSOR_MAP_INTERLEAVE_NONE,
        CU_TENSOR_MAP_SWIZZLE_128B, CU_TENSOR_MAP_L2_PROMOTION_L2_256B, CU_TENSOR_MAP_FLOAT_OOB_FILL_NONE);
}
template <typename T> static void* sym_addr(T& sym) { void* p = nullptr; cudaGetSymbolAddress(&p, sym); return p; }

extern "C" void kernel_launch(void* const* d_in, const int* in_sizes, int n_in, void* d_out, int out_size) {
    static Params prm;
    static RecParams rp;
    static bool ready = false;
    static const void* key[14];
    bool same = ready;
    for (int i = 0; i < 13 && same; i++) same = key[i] == d_in[i];
    same = same && key[13] == d_out;
    if (!same) {
        void* fn = nullptr;
        cudaDriverEntryPointQueryResult qr;
        cudaGetDriverEntryPoint("cuTensorMapEncodeTiled", &fn, cudaEnableDefault, &qr);
        EncodeFn enc = (EncodeFn)fn;
        make_map(enc, &prm.tm_h, sym_addr(g_h), S_, D_, 64);
        make_map(enc, &prm.tm_kv, sym_addr(g_kv), S_, 2 * HD_, 64);
        make_map(enc, &prm.tm_kvm, sym_addr(g_kvm), NSEG * 8, 2 * HD_, 32);
        make_map(enc, &prm.tm_o, sym_addr(g_o), S_, HD_, 64);
        make_map(enc, &prm.tm_op, sym_addr(g_op), OP_ROWS, D_, 64);
        make_map(enc, &prm.tm_h2, sym_addr(g_h2), S_, D_, 64);
        make_map(enc, &prm.tm_act, sym_addr(g_act), S_, DF_, 64);
        make_map(enc, &prm.tm_x1, sym_addr(g_x1), S_, D_, 64);
        make_map(enc, &prm.tm_out, d_out, S_, D_, 64);
        make_map(enc, &prm.tm_wq, d_in[2], D_, HD_, 64);
        make_map(enc, &prm.tm_wk, d_in[3], D_, HD_, 64);
        make_map(enc, &prm.tm_wv, d_in[4], D_, HD_, 64);
        make_map(enc, &prm.tm_wo, d_in[5], HD_, D_, 64);
        make_map(enc, &prm.tm_wg, d_in[8], D_, DF_, 64);
        make_map(enc, &prm.tm_wu, d_in[9], D_, DF_, 64);
        make_map(enc, &prm.tm_wd, d_in[10], DF_, D_, 64);
        prm.x = (const bf16*)d_in[0];
        rp.mem0 = (const bf16*)d_in[1];
        rp.wq = (const bf16*)d_in[2]; rp.wk = (const bf16*)d_in[3]; rp.wv = (const bf16*)d_in[4]; rp.wo = (const bf16*)d_in[5];
        cudaFuncSetAttribute(k_work, cudaFuncAttributeMaxDynamicSharedMemorySize, SMEM_BYTES);
        cudaFuncSetAttribute(k_rec, cudaFuncAttributeMaxDynamicSharedMemorySize, R_SMEM);
        cudaFuncSetAttribute(k_rec, cudaFuncAttributeNonPortableClusterSizeAllowed, 1);
        {
            cudaLaunchConfig_t cfg = {};
            cfg.gridDim = dim3(128); cfg.blockDim = dim3(384); cfg.dynamicSmemBytes = R_SMEM;
            cudaLaunchAttribute at[1];
            at[0].id = cudaLaunchAttributeClusterDimension; at[0].val.clusterDim.x = 16; at[0].val.clusterDim.y = 1; at[0].val.clusterDim.z = 1;
            cfg.attrs = at; cfg.numAttrs = 1;
            int n = 0;
            cudaOccupancyMaxActiveClusters(&n, k_rec, &cfg);
            rp.ncl = n < 4 ? 4 : (n > 8 ? 8 : n);
        }
        for (int i = 0; i < 13; i++) key[i] = d_in[i];
        key[13] = d_out;
        ready = true;
    }
    cudaStream_t st = cudaStreamPerThread;
    PrefetchList pf;
    pf.p[0] = (const bf16*)d_in[3]; pf.p[1] = (const bf16*)d_in[4]; pf.p[2] = (const bf16*)d_in[2]; pf.p[3] = (const bf16*)d_in[5]; pf.p[4] = nullptr;
    k_mod<<<96, 256, 0, st>>>((const bf16*)d_in[11], (const bf16*)d_in[12], pf);
    {
        cudaLaunchConfig_t cfg = {};
        cfg.gridDim = dim3(S_ / 8); cfg.blockDim = dim3(256); cfg.stream = st;
        cudaLaunchAttribute at[1];
        at[0].id = cudaLaunchAttributeProgrammaticStreamSerialization; at[0].val.programmaticStreamSerializationAllowed = 1;
        cfg.attrs = at; cfg.numAttrs = 1;
        cudaLaunchKernelEx(&cfg, k_ln1, (const bf16*)d_in[0]);
    }
    auto launch_rec = [&]() {
        cudaLaunchConfig_t cfg = {};
        cfg.gridDim = dim3(16 * rp.ncl); cfg.blockDim = dim3(384); cfg.dynamicSmemBytes = R_SMEM; cfg.stream = st;
        cudaLaunchAttribute at[1];
        at[0].id = cudaLaunchAttributeClusterDimension; at[0].val.clusterDim.x = 16; at[0].val.clusterDim.y = 1; at[0].val.clusterDim.z = 1;
        cfg.attrs = at; cfg.numAttrs = 1;
        cudaLaunchKernelEx(&cfg, k_rec, rp);
    };
    auto launch_work = [&](int qmask, int pdl) {
        prm.qmask = qmask;
        cudaLaunchConfig_t cfg = {};
        cfg.gridDim = dim3(132); cfg.blockDim = dim3(384); cfg.dynamicSmemBytes = SMEM_BYTES; cfg.stream = st;
        cudaLaunchAttribute at[1];
        at[0].id = cudaLaunchAttributeProgrammaticStreamSerialization; at[0].val.programmaticStreamSerializationAllowed = 1;
        cfg.attrs = at; cfg.numAttrs = pdl;
        cudaLaunchKernelEx(&cfg, k_work, prm);
    };
    launch_rec();
    launch_work(0x3f, 1);
}
```

```cpp
#include <cuda_runtime.h>
#include <cuda_bf16.h>
#include <cuda.h>
#include <stdint.h>

typedef __nv_bfloat16 bf16;

constexpr int S_ = 2048, D_ = 512, H_ = 32, DH_ = 128, HD_ = 4096, NSEG = 64, DF_ = 1792;
constexpr int NRB = 16;
constexpr int OSPLIT = 4;

__device__ __align__(1024) bf16 g_h[S_ * D_];
__device__ __align__(1024) bf16 g_kv[S_ * 2 * HD_];
__device__ __align__(1024) bf16 g_kvm[NSEG * 8 * 2 * HD_];
__device__ __align__(1024) bf16 g_o[S_ * HD_];
#define FINE_RB_ 14
constexpr int FINE_RB = FINE_RB_;
constexpr int OSPLIT2 = 16;
constexpr int OP_ROWS = OSPLIT * S_ + OSPLIT2 * (NRB - FINE_RB) * 128;
__device__ __align__(1024) bf16 g_op[OP_ROWS * D_];
__device__ __align__(1024) bf16 g_x1[S_ * D_];
__device__ __align__(1024) bf16 g_h2[S_ * D_];
__device__ __align__(1024) bf16 g_act[S_ * DF_];
__device__ __align__(1024) bf16 g_mod[6 * D_];
__device__ uint32_t g_Fraw[131072 + 65536 + 2048];
#define g_F ((uint32_t*)(((uint64_t)g_Fraw + 0x7FFFFull) & ~0x7FFFFull))
constexpr int F_KV = 0, F_MEM = 32, F_O = 64, F_OP = 96, F_H2 = 128, F_ACT = 160, F_CLAIM = 192  , F_SIDE = 384  , F_TOTAL = 448;
__device__ __align__(128) unsigned int g_flags[F_TOTAL];
#define TR(j, i) do {} while (0)

__device__ __forceinline__ uint32_t smem_u32(const void* p) { return (uint32_t)__cvta_generic_to_shared(p); }
__device__ __forceinline__ uint32_t clk32() { uint32_t c; asm volatile("mov.u32 %0, %%clock;" : "=r"(c)); return c; }
__device__ __forceinline__ uint32_t mapa_u32(uint32_t addr, uint32_t rank) {
    uint32_t r; asm volatile("mapa.shared::cluster.u32 %0, %1, %2;" : "=r"(r) : "r"(addr), "r"(rank)); return r;
}
__device__ __forceinline__ void mbar_init(uint32_t bar, uint32_t cnt) {
    asm volatile("mbarrier.init.shared::cta.b64 [%0], %1;" :: "r"(bar), "r"(cnt) : "memory");
}
__device__ __forceinline__ void mbar_inval(uint32_t bar) {
    asm volatile("mbarrier.inval.shared::cta.b64 [%0];" :: "r"(bar) : "memory");
}
__device__ __forceinline__ void mbar_expect_tx(uint32_t bar, uint32_t bytes) {
    asm volatile("mbarrier.arrive.expect_tx.shared::cta.b64 _, [%0], %1;" :: "r"(bar), "r"(bytes) : "memory");
}
__device__ __forceinline__ void mbar_arrive(uint32_t bar) {
    asm volatile("mbarrier.arrive.shared::cta.b64 _, [%0];" :: "r"(bar) : "memory");
}
__device__ __forceinline__ bool mbar_try_wait(uint32_t bar, uint32_t parity) {
    uint32_t ok;
    asm volatile("{\n.reg .pred p;\nmbarrier.try_wait.parity.shared::cta.b64 p, [%1], %2;\nselp.u32 %0, 1, 0, p;\n}"
                 : "=r"(ok) : "r"(bar), "r"(parity) : "memory");
    return ok;
}
__device__ __forceinline__ bool mbar_try_wait_cluster(uint32_t bar, uint32_t parity) {
    uint32_t ok;
    asm volatile("{\n.reg .pred p;\nmbarrier.try_wait.parity.acquire.cluster.shared::cta.b64 p, [%1], %2;\nselp.u32 %0, 1, 0, p;\n}"
                 : "=r"(ok) : "r"(bar), "r"(parity) : "memory");
    return ok;
}
constexpr int SPIN_LIMIT = 1 << 18;
#define TIMEOUT(code, info) do {} while (0)
__device__ __forceinline__ void mbar_wait(uint32_t bar, uint32_t parity) {
    int g = 0;
#pragma unroll 1
    while (!mbar_try_wait(bar, parity)) { if (++g >= SPIN_LIMIT) { TIMEOUT(0, bar & 255); break; } }
}
__device__ __forceinline__ void mbar_wait_cluster(uint32_t bar, uint32_t parity) {
    int g = 0;
#pragma unroll 1
    while (!mbar_try_wait_cluster(bar, parity)) { if (++g >= SPIN_LIMIT) { TIMEOUT(1, bar & 255); break; } }
}
__device__ __forceinline__ void bar_sync(int id, int n) { asm volatile("bar.sync %0, %1;" :: "r"(id), "r"(n) : "memory"); }
__device__ __forceinline__ void bar_arrive(int id, int n) { asm volatile("bar.arrive %0, %1;" :: "r"(id), "r"(n) : "memory"); }
__device__ __forceinline__ void cluster_sync_all() {
    asm volatile("barrier.cluster.arrive.aligned;\nbarrier.cluster.wait.aligned;" ::: "memory");
}
__device__ __forceinline__ void st_async_v2(uint32_t addr, float a, float b, uint32_t bar) {
    asm volatile("st.async.weak.shared::cluster.mbarrier::complete_tx::bytes.v2.f32 [%0], {%1,%2}, [%3];"
                 :: "r"(addr), "f"(a), "f"(b), "r"(bar) : "memory");
}
__device__ __forceinline__ void st_async_v4(uint32_t addr, uint4 v, uint32_t bar) {
    asm volatile("st.async.weak.shared::cluster.mbarrier::complete_tx::bytes.v4.b32 [%0], {%1,%2,%3,%4}, [%5];"
                 :: "r"(addr), "r"(v.x), "r"(v.y), "r"(v.z), "r"(v.w), "r"(bar) : "memory");
}
__device__ __forceinline__ uint2 ldg_relaxed2(const uint2* p) {
    uint2 v;
    asm volatile("ld.relaxed.gpu.global.v2.b32 {%0,%1}, [%2];" : "=r"(v.x), "=r"(v.y) : "l"(p) : "memory");
    return v;
}
__device__ __forceinline__ void stg_relaxed2(uint2* p, uint2 v) {
    asm volatile("st.relaxed.gpu.global.v2.b32 [%0], {%1,%2};" :: "l"(p), "r"(v.x), "r"(v.y) : "memory");
}
__device__ __forceinline__ uint4 ldg_relaxed(const uint4* p) {
    uint4 v;
    asm volatile("ld.relaxed.gpu.global.v4.b32 {%0,%1,%2,%3}, [%4];" : "=r"(v.x), "=r"(v.y), "=r"(v.z), "=r"(v.w) : "l"(p) : "memory");
    return v;
}
__device__ __forceinline__ void stg_relaxed(uint4* p, uint4 v) {
    asm volatile("st.relaxed.gpu.global.v4.b32 [%0], {%1,%2,%3,%4};" :: "l"(p), "r"(v.x), "r"(v.y), "r"(v.z), "r"(v.w) : "memory");
}
__device__ __forceinline__ void stg_relaxed32(uint32_t* p, uint32_t v) {
    asm volatile("st.relaxed.gpu.global.b32 [%0], %1;" :: "l"(p), "r"(v) : "memory");
}
__device__ __forceinline__ uint32_t ldg_relaxed32(const uint32_t* p) {
    uint32_t v; asm volatile("ld.relaxed.gpu.global.b32 %0, [%1];" : "=r"(v) : "l"(p) : "memory"); return v;
}
__device__ __forceinline__ unsigned int ld_acquire(const unsigned int* p) {
    unsigned int v; asm volatile("ld.acquire.gpu.global.u32 %0, [%1];" : "=r"(v) : "l"(p) : "memory"); return v;
}
__device__ __forceinline__ void red_release(unsigned int* p, unsigned int v) {
    asm volatile("red.release.gpu.global.add.u32 [%0], %1;" :: "l"(p), "r"(v) : "memory");
}
__device__ __forceinline__ void wait_flag(int idx, unsigned int target) {
    const unsigned int* p = &g_flags[idx];
    int g = 0;
#pragma unroll 1
    while (ld_acquire(p) < target) { __nanosleep(20); if (++g >= 64 * SPIN_LIMIT) { TIMEOUT(2, idx); break; } }
}
__device__ __forceinline__ void cp_async16(uint32_t dst, const void* src) {
    asm volatile("cp.async.cg.shared.global [%0], [%1], 16;" :: "r"(dst), "l"(src) : "memory");
}
__device__ __forceinline__ void cp_async_commit() { asm volatile("cp.async.commit_group;" ::: "memory"); }
template <int N> __device__ __forceinline__ void cp_async_wait() { asm volatile("cp.async.wait_group %0;" :: "n"(N) : "memory"); }
__device__ __forceinline__ void ldsm4(uint32_t& r0, uint32_t& r1, uint32_t& r2, uint32_t& r3, uint32_t addr) {
    asm volatile("ldmatrix.sync.aligned.m8n8.x4.shared.b16 {%0,%1,%2,%3}, [%4];" : "=r"(r0), "=r"(r1), "=r"(r2), "=r"(r3) : "r"(addr) : "memory");
}
__device__ __forceinline__ void ldsm4t(uint32_t& r0, uint32_t& r1, uint32_t& r2, uint32_t& r3, uint32_t addr) {
    asm volatile("ldmatrix.sync.aligned.m8n8.x4.trans.shared.b16 {%0,%1,%2,%3}, [%4];" : "=r"(r0), "=r"(r1), "=r"(r2), "=r"(r3) : "r"(addr) : "memory");
}
__device__ __forceinline__ void ldsm2t(uint32_t& r0, uint32_t& r1, uint32_t addr) {
    asm volatile("ldmatrix.sync.aligned.m8n8.x2.trans.shared.b16 {%0,%1}, [%2];" : "=r"(r0), "=r"(r1) : "r"(addr) : "memory");
}
__device__ __forceinline__ void stsm4(uint32_t addr, uint32_t r0, uint32_t r1, uint32_t r2, uint32_t r3) {
    asm volatile("stmatrix.sync.aligned.m8n8.x4.shared.b16 [%0], {%1,%2,%3,%4};" :: "r"(addr), "r"(r0), "r"(r1), "r"(r2), "r"(r3) : "memory");
}
__device__ __forceinline__ void stsm2t(uint32_t addr, uint32_t r0, uint32_t r1) {
    asm volatile("stmatrix.sync.aligned.m8n8.x2.trans.shared.b16 [%0], {%1,%2};" :: "r"(addr), "r"(r0), "r"(r1) : "memory");
}
__device__ __forceinline__ void mma16816(float* d, uint32_t a0, uint32_t a1, uint32_t a2, uint32_t a3, uint32_t b0, uint32_t b1) {
    asm volatile("mma.sync.aligned.m16n8k16.row.col.f32.bf16.bf16.f32 {%0,%1,%2,%3}, {%4,%5,%6,%7}, {%8,%9}, {%0,%1,%2,%3};"
                 : "+f"(d[0]), "+f"(d[1]), "+f"(d[2]), "+f"(d[3]) : "r"(a0), "r"(a1), "r"(a2), "r"(a3), "r"(b0), "r"(b1));
}
__device__ __forceinline__ void mma1688(float* d, uint32_t a0, uint32_t a1, uint32_t b0) {
    asm volatile("mma.sync.aligned.m16n8k8.row.col.f32.bf16.bf16.f32 {%0,%1,%2,%3}, {%4,%5}, {%6}, {%0,%1,%2,%3};"
                 : "+f"(d[0]), "+f"(d[1]), "+f"(d[2]), "+f"(d[3]) : "r"(a0), "r"(a1), "r"(b0));
}
__device__ __forceinline__ void mma16816h(float* d, uint32_t a0, uint32_t a2, uint32_t b0, uint32_t b1) {
    asm volatile("{\n.reg .b32 ju, jv;\nmma.sync.aligned.m16n8k16.row.col.f32.bf16.bf16.f32 {%0,%1,%2,%3}, {%4,ju,%5,jv}, {%6,%7}, {%0,%1,%2,%3};\n}"
                 : "+f"(d[0]), "+f"(d[1]), "+f"(d[2]), "+f"(d[3]) : "r"(a0), "r"(a2), "r"(b0), "r"(b1));
}
__device__ __forceinline__ void mma1688h(float* d, uint32_t a0, uint32_t b0) {
    asm volatile("{\n.reg .b32 ju;\nmma.sync.aligned.m16n8k8.row.col.f32.bf16.bf16.f32 {%0,%1,%2,%3}, {%4,ju}, {%5}, {%0,%1,%2,%3};\n}"
                 : "+f"(d[0]), "+f"(d[1]), "+f"(d[2]), "+f"(d[3]) : "r"(a0), "r"(b0));
}
__device__ __forceinline__ uint32_t pack2(float lo, float hi) {
    uint32_t r; asm("cvt.rn.bf16x2.f32 %0, %1, %2;" : "=r"(r) : "f"(hi), "f"(lo)); return r;
}
__device__ __forceinline__ float bflo(uint32_t w) { return __uint_as_float(w << 16); }
__device__ __forceinline__ float bfhi(uint32_t w) { return __uint_as_float(w & 0xffff0000u); }
__device__ __forceinline__ float rbf(float x) { return __bfloat162float(__float2bfloat16_rn(x)); }
__device__ __forceinline__ float ex2(float x) { float y; asm("ex2.approx.ftz.f32 %0, %1;" : "=f"(y) : "f"(x)); return y; }
__device__ __forceinline__ void sts128(uint32_t addr, uint4 v) {
    asm volatile("st.shared.v4.b32 [%0], {%1,%2,%3,%4};" :: "r"(addr), "r"(v.x), "r"(v.y), "r"(v.z), "r"(v.w) : "memory");
}
__device__ __forceinline__ uint4 lds128(uint32_t addr) {
    uint4 v; asm volatile("ld.shared.v4.b32 {%0,%1,%2,%3}, [%4];" : "=r"(v.x), "=r"(v.y), "=r"(v.z), "=r"(v.w) : "r"(addr) : "memory"); return v;
}
__device__ __forceinline__ float2 lds64f(uint32_t addr) {
    float2 v; asm volatile("ld.shared.v2.f32 {%0,%1}, [%2];" : "=f"(v.x), "=f"(v.y) : "r"(addr) : "memory"); return v;
}
__device__ __forceinline__ float lds32f(uint32_t addr) {
    float v; asm volatile("ld.shared.f32 %0, [%1];" : "=f"(v) : "r"(addr) : "memory"); return v;
}
__device__ __forceinline__ uint32_t lds32(uint32_t addr) {
    uint32_t v; asm volatile("ld.shared.b32 %0, [%1];" : "=r"(v) : "r"(addr) : "memory"); return v;
}
__device__ __forceinline__ void sts32(uint32_t addr, uint32_t v) { asm volatile("st.shared.b32 [%0], %1;" :: "r"(addr), "r"(v) : "memory"); }
__device__ __forceinline__ void sts64f(uint32_t addr, float a, float b) { asm volatile("st.shared.v2.f32 [%0], {%1,%2};" :: "r"(addr), "f"(a), "f"(b) : "memory"); }

__device__ __forceinline__ void tma_load2d(uint32_t dst, const CUtensorMap* tm, int c0, int c1, uint32_t bar) {
    asm volatile("cp.async.bulk.tensor.2d.shared::cluster.global.mbarrier::complete_tx::bytes [%0], [%1, {%3, %4}], [%2];"
                 :: "r"(dst), "l"(tm), "r"(bar), "r"(c0), "r"(c1) : "memory");
}
__device__ __forceinline__ void tma_store2d(const CUtensorMap* tm, uint32_t src, int c0, int c1) {
    asm volatile("cp.async.bulk.tensor.2d.global.shared::cta.bulk_group [%0, {%2, %3}], [%1];"
                 :: "l"(tm), "r"(src), "r"(c0), "r"(c1) : "memory");
}
__device__ __forceinline__ void bulk_commit() { asm volatile("cp.async.bulk.commit_group;" ::: "memory"); }
__device__ __forceinline__ void bulk_wait0() { asm volatile("cp.async.bulk.wait_group 0;" ::: "memory"); }
__device__ __forceinline__ void fence_async_smem() { asm volatile("fence.proxy.async.shared::cta;" ::: "memory"); }
__device__ __forceinline__ void fence_async_all() { asm volatile("fence.proxy.async;" ::: "memory"); }

__device__ __forceinline__ void wg_fence() { asm volatile("wgmma.fence.sync.aligned;" ::: "memory"); }
__device__ __forceinline__ void wg_commit() { asm volatile("wgmma.commit_group.sync.aligned;" ::: "memory"); }
__device__ __forceinline__ void wg_wait0() { asm volatile("wgmma.wait_group.sync.aligned 0;" ::: "memory"); }
__device__ __forceinline__ uint64_t mkdesc(uint32_t saddr, uint32_t lbo, uint32_t sbo) {
    return (uint64_t)((saddr & 0x3FFFF) >> 4) | ((uint64_t)(lbo >> 4) << 16) | ((uint64_t)(sbo >> 4) << 32) | (1ull << 62);
}
#define ACC8(i) "+f"(d[i]), "+f"(d[i + 1]), "+f"(d[i + 2]), "+f"(d[i + 3]), "+f"(d[i + 4]), "+f"(d[i + 5]), "+f"(d[i + 6]), "+f"(d[i + 7])
__device__ __forceinline__ void wgmma_n256(float* d, uint64_t da, uint64_t db, int scale_d) {
    asm volatile(
        "{\n.reg .pred p;\nsetp.ne.b32 p, %130, 0;\n"
        "wgmma.mma_async.sync.aligned.m64n256k16.f32.bf16.bf16 "
        "{%0,%1,%2,%3,%4,%5,%6,%7,%8,%9,%10,%11,%12,%13,%14,%15,%16,%17,%18,%19,%20,%21,%22,%23,%24,%25,%26,%27,%28,%29,%30,%31,"
        "%32,%33,%34,%35,%36,%37,%38,%39,%40,%41,%42,%43,%44,%45,%46,%47,%48,%49,%50,%51,%52,%53,%54,%55,%56,%57,%58,%59,%60,%61,%62,%63,"
        "%64,%65,%66,%67,%68,%69,%70,%71,%72,%73,%74,%75,%76,%77,%78,%79,%80,%81,%82,%83,%84,%85,%86,%87,%88,%89,%90,%91,%92,%93,%94,%95,"
        "%96,%97,%98,%99,%100,%101,%102,%103,%104,%105,%106,%107,%108,%109,%110,%111,%112,%113,%114,%115,%116,%117,%118,%119,%120,%121,%122,%123,%124,%125,%126,%127}, "
        "%128, %129, p, 1, 1, 0, 1;\n}"
        : ACC8(0), ACC8(8), ACC8(16), ACC8(24), ACC8(32), ACC8(40), ACC8(48), ACC8(56),
          ACC8(64), ACC8(72), ACC8(80), ACC8(88), ACC8(96), ACC8(104), ACC8(112), ACC8(120)
        : "l"(da), "l"(db), "r"(scale_d));
}
__device__ __forceinline__ void wgmma_n128(float* d, uint64_t da, uint64_t db, int scale_d) {
    asm volatile(
        "{\n.reg .pred p;\nsetp.ne.b32 p, %66, 0;\n"
        "wgmma.mma_async.sync.aligned.m64n128k16.f32.bf16.bf16 "
        "{%0,%1,%2,%3,%4,%5,%6,%7,%8,%9,%10,%11,%12,%13,%14,%15,%16,%17,%18,%19,%20,%21,%22,%23,%24,%25,%26,%27,%28,%29,%30,%31,"
        "%32,%33,%34,%35,%36,%37,%38,%39,%40,%41,%42,%43,%44,%45,%46,%47,%48,%49,%50,%51,%52,%53,%54,%55,%56,%57,%58,%59,%60,%61,%62,%63}, "
        "%64, %65, p, 1, 1, 0, 1;\n}"
        : ACC8(0), ACC8(8), ACC8(16), ACC8(24), ACC8(32), ACC8(40), ACC8(48), ACC8(56)
        : "l"(da), "l"(db), "r"(scale_d));
}

__device__ __forceinline__ void wgmma_n64(float* d, uint64_t da, uint64_t db) {
    asm volatile(
        "wgmma.mma_async.sync.aligned.m64n64k16.f32.bf16.bf16 "
        "{%0,%1,%2,%3,%4,%5,%6,%7,%8,%9,%10,%11,%12,%13,%14,%15,%16,%17,%18,%19,%20,%21,%22,%23,%24,%25,%26,%27,%28,%29,%30,%31}, "
        "%32, %33, 1, 1, 1, 0, 1;"
        : ACC8(0), ACC8(8), ACC8(16), ACC8(24)
        : "l"(da), "l"(db));
}
__device__ __forceinline__ void wgmma_n8_ta(float* d, uint64_t da, uint64_t db, int scale_d) {
    asm volatile(
        "{\n.reg .pred p;\nsetp.ne.b32 p, %6, 0;\n"
        "wgmma.mma_async.sync.aligned.m64n8k16.f32.bf16.bf16 {%0,%1,%2,%3}, %4, %5, p, 1, 1, 1, 0;\n}"
        : "+f"(d[0]), "+f"(d[1]), "+f"(d[2]), "+f"(d[3]) : "l"(da), "l"(db), "r"(scale_d));
}

struct PrefetchList { const bf16* p[5]; };
__global__ void __launch_bounds__(256) k_mod(const bf16* __restrict__ c, const bf16* __restrict__ w_mod, const PrefetchList pf) {
    asm volatile("griddepcontrol.launch_dependents;");
    __shared__ float s_c[D_];
    __shared__ float s_red[64][33];
    const int tid = threadIdx.x;
    const int cq = tid & 3, rg = tid >> 2;
    uint4 w[8];
#pragma unroll
    for (int i = 0; i < 8; i++)
        w[i] = __ldg((const uint4*)(w_mod + (size_t)(rg * 8 + i) * (6 * D_) + blockIdx.x * 32 + cq * 8));
    for (int i = tid; i < D_; i += 256) {
        float v = __bfloat162float(c[i]);
        s_c[i] = rbf(v / (1.f + __expf(-v)));
    }
    {
        const int gt = blockIdx.x * 256 + tid, nt = gridDim.x * 256;
        for (int i = gt; i < F_TOTAL; i += nt) g_flags[i] = 0;
        for (int i = gt; i < 65536 + 2048; i += nt) g_F[i] = 0;
        if (tid < 11) {
            const int i = tid * gridDim.x + blockIdx.x;
            if (i < 1024) asm volatile("cp.async.bulk.prefetch.L2.global [%0], %1;" :: "l"(pf.p[i >> 8] + (size_t)(i & 255) * 8192), "r"(16384) : "memory");
        }
    }
    __syncthreads();
    float a[8];
#pragma unroll
    for (int j = 0; j < 8; j++) a[j] = 0.f;
#pragma unroll
    for (int i = 0; i < 8; i++) {
        float cv = s_c[rg * 8 + i];
        a[0] += cv * bflo(w[i].x); a[1] += cv * bfhi(w[i].x); a[2] += cv * bflo(w[i].y); a[3] += cv * bfhi(w[i].y);
        a[4] += cv * bflo(w[i].z); a[5] += cv * bfhi(w[i].z); a[6] += cv * bflo(w[i].w); a[7] += cv * bfhi(w[i].w);
    }
#pragma unroll
    for (int j = 0; j < 8; j++) s_red[rg][cq * 8 + j] = a[j];
    __syncthreads();
    if (tid < 32) {
        float s = 0.f;
#pragma unroll 8
        for (int r = 0; r < 64; r++) s += s_red[r][tid];
        g_mod[blockIdx.x * 32 + tid] = __float2bfloat16_rn(s);
    }
}

__device__ __forceinline__ uint32_t hadd2(uint32_t a, uint32_t b) { uint32_t r; asm("add.rn.bf16x2 %0, %1, %2;" : "=r"(r) : "r"(a), "r"(b)); return r; }
__device__ __forceinline__ uint32_t hsub2(uint32_t a, uint32_t b) { uint32_t r; asm("sub.rn.bf16x2 %0, %1, %2;" : "=r"(r) : "r"(a), "r"(b)); return r; }
__device__ __forceinline__ uint32_t hmul2(uint32_t a, uint32_t b) { uint32_t r; asm("mul.rn.bf16x2 %0, %1, %2;" : "=r"(r) : "r"(a), "r"(b)); return r; }
__device__ __forceinline__ void load_mod8(const bf16* m, int lane, uint32_t* v) {
    const uint4 a = __ldcg((const uint4*)m + lane), b = __ldcg((const uint4*)m + 32 + lane);
    v[0] = a.x; v[1] = a.y; v[2] = a.z; v[3] = a.w; v[4] = b.x; v[5] = b.y; v[6] = b.z; v[7] = b.w;
}
__device__ __forceinline__ void ln_stats(const uint32_t* x, uint32_t& mu2, float& rden) {
    float s = 0.f;
#pragma unroll
    for (int i = 0; i < 8; i++) s += bflo(x[i]) + bfhi(x[i]);
#pragma unroll
    for (int o = 16; o > 0; o >>= 1) s += __shfl_xor_sync(~0u, s, o);
    const float mean = s * (1.f / D_);
    float q = 0.f;
#pragma unroll
    for (int i = 0; i < 8; i++) { const float d0 = bflo(x[i]) - mean, d1 = bfhi(x[i]) - mean; q = fmaf(d0, d0, q); q = fmaf(d1, d1, q); }
#pragma unroll
    for (int o = 16; o > 0; o >>= 1) q += __shfl_xor_sync(~0u, q, o);
    mu2 = pack2(mean, mean);
    rden = __frcp_rn(rbf(__fsqrt_rn(rbf(rbf(q * (1.f / D_)) + 1e-5f))));
}
__device__ __forceinline__ void ln_apply(const uint32_t* x, uint32_t mu2, float rden, const uint32_t* c1, const uint32_t* sm, uint32_t* r) {
#pragma unroll
    for (int i = 0; i < 8; i++) {
        const uint32_t d = hsub2(x[i], mu2);
        r[i] = hadd2(hmul2(pack2(bflo(d) * rden, bfhi(d) * rden), c1[i]), sm[i]);
    }
}

__global__ void __launch_bounds__(256) k_ln1(const bf16* __restrict__ x) {
    const int lane = threadIdx.x & 31, row = blockIdx.x * 8 + (threadIdx.x >> 5);
    const uint4* xr = (const uint4*)(x + (size_t)row * D_);
    const uint4 a = __ldg(xr + lane), b = __ldg(xr + 32 + lane);
    const uint32_t v[8] = {a.x, a.y, a.z, a.w, b.x, b.y, b.z, b.w};
    uint32_t mu2; float rden;
    ln_stats(v, mu2, rden);
    asm volatile("griddepcontrol.wait;" ::: "memory");
    uint32_t c1[8], sm[8], r[8];
    load_mod8(g_mod + D_, lane, c1);
    load_mod8(g_mod, lane, sm);
#pragma unroll
    for (int i = 0; i < 8; i++) c1[i] = hadd2(c1[i], 0x3F803F80u);
    ln_apply(v, mu2, rden, c1, sm, r);
    uint4* hr = (uint4*)(g_h + (size_t)row * D_);
    hr[lane] = make_uint4(r[0], r[1], r[2], r[3]); hr[32 + lane] = make_uint4(r[4], r[5], r[6], r[7]);
}

struct __align__(64) Params {
    CUtensorMap tm_h, tm_kv, tm_kvm, tm_o, tm_op, tm_h2, tm_act, tm_x1, tm_out;
    CUtensorMap tm_wq, tm_wk, tm_wv, tm_wo, tm_wg, tm_wu, tm_wd;
    const bf16* x;
    int qmask;
};

constexpr int R_NST = 3;
constexpr uint32_t R_WV = 0, R_MEM = 65536, R_KX = 73728, R_VX = R_KX + R_NST * 4096, R_QS = R_VX + R_NST * 4096,
                   R_KMS = R_QS + 1024, R_VMS = R_KMS + 1024, R_OS = R_VMS + 1024, R_SX = R_OS + 1024, R_BAR = R_SX + 2560,
                   R_RS = 105472  , R_VP = R_RS + 8192  ,
                   R_STG = R_VP + 8192  , R_SMEM = R_STG + 98304;
static_assert(R_BAR + 64 <= R_RS, "smem");
constexpr uint32_t RB_SX = R_BAR, RB_V = R_BAR + 8, RB_E = R_BAR + 16, RB_A = R_BAR + 24, RB_ROLE = R_BAR + 32, RB_A1 = R_BAR + 40;
constexpr int W_NST = 3;
constexpr uint32_t W_STAGE = 49152, W_STG = W_NST * W_STAGE, W_END = W_STG + 65536;
constexpr uint32_t SM_BAR = W_END;
constexpr uint32_t SMEM_BYTES = W_END + 1024;
constexpr uint32_t B_FULL = 0, B_EMPTY = 32, B_STGFREE = 64, B_REQ = 80, B_RSP = 88, B_NEXT = 96, B_RING = 128;
#define PICK_AHEAD 2

constexpr int NB_X = 11  , NB_Y = 1, NB_B = 2, NB_C = 3, NB_D = 4, NB_W0 = 6  , NB_ST = 9  ;

__device__ __forceinline__ int pos_of_d(int d) {
    const int rem = d & 31;
    return (d & ~31) + ((rem & 7) >> 1) * 8 + (rem & 1) * 4 + (rem >> 3);
}

#define PROF(i) do {} while (0)
#define PROFG(i) do {} while (0)
#define OPAQUE(x) asm volatile("" : "+r"(x))
#define FENCE_SCHED(x) do { if ((x) == 0u) asm volatile("trap;"); } while (0)
#define VK0_ 4
constexpr int VK0 = VK0_;
constexpr int NOFF = 8;
#define VDELAY -1
#define POLL_GAP 100

struct RecParams { const bf16 *mem0, *wq, *wk, *wv, *wo; int ncl; };

__device__ __forceinline__ void rec_qk(const RecParams& p, const uint32_t sb, const int cta, const int warp, int lane, const int sel) {
    const int crank = cta & 15, cl = cta >> 4, rank = cta & 1;
    const int kh = warp >> 2, aa = warp & 3;
    uint32_t wa[2][16][4];
    const uint32_t stg = sb + R_STG + kh * 32768;
    {
        const int t128 = aa * 32 + lane;
        const int row = (lane >> 4) * 8 + (lane & 7);
        const int ch = t128 & 7;
        const size_t goff = (size_t)kh * 256 * HD_ + cta * 64 + ch * 8;
#pragma unroll 4
        for (int dd = 0; dd < 16; dd++) {
            const int d = dd * 16 + (t128 >> 3), pp = pos_of_d(d);
            cp_async16(sb + R_WV + kh * 32768 + pp * 128 + ((ch ^ (pp & 7)) << 4), p.wv + goff + (size_t)d * HD_);
        }
        cp_async_commit();
#pragma unroll 4
        for (int dd = 0; dd < 16; dd++) {
            const int d = dd * 16 + (t128 >> 3), pp = pos_of_d(d);
            cp_async16(stg + pp * 128 + ((ch ^ (pp & 7)) << 4), p.wq + goff + (size_t)d * HD_);
        }
        cp_async_commit();
        {
            const int i0 = (warp * 32 + lane) * 16, tok = i0 >> 9;
            const uint4 m0 = __ldg((const uint4*)(p.mem0 + i0)), m1 = __ldg((const uint4*)(p.mem0 + i0 + 8));
            const uint32_t mw[8] = {m0.x, m0.y, m0.z, m0.w, m1.x, m1.y, m1.z, m1.w};
#pragma unroll
            for (int e = 0; e < 16; e++) {
                const int pp = pos_of_d((i0 & 511) + e);
                const unsigned short v = (unsigned short)(mw[e >> 1] >> ((e & 1) * 16));
                asm volatile("st.shared.u16 [%0], %1;" :: "r"(sb + R_MEM + (pp >> 3) * 128 + tok * 16 + (pp & 7) * 2), "h"(v) : "memory");
            }
        }
        cp_async_wait<1>();
        bar_sync(NB_W0 + kh, 128);
        const uint32_t fv = row * 128 + (((2 * aa + ((lane >> 3) & 1)) ^ (row & 7)) << 4);
#pragma unroll
        for (int ks = 0; ks < 16; ks++) ldsm4t(wa[0][ks][0], wa[0][ks][1], wa[0][ks][2], wa[0][ks][3], sb + R_WV + kh * 32768 + fv + ks * 2048);
        bar_sync(NB_W0 + kh, 128);
#pragma unroll
        for (int ks = 0; ks < 16; ks++)
            sts128(sb + R_WV + kh * 32768 + (aa * 16 + ks) * 512 + lane * 16, make_uint4(wa[0][ks][0], wa[0][ks][1], wa[0][ks][2], wa[0][ks][3]));
        const uint32_t fo = stg + row * 128 + (((4 * (aa & 1) + ((lane >> 3) & 1)) ^ (row & 7)) << 4);
#pragma unroll 1
        for (int m = 0; m < 2; m++) {
            cp_async_wait<0>();
            bar_sync(NB_W0 + kh, 128);
            if ((aa >> 1) == m) {
#pragma unroll
                for (int ks = 0; ks < 16; ks++) {
                    ldsm4t(wa[0][ks][0], wa[0][ks][1], wa[0][ks][2], wa[0][ks][3], fo + ks * 2048);
                    ldsm4t(wa[1][ks][0], wa[1][ks][1], wa[1][ks][2], wa[1][ks][3], (fo ^ 32) + ks * 2048);
                }
            }
            bar_sync(NB_W0 + kh, 128);
            if (m == 0) {
#pragma unroll 4
                for (int dd = 0; dd < 16; dd++) {
                    const int d = dd * 16 + (t128 >> 3), pp = pos_of_d(d);
                    cp_async16(stg + pp * 128 + ((ch ^ (pp & 7)) << 4), p.wk + goff + (size_t)d * HD_);
                }
                cp_async_commit();
            }
        }
    }
    const uint32_t tab = stg + (aa * 32 + lane) * 16;
    {
        const uint32_t l7 = lane & 7, l8 = lane >> 3, g = lane >> 2, t = lane & 3;
        const uint32_t t0 = l7 * 128 + ((l8 ^ l7) << 4);
        const uint32_t tq = l7 * 128 + (((l8 >> 1) ^ l7) << 4);
        const uint32_t bq = warp >> 1, tp = warp & 1;
        uint4 v;
        v.x = sb + (aa < 2 ? R_QS : R_KMS) + l7 * 128 + (((4 * (aa & 1) + 2 * kh + (l8 & 1)) ^ l7) << 4);
        v.y = sb + R_QS + tq;
        v.z = sb + (warp == 0 ? R_KMS : R_KX + (warp - 1) * 1024) + t0;
        v.w = mapa_u32(sb + R_SX + (rank * 5 + warp) * 256 + lane * 8, crank ^ 1);
        sts128(tab, v);
        sts128(tab + 2048, make_uint4(sb + lane * 16 + R_MEM + kh * 4096, sb + lane * 16 + R_WV + warp * 8192,
                                      sb + lane * 16 + R_VP + warp * 512, sb + lane * 16 + R_VP + 4096 + (warp ^ 4) * 512));
        const uint32_t src = (l8 >> 1) * 8 + l7;
        const uint32_t L = bq * 8 + 2 * tp + (l8 & 1);
        const uint32_t d0 = (crank + ((t >> 1) | (g & 6))) & 15;
        v.x = sb + R_RS + src * 512 + ((L ^ (src & 7)) << 4);
        v.y = mapa_u32(sb + R_MEM + (crank * 4 + bq) * 128 + (4 * tp + 2 * (t & 1) + (g & 1)) * 16, d0);
        v.z = mapa_u32(sb + ((crank & 2) ? RB_A1 : RB_A), d0);
        v.w = lane;
        sts128(tab + 4096, v);
        const uint64_t wr = (uint64_t)(g_F + ((crank * 2 + ((crank ^ (crank >> 3) ^ sel) & 1)) * 1024 + warp * 128 + cl * 32 + lane));
        sts128(tab + 6144, make_uint4((uint32_t)wr, (uint32_t)(wr >> 32), (uint32_t)((((cl + 1) & 3) - cl) * 128), (uint32_t)((((cl + 2) & 3) - cl) * 128)));
        sts32(tab + 8192, (uint32_t)((((cl + 3) & 3) - cl) * 128));
#pragma unroll
        for (int i = 0; i < NOFF; i++)
            sts128(tab + 10240 + i * 2048, make_uint4(wa[i & 1][i >> 1][0], wa[i & 1][i >> 1][1], wa[i & 1][i >> 1][2], wa[i & 1][i >> 1][3]));
    }
    bar_sync(NB_D, 384);
    uint32_t slot_off = 0;
    const uint32_t slot_inc = warp == 0 ? 0 : 4096;
    const uint32_t sx_bar_rem = (sb + RB_SX) ^ (1u << 24);
    uint4 tb = lds128(tab + 2048);
#pragma unroll 1
    for (int s = 0; s < NSEG; s++) {
        if (s > 0) mbar_wait(sb + RB_A, (s - 1) & 1);
        if (warp == 0) { PROF(0); PROFG(13); }
        uint4 ta;
        {
            float acc[5][4];
#pragma unroll
            for (int c = 0; c < 5; c++) { acc[c][0] = acc[c][1] = acc[c][2] = acc[c][3] = 0.f; }
            uint32_t b[8][4];
            uint4 av[16];
            static_assert(VK0 == 4, "order below assumes the V/O warps cover slices 0,1");
            ldsm4(b[0][0], b[0][1], b[0][2], b[0][3], tb.x);
            ldsm4(b[1][0], b[1][1], b[1][2], b[1][3], tb.x + 512);
            ldsm4(b[4][0], b[4][1], b[4][2], b[4][3], tb.x + 2048);
            ldsm4(b[5][0], b[5][1], b[5][2], b[5][3], tb.x + 2560);
#pragma unroll
            for (int kk = 0; kk < 8; kk++) {
                const int k2 = kk < 2 ? kk : (kk < 4 ? kk + 2 : (kk < 6 ? kk - 2 : kk));
                if (kk == 4) {
                    if (s > 0) mbar_wait(sb + RB_A1, (s - 1) & 1);
                    ldsm4(b[2][0], b[2][1], b[2][2], b[2][3], tb.x + 1024);
                    ldsm4(b[3][0], b[3][1], b[3][2], b[3][3], tb.x + 1536);
                    ldsm4(b[6][0], b[6][1], b[6][2], b[6][3], tb.x + 3072);
                    ldsm4(b[7][0], b[7][1], b[7][2], b[7][3], tb.x + 3584);
#pragma unroll
                    for (int i = 12; i < 16; i++) av[i] = lds128(tb.y + i * 512);
                    ta = lds128(tab);
                }
                mma16816(acc[0], wa[0][2 * k2][0], wa[0][2 * k2][1], wa[0][2 * k2][2], wa[0][2 * k2][3], b[k2][0], b[k2][1]);
                mma16816(acc[1], wa[1][2 * k2][0], wa[1][2 * k2][1], wa[1][2 * k2][2], wa[1][2 * k2][3], b[k2][0], b[k2][1]);
                mma16816(acc[3], wa[0][2 * k2 + 1][0], wa[0][2 * k2 + 1][1], wa[0][2 * k2 + 1][2], wa[0][2 * k2 + 1][3], b[k2][2], b[k2][3]);
                mma16816(acc[4], wa[1][2 * k2 + 1][0], wa[1][2 * k2 + 1][1], wa[1][2 * k2 + 1][2], wa[1][2 * k2 + 1][3], b[k2][2], b[k2][3]);
                if (2 * k2 >= VK0) {
                    mma16816(acc[2], av[2 * k2].x, av[2 * k2].y, av[2 * k2].z, av[2 * k2].w, b[k2][0], b[k2][1]);
                    mma16816(acc[2], av[2 * k2 + 1].x, av[2 * k2 + 1].y, av[2 * k2 + 1].z, av[2 * k2 + 1].w, b[k2][2], b[k2][3]);
                }
                if (kk == 0) { av[8] = lds128(tb.y + 8 * 512); av[9] = lds128(tb.y + 9 * 512); }
                if (kk == 1) { av[10] = lds128(tb.y + 10 * 512); av[11] = lds128(tb.y + 11 * 512); }
                if (kk == 2) { av[4] = lds128(tb.y + 4 * 512); av[5] = lds128(tb.y + 5 * 512); }
                if (kk == 3) { av[6] = lds128(tb.y + 6 * 512); av[7] = lds128(tb.y + 7 * 512); }
            }
#pragma unroll
            for (int i = 0; i < 4; i++) { acc[0][i] += acc[3][i]; acc[1][i] += acc[4][i]; }
            const float g0 = kh ? acc[0][0] : acc[1][0], g1 = kh ? acc[0][1] : acc[1][1], g2 = kh ? acc[0][2] : acc[1][2], g3 = kh ? acc[0][3] : acc[1][3];
            sts128(tb.w, make_uint4(__float_as_uint(g0), __float_as_uint(g1), __float_as_uint(g2), __float_as_uint(g3)));
            const float k0 = kh ? acc[1][0] : acc[0][0], k1 = kh ? acc[1][1] : acc[0][1], k2_ = kh ? acc[1][2] : acc[0][2], k3 = kh ? acc[1][3] : acc[0][3];
            if (warp == 0) PROF(1);
            bar_sync(NB_X + aa, 64);
            const uint4 o = lds128(tb.z + 4096);
            stsm2t(ta.x, pack2(k0 + __uint_as_float(o.x), k1 + __uint_as_float(o.y)), pack2(k2_ + __uint_as_float(o.z), k3 + __uint_as_float(o.w)));
            sts128(tb.z, make_uint4(__float_as_uint(acc[2][0]), __float_as_uint(acc[2][1]), __float_as_uint(acc[2][2]), __float_as_uint(acc[2][3])));
        }
        const uint32_t kb = ta.z + slot_off;
        if (warp == 0) PROF(14);
        bar_sync(NB_B, 256);
        if (warp < 5) {
            uint32_t q[16], k0, k1, k2, k3, k4, k5, k6, k7;
            float sa[4] = {0.f, 0.f, 0.f, 0.f}, sc[4] = {0.f, 0.f, 0.f, 0.f};
            ldsm4(q[0], q[1], q[2], q[3], ta.y);
            ldsm4(k0, k1, k2, k3, kb);
            ldsm4(q[4], q[5], q[6], q[7], ta.y ^ 32);
            ldsm4(q[8], q[9], q[10], q[11], ta.y ^ 64);
            ldsm4(k4, k5, k6, k7, kb ^ 64);
            ldsm4(q[12], q[13], q[14], q[15], ta.y ^ 96);
            mma16816(sa, q[0], q[1], q[2], q[3], k0, k1);
            bar_arrive(NB_Y, 288);
            mma16816(sc, q[4], q[5], q[6], q[7], k2, k3);
            mma16816(sa, q[8], q[9], q[10], q[11], k4, k5);
            mma16816(sc, q[12], q[13], q[14], q[15], k6, k7);
            const float scl = 0.08838834764831845f * 1.4426950408889634f;
            const float r0 = (sa[0] + sc[0]) * scl, r1 = (sa[1] + sc[1]) * scl;
            if (s != NSEG - 1) {
                st_async_v2(ta.w, r0, r1, sx_bar_rem);
                st_async_v2(ta.w ^ (1u << 24), r0, r1, sx_bar_rem ^ (1u << 24));
            }
            if (warp == 0) PROF(2);
        } else if (s > 0 && warp == 7 && lane == 0) {
            mbar_expect_tx(sb + RB_A, 4096);
            mbar_expect_tx(sb + RB_A1, 4096);
        }
        if (s == NSEG - 1) break;
        slot_off = slot_off == (R_NST - 1) * 4096 ? 0 : slot_off + slot_inc;
        const uint4 tc = lds128(tab + 4096), td = lds128(tab + 6144);
        const uint32_t te = lds32(tab + 8192);
        uint32_t* wr = (uint32_t*)(((uint64_t)td.y << 32) | (td.x ^ ((s & 1) * 0x21000)));
        const uint32_t* r1p = (const uint32_t*)((const char*)wr + (int)td.z);
        const uint32_t* r2p = (const uint32_t*)((const char*)wr + (int)td.w);
        const uint32_t* r3p = (const uint32_t*)((const char*)wr + (int)te);
        const uint32_t tag = ((s >> 1) + 1) & 1;
        mbar_wait(sb + RB_E, s & 1);
        if (warp == 0) PROF(7);
        {
            uint32_t a0, a1, a2, a3, a4, a5, a6, a7;
            ldsm4t(a0, a1, a2, a3, tc.x);
            ldsm4t(a4, a5, a6, a7, tc.x ^ 64);
            const uint32_t one = 0x3F803F80u;
            float d0_[4] = {0.f, 0.f, 0.f, 0.f}, d1_[4] = {0.f, 0.f, 0.f, 0.f};
            mma16816(d0_, a0, a1, a2, a3, one, one);
            mma16816(d1_, a4, a5, a6, a7, one, one);
            const bool t1 = tc.w & 1, t2 = tc.w & 2;
            const float x = t2 ? (t1 ? d1_[2] : d1_[0]) : (t1 ? d0_[2] : d0_[0]);
            const uint32_t own = (__float_as_uint(x) & ~1u) | tag;
            stg_relaxed32(wr, own);
            const uint32_t tq = clk32();
            if (warp == 0) PROF(8);
            PROFG(16 + warp);
#pragma unroll
            for (int i = 0; i < NOFF; i++) {
                const uint4 f0 = lds128(tab + 10240 + i * 2048);
                wa[i & 1][i >> 1][0] = f0.x; wa[i & 1][i >> 1][1] = f0.y; wa[i & 1][i >> 1][2] = f0.z; wa[i & 1][i >> 1][3] = f0.w;
            }
            tb = lds128(tab + 2048);
            while ((int)(clk32() - tq) < POLL_GAP) {}
            uint32_t f1, f2, f3;
            int gg = 0;
#pragma unroll 1
            while (true) {
                f1 = ldg_relaxed32(r1p); f2 = ldg_relaxed32(r2p); f3 = ldg_relaxed32(r3p);
                if (__all_sync(~0u, (((f1 ^ tag) | (f2 ^ tag) | (f3 ^ tag)) & 1) == 0)) break;
                if (++gg > 16 * SPIN_LIMIT) { TIMEOUT(3, s); break; }
            }
            if (warp == 0) PROF(9);
            PROFG(32 + warp);
            const float v = (__uint_as_float(own) + __uint_as_float(f2)) + (__uint_as_float(f1) + __uint_as_float(f3));
            const bool b8 = tc.w & 8, b16 = tc.w & 16;
            const float recv = __shfl_xor_sync(~0u, v, 8);
            const uint32_t word = b8 ? pack2(recv, v) : pack2(v, recv);
            const uint32_t oth = __shfl_xor_sync(~0u, word, 16);
            const uint32_t wl = b16 ? oth : word, wh = b16 ? word : oth;
            const uint32_t p0 = __shfl_xor_sync(~0u, wl, 2), p1 = __shfl_xor_sync(~0u, wh, 2);
            const uint4 item = t2 ? make_uint4(p0, p1, wl, wh) : make_uint4(wl, wh, p0, p1);
            st_async_v4(tc.y, item, tc.z);
            st_async_v4(tc.y ^ (8u << 24), item, tc.z ^ (8u << 24));
            if (tc.w == 0 && warp == 7) mbar_expect_tx(sb + RB_E, 8192);
            if (warp == 0) PROF(10);
            PROF(40 + warp);
        }
        bar_sync(NB_D, 384);
    }
}

__device__ __forceinline__ void rec_load_kv(uint32_t sb, int col0, int s, uint32_t slot_off, int t128) {
    const int row = t128 >> 2, c2 = (t128 & 3) * 2;
    const bf16* src = g_kv + ((size_t)(s * 32 + row) * (2 * HD_) + col0 + c2 * 8);
    const uint32_t d0 = sb + R_KX + slot_off + row * 128 + ((c2 ^ (row & 7)) << 4);
    cp_async16(d0, src);
    cp_async16(d0 ^ 16, src + 8);
    cp_async16(d0 + (R_VX - R_KX), src + HD_);
    cp_async16((d0 ^ 16) + (R_VX - R_KX), src + HD_ + 8);
}

__device__ __forceinline__ void rec_vo(const RecParams& p, const uint32_t sb, const int cta, const int warp, int lane) {
    const int w = warp - 8, crank = cta & 15;
    const int col0 = cta * 64;
    uint32_t wo[8][4][4];
    {
        const int t128 = w * 32 + lane;
        const bf16* Wo = p.wo + (size_t)col0 * D_;
        const uint32_t stg = sb + R_STG + 2 * 32768;
#pragma unroll
        for (int half = 0; half < 2; half++) {
#pragma unroll 4
            for (int i = t128; i < 2048; i += 128) {
                const int e = i >> 6, ch = i & 63;
                cp_async16(stg + e * 1024 + ((ch ^ (e & 7)) << 4), Wo + (size_t)(half * 32 + e) * D_ + ch * 8);
            }
            cp_async_commit();
            cp_async_wait<0>();
            bar_sync(NB_W0 + 2, 128);
#pragma unroll
            for (int j = 0; j < 8; j++)
#pragma unroll
                for (int kk = 0; kk < 2; kk++) {
                    const int e = kk * 16 + (lane >> 4) * 8 + (lane & 7);
                    const int ch = (w * 8 + j) * 2 + ((lane >> 3) & 1);
                    ldsm4t(wo[j][half * 2 + kk][0], wo[j][half * 2 + kk][1], wo[j][half * 2 + kk][2], wo[j][half * 2 + kk][3],
                           stg + e * 1024 + ((ch ^ (e & 7)) << 4));
                }
            bar_sync(NB_W0 + 2, 128);
        }
        if (lane == 0) wait_flag(F_KV + 0, 64);
        __syncwarp();
        rec_load_kv(sb, col0, 0, 0, t128); cp_async_commit();
        rec_load_kv(sb, col0, 1, 4096, t128); cp_async_commit();
        cp_async_wait<1>();
    }
    const uint32_t tab = sb + R_STG + 2 * 32768 + (w * 32 + lane) * 16;
    {
        const uint32_t l7 = lane & 7, l8 = lane >> 3, g = lane >> 2;
        uint4 v;
        v.x = sb + R_VX + ((l8 & 1) * 8 + l7) * 128 + (((2 * w + (l8 >> 1)) ^ l7) << 4);
        v.y = sb + R_OS + g * 128 + (((2 * w) ^ g) << 4) + (lane & 3) * 4;
        v.z = sb + R_VMS + l7 * 128 + (((2 * w + (l8 & 1)) ^ l7) << 4);
        v.w = sb + R_OS + l7 * 128 + ((l8 ^ l7) << 4);
        sts128(tab, v);
        v.x = mapa_u32(sb + R_RS + crank * 512 + ((lane ^ (crank & 7)) << 4), w * 4);
        v.y = mapa_u32(sb + RB_E, w * 4);
        v.z = sb + R_VP + w * 512 + lane * 16;
        v.w = sb + R_SX + lane * 8;
        sts128(tab + 2048, v);
#pragma unroll
        for (int i = 0; i < 8; i++) sts128(tab + 4096 + i * 2048, make_uint4(wo[i][0][0], wo[i][0][1], wo[i][0][2], wo[i][0][3]));
    }
    bar_sync(NB_D, 384);
    const uint32_t lane16 = lds32(tab + 2048 + 8) - R_VP - w * 512;
    uint4 av[2 * VK0];
#pragma unroll
    for (int i = 0; i < 2 * VK0; i++) av[i] = lds128(lane16 + R_WV + (i / VK0) * 32768 + (w * 16 + i % VK0) * 512);
    uint32_t slot_off = 0;
#pragma unroll 1
    for (int s = 0; s < NSEG; s++) {
        bar_sync(NB_Y, 288);
        uint32_t vb0, vb1;
        {
            float va[4] = {0.f, 0.f, 0.f, 0.f}, vc[4] = {0.f, 0.f, 0.f, 0.f};
            uint32_t bb[VK0][4];
#pragma unroll
            for (int k2 = 0; k2 < VK0; k2++) ldsm4(bb[k2][0], bb[k2][1], bb[k2][2], bb[k2][3], lane16 + R_MEM + (k2 / (VK0 / 2)) * 4096 + (k2 % (VK0 / 2)) * 512);
#pragma unroll
            for (int k2 = 0; k2 < VK0; k2++) {
                mma16816(va, av[2 * k2].x, av[2 * k2].y, av[2 * k2].z, av[2 * k2].w, bb[k2][0], bb[k2][1]);
                mma16816(vc, av[2 * k2 + 1].x, av[2 * k2 + 1].y, av[2 * k2 + 1].z, av[2 * k2 + 1].w, bb[k2][2], bb[k2][3]);
            }
            const uint4 a = lds128(lane16 + R_VP + w * 512), b = lds128(lane16 + R_VP + 2048 + w * 512);
            vb0 = pack2((va[0] + vc[0]) + (__uint_as_float(a.x) + __uint_as_float(b.x)), (va[1] + vc[1]) + (__uint_as_float(a.y) + __uint_as_float(b.y)));
            vb1 = pack2((va[2] + vc[2]) + (__uint_as_float(a.z) + __uint_as_float(b.z)), (va[3] + vc[3]) + (__uint_as_float(a.w) + __uint_as_float(b.w)));
        }
        const uint4 ta = lds128(tab), tb = lds128(tab + 2048);
        uint32_t vx[8];
        ldsm4t(vx[0], vx[1], vx[2], vx[3], ta.x + slot_off);
        ldsm4t(vx[4], vx[5], vx[6], vx[7], ta.x + slot_off + 2048);
#pragma unroll
        for (int i = 0; i < 4; i++) {
            const uint4 f0 = lds128(tab + 4096 + i * 2048);
            wo[i][0][0] = f0.x; wo[i][0][1] = f0.y; wo[i][0][2] = f0.z; wo[i][0][3] = f0.w;
        }
        if (w == 0) PROF(11);
        uint32_t pf[5];
        float oa[2][4] = {{0.f, 0.f, 0.f, 0.f}, {0.f, 0.f, 0.f, 0.f}}, ob_[2][4] = {{0.f, 0.f, 0.f, 0.f}, {0.f, 0.f, 0.f, 0.f}};
        float sm0[4] = {0.f, 0.f, 0.f, 0.f}, sm1[4] = {0.f, 0.f, 0.f, 0.f};
        if (s != NSEG - 1) {
            mbar_wait(sb + RB_SX, s & 1);
            if (w == 0) PROF(4);
            float sv[10];
#pragma unroll
            for (int n = 0; n < 5; n++) {
                const float2 a = lds64f(tb.w + n * 256), b = lds64f(tb.w + (5 + n) * 256);
                sv[2 * n] = a.x + b.x; sv[2 * n + 1] = a.y + b.y;
            }
            float mx = fmaxf(fmaxf(fmaxf(sv[0], sv[1]), fmaxf(sv[2], sv[3])), fmaxf(fmaxf(sv[4], sv[5]), fmaxf(sv[6], sv[7])));
            mx = fmaxf(mx, fmaxf(sv[8], sv[9]));
            mx = fmaxf(mx, __shfl_xor_sync(~0u, mx, 1));
            mx = fmaxf(mx, __shfl_xor_sync(~0u, mx, 2));
#pragma unroll
            for (int n = 1; n < 5; n++) pf[n] = pack2(ex2(sv[2 * n] - mx), ex2(sv[2 * n + 1] - mx));
            pf[0] = pack2(ex2(sv[0] - mx), ex2(sv[1] - mx));
            if (w == 0) PROF(12);
            const uint32_t one = 0x3F803F80u;
            mma16816h(sm0, pf[1], pf[2], one, one);
            mma16816h(oa[0], pf[1], pf[2], vx[0], vx[1]);
            mma16816h(oa[1], pf[1], pf[2], vx[2], vx[3]);
            mma16816h(sm1, pf[3], pf[4], one, one);
            mma16816h(ob_[0], pf[3], pf[4], vx[4], vx[5]);
            mma16816h(ob_[1], pf[3], pf[4], vx[6], vx[7]);
            mma1688h(sm0, pf[0], one);
            mma1688h(oa[0], pf[0], vb0);
            mma1688h(oa[1], pf[0], vb1);
            float inv;
            asm("rcp.approx.ftz.f32 %0, %1;" : "=f"(inv) : "f"(sm0[0] + sm1[0]));
            oa[0][0] += ob_[0][0]; oa[0][1] += ob_[0][1]; oa[1][0] += ob_[1][0]; oa[1][1] += ob_[1][1];
            sts32(ta.y, pack2(oa[0][0] * inv, oa[0][1] * inv));
            sts32(ta.y ^ 16, pack2(oa[1][0] * inv, oa[1][1] * inv));
            const uint32_t oa2 = ta.w ^ 64;
            bar_sync(NB_C, 128);
            if (w == 0) PROF(5);
            uint32_t ob[8];
            ldsm4(ob[0], ob[1], ob[2], ob[3], ta.w);
            ldsm4(ob[4], ob[5], ob[6], ob[7], oa2);
#pragma unroll
            for (int i = 4; i < 8; i++) {
                const uint4 f0 = lds128(tab + 4096 + i * 2048);
                wo[i][0][0] = f0.x; wo[i][0][1] = f0.y; wo[i][0][2] = f0.z; wo[i][0][3] = f0.w;
            }
#pragma unroll
            for (int jj = 0; jj < 2; jj++) {
                if (jj == 1 && tb.w == 0) break;
                float acc[4][4];
#pragma unroll
                for (int c = 0; c < 4; c++) { acc[c][0] = acc[c][1] = acc[c][2] = acc[c][3] = 0.f; }
#pragma unroll
                for (int ks = 0; ks < 4; ks++)
#pragma unroll
                    for (int c = 0; c < 4; c++)
                        mma16816(acc[c], wo[jj * 4 + c][ks][0], wo[jj * 4 + c][ks][1], wo[jj * 4 + c][ks][2], wo[jj * 4 + c][ks][3], ob[2 * ks], ob[2 * ks + 1]);
#pragma unroll
                for (int pr = 0; pr < 2; pr++) {
                    uint4 v;
                    v.x = pack2(acc[2 * pr][0], acc[2 * pr][1]);
                    v.y = pack2(acc[2 * pr][2], acc[2 * pr][3]);
                    v.z = pack2(acc[2 * pr + 1][0], acc[2 * pr + 1][1]);
                    v.w = pack2(acc[2 * pr + 1][2], acc[2 * pr + 1][3]);
                    st_async_v4(tb.x + ((jj * 2 + pr) << 24), v, tb.y + ((jj * 2 + pr) << 24));
                }
            }
            if (w == 0) PROF(6);
        }
        {
            stsm2t(ta.z, vb0, vb1);
            cp_async_wait<0>();
            bar_sync(NB_C, 128);
            if (w == 0 && lane == 0 && s != NSEG - 1) mbar_expect_tx(sb + RB_SX, 2560);
            const int omat = w >> 1, otok = (w & 1) * 4 + (lane >> 3), och = lane & 7;
            const uint4 v = lds128(sb + (omat ? R_VMS : R_KMS) + otok * 128 + ((och ^ otok) << 4));
            *(uint4*)(g_kvm + ((s * 8 + otok) * (2 * HD_) + omat * HD_ + col0 + och * 8)) = v;
            if (s != NSEG - 1) bar_arrive(NB_D, 384);
#pragma unroll
            for (int i = 0; i < 2 * VK0; i++) av[i] = lds128(lane16 + R_WV + (i / VK0) * 32768 + (w * 16 + i % VK0) * 512);
            if (s + 2 < NSEG - 1) {
                if (((s + 2) & 3) == 0) { if (lane == 0) wait_flag(F_KV + ((s + 2) >> 2), 64); __syncwarp(); }
                rec_load_kv(sb, col0, s + 2, slot_off == 0 ? (R_NST - 1) * 4096 : slot_off - 4096, w * 32 + lane);
            }
            cp_async_commit();
            if ((s & 3) == 3) {
                bar_sync(NB_C, 128);
                if (w == 0 && lane == 0) red_release(&g_flags[F_MEM + (s >> 2)], 1);
            }
        }
        slot_off = slot_off == (R_NST - 1) * 4096 ? 0 : slot_off + 4096;
    }
}

__global__ void __launch_bounds__(384, 1) k_rec(const RecParams p) {
    extern __shared__ __align__(1024) unsigned char smem_raw[];
    const uint32_t sb = __shfl_sync(~0u, smem_u32(smem_raw), 0);
    const int warp = __shfl_sync(~0u, threadIdx.x >> 5, 0);
    int lane; asm volatile("mov.u32 %0, %%laneid;" : "=r"(lane));
    const int crank = blockIdx.x & 15, slot = blockIdx.x >> 4;
    asm volatile("griddepcontrol.launch_dependents;");
    if (threadIdx.x == 0) {
        mbar_init(sb + RB_SX, 1); mbar_init(sb + RB_E, 1); mbar_init(sb + RB_A, 1); mbar_init(sb + RB_A1, 1); mbar_init(sb + RB_ROLE, 1);
        asm volatile("fence.mbarrier_init.release.cluster;" ::: "memory");
        mbar_expect_tx(sb + RB_SX, 2560);
        mbar_expect_tx(sb + RB_E, 8192);
        mbar_expect_tx(sb + RB_A, 4096);
        mbar_expect_tx(sb + RB_A1, 4096);
        mbar_expect_tx(sb + RB_ROLE, 4);
    }
    unsigned role = 0;
    if (crank == 0 && threadIdx.x == 0) {
        unsigned x = 0;
        int tm[2] = {0x7fffffff, 0x7fffffff};
#pragma unroll 1
        for (int i = 0; i < 6; i++) {
            const uint32_t t0 = clk32();
            x = atomicAdd(&g_F[65536 + (i & 1) * 1024 + slot * 64 + (x >> 31)], 0u) & 0x7fffffffu;
            if (x == 0x7654321u) sts32(sb + R_BAR + 56, x);
            const int dt = (int)(clk32() - t0);
            if (i >= 2) { if (i & 1) tm[1] = min(tm[1], dt); else tm[0] = min(tm[0], dt); }
        }
        const int side = tm[1] > tm[0];
        const unsigned old = atomicAdd(&g_flags[F_SIDE + side * 32], 1u);
        unsigned c0, c1; int gd = 0;
#pragma unroll 1
        do { c0 = ldg_relaxed32(&g_flags[F_SIDE]); c1 = ldg_relaxed32(&g_flags[F_SIDE + 32]); } while ((int)(c0 + c1) < p.ncl && ++gd < 64 * SPIN_LIMIT);
        const int big = c1 > c0;
        role = side == big ? old : (big ? c1 : c0) + old;
        role |= (big ^ 1) << 8;
    }
    __syncwarp();
    asm volatile("barrier.cluster.arrive.relaxed.aligned;\nbarrier.cluster.wait.aligned;" ::: "memory");
    if (crank == 0 && warp == 0) {
        role = __shfl_sync(~0u, role, 0);
        if (lane < 16)
            asm volatile("st.async.weak.shared::cluster.mbarrier::complete_tx::bytes.u32 [%0], %1, [%2];"
                         :: "r"(mapa_u32(sb + R_BAR + 48, lane)), "r"(role), "r"(mapa_u32(sb + RB_ROLE, lane)) : "memory");
    }
    mbar_wait(sb + RB_ROLE, 0);
    const int rolew = __shfl_sync(~0u, lds32(sb + R_BAR + 48), 0);
    const int cl = rolew & 255;
    if (cl >= 4) return;
    const int cta = cl * 16 + crank;
    if (warp < 8) rec_qk(p, sb, cta, warp, lane, rolew >> 8);
    else rec_vo(p, sb, cta, warp, lane);
}

enum { J_KV = 0, J_QA = 1, J_O = 2, J_LN = 3, J_UP = 4, J_DN = 5, J_UP2 = 6, J_END = 8 };
constexpr int NJ_O = 2 * OSPLIT, NJ_O2 = 2 * OSPLIT2, NJ_LN = 8, NJ_LN2 = 16, NJ_UP = 14, NJ_UP2 = 28, NJ_DN = 8;
__device__ __forceinline__ int nj_coarse(int q) { return q == J_KV ? 32 : (q == J_QA ? 16 : (q == J_O ? NJ_O : (q == J_LN ? NJ_LN : (q == J_UP ? NJ_UP : NJ_DN)))); }
__device__ __forceinline__ int nj_fine(int q) { return q == J_KV ? 32 : (q == J_QA ? 16 : (q == J_O ? NJ_O2 : (q == J_LN ? NJ_LN2 : (q == J_UP ? NJ_UP2 : NJ_DN)))); }
__device__ __forceinline__ int pick_job(int lane, int qmask, int& idx) {
    const int rb = lane & 15, half = lane >> 4;
    const bool fine = rb >= FINE_RB;
    int gd = 0;
#pragma unroll 1
    while (true) {
        unsigned cl[3], dp[3];
#pragma unroll
        for (int i = 0; i < 3; i++) {
            const int q = half + 2 * i;
            cl[i] = ldg_relaxed32(&g_flags[F_CLAIM + q * 32 + rb]);
            dp[i] = ldg_relaxed32(&g_flags[q * 32 + (q == J_QA ? max(rb - 1, 0) : rb)]);
        }
        int pick_q = -1, pick_rb = 0, early_q = -1, early_rb = 0;
        unsigned prev16 = 0;
        bool any = false;
#pragma unroll
        for (int i = 0; i < 3; i++) {
            const int q = half + 2 * i;
            const bool have = ((qmask >> q) & 1) && (int)cl[i] < (fine ? nj_fine(q) : nj_coarse(q));
            const unsigned tgt = q == J_QA ? 64 : 2 * (fine ? nj_fine(q - 1) : nj_coarse(q - 1));
            const bool ready = have && (q == J_KV || (q == J_QA && rb == 0) || dp[i] >= tgt);
            const unsigned mh = __ballot_sync(~0u, have), mr = __ballot_sync(~0u, ready);
            any |= mh != 0;
#pragma unroll
            for (int hf = 0; hf < 2; hf++) {
                const int qq = hf + 2 * i;
                const unsigned r16 = (mr >> (16 * hf)) & 0xffffu, h16 = (mh >> (16 * hf)) & 0xffffu;
                if (r16 && pick_q != J_KV) { pick_q = qq; pick_rb = __ffs(r16) - 1; }
                if (qq >= J_O && early_q < 0 && h16 && __ffs(h16) - 1 >= FINE_RB && (prev16 & ((2u << (__ffs(h16) - 1)) - 1)) == 0) {
                    early_q = qq; early_rb = __ffs(h16) - 1;
                }
                prev16 |= h16;
            }
        }
        if (!any) return J_END;
        if (pick_q < 0) { pick_q = early_q; pick_rb = early_rb; }
        if (pick_q >= 0) {
            int c = 0;
            if (lane == 0) c = (int)atomicAdd(&g_flags[F_CLAIM + pick_q * 32 + pick_rb], 1u);
            c = __shfl_sync(~0u, c, 0);
            const bool f = pick_rb >= FINE_RB;
            if (c < (f ? nj_fine(pick_q) : nj_coarse(pick_q))) {
                idx = pick_q * 600 + pick_rb * 32 + c;
                return (pick_q == J_UP && f ? J_UP2 : pick_q) | (pick_rb << 8) | (c << 16);
            }
        } else {
            __nanosleep(200);
            if (++gd > 16 * SPIN_LIMIT) { TIMEOUT(5, 0); return J_END; }
        }
    }
}
__device__ __forceinline__ int op_row(int rb, int split) {
    return rb < FINE_RB ? split * S_ + rb * 128 : OSPLIT * S_ + (split * (NRB - FINE_RB) + rb - FINE_RB) * 128;
}

struct Pipe { uint32_t stage, phase; };
__device__ __forceinline__ void pipe_next(Pipe& p) { if (++p.stage == W_NST) { p.stage = 0; p.phase ^= 1; } }

__device__ __forceinline__ void scheduler(const Params& p, uint32_t sb, int lane) {
    const uint32_t bars = sb + SM_BAR;
    uint32_t ph = 0;
#pragma unroll 1
    while (true) {
        mbar_wait(bars + B_REQ, ph);
        int j = 4095;
        const int jd = pick_job(lane, p.qmask, j);
        if (lane == 0) { sts32(bars + B_NEXT, (uint32_t)jd); sts32(bars + B_NEXT + 4, (uint32_t)j); mbar_arrive(bars + B_RSP); }
        ph ^= 1;
        if (jd == J_END) break;
        __syncwarp();
    }
}

__device__ __forceinline__ void producer(const Params& p, uint32_t sb) {
    Pipe pp{0, 1};
    const uint32_t bars = sb + SM_BAR;
    uint32_t seq = 0;
    mbar_arrive(bars + B_REQ);
#pragma unroll 1
    while (true) {
        mbar_wait(bars + B_RSP, seq & 1);
        const int jd = (int)lds32(bars + B_NEXT), j = (int)lds32(bars + B_NEXT + 4);
        int left = (jd & 255) == J_DN ? 15 : ((jd & 255) == J_QA ? 12 : ((jd & 255) == J_O ? (((jd >> 8) & 255) >= FINE_RB ? 64 / OSPLIT2 : 64 / OSPLIT) : ((jd & 255) == J_LN ? 1 : 8)));
        left = max(left - PICK_AHEAD, 1);
        TR(j, 1);
        const int type = jd & 255, rb = (jd >> 8) & 255, cb = jd >> 16;
        const bool fine = rb >= FINE_RB;
        bool first = true;
        auto begin_stage = [&](uint32_t bytes) -> uint32_t {
            mbar_wait(bars + B_EMPTY + pp.stage * 8, pp.phase);
            if (first) { sts32(bars + B_RING + (seq & 7) * 4, (uint32_t)jd); sts32(bars + B_RING + 32 + (seq & 7) * 4, (uint32_t)j); first = false; }
            const uint32_t fb = bars + B_FULL + pp.stage * 8;
            if (bytes) mbar_expect_tx(fb, bytes); else mbar_arrive(fb);
            if (--left == 0 && type != J_END) mbar_arrive(bars + B_REQ);
            return fb;
        };
        if (type == J_END || type == J_LN) {
            if (type == J_LN) wait_flag(F_OP + rb, 2 * (fine ? NJ_O2 : NJ_O));
            TR(j, 2);
            begin_stage(0); pipe_next(pp);
            seq++;
            if (type == J_END) break;
            continue;
        }
        const CUtensorMap *ta, *tb0, *tb1;
        int k0 = 0, nk = 8, n0 = cb * 256, n1 = n0 + 128, nb = 4, dep = -1;
        unsigned tgt = 0;
        switch (type) {
            case J_KV: ta = &p.tm_h; tb0 = tb1 = cb < 16 ? &p.tm_wk : &p.tm_wv; n0 = (cb & 15) * 256; n1 = n0 + 128; break;
            case J_QA: ta = &p.tm_h; tb0 = tb1 = &p.tm_wq; break;
            case J_O: ta = &p.tm_o; tb0 = tb1 = &p.tm_wo; n0 = (cb & 1) * 256; n1 = n0 + 128; nk = fine ? 64 / OSPLIT2 : 64 / OSPLIT; k0 = (cb >> 1) * nk * 64;
                      dep = F_O + rb; tgt = 32; break;
            case J_UP: ta = &p.tm_h2; tb0 = &p.tm_wg; tb1 = &p.tm_wu; n0 = n1 = cb * 128; dep = F_H2 + rb; tgt = 2 * NJ_LN; break;
            case J_UP2: ta = &p.tm_h2; tb0 = &p.tm_wg; tb1 = &p.tm_wu; n0 = n1 = cb * 64; nb = 2; dep = F_H2 + rb; tgt = 2 * NJ_LN2; break;
            default: ta = &p.tm_act; tb0 = tb1 = &p.tm_wd; n0 = cb * 64; nk = 0; break;
        }
        const int m0 = rb * 128;
        if (type == J_DN) {
#pragma unroll 1
            for (int kb = 0; kb < 14; kb++) {
                const uint32_t fb = begin_stage(49152);
                const uint32_t st = sb + pp.stage * W_STAGE;
                const int k = kb * 128;
                tma_load2d(st + 32768, tb0, n0, k, fb);
                tma_load2d(st + 40960, tb0, n0, k + 64, fb);
                if (kb == 0) { wait_flag(F_ACT + rb, 2 * (fine ? NJ_UP2 : NJ_UP)); fence_async_all(); TR(j, 2); }
                tma_load2d(st, ta, k, m0, fb);
                tma_load2d(st + 8192, ta, k, m0 + 64, fb);
                tma_load2d(st + 16384, ta, k + 64, m0, fb);
                tma_load2d(st + 24576, ta, k + 64, m0 + 64, fb);
                pipe_next(pp);
            }
        }
#pragma unroll 1
        for (int kb = 0; kb < nk; kb++) {
            const uint32_t fb = begin_stage(16384 + nb * 8192);
            const uint32_t st = sb + pp.stage * W_STAGE;
            const int k = k0 + kb * 64;
            tma_load2d(st + 16384, tb0, n0, k, fb);
            if (nb == 4) {
                tma_load2d(st + 16384 + 8192, tb0, n0 + 64, k, fb);
                tma_load2d(st + 16384 + 16384, tb1, n1, k, fb);
                tma_load2d(st + 16384 + 24576, tb1, n1 + 64, k, fb);
            } else if (nb == 2) {
                tma_load2d(st + 16384 + 8192, tb1, n1, k, fb);
            }
            if (kb == 0) {
                if (dep >= 0) { wait_flag(dep, tgt); if (type >= J_UP) fence_async_all(); }
                TR(j, 2);
            }
            tma_load2d(st, ta, k, m0, fb);
            tma_load2d(st + 8192, ta, k, m0 + 64, fb);
            pipe_next(pp);
        }
        if (type == J_QA) {
            wait_flag(F_KV + rb, 64);
#pragma unroll 1
            for (int i = 0; i < 4; i++) {
                const uint32_t fb = begin_stage(40960);
                const uint32_t st = sb + pp.stage * W_STAGE;
                const int col = (i & 1) * HD_ + (cb * 2 + (i >> 1)) * DH_;
                tma_load2d(st, &p.tm_kv, col, m0, fb);
                tma_load2d(st + 8192, &p.tm_kv, col, m0 + 64, fb);
                tma_load2d(st + 16384, &p.tm_kv, col + 64, m0, fb);
                tma_load2d(st + 24576, &p.tm_kv, col + 64, m0 + 64, fb);
                if (i == 0) { wait_flag(F_MEM + rb, 64); fence_async_all(); }
                tma_load2d(st + 32768, &p.tm_kvm, col, rb * 32, fb);
                tma_load2d(st + 36864, &p.tm_kvm, col + 64, rb * 32, fb);
                pipe_next(pp);
            }
        } else if (type == J_DN) {
            const uint32_t fb = begin_stage(16384);
            const uint32_t st = sb + pp.stage * W_STAGE;
            tma_load2d(st, &p.tm_x1, n0, m0, fb);
            tma_load2d(st + 8192, &p.tm_x1, n0, m0 + 64, fb);
            pipe_next(pp);
        }
        seq++;
    }
}

__device__ __forceinline__ void store_warp(const Params& p, uint32_t sb, int wg, int lane) {
    const uint32_t bars = sb + SM_BAR;
    uint32_t seq = 0;
#pragma unroll 1
    while (true) {
        bar_sync(NB_ST + wg, 160);
        const uint32_t jd = lds32(bars + B_RING + (seq & 7) * 4);
        seq++;
        const int type = jd & 255, rb = (jd >> 8) & 255, cb = jd >> 16;
        if (type == J_END) break;
        if (lane == 0) {
            const uint32_t src = sb + W_STG + wg * 32768;
            const CUtensorMap* tm = nullptr; int n0 = cb * 256, nbox = 4, mrow = rb * 128 + wg * 64, flag = 0;
            switch (type) {
                case J_KV: tm = &p.tm_kv; flag = F_KV + rb; break;
                case J_QA: tm = &p.tm_o; flag = F_O + rb; break;
                case J_O: tm = &p.tm_op; n0 = (cb & 1) * 256; mrow = op_row(rb, cb >> 1) + wg * 64; flag = F_OP + rb; break;
                case J_LN: flag = F_H2 + rb; nbox = 0; break;
                case J_UP: tm = &p.tm_act; n0 = cb * 128; nbox = 2; flag = F_ACT + rb; break;
                case J_UP2: tm = &p.tm_act; n0 = cb * 64; nbox = 1; flag = F_ACT + rb; break;
                default: tm = &p.tm_out; n0 = cb * 64; nbox = 1; flag = -1; break;
            }
#pragma unroll 1
            for (int b = 0; b < nbox; b++) tma_store2d(tm, src + b * 8192, n0 + b * 64, mrow);
            bulk_commit();
            bulk_wait0();
            mbar_arrive(bars + B_STGFREE + wg * 8);
            if (flag >= 0) red_release(&g_flags[flag], 1);
        }
        __syncwarp();
    }
}

__device__ __forceinline__ float gelu_tanh(float x) {
    const float t = x * fmaf(-0.10294324397f, x * x, -2.30220819814f);
    float r; asm("rcp.approx.ftz.f32 %0, %1;" : "=f"(r) : "f"(1.f + ex2(t)));
    return x * r;
}

#define CTR(i) do {} while (0)

template <int NSPLIT>
__device__ __forceinline__ void ln2_row(const Params& p, int rb, int r, int lane) {
    const int row = rb * 128 + r;
    uint4 u[2 * NSPLIT];
#pragma unroll
    for (int sp = 0; sp < NSPLIT; sp++) {
        const uint4* src = (const uint4*)(g_op + (size_t)(op_row(rb, sp) + r) * D_);
        u[2 * sp] = __ldcg(src + lane); u[2 * sp + 1] = __ldcg(src + 32 + lane);
    }
    const uint4* xr = (const uint4*)(p.x + (size_t)row * D_);
    const uint4 xa = __ldg(xr + lane), xb = __ldg(xr + 32 + lane);
    uint32_t ga[8], c1[8], sm[8];
    load_mod8(g_mod + 2 * D_, lane, ga);
    load_mod8(g_mod + 4 * D_, lane, c1);
    load_mod8(g_mod + 3 * D_, lane, sm);
    float a[16];
#pragma unroll
    for (int i = 0; i < 16; i++) a[i] = 0.f;
#pragma unroll
    for (int sp = 0; sp < 2 * NSPLIT; sp++) {
        float* q = a + (sp & 1) * 8;
        q[0] += bflo(u[sp].x); q[1] += bfhi(u[sp].x); q[2] += bflo(u[sp].y); q[3] += bfhi(u[sp].y);
        q[4] += bflo(u[sp].z); q[5] += bfhi(u[sp].z); q[6] += bflo(u[sp].w); q[7] += bfhi(u[sp].w);
    }
    const uint32_t xv[8] = {xa.x, xa.y, xa.z, xa.w, xb.x, xb.y, xb.z, xb.w};
    uint32_t v[8], r8[8];
#pragma unroll
    for (int i = 0; i < 8; i++) v[i] = hadd2(xv[i], hmul2(ga[i], pack2(a[2 * i], a[2 * i + 1])));
    uint4* x1r = (uint4*)(g_x1 + (size_t)row * D_);
    x1r[lane] = make_uint4(v[0], v[1], v[2], v[3]); x1r[32 + lane] = make_uint4(v[4], v[5], v[6], v[7]);
    uint32_t mu2; float rden;
    ln_stats(v, mu2, rden);
#pragma unroll
    for (int i = 0; i < 8; i++) c1[i] = hadd2(c1[i], 0x3F803F80u);
    ln_apply(v, mu2, rden, c1, sm, r8);
    uint4* hr = (uint4*)(g_h2 + (size_t)row * D_);
    hr[lane] = make_uint4(r8[0], r8[1], r8[2], r8[3]); hr[32 + lane] = make_uint4(r8[4], r8[5], r8[6], r8[7]);
}

__device__ __forceinline__ void consumer(const Params& p, uint32_t sb, int warp, int lane) {
    const uint32_t bars = sb + SM_BAR;
    const int wg = warp >> 2, wl = warp & 3;
    const uint32_t l7 = lane & 7, l8 = lane >> 3, g = lane >> 2, t = lane & 3;
    Pipe pp{0, 0};
    uint32_t seq = 0, stg_phase = 1;
    const int srow = wl * 16 + l7 + (l8 & 1) * 8;
    const uint32_t stg_base = sb + W_STG + wg * 32768 + srow * 128;
    const uint32_t sx = ((lane >> 4) ^ (srow & 7)) << 4;
#pragma unroll 1
    while (true) {
        mbar_wait(bars + B_FULL + pp.stage * 8, pp.phase);
        const uint32_t jd = lds32(bars + B_RING + (seq & 7) * 4);
        CTR(3);
        seq++;
        const int type = jd & 255, rb = (jd >> 8) & 255, cb = jd >> 16;
        if (type == J_END) { mbar_wait(bars + B_STGFREE + wg * 8, stg_phase); bar_arrive(NB_ST + wg, 160); break; }
        if (type == J_LN) {
            __syncwarp();
            if (lane == 0) mbar_arrive(bars + B_EMPTY + pp.stage * 8);
            pipe_next(pp);
            if (rb >= FINE_RB) ln2_row<OSPLIT2>(p, rb, cb * 8 + warp, lane);
            else {
#pragma unroll 1
                for (int rr = 0; rr < 2; rr++) ln2_row<OSPLIT>(p, rb, cb * 16 + warp * 2 + rr, lane);
            }
            mbar_wait(bars + B_STGFREE + wg * 8, stg_phase); stg_phase ^= 1;
            CTR(4); CTR(5);
            bar_arrive(NB_ST + wg, 160);
            continue;
        }
        if (type >= J_DN) {
            float acc[64];
#pragma unroll
            for (int i = 0; i < 64; i++) acc[i] = 0.f;
            if (type == J_DN) {
#pragma unroll 1
                for (int kb = 0; kb < 14; kb++) {
                    if (kb) mbar_wait(bars + B_FULL + pp.stage * 8, pp.phase);
                    const uint32_t st = sb + pp.stage * W_STAGE;
                    const uint64_t da = mkdesc(st + wg * 8192, 16, 1024), db = mkdesc(st + 32768, 8192, 1024);
                    wg_fence();
#pragma unroll
                    for (int ks = 0; ks < 8; ks++) wgmma_n64(acc, da + (ks >> 2) * 1024 + (ks & 3) * 2, db + ks * 128);
                    wg_commit();
                    wg_wait0();
                    if (lane == 0) mbar_arrive(bars + B_EMPTY + pp.stage * 8);
                    pipe_next(pp);
                }
            } else {
#pragma unroll 1
                for (int kb = 0; kb < 8; kb++) {
                    if (kb) mbar_wait(bars + B_FULL + pp.stage * 8, pp.phase);
                    const uint32_t st = sb + pp.stage * W_STAGE;
                    const uint64_t da = mkdesc(st + wg * 8192, 16, 1024), db = mkdesc(st + 16384, 8192, 1024);
                    wg_fence();
#pragma unroll
                    for (int ks = 0; ks < 4; ks++) wgmma_n128(acc, da + ks * 2, db + ks * 128, 1);
                    wg_commit();
                    wg_wait0();
                    if (lane == 0) mbar_arrive(bars + B_EMPTY + pp.stage * 8);
                    pipe_next(pp);
                }
            }
            CTR(4);
            if (type == J_UP2) {
                mbar_wait(bars + B_STGFREE + wg * 8, stg_phase); stg_phase ^= 1;
#pragma unroll
                for (int j = 0; j < 4; j++) {
                    uint32_t r[4];
#pragma unroll
                    for (int q = 0; q < 4; q++) {
                        const uint32_t gw = pack2(acc[8 * j + 2 * q], acc[8 * j + 2 * q + 1]);
                        const uint32_t uw = pack2(acc[32 + 8 * j + 2 * q], acc[32 + 8 * j + 2 * q + 1]);
                        r[q] = hmul2(pack2(gelu_tanh(bflo(gw)), gelu_tanh(bfhi(gw))), uw);
                    }
                    stsm4(stg_base + (sx ^ (j << 5)), r[0], r[1], r[2], r[3]);
                }
            } else {
                mbar_wait(bars + B_FULL + pp.stage * 8, pp.phase);
                const uint32_t st = sb + pp.stage * W_STAGE;
                mbar_wait(bars + B_STGFREE + wg * 8, stg_phase); stg_phase ^= 1;
                const uint32_t* gb = (const uint32_t*)(g_mod + 5 * D_ + cb * 64) + t;
                const uint32_t xa = st + wg * 8192 + (wl * 16 + g) * 128 + (g << 4) + t * 4;
#pragma unroll
                for (int j = 0; j < 4; j++) {
                    uint32_t r[4];
#pragma unroll
                    for (int q = 0; q < 4; q++) {
                        const int nt = 2 * j + (q >> 1);
                        const uint32_t xw = lds32((xa ^ ((nt & 7) << 4)) + (nt >> 3) * 16384 + (q & 1) * 1024);
                        r[q] = hadd2(xw, hmul2(__ldcg(gb + nt * 4), pack2(acc[8 * j + 2 * q], acc[8 * j + 2 * q + 1])));
                    }
                    stsm4(stg_base + (j >> 2) * 8192 + (sx ^ ((2 * j & 7) << 4)), r[0], r[1], r[2], r[3]);
                }
                __syncwarp();
                if (lane == 0) mbar_arrive(bars + B_EMPTY + pp.stage * 8);
                pipe_next(pp);
            }
            fence_async_smem();
            CTR(5);
            bar_arrive(NB_ST + wg, 160);
            continue;
        }
        float acc[128];
#pragma unroll
        for (int i = 0; i < 128; i++) acc[i] = 0.f;
        const int nk = type == J_O ? (rb >= FINE_RB ? 64 / OSPLIT2 : 64 / OSPLIT) : 8;
#pragma unroll 1
        for (int kb = 0; kb < nk; kb++) {
            if (kb) mbar_wait(bars + B_FULL + pp.stage * 8, pp.phase);
            const uint32_t st = sb + pp.stage * W_STAGE;
            const uint64_t da = mkdesc(st + wg * 8192, 16, 1024), db = mkdesc(st + 16384, 8192, 1024);
            wg_fence();
#pragma unroll
            for (int ks = 0; ks < 4; ks++) wgmma_n256(acc, da + ks * 2, db + ks * 128, 1);
            wg_commit();
            wg_wait0();
            if (lane == 0) mbar_arrive(bars + B_EMPTY + pp.stage * 8);
            pipe_next(pp);
        }
        CTR(4);
        if (type == J_QA) {
            uint32_t qf[64];
#pragma unroll
            for (int i = 0; i < 64; i++) qf[i] = pack2(acc[2 * i], acc[2 * i + 1]);
            const int sg = warp >> 1, half = warp & 1;
            const float sc = 0.08838834764831845f * 1.4426950408889634f;
            const uint32_t xoff = (sg >> 1) * 8192 + ((sg & 1) * 32 + l7) * 128;
            const uint32_t moff = 32768 + (sg * 8 + l7) * 128;
            const uint32_t kch = (l8 ^ l7) << 4;
            const uint32_t vch = ((l8 & 1) ^ l7) << 4;
            mbar_wait(bars + B_STGFREE + wg * 8, stg_phase); stg_phase ^= 1;
#pragma unroll 1
            for (int hh = 0; hh < 2; hh++) {
                mbar_wait(bars + B_FULL + pp.stage * 8, pp.phase);
                uint32_t st = sb + pp.stage * W_STAGE;
                float sa[5][4];
#pragma unroll
                for (int n = 0; n < 5; n++) sa[n][0] = sa[n][1] = sa[n][2] = sa[n][3] = 0.f;
#pragma unroll
                for (int i = 0; i < 4; i++) {
                    const uint32_t* q = qf + i * 8;
                    uint32_t kk[5][4];
                    ldsm4(kk[0][0], kk[0][1], kk[0][2], kk[0][3], st + moff + (i >> 1) * 4096 + (kch ^ ((i & 1) * 64)));
#pragma unroll
                    for (int n = 1; n < 5; n++)
                        ldsm4(kk[n][0], kk[n][1], kk[n][2], kk[n][3], st + xoff + (n - 1) * 1024 + (i >> 1) * 16384 + (kch ^ ((i & 1) * 64)));
#pragma unroll
                    for (int n = 0; n < 5; n++) mma16816(sa[n], q[0], q[1], q[2], q[3], kk[n][0], kk[n][1]);
#pragma unroll
                    for (int n = 0; n < 5; n++) mma16816(sa[n], q[4], q[5], q[6], q[7], kk[n][2], kk[n][3]);
                }
                __syncwarp();
                if (lane == 0) mbar_arrive(bars + B_EMPTY + pp.stage * 8);
                pipe_next(pp);
                const int iq0 = half * 16 + g - 2 * t, iq1 = iq0 + 8;
                float m0 = fmaxf(sa[0][0], sa[0][1]), m1 = fmaxf(sa[0][2], sa[0][3]);
#pragma unroll
                for (int n = 1; n < 5; n++) {
#pragma unroll
                    for (int e = 0; e < 2; e++) {
                        const int jx = (n - 1) * 8 + e;
                        if (jx > iq0) sa[n][e] = -3.0e38f;
                        if (jx > iq1) sa[n][2 + e] = -3.0e38f;
                        m0 = fmaxf(m0, sa[n][e]); m1 = fmaxf(m1, sa[n][2 + e]);
                    }
                }
                m0 = fmaxf(m0, __shfl_xor_sync(~0u, m0, 1)); m1 = fmaxf(m1, __shfl_xor_sync(~0u, m1, 1));
                m0 = fmaxf(m0, __shfl_xor_sync(~0u, m0, 2)); m1 = fmaxf(m1, __shfl_xor_sync(~0u, m1, 2));
                m0 *= -sc; m1 *= -sc;
                float l0 = 0.f, l1 = 0.f;
                uint32_t p0[5], p1[5];
#pragma unroll
                for (int n = 0; n < 5; n++) {
                    const float e0 = ex2(fmaf(sa[n][0], sc, m0)), e1 = ex2(fmaf(sa[n][1], sc, m0));
                    const float e2 = ex2(fmaf(sa[n][2], sc, m1)), e3 = ex2(fmaf(sa[n][3], sc, m1));
                    l0 += e0 + e1; l1 += e2 + e3;
                    p0[n] = pack2(e0, e1); p1[n] = pack2(e2, e3);
                }
                l0 += __shfl_xor_sync(~0u, l0, 1); l1 += __shfl_xor_sync(~0u, l1, 1);
                l0 += __shfl_xor_sync(~0u, l0, 2); l1 += __shfl_xor_sync(~0u, l1, 2);
                const float i0 = __fdividef(1.f, l0), i1 = __fdividef(1.f, l1);
                mbar_wait(bars + B_FULL + pp.stage * 8, pp.phase);
                st = sb + pp.stage * W_STAGE;
#pragma unroll
                for (int i = 0; i < 32; i++) qf[i] = qf[32 + i];
#pragma unroll 1
                for (int bx = 0; bx < 2; bx++) {
                    float o[8][4];
                    uint32_t vm[8], v0[4][4], v1[4][4];
#pragma unroll
                    for (int ep = 0; ep < 4; ep++) {
                        ldsm2t(vm[2 * ep], vm[2 * ep + 1], st + moff + bx * 4096 + (vch ^ (ep << 5)));
                        const uint32_t va = st + xoff + (l8 >> 1) * 1024 + bx * 16384 + (vch ^ (ep << 5));
                        ldsm4t(v0[ep][0], v0[ep][1], v0[ep][2], v0[ep][3], va);
                        ldsm4t(v1[ep][0], v1[ep][1], v1[ep][2], v1[ep][3], va + 2048);
                    }
#pragma unroll
                    for (int n = 0; n < 8; n++) { o[n][0] = o[n][1] = o[n][2] = o[n][3] = 0.f; mma16816(o[n], p0[0], p1[0], p0[1], p1[1], vm[n], v0[n >> 1][n & 1]); }
#pragma unroll
                    for (int n = 0; n < 8; n++) mma16816(o[n], p0[2], p1[2], p0[3], p1[3], v0[n >> 1][2 + (n & 1)], v1[n >> 1][n & 1]);
#pragma unroll
                    for (int n = 0; n < 8; n++) mma1688(o[n], p0[4], p1[4], v1[n >> 1][2 + (n & 1)]);
#pragma unroll
                    for (int ep = 0; ep < 4; ep++)
                        stsm4(stg_base + (hh * 2 + bx) * 8192 + (sx ^ (ep << 5)),
                              pack2(o[2 * ep][0] * i0, o[2 * ep][1] * i0), pack2(o[2 * ep][2] * i1, o[2 * ep][3] * i1),
                              pack2(o[2 * ep + 1][0] * i0, o[2 * ep + 1][1] * i0), pack2(o[2 * ep + 1][2] * i1, o[2 * ep + 1][3] * i1));
                }
                __syncwarp();
                if (lane == 0) mbar_arrive(bars + B_EMPTY + pp.stage * 8);
                pipe_next(pp);
            }
        } else if (type == J_UP) {
            mbar_wait(bars + B_STGFREE + wg * 8, stg_phase); stg_phase ^= 1;
#pragma unroll
            for (int j = 0; j < 8; j++) {
                uint32_t r[4];
#pragma unroll
                for (int q = 0; q < 4; q++) {
                    const uint32_t gw = pack2(acc[8 * j + 2 * q], acc[8 * j + 2 * q + 1]);
                    const uint32_t uw = pack2(acc[64 + 8 * j + 2 * q], acc[64 + 8 * j + 2 * q + 1]);
                    r[q] = hmul2(pack2(gelu_tanh(bflo(gw)), gelu_tanh(bfhi(gw))), uw);
                }
                stsm4(stg_base + (j >> 2) * 8192 + (sx ^ ((2 * j & 7) << 4)), r[0], r[1], r[2], r[3]);
            }
        } else {
            mbar_wait(bars + B_STGFREE + wg * 8, stg_phase); stg_phase ^= 1;
#pragma unroll
            for (int j = 0; j < 16; j++)
                stsm4(stg_base + (j >> 2) * 8192 + (sx ^ ((2 * j & 7) << 4)),
                      pack2(acc[8 * j], acc[8 * j + 1]), pack2(acc[8 * j + 2], acc[8 * j + 3]),
                      pack2(acc[8 * j + 4], acc[8 * j + 5]), pack2(acc[8 * j + 6], acc[8 * j + 7]));
        }
        fence_async_smem();
        CTR(5);
        bar_arrive(NB_ST + wg, 160);
    }
}

__global__ void __launch_bounds__(384, 1) k_work(const __grid_constant__ Params p) {
    extern __shared__ __align__(1024) unsigned char smem_raw[];
    const uint32_t sb = smem_u32(smem_raw);
    if (sb & 1023) __trap();
    const int warp = __shfl_sync(~0u, threadIdx.x >> 5, 0);
    int lane; asm volatile("mov.u32 %0, %%laneid;" : "=r"(lane));
    if (threadIdx.x == 0) {
        const uint32_t bars = sb + SM_BAR;
        for (int i = 0; i < W_NST; i++) { mbar_init(bars + B_FULL + i * 8, 1); mbar_init(bars + B_EMPTY + i * 8, 8); }
        mbar_init(bars + B_STGFREE, 1); mbar_init(bars + B_STGFREE + 8, 1); mbar_init(bars + B_REQ, 1); mbar_init(bars + B_RSP, 1);
        asm volatile("fence.mbarrier_init.release.cluster;" ::: "memory");
    }
    __syncthreads();
    if (warp < 8) {
        asm volatile("setmaxnreg.inc.sync.aligned.u32 232;");
        consumer(p, sb, warp, lane);
    } else {
        asm volatile("setmaxnreg.dec.sync.aligned.u32 40;");
        if (warp == 8) { if (lane == 0) producer(p, sb); }
        else if (warp < 11) store_warp(p, sb, warp - 9, lane);
        else scheduler(p, sb, lane);
    }
}

typedef CUresult (*EncodeFn)(CUtensorMap*, CUtensorMapDataType, cuuint32_t, void*, const cuuint64_t*, const cuuint64_t*,
                             const cuuint32_t*, const cuuint32_t*, CUtensorMapInterleave, CUtensorMapSwizzle,
                             CUtensorMapL2promotion, CUtensorMapFloatOOBfill);

static void make_map(EncodeFn enc, CUtensorMap* m, const void* ptr, uint64_t rows, uint64_t cols, uint32_t box_rows) {
    cuuint64_t dims[2] = {cols, rows};
    cuuint64_t strides[1] = {cols * 2};
    cuuint32_t box[2] = {64, box_rows};
    cuuint32_t es[2] = {1, 1};
    enc(m, CU_TENSOR_MAP_DATA_TYPE_BFLOAT16, 2, const_cast<void*>(ptr), dims, strides, box, es, CU_TENSOR_MAP_INTERLEAVE_NONE,
        CU_TENSOR_MAP_SWIZZLE_128B, CU_TENSOR_MAP_L2_PROMOTION_L2_256B, CU_TENSOR_MAP_FLOAT_OOB_FILL_NONE);
}
template <typename T> static void* sym_addr(T& sym) { void* p = nullptr; cudaGetSymbolAddress(&p, sym); return p; }

extern "C" void kernel_launch(void* const* d_in, const int* in_sizes, int n_in, void* d_out, int out_size) {
    static Params prm;
    static RecParams rp;
    static bool ready = false;
    static const void* key[14];
    bool same = ready;
    for (int i = 0; i < 13 && same; i++) same = key[i] == d_in[i];
    same = same && key[13] == d_out;
    if (!same) {
        void* fn = nullptr;
        cudaDriverEntryPointQueryResult qr;
        cudaGetDriverEntryPoint("cuTensorMapEncodeTiled", &fn, cudaEnableDefault, &qr);
        EncodeFn enc = (EncodeFn)fn;
        make_map(enc, &prm.tm_h, sym_addr(g_h), S_, D_, 64);
        make_map(enc, &prm.tm_kv, sym_addr(g_kv), S_, 2 * HD_, 64);
        make_map(enc, &prm.tm_kvm, sym_addr(g_kvm), NSEG * 8, 2 * HD_, 32);
        make_map(enc, &prm.tm_o, sym_addr(g_o), S_, HD_, 64);
        make_map(enc, &prm.tm_op, sym_addr(g_op), OP_ROWS, D_, 64);
        make_map(enc, &prm.tm_h2, sym_addr(g_h2), S_, D_, 64);
        make_map(enc, &prm.tm_act, sym_addr(g_act), S_, DF_, 64);
        make_map(enc, &prm.tm_x1, sym_addr(g_x1), S_, D_, 64);
        make_map(enc, &prm.tm_out, d_out, S_, D_, 64);
        make_map(enc, &prm.tm_wq, d_in[2], D_, HD_, 64);
        make_map(enc, &prm.tm_wk, d_in[3], D_, HD_, 64);
        make_map(enc, &prm.tm_wv, d_in[4], D_, HD_, 64);
        make_map(enc, &prm.tm_wo, d_in[5], HD_, D_, 64);
        make_map(enc, &prm.tm_wg, d_in[8], D_, DF_, 64);
        make_map(enc, &prm.tm_wu, d_in[9], D_, DF_, 64);
        make_map(enc, &prm.tm_wd, d_in[10], DF_, D_, 64);
        prm.x = (const bf16*)d_in[0];
        rp.mem0 = (const bf16*)d_in[1];
        rp.wq = (const bf16*)d_in[2]; rp.wk = (const bf16*)d_in[3]; rp.wv = (const bf16*)d_in[4]; rp.wo = (const bf16*)d_in[5];
        cudaFuncSetAttribute(k_work, cudaFuncAttributeMaxDynamicSharedMemorySize, SMEM_BYTES);
        cudaFuncSetAttribute(k_rec, cudaFuncAttributeMaxDynamicSharedMemorySize, R_SMEM);
        cudaFuncSetAttribute(k_rec, cudaFuncAttributeNonPortableClusterSizeAllowed, 1);
        {
            cudaLaunchConfig_t cfg = {};
            cfg.gridDim = dim3(128); cfg.blockDim = dim3(384); cfg.dynamicSmemBytes = R_SMEM;
            cudaLaunchAttribute at[1];
            at[0].id = cudaLaunchAttributeClusterDimension; at[0].val.clusterDim.x = 16; at[0].val.clusterDim.y = 1; at[0].val.clusterDim.z = 1;
            cfg.attrs = at; cfg.numAttrs = 1;
            int n = 0;
            cudaOccupancyMaxActiveClusters(&n, k_rec, &cfg);
            rp.ncl = n < 4 ? 4 : (n > 8 ? 8 : n);
        }
        for (int i = 0; i < 13; i++) key[i] = d_in[i];
        key[13] = d_out;
        ready = true;
    }
    cudaStream_t st = cudaStreamPerThread;
    PrefetchList pf;
    pf.p[0] = (const bf16*)d_in[3]; pf.p[1] = (const bf16*)d_in[4]; pf.p[2] = (const bf16*)d_in[2]; pf.p[3] = (const bf16*)d_in[5]; pf.p[4] = nullptr;
    k_mod<<<96, 256, 0, st>>>((const bf16*)d_in[11], (const bf16*)d_in[12], pf);
    {
        cudaLaunchConfig_t cfg = {};
        cfg.gridDim = dim3(S_ / 8); cfg.blockDim = dim3(256); cfg.stream = st;
        cudaLaunchAttribute at[1];
        at[0].id = cudaLaunchAttributeProgrammaticStreamSerialization; at[0].val.programmaticStreamSerializationAllowed = 1;
        cfg.attrs = at; cfg.numAttrs = 1;
        cudaLaunchKernelEx(&cfg, k_ln1, (const bf16*)d_in[0]);
    }
    auto launch_rec = [&]() {
        cudaLaunchConfig_t cfg = {};
        cfg.gridDim = dim3(16 * rp.ncl); cfg.blockDim = dim3(384); cfg.dynamicSmemBytes = R_SMEM; cfg.stream = st;
        cudaLaunchAttribute at[1];
        at[0].id = cudaLaunchAttributeClusterDimension; at[0].val.clusterDim.x = 16; at[0].val.clusterDim.y = 1; at[0].val.clusterDim.z = 1;
        cfg.attrs = at; cfg.numAttrs = 1;
        cudaLaunchKernelEx(&cfg, k_rec, rp);
    };
    auto launch_work = [&](int qmask, int pdl) {
        prm.qmask = qmask;
        cudaLaunchConfig_t cfg = {};
        cfg.gridDim = dim3(132); cfg.blockDim = dim3(384); cfg.dynamicSmemBytes = SMEM_BYTES; cfg.stream = st;
        cudaLaunchAttribute at[1];
        at[0].id = cudaLaunchAttributeProgrammaticStreamSerialization; at[0].val.programmaticStreamSerializationAllowed = 1;
        cfg.attrs = at; cfg.numAttrs = pdl;
        cudaLaunchKernelEx(&cfg, k_work, prm);
    };
    launch_rec();
    launch_work(0x3f, 1);
}
```

```cpp
#include <cuda_runtime.h>
#include <cuda_bf16.h>
#include <cuda.h>
#include <stdint.h>

typedef __nv_bfloat16 bf16;

constexpr int S_ = 2048, D_ = 512, H_ = 32, DH_ = 128, HD_ = 4096, NSEG = 64, DF_ = 1792;
constexpr int NRB = 16;
constexpr int OSPLIT = 4;

__device__ __align__(1024) bf16 g_h[S_ * D_];
__device__ __align__(1024) bf16 g_kv[S_ * 2 * HD_];
__device__ __align__(1024) bf16 g_kvm[NSEG * 8 * 2 * HD_];
__device__ __align__(1024) bf16 g_o[S_ * HD_];
#define FINE_RB_ 14
constexpr int FINE_RB = FINE_RB_;
constexpr int OSPLIT2 = 16;
constexpr int OP_ROWS = OSPLIT * S_ + OSPLIT2 * (NRB - FINE_RB) * 128;
__device__ __align__(1024) bf16 g_op[OP_ROWS * D_];
__device__ __align__(1024) bf16 g_x1[S_ * D_];
__device__ __align__(1024) bf16 g_h2[S_ * D_];
__device__ __align__(1024) bf16 g_act[S_ * DF_];
__device__ __align__(1024) bf16 g_mod[6 * D_];
__device__ uint32_t g_Fraw[131072 + 65536 + 2048];
#define g_F ((uint32_t*)(((uint64_t)g_Fraw + 0x7FFFFull) & ~0x7FFFFull))
constexpr int F_KV = 0, F_MEM = 32, F_O = 64, F_OP = 96, F_H2 = 128, F_ACT = 160, F_CLAIM = 192  , F_SIDE = 384  , F_TOTAL = 448;
__device__ __align__(128) unsigned int g_flags[F_TOTAL];
#define TR(j, i) do {} while (0)

__device__ __forceinline__ uint32_t smem_u32(const void* p) { return (uint32_t)__cvta_generic_to_shared(p); }
__device__ __forceinline__ uint32_t clk32() { uint32_t c; asm volatile("mov.u32 %0, %%clock;" : "=r"(c)); return c; }
__device__ __forceinline__ uint32_t mapa_u32(uint32_t addr, uint32_t rank) {
    uint32_t r; asm volatile("mapa.shared::cluster.u32 %0, %1, %2;" : "=r"(r) : "r"(addr), "r"(rank)); return r;
}
__device__ __forceinline__ void mbar_init(uint32_t bar, uint32_t cnt) {
    asm volatile("mbarrier.init.shared::cta.b64 [%0], %1;" :: "r"(bar), "r"(cnt) : "memory");
}
__device__ __forceinline__ void mbar_inval(uint32_t bar) {
    asm volatile("mbarrier.inval.shared::cta.b64 [%0];" :: "r"(bar) : "memory");
}
__device__ __forceinline__ void mbar_expect_tx(uint32_t bar, uint32_t bytes) {
    asm volatile("mbarrier.arrive.expect_tx.shared::cta.b64 _, [%0], %1;" :: "r"(bar), "r"(bytes) : "memory");
}
__device__ __forceinline__ void mbar_arrive(uint32_t bar) {
    asm volatile("mbarrier.arrive.shared::cta.b64 _, [%0];" :: "r"(bar) : "memory");
}
__device__ __forceinline__ bool mbar_try_wait(uint32_t bar, uint32_t parity) {
    uint32_t ok;
    asm volatile("{\n.reg .pred p;\nmbarrier.try_wait.parity.shared::cta.b64 p, [%1], %2;\nselp.u32 %0, 1, 0, p;\n}"
                 : "=r"(ok) : "r"(bar), "r"(parity) : "memory");
    return ok;
}
__device__ __forceinline__ bool mbar_try_wait_cluster(uint32_t bar, uint32_t parity) {
    uint32_t ok;
    asm volatile("{\n.reg .pred p;\nmbarrier.try_wait.parity.acquire.cluster.shared::cta.b64 p, [%1], %2;\nselp.u32 %0, 1, 0, p;\n}"
                 : "=r"(ok) : "r"(bar), "r"(parity) : "memory");
    return ok;
}
constexpr int SPIN_LIMIT = 1 << 18;
#define TIMEOUT(code, info) do {} while (0)
__device__ __forceinline__ void mbar_wait(uint32_t bar, uint32_t parity) {
    int g = 0;
#pragma unroll 1
    while (!mbar_try_wait(bar, parity)) { if (++g >= SPIN_LIMIT) { TIMEOUT(0, bar & 255); break; } }
}
__device__ __forceinline__ void mbar_wait_cluster(uint32_t bar, uint32_t parity) {
    int g = 0;
#pragma unroll 1
    while (!mbar_try_wait_cluster(bar, parity)) { if (++g >= SPIN_LIMIT) { TIMEOUT(1, bar & 255); break; } }
}
__device__ __forceinline__ void bar_sync(int id, int n) { asm volatile("bar.sync %0, %1;" :: "r"(id), "r"(n) : "memory"); }
__device__ __forceinline__ void bar_arrive(int id, int n) { asm volatile("bar.arrive %0, %1;" :: "r"(id), "r"(n) : "memory"); }
__device__ __forceinline__ void cluster_sync_all() {
    asm volatile("barrier.cluster.arrive.aligned;\nbarrier.cluster.wait.aligned;" ::: "memory");
}
__device__ __forceinline__ void st_async_v2(uint32_t addr, float a, float b, uint32_t bar) {
    asm volatile("st.async.weak.shared::cluster.mbarrier::complete_tx::bytes.v2.f32 [%0], {%1,%2}, [%3];"
                 :: "r"(addr), "f"(a), "f"(b), "r"(bar) : "memory");
}
__device__ __forceinline__ void st_async_v4(uint32_t addr, uint4 v, uint32_t bar) {
    asm volatile("st.async.weak.shared::cluster.mbarrier::complete_tx::bytes.v4.b32 [%0], {%1,%2,%3,%4}, [%5];"
                 :: "r"(addr), "r"(v.x), "r"(v.y), "r"(v.z), "r"(v.w), "r"(bar) : "memory");
}
__device__ __forceinline__ uint2 ldg_relaxed2(const uint2* p) {
    uint2 v;
    asm volatile("ld.relaxed.gpu.global.v2.b32 {%0,%1}, [%2];" : "=r"(v.x), "=r"(v.y) : "l"(p) : "memory");
    return v;
}
__device__ __forceinline__ void stg_relaxed2(uint2* p, uint2 v) {
    asm volatile("st.relaxed.gpu.global.v2.b32 [%0], {%1,%2};" :: "l"(p), "r"(v.x), "r"(v.y) : "memory");
}
__device__ __forceinline__ uint4 ldg_relaxed(const uint4* p) {
    uint4 v;
    asm volatile("ld.relaxed.gpu.global.v4.b32 {%0,%1,%2,%3}, [%4];" : "=r"(v.x), "=r"(v.y), "=r"(v.z), "=r"(v.w) : "l"(p) : "memory");
    return v;
}
__device__ __forceinline__ void stg_relaxed(uint4* p, uint4 v) {
    asm volatile("st.relaxed.gpu.global.v4.b32 [%0], {%1,%2,%3,%4};" :: "l"(p), "r"(v.x), "r"(v.y), "r"(v.z), "r"(v.w) : "memory");
}
__device__ __forceinline__ void stg_relaxed32(uint32_t* p, uint32_t v) {
    asm volatile("st.relaxed.gpu.global.b32 [%0], %1;" :: "l"(p), "r"(v) : "memory");
}
__device__ __forceinline__ uint32_t ldg_relaxed32(const uint32_t* p) {
    uint32_t v; asm volatile("ld.relaxed.gpu.global.b32 %0, [%1];" : "=r"(v) : "l"(p) : "memory"); return v;
}
__device__ __forceinline__ unsigned int ld_acquire(const unsigned int* p) {
    unsigned int v; asm volatile("ld.acquire.gpu.global.u32 %0, [%1];" : "=r"(v) : "l"(p) : "memory"); return v;
}
__device__ __forceinline__ void red_release(unsigned int* p, unsigned int v) {
    asm volatile("red.release.gpu.global.add.u32 [%0], %1;" :: "l"(p), "r"(v) : "memory");
}
__device__ __forceinline__ void wait_flag(int idx, unsigned int target) {
    const unsigned int* p = &g_flags[idx];
    int g = 0;
#pragma unroll 1
    while (ld_acquire(p) < target) { __nanosleep(20); if (++g >= 64 * SPIN_LIMIT) { TIMEOUT(2, idx); break; } }
}
__device__ __forceinline__ void cp_async16(uint32_t dst, const void* src) {
    asm volatile("cp.async.cg.shared.global [%0], [%1], 16;" :: "r"(dst), "l"(src) : "memory");
}
__device__ __forceinline__ void cp_async_commit() { asm volatile("cp.async.commit_group;" ::: "memory"); }
template <int N> __device__ __forceinline__ void cp_async_wait() { asm volatile("cp.async.wait_group %0;" :: "n"(N) : "memory"); }
__device__ __forceinline__ void ldsm4(uint32_t& r0, uint32_t& r1, uint32_t& r2, uint32_t& r3, uint32_t addr) {
    asm volatile("ldmatrix.sync.aligned.m8n8.x4.shared.b16 {%0,%1,%2,%3}, [%4];" : "=r"(r0), "=r"(r1), "=r"(r2), "=r"(r3) : "r"(addr) : "memory");
}
__device__ __forceinline__ void ldsm4t(uint32_t& r0, uint32_t& r1, uint32_t& r2, uint32_t& r3, uint32_t addr) {
    asm volatile("ldmatrix.sync.aligned.m8n8.x4.trans.shared.b16 {%0,%1,%2,%3}, [%4];" : "=r"(r0), "=r"(r1), "=r"(r2), "=r"(r3) : "r"(addr) : "memory");
}
__device__ __forceinline__ void ldsm2t(uint32_t& r0, uint32_t& r1, uint32_t addr) {
    asm volatile("ldmatrix.sync.aligned.m8n8.x2.trans.shared.b16 {%0,%1}, [%2];" : "=r"(r0), "=r"(r1) : "r"(addr) : "memory");
}
__device__ __forceinline__ void stsm4(uint32_t addr, uint32_t r0, uint32_t r1, uint32_t r2, uint32_t r3) {
    asm volatile("stmatrix.sync.aligned.m8n8.x4.shared.b16 [%0], {%1,%2,%3,%4};" :: "r"(addr), "r"(r0), "r"(r1), "r"(r2), "r"(r3) : "memory");
}
__device__ __forceinline__ void stsm2t(uint32_t addr, uint32_t r0, uint32_t r1) {
    asm volatile("stmatrix.sync.aligned.m8n8.x2.trans.shared.b16 [%0], {%1,%2};" :: "r"(addr), "r"(r0), "r"(r1) : "memory");
}
__device__ __forceinline__ void mma16816(float* d, uint32_t a0, uint32_t a1, uint32_t a2, uint32_t a3, uint32_t b0, uint32_t b1) {
    asm volatile("mma.sync.aligned.m16n8k16.row.col.f32.bf16.bf16.f32 {%0,%1,%2,%3}, {%4,%5,%6,%7}, {%8,%9}, {%0,%1,%2,%3};"
                 : "+f"(d[0]), "+f"(d[1]), "+f"(d[2]), "+f"(d[3]) : "r"(a0), "r"(a1), "r"(a2), "r"(a3), "r"(b0), "r"(b1));
}
__device__ __forceinline__ void mma1688(float* d, uint32_t a0, uint32_t a1, uint32_t b0) {
    asm volatile("mma.sync.aligned.m16n8k8.row.col.f32.bf16.bf16.f32 {%0,%1,%2,%3}, {%4,%5}, {%6}, {%0,%1,%2,%3};"
                 : "+f"(d[0]), "+f"(d[1]), "+f"(d[2]), "+f"(d[3]) : "r"(a0), "r"(a1), "r"(b0));
}
__device__ __forceinline__ void mma16816h(float* d, uint32_t a0, uint32_t a2, uint32_t b0, uint32_t b1) {
    asm volatile("{\n.reg .b32 ju, jv;\nmma.sync.aligned.m16n8k16.row.col.f32.bf16.bf16.f32 {%0,%1,%2,%3}, {%4,ju,%5,jv}, {%6,%7}, {%0,%1,%2,%3};\n}"
                 : "+f"(d[0]), "+f"(d[1]), "+f"(d[2]), "+f"(d[3]) : "r"(a0), "r"(a2), "r"(b0), "r"(b1));
}
__device__ __forceinline__ void mma1688h(float* d, uint32_t a0, uint32_t b0) {
    asm volatile("{\n.reg .b32 ju;\nmma.sync.aligned.m16n8k8.row.col.f32.bf16.bf16.f32 {%0,%1,%2,%3}, {%4,ju}, {%5}, {%0,%1,%2,%3};\n}"
                 : "+f"(d[0]), "+f"(d[1]), "+f"(d[2]), "+f"(d[3]) : "r"(a0), "r"(b0));
}
__device__ __forceinline__ uint32_t pack2(float lo, float hi) {
    uint32_t r; asm("cvt.rn.bf16x2.f32 %0, %1, %2;" : "=r"(r) : "f"(hi), "f"(lo)); return r;
}
__device__ __forceinline__ float bflo(uint32_t w) { return __uint_as_float(w << 16); }
__device__ __forceinline__ float bfhi(uint32_t w) { return __uint_as_float(w & 0xffff0000u); }
__device__ __forceinline__ float rbf(float x) { return __bfloat162float(__float2bfloat16_rn(x)); }
__device__ __forceinline__ float ex2(float x) { float y; asm("ex2.approx.ftz.f32 %0, %1;" : "=f"(y) : "f"(x)); return y; }
__device__ __forceinline__ void sts128(uint32_t addr, uint4 v) {
    asm volatile("st.shared.v4.b32 [%0], {%1,%2,%3,%4};" :: "r"(addr), "r"(v.x), "r"(v.y), "r"(v.z), "r"(v.w) : "memory");
}
__device__ __forceinline__ uint4 lds128(uint32_t addr) {
    uint4 v; asm volatile("ld.shared.v4.b32 {%0,%1,%2,%3}, [%4];" : "=r"(v.x), "=r"(v.y), "=r"(v.z), "=r"(v.w) : "r"(addr) : "memory"); return v;
}
__device__ __forceinline__ float2 lds64f(uint32_t addr) {
    float2 v; asm volatile("ld.shared.v2.f32 {%0,%1}, [%2];" : "=f"(v.x), "=f"(v.y) : "r"(addr) : "memory"); return v;
}
__device__ __forceinline__ float lds32f(uint32_t addr) {
    float v; asm volatile("ld.shared.f32 %0, [%1];" : "=f"(v) : "r"(addr) : "memory"); return v;
}
__device__ __forceinline__ uint32_t lds32(uint32_t addr) {
    uint32_t v; asm volatile("ld.shared.b32 %0, [%1];" : "=r"(v) : "r"(addr) : "memory"); return v;
}
__device__ __forceinline__ void sts32(uint32_t addr, uint32_t v) { asm volatile("st.shared.b32 [%0], %1;" :: "r"(addr), "r"(v) : "memory"); }
__device__ __forceinline__ void sts64f(uint32_t addr, float a, float b) { asm volatile("st.shared.v2.f32 [%0], {%1,%2};" :: "r"(addr), "f"(a), "f"(b) : "memory"); }

__device__ __forceinline__ void tma_load2d(uint32_t dst, const CUtensorMap* tm, int c0, int c1, uint32_t bar) {
    asm volatile("cp.async.bulk.tensor.2d.shared::cluster.global.mbarrier::complete_tx::bytes [%0], [%1, {%3, %4}], [%2];"
                 :: "r"(dst), "l"(tm), "r"(bar), "r"(c0), "r"(c1) : "memory");
}
__device__ __forceinline__ void tma_store2d(const CUtensorMap* tm, uint32_t src, int c0, int c1) {
    asm volatile("cp.async.bulk.tensor.2d.global.shared::cta.bulk_group [%0, {%2, %3}], [%1];"
                 :: "l"(tm), "r"(src), "r"(c0), "r"(c1) : "memory");
}
__device__ __forceinline__ void bulk_commit() { asm volatile("cp.async.bulk.commit_group;" ::: "memory"); }
__device__ __forceinline__ void bulk_wait0() { asm volatile("cp.async.bulk.wait_group 0;" ::: "memory"); }
__device__ __forceinline__ void fence_async_smem() { asm volatile("fence.proxy.async.shared::cta;" ::: "memory"); }
__device__ __forceinline__ void fence_async_all() { asm volatile("fence.proxy.async;" ::: "memory"); }

__device__ __forceinline__ void wg_fence() { asm volatile("wgmma.fence.sync.aligned;" ::: "memory"); }
__device__ __forceinline__ void wg_commit() { asm volatile("wgmma.commit_group.sync.aligned;" ::: "memory"); }
__device__ __forceinline__ void wg_wait0() { asm volatile("wgmma.wait_group.sync.aligned 0;" ::: "memory"); }
__device__ __forceinline__ uint64_t mkdesc(uint32_t saddr, uint32_t lbo, uint32_t sbo) {
    return (uint64_t)((saddr & 0x3FFFF) >> 4) | ((uint64_t)(lbo >> 4) << 16) | ((uint64_t)(sbo >> 4) << 32) | (1ull << 62);
}
#define ACC8(i) "+f"(d[i]), "+f"(d[i + 1]), "+f"(d[i + 2]), "+f"(d[i + 3]), "+f"(d[i + 4]), "+f"(d[i + 5]), "+f"(d[i + 6]), "+f"(d[i + 7])
__device__ __forceinline__ void wgmma_n256(float* d, uint64_t da, uint64_t db, int scale_d) {
    asm volatile(
        "{\n.reg .pred p;\nsetp.ne.b32 p, %130, 0;\n"
        "wgmma.mma_async.sync.aligned.m64n256k16.f32.bf16.bf16 "
        "{%0,%1,%2,%3,%4,%5,%6,%7,%8,%9,%10,%11,%12,%13,%14,%15,%16,%17,%18,%19,%20,%21,%22,%23,%24,%25,%26,%27,%28,%29,%30,%31,"
        "%32,%33,%34,%35,%36,%37,%38,%39,%40,%41,%42,%43,%44,%45,%46,%47,%48,%49,%50,%51,%52,%53,%54,%55,%56,%57,%58,%59,%60,%61,%62,%63,"
        "%64,%65,%66,%67,%68,%69,%70,%71,%72,%73,%74,%75,%76,%77,%78,%79,%80,%81,%82,%83,%84,%85,%86,%87,%88,%89,%90,%91,%92,%93,%94,%95,"
        "%96,%97,%98,%99,%100,%101,%102,%103,%104,%105,%106,%107,%108,%109,%110,%111,%112,%113,%114,%115,%116,%117,%118,%119,%120,%121,%122,%123,%124,%125,%126,%127}, "
        "%128, %129, p, 1, 1, 0, 1;\n}"
        : ACC8(0), ACC8(8), ACC8(16), ACC8(24), ACC8(32), ACC8(40), ACC8(48), ACC8(56),
          ACC8(64), ACC8(72), ACC8(80), ACC8(88), ACC8(96), ACC8(104), ACC8(112), ACC8(120)
        : "l"(da), "l"(db), "r"(scale_d));
}
__device__ __forceinline__ void wgmma_n128(float* d, uint64_t da, uint64_t db, int scale_d) {
    asm volatile(
        "{\n.reg .pred p;\nsetp.ne.b32 p, %66, 0;\n"
        "wgmma.mma_async.sync.aligned.m64n128k16.f32.bf16.bf16 "
        "{%0,%1,%2,%3,%4,%5,%6,%7,%8,%9,%10,%11,%12,%13,%14,%15,%16,%17,%18,%19,%20,%21,%22,%23,%24,%25,%26,%27,%28,%29,%30,%31,"
        "%32,%33,%34,%35,%36,%37,%38,%39,%40,%41,%42,%43,%44,%45,%46,%47,%48,%49,%50,%51,%52,%53,%54,%55,%56,%57,%58,%59,%60,%61,%62,%63}, "
        "%64, %65, p, 1, 1, 0, 1;\n}"
        : ACC8(0), ACC8(8), ACC8(16), ACC8(24), ACC8(32), ACC8(40), ACC8(48), ACC8(56)
        : "l"(da), "l"(db), "r"(scale_d));
}

__device__ __forceinline__ void wgmma_n64(float* d, uint64_t da, uint64_t db) {
    asm volatile(
        "wgmma.mma_async.sync.aligned.m64n64k16.f32.bf16.bf16 "
        "{%0,%1,%2,%3,%4,%5,%6,%7,%8,%9,%10,%11,%12,%13,%14,%15,%16,%17,%18,%19,%20,%21,%22,%23,%24,%25,%26,%27,%28,%29,%30,%31}, "
        "%32, %33, 1, 1, 1, 0, 1;"
        : ACC8(0), ACC8(8), ACC8(16), ACC8(24)
        : "l"(da), "l"(db));
}
__device__ __forceinline__ void wgmma_n8_ta(float* d, uint64_t da, uint64_t db, int scale_d) {
    asm volatile(
        "{\n.reg .pred p;\nsetp.ne.b32 p, %6, 0;\n"
        "wgmma.mma_async.sync.aligned.m64n8k16.f32.bf16.bf16 {%0,%1,%2,%3}, %4, %5, p, 1, 1, 1, 0;\n}"
        : "+f"(d[0]), "+f"(d[1]), "+f"(d[2]), "+f"(d[3]) : "l"(da), "l"(db), "r"(scale_d));
}

struct PrefetchList { const bf16* p[5]; };
__global__ void __launch_bounds__(256) k_mod(const bf16* __restrict__ c, const bf16* __restrict__ w_mod, const PrefetchList pf) {
    asm volatile("griddepcontrol.launch_dependents;");
    __shared__ float s_c[D_];
    __shared__ float s_red[64][33];
    const int tid = threadIdx.x;
    const int cq = tid & 3, rg = tid >> 2;
    uint4 w[8];
#pragma unroll
    for (int i = 0; i < 8; i++)
        w[i] = __ldg((const uint4*)(w_mod + (size_t)(rg * 8 + i) * (6 * D_) + blockIdx.x * 32 + cq * 8));
    for (int i = tid; i < D_; i += 256) {
        float v = __bfloat162float(c[i]);
        s_c[i] = rbf(v / (1.f + __expf(-v)));
    }
    {
        const int gt = blockIdx.x * 256 + tid, nt = gridDim.x * 256;
        for (int i = gt; i < F_TOTAL; i += nt) g_flags[i] = 0;
        for (int i = gt; i < 65536 + 2048; i += nt) g_F[i] = 0;
        if (tid < 11) {
            const int i = tid * gridDim.x + blockIdx.x;
            if (i < 1024) asm volatile("cp.async.bulk.prefetch.L2.global [%0], %1;" :: "l"(pf.p[i >> 8] + (size_t)(i & 255) * 8192), "r"(16384) : "memory");
        }
    }
    __syncthreads();
    float a[8];
#pragma unroll
    for (int j = 0; j < 8; j++) a[j] = 0.f;
#pragma unroll
    for (int i = 0; i < 8; i++) {
        float cv = s_c[rg * 8 + i];
        a[0] += cv * bflo(w[i].x); a[1] += cv * bfhi(w[i].x); a[2] += cv * bflo(w[i].y); a[3] += cv * bfhi(w[i].y);
        a[4] += cv * bflo(w[i].z); a[5] += cv * bfhi(w[i].z); a[6] += cv * bflo(w[i].w); a[7] += cv * bfhi(w[i].w);
    }
#pragma unroll
    for (int j = 0; j < 8; j++) s_red[rg][cq * 8 + j] = a[j];
    __syncthreads();
    if (tid < 32) {
        float s = 0.f;
#pragma unroll 8
        for (int r = 0; r < 64; r++) s += s_red[r][tid];
        g_mod[blockIdx.x * 32 + tid] = __float2bfloat16_rn(s);
    }
}

__device__ __forceinline__ uint32_t hadd2(uint32_t a, uint32_t b) { uint32_t r; asm("add.rn.bf16x2 %0, %1, %2;" : "=r"(r) : "r"(a), "r"(b)); return r; }
__device__ __forceinline__ uint32_t hsub2(uint32_t a, uint32_t b) { uint32_t r; asm("sub.rn.bf16x2 %0, %1, %2;" : "=r"(r) : "r"(a), "r"(b)); return r; }
__device__ __forceinline__ uint32_t hmul2(uint32_t a, uint32_t b) { uint32_t r; asm("mul.rn.bf16x2 %0, %1, %2;" : "=r"(r) : "r"(a), "r"(b)); return r; }
__device__ __forceinline__ void load_mod8(const bf16* m, int lane, uint32_t* v) {
    const uint4 a = __ldcg((const uint4*)m + lane), b = __ldcg((const uint4*)m + 32 + lane);
    v[0] = a.x; v[1] = a.y; v[2] = a.z; v[3] = a.w; v[4] = b.x; v[5] = b.y; v[6] = b.z; v[7] = b.w;
}
__device__ __forceinline__ void ln_stats(const uint32_t* x, uint32_t& mu2, float& rden) {
    float s = 0.f;
#pragma unroll
    for (int i = 0; i < 8; i++) s += bflo(x[i]) + bfhi(x[i]);
#pragma unroll
    for (int o = 16; o > 0; o >>= 1) s += __shfl_xor_sync(~0u, s, o);
    const float mean = s * (1.f / D_);
    float q = 0.f;
#pragma unroll
    for (int i = 0; i < 8; i++) { const float d0 = bflo(x[i]) - mean, d1 = bfhi(x[i]) - mean; q = fmaf(d0, d0, q); q = fmaf(d1, d1, q); }
#pragma unroll
    for (int o = 16; o > 0; o >>= 1) q += __shfl_xor_sync(~0u, q, o);
    mu2 = pack2(mean, mean);
    rden = __frcp_rn(rbf(__fsqrt_rn(rbf(rbf(q * (1.f / D_)) + 1e-5f))));
}
__device__ __forceinline__ void ln_apply(const uint32_t* x, uint32_t mu2, float rden, const uint32_t* c1, const uint32_t* sm, uint32_t* r) {
#pragma unroll
    for (int i = 0; i < 8; i++) {
        const uint32_t d = hsub2(x[i], mu2);
        r[i] = hadd2(hmul2(pack2(bflo(d) * rden, bfhi(d) * rden), c1[i]), sm[i]);
    }
}

__global__ void __launch_bounds__(256) k_ln1(const bf16* __restrict__ x) {
    const int lane = threadIdx.x & 31, row = blockIdx.x * 8 + (threadIdx.x >> 5);
    const uint4* xr = (const uint4*)(x + (size_t)row * D_);
    const uint4 a = __ldg(xr + lane), b = __ldg(xr + 32 + lane);
    const uint32_t v[8] = {a.x, a.y, a.z, a.w, b.x, b.y, b.z, b.w};
    uint32_t mu2; float rden;
    ln_stats(v, mu2, rden);
    asm volatile("griddepcontrol.wait;" ::: "memory");
    uint32_t c1[8], sm[8], r[8];
    load_mod8(g_mod + D_, lane, c1);
    load_mod8(g_mod, lane, sm);
#pragma unroll
    for (int i = 0; i < 8; i++) c1[i] = hadd2(c1[i], 0x3F803F80u);
    ln_apply(v, mu2, rden, c1, sm, r);
    uint4* hr = (uint4*)(g_h + (size_t)row * D_);
    hr[lane] = make_uint4(r[0], r[1], r[2], r[3]); hr[32 + lane] = make_uint4(r[4], r[5], r[6], r[7]);
}

struct __align__(64) Params {
    CUtensorMap tm_h, tm_kv, tm_kvm, tm_o, tm_op, tm_h2, tm_act, tm_x1, tm_out;
    CUtensorMap tm_wq, tm_wk, tm_wv, tm_wo, tm_wg, tm_wu, tm_wd;
    const bf16* x;
    int qmask;
};

constexpr int R_NST = 3;
constexpr uint32_t R_WV = 0, R_MEM = 65536, R_KX = 73728, R_VX = R_KX + R_NST * 4096, R_QS = R_VX + R_NST * 4096,
                   R_KMS = R_QS + 1024, R_VMS = R_KMS + 1024, R_OS = R_VMS + 1024, R_SX = R_OS + 1024, R_BAR = R_SX + 2560,
                   R_RS = 105472  , R_VP = R_RS + 8192  ,
                   R_STG = R_VP + 8192  , R_SMEM = R_STG + 98304;
static_assert(R_BAR + 64 <= R_RS, "smem");
constexpr uint32_t RB_SX = R_BAR, RB_V = R_BAR + 8, RB_E = R_BAR + 16, RB_A = R_BAR + 24, RB_ROLE = R_BAR + 32, RB_A1 = R_BAR + 40;
constexpr int W_NST = 3;
constexpr uint32_t W_STAGE = 49152, W_STG = W_NST * W_STAGE, W_END = W_STG + 65536;
constexpr uint32_t SM_BAR = W_END;
constexpr uint32_t SMEM_BYTES = W_END + 1024;
constexpr uint32_t B_FULL = 0, B_EMPTY = 32, B_STGFREE = 64, B_REQ = 80, B_RSP = 88, B_NEXT = 96, B_RING = 128;
#define PICK_AHEAD 2

constexpr int NB_X = 11  , NB_Y = 1, NB_Z = 5, NB_B = 2, NB_C = 3, NB_D = 4, NB_W0 = 6  , NB_ST = 9  ;

__device__ __forceinline__ int pos_of_d(int d) {
    const int rem = d & 31;
    return (d & ~31) + ((rem & 7) >> 1) * 8 + (rem & 1) * 4 + (rem >> 3);
}

#define PROF(i) do {} while (0)
#define PROFG(i) do {} while (0)
#define OPAQUE(x) asm volatile("" : "+r"(x))
#define FENCE_SCHED(x) do { if ((x) == 0u) asm volatile("trap;"); } while (0)
#define VK0_ 4
constexpr int VK0 = VK0_;
constexpr int NOFF = 8;
#define VDELAY -1
#define POLL_GAP 90

struct RecParams { const bf16 *mem0, *wq, *wk, *wv, *wo; int ncl; };

__device__ __forceinline__ void rec_qk(const RecParams& p, const uint32_t sb, const int cta, const int warp, int lane, const int sel) {
    const int crank = cta & 15, cl = cta >> 4, rank = cta & 1;
    const int kh = warp >> 2, aa = warp & 3;
    uint32_t wa[2][16][4];
    const uint32_t stg = sb + R_STG + kh * 32768;
    {
        const int t128 = aa * 32 + lane;
        const int row = (lane >> 4) * 8 + (lane & 7);
        const int ch = t128 & 7;
        const size_t goff = (size_t)kh * 256 * HD_ + cta * 64 + ch * 8;
#pragma unroll 4
        for (int dd = 0; dd < 16; dd++) {
            const int d = dd * 16 + (t128 >> 3), pp = pos_of_d(d);
            cp_async16(sb + R_WV + kh * 32768 + pp * 128 + ((ch ^ (pp & 7)) << 4), p.wv + goff + (size_t)d * HD_);
        }
        cp_async_commit();
#pragma unroll 4
        for (int dd = 0; dd < 16; dd++) {
            const int d = dd * 16 + (t128 >> 3), pp = pos_of_d(d);
            cp_async16(stg + pp * 128 + ((ch ^ (pp & 7)) << 4), p.wq + goff + (size_t)d * HD_);
        }
        cp_async_commit();
        {
            const int i0 = (warp * 32 + lane) * 16, tok = i0 >> 9;
            const uint4 m0 = __ldg((const uint4*)(p.mem0 + i0)), m1 = __ldg((const uint4*)(p.mem0 + i0 + 8));
            const uint32_t mw[8] = {m0.x, m0.y, m0.z, m0.w, m1.x, m1.y, m1.z, m1.w};
#pragma unroll
            for (int e = 0; e < 16; e++) {
                const int pp = pos_of_d((i0 & 511) + e);
                const unsigned short v = (unsigned short)(mw[e >> 1] >> ((e & 1) * 16));
                asm volatile("st.shared.u16 [%0], %1;" :: "r"(sb + R_MEM + (pp >> 3) * 128 + tok * 16 + (pp & 7) * 2), "h"(v) : "memory");
            }
        }
        cp_async_wait<1>();
        bar_sync(NB_W0 + kh, 128);
        const uint32_t fv = row * 128 + (((2 * aa + ((lane >> 3) & 1)) ^ (row & 7)) << 4);
#pragma unroll
        for (int ks = 0; ks < 16; ks++) ldsm4t(wa[0][ks][0], wa[0][ks][1], wa[0][ks][2], wa[0][ks][3], sb + R_WV + kh * 32768 + fv + ks * 2048);
        bar_sync(NB_W0 + kh, 128);
#pragma unroll
        for (int ks = 0; ks < 16; ks++)
            sts128(sb + R_WV + kh * 32768 + (aa * 16 + ks) * 512 + lane * 16, make_uint4(wa[0][ks][0], wa[0][ks][1], wa[0][ks][2], wa[0][ks][3]));
        const uint32_t fo = stg + row * 128 + (((4 * (aa & 1) + ((lane >> 3) & 1)) ^ (row & 7)) << 4);
#pragma unroll 1
        for (int m = 0; m < 2; m++) {
            cp_async_wait<0>();
            bar_sync(NB_W0 + kh, 128);
            if ((aa >> 1) == m) {
#pragma unroll
                for (int ks = 0; ks < 16; ks++) {
                    ldsm4t(wa[0][ks][0], wa[0][ks][1], wa[0][ks][2], wa[0][ks][3], fo + ks * 2048);
                    ldsm4t(wa[1][ks][0], wa[1][ks][1], wa[1][ks][2], wa[1][ks][3], (fo ^ 32) + ks * 2048);
                }
            }
            bar_sync(NB_W0 + kh, 128);
            if (m == 0) {
#pragma unroll 4
                for (int dd = 0; dd < 16; dd++) {
                    const int d = dd * 16 + (t128 >> 3), pp = pos_of_d(d);
                    cp_async16(stg + pp * 128 + ((ch ^ (pp & 7)) << 4), p.wk + goff + (size_t)d * HD_);
                }
                cp_async_commit();
            }
        }
    }
    const uint32_t tab = stg + (aa * 32 + lane) * 16;
    {
        const uint32_t l7 = lane & 7, l8 = lane >> 3, g = lane >> 2, t = lane & 3;
        const uint32_t t0 = l7 * 128 + ((l8 ^ l7) << 4);
        const uint32_t tq = l7 * 128 + (((l8 >> 1) ^ l7) << 4);
        const uint32_t bq = warp >> 1, tp = warp & 1;
        uint4 v;
        v.x = sb + (aa < 2 ? R_QS : R_KMS) + l7 * 128 + (((4 * (aa & 1) + 2 * kh + (l8 & 1)) ^ l7) << 4);
        v.y = sb + R_QS + tq;
        v.z = sb + (warp == 0 ? R_KMS : R_KX + (warp - 1) * 1024) + t0;
        v.w = mapa_u32(sb + R_SX + (rank * 5 + warp) * 256 + lane * 8, crank ^ 1);
        sts128(tab, v);
        sts128(tab + 2048, make_uint4(sb + lane * 16 + R_MEM + kh * 4096, sb + lane * 16 + R_WV + warp * 8192,
                                      sb + lane * 16 + R_VP + warp * 512, sb + lane * 16 + R_VP + 4096 + (warp ^ 4) * 512));
        const uint32_t src = (l8 >> 1) * 8 + l7;
        const uint32_t L = bq * 8 + 2 * tp + (l8 & 1);
        const uint32_t d0 = (crank + ((t >> 1) | (g & 6))) & 15;
        v.x = sb + R_RS + src * 512 + ((L ^ (src & 7)) << 4);
        v.y = mapa_u32(sb + R_MEM + (crank * 4 + bq) * 128 + (4 * tp + 2 * (t & 1) + (g & 1)) * 16, d0);
        v.z = mapa_u32(sb + ((crank & 2) ? RB_A1 : RB_A), d0);
        v.w = lane;
        sts128(tab + 4096, v);
        const uint64_t wr = (uint64_t)(g_F + ((crank * 2 + ((crank ^ (crank >> 3) ^ sel) & 1)) * 1024 + warp * 128 + cl * 32 + lane));
        sts128(tab + 6144, make_uint4((uint32_t)wr, (uint32_t)(wr >> 32), (uint32_t)((((cl + 1) & 3) - cl) * 128), (uint32_t)((((cl + 2) & 3) - cl) * 128)));
        sts32(tab + 8192, (uint32_t)((((cl + 3) & 3) - cl) * 128));
#pragma unroll
        for (int i = 0; i < NOFF; i++)
            sts128(tab + 10240 + i * 2048, make_uint4(wa[i & 1][i >> 1][0], wa[i & 1][i >> 1][1], wa[i & 1][i >> 1][2], wa[i & 1][i >> 1][3]));
    }
    bar_sync(NB_D, 384);
    uint32_t slot_off = 0;
    const uint32_t slot_inc = warp == 0 ? 0 : 4096;
    const uint32_t sx_bar_rem = (sb + RB_SX) ^ (1u << 24);
    uint4 tb = lds128(tab + 2048);
#pragma unroll 1
    for (int s = 0; s < NSEG; s++) {
        if (s > 0) mbar_wait(sb + RB_A, (s - 1) & 1);
        if (warp == 0) { PROF(0); PROFG(13); }
        uint4 ta;
        {
            float acc[5][4];
#pragma unroll
            for (int c = 0; c < 5; c++) { acc[c][0] = acc[c][1] = acc[c][2] = acc[c][3] = 0.f; }
            uint32_t b[8][4];
            uint4 av[16];
            static_assert(VK0 == 4, "order below assumes the V/O warps cover slices 0,1");
            ldsm4(b[0][0], b[0][1], b[0][2], b[0][3], tb.x);
            ldsm4(b[1][0], b[1][1], b[1][2], b[1][3], tb.x + 512);
            ldsm4(b[4][0], b[4][1], b[4][2], b[4][3], tb.x + 2048);
            ldsm4(b[5][0], b[5][1], b[5][2], b[5][3], tb.x + 2560);
#pragma unroll
            for (int kk = 0; kk < 8; kk++) {
                const int k2 = kk < 2 ? kk : (kk < 4 ? kk + 2 : (kk < 6 ? kk - 2 : kk));
                if (kk == 4) {
                    if (s > 0) mbar_wait(sb + RB_A1, (s - 1) & 1);
                    ldsm4(b[2][0], b[2][1], b[2][2], b[2][3], tb.x + 1024);
                    ldsm4(b[3][0], b[3][1], b[3][2], b[3][3], tb.x + 1536);
                    ldsm4(b[6][0], b[6][1], b[6][2], b[6][3], tb.x + 3072);
                    ldsm4(b[7][0], b[7][1], b[7][2], b[7][3], tb.x + 3584);
#pragma unroll
                    for (int i = 12; i < 16; i++) av[i] = lds128(tb.y + i * 512);
                    ta = lds128(tab);
                }
                mma16816(acc[0], wa[0][2 * k2][0], wa[0][2 * k2][1], wa[0][2 * k2][2], wa[0][2 * k2][3], b[k2][0], b[k2][1]);
                mma16816(acc[1], wa[1][2 * k2][0], wa[1][2 * k2][1], wa[1][2 * k2][2], wa[1][2 * k2][3], b[k2][0], b[k2][1]);
                mma16816(acc[3], wa[0][2 * k2 + 1][0], wa[0][2 * k2 + 1][1], wa[0][2 * k2 + 1][2], wa[0][2 * k2 + 1][3], b[k2][2], b[k2][3]);
                mma16816(acc[4], wa[1][2 * k2 + 1][0], wa[1][2 * k2 + 1][1], wa[1][2 * k2 + 1][2], wa[1][2 * k2 + 1][3], b[k2][2], b[k2][3]);
                if (2 * k2 >= VK0) {
                    mma16816(acc[2], av[2 * k2].x, av[2 * k2].y, av[2 * k2].z, av[2 * k2].w, b[k2][0], b[k2][1]);
                    mma16816(acc[2], av[2 * k2 + 1].x, av[2 * k2 + 1].y, av[2 * k2 + 1].z, av[2 * k2 + 1].w, b[k2][2], b[k2][3]);
                }
                if (kk == 0) { av[8] = lds128(tb.y + 8 * 512); av[9] = lds128(tb.y + 9 * 512); }
                if (kk == 1) { av[10] = lds128(tb.y + 10 * 512); av[11] = lds128(tb.y + 11 * 512); }
                if (kk == 2) { av[4] = lds128(tb.y + 4 * 512); av[5] = lds128(tb.y + 5 * 512); }
                if (kk == 3) { av[6] = lds128(tb.y + 6 * 512); av[7] = lds128(tb.y + 7 * 512); }
            }
#pragma unroll
            for (int i = 0; i < 4; i++) { acc[0][i] += acc[3][i]; acc[1][i] += acc[4][i]; }
            const float g0 = kh ? acc[0][0] : acc[1][0], g1 = kh ? acc[0][1] : acc[1][1], g2 = kh ? acc[0][2] : acc[1][2], g3 = kh ? acc[0][3] : acc[1][3];
            sts128(tb.w, make_uint4(__float_as_uint(g0), __float_as_uint(g1), __float_as_uint(g2), __float_as_uint(g3)));
            const float k0 = kh ? acc[1][0] : acc[0][0], k1 = kh ? acc[1][1] : acc[0][1], k2_ = kh ? acc[1][2] : acc[0][2], k3 = kh ? acc[1][3] : acc[0][3];
            if (warp == 0) PROF(1);
            bar_sync(NB_X + aa, 64);
            const uint4 o = lds128(tb.z + 4096);
            stsm2t(ta.x, pack2(k0 + __uint_as_float(o.x), k1 + __uint_as_float(o.y)), pack2(k2_ + __uint_as_float(o.z), k3 + __uint_as_float(o.w)));
            sts128(tb.z, make_uint4(__float_as_uint(acc[2][0]), __float_as_uint(acc[2][1]), __float_as_uint(acc[2][2]), __float_as_uint(acc[2][3])));
        }
        const uint32_t kb = ta.z + slot_off;
        if (warp == 0) PROF(14);
        bar_sync(NB_B, 256);
        if (warp < 5) {
            uint32_t q[16], k0, k1, k2, k3, k4, k5, k6, k7;
            float sa[4] = {0.f, 0.f, 0.f, 0.f}, sc[4] = {0.f, 0.f, 0.f, 0.f};
            ldsm4(q[0], q[1], q[2], q[3], ta.y);
            ldsm4(k0, k1, k2, k3, kb);
            ldsm4(q[4], q[5], q[6], q[7], ta.y ^ 32);
            ldsm4(q[8], q[9], q[10], q[11], ta.y ^ 64);
            ldsm4(k4, k5, k6, k7, kb ^ 64);
            ldsm4(q[12], q[13], q[14], q[15], ta.y ^ 96);
            mma16816(sa, q[0], q[1], q[2], q[3], k0, k1);
            bar_arrive(NB_Y, 288);
            mma16816(sc, q[4], q[5], q[6], q[7], k2, k3);
            mma16816(sa, q[8], q[9], q[10], q[11], k4, k5);
            mma16816(sc, q[12], q[13], q[14], q[15], k6, k7);
            const float scl = 0.08838834764831845f * 1.4426950408889634f;
            const float r0 = (sa[0] + sc[0]) * scl, r1 = (sa[1] + sc[1]) * scl;
            if (s != NSEG - 1) {
                st_async_v2(ta.w, r0, r1, sx_bar_rem);
                st_async_v2(ta.w ^ (1u << 24), r0, r1, sx_bar_rem ^ (1u << 24));
            }
            if (warp == 0) PROF(2);
        } else if (s > 0 && warp == 7 && lane == 0) {
            mbar_expect_tx(sb + RB_A, 4096);
            mbar_expect_tx(sb + RB_A1, 4096);
        }
        if (s == NSEG - 1) break;
        slot_off = slot_off == (R_NST - 1) * 4096 ? 0 : slot_off + slot_inc;
        const uint4 tc = lds128(tab + 4096), td = lds128(tab + 6144);
        const uint32_t te = lds32(tab + 8192);
        uint32_t* wr = (uint32_t*)(((uint64_t)td.y << 32) | (td.x ^ ((s & 1) * 0x21000)));
        const uint32_t* r1p = (const uint32_t*)((const char*)wr + (int)td.z);
        const uint32_t* r2p = (const uint32_t*)((const char*)wr + (int)td.w);
        const uint32_t* r3p = (const uint32_t*)((const char*)wr + (int)te);
        const uint32_t tag = ((s >> 1) + 1) & 1;
        mbar_wait(sb + RB_E, s & 1);
        if (warp == 0) PROF(7);
        {
            uint32_t a0, a1, a2, a3, a4, a5, a6, a7;
            ldsm4t(a0, a1, a2, a3, tc.x);
            ldsm4t(a4, a5, a6, a7, tc.x ^ 64);
            const uint32_t one = 0x3F803F80u;
            float d0_[4] = {0.f, 0.f, 0.f, 0.f}, d1_[4] = {0.f, 0.f, 0.f, 0.f};
            mma16816(d0_, a0, a1, a2, a3, one, one);
            mma16816(d1_, a4, a5, a6, a7, one, one);
            const bool t1 = tc.w & 1, t2 = tc.w & 2;
            const float x = t2 ? (t1 ? d1_[2] : d1_[0]) : (t1 ? d0_[2] : d0_[0]);
            const uint32_t own = (__float_as_uint(x) & ~1u) | tag;
            stg_relaxed32(wr, own);
            const uint32_t tq = clk32();
            if (warp == 0) PROF(8);
            PROFG(16 + warp);
            while ((int)(clk32() - tq) < POLL_GAP) {}
            uint32_t f1 = ldg_relaxed32(r1p), f2 = ldg_relaxed32(r2p), f3 = ldg_relaxed32(r3p);
#pragma unroll
            for (int i = 0; i < NOFF; i++) {
                const uint4 f0 = lds128(tab + 10240 + i * 2048);
                wa[i & 1][i >> 1][0] = f0.x; wa[i & 1][i >> 1][1] = f0.y; wa[i & 1][i >> 1][2] = f0.z; wa[i & 1][i >> 1][3] = f0.w;
            }
            tb = lds128(tab + 2048);
            int gg = 0;
#pragma unroll 1
            while (!__all_sync(~0u, (((f1 ^ tag) | (f2 ^ tag) | (f3 ^ tag)) & 1) == 0)) {
                f1 = ldg_relaxed32(r1p); f2 = ldg_relaxed32(r2p); f3 = ldg_relaxed32(r3p);
                if (++gg > 16 * SPIN_LIMIT) { TIMEOUT(3, s); break; }
            }
            if (warp == 0) PROF(9);
            const float v = (__uint_as_float(own) + __uint_as_float(f2)) + (__uint_as_float(f1) + __uint_as_float(f3));
            const bool b8 = tc.w & 8, b16 = tc.w & 16;
            const float recv = __shfl_xor_sync(~0u, v, 8);
            const uint32_t word = b8 ? pack2(recv, v) : pack2(v, recv);
            const uint32_t oth = __shfl_xor_sync(~0u, word, 16);
            const uint32_t wl = b16 ? oth : word, wh = b16 ? word : oth;
            const uint32_t p0 = __shfl_xor_sync(~0u, wl, 2), p1 = __shfl_xor_sync(~0u, wh, 2);
            const uint4 item = t2 ? make_uint4(p0, p1, wl, wh) : make_uint4(wl, wh, p0, p1);
            st_async_v4(tc.y, item, tc.z);
            st_async_v4(tc.y ^ (8u << 24), item, tc.z ^ (8u << 24));
            if (tc.w == 0 && warp == 7) mbar_expect_tx(sb + RB_E, 8192);
            if (warp == 0) PROF(10);
            PROF(40 + warp);
        }
        bar_sync(NB_D, 384);
    }
}

__device__ __forceinline__ void rec_load_kv(uint32_t sb, int col0, int s, uint32_t slot_off, int t128) {
    const int row = t128 >> 2, c2 = (t128 & 3) * 2;
    const bf16* src = g_kv + ((size_t)(s * 32 + row) * (2 * HD_) + col0 + c2 * 8);
    const uint32_t d0 = sb + R_KX + slot_off + row * 128 + ((c2 ^ (row & 7)) << 4);
    cp_async16(d0, src);
    cp_async16(d0 ^ 16, src + 8);
    cp_async16(d0 + (R_VX - R_KX), src + HD_);
    cp_async16((d0 ^ 16) + (R_VX - R_KX), src + HD_ + 8);
}

__device__ __forceinline__ void rec_vo(const RecParams& p, const uint32_t sb, const int cta, const int warp, int lane) {
    const int w = warp - 8, crank = cta & 15;
    const int col0 = cta * 64;
    uint32_t wo[8][4][4];
    {
        const int t128 = w * 32 + lane;
        const bf16* Wo = p.wo + (size_t)col0 * D_;
        const uint32_t stg = sb + R_STG + 2 * 32768;
#pragma unroll
        for (int half = 0; half < 2; half++) {
#pragma unroll 4
            for (int i = t128; i < 2048; i += 128) {
                const int e = i >> 6, ch = i & 63;
                cp_async16(stg + e * 1024 + ((ch ^ (e & 7)) << 4), Wo + (size_t)(half * 32 + e) * D_ + ch * 8);
            }
            cp_async_commit();
            cp_async_wait<0>();
            bar_sync(NB_W0 + 2, 128);
#pragma unroll
            for (int j = 0; j < 8; j++)
#pragma unroll
                for (int kk = 0; kk < 2; kk++) {
                    const int e = kk * 16 + (lane >> 4) * 8 + (lane & 7);
                    const int ch = (w * 8 + j) * 2 + ((lane >> 3) & 1);
                    ldsm4t(wo[j][half * 2 + kk][0], wo[j][half * 2 + kk][1], wo[j][half * 2 + kk][2], wo[j][half * 2 + kk][3],
                           stg + e * 1024 + ((ch ^ (e & 7)) << 4));
                }
            bar_sync(NB_W0 + 2, 128);
        }
        if (lane == 0) wait_flag(F_KV + 0, 64);
        __syncwarp();
        rec_load_kv(sb, col0, 0, 0, t128); cp_async_commit();
        rec_load_kv(sb, col0, 1, 4096, t128); cp_async_commit();
        cp_async_wait<1>();
    }
    const uint32_t tab = sb + R_STG + 2 * 32768 + (w * 32 + lane) * 16;
    {
        const uint32_t l7 = lane & 7, l8 = lane >> 3, g = lane >> 2;
        uint4 v;
        v.x = sb + R_VX + ((l8 & 1) * 8 + l7) * 128 + (((2 * w + (l8 >> 1)) ^ l7) << 4);
        v.y = sb + R_OS + g * 128 + (((2 * w) ^ g) << 4) + (lane & 3) * 4;
        v.z = sb + R_VMS + l7 * 128 + (((2 * w + (l8 & 1)) ^ l7) << 4);
        v.w = sb + R_OS + l7 * 128 + ((l8 ^ l7) << 4);
        sts128(tab, v);
        v.x = mapa_u32(sb + R_RS + crank * 512 + ((lane ^ (crank & 7)) << 4), w * 4);
        v.y = mapa_u32(sb + RB_E, w * 4);
        v.z = sb + R_VP + w * 512 + lane * 16;
        v.w = sb + R_SX + lane * 8;
        sts128(tab + 2048, v);
#pragma unroll
        for (int i = 0; i < 8; i++) sts128(tab + 4096 + i * 2048, make_uint4(wo[i][0][0], wo[i][0][1], wo[i][0][2], wo[i][0][3]));
    }
    bar_sync(NB_D, 384);
    const uint32_t lane16 = lds32(tab + 2048 + 8) - R_VP - w * 512;
    uint4 av[2 * VK0];
#pragma unroll
    for (int i = 0; i < 2 * VK0; i++) av[i] = lds128(lane16 + R_WV + (i / VK0) * 32768 + (w * 16 + i % VK0) * 512);
    uint32_t slot_off = 0;
    uint4 kvm = make_uint4(0, 0, 0, 0);
    bf16* kvm_dst = g_kvm + (((w & 1) * 4 + (lane >> 3)) * (2 * HD_) + (w >> 1) * HD_ + col0 + (lane & 7) * 8);
#pragma unroll 1
    for (int s = 0; s < NSEG; s++) {
        if (s > 0) {
            mbar_wait(sb + RB_A, (s - 1) & 1);
            *(uint4*)(kvm_dst + (size_t)(s - 1) * 8 * (2 * HD_)) = kvm;
            if (s + 1 < NSEG - 1) {
                if (((s + 1) & 3) == 0) { if (lane == 0) wait_flag(F_KV + ((s + 1) >> 2), 64); __syncwarp(); }
                rec_load_kv(sb, col0, s + 1, slot_off == (R_NST - 1) * 4096 ? 0 : slot_off + 4096, w * 32 + lane);
            }
            cp_async_commit();
            if ((s & 3) == 0) {
                bar_sync(NB_C, 128);
                if (w == 0 && lane == 0) red_release(&g_flags[F_MEM + (s >> 2) - 1], 1);
            }
        }
        bar_sync(NB_Y, 288);
        uint32_t vb0, vb1;
        {
            float va[4] = {0.f, 0.f, 0.f, 0.f}, vc[4] = {0.f, 0.f, 0.f, 0.f};
            uint32_t bb[VK0][4];
#pragma unroll
            for (int k2 = 0; k2 < VK0; k2++) ldsm4(bb[k2][0], bb[k2][1], bb[k2][2], bb[k2][3], lane16 + R_MEM + (k2 / (VK0 / 2)) * 4096 + (k2 % (VK0 / 2)) * 512);
#pragma unroll
            for (int k2 = 0; k2 < VK0; k2++) {
                mma16816(va, av[2 * k2].x, av[2 * k2].y, av[2 * k2].z, av[2 * k2].w, bb[k2][0], bb[k2][1]);
                mma16816(vc, av[2 * k2 + 1].x, av[2 * k2 + 1].y, av[2 * k2 + 1].z, av[2 * k2 + 1].w, bb[k2][2], bb[k2][3]);
            }
            const uint4 a = lds128(lane16 + R_VP + w * 512), b = lds128(lane16 + R_VP + 2048 + w * 512);
            vb0 = pack2((va[0] + vc[0]) + (__uint_as_float(a.x) + __uint_as_float(b.x)), (va[1] + vc[1]) + (__uint_as_float(a.y) + __uint_as_float(b.y)));
            vb1 = pack2((va[2] + vc[2]) + (__uint_as_float(a.z) + __uint_as_float(b.z)), (va[3] + vc[3]) + (__uint_as_float(a.w) + __uint_as_float(b.w)));
        }
        const uint4 ta = lds128(tab), tb = lds128(tab + 2048);
        uint32_t vx[8];
        ldsm4t(vx[0], vx[1], vx[2], vx[3], ta.x + slot_off);
        ldsm4t(vx[4], vx[5], vx[6], vx[7], ta.x + slot_off + 2048);
#pragma unroll
        for (int i = 0; i < 4; i++) {
            const uint4 f0 = lds128(tab + 4096 + i * 2048);
            wo[i][0][0] = f0.x; wo[i][0][1] = f0.y; wo[i][0][2] = f0.z; wo[i][0][3] = f0.w;
        }
        if (w == 0) PROF(11);
        uint32_t pf[5];
        float oa[2][4] = {{0.f, 0.f, 0.f, 0.f}, {0.f, 0.f, 0.f, 0.f}}, ob_[2][4] = {{0.f, 0.f, 0.f, 0.f}, {0.f, 0.f, 0.f, 0.f}};
        float sm0[4] = {0.f, 0.f, 0.f, 0.f}, sm1[4] = {0.f, 0.f, 0.f, 0.f};
        if (s != NSEG - 1) {
            mbar_wait(sb + RB_SX, s & 1);
            if (w == 0) PROF(4);
            float sv[10];
#pragma unroll
            for (int n = 0; n < 5; n++) {
                const float2 a = lds64f(tb.w + n * 256), b = lds64f(tb.w + (5 + n) * 256);
                sv[2 * n] = a.x + b.x; sv[2 * n + 1] = a.y + b.y;
            }
            float mx = fmaxf(fmaxf(fmaxf(sv[0], sv[1]), fmaxf(sv[2], sv[3])), fmaxf(fmaxf(sv[4], sv[5]), fmaxf(sv[6], sv[7])));
            mx = fmaxf(mx, fmaxf(sv[8], sv[9]));
            mx = fmaxf(mx, __shfl_xor_sync(~0u, mx, 1));
            mx = fmaxf(mx, __shfl_xor_sync(~0u, mx, 2));
#pragma unroll
            for (int n = 1; n < 5; n++) pf[n] = pack2(ex2(sv[2 * n] - mx), ex2(sv[2 * n + 1] - mx));
            pf[0] = pack2(ex2(sv[0] - mx), ex2(sv[1] - mx));
            if (w == 0) PROF(12);
            const uint32_t one = 0x3F803F80u;
            mma16816h(sm0, pf[1], pf[2], one, one);
            mma16816h(oa[0], pf[1], pf[2], vx[0], vx[1]);
            mma16816h(oa[1], pf[1], pf[2], vx[2], vx[3]);
            mma16816h(sm1, pf[3], pf[4], one, one);
            mma16816h(ob_[0], pf[3], pf[4], vx[4], vx[5]);
            mma16816h(ob_[1], pf[3], pf[4], vx[6], vx[7]);
            mma1688h(sm0, pf[0], one);
            mma1688h(oa[0], pf[0], vb0);
            mma1688h(oa[1], pf[0], vb1);
            float inv;
            asm("rcp.approx.ftz.f32 %0, %1;" : "=f"(inv) : "f"(sm0[0] + sm1[0]));
            oa[0][0] += ob_[0][0]; oa[0][1] += ob_[0][1]; oa[1][0] += ob_[1][0]; oa[1][1] += ob_[1][1];
            sts32(ta.y, pack2(oa[0][0] * inv, oa[0][1] * inv));
            sts32(ta.y ^ 16, pack2(oa[1][0] * inv, oa[1][1] * inv));
            const uint32_t oa2 = ta.w ^ 64;
            bar_sync(NB_C, 128);
            if (w == 0) PROF(5);
            uint32_t ob[8];
            ldsm4(ob[0], ob[1], ob[2], ob[3], ta.w);
            ldsm4(ob[4], ob[5], ob[6], ob[7], oa2);
#pragma unroll
            for (int i = 4; i < 8; i++) {
                const uint4 f0 = lds128(tab + 4096 + i * 2048);
                wo[i][0][0] = f0.x; wo[i][0][1] = f0.y; wo[i][0][2] = f0.z; wo[i][0][3] = f0.w;
            }
#pragma unroll
            for (int jj = 0; jj < 2; jj++) {
                if (jj == 1 && tb.w == 0) break;
                float acc[4][4];
#pragma unroll
                for (int c = 0; c < 4; c++) { acc[c][0] = acc[c][1] = acc[c][2] = acc[c][3] = 0.f; }
#pragma unroll
                for (int ks = 0; ks < 4; ks++)
#pragma unroll
                    for (int c = 0; c < 4; c++)
                        mma16816(acc[c], wo[jj * 4 + c][ks][0], wo[jj * 4 + c][ks][1], wo[jj * 4 + c][ks][2], wo[jj * 4 + c][ks][3], ob[2 * ks], ob[2 * ks + 1]);
#pragma unroll
                for (int pr = 0; pr < 2; pr++) {
                    uint4 v;
                    v.x = pack2(acc[2 * pr][0], acc[2 * pr][1]);
                    v.y = pack2(acc[2 * pr][2], acc[2 * pr][3]);
                    v.z = pack2(acc[2 * pr + 1][0], acc[2 * pr + 1][1]);
                    v.w = pack2(acc[2 * pr + 1][2], acc[2 * pr + 1][3]);
                    st_async_v4(tb.x + ((jj * 2 + pr) << 24), v, tb.y + ((jj * 2 + pr) << 24));
                }
            }
            if (w == 0) PROF(6);
        }
        stsm2t(ta.z, vb0, vb1);
        cp_async_wait<0>();
        bar_sync(NB_C, 128);
        if (w == 0 && lane == 0 && s != NSEG - 1) mbar_expect_tx(sb + RB_SX, 2560);
        kvm = lds128(sb + ((w >> 1) ? R_VMS : R_KMS) + ((w & 1) * 4 + (lane >> 3)) * 128 + (((lane & 7) ^ ((w & 1) * 4 + (lane >> 3))) << 4));
        if (s != NSEG - 1) {
            bar_arrive(NB_D, 384);
#pragma unroll
            for (int i = 0; i < 2 * VK0; i++) av[i] = lds128(lane16 + R_WV + (i / VK0) * 32768 + (w * 16 + i % VK0) * 512);
        }
        slot_off = slot_off == (R_NST - 1) * 4096 ? 0 : slot_off + 4096;
    }
    *(uint4*)(kvm_dst + (size_t)(NSEG - 1) * 8 * (2 * HD_)) = kvm;
    bar_sync(NB_C, 128);
    if (w == 0 && lane == 0) red_release(&g_flags[F_MEM + NRB - 1], 1);
}

__global__ void __launch_bounds__(384, 1) k_rec(const RecParams p) {
    extern __shared__ __align__(1024) unsigned char smem_raw[];
    const uint32_t sb = __shfl_sync(~0u, smem_u32(smem_raw), 0);
    const int warp = __shfl_sync(~0u, threadIdx.x >> 5, 0);
    int lane; asm volatile("mov.u32 %0, %%laneid;" : "=r"(lane));
    const int crank = blockIdx.x & 15, slot = blockIdx.x >> 4;
    asm volatile("griddepcontrol.launch_dependents;");
    if (threadIdx.x == 0) {
        mbar_init(sb + RB_SX, 1); mbar_init(sb + RB_E, 1); mbar_init(sb + RB_A, 1); mbar_init(sb + RB_A1, 1); mbar_init(sb + RB_ROLE, 1);
        asm volatile("fence.mbarrier_init.release.cluster;" ::: "memory");
        mbar_expect_tx(sb + RB_SX, 2560);
        mbar_expect_tx(sb + RB_E, 8192);
        mbar_expect_tx(sb + RB_A, 4096);
        mbar_expect_tx(sb + RB_A1, 4096);
        mbar_expect_tx(sb + RB_ROLE, 4);
    }
    unsigned role = 0;
    if (crank == 0 && threadIdx.x == 0) {
        unsigned x = 0;
        int tm[2] = {0x7fffffff, 0x7fffffff};
#pragma unroll 1
        for (int i = 0; i < 6; i++) {
            const uint32_t t0 = clk32();
            x = atomicAdd(&g_F[65536 + (i & 1) * 1024 + slot * 64 + (x >> 31)], 0u) & 0x7fffffffu;
            if (x == 0x7654321u) sts32(sb + R_BAR + 56, x);
            const int dt = (int)(clk32() - t0);
            if (i >= 2) { if (i & 1) tm[1] = min(tm[1], dt); else tm[0] = min(tm[0], dt); }
        }
        const int side = tm[1] > tm[0];
        const unsigned old = atomicAdd(&g_flags[F_SIDE + side * 32], 1u);
        unsigned c0, c1; int gd = 0;
#pragma unroll 1
        do { c0 = ldg_relaxed32(&g_flags[F_SIDE]); c1 = ldg_relaxed32(&g_flags[F_SIDE + 32]); } while ((int)(c0 + c1) < p.ncl && ++gd < 64 * SPIN_LIMIT);
        const int big = c1 > c0;
        role = side == big ? old : (big ? c1 : c0) + old;
        role |= (big ^ 1) << 8;
    }
    __syncwarp();
    asm volatile("barrier.cluster.arrive.relaxed.aligned;\nbarrier.cluster.wait.aligned;" ::: "memory");
    if (crank == 0 && warp == 0) {
        role = __shfl_sync(~0u, role, 0);
        if (lane < 16)
            asm volatile("st.async.weak.shared::cluster.mbarrier::complete_tx::bytes.u32 [%0], %1, [%2];"
                         :: "r"(mapa_u32(sb + R_BAR + 48, lane)), "r"(role), "r"(mapa_u32(sb + RB_ROLE, lane)) : "memory");
    }
    mbar_wait(sb + RB_ROLE, 0);
    const int rolew = __shfl_sync(~0u, lds32(sb + R_BAR + 48), 0);
    const int cl = rolew & 255;
    if (cl >= 4) return;
    const int cta = cl * 16 + crank;
    if (warp < 8) rec_qk(p, sb, cta, warp, lane, rolew >> 8);
    else rec_vo(p, sb, cta, warp, lane);
}

enum { J_KV = 0, J_QA = 1, J_O = 2, J_LN = 3, J_UP = 4, J_DN = 5, J_UP2 = 6, J_END = 8 };
constexpr int NJ_O = 2 * OSPLIT, NJ_O2 = 2 * OSPLIT2, NJ_LN = 8, NJ_LN2 = 16, NJ_UP = 14, NJ_UP2 = 28, NJ_DN = 8;
__device__ __forceinline__ int nj_coarse(int q) { return q == J_KV ? 32 : (q == J_QA ? 16 : (q == J_O ? NJ_O : (q == J_LN ? NJ_LN : (q == J_UP ? NJ_UP : NJ_DN)))); }
__device__ __forceinline__ int nj_fine(int q) { return q == J_KV ? 32 : (q == J_QA ? 16 : (q == J_O ? NJ_O2 : (q == J_LN ? NJ_LN2 : (q == J_UP ? NJ_UP2 : NJ_DN)))); }
__device__ __forceinline__ int pick_job(int lane, int qmask, int& idx) {
    const int rb = lane & 15, half = lane >> 4;
    const bool fine = rb >= FINE_RB;
    int gd = 0;
#pragma unroll 1
    while (true) {
        unsigned cl[3], dp[3];
#pragma unroll
        for (int i = 0; i < 3; i++) {
            const int q = half + 2 * i;
            cl[i] = ldg_relaxed32(&g_flags[F_CLAIM + q * 32 + rb]);
            dp[i] = ldg_relaxed32(&g_flags[q * 32 + (q == J_QA ? max(rb - 1, 0) : rb)]);
        }
        int pick_q = -1, pick_rb = 0, early_q = -1, early_rb = 0;
        unsigned prev16 = 0;
        bool any = false;
#pragma unroll
        for (int i = 0; i < 3; i++) {
            const int q = half + 2 * i;
            const bool have = ((qmask >> q) & 1) && (int)cl[i] < (fine ? nj_fine(q) : nj_coarse(q));
            const unsigned tgt = q == J_QA ? 64 : 2 * (fine ? nj_fine(q - 1) : nj_coarse(q - 1));
            const bool ready = have && (q == J_KV || (q == J_QA && rb == 0) || dp[i] >= tgt);
            const unsigned mh = __ballot_sync(~0u, have), mr = __ballot_sync(~0u, ready);
            any |= mh != 0;
#pragma unroll
            for (int hf = 0; hf < 2; hf++) {
                const int qq = hf + 2 * i;
                const unsigned r16 = (mr >> (16 * hf)) & 0xffffu, h16 = (mh >> (16 * hf)) & 0xffffu;
                if (r16 && pick_q != J_KV) { pick_q = qq; pick_rb = __ffs(r16) - 1; }
                if (qq >= J_O && early_q < 0 && h16 && __ffs(h16) - 1 >= FINE_RB && (prev16 & ((2u << (__ffs(h16) - 1)) - 1)) == 0) {
                    early_q = qq; early_rb = __ffs(h16) - 1;
                }
                prev16 |= h16;
            }
        }
        if (!any) return J_END;
        if (pick_q < 0) { pick_q = early_q; pick_rb = early_rb; }
        if (pick_q >= 0) {
            int c = 0;
            if (lane == 0) c = (int)atomicAdd(&g_flags[F_CLAIM + pick_q * 32 + pick_rb], 1u);
            c = __shfl_sync(~0u, c, 0);
            const bool f = pick_rb >= FINE_RB;
            if (c < (f ? nj_fine(pick_q) : nj_coarse(pick_q))) {
                idx = pick_q * 600 + pick_rb * 32 + c;
                return (pick_q == J_UP && f ? J_UP2 : pick_q) | (pick_rb << 8) | (c << 16);
            }
        } else {
            __nanosleep(200);
            if (++gd > 16 * SPIN_LIMIT) { TIMEOUT(5, 0); return J_END; }
        }
    }
}
__device__ __forceinline__ int op_row(int rb, int split) {
    return rb < FINE_RB ? split * S_ + rb * 128 : OSPLIT * S_ + (split * (NRB - FINE_RB) + rb - FINE_RB) * 128;
}

struct Pipe { uint32_t stage, phase; };
__device__ __forceinline__ void pipe_next(Pipe& p) { if (++p.stage == W_NST) { p.stage = 0; p.phase ^= 1; } }

__device__ __forceinline__ void scheduler(const Params& p, uint32_t sb, int lane) {
    const uint32_t bars = sb + SM_BAR;
    uint32_t ph = 0;
#pragma unroll 1
    while (true) {
        mbar_wait(bars + B_REQ, ph);
        int j = 4095;
        const int jd = pick_job(lane, p.qmask, j);
        if (lane == 0) { sts32(bars + B_NEXT, (uint32_t)jd); sts32(bars + B_NEXT + 4, (uint32_t)j); mbar_arrive(bars + B_RSP); }
        ph ^= 1;
        if (jd == J_END) break;
        __syncwarp();
    }
}

__device__ __forceinline__ void producer(const Params& p, uint32_t sb) {
    Pipe pp{0, 1};
    const uint32_t bars = sb + SM_BAR;
    uint32_t seq = 0;
    mbar_arrive(bars + B_REQ);
#pragma unroll 1
    while (true) {
        mbar_wait(bars + B_RSP, seq & 1);
        const int jd = (int)lds32(bars + B_NEXT), j = (int)lds32(bars + B_NEXT + 4);
        int left = (jd & 255) == J_DN ? 15 : ((jd & 255) == J_QA ? 12 : ((jd & 255) == J_O ? (((jd >> 8) & 255) >= FINE_RB ? 64 / OSPLIT2 : 64 / OSPLIT) : ((jd & 255) == J_LN ? 1 : 8)));
        left = max(left - PICK_AHEAD, 1);
        TR(j, 1);
        const int type = jd & 255, rb = (jd >> 8) & 255, cb = jd >> 16;
        const bool fine = rb >= FINE_RB;
        bool first = true;
        auto begin_stage = [&](uint32_t bytes) -> uint32_t {
            mbar_wait(bars + B_EMPTY + pp.stage * 8, pp.phase);
            if (first) { sts32(bars + B_RING + (seq & 7) * 4, (uint32_t)jd); sts32(bars + B_RING + 32 + (seq & 7) * 4, (uint32_t)j); first = false; }
            const uint32_t fb = bars + B_FULL + pp.stage * 8;
            if (bytes) mbar_expect_tx(fb, bytes); else mbar_arrive(fb);
            if (--left == 0 && type != J_END) mbar_arrive(bars + B_REQ);
            return fb;
        };
        if (type == J_END || type == J_LN) {
            if (type == J_LN) wait_flag(F_OP + rb, 2 * (fine ? NJ_O2 : NJ_O));
            TR(j, 2);
            begin_stage(0); pipe_next(pp);
            seq++;
            if (type == J_END) break;
            continue;
        }
        const CUtensorMap *ta, *tb0, *tb1;
        int k0 = 0, nk = 8, n0 = cb * 256, n1 = n0 + 128, nb = 4, dep = -1;
        unsigned tgt = 0;
        switch (type) {
            case J_KV: ta = &p.tm_h; tb0 = tb1 = cb < 16 ? &p.tm_wk : &p.tm_wv; n0 = (cb & 15) * 256; n1 = n0 + 128; break;
            case J_QA: ta = &p.tm_h; tb0 = tb1 = &p.tm_wq; break;
            case J_O: ta = &p.tm_o; tb0 = tb1 = &p.tm_wo; n0 = (cb & 1) * 256; n1 = n0 + 128; nk = fine ? 64 / OSPLIT2 : 64 / OSPLIT; k0 = (cb >> 1) * nk * 64;
                      dep = F_O + rb; tgt = 32; break;
            case J_UP: ta = &p.tm_h2; tb0 = &p.tm_wg; tb1 = &p.tm_wu; n0 = n1 = cb * 128; dep = F_H2 + rb; tgt = 2 * NJ_LN; break;
            case J_UP2: ta = &p.tm_h2; tb0 = &p.tm_wg; tb1 = &p.tm_wu; n0 = n1 = cb * 64; nb = 2; dep = F_H2 + rb; tgt = 2 * NJ_LN2; break;
            default: ta = &p.tm_act; tb0 = tb1 = &p.tm_wd; n0 = cb * 64; nk = 0; break;
        }
        const int m0 = rb * 128;
        if (type == J_DN) {
#pragma unroll 1
            for (int kb = 0; kb < 14; kb++) {
                const uint32_t fb = begin_stage(49152);
                const uint32_t st = sb + pp.stage * W_STAGE;
                const int k = kb * 128;
                tma_load2d(st + 32768, tb0, n0, k, fb);
                tma_load2d(st + 40960, tb0, n0, k + 64, fb);
                if (kb == 0) { wait_flag(F_ACT + rb, 2 * (fine ? NJ_UP2 : NJ_UP)); fence_async_all(); TR(j, 2); }
                tma_load2d(st, ta, k, m0, fb);
                tma_load2d(st + 8192, ta, k, m0 + 64, fb);
                tma_load2d(st + 16384, ta, k + 64, m0, fb);
                tma_load2d(st + 24576, ta, k + 64, m0 + 64, fb);
                pipe_next(pp);
            }
        }
#pragma unroll 1
        for (int kb = 0; kb < nk; kb++) {
            const uint32_t fb = begin_stage(16384 + nb * 8192);
            const uint32_t st = sb + pp.stage * W_STAGE;
            const int k = k0 + kb * 64;
            tma_load2d(st + 16384, tb0, n0, k, fb);
            if (nb == 4) {
                tma_load2d(st + 16384 + 8192, tb0, n0 + 64, k, fb);
                tma_load2d(st + 16384 + 16384, tb1, n1, k, fb);
                tma_load2d(st + 16384 + 24576, tb1, n1 + 64, k, fb);
            } else if (nb == 2) {
                tma_load2d(st + 16384 + 8192, tb1, n1, k, fb);
            }
            if (kb == 0) {
                if (dep >= 0) { wait_flag(dep, tgt); if (type >= J_UP) fence_async_all(); }
                TR(j, 2);
            }
            tma_load2d(st, ta, k, m0, fb);
            tma_load2d(st + 8192, ta, k, m0 + 64, fb);
            pipe_next(pp);
        }
        if (type == J_QA) {
            wait_flag(F_KV + rb, 64);
#pragma unroll 1
            for (int i = 0; i < 4; i++) {
                const uint32_t fb = begin_stage(40960);
                const uint32_t st = sb + pp.stage * W_STAGE;
                const int col = (i & 1) * HD_ + (cb * 2 + (i >> 1)) * DH_;
                tma_load2d(st, &p.tm_kv, col, m0, fb);
                tma_load2d(st + 8192, &p.tm_kv, col, m0 + 64, fb);
                tma_load2d(st + 16384, &p.tm_kv, col + 64, m0, fb);
                tma_load2d(st + 24576, &p.tm_kv, col + 64, m0 + 64, fb);
                if (i == 0) { wait_flag(F_MEM + rb, 64); fence_async_all(); }
                tma_load2d(st + 32768, &p.tm_kvm, col, rb * 32, fb);
                tma_load2d(st + 36864, &p.tm_kvm, col + 64, rb * 32, fb);
                pipe_next(pp);
            }
        } else if (type == J_DN) {
            const uint32_t fb = begin_stage(16384);
            const uint32_t st = sb + pp.stage * W_STAGE;
            tma_load2d(st, &p.tm_x1, n0, m0, fb);
            tma_load2d(st + 8192, &p.tm_x1, n0, m0 + 64, fb);
            pipe_next(pp);
        }
        seq++;
    }
}

__device__ __forceinline__ void store_warp(const Params& p, uint32_t sb, int wg, int lane) {
    const uint32_t bars = sb + SM_BAR;
    uint32_t seq = 0;
#pragma unroll 1
    while (true) {
        bar_sync(NB_ST + wg, 160);
        const uint32_t jd = lds32(bars + B_RING + (seq & 7) * 4);
        seq++;
        const int type = jd & 255, rb = (jd >> 8) & 255, cb = jd >> 16;
        if (type == J_END) break;
        if (lane == 0) {
            const uint32_t src = sb + W_STG + wg * 32768;
            const CUtensorMap* tm = nullptr; int n0 = cb * 256, nbox = 4, mrow = rb * 128 + wg * 64, flag = 0;
            switch (type) {
                case J_KV: tm = &p.tm_kv; flag = F_KV + rb; break;
                case J_QA: tm = &p.tm_o; flag = F_O + rb; break;
                case J_O: tm = &p.tm_op; n0 = (cb & 1) * 256; mrow = op_row(rb, cb >> 1) + wg * 64; flag = F_OP + rb; break;
                case J_LN: flag = F_H2 + rb; nbox = 0; break;
                case J_UP: tm = &p.tm_act; n0 = cb * 128; nbox = 2; flag = F_ACT + rb; break;
                case J_UP2: tm = &p.tm_act; n0 = cb * 64; nbox = 1; flag = F_ACT + rb; break;
                default: tm = &p.tm_out; n0 = cb * 64; nbox = 1; flag = -1; break;
            }
#pragma unroll 1
            for (int b = 0; b < nbox; b++) tma_store2d(tm, src + b * 8192, n0 + b * 64, mrow);
            bulk_commit();
            bulk_wait0();
            mbar_arrive(bars + B_STGFREE + wg * 8);
            if (flag >= 0) red_release(&g_flags[flag], 1);
        }
        __syncwarp();
    }
}

__device__ __forceinline__ float gelu_tanh(float x) {
    const float t = x * fmaf(-0.10294324397f, x * x, -2.30220819814f);
    float r; asm("rcp.approx.ftz.f32 %0, %1;" : "=f"(r) : "f"(1.f + ex2(t)));
    return x * r;
}

#define CTR(i) do {} while (0)

template <int NSPLIT>
__device__ __forceinline__ void ln2_row(const Params& p, int rb, int r, int lane) {
    const int row = rb * 128 + r;
    uint4 u[2 * NSPLIT];
#pragma unroll
    for (int sp = 0; sp < NSPLIT; sp++) {
        const uint4* src = (const uint4*)(g_op + (size_t)(op_row(rb, sp) + r) * D_);
        u[2 * sp] = __ldcg(src + lane); u[2 * sp + 1] = __ldcg(src + 32 + lane);
    }
    const uint4* xr = (const uint4*)(p.x + (size_t)row * D_);
    const uint4 xa = __ldg(xr + lane), xb = __ldg(xr + 32 + lane);
    uint32_t ga[8], c1[8], sm[8];
    load_mod8(g_mod + 2 * D_, lane, ga);
    load_mod8(g_mod + 4 * D_, lane, c1);
    load_mod8(g_mod + 3 * D_, lane, sm);
    float a[16];
#pragma unroll
    for (int i = 0; i < 16; i++) a[i] = 0.f;
#pragma unroll
    for (int sp = 0; sp < 2 * NSPLIT; sp++) {
        float* q = a + (sp & 1) * 8;
        q[0] += bflo(u[sp].x); q[1] += bfhi(u[sp].x); q[2] += bflo(u[sp].y); q[3] += bfhi(u[sp].y);
        q[4] += bflo(u[sp].z); q[5] += bfhi(u[sp].z); q[6] += bflo(u[sp].w); q[7] += bfhi(u[sp].w);
    }
    const uint32_t xv[8] = {xa.x, xa.y, xa.z, xa.w, xb.x, xb.y, xb.z, xb.w};
    uint32_t v[8], r8[8];
#pragma unroll
    for (int i = 0; i < 8; i++) v[i] = hadd2(xv[i], hmul2(ga[i], pack2(a[2 * i], a[2 * i + 1])));
    uint4* x1r = (uint4*)(g_x1 + (size_t)row * D_);
    x1r[lane] = make_uint4(v[0], v[1], v[2], v[3]); x1r[32 + lane] = make_uint4(v[4], v[5], v[6], v[7]);
    uint32_t mu2; float rden;
    ln_stats(v, mu2, rden);
#pragma unroll
    for (int i = 0; i < 8; i++) c1[i] = hadd2(c1[i], 0x3F803F80u);
    ln_apply(v, mu2, rden, c1, sm, r8);
    uint4* hr = (uint4*)(g_h2 + (size_t)row * D_);
    hr[lane] = make_uint4(r8[0], r8[1], r8[2], r8[3]); hr[32 + lane] = make_uint4(r8[4], r8[5], r8[6], r8[7]);
}

__device__ __forceinline__ void consumer(const Params& p, uint32_t sb, int warp, int lane) {
    const uint32_t bars = sb + SM_BAR;
    const int wg = warp >> 2, wl = warp & 3;
    const uint32_t l7 = lane & 7, l8 = lane >> 3, g = lane >> 2, t = lane & 3;
    Pipe pp{0, 0};
    uint32_t seq = 0, stg_phase = 1;
    const int srow = wl * 16 + l7 + (l8 & 1) * 8;
    const uint32_t stg_base = sb + W_STG + wg * 32768 + srow * 128;
    const uint32_t sx = ((lane >> 4) ^ (srow & 7)) << 4;
#pragma unroll 1
    while (true) {
        mbar_wait(bars + B_FULL + pp.stage * 8, pp.phase);
        const uint32_t jd = lds32(bars + B_RING + (seq & 7) * 4);
        CTR(3);
        seq++;
        const int type = jd & 255, rb = (jd >> 8) & 255, cb = jd >> 16;
        if (type == J_END) { mbar_wait(bars + B_STGFREE + wg * 8, stg_phase); bar_arrive(NB_ST + wg, 160); break; }
        if (type == J_LN) {
            __syncwarp();
            if (lane == 0) mbar_arrive(bars + B_EMPTY + pp.stage * 8);
            pipe_next(pp);
            if (rb >= FINE_RB) ln2_row<OSPLIT2>(p, rb, cb * 8 + warp, lane);
            else {
#pragma unroll 1
                for (int rr = 0; rr < 2; rr++) ln2_row<OSPLIT>(p, rb, cb * 16 + warp * 2 + rr, lane);
            }
            mbar_wait(bars + B_STGFREE + wg * 8, stg_phase); stg_phase ^= 1;
            CTR(4); CTR(5);
            bar_arrive(NB_ST + wg, 160);
            continue;
        }
        if (type >= J_DN) {
            float acc[64];
#pragma unroll
            for (int i = 0; i < 64; i++) acc[i] = 0.f;
            if (type == J_DN) {
#pragma unroll 1
                for (int kb = 0; kb < 14; kb++) {
                    if (kb) mbar_wait(bars + B_FULL + pp.stage * 8, pp.phase);
                    const uint32_t st = sb + pp.stage * W_STAGE;
                    const uint64_t da = mkdesc(st + wg * 8192, 16, 1024), db = mkdesc(st + 32768, 8192, 1024);
                    wg_fence();
#pragma unroll
                    for (int ks = 0; ks < 8; ks++) wgmma_n64(acc, da + (ks >> 2) * 1024 + (ks & 3) * 2, db + ks * 128);
                    wg_commit();
                    wg_wait0();
                    if (lane == 0) mbar_arrive(bars + B_EMPTY + pp.stage * 8);
                    pipe_next(pp);
                }
            } else {
#pragma unroll 1
                for (int kb = 0; kb < 8; kb++) {
                    if (kb) mbar_wait(bars + B_FULL + pp.stage * 8, pp.phase);
                    const uint32_t st = sb + pp.stage * W_STAGE;
                    const uint64_t da = mkdesc(st + wg * 8192, 16, 1024), db = mkdesc(st + 16384, 8192, 1024);
                    wg_fence();
#pragma unroll
                    for (int ks = 0; ks < 4; ks++) wgmma_n128(acc, da + ks * 2, db + ks * 128, 1);
                    wg_commit();
                    wg_wait0();
                    if (lane == 0) mbar_arrive(bars + B_EMPTY + pp.stage * 8);
                    pipe_next(pp);
                }
            }
            CTR(4);
            if (type == J_UP2) {
                mbar_wait(bars + B_STGFREE + wg * 8, stg_phase); stg_phase ^= 1;
#pragma unroll
                for (int j = 0; j < 4; j++) {
                    uint32_t r[4];
#pragma unroll
                    for (int q = 0; q < 4; q++) {
                        const uint32_t gw = pack2(acc[8 * j + 2 * q], acc[8 * j + 2 * q + 1]);
                        const uint32_t uw = pack2(acc[32 + 8 * j + 2 * q], acc[32 + 8 * j + 2 * q + 1]);
                        r[q] = hmul2(pack2(gelu_tanh(bflo(gw)), gelu_tanh(bfhi(gw))), uw);
                    }
                    stsm4(stg_base + (sx ^ (j << 5)), r[0], r[1], r[2], r[3]);
                }
            } else {
                mbar_wait(bars + B_FULL + pp.stage * 8, pp.phase);
                const uint32_t st = sb + pp.stage * W_STAGE;
                mbar_wait(bars + B_STGFREE + wg * 8, stg_phase); stg_phase ^= 1;
                const uint32_t* gb = (const uint32_t*)(g_mod + 5 * D_ + cb * 64) + t;
                const uint32_t xa = st + wg * 8192 + (wl * 16 + g) * 128 + (g << 4) + t * 4;
#pragma unroll
                for (int j = 0; j < 4; j++) {
                    uint32_t r[4];
#pragma unroll
                    for (int q = 0; q < 4; q++) {
                        const int nt = 2 * j + (q >> 1);
                        const uint32_t xw = lds32((xa ^ ((nt & 7) << 4)) + (nt >> 3) * 16384 + (q & 1) * 1024);
                        r[q] = hadd2(xw, hmul2(__ldcg(gb + nt * 4), pack2(acc[8 * j + 2 * q], acc[8 * j + 2 * q + 1])));
                    }
                    stsm4(stg_base + (j >> 2) * 8192 + (sx ^ ((2 * j & 7) << 4)), r[0], r[1], r[2], r[3]);
                }
                __syncwarp();
                if (lane == 0) mbar_arrive(bars + B_EMPTY + pp.stage * 8);
                pipe_next(pp);
            }
            fence_async_smem();
            CTR(5);
            bar_arrive(NB_ST + wg, 160);
            continue;
        }
        float acc[128];
#pragma unroll
        for (int i = 0; i < 128; i++) acc[i] = 0.f;
        const int nk = type == J_O ? (rb >= FINE_RB ? 64 / OSPLIT2 : 64 / OSPLIT) : 8;
#pragma unroll 1
        for (int kb = 0; kb < nk; kb++) {
            if (kb) mbar_wait(bars + B_FULL + pp.stage * 8, pp.phase);
            const uint32_t st = sb + pp.stage * W_STAGE;
            const uint64_t da = mkdesc(st + wg * 8192, 16, 1024), db = mkdesc(st + 16384, 8192, 1024);
            wg_fence();
#pragma unroll
            for (int ks = 0; ks < 4; ks++) wgmma_n256(acc, da + ks * 2, db + ks * 128, 1);
            wg_commit();
            wg_wait0();
            if (lane == 0) mbar_arrive(bars + B_EMPTY + pp.stage * 8);
            pipe_next(pp);
        }
        CTR(4);
        if (type == J_QA) {
            uint32_t qf[64];
#pragma unroll
            for (int i = 0; i < 64; i++) qf[i] = pack2(acc[2 * i], acc[2 * i + 1]);
            const int sg = warp >> 1, half = warp & 1;
            const float sc = 0.08838834764831845f * 1.4426950408889634f;
            const uint32_t xoff = (sg >> 1) * 8192 + ((sg & 1) * 32 + l7) * 128;
            const uint32_t moff = 32768 + (sg * 8 + l7) * 128;
            const uint32_t kch = (l8 ^ l7) << 4;
            const uint32_t vch = ((l8 & 1) ^ l7) << 4;
            mbar_wait(bars + B_STGFREE + wg * 8, stg_phase); stg_phase ^= 1;
#pragma unroll 1
            for (int hh = 0; hh < 2; hh++) {
                mbar_wait(bars + B_FULL + pp.stage * 8, pp.phase);
                uint32_t st = sb + pp.stage * W_STAGE;
                float sa[5][4];
#pragma unroll
                for (int n = 0; n < 5; n++) sa[n][0] = sa[n][1] = sa[n][2] = sa[n][3] = 0.f;
#pragma unroll
                for (int i = 0; i < 4; i++) {
                    const uint32_t* q = qf + i * 8;
                    uint32_t kk[5][4];
                    ldsm4(kk[0][0], kk[0][1], kk[0][2], kk[0][3], st + moff + (i >> 1) * 4096 + (kch ^ ((i & 1) * 64)));
#pragma unroll
                    for (int n = 1; n < 5; n++)
                        ldsm4(kk[n][0], kk[n][1], kk[n][2], kk[n][3], st + xoff + (n - 1) * 1024 + (i >> 1) * 16384 + (kch ^ ((i & 1) * 64)));
#pragma unroll
                    for (int n = 0; n < 5; n++) mma16816(sa[n], q[0], q[1], q[2], q[3], kk[n][0], kk[n][1]);
#pragma unroll
                    for (int n = 0; n < 5; n++) mma16816(sa[n], q[4], q[5], q[6], q[7], kk[n][2], kk[n][3]);
                }
                __syncwarp();
                if (lane == 0) mbar_arrive(bars + B_EMPTY + pp.stage * 8);
                pipe_next(pp);
                const int iq0 = half * 16 + g - 2 * t, iq1 = iq0 + 8;
                float m0 = fmaxf(sa[0][0], sa[0][1]), m1 = fmaxf(sa[0][2], sa[0][3]);
#pragma unroll
                for (int n = 1; n < 5; n++) {
#pragma unroll
                    for (int e = 0; e < 2; e++) {
                        const int jx = (n - 1) * 8 + e;
                        if (jx > iq0) sa[n][e] = -3.0e38f;
                        if (jx > iq1) sa[n][2 + e] = -3.0e38f;
                        m0 = fmaxf(m0, sa[n][e]); m1 = fmaxf(m1, sa[n][2 + e]);
                    }
                }
                m0 = fmaxf(m0, __shfl_xor_sync(~0u, m0, 1)); m1 = fmaxf(m1, __shfl_xor_sync(~0u, m1, 1));
                m0 = fmaxf(m0, __shfl_xor_sync(~0u, m0, 2)); m1 = fmaxf(m1, __shfl_xor_sync(~0u, m1, 2));
                m0 *= -sc; m1 *= -sc;
                float l0 = 0.f, l1 = 0.f;
                uint32_t p0[5], p1[5];
#pragma unroll
                for (int n = 0; n < 5; n++) {
                    const float e0 = ex2(fmaf(sa[n][0], sc, m0)), e1 = ex2(fmaf(sa[n][1], sc, m0));
                    const float e2 = ex2(fmaf(sa[n][2], sc, m1)), e3 = ex2(fmaf(sa[n][3], sc, m1));
                    l0 += e0 + e1; l1 += e2 + e3;
                    p0[n] = pack2(e0, e1); p1[n] = pack2(e2, e3);
                }
                l0 += __shfl_xor_sync(~0u, l0, 1); l1 += __shfl_xor_sync(~0u, l1, 1);
                l0 += __shfl_xor_sync(~0u, l0, 2); l1 += __shfl_xor_sync(~0u, l1, 2);
                const float i0 = __fdividef(1.f, l0), i1 = __fdividef(1.f, l1);
                mbar_wait(bars + B_FULL + pp.stage * 8, pp.phase);
                st = sb + pp.stage * W_STAGE;
#pragma unroll
                for (int i = 0; i < 32; i++) qf[i] = qf[32 + i];
#pragma unroll 1
                for (int bx = 0; bx < 2; bx++) {
                    float o[8][4];
                    uint32_t vm[8], v0[4][4], v1[4][4];
#pragma unroll
                    for (int ep = 0; ep < 4; ep++) {
                        ldsm2t(vm[2 * ep], vm[2 * ep + 1], st + moff + bx * 4096 + (vch ^ (ep << 5)));
                        const uint32_t va = st + xoff + (l8 >> 1) * 1024 + bx * 16384 + (vch ^ (ep << 5));
                        ldsm4t(v0[ep][0], v0[ep][1], v0[ep][2], v0[ep][3], va);
                        ldsm4t(v1[ep][0], v1[ep][1], v1[ep][2], v1[ep][3], va + 2048);
                    }
#pragma unroll
                    for (int n = 0; n < 8; n++) { o[n][0] = o[n][1] = o[n][2] = o[n][3] = 0.f; mma16816(o[n], p0[0], p1[0], p0[1], p1[1], vm[n], v0[n >> 1][n & 1]); }
#pragma unroll
                    for (int n = 0; n < 8; n++) mma16816(o[n], p0[2], p1[2], p0[3], p1[3], v0[n >> 1][2 + (n & 1)], v1[n >> 1][n & 1]);
#pragma unroll
                    for (int n = 0; n < 8; n++) mma1688(o[n], p0[4], p1[4], v1[n >> 1][2 + (n & 1)]);
#pragma unroll
                    for (int ep = 0; ep < 4; ep++)
                        stsm4(stg_base + (hh * 2 + bx) * 8192 + (sx ^ (ep << 5)),
                              pack2(o[2 * ep][0] * i0, o[2 * ep][1] * i0), pack2(o[2 * ep][2] * i1, o[2 * ep][3] * i1),
                              pack2(o[2 * ep + 1][0] * i0, o[2 * ep + 1][1] * i0), pack2(o[2 * ep + 1][2] * i1, o[2 * ep + 1][3] * i1));
                }
                __syncwarp();
                if (lane == 0) mbar_arrive(bars + B_EMPTY + pp.stage * 8);
                pipe_next(pp);
            }
        } else if (type == J_UP) {
            mbar_wait(bars + B_STGFREE + wg * 8, stg_phase); stg_phase ^= 1;
#pragma unroll
            for (int j = 0; j < 8; j++) {
                uint32_t r[4];
#pragma unroll
                for (int q = 0; q < 4; q++) {
                    const uint32_t gw = pack2(acc[8 * j + 2 * q], acc[8 * j + 2 * q + 1]);
                    const uint32_t uw = pack2(acc[64 + 8 * j + 2 * q], acc[64 + 8 * j + 2 * q + 1]);
                    r[q] = hmul2(pack2(gelu_tanh(bflo(gw)), gelu_tanh(bfhi(gw))), uw);
                }
                stsm4(stg_base + (j >> 2) * 8192 + (sx ^ ((2 * j & 7) << 4)), r[0], r[1], r[2], r[3]);
            }
        } else {
            mbar_wait(bars + B_STGFREE + wg * 8, stg_phase); stg_phase ^= 1;
#pragma unroll
            for (int j = 0; j < 16; j++)
                stsm4(stg_base + (j >> 2) * 8192 + (sx ^ ((2 * j & 7) << 4)),
                      pack2(acc[8 * j], acc[8 * j + 1]), pack2(acc[8 * j + 2], acc[8 * j + 3]),
                      pack2(acc[8 * j + 4], acc[8 * j + 5]), pack2(acc[8 * j + 6], acc[8 * j + 7]));
        }
        fence_async_smem();
        CTR(5);
        bar_arrive(NB_ST + wg, 160);
    }
}

__global__ void __launch_bounds__(384, 1) k_work(const __grid_constant__ Params p) {
    extern __shared__ __align__(1024) unsigned char smem_raw[];
    const uint32_t sb = smem_u32(smem_raw);
    if (sb & 1023) __trap();
    const int warp = __shfl_sync(~0u, threadIdx.x >> 5, 0);
    int lane; asm volatile("mov.u32 %0, %%laneid;" : "=r"(lane));
    if (threadIdx.x == 0) {
        const uint32_t bars = sb + SM_BAR;
        for (int i = 0; i < W_NST; i++) { mbar_init(bars + B_FULL + i * 8, 1); mbar_init(bars + B_EMPTY + i * 8, 8); }
        mbar_init(bars + B_STGFREE, 1); mbar_init(bars + B_STGFREE + 8, 1); mbar_init(bars + B_REQ, 1); mbar_init(bars + B_RSP, 1);
        asm volatile("fence.mbarrier_init.release.cluster;" ::: "memory");
    }
    __syncthreads();
    if (warp < 8) {
        asm volatile("setmaxnreg.inc.sync.aligned.u32 232;");
        consumer(p, sb, warp, lane);
    } else {
        asm volatile("setmaxnreg.dec.sync.aligned.u32 40;");
        if (warp == 8) { if (lane == 0) producer(p, sb); }
        else if (warp < 11) store_warp(p, sb, warp - 9, lane);
        else scheduler(p, sb, lane);
    }
}

typedef CUresult (*EncodeFn)(CUtensorMap*, CUtensorMapDataType, cuuint32_t, void*, const cuuint64_t*, const cuuint64_t*,
                             const cuuint32_t*, const cuuint32_t*, CUtensorMapInterleave, CUtensorMapSwizzle,
                             CUtensorMapL2promotion, CUtensorMapFloatOOBfill);

static void make_map(EncodeFn enc, CUtensorMap* m, const void* ptr, uint64_t rows, uint64_t cols, uint32_t box_rows) {
    cuuint64_t dims[2] = {cols, rows};
    cuuint64_t strides[1] = {cols * 2};
    cuuint32_t box[2] = {64, box_rows};
    cuuint32_t es[2] = {1, 1};
    enc(m, CU_TENSOR_MAP_DATA_TYPE_BFLOAT16, 2, const_cast<void*>(ptr), dims, strides, box, es, CU_TENSOR_MAP_INTERLEAVE_NONE,
        CU_TENSOR_MAP_SWIZZLE_128B, CU_TENSOR_MAP_L2_PROMOTION_L2_256B, CU_TENSOR_MAP_FLOAT_OOB_FILL_NONE);
}
template <typename T> static void* sym_addr(T& sym) { void* p = nullptr; cudaGetSymbolAddress(&p, sym); return p; }

extern "C" void kernel_launch(void* const* d_in, const int* in_sizes, int n_in, void* d_out, int out_size) {
    static Params prm;
    static RecParams rp;
    static bool ready = false;
    static const void* key[14];
    bool same = ready;
    for (int i = 0; i < 13 && same; i++) same = key[i] == d_in[i];
    same = same && key[13] == d_out;
    if (!same) {
        void* fn = nullptr;
        cudaDriverEntryPointQueryResult qr;
        cudaGetDriverEntryPoint("cuTensorMapEncodeTiled", &fn, cudaEnableDefault, &qr);
        EncodeFn enc = (EncodeFn)fn;
        make_map(enc, &prm.tm_h, sym_addr(g_h), S_, D_, 64);
        make_map(enc, &prm.tm_kv, sym_addr(g_kv), S_, 2 * HD_, 64);
        make_map(enc, &prm.tm_kvm, sym_addr(g_kvm), NSEG * 8, 2 * HD_, 32);
        make_map(enc, &prm.tm_o, sym_addr(g_o), S_, HD_, 64);
        make_map(enc, &prm.tm_op, sym_addr(g_op), OP_ROWS, D_, 64);
        make_map(enc, &prm.tm_h2, sym_addr(g_h2), S_, D_, 64);
        make_map(enc, &prm.tm_act, sym_addr(g_act), S_, DF_, 64);
        make_map(enc, &prm.tm_x1, sym_addr(g_x1), S_, D_, 64);
        make_map(enc, &prm.tm_out, d_out, S_, D_, 64);
        make_map(enc, &prm.tm_wq, d_in[2], D_, HD_, 64);
        make_map(enc, &prm.tm_wk, d_in[3], D_, HD_, 64);
        make_map(enc, &prm.tm_wv, d_in[4], D_, HD_, 64);
        make_map(enc, &prm.tm_wo, d_in[5], HD_, D_, 64);
        make_map(enc, &prm.tm_wg, d_in[8], D_, DF_, 64);
        make_map(enc, &prm.tm_wu, d_in[9], D_, DF_, 64);
        make_map(enc, &prm.tm_wd, d_in[10], DF_, D_, 64);
        prm.x = (const bf16*)d_in[0];
        rp.mem0 = (const bf16*)d_in[1];
        rp.wq = (const bf16*)d_in[2]; rp.wk = (const bf16*)d_in[3]; rp.wv = (const bf16*)d_in[4]; rp.wo = (const bf16*)d_in[5];
        cudaFuncSetAttribute(k_work, cudaFuncAttributeMaxDynamicSharedMemorySize, SMEM_BYTES);
        cudaFuncSetAttribute(k_rec, cudaFuncAttributeMaxDynamicSharedMemorySize, R_SMEM);
        cudaFuncSetAttribute(k_rec, cudaFuncAttributeNonPortableClusterSizeAllowed, 1);
        {
            cudaLaunchConfig_t cfg = {};
            cfg.gridDim = dim3(128); cfg.blockDim = dim3(384); cfg.dynamicSmemBytes = R_SMEM;
            cudaLaunchAttribute at[1];
            at[0].id = cudaLaunchAttributeClusterDimension; at[0].val.clusterDim.x = 16; at[0].val.clusterDim.y = 1; at[0].val.clusterDim.z = 1;
            cfg.attrs = at; cfg.numAttrs = 1;
            int n = 0;
            cudaOccupancyMaxActiveClusters(&n, k_rec, &cfg);
            rp.ncl = n < 4 ? 4 : (n > 8 ? 8 : n);
        }
        for (int i = 0; i < 13; i++) key[i] = d_in[i];
        key[13] = d_out;
        ready = true;
    }
    cudaStream_t st = cudaStreamPerThread;
    PrefetchList pf;
    pf.p[0] = (const bf16*)d_in[3]; pf.p[1] = (const bf16*)d_in[4]; pf.p[2] = (const bf16*)d_in[2]; pf.p[3] = (const bf16*)d_in[5]; pf.p[4] = nullptr;
    k_mod<<<96, 256, 0, st>>>((const bf16*)d_in[11], (const bf16*)d_in[12], pf);
    {
        cudaLaunchConfig_t cfg = {};
        cfg.gridDim = dim3(S_ / 8); cfg.blockDim = dim3(256); cfg.stream = st;
        cudaLaunchAttribute at[1];
        at[0].id = cudaLaunchAttributeProgrammaticStreamSerialization; at[0].val.programmaticStreamSerializationAllowed = 1;
        cfg.attrs = at; cfg.numAttrs = 1;
        cudaLaunchKernelEx(&cfg, k_ln1, (const bf16*)d_in[0]);
    }
    auto launch_rec = [&]() {
        cudaLaunchConfig_t cfg = {};
        cfg.gridDim = dim3(16 * rp.ncl); cfg.blockDim = dim3(384); cfg.dynamicSmemBytes = R_SMEM; cfg.stream = st;
        cudaLaunchAttribute at[1];
        at[0].id = cudaLaunchAttributeClusterDimension; at[0].val.clusterDim.x = 16; at[0].val.clusterDim.y = 1; at[0].val.clusterDim.z = 1;
        cfg.attrs = at; cfg.numAttrs = 1;
        cudaLaunchKernelEx(&cfg, k_rec, rp);
    };
    auto launch_work = [&](int qmask, int pdl) {
        prm.qmask = qmask;
        cudaLaunchConfig_t cfg = {};
        cfg.gridDim = dim3(132); cfg.blockDim = dim3(384); cfg.dynamicSmemBytes = SMEM_BYTES; cfg.stream = st;
        cudaLaunchAttribute at[1];
        at[0].id = cudaLaunchAttributeProgrammaticStreamSerialization; at[0].val.programmaticStreamSerializationAllowed = 1;
        cfg.attrs = at; cfg.numAttrs = pdl;
        cudaLaunchKernelEx(&cfg, k_work, prm);
    };
    launch_rec();
    launch_work(0x3f, 1);
}
```

```cpp
#include <cuda_runtime.h>
#include <cuda_bf16.h>
#include <cuda.h>
#include <stdint.h>

typedef __nv_bfloat16 bf16;

constexpr int S_ = 2048, D_ = 512, H_ = 32, DH_ = 128, HD_ = 4096, NSEG = 64, DF_ = 1792;
constexpr int NRB = 16;
constexpr int OSPLIT = 4;

__device__ __align__(1024) bf16 g_h[S_ * D_];
__device__ __align__(1024) bf16 g_kv[S_ * 2 * HD_];
__device__ __align__(1024) bf16 g_kvm[NSEG * 8 * 2 * HD_];
__device__ __align__(1024) bf16 g_o[S_ * HD_];
#define FINE_RB_ 14
constexpr int FINE_RB = FINE_RB_;
constexpr int OSPLIT2 = 16;
constexpr int OP_ROWS = OSPLIT * S_ + OSPLIT2 * (NRB - FINE_RB) * 128;
__device__ __align__(1024) bf16 g_op[OP_ROWS * D_];
__device__ __align__(1024) bf16 g_x1[S_ * D_];
__device__ __align__(1024) bf16 g_h2[S_ * D_];
__device__ __align__(1024) bf16 g_act[S_ * DF_];
__device__ __align__(1024) bf16 g_mod[6 * D_];
__device__ uint32_t g_Fraw[131072 + 65536 + 2048];
#define g_F ((uint32_t*)(((uint64_t)g_Fraw + 0x7FFFFull) & ~0x7FFFFull))
constexpr int F_KV = 0, F_MEM = 32, F_O = 64, F_OP = 96, F_H2 = 128, F_ACT = 160, F_CLAIM = 192  , F_SIDE = 384  , F_TOTAL = 448;
__device__ __align__(128) unsigned int g_flags[F_TOTAL];
#define TR(j, i) do {} while (0)

__device__ __forceinline__ uint32_t smem_u32(const void* p) { return (uint32_t)__cvta_generic_to_shared(p); }
__device__ __forceinline__ uint32_t clk32() { uint32_t c; asm volatile("mov.u32 %0, %%clock;" : "=r"(c)); return c; }
__device__ __forceinline__ uint32_t mapa_u32(uint32_t addr, uint32_t rank) {
    uint32_t r; asm volatile("mapa.shared::cluster.u32 %0, %1, %2;" : "=r"(r) : "r"(addr), "r"(rank)); return r;
}
__device__ __forceinline__ void mbar_init(uint32_t bar, uint32_t cnt) {
    asm volatile("mbarrier.init.shared::cta.b64 [%0], %1;" :: "r"(bar), "r"(cnt) : "memory");
}
__device__ __forceinline__ void mbar_inval(uint32_t bar) {
    asm volatile("mbarrier.inval.shared::cta.b64 [%0];" :: "r"(bar) : "memory");
}
__device__ __forceinline__ void mbar_expect_tx(uint32_t bar, uint32_t bytes) {
    asm volatile("mbarrier.arrive.expect_tx.shared::cta.b64 _, [%0], %1;" :: "r"(bar), "r"(bytes) : "memory");
}
__device__ __forceinline__ void mbar_arrive(uint32_t bar) {
    asm volatile("mbarrier.arrive.shared::cta.b64 _, [%0];" :: "r"(bar) : "memory");
}
__device__ __forceinline__ bool mbar_try_wait(uint32_t bar, uint32_t parity) {
    uint32_t ok;
    asm volatile("{\n.reg .pred p;\nmbarrier.try_wait.parity.shared::cta.b64 p, [%1], %2;\nselp.u32 %0, 1, 0, p;\n}"
                 : "=r"(ok) : "r"(bar), "r"(parity) : "memory");
    return ok;
}
__device__ __forceinline__ bool mbar_try_wait_cluster(uint32_t bar, uint32_t parity) {
    uint32_t ok;
    asm volatile("{\n.reg .pred p;\nmbarrier.try_wait.parity.acquire.cluster.shared::cta.b64 p, [%1], %2;\nselp.u32 %0, 1, 0, p;\n}"
                 : "=r"(ok) : "r"(bar), "r"(parity) : "memory");
    return ok;
}
constexpr int SPIN_LIMIT = 1 << 18;
#define TIMEOUT(code, info) do {} while (0)
__device__ __forceinline__ void mbar_wait(uint32_t bar, uint32_t parity) {
    int g = 0;
#pragma unroll 1
    while (!mbar_try_wait(bar, parity)) { if (++g >= SPIN_LIMIT) { TIMEOUT(0, bar & 255); break; } }
}
__device__ __forceinline__ void mbar_wait_cluster(uint32_t bar, uint32_t parity) {
    int g = 0;
#pragma unroll 1
    while (!mbar_try_wait_cluster(bar, parity)) { if (++g >= SPIN_LIMIT) { TIMEOUT(1, bar & 255); break; } }
}
__device__ __forceinline__ void bar_sync(int id, int n) { asm volatile("bar.sync %0, %1;" :: "r"(id), "r"(n) : "memory"); }
__device__ __forceinline__ void bar_arrive(int id, int n) { asm volatile("bar.arrive %0, %1;" :: "r"(id), "r"(n) : "memory"); }
__device__ __forceinline__ void cluster_sync_all() {
    asm volatile("barrier.cluster.arrive.aligned;\nbarrier.cluster.wait.aligned;" ::: "memory");
}
__device__ __forceinline__ void st_async_v2(uint32_t addr, float a, float b, uint32_t bar) {
    asm volatile("st.async.weak.shared::cluster.mbarrier::complete_tx::bytes.v2.f32 [%0], {%1,%2}, [%3];"
                 :: "r"(addr), "f"(a), "f"(b), "r"(bar) : "memory");
}
__device__ __forceinline__ void st_async_v4(uint32_t addr, uint4 v, uint32_t bar) {
    asm volatile("st.async.weak.shared::cluster.mbarrier::complete_tx::bytes.v4.b32 [%0], {%1,%2,%3,%4}, [%5];"
                 :: "r"(addr), "r"(v.x), "r"(v.y), "r"(v.z), "r"(v.w), "r"(bar) : "memory");
}
__device__ __forceinline__ uint2 ldg_relaxed2(const uint2* p) {
    uint2 v;
    asm volatile("ld.relaxed.gpu.global.v2.b32 {%0,%1}, [%2];" : "=r"(v.x), "=r"(v.y) : "l"(p) : "memory");
    return v;
}
__device__ __forceinline__ void stg_relaxed2(uint2* p, uint2 v) {
    asm volatile("st.relaxed.gpu.global.v2.b32 [%0], {%1,%2};" :: "l"(p), "r"(v.x), "r"(v.y) : "memory");
}
__device__ __forceinline__ uint4 ldg_relaxed(const uint4* p) {
    uint4 v;
    asm volatile("ld.relaxed.gpu.global.v4.b32 {%0,%1,%2,%3}, [%4];" : "=r"(v.x), "=r"(v.y), "=r"(v.z), "=r"(v.w) : "l"(p) : "memory");
    return v;
}
__device__ __forceinline__ void stg_relaxed(uint4* p, uint4 v) {
    asm volatile("st.relaxed.gpu.global.v4.b32 [%0], {%1,%2,%3,%4};" :: "l"(p), "r"(v.x), "r"(v.y), "r"(v.z), "r"(v.w) : "memory");
}
__device__ __forceinline__ void stg_relaxed32(uint32_t* p, uint32_t v) {
    asm volatile("st.relaxed.gpu.global.b32 [%0], %1;" :: "l"(p), "r"(v) : "memory");
}
__device__ __forceinline__ uint32_t ldg_relaxed32(const uint32_t* p) {
    uint32_t v; asm volatile("ld.relaxed.gpu.global.b32 %0, [%1];" : "=r"(v) : "l"(p) : "memory"); return v;
}
__device__ __forceinline__ unsigned int ld_acquire(const unsigned int* p) {
    unsigned int v; asm volatile("ld.acquire.gpu.global.u32 %0, [%1];" : "=r"(v) : "l"(p) : "memory"); return v;
}
__device__ __forceinline__ void red_release(unsigned int* p, unsigned int v) {
    asm volatile("red.release.gpu.global.add.u32 [%0], %1;" :: "l"(p), "r"(v) : "memory");
}
__device__ __forceinline__ void wait_flag(int idx, unsigned int target) {
    const unsigned int* p = &g_flags[idx];
    int g = 0;
#pragma unroll 1
    while (ld_acquire(p) < target) { __nanosleep(20); if (++g >= 64 * SPIN_LIMIT) { TIMEOUT(2, idx); break; } }
}
__device__ __forceinline__ void cp_async16(uint32_t dst, const void* src) {
    asm volatile("cp.async.cg.shared.global [%0], [%1], 16;" :: "r"(dst), "l"(src) : "memory");
}
__device__ __forceinline__ void cp_async_commit() { asm volatile("cp.async.commit_group;" ::: "memory"); }
template <int N> __device__ __forceinline__ void cp_async_wait() { asm volatile("cp.async.wait_group %0;" :: "n"(N) : "memory"); }
__device__ __forceinline__ void ldsm4(uint32_t& r0, uint32_t& r1, uint32_t& r2, uint32_t& r3, uint32_t addr) {
    asm volatile("ldmatrix.sync.aligned.m8n8.x4.shared.b16 {%0,%1,%2,%3}, [%4];" : "=r"(r0), "=r"(r1), "=r"(r2), "=r"(r3) : "r"(addr) : "memory");
}
__device__ __forceinline__ void ldsm4t(uint32_t& r0, uint32_t& r1, uint32_t& r2, uint32_t& r3, uint32_t addr) {
    asm volatile("ldmatrix.sync.aligned.m8n8.x4.trans.shared.b16 {%0,%1,%2,%3}, [%4];" : "=r"(r0), "=r"(r1), "=r"(r2), "=r"(r3) : "r"(addr) : "memory");
}
__device__ __forceinline__ void ldsm2t(uint32_t& r0, uint32_t& r1, uint32_t addr) {
    asm volatile("ldmatrix.sync.aligned.m8n8.x2.trans.shared.b16 {%0,%1}, [%2];" : "=r"(r0), "=r"(r1) : "r"(addr) : "memory");
}
__device__ __forceinline__ void stsm4(uint32_t addr, uint32_t r0, uint32_t r1, uint32_t r2, uint32_t r3) {
    asm volatile("stmatrix.sync.aligned.m8n8.x4.shared.b16 [%0], {%1,%2,%3,%4};" :: "r"(addr), "r"(r0), "r"(r1), "r"(r2), "r"(r3) : "memory");
}
__device__ __forceinline__ void stsm2t(uint32_t addr, uint32_t r0, uint32_t r1) {
    asm volatile("stmatrix.sync.aligned.m8n8.x2.trans.shared.b16 [%0], {%1,%2};" :: "r"(addr), "r"(r0), "r"(r1) : "memory");
}
__device__ __forceinline__ void mma16816(float* d, uint32_t a0, uint32_t a1, uint32_t a2, uint32_t a3, uint32_t b0, uint32_t b1) {
    asm volatile("mma.sync.aligned.m16n8k16.row.col.f32.bf16.bf16.f32 {%0,%1,%2,%3}, {%4,%5,%6,%7}, {%8,%9}, {%0,%1,%2,%3};"
                 : "+f"(d[0]), "+f"(d[1]), "+f"(d[2]), "+f"(d[3]) : "r"(a0), "r"(a1), "r"(a2), "r"(a3), "r"(b0), "r"(b1));
}
__device__ __forceinline__ void mma1688(float* d, uint32_t a0, uint32_t a1, uint32_t b0) {
    asm volatile("mma.sync.aligned.m16n8k8.row.col.f32.bf16.bf16.f32 {%0,%1,%2,%3}, {%4,%5}, {%6}, {%0,%1,%2,%3};"
                 : "+f"(d[0]), "+f"(d[1]), "+f"(d[2]), "+f"(d[3]) : "r"(a0), "r"(a1), "r"(b0));
}
__device__ __forceinline__ void mma16816h(float* d, uint32_t a0, uint32_t a2, uint32_t b0, uint32_t b1) {
    asm volatile("{\n.reg .b32 ju, jv;\nmma.sync.aligned.m16n8k16.row.col.f32.bf16.bf16.f32 {%0,%1,%2,%3}, {%4,ju,%5,jv}, {%6,%7}, {%0,%1,%2,%3};\n}"
                 : "+f"(d[0]), "+f"(d[1]), "+f"(d[2]), "+f"(d[3]) : "r"(a0), "r"(a2), "r"(b0), "r"(b1));
}
__device__ __forceinline__ void mma1688h(float* d, uint32_t a0, uint32_t b0) {
    asm volatile("{\n.reg .b32 ju;\nmma.sync.aligned.m16n8k8.row.col.f32.bf16.bf16.f32 {%0,%1,%2,%3}, {%4,ju}, {%5}, {%0,%1,%2,%3};\n}"
                 : "+f"(d[0]), "+f"(d[1]), "+f"(d[2]), "+f"(d[3]) : "r"(a0), "r"(b0));
}
__device__ __forceinline__ uint32_t pack2(float lo, float hi) {
    uint32_t r; asm("cvt.rn.bf16x2.f32 %0, %1, %2;" : "=r"(r) : "f"(hi), "f"(lo)); return r;
}
__device__ __forceinline__ float bflo(uint32_t w) { return __uint_as_float(w << 16); }
__device__ __forceinline__ float bfhi(uint32_t w) { return __uint_as_float(w & 0xffff0000u); }
__device__ __forceinline__ float rbf(float x) { return __bfloat162float(__float2bfloat16_rn(x)); }
__device__ __forceinline__ float ex2(float x) { float y; asm("ex2.approx.ftz.f32 %0, %1;" : "=f"(y) : "f"(x)); return y; }
__device__ __forceinline__ void sts128(uint32_t addr, uint4 v) {
    asm volatile("st.shared.v4.b32 [%0], {%1,%2,%3,%4};" :: "r"(addr), "r"(v.x), "r"(v.y), "r"(v.z), "r"(v.w) : "memory");
}
__device__ __forceinline__ uint4 lds128(uint32_t addr) {
    uint4 v; asm volatile("ld.shared.v4.b32 {%0,%1,%2,%3}, [%4];" : "=r"(v.x), "=r"(v.y), "=r"(v.z), "=r"(v.w) : "r"(addr) : "memory"); return v;
}
__device__ __forceinline__ float2 lds64f(uint32_t addr) {
    float2 v; asm volatile("ld.shared.v2.f32 {%0,%1}, [%2];" : "=f"(v.x), "=f"(v.y) : "r"(addr) : "memory"); return v;
}
__device__ __forceinline__ float lds32f(uint32_t addr) {
    float v; asm volatile("ld.shared.f32 %0, [%1];" : "=f"(v) : "r"(addr) : "memory"); return v;
}
__device__ __forceinline__ uint32_t lds32(uint32_t addr) {
    uint32_t v; asm volatile("ld.shared.b32 %0, [%1];" : "=r"(v) : "r"(addr) : "memory"); return v;
}
__device__ __forceinline__ void sts32(uint32_t addr, uint32_t v) { asm volatile("st.shared.b32 [%0], %1;" :: "r"(addr), "r"(v) : "memory"); }
__device__ __forceinline__ void sts64f(uint32_t addr, float a, float b) { asm volatile("st.shared.v2.f32 [%0], {%1,%2};" :: "r"(addr), "f"(a), "f"(b) : "memory"); }

__device__ __forceinline__ void tma_load2d(uint32_t dst, const CUtensorMap* tm, int c0, int c1, uint32_t bar) {
    asm volatile("cp.async.bulk.tensor.2d.shared::cluster.global.mbarrier::complete_tx::bytes [%0], [%1, {%3, %4}], [%2];"
                 :: "r"(dst), "l"(tm), "r"(bar), "r"(c0), "r"(c1) : "memory");
}
__device__ __forceinline__ void tma_store2d(const CUtensorMap* tm, uint32_t src, int c0, int c1) {
    asm volatile("cp.async.bulk.tensor.2d.global.shared::cta.bulk_group [%0, {%2, %3}], [%1];"
                 :: "l"(tm), "r"(src), "r"(c0), "r"(c1) : "memory");
}
__device__ __forceinline__ void bulk_commit() { asm volatile("cp.async.bulk.commit_group;" ::: "memory"); }
__device__ __forceinline__ void bulk_wait0() { asm volatile("cp.async.bulk.wait_group 0;" ::: "memory"); }
__device__ __forceinline__ void fence_async_smem() { asm volatile("fence.proxy.async.shared::cta;" ::: "memory"); }
__device__ __forceinline__ void fence_async_all() { asm volatile("fence.proxy.async;" ::: "memory"); }

__device__ __forceinline__ void wg_fence() { asm volatile("wgmma.fence.sync.aligned;" ::: "memory"); }
__device__ __forceinline__ void wg_commit() { asm volatile("wgmma.commit_group.sync.aligned;" ::: "memory"); }
__device__ __forceinline__ void wg_wait0() { asm volatile("wgmma.wait_group.sync.aligned 0;" ::: "memory"); }
__device__ __forceinline__ uint64_t mkdesc(uint32_t saddr, uint32_t lbo, uint32_t sbo) {
    return (uint64_t)((saddr & 0x3FFFF) >> 4) | ((uint64_t)(lbo >> 4) << 16) | ((uint64_t)(sbo >> 4) << 32) | (1ull << 62);
}
#define ACC8(i) "+f"(d[i]), "+f"(d[i + 1]), "+f"(d[i + 2]), "+f"(d[i + 3]), "+f"(d[i + 4]), "+f"(d[i + 5]), "+f"(d[i + 6]), "+f"(d[i + 7])
__device__ __forceinline__ void wgmma_n256(float* d, uint64_t da, uint64_t db, int scale_d) {
    asm volatile(
        "{\n.reg .pred p;\nsetp.ne.b32 p, %130, 0;\n"
        "wgmma.mma_async.sync.aligned.m64n256k16.f32.bf16.bf16 "
        "{%0,%1,%2,%3,%4,%5,%6,%7,%8,%9,%10,%11,%12,%13,%14,%15,%16,%17,%18,%19,%20,%21,%22,%23,%24,%25,%26,%27,%28,%29,%30,%31,"
        "%32,%33,%34,%35,%36,%37,%38,%39,%40,%41,%42,%43,%44,%45,%46,%47,%48,%49,%50,%51,%52,%53,%54,%55,%56,%57,%58,%59,%60,%61,%62,%63,"
        "%64,%65,%66,%67,%68,%69,%70,%71,%72,%73,%74,%75,%76,%77,%78,%79,%80,%81,%82,%83,%84,%85,%86,%87,%88,%89,%90,%91,%92,%93,%94,%95,"
        "%96,%97,%98,%99,%100,%101,%102,%103,%104,%105,%106,%107,%108,%109,%110,%111,%112,%113,%114,%115,%116,%117,%118,%119,%120,%121,%122,%123,%124,%125,%126,%127}, "
        "%128, %129, p, 1, 1, 0, 1;\n}"
        : ACC8(0), ACC8(8), ACC8(16), ACC8(24), ACC8(32), ACC8(40), ACC8(48), ACC8(56),
          ACC8(64), ACC8(72), ACC8(80), ACC8(88), ACC8(96), ACC8(104), ACC8(112), ACC8(120)
        : "l"(da), "l"(db), "r"(scale_d));
}
__device__ __forceinline__ void wgmma_n128(float* d, uint64_t da, uint64_t db, int scale_d) {
    asm volatile(
        "{\n.reg .pred p;\nsetp.ne.b32 p, %66, 0;\n"
        "wgmma.mma_async.sync.aligned.m64n128k16.f32.bf16.bf16 "
        "{%0,%1,%2,%3,%4,%5,%6,%7,%8,%9,%10,%11,%12,%13,%14,%15,%16,%17,%18,%19,%20,%21,%22,%23,%24,%25,%26,%27,%28,%29,%30,%31,"
        "%32,%33,%34,%35,%36,%37,%38,%39,%40,%41,%42,%43,%44,%45,%46,%47,%48,%49,%50,%51,%52,%53,%54,%55,%56,%57,%58,%59,%60,%61,%62,%63}, "
        "%64, %65, p, 1, 1, 0, 1;\n}"
        : ACC8(0), ACC8(8), ACC8(16), ACC8(24), ACC8(32), ACC8(40), ACC8(48), ACC8(56)
        : "l"(da), "l"(db), "r"(scale_d));
}

__device__ __forceinline__ void wgmma_n64(float* d, uint64_t da, uint64_t db) {
    asm volatile(
        "wgmma.mma_async.sync.aligned.m64n64k16.f32.bf16.bf16 "
        "{%0,%1,%2,%3,%4,%5,%6,%7,%8,%9,%10,%11,%12,%13,%14,%15,%16,%17,%18,%19,%20,%21,%22,%23,%24,%25,%26,%27,%28,%29,%30,%31}, "
        "%32, %33, 1, 1, 1, 0, 1;"
        : ACC8(0), ACC8(8), ACC8(16), ACC8(24)
        : "l"(da), "l"(db));
}
__device__ __forceinline__ void wgmma_n8_ta(float* d, uint64_t da, uint64_t db, int scale_d) {
    asm volatile(
        "{\n.reg .pred p;\nsetp.ne.b32 p, %6, 0;\n"
        "wgmma.mma_async.sync.aligned.m64n8k16.f32.bf16.bf16 {%0,%1,%2,%3}, %4, %5, p, 1, 1, 1, 0;\n}"
        : "+f"(d[0]), "+f"(d[1]), "+f"(d[2]), "+f"(d[3]) : "l"(da), "l"(db), "r"(scale_d));
}

struct PrefetchList { const bf16* p[5]; };
__global__ void __launch_bounds__(256) k_mod(const bf16* __restrict__ c, const bf16* __restrict__ w_mod, const PrefetchList pf) {
    asm volatile("griddepcontrol.launch_dependents;");
    __shared__ float s_c[D_];
    __shared__ float s_red[64][33];
    const int tid = threadIdx.x;
    const int cq = tid & 3, rg = tid >> 2;
    uint4 w[8];
#pragma unroll
    for (int i = 0; i < 8; i++)
        w[i] = __ldg((const uint4*)(w_mod + (size_t)(rg * 8 + i) * (6 * D_) + blockIdx.x * 32 + cq * 8));
    for (int i = tid; i < D_; i += 256) {
        float v = __bfloat162float(c[i]);
        s_c[i] = rbf(v / (1.f + __expf(-v)));
    }
    {
        const int gt = blockIdx.x * 256 + tid, nt = gridDim.x * 256;
        for (int i = gt; i < F_TOTAL; i += nt) g_flags[i] = 0;
        for (int i = gt; i < 65536 + 2048; i += nt) g_F[i] = 0;
        if (tid < 11) {
            const int i = tid * gridDim.x + blockIdx.x;
            if (i < 1024) asm volatile("cp.async.bulk.prefetch.L2.global [%0], %1;" :: "l"(pf.p[i >> 8] + (size_t)(i & 255) * 8192), "r"(16384) : "memory");
        }
    }
    __syncthreads();
    float a[8];
#pragma unroll
    for (int j = 0; j < 8; j++) a[j] = 0.f;
#pragma unroll
    for (int i = 0; i < 8; i++) {
        float cv = s_c[rg * 8 + i];
        a[0] += cv * bflo(w[i].x); a[1] += cv * bfhi(w[i].x); a[2] += cv * bflo(w[i].y); a[3] += cv * bfhi(w[i].y);
        a[4] += cv * bflo(w[i].z); a[5] += cv * bfhi(w[i].z); a[6] += cv * bflo(w[i].w); a[7] += cv * bfhi(w[i].w);
    }
#pragma unroll
    for (int j = 0; j < 8; j++) s_red[rg][cq * 8 + j] = a[j];
    __syncthreads();
    if (tid < 32) {
        float s = 0.f;
#pragma unroll 8
        for (int r = 0; r < 64; r++) s += s_red[r][tid];
        g_mod[blockIdx.x * 32 + tid] = __float2bfloat16_rn(s);
    }
}

__device__ __forceinline__ uint32_t hadd2(uint32_t a, uint32_t b) { uint32_t r; asm("add.rn.bf16x2 %0, %1, %2;" : "=r"(r) : "r"(a), "r"(b)); return r; }
__device__ __forceinline__ uint32_t hsub2(uint32_t a, uint32_t b) { uint32_t r; asm("sub.rn.bf16x2 %0, %1, %2;" : "=r"(r) : "r"(a), "r"(b)); return r; }
__device__ __forceinline__ uint32_t hmul2(uint32_t a, uint32_t b) { uint32_t r; asm("mul.rn.bf16x2 %0, %1, %2;" : "=r"(r) : "r"(a), "r"(b)); return r; }
__device__ __forceinline__ void load_mod8(const bf16* m, int lane, uint32_t* v) {
    const uint4 a = __ldcg((const uint4*)m + lane), b = __ldcg((const uint4*)m + 32 + lane);
    v[0] = a.x; v[1] = a.y; v[2] = a.z; v[3] = a.w; v[4] = b.x; v[5] = b.y; v[6] = b.z; v[7] = b.w;
}
__device__ __forceinline__ void ln_stats(const uint32_t* x, uint32_t& mu2, float& rden) {
    float s = 0.f;
#pragma unroll
    for (int i = 0; i < 8; i++) s += bflo(x[i]) + bfhi(x[i]);
#pragma unroll
    for (int o = 16; o > 0; o >>= 1) s += __shfl_xor_sync(~0u, s, o);
    const float mean = s * (1.f / D_);
    float q = 0.f;
#pragma unroll
    for (int i = 0; i < 8; i++) { const float d0 = bflo(x[i]) - mean, d1 = bfhi(x[i]) - mean; q = fmaf(d0, d0, q); q = fmaf(d1, d1, q); }
#pragma unroll
    for (int o = 16; o > 0; o >>= 1) q += __shfl_xor_sync(~0u, q, o);
    mu2 = pack2(mean, mean);
    rden = __frcp_rn(rbf(__fsqrt_rn(rbf(rbf(q * (1.f / D_)) + 1e-5f))));
}
__device__ __forceinline__ void ln_apply(const uint32_t* x, uint32_t mu2, float rden, const uint32_t* c1, const uint32_t* sm, uint32_t* r) {
#pragma unroll
    for (int i = 0; i < 8; i++) {
        const uint32_t d = hsub2(x[i], mu2);
        r[i] = hadd2(hmul2(pack2(bflo(d) * rden, bfhi(d) * rden), c1[i]), sm[i]);
    }
}

__global__ void __launch_bounds__(256) k_ln1(const bf16* __restrict__ x) {
    const int lane = threadIdx.x & 31, row = blockIdx.x * 8 + (threadIdx.x >> 5);
    const uint4* xr = (const uint4*)(x + (size_t)row * D_);
    const uint4 a = __ldg(xr + lane), b = __ldg(xr + 32 + lane);
    const uint32_t v[8] = {a.x, a.y, a.z, a.w, b.x, b.y, b.z, b.w};
    uint32_t mu2; float rden;
    ln_stats(v, mu2, rden);
    asm volatile("griddepcontrol.wait;" ::: "memory");
    uint32_t c1[8], sm[8], r[8];
    load_mod8(g_mod + D_, lane, c1);
    load_mod8(g_mod, lane, sm);
#pragma unroll
    for (int i = 0; i < 8; i++) c1[i] = hadd2(c1[i], 0x3F803F80u);
    ln_apply(v, mu2, rden, c1, sm, r);
    uint4* hr = (uint4*)(g_h + (size_t)row * D_);
    hr[lane] = make_uint4(r[0], r[1], r[2], r[3]); hr[32 + lane] = make_uint4(r[4], r[5], r[6], r[7]);
}

struct __align__(64) Params {
    CUtensorMap tm_h, tm_kv, tm_kvm, tm_o, tm_op, tm_h2, tm_act, tm_x1, tm_out;
    CUtensorMap tm_wq, tm_wk, tm_wv, tm_wo, tm_wg, tm_wu, tm_wd;
    const bf16* x;
    int qmask;
};

constexpr int R_NST = 3;
constexpr uint32_t R_WV = 0, R_MEM = 65536, R_KX = 73728, R_VX = R_KX + R_NST * 4096,
                   R_KMS = R_VX + R_NST * 4096  , R_VMS = R_KMS + 1024,
                   R_QS = R_KMS + 4096, R_OS = R_QS + 1024, R_SX = R_OS + 1024, R_BAR = R_SX + 2560,
                   R_RS = 107520  , R_VP = R_RS + 8192  ,
                   R_STG = R_VP + 8192  , R_SMEM = R_STG + 98304;
static_assert((R_KMS & 4095) == 0, "smem");
static_assert(R_BAR + 64 <= R_RS, "smem");
constexpr uint32_t RB_SX = R_BAR, RB_V = R_BAR + 8, RB_E = R_BAR + 16, RB_A = R_BAR + 24, RB_ROLE = R_BAR + 32, RB_A1 = R_BAR + 40;
constexpr int W_NST = 3;
constexpr uint32_t W_STAGE = 49152, W_STG = W_NST * W_STAGE, W_END = W_STG + 65536;
constexpr uint32_t SM_BAR = W_END;
constexpr uint32_t SMEM_BYTES = W_END + 1024;
constexpr uint32_t B_FULL = 0, B_EMPTY = 32, B_STGFREE = 64, B_REQ = 80, B_RSP = 88, B_NEXT = 96, B_RING = 128;
#define PICK_AHEAD 2

constexpr int NB_X = 11  , NB_Y = 1, NB_Z = 5, NB_B = 2, NB_C = 3, NB_D = 4, NB_W0 = 6  , NB_ST = 9  ;

__device__ __forceinline__ int pos_of_d(int d) {
    const int rem = d & 31;
    return (d & ~31) + ((rem & 7) >> 1) * 8 + (rem & 1) * 4 + (rem >> 3);
}

#define PROF(i) do {} while (0)
#define PROFG(i) do {} while (0)
#define OPAQUE(x) asm volatile("" : "+r"(x))
#define FENCE_SCHED(x) do { if ((x) == 0u) asm volatile("trap;"); } while (0)
#define VK0_ 4
constexpr int VK0 = VK0_;
constexpr int NOFF = 8;
#define VDELAY -1
#define POLL_GAP 90

struct RecParams { const bf16 *mem0, *wq, *wk, *wv, *wo; int ncl; };

__device__ __forceinline__ void rec_qk(const RecParams& p, const uint32_t sb, const int cta, const int warp, int lane, const int sel) {
    const int crank = cta & 15, cl = cta >> 4, rank = cta & 1;
    const int kh = warp >> 2, aa = warp & 3;
    uint32_t wa[2][16][4];
    const uint32_t stg = sb + R_STG + kh * 32768;
    {
        const int t128 = aa * 32 + lane;
        const int row = (lane >> 4) * 8 + (lane & 7);
        const int ch = t128 & 7;
        const size_t goff = (size_t)kh * 256 * HD_ + cta * 64 + ch * 8;
#pragma unroll 4
        for (int dd = 0; dd < 16; dd++) {
            const int d = dd * 16 + (t128 >> 3), pp = pos_of_d(d);
            cp_async16(sb + R_WV + kh * 32768 + pp * 128 + ((ch ^ (pp & 7)) << 4), p.wv + goff + (size_t)d * HD_);
        }
        cp_async_commit();
#pragma unroll 4
        for (int dd = 0; dd < 16; dd++) {
            const int d = dd * 16 + (t128 >> 3), pp = pos_of_d(d);
            cp_async16(stg + pp * 128 + ((ch ^ (pp & 7)) << 4), p.wq + goff + (size_t)d * HD_);
        }
        cp_async_commit();
        {
            const int i0 = (warp * 32 + lane) * 16, tok = i0 >> 9;
            const uint4 m0 = __ldg((const uint4*)(p.mem0 + i0)), m1 = __ldg((const uint4*)(p.mem0 + i0 + 8));
            const uint32_t mw[8] = {m0.x, m0.y, m0.z, m0.w, m1.x, m1.y, m1.z, m1.w};
#pragma unroll
            for (int e = 0; e < 16; e++) {
                const int pp = pos_of_d((i0 & 511) + e);
                const unsigned short v = (unsigned short)(mw[e >> 1] >> ((e & 1) * 16));
                asm volatile("st.shared.u16 [%0], %1;" :: "r"(sb + R_MEM + (pp >> 3) * 128 + tok * 16 + (pp & 7) * 2), "h"(v) : "memory");
            }
        }
        cp_async_wait<1>();
        bar_sync(NB_W0 + kh, 128);
        const uint32_t fv = row * 128 + (((2 * aa + ((lane >> 3) & 1)) ^ (row & 7)) << 4);
#pragma unroll
        for (int ks = 0; ks < 16; ks++) ldsm4t(wa[0][ks][0], wa[0][ks][1], wa[0][ks][2], wa[0][ks][3], sb + R_WV + kh * 32768 + fv + ks * 2048);
        bar_sync(NB_W0 + kh, 128);
#pragma unroll
        for (int ks = 0; ks < 16; ks++)
            sts128(sb + R_WV + kh * 32768 + (aa * 16 + ks) * 512 + lane * 16, make_uint4(wa[0][ks][0], wa[0][ks][1], wa[0][ks][2], wa[0][ks][3]));
        const uint32_t fo = stg + row * 128 + (((4 * (aa & 1) + ((lane >> 3) & 1)) ^ (row & 7)) << 4);
#pragma unroll 1
        for (int m = 0; m < 2; m++) {
            cp_async_wait<0>();
            bar_sync(NB_W0 + kh, 128);
            if ((aa >> 1) == m) {
#pragma unroll
                for (int ks = 0; ks < 16; ks++) {
                    ldsm4t(wa[0][ks][0], wa[0][ks][1], wa[0][ks][2], wa[0][ks][3], fo + ks * 2048);
                    ldsm4t(wa[1][ks][0], wa[1][ks][1], wa[1][ks][2], wa[1][ks][3], (fo ^ 32) + ks * 2048);
                }
            }
            bar_sync(NB_W0 + kh, 128);
            if (m == 0) {
#pragma unroll 4
                for (int dd = 0; dd < 16; dd++) {
                    const int d = dd * 16 + (t128 >> 3), pp = pos_of_d(d);
                    cp_async16(stg + pp * 128 + ((ch ^ (pp & 7)) << 4), p.wk + goff + (size_t)d * HD_);
                }
                cp_async_commit();
            }
        }
    }
    const uint32_t tab = stg + (aa * 32 + lane) * 16;
    {
        const uint32_t l7 = lane & 7, l8 = lane >> 3, g = lane >> 2, t = lane & 3;
        const uint32_t t0 = l7 * 128 + ((l8 ^ l7) << 4);
        const uint32_t tq = l7 * 128 + (((l8 >> 1) ^ l7) << 4);
        const uint32_t bq = warp >> 1, tp = warp & 1;
        uint4 v;
        v.x = sb + (aa < 2 ? R_QS : R_KMS) + l7 * 128 + (((4 * (aa & 1) + 2 * kh + (l8 & 1)) ^ l7) << 4);
        v.y = sb + R_QS + tq;
        v.z = sb + (warp == 0 ? R_KMS : R_KX + (warp - 1) * 1024) + t0;
        v.w = mapa_u32(sb + R_SX + (rank * 5 + warp) * 256 + lane * 8, crank ^ 1);
        sts128(tab, v);
        sts128(tab + 2048, make_uint4(sb + lane * 16 + R_MEM + kh * 4096, sb + lane * 16 + R_WV + warp * 8192,
                                      sb + lane * 16 + R_VP + warp * 512, sb + lane * 16 + R_VP + 4096 + (warp ^ 4) * 512));
        const uint32_t src = (l8 >> 1) * 8 + l7;
        const uint32_t L = bq * 8 + 2 * tp + (l8 & 1);
        const uint32_t d0 = (crank + ((t >> 1) | (g & 6))) & 15;
        v.x = sb + R_RS + src * 512 + ((L ^ (src & 7)) << 4);
        v.y = mapa_u32(sb + R_MEM + (crank * 4 + bq) * 128 + (4 * tp + 2 * (t & 1) + (g & 1)) * 16, d0);
        v.z = mapa_u32(sb + ((crank & 2) ? RB_A1 : RB_A), d0);
        v.w = lane;
        sts128(tab + 4096, v);
        const uint64_t wr = (uint64_t)(g_F + ((crank * 2 + ((crank ^ (crank >> 3) ^ sel) & 1)) * 1024 + warp * 128 + cl * 32 + lane));
        sts128(tab + 6144, make_uint4((uint32_t)wr, (uint32_t)(wr >> 32), (uint32_t)((((cl + 1) & 3) - cl) * 128), (uint32_t)((((cl + 2) & 3) - cl) * 128)));
        sts32(tab + 8192, (uint32_t)((((cl + 3) & 3) - cl) * 128));
#pragma unroll
        for (int i = 0; i < NOFF; i++)
            sts128(tab + 10240 + i * 2048, make_uint4(wa[i & 1][i >> 1][0], wa[i & 1][i >> 1][1], wa[i & 1][i >> 1][2], wa[i & 1][i >> 1][3]));
    }
    bar_sync(NB_D, 384);
    uint32_t slot_off = 0;
    const uint32_t slot_inc = warp == 0 ? 2048 : 4096, slot_last = warp == 0 ? 2048 : (R_NST - 1) * 4096;
    const uint32_t sx_bar_rem = (sb + RB_SX) ^ (1u << 24);
    uint4 tb = lds128(tab + 2048);
#pragma unroll 1
    for (int s = 0; s < NSEG; s++) {
        if (s > 0) mbar_wait(sb + RB_A, (s - 1) & 1);
        if (warp == 0) { PROF(0); PROFG(13); }
        uint4 ta;
        const uint32_t km_tog = aa >= 2 ? (s & 1) * 2048 : 0;
        {
            float acc[5][4];
#pragma unroll
            for (int c = 0; c < 5; c++) { acc[c][0] = acc[c][1] = acc[c][2] = acc[c][3] = 0.f; }
            uint32_t b[8][4];
            uint4 av[16];
            static_assert(VK0 == 4, "order below assumes the V/O warps cover slices 0,1");
            ldsm4(b[0][0], b[0][1], b[0][2], b[0][3], tb.x);
            ldsm4(b[1][0], b[1][1], b[1][2], b[1][3], tb.x + 512);
            ldsm4(b[4][0], b[4][1], b[4][2], b[4][3], tb.x + 2048);
            ldsm4(b[5][0], b[5][1], b[5][2], b[5][3], tb.x + 2560);
#pragma unroll
            for (int kk = 0; kk < 8; kk++) {
                const int k2 = kk < 2 ? kk : (kk < 4 ? kk + 2 : (kk < 6 ? kk - 2 : kk));
                if (kk == 4) {
                    if (s > 0) mbar_wait(sb + RB_A1, (s - 1) & 1);
                    ldsm4(b[2][0], b[2][1], b[2][2], b[2][3], tb.x + 1024);
                    ldsm4(b[3][0], b[3][1], b[3][2], b[3][3], tb.x + 1536);
                    ldsm4(b[6][0], b[6][1], b[6][2], b[6][3], tb.x + 3072);
                    ldsm4(b[7][0], b[7][1], b[7][2], b[7][3], tb.x + 3584);
#pragma unroll
                    for (int i = 12; i < 16; i++) av[i] = lds128(tb.y + i * 512);
                    ta = lds128(tab);
                }
                mma16816(acc[0], wa[0][2 * k2][0], wa[0][2 * k2][1], wa[0][2 * k2][2], wa[0][2 * k2][3], b[k2][0], b[k2][1]);
                mma16816(acc[1], wa[1][2 * k2][0], wa[1][2 * k2][1], wa[1][2 * k2][2], wa[1][2 * k2][3], b[k2][0], b[k2][1]);
                mma16816(acc[3], wa[0][2 * k2 + 1][0], wa[0][2 * k2 + 1][1], wa[0][2 * k2 + 1][2], wa[0][2 * k2 + 1][3], b[k2][2], b[k2][3]);
                mma16816(acc[4], wa[1][2 * k2 + 1][0], wa[1][2 * k2 + 1][1], wa[1][2 * k2 + 1][2], wa[1][2 * k2 + 1][3], b[k2][2], b[k2][3]);
                if (2 * k2 >= VK0) {
                    mma16816(acc[2], av[2 * k2].x, av[2 * k2].y, av[2 * k2].z, av[2 * k2].w, b[k2][0], b[k2][1]);
                    mma16816(acc[2], av[2 * k2 + 1].x, av[2 * k2 + 1].y, av[2 * k2 + 1].z, av[2 * k2 + 1].w, b[k2][2], b[k2][3]);
                }
                if (kk == 0) { av[8] = lds128(tb.y + 8 * 512); av[9] = lds128(tb.y + 9 * 512); }
                if (kk == 1) { av[10] = lds128(tb.y + 10 * 512); av[11] = lds128(tb.y + 11 * 512); }
                if (kk == 2) { av[4] = lds128(tb.y + 4 * 512); av[5] = lds128(tb.y + 5 * 512); }
                if (kk == 3) { av[6] = lds128(tb.y + 6 * 512); av[7] = lds128(tb.y + 7 * 512); }
            }
#pragma unroll
            for (int i = 0; i < 4; i++) { acc[0][i] += acc[3][i]; acc[1][i] += acc[4][i]; }
            const float g0 = kh ? acc[0][0] : acc[1][0], g1 = kh ? acc[0][1] : acc[1][1], g2 = kh ? acc[0][2] : acc[1][2], g3 = kh ? acc[0][3] : acc[1][3];
            sts128(tb.w, make_uint4(__float_as_uint(g0), __float_as_uint(g1), __float_as_uint(g2), __float_as_uint(g3)));
            const float k0 = kh ? acc[1][0] : acc[0][0], k1 = kh ? acc[1][1] : acc[0][1], k2_ = kh ? acc[1][2] : acc[0][2], k3 = kh ? acc[1][3] : acc[0][3];
            if (warp == 0) PROF(1);
            bar_sync(NB_X + aa, 64);
            const uint4 o = lds128(tb.z + 4096);
            stsm2t(ta.x ^ km_tog, pack2(k0 + __uint_as_float(o.x), k1 + __uint_as_float(o.y)), pack2(k2_ + __uint_as_float(o.z), k3 + __uint_as_float(o.w)));
            sts128(tb.z, make_uint4(__float_as_uint(acc[2][0]), __float_as_uint(acc[2][1]), __float_as_uint(acc[2][2]), __float_as_uint(acc[2][3])));
        }
        const uint32_t kb = ta.z + slot_off;
        if (warp == 0) PROF(14);
        bar_sync(NB_B, 256);
        if (warp < 5) {
            uint32_t q[16], k0, k1, k2, k3, k4, k5, k6, k7;
            float sa[4] = {0.f, 0.f, 0.f, 0.f}, sc[4] = {0.f, 0.f, 0.f, 0.f};
            ldsm4(q[0], q[1], q[2], q[3], ta.y);
            ldsm4(k0, k1, k2, k3, kb);
            ldsm4(q[4], q[5], q[6], q[7], ta.y ^ 32);
            ldsm4(q[8], q[9], q[10], q[11], ta.y ^ 64);
            ldsm4(k4, k5, k6, k7, kb ^ 64);
            ldsm4(q[12], q[13], q[14], q[15], ta.y ^ 96);
            mma16816(sa, q[0], q[1], q[2], q[3], k0, k1);
            bar_arrive(NB_Y, 288);
            mma16816(sc, q[4], q[5], q[6], q[7], k2, k3);
            mma16816(sa, q[8], q[9], q[10], q[11], k4, k5);
            mma16816(sc, q[12], q[13], q[14], q[15], k6, k7);
            const float scl = 0.08838834764831845f * 1.4426950408889634f;
            const float r0 = (sa[0] + sc[0]) * scl, r1 = (sa[1] + sc[1]) * scl;
            if (s != NSEG - 1) {
                st_async_v2(ta.w, r0, r1, sx_bar_rem);
                st_async_v2(ta.w ^ (1u << 24), r0, r1, sx_bar_rem ^ (1u << 24));
            }
            if (warp == 0) PROF(2);
        } else if (s > 0 && warp == 7 && lane == 0) {
            mbar_expect_tx(sb + RB_A, 4096);
            mbar_expect_tx(sb + RB_A1, 4096);
        }
        if (s == NSEG - 1) break;
        slot_off = slot_off == slot_last ? 0 : slot_off + slot_inc;
        const uint4 tc = lds128(tab + 4096), td = lds128(tab + 6144);
        const uint32_t te = lds32(tab + 8192);
        uint32_t* wr = (uint32_t*)(((uint64_t)td.y << 32) | (td.x ^ ((s & 1) * 0x21000)));
        const uint32_t* r1p = (const uint32_t*)((const char*)wr + (int)td.z);
        const uint32_t* r2p = (const uint32_t*)((const char*)wr + (int)td.w);
        const uint32_t* r3p = (const uint32_t*)((const char*)wr + (int)te);
        const uint32_t tag = ((s >> 1) + 1) & 1;
        mbar_wait(sb + RB_E, s & 1);
        if (warp == 0) PROF(7);
        {
            uint32_t a0, a1, a2, a3, a4, a5, a6, a7;
            ldsm4t(a0, a1, a2, a3, tc.x);
            ldsm4t(a4, a5, a6, a7, tc.x ^ 64);
            const uint32_t one = 0x3F803F80u;
            float d0_[4] = {0.f, 0.f, 0.f, 0.f}, d1_[4] = {0.f, 0.f, 0.f, 0.f};
            mma16816(d0_, a0, a1, a2, a3, one, one);
            mma16816(d1_, a4, a5, a6, a7, one, one);
            const bool t1 = tc.w & 1, t2 = tc.w & 2;
            const float x = t2 ? (t1 ? d1_[2] : d1_[0]) : (t1 ? d0_[2] : d0_[0]);
            const uint32_t own = (__float_as_uint(x) & ~1u) | tag;
            stg_relaxed32(wr, own);
            const uint32_t tq = clk32();
            if (warp == 0) PROF(8);
            PROFG(16 + warp);
            while ((int)(clk32() - tq) < POLL_GAP) {}
            uint32_t f1 = ldg_relaxed32(r1p), f2 = ldg_relaxed32(r2p), f3 = ldg_relaxed32(r3p);
#pragma unroll
            for (int i = 0; i < NOFF; i++) {
                const uint4 f0 = lds128(tab + 10240 + i * 2048);
                wa[i & 1][i >> 1][0] = f0.x; wa[i & 1][i >> 1][1] = f0.y; wa[i & 1][i >> 1][2] = f0.z; wa[i & 1][i >> 1][3] = f0.w;
            }
            tb = lds128(tab + 2048);
            int gg = 0;
#pragma unroll 1
            while (!__all_sync(~0u, (((f1 ^ tag) | (f2 ^ tag) | (f3 ^ tag)) & 1) == 0)) {
                f1 = ldg_relaxed32(r1p); f2 = ldg_relaxed32(r2p); f3 = ldg_relaxed32(r3p);
                if (++gg > 16 * SPIN_LIMIT) { TIMEOUT(3, s); break; }
            }
            if (warp == 0) PROF(9);
            const float v = (__uint_as_float(own) + __uint_as_float(f2)) + (__uint_as_float(f1) + __uint_as_float(f3));
            const bool b8 = tc.w & 8, b16 = tc.w & 16;
            const float recv = __shfl_xor_sync(~0u, v, 8);
            const uint32_t word = b8 ? pack2(recv, v) : pack2(v, recv);
            const uint32_t oth = __shfl_xor_sync(~0u, word, 16);
            const uint32_t wl = b16 ? oth : word, wh = b16 ? word : oth;
            const uint32_t p0 = __shfl_xor_sync(~0u, wl, 2), p1 = __shfl_xor_sync(~0u, wh, 2);
            const uint4 item = t2 ? make_uint4(p0, p1, wl, wh) : make_uint4(wl, wh, p0, p1);
            st_async_v4(tc.y, item, tc.z);
            st_async_v4(tc.y ^ (8u << 24), item, tc.z ^ (8u << 24));
            if (tc.w == 0 && warp == 7) mbar_expect_tx(sb + RB_E, 8192);
            if (warp == 0) PROF(10);
            PROF(40 + warp);
        }
        bar_sync(NB_D, 384);
    }
}

__device__ __forceinline__ void rec_load_kv(uint32_t sb, int col0, int s, uint32_t slot_off, int t128) {
    const int row = t128 >> 2, c2 = (t128 & 3) * 2;
    const bf16* src = g_kv + ((size_t)(s * 32 + row) * (2 * HD_) + col0 + c2 * 8);
    const uint32_t d0 = sb + R_KX + slot_off + row * 128 + ((c2 ^ (row & 7)) << 4);
    cp_async16(d0, src);
    cp_async16(d0 ^ 16, src + 8);
    cp_async16(d0 + (R_VX - R_KX), src + HD_);
    cp_async16((d0 ^ 16) + (R_VX - R_KX), src + HD_ + 8);
}

__device__ __forceinline__ void rec_store_kvm(uint32_t sb, int col0, int s, int w, int lane) {
    const int tok = (w & 1) * 4 + (lane >> 3);
    const uint4 v = lds128(sb + R_KMS + (s & 1) * 2048 + (w >> 1) * 1024 + tok * 128 + (((lane & 7) ^ tok) << 4));
    *(uint4*)(g_kvm + ((s * 8 + tok) * (2 * HD_) + (w >> 1) * HD_ + col0 + (lane & 7) * 8)) = v;
}

__device__ __forceinline__ void rec_vo(const RecParams& p, const uint32_t sb, const int cta, const int warp, int lane) {
    const int w = warp - 8, crank = cta & 15;
    const int col0 = cta * 64;
    uint32_t wo[8][4][4];
    {
        const int t128 = w * 32 + lane;
        const bf16* Wo = p.wo + (size_t)col0 * D_;
        const uint32_t stg = sb + R_STG + 2 * 32768;
#pragma unroll
        for (int half = 0; half < 2; half++) {
#pragma unroll 4
            for (int i = t128; i < 2048; i += 128) {
                const int e = i >> 6, ch = i & 63;
                cp_async16(stg + e * 1024 + ((ch ^ (e & 7)) << 4), Wo + (size_t)(half * 32 + e) * D_ + ch * 8);
            }
            cp_async_commit();
            cp_async_wait<0>();
            bar_sync(NB_W0 + 2, 128);
#pragma unroll
            for (int j = 0; j < 8; j++)
#pragma unroll
                for (int kk = 0; kk < 2; kk++) {
                    const int e = kk * 16 + (lane >> 4) * 8 + (lane & 7);
                    const int ch = (w * 8 + j) * 2 + ((lane >> 3) & 1);
                    ldsm4t(wo[j][half * 2 + kk][0], wo[j][half * 2 + kk][1], wo[j][half * 2 + kk][2], wo[j][half * 2 + kk][3],
                           stg + e * 1024 + ((ch ^ (e & 7)) << 4));
                }
            bar_sync(NB_W0 + 2, 128);
        }
        if (lane == 0) wait_flag(F_KV + 0, 64);
        __syncwarp();
        rec_load_kv(sb, col0, 0, 0, t128); cp_async_commit();
        rec_load_kv(sb, col0, 1, 4096, t128); cp_async_commit();
        cp_async_wait<1>();
    }
    const uint32_t tab = sb + R_STG + 2 * 32768 + (w * 32 + lane) * 16;
    {
        const uint32_t l7 = lane & 7, l8 = lane >> 3, g = lane >> 2;
        uint4 v;
        v.x = sb + R_VX + ((l8 & 1) * 8 + l7) * 128 + (((2 * w + (l8 >> 1)) ^ l7) << 4);
        v.y = sb + R_OS + g * 128 + (((2 * w) ^ g) << 4) + (lane & 3) * 4;
        v.z = sb + R_VMS + l7 * 128 + (((2 * w + (l8 & 1)) ^ l7) << 4);
        v.w = sb + R_OS + l7 * 128 + ((l8 ^ l7) << 4);
        sts128(tab, v);
        v.x = mapa_u32(sb + R_RS + crank * 512 + ((lane ^ (crank & 7)) << 4), w * 4);
        v.y = mapa_u32(sb + RB_E, w * 4);
        v.z = sb + R_VP + w * 512 + lane * 16;
        v.w = sb + R_SX + lane * 8;
        sts128(tab + 2048, v);
#pragma unroll
        for (int i = 0; i < 8; i++) sts128(tab + 4096 + i * 2048, make_uint4(wo[i][0][0], wo[i][0][1], wo[i][0][2], wo[i][0][3]));
    }
    bar_sync(NB_D, 384);
    const uint32_t lane16 = lds32(tab + 2048 + 8) - R_VP - w * 512;
    uint4 av[2 * VK0];
#pragma unroll
    for (int i = 0; i < 2 * VK0; i++) av[i] = lds128(lane16 + R_WV + (i / VK0) * 32768 + (w * 16 + i % VK0) * 512);
    uint32_t slot_off = 0;
#pragma unroll 1
    for (int s = 0; s < NSEG; s++) {
        if (s > 0) {
            mbar_wait(sb + RB_A, (s - 1) & 1);
            OPAQUE(lane);
            if ((s & 3) == 1 && s > 1 && w == 0 && lane == 0) red_release(&g_flags[F_MEM + (s >> 2) - 1], 1);
            rec_store_kvm(sb, col0, s - 1, w, lane);
            if (s + 1 < NSEG - 1) {
                if (((s + 1) & 3) == 0) { if (lane == 0) wait_flag(F_KV + ((s + 1) >> 2), 64); __syncwarp(); }
                rec_load_kv(sb, col0, s + 1, slot_off == (R_NST - 1) * 4096 ? 0 : slot_off + 4096, w * 32 + lane);
            }
            cp_async_commit();
        }
        bar_sync(NB_Y, 288);
        uint32_t vb0, vb1;
        {
            float va[4] = {0.f, 0.f, 0.f, 0.f}, vc[4] = {0.f, 0.f, 0.f, 0.f};
            uint32_t bb[VK0][4];
#pragma unroll
            for (int k2 = 0; k2 < VK0; k2++) ldsm4(bb[k2][0], bb[k2][1], bb[k2][2], bb[k2][3], lane16 + R_MEM + (k2 / (VK0 / 2)) * 4096 + (k2 % (VK0 / 2)) * 512);
#pragma unroll
            for (int k2 = 0; k2 < VK0; k2++) {
                mma16816(va, av[2 * k2].x, av[2 * k2].y, av[2 * k2].z, av[2 * k2].w, bb[k2][0], bb[k2][1]);
                mma16816(vc, av[2 * k2 + 1].x, av[2 * k2 + 1].y, av[2 * k2 + 1].z, av[2 * k2 + 1].w, bb[k2][2], bb[k2][3]);
            }
            const uint4 a = lds128(lane16 + R_VP + w * 512), b = lds128(lane16 + R_VP + 2048 + w * 512);
            vb0 = pack2((va[0] + vc[0]) + (__uint_as_float(a.x) + __uint_as_float(b.x)), (va[1] + vc[1]) + (__uint_as_float(a.y) + __uint_as_float(b.y)));
            vb1 = pack2((va[2] + vc[2]) + (__uint_as_float(a.z) + __uint_as_float(b.z)), (va[3] + vc[3]) + (__uint_as_float(a.w) + __uint_as_float(b.w)));
        }
        const uint4 ta = lds128(tab), tb = lds128(tab + 2048);
        uint32_t vx[8];
        ldsm4t(vx[0], vx[1], vx[2], vx[3], ta.x + slot_off);
        ldsm4t(vx[4], vx[5], vx[6], vx[7], ta.x + slot_off + 2048);
#pragma unroll
        for (int i = 0; i < 4; i++) {
            const uint4 f0 = lds128(tab + 4096 + i * 2048);
            wo[i][0][0] = f0.x; wo[i][0][1] = f0.y; wo[i][0][2] = f0.z; wo[i][0][3] = f0.w;
        }
        if (w == 0) PROF(11);
        uint32_t pf[5];
        float oa[2][4] = {{0.f, 0.f, 0.f, 0.f}, {0.f, 0.f, 0.f, 0.f}}, ob_[2][4] = {{0.f, 0.f, 0.f, 0.f}, {0.f, 0.f, 0.f, 0.f}};
        float sm0[4] = {0.f, 0.f, 0.f, 0.f}, sm1[4] = {0.f, 0.f, 0.f, 0.f};
        if (s != NSEG - 1) {
            mbar_wait(sb + RB_SX, s & 1);
            if (w == 0) PROF(4);
            float sv[10];
#pragma unroll
            for (int n = 0; n < 5; n++) {
                const float2 a = lds64f(tb.w + n * 256), b = lds64f(tb.w + (5 + n) * 256);
                sv[2 * n] = a.x + b.x; sv[2 * n + 1] = a.y + b.y;
            }
            float mx = fmaxf(fmaxf(fmaxf(sv[0], sv[1]), fmaxf(sv[2], sv[3])), fmaxf(fmaxf(sv[4], sv[5]), fmaxf(sv[6], sv[7])));
            mx = fmaxf(mx, fmaxf(sv[8], sv[9]));
            mx = fmaxf(mx, __shfl_xor_sync(~0u, mx, 1));
            mx = fmaxf(mx, __shfl_xor_sync(~0u, mx, 2));
#pragma unroll
            for (int n = 1; n < 5; n++) pf[n] = pack2(ex2(sv[2 * n] - mx), ex2(sv[2 * n + 1] - mx));
            pf[0] = pack2(ex2(sv[0] - mx), ex2(sv[1] - mx));
            if (w == 0) PROF(12);
            const uint32_t one = 0x3F803F80u;
            mma16816h(sm0, pf[1], pf[2], one, one);
            mma16816h(oa[0], pf[1], pf[2], vx[0], vx[1]);
            mma16816h(oa[1], pf[1], pf[2], vx[2], vx[3]);
            mma16816h(sm1, pf[3], pf[4], one, one);
            mma16816h(ob_[0], pf[3], pf[4], vx[4], vx[5]);
            mma16816h(ob_[1], pf[3], pf[4], vx[6], vx[7]);
            mma1688h(sm0, pf[0], one);
            mma1688h(oa[0], pf[0], vb0);
            mma1688h(oa[1], pf[0], vb1);
            float inv;
            asm("rcp.approx.ftz.f32 %0, %1;" : "=f"(inv) : "f"(sm0[0] + sm1[0]));
            oa[0][0] += ob_[0][0]; oa[0][1] += ob_[0][1]; oa[1][0] += ob_[1][0]; oa[1][1] += ob_[1][1];
            sts32(ta.y, pack2(oa[0][0] * inv, oa[0][1] * inv));
            sts32(ta.y ^ 16, pack2(oa[1][0] * inv, oa[1][1] * inv));
            const uint32_t oa2 = ta.w ^ 64;
            bar_sync(NB_C, 128);
            if (w == 0) PROF(5);
            uint32_t ob[8];
            ldsm4(ob[0], ob[1], ob[2], ob[3], ta.w);
            ldsm4(ob[4], ob[5], ob[6], ob[7], oa2);
#pragma unroll
            for (int i = 4; i < 8; i++) {
                const uint4 f0 = lds128(tab + 4096 + i * 2048);
                wo[i][0][0] = f0.x; wo[i][0][1] = f0.y; wo[i][0][2] = f0.z; wo[i][0][3] = f0.w;
            }
#pragma unroll
            for (int jj = 0; jj < 2; jj++) {
                if (jj == 1 && tb.w == 0) break;
                float acc[4][4];
#pragma unroll
                for (int c = 0; c < 4; c++) { acc[c][0] = acc[c][1] = acc[c][2] = acc[c][3] = 0.f; }
#pragma unroll
                for (int ks = 0; ks < 4; ks++)
#pragma unroll
                    for (int c = 0; c < 4; c++)
                        mma16816(acc[c], wo[jj * 4 + c][ks][0], wo[jj * 4 + c][ks][1], wo[jj * 4 + c][ks][2], wo[jj * 4 + c][ks][3], ob[2 * ks], ob[2 * ks + 1]);
#pragma unroll
                for (int pr = 0; pr < 2; pr++) {
                    uint4 v;
                    v.x = pack2(acc[2 * pr][0], acc[2 * pr][1]);
                    v.y = pack2(acc[2 * pr][2], acc[2 * pr][3]);
                    v.z = pack2(acc[2 * pr + 1][0], acc[2 * pr + 1][1]);
                    v.w = pack2(acc[2 * pr + 1][2], acc[2 * pr + 1][3]);
                    st_async_v4(tb.x + ((jj * 2 + pr) << 24), v, tb.y + ((jj * 2 + pr) << 24));
                }
            }
            if (w == 0) PROF(6);
        }
        stsm2t(ta.z + (s & 1) * 2048, vb0, vb1);
        cp_async_wait<0>();
        bar_sync(NB_C, 128);
        if (w == 0 && lane == 0 && s != NSEG - 1) mbar_expect_tx(sb + RB_SX, 2560);
        if (s != NSEG - 1) {
            bar_arrive(NB_D, 384);
#pragma unroll
            for (int i = 0; i < 2 * VK0; i++) av[i] = lds128(lane16 + R_WV + (i / VK0) * 32768 + (w * 16 + i % VK0) * 512);
        }
        slot_off = slot_off == (R_NST - 1) * 4096 ? 0 : slot_off + 4096;
    }
    rec_store_kvm(sb, col0, NSEG - 1, w, lane);
    bar_sync(NB_C, 128);
    if (w == 0 && lane == 0) red_release(&g_flags[F_MEM + NRB - 1], 1);
}

__global__ void __launch_bounds__(384, 1) k_rec(const RecParams p) {
    extern __shared__ __align__(1024) unsigned char smem_raw[];
    const uint32_t sb = __shfl_sync(~0u, smem_u32(smem_raw), 0);
    const int warp = __shfl_sync(~0u, threadIdx.x >> 5, 0);
    int lane; asm volatile("mov.u32 %0, %%laneid;" : "=r"(lane));
    const int crank = blockIdx.x & 15, slot = blockIdx.x >> 4;
    asm volatile("griddepcontrol.launch_dependents;");
    if (threadIdx.x == 0) {
        mbar_init(sb + RB_SX, 1); mbar_init(sb + RB_E, 1); mbar_init(sb + RB_A, 1); mbar_init(sb + RB_A1, 1); mbar_init(sb + RB_ROLE, 1);
        asm volatile("fence.mbarrier_init.release.cluster;" ::: "memory");
        mbar_expect_tx(sb + RB_SX, 2560);
        mbar_expect_tx(sb + RB_E, 8192);
        mbar_expect_tx(sb + RB_A, 4096);
        mbar_expect_tx(sb + RB_A1, 4096);
        mbar_expect_tx(sb + RB_ROLE, 4);
    }
    unsigned role = 0;
    if (crank == 0 && threadIdx.x == 0) {
        unsigned x = 0;
        int tm[2] = {0x7fffffff, 0x7fffffff};
#pragma unroll 1
        for (int i = 0; i < 6; i++) {
            const uint32_t t0 = clk32();
            x = atomicAdd(&g_F[65536 + (i & 1) * 1024 + slot * 64 + (x >> 31)], 0u) & 0x7fffffffu;
            if (x == 0x7654321u) sts32(sb + R_BAR + 56, x);
            const int dt = (int)(clk32() - t0);
            if (i >= 2) { if (i & 1) tm[1] = min(tm[1], dt); else tm[0] = min(tm[0], dt); }
        }
        const int side = tm[1] > tm[0];
        const unsigned old = atomicAdd(&g_flags[F_SIDE + side * 32], 1u);
        unsigned c0, c1; int gd = 0;
#pragma unroll 1
        do { c0 = ldg_relaxed32(&g_flags[F_SIDE]); c1 = ldg_relaxed32(&g_flags[F_SIDE + 32]); } while ((int)(c0 + c1) < p.ncl && ++gd < 64 * SPIN_LIMIT);
        const int big = c1 > c0;
        role = side == big ? old : (big ? c1 : c0) + old;
        role |= (big ^ 1) << 8;
    }
    __syncwarp();
    asm volatile("barrier.cluster.arrive.relaxed.aligned;\nbarrier.cluster.wait.aligned;" ::: "memory");
    if (crank == 0 && warp == 0) {
        role = __shfl_sync(~0u, role, 0);
        if (lane < 16)
            asm volatile("st.async.weak.shared::cluster.mbarrier::complete_tx::bytes.u32 [%0], %1, [%2];"
                         :: "r"(mapa_u32(sb + R_BAR + 48, lane)), "r"(role), "r"(mapa_u32(sb + RB_ROLE, lane)) : "memory");
    }
    mbar_wait(sb + RB_ROLE, 0);
    const int rolew = __shfl_sync(~0u, lds32(sb + R_BAR + 48), 0);
    const int cl = rolew & 255;
    if (cl >= 4) return;
    const int cta = cl * 16 + crank;
    if (warp < 8) rec_qk(p, sb, cta, warp, lane, rolew >> 8);
    else rec_vo(p, sb, cta, warp, lane);
}

enum { J_KV = 0, J_QA = 1, J_O = 2, J_LN = 3, J_UP = 4, J_DN = 5, J_UP2 = 6, J_END = 8 };
constexpr int NJ_O = 2 * OSPLIT, NJ_O2 = 2 * OSPLIT2, NJ_LN = 8, NJ_LN2 = 16, NJ_UP = 14, NJ_UP2 = 28, NJ_DN = 8;
__device__ __forceinline__ int nj_coarse(int q) { return q == J_KV ? 32 : (q == J_QA ? 16 : (q == J_O ? NJ_O : (q == J_LN ? NJ_LN : (q == J_UP ? NJ_UP : NJ_DN)))); }
__device__ __forceinline__ int nj_fine(int q) { return q == J_KV ? 32 : (q == J_QA ? 16 : (q == J_O ? NJ_O2 : (q == J_LN ? NJ_LN2 : (q == J_UP ? NJ_UP2 : NJ_DN)))); }
__device__ __forceinline__ int pick_job(int lane, int qmask, int& idx) {
    const int rb = lane & 15, half = lane >> 4;
    const bool fine = rb >= FINE_RB;
    int gd = 0;
#pragma unroll 1
    while (true) {
        unsigned cl[3], dp[3];
#pragma unroll
        for (int i = 0; i < 3; i++) {
            const int q = half + 2 * i;
            cl[i] = ldg_relaxed32(&g_flags[F_CLAIM + q * 32 + rb]);
            dp[i] = ldg_relaxed32(&g_flags[q * 32 + (q == J_QA ? max(rb - 1, 0) : rb)]);
        }
        int pick_q = -1, pick_rb = 0, early_q = -1, early_rb = 0;
        unsigned prev16 = 0;
        bool any = false;
#pragma unroll
        for (int i = 0; i < 3; i++) {
            const int q = half + 2 * i;
            const bool have = ((qmask >> q) & 1) && (int)cl[i] < (fine ? nj_fine(q) : nj_coarse(q));
            const unsigned tgt = q == J_QA ? 64 : 2 * (fine ? nj_fine(q - 1) : nj_coarse(q - 1));
            const bool ready = have && (q == J_KV || (q == J_QA && rb == 0) || dp[i] >= tgt);
            const unsigned mh = __ballot_sync(~0u, have), mr = __ballot_sync(~0u, ready);
            any |= mh != 0;
#pragma unroll
            for (int hf = 0; hf < 2; hf++) {
                const int qq = hf + 2 * i;
                const unsigned r16 = (mr >> (16 * hf)) & 0xffffu, h16 = (mh >> (16 * hf)) & 0xffffu;
                if (r16 && pick_q != J_KV) { pick_q = qq; pick_rb = __ffs(r16) - 1; }
                if (qq >= J_O && early_q < 0 && h16 && __ffs(h16) - 1 >= FINE_RB && (prev16 & ((2u << (__ffs(h16) - 1)) - 1)) == 0) {
                    early_q = qq; early_rb = __ffs(h16) - 1;
                }
                prev16 |= h16;
            }
        }
        if (!any) return J_END;
        if (pick_q < 0) { pick_q = early_q; pick_rb = early_rb; }
        if (pick_q >= 0) {
            int c = 0;
            if (lane == 0) c = (int)atomicAdd(&g_flags[F_CLAIM + pick_q * 32 + pick_rb], 1u);
            c = __shfl_sync(~0u, c, 0);
            const bool f = pick_rb >= FINE_RB;
            if (c < (f ? nj_fine(pick_q) : nj_coarse(pick_q))) {
                idx = pick_q * 600 + pick_rb * 32 + c;
                return (pick_q == J_UP && f ? J_UP2 : pick_q) | (pick_rb << 8) | (c << 16);
            }
        } else {
            __nanosleep(200);
            if (++gd > 16 * SPIN_LIMIT) { TIMEOUT(5, 0); return J_END; }
        }
    }
}
__device__ __forceinline__ int op_row(int rb, int split) {
    return rb < FINE_RB ? split * S_ + rb * 128 : OSPLIT * S_ + (split * (NRB - FINE_RB) + rb - FINE_RB) * 128;
}

struct Pipe { uint32_t stage, phase; };
__device__ __forceinline__ void pipe_next(Pipe& p) { if (++p.stage == W_NST) { p.stage = 0; p.phase ^= 1; } }

__device__ __forceinline__ void scheduler(const Params& p, uint32_t sb, int lane) {
    const uint32_t bars = sb + SM_BAR;
    uint32_t ph = 0;
#pragma unroll 1
    while (true) {
        mbar_wait(bars + B_REQ, ph);
        int j = 4095;
        const int jd = pick_job(lane, p.qmask, j);
        if (lane == 0) { sts32(bars + B_NEXT, (uint32_t)jd); sts32(bars + B_NEXT + 4, (uint32_t)j); mbar_arrive(bars + B_RSP); }
        ph ^= 1;
        if (jd == J_END) break;
        __syncwarp();
    }
}

__device__ __forceinline__ void producer(const Params& p, uint32_t sb) {
    Pipe pp{0, 1};
    const uint32_t bars = sb + SM_BAR;
    uint32_t seq = 0;
    mbar_arrive(bars + B_REQ);
#pragma unroll 1
    while (true) {
        mbar_wait(bars + B_RSP, seq & 1);
        const int jd = (int)lds32(bars + B_NEXT), j = (int)lds32(bars + B_NEXT + 4);
        int left = (jd & 255) == J_DN ? 15 : ((jd & 255) == J_QA ? 12 : ((jd & 255) == J_O ? (((jd >> 8) & 255) >= FINE_RB ? 64 / OSPLIT2 : 64 / OSPLIT) : ((jd & 255) == J_LN ? 1 : 8)));
        left = max(left - PICK_AHEAD, 1);
        TR(j, 1);
        const int type = jd & 255, rb = (jd >> 8) & 255, cb = jd >> 16;
        const bool fine = rb >= FINE_RB;
        bool first = true;
        auto begin_stage = [&](uint32_t bytes) -> uint32_t {
            mbar_wait(bars + B_EMPTY + pp.stage * 8, pp.phase);
            if (first) { sts32(bars + B_RING + (seq & 7) * 4, (uint32_t)jd); sts32(bars + B_RING + 32 + (seq & 7) * 4, (uint32_t)j); first = false; }
            const uint32_t fb = bars + B_FULL + pp.stage * 8;
            if (bytes) mbar_expect_tx(fb, bytes); else mbar_arrive(fb);
            if (--left == 0 && type != J_END) mbar_arrive(bars + B_REQ);
            return fb;
        };
        if (type == J_END || type == J_LN) {
            if (type == J_LN) wait_flag(F_OP + rb, 2 * (fine ? NJ_O2 : NJ_O));
            TR(j, 2);
            begin_stage(0); pipe_next(pp);
            seq++;
            if (type == J_END) break;
            continue;
        }
        const CUtensorMap *ta, *tb0, *tb1;
        int k0 = 0, nk = 8, n0 = cb * 256, n1 = n0 + 128, nb = 4, dep = -1;
        unsigned tgt = 0;
        switch (type) {
            case J_KV: ta = &p.tm_h; tb0 = tb1 = cb < 16 ? &p.tm_wk : &p.tm_wv; n0 = (cb & 15) * 256; n1 = n0 + 128; break;
            case J_QA: ta = &p.tm_h; tb0 = tb1 = &p.tm_wq; break;
            case J_O: ta = &p.tm_o; tb0 = tb1 = &p.tm_wo; n0 = (cb & 1) * 256; n1 = n0 + 128; nk = fine ? 64 / OSPLIT2 : 64 / OSPLIT; k0 = (cb >> 1) * nk * 64;
                      dep = F_O + rb; tgt = 32; break;
            case J_UP: ta = &p.tm_h2; tb0 = &p.tm_wg; tb1 = &p.tm_wu; n0 = n1 = cb * 128; dep = F_H2 + rb; tgt = 2 * NJ_LN; break;
            case J_UP2: ta = &p.tm_h2; tb0 = &p.tm_wg; tb1 = &p.tm_wu; n0 = n1 = cb * 64; nb = 2; dep = F_H2 + rb; tgt = 2 * NJ_LN2; break;
            default: ta = &p.tm_act; tb0 = tb1 = &p.tm_wd; n0 = cb * 64; nk = 0; break;
        }
        const int m0 = rb * 128;
        if (type == J_DN) {
#pragma unroll 1
            for (int kb = 0; kb < 14; kb++) {
                const uint32_t fb = begin_stage(49152);
                const uint32_t st = sb + pp.stage * W_STAGE;
                const int k = kb * 128;
                tma_load2d(st + 32768, tb0, n0, k, fb);
                tma_load2d(st + 40960, tb0, n0, k + 64, fb);
                if (kb == 0) { wait_flag(F_ACT + rb, 2 * (fine ? NJ_UP2 : NJ_UP)); fence_async_all(); TR(j, 2); }
                tma_load2d(st, ta, k, m0, fb);
                tma_load2d(st + 8192, ta, k, m0 + 64, fb);
                tma_load2d(st + 16384, ta, k + 64, m0, fb);
                tma_load2d(st + 24576, ta, k + 64, m0 + 64, fb);
                pipe_next(pp);
            }
        }
#pragma unroll 1
        for (int kb = 0; kb < nk; kb++) {
            const uint32_t fb = begin_stage(16384 + nb * 8192);
            const uint32_t st = sb + pp.stage * W_STAGE;
            const int k = k0 + kb * 64;
            tma_load2d(st + 16384, tb0, n0, k, fb);
            if (nb == 4) {
                tma_load2d(st + 16384 + 8192, tb0, n0 + 64, k, fb);
                tma_load2d(st + 16384 + 16384, tb1, n1, k, fb);
                tma_load2d(st + 16384 + 24576, tb1, n1 + 64, k, fb);
            } else if (nb == 2) {
                tma_load2d(st + 16384 + 8192, tb1, n1, k, fb);
            }
            if (kb == 0) {
                if (dep >= 0) { wait_flag(dep, tgt); if (type >= J_UP) fence_async_all(); }
                TR(j, 2);
            }
            tma_load2d(st, ta, k, m0, fb);
            tma_load2d(st + 8192, ta, k, m0 + 64, fb);
            pipe_next(pp);
        }
        if (type == J_QA) {
            wait_flag(F_KV + rb, 64);
#pragma unroll 1
            for (int i = 0; i < 4; i++) {
                const uint32_t fb = begin_stage(40960);
                const uint32_t st = sb + pp.stage * W_STAGE;
                const int col = (i & 1) * HD_ + (cb * 2 + (i >> 1)) * DH_;
                tma_load2d(st, &p.tm_kv, col, m0, fb);
                tma_load2d(st + 8192, &p.tm_kv, col, m0 + 64, fb);
                tma_load2d(st + 16384, &p.tm_kv, col + 64, m0, fb);
                tma_load2d(st + 24576, &p.tm_kv, col + 64, m0 + 64, fb);
                if (i == 0) { wait_flag(F_MEM + rb, 64); fence_async_all(); }
                tma_load2d(st + 32768, &p.tm_kvm, col, rb * 32, fb);
                tma_load2d(st + 36864, &p.tm_kvm, col + 64, rb * 32, fb);
                pipe_next(pp);
            }
        } else if (type == J_DN) {
            const uint32_t fb = begin_stage(16384);
            const uint32_t st = sb + pp.stage * W_STAGE;
            tma_load2d(st, &p.tm_x1, n0, m0, fb);
            tma_load2d(st + 8192, &p.tm_x1, n0, m0 + 64, fb);
            pipe_next(pp);
        }
        seq++;
    }
}

__device__ __forceinline__ void store_warp(const Params& p, uint32_t sb, int wg, int lane) {
    const uint32_t bars = sb + SM_BAR;
    uint32_t seq = 0;
#pragma unroll 1
    while (true) {
        bar_sync(NB_ST + wg, 160);
        const uint32_t jd = lds32(bars + B_RING + (seq & 7) * 4);
        seq++;
        const int type = jd & 255, rb = (jd >> 8) & 255, cb = jd >> 16;
        if (type == J_END) break;
        if (lane == 0) {
            const uint32_t src = sb + W_STG + wg * 32768;
            const CUtensorMap* tm = nullptr; int n0 = cb * 256, nbox = 4, mrow = rb * 128 + wg * 64, flag = 0;
            switch (type) {
                case J_KV: tm = &p.tm_kv; flag = F_KV + rb; break;
                case J_QA: tm = &p.tm_o; flag = F_O + rb; break;
                case J_O: tm = &p.tm_op; n0 = (cb & 1) * 256; mrow = op_row(rb, cb >> 1) + wg * 64; flag = F_OP + rb; break;
                case J_LN: flag = F_H2 + rb; nbox = 0; break;
                case J_UP: tm = &p.tm_act; n0 = cb * 128; nbox = 2; flag = F_ACT + rb; break;
                case J_UP2: tm = &p.tm_act; n0 = cb * 64; nbox = 1; flag = F_ACT + rb; break;
                default: tm = &p.tm_out; n0 = cb * 64; nbox = 1; flag = -1; break;
            }
#pragma unroll 1
            for (int b = 0; b < nbox; b++) tma_store2d(tm, src + b * 8192, n0 + b * 64, mrow);
            bulk_commit();
            bulk_wait0();
            mbar_arrive(bars + B_STGFREE + wg * 8);
            if (flag >= 0) red_release(&g_flags[flag], 1);
        }
        __syncwarp();
    }
}

__device__ __forceinline__ float gelu_tanh(float x) {
    const float t = x * fmaf(-0.10294324397f, x * x, -2.30220819814f);
    float r; asm("rcp.approx.ftz.f32 %0, %1;" : "=f"(r) : "f"(1.f + ex2(t)));
    return x * r;
}

#define CTR(i) do {} while (0)

template <int NSPLIT>
__device__ __forceinline__ void ln2_row(const Params& p, int rb, int r, int lane) {
    const int row = rb * 128 + r;
    uint4 u[2 * NSPLIT];
#pragma unroll
    for (int sp = 0; sp < NSPLIT; sp++) {
        const uint4* src = (const uint4*)(g_op + (size_t)(op_row(rb, sp) + r) * D_);
        u[2 * sp] = __ldcg(src + lane); u[2 * sp + 1] = __ldcg(src + 32 + lane);
    }
    const uint4* xr = (const uint4*)(p.x + (size_t)row * D_);
    const uint4 xa = __ldg(xr + lane), xb = __ldg(xr + 32 + lane);
    uint32_t ga[8], c1[8], sm[8];
    load_mod8(g_mod + 2 * D_, lane, ga);
    load_mod8(g_mod + 4 * D_, lane, c1);
    load_mod8(g_mod + 3 * D_, lane, sm);
    float a[16];
#pragma unroll
    for (int i = 0; i < 16; i++) a[i] = 0.f;
#pragma unroll
    for (int sp = 0; sp < 2 * NSPLIT; sp++) {
        float* q = a + (sp & 1) * 8;
        q[0] += bflo(u[sp].x); q[1] += bfhi(u[sp].x); q[2] += bflo(u[sp].y); q[3] += bfhi(u[sp].y);
        q[4] += bflo(u[sp].z); q[5] += bfhi(u[sp].z); q[6] += bflo(u[sp].w); q[7] += bfhi(u[sp].w);
    }
    const uint32_t xv[8] = {xa.x, xa.y, xa.z, xa.w, xb.x, xb.y, xb.z, xb.w};
    uint32_t v[8], r8[8];
#pragma unroll
    for (int i = 0; i < 8; i++) v[i] = hadd2(xv[i], hmul2(ga[i], pack2(a[2 * i], a[2 * i + 1])));
    uint4* x1r = (uint4*)(g_x1 + (size_t)row * D_);
    x1r[lane] = make_uint4(v[0], v[1], v[2], v[3]); x1r[32 + lane] = make_uint4(v[4], v[5], v[6], v[7]);
    uint32_t mu2; float rden;
    ln_stats(v, mu2, rden);
#pragma unroll
    for (int i = 0; i < 8; i++) c1[i] = hadd2(c1[i], 0x3F803F80u);
    ln_apply(v, mu2, rden, c1, sm, r8);
    uint4* hr = (uint4*)(g_h2 + (size_t)row * D_);
    hr[lane] = make_uint4(r8[0], r8[1], r8[2], r8[3]); hr[32 + lane] = make_uint4(r8[4], r8[5], r8[6], r8[7]);
}

__device__ __forceinline__ void consumer(const Params& p, uint32_t sb, int warp, int lane) {
    const uint32_t bars = sb + SM_BAR;
    const int wg = warp >> 2, wl = warp & 3;
    const uint32_t l7 = lane & 7, l8 = lane >> 3, g = lane >> 2, t = lane & 3;
    Pipe pp{0, 0};
    uint32_t seq = 0, stg_phase = 1;
    const int srow = wl * 16 + l7 + (l8 & 1) * 8;
    const uint32_t stg_base = sb + W_STG + wg * 32768 + srow * 128;
    const uint32_t sx = ((lane >> 4) ^ (srow & 7)) << 4;
#pragma unroll 1
    while (true) {
        mbar_wait(bars + B_FULL + pp.stage * 8, pp.phase);
        const uint32_t jd = lds32(bars + B_RING + (seq & 7) * 4);
        CTR(3);
        seq++;
        const int type = jd & 255, rb = (jd >> 8) & 255, cb = jd >> 16;
        if (type == J_END) { mbar_wait(bars + B_STGFREE + wg * 8, stg_phase); bar_arrive(NB_ST + wg, 160); break; }
        if (type == J_LN) {
            __syncwarp();
            if (lane == 0) mbar_arrive(bars + B_EMPTY + pp.stage * 8);
            pipe_next(pp);
            if (rb >= FINE_RB) ln2_row<OSPLIT2>(p, rb, cb * 8 + warp, lane);
            else {
#pragma unroll 1
                for (int rr = 0; rr < 2; rr++) ln2_row<OSPLIT>(p, rb, cb * 16 + warp * 2 + rr, lane);
            }
            mbar_wait(bars + B_STGFREE + wg * 8, stg_phase); stg_phase ^= 1;
            CTR(4); CTR(5);
            bar_arrive(NB_ST + wg, 160);
            continue;
        }
        if (type >= J_DN) {
            float acc[64];
#pragma unroll
            for (int i = 0; i < 64; i++) acc[i] = 0.f;
            if (type == J_DN) {
#pragma unroll 1
                for (int kb = 0; kb < 14; kb++) {
                    if (kb) mbar_wait(bars + B_FULL + pp.stage * 8, pp.phase);
                    const uint32_t st = sb + pp.stage * W_STAGE;
                    const uint64_t da = mkdesc(st + wg * 8192, 16, 1024), db = mkdesc(st + 32768, 8192, 1024);
                    wg_fence();
#pragma unroll
                    for (int ks = 0; ks < 8; ks++) wgmma_n64(acc, da + (ks >> 2) * 1024 + (ks & 3) * 2, db + ks * 128);
                    wg_commit();
                    wg_wait0();
                    if (lane == 0) mbar_arrive(bars + B_EMPTY + pp.stage * 8);
                    pipe_next(pp);
                }
            } else {
#pragma unroll 1
                for (int kb = 0; kb < 8; kb++) {
                    if (kb) mbar_wait(bars + B_FULL + pp.stage * 8, pp.phase);
                    const uint32_t st = sb + pp.stage * W_STAGE;
                    const uint64_t da = mkdesc(st + wg * 8192, 16, 1024), db = mkdesc(st + 16384, 8192, 1024);
                    wg_fence();
#pragma unroll
                    for (int ks = 0; ks < 4; ks++) wgmma_n128(acc, da + ks * 2, db + ks * 128, 1);
                    wg_commit();
                    wg_wait0();
                    if (lane == 0) mbar_arrive(bars + B_EMPTY + pp.stage * 8);
                    pipe_next(pp);
                }
            }
            CTR(4);
            if (type == J_UP2) {
                mbar_wait(bars + B_STGFREE + wg * 8, stg_phase); stg_phase ^= 1;
#pragma unroll
                for (int j = 0; j < 4; j++) {
                    uint32_t r[4];
#pragma unroll
                    for (int q = 0; q < 4; q++) {
                        const uint32_t gw = pack2(acc[8 * j + 2 * q], acc[8 * j + 2 * q + 1]);
                        const uint32_t uw = pack2(acc[32 + 8 * j + 2 * q], acc[32 + 8 * j + 2 * q + 1]);
                        r[q] = hmul2(pack2(gelu_tanh(bflo(gw)), gelu_tanh(bfhi(gw))), uw);
                    }
                    stsm4(stg_base + (sx ^ (j << 5)), r[0], r[1], r[2], r[3]);
                }
            } else {
                mbar_wait(bars + B_FULL + pp.stage * 8, pp.phase);
                const uint32_t st = sb + pp.stage * W_STAGE;
                mbar_wait(bars + B_STGFREE + wg * 8, stg_phase); stg_phase ^= 1;
                const uint32_t* gb = (const uint32_t*)(g_mod + 5 * D_ + cb * 64) + t;
                const uint32_t xa = st + wg * 8192 + (wl * 16 + g) * 128 + (g << 4) + t * 4;
#pragma unroll
                for (int j = 0; j < 4; j++) {
                    uint32_t r[4];
#pragma unroll
                    for (int q = 0; q < 4; q++) {
                        const int nt = 2 * j + (q >> 1);
                        const uint32_t xw = lds32((xa ^ ((nt & 7) << 4)) + (nt >> 3) * 16384 + (q & 1) * 1024);
                        r[q] = hadd2(xw, hmul2(__ldcg(gb + nt * 4), pack2(acc[8 * j + 2 * q], acc[8 * j + 2 * q + 1])));
                    }
                    stsm4(stg_base + (j >> 2) * 8192 + (sx ^ ((2 * j & 7) << 4)), r[0], r[1], r[2], r[3]);
                }
                __syncwarp();
                if (lane == 0) mbar_arrive(bars + B_EMPTY + pp.stage * 8);
                pipe_next(pp);
            }
            fence_async_smem();
            CTR(5);
            bar_arrive(NB_ST + wg, 160);
            continue;
        }
        float acc[128];
#pragma unroll
        for (int i = 0; i < 128; i++) acc[i] = 0.f;
        const int nk = type == J_O ? (rb >= FINE_RB ? 64 / OSPLIT2 : 64 / OSPLIT) : 8;
#pragma unroll 1
        for (int kb = 0; kb < nk; kb++) {
            if (kb) mbar_wait(bars + B_FULL + pp.stage * 8, pp.phase);
            const uint32_t st = sb + pp.stage * W_STAGE;
            const uint64_t da = mkdesc(st + wg * 8192, 16, 1024), db = mkdesc(st + 16384, 8192, 1024);
            wg_fence();
#pragma unroll
            for (int ks = 0; ks < 4; ks++) wgmma_n256(acc, da + ks * 2, db + ks * 128, 1);
            wg_commit();
            wg_wait0();
            if (lane == 0) mbar_arrive(bars + B_EMPTY + pp.stage * 8);
            pipe_next(pp);
        }
        CTR(4);
        if (type == J_QA) {
            uint32_t qf[64];
#pragma unroll
            for (int i = 0; i < 64; i++) qf[i] = pack2(acc[2 * i], acc[2 * i + 1]);
            const int sg = warp >> 1, half = warp & 1;
            const float sc = 0.08838834764831845f * 1.4426950408889634f;
            const uint32_t xoff = (sg >> 1) * 8192 + ((sg & 1) * 32 + l7) * 128;
            const uint32_t moff = 32768 + (sg * 8 + l7) * 128;
            const uint32_t kch = (l8 ^ l7) << 4;
            const uint32_t vch = ((l8 & 1) ^ l7) << 4;
            mbar_wait(bars + B_STGFREE + wg * 8, stg_phase); stg_phase ^= 1;
#pragma unroll 1
            for (int hh = 0; hh < 2; hh++) {
                mbar_wait(bars + B_FULL + pp.stage * 8, pp.phase);
                uint32_t st = sb + pp.stage * W_STAGE;
                float sa[5][4];
#pragma unroll
                for (int n = 0; n < 5; n++) sa[n][0] = sa[n][1] = sa[n][2] = sa[n][3] = 0.f;
#pragma unroll
                for (int i = 0; i < 4; i++) {
                    const uint32_t* q = qf + i * 8;
                    uint32_t kk[5][4];
                    ldsm4(kk[0][0], kk[0][1], kk[0][2], kk[0][3], st + moff + (i >> 1) * 4096 + (kch ^ ((i & 1) * 64)));
#pragma unroll
                    for (int n = 1; n < 5; n++)
                        ldsm4(kk[n][0], kk[n][1], kk[n][2], kk[n][3], st + xoff + (n - 1) * 1024 + (i >> 1) * 16384 + (kch ^ ((i & 1) * 64)));
#pragma unroll
                    for (int n = 0; n < 5; n++) mma16816(sa[n], q[0], q[1], q[2], q[3], kk[n][0], kk[n][1]);
#pragma unroll
                    for (int n = 0; n < 5; n++) mma16816(sa[n], q[4], q[5], q[6], q[7], kk[n][2], kk[n][3]);
                }
                __syncwarp();
                if (lane == 0) mbar_arrive(bars + B_EMPTY + pp.stage * 8);
                pipe_next(pp);
                const int iq0 = half * 16 + g - 2 * t, iq1 = iq0 + 8;
                float m0 = fmaxf(sa[0][0], sa[0][1]), m1 = fmaxf(sa[0][2], sa[0][3]);
#pragma unroll
                for (int n = 1; n < 5; n++) {
#pragma unroll
                    for (int e = 0; e < 2; e++) {
                        const int jx = (n - 1) * 8 + e;
                        if (jx > iq0) sa[n][e] = -3.0e38f;
                        if (jx > iq1) sa[n][2 + e] = -3.0e38f;
                        m0 = fmaxf(m0, sa[n][e]); m1 = fmaxf(m1, sa[n][2 + e]);
                    }
                }
                m0 = fmaxf(m0, __shfl_xor_sync(~0u, m0, 1)); m1 = fmaxf(m1, __shfl_xor_sync(~0u, m1, 1));
                m0 = fmaxf(m0, __shfl_xor_sync(~0u, m0, 2)); m1 = fmaxf(m1, __shfl_xor_sync(~0u, m1, 2));
                m0 *= -sc; m1 *= -sc;
                float l0 = 0.f, l1 = 0.f;
                uint32_t p0[5], p1[5];
#pragma unroll
                for (int n = 0; n < 5; n++) {
                    const float e0 = ex2(fmaf(sa[n][0], sc, m0)), e1 = ex2(fmaf(sa[n][1], sc, m0));
                    const float e2 = ex2(fmaf(sa[n][2], sc, m1)), e3 = ex2(fmaf(sa[n][3], sc, m1));
                    l0 += e0 + e1; l1 += e2 + e3;
                    p0[n] = pack2(e0, e1); p1[n] = pack2(e2, e3);
                }
                l0 += __shfl_xor_sync(~0u, l0, 1); l1 += __shfl_xor_sync(~0u, l1, 1);
                l0 += __shfl_xor_sync(~0u, l0, 2); l1 += __shfl_xor_sync(~0u, l1, 2);
                const float i0 = __fdividef(1.f, l0), i1 = __fdividef(1.f, l1);
                mbar_wait(bars + B_FULL + pp.stage * 8, pp.phase);
                st = sb + pp.stage * W_STAGE;
#pragma unroll
                for (int i = 0; i < 32; i++) qf[i] = qf[32 + i];
#pragma unroll 1
                for (int bx = 0; bx < 2; bx++) {
                    float o[8][4];
                    uint32_t vm[8], v0[4][4], v1[4][4];
#pragma unroll
                    for (int ep = 0; ep < 4; ep++) {
                        ldsm2t(vm[2 * ep], vm[2 * ep + 1], st + moff + bx * 4096 + (vch ^ (ep << 5)));
                        const uint32_t va = st + xoff + (l8 >> 1) * 1024 + bx * 16384 + (vch ^ (ep << 5));
                        ldsm4t(v0[ep][0], v0[ep][1], v0[ep][2], v0[ep][3], va);
                        ldsm4t(v1[ep][0], v1[ep][1], v1[ep][2], v1[ep][3], va + 2048);
                    }
#pragma unroll
                    for (int n = 0; n < 8; n++) { o[n][0] = o[n][1] = o[n][2] = o[n][3] = 0.f; mma16816(o[n], p0[0], p1[0], p0[1], p1[1], vm[n], v0[n >> 1][n & 1]); }
#pragma unroll
                    for (int n = 0; n < 8; n++) mma16816(o[n], p0[2], p1[2], p0[3], p1[3], v0[n >> 1][2 + (n & 1)], v1[n >> 1][n & 1]);
#pragma unroll
                    for (int n = 0; n < 8; n++) mma1688(o[n], p0[4], p1[4], v1[n >> 1][2 + (n & 1)]);
#pragma unroll
                    for (int ep = 0; ep < 4; ep++)
                        stsm4(stg_base + (hh * 2 + bx) * 8192 + (sx ^ (ep << 5)),
                              pack2(o[2 * ep][0] * i0, o[2 * ep][1] * i0), pack2(o[2 * ep][2] * i1, o[2 * ep][3] * i1),
                              pack2(o[2 * ep + 1][0] * i0, o[2 * ep + 1][1] * i0), pack2(o[2 * ep + 1][2] * i1, o[2 * ep + 1][3] * i1));
                }
                __syncwarp();
                if (lane == 0) mbar_arrive(bars + B_EMPTY + pp.stage * 8);
                pipe_next(pp);
            }
        } else if (type == J_UP) {
            mbar_wait(bars + B_STGFREE + wg * 8, stg_phase); stg_phase ^= 1;
#pragma unroll
            for (int j = 0; j < 8; j++) {
                uint32_t r[4];
#pragma unroll
                for (int q = 0; q < 4; q++) {
                    const uint32_t gw = pack2(acc[8 * j + 2 * q], acc[8 * j + 2 * q + 1]);
                    const uint32_t uw = pack2(acc[64 + 8 * j + 2 * q], acc[64 + 8 * j + 2 * q + 1]);
                    r[q] = hmul2(pack2(gelu_tanh(bflo(gw)), gelu_tanh(bfhi(gw))), uw);
                }
                stsm4(stg_base + (j >> 2) * 8192 + (sx ^ ((2 * j & 7) << 4)), r[0], r[1], r[2], r[3]);
            }
        } else {
            mbar_wait(bars + B_STGFREE + wg * 8, stg_phase); stg_phase ^= 1;
#pragma unroll
            for (int j = 0; j < 16; j++)
                stsm4(stg_base + (j >> 2) * 8192 + (sx ^ ((2 * j & 7) << 4)),
                      pack2(acc[8 * j], acc[8 * j + 1]), pack2(acc[8 * j + 2], acc[8 * j + 3]),
                      pack2(acc[8 * j + 4], acc[8 * j + 5]), pack2(acc[8 * j + 6], acc[8 * j + 7]));
        }
        fence_async_smem();
        CTR(5);
        bar_arrive(NB_ST + wg, 160);
    }
}

__global__ void __launch_bounds__(384, 1) k_work(const __grid_constant__ Params p) {
    extern __shared__ __align__(1024) unsigned char smem_raw[];
    const uint32_t sb = smem_u32(smem_raw);
    if (sb & 1023) __trap();
    const int warp = __shfl_sync(~0u, threadIdx.x >> 5, 0);
    int lane; asm volatile("mov.u32 %0, %%laneid;" : "=r"(lane));
    if (threadIdx.x == 0) {
        const uint32_t bars = sb + SM_BAR;
        for (int i = 0; i < W_NST; i++) { mbar_init(bars + B_FULL + i * 8, 1); mbar_init(bars + B_EMPTY + i * 8, 8); }
        mbar_init(bars + B_STGFREE, 1); mbar_init(bars + B_STGFREE + 8, 1); mbar_init(bars + B_REQ, 1); mbar_init(bars + B_RSP, 1);
        asm volatile("fence.mbarrier_init.release.cluster;" ::: "memory");
    }
    __syncthreads();
    if (warp < 8) {
        asm volatile("setmaxnreg.inc.sync.aligned.u32 232;");
        consumer(p, sb, warp, lane);
    } else {
        asm volatile("setmaxnreg.dec.sync.aligned.u32 40;");
        if (warp == 8) { if (lane == 0) producer(p, sb); }
        else if (warp < 11) store_warp(p, sb, warp - 9, lane);
        else scheduler(p, sb, lane);
    }
}

typedef CUresult (*EncodeFn)(CUtensorMap*, CUtensorMapDataType, cuuint32_t, void*, const cuuint64_t*, const cuuint64_t*,
                             const cuuint32_t*, const cuuint32_t*, CUtensorMapInterleave, CUtensorMapSwizzle,
                             CUtensorMapL2promotion, CUtensorMapFloatOOBfill);

static void make_map(EncodeFn enc, CUtensorMap* m, const void* ptr, uint64_t rows, uint64_t cols, uint32_t box_rows) {
    cuuint64_t dims[2] = {cols, rows};
    cuuint64_t strides[1] = {cols * 2};
    cuuint32_t box[2] = {64, box_rows};
    cuuint32_t es[2] = {1, 1};
    enc(m, CU_TENSOR_MAP_DATA_TYPE_BFLOAT16, 2, const_cast<void*>(ptr), dims, strides, box, es, CU_TENSOR_MAP_INTERLEAVE_NONE,
        CU_TENSOR_MAP_SWIZZLE_128B, CU_TENSOR_MAP_L2_PROMOTION_L2_256B, CU_TENSOR_MAP_FLOAT_OOB_FILL_NONE);
}
template <typename T> static void* sym_addr(T& sym) { void* p = nullptr; cudaGetSymbolAddress(&p, sym); return p; }

extern "C" void kernel_launch(void* const* d_in, const int* in_sizes, int n_in, void* d_out, int out_size) {
    static Params prm;
    static RecParams rp;
    static bool ready = false;
    static const void* key[14];
    bool same = ready;
    for (int i = 0; i < 13 && same; i++) same = key[i] == d_in[i];
    same = same && key[13] == d_out;
    if (!same) {
        void* fn = nullptr;
        cudaDriverEntryPointQueryResult qr;
        cudaGetDriverEntryPoint("cuTensorMapEncodeTiled", &fn, cudaEnableDefault, &qr);
        EncodeFn enc = (EncodeFn)fn;
        make_map(enc, &prm.tm_h, sym_addr(g_h), S_, D_, 64);
        make_map(enc, &prm.tm_kv, sym_addr(g_kv), S_, 2 * HD_, 64);
        make_map(enc, &prm.tm_kvm, sym_addr(g_kvm), NSEG * 8, 2 * HD_, 32);
        make_map(enc, &prm.tm_o, sym_addr(g_o), S_, HD_, 64);
        make_map(enc, &prm.tm_op, sym_addr(g_op), OP_ROWS, D_, 64);
        make_map(enc, &prm.tm_h2, sym_addr(g_h2), S_, D_, 64);
        make_map(enc, &prm.tm_act, sym_addr(g_act), S_, DF_, 64);
        make_map(enc, &prm.tm_x1, sym_addr(g_x1), S_, D_, 64);
        make_map(enc, &prm.tm_out, d_out, S_, D_, 64);
        make_map(enc, &prm.tm_wq, d_in[2], D_, HD_, 64);
        make_map(enc, &prm.tm_wk, d_in[3], D_, HD_, 64);
        make_map(enc, &prm.tm_wv, d_in[4], D_, HD_, 64);
        make_map(enc, &prm.tm_wo, d_in[5], HD_, D_, 64);
        make_map(enc, &prm.tm_wg, d_in[8], D_, DF_, 64);
        make_map(enc, &prm.tm_wu, d_in[9], D_, DF_, 64);
        make_map(enc, &prm.tm_wd, d_in[10], DF_, D_, 64);
        prm.x = (const bf16*)d_in[0];
        rp.mem0 = (const bf16*)d_in[1];
        rp.wq = (const bf16*)d_in[2]; rp.wk = (const bf16*)d_in[3]; rp.wv = (const bf16*)d_in[4]; rp.wo = (const bf16*)d_in[5];
        cudaFuncSetAttribute(k_work, cudaFuncAttributeMaxDynamicSharedMemorySize, SMEM_BYTES);
        cudaFuncSetAttribute(k_rec, cudaFuncAttributeMaxDynamicSharedMemorySize, R_SMEM);
        cudaFuncSetAttribute(k_rec, cudaFuncAttributeNonPortableClusterSizeAllowed, 1);
        {
            cudaLaunchConfig_t cfg = {};
            cfg.gridDim = dim3(128); cfg.blockDim = dim3(384); cfg.dynamicSmemBytes = R_SMEM;
            cudaLaunchAttribute at[1];
            at[0].id = cudaLaunchAttributeClusterDimension; at[0].val.clusterDim.x = 16; at[0].val.clusterDim.y = 1; at[0].val.clusterDim.z = 1;
            cfg.attrs = at; cfg.numAttrs = 1;
            int n = 0;
            cudaOccupancyMaxActiveClusters(&n, k_rec, &cfg);
            rp.ncl = n < 4 ? 4 : (n > 8 ? 8 : n);
        }
        for (int i = 0; i < 13; i++) key[i] = d_in[i];
        key[13] = d_out;
        ready = true;
    }
    cudaStream_t st = cudaStreamPerThread;
    PrefetchList pf;
    pf.p[0] = (const bf16*)d_in[3]; pf.p[1] = (const bf16*)d_in[4]; pf.p[2] = (const bf16*)d_in[2]; pf.p[3] = (const bf16*)d_in[5]; pf.p[4] = nullptr;
    k_mod<<<96, 256, 0, st>>>((const bf16*)d_in[11], (const bf16*)d_in[12], pf);
    {
        cudaLaunchConfig_t cfg = {};
        cfg.gridDim = dim3(S_ / 8); cfg.blockDim = dim3(256); cfg.stream = st;
        cudaLaunchAttribute at[1];
        at[0].id = cudaLaunchAttributeProgrammaticStreamSerialization; at[0].val.programmaticStreamSerializationAllowed = 1;
        cfg.attrs = at; cfg.numAttrs = 1;
        cudaLaunchKernelEx(&cfg, k_ln1, (const bf16*)d_in[0]);
    }
    auto launch_rec = [&]() {
        cudaLaunchConfig_t cfg = {};
        cfg.gridDim = dim3(16 * rp.ncl); cfg.blockDim = dim3(384); cfg.dynamicSmemBytes = R_SMEM; cfg.stream = st;
        cudaLaunchAttribute at[1];
        at[0].id = cudaLaunchAttributeClusterDimension; at[0].val.clusterDim.x = 16; at[0].val.clusterDim.y = 1; at[0].val.clusterDim.z = 1;
        cfg.attrs = at; cfg.numAttrs = 1;
        cudaLaunchKernelEx(&cfg, k_rec, rp);
    };
    auto launch_work = [&](int qmask, int pdl) {
        prm.qmask = qmask;
        cudaLaunchConfig_t cfg = {};
        cfg.gridDim = dim3(132); cfg.blockDim = dim3(384); cfg.dynamicSmemBytes = SMEM_BYTES; cfg.stream = st;
        cudaLaunchAttribute at[1];
        at[0].id = cudaLaunchAttributeProgrammaticStreamSerialization; at[0].val.programmaticStreamSerializationAllowed = 1;
        cfg.attrs = at; cfg.numAttrs = pdl;
        cudaLaunchKernelEx(&cfg, k_work, prm);
    };
    launch_rec();
    launch_work(0x3f, 1);
}
```

```cpp
#include <cuda_runtime.h>
#include <cuda_bf16.h>
#include <cuda.h>
#include <stdint.h>

typedef __nv_bfloat16 bf16;

constexpr int S_ = 2048, D_ = 512, H_ = 32, DH_ = 128, HD_ = 4096, NSEG = 64, DF_ = 1792;
constexpr int NRB = 16;
constexpr int OSPLIT = 4;

__device__ __align__(1024) bf16 g_h[S_ * D_];
__device__ __align__(1024) bf16 g_kv[S_ * 2 * HD_];
__device__ __align__(1024) bf16 g_kvm[NSEG * 8 * 2 * HD_];
__device__ __align__(1024) bf16 g_o[S_ * HD_];
#define FINE_RB_ 14
constexpr int FINE_RB = FINE_RB_;
constexpr int OSPLIT2 = 16;
constexpr int OP_ROWS = OSPLIT * S_ + OSPLIT2 * (NRB - FINE_RB) * 128;
__device__ __align__(1024) bf16 g_op[OP_ROWS * D_];
__device__ __align__(1024) bf16 g_x1[S_ * D_];
__device__ __align__(1024) bf16 g_h2[S_ * D_];
__device__ __align__(1024) bf16 g_act[S_ * DF_];
__device__ __align__(1024) bf16 g_mod[6 * D_];
__device__ uint32_t g_Fraw[131072 + 65536 + 2048];
#define g_F ((uint32_t*)(((uint64_t)g_Fraw + 0x7FFFFull) & ~0x7FFFFull))
constexpr int F_KV = 0, F_MEM = 32, F_O = 64, F_OP = 96, F_H2 = 128, F_ACT = 160, F_CLAIM = 192  , F_SIDE = 384  , F_TOTAL = 448;
__device__ __align__(128) unsigned int g_flags[F_TOTAL];
#define TR(j, i) do {} while (0)

__device__ __forceinline__ uint32_t smem_u32(const void* p) { return (uint32_t)__cvta_generic_to_shared(p); }
__device__ __forceinline__ uint32_t clk32() { uint32_t c; asm volatile("mov.u32 %0, %%clock;" : "=r"(c)); return c; }
__device__ __forceinline__ uint32_t mapa_u32(uint32_t addr, uint32_t rank) {
    uint32_t r; asm volatile("mapa.shared::cluster.u32 %0, %1, %2;" : "=r"(r) : "r"(addr), "r"(rank)); return r;
}
__device__ __forceinline__ void mbar_init(uint32_t bar, uint32_t cnt) {
    asm volatile("mbarrier.init.shared::cta.b64 [%0], %1;" :: "r"(bar), "r"(cnt) : "memory");
}
__device__ __forceinline__ void mbar_inval(uint32_t bar) {
    asm volatile("mbarrier.inval.shared::cta.b64 [%0];" :: "r"(bar) : "memory");
}
__device__ __forceinline__ void mbar_expect_tx(uint32_t bar, uint32_t bytes) {
    asm volatile("mbarrier.arrive.expect_tx.shared::cta.b64 _, [%0], %1;" :: "r"(bar), "r"(bytes) : "memory");
}
__device__ __forceinline__ void mbar_arrive(uint32_t bar) {
    asm volatile("mbarrier.arrive.shared::cta.b64 _, [%0];" :: "r"(bar) : "memory");
}
__device__ __forceinline__ bool mbar_try_wait(uint32_t bar, uint32_t parity) {
    uint32_t ok;
    asm volatile("{\n.reg .pred p;\nmbarrier.try_wait.parity.shared::cta.b64 p, [%1], %2;\nselp.u32 %0, 1, 0, p;\n}"
                 : "=r"(ok) : "r"(bar), "r"(parity) : "memory");
    return ok;
}
__device__ __forceinline__ bool mbar_try_wait_cluster(uint32_t bar, uint32_t parity) {
    uint32_t ok;
    asm volatile("{\n.reg .pred p;\nmbarrier.try_wait.parity.acquire.cluster.shared::cta.b64 p, [%1], %2;\nselp.u32 %0, 1, 0, p;\n}"
                 : "=r"(ok) : "r"(bar), "r"(parity) : "memory");
    return ok;
}
constexpr int SPIN_LIMIT = 1 << 18;
#define TIMEOUT(code, info) do {} while (0)
__device__ __forceinline__ void mbar_wait(uint32_t bar, uint32_t parity) {
    int g = 0;
#pragma unroll 1
    while (!mbar_try_wait(bar, parity)) { if (++g >= SPIN_LIMIT) { TIMEOUT(0, bar & 255); break; } }
}
__device__ __forceinline__ void mbar_wait_cluster(uint32_t bar, uint32_t parity) {
    int g = 0;
#pragma unroll 1
    while (!mbar_try_wait_cluster(bar, parity)) { if (++g >= SPIN_LIMIT) { TIMEOUT(1, bar & 255); break; } }
}
__device__ __forceinline__ void bar_sync(int id, int n) { asm volatile("bar.sync %0, %1;" :: "r"(id), "r"(n) : "memory"); }
__device__ __forceinline__ void bar_arrive(int id, int n) { asm volatile("bar.arrive %0, %1;" :: "r"(id), "r"(n) : "memory"); }
__device__ __forceinline__ void cluster_sync_all() {
    asm volatile("barrier.cluster.arrive.aligned;\nbarrier.cluster.wait.aligned;" ::: "memory");
}
__device__ __forceinline__ void st_async_v2(uint32_t addr, float a, float b, uint32_t bar) {
    asm volatile("st.async.weak.shared::cluster.mbarrier::complete_tx::bytes.v2.f32 [%0], {%1,%2}, [%3];"
                 :: "r"(addr), "f"(a), "f"(b), "r"(bar) : "memory");
}
__device__ __forceinline__ void st_async_v4(uint32_t addr, uint4 v, uint32_t bar) {
    asm volatile("st.async.weak.shared::cluster.mbarrier::complete_tx::bytes.v4.b32 [%0], {%1,%2,%3,%4}, [%5];"
                 :: "r"(addr), "r"(v.x), "r"(v.y), "r"(v.z), "r"(v.w), "r"(bar) : "memory");
}
__device__ __forceinline__ uint2 ldg_relaxed2(const uint2* p) {
    uint2 v;
    asm volatile("ld.relaxed.gpu.global.v2.b32 {%0,%1}, [%2];" : "=r"(v.x), "=r"(v.y) : "l"(p) : "memory");
    return v;
}
__device__ __forceinline__ void stg_relaxed2(uint2* p, uint2 v) {
    asm volatile("st.relaxed.gpu.global.v2.b32 [%0], {%1,%2};" :: "l"(p), "r"(v.x), "r"(v.y) : "memory");
}
__device__ __forceinline__ uint4 ldg_relaxed(const uint4* p) {
    uint4 v;
    asm volatile("ld.relaxed.gpu.global.v4.b32 {%0,%1,%2,%3}, [%4];" : "=r"(v.x), "=r"(v.y), "=r"(v.z), "=r"(v.w) : "l"(p) : "memory");
    return v;
}
__device__ __forceinline__ void stg_relaxed(uint4* p, uint4 v) {
    asm volatile("st.relaxed.gpu.global.v4.b32 [%0], {%1,%2,%3,%4};" :: "l"(p), "r"(v.x), "r"(v.y), "r"(v.z), "r"(v.w) : "memory");
}
__device__ __forceinline__ void stg_relaxed32(uint32_t* p, uint32_t v) {
    asm volatile("st.relaxed.gpu.global.b32 [%0], %1;" :: "l"(p), "r"(v) : "memory");
}
__device__ __forceinline__ uint32_t ldg_relaxed32(const uint32_t* p) {
    uint32_t v; asm volatile("ld.relaxed.gpu.global.b32 %0, [%1];" : "=r"(v) : "l"(p) : "memory"); return v;
}
__device__ __forceinline__ unsigned int ld_acquire(const unsigned int* p) {
    unsigned int v; asm volatile("ld.acquire.gpu.global.u32 %0, [%1];" : "=r"(v) : "l"(p) : "memory"); return v;
}
__device__ __forceinline__ void red_release(unsigned int* p, unsigned int v) {
    asm volatile("red.release.gpu.global.add.u32 [%0], %1;" :: "l"(p), "r"(v) : "memory");
}
__device__ __forceinline__ void wait_flag(int idx, unsigned int target) {
    const unsigned int* p = &g_flags[idx];
    int g = 0;
#pragma unroll 1
    while (ld_acquire(p) < target) { __nanosleep(20); if (++g >= 64 * SPIN_LIMIT) { TIMEOUT(2, idx); break; } }
}
__device__ __forceinline__ void cp_async16(uint32_t dst, const void* src) {
    asm volatile("cp.async.cg.shared.global [%0], [%1], 16;" :: "r"(dst), "l"(src) : "memory");
}
__device__ __forceinline__ void cp_async_commit() { asm volatile("cp.async.commit_group;" ::: "memory"); }
template <int N> __device__ __forceinline__ void cp_async_wait() { asm volatile("cp.async.wait_group %0;" :: "n"(N) : "memory"); }
__device__ __forceinline__ void ldsm4(uint32_t& r0, uint32_t& r1, uint32_t& r2, uint32_t& r3, uint32_t addr) {
    asm volatile("ldmatrix.sync.aligned.m8n8.x4.shared.b16 {%0,%1,%2,%3}, [%4];" : "=r"(r0), "=r"(r1), "=r"(r2), "=r"(r3) : "r"(addr) : "memory");
}
__device__ __forceinline__ void ldsm4t(uint32_t& r0, uint32_t& r1, uint32_t& r2, uint32_t& r3, uint32_t addr) {
    asm volatile("ldmatrix.sync.aligned.m8n8.x4.trans.shared.b16 {%0,%1,%2,%3}, [%4];" : "=r"(r0), "=r"(r1), "=r"(r2), "=r"(r3) : "r"(addr) : "memory");
}
__device__ __forceinline__ void ldsm2t(uint32_t& r0, uint32_t& r1, uint32_t addr) {
    asm volatile("ldmatrix.sync.aligned.m8n8.x2.trans.shared.b16 {%0,%1}, [%2];" : "=r"(r0), "=r"(r1) : "r"(addr) : "memory");
}
__device__ __forceinline__ void stsm4(uint32_t addr, uint32_t r0, uint32_t r1, uint32_t r2, uint32_t r3) {
    asm volatile("stmatrix.sync.aligned.m8n8.x4.shared.b16 [%0], {%1,%2,%3,%4};" :: "r"(addr), "r"(r0), "r"(r1), "r"(r2), "r"(r3) : "memory");
}
__device__ __forceinline__ void stsm2t(uint32_t addr, uint32_t r0, uint32_t r1) {
    asm volatile("stmatrix.sync.aligned.m8n8.x2.trans.shared.b16 [%0], {%1,%2};" :: "r"(addr), "r"(r0), "r"(r1) : "memory");
}
__device__ __forceinline__ void mma16816(float* d, uint32_t a0, uint32_t a1, uint32_t a2, uint32_t a3, uint32_t b0, uint32_t b1) {
    asm volatile("mma.sync.aligned.m16n8k16.row.col.f32.bf16.bf16.f32 {%0,%1,%2,%3}, {%4,%5,%6,%7}, {%8,%9}, {%0,%1,%2,%3};"
                 : "+f"(d[0]), "+f"(d[1]), "+f"(d[2]), "+f"(d[3]) : "r"(a0), "r"(a1), "r"(a2), "r"(a3), "r"(b0), "r"(b1));
}
__device__ __forceinline__ void mma1688(float* d, uint32_t a0, uint32_t a1, uint32_t b0) {
    asm volatile("mma.sync.aligned.m16n8k8.row.col.f32.bf16.bf16.f32 {%0,%1,%2,%3}, {%4,%5}, {%6}, {%0,%1,%2,%3};"
                 : "+f"(d[0]), "+f"(d[1]), "+f"(d[2]), "+f"(d[3]) : "r"(a0), "r"(a1), "r"(b0));
}
__device__ __forceinline__ void mma16816h(float* d, uint32_t a0, uint32_t a2, uint32_t b0, uint32_t b1) {
    asm volatile("{\n.reg .b32 ju, jv;\nmma.sync.aligned.m16n8k16.row.col.f32.bf16.bf16.f32 {%0,%1,%2,%3}, {%4,ju,%5,jv}, {%6,%7}, {%0,%1,%2,%3};\n}"
                 : "+f"(d[0]), "+f"(d[1]), "+f"(d[2]), "+f"(d[3]) : "r"(a0), "r"(a2), "r"(b0), "r"(b1));
}
__device__ __forceinline__ void mma1688h(float* d, uint32_t a0, uint32_t b0) {
    asm volatile("{\n.reg .b32 ju;\nmma.sync.aligned.m16n8k8.row.col.f32.bf16.bf16.f32 {%0,%1,%2,%3}, {%4,ju}, {%5}, {%0,%1,%2,%3};\n}"
                 : "+f"(d[0]), "+f"(d[1]), "+f"(d[2]), "+f"(d[3]) : "r"(a0), "r"(b0));
}
__device__ __forceinline__ uint32_t pack2(float lo, float hi) {
    uint32_t r; asm("cvt.rn.bf16x2.f32 %0, %1, %2;" : "=r"(r) : "f"(hi), "f"(lo)); return r;
}
__device__ __forceinline__ float bflo(uint32_t w) { return __uint_as_float(w << 16); }
__device__ __forceinline__ float bfhi(uint32_t w) { return __uint_as_float(w & 0xffff0000u); }
__device__ __forceinline__ float rbf(float x) { return __bfloat162float(__float2bfloat16_rn(x)); }
__device__ __forceinline__ float ex2(float x) { float y; asm("ex2.approx.ftz.f32 %0, %1;" : "=f"(y) : "f"(x)); return y; }
__device__ __forceinline__ void sts128(uint32_t addr, uint4 v) {
    asm volatile("st.shared.v4.b32 [%0], {%1,%2,%3,%4};" :: "r"(addr), "r"(v.x), "r"(v.y), "r"(v.z), "r"(v.w) : "memory");
}
__device__ __forceinline__ uint4 lds128(uint32_t addr) {
    uint4 v; asm volatile("ld.shared.v4.b32 {%0,%1,%2,%3}, [%4];" : "=r"(v.x), "=r"(v.y), "=r"(v.z), "=r"(v.w) : "r"(addr) : "memory"); return v;
}
__device__ __forceinline__ float2 lds64f(uint32_t addr) {
    float2 v; asm volatile("ld.shared.v2.f32 {%0,%1}, [%2];" : "=f"(v.x), "=f"(v.y) : "r"(addr) : "memory"); return v;
}
__device__ __forceinline__ float lds32f(uint32_t addr) {
    float v; asm volatile("ld.shared.f32 %0, [%1];" : "=f"(v) : "r"(addr) : "memory"); return v;
}
__device__ __forceinline__ uint32_t lds32(uint32_t addr) {
    uint32_t v; asm volatile("ld.shared.b32 %0, [%1];" : "=r"(v) : "r"(addr) : "memory"); return v;
}
__device__ __forceinline__ void sts32(uint32_t addr, uint32_t v) { asm volatile("st.shared.b32 [%0], %1;" :: "r"(addr), "r"(v) : "memory"); }
__device__ __forceinline__ void sts64f(uint32_t addr, float a, float b) { asm volatile("st.shared.v2.f32 [%0], {%1,%2};" :: "r"(addr), "f"(a), "f"(b) : "memory"); }

__device__ __forceinline__ void tma_load2d(uint32_t dst, const CUtensorMap* tm, int c0, int c1, uint32_t bar) {
    asm volatile("cp.async.bulk.tensor.2d.shared::cluster.global.mbarrier::complete_tx::bytes [%0], [%1, {%3, %4}], [%2];"
                 :: "r"(dst), "l"(tm), "r"(bar), "r"(c0), "r"(c1) : "memory");
}
__device__ __forceinline__ void tma_store2d(const CUtensorMap* tm, uint32_t src, int c0, int c1) {
    asm volatile("cp.async.bulk.tensor.2d.global.shared::cta.bulk_group [%0, {%2, %3}], [%1];"
                 :: "l"(tm), "r"(src), "r"(c0), "r"(c1) : "memory");
}
__device__ __forceinline__ void bulk_commit() { asm volatile("cp.async.bulk.commit_group;" ::: "memory"); }
__device__ __forceinline__ void bulk_wait0() { asm volatile("cp.async.bulk.wait_group 0;" ::: "memory"); }
__device__ __forceinline__ void fence_async_smem() { asm volatile("fence.proxy.async.shared::cta;" ::: "memory"); }
__device__ __forceinline__ void fence_async_all() { asm volatile("fence.proxy.async;" ::: "memory"); }

__device__ __forceinline__ void wg_fence() { asm volatile("wgmma.fence.sync.aligned;" ::: "memory"); }
__device__ __forceinline__ void wg_commit() { asm volatile("wgmma.commit_group.sync.aligned;" ::: "memory"); }
__device__ __forceinline__ void wg_wait0() { asm volatile("wgmma.wait_group.sync.aligned 0;" ::: "memory"); }
__device__ __forceinline__ uint64_t mkdesc(uint32_t saddr, uint32_t lbo, uint32_t sbo) {
    return (uint64_t)((saddr & 0x3FFFF) >> 4) | ((uint64_t)(lbo >> 4) << 16) | ((uint64_t)(sbo >> 4) << 32) | (1ull << 62);
}
#define ACC8(i) "+f"(d[i]), "+f"(d[i + 1]), "+f"(d[i + 2]), "+f"(d[i + 3]), "+f"(d[i + 4]), "+f"(d[i + 5]), "+f"(d[i + 6]), "+f"(d[i + 7])
__device__ __forceinline__ void wgmma_n256(float* d, uint64_t da, uint64_t db, int scale_d) {
    asm volatile(
        "{\n.reg .pred p;\nsetp.ne.b32 p, %130, 0;\n"
        "wgmma.mma_async.sync.aligned.m64n256k16.f32.bf16.bf16 "
        "{%0,%1,%2,%3,%4,%5,%6,%7,%8,%9,%10,%11,%12,%13,%14,%15,%16,%17,%18,%19,%20,%21,%22,%23,%24,%25,%26,%27,%28,%29,%30,%31,"
        "%32,%33,%34,%35,%36,%37,%38,%39,%40,%41,%42,%43,%44,%45,%46,%47,%48,%49,%50,%51,%52,%53,%54,%55,%56,%57,%58,%59,%60,%61,%62,%63,"
        "%64,%65,%66,%67,%68,%69,%70,%71,%72,%73,%74,%75,%76,%77,%78,%79,%80,%81,%82,%83,%84,%85,%86,%87,%88,%89,%90,%91,%92,%93,%94,%95,"
        "%96,%97,%98,%99,%100,%101,%102,%103,%104,%105,%106,%107,%108,%109,%110,%111,%112,%113,%114,%115,%116,%117,%118,%119,%120,%121,%122,%123,%124,%125,%126,%127}, "
        "%128, %129, p, 1, 1, 0, 1;\n}"
        : ACC8(0), ACC8(8), ACC8(16), ACC8(24), ACC8(32), ACC8(40), ACC8(48), ACC8(56),
          ACC8(64), ACC8(72), ACC8(80), ACC8(88), ACC8(96), ACC8(104), ACC8(112), ACC8(120)
        : "l"(da), "l"(db), "r"(scale_d));
}
__device__ __forceinline__ void wgmma_n128(float* d, uint64_t da, uint64_t db, int scale_d) {
    asm volatile(
        "{\n.reg .pred p;\nsetp.ne.b32 p, %66, 0;\n"
        "wgmma.mma_async.sync.aligned.m64n128k16.f32.bf16.bf16 "
        "{%0,%1,%2,%3,%4,%5,%6,%7,%8,%9,%10,%11,%12,%13,%14,%15,%16,%17,%18,%19,%20,%21,%22,%23,%24,%25,%26,%27,%28,%29,%30,%31,"
        "%32,%33,%34,%35,%36,%37,%38,%39,%40,%41,%42,%43,%44,%45,%46,%47,%48,%49,%50,%51,%52,%53,%54,%55,%56,%57,%58,%59,%60,%61,%62,%63}, "
        "%64, %65, p, 1, 1, 0, 1;\n}"
        : ACC8(0), ACC8(8), ACC8(16), ACC8(24), ACC8(32), ACC8(40), ACC8(48), ACC8(56)
        : "l"(da), "l"(db), "r"(scale_d));
}

__device__ __forceinline__ void wgmma_n64(float* d, uint64_t da, uint64_t db) {
    asm volatile(
        "wgmma.mma_async.sync.aligned.m64n64k16.f32.bf16.bf16 "
        "{%0,%1,%2,%3,%4,%5,%6,%7,%8,%9,%10,%11,%12,%13,%14,%15,%16,%17,%18,%19,%20,%21,%22,%23,%24,%25,%26,%27,%28,%29,%30,%31}, "
        "%32, %33, 1, 1, 1, 0, 1;"
        : ACC8(0), ACC8(8), ACC8(16), ACC8(24)
        : "l"(da), "l"(db));
}
__device__ __forceinline__ void wgmma_n8_ta(float* d, uint64_t da, uint64_t db, int scale_d) {
    asm volatile(
        "{\n.reg .pred p;\nsetp.ne.b32 p, %6, 0;\n"
        "wgmma.mma_async.sync.aligned.m64n8k16.f32.bf16.bf16 {%0,%1,%2,%3}, %4, %5, p, 1, 1, 1, 0;\n}"
        : "+f"(d[0]), "+f"(d[1]), "+f"(d[2]), "+f"(d[3]) : "l"(da), "l"(db), "r"(scale_d));
}

struct PrefetchList { const bf16* p[5]; };
__global__ void __launch_bounds__(256) k_mod(const bf16* __restrict__ c, const bf16* __restrict__ w_mod, const PrefetchList pf) {
    asm volatile("griddepcontrol.launch_dependents;");
    __shared__ float s_c[D_];
    __shared__ float s_red[64][33];
    const int tid = threadIdx.x;
    const int cq = tid & 3, rg = tid >> 2;
    uint4 w[8];
#pragma unroll
    for (int i = 0; i < 8; i++)
        w[i] = __ldg((const uint4*)(w_mod + (size_t)(rg * 8 + i) * (6 * D_) + blockIdx.x * 32 + cq * 8));
    for (int i = tid; i < D_; i += 256) {
        float v = __bfloat162float(c[i]);
        s_c[i] = rbf(v / (1.f + __expf(-v)));
    }
    {
        const int gt = blockIdx.x * 256 + tid, nt = gridDim.x * 256;
        for (int i = gt; i < F_TOTAL; i += nt) g_flags[i] = 0;
        for (int i = gt; i < 65536 + 2048; i += nt) g_F[i] = 0;
        if (tid < 11) {
            const int i = tid * gridDim.x + blockIdx.x;
            if (i < 1024) asm volatile("cp.async.bulk.prefetch.L2.global [%0], %1;" :: "l"(pf.p[i >> 8] + (size_t)(i & 255) * 8192), "r"(16384) : "memory");
        }
    }
    __syncthreads();
    float a[8];
#pragma unroll
    for (int j = 0; j < 8; j++) a[j] = 0.f;
#pragma unroll
    for (int i = 0; i < 8; i++) {
        float cv = s_c[rg * 8 + i];
        a[0] += cv * bflo(w[i].x); a[1] += cv * bfhi(w[i].x); a[2] += cv * bflo(w[i].y); a[3] += cv * bfhi(w[i].y);
        a[4] += cv * bflo(w[i].z); a[5] += cv * bfhi(w[i].z); a[6] += cv * bflo(w[i].w); a[7] += cv * bfhi(w[i].w);
    }
#pragma unroll
    for (int j = 0; j < 8; j++) s_red[rg][cq * 8 + j] = a[j];
    __syncthreads();
    if (tid < 32) {
        float s = 0.f;
#pragma unroll 8
        for (int r = 0; r < 64; r++) s += s_red[r][tid];
        g_mod[blockIdx.x * 32 + tid] = __float2bfloat16_rn(s);
    }
}

__device__ __forceinline__ uint32_t hadd2(uint32_t a, uint32_t b) { uint32_t r; asm("add.rn.bf16x2 %0, %1, %2;" : "=r"(r) : "r"(a), "r"(b)); return r; }
__device__ __forceinline__ uint32_t hsub2(uint32_t a, uint32_t b) { uint32_t r; asm("sub.rn.bf16x2 %0, %1, %2;" : "=r"(r) : "r"(a), "r"(b)); return r; }
__device__ __forceinline__ uint32_t hmul2(uint32_t a, uint32_t b) { uint32_t r; asm("mul.rn.bf16x2 %0, %1, %2;" : "=r"(r) : "r"(a), "r"(b)); return r; }
__device__ __forceinline__ void load_mod8(const bf16* m, int lane, uint32_t* v) {
    const uint4 a = __ldcg((const uint4*)m + lane), b = __ldcg((const uint4*)m + 32 + lane);
    v[0] = a.x; v[1] = a.y; v[2] = a.z; v[3] = a.w; v[4] = b.x; v[5] = b.y; v[6] = b.z; v[7] = b.w;
}
__device__ __forceinline__ void ln_stats(const uint32_t* x, uint32_t& mu2, float& rden) {
    float s = 0.f;
#pragma unroll
    for (int i = 0; i < 8; i++) s += bflo(x[i]) + bfhi(x[i]);
#pragma unroll
    for (int o = 16; o > 0; o >>= 1) s += __shfl_xor_sync(~0u, s, o);
    const float mean = s * (1.f / D_);
    float q = 0.f;
#pragma unroll
    for (int i = 0; i < 8; i++) { const float d0 = bflo(x[i]) - mean, d1 = bfhi(x[i]) - mean; q = fmaf(d0, d0, q); q = fmaf(d1, d1, q); }
#pragma unroll
    for (int o = 16; o > 0; o >>= 1) q += __shfl_xor_sync(~0u, q, o);
    mu2 = pack2(mean, mean);
    rden = __frcp_rn(rbf(__fsqrt_rn(rbf(rbf(q * (1.f / D_)) + 1e-5f))));
}
__device__ __forceinline__ void ln_apply(const uint32_t* x, uint32_t mu2, float rden, const uint32_t* c1, const uint32_t* sm, uint32_t* r) {
#pragma unroll
    for (int i = 0; i < 8; i++) {
        const uint32_t d = hsub2(x[i], mu2);
        r[i] = hadd2(hmul2(pack2(bflo(d) * rden, bfhi(d) * rden), c1[i]), sm[i]);
    }
}

__global__ void __launch_bounds__(256) k_ln1(const bf16* __restrict__ x) {
    const int lane = threadIdx.x & 31, row = blockIdx.x * 8 + (threadIdx.x >> 5);
    const uint4* xr = (const uint4*)(x + (size_t)row * D_);
    const uint4 a = __ldg(xr + lane), b = __ldg(xr + 32 + lane);
    const uint32_t v[8] = {a.x, a.y, a.z, a.w, b.x, b.y, b.z, b.w};
    uint32_t mu2; float rden;
    ln_stats(v, mu2, rden);
    asm volatile("griddepcontrol.wait;" ::: "memory");
    uint32_t c1[8], sm[8], r[8];
    load_mod8(g_mod + D_, lane, c1);
    load_mod8(g_mod, lane, sm);
#pragma unroll
    for (int i = 0; i < 8; i++) c1[i] = hadd2(c1[i], 0x3F803F80u);
    ln_apply(v, mu2, rden, c1, sm, r);
    uint4* hr = (uint4*)(g_h + (size_t)row * D_);
    hr[lane] = make_uint4(r[0], r[1], r[2], r[3]); hr[32 + lane] = make_uint4(r[4], r[5], r[6], r[7]);
}

struct __align__(64) Params {
    CUtensorMap tm_h, tm_kv, tm_kvm, tm_o, tm_op, tm_h2, tm_act, tm_x1, tm_out;
    CUtensorMap tm_wq, tm_wk, tm_wv, tm_wo, tm_wg, tm_wu, tm_wd;
    const bf16* x;
    int qmask;
};

constexpr int R_NST = 3;
constexpr uint32_t R_WV = 0, R_MEM = 65536, R_KX = 73728, R_VX = R_KX + R_NST * 4096,
                   R_KMS = R_VX + R_NST * 4096  , R_VMS = R_KMS + 1024,
                   R_QS = R_KMS + 4096, R_OS = R_QS + 1024, R_SX = R_OS + 1024, R_BAR = R_SX + 2560,
                   R_RS = 107520  , R_VP = R_RS + 8192  ,
                   R_STG = R_VP + 8192  , R_SMEM = R_STG + 98304;
static_assert((R_KMS & 4095) == 0, "smem");
static_assert(R_BAR + 64 <= R_RS, "smem");
constexpr uint32_t RB_SX = R_BAR, RB_V = R_BAR + 8, RB_E = R_BAR + 16, RB_A = R_BAR + 24, RB_ROLE = R_BAR + 32, RB_A1 = R_BAR + 40;
constexpr int W_NST = 3;
constexpr uint32_t W_STAGE = 49152, W_STG = W_NST * W_STAGE, W_END = W_STG + 65536;
constexpr uint32_t SM_BAR = W_END;
constexpr uint32_t SMEM_BYTES = W_END + 1024;
constexpr uint32_t B_FULL = 0, B_EMPTY = 32, B_STGFREE = 64, B_REQ = 80, B_RSP = 88, B_NEXT = 96, B_RING = 128;
#define PICK_AHEAD 2

constexpr int NB_X = 11  , NB_Y = 1, NB_Z = 5, NB_B = 2, NB_C = 3, NB_D = 4, NB_W0 = 6  , NB_ST = 9  ;

__device__ __forceinline__ int pos_of_d(int d) {
    const int rem = d & 31;
    return (d & ~31) + ((rem & 7) >> 1) * 8 + (rem & 1) * 4 + (rem >> 3);
}

#define PROF(i) do {} while (0)
#define PROFG(i) do {} while (0)
#define OPAQUE(x) asm volatile("" : "+r"(x))
#define FENCE_SCHED(x) do { if ((x) == 0u) asm volatile("trap;"); } while (0)
#define VK0_ 4
constexpr int VK0 = VK0_;
constexpr int NOFF = 8;
#define VDELAY -1
#define POLL_GAP 90

struct RecParams { const bf16 *mem0, *wq, *wk, *wv, *wo; int ncl; };

__device__ __forceinline__ void rec_qk(const RecParams& p, const uint32_t sb, const int cta, const int warp, int lane, const int sel) {
    const int crank = cta & 15, cl = cta >> 4, rank = cta & 1;
    const int kh = warp >> 2, aa = warp & 3;
    uint32_t wa[2][16][4];
    const uint32_t stg = sb + R_STG + kh * 32768;
    {
        const int t128 = aa * 32 + lane;
        const int row = (lane >> 4) * 8 + (lane & 7);
        const int ch = t128 & 7;
        const size_t goff = (size_t)kh * 256 * HD_ + cta * 64 + ch * 8;
#pragma unroll 4
        for (int dd = 0; dd < 16; dd++) {
            const int d = dd * 16 + (t128 >> 3), pp = pos_of_d(d);
            cp_async16(sb + R_WV + kh * 32768 + pp * 128 + ((ch ^ (pp & 7)) << 4), p.wv + goff + (size_t)d * HD_);
        }
        cp_async_commit();
#pragma unroll 4
        for (int dd = 0; dd < 16; dd++) {
            const int d = dd * 16 + (t128 >> 3), pp = pos_of_d(d);
            cp_async16(stg + pp * 128 + ((ch ^ (pp & 7)) << 4), p.wq + goff + (size_t)d * HD_);
        }
        cp_async_commit();
        {
            const int i0 = (warp * 32 + lane) * 16, tok = i0 >> 9;
            const uint4 m0 = __ldg((const uint4*)(p.mem0 + i0)), m1 = __ldg((const uint4*)(p.mem0 + i0 + 8));
            const uint32_t mw[8] = {m0.x, m0.y, m0.z, m0.w, m1.x, m1.y, m1.z, m1.w};
#pragma unroll
            for (int e = 0; e < 16; e++) {
                const int pp = pos_of_d((i0 & 511) + e);
                const unsigned short v = (unsigned short)(mw[e >> 1] >> ((e & 1) * 16));
                asm volatile("st.shared.u16 [%0], %1;" :: "r"(sb + R_MEM + (pp >> 3) * 128 + tok * 16 + (pp & 7) * 2), "h"(v) : "memory");
            }
        }
        cp_async_wait<1>();
        bar_sync(NB_W0 + kh, 128);
        const uint32_t fv = row * 128 + (((2 * aa + ((lane >> 3) & 1)) ^ (row & 7)) << 4);
#pragma unroll
        for (int ks = 0; ks < 16; ks++) ldsm4t(wa[0][ks][0], wa[0][ks][1], wa[0][ks][2], wa[0][ks][3], sb + R_WV + kh * 32768 + fv + ks * 2048);
        bar_sync(NB_W0 + kh, 128);
#pragma unroll
        for (int ks = 0; ks < 16; ks++)
            sts128(sb + R_WV + kh * 32768 + (aa * 16 + ks) * 512 + lane * 16, make_uint4(wa[0][ks][0], wa[0][ks][1], wa[0][ks][2], wa[0][ks][3]));
        const uint32_t fo = stg + row * 128 + (((4 * (aa & 1) + ((lane >> 3) & 1)) ^ (row & 7)) << 4);
#pragma unroll 1
        for (int m = 0; m < 2; m++) {
            cp_async_wait<0>();
            bar_sync(NB_W0 + kh, 128);
            if ((aa >> 1) == m) {
#pragma unroll
                for (int ks = 0; ks < 16; ks++) {
                    ldsm4t(wa[0][ks][0], wa[0][ks][1], wa[0][ks][2], wa[0][ks][3], fo + ks * 2048);
                    ldsm4t(wa[1][ks][0], wa[1][ks][1], wa[1][ks][2], wa[1][ks][3], (fo ^ 32) + ks * 2048);
                }
            }
            bar_sync(NB_W0 + kh, 128);
            if (m == 0) {
#pragma unroll 4
                for (int dd = 0; dd < 16; dd++) {
                    const int d = dd * 16 + (t128 >> 3), pp = pos_of_d(d);
                    cp_async16(stg + pp * 128 + ((ch ^ (pp & 7)) << 4), p.wk + goff + (size_t)d * HD_);
                }
                cp_async_commit();
            }
        }
    }
    const uint32_t tab = stg + (aa * 32 + lane) * 16;
    {
        const uint32_t l7 = lane & 7, l8 = lane >> 3, g = lane >> 2, t = lane & 3;
        const uint32_t t0 = l7 * 128 + ((l8 ^ l7) << 4);
        const uint32_t tq = l7 * 128 + (((l8 >> 1) ^ l7) << 4);
        const uint32_t bq = warp >> 1, tp = warp & 1;
        uint4 v;
        v.x = sb + (aa < 2 ? R_QS : R_KMS) + l7 * 128 + (((4 * (aa & 1) + 2 * kh + (l8 & 1)) ^ l7) << 4);
        v.y = sb + R_QS + tq;
        v.z = sb + (warp == 0 ? R_KMS : R_KX + (warp - 1) * 1024) + t0;
        v.w = mapa_u32(sb + R_SX + (rank * 5 + warp) * 256 + lane * 8, crank ^ 1);
        sts128(tab, v);
        sts128(tab + 2048, make_uint4(sb + lane * 16 + R_MEM + kh * 4096, sb + lane * 16 + R_WV + warp * 8192,
                                      sb + lane * 16 + R_VP + warp * 512, sb + lane * 16 + R_VP + 4096 + (warp ^ 4) * 512));
        const uint32_t src = (l8 >> 1) * 8 + l7;
        const uint32_t L = bq * 8 + 2 * tp + (l8 & 1);
        const uint32_t d0 = (crank + ((t >> 1) | (g & 6))) & 15;
        v.x = sb + R_RS + src * 512 + ((L ^ (src & 7)) << 4);
        v.y = mapa_u32(sb + R_MEM + (crank * 4 + bq) * 128 + (4 * tp + 2 * (t & 1) + (g & 1)) * 16, d0);
        v.z = mapa_u32(sb + ((crank & 2) ? RB_A1 : RB_A), d0);
        v.w = lane;
        sts128(tab + 4096, v);
        const uint64_t wr = (uint64_t)(g_F + ((crank * 2 + ((crank ^ (crank >> 3) ^ sel) & 1)) * 1024 + warp * 128 + cl * 32 + lane));
        sts128(tab + 6144, make_uint4((uint32_t)wr, (uint32_t)(wr >> 32), (uint32_t)((((cl + 1) & 3) - cl) * 128), (uint32_t)((((cl + 2) & 3) - cl) * 128)));
        sts32(tab + 8192, (uint32_t)((((cl + 3) & 3) - cl) * 128));
#pragma unroll
        for (int i = 0; i < NOFF; i++)
            sts128(tab + 10240 + i * 2048, make_uint4(wa[i & 1][i >> 1][0], wa[i & 1][i >> 1][1], wa[i & 1][i >> 1][2], wa[i & 1][i >> 1][3]));
    }
    bar_sync(NB_D, 384);
    uint32_t slot_off = 0;
    const uint32_t slot_inc = warp == 0 ? 2048 : 4096, slot_last = warp == 0 ? 2048 : (R_NST - 1) * 4096;
    const uint32_t sx_bar_rem = (sb + RB_SX) ^ (1u << 24);
    uint4 tb = lds128(tab + 2048);
#pragma unroll 1
    for (int s = 0; s < NSEG; s++) {
        if (s > 0) mbar_wait(sb + RB_A, (s - 1) & 1);
        if (warp == 0) { PROF(0); PROFG(13); }
        uint4 ta;
        const uint32_t km_tog = aa >= 2 ? (s & 1) * 2048 : 0;
        {
            float acc[5][4];
#pragma unroll
            for (int c = 0; c < 5; c++) { acc[c][0] = acc[c][1] = acc[c][2] = acc[c][3] = 0.f; }
            uint32_t b[8][4];
            uint4 av[16];
            static_assert(VK0 == 4, "order below assumes the V/O warps cover slices 0,1");
            ldsm4(b[0][0], b[0][1], b[0][2], b[0][3], tb.x);
            ldsm4(b[1][0], b[1][1], b[1][2], b[1][3], tb.x + 512);
            ldsm4(b[4][0], b[4][1], b[4][2], b[4][3], tb.x + 2048);
            ldsm4(b[5][0], b[5][1], b[5][2], b[5][3], tb.x + 2560);
#pragma unroll
            for (int kk = 0; kk < 8; kk++) {
                const int k2 = kk < 2 ? kk : (kk < 4 ? kk + 2 : (kk < 6 ? kk - 2 : kk));
                if (kk == 4) {
                    if (s > 0) mbar_wait(sb + RB_A1, (s - 1) & 1);
                    ldsm4(b[2][0], b[2][1], b[2][2], b[2][3], tb.x + 1024);
                    ldsm4(b[3][0], b[3][1], b[3][2], b[3][3], tb.x + 1536);
                    ldsm4(b[6][0], b[6][1], b[6][2], b[6][3], tb.x + 3072);
                    ldsm4(b[7][0], b[7][1], b[7][2], b[7][3], tb.x + 3584);
#pragma unroll
                    for (int i = 12; i < 16; i++) av[i] = lds128(tb.y + i * 512);
                    ta = lds128(tab);
                }
                mma16816(acc[0], wa[0][2 * k2][0], wa[0][2 * k2][1], wa[0][2 * k2][2], wa[0][2 * k2][3], b[k2][0], b[k2][1]);
                mma16816(acc[1], wa[1][2 * k2][0], wa[1][2 * k2][1], wa[1][2 * k2][2], wa[1][2 * k2][3], b[k2][0], b[k2][1]);
                mma16816(acc[3], wa[0][2 * k2 + 1][0], wa[0][2 * k2 + 1][1], wa[0][2 * k2 + 1][2], wa[0][2 * k2 + 1][3], b[k2][2], b[k2][3]);
                mma16816(acc[4], wa[1][2 * k2 + 1][0], wa[1][2 * k2 + 1][1], wa[1][2 * k2 + 1][2], wa[1][2 * k2 + 1][3], b[k2][2], b[k2][3]);
                if (2 * k2 >= VK0) {
                    mma16816(acc[2], av[2 * k2].x, av[2 * k2].y, av[2 * k2].z, av[2 * k2].w, b[k2][0], b[k2][1]);
                    mma16816(acc[2], av[2 * k2 + 1].x, av[2 * k2 + 1].y, av[2 * k2 + 1].z, av[2 * k2 + 1].w, b[k2][2], b[k2][3]);
                }
                if (kk == 0) { av[8] = lds128(tb.y + 8 * 512); av[9] = lds128(tb.y + 9 * 512); }
                if (kk == 1) { av[10] = lds128(tb.y + 10 * 512); av[11] = lds128(tb.y + 11 * 512); }
                if (kk == 2) { av[4] = lds128(tb.y + 4 * 512); av[5] = lds128(tb.y + 5 * 512); }
                if (kk == 3) { av[6] = lds128(tb.y + 6 * 512); av[7] = lds128(tb.y + 7 * 512); }
            }
#pragma unroll
            for (int i = 0; i < 4; i++) { acc[0][i] += acc[3][i]; acc[1][i] += acc[4][i]; }
            const float g0 = kh ? acc[0][0] : acc[1][0], g1 = kh ? acc[0][1] : acc[1][1], g2 = kh ? acc[0][2] : acc[1][2], g3 = kh ? acc[0][3] : acc[1][3];
            sts128(tb.w, make_uint4(__float_as_uint(g0), __float_as_uint(g1), __float_as_uint(g2), __float_as_uint(g3)));
            const float k0 = kh ? acc[1][0] : acc[0][0], k1 = kh ? acc[1][1] : acc[0][1], k2_ = kh ? acc[1][2] : acc[0][2], k3 = kh ? acc[1][3] : acc[0][3];
            if (warp == 0) PROF(1);
            bar_sync(NB_X + aa, 64);
            const uint4 o = lds128(tb.z + 4096);
            stsm2t(ta.x ^ km_tog, pack2(k0 + __uint_as_float(o.x), k1 + __uint_as_float(o.y)), pack2(k2_ + __uint_as_float(o.z), k3 + __uint_as_float(o.w)));
            sts128(tb.z, make_uint4(__float_as_uint(acc[2][0]), __float_as_uint(acc[2][1]), __float_as_uint(acc[2][2]), __float_as_uint(acc[2][3])));
        }
        const uint32_t kb = ta.z + slot_off;
        if (warp == 0) PROF(14);
        bar_sync(NB_B, 256);
        if (warp < 5) {
            uint32_t q[16], k0, k1, k2, k3, k4, k5, k6, k7;
            float sa[4] = {0.f, 0.f, 0.f, 0.f}, sc[4] = {0.f, 0.f, 0.f, 0.f};
            ldsm4(q[0], q[1], q[2], q[3], ta.y);
            ldsm4(k0, k1, k2, k3, kb);
            ldsm4(q[4], q[5], q[6], q[7], ta.y ^ 32);
            ldsm4(q[8], q[9], q[10], q[11], ta.y ^ 64);
            ldsm4(k4, k5, k6, k7, kb ^ 64);
            ldsm4(q[12], q[13], q[14], q[15], ta.y ^ 96);
            mma16816(sa, q[0], q[1], q[2], q[3], k0, k1);
            bar_arrive(NB_Y, 288);
            mma16816(sc, q[4], q[5], q[6], q[7], k2, k3);
            mma16816(sa, q[8], q[9], q[10], q[11], k4, k5);
            mma16816(sc, q[12], q[13], q[14], q[15], k6, k7);
            const float scl = 0.08838834764831845f * 1.4426950408889634f;
            const float r0 = (sa[0] + sc[0]) * scl, r1 = (sa[1] + sc[1]) * scl;
            if (s != NSEG - 1) {
                st_async_v2(ta.w, r0, r1, sx_bar_rem);
                st_async_v2(ta.w ^ (1u << 24), r0, r1, sx_bar_rem ^ (1u << 24));
            }
            if (warp == 0) PROF(2);
        } else if (s > 0 && warp == 7 && lane == 0) {
            mbar_expect_tx(sb + RB_A, 4096);
            mbar_expect_tx(sb + RB_A1, 4096);
        }
        if (s == NSEG - 1) break;
        slot_off = slot_off == slot_last ? 0 : slot_off + slot_inc;
        const uint4 tc = lds128(tab + 4096), td = lds128(tab + 6144);
        const uint32_t te = lds32(tab + 8192);
        uint32_t* wr = (uint32_t*)(((uint64_t)td.y << 32) | (td.x ^ ((s & 1) * 0x21000)));
        const uint32_t* r1p = (const uint32_t*)((const char*)wr + (int)td.z);
        const uint32_t* r2p = (const uint32_t*)((const char*)wr + (int)td.w);
        const uint32_t* r3p = (const uint32_t*)((const char*)wr + (int)te);
        const uint32_t tag = ((s >> 1) + 1) & 1;
        mbar_wait(sb + RB_E, s & 1);
        if (warp == 0) PROF(7);
        {
            uint32_t a0, a1, a2, a3, a4, a5, a6, a7;
            ldsm4t(a0, a1, a2, a3, tc.x);
            ldsm4t(a4, a5, a6, a7, tc.x ^ 64);
            const uint32_t one = 0x3F803F80u;
            float d0_[4] = {0.f, 0.f, 0.f, 0.f}, d1_[4] = {0.f, 0.f, 0.f, 0.f};
            mma16816(d0_, a0, a1, a2, a3, one, one);
            mma16816(d1_, a4, a5, a6, a7, one, one);
            const bool t1 = tc.w & 1, t2 = tc.w & 2;
            const float x = t2 ? (t1 ? d1_[2] : d1_[0]) : (t1 ? d0_[2] : d0_[0]);
            const uint32_t own = (__float_as_uint(x) & ~1u) | tag;
            stg_relaxed32(wr, own);
            const uint32_t tq = clk32();
            if (warp == 0) PROF(8);
            PROFG(16 + warp);
            while ((int)(clk32() - tq) < POLL_GAP) {}
            uint32_t f1 = ldg_relaxed32(r1p), f2 = ldg_relaxed32(r2p), f3 = ldg_relaxed32(r3p);
#pragma unroll
            for (int i = 0; i < NOFF; i++) {
                const uint4 f0 = lds128(tab + 10240 + i * 2048);
                wa[i & 1][i >> 1][0] = f0.x; wa[i & 1][i >> 1][1] = f0.y; wa[i & 1][i >> 1][2] = f0.z; wa[i & 1][i >> 1][3] = f0.w;
            }
            tb = lds128(tab + 2048);
            int gg = 0;
#pragma unroll 1
            while (!__all_sync(~0u, (((f1 ^ tag) | (f2 ^ tag) | (f3 ^ tag)) & 1) == 0)) {
                f1 = ldg_relaxed32(r1p); f2 = ldg_relaxed32(r2p); f3 = ldg_relaxed32(r3p);
                if (++gg > 16 * SPIN_LIMIT) { TIMEOUT(3, s); break; }
            }
            if (warp == 0) PROF(9);
            const float v = (__uint_as_float(own) + __uint_as_float(f2)) + (__uint_as_float(f1) + __uint_as_float(f3));
            const bool b8 = tc.w & 8, b16 = tc.w & 16;
            const float recv = __shfl_xor_sync(~0u, v, 8);
            const uint32_t word = b8 ? pack2(recv, v) : pack2(v, recv);
            const uint32_t oth = __shfl_xor_sync(~0u, word, 16);
            const uint32_t wl = b16 ? oth : word, wh = b16 ? word : oth;
            const uint32_t p0 = __shfl_xor_sync(~0u, wl, 2), p1 = __shfl_xor_sync(~0u, wh, 2);
            const uint4 item = t2 ? make_uint4(p0, p1, wl, wh) : make_uint4(wl, wh, p0, p1);
            st_async_v4(tc.y, item, tc.z);
            st_async_v4(tc.y ^ (8u << 24), item, tc.z ^ (8u << 24));
            if (tc.w == 0 && warp == 7) mbar_expect_tx(sb + RB_E, 8192);
            if (warp == 0) PROF(10);
            PROF(40 + warp);
        }
        bar_sync(NB_D, 384);
    }
}

__device__ __forceinline__ void rec_load_kv(uint32_t sb, int col0, int s, uint32_t slot_off, int t128) {
    const int row = t128 >> 2, c2 = (t128 & 3) * 2;
    const bf16* src = g_kv + ((size_t)(s * 32 + row) * (2 * HD_) + col0 + c2 * 8);
    const uint32_t d0 = sb + R_KX + slot_off + row * 128 + ((c2 ^ (row & 7)) << 4);
    cp_async16(d0, src);
    cp_async16(d0 ^ 16, src + 8);
    cp_async16(d0 + (R_VX - R_KX), src + HD_);
    cp_async16((d0 ^ 16) + (R_VX - R_KX), src + HD_ + 8);
}

__device__ __forceinline__ void rec_store_kvm(uint32_t sb, int col0, int s, int w, int lane) {
    const int tok = (w & 1) * 4 + (lane >> 3);
    const uint4 v = lds128(sb + R_KMS + (s & 1) * 2048 + (w >> 1) * 1024 + tok * 128 + (((lane & 7) ^ tok) << 4));
    *(uint4*)(g_kvm + ((s * 8 + tok) * (2 * HD_) + (w >> 1) * HD_ + col0 + (lane & 7) * 8)) = v;
}

__device__ __forceinline__ void rec_vo(const RecParams& p, const uint32_t sb, const int cta, const int warp, int lane) {
    const int w = warp - 8, crank = cta & 15;
    const int col0 = cta * 64;
    uint32_t wo[8][4][4];
    {
        const int t128 = w * 32 + lane;
        const bf16* Wo = p.wo + (size_t)col0 * D_;
        const uint32_t stg = sb + R_STG + 2 * 32768;
#pragma unroll
        for (int half = 0; half < 2; half++) {
#pragma unroll 4
            for (int i = t128; i < 2048; i += 128) {
                const int e = i >> 6, ch = i & 63;
                cp_async16(stg + e * 1024 + ((ch ^ (e & 7)) << 4), Wo + (size_t)(half * 32 + e) * D_ + ch * 8);
            }
            cp_async_commit();
            cp_async_wait<0>();
            bar_sync(NB_W0 + 2, 128);
#pragma unroll
            for (int j = 0; j < 8; j++)
#pragma unroll
                for (int kk = 0; kk < 2; kk++) {
                    const int e = kk * 16 + (lane >> 4) * 8 + (lane & 7);
                    const int ch = (w * 8 + j) * 2 + ((lane >> 3) & 1);
                    ldsm4t(wo[j][half * 2 + kk][0], wo[j][half * 2 + kk][1], wo[j][half * 2 + kk][2], wo[j][half * 2 + kk][3],
                           stg + e * 1024 + ((ch ^ (e & 7)) << 4));
                }
            bar_sync(NB_W0 + 2, 128);
        }
        if (lane == 0) wait_flag(F_KV + 0, 64);
        __syncwarp();
        rec_load_kv(sb, col0, 0, 0, t128); cp_async_commit();
        rec_load_kv(sb, col0, 1, 4096, t128); cp_async_commit();
        cp_async_wait<1>();
    }
    const uint32_t tab = sb + R_STG + 2 * 32768 + (w * 32 + lane) * 16;
    {
        const uint32_t l7 = lane & 7, l8 = lane >> 3, g = lane >> 2;
        uint4 v;
        v.x = sb + R_VX + ((l8 & 1) * 8 + l7) * 128 + (((2 * w + (l8 >> 1)) ^ l7) << 4);
        v.y = sb + R_OS + g * 128 + (((2 * w) ^ g) << 4) + (lane & 3) * 4;
        v.z = sb + R_VMS + l7 * 128 + (((2 * w + (l8 & 1)) ^ l7) << 4);
        v.w = sb + R_OS + l7 * 128 + ((l8 ^ l7) << 4);
        sts128(tab, v);
        v.x = mapa_u32(sb + R_RS + crank * 512 + ((lane ^ (crank & 7)) << 4), w * 4);
        v.y = mapa_u32(sb + RB_E, w * 4);
        v.z = sb + R_VP + w * 512 + lane * 16;
        v.w = sb + R_SX + lane * 8;
        sts128(tab + 2048, v);
#pragma unroll
        for (int i = 0; i < 8; i++) sts128(tab + 4096 + i * 2048, make_uint4(wo[i][0][0], wo[i][0][1], wo[i][0][2], wo[i][0][3]));
        const int tok = (w & 1) * 4 + (lane >> 3), row = (w * 32 + lane) >> 2, c2 = (lane & 3) * 2;
        const uint64_t kd = (uint64_t)(g_kvm + (tok * (2 * HD_) + (w >> 1) * HD_ + col0 + (lane & 7) * 8));
        const uint64_t ks = (uint64_t)(g_kv + ((size_t)row * (2 * HD_) + col0 + c2 * 8));
        sts128(tab + 20480, make_uint4((uint32_t)kd, (uint32_t)(kd >> 32), (uint32_t)ks, (uint32_t)(ks >> 32)));
        sts128(tab + 22528, make_uint4(sb + R_KMS + (w >> 1) * 1024 + tok * 128 + (((lane & 7) ^ tok) << 4),
                                       sb + R_KX + row * 128 + ((c2 ^ (row & 7)) << 4), lane, 0));
    }
    bar_sync(NB_D, 384);
    const uint32_t lane16 = lds32(tab + 2048 + 8) - R_VP - w * 512;
    uint4 av[2 * VK0];
#pragma unroll
    for (int i = 0; i < 2 * VK0; i++) av[i] = lds128(lane16 + R_WV + (i / VK0) * 32768 + (w * 16 + i % VK0) * 512);
    uint32_t slot_off = 0;
#pragma unroll 1
    for (int s = 0; s < NSEG; s++) {
        if (s > 0) {
            mbar_wait(sb + RB_A, (s - 1) & 1);
            const uint4 tp = lds128(tab + 20480), tq = lds128(tab + 22528);
            if ((s & 3) == 1 && s > 1 && w == 0 && tq.z == 0) red_release(&g_flags[F_MEM + (s >> 2) - 1], 1);
            const uint4 kvm = lds128(tq.x + ((s - 1) & 1) * 2048);
            *(uint4*)((((uint64_t)tp.y << 32) | tp.x) + (uint64_t)(s - 1) * (8 * 2 * HD_ * 2)) = kvm;
            if (s + 1 < NSEG - 1) {
                if (((s + 1) & 3) == 0) { if (tq.z == 0) wait_flag(F_KV + ((s + 1) >> 2), 64); __syncwarp(); }
                const char* src = (const char*)((((uint64_t)tp.w << 32) | tp.z) + (uint64_t)(s + 1) * (32 * 2 * HD_ * 2));
                const uint32_t d0 = tq.y + (slot_off == (R_NST - 1) * 4096 ? 0 : slot_off + 4096);
                cp_async16(d0, src);
                cp_async16(d0 ^ 16, src + 16);
                cp_async16(d0 + (R_VX - R_KX), src + HD_ * 2);
                cp_async16((d0 ^ 16) + (R_VX - R_KX), src + HD_ * 2 + 16);
            }
            cp_async_commit();
        }
        bar_sync(NB_Y, 288);
        uint32_t vb0, vb1;
        {
            float va[4] = {0.f, 0.f, 0.f, 0.f}, vc[4] = {0.f, 0.f, 0.f, 0.f};
            uint32_t bb[VK0][4];
#pragma unroll
            for (int k2 = 0; k2 < VK0; k2++) ldsm4(bb[k2][0], bb[k2][1], bb[k2][2], bb[k2][3], lane16 + R_MEM + (k2 / (VK0 / 2)) * 4096 + (k2 % (VK0 / 2)) * 512);
#pragma unroll
            for (int k2 = 0; k2 < VK0; k2++) {
                mma16816(va, av[2 * k2].x, av[2 * k2].y, av[2 * k2].z, av[2 * k2].w, bb[k2][0], bb[k2][1]);
                mma16816(vc, av[2 * k2 + 1].x, av[2 * k2 + 1].y, av[2 * k2 + 1].z, av[2 * k2 + 1].w, bb[k2][2], bb[k2][3]);
            }
            const uint4 a = lds128(lane16 + R_VP + w * 512), b = lds128(lane16 + R_VP + 2048 + w * 512);
            vb0 = pack2((va[0] + vc[0]) + (__uint_as_float(a.x) + __uint_as_float(b.x)), (va[1] + vc[1]) + (__uint_as_float(a.y) + __uint_as_float(b.y)));
            vb1 = pack2((va[2] + vc[2]) + (__uint_as_float(a.z) + __uint_as_float(b.z)), (va[3] + vc[3]) + (__uint_as_float(a.w) + __uint_as_float(b.w)));
        }
        const uint4 ta = lds128(tab), tb = lds128(tab + 2048);
        uint32_t vx[8];
        ldsm4t(vx[0], vx[1], vx[2], vx[3], ta.x + slot_off);
        ldsm4t(vx[4], vx[5], vx[6], vx[7], ta.x + slot_off + 2048);
#pragma unroll
        for (int i = 0; i < 4; i++) {
            const uint4 f0 = lds128(tab + 4096 + i * 2048);
            wo[i][0][0] = f0.x; wo[i][0][1] = f0.y; wo[i][0][2] = f0.z; wo[i][0][3] = f0.w;
        }
        if (w == 0) PROF(11);
        uint32_t pf[5];
        float oa[2][4] = {{0.f, 0.f, 0.f, 0.f}, {0.f, 0.f, 0.f, 0.f}}, ob_[2][4] = {{0.f, 0.f, 0.f, 0.f}, {0.f, 0.f, 0.f, 0.f}};
        float sm0[4] = {0.f, 0.f, 0.f, 0.f}, sm1[4] = {0.f, 0.f, 0.f, 0.f};
        if (s != NSEG - 1) {
            mbar_wait(sb + RB_SX, s & 1);
            if (w == 0) PROF(4);
            float sv[10];
#pragma unroll
            for (int n = 0; n < 5; n++) {
                const float2 a = lds64f(tb.w + n * 256), b = lds64f(tb.w + (5 + n) * 256);
                sv[2 * n] = a.x + b.x; sv[2 * n + 1] = a.y + b.y;
            }
            float mx = fmaxf(fmaxf(fmaxf(sv[0], sv[1]), fmaxf(sv[2], sv[3])), fmaxf(fmaxf(sv[4], sv[5]), fmaxf(sv[6], sv[7])));
            mx = fmaxf(mx, fmaxf(sv[8], sv[9]));
            mx = fmaxf(mx, __shfl_xor_sync(~0u, mx, 1));
            mx = fmaxf(mx, __shfl_xor_sync(~0u, mx, 2));
#pragma unroll
            for (int n = 1; n < 5; n++) pf[n] = pack2(ex2(sv[2 * n] - mx), ex2(sv[2 * n + 1] - mx));
            pf[0] = pack2(ex2(sv[0] - mx), ex2(sv[1] - mx));
            if (w == 0) PROF(12);
            const uint32_t one = 0x3F803F80u;
            mma16816h(sm0, pf[1], pf[2], one, one);
            mma16816h(oa[0], pf[1], pf[2], vx[0], vx[1]);
            mma16816h(oa[1], pf[1], pf[2], vx[2], vx[3]);
            mma16816h(sm1, pf[3], pf[4], one, one);
            mma16816h(ob_[0], pf[3], pf[4], vx[4], vx[5]);
            mma16816h(ob_[1], pf[3], pf[4], vx[6], vx[7]);
            mma1688h(sm0, pf[0], one);
            mma1688h(oa[0], pf[0], vb0);
            mma1688h(oa[1], pf[0], vb1);
            float inv;
            asm("rcp.approx.ftz.f32 %0, %1;" : "=f"(inv) : "f"(sm0[0] + sm1[0]));
            oa[0][0] += ob_[0][0]; oa[0][1] += ob_[0][1]; oa[1][0] += ob_[1][0]; oa[1][1] += ob_[1][1];
            sts32(ta.y, pack2(oa[0][0] * inv, oa[0][1] * inv));
            sts32(ta.y ^ 16, pack2(oa[1][0] * inv, oa[1][1] * inv));
            const uint32_t oa2 = ta.w ^ 64;
            bar_sync(NB_C, 128);
            if (w == 0) PROF(5);
            uint32_t ob[8];
            ldsm4(ob[0], ob[1], ob[2], ob[3], ta.w);
            ldsm4(ob[4], ob[5], ob[6], ob[7], oa2);
#pragma unroll
            for (int i = 4; i < 8; i++) {
                const uint4 f0 = lds128(tab + 4096 + i * 2048);
                wo[i][0][0] = f0.x; wo[i][0][1] = f0.y; wo[i][0][2] = f0.z; wo[i][0][3] = f0.w;
            }
#pragma unroll
            for (int jj = 0; jj < 2; jj++) {
                if (jj == 1 && tb.w == 0) break;
                float acc[4][4];
#pragma unroll
                for (int c = 0; c < 4; c++) { acc[c][0] = acc[c][1] = acc[c][2] = acc[c][3] = 0.f; }
#pragma unroll
                for (int ks = 0; ks < 4; ks++)
#pragma unroll
                    for (int c = 0; c < 4; c++)
                        mma16816(acc[c], wo[jj * 4 + c][ks][0], wo[jj * 4 + c][ks][1], wo[jj * 4 + c][ks][2], wo[jj * 4 + c][ks][3], ob[2 * ks], ob[2 * ks + 1]);
#pragma unroll
                for (int pr = 0; pr < 2; pr++) {
                    uint4 v;
                    v.x = pack2(acc[2 * pr][0], acc[2 * pr][1]);
                    v.y = pack2(acc[2 * pr][2], acc[2 * pr][3]);
                    v.z = pack2(acc[2 * pr + 1][0], acc[2 * pr + 1][1]);
                    v.w = pack2(acc[2 * pr + 1][2], acc[2 * pr + 1][3]);
                    st_async_v4(tb.x + ((jj * 2 + pr) << 24), v, tb.y + ((jj * 2 + pr) << 24));
                }
            }
            if (w == 0) PROF(6);
        }
        stsm2t(ta.z + (s & 1) * 2048, vb0, vb1);
        cp_async_wait<0>();
        bar_sync(NB_C, 128);
        if (w == 0 && lane == 0 && s != NSEG - 1) mbar_expect_tx(sb + RB_SX, 2560);
        if (s != NSEG - 1) bar_arrive(NB_D, 384);
#pragma unroll
        for (int i = 0; i < 2 * VK0; i++) av[i] = lds128(lane16 + R_WV + (i / VK0) * 32768 + (w * 16 + i % VK0) * 512);
        slot_off = slot_off == (R_NST - 1) * 4096 ? 0 : slot_off + 4096;
    }
    rec_store_kvm(sb, col0, NSEG - 1, w, lane);
    bar_sync(NB_C, 128);
    if (w == 0 && lane == 0) red_release(&g_flags[F_MEM + NRB - 1], 1);
}

__global__ void __launch_bounds__(384, 1) k_rec(const RecParams p) {
    extern __shared__ __align__(1024) unsigned char smem_raw[];
    const uint32_t sb = __shfl_sync(~0u, smem_u32(smem_raw), 0);
    const int warp = __shfl_sync(~0u, threadIdx.x >> 5, 0);
    int lane; asm volatile("mov.u32 %0, %%laneid;" : "=r"(lane));
    const int crank = blockIdx.x & 15, slot = blockIdx.x >> 4;
    asm volatile("griddepcontrol.launch_dependents;");
    if (threadIdx.x == 0) {
        mbar_init(sb + RB_SX, 1); mbar_init(sb + RB_E, 1); mbar_init(sb + RB_A, 1); mbar_init(sb + RB_A1, 1); mbar_init(sb + RB_ROLE, 1);
        asm volatile("fence.mbarrier_init.release.cluster;" ::: "memory");
        mbar_expect_tx(sb + RB_SX, 2560);
        mbar_expect_tx(sb + RB_E, 8192);
        mbar_expect_tx(sb + RB_A, 4096);
        mbar_expect_tx(sb + RB_A1, 4096);
        mbar_expect_tx(sb + RB_ROLE, 4);
    }
    unsigned role = 0;
    if (crank == 0 && threadIdx.x == 0) {
        unsigned x = 0;
        int tm[2] = {0x7fffffff, 0x7fffffff};
#pragma unroll 1
        for (int i = 0; i < 6; i++) {
            const uint32_t t0 = clk32();
            x = atomicAdd(&g_F[65536 + (i & 1) * 1024 + slot * 64 + (x >> 31)], 0u) & 0x7fffffffu;
            if (x == 0x7654321u) sts32(sb + R_BAR + 56, x);
            const int dt = (int)(clk32() - t0);
            if (i >= 2) { if (i & 1) tm[1] = min(tm[1], dt); else tm[0] = min(tm[0], dt); }
        }
        const int side = tm[1] > tm[0];
        const unsigned old = atomicAdd(&g_flags[F_SIDE + side * 32], 1u);
        unsigned c0, c1; int gd = 0;
#pragma unroll 1
        do { c0 = ldg_relaxed32(&g_flags[F_SIDE]); c1 = ldg_relaxed32(&g_flags[F_SIDE + 32]); } while ((int)(c0 + c1) < p.ncl && ++gd < 64 * SPIN_LIMIT);
        const int big = c1 > c0;
        role = side == big ? old : (big ? c1 : c0) + old;
        role |= (big ^ 1) << 8;
    }
    __syncwarp();
    asm volatile("barrier.cluster.arrive.relaxed.aligned;\nbarrier.cluster.wait.aligned;" ::: "memory");
    if (crank == 0 && warp == 0) {
        role = __shfl_sync(~0u, role, 0);
        if (lane < 16)
            asm volatile("st.async.weak.shared::cluster.mbarrier::complete_tx::bytes.u32 [%0], %1, [%2];"
                         :: "r"(mapa_u32(sb + R_BAR + 48, lane)), "r"(role), "r"(mapa_u32(sb + RB_ROLE, lane)) : "memory");
    }
    mbar_wait(sb + RB_ROLE, 0);
    const int rolew = __shfl_sync(~0u, lds32(sb + R_BAR + 48), 0);
    const int cl = rolew & 255;
    if (cl >= 4) return;
    const int cta = cl * 16 + crank;
    if (warp < 8) rec_qk(p, sb, cta, warp, lane, rolew >> 8);
    else rec_vo(p, sb, cta, warp, lane);
}

enum { J_KV = 0, J_QA = 1, J_O = 2, J_LN = 3, J_UP = 4, J_DN = 5, J_UP2 = 6, J_END = 8 };
constexpr int NJ_O = 2 * OSPLIT, NJ_O2 = 2 * OSPLIT2, NJ_LN = 8, NJ_LN2 = 16, NJ_UP = 14, NJ_UP2 = 28, NJ_DN = 8;
__device__ __forceinline__ int nj_coarse(int q) { return q == J_KV ? 32 : (q == J_QA ? 16 : (q == J_O ? NJ_O : (q == J_LN ? NJ_LN : (q == J_UP ? NJ_UP : NJ_DN)))); }
__device__ __forceinline__ int nj_fine(int q) { return q == J_KV ? 32 : (q == J_QA ? 16 : (q == J_O ? NJ_O2 : (q == J_LN ? NJ_LN2 : (q == J_UP ? NJ_UP2 : NJ_DN)))); }
__device__ __forceinline__ int pick_job(int lane, int qmask, int& idx) {
    const int rb = lane & 15, half = lane >> 4;
    const bool fine = rb >= FINE_RB;
    int gd = 0;
#pragma unroll 1
    while (true) {
        unsigned cl[3], dp[3];
#pragma unroll
        for (int i = 0; i < 3; i++) {
            const int q = half + 2 * i;
            cl[i] = ldg_relaxed32(&g_flags[F_CLAIM + q * 32 + rb]);
            dp[i] = ldg_relaxed32(&g_flags[q * 32 + (q == J_QA ? max(rb - 1, 0) : rb)]);
        }
        int pick_q = -1, pick_rb = 0, early_q = -1, early_rb = 0;
        unsigned prev16 = 0;
        bool any = false;
#pragma unroll
        for (int i = 0; i < 3; i++) {
            const int q = half + 2 * i;
            const bool have = ((qmask >> q) & 1) && (int)cl[i] < (fine ? nj_fine(q) : nj_coarse(q));
            const unsigned tgt = q == J_QA ? 64 : 2 * (fine ? nj_fine(q - 1) : nj_coarse(q - 1));
            const bool ready = have && (q == J_KV || (q == J_QA && rb == 0) || dp[i] >= tgt);
            const unsigned mh = __ballot_sync(~0u, have), mr = __ballot_sync(~0u, ready);
            any |= mh != 0;
#pragma unroll
            for (int hf = 0; hf < 2; hf++) {
                const int qq = hf + 2 * i;
                const unsigned r16 = (mr >> (16 * hf)) & 0xffffu, h16 = (mh >> (16 * hf)) & 0xffffu;
                if (r16 && pick_q != J_KV) { pick_q = qq; pick_rb = __ffs(r16) - 1; }
                if (qq >= J_O && early_q < 0 && h16 && __ffs(h16) - 1 >= FINE_RB && (prev16 & ((2u << (__ffs(h16) - 1)) - 1)) == 0) {
                    early_q = qq; early_rb = __ffs(h16) - 1;
                }
                prev16 |= h16;
            }
        }
        if (!any) return J_END;
        if (pick_q < 0) { pick_q = early_q; pick_rb = early_rb; }
        if (pick_q >= 0) {
            int c = 0;
            if (lane == 0) c = (int)atomicAdd(&g_flags[F_CLAIM + pick_q * 32 + pick_rb], 1u);
            c = __shfl_sync(~0u, c, 0);
            const bool f = pick_rb >= FINE_RB;
            if (c < (f ? nj_fine(pick_q) : nj_coarse(pick_q))) {
                idx = pick_q * 600 + pick_rb * 32 + c;
                return (pick_q == J_UP && f ? J_UP2 : pick_q) | (pick_rb << 8) | (c << 16);
            }
        } else {
            __nanosleep(200);
            if (++gd > 16 * SPIN_LIMIT) { TIMEOUT(5, 0); return J_END; }
        }
    }
}
__device__ __forceinline__ int op_row(int rb, int split) {
    return rb < FINE_RB ? split * S_ + rb * 128 : OSPLIT * S_ + (split * (NRB - FINE_RB) + rb - FINE_RB) * 128;
}

struct Pipe { uint32_t stage, phase; };
__device__ __forceinline__ void pipe_next(Pipe& p) { if (++p.stage == W_NST) { p.stage = 0; p.phase ^= 1; } }

__device__ __forceinline__ void scheduler(const Params& p, uint32_t sb, int lane) {
    const uint32_t bars = sb + SM_BAR;
    uint32_t ph = 0;
#pragma unroll 1
    while (true) {
        mbar_wait(bars + B_REQ, ph);
        int j = 4095;
        const int jd = pick_job(lane, p.qmask, j);
        if (lane == 0) { sts32(bars + B_NEXT, (uint32_t)jd); sts32(bars + B_NEXT + 4, (uint32_t)j); mbar_arrive(bars + B_RSP); }
        ph ^= 1;
        if (jd == J_END) break;
        __syncwarp();
    }
}

__device__ __forceinline__ void producer(const Params& p, uint32_t sb) {
    Pipe pp{0, 1};
    const uint32_t bars = sb + SM_BAR;
    uint32_t seq = 0;
    mbar_arrive(bars + B_REQ);
#pragma unroll 1
    while (true) {
        mbar_wait(bars + B_RSP, seq & 1);
        const int jd = (int)lds32(bars + B_NEXT), j = (int)lds32(bars + B_NEXT + 4);
        int left = (jd & 255) == J_DN ? 15 : ((jd & 255) == J_QA ? 12 : ((jd & 255) == J_O ? (((jd >> 8) & 255) >= FINE_RB ? 64 / OSPLIT2 : 64 / OSPLIT) : ((jd & 255) == J_LN ? 1 : 8)));
        left = max(left - PICK_AHEAD, 1);
        TR(j, 1);
        const int type = jd & 255, rb = (jd >> 8) & 255, cb = jd >> 16;
        const bool fine = rb >= FINE_RB;
        bool first = true;
        auto begin_stage = [&](uint32_t bytes) -> uint32_t {
            mbar_wait(bars + B_EMPTY + pp.stage * 8, pp.phase);
            if (first) { sts32(bars + B_RING + (seq & 7) * 4, (uint32_t)jd); sts32(bars + B_RING + 32 + (seq & 7) * 4, (uint32_t)j); first = false; }
            const uint32_t fb = bars + B_FULL + pp.stage * 8;
            if (bytes) mbar_expect_tx(fb, bytes); else mbar_arrive(fb);
            if (--left == 0 && type != J_END) mbar_arrive(bars + B_REQ);
            return fb;
        };
        if (type == J_END || type == J_LN) {
            if (type == J_LN) wait_flag(F_OP + rb, 2 * (fine ? NJ_O2 : NJ_O));
            TR(j, 2);
            begin_stage(0); pipe_next(pp);
            seq++;
            if (type == J_END) break;
            continue;
        }
        const CUtensorMap *ta, *tb0, *tb1;
        int k0 = 0, nk = 8, n0 = cb * 256, n1 = n0 + 128, nb = 4, dep = -1;
        unsigned tgt = 0;
        switch (type) {
            case J_KV: ta = &p.tm_h; tb0 = tb1 = cb < 16 ? &p.tm_wk : &p.tm_wv; n0 = (cb & 15) * 256; n1 = n0 + 128; break;
            case J_QA: ta = &p.tm_h; tb0 = tb1 = &p.tm_wq; break;
            case J_O: ta = &p.tm_o; tb0 = tb1 = &p.tm_wo; n0 = (cb & 1) * 256; n1 = n0 + 128; nk = fine ? 64 / OSPLIT2 : 64 / OSPLIT; k0 = (cb >> 1) * nk * 64;
                      dep = F_O + rb; tgt = 32; break;
            case J_UP: ta = &p.tm_h2; tb0 = &p.tm_wg; tb1 = &p.tm_wu; n0 = n1 = cb * 128; dep = F_H2 + rb; tgt = 2 * NJ_LN; break;
            case J_UP2: ta = &p.tm_h2; tb0 = &p.tm_wg; tb1 = &p.tm_wu; n0 = n1 = cb * 64; nb = 2; dep = F_H2 + rb; tgt = 2 * NJ_LN2; break;
            default: ta = &p.tm_act; tb0 = tb1 = &p.tm_wd; n0 = cb * 64; nk = 0; break;
        }
        const int m0 = rb * 128;
        if (type == J_DN) {
#pragma unroll 1
            for (int kb = 0; kb < 14; kb++) {
                const uint32_t fb = begin_stage(49152);
                const uint32_t st = sb + pp.stage * W_STAGE;
                const int k = kb * 128;
                tma_load2d(st + 32768, tb0, n0, k, fb);
                tma_load2d(st + 40960, tb0, n0, k + 64, fb);
                if (kb == 0) { wait_flag(F_ACT + rb, 2 * (fine ? NJ_UP2 : NJ_UP)); fence_async_all(); TR(j, 2); }
                tma_load2d(st, ta, k, m0, fb);
                tma_load2d(st + 8192, ta, k, m0 + 64, fb);
                tma_load2d(st + 16384, ta, k + 64, m0, fb);
                tma_load2d(st + 24576, ta, k + 64, m0 + 64, fb);
                pipe_next(pp);
            }
        }
#pragma unroll 1
        for (int kb = 0; kb < nk; kb++) {
            const uint32_t fb = begin_stage(16384 + nb * 8192);
            const uint32_t st = sb + pp.stage * W_STAGE;
            const int k = k0 + kb * 64;
            tma_load2d(st + 16384, tb0, n0, k, fb);
            if (nb == 4) {
                tma_load2d(st + 16384 + 8192, tb0, n0 + 64, k, fb);
                tma_load2d(st + 16384 + 16384, tb1, n1, k, fb);
                tma_load2d(st + 16384 + 24576, tb1, n1 + 64, k, fb);
            } else if (nb == 2) {
                tma_load2d(st + 16384 + 8192, tb1, n1, k, fb);
            }
            if (kb == 0) {
                if (dep >= 0) { wait_flag(dep, tgt); if (type >= J_UP) fence_async_all(); }
                TR(j, 2);
            }
            tma_load2d(st, ta, k, m0, fb);
            tma_load2d(st + 8192, ta, k, m0 + 64, fb);
            pipe_next(pp);
        }
        if (type == J_QA) {
            wait_flag(F_KV + rb, 64);
#pragma unroll 1
            for (int i = 0; i < 4; i++) {
                const uint32_t fb = begin_stage(40960);
                const uint32_t st = sb + pp.stage * W_STAGE;
                const int col = (i & 1) * HD_ + (cb * 2 + (i >> 1)) * DH_;
                tma_load2d(st, &p.tm_kv, col, m0, fb);
                tma_load2d(st + 8192, &p.tm_kv, col, m0 + 64, fb);
                tma_load2d(st + 16384, &p.tm_kv, col + 64, m0, fb);
                tma_load2d(st + 24576, &p.tm_kv, col + 64, m0 + 64, fb);
                if (i == 0) { wait_flag(F_MEM + rb, 64); fence_async_all(); }
                tma_load2d(st + 32768, &p.tm_kvm, col, rb * 32, fb);
                tma_load2d(st + 36864, &p.tm_kvm, col + 64, rb * 32, fb);
                pipe_next(pp);
            }
        } else if (type == J_DN) {
            const uint32_t fb = begin_stage(16384);
            const uint32_t st = sb + pp.stage * W_STAGE;
            tma_load2d(st, &p.tm_x1, n0, m0, fb);
            tma_load2d(st + 8192, &p.tm_x1, n0, m0 + 64, fb);
            pipe_next(pp);
        }
        seq++;
    }
}

__device__ __forceinline__ void store_warp(const Params& p, uint32_t sb, int wg, int lane) {
    const uint32_t bars = sb + SM_BAR;
    uint32_t seq = 0;
#pragma unroll 1
    while (true) {
        bar_sync(NB_ST + wg, 160);
        const uint32_t jd = lds32(bars + B_RING + (seq & 7) * 4);
        seq++;
        const int type = jd & 255, rb = (jd >> 8) & 255, cb = jd >> 16;
        if (type == J_END) break;
        if (lane == 0) {
            const uint32_t src = sb + W_STG + wg * 32768;
            const CUtensorMap* tm = nullptr; int n0 = cb * 256, nbox = 4, mrow = rb * 128 + wg * 64, flag = 0;
            switch (type) {
                case J_KV: tm = &p.tm_kv; flag = F_KV + rb; break;
                case J_QA: tm = &p.tm_o; flag = F_O + rb; break;
                case J_O: tm = &p.tm_op; n0 = (cb & 1) * 256; mrow = op_row(rb, cb >> 1) + wg * 64; flag = F_OP + rb; break;
                case J_LN: flag = F_H2 + rb; nbox = 0; break;
                case J_UP: tm = &p.tm_act; n0 = cb * 128; nbox = 2; flag = F_ACT + rb; break;
                case J_UP2: tm = &p.tm_act; n0 = cb * 64; nbox = 1; flag = F_ACT + rb; break;
                default: tm = &p.tm_out; n0 = cb * 64; nbox = 1; flag = -1; break;
            }
#pragma unroll 1
            for (int b = 0; b < nbox; b++) tma_store2d(tm, src + b * 8192, n0 + b * 64, mrow);
            bulk_commit();
            bulk_wait0();
            mbar_arrive(bars + B_STGFREE + wg * 8);
            if (flag >= 0) red_release(&g_flags[flag], 1);
        }
        __syncwarp();
    }
}

__device__ __forceinline__ float gelu_tanh(float x) {
    const float t = x * fmaf(-0.10294324397f, x * x, -2.30220819814f);
    float r; asm("rcp.approx.ftz.f32 %0, %1;" : "=f"(r) : "f"(1.f + ex2(t)));
    return x * r;
}

#define CTR(i) do {} while (0)

template <int NSPLIT>
__device__ __forceinline__ void ln2_row(const Params& p, int rb, int r, int lane) {
    const int row = rb * 128 + r;
    uint4 u[2 * NSPLIT];
#pragma unroll
    for (int sp = 0; sp < NSPLIT; sp++) {
        const uint4* src = (const uint4*)(g_op + (size_t)(op_row(rb, sp) + r) * D_);
        u[2 * sp] = __ldcg(src + lane); u[2 * sp + 1] = __ldcg(src + 32 + lane);
    }
    const uint4* xr = (const uint4*)(p.x + (size_t)row * D_);
    const uint4 xa = __ldg(xr + lane), xb = __ldg(xr + 32 + lane);
    uint32_t ga[8], c1[8], sm[8];
    load_mod8(g_mod + 2 * D_, lane, ga);
    load_mod8(g_mod + 4 * D_, lane, c1);
    load_mod8(g_mod + 3 * D_, lane, sm);
    float a[16];
#pragma unroll
    for (int i = 0; i < 16; i++) a[i] = 0.f;
#pragma unroll
    for (int sp = 0; sp < 2 * NSPLIT; sp++) {
        float* q = a + (sp & 1) * 8;
        q[0] += bflo(u[sp].x); q[1] += bfhi(u[sp].x); q[2] += bflo(u[sp].y); q[3] += bfhi(u[sp].y);
        q[4] += bflo(u[sp].z); q[5] += bfhi(u[sp].z); q[6] += bflo(u[sp].w); q[7] += bfhi(u[sp].w);
    }
    const uint32_t xv[8] = {xa.x, xa.y, xa.z, xa.w, xb.x, xb.y, xb.z, xb.w};
    uint32_t v[8], r8[8];
#pragma unroll
    for (int i = 0; i < 8; i++) v[i] = hadd2(xv[i], hmul2(ga[i], pack2(a[2 * i], a[2 * i + 1])));
    uint4* x1r = (uint4*)(g_x1 + (size_t)row * D_);
    x1r[lane] = make_uint4(v[0], v[1], v[2], v[3]); x1r[32 + lane] = make_uint4(v[4], v[5], v[6], v[7]);
    uint32_t mu2; float rden;
    ln_stats(v, mu2, rden);
#pragma unroll
    for (int i = 0; i < 8; i++) c1[i] = hadd2(c1[i], 0x3F803F80u);
    ln_apply(v, mu2, rden, c1, sm, r8);
    uint4* hr = (uint4*)(g_h2 + (size_t)row * D_);
    hr[lane] = make_uint4(r8[0], r8[1], r8[2], r8[3]); hr[32 + lane] = make_uint4(r8[4], r8[5], r8[6], r8[7]);
}

__device__ __forceinline__ void consumer(const Params& p, uint32_t sb, int warp, int lane) {
    const uint32_t bars = sb + SM_BAR;
    const int wg = warp >> 2, wl = warp & 3;
    const uint32_t l7 = lane & 7, l8 = lane >> 3, g = lane >> 2, t = lane & 3;
    Pipe pp{0, 0};
    uint32_t seq = 0, stg_phase = 1;
    const int srow = wl * 16 + l7 + (l8 & 1) * 8;
    const uint32_t stg_base = sb + W_STG + wg * 32768 + srow * 128;
    const uint32_t sx = ((lane >> 4) ^ (srow & 7)) << 4;
#pragma unroll 1
    while (true) {
        mbar_wait(bars + B_FULL + pp.stage * 8, pp.phase);
        const uint32_t jd = lds32(bars + B_RING + (seq & 7) * 4);
        CTR(3);
        seq++;
        const int type = jd & 255, rb = (jd >> 8) & 255, cb = jd >> 16;
        if (type == J_END) { mbar_wait(bars + B_STGFREE + wg * 8, stg_phase); bar_arrive(NB_ST + wg, 160); break; }
        if (type == J_LN) {
            __syncwarp();
            if (lane == 0) mbar_arrive(bars + B_EMPTY + pp.stage * 8);
            pipe_next(pp);
            if (rb >= FINE_RB) ln2_row<OSPLIT2>(p, rb, cb * 8 + warp, lane);
            else {
#pragma unroll 1
                for (int rr = 0; rr < 2; rr++) ln2_row<OSPLIT>(p, rb, cb * 16 + warp * 2 + rr, lane);
            }
            mbar_wait(bars + B_STGFREE + wg * 8, stg_phase); stg_phase ^= 1;
            CTR(4); CTR(5);
            bar_arrive(NB_ST + wg, 160);
            continue;
        }
        if (type >= J_DN) {
            float acc[64];
#pragma unroll
            for (int i = 0; i < 64; i++) acc[i] = 0.f;
            if (type == J_DN) {
#pragma unroll 1
                for (int kb = 0; kb < 14; kb++) {
                    if (kb) mbar_wait(bars + B_FULL + pp.stage * 8, pp.phase);
                    const uint32_t st = sb + pp.stage * W_STAGE;
                    const uint64_t da = mkdesc(st + wg * 8192, 16, 1024), db = mkdesc(st + 32768, 8192, 1024);
                    wg_fence();
#pragma unroll
                    for (int ks = 0; ks < 8; ks++) wgmma_n64(acc, da + (ks >> 2) * 1024 + (ks & 3) * 2, db + ks * 128);
                    wg_commit();
                    wg_wait0();
                    if (lane == 0) mbar_arrive(bars + B_EMPTY + pp.stage * 8);
                    pipe_next(pp);
                }
            } else {
#pragma unroll 1
                for (int kb = 0; kb < 8; kb++) {
                    if (kb) mbar_wait(bars + B_FULL + pp.stage * 8, pp.phase);
                    const uint32_t st = sb + pp.stage * W_STAGE;
                    const uint64_t da = mkdesc(st + wg * 8192, 16, 1024), db = mkdesc(st + 16384, 8192, 1024);
                    wg_fence();
#pragma unroll
                    for (int ks = 0; ks < 4; ks++) wgmma_n128(acc, da + ks * 2, db + ks * 128, 1);
                    wg_commit();
                    wg_wait0();
                    if (lane == 0) mbar_arrive(bars + B_EMPTY + pp.stage * 8);
                    pipe_next(pp);
                }
            }
            CTR(4);
            if (type == J_UP2) {
                mbar_wait(bars + B_STGFREE + wg * 8, stg_phase); stg_phase ^= 1;
#pragma unroll
                for (int j = 0; j < 4; j++) {
                    uint32_t r[4];
#pragma unroll
                    for (int q = 0; q < 4; q++) {
                        const uint32_t gw = pack2(acc[8 * j + 2 * q], acc[8 * j + 2 * q + 1]);
                        const uint32_t uw = pack2(acc[32 + 8 * j + 2 * q], acc[32 + 8 * j + 2 * q + 1]);
                        r[q] = hmul2(pack2(gelu_tanh(bflo(gw)), gelu_tanh(bfhi(gw))), uw);
                    }
                    stsm4(stg_base + (sx ^ (j << 5)), r[0], r[1], r[2], r[3]);
                }
            } else {
                mbar_wait(bars + B_FULL + pp.stage * 8, pp.phase);
                const uint32_t st = sb + pp.stage * W_STAGE;
                mbar_wait(bars + B_STGFREE + wg * 8, stg_phase); stg_phase ^= 1;
                const uint32_t* gb = (const uint32_t*)(g_mod + 5 * D_ + cb * 64) + t;
                const uint32_t xa = st + wg * 8192 + (wl * 16 + g) * 128 + (g << 4) + t * 4;
#pragma unroll
                for (int j = 0; j < 4; j++) {
                    uint32_t r[4];
#pragma unroll
                    for (int q = 0; q < 4; q++) {
                        const int nt = 2 * j + (q >> 1);
                        const uint32_t xw = lds32((xa ^ ((nt & 7) << 4)) + (nt >> 3) * 16384 + (q & 1) * 1024);
                        r[q] = hadd2(xw, hmul2(__ldcg(gb + nt * 4), pack2(acc[8 * j + 2 * q], acc[8 * j + 2 * q + 1])));
                    }
                    stsm4(stg_base + (j >> 2) * 8192 + (sx ^ ((2 * j & 7) << 4)), r[0], r[1], r[2], r[3]);
                }
                __syncwarp();
                if (lane == 0) mbar_arrive(bars + B_EMPTY + pp.stage * 8);
                pipe_next(pp);
            }
            fence_async_smem();
            CTR(5);
            bar_arrive(NB_ST + wg, 160);
            continue;
        }
        float acc[128];
#pragma unroll
        for (int i = 0; i < 128; i++) acc[i] = 0.f;
        const int nk = type == J_O ? (rb >= FINE_RB ? 64 / OSPLIT2 : 64 / OSPLIT) : 8;
#pragma unroll 1
        for (int kb = 0; kb < nk; kb++) {
            if (kb) mbar_wait(bars + B_FULL + pp.stage * 8, pp.phase);
            const uint32_t st = sb + pp.stage * W_STAGE;
            const uint64_t da = mkdesc(st + wg * 8192, 16, 1024), db = mkdesc(st + 16384, 8192, 1024);
            wg_fence();
#pragma unroll
            for (int ks = 0; ks < 4; ks++) wgmma_n256(acc, da + ks * 2, db + ks * 128, 1);
            wg_commit();
            wg_wait0();
            if (lane == 0) mbar_arrive(bars + B_EMPTY + pp.stage * 8);
            pipe_next(pp);
        }
        CTR(4);
        if (type == J_QA) {
            uint32_t qf[64];
#pragma unroll
            for (int i = 0; i < 64; i++) qf[i] = pack2(acc[2 * i], acc[2 * i + 1]);
            const int sg = warp >> 1, half = warp & 1;
            const float sc = 0.08838834764831845f * 1.4426950408889634f;
            const uint32_t xoff = (sg >> 1) * 8192 + ((sg & 1) * 32 + l7) * 128;
            const uint32_t moff = 32768 + (sg * 8 + l7) * 128;
            const uint32_t kch = (l8 ^ l7) << 4;
            const uint32_t vch = ((l8 & 1) ^ l7) << 4;
            mbar_wait(bars + B_STGFREE + wg * 8, stg_phase); stg_phase ^= 1;
#pragma unroll 1
            for (int hh = 0; hh < 2; hh++) {
                mbar_wait(bars + B_FULL + pp.stage * 8, pp.phase);
                uint32_t st = sb + pp.stage * W_STAGE;
                float sa[5][4];
#pragma unroll
                for (int n = 0; n < 5; n++) sa[n][0] = sa[n][1] = sa[n][2] = sa[n][3] = 0.f;
#pragma unroll
                for (int i = 0; i < 4; i++) {
                    const uint32_t* q = qf + i * 8;
                    uint32_t kk[5][4];
                    ldsm4(kk[0][0], kk[0][1], kk[0][2], kk[0][3], st + moff + (i >> 1) * 4096 + (kch ^ ((i & 1) * 64)));
#pragma unroll
                    for (int n = 1; n < 5; n++)
                        ldsm4(kk[n][0], kk[n][1], kk[n][2], kk[n][3], st + xoff + (n - 1) * 1024 + (i >> 1) * 16384 + (kch ^ ((i & 1) * 64)));
#pragma unroll
                    for (int n = 0; n < 5; n++) mma16816(sa[n], q[0], q[1], q[2], q[3], kk[n][0], kk[n][1]);
#pragma unroll
                    for (int n = 0; n < 5; n++) mma16816(sa[n], q[4], q[5], q[6], q[7], kk[n][2], kk[n][3]);
                }
                __syncwarp();
                if (lane == 0) mbar_arrive(bars + B_EMPTY + pp.stage * 8);
                pipe_next(pp);
                const int iq0 = half * 16 + g - 2 * t, iq1 = iq0 + 8;
                float m0 = fmaxf(sa[0][0], sa[0][1]), m1 = fmaxf(sa[0][2], sa[0][3]);
#pragma unroll
                for (int n = 1; n < 5; n++) {
#pragma unroll
                    for (int e = 0; e < 2; e++) {
                        const int jx = (n - 1) * 8 + e;
                        if (jx > iq0) sa[n][e] = -3.0e38f;
                        if (jx > iq1) sa[n][2 + e] = -3.0e38f;
                        m0 = fmaxf(m0, sa[n][e]); m1 = fmaxf(m1, sa[n][2 + e]);
                    }
                }
                m0 = fmaxf(m0, __shfl_xor_sync(~0u, m0, 1)); m1 = fmaxf(m1, __shfl_xor_sync(~0u, m1, 1));
                m0 = fmaxf(m0, __shfl_xor_sync(~0u, m0, 2)); m1 = fmaxf(m1, __shfl_xor_sync(~0u, m1, 2));
                m0 *= -sc; m1 *= -sc;
                float l0 = 0.f, l1 = 0.f;
                uint32_t p0[5], p1[5];
#pragma unroll
                for (int n = 0; n < 5; n++) {
                    const float e0 = ex2(fmaf(sa[n][0], sc, m0)), e1 = ex2(fmaf(sa[n][1], sc, m0));
                    const float e2 = ex2(fmaf(sa[n][2], sc, m1)), e3 = ex2(fmaf(sa[n][3], sc, m1));
                    l0 += e0 + e1; l1 += e2 + e3;
                    p0[n] = pack2(e0, e1); p1[n] = pack2(e2, e3);
                }
                l0 += __shfl_xor_sync(~0u, l0, 1); l1 += __shfl_xor_sync(~0u, l1, 1);
                l0 += __shfl_xor_sync(~0u, l0, 2); l1 += __shfl_xor_sync(~0u, l1, 2);
                const float i0 = __fdividef(1.f, l0), i1 = __fdividef(1.f, l1);
                mbar_wait(bars + B_FULL + pp.stage * 8, pp.phase);
                st = sb + pp.stage * W_STAGE;
#pragma unroll
                for (int i = 0; i < 32; i++) qf[i] = qf[32 + i];
#pragma unroll 1
                for (int bx = 0; bx < 2; bx++) {
                    float o[8][4];
                    uint32_t vm[8], v0[4][4], v1[4][4];
#pragma unroll
                    for (int ep = 0; ep < 4; ep++) {
                        ldsm2t(vm[2 * ep], vm[2 * ep + 1], st + moff + bx * 4096 + (vch ^ (ep << 5)));
                        const uint32_t va = st + xoff + (l8 >> 1) * 1024 + bx * 16384 + (vch ^ (ep << 5));
                        ldsm4t(v0[ep][0], v0[ep][1], v0[ep][2], v0[ep][3], va);
                        ldsm4t(v1[ep][0], v1[ep][1], v1[ep][2], v1[ep][3], va + 2048);
                    }
#pragma unroll
                    for (int n = 0; n < 8; n++) { o[n][0] = o[n][1] = o[n][2] = o[n][3] = 0.f; mma16816(o[n], p0[0], p1[0], p0[1], p1[1], vm[n], v0[n >> 1][n & 1]); }
#pragma unroll
                    for (int n = 0; n < 8; n++) mma16816(o[n], p0[2], p1[2], p0[3], p1[3], v0[n >> 1][2 + (n & 1)], v1[n >> 1][n & 1]);
#pragma unroll
                    for (int n = 0; n < 8; n++) mma1688(o[n], p0[4], p1[4], v1[n >> 1][2 + (n & 1)]);
#pragma unroll
                    for (int ep = 0; ep < 4; ep++)
                        stsm4(stg_base + (hh * 2 + bx) * 8192 + (sx ^ (ep << 5)),
                              pack2(o[2 * ep][0] * i0, o[2 * ep][1] * i0), pack2(o[2 * ep][2] * i1, o[2 * ep][3] * i1),
                              pack2(o[2 * ep + 1][0] * i0, o[2 * ep + 1][1] * i0), pack2(o[2 * ep + 1][2] * i1, o[2 * ep + 1][3] * i1));
                }
                __syncwarp();
                if (lane == 0) mbar_arrive(bars + B_EMPTY + pp.stage * 8);
                pipe_next(pp);
            }
        } else if (type == J_UP) {
            mbar_wait(bars + B_STGFREE + wg * 8, stg_phase); stg_phase ^= 1;
#pragma unroll
            for (int j = 0; j < 8; j++) {
                uint32_t r[4];
#pragma unroll
                for (int q = 0; q < 4; q++) {
                    const uint32_t gw = pack2(acc[8 * j + 2 * q], acc[8 * j + 2 * q + 1]);
                    const uint32_t uw = pack2(acc[64 + 8 * j + 2 * q], acc[64 + 8 * j + 2 * q + 1]);
                    r[q] = hmul2(pack2(gelu_tanh(bflo(gw)), gelu_tanh(bfhi(gw))), uw);
                }
                stsm4(stg_base + (j >> 2) * 8192 + (sx ^ ((2 * j & 7) << 4)), r[0], r[1], r[2], r[3]);
            }
        } else {
            mbar_wait(bars + B_STGFREE + wg * 8, stg_phase); stg_phase ^= 1;
#pragma unroll
            for (int j = 0; j < 16; j++)
                stsm4(stg_base + (j >> 2) * 8192 + (sx ^ ((2 * j & 7) << 4)),
                      pack2(acc[8 * j], acc[8 * j + 1]), pack2(acc[8 * j + 2], acc[8 * j + 3]),
                      pack2(acc[8 * j + 4], acc[8 * j + 5]), pack2(acc[8 * j + 6], acc[8 * j + 7]));
        }
        fence_async_smem();
        CTR(5);
        bar_arrive(NB_ST + wg, 160);
    }
}

__global__ void __launch_bounds__(384, 1) k_work(const __grid_constant__ Params p) {
    extern __shared__ __align__(1024) unsigned char smem_raw[];
    const uint32_t sb = smem_u32(smem_raw);
    if (sb & 1023) __trap();
    const int warp = __shfl_sync(~0u, threadIdx.x >> 5, 0);
    int lane; asm volatile("mov.u32 %0, %%laneid;" : "=r"(lane));
    if (threadIdx.x == 0) {
        const uint32_t bars = sb + SM_BAR;
        for (int i = 0; i < W_NST; i++) { mbar_init(bars + B_FULL + i * 8, 1); mbar_init(bars + B_EMPTY + i * 8, 8); }
        mbar_init(bars + B_STGFREE, 1); mbar_init(bars + B_STGFREE + 8, 1); mbar_init(bars + B_REQ, 1); mbar_init(bars + B_RSP, 1);
        asm volatile("fence.mbarrier_init.release.cluster;" ::: "memory");
    }
    __syncthreads();
    if (warp < 8) {
        asm volatile("setmaxnreg.inc.sync.aligned.u32 232;");
        consumer(p, sb, warp, lane);
    } else {
        asm volatile("setmaxnreg.dec.sync.aligned.u32 40;");
        if (warp == 8) { if (lane == 0) producer(p, sb); }
        else if (warp < 11) store_warp(p, sb, warp - 9, lane);
        else scheduler(p, sb, lane);
    }
}

typedef CUresult (*EncodeFn)(CUtensorMap*, CUtensorMapDataType, cuuint32_t, void*, const cuuint64_t*, const cuuint64_t*,
                             const cuuint32_t*, const cuuint32_t*, CUtensorMapInterleave, CUtensorMapSwizzle,
                             CUtensorMapL2promotion, CUtensorMapFloatOOBfill);

static void make_map(EncodeFn enc, CUtensorMap* m, const void* ptr, uint64_t rows, uint64_t cols, uint32_t box_rows) {
    cuuint64_t dims[2] = {cols, rows};
    cuuint64_t strides[1] = {cols * 2};
    cuuint32_t box[2] = {64, box_rows};
    cuuint32_t es[2] = {1, 1};
    enc(m, CU_TENSOR_MAP_DATA_TYPE_BFLOAT16, 2, const_cast<void*>(ptr), dims, strides, box, es, CU_TENSOR_MAP_INTERLEAVE_NONE,
        CU_TENSOR_MAP_SWIZZLE_128B, CU_TENSOR_MAP_L2_PROMOTION_L2_256B, CU_TENSOR_MAP_FLOAT_OOB_FILL_NONE);
}
template <typename T> static void* sym_addr(T& sym) { void* p = nullptr; cudaGetSymbolAddress(&p, sym); return p; }

extern "C" void kernel_launch(void* const* d_in, const int* in_sizes, int n_in, void* d_out, int out_size) {
    static Params prm;
    static RecParams rp;
    static bool ready = false;
    static const void* key[14];
    bool same = ready;
    for (int i = 0; i < 13 && same; i++) same = key[i] == d_in[i];
    same = same && key[13] == d_out;
    if (!same) {
        void* fn = nullptr;
        cudaDriverEntryPointQueryResult qr;
        cudaGetDriverEntryPoint("cuTensorMapEncodeTiled", &fn, cudaEnableDefault, &qr);
        EncodeFn enc = (EncodeFn)fn;
        make_map(enc, &prm.tm_h, sym_addr(g_h), S_, D_, 64);
        make_map(enc, &prm.tm_kv, sym_addr(g_kv), S_, 2 * HD_, 64);
        make_map(enc, &prm.tm_kvm, sym_addr(g_kvm), NSEG * 8, 2 * HD_, 32);
        make_map(enc, &prm.tm_o, sym_addr(g_o), S_, HD_, 64);
        make_map(enc, &prm.tm_op, sym_addr(g_op), OP_ROWS, D_, 64);
        make_map(enc, &prm.tm_h2, sym_addr(g_h2), S_, D_, 64);
        make_map(enc, &prm.tm_act, sym_addr(g_act), S_, DF_, 64);
        make_map(enc, &prm.tm_x1, sym_addr(g_x1), S_, D_, 64);
        make_map(enc, &prm.tm_out, d_out, S_, D_, 64);
        make_map(enc, &prm.tm_wq, d_in[2], D_, HD_, 64);
        make_map(enc, &prm.tm_wk, d_in[3], D_, HD_, 64);
        make_map(enc, &prm.tm_wv, d_in[4], D_, HD_, 64);
        make_map(enc, &prm.tm_wo, d_in[5], HD_, D_, 64);
        make_map(enc, &prm.tm_wg, d_in[8], D_, DF_, 64);
        make_map(enc, &prm.tm_wu, d_in[9], D_, DF_, 64);
        make_map(enc, &prm.tm_wd, d_in[10], DF_, D_, 64);
        prm.x = (const bf16*)d_in[0];
        rp.mem0 = (const bf16*)d_in[1];
        rp.wq = (const bf16*)d_in[2]; rp.wk = (const bf16*)d_in[3]; rp.wv = (const bf16*)d_in[4]; rp.wo = (const bf16*)d_in[5];
        cudaFuncSetAttribute(k_work, cudaFuncAttributeMaxDynamicSharedMemorySize, SMEM_BYTES);
        cudaFuncSetAttribute(k_rec, cudaFuncAttributeMaxDynamicSharedMemorySize, R_SMEM);
        cudaFuncSetAttribute(k_rec, cudaFuncAttributeNonPortableClusterSizeAllowed, 1);
        {
            cudaLaunchConfig_t cfg = {};
            cfg.gridDim = dim3(128); cfg.blockDim = dim3(384); cfg.dynamicSmemBytes = R_SMEM;
            cudaLaunchAttribute at[1];
            at[0].id = cudaLaunchAttributeClusterDimension; at[0].val.clusterDim.x = 16; at[0].val.clusterDim.y = 1; at[0].val.clusterDim.z = 1;
            cfg.attrs = at; cfg.numAttrs = 1;
            int n = 0;
            cudaOccupancyMaxActiveClusters(&n, k_rec, &cfg);
            rp.ncl = n < 4 ? 4 : (n > 8 ? 8 : n);
        }
        for (int i = 0; i < 13; i++) key[i] = d_in[i];
        key[13] = d_out;
        ready = true;
    }
    cudaStream_t st = cudaStreamPerThread;
    PrefetchList pf;
    pf.p[0] = (const bf16*)d_in[3]; pf.p[1] = (const bf16*)d_in[4]; pf.p[2] = (const bf16*)d_in[2]; pf.p[3] = (const bf16*)d_in[5]; pf.p[4] = nullptr;
    k_mod<<<96, 256, 0, st>>>((const bf16*)d_in[11], (const bf16*)d_in[12], pf);
    {
        cudaLaunchConfig_t cfg = {};
        cfg.gridDim = dim3(S_ / 8); cfg.blockDim = dim3(256); cfg.stream = st;
        cudaLaunchAttribute at[1];
        at[0].id = cudaLaunchAttributeProgrammaticStreamSerialization; at[0].val.programmaticStreamSerializationAllowed = 1;
        cfg.attrs = at; cfg.numAttrs = 1;
        cudaLaunchKernelEx(&cfg, k_ln1, (const bf16*)d_in[0]);
    }
    auto launch_rec = [&]() {
        cudaLaunchConfig_t cfg = {};
        cfg.gridDim = dim3(16 * rp.ncl); cfg.blockDim = dim3(384); cfg.dynamicSmemBytes = R_SMEM; cfg.stream = st;
        cudaLaunchAttribute at[1];
        at[0].id = cudaLaunchAttributeClusterDimension; at[0].val.clusterDim.x = 16; at[0].val.clusterDim.y = 1; at[0].val.clusterDim.z = 1;
        cfg.attrs = at; cfg.numAttrs = 1;
        cudaLaunchKernelEx(&cfg, k_rec, rp);
    };
    auto launch_work = [&](int qmask, int pdl) {
        prm.qmask = qmask;
        cudaLaunchConfig_t cfg = {};
        cfg.gridDim = dim3(132); cfg.blockDim = dim3(384); cfg.dynamicSmemBytes = SMEM_BYTES; cfg.stream = st;
        cudaLaunchAttribute at[1];
        at[0].id = cudaLaunchAttributeProgrammaticStreamSerialization; at[0].val.programmaticStreamSerializationAllowed = 1;
        cfg.attrs = at; cfg.numAttrs = pdl;
        cudaLaunchKernelEx(&cfg, k_work, prm);
    };
    launch_rec();
    launch_work(0x3f, 1);
}
```

```cpp
#include <cuda_runtime.h>
#include <cuda_bf16.h>
#include <cuda.h>
#include <stdint.h>

typedef __nv_bfloat16 bf16;

constexpr int S_ = 2048, D_ = 512, H_ = 32, DH_ = 128, HD_ = 4096, NSEG = 64, DF_ = 1792;
constexpr int NRB = 16;
constexpr int OSPLIT = 4;

__device__ __align__(1024) bf16 g_h[S_ * D_];
__device__ __align__(1024) bf16 g_kv[S_ * 2 * HD_];
__device__ __align__(1024) bf16 g_kvm[NSEG * 8 * 2 * HD_];
__device__ __align__(1024) bf16 g_o[S_ * HD_];
#define FINE_RB_ 14
constexpr int FINE_RB = FINE_RB_;
constexpr int OSPLIT2 = 8;
constexpr int OP_ROWS = OSPLIT * S_ + OSPLIT2 * (NRB - FINE_RB) * 128;
__device__ __align__(1024) bf16 g_op[OP_ROWS * D_];
__device__ __align__(1024) bf16 g_x1[S_ * D_];
__device__ __align__(1024) bf16 g_h2[S_ * D_];
__device__ __align__(1024) bf16 g_act[S_ * DF_];
__device__ __align__(1024) bf16 g_mod[6 * D_];
__device__ uint32_t g_Fraw[131072 + 65536 + 2048];
#define g_F ((uint32_t*)(((uint64_t)g_Fraw + 0x7FFFFull) & ~0x7FFFFull))
constexpr int F_H = 0, F_MEM = 32, F_O = 64, F_OP = 96, F_H2 = 128, F_ACT = 160, F_MOD = 192, F_KV = 224, F_CLAIM = 256  ,
              F_SIDE = 512  , F_DONE = 576, F_TOTAL = 608;
__device__ __align__(128) unsigned int g_flags[F_TOTAL];
#define TR(j, i) do {} while (0)

__device__ __forceinline__ uint32_t smem_u32(const void* p) { return (uint32_t)__cvta_generic_to_shared(p); }
__device__ __forceinline__ uint32_t clk32() { uint32_t c; asm volatile("mov.u32 %0, %%clock;" : "=r"(c)); return c; }
__device__ __forceinline__ uint32_t mapa_u32(uint32_t addr, uint32_t rank) {
    uint32_t r; asm volatile("mapa.shared::cluster.u32 %0, %1, %2;" : "=r"(r) : "r"(addr), "r"(rank)); return r;
}
__device__ __forceinline__ void mbar_init(uint32_t bar, uint32_t cnt) {
    asm volatile("mbarrier.init.shared::cta.b64 [%0], %1;" :: "r"(bar), "r"(cnt) : "memory");
}
__device__ __forceinline__ void mbar_inval(uint32_t bar) {
    asm volatile("mbarrier.inval.shared::cta.b64 [%0];" :: "r"(bar) : "memory");
}
__device__ __forceinline__ void mbar_expect_tx(uint32_t bar, uint32_t bytes) {
    asm volatile("mbarrier.arrive.expect_tx.shared::cta.b64 _, [%0], %1;" :: "r"(bar), "r"(bytes) : "memory");
}
__device__ __forceinline__ void mbar_arrive(uint32_t bar) {
    asm volatile("mbarrier.arrive.shared::cta.b64 _, [%0];" :: "r"(bar) : "memory");
}
__device__ __forceinline__ bool mbar_try_wait(uint32_t bar, uint32_t parity) {
    uint32_t ok;
    asm volatile("{\n.reg .pred p;\nmbarrier.try_wait.parity.shared::cta.b64 p, [%1], %2;\nselp.u32 %0, 1, 0, p;\n}"
                 : "=r"(ok) : "r"(bar), "r"(parity) : "memory");
    return ok;
}
__device__ __forceinline__ bool mbar_try_wait_cluster(uint32_t bar, uint32_t parity) {
    uint32_t ok;
    asm volatile("{\n.reg .pred p;\nmbarrier.try_wait.parity.acquire.cluster.shared::cta.b64 p, [%1], %2;\nselp.u32 %0, 1, 0, p;\n}"
                 : "=r"(ok) : "r"(bar), "r"(parity) : "memory");
    return ok;
}
constexpr int SPIN_LIMIT = 1 << 18;
#define TIMEOUT(code, info) do {} while (0)
__device__ __forceinline__ void mbar_wait(uint32_t bar, uint32_t parity) {
    int g = 0;
#pragma unroll 1
    while (!mbar_try_wait(bar, parity)) { if (++g >= SPIN_LIMIT) { TIMEOUT(0, bar & 255); break; } }
}
__device__ __forceinline__ void mbar_wait_cluster(uint32_t bar, uint32_t parity) {
    int g = 0;
#pragma unroll 1
    while (!mbar_try_wait_cluster(bar, parity)) { if (++g >= SPIN_LIMIT) { TIMEOUT(1, bar & 255); break; } }
}
__device__ __forceinline__ void bar_sync(int id, int n) { asm volatile("bar.sync %0, %1;" :: "r"(id), "r"(n) : "memory"); }
__device__ __forceinline__ void bar_arrive(int id, int n) { asm volatile("bar.arrive %0, %1;" :: "r"(id), "r"(n) : "memory"); }
__device__ __forceinline__ void cluster_sync_all() {
    asm volatile("barrier.cluster.arrive.aligned;\nbarrier.cluster.wait.aligned;" ::: "memory");
}
__device__ __forceinline__ void st_async_v2(uint32_t addr, float a, float b, uint32_t bar) {
    asm volatile("st.async.weak.shared::cluster.mbarrier::complete_tx::bytes.v2.f32 [%0], {%1,%2}, [%3];"
                 :: "r"(addr), "f"(a), "f"(b), "r"(bar) : "memory");
}
__device__ __forceinline__ void st_async_v4(uint32_t addr, uint4 v, uint32_t bar) {
    asm volatile("st.async.weak.shared::cluster.mbarrier::complete_tx::bytes.v4.b32 [%0], {%1,%2,%3,%4}, [%5];"
                 :: "r"(addr), "r"(v.x), "r"(v.y), "r"(v.z), "r"(v.w), "r"(bar) : "memory");
}
__device__ __forceinline__ uint2 ldg_relaxed2(const uint2* p) {
    uint2 v;
    asm volatile("ld.relaxed.gpu.global.v2.b32 {%0,%1}, [%2];" : "=r"(v.x), "=r"(v.y) : "l"(p) : "memory");
    return v;
}
__device__ __forceinline__ void stg_relaxed2(uint2* p, uint2 v) {
    asm volatile("st.relaxed.gpu.global.v2.b32 [%0], {%1,%2};" :: "l"(p), "r"(v.x), "r"(v.y) : "memory");
}
__device__ __forceinline__ uint4 ldg_relaxed(const uint4* p) {
    uint4 v;
    asm volatile("ld.relaxed.gpu.global.v4.b32 {%0,%1,%2,%3}, [%4];" : "=r"(v.x), "=r"(v.y), "=r"(v.z), "=r"(v.w) : "l"(p) : "memory");
    return v;
}
__device__ __forceinline__ void stg_relaxed(uint4* p, uint4 v) {
    asm volatile("st.relaxed.gpu.global.v4.b32 [%0], {%1,%2,%3,%4};" :: "l"(p), "r"(v.x), "r"(v.y), "r"(v.z), "r"(v.w) : "memory");
}
__device__ __forceinline__ void stg_relaxed32(uint32_t* p, uint32_t v) {
    asm volatile("st.relaxed.gpu.global.b32 [%0], %1;" :: "l"(p), "r"(v) : "memory");
}
__device__ __forceinline__ uint32_t ldg_relaxed32(const uint32_t* p) {
    uint32_t v; asm volatile("ld.relaxed.gpu.global.b32 %0, [%1];" : "=r"(v) : "l"(p) : "memory"); return v;
}
__device__ __forceinline__ unsigned int ld_acquire(const unsigned int* p) {
    unsigned int v; asm volatile("ld.acquire.gpu.global.u32 %0, [%1];" : "=r"(v) : "l"(p) : "memory"); return v;
}
__device__ __forceinline__ void red_release(unsigned int* p, unsigned int v) {
    asm volatile("red.release.gpu.global.add.u32 [%0], %1;" :: "l"(p), "r"(v) : "memory");
}
__device__ __forceinline__ void wait_flag(int idx, unsigned int target) {
    const unsigned int* p = &g_flags[idx];
    int g = 0;
#pragma unroll 1
    while (ld_acquire(p) < target) { __nanosleep(20); if (++g >= 64 * SPIN_LIMIT) { TIMEOUT(2, idx); break; } }
}
__device__ __forceinline__ void cp_async16(uint32_t dst, const void* src) {
    asm volatile("cp.async.cg.shared.global [%0], [%1], 16;" :: "r"(dst), "l"(src) : "memory");
}
__device__ __forceinline__ void cp_async_commit() { asm volatile("cp.async.commit_group;" ::: "memory"); }
template <int N> __device__ __forceinline__ void cp_async_wait() { asm volatile("cp.async.wait_group %0;" :: "n"(N) : "memory"); }
__device__ __forceinline__ void ldsm4(uint32_t& r0, uint32_t& r1, uint32_t& r2, uint32_t& r3, uint32_t addr) {
    asm volatile("ldmatrix.sync.aligned.m8n8.x4.shared.b16 {%0,%1,%2,%3}, [%4];" : "=r"(r0), "=r"(r1), "=r"(r2), "=r"(r3) : "r"(addr) : "memory");
}
__device__ __forceinline__ void ldsm4t(uint32_t& r0, uint32_t& r1, uint32_t& r2, uint32_t& r3, uint32_t addr) {
    asm volatile("ldmatrix.sync.aligned.m8n8.x4.trans.shared.b16 {%0,%1,%2,%3}, [%4];" : "=r"(r0), "=r"(r1), "=r"(r2), "=r"(r3) : "r"(addr) : "memory");
}
__device__ __forceinline__ void ldsm2t(uint32_t& r0, uint32_t& r1, uint32_t addr) {
    asm volatile("ldmatrix.sync.aligned.m8n8.x2.trans.shared.b16 {%0,%1}, [%2];" : "=r"(r0), "=r"(r1) : "r"(addr) : "memory");
}
__device__ __forceinline__ void stsm4(uint32_t addr, uint32_t r0, uint32_t r1, uint32_t r2, uint32_t r3) {
    asm volatile("stmatrix.sync.aligned.m8n8.x4.shared.b16 [%0], {%1,%2,%3,%4};" :: "r"(addr), "r"(r0), "r"(r1), "r"(r2), "r"(r3) : "memory");
}
__device__ __forceinline__ void stsm2t(uint32_t addr, uint32_t r0, uint32_t r1) {
    asm volatile("stmatrix.sync.aligned.m8n8.x2.trans.shared.b16 [%0], {%1,%2};" :: "r"(addr), "r"(r0), "r"(r1) : "memory");
}
__device__ __forceinline__ void mma16816(float* d, uint32_t a0, uint32_t a1, uint32_t a2, uint32_t a3, uint32_t b0, uint32_t b1) {
    asm volatile("mma.sync.aligned.m16n8k16.row.col.f32.bf16.bf16.f32 {%0,%1,%2,%3}, {%4,%5,%6,%7}, {%8,%9}, {%0,%1,%2,%3};"
                 : "+f"(d[0]), "+f"(d[1]), "+f"(d[2]), "+f"(d[3]) : "r"(a0), "r"(a1), "r"(a2), "r"(a3), "r"(b0), "r"(b1));
}
__device__ __forceinline__ void mma1688(float* d, uint32_t a0, uint32_t a1, uint32_t b0) {
    asm volatile("mma.sync.aligned.m16n8k8.row.col.f32.bf16.bf16.f32 {%0,%1,%2,%3}, {%4,%5}, {%6}, {%0,%1,%2,%3};"
                 : "+f"(d[0]), "+f"(d[1]), "+f"(d[2]), "+f"(d[3]) : "r"(a0), "r"(a1), "r"(b0));
}
__device__ __forceinline__ void mma16816h(float* d, uint32_t a0, uint32_t a2, uint32_t b0, uint32_t b1) {
    asm volatile("{\n.reg .b32 ju, jv;\nmma.sync.aligned.m16n8k16.row.col.f32.bf16.bf16.f32 {%0,%1,%2,%3}, {%4,ju,%5,jv}, {%6,%7}, {%0,%1,%2,%3};\n}"
                 : "+f"(d[0]), "+f"(d[1]), "+f"(d[2]), "+f"(d[3]) : "r"(a0), "r"(a2), "r"(b0), "r"(b1));
}
__device__ __forceinline__ void mma1688h(float* d, uint32_t a0, uint32_t b0) {
    asm volatile("{\n.reg .b32 ju;\nmma.sync.aligned.m16n8k8.row.col.f32.bf16.bf16.f32 {%0,%1,%2,%3}, {%4,ju}, {%5}, {%0,%1,%2,%3};\n}"
                 : "+f"(d[0]), "+f"(d[1]), "+f"(d[2]), "+f"(d[3]) : "r"(a0), "r"(b0));
}
__device__ __forceinline__ uint32_t pack2(float lo, float hi) {
    uint32_t r; asm("cvt.rn.bf16x2.f32 %0, %1, %2;" : "=r"(r) : "f"(hi), "f"(lo)); return r;
}
__device__ __forceinline__ float bflo(uint32_t w) { return __uint_as_float(w << 16); }
__device__ __forceinline__ float bfhi(uint32_t w) { return __uint_as_float(w & 0xffff0000u); }
__device__ __forceinline__ float rbf(float x) { return __bfloat162float(__float2bfloat16_rn(x)); }
__device__ __forceinline__ float ex2(float x) { float y; asm("ex2.approx.ftz.f32 %0, %1;" : "=f"(y) : "f"(x)); return y; }
__device__ __forceinline__ void sts128(uint32_t addr, uint4 v) {
    asm volatile("st.shared.v4.b32 [%0], {%1,%2,%3,%4};" :: "r"(addr), "r"(v.x), "r"(v.y), "r"(v.z), "r"(v.w) : "memory");
}
__device__ __forceinline__ uint4 lds128(uint32_t addr) {
    uint4 v; asm volatile("ld.shared.v4.b32 {%0,%1,%2,%3}, [%4];" : "=r"(v.x), "=r"(v.y), "=r"(v.z), "=r"(v.w) : "r"(addr) : "memory"); return v;
}
__device__ __forceinline__ float2 lds64f(uint32_t addr) {
    float2 v; asm volatile("ld.shared.v2.f32 {%0,%1}, [%2];" : "=f"(v.x), "=f"(v.y) : "r"(addr) : "memory"); return v;
}
__device__ __forceinline__ float lds32f(uint32_t addr) {
    float v; asm volatile("ld.shared.f32 %0, [%1];" : "=f"(v) : "r"(addr) : "memory"); return v;
}
__device__ __forceinline__ uint32_t lds32(uint32_t addr) {
    uint32_t v; asm volatile("ld.shared.b32 %0, [%1];" : "=r"(v) : "r"(addr) : "memory"); return v;
}
__device__ __forceinline__ void sts32(uint32_t addr, uint32_t v) { asm volatile("st.shared.b32 [%0], %1;" :: "r"(addr), "r"(v) : "memory"); }
__device__ __forceinline__ void sts64f(uint32_t addr, float a, float b) { asm volatile("st.shared.v2.f32 [%0], {%1,%2};" :: "r"(addr), "f"(a), "f"(b) : "memory"); }

__device__ __forceinline__ void tma_load2d(uint32_t dst, const CUtensorMap* tm, int c0, int c1, uint32_t bar) {
    asm volatile("cp.async.bulk.tensor.2d.shared::cluster.global.mbarrier::complete_tx::bytes [%0], [%1, {%3, %4}], [%2];"
                 :: "r"(dst), "l"(tm), "r"(bar), "r"(c0), "r"(c1) : "memory");
}
__device__ __forceinline__ void tma_store2d(const CUtensorMap* tm, uint32_t src, int c0, int c1) {
    asm volatile("cp.async.bulk.tensor.2d.global.shared::cta.bulk_group [%0, {%2, %3}], [%1];"
                 :: "l"(tm), "r"(src), "r"(c0), "r"(c1) : "memory");
}
__device__ __forceinline__ void bulk_commit() { asm volatile("cp.async.bulk.commit_group;" ::: "memory"); }
__device__ __forceinline__ void bulk_wait0() { asm volatile("cp.async.bulk.wait_group 0;" ::: "memory"); }
__device__ __forceinline__ void fence_async_smem() { asm volatile("fence.proxy.async.shared::cta;" ::: "memory"); }
__device__ __forceinline__ void fence_async_all() { asm volatile("fence.proxy.async;" ::: "memory"); }

__device__ __forceinline__ void wg_fence() { asm volatile("wgmma.fence.sync.aligned;" ::: "memory"); }
__device__ __forceinline__ void wg_commit() { asm volatile("wgmma.commit_group.sync.aligned;" ::: "memory"); }
__device__ __forceinline__ void wg_wait0() { asm volatile("wgmma.wait_group.sync.aligned 0;" ::: "memory"); }
__device__ __forceinline__ uint64_t mkdesc(uint32_t saddr, uint32_t lbo, uint32_t sbo) {
    return (uint64_t)((saddr & 0x3FFFF) >> 4) | ((uint64_t)(lbo >> 4) << 16) | ((uint64_t)(sbo >> 4) << 32) | (1ull << 62);
}
#define ACC8(i) "+f"(d[i]), "+f"(d[i + 1]), "+f"(d[i + 2]), "+f"(d[i + 3]), "+f"(d[i + 4]), "+f"(d[i + 5]), "+f"(d[i + 6]), "+f"(d[i + 7])
__device__ __forceinline__ void wgmma_n256(float* d, uint64_t da, uint64_t db, int scale_d) {
    asm volatile(
        "{\n.reg .pred p;\nsetp.ne.b32 p, %130, 0;\n"
        "wgmma.mma_async.sync.aligned.m64n256k16.f32.bf16.bf16 "
        "{%0,%1,%2,%3,%4,%5,%6,%7,%8,%9,%10,%11,%12,%13,%14,%15,%16,%17,%18,%19,%20,%21,%22,%23,%24,%25,%26,%27,%28,%29,%30,%31,"
        "%32,%33,%34,%35,%36,%37,%38,%39,%40,%41,%42,%43,%44,%45,%46,%47,%48,%49,%50,%51,%52,%53,%54,%55,%56,%57,%58,%59,%60,%61,%62,%63,"
        "%64,%65,%66,%67,%68,%69,%70,%71,%72,%73,%74,%75,%76,%77,%78,%79,%80,%81,%82,%83,%84,%85,%86,%87,%88,%89,%90,%91,%92,%93,%94,%95,"
        "%96,%97,%98,%99,%100,%101,%102,%103,%104,%105,%106,%107,%108,%109,%110,%111,%112,%113,%114,%115,%116,%117,%118,%119,%120,%121,%122,%123,%124,%125,%126,%127}, "
        "%128, %129, p, 1, 1, 0, 1;\n}"
        : ACC8(0), ACC8(8), ACC8(16), ACC8(24), ACC8(32), ACC8(40), ACC8(48), ACC8(56),
          ACC8(64), ACC8(72), ACC8(80), ACC8(88), ACC8(96), ACC8(104), ACC8(112), ACC8(120)
        : "l"(da), "l"(db), "r"(scale_d));
}
__device__ __forceinline__ void wgmma_n128(float* d, uint64_t da, uint64_t db, int scale_d) {
    asm volatile(
        "{\n.reg .pred p;\nsetp.ne.b32 p, %66, 0;\n"
        "wgmma.mma_async.sync.aligned.m64n128k16.f32.bf16.bf16 "
        "{%0,%1,%2,%3,%4,%5,%6,%7,%8,%9,%10,%11,%12,%13,%14,%15,%16,%17,%18,%19,%20,%21,%22,%23,%24,%25,%26,%27,%28,%29,%30,%31,"
        "%32,%33,%34,%35,%36,%37,%38,%39,%40,%41,%42,%43,%44,%45,%46,%47,%48,%49,%50,%51,%52,%53,%54,%55,%56,%57,%58,%59,%60,%61,%62,%63}, "
        "%64, %65, p, 1, 1, 0, 1;\n}"
        : ACC8(0), ACC8(8), ACC8(16), ACC8(24), ACC8(32), ACC8(40), ACC8(48), ACC8(56)
        : "l"(da), "l"(db), "r"(scale_d));
}

__device__ __forceinline__ void wgmma_n64(float* d, uint64_t da, uint64_t db) {
    asm volatile(
        "wgmma.mma_async.sync.aligned.m64n64k16.f32.bf16.bf16 "
        "{%0,%1,%2,%3,%4,%5,%6,%7,%8,%9,%10,%11,%12,%13,%14,%15,%16,%17,%18,%19,%20,%21,%22,%23,%24,%25,%26,%27,%28,%29,%30,%31}, "
        "%32, %33, 1, 1, 1, 0, 1;"
        : ACC8(0), ACC8(8), ACC8(16), ACC8(24)
        : "l"(da), "l"(db));
}
__device__ __forceinline__ void wgmma_n8_ta(float* d, uint64_t da, uint64_t db, int scale_d) {
    asm volatile(
        "{\n.reg .pred p;\nsetp.ne.b32 p, %6, 0;\n"
        "wgmma.mma_async.sync.aligned.m64n8k16.f32.bf16.bf16 {%0,%1,%2,%3}, %4, %5, p, 1, 1, 1, 0;\n}"
        : "+f"(d[0]), "+f"(d[1]), "+f"(d[2]), "+f"(d[3]) : "l"(da), "l"(db), "r"(scale_d));
}

__device__ __forceinline__ uint32_t hadd2(uint32_t a, uint32_t b) { uint32_t r; asm("add.rn.bf16x2 %0, %1, %2;" : "=r"(r) : "r"(a), "r"(b)); return r; }
__device__ __forceinline__ uint32_t hsub2(uint32_t a, uint32_t b) { uint32_t r; asm("sub.rn.bf16x2 %0, %1, %2;" : "=r"(r) : "r"(a), "r"(b)); return r; }
__device__ __forceinline__ uint32_t hmul2(uint32_t a, uint32_t b) { uint32_t r; asm("mul.rn.bf16x2 %0, %1, %2;" : "=r"(r) : "r"(a), "r"(b)); return r; }
__device__ __forceinline__ void load_mod8(const bf16* m, int lane, uint32_t* v) {
    const uint4 a = __ldcg((const uint4*)m + lane), b = __ldcg((const uint4*)m + 32 + lane);
    v[0] = a.x; v[1] = a.y; v[2] = a.z; v[3] = a.w; v[4] = b.x; v[5] = b.y; v[6] = b.z; v[7] = b.w;
}
__device__ __forceinline__ void ln_stats(const uint32_t* x, uint32_t& mu2, float& rden) {
    float s = 0.f;
#pragma unroll
    for (int i = 0; i < 8; i++) s += bflo(x[i]) + bfhi(x[i]);
#pragma unroll
    for (int o = 16; o > 0; o >>= 1) s += __shfl_xor_sync(~0u, s, o);
    const float mean = s * (1.f / D_);
    float q = 0.f;
#pragma unroll
    for (int i = 0; i < 8; i++) { const float d0 = bflo(x[i]) - mean, d1 = bfhi(x[i]) - mean; q = fmaf(d0, d0, q); q = fmaf(d1, d1, q); }
#pragma unroll
    for (int o = 16; o > 0; o >>= 1) q += __shfl_xor_sync(~0u, q, o);
    mu2 = pack2(mean, mean);
    rden = __frcp_rn(rbf(__fsqrt_rn(rbf(rbf(q * (1.f / D_)) + 1e-5f))));
}
__device__ __forceinline__ void ln_apply(const uint32_t* x, uint32_t mu2, float rden, const uint32_t* c1, const uint32_t* sm, uint32_t* r) {
#pragma unroll
    for (int i = 0; i < 8; i++) {
        const uint32_t d = hsub2(x[i], mu2);
        r[i] = hadd2(hmul2(pack2(bflo(d) * rden, bfhi(d) * rden), c1[i]), sm[i]);
    }
}

struct __align__(64) Params {
    CUtensorMap tm_h, tm_kv, tm_kvm, tm_o, tm_op, tm_h2, tm_act, tm_x1, tm_out;
    CUtensorMap tm_wq, tm_wk, tm_wv, tm_wo, tm_wg, tm_wu, tm_wd;
    const bf16 *x, *c, *w_mod;
    int qmask;
};

constexpr int R_NST = 3;
constexpr uint32_t R_WV = 0, R_MEM = 65536, R_KX = 73728, R_VX = R_KX + R_NST * 4096,
                   R_KMS = R_VX + R_NST * 4096  , R_VMS = R_KMS + 1024,
                   R_QS = R_KMS + 4096, R_OS = R_QS + 1024, R_SX = R_OS + 1024, R_BAR = R_SX + 2560,
                   R_RS = 107520  , R_VP = R_RS + 8192  ,
                   R_STG = R_VP + 8192  , R_SMEM = R_STG + 98304;
static_assert((R_KMS & 4095) == 0, "smem");
static_assert(R_BAR + 64 <= R_RS, "smem");
constexpr uint32_t RB_SX = R_BAR, RB_V = R_BAR + 8, RB_E = R_BAR + 16, RB_A = R_BAR + 24, RB_ROLE = R_BAR + 32, RB_A1 = R_BAR + 40;
constexpr int W_NST = 3;
constexpr uint32_t W_STAGE = 49152, W_STG = W_NST * W_STAGE, W_END = W_STG + 65536;
constexpr uint32_t SM_BAR = W_END;
constexpr uint32_t SMEM_BYTES = W_END + 1024 + 2048;
constexpr uint32_t B_FULL = 0, B_EMPTY = 32, B_STGFREE = 64, B_REQ = 80, B_RSP = 88, B_NEXT = 96, B_RING = 128;
#define PICK_AHEAD 2

constexpr int NB_X = 11  , NB_Y = 1, NB_M = 5, NB_B = 2, NB_C = 3, NB_D = 4, NB_W0 = 6  , NB_ST = 9  ;

__device__ __forceinline__ int pos_of_d(int d) {
    const int rem = d & 31;
    return (d & ~31) + ((rem & 7) >> 1) * 8 + (rem & 1) * 4 + (rem >> 3);
}

#define PROF(i) do {} while (0)
#define PROFG(i) do {} while (0)
#define OPAQUE(x) asm volatile("" : "+r"(x))
#define FENCE_SCHED(x) do { if ((x) == 0u) asm volatile("trap;"); } while (0)
#define VK0_ 4
constexpr int VK0 = VK0_;
constexpr int NOFF = 8;
#define VDELAY -1
#define POLL_GAP 110

struct RecParams { const bf16 *mem0, *wq, *wk, *wv, *wo; int ncl; };

__device__ __forceinline__ void rec_qk(const RecParams& p, const uint32_t sb, const int cta, const int warp, int lane, const int sel) {
    const int crank = cta & 15, cl = cta >> 4, rank = cta & 1;
    const int kh = warp >> 2, aa = warp & 3;
    uint32_t wa[2][16][4];
    const uint32_t stg = sb + R_STG + kh * 32768;
    {
        const int t128 = aa * 32 + lane;
        const int row = (lane >> 4) * 8 + (lane & 7);
        const int ch = t128 & 7;
        const size_t goff = (size_t)kh * 256 * HD_ + cta * 64 + ch * 8;
#pragma unroll 4
        for (int dd = 0; dd < 16; dd++) {
            const int d = dd * 16 + (t128 >> 3), pp = pos_of_d(d);
            cp_async16(sb + R_WV + kh * 32768 + pp * 128 + ((ch ^ (pp & 7)) << 4), p.wv + goff + (size_t)d * HD_);
        }
        cp_async_commit();
#pragma unroll 4
        for (int dd = 0; dd < 16; dd++) {
            const int d = dd * 16 + (t128 >> 3), pp = pos_of_d(d);
            cp_async16(stg + pp * 128 + ((ch ^ (pp & 7)) << 4), p.wq + goff + (size_t)d * HD_);
        }
        cp_async_commit();
        {
            const int i0 = (warp * 32 + lane) * 16, tok = i0 >> 9;
            const uint4 m0 = __ldg((const uint4*)(p.mem0 + i0)), m1 = __ldg((const uint4*)(p.mem0 + i0 + 8));
            const uint32_t mw[8] = {m0.x, m0.y, m0.z, m0.w, m1.x, m1.y, m1.z, m1.w};
#pragma unroll
            for (int e = 0; e < 16; e++) {
                const int pp = pos_of_d((i0 & 511) + e);
                const unsigned short v = (unsigned short)(mw[e >> 1] >> ((e & 1) * 16));
                asm volatile("st.shared.u16 [%0], %1;" :: "r"(sb + R_MEM + (pp >> 3) * 128 + tok * 16 + (pp & 7) * 2), "h"(v) : "memory");
            }
        }
        cp_async_wait<1>();
        bar_sync(NB_W0 + kh, 128);
        const uint32_t fv = row * 128 + (((2 * aa + ((lane >> 3) & 1)) ^ (row & 7)) << 4);
#pragma unroll
        for (int ks = 0; ks < 16; ks++) ldsm4t(wa[0][ks][0], wa[0][ks][1], wa[0][ks][2], wa[0][ks][3], sb + R_WV + kh * 32768 + fv + ks * 2048);
        bar_sync(NB_W0 + kh, 128);
#pragma unroll
        for (int ks = 0; ks < 16; ks++)
            sts128(sb + R_WV + kh * 32768 + (aa * 16 + ks) * 512 + lane * 16, make_uint4(wa[0][ks][0], wa[0][ks][1], wa[0][ks][2], wa[0][ks][3]));
        const uint32_t fo = stg + row * 128 + (((4 * (aa & 1) + ((lane >> 3) & 1)) ^ (row & 7)) << 4);
#pragma unroll 1
        for (int m = 0; m < 2; m++) {
            cp_async_wait<0>();
            bar_sync(NB_W0 + kh, 128);
            if ((aa >> 1) == m) {
#pragma unroll
                for (int ks = 0; ks < 16; ks++) {
                    ldsm4t(wa[0][ks][0], wa[0][ks][1], wa[0][ks][2], wa[0][ks][3], fo + ks * 2048);
                    ldsm4t(wa[1][ks][0], wa[1][ks][1], wa[1][ks][2], wa[1][ks][3], (fo ^ 32) + ks * 2048);
                }
            }
            bar_sync(NB_W0 + kh, 128);
            if (m == 0) {
#pragma unroll 4
                for (int dd = 0; dd < 16; dd++) {
                    const int d = dd * 16 + (t128 >> 3), pp = pos_of_d(d);
                    cp_async16(stg + pp * 128 + ((ch ^ (pp & 7)) << 4), p.wk + goff + (size_t)d * HD_);
                }
                cp_async_commit();
            }
        }
    }
    const uint32_t tab = stg + (aa * 32 + lane) * 16;
    {
        const uint32_t l7 = lane & 7, l8 = lane >> 3, g = lane >> 2, t = lane & 3;
        const uint32_t t0 = l7 * 128 + ((l8 ^ l7) << 4);
        const uint32_t tq = l7 * 128 + (((l8 >> 1) ^ l7) << 4);
        const uint32_t bq = warp >> 1, tp = warp & 1;
        uint4 v;
        v.x = sb + (aa < 2 ? R_QS : R_KMS) + l7 * 128 + (((4 * (aa & 1) + 2 * kh + (l8 & 1)) ^ l7) << 4);
        v.y = sb + R_QS + tq;
        v.z = sb + (warp == 0 ? R_KMS : R_KX + (warp - 1) * 1024) + t0;
        v.w = mapa_u32(sb + R_SX + (rank * 5 + warp) * 256 + lane * 8, crank ^ 1);
        sts128(tab, v);
        sts128(tab + 2048, make_uint4(sb + lane * 16 + R_MEM + kh * 4096, sb + lane * 16 + R_WV + warp * 8192,
                                      sb + lane * 16 + R_VP + warp * 512, sb + lane * 16 + R_VP + 4096 + (warp ^ 4) * 512));
        const uint32_t src = (l8 >> 1) * 8 + l7;
        const uint32_t L = bq * 8 + 2 * tp + (l8 & 1);
        const uint32_t d0 = (crank + ((t >> 1) | (g & 6))) & 15;
        v.x = sb + R_RS + src * 512 + ((L ^ (src & 7)) << 4);
        v.y = mapa_u32(sb + R_MEM + (crank * 4 + bq) * 128 + (4 * tp + 2 * (t & 1) + (g & 1)) * 16, d0);
        v.z = mapa_u32(sb + ((crank & 2) ? RB_A1 : RB_A), d0);
        v.w = lane;
        sts128(tab + 4096, v);
        const uint64_t wr = (uint64_t)(g_F + ((crank * 2 + ((crank ^ (crank >> 3) ^ sel) & 1)) * 1024 + warp * 128 + cl * 32 + lane));
        sts128(tab + 6144, make_uint4((uint32_t)wr, (uint32_t)(wr >> 32), (uint32_t)((((cl + 1) & 3) - cl) * 128), (uint32_t)((((cl + 2) & 3) - cl) * 128)));
        sts32(tab + 8192, (uint32_t)((((cl + 3) & 3) - cl) * 128));
#pragma unroll
        for (int i = 0; i < NOFF; i++)
            sts128(tab + 10240 + i * 2048, make_uint4(wa[i & 1][i >> 1][0], wa[i & 1][i >> 1][1], wa[i & 1][i >> 1][2], wa[i & 1][i >> 1][3]));
    }
    bar_sync(NB_D, 384);
    uint32_t slot_off = 0;
    const uint32_t slot_inc = warp == 0 ? 2048 : 4096, slot_last = warp == 0 ? 2048 : (R_NST - 1) * 4096;
    const uint32_t sx_bar_rem = (sb + RB_SX) ^ (1u << 24);
    uint4 tb = lds128(tab + 2048);
#pragma unroll 1
    for (int s = 0; s < NSEG; s++) {
        if (s > 0) mbar_wait(sb + RB_A, (s - 1) & 1);
        if (warp == 0) { PROF(0); PROFG(13); }
        uint4 ta;
        const uint32_t km_tog = aa >= 2 ? (s & 1) * 2048 : 0;
        {
            float acc[5][4];
#pragma unroll
            for (int c = 0; c < 5; c++) { acc[c][0] = acc[c][1] = acc[c][2] = acc[c][3] = 0.f; }
            uint32_t b[8][4];
            uint4 av[16];
            static_assert(VK0 == 4, "order below assumes the V/O warps cover slices 0,1");
            ldsm4(b[0][0], b[0][1], b[0][2], b[0][3], tb.x);
            ldsm4(b[1][0], b[1][1], b[1][2], b[1][3], tb.x + 512);
            ldsm4(b[4][0], b[4][1], b[4][2], b[4][3], tb.x + 2048);
            ldsm4(b[5][0], b[5][1], b[5][2], b[5][3], tb.x + 2560);
#pragma unroll
            for (int kk = 0; kk < 8; kk++) {
                const int k2 = kk < 2 ? kk : (kk < 4 ? kk + 2 : (kk < 6 ? kk - 2 : kk));
                if (kk == 4) {
                    if (s > 0) mbar_wait(sb + RB_A1, (s - 1) & 1);
                    ldsm4(b[2][0], b[2][1], b[2][2], b[2][3], tb.x + 1024);
                    ldsm4(b[3][0], b[3][1], b[3][2], b[3][3], tb.x + 1536);
                    ldsm4(b[6][0], b[6][1], b[6][2], b[6][3], tb.x + 3072);
                    ldsm4(b[7][0], b[7][1], b[7][2], b[7][3], tb.x + 3584);
#pragma unroll
                    for (int i = 12; i < 16; i++) av[i] = lds128(tb.y + i * 512);
                    ta = lds128(tab);
                }
                mma16816(acc[0], wa[0][2 * k2][0], wa[0][2 * k2][1], wa[0][2 * k2][2], wa[0][2 * k2][3], b[k2][0], b[k2][1]);
                mma16816(acc[1], wa[1][2 * k2][0], wa[1][2 * k2][1], wa[1][2 * k2][2], wa[1][2 * k2][3], b[k2][0], b[k2][1]);
                mma16816(acc[3], wa[0][2 * k2 + 1][0], wa[0][2 * k2 + 1][1], wa[0][2 * k2 + 1][2], wa[0][2 * k2 + 1][3], b[k2][2], b[k2][3]);
                mma16816(acc[4], wa[1][2 * k2 + 1][0], wa[1][2 * k2 + 1][1], wa[1][2 * k2 + 1][2], wa[1][2 * k2 + 1][3], b[k2][2], b[k2][3]);
                if (2 * k2 >= VK0) {
                    mma16816(acc[2], av[2 * k2].x, av[2 * k2].y, av[2 * k2].z, av[2 * k2].w, b[k2][0], b[k2][1]);
                    mma16816(acc[2], av[2 * k2 + 1].x, av[2 * k2 + 1].y, av[2 * k2 + 1].z, av[2 * k2 + 1].w, b[k2][2], b[k2][3]);
                }
                if (kk == 0) { av[8] = lds128(tb.y + 8 * 512); av[9] = lds128(tb.y + 9 * 512); }
                if (kk == 1) { av[10] = lds128(tb.y + 10 * 512); av[11] = lds128(tb.y + 11 * 512); }
                if (kk == 2) { av[4] = lds128(tb.y + 4 * 512); av[5] = lds128(tb.y + 5 * 512); }
                if (kk == 3) { av[6] = lds128(tb.y + 6 * 512); av[7] = lds128(tb.y + 7 * 512); }
            }
#pragma unroll
            for (int i = 0; i < 4; i++) { acc[0][i] += acc[3][i]; acc[1][i] += acc[4][i]; }
            const float g0 = kh ? acc[0][0] : acc[1][0], g1 = kh ? acc[0][1] : acc[1][1], g2 = kh ? acc[0][2] : acc[1][2], g3 = kh ? acc[0][3] : acc[1][3];
            sts128(tb.w, make_uint4(__float_as_uint(g0), __float_as_uint(g1), __float_as_uint(g2), __float_as_uint(g3)));
            const float k0 = kh ? acc[1][0] : acc[0][0], k1 = kh ? acc[1][1] : acc[0][1], k2_ = kh ? acc[1][2] : acc[0][2], k3 = kh ? acc[1][3] : acc[0][3];
            if (warp == 0) PROF(1);
            bar_sync(NB_X + aa, 64);
            const uint4 o = lds128(tb.z + 4096);
            stsm2t(ta.x ^ km_tog, pack2(k0 + __uint_as_float(o.x), k1 + __uint_as_float(o.y)), pack2(k2_ + __uint_as_float(o.z), k3 + __uint_as_float(o.w)));
            sts128(tb.z, make_uint4(__float_as_uint(acc[2][0]), __float_as_uint(acc[2][1]), __float_as_uint(acc[2][2]), __float_as_uint(acc[2][3])));
        }
        const uint32_t kb = ta.z + slot_off;
        if (warp == 0) PROF(14);
        bar_sync(NB_B, 256);
        if (warp < 5) {
            uint32_t q[16], k0, k1, k2, k3, k4, k5, k6, k7;
            float sa[4] = {0.f, 0.f, 0.f, 0.f}, sc[4] = {0.f, 0.f, 0.f, 0.f};
            ldsm4(q[0], q[1], q[2], q[3], ta.y);
            ldsm4(k0, k1, k2, k3, kb);
            ldsm4(q[4], q[5], q[6], q[7], ta.y ^ 32);
            ldsm4(q[8], q[9], q[10], q[11], ta.y ^ 64);
            ldsm4(k4, k5, k6, k7, kb ^ 64);
            ldsm4(q[12], q[13], q[14], q[15], ta.y ^ 96);
            mma16816(sa, q[0], q[1], q[2], q[3], k0, k1);
            bar_arrive(NB_Y, 288);
            mma16816(sc, q[4], q[5], q[6], q[7], k2, k3);
            mma16816(sa, q[8], q[9], q[10], q[11], k4, k5);
            mma16816(sc, q[12], q[13], q[14], q[15], k6, k7);
            const float scl = 0.08838834764831845f * 1.4426950408889634f;
            const float r0 = (sa[0] + sc[0]) * scl, r1 = (sa[1] + sc[1]) * scl;
            if (s != NSEG - 1) {
                st_async_v2(ta.w, r0, r1, sx_bar_rem);
                st_async_v2(ta.w ^ (1u << 24), r0, r1, sx_bar_rem ^ (1u << 24));
            }
            if (warp == 0) PROF(2);
        } else if (s > 0 && warp == 7 && lane == 0) {
            mbar_expect_tx(sb + RB_A, 4096);
            mbar_expect_tx(sb + RB_A1, 4096);
        }
        if (s == NSEG - 1) {
            const uint4 td = lds128(tab + 6144);
            stg_relaxed32((uint32_t*)(((uint64_t)td.y << 32) | (td.x ^ 0x21000)), 0u);
            break;
        }
        slot_off = slot_off == slot_last ? 0 : slot_off + slot_inc;
        const uint4 tc = lds128(tab + 4096), td = lds128(tab + 6144);
        const uint32_t te = lds32(tab + 8192);
        uint32_t* wr = (uint32_t*)(((uint64_t)td.y << 32) | (td.x ^ ((s & 1) * 0x21000)));
        const uint32_t* r1p = (const uint32_t*)((const char*)wr + (int)td.z);
        const uint32_t* r2p = (const uint32_t*)((const char*)wr + (int)td.w);
        const uint32_t* r3p = (const uint32_t*)((const char*)wr + (int)te);
        const uint32_t tag = ((s >> 1) + 1) & 1;
        mbar_wait(sb + RB_E, s & 1);
        if (warp == 0) PROF(7);
        {
            uint32_t a0, a1, a2, a3, a4, a5, a6, a7;
            ldsm4t(a0, a1, a2, a3, tc.x);
            ldsm4t(a4, a5, a6, a7, tc.x ^ 64);
            const uint32_t one = 0x3F803F80u;
            float d0_[4] = {0.f, 0.f, 0.f, 0.f}, d1_[4] = {0.f, 0.f, 0.f, 0.f};
            mma16816(d0_, a0, a1, a2, a3, one, one);
            mma16816(d1_, a4, a5, a6, a7, one, one);
            const bool t1 = tc.w & 1, t2 = tc.w & 2;
            const float x = t2 ? (t1 ? d1_[2] : d1_[0]) : (t1 ? d0_[2] : d0_[0]);
            const uint32_t own = (__float_as_uint(x) & ~1u) | tag;
            stg_relaxed32(wr, own);
            const uint32_t tq = clk32();
            if (warp == 0) PROF(8);
            PROFG(16 + warp);
            while ((int)(clk32() - tq) < POLL_GAP) {}
            uint32_t f1 = ldg_relaxed32(r1p), f2 = ldg_relaxed32(r2p), f3 = ldg_relaxed32(r3p);
#pragma unroll
            for (int i = 0; i < NOFF; i++) {
                const uint4 f0 = lds128(tab + 10240 + i * 2048);
                wa[i & 1][i >> 1][0] = f0.x; wa[i & 1][i >> 1][1] = f0.y; wa[i & 1][i >> 1][2] = f0.z; wa[i & 1][i >> 1][3] = f0.w;
            }
            tb = lds128(tab + 2048);
            int gg = 0;
#pragma unroll 1
            while (!__all_sync(~0u, (((f1 ^ tag) | (f2 ^ tag) | (f3 ^ tag)) & 1) == 0)) {
                f1 = ldg_relaxed32(r1p); f2 = ldg_relaxed32(r2p); f3 = ldg_relaxed32(r3p);
                if (++gg > 16 * SPIN_LIMIT) { TIMEOUT(3, s); break; }
            }
            if (warp == 0) PROF(9);
            const float v = (__uint_as_float(own) + __uint_as_float(f2)) + (__uint_as_float(f1) + __uint_as_float(f3));
            const bool b8 = tc.w & 8, b16 = tc.w & 16;
            const float recv = __shfl_xor_sync(~0u, v, 8);
            const uint32_t word = b8 ? pack2(recv, v) : pack2(v, recv);
            const uint32_t oth = __shfl_xor_sync(~0u, word, 16);
            const uint32_t wl = b16 ? oth : word, wh = b16 ? word : oth;
            const uint32_t p0 = __shfl_xor_sync(~0u, wl, 2), p1 = __shfl_xor_sync(~0u, wh, 2);
            const uint4 item = t2 ? make_uint4(p0, p1, wl, wh) : make_uint4(wl, wh, p0, p1);
            st_async_v4(tc.y, item, tc.z);
            st_async_v4(tc.y ^ (8u << 24), item, tc.z ^ (8u << 24));
            if (tc.w == 0 && warp == 7) mbar_expect_tx(sb + RB_E, 8192);
            if (warp == 0) PROF(10);
            PROF(40 + warp);
        }
        bar_sync(NB_D, 384);
    }
}

__device__ __forceinline__ void rec_load_kv(uint32_t sb, int col0, int s, uint32_t slot_off, int t128) {
    const int row = t128 >> 2, c2 = (t128 & 3) * 2;
    const bf16* src = g_kv + ((size_t)(s * 32 + row) * (2 * HD_) + col0 + c2 * 8);
    const uint32_t d0 = sb + R_KX + slot_off + row * 128 + ((c2 ^ (row & 7)) << 4);
    cp_async16(d0, src);
    cp_async16(d0 ^ 16, src + 8);
    cp_async16(d0 + (R_VX - R_KX), src + HD_);
    cp_async16((d0 ^ 16) + (R_VX - R_KX), src + HD_ + 8);
}

__device__ __forceinline__ void rec_store_kvm(uint32_t sb, int col0, int s, int w, int lane) {
    const int tok = (w & 1) * 4 + (lane >> 3);
    const uint4 v = lds128(sb + R_KMS + (s & 1) * 2048 + (w >> 1) * 1024 + tok * 128 + (((lane & 7) ^ tok) << 4));
    *(uint4*)(g_kvm + ((s * 8 + tok) * (2 * HD_) + (w >> 1) * HD_ + col0 + (lane & 7) * 8)) = v;
}

__device__ __forceinline__ void rec_vo(const RecParams& p, const uint32_t sb, const int cta, const int warp, int lane) {
    const int w = warp - 8, crank = cta & 15;
    const int col0 = cta * 64;
    uint32_t wo[8][4][4];
    {
        const int t128 = w * 32 + lane;
        const bf16* Wo = p.wo + (size_t)col0 * D_;
        const uint32_t stg = sb + R_STG + 2 * 32768;
#pragma unroll
        for (int half = 0; half < 2; half++) {
#pragma unroll 4
            for (int i = t128; i < 2048; i += 128) {
                const int e = i >> 6, ch = i & 63;
                cp_async16(stg + e * 1024 + ((ch ^ (e & 7)) << 4), Wo + (size_t)(half * 32 + e) * D_ + ch * 8);
            }
            cp_async_commit();
            cp_async_wait<0>();
            bar_sync(NB_W0 + 2, 128);
#pragma unroll
            for (int j = 0; j < 8; j++)
#pragma unroll
                for (int kk = 0; kk < 2; kk++) {
                    const int e = kk * 16 + (lane >> 4) * 8 + (lane & 7);
                    const int ch = (w * 8 + j) * 2 + ((lane >> 3) & 1);
                    ldsm4t(wo[j][half * 2 + kk][0], wo[j][half * 2 + kk][1], wo[j][half * 2 + kk][2], wo[j][half * 2 + kk][3],
                           stg + e * 1024 + ((ch ^ (e & 7)) << 4));
                }
            bar_sync(NB_W0 + 2, 128);
        }
        if (lane == 0) wait_flag(F_KV + 0, 64);
        __syncwarp();
        rec_load_kv(sb, col0, 0, 0, t128); cp_async_commit();
        rec_load_kv(sb, col0, 1, 4096, t128); cp_async_commit();
        cp_async_wait<1>();
    }
    const uint32_t tab = sb + R_STG + 2 * 32768 + (w * 32 + lane) * 16;
    {
        const uint32_t l7 = lane & 7, l8 = lane >> 3, g = lane >> 2;
        uint4 v;
        v.x = sb + R_VX + ((l8 & 1) * 8 + l7) * 128 + (((2 * w + (l8 >> 1)) ^ l7) << 4);
        v.y = sb + R_OS + g * 128 + (((2 * w) ^ g) << 4) + (lane & 3) * 4;
        v.z = sb + R_VMS + l7 * 128 + (((2 * w + (l8 & 1)) ^ l7) << 4);
        v.w = sb + R_OS + l7 * 128 + ((l8 ^ l7) << 4);
        sts128(tab, v);
        v.x = mapa_u32(sb + R_RS + crank * 512 + ((lane ^ (crank & 7)) << 4), w * 4);
        v.y = mapa_u32(sb + RB_E, w * 4);
        v.z = sb + R_VP + w * 512 + lane * 16;
        v.w = sb + R_SX + lane * 8;
        sts128(tab + 2048, v);
#pragma unroll
        for (int i = 0; i < 8; i++) sts128(tab + 4096 + i * 2048, make_uint4(wo[i][0][0], wo[i][0][1], wo[i][0][2], wo[i][0][3]));
        const int tok = (w & 1) * 4 + (lane >> 3), row = (w * 32 + lane) >> 2, c2 = (lane & 3) * 2;
        const uint64_t kd = (uint64_t)(g_kvm + (tok * (2 * HD_) + (w >> 1) * HD_ + col0 + (lane & 7) * 8));
        const uint64_t ks = (uint64_t)(g_kv + ((size_t)row * (2 * HD_) + col0 + c2 * 8));
        sts128(tab + 20480, make_uint4((uint32_t)kd, (uint32_t)(kd >> 32), (uint32_t)ks, (uint32_t)(ks >> 32)));
        sts128(tab + 22528, make_uint4(sb + R_KMS + (w >> 1) * 1024 + tok * 128 + (((lane & 7) ^ tok) << 4),
                                       sb + R_KX + row * 128 + ((c2 ^ (row & 7)) << 4), lane, 0));
    }
    bar_sync(NB_D, 384);
    const uint32_t lane16 = lds32(tab + 2048 + 8) - R_VP - w * 512;
    uint4 av[2 * VK0];
#pragma unroll
    for (int i = 0; i < 2 * VK0; i++) av[i] = lds128(lane16 + R_WV + (i / VK0) * 32768 + (w * 16 + i % VK0) * 512);
    uint32_t slot_off = 0;
#pragma unroll 1
    for (int s = 0; s < NSEG; s++) {
        if (s > 0) {
            mbar_wait(sb + RB_A, (s - 1) & 1);
            const uint4 tp = lds128(tab + 20480), tq = lds128(tab + 22528);
            if ((s & 3) == 1 && s > 1 && w == 0 && tq.z == 0) red_release(&g_flags[F_MEM + (s >> 2) - 1], 1);
            const uint4 kvm = lds128(tq.x + ((s - 1) & 1) * 2048);
            *(uint4*)((((uint64_t)tp.y << 32) | tp.x) + (uint64_t)(s - 1) * (8 * 2 * HD_ * 2)) = kvm;
            if (s + 1 < NSEG - 1) {
                if (((s + 1) & 3) == 0) { if (tq.z == 0) wait_flag(F_KV + ((s + 1) >> 2), 64); __syncwarp(); }
                const char* src = (const char*)((((uint64_t)tp.w << 32) | tp.z) + (uint64_t)(s + 1) * (32 * 2 * HD_ * 2));
                const uint32_t d0 = tq.y + (slot_off == (R_NST - 1) * 4096 ? 0 : slot_off + 4096);
                cp_async16(d0, src);
                cp_async16(d0 ^ 16, src + 16);
                cp_async16(d0 + (R_VX - R_KX), src + HD_ * 2);
                cp_async16((d0 ^ 16) + (R_VX - R_KX), src + HD_ * 2 + 16);
            }
            cp_async_commit();
        }
        bar_sync(NB_Y, 288);
        uint32_t vb0, vb1;
        {
            float va[4] = {0.f, 0.f, 0.f, 0.f}, vc[4] = {0.f, 0.f, 0.f, 0.f};
            uint32_t bb[VK0][4];
#pragma unroll
            for (int k2 = 0; k2 < VK0; k2++) ldsm4(bb[k2][0], bb[k2][1], bb[k2][2], bb[k2][3], lane16 + R_MEM + (k2 / (VK0 / 2)) * 4096 + (k2 % (VK0 / 2)) * 512);
#pragma unroll
            for (int k2 = 0; k2 < VK0; k2++) {
                mma16816(va, av[2 * k2].x, av[2 * k2].y, av[2 * k2].z, av[2 * k2].w, bb[k2][0], bb[k2][1]);
                mma16816(vc, av[2 * k2 + 1].x, av[2 * k2 + 1].y, av[2 * k2 + 1].z, av[2 * k2 + 1].w, bb[k2][2], bb[k2][3]);
            }
            const uint4 a = lds128(lane16 + R_VP + w * 512), b = lds128(lane16 + R_VP + 2048 + w * 512);
            vb0 = pack2((va[0] + vc[0]) + (__uint_as_float(a.x) + __uint_as_float(b.x)), (va[1] + vc[1]) + (__uint_as_float(a.y) + __uint_as_float(b.y)));
            vb1 = pack2((va[2] + vc[2]) + (__uint_as_float(a.z) + __uint_as_float(b.z)), (va[3] + vc[3]) + (__uint_as_float(a.w) + __uint_as_float(b.w)));
        }
        const uint4 ta = lds128(tab), tb = lds128(tab + 2048);
        uint32_t vx[8];
        ldsm4t(vx[0], vx[1], vx[2], vx[3], ta.x + slot_off);
        ldsm4t(vx[4], vx[5], vx[6], vx[7], ta.x + slot_off + 2048);
#pragma unroll
        for (int i = 0; i < 4; i++) {
            const uint4 f0 = lds128(tab + 4096 + i * 2048);
            wo[i][0][0] = f0.x; wo[i][0][1] = f0.y; wo[i][0][2] = f0.z; wo[i][0][3] = f0.w;
        }
        if (w == 0) PROF(11);
        uint32_t pf[5];
        float oa[2][4] = {{0.f, 0.f, 0.f, 0.f}, {0.f, 0.f, 0.f, 0.f}}, ob_[2][4] = {{0.f, 0.f, 0.f, 0.f}, {0.f, 0.f, 0.f, 0.f}};
        float sm0[4] = {0.f, 0.f, 0.f, 0.f}, sm1[4] = {0.f, 0.f, 0.f, 0.f};
        if (s != NSEG - 1) {
            mbar_wait(sb + RB_SX, s & 1);
            if (w == 0) PROF(4);
            float sv[10];
#pragma unroll
            for (int n = 0; n < 5; n++) {
                const float2 a = lds64f(tb.w + n * 256), b = lds64f(tb.w + (5 + n) * 256);
                sv[2 * n] = a.x + b.x; sv[2 * n + 1] = a.y + b.y;
            }
            float mx = fmaxf(fmaxf(fmaxf(sv[0], sv[1]), fmaxf(sv[2], sv[3])), fmaxf(fmaxf(sv[4], sv[5]), fmaxf(sv[6], sv[7])));
            mx = fmaxf(mx, fmaxf(sv[8], sv[9]));
            mx = fmaxf(mx, __shfl_xor_sync(~0u, mx, 1));
            mx = fmaxf(mx, __shfl_xor_sync(~0u, mx, 2));
#pragma unroll
            for (int n = 1; n < 5; n++) pf[n] = pack2(ex2(sv[2 * n] - mx), ex2(sv[2 * n + 1] - mx));
            pf[0] = pack2(ex2(sv[0] - mx), ex2(sv[1] - mx));
            if (w == 0) PROF(12);
            const uint32_t one = 0x3F803F80u;
            mma16816h(sm0, pf[1], pf[2], one, one);
            mma16816h(oa[0], pf[1], pf[2], vx[0], vx[1]);
            mma16816h(oa[1], pf[1], pf[2], vx[2], vx[3]);
            mma16816h(sm1, pf[3], pf[4], one, one);
            mma16816h(ob_[0], pf[3], pf[4], vx[4], vx[5]);
            mma16816h(ob_[1], pf[3], pf[4], vx[6], vx[7]);
            mma1688h(sm0, pf[0], one);
            mma1688h(oa[0], pf[0], vb0);
            mma1688h(oa[1], pf[0], vb1);
            float inv;
            asm("rcp.approx.ftz.f32 %0, %1;" : "=f"(inv) : "f"(sm0[0] + sm1[0]));
            oa[0][0] += ob_[0][0]; oa[0][1] += ob_[0][1]; oa[1][0] += ob_[1][0]; oa[1][1] += ob_[1][1];
            sts32(ta.y, pack2(oa[0][0] * inv, oa[0][1] * inv));
            sts32(ta.y ^ 16, pack2(oa[1][0] * inv, oa[1][1] * inv));
            const uint32_t oa2 = ta.w ^ 64;
            bar_sync(NB_C, 128);
            if (w == 0) PROF(5);
            uint32_t ob[8];
            ldsm4(ob[0], ob[1], ob[2], ob[3], ta.w);
            ldsm4(ob[4], ob[5], ob[6], ob[7], oa2);
#pragma unroll
            for (int i = 4; i < 8; i++) {
                const uint4 f0 = lds128(tab + 4096 + i * 2048);
                wo[i][0][0] = f0.x; wo[i][0][1] = f0.y; wo[i][0][2] = f0.z; wo[i][0][3] = f0.w;
            }
#pragma unroll
            for (int jj = 0; jj < 2; jj++) {
                if (jj == 1 && tb.w == 0) break;
                float acc[4][4];
#pragma unroll
                for (int c = 0; c < 4; c++) { acc[c][0] = acc[c][1] = acc[c][2] = acc[c][3] = 0.f; }
#pragma unroll
                for (int ks = 0; ks < 4; ks++)
#pragma unroll
                    for (int c = 0; c < 4; c++)
                        mma16816(acc[c], wo[jj * 4 + c][ks][0], wo[jj * 4 + c][ks][1], wo[jj * 4 + c][ks][2], wo[jj * 4 + c][ks][3], ob[2 * ks], ob[2 * ks + 1]);
#pragma unroll
                for (int pr = 0; pr < 2; pr++) {
                    uint4 v;
                    v.x = pack2(acc[2 * pr][0], acc[2 * pr][1]);
                    v.y = pack2(acc[2 * pr][2], acc[2 * pr][3]);
                    v.z = pack2(acc[2 * pr + 1][0], acc[2 * pr + 1][1]);
                    v.w = pack2(acc[2 * pr + 1][2], acc[2 * pr + 1][3]);
                    st_async_v4(tb.x + ((jj * 2 + pr) << 24), v, tb.y + ((jj * 2 + pr) << 24));
                }
            }
            if (w == 0) PROF(6);
        }
        stsm2t(ta.z + (s & 1) * 2048, vb0, vb1);
        cp_async_wait<0>();
        bar_sync(NB_C, 128);
        if (w == 0 && lane == 0 && s != NSEG - 1) mbar_expect_tx(sb + RB_SX, 2560);
        if (s != NSEG - 1) bar_arrive(NB_D, 384);
#pragma unroll
        for (int i = 0; i < 2 * VK0; i++) av[i] = lds128(lane16 + R_WV + (i / VK0) * 32768 + (w * 16 + i % VK0) * 512);
        slot_off = slot_off == (R_NST - 1) * 4096 ? 0 : slot_off + 4096;
    }
    rec_store_kvm(sb, col0, NSEG - 1, w, lane);
    bar_sync(NB_C, 128);
    if (w == 0 && lane == 0) red_release(&g_flags[F_MEM + NRB - 1], 1);
}

__global__ void __launch_bounds__(384, 1) k_rec(const RecParams p) {
    extern __shared__ __align__(1024) unsigned char smem_raw[];
    const uint32_t sb = __shfl_sync(~0u, smem_u32(smem_raw), 0);
    const int warp = __shfl_sync(~0u, threadIdx.x >> 5, 0);
    int lane; asm volatile("mov.u32 %0, %%laneid;" : "=r"(lane));
    const int crank = blockIdx.x & 15, slot = blockIdx.x >> 4;
    asm volatile("griddepcontrol.launch_dependents;");
    if (threadIdx.x == 0) {
        mbar_init(sb + RB_SX, 1); mbar_init(sb + RB_E, 1); mbar_init(sb + RB_A, 1); mbar_init(sb + RB_A1, 1); mbar_init(sb + RB_ROLE, 1);
        asm volatile("fence.mbarrier_init.release.cluster;" ::: "memory");
        mbar_expect_tx(sb + RB_SX, 2560);
        mbar_expect_tx(sb + RB_E, 8192);
        mbar_expect_tx(sb + RB_A, 4096);
        mbar_expect_tx(sb + RB_A1, 4096);
        mbar_expect_tx(sb + RB_ROLE, 4);
    }
    unsigned role = 0;
    if (crank == 0 && threadIdx.x == 0) {
        unsigned x = 0;
        int tm[2] = {0x7fffffff, 0x7fffffff};
#pragma unroll 1
        for (int i = 0; i < 6; i++) {
            const uint32_t t0 = clk32();
            x = atomicAdd(&g_F[65536 + (i & 1) * 1024 + slot * 64 + (x >> 31)], 0u) & 0x7fffffffu;
            if (x == 0x7654321u) sts32(sb + R_BAR + 56, x);
            const int dt = (int)(clk32() - t0);
            if (i >= 2) { if (i & 1) tm[1] = min(tm[1], dt); else tm[0] = min(tm[0], dt); }
        }
        const int side = tm[1] > tm[0];
        const unsigned old = atomicAdd(&g_flags[F_SIDE + side * 32], 1u);
        unsigned c0, c1; int gd = 0;
#pragma unroll 1
        do { c0 = ldg_relaxed32(&g_flags[F_SIDE]); c1 = ldg_relaxed32(&g_flags[F_SIDE + 32]); } while ((int)(c0 + c1) < p.ncl && ++gd < 64 * SPIN_LIMIT);
        const int big = c1 > c0;
        role = side == big ? old : (big ? c1 : c0) + old;
        role |= (big ^ 1) << 8;
    }
    __syncwarp();
    asm volatile("barrier.cluster.arrive.relaxed.aligned;\nbarrier.cluster.wait.aligned;" ::: "memory");
    if (crank == 0 && warp == 0) {
        role = __shfl_sync(~0u, role, 0);
        if (lane < 16)
            asm volatile("st.async.weak.shared::cluster.mbarrier::complete_tx::bytes.u32 [%0], %1, [%2];"
                         :: "r"(mapa_u32(sb + R_BAR + 48, lane)), "r"(role), "r"(mapa_u32(sb + RB_ROLE, lane)) : "memory");
    }
    mbar_wait(sb + RB_ROLE, 0);
    const int rolew = __shfl_sync(~0u, lds32(sb + R_BAR + 48), 0);
    const int cl = rolew & 255;
    if (cl >= 4) return;
    const int cta = cl * 16 + crank;
    if (warp < 8) rec_qk(p, sb, cta, warp, lane, rolew >> 8);
    else rec_vo(p, sb, cta, warp, lane);
}

enum { J_KV = 0, J_QA = 1, J_O = 2, J_LN = 3, J_UP = 4, J_DN = 5, J_LN1 = 6, J_MOD = 7, J_UP2 = 8, J_END = 9 };
constexpr int NJ_O = 2 * OSPLIT, NJ_O2 = 2 * OSPLIT2, NJ_LN = 8, NJ_LN2 = 16, NJ_UP = 14, NJ_UP2 = 28, NJ_DN = 8, NJ_LN1 = 8;
__device__ __forceinline__ int nj_of(int q, int rb) {
    const bool f = rb >= FINE_RB;
    return q == J_KV ? 32 : (q == J_QA ? 16 : (q == J_O ? (f ? NJ_O2 : NJ_O) : (q == J_LN ? (f ? NJ_LN2 : NJ_LN) : (q == J_UP ? (f ? NJ_UP2 : NJ_UP) :
           (q == J_MOD ? (rb < 3 ? 16 : 0) : 8)))));
}
__device__ __forceinline__ int pick_job(int lane, int qmask, int& idx) {
    const int rb = lane & 15, half = lane >> 4;
    int gd = 0;
#pragma unroll 1
    while (true) {
        unsigned cl[4], dp[4];
#pragma unroll
        for (int i = 0; i < 4; i++) {
            const int q = half + 2 * i;
            cl[i] = ldg_relaxed32(&g_flags[F_CLAIM + q * 32 + rb]);
            dp[i] = ldg_relaxed32(&g_flags[q * 32 + (q == J_QA ? max(rb - 1, 0) : (q == J_LN1 ? 0 : rb))]);
        }
        unsigned r16[8], h16[8];
#pragma unroll
        for (int i = 0; i < 4; i++) {
            const int q = half + 2 * i;
            const bool have = ((qmask >> q) & 1) && (int)cl[i] < nj_of(q, rb);
            const unsigned tgt = q == J_QA ? 64 : (q == J_KV ? 2 * NJ_LN1 : (q == J_LN1 ? 32 : 2 * nj_of(q - 1, rb)));
            const bool ready = have && (q == J_MOD || (q == J_QA && rb == 0) || dp[i] >= tgt);
            const unsigned mh = __ballot_sync(~0u, have), mr = __ballot_sync(~0u, ready);
            r16[2 * i] = mr & 0xffffu; r16[2 * i + 1] = mr >> 16; h16[2 * i] = mh & 0xffffu; h16[2 * i + 1] = mh >> 16;
        }
        if (h16[J_KV] | h16[J_LN1]) r16[J_QA] = 0;
        int pq = -1;
        unsigned pm = 0;
        if (r16[J_MOD]) { pq = J_MOD; pm = r16[J_MOD]; }
        else if (r16[J_KV]) { pq = J_KV; pm = r16[J_KV]; }
        else if (r16[J_LN1]) { pq = J_LN1; pm = r16[J_LN1]; }
        else if (r16[J_QA] >> FINE_RB) { pq = J_QA; pm = r16[J_QA]; }
        else if (r16[J_DN]) { pq = J_DN; pm = r16[J_DN]; }
        else if (r16[J_UP]) { pq = J_UP; pm = r16[J_UP]; }
        else if (r16[J_LN]) { pq = J_LN; pm = r16[J_LN]; }
        else if (r16[J_O]) { pq = J_O; pm = r16[J_O]; }
        else if (r16[J_QA]) { pq = J_QA; pm = r16[J_QA]; }
        else if ((h16[J_MOD] | h16[J_KV] | h16[J_LN1] | h16[J_QA]) == 0) {
            unsigned prev = 0;
#pragma unroll
            for (int q = J_O; q <= J_DN; q++) {
                const int b = __ffs(h16[q]) - 1;
                if (pq < 0 && b >= FINE_RB && (prev & ((2u << b) - 1)) == 0) { pq = q; pm = h16[q]; }
                prev |= h16[q];
            }
            if (prev == 0) return J_END;
        }
        if (pq >= 0) {
            const int prb = __ffs(pm) - 1;
            int c = 0;
            if (lane == 0) c = (int)atomicAdd(&g_flags[F_CLAIM + pq * 32 + prb], 1u);
            c = __shfl_sync(~0u, c, 0);
            if (c < nj_of(pq, prb)) {
                idx = pq * 512 + prb * 32 + c;
                return (pq == J_UP && prb >= FINE_RB ? J_UP2 : pq) | (prb << 8) | (c << 16);
            }
        } else {
            __nanosleep(150);
            if (++gd > 16 * SPIN_LIMIT) { TIMEOUT(5, 0); return J_END; }
        }
    }
}
__device__ __forceinline__ int op_row(int rb, int split) {
    return rb < FINE_RB ? split * S_ + rb * 128 : OSPLIT * S_ + (split * (NRB - FINE_RB) + rb - FINE_RB) * 128;
}

struct Pipe { uint32_t stage, phase; };
__device__ __forceinline__ void pipe_next(Pipe& p) { if (++p.stage == W_NST) { p.stage = 0; p.phase ^= 1; } }

__device__ __forceinline__ void scheduler(const Params& p, uint32_t sb, int lane) {
    const uint32_t bars = sb + SM_BAR;
    uint32_t ph = 0;
#pragma unroll 1
    while (true) {
        mbar_wait(bars + B_REQ, ph);
        int j = 4095;
        const int jd = pick_job(lane, p.qmask, j);
        if (lane == 0) { sts32(bars + B_NEXT, (uint32_t)jd); sts32(bars + B_NEXT + 4, (uint32_t)j); mbar_arrive(bars + B_RSP); }
        ph ^= 1;
        if (jd == J_END) break;
        __syncwarp();
    }
}

__device__ __forceinline__ void producer(const Params& p, uint32_t sb) {
    Pipe pp{0, 1};
    const uint32_t bars = sb + SM_BAR;
    uint32_t seq = 0;
    mbar_arrive(bars + B_REQ);
#pragma unroll 1
    while (true) {
        mbar_wait(bars + B_RSP, seq & 1);
        const int jd = (int)lds32(bars + B_NEXT), j = (int)lds32(bars + B_NEXT + 4);
        int left = (jd & 255) == J_DN ? 15 : ((jd & 255) == J_QA ? 12 : ((jd & 255) == J_O ? (((jd >> 8) & 255) >= FINE_RB ? 64 / OSPLIT2 : 64 / OSPLIT) : ((jd & 255) == J_LN || (jd & 255) == J_LN1 || (jd & 255) == J_MOD ? 1 : 8)));
        left = max(left - PICK_AHEAD, 1);
        TR(j, 1);
        const int type = jd & 255, rb = (jd >> 8) & 255, cb = jd >> 16;
        const bool fine = rb >= FINE_RB;
        bool first = true;
        auto begin_stage = [&](uint32_t bytes) -> uint32_t {
            mbar_wait(bars + B_EMPTY + pp.stage * 8, pp.phase);
            if (first) { sts32(bars + B_RING + (seq & 7) * 4, (uint32_t)jd); sts32(bars + B_RING + 32 + (seq & 7) * 4, (uint32_t)j); first = false; }
            const uint32_t fb = bars + B_FULL + pp.stage * 8;
            if (bytes) mbar_expect_tx(fb, bytes); else mbar_arrive(fb);
            if (--left == 0 && type != J_END) mbar_arrive(bars + B_REQ);
            return fb;
        };
        if (type == J_END || type == J_LN || type == J_LN1 || type == J_MOD) {
            if (type == J_LN) { wait_flag(F_OP + rb, 2 * (fine ? NJ_O2 : NJ_O)); wait_flag(F_MOD + 1, 32); wait_flag(F_MOD + 2, 32); }
            if (type == J_LN1) wait_flag(F_MOD, 32);
            TR(j, 2);
            begin_stage(0); pipe_next(pp);
            seq++;
            if (type == J_END) break;
            continue;
        }
        const CUtensorMap *ta, *tb0, *tb1;
        int k0 = 0, nk = 8, n0 = cb * 256, n1 = n0 + 128, nb = 4, dep = -1;
        unsigned tgt = 0;
        switch (type) {
            case J_KV: ta = &p.tm_h; tb0 = tb1 = cb < 16 ? &p.tm_wk : &p.tm_wv; n0 = (cb & 15) * 256; n1 = n0 + 128; dep = F_H + rb; tgt = 2 * NJ_LN1; break;
            case J_QA: ta = &p.tm_h; tb0 = tb1 = &p.tm_wq; dep = F_H + rb; tgt = 2 * NJ_LN1; break;
            case J_O: ta = &p.tm_o; tb0 = tb1 = &p.tm_wo; n0 = (cb & 1) * 256; n1 = n0 + 128; nk = fine ? 64 / OSPLIT2 : 64 / OSPLIT; k0 = (cb >> 1) * nk * 64;
                      dep = F_O + rb; tgt = 32; break;
            case J_UP: ta = &p.tm_h2; tb0 = &p.tm_wg; tb1 = &p.tm_wu; n0 = n1 = cb * 128; dep = F_H2 + rb; tgt = 2 * NJ_LN; break;
            case J_UP2: ta = &p.tm_h2; tb0 = &p.tm_wg; tb1 = &p.tm_wu; n0 = n1 = cb * 64; nb = 2; dep = F_H2 + rb; tgt = 2 * NJ_LN2; break;
            default: ta = &p.tm_act; tb0 = tb1 = &p.tm_wd; n0 = cb * 64; nk = 0; break;
        }
        const int m0 = rb * 128;
        if (type == J_DN) {
#pragma unroll 1
            for (int kb = 0; kb < 14; kb++) {
                const uint32_t fb = begin_stage(49152);
                const uint32_t st = sb + pp.stage * W_STAGE;
                const int k = kb * 128;
                tma_load2d(st + 32768, tb0, n0, k, fb);
                tma_load2d(st + 40960, tb0, n0, k + 64, fb);
                if (kb == 0) { wait_flag(F_ACT + rb, 2 * (fine ? NJ_UP2 : NJ_UP)); asm volatile("fence.proxy.async.global;" ::: "memory"); TR(j, 2); }
                tma_load2d(st, ta, k, m0, fb);
                tma_load2d(st + 8192, ta, k, m0 + 64, fb);
                tma_load2d(st + 16384, ta, k + 64, m0, fb);
                tma_load2d(st + 24576, ta, k + 64, m0 + 64, fb);
                pipe_next(pp);
            }
        }
#pragma unroll 1
        for (int kb = 0; kb < nk; kb++) {
            const uint32_t fb = begin_stage(16384 + nb * 8192);
            const uint32_t st = sb + pp.stage * W_STAGE;
            const int k = k0 + kb * 64;
            tma_load2d(st + 16384, tb0, n0, k, fb);
            if (nb == 4) {
                tma_load2d(st + 16384 + 8192, tb0, n0 + 64, k, fb);
                tma_load2d(st + 16384 + 16384, tb1, n1, k, fb);
                tma_load2d(st + 16384 + 24576, tb1, n1 + 64, k, fb);
            } else if (nb == 2) {
                tma_load2d(st + 16384 + 8192, tb1, n1, k, fb);
            }
            if (kb == 0) {
                if (dep >= 0) { wait_flag(dep, tgt); if (type != J_O) asm volatile("fence.proxy.async.global;" ::: "memory"); }
                TR(j, 2);
            }
            tma_load2d(st, ta, k, m0, fb);
            tma_load2d(st + 8192, ta, k, m0 + 64, fb);
            pipe_next(pp);
        }
        if (type == J_QA) {
            wait_flag(F_KV + rb, 64);
#pragma unroll 1
            for (int i = 0; i < 4; i++) {
                const uint32_t fb = begin_stage(40960);
                const uint32_t st = sb + pp.stage * W_STAGE;
                const int col = (i & 1) * HD_ + (cb * 2 + (i >> 1)) * DH_;
                tma_load2d(st, &p.tm_kv, col, m0, fb);
                tma_load2d(st + 8192, &p.tm_kv, col, m0 + 64, fb);
                tma_load2d(st + 16384, &p.tm_kv, col + 64, m0, fb);
                tma_load2d(st + 24576, &p.tm_kv, col + 64, m0 + 64, fb);
                if (i == 0) { wait_flag(F_MEM + rb, 64); asm volatile("fence.proxy.async.global;" ::: "memory"); }
                tma_load2d(st + 32768, &p.tm_kvm, col, rb * 32, fb);
                tma_load2d(st + 36864, &p.tm_kvm, col + 64, rb * 32, fb);
                pipe_next(pp);
            }
        } else if (type == J_DN) {
            const uint32_t fb = begin_stage(16384);
            const uint32_t st = sb + pp.stage * W_STAGE;
            tma_load2d(st, &p.tm_x1, n0, m0, fb);
            tma_load2d(st + 8192, &p.tm_x1, n0, m0 + 64, fb);
            pipe_next(pp);
        }
        seq++;
    }
}

__device__ __forceinline__ void store_warp(const Params& p, uint32_t sb, int wg, int lane) {
    const uint32_t bars = sb + SM_BAR;
    uint32_t seq = 0;
#pragma unroll 1
    while (true) {
        bar_sync(NB_ST + wg, 160);
        const uint32_t jd = lds32(bars + B_RING + (seq & 7) * 4);
        seq++;
        const int type = jd & 255, rb = (jd >> 8) & 255, cb = jd >> 16;
        if (type == J_END) break;
        if (lane == 0) {
            const uint32_t src = sb + W_STG + wg * 32768;
            const CUtensorMap* tm = nullptr; int n0 = cb * 256, nbox = 4, mrow = rb * 128 + wg * 64, flag = 0;
            switch (type) {
                case J_KV: tm = &p.tm_kv; flag = F_KV + rb; break;
                case J_QA: tm = &p.tm_o; flag = F_O + rb; break;
                case J_O: tm = &p.tm_op; n0 = (cb & 1) * 256; mrow = op_row(rb, cb >> 1) + wg * 64; flag = F_OP + rb; break;
                case J_LN: flag = F_H2 + rb; nbox = 0; break;
                case J_LN1: flag = F_H + rb; nbox = 0; break;
                case J_MOD: flag = F_MOD + rb; nbox = 0; break;
                case J_UP: tm = &p.tm_act; n0 = cb * 128; nbox = 2; flag = F_ACT + rb; break;
                case J_UP2: tm = &p.tm_act; n0 = cb * 64; nbox = 1; flag = F_ACT + rb; break;
                default: tm = &p.tm_out; n0 = cb * 64; nbox = 1; flag = -1; break;
            }
#pragma unroll 1
            for (int b = 0; b < nbox; b++) tma_store2d(tm, src + b * 8192, n0 + b * 64, mrow);
            bulk_commit();
            bulk_wait0();
            mbar_arrive(bars + B_STGFREE + wg * 8);
            if (flag >= 0) red_release(&g_flags[flag], 1);
        }
        __syncwarp();
    }
}

__device__ __forceinline__ float gelu_tanh(float x) {
    const float t = x * fmaf(-0.10294324397f, x * x, -2.30220819814f);
    float r; asm("rcp.approx.ftz.f32 %0, %1;" : "=f"(r) : "f"(1.f + ex2(t)));
    return x * r;
}

#define CTR(i) do {} while (0)

template <int NSPLIT>
__device__ __forceinline__ void ln2_row(const Params& p, int rb, int r, int lane) {
    const int row = rb * 128 + r;
    uint4 u[2 * NSPLIT];
#pragma unroll
    for (int sp = 0; sp < NSPLIT; sp++) {
        const uint4* src = (const uint4*)(g_op + (size_t)(op_row(rb, sp) + r) * D_);
        u[2 * sp] = __ldcg(src + lane); u[2 * sp + 1] = __ldcg(src + 32 + lane);
    }
    const uint4* xr = (const uint4*)(p.x + (size_t)row * D_);
    const uint4 xa = __ldg(xr + lane), xb = __ldg(xr + 32 + lane);
    uint32_t ga[8], c1[8], sm[8];
    load_mod8(g_mod + 2 * D_, lane, ga);
    load_mod8(g_mod + 4 * D_, lane, c1);
    load_mod8(g_mod + 3 * D_, lane, sm);
    float a[16];
#pragma unroll
    for (int i = 0; i < 16; i++) a[i] = 0.f;
#pragma unroll
    for (int sp = 0; sp < 2 * NSPLIT; sp++) {
        float* q = a + (sp & 1) * 8;
        q[0] += bflo(u[sp].x); q[1] += bfhi(u[sp].x); q[2] += bflo(u[sp].y); q[3] += bfhi(u[sp].y);
        q[4] += bflo(u[sp].z); q[5] += bfhi(u[sp].z); q[6] += bflo(u[sp].w); q[7] += bfhi(u[sp].w);
    }
    const uint32_t xv[8] = {xa.x, xa.y, xa.z, xa.w, xb.x, xb.y, xb.z, xb.w};
    uint32_t v[8], r8[8];
#pragma unroll
    for (int i = 0; i < 8; i++) v[i] = hadd2(xv[i], hmul2(ga[i], pack2(a[2 * i], a[2 * i + 1])));
    uint4* x1r = (uint4*)(g_x1 + (size_t)row * D_);
    x1r[lane] = make_uint4(v[0], v[1], v[2], v[3]); x1r[32 + lane] = make_uint4(v[4], v[5], v[6], v[7]);
    uint32_t mu2; float rden;
    ln_stats(v, mu2, rden);
#pragma unroll
    for (int i = 0; i < 8; i++) c1[i] = hadd2(c1[i], 0x3F803F80u);
    ln_apply(v, mu2, rden, c1, sm, r8);
    uint4* hr = (uint4*)(g_h2 + (size_t)row * D_);
    hr[lane] = make_uint4(r8[0], r8[1], r8[2], r8[3]); hr[32 + lane] = make_uint4(r8[4], r8[5], r8[6], r8[7]);
}

__device__ __forceinline__ void consumer(const Params& p, uint32_t sb, int warp, int lane) {
    const uint32_t bars = sb + SM_BAR;
    const int wg = warp >> 2, wl = warp & 3;
    const uint32_t l7 = lane & 7, l8 = lane >> 3, g = lane >> 2, t = lane & 3;
    Pipe pp{0, 0};
    uint32_t seq = 0, stg_phase = 1;
    const int srow = wl * 16 + l7 + (l8 & 1) * 8;
    const uint32_t stg_base = sb + W_STG + wg * 32768 + srow * 128;
    const uint32_t sx = ((lane >> 4) ^ (srow & 7)) << 4;
#pragma unroll 1
    while (true) {
        mbar_wait(bars + B_FULL + pp.stage * 8, pp.phase);
        const uint32_t jd = lds32(bars + B_RING + (seq & 7) * 4);
        CTR(3);
        seq++;
        const int type = jd & 255, rb = (jd >> 8) & 255, cb = jd >> 16;
        if (type == J_END) { mbar_wait(bars + B_STGFREE + wg * 8, stg_phase); bar_arrive(NB_ST + wg, 160); break; }
        if (type == J_MOD) {
            __syncwarp();
            if (lane == 0) mbar_arrive(bars + B_EMPTY + pp.stage * 8);
            pipe_next(pp);
            const int rg = warp * 4 + l8, col = rb * 1024 + cb * 64;
            uint4 wv[16];
#pragma unroll
            for (int i = 0; i < 16; i++) wv[i] = __ldg((const uint4*)(p.w_mod + (size_t)(rg * 16 + i) * (6 * D_) + col + l7 * 8));
            const uint4 c0 = __ldg((const uint4*)(p.c + rg * 16)), c1 = __ldg((const uint4*)(p.c + rg * 16 + 8));
            const uint32_t cw[8] = {c0.x, c0.y, c0.z, c0.w, c1.x, c1.y, c1.z, c1.w};
            float a[8];
#pragma unroll
            for (int i = 0; i < 8; i++) a[i] = 0.f;
#pragma unroll
            for (int i = 0; i < 16; i++) {
                float cv = (i & 1) ? bfhi(cw[i >> 1]) : bflo(cw[i >> 1]);
                cv = rbf(__fdividef(cv, 1.f + __expf(-cv)));
                a[0] = fmaf(cv, bflo(wv[i].x), a[0]); a[1] = fmaf(cv, bfhi(wv[i].x), a[1]); a[2] = fmaf(cv, bflo(wv[i].y), a[2]); a[3] = fmaf(cv, bfhi(wv[i].y), a[3]);
                a[4] = fmaf(cv, bflo(wv[i].z), a[4]); a[5] = fmaf(cv, bfhi(wv[i].z), a[5]); a[6] = fmaf(cv, bflo(wv[i].w), a[6]); a[7] = fmaf(cv, bfhi(wv[i].w), a[7]);
            }
#pragma unroll
            for (int i = 0; i < 8; i++) { a[i] += __shfl_xor_sync(~0u, a[i], 8); a[i] += __shfl_xor_sync(~0u, a[i], 16); }
            const uint32_t red = sb + SM_BAR + 1024;
            bar_sync(NB_M, 256);
            if (lane < 8) {
                sts128(red + warp * 256 + lane * 32, make_uint4(__float_as_uint(a[0]), __float_as_uint(a[1]), __float_as_uint(a[2]), __float_as_uint(a[3])));
                sts128(red + warp * 256 + lane * 32 + 16, make_uint4(__float_as_uint(a[4]), __float_as_uint(a[5]), __float_as_uint(a[6]), __float_as_uint(a[7])));
            }
            bar_sync(NB_M, 256);
            if (wl == 0) {
                const uint32_t ra = red + (wg * 32 + lane) * 4;
                float v = 0.f;
#pragma unroll
                for (int i = 0; i < 8; i++) v += lds32f(ra + i * 256);
                g_mod[col + wg * 32 + lane] = __float2bfloat16_rn(v);
            }
            mbar_wait(bars + B_STGFREE + wg * 8, stg_phase); stg_phase ^= 1;
            CTR(4); CTR(5);
            bar_arrive(NB_ST + wg, 160);
            continue;
        }
        if (type == J_LN || type == J_LN1) {
            __syncwarp();
            if (lane == 0) mbar_arrive(bars + B_EMPTY + pp.stage * 8);
            pipe_next(pp);
            if (type == J_LN1) {
                const int row = rb * 128 + cb * 16 + warp * 2;
                const uint4* xr = (const uint4*)(p.x + (size_t)row * D_);
                const uint4 xa[4] = {__ldg(xr + lane), __ldg(xr + 32 + lane), __ldg(xr + 64 + lane), __ldg(xr + 96 + lane)};
                uint32_t c1[8], sm[8];
                load_mod8(g_mod + D_, lane, c1);
                load_mod8(g_mod, lane, sm);
#pragma unroll
                for (int i = 0; i < 8; i++) c1[i] = hadd2(c1[i], 0x3F803F80u);
#pragma unroll
                for (int rr = 0; rr < 2; rr++) {
                    const uint32_t v[8] = {xa[2 * rr].x, xa[2 * rr].y, xa[2 * rr].z, xa[2 * rr].w, xa[2 * rr + 1].x, xa[2 * rr + 1].y, xa[2 * rr + 1].z, xa[2 * rr + 1].w};
                    uint32_t mu2, r[8]; float rden;
                    ln_stats(v, mu2, rden);
                    ln_apply(v, mu2, rden, c1, sm, r);
                    uint4* hr = (uint4*)(g_h + (size_t)(row + rr) * D_);
                    hr[lane] = make_uint4(r[0], r[1], r[2], r[3]); hr[32 + lane] = make_uint4(r[4], r[5], r[6], r[7]);
                }
            } else if (rb >= FINE_RB) ln2_row<OSPLIT2>(p, rb, cb * 8 + warp, lane);
            else {
#pragma unroll 1
                for (int rr = 0; rr < 2; rr++) ln2_row<OSPLIT>(p, rb, cb * 16 + warp * 2 + rr, lane);
            }
            mbar_wait(bars + B_STGFREE + wg * 8, stg_phase); stg_phase ^= 1;
            CTR(4); CTR(5);
            bar_arrive(NB_ST + wg, 160);
            continue;
        }
        if (type == J_DN || type == J_UP2) {
            float acc[64];
#pragma unroll
            for (int i = 0; i < 64; i++) acc[i] = 0.f;
            if (type == J_DN) {
#pragma unroll 1
                for (int kb = 0; kb < 14; kb++) {
                    if (kb) mbar_wait(bars + B_FULL + pp.stage * 8, pp.phase);
                    const uint32_t st = sb + pp.stage * W_STAGE;
                    const uint64_t da = mkdesc(st + wg * 8192, 16, 1024), db = mkdesc(st + 32768, 8192, 1024);
                    wg_fence();
#pragma unroll
                    for (int ks = 0; ks < 8; ks++) wgmma_n64(acc, da + (ks >> 2) * 1024 + (ks & 3) * 2, db + ks * 128);
                    wg_commit();
                    wg_wait0();
                    if (lane == 0) mbar_arrive(bars + B_EMPTY + pp.stage * 8);
                    pipe_next(pp);
                }
            } else {
#pragma unroll 1
                for (int kb = 0; kb < 8; kb++) {
                    if (kb) mbar_wait(bars + B_FULL + pp.stage * 8, pp.phase);
                    const uint32_t st = sb + pp.stage * W_STAGE;
                    const uint64_t da = mkdesc(st + wg * 8192, 16, 1024), db = mkdesc(st + 16384, 8192, 1024);
                    wg_fence();
#pragma unroll
                    for (int ks = 0; ks < 4; ks++) wgmma_n128(acc, da + ks * 2, db + ks * 128, 1);
                    wg_commit();
                    wg_wait0();
                    if (lane == 0) mbar_arrive(bars + B_EMPTY + pp.stage * 8);
                    pipe_next(pp);
                }
            }
            CTR(4);
            if (type == J_UP2) {
                mbar_wait(bars + B_STGFREE + wg * 8, stg_phase); stg_phase ^= 1;
#pragma unroll
                for (int j = 0; j < 4; j++) {
                    uint32_t r[4];
#pragma unroll
                    for (int q = 0; q < 4; q++) {
                        const uint32_t gw = pack2(acc[8 * j + 2 * q], acc[8 * j + 2 * q + 1]);
                        const uint32_t uw = pack2(acc[32 + 8 * j + 2 * q], acc[32 + 8 * j + 2 * q + 1]);
                        r[q] = hmul2(pack2(gelu_tanh(bflo(gw)), gelu_tanh(bfhi(gw))), uw);
                    }
                    stsm4(stg_base + (sx ^ (j << 5)), r[0], r[1], r[2], r[3]);
                }
            } else {
                mbar_wait(bars + B_FULL + pp.stage * 8, pp.phase);
                const uint32_t st = sb + pp.stage * W_STAGE;
                mbar_wait(bars + B_STGFREE + wg * 8, stg_phase); stg_phase ^= 1;
                const uint32_t* gb = (const uint32_t*)(g_mod + 5 * D_ + cb * 64) + t;
                const uint32_t xa = st + wg * 8192 + (wl * 16 + g) * 128 + (g << 4) + t * 4;
#pragma unroll
                for (int j = 0; j < 4; j++) {
                    uint32_t r[4];
#pragma unroll
                    for (int q = 0; q < 4; q++) {
                        const int nt = 2 * j + (q >> 1);
                        const uint32_t xw = lds32((xa ^ ((nt & 7) << 4)) + (nt >> 3) * 16384 + (q & 1) * 1024);
                        r[q] = hadd2(xw, hmul2(__ldcg(gb + nt * 4), pack2(acc[8 * j + 2 * q], acc[8 * j + 2 * q + 1])));
                    }
                    stsm4(stg_base + (j >> 2) * 8192 + (sx ^ ((2 * j & 7) << 4)), r[0], r[1], r[2], r[3]);
                }
                __syncwarp();
                if (lane == 0) mbar_arrive(bars + B_EMPTY + pp.stage * 8);
                pipe_next(pp);
            }
            fence_async_smem();
            CTR(5);
            bar_arrive(NB_ST + wg, 160);
            continue;
        }
        float acc[128];
#pragma unroll
        for (int i = 0; i < 128; i++) acc[i] = 0.f;
        const int nk = type == J_O ? (rb >= FINE_RB ? 64 / OSPLIT2 : 64 / OSPLIT) : 8;
#pragma unroll 1
        for (int kb = 0; kb < nk; kb++) {
            if (kb) mbar_wait(bars + B_FULL + pp.stage * 8, pp.phase);
            const uint32_t st = sb + pp.stage * W_STAGE;
            const uint64_t da = mkdesc(st + wg * 8192, 16, 1024), db = mkdesc(st + 16384, 8192, 1024);
            wg_fence();
#pragma unroll
            for (int ks = 0; ks < 4; ks++) wgmma_n256(acc, da + ks * 2, db + ks * 128, 1);
            wg_commit();
            wg_wait0();
            if (lane == 0) mbar_arrive(bars + B_EMPTY + pp.stage * 8);
            pipe_next(pp);
        }
        CTR(4);
        if (type == J_QA) {
            uint32_t qf[64];
#pragma unroll
            for (int i = 0; i < 64; i++) qf[i] = pack2(acc[2 * i], acc[2 * i + 1]);
            const int sg = warp >> 1, half = warp & 1;
            const float sc = 0.08838834764831845f * 1.4426950408889634f;
            const uint32_t xoff = (sg >> 1) * 8192 + ((sg & 1) * 32 + l7) * 128;
            const uint32_t moff = 32768 + (sg * 8 + l7) * 128;
            const uint32_t kch = (l8 ^ l7) << 4;
            const uint32_t vch = ((l8 & 1) ^ l7) << 4;
            mbar_wait(bars + B_STGFREE + wg * 8, stg_phase); stg_phase ^= 1;
#pragma unroll 1
            for (int hh = 0; hh < 2; hh++) {
                mbar_wait(bars + B_FULL + pp.stage * 8, pp.phase);
                uint32_t st = sb + pp.stage * W_STAGE;
                float sa[5][4];
#pragma unroll
                for (int n = 0; n < 5; n++) sa[n][0] = sa[n][1] = sa[n][2] = sa[n][3] = 0.f;
#pragma unroll
                for (int i = 0; i < 4; i++) {
                    const uint32_t* q = qf + i * 8;
                    uint32_t kk[5][4];
                    ldsm4(kk[0][0], kk[0][1], kk[0][2], kk[0][3], st + moff + (i >> 1) * 4096 + (kch ^ ((i & 1) * 64)));
#pragma unroll
                    for (int n = 1; n < 5; n++)
                        ldsm4(kk[n][0], kk[n][1], kk[n][2], kk[n][3], st + xoff + (n - 1) * 1024 + (i >> 1) * 16384 + (kch ^ ((i & 1) * 64)));
#pragma unroll
                    for (int n = 0; n < 5; n++) mma16816(sa[n], q[0], q[1], q[2], q[3], kk[n][0], kk[n][1]);
#pragma unroll
                    for (int n = 0; n < 5; n++) mma16816(sa[n], q[4], q[5], q[6], q[7], kk[n][2], kk[n][3]);
                }
                __syncwarp();
                if (lane == 0) mbar_arrive(bars + B_EMPTY + pp.stage * 8);
                pipe_next(pp);
                const int iq0 = half * 16 + g - 2 * t, iq1 = iq0 + 8;
                float m0 = fmaxf(sa[0][0], sa[0][1]), m1 = fmaxf(sa[0][2], sa[0][3]);
#pragma unroll
                for (int n = 1; n < 5; n++) {
#pragma unroll
                    for (int e = 0; e < 2; e++) {
                        const int jx = (n - 1) * 8 + e;
                        if (jx > iq0) sa[n][e] = -3.0e38f;
                        if (jx > iq1) sa[n][2 + e] = -3.0e38f;
                        m0 = fmaxf(m0, sa[n][e]); m1 = fmaxf(m1, sa[n][2 + e]);
                    }
                }
                m0 = fmaxf(m0, __shfl_xor_sync(~0u, m0, 1)); m1 = fmaxf(m1, __shfl_xor_sync(~0u, m1, 1));
                m0 = fmaxf(m0, __shfl_xor_sync(~0u, m0, 2)); m1 = fmaxf(m1, __shfl_xor_sync(~0u, m1, 2));
                m0 *= -sc; m1 *= -sc;
                float l0 = 0.f, l1 = 0.f;
                uint32_t p0[5], p1[5];
#pragma unroll
                for (int n = 0; n < 5; n++) {
                    const float e0 = ex2(fmaf(sa[n][0], sc, m0)), e1 = ex2(fmaf(sa[n][1], sc, m0));
                    const float e2 = ex2(fmaf(sa[n][2], sc, m1)), e3 = ex2(fmaf(sa[n][3], sc, m1));
                    l0 += e0 + e1; l1 += e2 + e3;
                    p0[n] = pack2(e0, e1); p1[n] = pack2(e2, e3);
                }
                l0 += __shfl_xor_sync(~0u, l0, 1); l1 += __shfl_xor_sync(~0u, l1, 1);
                l0 += __shfl_xor_sync(~0u, l0, 2); l1 += __shfl_xor_sync(~0u, l1, 2);
                const float i0 = __fdividef(1.f, l0), i1 = __fdividef(1.f, l1);
                mbar_wait(bars + B_FULL + pp.stage * 8, pp.phase);
                st = sb + pp.stage * W_STAGE;
#pragma unroll
                for (int i = 0; i < 32; i++) qf[i] = qf[32 + i];
#pragma unroll 1
                for (int bx = 0; bx < 2; bx++) {
                    float o[8][4];
                    uint32_t vm[8], v0[4][4], v1[4][4];
#pragma unroll
                    for (int ep = 0; ep < 4; ep++) {
                        ldsm2t(vm[2 * ep], vm[2 * ep + 1], st + moff + bx * 4096 + (vch ^ (ep << 5)));
                        const uint32_t va = st + xoff + (l8 >> 1) * 1024 + bx * 16384 + (vch ^ (ep << 5));
                        ldsm4t(v0[ep][0], v0[ep][1], v0[ep][2], v0[ep][3], va);
                        ldsm4t(v1[ep][0], v1[ep][1], v1[ep][2], v1[ep][3], va + 2048);
                    }
#pragma unroll
                    for (int n = 0; n < 8; n++) { o[n][0] = o[n][1] = o[n][2] = o[n][3] = 0.f; mma16816(o[n], p0[0], p1[0], p0[1], p1[1], vm[n], v0[n >> 1][n & 1]); }
#pragma unroll
                    for (int n = 0; n < 8; n++) mma16816(o[n], p0[2], p1[2], p0[3], p1[3], v0[n >> 1][2 + (n & 1)], v1[n >> 1][n & 1]);
#pragma unroll
                    for (int n = 0; n < 8; n++) mma1688(o[n], p0[4], p1[4], v1[n >> 1][2 + (n & 1)]);
#pragma unroll
                    for (int ep = 0; ep < 4; ep++)
                        stsm4(stg_base + (hh * 2 + bx) * 8192 + (sx ^ (ep << 5)),
                              pack2(o[2 * ep][0] * i0, o[2 * ep][1] * i0), pack2(o[2 * ep][2] * i1, o[2 * ep][3] * i1),
                              pack2(o[2 * ep + 1][0] * i0, o[2 * ep + 1][1] * i0), pack2(o[2 * ep + 1][2] * i1, o[2 * ep + 1][3] * i1));
                }
                __syncwarp();
                if (lane == 0) mbar_arrive(bars + B_EMPTY + pp.stage * 8);
                pipe_next(pp);
            }
        } else if (type == J_UP) {
            mbar_wait(bars + B_STGFREE + wg * 8, stg_phase); stg_phase ^= 1;
#pragma unroll
            for (int j = 0; j < 8; j++) {
                uint32_t r[4];
#pragma unroll
                for (int q = 0; q < 4; q++) {
                    const uint32_t gw = pack2(acc[8 * j + 2 * q], acc[8 * j + 2 * q + 1]);
                    const uint32_t uw = pack2(acc[64 + 8 * j + 2 * q], acc[64 + 8 * j + 2 * q + 1]);
                    r[q] = hmul2(pack2(gelu_tanh(bflo(gw)), gelu_tanh(bfhi(gw))), uw);
                }
                stsm4(stg_base + (j >> 2) * 8192 + (sx ^ ((2 * j & 7) << 4)), r[0], r[1], r[2], r[3]);
            }
        } else {
            mbar_wait(bars + B_STGFREE + wg * 8, stg_phase); stg_phase ^= 1;
#pragma unroll
            for (int j = 0; j < 16; j++)
                stsm4(stg_base + (j >> 2) * 8192 + (sx ^ ((2 * j & 7) << 4)),
                      pack2(acc[8 * j], acc[8 * j + 1]), pack2(acc[8 * j + 2], acc[8 * j + 3]),
                      pack2(acc[8 * j + 4], acc[8 * j + 5]), pack2(acc[8 * j + 6], acc[8 * j + 7]));
        }
        fence_async_smem();
        CTR(5);
        bar_arrive(NB_ST + wg, 160);
    }
}

__global__ void __launch_bounds__(384, 1) k_work(const __grid_constant__ Params p) {
    extern __shared__ __align__(1024) unsigned char smem_raw[];
    const uint32_t sb = smem_u32(smem_raw);
    if (sb & 1023) __trap();
    const int warp = __shfl_sync(~0u, threadIdx.x >> 5, 0);
    int lane; asm volatile("mov.u32 %0, %%laneid;" : "=r"(lane));
    if (threadIdx.x == 0) {
        const uint32_t bars = sb + SM_BAR;
        for (int i = 0; i < W_NST; i++) { mbar_init(bars + B_FULL + i * 8, 1); mbar_init(bars + B_EMPTY + i * 8, 8); }
        mbar_init(bars + B_STGFREE, 1); mbar_init(bars + B_STGFREE + 8, 1); mbar_init(bars + B_REQ, 1); mbar_init(bars + B_RSP, 1);
        asm volatile("fence.mbarrier_init.release.cluster;" ::: "memory");
    }
    __syncthreads();
    if (warp < 8) {
        asm volatile("setmaxnreg.inc.sync.aligned.u32 232;");
        consumer(p, sb, warp, lane);
    } else {
        asm volatile("setmaxnreg.dec.sync.aligned.u32 40;");
        if (warp == 8) { if (lane == 0) producer(p, sb); }
        else if (warp < 11) store_warp(p, sb, warp - 9, lane);
        else scheduler(p, sb, lane);
        __syncwarp();
        bar_sync(NB_W0, 128);
        if (warp == 8 && p.qmask == 0xff) {
            unsigned last = 0;
            if (lane == 0) { __threadfence(); last = atomicAdd(&g_flags[F_DONE], 1u) == gridDim.x - 1; }
            if (__shfl_sync(~0u, last, 0))
                for (int i = lane; i < F_TOTAL; i += 32) g_flags[i] = 0;
        }
    }
}

typedef CUresult (*EncodeFn)(CUtensorMap*, CUtensorMapDataType, cuuint32_t, void*, const cuuint64_t*, const cuuint64_t*,
                             const cuuint32_t*, const cuuint32_t*, CUtensorMapInterleave, CUtensorMapSwizzle,
                             CUtensorMapL2promotion, CUtensorMapFloatOOBfill);

static void make_map(EncodeFn enc, CUtensorMap* m, const void* ptr, uint64_t rows, uint64_t cols, uint32_t box_rows) {
    cuuint64_t dims[2] = {cols, rows};
    cuuint64_t strides[1] = {cols * 2};
    cuuint32_t box[2] = {64, box_rows};
    cuuint32_t es[2] = {1, 1};
    enc(m, CU_TENSOR_MAP_DATA_TYPE_BFLOAT16, 2, const_cast<void*>(ptr), dims, strides, box, es, CU_TENSOR_MAP_INTERLEAVE_NONE,
        CU_TENSOR_MAP_SWIZZLE_128B, CU_TENSOR_MAP_L2_PROMOTION_L2_256B, CU_TENSOR_MAP_FLOAT_OOB_FILL_NONE);
}
template <typename T> static void* sym_addr(T& sym) { void* p = nullptr; cudaGetSymbolAddress(&p, sym); return p; }

extern "C" void kernel_launch(void* const* d_in, const int* in_sizes, int n_in, void* d_out, int out_size) {
    static Params prm;
    static RecParams rp;
    static bool ready = false;
    static const void* key[14];
    bool same = ready;
    for (int i = 0; i < 13 && same; i++) same = key[i] == d_in[i];
    same = same && key[13] == d_out;
    if (!same) {
        void* fn = nullptr;
        cudaDriverEntryPointQueryResult qr;
        cudaGetDriverEntryPoint("cuTensorMapEncodeTiled", &fn, cudaEnableDefault, &qr);
        EncodeFn enc = (EncodeFn)fn;
        make_map(enc, &prm.tm_h, sym_addr(g_h), S_, D_, 64);
        make_map(enc, &prm.tm_kv, sym_addr(g_kv), S_, 2 * HD_, 64);
        make_map(enc, &prm.tm_kvm, sym_addr(g_kvm), NSEG * 8, 2 * HD_, 32);
        make_map(enc, &prm.tm_o, sym_addr(g_o), S_, HD_, 64);
        make_map(enc, &prm.tm_op, sym_addr(g_op), OP_ROWS, D_, 64);
        make_map(enc, &prm.tm_h2, sym_addr(g_h2), S_, D_, 64);
        make_map(enc, &prm.tm_act, sym_addr(g_act), S_, DF_, 64);
        make_map(enc, &prm.tm_x1, sym_addr(g_x1), S_, D_, 64);
        make_map(enc, &prm.tm_out, d_out, S_, D_, 64);
        make_map(enc, &prm.tm_wq, d_in[2], D_, HD_, 64);
        make_map(enc, &prm.tm_wk, d_in[3], D_, HD_, 64);
        make_map(enc, &prm.tm_wv, d_in[4], D_, HD_, 64);
        make_map(enc, &prm.tm_wo, d_in[5], HD_, D_, 64);
        make_map(enc, &prm.tm_wg, d_in[8], D_, DF_, 64);
        make_map(enc, &prm.tm_wu, d_in[9], D_, DF_, 64);
        make_map(enc, &prm.tm_wd, d_in[10], DF_, D_, 64);
        prm.x = (const bf16*)d_in[0]; prm.c = (const bf16*)d_in[11]; prm.w_mod = (const bf16*)d_in[12];
        rp.mem0 = (const bf16*)d_in[1];
        rp.wq = (const bf16*)d_in[2]; rp.wk = (const bf16*)d_in[3]; rp.wv = (const bf16*)d_in[4]; rp.wo = (const bf16*)d_in[5];
        cudaFuncSetAttribute(k_work, cudaFuncAttributeMaxDynamicSharedMemorySize, SMEM_BYTES);
        cudaFuncSetAttribute(k_rec, cudaFuncAttributeMaxDynamicSharedMemorySize, R_SMEM);
        cudaFuncSetAttribute(k_rec, cudaFuncAttributeNonPortableClusterSizeAllowed, 1);
        {
            cudaLaunchConfig_t cfg = {};
            cfg.gridDim = dim3(128); cfg.blockDim = dim3(384); cfg.dynamicSmemBytes = R_SMEM;
            cudaLaunchAttribute at[1];
            at[0].id = cudaLaunchAttributeClusterDimension; at[0].val.clusterDim.x = 16; at[0].val.clusterDim.y = 1; at[0].val.clusterDim.z = 1;
            cfg.attrs = at; cfg.numAttrs = 1;
            int n = 0;
            cudaOccupancyMaxActiveClusters(&n, k_rec, &cfg);
            rp.ncl = n < 4 ? 4 : (n > 8 ? 8 : n);
        }
        for (int i = 0; i < 13; i++) key[i] = d_in[i];
        key[13] = d_out;
        ready = true;
    }
    cudaStream_t st = cudaStreamPerThread;
    auto launch_rec = [&]() {
        cudaLaunchConfig_t cfg = {};
        cfg.gridDim = dim3(16 * rp.ncl); cfg.blockDim = dim3(384); cfg.dynamicSmemBytes = R_SMEM; cfg.stream = st;
        cudaLaunchAttribute at[1];
        at[0].id = cudaLaunchAttributeClusterDimension; at[0].val.clusterDim.x = 16; at[0].val.clusterDim.y = 1; at[0].val.clusterDim.z = 1;
        cfg.attrs = at; cfg.numAttrs = 1;
        cudaLaunchKernelEx(&cfg, k_rec, rp);
    };
    auto launch_work = [&](int qmask, int pdl) {
        prm.qmask = qmask;
        cudaLaunchConfig_t cfg = {};
        cfg.gridDim = dim3(132); cfg.blockDim = dim3(384); cfg.dynamicSmemBytes = SMEM_BYTES; cfg.stream = st;
        cudaLaunchAttribute at[1];
        at[0].id = cudaLaunchAttributeProgrammaticStreamSerialization; at[0].val.programmaticStreamSerializationAllowed = 1;
        cfg.attrs = at; cfg.numAttrs = pdl;
        cudaLaunchKernelEx(&cfg, k_work, prm);
    };
    launch_rec();
    launch_work(0xff, 1);
}
```

```cpp
#include <cuda_runtime.h>
#include <cuda_bf16.h>
#include <cuda.h>
#include <stdint.h>

typedef __nv_bfloat16 bf16;

constexpr int S_ = 2048, D_ = 512, H_ = 32, DH_ = 128, HD_ = 4096, NSEG = 64, DF_ = 1792;
constexpr int NRB = 16;
constexpr int OSPLIT = 4;

__device__ __align__(1024) bf16 g_h[S_ * D_];
__device__ __align__(1024) bf16 g_kv[S_ * 2 * HD_];
__device__ __align__(1024) bf16 g_kvm[NSEG * 8 * 2 * HD_];
__device__ __align__(1024) bf16 g_o[S_ * HD_];
#define FINE_RB_ 14
constexpr int FINE_RB = FINE_RB_;
constexpr int OSPLIT2 = 8;
constexpr int OP_ROWS = OSPLIT * S_ + OSPLIT2 * (NRB - FINE_RB) * 128;
__device__ __align__(1024) bf16 g_op[OP_ROWS * D_];
__device__ __align__(1024) bf16 g_x1[S_ * D_];
__device__ __align__(1024) bf16 g_h2[S_ * D_];
__device__ __align__(1024) bf16 g_act[S_ * DF_];
__device__ __align__(1024) bf16 g_mod[6 * D_];
__device__ uint32_t g_Fraw[131072 + 65536 + 2048];
#define g_F ((uint32_t*)(((uint64_t)g_Fraw + 0x7FFFFull) & ~0x7FFFFull))
constexpr int F_H = 0, F_MEM = 32, F_O = 64, F_OP = 96, F_H2 = 128, F_ACT = 160, F_MOD = 192, F_KV = 224, F_CLAIM = 256  ,
              F_SIDE = 512  , F_DONE = 576, F_TOTAL = 608;
__device__ __align__(128) unsigned int g_flags[F_TOTAL];
#define TR(j, i) do {} while (0)

__device__ __forceinline__ uint32_t smem_u32(const void* p) { return (uint32_t)__cvta_generic_to_shared(p); }
__device__ __forceinline__ uint32_t clk32() { uint32_t c; asm volatile("mov.u32 %0, %%clock;" : "=r"(c)); return c; }
__device__ __forceinline__ uint32_t mapa_u32(uint32_t addr, uint32_t rank) {
    uint32_t r; asm volatile("mapa.shared::cluster.u32 %0, %1, %2;" : "=r"(r) : "r"(addr), "r"(rank)); return r;
}
__device__ __forceinline__ void mbar_init(uint32_t bar, uint32_t cnt) {
    asm volatile("mbarrier.init.shared::cta.b64 [%0], %1;" :: "r"(bar), "r"(cnt) : "memory");
}
__device__ __forceinline__ void mbar_inval(uint32_t bar) {
    asm volatile("mbarrier.inval.shared::cta.b64 [%0];" :: "r"(bar) : "memory");
}
__device__ __forceinline__ void mbar_expect_tx(uint32_t bar, uint32_t bytes) {
    asm volatile("mbarrier.arrive.expect_tx.shared::cta.b64 _, [%0], %1;" :: "r"(bar), "r"(bytes) : "memory");
}
__device__ __forceinline__ void mbar_arrive(uint32_t bar) {
    asm volatile("mbarrier.arrive.shared::cta.b64 _, [%0];" :: "r"(bar) : "memory");
}
__device__ __forceinline__ bool mbar_try_wait(uint32_t bar, uint32_t parity) {
    uint32_t ok;
    asm volatile("{\n.reg .pred p;\nmbarrier.try_wait.parity.shared::cta.b64 p, [%1], %2;\nselp.u32 %0, 1, 0, p;\n}"
                 : "=r"(ok) : "r"(bar), "r"(parity) : "memory");
    return ok;
}
__device__ __forceinline__ bool mbar_try_wait_cluster(uint32_t bar, uint32_t parity) {
    uint32_t ok;
    asm volatile("{\n.reg .pred p;\nmbarrier.try_wait.parity.acquire.cluster.shared::cta.b64 p, [%1], %2;\nselp.u32 %0, 1, 0, p;\n}"
                 : "=r"(ok) : "r"(bar), "r"(parity) : "memory");
    return ok;
}
constexpr int SPIN_LIMIT = 1 << 18;
#define TIMEOUT(code, info) do {} while (0)
__device__ __forceinline__ void mbar_wait(uint32_t bar, uint32_t parity) {
    int g = 0;
#pragma unroll 1
    while (!mbar_try_wait(bar, parity)) { if (++g >= SPIN_LIMIT) { TIMEOUT(0, bar & 255); break; } }
}
__device__ __forceinline__ void mbar_wait_cluster(uint32_t bar, uint32_t parity) {
    int g = 0;
#pragma unroll 1
    while (!mbar_try_wait_cluster(bar, parity)) { if (++g >= SPIN_LIMIT) { TIMEOUT(1, bar & 255); break; } }
}
__device__ __forceinline__ void bar_sync(int id, int n) { asm volatile("bar.sync %0, %1;" :: "r"(id), "r"(n) : "memory"); }
__device__ __forceinline__ void bar_arrive(int id, int n) { asm volatile("bar.arrive %0, %1;" :: "r"(id), "r"(n) : "memory"); }
__device__ __forceinline__ void cluster_sync_all() {
    asm volatile("barrier.cluster.arrive.aligned;\nbarrier.cluster.wait.aligned;" ::: "memory");
}
__device__ __forceinline__ void st_async_v2(uint32_t addr, float a, float b, uint32_t bar) {
    asm volatile("st.async.weak.shared::cluster.mbarrier::complete_tx::bytes.v2.f32 [%0], {%1,%2}, [%3];"
                 :: "r"(addr), "f"(a), "f"(b), "r"(bar) : "memory");
}
__device__ __forceinline__ void st_async_v4(uint32_t addr, uint4 v, uint32_t bar) {
    asm volatile("st.async.weak.shared::cluster.mbarrier::complete_tx::bytes.v4.b32 [%0], {%1,%2,%3,%4}, [%5];"
                 :: "r"(addr), "r"(v.x), "r"(v.y), "r"(v.z), "r"(v.w), "r"(bar) : "memory");
}
__device__ __forceinline__ uint2 ldg_relaxed2(const uint2* p) {
    uint2 v;
    asm volatile("ld.relaxed.gpu.global.v2.b32 {%0,%1}, [%2];" : "=r"(v.x), "=r"(v.y) : "l"(p) : "memory");
    return v;
}
__device__ __forceinline__ void stg_relaxed2(uint2* p, uint2 v) {
    asm volatile("st.relaxed.gpu.global.v2.b32 [%0], {%1,%2};" :: "l"(p), "r"(v.x), "r"(v.y) : "memory");
}
__device__ __forceinline__ uint4 ldg_relaxed(const uint4* p) {
    uint4 v;
    asm volatile("ld.relaxed.gpu.global.v4.b32 {%0,%1,%2,%3}, [%4];" : "=r"(v.x), "=r"(v.y), "=r"(v.z), "=r"(v.w) : "l"(p) : "memory");
    return v;
}
__device__ __forceinline__ void stg_relaxed(uint4* p, uint4 v) {
    asm volatile("st.relaxed.gpu.global.v4.b32 [%0], {%1,%2,%3,%4};" :: "l"(p), "r"(v.x), "r"(v.y), "r"(v.z), "r"(v.w) : "memory");
}
__device__ __forceinline__ void stg_relaxed32(uint32_t* p, uint32_t v) {
    asm volatile("st.relaxed.gpu.global.b32 [%0], %1;" :: "l"(p), "r"(v) : "memory");
}
__device__ __forceinline__ uint32_t ldg_relaxed32(const uint32_t* p) {
    uint32_t v; asm volatile("ld.relaxed.gpu.global.b32 %0, [%1];" : "=r"(v) : "l"(p) : "memory"); return v;
}
__device__ __forceinline__ unsigned int ld_acquire(const unsigned int* p) {
    unsigned int v; asm volatile("ld.acquire.gpu.global.u32 %0, [%1];" : "=r"(v) : "l"(p) : "memory"); return v;
}
__device__ __forceinline__ void red_release(unsigned int* p, unsigned int v) {
    asm volatile("red.release.gpu.global.add.u32 [%0], %1;" :: "l"(p), "r"(v) : "memory");
}
__device__ __forceinline__ void wait_flag(int idx, unsigned int target) {
    const unsigned int* p = &g_flags[idx];
    int g = 0;
#pragma unroll 1
    while (ld_acquire(p) < target) { __nanosleep(20); if (++g >= 64 * SPIN_LIMIT) { TIMEOUT(2, idx); break; } }
}
__device__ __forceinline__ void cp_async16(uint32_t dst, const void* src) {
    asm volatile("cp.async.cg.shared.global [%0], [%1], 16;" :: "r"(dst), "l"(src) : "memory");
}
__device__ __forceinline__ void cp_async_commit() { asm volatile("cp.async.commit_group;" ::: "memory"); }
template <int N> __device__ __forceinline__ void cp_async_wait() { asm volatile("cp.async.wait_group %0;" :: "n"(N) : "memory"); }
__device__ __forceinline__ void ldsm4(uint32_t& r0, uint32_t& r1, uint32_t& r2, uint32_t& r3, uint32_t addr) {
    asm volatile("ldmatrix.sync.aligned.m8n8.x4.shared.b16 {%0,%1,%2,%3}, [%4];" : "=r"(r0), "=r"(r1), "=r"(r2), "=r"(r3) : "r"(addr) : "memory");
}
__device__ __forceinline__ void ldsm4t(uint32_t& r0, uint32_t& r1, uint32_t& r2, uint32_t& r3, uint32_t addr) {
    asm volatile("ldmatrix.sync.aligned.m8n8.x4.trans.shared.b16 {%0,%1,%2,%3}, [%4];" : "=r"(r0), "=r"(r1), "=r"(r2), "=r"(r3) : "r"(addr) : "memory");
}
__device__ __forceinline__ void ldsm2t(uint32_t& r0, uint32_t& r1, uint32_t addr) {
    asm volatile("ldmatrix.sync.aligned.m8n8.x2.trans.shared.b16 {%0,%1}, [%2];" : "=r"(r0), "=r"(r1) : "r"(addr) : "memory");
}
__device__ __forceinline__ void stsm4(uint32_t addr, uint32_t r0, uint32_t r1, uint32_t r2, uint32_t r3) {
    asm volatile("stmatrix.sync.aligned.m8n8.x4.shared.b16 [%0], {%1,%2,%3,%4};" :: "r"(addr), "r"(r0), "r"(r1), "r"(r2), "r"(r3) : "memory");
}
__device__ __forceinline__ void stsm2t(uint32_t addr, uint32_t r0, uint32_t r1) {
    asm volatile("stmatrix.sync.aligned.m8n8.x2.trans.shared.b16 [%0], {%1,%2};" :: "r"(addr), "r"(r0), "r"(r1) : "memory");
}
__device__ __forceinline__ void mma16816(float* d, uint32_t a0, uint32_t a1, uint32_t a2, uint32_t a3, uint32_t b0, uint32_t b1) {
    asm volatile("mma.sync.aligned.m16n8k16.row.col.f32.bf16.bf16.f32 {%0,%1,%2,%3}, {%4,%5,%6,%7}, {%8,%9}, {%0,%1,%2,%3};"
                 : "+f"(d[0]), "+f"(d[1]), "+f"(d[2]), "+f"(d[3]) : "r"(a0), "r"(a1), "r"(a2), "r"(a3), "r"(b0), "r"(b1));
}
__device__ __forceinline__ void mma1688(float* d, uint32_t a0, uint32_t a1, uint32_t b0) {
    asm volatile("mma.sync.aligned.m16n8k8.row.col.f32.bf16.bf16.f32 {%0,%1,%2,%3}, {%4,%5}, {%6}, {%0,%1,%2,%3};"
                 : "+f"(d[0]), "+f"(d[1]), "+f"(d[2]), "+f"(d[3]) : "r"(a0), "r"(a1), "r"(b0));
}
__device__ __forceinline__ void mma16816h(float* d, uint32_t a0, uint32_t a2, uint32_t b0, uint32_t b1) {
    asm volatile("{\n.reg .b32 ju, jv;\nmma.sync.aligned.m16n8k16.row.col.f32.bf16.bf16.f32 {%0,%1,%2,%3}, {%4,ju,%5,jv}, {%6,%7}, {%0,%1,%2,%3};\n}"
                 : "+f"(d[0]), "+f"(d[1]), "+f"(d[2]), "+f"(d[3]) : "r"(a0), "r"(a2), "r"(b0), "r"(b1));
}
__device__ __forceinline__ void mma1688h(float* d, uint32_t a0, uint32_t b0) {
    asm volatile("{\n.reg .b32 ju;\nmma.sync.aligned.m16n8k8.row.col.f32.bf16.bf16.f32 {%0,%1,%2,%3}, {%4,ju}, {%5}, {%0,%1,%2,%3};\n}"
                 : "+f"(d[0]), "+f"(d[1]), "+f"(d[2]), "+f"(d[3]) : "r"(a0), "r"(b0));
}
__device__ __forceinline__ uint32_t pack2(float lo, float hi) {
    uint32_t r; asm("cvt.rn.bf16x2.f32 %0, %1, %2;" : "=r"(r) : "f"(hi), "f"(lo)); return r;
}
__device__ __forceinline__ float bflo(uint32_t w) { return __uint_as_float(w << 16); }
__device__ __forceinline__ float bfhi(uint32_t w) { return __uint_as_float(w & 0xffff0000u); }
__device__ __forceinline__ float rbf(float x) { return __bfloat162float(__float2bfloat16_rn(x)); }
__device__ __forceinline__ float ex2(float x) { float y; asm("ex2.approx.ftz.f32 %0, %1;" : "=f"(y) : "f"(x)); return y; }
__device__ __forceinline__ void sts128(uint32_t addr, uint4 v) {
    asm volatile("st.shared.v4.b32 [%0], {%1,%2,%3,%4};" :: "r"(addr), "r"(v.x), "r"(v.y), "r"(v.z), "r"(v.w) : "memory");
}
__device__ __forceinline__ uint4 lds128(uint32_t addr) {
    uint4 v; asm volatile("ld.shared.v4.b32 {%0,%1,%2,%3}, [%4];" : "=r"(v.x), "=r"(v.y), "=r"(v.z), "=r"(v.w) : "r"(addr) : "memory"); return v;
}
__device__ __forceinline__ float2 lds64f(uint32_t addr) {
    float2 v; asm volatile("ld.shared.v2.f32 {%0,%1}, [%2];" : "=f"(v.x), "=f"(v.y) : "r"(addr) : "memory"); return v;
}
__device__ __forceinline__ float lds32f(uint32_t addr) {
    float v; asm volatile("ld.shared.f32 %0, [%1];" : "=f"(v) : "r"(addr) : "memory"); return v;
}
__device__ __forceinline__ uint32_t lds32(uint32_t addr) {
    uint32_t v; asm volatile("ld.shared.b32 %0, [%1];" : "=r"(v) : "r"(addr) : "memory"); return v;
}
__device__ __forceinline__ void sts32(uint32_t addr, uint32_t v) { asm volatile("st.shared.b32 [%0], %1;" :: "r"(addr), "r"(v) : "memory"); }
__device__ __forceinline__ void sts64f(uint32_t addr, float a, float b) { asm volatile("st.shared.v2.f32 [%0], {%1,%2};" :: "r"(addr), "f"(a), "f"(b) : "memory"); }

__device__ __forceinline__ void tma_load2d(uint32_t dst, const CUtensorMap* tm, int c0, int c1, uint32_t bar) {
    asm volatile("cp.async.bulk.tensor.2d.shared::cluster.global.mbarrier::complete_tx::bytes [%0], [%1, {%3, %4}], [%2];"
                 :: "r"(dst), "l"(tm), "r"(bar), "r"(c0), "r"(c1) : "memory");
}
__device__ __forceinline__ void tma_store2d(const CUtensorMap* tm, uint32_t src, int c0, int c1) {
    asm volatile("cp.async.bulk.tensor.2d.global.shared::cta.bulk_group [%0, {%2, %3}], [%1];"
                 :: "l"(tm), "r"(src), "r"(c0), "r"(c1) : "memory");
}
__device__ __forceinline__ void bulk_commit() { asm volatile("cp.async.bulk.commit_group;" ::: "memory"); }
__device__ __forceinline__ void bulk_wait0() { asm volatile("cp.async.bulk.wait_group 0;" ::: "memory"); }
__device__ __forceinline__ void fence_async_smem() { asm volatile("fence.proxy.async.shared::cta;" ::: "memory"); }
__device__ __forceinline__ void fence_async_all() { asm volatile("fence.proxy.async;" ::: "memory"); }

__device__ __forceinline__ void wg_fence() { asm volatile("wgmma.fence.sync.aligned;" ::: "memory"); }
__device__ __forceinline__ void wg_commit() { asm volatile("wgmma.commit_group.sync.aligned;" ::: "memory"); }
__device__ __forceinline__ void wg_wait0() { asm volatile("wgmma.wait_group.sync.aligned 0;" ::: "memory"); }
__device__ __forceinline__ uint64_t mkdesc(uint32_t saddr, uint32_t lbo, uint32_t sbo) {
    return (uint64_t)((saddr & 0x3FFFF) >> 4) | ((uint64_t)(lbo >> 4) << 16) | ((uint64_t)(sbo >> 4) << 32) | (1ull << 62);
}
#define ACC8(i) "+f"(d[i]), "+f"(d[i + 1]), "+f"(d[i + 2]), "+f"(d[i + 3]), "+f"(d[i + 4]), "+f"(d[i + 5]), "+f"(d[i + 6]), "+f"(d[i + 7])
__device__ __forceinline__ void wgmma_n256(float* d, uint64_t da, uint64_t db, int scale_d) {
    asm volatile(
        "{\n.reg .pred p;\nsetp.ne.b32 p, %130, 0;\n"
        "wgmma.mma_async.sync.aligned.m64n256k16.f32.bf16.bf16 "
        "{%0,%1,%2,%3,%4,%5,%6,%7,%8,%9,%10,%11,%12,%13,%14,%15,%16,%17,%18,%19,%20,%21,%22,%23,%24,%25,%26,%27,%28,%29,%30,%31,"
        "%32,%33,%34,%35,%36,%37,%38,%39,%40,%41,%42,%43,%44,%45,%46,%47,%48,%49,%50,%51,%52,%53,%54,%55,%56,%57,%58,%59,%60,%61,%62,%63,"
        "%64,%65,%66,%67,%68,%69,%70,%71,%72,%73,%74,%75,%76,%77,%78,%79,%80,%81,%82,%83,%84,%85,%86,%87,%88,%89,%90,%91,%92,%93,%94,%95,"
        "%96,%97,%98,%99,%100,%101,%102,%103,%104,%105,%106,%107,%108,%109,%110,%111,%112,%113,%114,%115,%116,%117,%118,%119,%120,%121,%122,%123,%124,%125,%126,%127}, "
        "%128, %129, p, 1, 1, 0, 1;\n}"
        : ACC8(0), ACC8(8), ACC8(16), ACC8(24), ACC8(32), ACC8(40), ACC8(48), ACC8(56),
          ACC8(64), ACC8(72), ACC8(80), ACC8(88), ACC8(96), ACC8(104), ACC8(112), ACC8(120)
        : "l"(da), "l"(db), "r"(scale_d));
}
__device__ __forceinline__ void wgmma_n128(float* d, uint64_t da, uint64_t db, int scale_d) {
    asm volatile(
        "{\n.reg .pred p;\nsetp.ne.b32 p, %66, 0;\n"
        "wgmma.mma_async.sync.aligned.m64n128k16.f32.bf16.bf16 "
        "{%0,%1,%2,%3,%4,%5,%6,%7,%8,%9,%10,%11,%12,%13,%14,%15,%16,%17,%18,%19,%20,%21,%22,%23,%24,%25,%26,%27,%28,%29,%30,%31,"
        "%32,%33,%34,%35,%36,%37,%38,%39,%40,%41,%42,%43,%44,%45,%46,%47,%48,%49,%50,%51,%52,%53,%54,%55,%56,%57,%58,%59,%60,%61,%62,%63}, "
        "%64, %65, p, 1, 1, 0, 1;\n}"
        : ACC8(0), ACC8(8), ACC8(16), ACC8(24), ACC8(32), ACC8(40), ACC8(48), ACC8(56)
        : "l"(da), "l"(db), "r"(scale_d));
}

__device__ __forceinline__ void wgmma_n64(float* d, uint64_t da, uint64_t db) {
    asm volatile(
        "wgmma.mma_async.sync.aligned.m64n64k16.f32.bf16.bf16 "
        "{%0,%1,%2,%3,%4,%5,%6,%7,%8,%9,%10,%11,%12,%13,%14,%15,%16,%17,%18,%19,%20,%21,%22,%23,%24,%25,%26,%27,%28,%29,%30,%31}, "
        "%32, %33, 1, 1, 1, 0, 1;"
        : ACC8(0), ACC8(8), ACC8(16), ACC8(24)
        : "l"(da), "l"(db));
}
__device__ __forceinline__ void wgmma_n8_ta(float* d, uint64_t da, uint64_t db, int scale_d) {
    asm volatile(
        "{\n.reg .pred p;\nsetp.ne.b32 p, %6, 0;\n"
        "wgmma.mma_async.sync.aligned.m64n8k16.f32.bf16.bf16 {%0,%1,%2,%3}, %4, %5, p, 1, 1, 1, 0;\n}"
        : "+f"(d[0]), "+f"(d[1]), "+f"(d[2]), "+f"(d[3]) : "l"(da), "l"(db), "r"(scale_d));
}

__device__ __forceinline__ uint32_t hadd2(uint32_t a, uint32_t b) { uint32_t r; asm("add.rn.bf16x2 %0, %1, %2;" : "=r"(r) : "r"(a), "r"(b)); return r; }
__device__ __forceinline__ uint32_t hsub2(uint32_t a, uint32_t b) { uint32_t r; asm("sub.rn.bf16x2 %0, %1, %2;" : "=r"(r) : "r"(a), "r"(b)); return r; }
__device__ __forceinline__ uint32_t hmul2(uint32_t a, uint32_t b) { uint32_t r; asm("mul.rn.bf16x2 %0, %1, %2;" : "=r"(r) : "r"(a), "r"(b)); return r; }
__device__ __forceinline__ void load_mod8(const bf16* m, int lane, uint32_t* v) {
    const uint4 a = __ldcg((const uint4*)m + lane), b = __ldcg((const uint4*)m + 32 + lane);
    v[0] = a.x; v[1] = a.y; v[2] = a.z; v[3] = a.w; v[4] = b.x; v[5] = b.y; v[6] = b.z; v[7] = b.w;
}
__device__ __forceinline__ void ln_stats(const uint32_t* x, uint32_t& mu2, float& rden) {
    float s = 0.f;
#pragma unroll
    for (int i = 0; i < 8; i++) s += bflo(x[i]) + bfhi(x[i]);
#pragma unroll
    for (int o = 16; o > 0; o >>= 1) s += __shfl_xor_sync(~0u, s, o);
    const float mean = s * (1.f / D_);
    float q = 0.f;
#pragma unroll
    for (int i = 0; i < 8; i++) { const float d0 = bflo(x[i]) - mean, d1 = bfhi(x[i]) - mean; q = fmaf(d0, d0, q); q = fmaf(d1, d1, q); }
#pragma unroll
    for (int o = 16; o > 0; o >>= 1) q += __shfl_xor_sync(~0u, q, o);
    mu2 = pack2(mean, mean);
    rden = __frcp_rn(rbf(__fsqrt_rn(rbf(rbf(q * (1.f / D_)) + 1e-5f))));
}
__device__ __forceinline__ void ln_apply(const uint32_t* x, uint32_t mu2, float rden, const uint32_t* c1, const uint32_t* sm, uint32_t* r) {
#pragma unroll
    for (int i = 0; i < 8; i++) {
        const uint32_t d = hsub2(x[i], mu2);
        r[i] = hadd2(hmul2(pack2(bflo(d) * rden, bfhi(d) * rden), c1[i]), sm[i]);
    }
}

struct __align__(64) Params {
    CUtensorMap tm_h, tm_kv, tm_kvm, tm_o, tm_op, tm_h2, tm_act, tm_x1, tm_out;
    CUtensorMap tm_wq, tm_wk, tm_wv, tm_wo, tm_wg, tm_wu, tm_wd;
    const bf16 *x, *c, *w_mod;
    int qmask;
};

constexpr int R_NST = 3;
constexpr uint32_t R_WV = 0, R_MEM = 65536, R_KX = 73728, R_VX = R_KX + R_NST * 4096,
                   R_KMS = R_VX + R_NST * 4096  , R_VMS = R_KMS + 1024,
                   R_QS = R_KMS + 4096, R_OS = R_QS + 1024, R_SX = R_OS + 1024, R_BAR = R_SX + 2560,
                   R_RS = 107520  , R_VP = R_RS + 8192  ,
                   R_STG = R_VP + 8192  , R_SMEM = R_STG + 98304;
static_assert((R_KMS & 4095) == 0, "smem");
static_assert(R_BAR + 64 <= R_RS, "smem");
constexpr uint32_t RB_SX = R_BAR, RB_V = R_BAR + 8, RB_E = R_BAR + 16, RB_A = R_BAR + 24, RB_ROLE = R_BAR + 32, RB_A1 = R_BAR + 40;
constexpr int W_NST = 3;
constexpr uint32_t W_STAGE = 49152, W_STG = W_NST * W_STAGE, W_END = W_STG + 65536;
constexpr uint32_t SM_BAR = W_END;
constexpr uint32_t SMEM_BYTES = W_END + 1024 + 2048;
constexpr uint32_t B_FULL = 0, B_EMPTY = 32, B_STGFREE = 64, B_REQ = 80, B_RSP = 88, B_NEXT = 96, B_RING = 128;
#define PICK_AHEAD 2

constexpr int NB_X = 11  , NB_Y = 1, NB_M = 5, NB_B = 2, NB_C = 3, NB_D = 4, NB_W0 = 6  , NB_ST = 9  ;

__device__ __forceinline__ int pos_of_d(int d) {
    const int rem = d & 31;
    return (d & ~31) + ((rem & 7) >> 1) * 8 + (rem & 1) * 4 + (rem >> 3);
}

#define PROF(i) do {} while (0)
#define PROFG(i) do {} while (0)
#define OPAQUE(x) asm volatile("" : "+r"(x))
#define FENCE_SCHED(x) do { if ((x) == 0u) asm volatile("trap;"); } while (0)
#define VK0_ 4
constexpr int VK0 = VK0_;
constexpr int NOFF = 8;
#define VDELAY -1
#define POLL_GAP 110

struct RecParams { const bf16 *mem0, *wq, *wk, *wv, *wo; int ncl; };

__device__ __forceinline__ void rec_qk(const RecParams& p, const uint32_t sb, const int cta, const int warp, int lane, const int sel) {
    const int crank = cta & 15, cl = cta >> 4, rank = cta & 1;
    const int kh = warp >> 2, aa = warp & 3;
    uint32_t wa[2][16][4];
    const uint32_t stg = sb + R_STG + kh * 32768;
    {
        const int t128 = aa * 32 + lane;
        const int row = (lane >> 4) * 8 + (lane & 7);
        const int ch = t128 & 7;
        const size_t goff = (size_t)kh * 256 * HD_ + cta * 64 + ch * 8;
#pragma unroll 4
        for (int dd = 0; dd < 16; dd++) {
            const int d = dd * 16 + (t128 >> 3), pp = pos_of_d(d);
            cp_async16(sb + R_WV + kh * 32768 + pp * 128 + ((ch ^ (pp & 7)) << 4), p.wv + goff + (size_t)d * HD_);
        }
        cp_async_commit();
#pragma unroll 4
        for (int dd = 0; dd < 16; dd++) {
            const int d = dd * 16 + (t128 >> 3), pp = pos_of_d(d);
            cp_async16(stg + pp * 128 + ((ch ^ (pp & 7)) << 4), p.wq + goff + (size_t)d * HD_);
        }
        cp_async_commit();
        {
            const int i0 = (warp * 32 + lane) * 16, tok = i0 >> 9;
            const uint4 m0 = __ldg((const uint4*)(p.mem0 + i0)), m1 = __ldg((const uint4*)(p.mem0 + i0 + 8));
            const uint32_t mw[8] = {m0.x, m0.y, m0.z, m0.w, m1.x, m1.y, m1.z, m1.w};
#pragma unroll
            for (int e = 0; e < 16; e++) {
                const int pp = pos_of_d((i0 & 511) + e);
                const unsigned short v = (unsigned short)(mw[e >> 1] >> ((e & 1) * 16));
                asm volatile("st.shared.u16 [%0], %1;" :: "r"(sb + R_MEM + (pp >> 3) * 128 + tok * 16 + (pp & 7) * 2), "h"(v) : "memory");
            }
        }
        cp_async_wait<1>();
        bar_sync(NB_W0 + kh, 128);
        const uint32_t fv = row * 128 + (((2 * aa + ((lane >> 3) & 1)) ^ (row & 7)) << 4);
#pragma unroll
        for (int ks = 0; ks < 16; ks++) ldsm4t(wa[0][ks][0], wa[0][ks][1], wa[0][ks][2], wa[0][ks][3], sb + R_WV + kh * 32768 + fv + ks * 2048);
        bar_sync(NB_W0 + kh, 128);
#pragma unroll
        for (int ks = 0; ks < 16; ks++)
            sts128(sb + R_WV + kh * 32768 + (aa * 16 + ks) * 512 + lane * 16, make_uint4(wa[0][ks][0], wa[0][ks][1], wa[0][ks][2], wa[0][ks][3]));
        const uint32_t fo = stg + row * 128 + (((4 * (aa & 1) + ((lane >> 3) & 1)) ^ (row & 7)) << 4);
#pragma unroll 1
        for (int m = 0; m < 2; m++) {
            cp_async_wait<0>();
            bar_sync(NB_W0 + kh, 128);
            if ((aa >> 1) == m) {
#pragma unroll
                for (int ks = 0; ks < 16; ks++) {
                    ldsm4t(wa[0][ks][0], wa[0][ks][1], wa[0][ks][2], wa[0][ks][3], fo + ks * 2048);
                    ldsm4t(wa[1][ks][0], wa[1][ks][1], wa[1][ks][2], wa[1][ks][3], (fo ^ 32) + ks * 2048);
                }
            }
            bar_sync(NB_W0 + kh, 128);
            if (m == 0) {
#pragma unroll 4
                for (int dd = 0; dd < 16; dd++) {
                    const int d = dd * 16 + (t128 >> 3), pp = pos_of_d(d);
                    cp_async16(stg + pp * 128 + ((ch ^ (pp & 7)) << 4), p.wk + goff + (size_t)d * HD_);
                }
                cp_async_commit();
            }
        }
    }
    const uint32_t tab = stg + (aa * 32 + lane) * 16;
    {
        const uint32_t l7 = lane & 7, l8 = lane >> 3, g = lane >> 2, t = lane & 3;
        const uint32_t t0 = l7 * 128 + ((l8 ^ l7) << 4);
        const uint32_t tq = l7 * 128 + (((l8 >> 1) ^ l7) << 4);
        const uint32_t bq = warp >> 1, tp = warp & 1;
        uint4 v;
        v.x = sb + (aa < 2 ? R_QS : R_KMS) + l7 * 128 + (((4 * (aa & 1) + 2 * kh + (l8 & 1)) ^ l7) << 4);
        v.y = sb + R_QS + tq;
        v.z = sb + (warp == 0 ? R_KMS : R_KX + (warp - 1) * 1024) + t0;
        v.w = mapa_u32(sb + R_SX + (rank * 5 + warp) * 256 + lane * 8, crank ^ 1);
        sts128(tab, v);
        sts128(tab + 2048, make_uint4(sb + lane * 16 + R_MEM + kh * 4096, sb + lane * 16 + R_WV + warp * 8192,
                                      sb + lane * 16 + R_VP + warp * 512, sb + lane * 16 + R_VP + 4096 + (warp ^ 4) * 512));
        const uint32_t src = (l8 >> 1) * 8 + l7;
        const uint32_t L = bq * 8 + 2 * tp + (l8 & 1);
        const uint32_t d0 = (crank + ((t >> 1) | (g & 6))) & 15;
        v.x = sb + R_RS + src * 512 + ((L ^ (src & 7)) << 4);
        v.y = mapa_u32(sb + R_MEM + (crank * 4 + bq) * 128 + (4 * tp + 2 * (t & 1) + (g & 1)) * 16, d0);
        v.z = mapa_u32(sb + ((crank & 2) ? RB_A1 : RB_A), d0);
        v.w = lane;
        sts128(tab + 4096, v);
        const uint64_t wr = (uint64_t)(g_F + ((crank * 2 + ((crank ^ (crank >> 3) ^ sel) & 1)) * 1024 + warp * 128 + cl * 32 + lane));
        sts128(tab + 6144, make_uint4((uint32_t)wr, (uint32_t)(wr >> 32), (uint32_t)((((cl + 1) & 3) - cl) * 128), (uint32_t)((((cl + 2) & 3) - cl) * 128)));
        sts32(tab + 8192, (uint32_t)((((cl + 3) & 3) - cl) * 128));
#pragma unroll
        for (int i = 0; i < NOFF; i++)
            sts128(tab + 10240 + i * 2048, make_uint4(wa[i & 1][i >> 1][0], wa[i & 1][i >> 1][1], wa[i & 1][i >> 1][2], wa[i & 1][i >> 1][3]));
    }
    bar_sync(NB_D, 384);
    uint32_t slot_off = 0;
    const uint32_t slot_inc = warp == 0 ? 2048 : 4096, slot_last = warp == 0 ? 2048 : (R_NST - 1) * 4096;
    const uint32_t sx_bar_rem = (sb + RB_SX) ^ (1u << 24);
    uint4 tb = lds128(tab + 2048);
#pragma unroll 1
    for (int s = 0; s < NSEG; s++) {
        if (s > 0) mbar_wait(sb + RB_A, (s - 1) & 1);
        if (warp == 0) { PROF(0); PROFG(13); }
        uint4 ta;
        const uint32_t km_tog = aa >= 2 ? (s & 1) * 2048 : 0;
        {
            float acc[5][4];
#pragma unroll
            for (int c = 0; c < 5; c++) { acc[c][0] = acc[c][1] = acc[c][2] = acc[c][3] = 0.f; }
            uint32_t b[8][4];
            uint4 av[16];
            static_assert(VK0 == 4, "order below assumes the V/O warps cover slices 0,1");
            ldsm4(b[0][0], b[0][1], b[0][2], b[0][3], tb.x);
            ldsm4(b[1][0], b[1][1], b[1][2], b[1][3], tb.x + 512);
            ldsm4(b[4][0], b[4][1], b[4][2], b[4][3], tb.x + 2048);
            ldsm4(b[5][0], b[5][1], b[5][2], b[5][3], tb.x + 2560);
#pragma unroll
            for (int kk = 0; kk < 8; kk++) {
                const int k2 = kk < 2 ? kk : (kk < 4 ? kk + 2 : (kk < 6 ? kk - 2 : kk));
                if (kk == 4) {
                    if (s > 0) mbar_wait(sb + RB_A1, (s - 1) & 1);
                    ldsm4(b[2][0], b[2][1], b[2][2], b[2][3], tb.x + 1024);
                    ldsm4(b[3][0], b[3][1], b[3][2], b[3][3], tb.x + 1536);
                    ldsm4(b[6][0], b[6][1], b[6][2], b[6][3], tb.x + 3072);
                    ldsm4(b[7][0], b[7][1], b[7][2], b[7][3], tb.x + 3584);
#pragma unroll
                    for (int i = 12; i < 16; i++) av[i] = lds128(tb.y + i * 512);
                    ta = lds128(tab);
                }
                mma16816(acc[0], wa[0][2 * k2][0], wa[0][2 * k2][1], wa[0][2 * k2][2], wa[0][2 * k2][3], b[k2][0], b[k2][1]);
                mma16816(acc[1], wa[1][2 * k2][0], wa[1][2 * k2][1], wa[1][2 * k2][2], wa[1][2 * k2][3], b[k2][0], b[k2][1]);
                mma16816(acc[3], wa[0][2 * k2 + 1][0], wa[0][2 * k2 + 1][1], wa[0][2 * k2 + 1][2], wa[0][2 * k2 + 1][3], b[k2][2], b[k2][3]);
                mma16816(acc[4], wa[1][2 * k2 + 1][0], wa[1][2 * k2 + 1][1], wa[1][2 * k2 + 1][2], wa[1][2 * k2 + 1][3], b[k2][2], b[k2][3]);
                if (2 * k2 >= VK0) {
                    mma16816(acc[2], av[2 * k2].x, av[2 * k2].y, av[2 * k2].z, av[2 * k2].w, b[k2][0], b[k2][1]);
                    mma16816(acc[2], av[2 * k2 + 1].x, av[2 * k2 + 1].y, av[2 * k2 + 1].z, av[2 * k2 + 1].w, b[k2][2], b[k2][3]);
                }
                if (kk == 0) { av[8] = lds128(tb.y + 8 * 512); av[9] = lds128(tb.y + 9 * 512); }
                if (kk == 1) { av[10] = lds128(tb.y + 10 * 512); av[11] = lds128(tb.y + 11 * 512); }
                if (kk == 2) { av[4] = lds128(tb.y + 4 * 512); av[5] = lds128(tb.y + 5 * 512); }
                if (kk == 3) { av[6] = lds128(tb.y + 6 * 512); av[7] = lds128(tb.y + 7 * 512); }
            }
#pragma unroll
            for (int i = 0; i < 4; i++) { acc[0][i] += acc[3][i]; acc[1][i] += acc[4][i]; }
            const float g0 = kh ? acc[0][0] : acc[1][0], g1 = kh ? acc[0][1] : acc[1][1], g2 = kh ? acc[0][2] : acc[1][2], g3 = kh ? acc[0][3] : acc[1][3];
            sts128(tb.w, make_uint4(__float_as_uint(g0), __float_as_uint(g1), __float_as_uint(g2), __float_as_uint(g3)));
            const float k0 = kh ? acc[1][0] : acc[0][0], k1 = kh ? acc[1][1] : acc[0][1], k2_ = kh ? acc[1][2] : acc[0][2], k3 = kh ? acc[1][3] : acc[0][3];
            if (warp == 0) PROF(1);
            bar_sync(NB_X + aa, 64);
            const uint4 o = lds128(tb.z + 4096);
            stsm2t(ta.x ^ km_tog, pack2(k0 + __uint_as_float(o.x), k1 + __uint_as_float(o.y)), pack2(k2_ + __uint_as_float(o.z), k3 + __uint_as_float(o.w)));
            sts128(tb.z, make_uint4(__float_as_uint(acc[2][0]), __float_as_uint(acc[2][1]), __float_as_uint(acc[2][2]), __float_as_uint(acc[2][3])));
        }
        const uint32_t kb = ta.z + slot_off;
        if (warp == 0) PROF(14);
        bar_sync(NB_B, 256);
        if (warp < 5) {
            uint32_t q[16], k0, k1, k2, k3, k4, k5, k6, k7;
            float sa[4] = {0.f, 0.f, 0.f, 0.f}, sc[4] = {0.f, 0.f, 0.f, 0.f};
            ldsm4(q[0], q[1], q[2], q[3], ta.y);
            ldsm4(k0, k1, k2, k3, kb);
            ldsm4(q[4], q[5], q[6], q[7], ta.y ^ 32);
            ldsm4(q[8], q[9], q[10], q[11], ta.y ^ 64);
            ldsm4(k4, k5, k6, k7, kb ^ 64);
            ldsm4(q[12], q[13], q[14], q[15], ta.y ^ 96);
            mma16816(sa, q[0], q[1], q[2], q[3], k0, k1);
            bar_arrive(NB_Y, 288);
            mma16816(sc, q[4], q[5], q[6], q[7], k2, k3);
            mma16816(sa, q[8], q[9], q[10], q[11], k4, k5);
            mma16816(sc, q[12], q[13], q[14], q[15], k6, k7);
            const float scl = 0.08838834764831845f * 1.4426950408889634f;
            const float r0 = (sa[0] + sc[0]) * scl, r1 = (sa[1] + sc[1]) * scl;
            if (s != NSEG - 1) {
                st_async_v2(ta.w, r0, r1, sx_bar_rem);
                st_async_v2(ta.w ^ (1u << 24), r0, r1, sx_bar_rem ^ (1u << 24));
            }
            if (warp == 0) PROF(2);
        } else if (s > 0 && warp == 7 && lane == 0) {
            mbar_expect_tx(sb + RB_A, 4096);
            mbar_expect_tx(sb + RB_A1, 4096);
        }
        if (s == NSEG - 1) {
            const uint4 td = lds128(tab + 6144);
            stg_relaxed32((uint32_t*)(((uint64_t)td.y << 32) | (td.x ^ 0x21000)), 0u);
            break;
        }
        slot_off = slot_off == slot_last ? 0 : slot_off + slot_inc;
        const uint4 tc = lds128(tab + 4096), td = lds128(tab + 6144);
        const uint32_t te = lds32(tab + 8192);
        uint32_t* wr = (uint32_t*)(((uint64_t)td.y << 32) | (td.x ^ ((s & 1) * 0x21000)));
        const uint32_t* r1p = (const uint32_t*)((const char*)wr + (int)td.z);
        const uint32_t* r2p = (const uint32_t*)((const char*)wr + (int)td.w);
        const uint32_t* r3p = (const uint32_t*)((const char*)wr + (int)te);
        const uint32_t tag = ((s >> 1) + 1) & 1;
        mbar_wait(sb + RB_E, s & 1);
        if (warp == 0) PROF(7);
        {
            uint32_t a0, a1, a2, a3, a4, a5, a6, a7;
            ldsm4t(a0, a1, a2, a3, tc.x);
            ldsm4t(a4, a5, a6, a7, tc.x ^ 64);
            const uint32_t one = 0x3F803F80u;
            float d0_[4] = {0.f, 0.f, 0.f, 0.f}, d1_[4] = {0.f, 0.f, 0.f, 0.f};
            mma16816(d0_, a0, a1, a2, a3, one, one);
            mma16816(d1_, a4, a5, a6, a7, one, one);
            const bool t1 = tc.w & 1, t2 = tc.w & 2;
            const float x = t2 ? (t1 ? d1_[2] : d1_[0]) : (t1 ? d0_[2] : d0_[0]);
            const uint32_t own = (__float_as_uint(x) & ~1u) | tag;
            stg_relaxed32(wr, own);
            const uint32_t tq = clk32();
            if (warp == 0) PROF(8);
            PROFG(16 + warp);
            while ((int)(clk32() - tq) < POLL_GAP) {}
            uint32_t f1 = ldg_relaxed32(r1p), f2 = ldg_relaxed32(r2p), f3 = ldg_relaxed32(r3p);
#pragma unroll
            for (int i = 0; i < NOFF; i++) {
                const uint4 f0 = lds128(tab + 10240 + i * 2048);
                wa[i & 1][i >> 1][0] = f0.x; wa[i & 1][i >> 1][1] = f0.y; wa[i & 1][i >> 1][2] = f0.z; wa[i & 1][i >> 1][3] = f0.w;
            }
            tb = lds128(tab + 2048);
            int gg = 0;
#pragma unroll 1
            while (!__all_sync(~0u, (((f1 ^ tag) | (f2 ^ tag) | (f3 ^ tag)) & 1) == 0)) {
                f1 = ldg_relaxed32(r1p); f2 = ldg_relaxed32(r2p); f3 = ldg_relaxed32(r3p);
                if (++gg > 16 * SPIN_LIMIT) { TIMEOUT(3, s); break; }
            }
            if (warp == 0) PROF(9);
            const float v = (__uint_as_float(own) + __uint_as_float(f2)) + (__uint_as_float(f1) + __uint_as_float(f3));
            const bool b8 = tc.w & 8, b16 = tc.w & 16;
            const float recv = __shfl_xor_sync(~0u, v, 8);
            const uint32_t word = b8 ? pack2(recv, v) : pack2(v, recv);
            const uint32_t oth = __shfl_xor_sync(~0u, word, 16);
            const uint32_t wl = b16 ? oth : word, wh = b16 ? word : oth;
            const uint32_t p0 = __shfl_xor_sync(~0u, wl, 2), p1 = __shfl_xor_sync(~0u, wh, 2);
            const uint4 item = t2 ? make_uint4(p0, p1, wl, wh) : make_uint4(wl, wh, p0, p1);
            st_async_v4(tc.y, item, tc.z);
            st_async_v4(tc.y ^ (8u << 24), item, tc.z ^ (8u << 24));
            if (tc.w == 0 && warp == 7) mbar_expect_tx(sb + RB_E, 8192);
            if (warp == 0) PROF(10);
            PROF(40 + warp);
        }
        bar_sync(NB_D, 384);
    }
}

__device__ __forceinline__ void rec_load_kv(uint32_t sb, int col0, int s, uint32_t slot_off, int t128) {
    const int row = t128 >> 2, c2 = (t128 & 3) * 2;
    const bf16* src = g_kv + ((size_t)(s * 32 + row) * (2 * HD_) + col0 + c2 * 8);
    const uint32_t d0 = sb + R_KX + slot_off + row * 128 + ((c2 ^ (row & 7)) << 4);
    cp_async16(d0, src);
    cp_async16(d0 ^ 16, src + 8);
    cp_async16(d0 + (R_VX - R_KX), src + HD_);
    cp_async16((d0 ^ 16) + (R_VX - R_KX), src + HD_ + 8);
}

__device__ __forceinline__ void rec_store_kvm(uint32_t sb, int col0, int s, int w, int lane) {
    const int tok = (w & 1) * 4 + (lane >> 3);
    const uint4 v = lds128(sb + R_KMS + (s & 1) * 2048 + (w >> 1) * 1024 + tok * 128 + (((lane & 7) ^ tok) << 4));
    *(uint4*)(g_kvm + ((s * 8 + tok) * (2 * HD_) + (w >> 1) * HD_ + col0 + (lane & 7) * 8)) = v;
}

__device__ __forceinline__ void rec_vo(const RecParams& p, const uint32_t sb, const int cta, const int warp, int lane) {
    const int w = warp - 8, crank = cta & 15;
    const int col0 = cta * 64;
    uint32_t wo[8][4][4];
    {
        const int t128 = w * 32 + lane;
        const bf16* Wo = p.wo + (size_t)col0 * D_;
        const uint32_t stg = sb + R_STG + 2 * 32768;
#pragma unroll
        for (int half = 0; half < 2; half++) {
#pragma unroll 4
            for (int i = t128; i < 2048; i += 128) {
                const int e = i >> 6, ch = i & 63;
                cp_async16(stg + e * 1024 + ((ch ^ (e & 7)) << 4), Wo + (size_t)(half * 32 + e) * D_ + ch * 8);
            }
            cp_async_commit();
            cp_async_wait<0>();
            bar_sync(NB_W0 + 2, 128);
#pragma unroll
            for (int j = 0; j < 8; j++)
#pragma unroll
                for (int kk = 0; kk < 2; kk++) {
                    const int e = kk * 16 + (lane >> 4) * 8 + (lane & 7);
                    const int ch = (w * 8 + j) * 2 + ((lane >> 3) & 1);
                    ldsm4t(wo[j][half * 2 + kk][0], wo[j][half * 2 + kk][1], wo[j][half * 2 + kk][2], wo[j][half * 2 + kk][3],
                           stg + e * 1024 + ((ch ^ (e & 7)) << 4));
                }
            bar_sync(NB_W0 + 2, 128);
        }
        if (lane == 0) wait_flag(F_KV + 0, 64);
        __syncwarp();
        rec_load_kv(sb, col0, 0, 0, t128); cp_async_commit();
        rec_load_kv(sb, col0, 1, 4096, t128); cp_async_commit();
        cp_async_wait<1>();
    }
    const uint32_t tab = sb + R_STG + 2 * 32768 + (w * 32 + lane) * 16;
    {
        const uint32_t l7 = lane & 7, l8 = lane >> 3, g = lane >> 2;
        uint4 v;
        v.x = sb + R_VX + ((l8 & 1) * 8 + l7) * 128 + (((2 * w + (l8 >> 1)) ^ l7) << 4);
        v.y = sb + R_OS + g * 128 + (((2 * w) ^ g) << 4) + (lane & 3) * 4;
        v.z = sb + R_VMS + l7 * 128 + (((2 * w + (l8 & 1)) ^ l7) << 4);
        v.w = sb + R_OS + l7 * 128 + ((l8 ^ l7) << 4);
        sts128(tab, v);
        v.x = mapa_u32(sb + R_RS + crank * 512 + ((lane ^ (crank & 7)) << 4), w * 4);
        v.y = mapa_u32(sb + RB_E, w * 4);
        v.z = sb + R_VP + w * 512 + lane * 16;
        v.w = sb + R_SX + lane * 8;
        sts128(tab + 2048, v);
#pragma unroll
        for (int i = 0; i < 8; i++) sts128(tab + 4096 + i * 2048, make_uint4(wo[i][0][0], wo[i][0][1], wo[i][0][2], wo[i][0][3]));
        const int tok = (w & 1) * 4 + (lane >> 3), row = (w * 32 + lane) >> 2, c2 = (lane & 3) * 2;
        const uint64_t kd = (uint64_t)(g_kvm + (tok * (2 * HD_) + (w >> 1) * HD_ + col0 + (lane & 7) * 8));
        const uint64_t ks = (uint64_t)(g_kv + ((size_t)row * (2 * HD_) + col0 + c2 * 8));
        sts128(tab + 20480, make_uint4((uint32_t)kd, (uint32_t)(kd >> 32), (uint32_t)ks, (uint32_t)(ks >> 32)));
        sts128(tab + 22528, make_uint4(sb + R_KMS + (w >> 1) * 1024 + tok * 128 + (((lane & 7) ^ tok) << 4),
                                       sb + R_KX + row * 128 + ((c2 ^ (row & 7)) << 4), lane, 0));
    }
    bar_sync(NB_D, 384);
    const uint32_t lane16 = lds32(tab + 2048 + 8) - R_VP - w * 512;
    uint4 av[2 * VK0];
#pragma unroll
    for (int i = 0; i < 2 * VK0; i++) av[i] = lds128(lane16 + R_WV + (i / VK0) * 32768 + (w * 16 + i % VK0) * 512);
    uint32_t slot_off = 0;
#pragma unroll 1
    for (int s = 0; s < NSEG; s++) {
        if (s > 0) {
            mbar_wait(sb + RB_A, (s - 1) & 1);
            const uint4 tp = lds128(tab + 20480), tq = lds128(tab + 22528);
            if ((s & 3) == 1 && s > 1 && w == 0 && tq.z == 0) red_release(&g_flags[F_MEM + (s >> 2) - 1], 1);
            const uint4 kvm = lds128(tq.x + ((s - 1) & 1) * 2048);
            *(uint4*)((((uint64_t)tp.y << 32) | tp.x) + (uint64_t)(s - 1) * (8 * 2 * HD_ * 2)) = kvm;
            if (s + 1 < NSEG - 1) {
                if (((s + 1) & 3) == 0) { if (tq.z == 0) wait_flag(F_KV + ((s + 1) >> 2), 64); __syncwarp(); }
                const char* src = (const char*)((((uint64_t)tp.w << 32) | tp.z) + (uint64_t)(s + 1) * (32 * 2 * HD_ * 2));
                const uint32_t d0 = tq.y + (slot_off == (R_NST - 1) * 4096 ? 0 : slot_off + 4096);
                cp_async16(d0, src);
                cp_async16(d0 ^ 16, src + 16);
                cp_async16(d0 + (R_VX - R_KX), src + HD_ * 2);
                cp_async16((d0 ^ 16) + (R_VX - R_KX), src + HD_ * 2 + 16);
            }
            cp_async_commit();
        }
        bar_sync(NB_Y, 288);
        uint32_t vb0, vb1;
        {
            float va[4] = {0.f, 0.f, 0.f, 0.f}, vc[4] = {0.f, 0.f, 0.f, 0.f};
            uint32_t bb[VK0][4];
#pragma unroll
            for (int k2 = 0; k2 < VK0; k2++) ldsm4(bb[k2][0], bb[k2][1], bb[k2][2], bb[k2][3], lane16 + R_MEM + (k2 / (VK0 / 2)) * 4096 + (k2 % (VK0 / 2)) * 512);
#pragma unroll
            for (int k2 = 0; k2 < VK0; k2++) {
                mma16816(va, av[2 * k2].x, av[2 * k2].y, av[2 * k2].z, av[2 * k2].w, bb[k2][0], bb[k2][1]);
                mma16816(vc, av[2 * k2 + 1].x, av[2 * k2 + 1].y, av[2 * k2 + 1].z, av[2 * k2 + 1].w, bb[k2][2], bb[k2][3]);
            }
            const uint4 a = lds128(lane16 + R_VP + w * 512), b = lds128(lane16 + R_VP + 2048 + w * 512);
            vb0 = pack2((va[0] + vc[0]) + (__uint_as_float(a.x) + __uint_as_float(b.x)), (va[1] + vc[1]) + (__uint_as_float(a.y) + __uint_as_float(b.y)));
            vb1 = pack2((va[2] + vc[2]) + (__uint_as_float(a.z) + __uint_as_float(b.z)), (va[3] + vc[3]) + (__uint_as_float(a.w) + __uint_as_float(b.w)));
        }
        const uint4 ta = lds128(tab), tb = lds128(tab + 2048);
        uint32_t vx[8];
        ldsm4t(vx[0], vx[1], vx[2], vx[3], ta.x + slot_off);
        ldsm4t(vx[4], vx[5], vx[6], vx[7], ta.x + slot_off + 2048);
#pragma unroll
        for (int i = 0; i < 4; i++) {
            const uint4 f0 = lds128(tab + 4096 + i * 2048);
            wo[i][0][0] = f0.x; wo[i][0][1] = f0.y; wo[i][0][2] = f0.z; wo[i][0][3] = f0.w;
        }
        if (w == 0) PROF(11);
        uint32_t pf[5];
        float oa[2][4] = {{0.f, 0.f, 0.f, 0.f}, {0.f, 0.f, 0.f, 0.f}}, ob_[2][4] = {{0.f, 0.f, 0.f, 0.f}, {0.f, 0.f, 0.f, 0.f}};
        float sm0[4] = {0.f, 0.f, 0.f, 0.f}, sm1[4] = {0.f, 0.f, 0.f, 0.f};
        if (s != NSEG - 1) {
            mbar_wait(sb + RB_SX, s & 1);
            if (w == 0) PROF(4);
            float sv[10];
#pragma unroll
            for (int n = 0; n < 5; n++) {
                const float2 a = lds64f(tb.w + n * 256), b = lds64f(tb.w + (5 + n) * 256);
                sv[2 * n] = a.x + b.x; sv[2 * n + 1] = a.y + b.y;
            }
            float mx = fmaxf(fmaxf(fmaxf(sv[0], sv[1]), fmaxf(sv[2], sv[3])), fmaxf(fmaxf(sv[4], sv[5]), fmaxf(sv[6], sv[7])));
            mx = fmaxf(mx, fmaxf(sv[8], sv[9]));
            mx = fmaxf(mx, __shfl_xor_sync(~0u, mx, 1));
            mx = fmaxf(mx, __shfl_xor_sync(~0u, mx, 2));
#pragma unroll
            for (int n = 1; n < 5; n++) pf[n] = pack2(ex2(sv[2 * n] - mx), ex2(sv[2 * n + 1] - mx));
            pf[0] = pack2(ex2(sv[0] - mx), ex2(sv[1] - mx));
            if (w == 0) PROF(12);
            const uint32_t one = 0x3F803F80u;
            mma16816h(sm0, pf[1], pf[2], one, one);
            mma16816h(oa[0], pf[1], pf[2], vx[0], vx[1]);
            mma16816h(oa[1], pf[1], pf[2], vx[2], vx[3]);
            mma16816h(sm1, pf[3], pf[4], one, one);
            mma16816h(ob_[0], pf[3], pf[4], vx[4], vx[5]);
            mma16816h(ob_[1], pf[3], pf[4], vx[6], vx[7]);
            mma1688h(sm0, pf[0], one);
            mma1688h(oa[0], pf[0], vb0);
            mma1688h(oa[1], pf[0], vb1);
            float inv;
            asm("rcp.approx.ftz.f32 %0, %1;" : "=f"(inv) : "f"(sm0[0] + sm1[0]));
            oa[0][0] += ob_[0][0]; oa[0][1] += ob_[0][1]; oa[1][0] += ob_[1][0]; oa[1][1] += ob_[1][1];
            sts32(ta.y, pack2(oa[0][0] * inv, oa[0][1] * inv));
            sts32(ta.y ^ 16, pack2(oa[1][0] * inv, oa[1][1] * inv));
            const uint32_t oa2 = ta.w ^ 64;
            bar_sync(NB_C, 128);
            if (w == 0) PROF(5);
            uint32_t ob[8];
            ldsm4(ob[0], ob[1], ob[2], ob[3], ta.w);
            ldsm4(ob[4], ob[5], ob[6], ob[7], oa2);
#pragma unroll
            for (int i = 4; i < 8; i++) {
                const uint4 f0 = lds128(tab + 4096 + i * 2048);
                wo[i][0][0] = f0.x; wo[i][0][1] = f0.y; wo[i][0][2] = f0.z; wo[i][0][3] = f0.w;
            }
#pragma unroll
            for (int jj = 0; jj < 2; jj++) {
                if (jj == 1 && tb.w == 0) break;
                float acc[4][4];
#pragma unroll
                for (int c = 0; c < 4; c++) { acc[c][0] = acc[c][1] = acc[c][2] = acc[c][3] = 0.f; }
#pragma unroll
                for (int ks = 0; ks < 4; ks++)
#pragma unroll
                    for (int c = 0; c < 4; c++)
                        mma16816(acc[c], wo[jj * 4 + c][ks][0], wo[jj * 4 + c][ks][1], wo[jj * 4 + c][ks][2], wo[jj * 4 + c][ks][3], ob[2 * ks], ob[2 * ks + 1]);
#pragma unroll
                for (int pr = 0; pr < 2; pr++) {
                    uint4 v;
                    v.x = pack2(acc[2 * pr][0], acc[2 * pr][1]);
                    v.y = pack2(acc[2 * pr][2], acc[2 * pr][3]);
                    v.z = pack2(acc[2 * pr + 1][0], acc[2 * pr + 1][1]);
                    v.w = pack2(acc[2 * pr + 1][2], acc[2 * pr + 1][3]);
                    st_async_v4(tb.x + ((jj * 2 + pr) << 24), v, tb.y + ((jj * 2 + pr) << 24));
                }
            }
            if (w == 0) PROF(6);
        }
        stsm2t(ta.z + (s & 1) * 2048, vb0, vb1);
        cp_async_wait<0>();
        bar_sync(NB_C, 128);
        if (w == 0 && lane == 0 && s != NSEG - 1) mbar_expect_tx(sb + RB_SX, 2560);
        if (s != NSEG - 1) bar_arrive(NB_D, 384);
#pragma unroll
        for (int i = 0; i < 2 * VK0; i++) av[i] = lds128(lane16 + R_WV + (i / VK0) * 32768 + (w * 16 + i % VK0) * 512);
        slot_off = slot_off == (R_NST - 1) * 4096 ? 0 : slot_off + 4096;
    }
    rec_store_kvm(sb, col0, NSEG - 1, w, lane);
    bar_sync(NB_C, 128);
    if (w == 0 && lane == 0) red_release(&g_flags[F_MEM + NRB - 1], 1);
}

__global__ void __launch_bounds__(384, 1) k_rec(const RecParams p) {
    extern __shared__ __align__(1024) unsigned char smem_raw[];
    const uint32_t sb = __shfl_sync(~0u, smem_u32(smem_raw), 0);
    const int warp = __shfl_sync(~0u, threadIdx.x >> 5, 0);
    int lane; asm volatile("mov.u32 %0, %%laneid;" : "=r"(lane));
    const int crank = blockIdx.x & 15, slot = blockIdx.x >> 4;
    asm volatile("griddepcontrol.launch_dependents;");
    if (threadIdx.x == 0) {
        mbar_init(sb + RB_SX, 1); mbar_init(sb + RB_E, 1); mbar_init(sb + RB_A, 1); mbar_init(sb + RB_A1, 1); mbar_init(sb + RB_ROLE, 1);
        asm volatile("fence.mbarrier_init.release.cluster;" ::: "memory");
        mbar_expect_tx(sb + RB_SX, 2560);
        mbar_expect_tx(sb + RB_E, 8192);
        mbar_expect_tx(sb + RB_A, 4096);
        mbar_expect_tx(sb + RB_A1, 4096);
        mbar_expect_tx(sb + RB_ROLE, 4);
    }
    unsigned role = 0;
    if (crank == 0 && threadIdx.x == 0) {
        unsigned x = 0;
        int tm[2] = {0x7fffffff, 0x7fffffff};
#pragma unroll 1
        for (int i = 0; i < 6; i++) {
            const uint32_t t0 = clk32();
            x = atomicAdd(&g_F[65536 + (i & 1) * 1024 + slot * 64 + (x >> 31)], 0u) & 0x7fffffffu;
            if (x == 0x7654321u) sts32(sb + R_BAR + 56, x);
            const int dt = (int)(clk32() - t0);
            if (i >= 2) { if (i & 1) tm[1] = min(tm[1], dt); else tm[0] = min(tm[0], dt); }
        }
        const int side = tm[1] > tm[0];
        const unsigned old = atomicAdd(&g_flags[F_SIDE + side * 32], 1u);
        unsigned c0, c1; int gd = 0;
#pragma unroll 1
        do { c0 = ldg_relaxed32(&g_flags[F_SIDE]); c1 = ldg_relaxed32(&g_flags[F_SIDE + 32]); } while ((int)(c0 + c1) < p.ncl && ++gd < 64 * SPIN_LIMIT);
        const int big = c1 > c0;
        role = side == big ? old : (big ? c1 : c0) + old;
        role |= (big ^ 1) << 8;
    }
    __syncwarp();
    asm volatile("barrier.cluster.arrive.relaxed.aligned;\nbarrier.cluster.wait.aligned;" ::: "memory");
    if (crank == 0 && warp == 0) {
        role = __shfl_sync(~0u, role, 0);
        if (lane < 16)
            asm volatile("st.async.weak.shared::cluster.mbarrier::complete_tx::bytes.u32 [%0], %1, [%2];"
                         :: "r"(mapa_u32(sb + R_BAR + 48, lane)), "r"(role), "r"(mapa_u32(sb + RB_ROLE, lane)) : "memory");
    }
    mbar_wait(sb + RB_ROLE, 0);
    const int rolew = __shfl_sync(~0u, lds32(sb + R_BAR + 48), 0);
    const int cl = rolew & 255;
    if (cl >= 4) return;
    const int cta = cl * 16 + crank;
    if (warp < 8) rec_qk(p, sb, cta, warp, lane, rolew >> 8);
    else rec_vo(p, sb, cta, warp, lane);
}

enum { J_KV = 0, J_QA = 1, J_O = 2, J_LN = 3, J_UP = 4, J_DN = 5, J_LN1 = 6, J_MOD = 7, J_UP2 = 8, J_END = 9 };
constexpr int NJ_O = 2 * OSPLIT, NJ_O2 = 2 * OSPLIT2, NJ_LN = 8, NJ_LN2 = 16, NJ_UP = 14, NJ_UP2 = 28, NJ_DN = 8, NJ_LN1 = 8;
__device__ __forceinline__ int nj_of(int q, int rb) {
    const bool f = rb >= FINE_RB;
    return q == J_KV ? 32 : (q == J_QA ? 16 : (q == J_O ? (f ? NJ_O2 : NJ_O) : (q == J_LN ? (f ? NJ_LN2 : NJ_LN) : (q == J_UP ? (f ? NJ_UP2 : NJ_UP) :
           (q == J_MOD ? (rb < 3 ? 16 : 0) : 8)))));
}
__device__ __forceinline__ int pick_job(int lane, int qmask, int& idx) {
    const int rb = lane & 15, half = lane >> 4;
    int gd = 0;
#pragma unroll 1
    while (true) {
        unsigned cl[4], dp[4];
#pragma unroll
        for (int i = 0; i < 4; i++) {
            const int q = half + 2 * i;
            cl[i] = ldg_relaxed32(&g_flags[F_CLAIM + q * 32 + rb]);
            dp[i] = ldg_relaxed32(&g_flags[q * 32 + (q == J_QA ? max(rb - 1, 0) : (q == J_LN1 ? 0 : rb))]);
        }
        unsigned r16[8], h16[8];
#pragma unroll
        for (int i = 0; i < 4; i++) {
            const int q = half + 2 * i;
            const bool have = ((qmask >> q) & 1) && (int)cl[i] < nj_of(q, rb);
            const unsigned tgt = q == J_QA ? 64 : (q == J_KV ? 2 * NJ_LN1 : (q == J_LN1 ? 32 : 2 * nj_of(q - 1, rb)));
            const bool ready = have && (q == J_MOD || (q == J_QA && rb == 0) || dp[i] >= tgt);
            const unsigned mh = __ballot_sync(~0u, have), mr = __ballot_sync(~0u, ready);
            r16[2 * i] = mr & 0xffffu; r16[2 * i + 1] = mr >> 16; h16[2 * i] = mh & 0xffffu; h16[2 * i + 1] = mh >> 16;
        }
        if (h16[J_KV] | h16[J_LN1]) r16[J_QA] = 0;
        int pq = -1;
        unsigned pm = 0;
        if (r16[J_MOD]) { pq = J_MOD; pm = r16[J_MOD]; }
        else if (h16[J_LN1] & 1) { pq = J_LN1; pm = 1; }
        else if (h16[J_KV] & 1) { pq = J_KV; pm = 1; }
        else if (r16[J_LN1]) { pq = J_LN1; pm = r16[J_LN1]; }
        else if (r16[J_KV]) { pq = J_KV; pm = r16[J_KV]; }
        else if (r16[J_QA] >> FINE_RB) { pq = J_QA; pm = r16[J_QA]; }
        else if (r16[J_DN]) { pq = J_DN; pm = r16[J_DN]; }
        else if (r16[J_UP]) { pq = J_UP; pm = r16[J_UP]; }
        else if (r16[J_LN]) { pq = J_LN; pm = r16[J_LN]; }
        else if (r16[J_O]) { pq = J_O; pm = r16[J_O]; }
        else if (r16[J_QA]) { pq = J_QA; pm = r16[J_QA]; }
        else if ((h16[J_MOD] | h16[J_KV] | h16[J_LN1] | h16[J_QA]) == 0) {
            unsigned prev = 0;
#pragma unroll
            for (int q = J_O; q <= J_DN; q++) {
                const int b = __ffs(h16[q]) - 1;
                if (pq < 0 && b >= FINE_RB && (prev & ((2u << b) - 1)) == 0) { pq = q; pm = h16[q]; }
                prev |= h16[q];
            }
            if (prev == 0) return J_END;
        }
        if (pq >= 0) {
            const int prb = __ffs(pm) - 1;
            int c = 0;
            if (lane == 0) c = (int)atomicAdd(&g_flags[F_CLAIM + pq * 32 + prb], 1u);
            c = __shfl_sync(~0u, c, 0);
            if (c < nj_of(pq, prb)) {
                idx = pq * 512 + prb * 32 + c;
                return (pq == J_UP && prb >= FINE_RB ? J_UP2 : pq) | (prb << 8) | (c << 16);
            }
        } else {
            __nanosleep(150);
            if (++gd > 16 * SPIN_LIMIT) { TIMEOUT(5, 0); return J_END; }
        }
    }
}
__device__ __forceinline__ int op_row(int rb, int split) {
    return rb < FINE_RB ? split * S_ + rb * 128 : OSPLIT * S_ + (split * (NRB - FINE_RB) + rb - FINE_RB) * 128;
}

struct Pipe { uint32_t stage, phase; };
__device__ __forceinline__ void pipe_next(Pipe& p) { if (++p.stage == W_NST) { p.stage = 0; p.phase ^= 1; } }

__device__ __forceinline__ void scheduler(const Params& p, uint32_t sb, int lane) {
    const uint32_t bars = sb + SM_BAR;
    uint32_t ph = 0;
#pragma unroll 1
    while (true) {
        mbar_wait(bars + B_REQ, ph);
        int j = 4095;
        const int jd = pick_job(lane, p.qmask, j);
        if (lane == 0) { sts32(bars + B_NEXT, (uint32_t)jd); sts32(bars + B_NEXT + 4, (uint32_t)j); mbar_arrive(bars + B_RSP); }
        ph ^= 1;
        if (jd == J_END) break;
        __syncwarp();
    }
}

__device__ __forceinline__ void producer(const Params& p, uint32_t sb) {
    Pipe pp{0, 1};
    const uint32_t bars = sb + SM_BAR;
    uint32_t seq = 0, h_seen = 0;
    mbar_arrive(bars + B_REQ);
#pragma unroll 1
    while (true) {
        mbar_wait(bars + B_RSP, seq & 1);
        const int jd = (int)lds32(bars + B_NEXT), j = (int)lds32(bars + B_NEXT + 4);
        int left = (jd & 255) == J_DN ? 15 : ((jd & 255) == J_QA ? 12 : ((jd & 255) == J_O ? (((jd >> 8) & 255) >= FINE_RB ? 64 / OSPLIT2 : 64 / OSPLIT) : ((jd & 255) == J_LN || (jd & 255) == J_LN1 || (jd & 255) == J_MOD ? 1 : 8)));
        left = max(left - PICK_AHEAD, 1);
        TR(j, 1);
        const int type = jd & 255, rb = (jd >> 8) & 255, cb = jd >> 16;
        const bool fine = rb >= FINE_RB;
        bool first = true;
        auto begin_stage = [&](uint32_t bytes) -> uint32_t {
            mbar_wait(bars + B_EMPTY + pp.stage * 8, pp.phase);
            if (first) { sts32(bars + B_RING + (seq & 7) * 4, (uint32_t)jd); sts32(bars + B_RING + 32 + (seq & 7) * 4, (uint32_t)j); first = false; }
            const uint32_t fb = bars + B_FULL + pp.stage * 8;
            if (bytes) mbar_expect_tx(fb, bytes); else mbar_arrive(fb);
            if (--left == 0 && type != J_END) mbar_arrive(bars + B_REQ);
            return fb;
        };
        if (type == J_END || type == J_LN || type == J_LN1 || type == J_MOD) {
            if (type == J_LN) { wait_flag(F_OP + rb, 2 * (fine ? NJ_O2 : NJ_O)); wait_flag(F_MOD + 1, 32); wait_flag(F_MOD + 2, 32); }

            TR(j, 2);
            begin_stage(0); pipe_next(pp);
            seq++;
            if (type == J_END) break;
            continue;
        }
        const CUtensorMap *ta, *tb0, *tb1;
        int k0 = 0, nk = 8, n0 = cb * 256, n1 = n0 + 128, nb = 4, dep = -1;
        unsigned tgt = 0;
        switch (type) {
            case J_KV: ta = &p.tm_h; tb0 = tb1 = cb < 16 ? &p.tm_wk : &p.tm_wv; n0 = (cb & 15) * 256; n1 = n0 + 128; dep = F_H + rb; tgt = 2 * NJ_LN1; break;
            case J_QA: ta = &p.tm_h; tb0 = tb1 = &p.tm_wq; dep = F_H + rb; tgt = 2 * NJ_LN1; break;
            case J_O: ta = &p.tm_o; tb0 = tb1 = &p.tm_wo; n0 = (cb & 1) * 256; n1 = n0 + 128; nk = fine ? 64 / OSPLIT2 : 64 / OSPLIT; k0 = (cb >> 1) * nk * 64;
                      dep = F_O + rb; tgt = 32; break;
            case J_UP: ta = &p.tm_h2; tb0 = &p.tm_wg; tb1 = &p.tm_wu; n0 = n1 = cb * 128; dep = F_H2 + rb; tgt = 2 * NJ_LN; break;
            case J_UP2: ta = &p.tm_h2; tb0 = &p.tm_wg; tb1 = &p.tm_wu; n0 = n1 = cb * 64; nb = 2; dep = F_H2 + rb; tgt = 2 * NJ_LN2; break;
            default: ta = &p.tm_act; tb0 = tb1 = &p.tm_wd; n0 = cb * 64; nk = 0; break;
        }
        const int m0 = rb * 128;
        if (type == J_DN) {
#pragma unroll 1
            for (int kb = 0; kb < 14; kb++) {
                const uint32_t fb = begin_stage(49152);
                const uint32_t st = sb + pp.stage * W_STAGE;
                const int k = kb * 128;
                tma_load2d(st + 32768, tb0, n0, k, fb);
                tma_load2d(st + 40960, tb0, n0, k + 64, fb);
                if (kb == 0) { wait_flag(F_ACT + rb, 2 * (fine ? NJ_UP2 : NJ_UP)); asm volatile("fence.proxy.async.global;" ::: "memory"); TR(j, 2); }
                tma_load2d(st, ta, k, m0, fb);
                tma_load2d(st + 8192, ta, k, m0 + 64, fb);
                tma_load2d(st + 16384, ta, k + 64, m0, fb);
                tma_load2d(st + 24576, ta, k + 64, m0 + 64, fb);
                pipe_next(pp);
            }
        }
#pragma unroll 1
        for (int kb = 0; kb < nk; kb++) {
            const uint32_t fb = begin_stage(16384 + nb * 8192);
            const uint32_t st = sb + pp.stage * W_STAGE;
            const int k = k0 + kb * 64;
            tma_load2d(st + 16384, tb0, n0, k, fb);
            if (nb == 4) {
                tma_load2d(st + 16384 + 8192, tb0, n0 + 64, k, fb);
                tma_load2d(st + 16384 + 16384, tb1, n1, k, fb);
                tma_load2d(st + 16384 + 24576, tb1, n1 + 64, k, fb);
            } else if (nb == 2) {
                tma_load2d(st + 16384 + 8192, tb1, n1, k, fb);
            }
            if (kb == 0) {
                if (dep >= 0 && !(dep < 32 && ((h_seen >> dep) & 1))) {
                    wait_flag(dep, tgt);
                    if (type != J_O) asm volatile("fence.proxy.async.global;" ::: "memory");
                    if (dep < 32) h_seen |= 1u << dep;
                }
                TR(j, 2);
            }
            tma_load2d(st, ta, k, m0, fb);
            tma_load2d(st + 8192, ta, k, m0 + 64, fb);
            pipe_next(pp);
        }
        if (type == J_QA) {
            wait_flag(F_KV + rb, 64);
#pragma unroll 1
            for (int i = 0; i < 4; i++) {
                const uint32_t fb = begin_stage(40960);
                const uint32_t st = sb + pp.stage * W_STAGE;
                const int col = (i & 1) * HD_ + (cb * 2 + (i >> 1)) * DH_;
                tma_load2d(st, &p.tm_kv, col, m0, fb);
                tma_load2d(st + 8192, &p.tm_kv, col, m0 + 64, fb);
                tma_load2d(st + 16384, &p.tm_kv, col + 64, m0, fb);
                tma_load2d(st + 24576, &p.tm_kv, col + 64, m0 + 64, fb);
                if (i == 0) { wait_flag(F_MEM + rb, 64); asm volatile("fence.proxy.async.global;" ::: "memory"); }
                tma_load2d(st + 32768, &p.tm_kvm, col, rb * 32, fb);
                tma_load2d(st + 36864, &p.tm_kvm, col + 64, rb * 32, fb);
                pipe_next(pp);
            }
        } else if (type == J_DN) {
            const uint32_t fb = begin_stage(16384);
            const uint32_t st = sb + pp.stage * W_STAGE;
            tma_load2d(st, &p.tm_x1, n0, m0, fb);
            tma_load2d(st + 8192, &p.tm_x1, n0, m0 + 64, fb);
            pipe_next(pp);
        }
        seq++;
    }
}

__device__ __forceinline__ void store_warp(const Params& p, uint32_t sb, int wg, int lane) {
    const uint32_t bars = sb + SM_BAR;
    uint32_t seq = 0;
#pragma unroll 1
    while (true) {
        bar_sync(NB_ST + wg, 160);
        const uint32_t jd = lds32(bars + B_RING + (seq & 7) * 4);
        seq++;
        const int type = jd & 255, rb = (jd >> 8) & 255, cb = jd >> 16;
        if (type == J_END) break;
        if (lane == 0) {
            const uint32_t src = sb + W_STG + wg * 32768;
            const CUtensorMap* tm = nullptr; int n0 = cb * 256, nbox = 4, mrow = rb * 128 + wg * 64, flag = 0;
            switch (type) {
                case J_KV: tm = &p.tm_kv; flag = F_KV + rb; break;
                case J_QA: tm = &p.tm_o; flag = F_O + rb; break;
                case J_O: tm = &p.tm_op; n0 = (cb & 1) * 256; mrow = op_row(rb, cb >> 1) + wg * 64; flag = F_OP + rb; break;
                case J_LN: flag = F_H2 + rb; nbox = 0; break;
                case J_LN1: flag = F_H + rb; nbox = 0; break;
                case J_MOD: flag = F_MOD + rb; nbox = 0; break;
                case J_UP: tm = &p.tm_act; n0 = cb * 128; nbox = 2; flag = F_ACT + rb; break;
                case J_UP2: tm = &p.tm_act; n0 = cb * 64; nbox = 1; flag = F_ACT + rb; break;
                default: tm = &p.tm_out; n0 = cb * 64; nbox = 1; flag = -1; break;
            }
#pragma unroll 1
            for (int b = 0; b < nbox; b++) tma_store2d(tm, src + b * 8192, n0 + b * 64, mrow);
            bulk_commit();
            bulk_wait0();
            mbar_arrive(bars + B_STGFREE + wg * 8);
            if (flag >= 0) red_release(&g_flags[flag], 1);
        }
        __syncwarp();
    }
}

__device__ __forceinline__ float gelu_tanh(float x) {
    const float t = x * fmaf(-0.10294324397f, x * x, -2.30220819814f);
    float r; asm("rcp.approx.ftz.f32 %0, %1;" : "=f"(r) : "f"(1.f + ex2(t)));
    return x * r;
}

#define CTR(i) do {} while (0)

template <int NSPLIT>
__device__ __forceinline__ void ln2_row(const Params& p, int rb, int r, int lane) {
    const int row = rb * 128 + r;
    uint4 u[2 * NSPLIT];
#pragma unroll
    for (int sp = 0; sp < NSPLIT; sp++) {
        const uint4* src = (const uint4*)(g_op + (size_t)(op_row(rb, sp) + r) * D_);
        u[2 * sp] = __ldcg(src + lane); u[2 * sp + 1] = __ldcg(src + 32 + lane);
    }
    const uint4* xr = (const uint4*)(p.x + (size_t)row * D_);
    const uint4 xa = __ldg(xr + lane), xb = __ldg(xr + 32 + lane);
    uint32_t ga[8], c1[8], sm[8];
    load_mod8(g_mod + 2 * D_, lane, ga);
    load_mod8(g_mod + 4 * D_, lane, c1);
    load_mod8(g_mod + 3 * D_, lane, sm);
    float a[16];
#pragma unroll
    for (int i = 0; i < 16; i++) a[i] = 0.f;
#pragma unroll
    for (int sp = 0; sp < 2 * NSPLIT; sp++) {
        float* q = a + (sp & 1) * 8;
        q[0] += bflo(u[sp].x); q[1] += bfhi(u[sp].x); q[2] += bflo(u[sp].y); q[3] += bfhi(u[sp].y);
        q[4] += bflo(u[sp].z); q[5] += bfhi(u[sp].z); q[6] += bflo(u[sp].w); q[7] += bfhi(u[sp].w);
    }
    const uint32_t xv[8] = {xa.x, xa.y, xa.z, xa.w, xb.x, xb.y, xb.z, xb.w};
    uint32_t v[8], r8[8];
#pragma unroll
    for (int i = 0; i < 8; i++) v[i] = hadd2(xv[i], hmul2(ga[i], pack2(a[2 * i], a[2 * i + 1])));
    uint4* x1r = (uint4*)(g_x1 + (size_t)row * D_);
    x1r[lane] = make_uint4(v[0], v[1], v[2], v[3]); x1r[32 + lane] = make_uint4(v[4], v[5], v[6], v[7]);
    uint32_t mu2; float rden;
    ln_stats(v, mu2, rden);
#pragma unroll
    for (int i = 0; i < 8; i++) c1[i] = hadd2(c1[i], 0x3F803F80u);
    ln_apply(v, mu2, rden, c1, sm, r8);
    uint4* hr = (uint4*)(g_h2 + (size_t)row * D_);
    hr[lane] = make_uint4(r8[0], r8[1], r8[2], r8[3]); hr[32 + lane] = make_uint4(r8[4], r8[5], r8[6], r8[7]);
}

__device__ __forceinline__ void consumer(const Params& p, uint32_t sb, int warp, int lane) {
    const uint32_t bars = sb + SM_BAR;
    const int wg = warp >> 2, wl = warp & 3;
    const uint32_t l7 = lane & 7, l8 = lane >> 3, g = lane >> 2, t = lane & 3;
    Pipe pp{0, 0};
    uint32_t seq = 0, stg_phase = 1;
    const int srow = wl * 16 + l7 + (l8 & 1) * 8;
    const uint32_t stg_base = sb + W_STG + wg * 32768 + srow * 128;
    const uint32_t sx = ((lane >> 4) ^ (srow & 7)) << 4;
#pragma unroll 1
    while (true) {
        mbar_wait(bars + B_FULL + pp.stage * 8, pp.phase);
        const uint32_t jd = lds32(bars + B_RING + (seq & 7) * 4);
        CTR(3);
        seq++;
        const int type = jd & 255, rb = (jd >> 8) & 255, cb = jd >> 16;
        if (type == J_END) { mbar_wait(bars + B_STGFREE + wg * 8, stg_phase); bar_arrive(NB_ST + wg, 160); break; }
        if (type == J_MOD) {
            __syncwarp();
            if (lane == 0) mbar_arrive(bars + B_EMPTY + pp.stage * 8);
            pipe_next(pp);
            const int rg = warp * 4 + l8, col = rb * 1024 + cb * 64;
            uint4 wv[16];
#pragma unroll
            for (int i = 0; i < 16; i++) wv[i] = __ldg((const uint4*)(p.w_mod + (size_t)(rg * 16 + i) * (6 * D_) + col + l7 * 8));
            const uint32_t cw = __ldg((const uint32_t*)(p.c + rg * 16) + l7);
            const float cl = bflo(cw), ch = bfhi(cw);
            const uint32_t sw = pack2(__fdividef(cl, 1.f + __expf(-cl)), __fdividef(ch, 1.f + __expf(-ch)));
            float a[8];
#pragma unroll
            for (int i = 0; i < 8; i++) a[i] = 0.f;
#pragma unroll
            for (int i = 0; i < 16; i++) {
                const uint32_t sv = __shfl_sync(~0u, sw, (lane & 24) + (i >> 1));
                const float cv = (i & 1) ? bfhi(sv) : bflo(sv);
                a[0] = fmaf(cv, bflo(wv[i].x), a[0]); a[1] = fmaf(cv, bfhi(wv[i].x), a[1]); a[2] = fmaf(cv, bflo(wv[i].y), a[2]); a[3] = fmaf(cv, bfhi(wv[i].y), a[3]);
                a[4] = fmaf(cv, bflo(wv[i].z), a[4]); a[5] = fmaf(cv, bfhi(wv[i].z), a[5]); a[6] = fmaf(cv, bflo(wv[i].w), a[6]); a[7] = fmaf(cv, bfhi(wv[i].w), a[7]);
            }
#pragma unroll
            for (int i = 0; i < 8; i++) { a[i] += __shfl_xor_sync(~0u, a[i], 8); a[i] += __shfl_xor_sync(~0u, a[i], 16); }
            const uint32_t red = sb + SM_BAR + 1024;
            bar_sync(NB_M, 256);
            if (lane < 8) {
                sts128(red + warp * 256 + lane * 32, make_uint4(__float_as_uint(a[0]), __float_as_uint(a[1]), __float_as_uint(a[2]), __float_as_uint(a[3])));
                sts128(red + warp * 256 + lane * 32 + 16, make_uint4(__float_as_uint(a[4]), __float_as_uint(a[5]), __float_as_uint(a[6]), __float_as_uint(a[7])));
            }
            bar_sync(NB_M, 256);
            if (wl == 0) {
                const uint32_t ra = red + (wg * 32 + lane) * 4;
                float v = 0.f;
#pragma unroll
                for (int i = 0; i < 8; i++) v += lds32f(ra + i * 256);
                g_mod[col + wg * 32 + lane] = __float2bfloat16_rn(v);
            }
            mbar_wait(bars + B_STGFREE + wg * 8, stg_phase); stg_phase ^= 1;
            CTR(4); CTR(5);
            bar_arrive(NB_ST + wg, 160);
            continue;
        }
        if (type == J_LN || type == J_LN1) {
            __syncwarp();
            if (lane == 0) mbar_arrive(bars + B_EMPTY + pp.stage * 8);
            pipe_next(pp);
            if (type == J_LN1) {
                const int row = rb * 128 + cb * 16 + warp * 2;
                const uint4* xr = (const uint4*)(p.x + (size_t)row * D_);
                const uint4 xa[4] = {__ldg(xr + lane), __ldg(xr + 32 + lane), __ldg(xr + 64 + lane), __ldg(xr + 96 + lane)};
                uint32_t c1[8], sm[8], mu2[2];
                float rden[2];
#pragma unroll
                for (int rr = 0; rr < 2; rr++) {
                    const uint32_t v[8] = {xa[2 * rr].x, xa[2 * rr].y, xa[2 * rr].z, xa[2 * rr].w, xa[2 * rr + 1].x, xa[2 * rr + 1].y, xa[2 * rr + 1].z, xa[2 * rr + 1].w};
                    ln_stats(v, mu2[rr], rden[rr]);
                }
                if (lane == 0) wait_flag(F_MOD, 32);
                __syncwarp();
                load_mod8(g_mod + D_, lane, c1);
                load_mod8(g_mod, lane, sm);
#pragma unroll
                for (int i = 0; i < 8; i++) c1[i] = hadd2(c1[i], 0x3F803F80u);
#pragma unroll
                for (int rr = 0; rr < 2; rr++) {
                    const uint32_t v[8] = {xa[2 * rr].x, xa[2 * rr].y, xa[2 * rr].z, xa[2 * rr].w, xa[2 * rr + 1].x, xa[2 * rr + 1].y, xa[2 * rr + 1].z, xa[2 * rr + 1].w};
                    uint32_t r[8];
                    ln_apply(v, mu2[rr], rden[rr], c1, sm, r);
                    uint4* hr = (uint4*)(g_h + (size_t)(row + rr) * D_);
                    hr[lane] = make_uint4(r[0], r[1], r[2], r[3]); hr[32 + lane] = make_uint4(r[4], r[5], r[6], r[7]);
                }
            } else if (rb >= FINE_RB) ln2_row<OSPLIT2>(p, rb, cb * 8 + warp, lane);
            else {
#pragma unroll 1
                for (int rr = 0; rr < 2; rr++) ln2_row<OSPLIT>(p, rb, cb * 16 + warp * 2 + rr, lane);
            }
            mbar_wait(bars + B_STGFREE + wg * 8, stg_phase); stg_phase ^= 1;
            CTR(4); CTR(5);
            bar_arrive(NB_ST + wg, 160);
            continue;
        }
        if (type == J_DN || type == J_UP2) {
            float acc[64];
#pragma unroll
            for (int i = 0; i < 64; i++) acc[i] = 0.f;
            if (type == J_DN) {
#pragma unroll 1
                for (int kb = 0; kb < 14; kb++) {
                    if (kb) mbar_wait(bars + B_FULL + pp.stage * 8, pp.phase);
                    const uint32_t st = sb + pp.stage * W_STAGE;
                    const uint64_t da = mkdesc(st + wg * 8192, 16, 1024), db = mkdesc(st + 32768, 8192, 1024);
                    wg_fence();
#pragma unroll
                    for (int ks = 0; ks < 8; ks++) wgmma_n64(acc, da + (ks >> 2) * 1024 + (ks & 3) * 2, db + ks * 128);
                    wg_commit();
                    wg_wait0();
                    if (lane == 0) mbar_arrive(bars + B_EMPTY + pp.stage * 8);
                    pipe_next(pp);
                }
            } else {
#pragma unroll 1
                for (int kb = 0; kb < 8; kb++) {
                    if (kb) mbar_wait(bars + B_FULL + pp.stage * 8, pp.phase);
                    const uint32_t st = sb + pp.stage * W_STAGE;
                    const uint64_t da = mkdesc(st + wg * 8192, 16, 1024), db = mkdesc(st + 16384, 8192, 1024);
                    wg_fence();
#pragma unroll
                    for (int ks = 0; ks < 4; ks++) wgmma_n128(acc, da + ks * 2, db + ks * 128, 1);
                    wg_commit();
                    wg_wait0();
                    if (lane == 0) mbar_arrive(bars + B_EMPTY + pp.stage * 8);
                    pipe_next(pp);
                }
            }
            CTR(4);
            if (type == J_UP2) {
                mbar_wait(bars + B_STGFREE + wg * 8, stg_phase); stg_phase ^= 1;
#pragma unroll
                for (int j = 0; j < 4; j++) {
                    uint32_t r[4];
#pragma unroll
                    for (int q = 0; q < 4; q++) {
                        const uint32_t gw = pack2(acc[8 * j + 2 * q], acc[8 * j + 2 * q + 1]);
                        const uint32_t uw = pack2(acc[32 + 8 * j + 2 * q], acc[32 + 8 * j + 2 * q + 1]);
                        r[q] = hmul2(pack2(gelu_tanh(bflo(gw)), gelu_tanh(bfhi(gw))), uw);
                    }
                    stsm4(stg_base + (sx ^ (j << 5)), r[0], r[1], r[2], r[3]);
                }
            } else {
                mbar_wait(bars + B_FULL + pp.stage * 8, pp.phase);
                const uint32_t st = sb + pp.stage * W_STAGE;
                mbar_wait(bars + B_STGFREE + wg * 8, stg_phase); stg_phase ^= 1;
                const uint32_t* gb = (const uint32_t*)(g_mod + 5 * D_ + cb * 64) + t;
                const uint32_t xa = st + wg * 8192 + (wl * 16 + g) * 128 + (g << 4) + t * 4;
#pragma unroll
                for (int j = 0; j < 4; j++) {
                    uint32_t r[4];
#pragma unroll
                    for (int q = 0; q < 4; q++) {
                        const int nt = 2 * j + (q >> 1);
                        const uint32_t xw = lds32((xa ^ ((nt & 7) << 4)) + (nt >> 3) * 16384 + (q & 1) * 1024);
                        r[q] = hadd2(xw, hmul2(__ldcg(gb + nt * 4), pack2(acc[8 * j + 2 * q], acc[8 * j + 2 * q + 1])));
                    }
                    stsm4(stg_base + (j >> 2) * 8192 + (sx ^ ((2 * j & 7) << 4)), r[0], r[1], r[2], r[3]);
                }
                __syncwarp();
                if (lane == 0) mbar_arrive(bars + B_EMPTY + pp.stage * 8);
                pipe_next(pp);
            }
            fence_async_smem();
            CTR(5);
            bar_arrive(NB_ST + wg, 160);
            continue;
        }
        float acc[128];
#pragma unroll
        for (int i = 0; i < 128; i++) acc[i] = 0.f;
        const int nk = type == J_O ? (rb >= FINE_RB ? 64 / OSPLIT2 : 64 / OSPLIT) : 8;
#pragma unroll 1
        for (int kb = 0; kb < nk; kb++) {
            if (kb) mbar_wait(bars + B_FULL + pp.stage * 8, pp.phase);
            const uint32_t st = sb + pp.stage * W_STAGE;
            const uint64_t da = mkdesc(st + wg * 8192, 16, 1024), db = mkdesc(st + 16384, 8192, 1024);
            wg_fence();
#pragma unroll
            for (int ks = 0; ks < 4; ks++) wgmma_n256(acc, da + ks * 2, db + ks * 128, 1);
            wg_commit();
            wg_wait0();
            if (lane == 0) mbar_arrive(bars + B_EMPTY + pp.stage * 8);
            pipe_next(pp);
        }
        CTR(4);
        if (type == J_QA) {
            uint32_t qf[64];
#pragma unroll
            for (int i = 0; i < 64; i++) qf[i] = pack2(acc[2 * i], acc[2 * i + 1]);
            const int sg = warp >> 1, half = warp & 1;
            const float sc = 0.08838834764831845f * 1.4426950408889634f;
            const uint32_t xoff = (sg >> 1) * 8192 + ((sg & 1) * 32 + l7) * 128;
            const uint32_t moff = 32768 + (sg * 8 + l7) * 128;
            const uint32_t kch = (l8 ^ l7) << 4;
            const uint32_t vch = ((l8 & 1) ^ l7) << 4;
            mbar_wait(bars + B_STGFREE + wg * 8, stg_phase); stg_phase ^= 1;
#pragma unroll 1
            for (int hh = 0; hh < 2; hh++) {
                mbar_wait(bars + B_FULL + pp.stage * 8, pp.phase);
                uint32_t st = sb + pp.stage * W_STAGE;
                float sa[5][4];
#pragma unroll
                for (int n = 0; n < 5; n++) sa[n][0] = sa[n][1] = sa[n][2] = sa[n][3] = 0.f;
#pragma unroll
                for (int i = 0; i < 4; i++) {
                    const uint32_t* q = qf + i * 8;
                    uint32_t kk[5][4];
                    ldsm4(kk[0][0], kk[0][1], kk[0][2], kk[0][3], st + moff + (i >> 1) * 4096 + (kch ^ ((i & 1) * 64)));
#pragma unroll
                    for (int n = 1; n < 5; n++)
                        ldsm4(kk[n][0], kk[n][1], kk[n][2], kk[n][3], st + xoff + (n - 1) * 1024 + (i >> 1) * 16384 + (kch ^ ((i & 1) * 64)));
#pragma unroll
                    for (int n = 0; n < 5; n++) mma16816(sa[n], q[0], q[1], q[2], q[3], kk[n][0], kk[n][1]);
#pragma unroll
                    for (int n = 0; n < 5; n++) mma16816(sa[n], q[4], q[5], q[6], q[7], kk[n][2], kk[n][3]);
                }
                __syncwarp();
                if (lane == 0) mbar_arrive(bars + B_EMPTY + pp.stage * 8);
                pipe_next(pp);
                const int iq0 = half * 16 + g - 2 * t, iq1 = iq0 + 8;
                float m0 = fmaxf(sa[0][0], sa[0][1]), m1 = fmaxf(sa[0][2], sa[0][3]);
#pragma unroll
                for (int n = 1; n < 5; n++) {
#pragma unroll
                    for (int e = 0; e < 2; e++) {
                        const int jx = (n - 1) * 8 + e;
                        if (jx > iq0) sa[n][e] = -3.0e38f;
                        if (jx > iq1) sa[n][2 + e] = -3.0e38f;
                        m0 = fmaxf(m0, sa[n][e]); m1 = fmaxf(m1, sa[n][2 + e]);
                    }
                }
                m0 = fmaxf(m0, __shfl_xor_sync(~0u, m0, 1)); m1 = fmaxf(m1, __shfl_xor_sync(~0u, m1, 1));
                m0 = fmaxf(m0, __shfl_xor_sync(~0u, m0, 2)); m1 = fmaxf(m1, __shfl_xor_sync(~0u, m1, 2));
                m0 *= -sc; m1 *= -sc;
                float l0 = 0.f, l1 = 0.f;
                uint32_t p0[5], p1[5];
#pragma unroll
                for (int n = 0; n < 5; n++) {
                    const float e0 = ex2(fmaf(sa[n][0], sc, m0)), e1 = ex2(fmaf(sa[n][1], sc, m0));
                    const float e2 = ex2(fmaf(sa[n][2], sc, m1)), e3 = ex2(fmaf(sa[n][3], sc, m1));
                    l0 += e0 + e1; l1 += e2 + e3;
                    p0[n] = pack2(e0, e1); p1[n] = pack2(e2, e3);
                }
                l0 += __shfl_xor_sync(~0u, l0, 1); l1 += __shfl_xor_sync(~0u, l1, 1);
                l0 += __shfl_xor_sync(~0u, l0, 2); l1 += __shfl_xor_sync(~0u, l1, 2);
                const float i0 = __fdividef(1.f, l0), i1 = __fdividef(1.f, l1);
                mbar_wait(bars + B_FULL + pp.stage * 8, pp.phase);
                st = sb + pp.stage * W_STAGE;
#pragma unroll
                for (int i = 0; i < 32; i++) qf[i] = qf[32 + i];
#pragma unroll 1
                for (int bx = 0; bx < 2; bx++) {
                    float o[8][4];
                    uint32_t vm[8], v0[4][4], v1[4][4];
#pragma unroll
                    for (int ep = 0; ep < 4; ep++) {
                        ldsm2t(vm[2 * ep], vm[2 * ep + 1], st + moff + bx * 4096 + (vch ^ (ep << 5)));
                        const uint32_t va = st + xoff + (l8 >> 1) * 1024 + bx * 16384 + (vch ^ (ep << 5));
                        ldsm4t(v0[ep][0], v0[ep][1], v0[ep][2], v0[ep][3], va);
                        ldsm4t(v1[ep][0], v1[ep][1], v1[ep][2], v1[ep][3], va + 2048);
                    }
#pragma unroll
                    for (int n = 0; n < 8; n++) { o[n][0] = o[n][1] = o[n][2] = o[n][3] = 0.f; mma16816(o[n], p0[0], p1[0], p0[1], p1[1], vm[n], v0[n >> 1][n & 1]); }
#pragma unroll
                    for (int n = 0; n < 8; n++) mma16816(o[n], p0[2], p1[2], p0[3], p1[3], v0[n >> 1][2 + (n & 1)], v1[n >> 1][n & 1]);
#pragma unroll
                    for (int n = 0; n < 8; n++) mma1688(o[n], p0[4], p1[4], v1[n >> 1][2 + (n & 1)]);
#pragma unroll
                    for (int ep = 0; ep < 4; ep++)
                        stsm4(stg_base + (hh * 2 + bx) * 8192 + (sx ^ (ep << 5)),
                              pack2(o[2 * ep][0] * i0, o[2 * ep][1] * i0), pack2(o[2 * ep][2] * i1, o[2 * ep][3] * i1),
                              pack2(o[2 * ep + 1][0] * i0, o[2 * ep + 1][1] * i0), pack2(o[2 * ep + 1][2] * i1, o[2 * ep + 1][3] * i1));
                }
                __syncwarp();
                if (lane == 0) mbar_arrive(bars + B_EMPTY + pp.stage * 8);
                pipe_next(pp);
            }
        } else if (type == J_UP) {
            mbar_wait(bars + B_STGFREE + wg * 8, stg_phase); stg_phase ^= 1;
#pragma unroll
            for (int j = 0; j < 8; j++) {
                uint32_t r[4];
#pragma unroll
                for (int q = 0; q < 4; q++) {
                    const uint32_t gw = pack2(acc[8 * j + 2 * q], acc[8 * j + 2 * q + 1]);
                    const uint32_t uw = pack2(acc[64 + 8 * j + 2 * q], acc[64 + 8 * j + 2 * q + 1]);
                    r[q] = hmul2(pack2(gelu_tanh(bflo(gw)), gelu_tanh(bfhi(gw))), uw);
                }
                stsm4(stg_base + (j >> 2) * 8192 + (sx ^ ((2 * j & 7) << 4)), r[0], r[1], r[2], r[3]);
            }
        } else {
            mbar_wait(bars + B_STGFREE + wg * 8, stg_phase); stg_phase ^= 1;
#pragma unroll
            for (int j = 0; j < 16; j++)
                stsm4(stg_base + (j >> 2) * 8192 + (sx ^ ((2 * j & 7) << 4)),
                      pack2(acc[8 * j], acc[8 * j + 1]), pack2(acc[8 * j + 2], acc[8 * j + 3]),
                      pack2(acc[8 * j + 4], acc[8 * j + 5]), pack2(acc[8 * j + 6], acc[8 * j + 7]));
        }
        fence_async_smem();
        CTR(5);
        bar_arrive(NB_ST + wg, 160);
    }
}

__global__ void __launch_bounds__(384, 1) k_work(const __grid_constant__ Params p) {
    extern __shared__ __align__(1024) unsigned char smem_raw[];
    const uint32_t sb = smem_u32(smem_raw);
    if (sb & 1023) __trap();
    const int warp = __shfl_sync(~0u, threadIdx.x >> 5, 0);
    int lane; asm volatile("mov.u32 %0, %%laneid;" : "=r"(lane));
    if (threadIdx.x == 0) {
        const uint32_t bars = sb + SM_BAR;
        for (int i = 0; i < W_NST; i++) { mbar_init(bars + B_FULL + i * 8, 1); mbar_init(bars + B_EMPTY + i * 8, 8); }
        mbar_init(bars + B_STGFREE, 1); mbar_init(bars + B_STGFREE + 8, 1); mbar_init(bars + B_REQ, 1); mbar_init(bars + B_RSP, 1);
        asm volatile("fence.mbarrier_init.release.cluster;" ::: "memory");
    }
    __syncthreads();
    if (warp < 8) {
        asm volatile("setmaxnreg.inc.sync.aligned.u32 232;");
        consumer(p, sb, warp, lane);
    } else {
        asm volatile("setmaxnreg.dec.sync.aligned.u32 40;");
        if (warp == 8) { if (lane == 0) producer(p, sb); }
        else if (warp < 11) store_warp(p, sb, warp - 9, lane);
        else scheduler(p, sb, lane);
        __syncwarp();
        bar_sync(NB_W0, 128);
        if (warp == 8 && p.qmask == 0xff) {
            unsigned last = 0;
            if (lane == 0) { __threadfence(); last = atomicAdd(&g_flags[F_DONE], 1u) == gridDim.x - 1; }
            if (__shfl_sync(~0u, last, 0))
                for (int i = lane; i < F_TOTAL; i += 32) g_flags[i] = 0;
        }
    }
}

typedef CUresult (*EncodeFn)(CUtensorMap*, CUtensorMapDataType, cuuint32_t, void*, const cuuint64_t*, const cuuint64_t*,
                             const cuuint32_t*, const cuuint32_t*, CUtensorMapInterleave, CUtensorMapSwizzle,
                             CUtensorMapL2promotion, CUtensorMapFloatOOBfill);

static void make_map(EncodeFn enc, CUtensorMap* m, const void* ptr, uint64_t rows, uint64_t cols, uint32_t box_rows) {
    cuuint64_t dims[2] = {cols, rows};
    cuuint64_t strides[1] = {cols * 2};
    cuuint32_t box[2] = {64, box_rows};
    cuuint32_t es[2] = {1, 1};
    enc(m, CU_TENSOR_MAP_DATA_TYPE_BFLOAT16, 2, const_cast<void*>(ptr), dims, strides, box, es, CU_TENSOR_MAP_INTERLEAVE_NONE,
        CU_TENSOR_MAP_SWIZZLE_128B, CU_TENSOR_MAP_L2_PROMOTION_L2_256B, CU_TENSOR_MAP_FLOAT_OOB_FILL_NONE);
}
template <typename T> static void* sym_addr(T& sym) { void* p = nullptr; cudaGetSymbolAddress(&p, sym); return p; }

extern "C" void kernel_launch(void* const* d_in, const int* in_sizes, int n_in, void* d_out, int out_size) {
    static Params prm;
    static RecParams rp;
    static bool ready = false;
    static const void* key[14];
    bool same = ready;
    for (int i = 0; i < 13 && same; i++) same = key[i] == d_in[i];
    same = same && key[13] == d_out;
    if (!same) {
        void* fn = nullptr;
        cudaDriverEntryPointQueryResult qr;
        cudaGetDriverEntryPoint("cuTensorMapEncodeTiled", &fn, cudaEnableDefault, &qr);
        EncodeFn enc = (EncodeFn)fn;
        make_map(enc, &prm.tm_h, sym_addr(g_h), S_, D_, 64);
        make_map(enc, &prm.tm_kv, sym_addr(g_kv), S_, 2 * HD_, 64);
        make_map(enc, &prm.tm_kvm, sym_addr(g_kvm), NSEG * 8, 2 * HD_, 32);
        make_map(enc, &prm.tm_o, sym_addr(g_o), S_, HD_, 64);
        make_map(enc, &prm.tm_op, sym_addr(g_op), OP_ROWS, D_, 64);
        make_map(enc, &prm.tm_h2, sym_addr(g_h2), S_, D_, 64);
        make_map(enc, &prm.tm_act, sym_addr(g_act), S_, DF_, 64);
        make_map(enc, &prm.tm_x1, sym_addr(g_x1), S_, D_, 64);
        make_map(enc, &prm.tm_out, d_out, S_, D_, 64);
        make_map(enc, &prm.tm_wq, d_in[2], D_, HD_, 64);
        make_map(enc, &prm.tm_wk, d_in[3], D_, HD_, 64);
        make_map(enc, &prm.tm_wv, d_in[4], D_, HD_, 64);
        make_map(enc, &prm.tm_wo, d_in[5], HD_, D_, 64);
        make_map(enc, &prm.tm_wg, d_in[8], D_, DF_, 64);
        make_map(enc, &prm.tm_wu, d_in[9], D_, DF_, 64);
        make_map(enc, &prm.tm_wd, d_in[10], DF_, D_, 64);
        prm.x = (const bf16*)d_in[0]; prm.c = (const bf16*)d_in[11]; prm.w_mod = (const bf16*)d_in[12];
        rp.mem0 = (const bf16*)d_in[1];
        rp.wq = (const bf16*)d_in[2]; rp.wk = (const bf16*)d_in[3]; rp.wv = (const bf16*)d_in[4]; rp.wo = (const bf16*)d_in[5];
        cudaFuncSetAttribute(k_work, cudaFuncAttributeMaxDynamicSharedMemorySize, SMEM_BYTES);
        cudaFuncSetAttribute(k_rec, cudaFuncAttributeMaxDynamicSharedMemorySize, R_SMEM);
        cudaFuncSetAttribute(k_rec, cudaFuncAttributeNonPortableClusterSizeAllowed, 1);
        {
            cudaLaunchConfig_t cfg = {};
            cfg.gridDim = dim3(128); cfg.blockDim = dim3(384); cfg.dynamicSmemBytes = R_SMEM;
            cudaLaunchAttribute at[1];
            at[0].id = cudaLaunchAttributeClusterDimension; at[0].val.clusterDim.x = 16; at[0].val.clusterDim.y = 1; at[0].val.clusterDim.z = 1;
            cfg.attrs = at; cfg.numAttrs = 1;
            int n = 0;
            cudaOccupancyMaxActiveClusters(&n, k_rec, &cfg);
            rp.ncl = n < 4 ? 4 : (n > 8 ? 8 : n);
        }
        for (int i = 0; i < 13; i++) key[i] = d_in[i];
        key[13] = d_out;
        ready = true;
    }
    cudaStream_t st = cudaStreamPerThread;
    auto launch_rec = [&]() {
        cudaLaunchConfig_t cfg = {};
        cfg.gridDim = dim3(16 * rp.ncl); cfg.blockDim = dim3(384); cfg.dynamicSmemBytes = R_SMEM; cfg.stream = st;
        cudaLaunchAttribute at[1];
        at[0].id = cudaLaunchAttributeClusterDimension; at[0].val.clusterDim.x = 16; at[0].val.clusterDim.y = 1; at[0].val.clusterDim.z = 1;
        cfg.attrs = at; cfg.numAttrs = 1;
        cudaLaunchKernelEx(&cfg, k_rec, rp);
    };
    auto launch_work = [&](int qmask, int pdl) {
        prm.qmask = qmask;
        cudaLaunchConfig_t cfg = {};
        cfg.gridDim = dim3(132); cfg.blockDim = dim3(384); cfg.dynamicSmemBytes = SMEM_BYTES; cfg.stream = st;
        cudaLaunchAttribute at[1];
        at[0].id = cudaLaunchAttributeProgrammaticStreamSerialization; at[0].val.programmaticStreamSerializationAllowed = 1;
        cfg.attrs = at; cfg.numAttrs = pdl;
        cudaLaunchKernelEx(&cfg, k_work, prm);
    };
    launch_rec();
    launch_work(0xff, 1);
}
```

```cpp
#include <cuda_runtime.h>
#include <cuda_bf16.h>
#include <cuda.h>
#include <stdint.h>

typedef __nv_bfloat16 bf16;

constexpr int S_ = 2048, D_ = 512, H_ = 32, DH_ = 128, HD_ = 4096, NSEG = 64, DF_ = 1792;
constexpr int NRB = 16;
constexpr int OSPLIT = 4;

__device__ __align__(1024) bf16 g_h[S_ * D_];
__device__ __align__(1024) bf16 g_kv[S_ * 2 * HD_];
__device__ __align__(1024) bf16 g_kvm[NSEG * 8 * 2 * HD_];
__device__ __align__(1024) bf16 g_o[S_ * HD_];
#define FINE_RB_ 14
constexpr int FINE_RB = FINE_RB_;
constexpr int OSPLIT2 = 8;
constexpr int OP_ROWS = OSPLIT * S_ + OSPLIT2 * (NRB - FINE_RB) * 128;
__device__ __align__(1024) bf16 g_op[OP_ROWS * D_];
__device__ __align__(1024) bf16 g_x1[S_ * D_];
__device__ __align__(1024) bf16 g_h2[S_ * D_];
__device__ __align__(1024) bf16 g_act[S_ * DF_];
__device__ __align__(1024) bf16 g_mod[6 * D_];
__device__ uint32_t g_Fraw[131072 + 65536 + 2048];
#define g_F ((uint32_t*)(((uint64_t)g_Fraw + 0x7FFFFull) & ~0x7FFFFull))
constexpr int F_H = 0, F_MEM = 32, F_O = 64, F_OP = 96, F_H2 = 128, F_ACT = 160, F_MOD = 192, F_KV = 224, F_CLAIM = 256  ,
              F_SIDE = 512  , F_DONE = 576, F_TOTAL = 608;
__device__ __align__(128) unsigned int g_flags[F_TOTAL];
#define TR(j, i) do {} while (0)

__device__ __forceinline__ uint32_t smem_u32(const void* p) { return (uint32_t)__cvta_generic_to_shared(p); }
__device__ __forceinline__ uint32_t clk32() { uint32_t c; asm volatile("mov.u32 %0, %%clock;" : "=r"(c)); return c; }
__device__ __forceinline__ uint32_t mapa_u32(uint32_t addr, uint32_t rank) {
    uint32_t r; asm volatile("mapa.shared::cluster.u32 %0, %1, %2;" : "=r"(r) : "r"(addr), "r"(rank)); return r;
}
__device__ __forceinline__ void mbar_init(uint32_t bar, uint32_t cnt) {
    asm volatile("mbarrier.init.shared::cta.b64 [%0], %1;" :: "r"(bar), "r"(cnt) : "memory");
}
__device__ __forceinline__ void mbar_inval(uint32_t bar) {
    asm volatile("mbarrier.inval.shared::cta.b64 [%0];" :: "r"(bar) : "memory");
}
__device__ __forceinline__ void mbar_expect_tx(uint32_t bar, uint32_t bytes) {
    asm volatile("mbarrier.arrive.expect_tx.shared::cta.b64 _, [%0], %1;" :: "r"(bar), "r"(bytes) : "memory");
}
__device__ __forceinline__ void mbar_arrive(uint32_t bar) {
    asm volatile("mbarrier.arrive.shared::cta.b64 _, [%0];" :: "r"(bar) : "memory");
}
__device__ __forceinline__ bool mbar_try_wait(uint32_t bar, uint32_t parity) {
    uint32_t ok;
    asm volatile("{\n.reg .pred p;\nmbarrier.try_wait.parity.shared::cta.b64 p, [%1], %2;\nselp.u32 %0, 1, 0, p;\n}"
                 : "=r"(ok) : "r"(bar), "r"(parity) : "memory");
    return ok;
}
__device__ __forceinline__ bool mbar_try_wait_cluster(uint32_t bar, uint32_t parity) {
    uint32_t ok;
    asm volatile("{\n.reg .pred p;\nmbarrier.try_wait.parity.acquire.cluster.shared::cta.b64 p, [%1], %2;\nselp.u32 %0, 1, 0, p;\n}"
                 : "=r"(ok) : "r"(bar), "r"(parity) : "memory");
    return ok;
}
constexpr int SPIN_LIMIT = 1 << 18;
#define TIMEOUT(code, info) do {} while (0)
__device__ __forceinline__ void mbar_wait(uint32_t bar, uint32_t parity) {
    int g = 0;
#pragma unroll 1
    while (!mbar_try_wait(bar, parity)) { if (++g >= SPIN_LIMIT) { TIMEOUT(0, bar & 255); break; } }
}
__device__ __forceinline__ void mbar_wait_cluster(uint32_t bar, uint32_t parity) {
    int g = 0;
#pragma unroll 1
    while (!mbar_try_wait_cluster(bar, parity)) { if (++g >= SPIN_LIMIT) { TIMEOUT(1, bar & 255); break; } }
}
__device__ __forceinline__ void bar_sync(int id, int n) { asm volatile("bar.sync %0, %1;" :: "r"(id), "r"(n) : "memory"); }
__device__ __forceinline__ void bar_arrive(int id, int n) { asm volatile("bar.arrive %0, %1;" :: "r"(id), "r"(n) : "memory"); }
__device__ __forceinline__ void cluster_sync_all() {
    asm volatile("barrier.cluster.arrive.aligned;\nbarrier.cluster.wait.aligned;" ::: "memory");
}
__device__ __forceinline__ void st_async_v2(uint32_t addr, float a, float b, uint32_t bar) {
    asm volatile("st.async.weak.shared::cluster.mbarrier::complete_tx::bytes.v2.f32 [%0], {%1,%2}, [%3];"
                 :: "r"(addr), "f"(a), "f"(b), "r"(bar) : "memory");
}
__device__ __forceinline__ void st_async_v4(uint32_t addr, uint4 v, uint32_t bar) {
    asm volatile("st.async.weak.shared::cluster.mbarrier::complete_tx::bytes.v4.b32 [%0], {%1,%2,%3,%4}, [%5];"
                 :: "r"(addr), "r"(v.x), "r"(v.y), "r"(v.z), "r"(v.w), "r"(bar) : "memory");
}
__device__ __forceinline__ uint2 ldg_relaxed2(const uint2* p) {
    uint2 v;
    asm volatile("ld.relaxed.gpu.global.v2.b32 {%0,%1}, [%2];" : "=r"(v.x), "=r"(v.y) : "l"(p) : "memory");
    return v;
}
__device__ __forceinline__ void stg_relaxed2(uint2* p, uint2 v) {
    asm volatile("st.relaxed.gpu.global.v2.b32 [%0], {%1,%2};" :: "l"(p), "r"(v.x), "r"(v.y) : "memory");
}
__device__ __forceinline__ uint4 ldg_relaxed(const uint4* p) {
    uint4 v;
    asm volatile("ld.relaxed.gpu.global.v4.b32 {%0,%1,%2,%3}, [%4];" : "=r"(v.x), "=r"(v.y), "=r"(v.z), "=r"(v.w) : "l"(p) : "memory");
    return v;
}
__device__ __forceinline__ void stg_relaxed(uint4* p, uint4 v) {
    asm volatile("st.relaxed.gpu.global.v4.b32 [%0], {%1,%2,%3,%4};" :: "l"(p), "r"(v.x), "r"(v.y), "r"(v.z), "r"(v.w) : "memory");
}
__device__ __forceinline__ void stg_relaxed32(uint32_t* p, uint32_t v) {
    asm volatile("st.relaxed.gpu.global.b32 [%0], %1;" :: "l"(p), "r"(v) : "memory");
}
__device__ __forceinline__ uint32_t ldg_relaxed32(const uint32_t* p) {
    uint32_t v; asm volatile("ld.relaxed.gpu.global.b32 %0, [%1];" : "=r"(v) : "l"(p) : "memory"); return v;
}
__device__ __forceinline__ unsigned int ld_acquire(const unsigned int* p) {
    unsigned int v; asm volatile("ld.acquire.gpu.global.u32 %0, [%1];" : "=r"(v) : "l"(p) : "memory"); return v;
}
__device__ __forceinline__ void red_release(unsigned int* p, unsigned int v) {
    asm volatile("red.release.gpu.global.add.u32 [%0], %1;" :: "l"(p), "r"(v) : "memory");
}
__device__ __forceinline__ void wait_flag(int idx, unsigned int target) {
    const unsigned int* p = &g_flags[idx];
    int g = 0;
#pragma unroll 1
    while (ld_acquire(p) < target) { __nanosleep(20); if (++g >= 64 * SPIN_LIMIT) { TIMEOUT(2, idx); break; } }
}
__device__ __forceinline__ void cp_async16(uint32_t dst, const void* src) {
    asm volatile("cp.async.cg.shared.global [%0], [%1], 16;" :: "r"(dst), "l"(src) : "memory");
}
__device__ __forceinline__ void cp_async_commit() { asm volatile("cp.async.commit_group;" ::: "memory"); }
template <int N> __device__ __forceinline__ void cp_async_wait() { asm volatile("cp.async.wait_group %0;" :: "n"(N) : "memory"); }
__device__ __forceinline__ void ldsm4(uint32_t& r0, uint32_t& r1, uint32_t& r2, uint32_t& r3, uint32_t addr) {
    asm volatile("ldmatrix.sync.aligned.m8n8.x4.shared.b16 {%0,%1,%2,%3}, [%4];" : "=r"(r0), "=r"(r1), "=r"(r2), "=r"(r3) : "r"(addr) : "memory");
}
__device__ __forceinline__ void ldsm4t(uint32_t& r0, uint32_t& r1, uint32_t& r2, uint32_t& r3, uint32_t addr) {
    asm volatile("ldmatrix.sync.aligned.m8n8.x4.trans.shared.b16 {%0,%1,%2,%3}, [%4];" : "=r"(r0), "=r"(r1), "=r"(r2), "=r"(r3) : "r"(addr) : "memory");
}
__device__ __forceinline__ void ldsm2t(uint32_t& r0, uint32_t& r1, uint32_t addr) {
    asm volatile("ldmatrix.sync.aligned.m8n8.x2.trans.shared.b16 {%0,%1}, [%2];" : "=r"(r0), "=r"(r1) : "r"(addr) : "memory");
}
__device__ __forceinline__ void stsm4(uint32_t addr, uint32_t r0, uint32_t r1, uint32_t r2, uint32_t r3) {
    asm volatile("stmatrix.sync.aligned.m8n8.x4.shared.b16 [%0], {%1,%2,%3,%4};" :: "r"(addr), "r"(r0), "r"(r1), "r"(r2), "r"(r3) : "memory");
}
__device__ __forceinline__ void stsm2t(uint32_t addr, uint32_t r0, uint32_t r1) {
    asm volatile("stmatrix.sync.aligned.m8n8.x2.trans.shared.b16 [%0], {%1,%2};" :: "r"(addr), "r"(r0), "r"(r1) : "memory");
}
__device__ __forceinline__ void mma16816(float* d, uint32_t a0, uint32_t a1, uint32_t a2, uint32_t a3, uint32_t b0, uint32_t b1) {
    asm volatile("mma.sync.aligned.m16n8k16.row.col.f32.bf16.bf16.f32 {%0,%1,%2,%3}, {%4,%5,%6,%7}, {%8,%9}, {%0,%1,%2,%3};"
                 : "+f"(d[0]), "+f"(d[1]), "+f"(d[2]), "+f"(d[3]) : "r"(a0), "r"(a1), "r"(a2), "r"(a3), "r"(b0), "r"(b1));
}
__device__ __forceinline__ void mma1688(float* d, uint32_t a0, uint32_t a1, uint32_t b0) {
    asm volatile("mma.sync.aligned.m16n8k8.row.col.f32.bf16.bf16.f32 {%0,%1,%2,%3}, {%4,%5}, {%6}, {%0,%1,%2,%3};"
                 : "+f"(d[0]), "+f"(d[1]), "+f"(d[2]), "+f"(d[3]) : "r"(a0), "r"(a1), "r"(b0));
}
__device__ __forceinline__ void mma16816h(float* d, uint32_t a0, uint32_t a2, uint32_t b0, uint32_t b1) {
    asm volatile("{\n.reg .b32 ju, jv;\nmma.sync.aligned.m16n8k16.row.col.f32.bf16.bf16.f32 {%0,%1,%2,%3}, {%4,ju,%5,jv}, {%6,%7}, {%0,%1,%2,%3};\n}"
                 : "+f"(d[0]), "+f"(d[1]), "+f"(d[2]), "+f"(d[3]) : "r"(a0), "r"(a2), "r"(b0), "r"(b1));
}
__device__ __forceinline__ void mma1688h(float* d, uint32_t a0, uint32_t b0) {
    asm volatile("{\n.reg .b32 ju;\nmma.sync.aligned.m16n8k8.row.col.f32.bf16.bf16.f32 {%0,%1,%2,%3}, {%4,ju}, {%5}, {%0,%1,%2,%3};\n}"
                 : "+f"(d[0]), "+f"(d[1]), "+f"(d[2]), "+f"(d[3]) : "r"(a0), "r"(b0));
}
__device__ __forceinline__ uint32_t pack2(float lo, float hi) {
    uint32_t r; asm("cvt.rn.bf16x2.f32 %0, %1, %2;" : "=r"(r) : "f"(hi), "f"(lo)); return r;
}
__device__ __forceinline__ float bflo(uint32_t w) { return __uint_as_float(w << 16); }
__device__ __forceinline__ float bfhi(uint32_t w) { return __uint_as_float(w & 0xffff0000u); }
__device__ __forceinline__ float rbf(float x) { return __bfloat162float(__float2bfloat16_rn(x)); }
__device__ __forceinline__ float ex2(float x) { float y; asm("ex2.approx.ftz.f32 %0, %1;" : "=f"(y) : "f"(x)); return y; }
__device__ __forceinline__ void sts128(uint32_t addr, uint4 v) {
    asm volatile("st.shared.v4.b32 [%0], {%1,%2,%3,%4};" :: "r"(addr), "r"(v.x), "r"(v.y), "r"(v.z), "r"(v.w) : "memory");
}
__device__ __forceinline__ uint4 lds128(uint32_t addr) {
    uint4 v; asm volatile("ld.shared.v4.b32 {%0,%1,%2,%3}, [%4];" : "=r"(v.x), "=r"(v.y), "=r"(v.z), "=r"(v.w) : "r"(addr) : "memory"); return v;
}
__device__ __forceinline__ float2 lds64f(uint32_t addr) {
    float2 v; asm volatile("ld.shared.v2.f32 {%0,%1}, [%2];" : "=f"(v.x), "=f"(v.y) : "r"(addr) : "memory"); return v;
}
__device__ __forceinline__ float lds32f(uint32_t addr) {
    float v; asm volatile("ld.shared.f32 %0, [%1];" : "=f"(v) : "r"(addr) : "memory"); return v;
}
__device__ __forceinline__ uint32_t lds32(uint32_t addr) {
    uint32_t v; asm volatile("ld.shared.b32 %0, [%1];" : "=r"(v) : "r"(addr) : "memory"); return v;
}
__device__ __forceinline__ void sts32(uint32_t addr, uint32_t v) { asm volatile("st.shared.b32 [%0], %1;" :: "r"(addr), "r"(v) : "memory"); }
__device__ __forceinline__ void sts64f(uint32_t addr, float a, float b) { asm volatile("st.shared.v2.f32 [%0], {%1,%2};" :: "r"(addr), "f"(a), "f"(b) : "memory"); }

__device__ __forceinline__ void tma_load2d(uint32_t dst, const CUtensorMap* tm, int c0, int c1, uint32_t bar) {
    asm volatile("cp.async.bulk.tensor.2d.shared::cluster.global.mbarrier::complete_tx::bytes [%0], [%1, {%3, %4}], [%2];"
                 :: "r"(dst), "l"(tm), "r"(bar), "r"(c0), "r"(c1) : "memory");
}
__device__ __forceinline__ void tma_store2d(const CUtensorMap* tm, uint32_t src, int c0, int c1) {
    asm volatile("cp.async.bulk.tensor.2d.global.shared::cta.bulk_group [%0, {%2, %3}], [%1];"
                 :: "l"(tm), "r"(src), "r"(c0), "r"(c1) : "memory");
}
__device__ __forceinline__ void bulk_commit() { asm volatile("cp.async.bulk.commit_group;" ::: "memory"); }
__device__ __forceinline__ void bulk_wait0() { asm volatile("cp.async.bulk.wait_group 0;" ::: "memory"); }
__device__ __forceinline__ void fence_async_smem() { asm volatile("fence.proxy.async.shared::cta;" ::: "memory"); }
__device__ __forceinline__ void fence_async_all() { asm volatile("fence.proxy.async;" ::: "memory"); }

__device__ __forceinline__ void wg_fence() { asm volatile("wgmma.fence.sync.aligned;" ::: "memory"); }
__device__ __forceinline__ void wg_commit() { asm volatile("wgmma.commit_group.sync.aligned;" ::: "memory"); }
__device__ __forceinline__ void wg_wait0() { asm volatile("wgmma.wait_group.sync.aligned 0;" ::: "memory"); }
__device__ __forceinline__ uint64_t mkdesc(uint32_t saddr, uint32_t lbo, uint32_t sbo) {
    return (uint64_t)((saddr & 0x3FFFF) >> 4) | ((uint64_t)(lbo >> 4) << 16) | ((uint64_t)(sbo >> 4) << 32) | (1ull << 62);
}
#define ACC8(i) "+f"(d[i]), "+f"(d[i + 1]), "+f"(d[i + 2]), "+f"(d[i + 3]), "+f"(d[i + 4]), "+f"(d[i + 5]), "+f"(d[i + 6]), "+f"(d[i + 7])
__device__ __forceinline__ void wgmma_n256(float* d, uint64_t da, uint64_t db, int scale_d) {
    asm volatile(
        "{\n.reg .pred p;\nsetp.ne.b32 p, %130, 0;\n"
        "wgmma.mma_async.sync.aligned.m64n256k16.f32.bf16.bf16 "
        "{%0,%1,%2,%3,%4,%5,%6,%7,%8,%9,%10,%11,%12,%13,%14,%15,%16,%17,%18,%19,%20,%21,%22,%23,%24,%25,%26,%27,%28,%29,%30,%31,"
        "%32,%33,%34,%35,%36,%37,%38,%39,%40,%41,%42,%43,%44,%45,%46,%47,%48,%49,%50,%51,%52,%53,%54,%55,%56,%57,%58,%59,%60,%61,%62,%63,"
        "%64,%65,%66,%67,%68,%69,%70,%71,%72,%73,%74,%75,%76,%77,%78,%79,%80,%81,%82,%83,%84,%85,%86,%87,%88,%89,%90,%91,%92,%93,%94,%95,"
        "%96,%97,%98,%99,%100,%101,%102,%103,%104,%105,%106,%107,%108,%109,%110,%111,%112,%113,%114,%115,%116,%117,%118,%119,%120,%121,%122,%123,%124,%125,%126,%127}, "
        "%128, %129, p, 1, 1, 0, 1;\n}"
        : ACC8(0), ACC8(8), ACC8(16), ACC8(24), ACC8(32), ACC8(40), ACC8(48), ACC8(56),
          ACC8(64), ACC8(72), ACC8(80), ACC8(88), ACC8(96), ACC8(104), ACC8(112), ACC8(120)
        : "l"(da), "l"(db), "r"(scale_d));
}
__device__ __forceinline__ void wgmma_n128(float* d, uint64_t da, uint64_t db, int scale_d) {
    asm volatile(
        "{\n.reg .pred p;\nsetp.ne.b32 p, %66, 0;\n"
        "wgmma.mma_async.sync.aligned.m64n128k16.f32.bf16.bf16 "
        "{%0,%1,%2,%3,%4,%5,%6,%7,%8,%9,%10,%11,%12,%13,%14,%15,%16,%17,%18,%19,%20,%21,%22,%23,%24,%25,%26,%27,%28,%29,%30,%31,"
        "%32,%33,%34,%35,%36,%37,%38,%39,%40,%41,%42,%43,%44,%45,%46,%47,%48,%49,%50,%51,%52,%53,%54,%55,%56,%57,%58,%59,%60,%61,%62,%63}, "
        "%64, %65, p, 1, 1, 0, 1;\n}"
        : ACC8(0), ACC8(8), ACC8(16), ACC8(24), ACC8(32), ACC8(40), ACC8(48), ACC8(56)
        : "l"(da), "l"(db), "r"(scale_d));
}

__device__ __forceinline__ void wgmma_n64(float* d, uint64_t da, uint64_t db) {
    asm volatile(
        "wgmma.mma_async.sync.aligned.m64n64k16.f32.bf16.bf16 "
        "{%0,%1,%2,%3,%4,%5,%6,%7,%8,%9,%10,%11,%12,%13,%14,%15,%16,%17,%18,%19,%20,%21,%22,%23,%24,%25,%26,%27,%28,%29,%30,%31}, "
        "%32, %33, 1, 1, 1, 0, 1;"
        : ACC8(0), ACC8(8), ACC8(16), ACC8(24)
        : "l"(da), "l"(db));
}
__device__ __forceinline__ void wgmma_n8_ta(float* d, uint64_t da, uint64_t db, int scale_d) {
    asm volatile(
        "{\n.reg .pred p;\nsetp.ne.b32 p, %6, 0;\n"
        "wgmma.mma_async.sync.aligned.m64n8k16.f32.bf16.bf16 {%0,%1,%2,%3}, %4, %5, p, 1, 1, 1, 0;\n}"
        : "+f"(d[0]), "+f"(d[1]), "+f"(d[2]), "+f"(d[3]) : "l"(da), "l"(db), "r"(scale_d));
}

__device__ __forceinline__ uint32_t hadd2(uint32_t a, uint32_t b) { uint32_t r; asm("add.rn.bf16x2 %0, %1, %2;" : "=r"(r) : "r"(a), "r"(b)); return r; }
__device__ __forceinline__ uint32_t hsub2(uint32_t a, uint32_t b) { uint32_t r; asm("sub.rn.bf16x2 %0, %1, %2;" : "=r"(r) : "r"(a), "r"(b)); return r; }
__device__ __forceinline__ uint32_t hmul2(uint32_t a, uint32_t b) { uint32_t r; asm("mul.rn.bf16x2 %0, %1, %2;" : "=r"(r) : "r"(a), "r"(b)); return r; }
__device__ __forceinline__ void load_mod8(const bf16* m, int lane, uint32_t* v) {
    const uint4 a = __ldcg((const uint4*)m + lane), b = __ldcg((const uint4*)m + 32 + lane);
    v[0] = a.x; v[1] = a.y; v[2] = a.z; v[3] = a.w; v[4] = b.x; v[5] = b.y; v[6] = b.z; v[7] = b.w;
}
__device__ __forceinline__ void ln_stats(const uint32_t* x, uint32_t& mu2, float& rden) {
    float s = 0.f;
#pragma unroll
    for (int i = 0; i < 8; i++) s += bflo(x[i]) + bfhi(x[i]);
#pragma unroll
    for (int o = 16; o > 0; o >>= 1) s += __shfl_xor_sync(~0u, s, o);
    const float mean = s * (1.f / D_);
    float q = 0.f;
#pragma unroll
    for (int i = 0; i < 8; i++) { const float d0 = bflo(x[i]) - mean, d1 = bfhi(x[i]) - mean; q = fmaf(d0, d0, q); q = fmaf(d1, d1, q); }
#pragma unroll
    for (int o = 16; o > 0; o >>= 1) q += __shfl_xor_sync(~0u, q, o);
    mu2 = pack2(mean, mean);
    rden = __frcp_rn(rbf(__fsqrt_rn(rbf(rbf(q * (1.f / D_)) + 1e-5f))));
}
__device__ __forceinline__ void ln_apply(const uint32_t* x, uint32_t mu2, float rden, const uint32_t* c1, const uint32_t* sm, uint32_t* r) {
#pragma unroll
    for (int i = 0; i < 8; i++) {
        const uint32_t d = hsub2(x[i], mu2);
        r[i] = hadd2(hmul2(pack2(bflo(d) * rden, bfhi(d) * rden), c1[i]), sm[i]);
    }
}

struct __align__(64) Params {
    CUtensorMap tm_h, tm_kv, tm_kvm, tm_o, tm_op, tm_h2, tm_act, tm_x1, tm_out;
    CUtensorMap tm_wq, tm_wk, tm_wv, tm_wo, tm_wg, tm_wu, tm_wd;
    const bf16 *x, *c, *w_mod;
    int qmask;
};

constexpr int R_NST = 3;
constexpr uint32_t R_WV = 0, R_MEM = 65536, R_KX = 73728, R_VX = R_KX + R_NST * 4096,
                   R_KMS = R_VX + R_NST * 4096  , R_VMS = R_KMS + 1024,
                   R_QS = R_KMS + 4096, R_OS = R_QS + 1024, R_SX = R_OS + 1024, R_BAR = R_SX + 2560,
                   R_RS = 107520  , R_VP = R_RS + 8192  ,
                   R_STG = R_VP + 8192  , R_SMEM = R_STG + 98304;
static_assert((R_KMS & 4095) == 0, "smem");
static_assert(R_BAR + 64 <= R_RS, "smem");
constexpr uint32_t RB_SX = R_BAR, RB_V = R_BAR + 8, RB_E = R_BAR + 16, RB_A = R_BAR + 24, RB_ROLE = R_BAR + 32, RB_A1 = R_BAR + 40;
constexpr int W_NST = 3;
constexpr uint32_t W_STAGE = 49152, W_STG = W_NST * W_STAGE, W_END = W_STG + 65536;
constexpr uint32_t SM_BAR = W_END;
constexpr uint32_t SMEM_BYTES = W_END + 1024 + 2048;
constexpr uint32_t B_FULL = 0, B_EMPTY = 32, B_STGFREE = 64, B_REQ = 80, B_RSP = 88, B_NEXT = 96, B_RING = 128;
#define PICK_AHEAD 3

constexpr int NB_X = 11  , NB_Y = 1, NB_M = 5, NB_B = 2, NB_C = 3, NB_D = 4, NB_W0 = 6  , NB_ST = 9  ;

__device__ __forceinline__ int pos_of_d(int d) {
    const int rem = d & 31;
    return (d & ~31) + ((rem & 7) >> 1) * 8 + (rem & 1) * 4 + (rem >> 3);
}

#define PROF(i) do {} while (0)
#define PROFG(i) do {} while (0)
#define OPAQUE(x) asm volatile("" : "+r"(x))
#define FENCE_SCHED(x) do { if ((x) == 0u) asm volatile("trap;"); } while (0)
#define VK0_ 4
constexpr int VK0 = VK0_;
constexpr int NOFF = 8;
#define VDELAY -1
#define POLL_GAP 110

struct RecParams { const bf16 *mem0, *wq, *wk, *wv, *wo; int ncl; };

__device__ __forceinline__ void rec_qk(const RecParams& p, const uint32_t sb, const int cta, const int warp, int lane, const int sel) {
    const int crank = cta & 15, cl = cta >> 4, rank = cta & 1;
    const int kh = warp >> 2, aa = warp & 3;
    uint32_t wa[2][16][4];
    const uint32_t stg = sb + R_STG + kh * 32768;
    {
        const int t128 = aa * 32 + lane;
        const int row = (lane >> 4) * 8 + (lane & 7);
        const int ch = t128 & 7;
        const size_t goff = (size_t)kh * 256 * HD_ + cta * 64 + ch * 8;
#pragma unroll 4
        for (int dd = 0; dd < 16; dd++) {
            const int d = dd * 16 + (t128 >> 3), pp = pos_of_d(d);
            cp_async16(sb + R_WV + kh * 32768 + pp * 128 + ((ch ^ (pp & 7)) << 4), p.wv + goff + (size_t)d * HD_);
        }
        cp_async_commit();
#pragma unroll 4
        for (int dd = 0; dd < 16; dd++) {
            const int d = dd * 16 + (t128 >> 3), pp = pos_of_d(d);
            cp_async16(stg + pp * 128 + ((ch ^ (pp & 7)) << 4), p.wq + goff + (size_t)d * HD_);
        }
        cp_async_commit();
        {
            const int i0 = (warp * 32 + lane) * 16, tok = i0 >> 9;
            const uint4 m0 = __ldg((const uint4*)(p.mem0 + i0)), m1 = __ldg((const uint4*)(p.mem0 + i0 + 8));
            const uint32_t mw[8] = {m0.x, m0.y, m0.z, m0.w, m1.x, m1.y, m1.z, m1.w};
#pragma unroll
            for (int e = 0; e < 16; e++) {
                const int pp = pos_of_d((i0 & 511) + e);
                const unsigned short v = (unsigned short)(mw[e >> 1] >> ((e & 1) * 16));
                asm volatile("st.shared.u16 [%0], %1;" :: "r"(sb + R_MEM + (pp >> 3) * 128 + tok * 16 + (pp & 7) * 2), "h"(v) : "memory");
            }
        }
        cp_async_wait<1>();
        bar_sync(NB_W0 + kh, 128);
        const uint32_t fv = row * 128 + (((2 * aa + ((lane >> 3) & 1)) ^ (row & 7)) << 4);
#pragma unroll
        for (int ks = 0; ks < 16; ks++) ldsm4t(wa[0][ks][0], wa[0][ks][1], wa[0][ks][2], wa[0][ks][3], sb + R_WV + kh * 32768 + fv + ks * 2048);
        bar_sync(NB_W0 + kh, 128);
#pragma unroll
        for (int ks = 0; ks < 16; ks++)
            sts128(sb + R_WV + kh * 32768 + (aa * 16 + ks) * 512 + lane * 16, make_uint4(wa[0][ks][0], wa[0][ks][1], wa[0][ks][2], wa[0][ks][3]));
        const uint32_t fo = stg + row * 128 + (((4 * (aa & 1) + ((lane >> 3) & 1)) ^ (row & 7)) << 4);
#pragma unroll 1
        for (int m = 0; m < 2; m++) {
            cp_async_wait<0>();
            bar_sync(NB_W0 + kh, 128);
            if ((aa >> 1) == m) {
#pragma unroll
                for (int ks = 0; ks < 16; ks++) {
                    ldsm4t(wa[0][ks][0], wa[0][ks][1], wa[0][ks][2], wa[0][ks][3], fo + ks * 2048);
                    ldsm4t(wa[1][ks][0], wa[1][ks][1], wa[1][ks][2], wa[1][ks][3], (fo ^ 32) + ks * 2048);
                }
            }
            bar_sync(NB_W0 + kh, 128);
            if (m == 0) {
#pragma unroll 4
                for (int dd = 0; dd < 16; dd++) {
                    const int d = dd * 16 + (t128 >> 3), pp = pos_of_d(d);
                    cp_async16(stg + pp * 128 + ((ch ^ (pp & 7)) << 4), p.wk + goff + (size_t)d * HD_);
                }
                cp_async_commit();
            }
        }
    }
    const uint32_t tab = stg + (aa * 32 + lane) * 16;
    {
        const uint32_t l7 = lane & 7, l8 = lane >> 3, g = lane >> 2, t = lane & 3;
        const uint32_t t0 = l7 * 128 + ((l8 ^ l7) << 4);
        const uint32_t tq = l7 * 128 + (((l8 >> 1) ^ l7) << 4);
        const uint32_t bq = warp >> 1, tp = warp & 1;
        uint4 v;
        v.x = sb + (aa < 2 ? R_QS : R_KMS) + l7 * 128 + (((4 * (aa & 1) + 2 * kh + (l8 & 1)) ^ l7) << 4);
        v.y = sb + R_QS + tq;
        v.z = sb + (warp == 0 ? R_KMS : R_KX + (warp - 1) * 1024) + t0;
        v.w = mapa_u32(sb + R_SX + (rank * 5 + warp) * 256 + lane * 8, crank ^ 1);
        sts128(tab, v);
        sts128(tab + 2048, make_uint4(sb + lane * 16 + R_MEM + kh * 4096, sb + lane * 16 + R_WV + warp * 8192,
                                      sb + lane * 16 + R_VP + warp * 512, sb + lane * 16 + R_VP + 4096 + (warp ^ 4) * 512));
        const uint32_t src = (l8 >> 1) * 8 + l7;
        const uint32_t L = bq * 8 + 2 * tp + (l8 & 1);
        const uint32_t d0 = (crank + ((t >> 1) | (g & 6))) & 15;
        v.x = sb + R_RS + src * 512 + ((L ^ (src & 7)) << 4);
        v.y = mapa_u32(sb + R_MEM + (crank * 4 + bq) * 128 + (4 * tp + 2 * (t & 1) + (g & 1)) * 16, d0);
        v.z = mapa_u32(sb + ((crank & 2) ? RB_A1 : RB_A), d0);
        v.w = lane;
        sts128(tab + 4096, v);
        const uint64_t wr = (uint64_t)(g_F + ((crank * 2 + ((crank ^ (crank >> 3) ^ sel) & 1)) * 1024 + warp * 128 + cl * 32 + lane));
        sts128(tab + 6144, make_uint4((uint32_t)wr, (uint32_t)(wr >> 32), (uint32_t)((((cl + 1) & 3) - cl) * 128), (uint32_t)((((cl + 2) & 3) - cl) * 128)));
        sts32(tab + 8192, (uint32_t)((((cl + 3) & 3) - cl) * 128));
#pragma unroll
        for (int i = 0; i < NOFF; i++)
            sts128(tab + 10240 + i * 2048, make_uint4(wa[i & 1][i >> 1][0], wa[i & 1][i >> 1][1], wa[i & 1][i >> 1][2], wa[i & 1][i >> 1][3]));
    }
    bar_sync(NB_D, 384);
    uint32_t slot_off = 0;
    const uint32_t slot_inc = warp == 0 ? 2048 : 4096, slot_last = warp == 0 ? 2048 : (R_NST - 1) * 4096;
    const uint32_t sx_bar_rem = (sb + RB_SX) ^ (1u << 24);
    uint4 tb = lds128(tab + 2048);
#pragma unroll 1
    for (int s = 0; s < NSEG; s++) {
        if (s > 0) mbar_wait(sb + RB_A, (s - 1) & 1);
        if (warp == 0) { PROF(0); PROFG(13); }
        uint4 ta;
        const uint32_t km_tog = aa >= 2 ? (s & 1) * 2048 : 0;
        {
            float acc[5][4];
#pragma unroll
            for (int c = 0; c < 5; c++) { acc[c][0] = acc[c][1] = acc[c][2] = acc[c][3] = 0.f; }
            uint32_t b[8][4];
            uint4 av[16];
            static_assert(VK0 == 4, "order below assumes the V/O warps cover slices 0,1");
            ldsm4(b[0][0], b[0][1], b[0][2], b[0][3], tb.x);
            ldsm4(b[1][0], b[1][1], b[1][2], b[1][3], tb.x + 512);
            ldsm4(b[4][0], b[4][1], b[4][2], b[4][3], tb.x + 2048);
            ldsm4(b[5][0], b[5][1], b[5][2], b[5][3], tb.x + 2560);
#pragma unroll
            for (int kk = 0; kk < 8; kk++) {
                const int k2 = kk < 2 ? kk : (kk < 4 ? kk + 2 : (kk < 6 ? kk - 2 : kk));
                if (kk == 4) {
                    if (s > 0) mbar_wait(sb + RB_A1, (s - 1) & 1);
                    ldsm4(b[2][0], b[2][1], b[2][2], b[2][3], tb.x + 1024);
                    ldsm4(b[3][0], b[3][1], b[3][2], b[3][3], tb.x + 1536);
                    ldsm4(b[6][0], b[6][1], b[6][2], b[6][3], tb.x + 3072);
                    ldsm4(b[7][0], b[7][1], b[7][2], b[7][3], tb.x + 3584);
#pragma unroll
                    for (int i = 12; i < 16; i++) av[i] = lds128(tb.y + i * 512);
                    ta = lds128(tab);
                }
                mma16816(acc[0], wa[0][2 * k2][0], wa[0][2 * k2][1], wa[0][2 * k2][2], wa[0][2 * k2][3], b[k2][0], b[k2][1]);
                mma16816(acc[1], wa[1][2 * k2][0], wa[1][2 * k2][1], wa[1][2 * k2][2], wa[1][2 * k2][3], b[k2][0], b[k2][1]);
                mma16816(acc[3], wa[0][2 * k2 + 1][0], wa[0][2 * k2 + 1][1], wa[0][2 * k2 + 1][2], wa[0][2 * k2 + 1][3], b[k2][2], b[k2][3]);
                mma16816(acc[4], wa[1][2 * k2 + 1][0], wa[1][2 * k2 + 1][1], wa[1][2 * k2 + 1][2], wa[1][2 * k2 + 1][3], b[k2][2], b[k2][3]);
                if (2 * k2 >= VK0) {
                    mma16816(acc[2], av[2 * k2].x, av[2 * k2].y, av[2 * k2].z, av[2 * k2].w, b[k2][0], b[k2][1]);
                    mma16816(acc[2], av[2 * k2 + 1].x, av[2 * k2 + 1].y, av[2 * k2 + 1].z, av[2 * k2 + 1].w, b[k2][2], b[k2][3]);
                }
                if (kk == 0) { av[8] = lds128(tb.y + 8 * 512); av[9] = lds128(tb.y + 9 * 512); }
                if (kk == 1) { av[10] = lds128(tb.y + 10 * 512); av[11] = lds128(tb.y + 11 * 512); }
                if (kk == 2) { av[4] = lds128(tb.y + 4 * 512); av[5] = lds128(tb.y + 5 * 512); }
                if (kk == 3) { av[6] = lds128(tb.y + 6 * 512); av[7] = lds128(tb.y + 7 * 512); }
            }
#pragma unroll
            for (int i = 0; i < 4; i++) { acc[0][i] += acc[3][i]; acc[1][i] += acc[4][i]; }
            const float g0 = kh ? acc[0][0] : acc[1][0], g1 = kh ? acc[0][1] : acc[1][1], g2 = kh ? acc[0][2] : acc[1][2], g3 = kh ? acc[0][3] : acc[1][3];
            sts128(tb.w, make_uint4(__float_as_uint(g0), __float_as_uint(g1), __float_as_uint(g2), __float_as_uint(g3)));
            const float k0 = kh ? acc[1][0] : acc[0][0], k1 = kh ? acc[1][1] : acc[0][1], k2_ = kh ? acc[1][2] : acc[0][2], k3 = kh ? acc[1][3] : acc[0][3];
            if (warp == 0) PROF(1);
            bar_sync(NB_X + aa, 64);
            const uint4 o = lds128(tb.z + 4096);
            stsm2t(ta.x ^ km_tog, pack2(k0 + __uint_as_float(o.x), k1 + __uint_as_float(o.y)), pack2(k2_ + __uint_as_float(o.z), k3 + __uint_as_float(o.w)));
            sts128(tb.z, make_uint4(__float_as_uint(acc[2][0]), __float_as_uint(acc[2][1]), __float_as_uint(acc[2][2]), __float_as_uint(acc[2][3])));
        }
        const uint32_t kb = ta.z + slot_off;
        if (warp == 0) PROF(14);
        bar_sync(NB_B, 256);
        if (warp < 5) {
            uint32_t q[16], k0, k1, k2, k3, k4, k5, k6, k7;
            float sa[4] = {0.f, 0.f, 0.f, 0.f}, sc[4] = {0.f, 0.f, 0.f, 0.f};
            ldsm4(q[0], q[1], q[2], q[3], ta.y);
            ldsm4(k0, k1, k2, k3, kb);
            ldsm4(q[4], q[5], q[6], q[7], ta.y ^ 32);
            ldsm4(q[8], q[9], q[10], q[11], ta.y ^ 64);
            ldsm4(k4, k5, k6, k7, kb ^ 64);
            ldsm4(q[12], q[13], q[14], q[15], ta.y ^ 96);
            mma16816(sa, q[0], q[1], q[2], q[3], k0, k1);
            bar_arrive(NB_Y, 288);
            mma16816(sc, q[4], q[5], q[6], q[7], k2, k3);
            mma16816(sa, q[8], q[9], q[10], q[11], k4, k5);
            mma16816(sc, q[12], q[13], q[14], q[15], k6, k7);
            const float scl = 0.08838834764831845f * 1.4426950408889634f;
            const float r0 = (sa[0] + sc[0]) * scl, r1 = (sa[1] + sc[1]) * scl;
            if (s != NSEG - 1) {
                st_async_v2(ta.w, r0, r1, sx_bar_rem);
                st_async_v2(ta.w ^ (1u << 24), r0, r1, sx_bar_rem ^ (1u << 24));
            }
            if (warp == 0) PROF(2);
        } else if (s > 0 && warp == 7 && lane == 0) {
            mbar_expect_tx(sb + RB_A, 4096);
            mbar_expect_tx(sb + RB_A1, 4096);
        }
        if (s == NSEG - 1) {
            const uint4 td = lds128(tab + 6144);
            stg_relaxed32((uint32_t*)(((uint64_t)td.y << 32) | (td.x ^ 0x21000)), 0u);
            break;
        }
        slot_off = slot_off == slot_last ? 0 : slot_off + slot_inc;
        const uint4 tc = lds128(tab + 4096), td = lds128(tab + 6144);
        const uint32_t te = lds32(tab + 8192);
        uint32_t* wr = (uint32_t*)(((uint64_t)td.y << 32) | (td.x ^ ((s & 1) * 0x21000)));
        const uint32_t* r1p = (const uint32_t*)((const char*)wr + (int)td.z);
        const uint32_t* r2p = (const uint32_t*)((const char*)wr + (int)td.w);
        const uint32_t* r3p = (const uint32_t*)((const char*)wr + (int)te);
        const uint32_t tag = ((s >> 1) + 1) & 1;
        mbar_wait(sb + RB_E, s & 1);
        if (warp == 0) PROF(7);
        {
            uint32_t a0, a1, a2, a3, a4, a5, a6, a7;
            ldsm4t(a0, a1, a2, a3, tc.x);
            ldsm4t(a4, a5, a6, a7, tc.x ^ 64);
            const uint32_t one = 0x3F803F80u;
            float d0_[4] = {0.f, 0.f, 0.f, 0.f}, d1_[4] = {0.f, 0.f, 0.f, 0.f};
            mma16816(d0_, a0, a1, a2, a3, one, one);
            mma16816(d1_, a4, a5, a6, a7, one, one);
            const bool t1 = tc.w & 1, t2 = tc.w & 2;
            const float x = t2 ? (t1 ? d1_[2] : d1_[0]) : (t1 ? d0_[2] : d0_[0]);
            const uint32_t own = (__float_as_uint(x) & ~1u) | tag;
            stg_relaxed32(wr, own);
            const uint32_t tq = clk32();
            if (warp == 0) PROF(8);
            PROFG(16 + warp);
            while ((int)(clk32() - tq) < POLL_GAP) {}
            uint32_t f1 = ldg_relaxed32(r1p), f2 = ldg_relaxed32(r2p), f3 = ldg_relaxed32(r3p);
#pragma unroll
            for (int i = 0; i < NOFF; i++) {
                const uint4 f0 = lds128(tab + 10240 + i * 2048);
                wa[i & 1][i >> 1][0] = f0.x; wa[i & 1][i >> 1][1] = f0.y; wa[i & 1][i >> 1][2] = f0.z; wa[i & 1][i >> 1][3] = f0.w;
            }
            tb = lds128(tab + 2048);
            int gg = 0;
#pragma unroll 1
            while (!__all_sync(~0u, (((f1 ^ tag) | (f2 ^ tag) | (f3 ^ tag)) & 1) == 0)) {
                f1 = ldg_relaxed32(r1p); f2 = ldg_relaxed32(r2p); f3 = ldg_relaxed32(r3p);
                if (++gg > 16 * SPIN_LIMIT) { TIMEOUT(3, s); break; }
            }
            if (warp == 0) PROF(9);
            const float v = (__uint_as_float(own) + __uint_as_float(f2)) + (__uint_as_float(f1) + __uint_as_float(f3));
            const bool b8 = tc.w & 8, b16 = tc.w & 16;
            const float recv = __shfl_xor_sync(~0u, v, 8);
            const uint32_t word = b8 ? pack2(recv, v) : pack2(v, recv);
            const uint32_t oth = __shfl_xor_sync(~0u, word, 16);
            const uint32_t wl = b16 ? oth : word, wh = b16 ? word : oth;
            const uint32_t p0 = __shfl_xor_sync(~0u, wl, 2), p1 = __shfl_xor_sync(~0u, wh, 2);
            const uint4 item = t2 ? make_uint4(p0, p1, wl, wh) : make_uint4(wl, wh, p0, p1);
            st_async_v4(tc.y, item, tc.z);
            st_async_v4(tc.y ^ (8u << 24), item, tc.z ^ (8u << 24));
            if (tc.w == 0 && warp == 7) mbar_expect_tx(sb + RB_E, 8192);
            if (warp == 0) PROF(10);
            PROF(40 + warp);
        }
        bar_sync(NB_D, 384);
    }
}

__device__ __forceinline__ void rec_load_kv(uint32_t sb, int col0, int s, uint32_t slot_off, int t128) {
    const int row = t128 >> 2, c2 = (t128 & 3) * 2;
    const bf16* src = g_kv + ((size_t)(s * 32 + row) * (2 * HD_) + col0 + c2 * 8);
    const uint32_t d0 = sb + R_KX + slot_off + row * 128 + ((c2 ^ (row & 7)) << 4);
    cp_async16(d0, src);
    cp_async16(d0 ^ 16, src + 8);
    cp_async16(d0 + (R_VX - R_KX), src + HD_);
    cp_async16((d0 ^ 16) + (R_VX - R_KX), src + HD_ + 8);
}

__device__ __forceinline__ void rec_store_kvm(uint32_t sb, int col0, int s, int w, int lane) {
    const int tok = (w & 1) * 4 + (lane >> 3);
    const uint4 v = lds128(sb + R_KMS + (s & 1) * 2048 + (w >> 1) * 1024 + tok * 128 + (((lane & 7) ^ tok) << 4));
    *(uint4*)(g_kvm + ((s * 8 + tok) * (2 * HD_) + (w >> 1) * HD_ + col0 + (lane & 7) * 8)) = v;
}

__device__ __forceinline__ void rec_vo(const RecParams& p, const uint32_t sb, const int cta, const int warp, int lane) {
    const int w = warp - 8, crank = cta & 15;
    const int col0 = cta * 64;
    uint32_t wo[8][4][4];
    {
        const int t128 = w * 32 + lane;
        const bf16* Wo = p.wo + (size_t)col0 * D_;
        const uint32_t stg = sb + R_STG + 2 * 32768;
#pragma unroll
        for (int half = 0; half < 2; half++) {
#pragma unroll 4
            for (int i = t128; i < 2048; i += 128) {
                const int e = i >> 6, ch = i & 63;
                cp_async16(stg + e * 1024 + ((ch ^ (e & 7)) << 4), Wo + (size_t)(half * 32 + e) * D_ + ch * 8);
            }
            cp_async_commit();
            cp_async_wait<0>();
            bar_sync(NB_W0 + 2, 128);
#pragma unroll
            for (int j = 0; j < 8; j++)
#pragma unroll
                for (int kk = 0; kk < 2; kk++) {
                    const int e = kk * 16 + (lane >> 4) * 8 + (lane & 7);
                    const int ch = (w * 8 + j) * 2 + ((lane >> 3) & 1);
                    ldsm4t(wo[j][half * 2 + kk][0], wo[j][half * 2 + kk][1], wo[j][half * 2 + kk][2], wo[j][half * 2 + kk][3],
                           stg + e * 1024 + ((ch ^ (e & 7)) << 4));
                }
            bar_sync(NB_W0 + 2, 128);
        }
        if (lane == 0) wait_flag(F_KV + 0, 64);
        __syncwarp();
        rec_load_kv(sb, col0, 0, 0, t128); cp_async_commit();
        rec_load_kv(sb, col0, 1, 4096, t128); cp_async_commit();
        cp_async_wait<1>();
    }
    const uint32_t tab = sb + R_STG + 2 * 32768 + (w * 32 + lane) * 16;
    {
        const uint32_t l7 = lane & 7, l8 = lane >> 3, g = lane >> 2;
        uint4 v;
        v.x = sb + R_VX + ((l8 & 1) * 8 + l7) * 128 + (((2 * w + (l8 >> 1)) ^ l7) << 4);
        v.y = sb + R_OS + g * 128 + (((2 * w) ^ g) << 4) + (lane & 3) * 4;
        v.z = sb + R_VMS + l7 * 128 + (((2 * w + (l8 & 1)) ^ l7) << 4);
        v.w = sb + R_OS + l7 * 128 + ((l8 ^ l7) << 4);
        sts128(tab, v);
        v.x = mapa_u32(sb + R_RS + crank * 512 + ((lane ^ (crank & 7)) << 4), w * 4);
        v.y = mapa_u32(sb + RB_E, w * 4);
        v.z = sb + R_VP + w * 512 + lane * 16;
        v.w = sb + R_SX + lane * 8;
        sts128(tab + 2048, v);
#pragma unroll
        for (int i = 0; i < 8; i++) sts128(tab + 4096 + i * 2048, make_uint4(wo[i][0][0], wo[i][0][1], wo[i][0][2], wo[i][0][3]));
        const int tok = (w & 1) * 4 + (lane >> 3), row = (w * 32 + lane) >> 2, c2 = (lane & 3) * 2;
        const uint64_t kd = (uint64_t)(g_kvm + (tok * (2 * HD_) + (w >> 1) * HD_ + col0 + (lane & 7) * 8));
        const uint64_t ks = (uint64_t)(g_kv + ((size_t)row * (2 * HD_) + col0 + c2 * 8));
        sts128(tab + 20480, make_uint4((uint32_t)kd, (uint32_t)(kd >> 32), (uint32_t)ks, (uint32_t)(ks >> 32)));
        sts128(tab + 22528, make_uint4(sb + R_KMS + (w >> 1) * 1024 + tok * 128 + (((lane & 7) ^ tok) << 4),
                                       sb + R_KX + row * 128 + ((c2 ^ (row & 7)) << 4), lane, 0));
    }
    bar_sync(NB_D, 384);
    const uint32_t lane16 = lds32(tab + 2048 + 8) - R_VP - w * 512;
    uint4 av[2 * VK0];
#pragma unroll
    for (int i = 0; i < 2 * VK0; i++) av[i] = lds128(lane16 + R_WV + (i / VK0) * 32768 + (w * 16 + i % VK0) * 512);
    uint32_t slot_off = 0;
#pragma unroll 1
    for (int s = 0; s < NSEG; s++) {
        if (s > 0) {
            mbar_wait(sb + RB_A, (s - 1) & 1);
            const uint4 tp = lds128(tab + 20480), tq = lds128(tab + 22528);
            if ((s & 3) == 1 && s > 1 && w == 0 && tq.z == 0) red_release(&g_flags[F_MEM + (s >> 2) - 1], 1);
            const uint4 kvm = lds128(tq.x + ((s - 1) & 1) * 2048);
            *(uint4*)((((uint64_t)tp.y << 32) | tp.x) + (uint64_t)(s - 1) * (8 * 2 * HD_ * 2)) = kvm;
            if (s + 1 < NSEG - 1) {
                if (((s + 1) & 3) == 0) { if (tq.z == 0) wait_flag(F_KV + ((s + 1) >> 2), 64); __syncwarp(); }
                const char* src = (const char*)((((uint64_t)tp.w << 32) | tp.z) + (uint64_t)(s + 1) * (32 * 2 * HD_ * 2));
                const uint32_t d0 = tq.y + (slot_off == (R_NST - 1) * 4096 ? 0 : slot_off + 4096);
                cp_async16(d0, src);
                cp_async16(d0 ^ 16, src + 16);
                cp_async16(d0 + (R_VX - R_KX), src + HD_ * 2);
                cp_async16((d0 ^ 16) + (R_VX - R_KX), src + HD_ * 2 + 16);
            }
            cp_async_commit();
        }
        bar_sync(NB_Y, 288);
        uint32_t vb0, vb1;
        {
            float va[4] = {0.f, 0.f, 0.f, 0.f}, vc[4] = {0.f, 0.f, 0.f, 0.f};
            uint32_t bb[VK0][4];
#pragma unroll
            for (int k2 = 0; k2 < VK0; k2++) ldsm4(bb[k2][0], bb[k2][1], bb[k2][2], bb[k2][3], lane16 + R_MEM + (k2 / (VK0 / 2)) * 4096 + (k2 % (VK0 / 2)) * 512);
#pragma unroll
            for (int k2 = 0; k2 < VK0; k2++) {
                mma16816(va, av[2 * k2].x, av[2 * k2].y, av[2 * k2].z, av[2 * k2].w, bb[k2][0], bb[k2][1]);
                mma16816(vc, av[2 * k2 + 1].x, av[2 * k2 + 1].y, av[2 * k2 + 1].z, av[2 * k2 + 1].w, bb[k2][2], bb[k2][3]);
            }
            const uint4 a = lds128(lane16 + R_VP + w * 512), b = lds128(lane16 + R_VP + 2048 + w * 512);
            vb0 = pack2((va[0] + vc[0]) + (__uint_as_float(a.x) + __uint_as_float(b.x)), (va[1] + vc[1]) + (__uint_as_float(a.y) + __uint_as_float(b.y)));
            vb1 = pack2((va[2] + vc[2]) + (__uint_as_float(a.z) + __uint_as_float(b.z)), (va[3] + vc[3]) + (__uint_as_float(a.w) + __uint_as_float(b.w)));
        }
        const uint4 ta = lds128(tab), tb = lds128(tab + 2048);
        uint32_t vx[8];
        ldsm4t(vx[0], vx[1], vx[2], vx[3], ta.x + slot_off);
        ldsm4t(vx[4], vx[5], vx[6], vx[7], ta.x + slot_off + 2048);
#pragma unroll
        for (int i = 0; i < 4; i++) {
            const uint4 f0 = lds128(tab + 4096 + i * 2048);
            wo[i][0][0] = f0.x; wo[i][0][1] = f0.y; wo[i][0][2] = f0.z; wo[i][0][3] = f0.w;
        }
        if (w == 0) PROF(11);
        uint32_t pf[5];
        float oa[2][4] = {{0.f, 0.f, 0.f, 0.f}, {0.f, 0.f, 0.f, 0.f}}, ob_[2][4] = {{0.f, 0.f, 0.f, 0.f}, {0.f, 0.f, 0.f, 0.f}};
        float sm0[4] = {0.f, 0.f, 0.f, 0.f}, sm1[4] = {0.f, 0.f, 0.f, 0.f};
        if (s != NSEG - 1) {
            mbar_wait(sb + RB_SX, s & 1);
            if (w == 0) PROF(4);
            float sv[10];
#pragma unroll
            for (int n = 0; n < 5; n++) {
                const float2 a = lds64f(tb.w + n * 256), b = lds64f(tb.w + (5 + n) * 256);
                sv[2 * n] = a.x + b.x; sv[2 * n + 1] = a.y + b.y;
            }
            float mx = fmaxf(fmaxf(fmaxf(sv[0], sv[1]), fmaxf(sv[2], sv[3])), fmaxf(fmaxf(sv[4], sv[5]), fmaxf(sv[6], sv[7])));
            mx = fmaxf(mx, fmaxf(sv[8], sv[9]));
            mx = fmaxf(mx, __shfl_xor_sync(~0u, mx, 1));
            mx = fmaxf(mx, __shfl_xor_sync(~0u, mx, 2));
#pragma unroll
            for (int n = 1; n < 5; n++) pf[n] = pack2(ex2(sv[2 * n] - mx), ex2(sv[2 * n + 1] - mx));
            pf[0] = pack2(ex2(sv[0] - mx), ex2(sv[1] - mx));
            if (w == 0) PROF(12);
            const uint32_t one = 0x3F803F80u;
            mma16816h(sm0, pf[1], pf[2], one, one);
            mma16816h(oa[0], pf[1], pf[2], vx[0], vx[1]);
            mma16816h(oa[1], pf[1], pf[2], vx[2], vx[3]);
            mma16816h(sm1, pf[3], pf[4], one, one);
            mma16816h(ob_[0], pf[3], pf[4], vx[4], vx[5]);
            mma16816h(ob_[1], pf[3], pf[4], vx[6], vx[7]);
            mma1688h(sm0, pf[0], one);
            mma1688h(oa[0], pf[0], vb0);
            mma1688h(oa[1], pf[0], vb1);
            float inv;
            asm("rcp.approx.ftz.f32 %0, %1;" : "=f"(inv) : "f"(sm0[0] + sm1[0]));
            oa[0][0] += ob_[0][0]; oa[0][1] += ob_[0][1]; oa[1][0] += ob_[1][0]; oa[1][1] += ob_[1][1];
            sts32(ta.y, pack2(oa[0][0] * inv, oa[0][1] * inv));
            sts32(ta.y ^ 16, pack2(oa[1][0] * inv, oa[1][1] * inv));
            const uint32_t oa2 = ta.w ^ 64;
            bar_sync(NB_C, 128);
            if (w == 0) PROF(5);
            uint32_t ob[8];
            ldsm4(ob[0], ob[1], ob[2], ob[3], ta.w);
            ldsm4(ob[4], ob[5], ob[6], ob[7], oa2);
#pragma unroll
            for (int i = 4; i < 8; i++) {
                const uint4 f0 = lds128(tab + 4096 + i * 2048);
                wo[i][0][0] = f0.x; wo[i][0][1] = f0.y; wo[i][0][2] = f0.z; wo[i][0][3] = f0.w;
            }
#pragma unroll
            for (int jj = 0; jj < 2; jj++) {
                if (jj == 1 && tb.w == 0) break;
                float acc[4][4];
#pragma unroll
                for (int c = 0; c < 4; c++) { acc[c][0] = acc[c][1] = acc[c][2] = acc[c][3] = 0.f; }
#pragma unroll
                for (int ks = 0; ks < 4; ks++)
#pragma unroll
                    for (int c = 0; c < 4; c++)
                        mma16816(acc[c], wo[jj * 4 + c][ks][0], wo[jj * 4 + c][ks][1], wo[jj * 4 + c][ks][2], wo[jj * 4 + c][ks][3], ob[2 * ks], ob[2 * ks + 1]);
#pragma unroll
                for (int pr = 0; pr < 2; pr++) {
                    uint4 v;
                    v.x = pack2(acc[2 * pr][0], acc[2 * pr][1]);
                    v.y = pack2(acc[2 * pr][2], acc[2 * pr][3]);
                    v.z = pack2(acc[2 * pr + 1][0], acc[2 * pr + 1][1]);
                    v.w = pack2(acc[2 * pr + 1][2], acc[2 * pr + 1][3]);
                    st_async_v4(tb.x + ((jj * 2 + pr) << 24), v, tb.y + ((jj * 2 + pr) << 24));
                }
            }
            if (w == 0) PROF(6);
        }
        stsm2t(ta.z + (s & 1) * 2048, vb0, vb1);
        cp_async_wait<0>();
        bar_sync(NB_C, 128);
        if (w == 0 && lane == 0 && s != NSEG - 1) mbar_expect_tx(sb + RB_SX, 2560);
        if (s != NSEG - 1) bar_arrive(NB_D, 384);
#pragma unroll
        for (int i = 0; i < 2 * VK0; i++) av[i] = lds128(lane16 + R_WV + (i / VK0) * 32768 + (w * 16 + i % VK0) * 512);
        slot_off = slot_off == (R_NST - 1) * 4096 ? 0 : slot_off + 4096;
    }
    rec_store_kvm(sb, col0, NSEG - 1, w, lane);
    bar_sync(NB_C, 128);
    if (w == 0 && lane == 0) red_release(&g_flags[F_MEM + NRB - 1], 1);
}

__global__ void __launch_bounds__(384, 1) k_rec(const RecParams p) {
    extern __shared__ __align__(1024) unsigned char smem_raw[];
    const uint32_t sb = __shfl_sync(~0u, smem_u32(smem_raw), 0);
    const int warp = __shfl_sync(~0u, threadIdx.x >> 5, 0);
    int lane; asm volatile("mov.u32 %0, %%laneid;" : "=r"(lane));
    const int crank = blockIdx.x & 15, slot = blockIdx.x >> 4;
    asm volatile("griddepcontrol.launch_dependents;");
    if (threadIdx.x == 0) {
        mbar_init(sb + RB_SX, 1); mbar_init(sb + RB_E, 1); mbar_init(sb + RB_A, 1); mbar_init(sb + RB_A1, 1); mbar_init(sb + RB_ROLE, 1);
        asm volatile("fence.mbarrier_init.release.cluster;" ::: "memory");
        mbar_expect_tx(sb + RB_SX, 2560);
        mbar_expect_tx(sb + RB_E, 8192);
        mbar_expect_tx(sb + RB_A, 4096);
        mbar_expect_tx(sb + RB_A1, 4096);
        mbar_expect_tx(sb + RB_ROLE, 4);
    }
    unsigned role = 0;
    if (crank == 0 && threadIdx.x == 0) {
        unsigned x = 0;
        int tm[2] = {0x7fffffff, 0x7fffffff};
#pragma unroll 1
        for (int i = 0; i < 6; i++) {
            const uint32_t t0 = clk32();
            x = atomicAdd(&g_F[65536 + (i & 1) * 1024 + slot * 64 + (x >> 31)], 0u) & 0x7fffffffu;
            if (x == 0x7654321u) sts32(sb + R_BAR + 56, x);
            const int dt = (int)(clk32() - t0);
            if (i >= 2) { if (i & 1) tm[1] = min(tm[1], dt); else tm[0] = min(tm[0], dt); }
        }
        const int side = tm[1] > tm[0];
        const unsigned old = atomicAdd(&g_flags[F_SIDE + side * 32], 1u);
        unsigned c0, c1; int gd = 0;
#pragma unroll 1
        do { c0 = ldg_relaxed32(&g_flags[F_SIDE]); c1 = ldg_relaxed32(&g_flags[F_SIDE + 32]); } while ((int)(c0 + c1) < p.ncl && ++gd < 64 * SPIN_LIMIT);
        const int big = c1 > c0;
        role = side == big ? old : (big ? c1 : c0) + old;
        role |= (big ^ 1) << 8;
    }
    __syncwarp();
    asm volatile("barrier.cluster.arrive.relaxed.aligned;\nbarrier.cluster.wait.aligned;" ::: "memory");
    if (crank == 0 && warp == 0) {
        role = __shfl_sync(~0u, role, 0);
        if (lane < 16)
            asm volatile("st.async.weak.shared::cluster.mbarrier::complete_tx::bytes.u32 [%0], %1, [%2];"
                         :: "r"(mapa_u32(sb + R_BAR + 48, lane)), "r"(role), "r"(mapa_u32(sb + RB_ROLE, lane)) : "memory");
    }
    mbar_wait(sb + RB_ROLE, 0);
    const int rolew = __shfl_sync(~0u, lds32(sb + R_BAR + 48), 0);
    const int cl = rolew & 255;
    if (cl >= 4) return;
    const int cta = cl * 16 + crank;
    if (warp < 8) rec_qk(p, sb, cta, warp, lane, rolew >> 8);
    else rec_vo(p, sb, cta, warp, lane);
}

enum { J_KV = 0, J_QA = 1, J_O = 2, J_LN = 3, J_UP = 4, J_DN = 5, J_LN1 = 6, J_MOD = 7, J_UP2 = 8, J_END = 9 };
constexpr int NJ_O = 2 * OSPLIT, NJ_O2 = 2 * OSPLIT2, NJ_LN = 8, NJ_LN2 = 16, NJ_UP = 14, NJ_UP2 = 28, NJ_DN = 8, NJ_LN1 = 8;
constexpr uint64_t pk8(int a, int b, int c, int d, int e, int f, int g, int h) {
    return (uint64_t)a | ((uint64_t)b << 8) | ((uint64_t)c << 16) | ((uint64_t)d << 24) | ((uint64_t)e << 32) | ((uint64_t)f << 40) | ((uint64_t)g << 48) | ((uint64_t)h << 56);
}
constexpr uint64_t NJ_C = pk8(32, 16, NJ_O, NJ_LN, NJ_UP, NJ_DN, NJ_LN1, 16), NJ_F = pk8(32, 16, NJ_O2, NJ_LN2, NJ_UP2, NJ_DN, NJ_LN1, 0);
constexpr uint64_t TG_C = pk8(2 * NJ_LN1, 64, 32, 2 * NJ_O, 2 * NJ_LN, 2 * NJ_UP, 32, 0), TG_F = pk8(2 * NJ_LN1, 64, 32, 2 * NJ_O2, 2 * NJ_LN2, 2 * NJ_UP2, 32, 0);
constexpr uint64_t PRIO = pk8(4, 10, 9, 8, 7, 6, 3, 0);
__device__ __forceinline__ int pick_job(int lane, int qmask, int& idx) {
    const int rb = lane & 15, half = lane >> 4;
    const uint64_t nj = (rb >= FINE_RB ? NJ_F : (rb < 3 ? NJ_C : NJ_C & ~(0xffull << 56))) >> (8 * half);
    const uint64_t tg = (rb >= FINE_RB ? TG_F : TG_C) >> (8 * half);
    const unsigned* cp = &g_flags[F_CLAIM + half * 32 + rb];
    const unsigned* dp = &g_flags[half * 32 + rb];
    int gd = 0;
#pragma unroll 1
    while (true) {
        const unsigned c0 = ldg_relaxed32(cp), c1 = ldg_relaxed32(cp + 64), c2 = ldg_relaxed32(cp + 128), c3 = ldg_relaxed32(cp + 192);
        const unsigned d0 = ldg_relaxed32(dp - (half && rb ? 1 : 0)), d1 = ldg_relaxed32(dp + 64), d2 = ldg_relaxed32(dp + 128), d3 = ldg_relaxed32(dp + 192 - rb);
        const unsigned cl[4] = {c0, c1, c2, c3}, dv[4] = {d0, d1, d2, d3};
        unsigned key = 0xffffu, key2 = 0xffffu;
        bool pre = false;
#pragma unroll
        for (int i = 0; i < 4; i++) {
            const int q = half + 2 * i;
            const bool have = ((qmask >> q) & 1) && cl[i] < (unsigned)((nj >> (16 * i)) & 255);
            bool ready = have && dv[i] >= (unsigned)((tg >> (16 * i)) & 255);
            unsigned pr = (unsigned)((PRIO >> (8 * q)) & 255);
            if (i == 0 && rb == 0) { ready = have; pr = half ? pr : 2; }
            if (i == 3 && rb == 0) ready = have;
            if (i == 3 && rb == 0 && !half) pr = 1;
            if (i == 0 && half && rb >= FINE_RB) pr = 5;
            if (ready) key = min(key, (pr << 8) | (rb << 4) | q);
            if (have) key2 = min(key2, rb >= FINE_RB ? (0x100u | (q << 4) | rb) : 0u);
            pre |= have && (i == 3 || (i == 0 && !half));
        }
        const bool anypre = __any_sync(~0u, pre);
        if (anypre && (key & 15) == J_QA) key = 0xffffu;
        key = __reduce_min_sync(~0u, key);
        key2 = __reduce_min_sync(~0u, key2);
        if (key2 == 0xffffu) return J_END;
        int pq, prb;
        if (key != 0xffffu) { pq = key & 15; prb = (key >> 4) & 15; }
        else if (key2 >= 0x120u) { pq = (key2 >> 4) & 15; prb = key2 & 15; }
        else {
            __nanosleep(150);
            if (++gd > 16 * SPIN_LIMIT) { TIMEOUT(5, 0); return J_END; }
            continue;
        }
        int c = 0;
        if (lane == 0) c = (int)atomicAdd(&g_flags[F_CLAIM + pq * 32 + prb], 1u);
        c = __shfl_sync(~0u, c, 0);
        if (c < (int)(((prb >= FINE_RB ? NJ_F : NJ_C) >> (8 * pq)) & 255)) {
            idx = pq * 512 + prb * 32 + c;
            return (pq == J_UP && prb >= FINE_RB ? J_UP2 : pq) | (prb << 8) | (c << 16);
        }
    }
}
__device__ __forceinline__ int op_row(int rb, int split) {
    return rb < FINE_RB ? split * S_ + rb * 128 : OSPLIT * S_ + (split * (NRB - FINE_RB) + rb - FINE_RB) * 128;
}

struct Pipe { uint32_t stage, phase; };
__device__ __forceinline__ void pipe_next(Pipe& p) { if (++p.stage == W_NST) { p.stage = 0; p.phase ^= 1; } }

__device__ __forceinline__ void scheduler(const Params& p, uint32_t sb, int lane) {
    const uint32_t bars = sb + SM_BAR;
    uint32_t ph = 0;
#pragma unroll 1
    while (true) {
        mbar_wait(bars + B_REQ, ph);
        int j = 4095;
        const int jd = pick_job(lane, p.qmask, j);
        if (lane == 0) { sts32(bars + B_NEXT, (uint32_t)jd); sts32(bars + B_NEXT + 4, (uint32_t)j); mbar_arrive(bars + B_RSP); }
        ph ^= 1;
        if (jd == J_END) break;
        __syncwarp();
    }
}

__device__ __forceinline__ void producer(const Params& p, uint32_t sb) {
    Pipe pp{0, 1};
    const uint32_t bars = sb + SM_BAR;
    uint32_t seq = 0, h_seen = 0;
    mbar_arrive(bars + B_REQ);
#pragma unroll 1
    while (true) {
        mbar_wait(bars + B_RSP, seq & 1);
        const int jd = (int)lds32(bars + B_NEXT), j = (int)lds32(bars + B_NEXT + 4);
        int left = (jd & 255) == J_DN ? 15 : ((jd & 255) == J_QA ? 12 : ((jd & 255) == J_O ? (((jd >> 8) & 255) >= FINE_RB ? 64 / OSPLIT2 : 64 / OSPLIT) : ((jd & 255) == J_LN || (jd & 255) == J_LN1 || (jd & 255) == J_MOD ? 1 : 8)));
        left = max(left - PICK_AHEAD, 1);
        TR(j, 1);
        const int type = jd & 255, rb = (jd >> 8) & 255, cb = jd >> 16;
        const bool fine = rb >= FINE_RB;
        bool first = true;
        auto begin_stage = [&](uint32_t bytes) -> uint32_t {
            mbar_wait(bars + B_EMPTY + pp.stage * 8, pp.phase);
            if (first) { sts32(bars + B_RING + (seq & 7) * 4, (uint32_t)jd); sts32(bars + B_RING + 32 + (seq & 7) * 4, (uint32_t)j); first = false; }
            const uint32_t fb = bars + B_FULL + pp.stage * 8;
            if (bytes) mbar_expect_tx(fb, bytes); else mbar_arrive(fb);
            if (--left == 0 && type != J_END) mbar_arrive(bars + B_REQ);
            return fb;
        };
        if (type == J_END || type == J_LN || type == J_LN1 || type == J_MOD) {
            if (type == J_LN) { wait_flag(F_OP + rb, 2 * (fine ? NJ_O2 : NJ_O)); wait_flag(F_MOD + 1, 32); wait_flag(F_MOD + 2, 32); }

            TR(j, 2);
            begin_stage(0); pipe_next(pp);
            seq++;
            if (type == J_END) break;
            continue;
        }
        const CUtensorMap *ta, *tb0, *tb1;
        int k0 = 0, nk = 8, n0 = cb * 256, n1 = n0 + 128, nb = 4, dep = -1;
        unsigned tgt = 0;
        switch (type) {
            case J_KV: ta = &p.tm_h; tb0 = tb1 = cb < 16 ? &p.tm_wk : &p.tm_wv; n0 = (cb & 15) * 256; n1 = n0 + 128; dep = F_H + rb; tgt = 2 * NJ_LN1; break;
            case J_QA: ta = &p.tm_h; tb0 = tb1 = &p.tm_wq; dep = F_H + rb; tgt = 2 * NJ_LN1; break;
            case J_O: ta = &p.tm_o; tb0 = tb1 = &p.tm_wo; n0 = (cb & 1) * 256; n1 = n0 + 128; nk = fine ? 64 / OSPLIT2 : 64 / OSPLIT; k0 = (cb >> 1) * nk * 64;
                      dep = F_O + rb; tgt = 32; break;
            case J_UP: ta = &p.tm_h2; tb0 = &p.tm_wg; tb1 = &p.tm_wu; n0 = n1 = cb * 128; dep = F_H2 + rb; tgt = 2 * NJ_LN; break;
            case J_UP2: ta = &p.tm_h2; tb0 = &p.tm_wg; tb1 = &p.tm_wu; n0 = n1 = cb * 64; nb = 2; dep = F_H2 + rb; tgt = 2 * NJ_LN2; break;
            default: ta = &p.tm_act; tb0 = tb1 = &p.tm_wd; n0 = cb * 64; nk = 0; break;
        }
        const int m0 = rb * 128;
        if (type == J_DN) {
#pragma unroll 1
            for (int kb = 0; kb < 14; kb++) {
                const uint32_t fb = begin_stage(49152);
                const uint32_t st = sb + pp.stage * W_STAGE;
                const int k = kb * 128;
                tma_load2d(st + 32768, tb0, n0, k, fb);
                tma_load2d(st + 40960, tb0, n0, k + 64, fb);
                if (kb == 0) { wait_flag(F_ACT + rb, 2 * (fine ? NJ_UP2 : NJ_UP)); asm volatile("fence.proxy.async.global;" ::: "memory"); TR(j, 2); }
                tma_load2d(st, ta, k, m0, fb);
                tma_load2d(st + 8192, ta, k, m0 + 64, fb);
                tma_load2d(st + 16384, ta, k + 64, m0, fb);
                tma_load2d(st + 24576, ta, k + 64, m0 + 64, fb);
                pipe_next(pp);
            }
        }
#pragma unroll 1
        for (int kb = 0; kb < nk; kb++) {
            const uint32_t fb = begin_stage(16384 + nb * 8192);
            const uint32_t st = sb + pp.stage * W_STAGE;
            const int k = k0 + kb * 64;
            tma_load2d(st + 16384, tb0, n0, k, fb);
            if (nb == 4) {
                tma_load2d(st + 16384 + 8192, tb0, n0 + 64, k, fb);
                tma_load2d(st + 16384 + 16384, tb1, n1, k, fb);
                tma_load2d(st + 16384 + 24576, tb1, n1 + 64, k, fb);
            } else if (nb == 2) {
                tma_load2d(st + 16384 + 8192, tb1, n1, k, fb);
            }
            if (kb == 0) {
                if (dep >= 0 && !(dep < 32 && ((h_seen >> dep) & 1))) {
                    wait_flag(dep, tgt);
                    if (type != J_O) asm volatile("fence.proxy.async.global;" ::: "memory");
                    if (dep < 32) h_seen |= 1u << dep;
                }
                TR(j, 2);
            }
            tma_load2d(st, ta, k, m0, fb);
            tma_load2d(st + 8192, ta, k, m0 + 64, fb);
            pipe_next(pp);
        }
        if (type == J_QA) {
            wait_flag(F_KV + rb, 64);
#pragma unroll 1
            for (int i = 0; i < 4; i++) {
                const uint32_t fb = begin_stage(40960);
                const uint32_t st = sb + pp.stage * W_STAGE;
                const int col = (i & 1) * HD_ + (cb * 2 + (i >> 1)) * DH_;
                tma_load2d(st, &p.tm_kv, col, m0, fb);
                tma_load2d(st + 8192, &p.tm_kv, col, m0 + 64, fb);
                tma_load2d(st + 16384, &p.tm_kv, col + 64, m0, fb);
                tma_load2d(st + 24576, &p.tm_kv, col + 64, m0 + 64, fb);
                if (i == 0) { wait_flag(F_MEM + rb, 64); asm volatile("fence.proxy.async.global;" ::: "memory"); }
                tma_load2d(st + 32768, &p.tm_kvm, col, rb * 32, fb);
                tma_load2d(st + 36864, &p.tm_kvm, col + 64, rb * 32, fb);
                pipe_next(pp);
            }
        } else if (type == J_DN) {
            const uint32_t fb = begin_stage(16384);
            const uint32_t st = sb + pp.stage * W_STAGE;
            tma_load2d(st, &p.tm_x1, n0, m0, fb);
            tma_load2d(st + 8192, &p.tm_x1, n0, m0 + 64, fb);
            pipe_next(pp);
        }
        seq++;
    }
}

__device__ __forceinline__ void store_warp(const Params& p, uint32_t sb, int wg, int lane) {
    const uint32_t bars = sb + SM_BAR;
    uint32_t seq = 0;
#pragma unroll 1
    while (true) {
        bar_sync(NB_ST + wg, 160);
        const uint32_t jd = lds32(bars + B_RING + (seq & 7) * 4);
        seq++;
        const int type = jd & 255, rb = (jd >> 8) & 255, cb = jd >> 16;
        if (type == J_END) break;
        if (lane == 0) {
            const uint32_t src = sb + W_STG + wg * 32768;
            const CUtensorMap* tm = nullptr; int n0 = cb * 256, nbox = 4, mrow = rb * 128 + wg * 64, flag = 0;
            switch (type) {
                case J_KV: tm = &p.tm_kv; flag = F_KV + rb; break;
                case J_QA: tm = &p.tm_o; flag = F_O + rb; break;
                case J_O: tm = &p.tm_op; n0 = (cb & 1) * 256; mrow = op_row(rb, cb >> 1) + wg * 64; flag = F_OP + rb; break;
                case J_LN: flag = F_H2 + rb; nbox = 0; break;
                case J_LN1: flag = F_H + rb; nbox = 0; break;
                case J_MOD: flag = F_MOD + rb; nbox = 0; break;
                case J_UP: tm = &p.tm_act; n0 = cb * 128; nbox = 2; flag = F_ACT + rb; break;
                case J_UP2: tm = &p.tm_act; n0 = cb * 64; nbox = 1; flag = F_ACT + rb; break;
                default: tm = &p.tm_out; n0 = cb * 64; nbox = 1; flag = -1; break;
            }
#pragma unroll 1
            for (int b = 0; b < nbox; b++) tma_store2d(tm, src + b * 8192, n0 + b * 64, mrow);
            bulk_commit();
            bulk_wait0();
            mbar_arrive(bars + B_STGFREE + wg * 8);
            if (flag >= 0) red_release(&g_flags[flag], 1);
        }
        __syncwarp();
    }
}

__device__ __forceinline__ float gelu_tanh(float x) {
    const float t = x * fmaf(-0.10294324397f, x * x, -2.30220819814f);
    float r; asm("rcp.approx.ftz.f32 %0, %1;" : "=f"(r) : "f"(1.f + ex2(t)));
    return x * r;
}

#define CTR(i) do {} while (0)

template <int NSPLIT>
__device__ __forceinline__ void ln2_row(const Params& p, int rb, int r, int lane) {
    const int row = rb * 128 + r;
    uint4 u[2 * NSPLIT];
#pragma unroll
    for (int sp = 0; sp < NSPLIT; sp++) {
        const uint4* src = (const uint4*)(g_op + (size_t)(op_row(rb, sp) + r) * D_);
        u[2 * sp] = __ldcg(src + lane); u[2 * sp + 1] = __ldcg(src + 32 + lane);
    }
    const uint4* xr = (const uint4*)(p.x + (size_t)row * D_);
    const uint4 xa = __ldg(xr + lane), xb = __ldg(xr + 32 + lane);
    uint32_t ga[8], c1[8], sm[8];
    load_mod8(g_mod + 2 * D_, lane, ga);
    load_mod8(g_mod + 4 * D_, lane, c1);
    load_mod8(g_mod + 3 * D_, lane, sm);
    float a[16];
#pragma unroll
    for (int i = 0; i < 16; i++) a[i] = 0.f;
#pragma unroll
    for (int sp = 0; sp < 2 * NSPLIT; sp++) {
        float* q = a + (sp & 1) * 8;
        q[0] += bflo(u[sp].x); q[1] += bfhi(u[sp].x); q[2] += bflo(u[sp].y); q[3] += bfhi(u[sp].y);
        q[4] += bflo(u[sp].z); q[5] += bfhi(u[sp].z); q[6] += bflo(u[sp].w); q[7] += bfhi(u[sp].w);
    }
    const uint32_t xv[8] = {xa.x, xa.y, xa.z, xa.w, xb.x, xb.y, xb.z, xb.w};
    uint32_t v[8], r8[8];
#pragma unroll
    for (int i = 0; i < 8; i++) v[i] = hadd2(xv[i], hmul2(ga[i], pack2(a[2 * i], a[2 * i + 1])));
    uint4* x1r = (uint4*)(g_x1 + (size_t)row * D_);
    x1r[lane] = make_uint4(v[0], v[1], v[2], v[3]); x1r[32 + lane] = make_uint4(v[4], v[5], v[6], v[7]);
    uint32_t mu2; float rden;
    ln_stats(v, mu2, rden);
#pragma unroll
    for (int i = 0; i < 8; i++) c1[i] = hadd2(c1[i], 0x3F803F80u);
    ln_apply(v, mu2, rden, c1, sm, r8);
    uint4* hr = (uint4*)(g_h2 + (size_t)row * D_);
    hr[lane] = make_uint4(r8[0], r8[1], r8[2], r8[3]); hr[32 + lane] = make_uint4(r8[4], r8[5], r8[6], r8[7]);
}

__device__ __forceinline__ void consumer(const Params& p, uint32_t sb, int warp, int lane) {
    const uint32_t bars = sb + SM_BAR;
    const int wg = warp >> 2, wl = warp & 3;
    const uint32_t l7 = lane & 7, l8 = lane >> 3, g = lane >> 2, t = lane & 3;
    Pipe pp{0, 0};
    uint32_t seq = 0, stg_phase = 1;
    const int srow = wl * 16 + l7 + (l8 & 1) * 8;
    const uint32_t stg_base = sb + W_STG + wg * 32768 + srow * 128;
    const uint32_t sx = ((lane >> 4) ^ (srow & 7)) << 4;
#pragma unroll 1
    while (true) {
        mbar_wait(bars + B_FULL + pp.stage * 8, pp.phase);
        const uint32_t jd = lds32(bars + B_RING + (seq & 7) * 4);
        CTR(3);
        seq++;
        const int type = jd & 255, rb = (jd >> 8) & 255, cb = jd >> 16;
        if (type == J_END) { mbar_wait(bars + B_STGFREE + wg * 8, stg_phase); bar_arrive(NB_ST + wg, 160); break; }
        if (type == J_MOD) {
            __syncwarp();
            if (lane == 0) mbar_arrive(bars + B_EMPTY + pp.stage * 8);
            pipe_next(pp);
            const int rg = warp * 4 + l8, col = rb * 1024 + cb * 64;
            uint4 wv[16];
#pragma unroll
            for (int i = 0; i < 16; i++) wv[i] = __ldg((const uint4*)(p.w_mod + (size_t)(rg * 16 + i) * (6 * D_) + col + l7 * 8));
            const uint32_t cw = __ldg((const uint32_t*)(p.c + rg * 16) + l7);
            const float cl = bflo(cw), ch = bfhi(cw);
            const uint32_t sw = pack2(__fdividef(cl, 1.f + __expf(-cl)), __fdividef(ch, 1.f + __expf(-ch)));
            float a[8];
#pragma unroll
            for (int i = 0; i < 8; i++) a[i] = 0.f;
#pragma unroll
            for (int i = 0; i < 16; i++) {
                const uint32_t sv = __shfl_sync(~0u, sw, (lane & 24) + (i >> 1));
                const float cv = (i & 1) ? bfhi(sv) : bflo(sv);
                a[0] = fmaf(cv, bflo(wv[i].x), a[0]); a[1] = fmaf(cv, bfhi(wv[i].x), a[1]); a[2] = fmaf(cv, bflo(wv[i].y), a[2]); a[3] = fmaf(cv, bfhi(wv[i].y), a[3]);
                a[4] = fmaf(cv, bflo(wv[i].z), a[4]); a[5] = fmaf(cv, bfhi(wv[i].z), a[5]); a[6] = fmaf(cv, bflo(wv[i].w), a[6]); a[7] = fmaf(cv, bfhi(wv[i].w), a[7]);
            }
#pragma unroll
            for (int i = 0; i < 8; i++) { a[i] += __shfl_xor_sync(~0u, a[i], 8); a[i] += __shfl_xor_sync(~0u, a[i], 16); }
            const uint32_t red = sb + SM_BAR + 1024;
            bar_sync(NB_M, 256);
            if (lane < 8) {
                sts128(red + warp * 256 + lane * 32, make_uint4(__float_as_uint(a[0]), __float_as_uint(a[1]), __float_as_uint(a[2]), __float_as_uint(a[3])));
                sts128(red + warp * 256 + lane * 32 + 16, make_uint4(__float_as_uint(a[4]), __float_as_uint(a[5]), __float_as_uint(a[6]), __float_as_uint(a[7])));
            }
            bar_sync(NB_M, 256);
            if (wl == 0) {
                const uint32_t ra = red + (wg * 32 + lane) * 4;
                float v = 0.f;
#pragma unroll
                for (int i = 0; i < 8; i++) v += lds32f(ra + i * 256);
                g_mod[col + wg * 32 + lane] = __float2bfloat16_rn(v);
            }
            mbar_wait(bars + B_STGFREE + wg * 8, stg_phase); stg_phase ^= 1;
            CTR(4); CTR(5);
            bar_arrive(NB_ST + wg, 160);
            continue;
        }
        if (type == J_LN || type == J_LN1) {
            __syncwarp();
            if (lane == 0) mbar_arrive(bars + B_EMPTY + pp.stage * 8);
            pipe_next(pp);
            if (type == J_LN1) {
                const int row = rb * 128 + cb * 16 + warp * 2;
                const uint4* xr = (const uint4*)(p.x + (size_t)row * D_);
                const uint4 xa[4] = {__ldg(xr + lane), __ldg(xr + 32 + lane), __ldg(xr + 64 + lane), __ldg(xr + 96 + lane)};
                uint32_t c1[8], sm[8], mu2[2];
                float rden[2];
#pragma unroll
                for (int rr = 0; rr < 2; rr++) {
                    const uint32_t v[8] = {xa[2 * rr].x, xa[2 * rr].y, xa[2 * rr].z, xa[2 * rr].w, xa[2 * rr + 1].x, xa[2 * rr + 1].y, xa[2 * rr + 1].z, xa[2 * rr + 1].w};
                    ln_stats(v, mu2[rr], rden[rr]);
                }
                if (lane == 0) wait_flag(F_MOD, 32);
                __syncwarp();
                load_mod8(g_mod + D_, lane, c1);
                load_mod8(g_mod, lane, sm);
#pragma unroll
                for (int i = 0; i < 8; i++) c1[i] = hadd2(c1[i], 0x3F803F80u);
#pragma unroll
                for (int rr = 0; rr < 2; rr++) {
                    const uint32_t v[8] = {xa[2 * rr].x, xa[2 * rr].y, xa[2 * rr].z, xa[2 * rr].w, xa[2 * rr + 1].x, xa[2 * rr + 1].y, xa[2 * rr + 1].z, xa[2 * rr + 1].w};
                    uint32_t r[8];
                    ln_apply(v, mu2[rr], rden[rr], c1, sm, r);
                    uint4* hr = (uint4*)(g_h + (size_t)(row + rr) * D_);
                    hr[lane] = make_uint4(r[0], r[1], r[2], r[3]); hr[32 + lane] = make_uint4(r[4], r[5], r[6], r[7]);
                }
            } else if (rb >= FINE_RB) ln2_row<OSPLIT2>(p, rb, cb * 8 + warp, lane);
            else {
#pragma unroll 1
                for (int rr = 0; rr < 2; rr++) ln2_row<OSPLIT>(p, rb, cb * 16 + warp * 2 + rr, lane);
            }
            mbar_wait(bars + B_STGFREE + wg * 8, stg_phase); stg_phase ^= 1;
            CTR(4); CTR(5);
            bar_arrive(NB_ST + wg, 160);
            continue;
        }
        if (type == J_DN || type == J_UP2) {
            float acc[64];
#pragma unroll
            for (int i = 0; i < 64; i++) acc[i] = 0.f;
            if (type == J_DN) {
#pragma unroll 1
                for (int kb = 0; kb < 14; kb++) {
                    if (kb) mbar_wait(bars + B_FULL + pp.stage * 8, pp.phase);
                    const uint32_t st = sb + pp.stage * W_STAGE;
                    const uint64_t da = mkdesc(st + wg * 8192, 16, 1024), db = mkdesc(st + 32768, 8192, 1024);
                    wg_fence();
#pragma unroll
                    for (int ks = 0; ks < 8; ks++) wgmma_n64(acc, da + (ks >> 2) * 1024 + (ks & 3) * 2, db + ks * 128);
                    wg_commit();
                    wg_wait0();
                    if (lane == 0) mbar_arrive(bars + B_EMPTY + pp.stage * 8);
                    pipe_next(pp);
                }
            } else {
#pragma unroll 1
                for (int kb = 0; kb < 8; kb++) {
                    if (kb) mbar_wait(bars + B_FULL + pp.stage * 8, pp.phase);
                    const uint32_t st = sb + pp.stage * W_STAGE;
                    const uint64_t da = mkdesc(st + wg * 8192, 16, 1024), db = mkdesc(st + 16384, 8192, 1024);
                    wg_fence();
#pragma unroll
                    for (int ks = 0; ks < 4; ks++) wgmma_n128(acc, da + ks * 2, db + ks * 128, 1);
                    wg_commit();
                    wg_wait0();
                    if (lane == 0) mbar_arrive(bars + B_EMPTY + pp.stage * 8);
                    pipe_next(pp);
                }
            }
            CTR(4);
            if (type == J_UP2) {
                mbar_wait(bars + B_STGFREE + wg * 8, stg_phase); stg_phase ^= 1;
#pragma unroll
                for (int j = 0; j < 4; j++) {
                    uint32_t r[4];
#pragma unroll
                    for (int q = 0; q < 4; q++) {
                        const uint32_t gw = pack2(acc[8 * j + 2 * q], acc[8 * j + 2 * q + 1]);
                        const uint32_t uw = pack2(acc[32 + 8 * j + 2 * q], acc[32 + 8 * j + 2 * q + 1]);
                        r[q] = hmul2(pack2(gelu_tanh(bflo(gw)), gelu_tanh(bfhi(gw))), uw);
                    }
                    stsm4(stg_base + (sx ^ (j << 5)), r[0], r[1], r[2], r[3]);
                }
            } else {
                mbar_wait(bars + B_FULL + pp.stage * 8, pp.phase);
                const uint32_t st = sb + pp.stage * W_STAGE;
                mbar_wait(bars + B_STGFREE + wg * 8, stg_phase); stg_phase ^= 1;
                const uint32_t* gb = (const uint32_t*)(g_mod + 5 * D_ + cb * 64) + t;
                const uint32_t xa = st + wg * 8192 + (wl * 16 + g) * 128 + (g << 4) + t * 4;
#pragma unroll
                for (int j = 0; j < 4; j++) {
                    uint32_t r[4];
#pragma unroll
                    for (int q = 0; q < 4; q++) {
                        const int nt = 2 * j + (q >> 1);
                        const uint32_t xw = lds32((xa ^ ((nt & 7) << 4)) + (nt >> 3) * 16384 + (q & 1) * 1024);
                        r[q] = hadd2(xw, hmul2(__ldcg(gb + nt * 4), pack2(acc[8 * j + 2 * q], acc[8 * j + 2 * q + 1])));
                    }
                    stsm4(stg_base + (j >> 2) * 8192 + (sx ^ ((2 * j & 7) << 4)), r[0], r[1], r[2], r[3]);
                }
                __syncwarp();
                if (lane == 0) mbar_arrive(bars + B_EMPTY + pp.stage * 8);
                pipe_next(pp);
            }
            fence_async_smem();
            CTR(5);
            bar_arrive(NB_ST + wg, 160);
            continue;
        }
        float acc[128];
#pragma unroll
        for (int i = 0; i < 128; i++) acc[i] = 0.f;
        const int nk = type == J_O ? (rb >= FINE_RB ? 64 / OSPLIT2 : 64 / OSPLIT) : 8;
#pragma unroll 1
        for (int kb = 0; kb < nk; kb++) {
            if (kb) mbar_wait(bars + B_FULL + pp.stage * 8, pp.phase);
            const uint32_t st = sb + pp.stage * W_STAGE;
            const uint64_t da = mkdesc(st + wg * 8192, 16, 1024), db = mkdesc(st + 16384, 8192, 1024);
            wg_fence();
#pragma unroll
            for (int ks = 0; ks < 4; ks++) wgmma_n256(acc, da + ks * 2, db + ks * 128, 1);
            wg_commit();
            wg_wait0();
            if (lane == 0) mbar_arrive(bars + B_EMPTY + pp.stage * 8);
            pipe_next(pp);
        }
        CTR(4);
        if (type == J_QA) {
            uint32_t qf[64];
#pragma unroll
            for (int i = 0; i < 64; i++) qf[i] = pack2(acc[2 * i], acc[2 * i + 1]);
            const int sg = warp >> 1, half = warp & 1;
            const float sc = 0.08838834764831845f * 1.4426950408889634f;
            const uint32_t xoff = (sg >> 1) * 8192 + ((sg & 1) * 32 + l7) * 128;
            const uint32_t moff = 32768 + (sg * 8 + l7) * 128;
            const uint32_t kch = (l8 ^ l7) << 4;
            const uint32_t vch = ((l8 & 1) ^ l7) << 4;
            mbar_wait(bars + B_STGFREE + wg * 8, stg_phase); stg_phase ^= 1;
#pragma unroll 1
            for (int hh = 0; hh < 2; hh++) {
                mbar_wait(bars + B_FULL + pp.stage * 8, pp.phase);
                uint32_t st = sb + pp.stage * W_STAGE;
                float sa[5][4];
#pragma unroll
                for (int n = 0; n < 5; n++) sa[n][0] = sa[n][1] = sa[n][2] = sa[n][3] = 0.f;
#pragma unroll
                for (int i = 0; i < 4; i++) {
                    const uint32_t* q = qf + i * 8;
                    uint32_t kk[5][4];
                    ldsm4(kk[0][0], kk[0][1], kk[0][2], kk[0][3], st + moff + (i >> 1) * 4096 + (kch ^ ((i & 1) * 64)));
#pragma unroll
                    for (int n = 1; n < 5; n++)
                        ldsm4(kk[n][0], kk[n][1], kk[n][2], kk[n][3], st + xoff + (n - 1) * 1024 + (i >> 1) * 16384 + (kch ^ ((i & 1) * 64)));
#pragma unroll
                    for (int n = 0; n < 5; n++) mma16816(sa[n], q[0], q[1], q[2], q[3], kk[n][0], kk[n][1]);
#pragma unroll
                    for (int n = 0; n < 5; n++) mma16816(sa[n], q[4], q[5], q[6], q[7], kk[n][2], kk[n][3]);
                }
                __syncwarp();
                if (lane == 0) mbar_arrive(bars + B_EMPTY + pp.stage * 8);
                pipe_next(pp);
                const int iq0 = half * 16 + g - 2 * t, iq1 = iq0 + 8;
                float m0 = fmaxf(sa[0][0], sa[0][1]), m1 = fmaxf(sa[0][2], sa[0][3]);
#pragma unroll
                for (int n = 1; n < 5; n++) {
#pragma unroll
                    for (int e = 0; e < 2; e++) {
                        const int jx = (n - 1) * 8 + e;
                        if (jx > iq0) sa[n][e] = -3.0e38f;
                        if (jx > iq1) sa[n][2 + e] = -3.0e38f;
                        m0 = fmaxf(m0, sa[n][e]); m1 = fmaxf(m1, sa[n][2 + e]);
                    }
                }
                m0 = fmaxf(m0, __shfl_xor_sync(~0u, m0, 1)); m1 = fmaxf(m1, __shfl_xor_sync(~0u, m1, 1));
                m0 = fmaxf(m0, __shfl_xor_sync(~0u, m0, 2)); m1 = fmaxf(m1, __shfl_xor_sync(~0u, m1, 2));
                m0 *= -sc; m1 *= -sc;
                float l0 = 0.f, l1 = 0.f;
                uint32_t p0[5], p1[5];
#pragma unroll
                for (int n = 0; n < 5; n++) {
                    const float e0 = ex2(fmaf(sa[n][0], sc, m0)), e1 = ex2(fmaf(sa[n][1], sc, m0));
                    const float e2 = ex2(fmaf(sa[n][2], sc, m1)), e3 = ex2(fmaf(sa[n][3], sc, m1));
                    l0 += e0 + e1; l1 += e2 + e3;
                    p0[n] = pack2(e0, e1); p1[n] = pack2(e2, e3);
                }
                l0 += __shfl_xor_sync(~0u, l0, 1); l1 += __shfl_xor_sync(~0u, l1, 1);
                l0 += __shfl_xor_sync(~0u, l0, 2); l1 += __shfl_xor_sync(~0u, l1, 2);
                const float i0 = __fdividef(1.f, l0), i1 = __fdividef(1.f, l1);
                mbar_wait(bars + B_FULL + pp.stage * 8, pp.phase);
                st = sb + pp.stage * W_STAGE;
#pragma unroll
                for (int i = 0; i < 32; i++) qf[i] = qf[32 + i];
#pragma unroll 1
                for (int bx = 0; bx < 2; bx++) {
                    float o[8][4];
                    uint32_t vm[8], v0[4][4], v1[4][4];
#pragma unroll
                    for (int ep = 0; ep < 4; ep++) {
                        ldsm2t(vm[2 * ep], vm[2 * ep + 1], st + moff + bx * 4096 + (vch ^ (ep << 5)));
                        const uint32_t va = st + xoff + (l8 >> 1) * 1024 + bx * 16384 + (vch ^ (ep << 5));
                        ldsm4t(v0[ep][0], v0[ep][1], v0[ep][2], v0[ep][3], va);
                        ldsm4t(v1[ep][0], v1[ep][1], v1[ep][2], v1[ep][3], va + 2048);
                    }
#pragma unroll
                    for (int n = 0; n < 8; n++) { o[n][0] = o[n][1] = o[n][2] = o[n][3] = 0.f; mma16816(o[n], p0[0], p1[0], p0[1], p1[1], vm[n], v0[n >> 1][n & 1]); }
#pragma unroll
                    for (int n = 0; n < 8; n++) mma16816(o[n], p0[2], p1[2], p0[3], p1[3], v0[n >> 1][2 + (n & 1)], v1[n >> 1][n & 1]);
#pragma unroll
                    for (int n = 0; n < 8; n++) mma1688(o[n], p0[4], p1[4], v1[n >> 1][2 + (n & 1)]);
#pragma unroll
                    for (int ep = 0; ep < 4; ep++)
                        stsm4(stg_base + (hh * 2 + bx) * 8192 + (sx ^ (ep << 5)),
                              pack2(o[2 * ep][0] * i0, o[2 * ep][1] * i0), pack2(o[2 * ep][2] * i1, o[2 * ep][3] * i1),
                              pack2(o[2 * ep + 1][0] * i0, o[2 * ep + 1][1] * i0), pack2(o[2 * ep + 1][2] * i1, o[2 * ep + 1][3] * i1));
                }
                __syncwarp();
                if (lane == 0) mbar_arrive(bars + B_EMPTY + pp.stage * 8);
                pipe_next(pp);
            }
        } else if (type == J_UP) {
            mbar_wait(bars + B_STGFREE + wg * 8, stg_phase); stg_phase ^= 1;
#pragma unroll
            for (int j = 0; j < 8; j++) {
                uint32_t r[4];
#pragma unroll
                for (int q = 0; q < 4; q++) {
                    const uint32_t gw = pack2(acc[8 * j + 2 * q], acc[8 * j + 2 * q + 1]);
                    const uint32_t uw = pack2(acc[64 + 8 * j + 2 * q], acc[64 + 8 * j + 2 * q + 1]);
                    r[q] = hmul2(pack2(gelu_tanh(bflo(gw)), gelu_tanh(bfhi(gw))), uw);
                }
                stsm4(stg_base + (j >> 2) * 8192 + (sx ^ ((2 * j & 7) << 4)), r[0], r[1], r[2], r[3]);
            }
        } else {
            mbar_wait(bars + B_STGFREE + wg * 8, stg_phase); stg_phase ^= 1;
#pragma unroll
            for (int j = 0; j < 16; j++)
                stsm4(stg_base + (j >> 2) * 8192 + (sx ^ ((2 * j & 7) << 4)),
                      pack2(acc[8 * j], acc[8 * j + 1]), pack2(acc[8 * j + 2], acc[8 * j + 3]),
                      pack2(acc[8 * j + 4], acc[8 * j + 5]), pack2(acc[8 * j + 6], acc[8 * j + 7]));
        }
        fence_async_smem();
        CTR(5);
        bar_arrive(NB_ST + wg, 160);
    }
}

__global__ void __launch_bounds__(384, 1) k_work(const __grid_constant__ Params p) {
    extern __shared__ __align__(1024) unsigned char smem_raw[];
    const uint32_t sb = smem_u32(smem_raw);
    if (sb & 1023) __trap();
    const int warp = __shfl_sync(~0u, threadIdx.x >> 5, 0);
    int lane; asm volatile("mov.u32 %0, %%laneid;" : "=r"(lane));
    if (threadIdx.x == 0) {
        const uint32_t bars = sb + SM_BAR;
        for (int i = 0; i < W_NST; i++) { mbar_init(bars + B_FULL + i * 8, 1); mbar_init(bars + B_EMPTY + i * 8, 8); }
        mbar_init(bars + B_STGFREE, 1); mbar_init(bars + B_STGFREE + 8, 1); mbar_init(bars + B_REQ, 1); mbar_init(bars + B_RSP, 1);
        asm volatile("fence.mbarrier_init.release.cluster;" ::: "memory");
    }
    __syncthreads();
    if (warp < 8) {
        asm volatile("setmaxnreg.inc.sync.aligned.u32 232;");
        consumer(p, sb, warp, lane);
    } else {
        asm volatile("setmaxnreg.dec.sync.aligned.u32 40;");
        if (warp == 8) { if (lane == 0) producer(p, sb); }
        else if (warp < 11) store_warp(p, sb, warp - 9, lane);
        else scheduler(p, sb, lane);
        __syncwarp();
        bar_sync(NB_W0, 128);
        if (warp == 8 && p.qmask == 0xff) {
            unsigned last = 0;
            if (lane == 0) { __threadfence(); last = atomicAdd(&g_flags[F_DONE], 1u) == gridDim.x - 1; }
            if (__shfl_sync(~0u, last, 0))
                for (int i = lane; i < F_TOTAL; i += 32) g_flags[i] = 0;
        }
    }
}

typedef CUresult (*EncodeFn)(CUtensorMap*, CUtensorMapDataType, cuuint32_t, void*, const cuuint64_t*, const cuuint64_t*,
                             const cuuint32_t*, const cuuint32_t*, CUtensorMapInterleave, CUtensorMapSwizzle,
                             CUtensorMapL2promotion, CUtensorMapFloatOOBfill);

static void make_map(EncodeFn enc, CUtensorMap* m, const void* ptr, uint64_t rows, uint64_t cols, uint32_t box_rows) {
    cuuint64_t dims[2] = {cols, rows};
    cuuint64_t strides[1] = {cols * 2};
    cuuint32_t box[2] = {64, box_rows};
    cuuint32_t es[2] = {1, 1};
    enc(m, CU_TENSOR_MAP_DATA_TYPE_BFLOAT16, 2, const_cast<void*>(ptr), dims, strides, box, es, CU_TENSOR_MAP_INTERLEAVE_NONE,
        CU_TENSOR_MAP_SWIZZLE_128B, CU_TENSOR_MAP_L2_PROMOTION_L2_256B, CU_TENSOR_MAP_FLOAT_OOB_FILL_NONE);
}
template <typename T> static void* sym_addr(T& sym) { void* p = nullptr; cudaGetSymbolAddress(&p, sym); return p; }

extern "C" void kernel_launch(void* const* d_in, const int* in_sizes, int n_in, void* d_out, int out_size) {
    static Params prm;
    static RecParams rp;
    static bool ready = false;
    static const void* key[14];
    bool same = ready;
    for (int i = 0; i < 13 && same; i++) same = key[i] == d_in[i];
    same = same && key[13] == d_out;
    if (!same) {
        void* fn = nullptr;
        cudaDriverEntryPointQueryResult qr;
        cudaGetDriverEntryPoint("cuTensorMapEncodeTiled", &fn, cudaEnableDefault, &qr);
        EncodeFn enc = (EncodeFn)fn;
        make_map(enc, &prm.tm_h, sym_addr(g_h), S_, D_, 64);
        make_map(enc, &prm.tm_kv, sym_addr(g_kv), S_, 2 * HD_, 64);
        make_map(enc, &prm.tm_kvm, sym_addr(g_kvm), NSEG * 8, 2 * HD_, 32);
        make_map(enc, &prm.tm_o, sym_addr(g_o), S_, HD_, 64);
        make_map(enc, &prm.tm_op, sym_addr(g_op), OP_ROWS, D_, 64);
        make_map(enc, &prm.tm_h2, sym_addr(g_h2), S_, D_, 64);
        make_map(enc, &prm.tm_act, sym_addr(g_act), S_, DF_, 64);
        make_map(enc, &prm.tm_x1, sym_addr(g_x1), S_, D_, 64);
        make_map(enc, &prm.tm_out, d_out, S_, D_, 64);
        make_map(enc, &prm.tm_wq, d_in[2], D_, HD_, 64);
        make_map(enc, &prm.tm_wk, d_in[3], D_, HD_, 64);
        make_map(enc, &prm.tm_wv, d_in[4], D_, HD_, 64);
        make_map(enc, &prm.tm_wo, d_in[5], HD_, D_, 64);
        make_map(enc, &prm.tm_wg, d_in[8], D_, DF_, 64);
        make_map(enc, &prm.tm_wu, d_in[9], D_, DF_, 64);
        make_map(enc, &prm.tm_wd, d_in[10], DF_, D_, 64);
        prm.x = (const bf16*)d_in[0]; prm.c = (const bf16*)d_in[11]; prm.w_mod = (const bf16*)d_in[12];
        rp.mem0 = (const bf16*)d_in[1];
        rp.wq = (const bf16*)d_in[2]; rp.wk = (const bf16*)d_in[3]; rp.wv = (const bf16*)d_in[4]; rp.wo = (const bf16*)d_in[5];
        cudaFuncSetAttribute(k_work, cudaFuncAttributeMaxDynamicSharedMemorySize, SMEM_BYTES);
        cudaFuncSetAttribute(k_rec, cudaFuncAttributeMaxDynamicSharedMemorySize, R_SMEM);
        cudaFuncSetAttribute(k_rec, cudaFuncAttributeNonPortableClusterSizeAllowed, 1);
        {
            cudaLaunchConfig_t cfg = {};
            cfg.gridDim = dim3(128); cfg.blockDim = dim3(384); cfg.dynamicSmemBytes = R_SMEM;
            cudaLaunchAttribute at[1];
            at[0].id = cudaLaunchAttributeClusterDimension; at[0].val.clusterDim.x = 16; at[0].val.clusterDim.y = 1; at[0].val.clusterDim.z = 1;
            cfg.attrs = at; cfg.numAttrs = 1;
            int n = 0;
            cudaOccupancyMaxActiveClusters(&n, k_rec, &cfg);
            rp.ncl = n < 4 ? 4 : (n > 8 ? 8 : n);
        }
        for (int i = 0; i < 13; i++) key[i] = d_in[i];
        key[13] = d_out;
        ready = true;
    }
    cudaStream_t st = cudaStreamPerThread;
    auto launch_rec = [&]() {
        cudaLaunchConfig_t cfg = {};
        cfg.gridDim = dim3(16 * rp.ncl); cfg.blockDim = dim3(384); cfg.dynamicSmemBytes = R_SMEM; cfg.stream = st;
        cudaLaunchAttribute at[1];
        at[0].id = cudaLaunchAttributeClusterDimension; at[0].val.clusterDim.x = 16; at[0].val.clusterDim.y = 1; at[0].val.clusterDim.z = 1;
        cfg.attrs = at; cfg.numAttrs = 1;
        cudaLaunchKernelEx(&cfg, k_rec, rp);
    };
    auto launch_work = [&](int qmask, int pdl) {
        prm.qmask = qmask;
        cudaLaunchConfig_t cfg = {};
        cfg.gridDim = dim3(132); cfg.blockDim = dim3(384); cfg.dynamicSmemBytes = SMEM_BYTES; cfg.stream = st;
        cudaLaunchAttribute at[1];
        at[0].id = cudaLaunchAttributeProgrammaticStreamSerialization; at[0].val.programmaticStreamSerializationAllowed = 1;
        cfg.attrs = at; cfg.numAttrs = pdl;
        cudaLaunchKernelEx(&cfg, k_work, prm);
    };
    launch_rec();
    launch_work(0xff, 1);
}
```

```cpp
#include <cuda_runtime.h>
#include <cuda_bf16.h>
#include <cuda.h>
#include <stdint.h>

typedef __nv_bfloat16 bf16;

constexpr int S_ = 2048, D_ = 512, H_ = 32, DH_ = 128, HD_ = 4096, NSEG = 64, DF_ = 1792;
constexpr int NRB = 16;
constexpr int OSPLIT = 4;

__device__ __align__(1024) bf16 g_h[S_ * D_];
__device__ __align__(1024) bf16 g_kv[S_ * 2 * HD_];
__device__ __align__(1024) bf16 g_kvm[NSEG * 8 * 2 * HD_];
__device__ __align__(1024) bf16 g_o[S_ * HD_];
#define FINE_RB_ 14
constexpr int FINE_RB = FINE_RB_;
constexpr int OSPLIT2 = 8;
constexpr int OP_ROWS = OSPLIT * S_ + OSPLIT2 * (NRB - FINE_RB) * 128;
__device__ __align__(1024) bf16 g_op[OP_ROWS * D_];
__device__ __align__(1024) bf16 g_x1[S_ * D_];
__device__ __align__(1024) bf16 g_h2[S_ * D_];
__device__ __align__(1024) bf16 g_act[S_ * DF_];
__device__ __align__(1024) bf16 g_mod[6 * D_];
__device__ uint32_t g_Fraw[131072 + 65536 + 2048];
#define g_F ((uint32_t*)(((uint64_t)g_Fraw + 0x7FFFFull) & ~0x7FFFFull))
constexpr int F_H = 0, F_MEM = 32, F_O = 64, F_OP = 96, F_H2 = 128, F_ACT = 160, F_MOD = 192, F_KV = 224, F_CLAIM = 256  ,
              F_SIDE = 512  , F_DONE = 576, F_TOTAL = 608;
__device__ __align__(128) unsigned int g_flags[F_TOTAL];
#define TR(j, i) do {} while (0)

__device__ __forceinline__ uint32_t smem_u32(const void* p) { return (uint32_t)__cvta_generic_to_shared(p); }
__device__ __forceinline__ uint32_t clk32() { uint32_t c; asm volatile("mov.u32 %0, %%clock;" : "=r"(c)); return c; }
__device__ __forceinline__ uint32_t mapa_u32(uint32_t addr, uint32_t rank) {
    uint32_t r; asm volatile("mapa.shared::cluster.u32 %0, %1, %2;" : "=r"(r) : "r"(addr), "r"(rank)); return r;
}
__device__ __forceinline__ void mbar_init(uint32_t bar, uint32_t cnt) {
    asm volatile("mbarrier.init.shared::cta.b64 [%0], %1;" :: "r"(bar), "r"(cnt) : "memory");
}
__device__ __forceinline__ void mbar_inval(uint32_t bar) {
    asm volatile("mbarrier.inval.shared::cta.b64 [%0];" :: "r"(bar) : "memory");
}
__device__ __forceinline__ void mbar_expect_tx(uint32_t bar, uint32_t bytes) {
    asm volatile("mbarrier.arrive.expect_tx.shared::cta.b64 _, [%0], %1;" :: "r"(bar), "r"(bytes) : "memory");
}
__device__ __forceinline__ void mbar_arrive(uint32_t bar) {
    asm volatile("mbarrier.arrive.shared::cta.b64 _, [%0];" :: "r"(bar) : "memory");
}
__device__ __forceinline__ bool mbar_try_wait(uint32_t bar, uint32_t parity) {
    uint32_t ok;
    asm volatile("{\n.reg .pred p;\nmbarrier.try_wait.parity.shared::cta.b64 p, [%1], %2;\nselp.u32 %0, 1, 0, p;\n}"
                 : "=r"(ok) : "r"(bar), "r"(parity) : "memory");
    return ok;
}
__device__ __forceinline__ bool mbar_try_wait_cluster(uint32_t bar, uint32_t parity) {
    uint32_t ok;
    asm volatile("{\n.reg .pred p;\nmbarrier.try_wait.parity.acquire.cluster.shared::cta.b64 p, [%1], %2;\nselp.u32 %0, 1, 0, p;\n}"
                 : "=r"(ok) : "r"(bar), "r"(parity) : "memory");
    return ok;
}
constexpr int SPIN_LIMIT = 1 << 18;
#define TIMEOUT(code, info) do {} while (0)
__device__ __forceinline__ void mbar_wait(uint32_t bar, uint32_t parity) {
    int g = 0;
#pragma unroll 1
    while (!mbar_try_wait(bar, parity)) { if (++g >= SPIN_LIMIT) { TIMEOUT(0, bar & 255); break; } }
}
__device__ __forceinline__ void mbar_wait_cluster(uint32_t bar, uint32_t parity) {
    int g = 0;
#pragma unroll 1
    while (!mbar_try_wait_cluster(bar, parity)) { if (++g >= SPIN_LIMIT) { TIMEOUT(1, bar & 255); break; } }
}
__device__ __forceinline__ void bar_sync(int id, int n) { asm volatile("bar.sync %0, %1;" :: "r"(id), "r"(n) : "memory"); }
__device__ __forceinline__ void bar_arrive(int id, int n) { asm volatile("bar.arrive %0, %1;" :: "r"(id), "r"(n) : "memory"); }
__device__ __forceinline__ void cluster_sync_all() {
    asm volatile("barrier.cluster.arrive.aligned;\nbarrier.cluster.wait.aligned;" ::: "memory");
}
__device__ __forceinline__ void st_async_v2(uint32_t addr, float a, float b, uint32_t bar) {
    asm volatile("st.async.weak.shared::cluster.mbarrier::complete_tx::bytes.v2.f32 [%0], {%1,%2}, [%3];"
                 :: "r"(addr), "f"(a), "f"(b), "r"(bar) : "memory");
}
__device__ __forceinline__ void st_async_v4(uint32_t addr, uint4 v, uint32_t bar) {
    asm volatile("st.async.weak.shared::cluster.mbarrier::complete_tx::bytes.v4.b32 [%0], {%1,%2,%3,%4}, [%5];"
                 :: "r"(addr), "r"(v.x), "r"(v.y), "r"(v.z), "r"(v.w), "r"(bar) : "memory");
}
__device__ __forceinline__ uint2 ldg_relaxed2(const uint2* p) {
    uint2 v;
    asm volatile("ld.relaxed.gpu.global.v2.b32 {%0,%1}, [%2];" : "=r"(v.x), "=r"(v.y) : "l"(p) : "memory");
    return v;
}
__device__ __forceinline__ void stg_relaxed2(uint2* p, uint2 v) {
    asm volatile("st.relaxed.gpu.global.v2.b32 [%0], {%1,%2};" :: "l"(p), "r"(v.x), "r"(v.y) : "memory");
}
__device__ __forceinline__ uint4 ldg_relaxed(const uint4* p) {
    uint4 v;
    asm volatile("ld.relaxed.gpu.global.v4.b32 {%0,%1,%2,%3}, [%4];" : "=r"(v.x), "=r"(v.y), "=r"(v.z), "=r"(v.w) : "l"(p) : "memory");
    return v;
}
__device__ __forceinline__ void stg_relaxed(uint4* p, uint4 v) {
    asm volatile("st.relaxed.gpu.global.v4.b32 [%0], {%1,%2,%3,%4};" :: "l"(p), "r"(v.x), "r"(v.y), "r"(v.z), "r"(v.w) : "memory");
}
__device__ __forceinline__ void stg_relaxed32(uint32_t* p, uint32_t v) {
    asm volatile("st.relaxed.gpu.global.b32 [%0], %1;" :: "l"(p), "r"(v) : "memory");
}
__device__ __forceinline__ uint32_t ldg_relaxed32(const uint32_t* p) {
    uint32_t v; asm volatile("ld.relaxed.gpu.global.b32 %0, [%1];" : "=r"(v) : "l"(p) : "memory"); return v;
}
__device__ __forceinline__ unsigned int ld_acquire(const unsigned int* p) {
    unsigned int v; asm volatile("ld.acquire.gpu.global.u32 %0, [%1];" : "=r"(v) : "l"(p) : "memory"); return v;
}
__device__ __forceinline__ void red_release(unsigned int* p, unsigned int v) {
    asm volatile("red.release.gpu.global.add.u32 [%0], %1;" :: "l"(p), "r"(v) : "memory");
}
__device__ __forceinline__ void wait_flag(int idx, unsigned int target) {
    const unsigned int* p = &g_flags[idx];
    int g = 0;
#pragma unroll 1
    while (ld_acquire(p) < target) { __nanosleep(20); if (++g >= 64 * SPIN_LIMIT) { TIMEOUT(2, idx); break; } }
}
__device__ __forceinline__ void cp_async16(uint32_t dst, const void* src) {
    asm volatile("cp.async.cg.shared.global [%0], [%1], 16;" :: "r"(dst), "l"(src) : "memory");
}
__device__ __forceinline__ void cp_async_commit() { asm volatile("cp.async.commit_group;" ::: "memory"); }
template <int N> __device__ __forceinline__ void cp_async_wait() { asm volatile("cp.async.wait_group %0;" :: "n"(N) : "memory"); }
__device__ __forceinline__ void ldsm4(uint32_t& r0, uint32_t& r1, uint32_t& r2, uint32_t& r3, uint32_t addr) {
    asm volatile("ldmatrix.sync.aligned.m8n8.x4.shared.b16 {%0,%1,%2,%3}, [%4];" : "=r"(r0), "=r"(r1), "=r"(r2), "=r"(r3) : "r"(addr) : "memory");
}
__device__ __forceinline__ void ldsm4t(uint32_t& r0, uint32_t& r1, uint32_t& r2, uint32_t& r3, uint32_t addr) {
    asm volatile("ldmatrix.sync.aligned.m8n8.x4.trans.shared.b16 {%0,%1,%2,%3}, [%4];" : "=r"(r0), "=r"(r1), "=r"(r2), "=r"(r3) : "r"(addr) : "memory");
}
__device__ __forceinline__ void ldsm2t(uint32_t& r0, uint32_t& r1, uint32_t addr) {
    asm volatile("ldmatrix.sync.aligned.m8n8.x2.trans.shared.b16 {%0,%1}, [%2];" : "=r"(r0), "=r"(r1) : "r"(addr) : "memory");
}
__device__ __forceinline__ void stsm4(uint32_t addr, uint32_t r0, uint32_t r1, uint32_t r2, uint32_t r3) {
    asm volatile("stmatrix.sync.aligned.m8n8.x4.shared.b16 [%0], {%1,%2,%3,%4};" :: "r"(addr), "r"(r0), "r"(r1), "r"(r2), "r"(r3) : "memory");
}
__device__ __forceinline__ void stsm2t(uint32_t addr, uint32_t r0, uint32_t r1) {
    asm volatile("stmatrix.sync.aligned.m8n8.x2.trans.shared.b16 [%0], {%1,%2};" :: "r"(addr), "r"(r0), "r"(r1) : "memory");
}
__device__ __forceinline__ void mma16816(float* d, uint32_t a0, uint32_t a1, uint32_t a2, uint32_t a3, uint32_t b0, uint32_t b1) {
    asm volatile("mma.sync.aligned.m16n8k16.row.col.f32.bf16.bf16.f32 {%0,%1,%2,%3}, {%4,%5,%6,%7}, {%8,%9}, {%0,%1,%2,%3};"
                 : "+f"(d[0]), "+f"(d[1]), "+f"(d[2]), "+f"(d[3]) : "r"(a0), "r"(a1), "r"(a2), "r"(a3), "r"(b0), "r"(b1));
}
__device__ __forceinline__ void mma1688(float* d, uint32_t a0, uint32_t a1, uint32_t b0) {
    asm volatile("mma.sync.aligned.m16n8k8.row.col.f32.bf16.bf16.f32 {%0,%1,%2,%3}, {%4,%5}, {%6}, {%0,%1,%2,%3};"
                 : "+f"(d[0]), "+f"(d[1]), "+f"(d[2]), "+f"(d[3]) : "r"(a0), "r"(a1), "r"(b0));
}
__device__ __forceinline__ void mma16816h(float* d, uint32_t a0, uint32_t a2, uint32_t b0, uint32_t b1) {
    asm volatile("{\n.reg .b32 ju, jv;\nmma.sync.aligned.m16n8k16.row.col.f32.bf16.bf16.f32 {%0,%1,%2,%3}, {%4,ju,%5,jv}, {%6,%7}, {%0,%1,%2,%3};\n}"
                 : "+f"(d[0]), "+f"(d[1]), "+f"(d[2]), "+f"(d[3]) : "r"(a0), "r"(a2), "r"(b0), "r"(b1));
}
__device__ __forceinline__ void mma1688h(float* d, uint32_t a0, uint32_t b0) {
    asm volatile("{\n.reg .b32 ju;\nmma.sync.aligned.m16n8k8.row.col.f32.bf16.bf16.f32 {%0,%1,%2,%3}, {%4,ju}, {%5}, {%0,%1,%2,%3};\n}"
                 : "+f"(d[0]), "+f"(d[1]), "+f"(d[2]), "+f"(d[3]) : "r"(a0), "r"(b0));
}
__device__ __forceinline__ uint32_t pack2(float lo, float hi) {
    uint32_t r; asm("cvt.rn.bf16x2.f32 %0, %1, %2;" : "=r"(r) : "f"(hi), "f"(lo)); return r;
}
__device__ __forceinline__ float bflo(uint32_t w) { return __uint_as_float(w << 16); }
__device__ __forceinline__ float bfhi(uint32_t w) { return __uint_as_float(w & 0xffff0000u); }
__device__ __forceinline__ float rbf(float x) { return __bfloat162float(__float2bfloat16_rn(x)); }
__device__ __forceinline__ float ex2(float x) { float y; asm("ex2.approx.ftz.f32 %0, %1;" : "=f"(y) : "f"(x)); return y; }
__device__ __forceinline__ void sts128(uint32_t addr, uint4 v) {
    asm volatile("st.shared.v4.b32 [%0], {%1,%2,%3,%4};" :: "r"(addr), "r"(v.x), "r"(v.y), "r"(v.z), "r"(v.w) : "memory");
}
__device__ __forceinline__ uint4 lds128(uint32_t addr) {
    uint4 v; asm volatile("ld.shared.v4.b32 {%0,%1,%2,%3}, [%4];" : "=r"(v.x), "=r"(v.y), "=r"(v.z), "=r"(v.w) : "r"(addr) : "memory"); return v;
}
__device__ __forceinline__ float2 lds64f(uint32_t addr) {
    float2 v; asm volatile("ld.shared.v2.f32 {%0,%1}, [%2];" : "=f"(v.x), "=f"(v.y) : "r"(addr) : "memory"); return v;
}
__device__ __forceinline__ float lds32f(uint32_t addr) {
    float v; asm volatile("ld.shared.f32 %0, [%1];" : "=f"(v) : "r"(addr) : "memory"); return v;
}
__device__ __forceinline__ uint32_t lds32(uint32_t addr) {
    uint32_t v; asm volatile("ld.shared.b32 %0, [%1];" : "=r"(v) : "r"(addr) : "memory"); return v;
}
__device__ __forceinline__ void sts32(uint32_t addr, uint32_t v) { asm volatile("st.shared.b32 [%0], %1;" :: "r"(addr), "r"(v) : "memory"); }
__device__ __forceinline__ void sts64f(uint32_t addr, float a, float b) { asm volatile("st.shared.v2.f32 [%0], {%1,%2};" :: "r"(addr), "f"(a), "f"(b) : "memory"); }

__device__ __forceinline__ void tma_load2d(uint32_t dst, const CUtensorMap* tm, int c0, int c1, uint32_t bar) {
    asm volatile("cp.async.bulk.tensor.2d.shared::cluster.global.mbarrier::complete_tx::bytes [%0], [%1, {%3, %4}], [%2];"
                 :: "r"(dst), "l"(tm), "r"(bar), "r"(c0), "r"(c1) : "memory");
}
__device__ __forceinline__ void tma_store2d(const CUtensorMap* tm, uint32_t src, int c0, int c1) {
    asm volatile("cp.async.bulk.tensor.2d.global.shared::cta.bulk_group [%0, {%2, %3}], [%1];"
                 :: "l"(tm), "r"(src), "r"(c0), "r"(c1) : "memory");
}
__device__ __forceinline__ void bulk_commit() { asm volatile("cp.async.bulk.commit_group;" ::: "memory"); }
__device__ __forceinline__ void bulk_wait0() { asm volatile("cp.async.bulk.wait_group 0;" ::: "memory"); }
__device__ __forceinline__ void fence_async_smem() { asm volatile("fence.proxy.async.shared::cta;" ::: "memory"); }
__device__ __forceinline__ void fence_async_all() { asm volatile("fence.proxy.async;" ::: "memory"); }

__device__ __forceinline__ void wg_fence() { asm volatile("wgmma.fence.sync.aligned;" ::: "memory"); }
__device__ __forceinline__ void wg_commit() { asm volatile("wgmma.commit_group.sync.aligned;" ::: "memory"); }
__device__ __forceinline__ void wg_wait0() { asm volatile("wgmma.wait_group.sync.aligned 0;" ::: "memory"); }
__device__ __forceinline__ uint64_t mkdesc(uint32_t saddr, uint32_t lbo, uint32_t sbo) {
    return (uint64_t)((saddr & 0x3FFFF) >> 4) | ((uint64_t)(lbo >> 4) << 16) | ((uint64_t)(sbo >> 4) << 32) | (1ull << 62);
}
#define ACC8(i) "+f"(d[i]), "+f"(d[i + 1]), "+f"(d[i + 2]), "+f"(d[i + 3]), "+f"(d[i + 4]), "+f"(d[i + 5]), "+f"(d[i + 6]), "+f"(d[i + 7])
__device__ __forceinline__ void wgmma_n256(float* d, uint64_t da, uint64_t db, int scale_d) {
    asm volatile(
        "{\n.reg .pred p;\nsetp.ne.b32 p, %130, 0;\n"
        "wgmma.mma_async.sync.aligned.m64n256k16.f32.bf16.bf16 "
        "{%0,%1,%2,%3,%4,%5,%6,%7,%8,%9,%10,%11,%12,%13,%14,%15,%16,%17,%18,%19,%20,%21,%22,%23,%24,%25,%26,%27,%28,%29,%30,%31,"
        "%32,%33,%34,%35,%36,%37,%38,%39,%40,%41,%42,%43,%44,%45,%46,%47,%48,%49,%50,%51,%52,%53,%54,%55,%56,%57,%58,%59,%60,%61,%62,%63,"
        "%64,%65,%66,%67,%68,%69,%70,%71,%72,%73,%74,%75,%76,%77,%78,%79,%80,%81,%82,%83,%84,%85,%86,%87,%88,%89,%90,%91,%92,%93,%94,%95,"
        "%96,%97,%98,%99,%100,%101,%102,%103,%104,%105,%106,%107,%108,%109,%110,%111,%112,%113,%114,%115,%116,%117,%118,%119,%120,%121,%122,%123,%124,%125,%126,%127}, "
        "%128, %129, p, 1, 1, 0, 1;\n}"
        : ACC8(0), ACC8(8), ACC8(16), ACC8(24), ACC8(32), ACC8(40), ACC8(48), ACC8(56),
          ACC8(64), ACC8(72), ACC8(80), ACC8(88), ACC8(96), ACC8(104), ACC8(112), ACC8(120)
        : "l"(da), "l"(db), "r"(scale_d));
}
__device__ __forceinline__ void wgmma_n128(float* d, uint64_t da, uint64_t db, int scale_d) {
    asm volatile(
        "{\n.reg .pred p;\nsetp.ne.b32 p, %66, 0;\n"
        "wgmma.mma_async.sync.aligned.m64n128k16.f32.bf16.bf16 "
        "{%0,%1,%2,%3,%4,%5,%6,%7,%8,%9,%10,%11,%12,%13,%14,%15,%16,%17,%18,%19,%20,%21,%22,%23,%24,%25,%26,%27,%28,%29,%30,%31,"
        "%32,%33,%34,%35,%36,%37,%38,%39,%40,%41,%42,%43,%44,%45,%46,%47,%48,%49,%50,%51,%52,%53,%54,%55,%56,%57,%58,%59,%60,%61,%62,%63}, "
        "%64, %65, p, 1, 1, 0, 1;\n}"
        : ACC8(0), ACC8(8), ACC8(16), ACC8(24), ACC8(32), ACC8(40), ACC8(48), ACC8(56)
        : "l"(da), "l"(db), "r"(scale_d));
}

__device__ __forceinline__ void wgmma_n64(float* d, uint64_t da, uint64_t db) {
    asm volatile(
        "wgmma.mma_async.sync.aligned.m64n64k16.f32.bf16.bf16 "
        "{%0,%1,%2,%3,%4,%5,%6,%7,%8,%9,%10,%11,%12,%13,%14,%15,%16,%17,%18,%19,%20,%21,%22,%23,%24,%25,%26,%27,%28,%29,%30,%31}, "
        "%32, %33, 1, 1, 1, 0, 1;"
        : ACC8(0), ACC8(8), ACC8(16), ACC8(24)
        : "l"(da), "l"(db));
}
__device__ __forceinline__ void wgmma_n8_ta(float* d, uint64_t da, uint64_t db, int scale_d) {
    asm volatile(
        "{\n.reg .pred p;\nsetp.ne.b32 p, %6, 0;\n"
        "wgmma.mma_async.sync.aligned.m64n8k16.f32.bf16.bf16 {%0,%1,%2,%3}, %4, %5, p, 1, 1, 1, 0;\n}"
        : "+f"(d[0]), "+f"(d[1]), "+f"(d[2]), "+f"(d[3]) : "l"(da), "l"(db), "r"(scale_d));
}

__device__ __forceinline__ uint32_t hadd2(uint32_t a, uint32_t b) { uint32_t r; asm("add.rn.bf16x2 %0, %1, %2;" : "=r"(r) : "r"(a), "r"(b)); return r; }
__device__ __forceinline__ uint32_t hsub2(uint32_t a, uint32_t b) { uint32_t r; asm("sub.rn.bf16x2 %0, %1, %2;" : "=r"(r) : "r"(a), "r"(b)); return r; }
__device__ __forceinline__ uint32_t hmul2(uint32_t a, uint32_t b) { uint32_t r; asm("mul.rn.bf16x2 %0, %1, %2;" : "=r"(r) : "r"(a), "r"(b)); return r; }
__device__ __forceinline__ void load_mod8(const bf16* m, int lane, uint32_t* v) {
    const uint4 a = __ldcg((const uint4*)m + lane), b = __ldcg((const uint4*)m + 32 + lane);
    v[0] = a.x; v[1] = a.y; v[2] = a.z; v[3] = a.w; v[4] = b.x; v[5] = b.y; v[6] = b.z; v[7] = b.w;
}
__device__ __forceinline__ void ln_stats(const uint32_t* x, uint32_t& mu2, float& rden) {
    float s = 0.f;
#pragma unroll
    for (int i = 0; i < 8; i++) s += bflo(x[i]) + bfhi(x[i]);
#pragma unroll
    for (int o = 16; o > 0; o >>= 1) s += __shfl_xor_sync(~0u, s, o);
    const float mean = s * (1.f / D_);
    float q = 0.f;
#pragma unroll
    for (int i = 0; i < 8; i++) { const float d0 = bflo(x[i]) - mean, d1 = bfhi(x[i]) - mean; q = fmaf(d0, d0, q); q = fmaf(d1, d1, q); }
#pragma unroll
    for (int o = 16; o > 0; o >>= 1) q += __shfl_xor_sync(~0u, q, o);
    mu2 = pack2(mean, mean);
    rden = __frcp_rn(rbf(__fsqrt_rn(rbf(rbf(q * (1.f / D_)) + 1e-5f))));
}
__device__ __forceinline__ void ln_apply(const uint32_t* x, uint32_t mu2, float rden, const uint32_t* c1, const uint32_t* sm, uint32_t* r) {
#pragma unroll
    for (int i = 0; i < 8; i++) {
        const uint32_t d = hsub2(x[i], mu2);
        r[i] = hadd2(hmul2(pack2(bflo(d) * rden, bfhi(d) * rden), c1[i]), sm[i]);
    }
}

struct __align__(64) Params {
    CUtensorMap tm_h, tm_kv, tm_kvm, tm_o, tm_op, tm_h2, tm_act, tm_x1, tm_out;
    CUtensorMap tm_wq, tm_wk, tm_wv, tm_wo, tm_wg, tm_wu, tm_wd;
    const bf16 *x, *c, *w_mod;
    int qmask;
};

constexpr int R_NST = 3;
constexpr uint32_t R_WV = 0, R_MEM = 65536, R_KX = 73728, R_VX = R_KX + R_NST * 4096,
                   R_KMS = R_VX + R_NST * 4096  , R_VMS = R_KMS + 1024,
                   R_QS = R_KMS + 4096, R_OS = R_QS + 1024, R_SX = R_OS + 1024, R_BAR = R_SX + 2560,
                   R_RS = 107520  , R_VP = R_RS + 8192  ,
                   R_STG = R_VP + 8192  , R_SMEM = R_STG + 98304;
static_assert((R_KMS & 4095) == 0, "smem");
static_assert(R_BAR + 64 <= R_RS, "smem");
constexpr uint32_t RB_SX = R_BAR, RB_V = R_BAR + 8, RB_E = R_BAR + 16, RB_A = R_BAR + 24, RB_ROLE = R_BAR + 32, RB_A1 = R_BAR + 40;
constexpr int W_NST = 3;
constexpr uint32_t W_STAGE = 49152, W_STG = W_NST * W_STAGE, W_END = W_STG + 65536;
constexpr uint32_t SM_BAR = W_END;
constexpr uint32_t SMEM_BYTES = W_END + 1024 + 2048;
constexpr uint32_t B_FULL = 0, B_EMPTY = 32, B_STGFREE = 64, B_REQ = 80, B_RSP = 88, B_NEXT = 96, B_RING = 128;
#define PICK_AHEAD 3

constexpr int NB_X = 11  , NB_Y = 1, NB_M = 5, NB_K = 5, NB_B = 2, NB_C = 3, NB_D = 4, NB_W0 = 6  , NB_ST = 9  ;

__device__ __forceinline__ int pos_of_d(int d) {
    const int rem = d & 31;
    return (d & ~31) + ((rem & 7) >> 1) * 8 + (rem & 1) * 4 + (rem >> 3);
}

#define PROF(i) do {} while (0)
#define PROFG(i) do {} while (0)
#define OPAQUE(x) asm volatile("" : "+r"(x))
#define FENCE_SCHED(x) do { if ((x) == 0u) asm volatile("trap;"); } while (0)
#define VK0_ 4
constexpr int VK0 = VK0_;
constexpr int NOFF = 8;
#define VDELAY -1
#define POLL_GAP 110

struct RecParams { const bf16 *mem0, *wq, *wk, *wv, *wo; int ncl; };

__device__ __forceinline__ void rec_qk(const RecParams& p, const uint32_t sb, const int cta, const int warp, int lane, const int sel) {
    const int crank = cta & 15, cl = cta >> 4, rank = cta & 1;
    const int kh = warp >> 2, aa = warp & 3;
    uint32_t wa[2][16][4];
    const uint32_t stg = sb + R_STG + kh * 32768;
    {
        const int t128 = aa * 32 + lane;
        const int row = (lane >> 4) * 8 + (lane & 7);
        const int ch = t128 & 7;
        const size_t goff = (size_t)kh * 256 * HD_ + cta * 64 + ch * 8;
#pragma unroll 4
        for (int dd = 0; dd < 16; dd++) {
            const int d = dd * 16 + (t128 >> 3), pp = pos_of_d(d);
            cp_async16(sb + R_WV + kh * 32768 + pp * 128 + ((ch ^ (pp & 7)) << 4), p.wv + goff + (size_t)d * HD_);
        }
        cp_async_commit();
#pragma unroll 4
        for (int dd = 0; dd < 16; dd++) {
            const int d = dd * 16 + (t128 >> 3), pp = pos_of_d(d);
            cp_async16(stg + pp * 128 + ((ch ^ (pp & 7)) << 4), p.wq + goff + (size_t)d * HD_);
        }
        cp_async_commit();
        {
            const int i0 = (warp * 32 + lane) * 16, tok = i0 >> 9;
            const uint4 m0 = __ldg((const uint4*)(p.mem0 + i0)), m1 = __ldg((const uint4*)(p.mem0 + i0 + 8));
            const uint32_t mw[8] = {m0.x, m0.y, m0.z, m0.w, m1.x, m1.y, m1.z, m1.w};
#pragma unroll
            for (int e = 0; e < 16; e++) {
                const int pp = pos_of_d((i0 & 511) + e);
                const unsigned short v = (unsigned short)(mw[e >> 1] >> ((e & 1) * 16));
                asm volatile("st.shared.u16 [%0], %1;" :: "r"(sb + R_MEM + (pp >> 3) * 128 + tok * 16 + (pp & 7) * 2), "h"(v) : "memory");
            }
        }
        cp_async_wait<1>();
        bar_sync(NB_W0 + kh, 128);
        const uint32_t fv = row * 128 + (((2 * aa + ((lane >> 3) & 1)) ^ (row & 7)) << 4);
#pragma unroll
        for (int ks = 0; ks < 16; ks++) ldsm4t(wa[0][ks][0], wa[0][ks][1], wa[0][ks][2], wa[0][ks][3], sb + R_WV + kh * 32768 + fv + ks * 2048);
        bar_sync(NB_W0 + kh, 128);
#pragma unroll
        for (int ks = 0; ks < 16; ks++)
            sts128(sb + R_WV + kh * 32768 + (aa * 16 + ks) * 512 + lane * 16, make_uint4(wa[0][ks][0], wa[0][ks][1], wa[0][ks][2], wa[0][ks][3]));
        const uint32_t fo = stg + row * 128 + (((4 * (aa & 1) + ((lane >> 3) & 1)) ^ (row & 7)) << 4);
#pragma unroll 1
        for (int m = 0; m < 2; m++) {
            cp_async_wait<0>();
            bar_sync(NB_W0 + kh, 128);
            if ((aa >> 1) == m) {
#pragma unroll
                for (int ks = 0; ks < 16; ks++) {
                    ldsm4t(wa[0][ks][0], wa[0][ks][1], wa[0][ks][2], wa[0][ks][3], fo + ks * 2048);
                    ldsm4t(wa[1][ks][0], wa[1][ks][1], wa[1][ks][2], wa[1][ks][3], (fo ^ 32) + ks * 2048);
                }
            }
            bar_sync(NB_W0 + kh, 128);
            if (m == 0) {
#pragma unroll 4
                for (int dd = 0; dd < 16; dd++) {
                    const int d = dd * 16 + (t128 >> 3), pp = pos_of_d(d);
                    cp_async16(stg + pp * 128 + ((ch ^ (pp & 7)) << 4), p.wk + goff + (size_t)d * HD_);
                }
                cp_async_commit();
            }
        }
    }
    const uint32_t tab = stg + (aa * 32 + lane) * 16;
    {
        const uint32_t l7 = lane & 7, l8 = lane >> 3, g = lane >> 2, t = lane & 3;
        const uint32_t t0 = l7 * 128 + ((l8 ^ l7) << 4);
        const uint32_t tq = l7 * 128 + (((l8 >> 1) ^ l7) << 4);
        const uint32_t bq = warp >> 1, tp = warp & 1;
        uint4 v;
        v.x = sb + (aa < 2 ? R_QS : R_KMS) + l7 * 128 + (((4 * (aa & 1) + 2 * kh + (l8 & 1)) ^ l7) << 4);
        v.y = sb + R_QS + tq;
        v.z = sb + (warp == 0 ? R_KMS : R_KX + (warp - 1) * 1024) + t0;
        v.w = mapa_u32(sb + R_SX + (rank * 5 + warp) * 256 + lane * 8, crank ^ 1);
        sts128(tab, v);
        sts128(tab + 2048, make_uint4(sb + lane * 16 + R_MEM + kh * 4096, sb + lane * 16 + R_WV + warp * 8192,
                                      sb + lane * 16 + R_VP + warp * 512, sb + lane * 16 + R_VP + 4096 + (warp ^ 4) * 512));
        const uint32_t src = (l8 >> 1) * 8 + l7;
        const uint32_t L = bq * 8 + 2 * tp + (l8 & 1);
        const uint32_t d0 = (crank + ((t >> 1) | (g & 6))) & 15;
        v.x = sb + R_RS + src * 512 + ((L ^ (src & 7)) << 4);
        v.y = mapa_u32(sb + R_MEM + (crank * 4 + bq) * 128 + (4 * tp + 2 * (t & 1) + (g & 1)) * 16, d0);
        v.z = mapa_u32(sb + ((crank & 2) ? RB_A1 : RB_A), d0);
        v.w = lane;
        sts128(tab + 4096, v);
        const uint64_t wr = (uint64_t)(g_F + ((crank * 2 + ((crank ^ (crank >> 3) ^ sel) & 1)) * 1024 + warp * 128 + cl * 32 + lane));
        sts128(tab + 6144, make_uint4((uint32_t)wr, (uint32_t)(wr >> 32), (uint32_t)((((cl + 1) & 3) - cl) * 128), (uint32_t)((((cl + 2) & 3) - cl) * 128)));
        sts32(tab + 8192, (uint32_t)((((cl + 3) & 3) - cl) * 128));
#pragma unroll
        for (int i = 0; i < NOFF; i++)
            sts128(tab + 10240 + i * 2048, make_uint4(wa[i & 1][i >> 1][0], wa[i & 1][i >> 1][1], wa[i & 1][i >> 1][2], wa[i & 1][i >> 1][3]));
    }
    bar_sync(NB_D, 384);
    uint32_t slot_off = 0;
    const uint32_t slot_inc = warp == 0 ? 2048 : 4096, slot_last = warp == 0 ? 2048 : (R_NST - 1) * 4096;
    const uint32_t sx_bar_rem = (sb + RB_SX) ^ (1u << 24);
    uint4 tb = lds128(tab + 2048);
#pragma unroll 1
    for (int s = 0; s < NSEG; s++) {
        if (s > 0) mbar_wait(sb + RB_A, (s - 1) & 1);
        if (warp == 0) { PROF(0); PROFG(13); }
        uint4 ta;
        const uint32_t km_tog = aa >= 2 ? (s & 1) * 2048 : 0;
        {
            float acc[5][4];
#pragma unroll
            for (int c = 0; c < 5; c++) { acc[c][0] = acc[c][1] = acc[c][2] = acc[c][3] = 0.f; }
            uint32_t b[8][4];
            uint4 av[16];
            static_assert(VK0 == 4, "order below assumes the V/O warps cover slices 0,1");
            ldsm4(b[0][0], b[0][1], b[0][2], b[0][3], tb.x);
            ldsm4(b[1][0], b[1][1], b[1][2], b[1][3], tb.x + 512);
            ldsm4(b[4][0], b[4][1], b[4][2], b[4][3], tb.x + 2048);
            ldsm4(b[5][0], b[5][1], b[5][2], b[5][3], tb.x + 2560);
#pragma unroll
            for (int kk = 0; kk < 8; kk++) {
                const int k2 = kk < 2 ? kk : (kk < 4 ? kk + 2 : (kk < 6 ? kk - 2 : kk));
                if (kk == 4) {
                    if (s > 0) mbar_wait(sb + RB_A1, (s - 1) & 1);
                    ldsm4(b[2][0], b[2][1], b[2][2], b[2][3], tb.x + 1024);
                    ldsm4(b[3][0], b[3][1], b[3][2], b[3][3], tb.x + 1536);
                    ldsm4(b[6][0], b[6][1], b[6][2], b[6][3], tb.x + 3072);
                    ldsm4(b[7][0], b[7][1], b[7][2], b[7][3], tb.x + 3584);
#pragma unroll
                    for (int i = 12; i < 16; i++) av[i] = lds128(tb.y + i * 512);
                    ta = lds128(tab);
                }
                mma16816(acc[0], wa[0][2 * k2][0], wa[0][2 * k2][1], wa[0][2 * k2][2], wa[0][2 * k2][3], b[k2][0], b[k2][1]);
                mma16816(acc[1], wa[1][2 * k2][0], wa[1][2 * k2][1], wa[1][2 * k2][2], wa[1][2 * k2][3], b[k2][0], b[k2][1]);
                mma16816(acc[3], wa[0][2 * k2 + 1][0], wa[0][2 * k2 + 1][1], wa[0][2 * k2 + 1][2], wa[0][2 * k2 + 1][3], b[k2][2], b[k2][3]);
                mma16816(acc[4], wa[1][2 * k2 + 1][0], wa[1][2 * k2 + 1][1], wa[1][2 * k2 + 1][2], wa[1][2 * k2 + 1][3], b[k2][2], b[k2][3]);
                if (2 * k2 >= VK0) {
                    mma16816(acc[2], av[2 * k2].x, av[2 * k2].y, av[2 * k2].z, av[2 * k2].w, b[k2][0], b[k2][1]);
                    mma16816(acc[2], av[2 * k2 + 1].x, av[2 * k2 + 1].y, av[2 * k2 + 1].z, av[2 * k2 + 1].w, b[k2][2], b[k2][3]);
                }
                if (kk == 0) { av[8] = lds128(tb.y + 8 * 512); av[9] = lds128(tb.y + 9 * 512); }
                if (kk == 1) { av[10] = lds128(tb.y + 10 * 512); av[11] = lds128(tb.y + 11 * 512); }
                if (kk == 2) { av[4] = lds128(tb.y + 4 * 512); av[5] = lds128(tb.y + 5 * 512); }
                if (kk == 3) { av[6] = lds128(tb.y + 6 * 512); av[7] = lds128(tb.y + 7 * 512); }
            }
#pragma unroll
            for (int i = 0; i < 4; i++) { acc[0][i] += acc[3][i]; acc[1][i] += acc[4][i]; }
            const float g0 = kh ? acc[0][0] : acc[1][0], g1 = kh ? acc[0][1] : acc[1][1], g2 = kh ? acc[0][2] : acc[1][2], g3 = kh ? acc[0][3] : acc[1][3];
            sts128(tb.w, make_uint4(__float_as_uint(g0), __float_as_uint(g1), __float_as_uint(g2), __float_as_uint(g3)));
            const float k0 = kh ? acc[1][0] : acc[0][0], k1 = kh ? acc[1][1] : acc[0][1], k2_ = kh ? acc[1][2] : acc[0][2], k3 = kh ? acc[1][3] : acc[0][3];
            if (warp == 0) PROF(1);
            bar_sync(NB_X + aa, 64);
            const uint4 o = lds128(tb.z + 4096);
            stsm2t(ta.x ^ km_tog, pack2(k0 + __uint_as_float(o.x), k1 + __uint_as_float(o.y)), pack2(k2_ + __uint_as_float(o.z), k3 + __uint_as_float(o.w)));
            sts128(tb.z, make_uint4(__float_as_uint(acc[2][0]), __float_as_uint(acc[2][1]), __float_as_uint(acc[2][2]), __float_as_uint(acc[2][3])));
        }
        const uint32_t kb = ta.z + slot_off;
        if (warp == 0) PROF(14);
        bar_sync(NB_B, 256);
        if (warp < 5) {
            uint32_t q[16], k0, k1, k2, k3, k4, k5, k6, k7;
            float sa[4] = {0.f, 0.f, 0.f, 0.f}, sc[4] = {0.f, 0.f, 0.f, 0.f};
            ldsm4(q[0], q[1], q[2], q[3], ta.y);
            ldsm4(k0, k1, k2, k3, kb);
            ldsm4(q[4], q[5], q[6], q[7], ta.y ^ 32);
            ldsm4(q[8], q[9], q[10], q[11], ta.y ^ 64);
            ldsm4(k4, k5, k6, k7, kb ^ 64);
            ldsm4(q[12], q[13], q[14], q[15], ta.y ^ 96);
            mma16816(sa, q[0], q[1], q[2], q[3], k0, k1);
            bar_arrive(NB_Y, 288);
            mma16816(sc, q[4], q[5], q[6], q[7], k2, k3);
            mma16816(sa, q[8], q[9], q[10], q[11], k4, k5);
            mma16816(sc, q[12], q[13], q[14], q[15], k6, k7);
            const float scl = 0.08838834764831845f * 1.4426950408889634f;
            const float r0 = (sa[0] + sc[0]) * scl, r1 = (sa[1] + sc[1]) * scl;
            if (s != NSEG - 1) {
                st_async_v2(ta.w, r0, r1, sx_bar_rem);
                st_async_v2(ta.w ^ (1u << 24), r0, r1, sx_bar_rem ^ (1u << 24));
            }
            if (warp == 0) PROF(2);
        } else if (s > 0 && warp == 7 && lane == 0) {
            mbar_expect_tx(sb + RB_A, 4096);
            mbar_expect_tx(sb + RB_A1, 4096);
        } else if (s > 0 && (s & 3) == 0 && warp == 6) {
            bar_sync(NB_K, 160);
            if (lane == 0) red_release(&g_flags[F_MEM + (s >> 2) - 1], 1);
            __syncwarp();
        }
        if (s == NSEG - 1) {
            const uint4 td = lds128(tab + 6144);
            stg_relaxed32((uint32_t*)(((uint64_t)td.y << 32) | (td.x ^ 0x21000)), 0u);
            break;
        }
        slot_off = slot_off == slot_last ? 0 : slot_off + slot_inc;
        const uint4 tc = lds128(tab + 4096), td = lds128(tab + 6144);
        const uint32_t te = lds32(tab + 8192);
        uint32_t* wr = (uint32_t*)(((uint64_t)td.y << 32) | (td.x ^ ((s & 1) * 0x21000)));
        const uint32_t* r1p = (const uint32_t*)((const char*)wr + (int)td.z);
        const uint32_t* r2p = (const uint32_t*)((const char*)wr + (int)td.w);
        const uint32_t* r3p = (const uint32_t*)((const char*)wr + (int)te);
        const uint32_t tag = ((s >> 1) + 1) & 1;
        mbar_wait(sb + RB_E, s & 1);
        if (warp == 0) PROF(7);
        {
            uint32_t a0, a1, a2, a3, a4, a5, a6, a7;
            ldsm4t(a0, a1, a2, a3, tc.x);
            ldsm4t(a4, a5, a6, a7, tc.x ^ 64);
            const uint32_t one = 0x3F803F80u;
            float d0_[4] = {0.f, 0.f, 0.f, 0.f}, d1_[4] = {0.f, 0.f, 0.f, 0.f};
            mma16816(d0_, a0, a1, a2, a3, one, one);
            mma16816(d1_, a4, a5, a6, a7, one, one);
            const bool t1 = tc.w & 1, t2 = tc.w & 2;
            const float x = t2 ? (t1 ? d1_[2] : d1_[0]) : (t1 ? d0_[2] : d0_[0]);
            const uint32_t own = (__float_as_uint(x) & ~1u) | tag;
            stg_relaxed32(wr, own);
            const uint32_t tq = clk32();
            if (warp == 0) PROF(8);
            PROFG(16 + warp);
            while ((int)(clk32() - tq) < POLL_GAP) {}
            uint32_t f1 = ldg_relaxed32(r1p), f2 = ldg_relaxed32(r2p), f3 = ldg_relaxed32(r3p);
#pragma unroll
            for (int i = 0; i < NOFF; i++) {
                const uint4 f0 = lds128(tab + 10240 + i * 2048);
                wa[i & 1][i >> 1][0] = f0.x; wa[i & 1][i >> 1][1] = f0.y; wa[i & 1][i >> 1][2] = f0.z; wa[i & 1][i >> 1][3] = f0.w;
            }
            tb = lds128(tab + 2048);
            int gg = 0;
#pragma unroll 1
            while (!__all_sync(~0u, (((f1 ^ tag) | (f2 ^ tag) | (f3 ^ tag)) & 1) == 0)) {
                f1 = ldg_relaxed32(r1p); f2 = ldg_relaxed32(r2p); f3 = ldg_relaxed32(r3p);
                if (++gg > 16 * SPIN_LIMIT) { TIMEOUT(3, s); break; }
            }
            if (warp == 0) PROF(9);
            const float v = (__uint_as_float(own) + __uint_as_float(f2)) + (__uint_as_float(f1) + __uint_as_float(f3));
            const bool b8 = tc.w & 8, b16 = tc.w & 16;
            const float recv = __shfl_xor_sync(~0u, v, 8);
            const uint32_t word = b8 ? pack2(recv, v) : pack2(v, recv);
            const uint32_t oth = __shfl_xor_sync(~0u, word, 16);
            const uint32_t wl = b16 ? oth : word, wh = b16 ? word : oth;
            const uint32_t p0 = __shfl_xor_sync(~0u, wl, 2), p1 = __shfl_xor_sync(~0u, wh, 2);
            const uint4 item = t2 ? make_uint4(p0, p1, wl, wh) : make_uint4(wl, wh, p0, p1);
            st_async_v4(tc.y, item, tc.z);
            st_async_v4(tc.y ^ (8u << 24), item, tc.z ^ (8u << 24));
            if (tc.w == 0 && warp == 7) mbar_expect_tx(sb + RB_E, 8192);
            if (warp == 0) PROF(10);
            PROF(40 + warp);
        }
        bar_sync(NB_D, 384);
    }
}

__device__ __forceinline__ void rec_load_kv(uint32_t sb, int col0, int s, uint32_t slot_off, int t128) {
    const int row = t128 >> 2, c2 = (t128 & 3) * 2;
    const bf16* src = g_kv + ((size_t)(s * 32 + row) * (2 * HD_) + col0 + c2 * 8);
    const uint32_t d0 = sb + R_KX + slot_off + row * 128 + ((c2 ^ (row & 7)) << 4);
    cp_async16(d0, src);
    cp_async16(d0 ^ 16, src + 8);
    cp_async16(d0 + (R_VX - R_KX), src + HD_);
    cp_async16((d0 ^ 16) + (R_VX - R_KX), src + HD_ + 8);
}

__device__ __forceinline__ void rec_store_kvm(uint32_t sb, int col0, int s, int w, int lane) {
    const int tok = (w & 1) * 4 + (lane >> 3);
    const uint4 v = lds128(sb + R_KMS + (s & 1) * 2048 + (w >> 1) * 1024 + tok * 128 + (((lane & 7) ^ tok) << 4));
    *(uint4*)(g_kvm + ((s * 8 + tok) * (2 * HD_) + (w >> 1) * HD_ + col0 + (lane & 7) * 8)) = v;
}

__device__ __forceinline__ void rec_vo(const RecParams& p, const uint32_t sb, const int cta, const int warp, int lane) {
    const int w = warp - 8, crank = cta & 15;
    const int col0 = cta * 64;
    uint32_t wo[8][4][4];
    {
        const int t128 = w * 32 + lane;
        const bf16* Wo = p.wo + (size_t)col0 * D_;
        const uint32_t stg = sb + R_STG + 2 * 32768;
#pragma unroll
        for (int half = 0; half < 2; half++) {
#pragma unroll 4
            for (int i = t128; i < 2048; i += 128) {
                const int e = i >> 6, ch = i & 63;
                cp_async16(stg + e * 1024 + ((ch ^ (e & 7)) << 4), Wo + (size_t)(half * 32 + e) * D_ + ch * 8);
            }
            cp_async_commit();
            cp_async_wait<0>();
            bar_sync(NB_W0 + 2, 128);
#pragma unroll
            for (int j = 0; j < 8; j++)
#pragma unroll
                for (int kk = 0; kk < 2; kk++) {
                    const int e = kk * 16 + (lane >> 4) * 8 + (lane & 7);
                    const int ch = (w * 8 + j) * 2 + ((lane >> 3) & 1);
                    ldsm4t(wo[j][half * 2 + kk][0], wo[j][half * 2 + kk][1], wo[j][half * 2 + kk][2], wo[j][half * 2 + kk][3],
                           stg + e * 1024 + ((ch ^ (e & 7)) << 4));
                }
            bar_sync(NB_W0 + 2, 128);
        }
        if (lane == 0) wait_flag(F_KV + 0, 64);
        __syncwarp();
        rec_load_kv(sb, col0, 0, 0, t128); cp_async_commit();
        rec_load_kv(sb, col0, 1, 4096, t128); cp_async_commit();
        cp_async_wait<1>();
    }
    const uint32_t tab = sb + R_STG + 2 * 32768 + (w * 32 + lane) * 16;
    {
        const uint32_t l7 = lane & 7, l8 = lane >> 3, g = lane >> 2;
        uint4 v;
        v.x = sb + R_VX + ((l8 & 1) * 8 + l7) * 128 + (((2 * w + (l8 >> 1)) ^ l7) << 4);
        v.y = sb + R_OS + g * 128 + (((2 * w) ^ g) << 4) + (lane & 3) * 4;
        v.z = sb + R_VMS + l7 * 128 + (((2 * w + (l8 & 1)) ^ l7) << 4);
        v.w = sb + R_OS + l7 * 128 + ((l8 ^ l7) << 4);
        sts128(tab, v);
        v.x = mapa_u32(sb + R_RS + crank * 512 + ((lane ^ (crank & 7)) << 4), w * 4);
        v.y = mapa_u32(sb + RB_E, w * 4);
        v.z = sb + R_VP + w * 512 + lane * 16;
        v.w = sb + R_SX + lane * 8;
        sts128(tab + 2048, v);
#pragma unroll
        for (int i = 0; i < 8; i++) sts128(tab + 4096 + i * 2048, make_uint4(wo[i][0][0], wo[i][0][1], wo[i][0][2], wo[i][0][3]));
        const int tok = (w & 1) * 4 + (lane >> 3), row = (w * 32 + lane) >> 2, c2 = (lane & 3) * 2;
        const uint64_t kd = (uint64_t)(g_kvm + (tok * (2 * HD_) + (w >> 1) * HD_ + col0 + (lane & 7) * 8));
        const uint64_t ks = (uint64_t)(g_kv + ((size_t)row * (2 * HD_) + col0 + c2 * 8));
        sts128(tab + 20480, make_uint4((uint32_t)kd, (uint32_t)(kd >> 32), (uint32_t)ks, (uint32_t)(ks >> 32)));
        sts128(tab + 22528, make_uint4(sb + R_KMS + (w >> 1) * 1024 + tok * 128 + (((lane & 7) ^ tok) << 4),
                                       sb + R_KX + row * 128 + ((c2 ^ (row & 7)) << 4), lane, 0));
    }
    bar_sync(NB_D, 384);
    const uint32_t lane16 = lds32(tab + 2048 + 8) - R_VP - w * 512;
    uint4 av[2 * VK0];
#pragma unroll
    for (int i = 0; i < 2 * VK0; i++) av[i] = lds128(lane16 + R_WV + (i / VK0) * 32768 + (w * 16 + i % VK0) * 512);
    uint32_t slot_off = 0;
#pragma unroll 1
    for (int s = 0; s < NSEG; s++) {
        if (s > 0) {
            mbar_wait(sb + RB_A, (s - 1) & 1);
            const uint4 tp = lds128(tab + 20480), tq = lds128(tab + 22528);
            const uint4 kvm = lds128(tq.x + ((s - 1) & 1) * 2048);
            *(uint4*)((((uint64_t)tp.y << 32) | tp.x) + (uint64_t)(s - 1) * (8 * 2 * HD_ * 2)) = kvm;
            if ((s & 3) == 0) bar_arrive(NB_K, 160);
            if (s + 1 < NSEG - 1) {
                if (((s + 1) & 3) == 0) { if (tq.z == 0) wait_flag(F_KV + ((s + 1) >> 2), 64); __syncwarp(); }
                const char* src = (const char*)((((uint64_t)tp.w << 32) | tp.z) + (uint64_t)(s + 1) * (32 * 2 * HD_ * 2));
                const uint32_t d0 = tq.y + (slot_off == (R_NST - 1) * 4096 ? 0 : slot_off + 4096);
                cp_async16(d0, src);
                cp_async16(d0 ^ 16, src + 16);
                cp_async16(d0 + (R_VX - R_KX), src + HD_ * 2);
                cp_async16((d0 ^ 16) + (R_VX - R_KX), src + HD_ * 2 + 16);
            }
            cp_async_commit();
        }
        bar_sync(NB_Y, 288);
        uint32_t vb0, vb1;
        {
            float va[4] = {0.f, 0.f, 0.f, 0.f}, vc[4] = {0.f, 0.f, 0.f, 0.f};
            uint32_t bb[VK0][4];
#pragma unroll
            for (int k2 = 0; k2 < VK0; k2++) ldsm4(bb[k2][0], bb[k2][1], bb[k2][2], bb[k2][3], lane16 + R_MEM + (k2 / (VK0 / 2)) * 4096 + (k2 % (VK0 / 2)) * 512);
#pragma unroll
            for (int k2 = 0; k2 < VK0; k2++) {
                mma16816(va, av[2 * k2].x, av[2 * k2].y, av[2 * k2].z, av[2 * k2].w, bb[k2][0], bb[k2][1]);
                mma16816(vc, av[2 * k2 + 1].x, av[2 * k2 + 1].y, av[2 * k2 + 1].z, av[2 * k2 + 1].w, bb[k2][2], bb[k2][3]);
            }
            const uint4 a = lds128(lane16 + R_VP + w * 512), b = lds128(lane16 + R_VP + 2048 + w * 512);
            vb0 = pack2((va[0] + vc[0]) + (__uint_as_float(a.x) + __uint_as_float(b.x)), (va[1] + vc[1]) + (__uint_as_float(a.y) + __uint_as_float(b.y)));
            vb1 = pack2((va[2] + vc[2]) + (__uint_as_float(a.z) + __uint_as_float(b.z)), (va[3] + vc[3]) + (__uint_as_float(a.w) + __uint_as_float(b.w)));
        }
        const uint4 ta = lds128(tab), tb = lds128(tab + 2048);
        uint32_t vx[8];
        ldsm4t(vx[0], vx[1], vx[2], vx[3], ta.x + slot_off);
        ldsm4t(vx[4], vx[5], vx[6], vx[7], ta.x + slot_off + 2048);
#pragma unroll
        for (int i = 0; i < 4; i++) {
            const uint4 f0 = lds128(tab + 4096 + i * 2048);
            wo[i][0][0] = f0.x; wo[i][0][1] = f0.y; wo[i][0][2] = f0.z; wo[i][0][3] = f0.w;
        }
        if (w == 0) PROF(11);
        uint32_t pf[5];
        float oa[2][4] = {{0.f, 0.f, 0.f, 0.f}, {0.f, 0.f, 0.f, 0.f}}, ob_[2][4] = {{0.f, 0.f, 0.f, 0.f}, {0.f, 0.f, 0.f, 0.f}};
        float sm0[4] = {0.f, 0.f, 0.f, 0.f}, sm1[4] = {0.f, 0.f, 0.f, 0.f};
        if (s != NSEG - 1) {
            mbar_wait(sb + RB_SX, s & 1);
            if (w == 0) PROF(4);
            float sv[10];
#pragma unroll
            for (int n = 0; n < 5; n++) {
                const float2 a = lds64f(tb.w + n * 256), b = lds64f(tb.w + (5 + n) * 256);
                sv[2 * n] = a.x + b.x; sv[2 * n + 1] = a.y + b.y;
            }
            float mx = fmaxf(fmaxf(fmaxf(sv[0], sv[1]), fmaxf(sv[2], sv[3])), fmaxf(fmaxf(sv[4], sv[5]), fmaxf(sv[6], sv[7])));
            mx = fmaxf(mx, fmaxf(sv[8], sv[9]));
            mx = fmaxf(mx, __shfl_xor_sync(~0u, mx, 1));
            mx = fmaxf(mx, __shfl_xor_sync(~0u, mx, 2));
#pragma unroll
            for (int n = 1; n < 5; n++) pf[n] = pack2(ex2(sv[2 * n] - mx), ex2(sv[2 * n + 1] - mx));
            pf[0] = pack2(ex2(sv[0] - mx), ex2(sv[1] - mx));
            if (w == 0) PROF(12);
            const uint32_t one = 0x3F803F80u;
            mma16816h(sm0, pf[1], pf[2], one, one);
            mma16816h(oa[0], pf[1], pf[2], vx[0], vx[1]);
            mma16816h(oa[1], pf[1], pf[2], vx[2], vx[3]);
            mma16816h(sm1, pf[3], pf[4], one, one);
            mma16816h(ob_[0], pf[3], pf[4], vx[4], vx[5]);
            mma16816h(ob_[1], pf[3], pf[4], vx[6], vx[7]);
            mma1688h(sm0, pf[0], one);
            mma1688h(oa[0], pf[0], vb0);
            mma1688h(oa[1], pf[0], vb1);
            float inv;
            asm("rcp.approx.ftz.f32 %0, %1;" : "=f"(inv) : "f"(sm0[0] + sm1[0]));
            oa[0][0] += ob_[0][0]; oa[0][1] += ob_[0][1]; oa[1][0] += ob_[1][0]; oa[1][1] += ob_[1][1];
            sts32(ta.y, pack2(oa[0][0] * inv, oa[0][1] * inv));
            sts32(ta.y ^ 16, pack2(oa[1][0] * inv, oa[1][1] * inv));
            const uint32_t oa2 = ta.w ^ 64;
            bar_sync(NB_C, 128);
            if (w == 0) PROF(5);
            uint32_t ob[8];
            ldsm4(ob[0], ob[1], ob[2], ob[3], ta.w);
            ldsm4(ob[4], ob[5], ob[6], ob[7], oa2);
#pragma unroll
            for (int i = 4; i < 8; i++) {
                const uint4 f0 = lds128(tab + 4096 + i * 2048);
                wo[i][0][0] = f0.x; wo[i][0][1] = f0.y; wo[i][0][2] = f0.z; wo[i][0][3] = f0.w;
            }
#pragma unroll
            for (int jj = 0; jj < 2; jj++) {
                if (jj == 1 && tb.w == 0) break;
                float acc[4][4];
#pragma unroll
                for (int c = 0; c < 4; c++) { acc[c][0] = acc[c][1] = acc[c][2] = acc[c][3] = 0.f; }
#pragma unroll
                for (int ks = 0; ks < 4; ks++)
#pragma unroll
                    for (int c = 0; c < 4; c++)
                        mma16816(acc[c], wo[jj * 4 + c][ks][0], wo[jj * 4 + c][ks][1], wo[jj * 4 + c][ks][2], wo[jj * 4 + c][ks][3], ob[2 * ks], ob[2 * ks + 1]);
#pragma unroll
                for (int pr = 0; pr < 2; pr++) {
                    uint4 v;
                    v.x = pack2(acc[2 * pr][0], acc[2 * pr][1]);
                    v.y = pack2(acc[2 * pr][2], acc[2 * pr][3]);
                    v.z = pack2(acc[2 * pr + 1][0], acc[2 * pr + 1][1]);
                    v.w = pack2(acc[2 * pr + 1][2], acc[2 * pr + 1][3]);
                    st_async_v4(tb.x + ((jj * 2 + pr) << 24), v, tb.y + ((jj * 2 + pr) << 24));
                }
            }
            if (w == 0) PROF(6);
        }
        stsm2t(ta.z + (s & 1) * 2048, vb0, vb1);
        cp_async_wait<0>();
        bar_sync(NB_C, 128);
        if (w == 0 && lane == 0 && s != NSEG - 1) mbar_expect_tx(sb + RB_SX, 2560);
        if (s != NSEG - 1) bar_arrive(NB_D, 384);
#pragma unroll
        for (int i = 0; i < 2 * VK0; i++) av[i] = lds128(lane16 + R_WV + (i / VK0) * 32768 + (w * 16 + i % VK0) * 512);
        slot_off = slot_off == (R_NST - 1) * 4096 ? 0 : slot_off + 4096;
    }
    rec_store_kvm(sb, col0, NSEG - 1, w, lane);
    bar_sync(NB_C, 128);
    if (w == 0 && lane == 0) red_release(&g_flags[F_MEM + NRB - 1], 1);
}

__global__ void __launch_bounds__(384, 1) k_rec(const RecParams p) {
    extern __shared__ __align__(1024) unsigned char smem_raw[];
    const uint32_t sb = __shfl_sync(~0u, smem_u32(smem_raw), 0);
    const int warp = __shfl_sync(~0u, threadIdx.x >> 5, 0);
    int lane; asm volatile("mov.u32 %0, %%laneid;" : "=r"(lane));
    const int crank = blockIdx.x & 15, slot = blockIdx.x >> 4;
    asm volatile("griddepcontrol.launch_dependents;");
    if (threadIdx.x == 0) {
        mbar_init(sb + RB_SX, 1); mbar_init(sb + RB_E, 1); mbar_init(sb + RB_A, 1); mbar_init(sb + RB_A1, 1); mbar_init(sb + RB_ROLE, 1);
        asm volatile("fence.mbarrier_init.release.cluster;" ::: "memory");
        mbar_expect_tx(sb + RB_SX, 2560);
        mbar_expect_tx(sb + RB_E, 8192);
        mbar_expect_tx(sb + RB_A, 4096);
        mbar_expect_tx(sb + RB_A1, 4096);
        mbar_expect_tx(sb + RB_ROLE, 4);
    }
    unsigned role = 0;
    if (crank == 0 && threadIdx.x == 0) {
        unsigned x = 0;
        int tm[2] = {0x7fffffff, 0x7fffffff};
#pragma unroll 1
        for (int i = 0; i < 6; i++) {
            const uint32_t t0 = clk32();
            x = atomicAdd(&g_F[65536 + (i & 1) * 1024 + slot * 64 + (x >> 31)], 0u) & 0x7fffffffu;
            if (x == 0x7654321u) sts32(sb + R_BAR + 56, x);
            const int dt = (int)(clk32() - t0);
            if (i >= 2) { if (i & 1) tm[1] = min(tm[1], dt); else tm[0] = min(tm[0], dt); }
        }
        const int side = tm[1] > tm[0];
        const unsigned old = atomicAdd(&g_flags[F_SIDE + side * 32], 1u);
        unsigned c0, c1; int gd = 0;
#pragma unroll 1
        do { c0 = ldg_relaxed32(&g_flags[F_SIDE]); c1 = ldg_relaxed32(&g_flags[F_SIDE + 32]); } while ((int)(c0 + c1) < p.ncl && ++gd < 64 * SPIN_LIMIT);
        const int big = c1 > c0;
        role = side == big ? old : (big ? c1 : c0) + old;
        role |= (big ^ 1) << 8;
    }
    __syncwarp();
    asm volatile("barrier.cluster.arrive.relaxed.aligned;\nbarrier.cluster.wait.aligned;" ::: "memory");
    if (crank == 0 && warp == 0) {
        role = __shfl_sync(~0u, role, 0);
        if (lane < 16)
            asm volatile("st.async.weak.shared::cluster.mbarrier::complete_tx::bytes.u32 [%0], %1, [%2];"
                         :: "r"(mapa_u32(sb + R_BAR + 48, lane)), "r"(role), "r"(mapa_u32(sb + RB_ROLE, lane)) : "memory");
    }
    mbar_wait(sb + RB_ROLE, 0);
    const int rolew = __shfl_sync(~0u, lds32(sb + R_BAR + 48), 0);
    const int cl = rolew & 255;
    if (cl >= 4) return;
    const int cta = cl * 16 + crank;
    if (warp < 8) rec_qk(p, sb, cta, warp, lane, rolew >> 8);
    else rec_vo(p, sb, cta, warp, lane);
}

enum { J_KV = 0, J_QA = 1, J_O = 2, J_LN = 3, J_UP = 4, J_DN = 5, J_LN1 = 6, J_MOD = 7, J_UP2 = 8, J_END = 9 };
constexpr int NJ_O = 2 * OSPLIT, NJ_O2 = 2 * OSPLIT2, NJ_LN = 8, NJ_LN2 = 16, NJ_UP = 14, NJ_UP2 = 28, NJ_DN = 8, NJ_LN1 = 8;
constexpr uint64_t pk8(int a, int b, int c, int d, int e, int f, int g, int h) {
    return (uint64_t)a | ((uint64_t)b << 8) | ((uint64_t)c << 16) | ((uint64_t)d << 24) | ((uint64_t)e << 32) | ((uint64_t)f << 40) | ((uint64_t)g << 48) | ((uint64_t)h << 56);
}
constexpr uint64_t NJ_C = pk8(32, 16, NJ_O, NJ_LN, NJ_UP, NJ_DN, NJ_LN1, 16), NJ_F = pk8(32, 16, NJ_O2, NJ_LN2, NJ_UP2, NJ_DN, NJ_LN1, 0);
constexpr uint64_t TG_C = pk8(2 * NJ_LN1, 64, 32, 2 * NJ_O, 2 * NJ_LN, 2 * NJ_UP, 32, 0), TG_F = pk8(2 * NJ_LN1, 64, 32, 2 * NJ_O2, 2 * NJ_LN2, 2 * NJ_UP2, 32, 0);
constexpr uint64_t PRIO = pk8(4, 10, 9, 8, 7, 6, 3, 0);
__device__ __forceinline__ int pick_job(int lane, int qmask, int& idx) {
    const int rb = lane & 15, half = lane >> 4;
    const uint64_t nj = (rb >= FINE_RB ? NJ_F : (rb < 3 ? NJ_C : NJ_C & ~(0xffull << 56))) >> (8 * half);
    const uint64_t tg = (rb >= FINE_RB ? TG_F : TG_C) >> (8 * half);
    const unsigned* cp = &g_flags[F_CLAIM + half * 32 + rb];
    const unsigned* dp = &g_flags[half * 32 + rb];
    int gd = 0;
#pragma unroll 1
    while (true) {
        const unsigned c0 = ldg_relaxed32(cp), c1 = ldg_relaxed32(cp + 64), c2 = ldg_relaxed32(cp + 128), c3 = ldg_relaxed32(cp + 192);
        const unsigned d0 = ldg_relaxed32(dp - (half ? (rb >= FINE_RB ? 2 : (rb ? 1 : 0)) : 0)), d1 = ldg_relaxed32(dp + 64), d2 = ldg_relaxed32(dp + 128), d3 = ldg_relaxed32(dp + 192 - rb);
        const unsigned cl[4] = {c0, c1, c2, c3}, dv[4] = {d0, d1, d2, d3};
        unsigned key = 0xffffu, key2 = 0xffffu;
        bool pre = false;
#pragma unroll
        for (int i = 0; i < 4; i++) {
            const int q = half + 2 * i;
            const bool have = ((qmask >> q) & 1) && cl[i] < (unsigned)((nj >> (16 * i)) & 255);
            bool ready = have && dv[i] >= (unsigned)((tg >> (16 * i)) & 255);
            unsigned pr = (unsigned)((PRIO >> (8 * q)) & 255);
            if (i == 0 && rb == 0) { ready = have; pr = half ? pr : 2; }
            if (i == 3 && rb == 0) ready = have;
            if (i == 3 && rb == 0 && !half) pr = 1;
            if (i == 3 && rb > 0) pr = 3;
            if (i == 0 && half && rb >= FINE_RB) pr = 5;
            if (ready) key = min(key, (pr << 8) | (rb << 4) | q);
            if (have) key2 = min(key2, rb >= FINE_RB ? (0x100u | (q << 4) | rb) : 0u);
            pre |= have && (i == 3 || (i == 0 && !half));
        }
        const bool anypre = __any_sync(~0u, pre);
        if (anypre && (key & 15) == J_QA) key = 0xffffu;
        key = __reduce_min_sync(~0u, key);
        key2 = __reduce_min_sync(~0u, key2);
        if (key2 == 0xffffu) return J_END;
        int pq, prb;
        if (key != 0xffffu) { pq = key & 15; prb = (key >> 4) & 15; }
        else if (key2 >= 0x120u) { pq = (key2 >> 4) & 15; prb = key2 & 15; }
        else {
            __nanosleep(150);
            if (++gd > 16 * SPIN_LIMIT) { TIMEOUT(5, 0); return J_END; }
            continue;
        }
        int c = 0;
        if (lane == 0) c = (int)atomicAdd(&g_flags[F_CLAIM + pq * 32 + prb], 1u);
        c = __shfl_sync(~0u, c, 0);
        if (c < (int)(((prb >= FINE_RB ? NJ_F : NJ_C) >> (8 * pq)) & 255)) {
            idx = pq * 512 + prb * 32 + c;
            int acq = 0;
            if (pq != J_QA && pq < J_LN1) {
                if (lane == 0 && ld_acquire(&g_flags[pq * 32 + prb]) >= (unsigned)(((prb >= FINE_RB ? TG_F : TG_C) >> (8 * pq)) & 255)) {
                    asm volatile("fence.proxy.async.global;" ::: "memory");
                    acq = 1 << 24;
                }
            }
            return (pq == J_UP && prb >= FINE_RB ? J_UP2 : pq) | (prb << 8) | (c << 16) | acq;
        }
    }
}
__device__ __forceinline__ int op_row(int rb, int split) {
    return rb < FINE_RB ? split * S_ + rb * 128 : OSPLIT * S_ + (split * (NRB - FINE_RB) + rb - FINE_RB) * 128;
}

struct Pipe { uint32_t stage, phase; };
__device__ __forceinline__ void pipe_next(Pipe& p) { if (++p.stage == W_NST) { p.stage = 0; p.phase ^= 1; } }

__device__ __forceinline__ void scheduler(const Params& p, uint32_t sb, int lane) {
    const uint32_t bars = sb + SM_BAR;
    uint32_t ph = 0;
#pragma unroll 1
    while (true) {
        mbar_wait(bars + B_REQ, ph);
        int j = 4095;
        const int jd = pick_job(lane, p.qmask, j);
        if (lane == 0) { sts32(bars + B_NEXT, (uint32_t)jd); sts32(bars + B_NEXT + 4, (uint32_t)j); mbar_arrive(bars + B_RSP); }
        ph ^= 1;
        if (jd == J_END) break;
        __syncwarp();
    }
}

__device__ __forceinline__ void producer(const Params& p, uint32_t sb) {
    Pipe pp{0, 1};
    const uint32_t bars = sb + SM_BAR;
    uint32_t seq = 0, h_seen = 0;
    mbar_arrive(bars + B_REQ);
#pragma unroll 1
    while (true) {
        mbar_wait(bars + B_RSP, seq & 1);
        const int jd = (int)lds32(bars + B_NEXT), j = (int)lds32(bars + B_NEXT + 4);
        int left = (jd & 255) == J_DN ? 15 : ((jd & 255) == J_QA ? 12 : ((jd & 255) == J_O ? (((jd >> 8) & 255) >= FINE_RB ? 64 / OSPLIT2 : 64 / OSPLIT) : ((jd & 255) == J_LN || (jd & 255) == J_LN1 || (jd & 255) == J_MOD ? 1 : 8)));
        left = max(left - PICK_AHEAD, 1);
        TR(j, 1);
        const int type = jd & 255, rb = (jd >> 8) & 255, cb = (jd >> 16) & 255;
        const bool fine = rb >= FINE_RB, acquired = (jd >> 24) & 1;
        bool first = true;
        auto begin_stage = [&](uint32_t bytes) -> uint32_t {
            mbar_wait(bars + B_EMPTY + pp.stage * 8, pp.phase);
            if (first) { sts32(bars + B_RING + (seq & 7) * 4, (uint32_t)jd); sts32(bars + B_RING + 32 + (seq & 7) * 4, (uint32_t)j); first = false; }
            const uint32_t fb = bars + B_FULL + pp.stage * 8;
            if (bytes) mbar_expect_tx(fb, bytes); else mbar_arrive(fb);
            if (--left == 0 && type != J_END) mbar_arrive(bars + B_REQ);
            return fb;
        };
        if (type == J_END || type == J_LN || type == J_LN1 || type == J_MOD) {
            if (type == J_LN) { if (!acquired) wait_flag(F_OP + rb, 2 * (fine ? NJ_O2 : NJ_O)); if (!(h_seen >> 31)) { wait_flag(F_MOD + 1, 32); wait_flag(F_MOD + 2, 32); h_seen |= 1u << 31; } }

            TR(j, 2);
            begin_stage(0); pipe_next(pp);
            seq++;
            if (type == J_END) break;
            continue;
        }
        const CUtensorMap *ta, *tb0, *tb1;
        int k0 = 0, nk = 8, n0 = cb * 256, n1 = n0 + 128, nb = 4, dep = -1;
        unsigned tgt = 0;
        switch (type) {
            case J_KV: ta = &p.tm_h; tb0 = tb1 = cb < 16 ? &p.tm_wk : &p.tm_wv; n0 = (cb & 15) * 256; n1 = n0 + 128; dep = F_H + rb; tgt = 2 * NJ_LN1; break;
            case J_QA: ta = &p.tm_h; tb0 = tb1 = &p.tm_wq; dep = F_H + rb; tgt = 2 * NJ_LN1; break;
            case J_O: ta = &p.tm_o; tb0 = tb1 = &p.tm_wo; n0 = (cb & 1) * 256; n1 = n0 + 128; nk = fine ? 64 / OSPLIT2 : 64 / OSPLIT; k0 = (cb >> 1) * nk * 64;
                      dep = F_O + rb; tgt = 32; break;
            case J_UP: ta = &p.tm_h2; tb0 = &p.tm_wg; tb1 = &p.tm_wu; n0 = n1 = cb * 128; dep = F_H2 + rb; tgt = 2 * NJ_LN; break;
            case J_UP2: ta = &p.tm_h2; tb0 = &p.tm_wg; tb1 = &p.tm_wu; n0 = n1 = cb * 64; nb = 2; dep = F_H2 + rb; tgt = 2 * NJ_LN2; break;
            default: ta = &p.tm_act; tb0 = tb1 = &p.tm_wd; n0 = cb * 64; nk = 0; break;
        }
        const int m0 = rb * 128;
        if (type == J_DN) {
#pragma unroll 1
            for (int kb = 0; kb < 14; kb++) {
                const uint32_t fb = begin_stage(49152);
                const uint32_t st = sb + pp.stage * W_STAGE;
                const int k = kb * 128;
                tma_load2d(st + 32768, tb0, n0, k, fb);
                tma_load2d(st + 40960, tb0, n0, k + 64, fb);
                if (kb == 0) { if (!acquired) { wait_flag(F_ACT + rb, 2 * (fine ? NJ_UP2 : NJ_UP)); asm volatile("fence.proxy.async.global;" ::: "memory"); } TR(j, 2); }
                tma_load2d(st, ta, k, m0, fb);
                tma_load2d(st + 8192, ta, k, m0 + 64, fb);
                tma_load2d(st + 16384, ta, k + 64, m0, fb);
                tma_load2d(st + 24576, ta, k + 64, m0 + 64, fb);
                pipe_next(pp);
            }
        }
#pragma unroll 1
        for (int kb = 0; kb < nk; kb++) {
            const uint32_t fb = begin_stage(16384 + nb * 8192);
            const uint32_t st = sb + pp.stage * W_STAGE;
            const int k = k0 + kb * 64;
            tma_load2d(st + 16384, tb0, n0, k, fb);
            if (nb == 4) {
                tma_load2d(st + 16384 + 8192, tb0, n0 + 64, k, fb);
                tma_load2d(st + 16384 + 16384, tb1, n1, k, fb);
                tma_load2d(st + 16384 + 24576, tb1, n1 + 64, k, fb);
            } else if (nb == 2) {
                tma_load2d(st + 16384 + 8192, tb1, n1, k, fb);
            }
            if (kb == 0) {
                if (acquired && dep < 16) h_seen |= 1u << dep;
                if (dep >= 0 && !acquired && !(dep < 16 && ((h_seen >> dep) & 1))) {
                    wait_flag(dep, tgt);
                    if (type != J_O) asm volatile("fence.proxy.async.global;" ::: "memory");
                    if (dep < 16) h_seen |= 1u << dep;
                }
                TR(j, 2);
            }
            tma_load2d(st, ta, k, m0, fb);
            tma_load2d(st + 8192, ta, k, m0 + 64, fb);
            pipe_next(pp);
        }
        if (type == J_QA) {
            wait_flag(F_KV + rb, 64);
#pragma unroll 1
            for (int i = 0; i < 4; i++) {
                const uint32_t fb = begin_stage(40960);
                const uint32_t st = sb + pp.stage * W_STAGE;
                const int col = (i & 1) * HD_ + (cb * 2 + (i >> 1)) * DH_;
                tma_load2d(st, &p.tm_kv, col, m0, fb);
                tma_load2d(st + 8192, &p.tm_kv, col, m0 + 64, fb);
                tma_load2d(st + 16384, &p.tm_kv, col + 64, m0, fb);
                tma_load2d(st + 24576, &p.tm_kv, col + 64, m0 + 64, fb);
                if (i == 0) { wait_flag(F_MEM + rb, 64); asm volatile("fence.proxy.async.global;" ::: "memory"); }
                tma_load2d(st + 32768, &p.tm_kvm, col, rb * 32, fb);
                tma_load2d(st + 36864, &p.tm_kvm, col + 64, rb * 32, fb);
                pipe_next(pp);
            }
        } else if (type == J_DN) {
            const uint32_t fb = begin_stage(16384);
            const uint32_t st = sb + pp.stage * W_STAGE;
            tma_load2d(st, &p.tm_x1, n0, m0, fb);
            tma_load2d(st + 8192, &p.tm_x1, n0, m0 + 64, fb);
            pipe_next(pp);
        }
        seq++;
    }
}

__device__ __forceinline__ void store_warp(const Params& p, uint32_t sb, int wg, int lane) {
    const uint32_t bars = sb + SM_BAR;
    uint32_t seq = 0;
#pragma unroll 1
    while (true) {
        bar_sync(NB_ST + wg, 160);
        const uint32_t jd = lds32(bars + B_RING + (seq & 7) * 4);
        seq++;
        const int type = jd & 255, rb = (jd >> 8) & 255, cb = (jd >> 16) & 255;
        if (type == J_END) break;
        if (lane == 0) {
            const uint32_t src = sb + W_STG + wg * 32768;
            const CUtensorMap* tm = nullptr; int n0 = cb * 256, nbox = 4, mrow = rb * 128 + wg * 64, flag = 0;
            switch (type) {
                case J_KV: tm = &p.tm_kv; flag = F_KV + rb; break;
                case J_QA: tm = &p.tm_o; flag = F_O + rb; break;
                case J_O: tm = &p.tm_op; n0 = (cb & 1) * 256; mrow = op_row(rb, cb >> 1) + wg * 64; flag = F_OP + rb; break;
                case J_LN: flag = F_H2 + rb; nbox = 0; break;
                case J_LN1: flag = F_H + rb; nbox = 0; break;
                case J_MOD: flag = F_MOD + rb; nbox = 0; break;
                case J_UP: tm = &p.tm_act; n0 = cb * 128; nbox = 2; flag = F_ACT + rb; break;
                case J_UP2: tm = &p.tm_act; n0 = cb * 64; nbox = 1; flag = F_ACT + rb; break;
                default: tm = &p.tm_out; n0 = cb * 64; nbox = 1; flag = -1; break;
            }
#pragma unroll 1
            for (int b = 0; b < nbox; b++) tma_store2d(tm, src + b * 8192, n0 + b * 64, mrow);
            bulk_commit();
            bulk_wait0();
            mbar_arrive(bars + B_STGFREE + wg * 8);
            if (flag >= 0) red_release(&g_flags[flag], 1);
        }
        __syncwarp();
    }
}

__device__ __forceinline__ float gelu_tanh(float x) {
    const float t = x * fmaf(-0.10294324397f, x * x, -2.30220819814f);
    float r; asm("rcp.approx.ftz.f32 %0, %1;" : "=f"(r) : "f"(1.f + ex2(t)));
    return x * r;
}

#define CTR(i) do {} while (0)

template <int NSPLIT>
__device__ __forceinline__ void ln2_row(const Params& p, int rb, int r, int lane) {
    const int row = rb * 128 + r;
    uint4 u[2 * NSPLIT];
#pragma unroll
    for (int sp = 0; sp < NSPLIT; sp++) {
        const uint4* src = (const uint4*)(g_op + (size_t)(op_row(rb, sp) + r) * D_);
        u[2 * sp] = __ldcg(src + lane); u[2 * sp + 1] = __ldcg(src + 32 + lane);
    }
    const uint4* xr = (const uint4*)(p.x + (size_t)row * D_);
    const uint4 xa = __ldg(xr + lane), xb = __ldg(xr + 32 + lane);
    uint32_t ga[8], c1[8], sm[8];
    load_mod8(g_mod + 2 * D_, lane, ga);
    load_mod8(g_mod + 4 * D_, lane, c1);
    load_mod8(g_mod + 3 * D_, lane, sm);
    float a[16];
#pragma unroll
    for (int i = 0; i < 16; i++) a[i] = 0.f;
#pragma unroll
    for (int sp = 0; sp < 2 * NSPLIT; sp++) {
        float* q = a + (sp & 1) * 8;
        q[0] += bflo(u[sp].x); q[1] += bfhi(u[sp].x); q[2] += bflo(u[sp].y); q[3] += bfhi(u[sp].y);
        q[4] += bflo(u[sp].z); q[5] += bfhi(u[sp].z); q[6] += bflo(u[sp].w); q[7] += bfhi(u[sp].w);
    }
    const uint32_t xv[8] = {xa.x, xa.y, xa.z, xa.w, xb.x, xb.y, xb.z, xb.w};
    uint32_t v[8], r8[8];
#pragma unroll
    for (int i = 0; i < 8; i++) v[i] = hadd2(xv[i], hmul2(ga[i], pack2(a[2 * i], a[2 * i + 1])));
    uint4* x1r = (uint4*)(g_x1 + (size_t)row * D_);
    x1r[lane] = make_uint4(v[0], v[1], v[2], v[3]); x1r[32 + lane] = make_uint4(v[4], v[5], v[6], v[7]);
    uint32_t mu2; float rden;
    ln_stats(v, mu2, rden);
#pragma unroll
    for (int i = 0; i < 8; i++) c1[i] = hadd2(c1[i], 0x3F803F80u);
    ln_apply(v, mu2, rden, c1, sm, r8);
    uint4* hr = (uint4*)(g_h2 + (size_t)row * D_);
    hr[lane] = make_uint4(r8[0], r8[1], r8[2], r8[3]); hr[32 + lane] = make_uint4(r8[4], r8[5], r8[6], r8[7]);
}

__device__ __forceinline__ void consumer(const Params& p, uint32_t sb, int warp, int lane) {
    const uint32_t bars = sb + SM_BAR;
    const int wg = warp >> 2, wl = warp & 3;
    const uint32_t l7 = lane & 7, l8 = lane >> 3, g = lane >> 2, t = lane & 3;
    Pipe pp{0, 0};
    uint32_t seq = 0, stg_phase = 1;
    const int srow = wl * 16 + l7 + (l8 & 1) * 8;
    const uint32_t stg_base = sb + W_STG + wg * 32768 + srow * 128;
    const uint32_t sx = ((lane >> 4) ^ (srow & 7)) << 4;
#pragma unroll 1
    while (true) {
        mbar_wait(bars + B_FULL + pp.stage * 8, pp.phase);
        const uint32_t jd = lds32(bars + B_RING + (seq & 7) * 4);
        CTR(3);
        seq++;
        const int type = jd & 255, rb = (jd >> 8) & 255, cb = (jd >> 16) & 255;
        if (type == J_END) { mbar_wait(bars + B_STGFREE + wg * 8, stg_phase); bar_arrive(NB_ST + wg, 160); break; }
        if (type == J_MOD) {
            __syncwarp();
            if (lane == 0) mbar_arrive(bars + B_EMPTY + pp.stage * 8);
            pipe_next(pp);
            const int rg = warp * 4 + l8, col = rb * 1024 + cb * 64;
            uint4 wv[16];
#pragma unroll
            for (int i = 0; i < 16; i++) wv[i] = __ldg((const uint4*)(p.w_mod + (size_t)(rg * 16 + i) * (6 * D_) + col + l7 * 8));
            const uint32_t cw = __ldg((const uint32_t*)(p.c + rg * 16) + l7);
            const float cl = bflo(cw), ch = bfhi(cw);
            const uint32_t sw = pack2(__fdividef(cl, 1.f + __expf(-cl)), __fdividef(ch, 1.f + __expf(-ch)));
            float a[8];
#pragma unroll
            for (int i = 0; i < 8; i++) a[i] = 0.f;
#pragma unroll
            for (int i = 0; i < 16; i++) {
                const uint32_t sv = __shfl_sync(~0u, sw, (lane & 24) + (i >> 1));
                const float cv = (i & 1) ? bfhi(sv) : bflo(sv);
                a[0] = fmaf(cv, bflo(wv[i].x), a[0]); a[1] = fmaf(cv, bfhi(wv[i].x), a[1]); a[2] = fmaf(cv, bflo(wv[i].y), a[2]); a[3] = fmaf(cv, bfhi(wv[i].y), a[3]);
                a[4] = fmaf(cv, bflo(wv[i].z), a[4]); a[5] = fmaf(cv, bfhi(wv[i].z), a[5]); a[6] = fmaf(cv, bflo(wv[i].w), a[6]); a[7] = fmaf(cv, bfhi(wv[i].w), a[7]);
            }
#pragma unroll
            for (int i = 0; i < 8; i++) { a[i] += __shfl_xor_sync(~0u, a[i], 8); a[i] += __shfl_xor_sync(~0u, a[i], 16); }
            const uint32_t red = sb + SM_BAR + 1024;
            bar_sync(NB_M, 256);
            if (lane < 8) {
                sts128(red + warp * 256 + lane * 32, make_uint4(__float_as_uint(a[0]), __float_as_uint(a[1]), __float_as_uint(a[2]), __float_as_uint(a[3])));
                sts128(red + warp * 256 + lane * 32 + 16, make_uint4(__float_as_uint(a[4]), __float_as_uint(a[5]), __float_as_uint(a[6]), __float_as_uint(a[7])));
            }
            bar_sync(NB_M, 256);
            if (wl == 0) {
                const uint32_t ra = red + (wg * 32 + lane) * 4;
                float v = 0.f;
#pragma unroll
                for (int i = 0; i < 8; i++) v += lds32f(ra + i * 256);
                g_mod[col + wg * 32 + lane] = __float2bfloat16_rn(v);
            }
            mbar_wait(bars + B_STGFREE + wg * 8, stg_phase); stg_phase ^= 1;
            CTR(4); CTR(5);
            bar_arrive(NB_ST + wg, 160);
            continue;
        }
        if (type == J_LN || type == J_LN1) {
            __syncwarp();
            if (lane == 0) mbar_arrive(bars + B_EMPTY + pp.stage * 8);
            pipe_next(pp);
            if (type == J_LN1) {
                const int row = rb * 128 + cb * 16 + warp * 2;
                const uint4* xr = (const uint4*)(p.x + (size_t)row * D_);
                const uint4 xa[4] = {__ldg(xr + lane), __ldg(xr + 32 + lane), __ldg(xr + 64 + lane), __ldg(xr + 96 + lane)};
                uint32_t c1[8], sm[8], mu2[2];
                float rden[2];
#pragma unroll
                for (int rr = 0; rr < 2; rr++) {
                    const uint32_t v[8] = {xa[2 * rr].x, xa[2 * rr].y, xa[2 * rr].z, xa[2 * rr].w, xa[2 * rr + 1].x, xa[2 * rr + 1].y, xa[2 * rr + 1].z, xa[2 * rr + 1].w};
                    ln_stats(v, mu2[rr], rden[rr]);
                }
                if (lane == 0) wait_flag(F_MOD, 32);
                __syncwarp();
                load_mod8(g_mod + D_, lane, c1);
                load_mod8(g_mod, lane, sm);
#pragma unroll
                for (int i = 0; i < 8; i++) c1[i] = hadd2(c1[i], 0x3F803F80u);
#pragma unroll
                for (int rr = 0; rr < 2; rr++) {
                    const uint32_t v[8] = {xa[2 * rr].x, xa[2 * rr].y, xa[2 * rr].z, xa[2 * rr].w, xa[2 * rr + 1].x, xa[2 * rr + 1].y, xa[2 * rr + 1].z, xa[2 * rr + 1].w};
                    uint32_t r[8];
                    ln_apply(v, mu2[rr], rden[rr], c1, sm, r);
                    uint4* hr = (uint4*)(g_h + (size_t)(row + rr) * D_);
                    hr[lane] = make_uint4(r[0], r[1], r[2], r[3]); hr[32 + lane] = make_uint4(r[4], r[5], r[6], r[7]);
                }
            } else if (rb >= FINE_RB) ln2_row<OSPLIT2>(p, rb, cb * 8 + warp, lane);
            else {
#pragma unroll 1
                for (int rr = 0; rr < 2; rr++) ln2_row<OSPLIT>(p, rb, cb * 16 + warp * 2 + rr, lane);
            }
            mbar_wait(bars + B_STGFREE + wg * 8, stg_phase); stg_phase ^= 1;
            CTR(4); CTR(5);
            bar_arrive(NB_ST + wg, 160);
            continue;
        }
        if (type == J_DN || type == J_UP2) {
            float acc[64];
#pragma unroll
            for (int i = 0; i < 64; i++) acc[i] = 0.f;
            if (type == J_DN) {
#pragma unroll 1
                for (int kb = 0; kb < 14; kb++) {
                    if (kb) mbar_wait(bars + B_FULL + pp.stage * 8, pp.phase);
                    const uint32_t st = sb + pp.stage * W_STAGE;
                    const uint64_t da = mkdesc(st + wg * 8192, 16, 1024), db = mkdesc(st + 32768, 8192, 1024);
                    wg_fence();
#pragma unroll
                    for (int ks = 0; ks < 8; ks++) wgmma_n64(acc, da + (ks >> 2) * 1024 + (ks & 3) * 2, db + ks * 128);
                    wg_commit();
                    wg_wait0();
                    if (lane == 0) mbar_arrive(bars + B_EMPTY + pp.stage * 8);
                    pipe_next(pp);
                }
            } else {
#pragma unroll 1
                for (int kb = 0; kb < 8; kb++) {
                    if (kb) mbar_wait(bars + B_FULL + pp.stage * 8, pp.phase);
                    const uint32_t st = sb + pp.stage * W_STAGE;
                    const uint64_t da = mkdesc(st + wg * 8192, 16, 1024), db = mkdesc(st + 16384, 8192, 1024);
                    wg_fence();
#pragma unroll
                    for (int ks = 0; ks < 4; ks++) wgmma_n128(acc, da + ks * 2, db + ks * 128, 1);
                    wg_commit();
                    wg_wait0();
                    if (lane == 0) mbar_arrive(bars + B_EMPTY + pp.stage * 8);
                    pipe_next(pp);
                }
            }
            CTR(4);
            if (type == J_UP2) {
                mbar_wait(bars + B_STGFREE + wg * 8, stg_phase); stg_phase ^= 1;
#pragma unroll
                for (int j = 0; j < 4; j++) {
                    uint32_t r[4];
#pragma unroll
                    for (int q = 0; q < 4; q++) {
                        const uint32_t gw = pack2(acc[8 * j + 2 * q], acc[8 * j + 2 * q + 1]);
                        const uint32_t uw = pack2(acc[32 + 8 * j + 2 * q], acc[32 + 8 * j + 2 * q + 1]);
                        r[q] = hmul2(pack2(gelu_tanh(bflo(gw)), gelu_tanh(bfhi(gw))), uw);
                    }
                    stsm4(stg_base + (sx ^ (j << 5)), r[0], r[1], r[2], r[3]);
                }
            } else {
                mbar_wait(bars + B_FULL + pp.stage * 8, pp.phase);
                const uint32_t st = sb + pp.stage * W_STAGE;
                mbar_wait(bars + B_STGFREE + wg * 8, stg_phase); stg_phase ^= 1;
                const uint32_t* gb = (const uint32_t*)(g_mod + 5 * D_ + cb * 64) + t;
                const uint32_t xa = st + wg * 8192 + (wl * 16 + g) * 128 + (g << 4) + t * 4;
#pragma unroll
                for (int j = 0; j < 4; j++) {
                    uint32_t r[4];
#pragma unroll
                    for (int q = 0; q < 4; q++) {
                        const int nt = 2 * j + (q >> 1);
                        const uint32_t xw = lds32((xa ^ ((nt & 7) << 4)) + (nt >> 3) * 16384 + (q & 1) * 1024);
                        r[q] = hadd2(xw, hmul2(__ldcg(gb + nt * 4), pack2(acc[8 * j + 2 * q], acc[8 * j + 2 * q + 1])));
                    }
                    stsm4(stg_base + (j >> 2) * 8192 + (sx ^ ((2 * j & 7) << 4)), r[0], r[1], r[2], r[3]);
                }
                __syncwarp();
                if (lane == 0) mbar_arrive(bars + B_EMPTY + pp.stage * 8);
                pipe_next(pp);
            }
            fence_async_smem();
            CTR(5);
            bar_arrive(NB_ST + wg, 160);
            continue;
        }
        float acc[128];
#pragma unroll
        for (int i = 0; i < 128; i++) acc[i] = 0.f;
        const int nk = type == J_O ? (rb >= FINE_RB ? 64 / OSPLIT2 : 64 / OSPLIT) : 8;
#pragma unroll 1
        for (int kb = 0; kb < nk; kb++) {
            if (kb) mbar_wait(bars + B_FULL + pp.stage * 8, pp.phase);
            const uint32_t st = sb + pp.stage * W_STAGE;
            const uint64_t da = mkdesc(st + wg * 8192, 16, 1024), db = mkdesc(st + 16384, 8192, 1024);
            wg_fence();
#pragma unroll
            for (int ks = 0; ks < 4; ks++) wgmma_n256(acc, da + ks * 2, db + ks * 128, 1);
            wg_commit();
            wg_wait0();
            if (lane == 0) mbar_arrive(bars + B_EMPTY + pp.stage * 8);
            pipe_next(pp);
        }
        CTR(4);
        if (type == J_QA) {
            uint32_t qf[64];
#pragma unroll
            for (int i = 0; i < 64; i++) qf[i] = pack2(acc[2 * i], acc[2 * i + 1]);
            const int sg = warp >> 1, half = warp & 1;
            const float sc = 0.08838834764831845f * 1.4426950408889634f;
            const uint32_t xoff = (sg >> 1) * 8192 + ((sg & 1) * 32 + l7) * 128;
            const uint32_t moff = 32768 + (sg * 8 + l7) * 128;
            const uint32_t kch = (l8 ^ l7) << 4;
            const uint32_t vch = ((l8 & 1) ^ l7) << 4;
            mbar_wait(bars + B_STGFREE + wg * 8, stg_phase); stg_phase ^= 1;
#pragma unroll 1
            for (int hh = 0; hh < 2; hh++) {
                mbar_wait(bars + B_FULL + pp.stage * 8, pp.phase);
                uint32_t st = sb + pp.stage * W_STAGE;
                float sa[5][4];
#pragma unroll
                for (int n = 0; n < 5; n++) sa[n][0] = sa[n][1] = sa[n][2] = sa[n][3] = 0.f;
#pragma unroll
                for (int i = 0; i < 4; i++) {
                    const uint32_t* q = qf + i * 8;
                    uint32_t kk[5][4];
                    ldsm4(kk[0][0], kk[0][1], kk[0][2], kk[0][3], st + moff + (i >> 1) * 4096 + (kch ^ ((i & 1) * 64)));
#pragma unroll
                    for (int n = 1; n < 5; n++)
                        ldsm4(kk[n][0], kk[n][1], kk[n][2], kk[n][3], st + xoff + (n - 1) * 1024 + (i >> 1) * 16384 + (kch ^ ((i & 1) * 64)));
#pragma unroll
                    for (int n = 0; n < 5; n++) mma16816(sa[n], q[0], q[1], q[2], q[3], kk[n][0], kk[n][1]);
#pragma unroll
                    for (int n = 0; n < 5; n++) mma16816(sa[n], q[4], q[5], q[6], q[7], kk[n][2], kk[n][3]);
                }
                __syncwarp();
                if (lane == 0) mbar_arrive(bars + B_EMPTY + pp.stage * 8);
                pipe_next(pp);
                const int iq0 = half * 16 + g - 2 * t, iq1 = iq0 + 8;
                float m0 = fmaxf(sa[0][0], sa[0][1]), m1 = fmaxf(sa[0][2], sa[0][3]);
#pragma unroll
                for (int n = 1; n < 5; n++) {
#pragma unroll
                    for (int e = 0; e < 2; e++) {
                        const int jx = (n - 1) * 8 + e;
                        if (jx > iq0) sa[n][e] = -3.0e38f;
                        if (jx > iq1) sa[n][2 + e] = -3.0e38f;
                        m0 = fmaxf(m0, sa[n][e]); m1 = fmaxf(m1, sa[n][2 + e]);
                    }
                }
                m0 = fmaxf(m0, __shfl_xor_sync(~0u, m0, 1)); m1 = fmaxf(m1, __shfl_xor_sync(~0u, m1, 1));
                m0 = fmaxf(m0, __shfl_xor_sync(~0u, m0, 2)); m1 = fmaxf(m1, __shfl_xor_sync(~0u, m1, 2));
                m0 *= -sc; m1 *= -sc;
                float l0 = 0.f, l1 = 0.f;
                uint32_t p0[5], p1[5];
#pragma unroll
                for (int n = 0; n < 5; n++) {
                    const float e0 = ex2(fmaf(sa[n][0], sc, m0)), e1 = ex2(fmaf(sa[n][1], sc, m0));
                    const float e2 = ex2(fmaf(sa[n][2], sc, m1)), e3 = ex2(fmaf(sa[n][3], sc, m1));
                    l0 += e0 + e1; l1 += e2 + e3;
                    p0[n] = pack2(e0, e1); p1[n] = pack2(e2, e3);
                }
                l0 += __shfl_xor_sync(~0u, l0, 1); l1 += __shfl_xor_sync(~0u, l1, 1);
                l0 += __shfl_xor_sync(~0u, l0, 2); l1 += __shfl_xor_sync(~0u, l1, 2);
                const float i0 = __fdividef(1.f, l0), i1 = __fdividef(1.f, l1);
                mbar_wait(bars + B_FULL + pp.stage * 8, pp.phase);
                st = sb + pp.stage * W_STAGE;
#pragma unroll
                for (int i = 0; i < 32; i++) qf[i] = qf[32 + i];
#pragma unroll 1
                for (int bx = 0; bx < 2; bx++) {
                    float o[8][4];
                    uint32_t vm[8], v0[4][4], v1[4][4];
#pragma unroll
                    for (int ep = 0; ep < 4; ep++) {
                        ldsm2t(vm[2 * ep], vm[2 * ep + 1], st + moff + bx * 4096 + (vch ^ (ep << 5)));
                        const uint32_t va = st + xoff + (l8 >> 1) * 1024 + bx * 16384 + (vch ^ (ep << 5));
                        ldsm4t(v0[ep][0], v0[ep][1], v0[ep][2], v0[ep][3], va);
                        ldsm4t(v1[ep][0], v1[ep][1], v1[ep][2], v1[ep][3], va + 2048);
                    }
#pragma unroll
                    for (int n = 0; n < 8; n++) { o[n][0] = o[n][1] = o[n][2] = o[n][3] = 0.f; mma16816(o[n], p0[0], p1[0], p0[1], p1[1], vm[n], v0[n >> 1][n & 1]); }
#pragma unroll
                    for (int n = 0; n < 8; n++) mma16816(o[n], p0[2], p1[2], p0[3], p1[3], v0[n >> 1][2 + (n & 1)], v1[n >> 1][n & 1]);
#pragma unroll
                    for (int n = 0; n < 8; n++) mma1688(o[n], p0[4], p1[4], v1[n >> 1][2 + (n & 1)]);
#pragma unroll
                    for (int ep = 0; ep < 4; ep++)
                        stsm4(stg_base + (hh * 2 + bx) * 8192 + (sx ^ (ep << 5)),
                              pack2(o[2 * ep][0] * i0, o[2 * ep][1] * i0), pack2(o[2 * ep][2] * i1, o[2 * ep][3] * i1),
                              pack2(o[2 * ep + 1][0] * i0, o[2 * ep + 1][1] * i0), pack2(o[2 * ep + 1][2] * i1, o[2 * ep + 1][3] * i1));
                }
                __syncwarp();
                if (lane == 0) mbar_arrive(bars + B_EMPTY + pp.stage * 8);
                pipe_next(pp);
            }
        } else if (type == J_UP) {
            mbar_wait(bars + B_STGFREE + wg * 8, stg_phase); stg_phase ^= 1;
#pragma unroll
            for (int j = 0; j < 8; j++) {
                uint32_t r[4];
#pragma unroll
                for (int q = 0; q < 4; q++) {
                    const uint32_t gw = pack2(acc[8 * j + 2 * q], acc[8 * j + 2 * q + 1]);
                    const uint32_t uw = pack2(acc[64 + 8 * j + 2 * q], acc[64 + 8 * j + 2 * q + 1]);
                    r[q] = hmul2(pack2(gelu_tanh(bflo(gw)), gelu_tanh(bfhi(gw))), uw);
                }
                stsm4(stg_base + (j >> 2) * 8192 + (sx ^ ((2 * j & 7) << 4)), r[0], r[1], r[2], r[3]);
            }
        } else {
            mbar_wait(bars + B_STGFREE + wg * 8, stg_phase); stg_phase ^= 1;
#pragma unroll
            for (int j = 0; j < 16; j++)
                stsm4(stg_base + (j >> 2) * 8192 + (sx ^ ((2 * j & 7) << 4)),
                      pack2(acc[8 * j], acc[8 * j + 1]), pack2(acc[8 * j + 2], acc[8 * j + 3]),
                      pack2(acc[8 * j + 4], acc[8 * j + 5]), pack2(acc[8 * j + 6], acc[8 * j + 7]));
        }
        fence_async_smem();
        CTR(5);
        bar_arrive(NB_ST + wg, 160);
    }
}

__global__ void __launch_bounds__(384, 1) k_work(const __grid_constant__ Params p) {
    extern __shared__ __align__(1024) unsigned char smem_raw[];
    const uint32_t sb = smem_u32(smem_raw);
    if (sb & 1023) __trap();
    const int warp = __shfl_sync(~0u, threadIdx.x >> 5, 0);
    int lane; asm volatile("mov.u32 %0, %%laneid;" : "=r"(lane));
    if (threadIdx.x == 0) {
        const uint32_t bars = sb + SM_BAR;
        for (int i = 0; i < W_NST; i++) { mbar_init(bars + B_FULL + i * 8, 1); mbar_init(bars + B_EMPTY + i * 8, 8); }
        mbar_init(bars + B_STGFREE, 1); mbar_init(bars + B_STGFREE + 8, 1); mbar_init(bars + B_REQ, 1); mbar_init(bars + B_RSP, 1);
        asm volatile("fence.mbarrier_init.release.cluster;" ::: "memory");
    }
    __syncthreads();
    if (warp < 8) {
        asm volatile("setmaxnreg.inc.sync.aligned.u32 224;");
        consumer(p, sb, warp, lane);
    } else {
        asm volatile("setmaxnreg.dec.sync.aligned.u32 56;");
        if (warp == 8) { if (lane == 0) producer(p, sb); }
        else if (warp < 11) store_warp(p, sb, warp - 9, lane);
        else scheduler(p, sb, lane);
        __syncwarp();
        bar_sync(NB_W0, 128);
        if (warp == 8 && p.qmask == 0xff) {
            unsigned last = 0;
            if (lane == 0) { __threadfence(); last = atomicAdd(&g_flags[F_DONE], 1u) == gridDim.x - 1; }
            if (__shfl_sync(~0u, last, 0))
                for (int i = lane; i < F_TOTAL; i += 32) g_flags[i] = 0;
        }
    }
}

typedef CUresult (*EncodeFn)(CUtensorMap*, CUtensorMapDataType, cuuint32_t, void*, const cuuint64_t*, const cuuint64_t*,
                             const cuuint32_t*, const cuuint32_t*, CUtensorMapInterleave, CUtensorMapSwizzle,
                             CUtensorMapL2promotion, CUtensorMapFloatOOBfill);

static void make_map(EncodeFn enc, CUtensorMap* m, const void* ptr, uint64_t rows, uint64_t cols, uint32_t box_rows) {
    cuuint64_t dims[2] = {cols, rows};
    cuuint64_t strides[1] = {cols * 2};
    cuuint32_t box[2] = {64, box_rows};
    cuuint32_t es[2] = {1, 1};
    enc(m, CU_TENSOR_MAP_DATA_TYPE_BFLOAT16, 2, const_cast<void*>(ptr), dims, strides, box, es, CU_TENSOR_MAP_INTERLEAVE_NONE,
        CU_TENSOR_MAP_SWIZZLE_128B, CU_TENSOR_MAP_L2_PROMOTION_L2_256B, CU_TENSOR_MAP_FLOAT_OOB_FILL_NONE);
}
template <typename T> static void* sym_addr(T& sym) { void* p = nullptr; cudaGetSymbolAddress(&p, sym); return p; }

extern "C" void kernel_launch(void* const* d_in, const int* in_sizes, int n_in, void* d_out, int out_size) {
    static Params prm;
    static RecParams rp;
    static bool ready = false;
    static const void* key[14];
    bool same = ready;
    for (int i = 0; i < 13 && same; i++) same = key[i] == d_in[i];
    same = same && key[13] == d_out;
    if (!same) {
        void* fn = nullptr;
        cudaDriverEntryPointQueryResult qr;
        cudaGetDriverEntryPoint("cuTensorMapEncodeTiled", &fn, cudaEnableDefault, &qr);
        EncodeFn enc = (EncodeFn)fn;
        make_map(enc, &prm.tm_h, sym_addr(g_h), S_, D_, 64);
        make_map(enc, &prm.tm_kv, sym_addr(g_kv), S_, 2 * HD_, 64);
        make_map(enc, &prm.tm_kvm, sym_addr(g_kvm), NSEG * 8, 2 * HD_, 32);
        make_map(enc, &prm.tm_o, sym_addr(g_o), S_, HD_, 64);
        make_map(enc, &prm.tm_op, sym_addr(g_op), OP_ROWS, D_, 64);
        make_map(enc, &prm.tm_h2, sym_addr(g_h2), S_, D_, 64);
        make_map(enc, &prm.tm_act, sym_addr(g_act), S_, DF_, 64);
        make_map(enc, &prm.tm_x1, sym_addr(g_x1), S_, D_, 64);
        make_map(enc, &prm.tm_out, d_out, S_, D_, 64);
        make_map(enc, &prm.tm_wq, d_in[2], D_, HD_, 64);
        make_map(enc, &prm.tm_wk, d_in[3], D_, HD_, 64);
        make_map(enc, &prm.tm_wv, d_in[4], D_, HD_, 64);
        make_map(enc, &prm.tm_wo, d_in[5], HD_, D_, 64);
        make_map(enc, &prm.tm_wg, d_in[8], D_, DF_, 64);
        make_map(enc, &prm.tm_wu, d_in[9], D_, DF_, 64);
        make_map(enc, &prm.tm_wd, d_in[10], DF_, D_, 64);
        prm.x = (const bf16*)d_in[0]; prm.c = (const bf16*)d_in[11]; prm.w_mod = (const bf16*)d_in[12];
        rp.mem0 = (const bf16*)d_in[1];
        rp.wq = (const bf16*)d_in[2]; rp.wk = (const bf16*)d_in[3]; rp.wv = (const bf16*)d_in[4]; rp.wo = (const bf16*)d_in[5];
        cudaFuncSetAttribute(k_work, cudaFuncAttributeMaxDynamicSharedMemorySize, SMEM_BYTES);
        cudaFuncSetAttribute(k_rec, cudaFuncAttributeMaxDynamicSharedMemorySize, R_SMEM);
        cudaFuncSetAttribute(k_rec, cudaFuncAttributeNonPortableClusterSizeAllowed, 1);
        {
            cudaLaunchConfig_t cfg = {};
            cfg.gridDim = dim3(128); cfg.blockDim = dim3(384); cfg.dynamicSmemBytes = R_SMEM;
            cudaLaunchAttribute at[1];
            at[0].id = cudaLaunchAttributeClusterDimension; at[0].val.clusterDim.x = 16; at[0].val.clusterDim.y = 1; at[0].val.clusterDim.z = 1;
            cfg.attrs = at; cfg.numAttrs = 1;
            int n = 0;
            cudaOccupancyMaxActiveClusters(&n, k_rec, &cfg);
            rp.ncl = n < 4 ? 4 : (n > 8 ? 8 : n);
        }
        for (int i = 0; i < 13; i++) key[i] = d_in[i];
        key[13] = d_out;
        ready = true;
    }
    cudaStream_t st = cudaStreamPerThread;
    auto launch_rec = [&]() {
        cudaLaunchConfig_t cfg = {};
        cfg.gridDim = dim3(16 * rp.ncl); cfg.blockDim = dim3(384); cfg.dynamicSmemBytes = R_SMEM; cfg.stream = st;
        cudaLaunchAttribute at[1];
        at[0].id = cudaLaunchAttributeClusterDimension; at[0].val.clusterDim.x = 16; at[0].val.clusterDim.y = 1; at[0].val.clusterDim.z = 1;
        cfg.attrs = at; cfg.numAttrs = 1;
        cudaLaunchKernelEx(&cfg, k_rec, rp);
    };
    auto launch_work = [&](int qmask, int pdl) {
        prm.qmask = qmask;
        cudaLaunchConfig_t cfg = {};
        cfg.gridDim = dim3(132); cfg.blockDim = dim3(384); cfg.dynamicSmemBytes = SMEM_BYTES; cfg.stream = st;
        cudaLaunchAttribute at[1];
        at[0].id = cudaLaunchAttributeProgrammaticStreamSerialization; at[0].val.programmaticStreamSerializationAllowed = 1;
        cfg.attrs = at; cfg.numAttrs = pdl;
        cudaLaunchKernelEx(&cfg, k_work, prm);
    };
    launch_rec();
    launch_work(0xff, 1);
}
```

```cpp
#include <cuda_runtime.h>
#include <cuda_bf16.h>
#include <cuda.h>
#include <stdint.h>

typedef __nv_bfloat16 bf16;
#define IDLE_NS 150
#define FLAG_NS 20

constexpr int S_ = 2048, D_ = 512, H_ = 32, DH_ = 128, HD_ = 4096, NSEG = 64, DF_ = 1792;
constexpr int NRB = 16;
constexpr int OSPLIT = 4;

__device__ __align__(1024) bf16 g_h[S_ * D_];
__device__ __align__(1024) bf16 g_kv[S_ * 2 * HD_];
__device__ __align__(1024) bf16 g_kvm[NSEG * 8 * 2 * HD_];
__device__ __align__(1024) bf16 g_o[S_ * HD_];
#define FINE_RB_ 14
constexpr int FINE_RB = FINE_RB_;
#define OSPLIT2_ 8
constexpr int OSPLIT2 = OSPLIT2_;
constexpr int OP_ROWS = OSPLIT * S_ + OSPLIT2 * (NRB - FINE_RB) * 128;
__device__ __align__(1024) bf16 g_op[OP_ROWS * D_];
__device__ __align__(1024) bf16 g_x1[S_ * D_];
__device__ __align__(1024) bf16 g_h2[S_ * D_];
__device__ __align__(1024) bf16 g_act[S_ * DF_];
__device__ __align__(1024) bf16 g_mod[6 * D_];
__device__ uint32_t g_Fraw[131072 + 65536 + 2048];
#define g_F ((uint32_t*)(((uint64_t)g_Fraw + 0x7FFFFull) & ~0x7FFFFull))
constexpr int F_H = 0, F_MEM = 32, F_O = 64, F_OP = 96, F_H2 = 128, F_ACT = 160, F_MOD = 192, F_KV = 224, F_CLAIM = 256  ,
              F_SIDE = 512  , F_DONE = 576, F_TOTAL = 608;
__device__ __align__(128) unsigned int g_flags[F_TOTAL];
#define TR(j, i) do {} while (0)

__device__ __forceinline__ uint32_t smem_u32(const void* p) { return (uint32_t)__cvta_generic_to_shared(p); }
__device__ __forceinline__ uint32_t clk32() { uint32_t c; asm volatile("mov.u32 %0, %%clock;" : "=r"(c)); return c; }
__device__ __forceinline__ uint32_t mapa_u32(uint32_t addr, uint32_t rank) {
    uint32_t r; asm volatile("mapa.shared::cluster.u32 %0, %1, %2;" : "=r"(r) : "r"(addr), "r"(rank)); return r;
}
__device__ __forceinline__ void mbar_init(uint32_t bar, uint32_t cnt) {
    asm volatile("mbarrier.init.shared::cta.b64 [%0], %1;" :: "r"(bar), "r"(cnt) : "memory");
}
__device__ __forceinline__ void mbar_inval(uint32_t bar) {
    asm volatile("mbarrier.inval.shared::cta.b64 [%0];" :: "r"(bar) : "memory");
}
__device__ __forceinline__ void mbar_expect_tx(uint32_t bar, uint32_t bytes) {
    asm volatile("mbarrier.arrive.expect_tx.shared::cta.b64 _, [%0], %1;" :: "r"(bar), "r"(bytes) : "memory");
}
__device__ __forceinline__ void mbar_arrive(uint32_t bar) {
    asm volatile("mbarrier.arrive.shared::cta.b64 _, [%0];" :: "r"(bar) : "memory");
}
__device__ __forceinline__ bool mbar_try_wait(uint32_t bar, uint32_t parity) {
    uint32_t ok;
    asm volatile("{\n.reg .pred p;\nmbarrier.try_wait.parity.shared::cta.b64 p, [%1], %2;\nselp.u32 %0, 1, 0, p;\n}"
                 : "=r"(ok) : "r"(bar), "r"(parity) : "memory");
    return ok;
}
__device__ __forceinline__ bool mbar_try_wait_cluster(uint32_t bar, uint32_t parity) {
    uint32_t ok;
    asm volatile("{\n.reg .pred p;\nmbarrier.try_wait.parity.acquire.cluster.shared::cta.b64 p, [%1], %2;\nselp.u32 %0, 1, 0, p;\n}"
                 : "=r"(ok) : "r"(bar), "r"(parity) : "memory");
    return ok;
}
constexpr int SPIN_LIMIT = 1 << 18;
#define TIMEOUT(code, info) do {} while (0)
__device__ __forceinline__ void mbar_wait(uint32_t bar, uint32_t parity) {
    int g = 0;
#pragma unroll 1
    while (!mbar_try_wait(bar, parity)) { if (++g >= SPIN_LIMIT) { TIMEOUT(0, bar & 255); break; } }
}
__device__ __forceinline__ void mbar_wait_cluster(uint32_t bar, uint32_t parity) {
    int g = 0;
#pragma unroll 1
    while (!mbar_try_wait_cluster(bar, parity)) { if (++g >= SPIN_LIMIT) { TIMEOUT(1, bar & 255); break; } }
}
__device__ __forceinline__ void bar_sync(int id, int n) { asm volatile("bar.sync %0, %1;" :: "r"(id), "r"(n) : "memory"); }
__device__ __forceinline__ void bar_arrive(int id, int n) { asm volatile("bar.arrive %0, %1;" :: "r"(id), "r"(n) : "memory"); }
__device__ __forceinline__ void cluster_sync_all() {
    asm volatile("barrier.cluster.arrive.aligned;\nbarrier.cluster.wait.aligned;" ::: "memory");
}
__device__ __forceinline__ void st_async_v2(uint32_t addr, float a, float b, uint32_t bar) {
    asm volatile("st.async.weak.shared::cluster.mbarrier::complete_tx::bytes.v2.f32 [%0], {%1,%2}, [%3];"
                 :: "r"(addr), "f"(a), "f"(b), "r"(bar) : "memory");
}
__device__ __forceinline__ void st_async_v4(uint32_t addr, uint4 v, uint32_t bar) {
    asm volatile("st.async.weak.shared::cluster.mbarrier::complete_tx::bytes.v4.b32 [%0], {%1,%2,%3,%4}, [%5];"
                 :: "r"(addr), "r"(v.x), "r"(v.y), "r"(v.z), "r"(v.w), "r"(bar) : "memory");
}
__device__ __forceinline__ uint2 ldg_relaxed2(const uint2* p) {
    uint2 v;
    asm volatile("ld.relaxed.gpu.global.v2.b32 {%0,%1}, [%2];" : "=r"(v.x), "=r"(v.y) : "l"(p) : "memory");
    return v;
}
__device__ __forceinline__ void stg_relaxed2(uint2* p, uint2 v) {
    asm volatile("st.relaxed.gpu.global.v2.b32 [%0], {%1,%2};" :: "l"(p), "r"(v.x), "r"(v.y) : "memory");
}
__device__ __forceinline__ uint4 ldg_relaxed(const uint4* p) {
    uint4 v;
    asm volatile("ld.relaxed.gpu.global.v4.b32 {%0,%1,%2,%3}, [%4];" : "=r"(v.x), "=r"(v.y), "=r"(v.z), "=r"(v.w) : "l"(p) : "memory");
    return v;
}
__device__ __forceinline__ void stg_relaxed(uint4* p, uint4 v) {
    asm volatile("st.relaxed.gpu.global.v4.b32 [%0], {%1,%2,%3,%4};" :: "l"(p), "r"(v.x), "r"(v.y), "r"(v.z), "r"(v.w) : "memory");
}
__device__ __forceinline__ void stg_relaxed32(uint32_t* p, uint32_t v) {
    asm volatile("st.relaxed.gpu.global.b32 [%0], %1;" :: "l"(p), "r"(v) : "memory");
}
__device__ __forceinline__ uint32_t ldg_relaxed32(const uint32_t* p) {
    uint32_t v; asm volatile("ld.relaxed.gpu.global.b32 %0, [%1];" : "=r"(v) : "l"(p) : "memory"); return v;
}
__device__ __forceinline__ unsigned int ld_acquire(const unsigned int* p) {
    unsigned int v; asm volatile("ld.acquire.gpu.global.u32 %0, [%1];" : "=r"(v) : "l"(p) : "memory"); return v;
}
__device__ __forceinline__ void red_release(unsigned int* p, unsigned int v) {
    asm volatile("red.release.gpu.global.add.u32 [%0], %1;" :: "l"(p), "r"(v) : "memory");
}
__device__ __forceinline__ void wait_flag(int idx, unsigned int target) {
    const unsigned int* p = &g_flags[idx];
    int g = 0;
#pragma unroll 1
    while (ld_acquire(p) < target) { __nanosleep(FLAG_NS); if (++g >= 64 * SPIN_LIMIT) { TIMEOUT(2, idx); break; } }
}
__device__ __forceinline__ void cp_async16(uint32_t dst, const void* src) {
    asm volatile("cp.async.cg.shared.global [%0], [%1], 16;" :: "r"(dst), "l"(src) : "memory");
}
__device__ __forceinline__ void cp_async_commit() { asm volatile("cp.async.commit_group;" ::: "memory"); }
template <int N> __device__ __forceinline__ void cp_async_wait() { asm volatile("cp.async.wait_group %0;" :: "n"(N) : "memory"); }
__device__ __forceinline__ void ldsm4(uint32_t& r0, uint32_t& r1, uint32_t& r2, uint32_t& r3, uint32_t addr) {
    asm volatile("ldmatrix.sync.aligned.m8n8.x4.shared.b16 {%0,%1,%2,%3}, [%4];" : "=r"(r0), "=r"(r1), "=r"(r2), "=r"(r3) : "r"(addr) : "memory");
}
__device__ __forceinline__ void ldsm4t(uint32_t& r0, uint32_t& r1, uint32_t& r2, uint32_t& r3, uint32_t addr) {
    asm volatile("ldmatrix.sync.aligned.m8n8.x4.trans.shared.b16 {%0,%1,%2,%3}, [%4];" : "=r"(r0), "=r"(r1), "=r"(r2), "=r"(r3) : "r"(addr) : "memory");
}
__device__ __forceinline__ void ldsm2t(uint32_t& r0, uint32_t& r1, uint32_t addr) {
    asm volatile("ldmatrix.sync.aligned.m8n8.x2.trans.shared.b16 {%0,%1}, [%2];" : "=r"(r0), "=r"(r1) : "r"(addr) : "memory");
}
__device__ __forceinline__ void stsm4(uint32_t addr, uint32_t r0, uint32_t r1, uint32_t r2, uint32_t r3) {
    asm volatile("stmatrix.sync.aligned.m8n8.x4.shared.b16 [%0], {%1,%2,%3,%4};" :: "r"(addr), "r"(r0), "r"(r1), "r"(r2), "r"(r3) : "memory");
}
__device__ __forceinline__ void stsm2t(uint32_t addr, uint32_t r0, uint32_t r1) {
    asm volatile("stmatrix.sync.aligned.m8n8.x2.trans.shared.b16 [%0], {%1,%2};" :: "r"(addr), "r"(r0), "r"(r1) : "memory");
}
__device__ __forceinline__ void mma16816(float* d, uint32_t a0, uint32_t a1, uint32_t a2, uint32_t a3, uint32_t b0, uint32_t b1) {
    asm volatile("mma.sync.aligned.m16n8k16.row.col.f32.bf16.bf16.f32 {%0,%1,%2,%3}, {%4,%5,%6,%7}, {%8,%9}, {%0,%1,%2,%3};"
                 : "+f"(d[0]), "+f"(d[1]), "+f"(d[2]), "+f"(d[3]) : "r"(a0), "r"(a1), "r"(a2), "r"(a3), "r"(b0), "r"(b1));
}
__device__ __forceinline__ void mma1688(float* d, uint32_t a0, uint32_t a1, uint32_t b0) {
    asm volatile("mma.sync.aligned.m16n8k8.row.col.f32.bf16.bf16.f32 {%0,%1,%2,%3}, {%4,%5}, {%6}, {%0,%1,%2,%3};"
                 : "+f"(d[0]), "+f"(d[1]), "+f"(d[2]), "+f"(d[3]) : "r"(a0), "r"(a1), "r"(b0));
}
__device__ __forceinline__ void mma16816h(float* d, uint32_t a0, uint32_t a2, uint32_t b0, uint32_t b1) {
    asm volatile("{\n.reg .b32 ju, jv;\nmma.sync.aligned.m16n8k16.row.col.f32.bf16.bf16.f32 {%0,%1,%2,%3}, {%4,ju,%5,jv}, {%6,%7}, {%0,%1,%2,%3};\n}"
                 : "+f"(d[0]), "+f"(d[1]), "+f"(d[2]), "+f"(d[3]) : "r"(a0), "r"(a2), "r"(b0), "r"(b1));
}
__device__ __forceinline__ void mma1688h(float* d, uint32_t a0, uint32_t b0) {
    asm volatile("{\n.reg .b32 ju;\nmma.sync.aligned.m16n8k8.row.col.f32.bf16.bf16.f32 {%0,%1,%2,%3}, {%4,ju}, {%5}, {%0,%1,%2,%3};\n}"
                 : "+f"(d[0]), "+f"(d[1]), "+f"(d[2]), "+f"(d[3]) : "r"(a0), "r"(b0));
}
__device__ __forceinline__ uint32_t pack2(float lo, float hi) {
    uint32_t r; asm("cvt.rn.bf16x2.f32 %0, %1, %2;" : "=r"(r) : "f"(hi), "f"(lo)); return r;
}
__device__ __forceinline__ float bflo(uint32_t w) { return __uint_as_float(w << 16); }
__device__ __forceinline__ float bfhi(uint32_t w) { return __uint_as_float(w & 0xffff0000u); }
__device__ __forceinline__ float rbf(float x) { return __bfloat162float(__float2bfloat16_rn(x)); }
__device__ __forceinline__ float ex2(float x) { float y; asm("ex2.approx.ftz.f32 %0, %1;" : "=f"(y) : "f"(x)); return y; }
__device__ __forceinline__ void sts128(uint32_t addr, uint4 v) {
    asm volatile("st.shared.v4.b32 [%0], {%1,%2,%3,%4};" :: "r"(addr), "r"(v.x), "r"(v.y), "r"(v.z), "r"(v.w) : "memory");
}
__device__ __forceinline__ uint4 lds128(uint32_t addr) {
    uint4 v; asm volatile("ld.shared.v4.b32 {%0,%1,%2,%3}, [%4];" : "=r"(v.x), "=r"(v.y), "=r"(v.z), "=r"(v.w) : "r"(addr) : "memory"); return v;
}
__device__ __forceinline__ float2 lds64f(uint32_t addr) {
    float2 v; asm volatile("ld.shared.v2.f32 {%0,%1}, [%2];" : "=f"(v.x), "=f"(v.y) : "r"(addr) : "memory"); return v;
}
__device__ __forceinline__ float lds32f(uint32_t addr) {
    float v; asm volatile("ld.shared.f32 %0, [%1];" : "=f"(v) : "r"(addr) : "memory"); return v;
}
__device__ __forceinline__ uint32_t lds32(uint32_t addr) {
    uint32_t v; asm volatile("ld.shared.b32 %0, [%1];" : "=r"(v) : "r"(addr) : "memory"); return v;
}
__device__ __forceinline__ void sts32(uint32_t addr, uint32_t v) { asm volatile("st.shared.b32 [%0], %1;" :: "r"(addr), "r"(v) : "memory"); }
__device__ __forceinline__ void sts64f(uint32_t addr, float a, float b) { asm volatile("st.shared.v2.f32 [%0], {%1,%2};" :: "r"(addr), "f"(a), "f"(b) : "memory"); }

__device__ __forceinline__ void tma_load2d(uint32_t dst, const CUtensorMap* tm, int c0, int c1, uint32_t bar) {
    asm volatile("cp.async.bulk.tensor.2d.shared::cluster.global.mbarrier::complete_tx::bytes [%0], [%1, {%3, %4}], [%2];"
                 :: "r"(dst), "l"(tm), "r"(bar), "r"(c0), "r"(c1) : "memory");
}
__device__ __forceinline__ void tma_store2d(const CUtensorMap* tm, uint32_t src, int c0, int c1) {
    asm volatile("cp.async.bulk.tensor.2d.global.shared::cta.bulk_group [%0, {%2, %3}], [%1];"
                 :: "l"(tm), "r"(src), "r"(c0), "r"(c1) : "memory");
}
__device__ __forceinline__ void bulk_commit() { asm volatile("cp.async.bulk.commit_group;" ::: "memory"); }
__device__ __forceinline__ void bulk_wait0() { asm volatile("cp.async.bulk.wait_group 0;" ::: "memory"); }
__device__ __forceinline__ void fence_async_smem() { asm volatile("fence.proxy.async.shared::cta;" ::: "memory"); }
__device__ __forceinline__ void fence_async_all() { asm volatile("fence.proxy.async;" ::: "memory"); }

__device__ __forceinline__ void wg_fence() { asm volatile("wgmma.fence.sync.aligned;" ::: "memory"); }
__device__ __forceinline__ void wg_commit() { asm volatile("wgmma.commit_group.sync.aligned;" ::: "memory"); }
__device__ __forceinline__ void wg_wait0() { asm volatile("wgmma.wait_group.sync.aligned 0;" ::: "memory"); }
__device__ __forceinline__ uint64_t mkdesc(uint32_t saddr, uint32_t lbo, uint32_t sbo) {
    return (uint64_t)((saddr & 0x3FFFF) >> 4) | ((uint64_t)(lbo >> 4) << 16) | ((uint64_t)(sbo >> 4) << 32) | (1ull << 62);
}
#define ACC8(i) "+f"(d[i]), "+f"(d[i + 1]), "+f"(d[i + 2]), "+f"(d[i + 3]), "+f"(d[i + 4]), "+f"(d[i + 5]), "+f"(d[i + 6]), "+f"(d[i + 7])
__device__ __forceinline__ void wgmma_n256(float* d, uint64_t da, uint64_t db, int scale_d) {
    asm volatile(
        "{\n.reg .pred p;\nsetp.ne.b32 p, %130, 0;\n"
        "wgmma.mma_async.sync.aligned.m64n256k16.f32.bf16.bf16 "
        "{%0,%1,%2,%3,%4,%5,%6,%7,%8,%9,%10,%11,%12,%13,%14,%15,%16,%17,%18,%19,%20,%21,%22,%23,%24,%25,%26,%27,%28,%29,%30,%31,"
        "%32,%33,%34,%35,%36,%37,%38,%39,%40,%41,%42,%43,%44,%45,%46,%47,%48,%49,%50,%51,%52,%53,%54,%55,%56,%57,%58,%59,%60,%61,%62,%63,"
        "%64,%65,%66,%67,%68,%69,%70,%71,%72,%73,%74,%75,%76,%77,%78,%79,%80,%81,%82,%83,%84,%85,%86,%87,%88,%89,%90,%91,%92,%93,%94,%95,"
        "%96,%97,%98,%99,%100,%101,%102,%103,%104,%105,%106,%107,%108,%109,%110,%111,%112,%113,%114,%115,%116,%117,%118,%119,%120,%121,%122,%123,%124,%125,%126,%127}, "
        "%128, %129, p, 1, 1, 0, 1;\n}"
        : ACC8(0), ACC8(8), ACC8(16), ACC8(24), ACC8(32), ACC8(40), ACC8(48), ACC8(56),
          ACC8(64), ACC8(72), ACC8(80), ACC8(88), ACC8(96), ACC8(104), ACC8(112), ACC8(120)
        : "l"(da), "l"(db), "r"(scale_d));
}
__device__ __forceinline__ void wgmma_n128(float* d, uint64_t da, uint64_t db, int scale_d) {
    asm volatile(
        "{\n.reg .pred p;\nsetp.ne.b32 p, %66, 0;\n"
        "wgmma.mma_async.sync.aligned.m64n128k16.f32.bf16.bf16 "
        "{%0,%1,%2,%3,%4,%5,%6,%7,%8,%9,%10,%11,%12,%13,%14,%15,%16,%17,%18,%19,%20,%21,%22,%23,%24,%25,%26,%27,%28,%29,%30,%31,"
        "%32,%33,%34,%35,%36,%37,%38,%39,%40,%41,%42,%43,%44,%45,%46,%47,%48,%49,%50,%51,%52,%53,%54,%55,%56,%57,%58,%59,%60,%61,%62,%63}, "
        "%64, %65, p, 1, 1, 0, 1;\n}"
        : ACC8(0), ACC8(8), ACC8(16), ACC8(24), ACC8(32), ACC8(40), ACC8(48), ACC8(56)
        : "l"(da), "l"(db), "r"(scale_d));
}

__device__ __forceinline__ void wgmma_n64(float* d, uint64_t da, uint64_t db) {
    asm volatile(
        "wgmma.mma_async.sync.aligned.m64n64k16.f32.bf16.bf16 "
        "{%0,%1,%2,%3,%4,%5,%6,%7,%8,%9,%10,%11,%12,%13,%14,%15,%16,%17,%18,%19,%20,%21,%22,%23,%24,%25,%26,%27,%28,%29,%30,%31}, "
        "%32, %33, 1, 1, 1, 0, 1;"
        : ACC8(0), ACC8(8), ACC8(16), ACC8(24)
        : "l"(da), "l"(db));
}
__device__ __forceinline__ void wgmma_n8_ta(float* d, uint64_t da, uint64_t db, int scale_d) {
    asm volatile(
        "{\n.reg .pred p;\nsetp.ne.b32 p, %6, 0;\n"
        "wgmma.mma_async.sync.aligned.m64n8k16.f32.bf16.bf16 {%0,%1,%2,%3}, %4, %5, p, 1, 1, 1, 0;\n}"
        : "+f"(d[0]), "+f"(d[1]), "+f"(d[2]), "+f"(d[3]) : "l"(da), "l"(db), "r"(scale_d));
}

__device__ __forceinline__ uint32_t hadd2(uint32_t a, uint32_t b) { uint32_t r; asm("add.rn.bf16x2 %0, %1, %2;" : "=r"(r) : "r"(a), "r"(b)); return r; }
__device__ __forceinline__ uint32_t hsub2(uint32_t a, uint32_t b) { uint32_t r; asm("sub.rn.bf16x2 %0, %1, %2;" : "=r"(r) : "r"(a), "r"(b)); return r; }
__device__ __forceinline__ uint32_t hmul2(uint32_t a, uint32_t b) { uint32_t r; asm("mul.rn.bf16x2 %0, %1, %2;" : "=r"(r) : "r"(a), "r"(b)); return r; }
__device__ __forceinline__ void load_mod8(const bf16* m, int lane, uint32_t* v) {
    const uint4 a = __ldcg((const uint4*)m + lane), b = __ldcg((const uint4*)m + 32 + lane);
    v[0] = a.x; v[1] = a.y; v[2] = a.z; v[3] = a.w; v[4] = b.x; v[5] = b.y; v[6] = b.z; v[7] = b.w;
}
__device__ __forceinline__ void ln_stats(const uint32_t* x, uint32_t& mu2, float& rden) {
    float s = 0.f;
#pragma unroll
    for (int i = 0; i < 8; i++) s += bflo(x[i]) + bfhi(x[i]);
#pragma unroll
    for (int o = 16; o > 0; o >>= 1) s += __shfl_xor_sync(~0u, s, o);
    const float mean = s * (1.f / D_);
    float q = 0.f;
#pragma unroll
    for (int i = 0; i < 8; i++) { const float d0 = bflo(x[i]) - mean, d1 = bfhi(x[i]) - mean; q = fmaf(d0, d0, q); q = fmaf(d1, d1, q); }
#pragma unroll
    for (int o = 16; o > 0; o >>= 1) q += __shfl_xor_sync(~0u, q, o);
    mu2 = pack2(mean, mean);
    rden = __frcp_rn(rbf(__fsqrt_rn(rbf(rbf(q * (1.f / D_)) + 1e-5f))));
}
__device__ __forceinline__ void ln_apply(const uint32_t* x, uint32_t mu2, float rden, const uint32_t* c1, const uint32_t* sm, uint32_t* r) {
#pragma unroll
    for (int i = 0; i < 8; i++) {
        const uint32_t d = hsub2(x[i], mu2);
        r[i] = hadd2(hmul2(pack2(bflo(d) * rden, bfhi(d) * rden), c1[i]), sm[i]);
    }
}

struct __align__(64) Params {
    CUtensorMap tm_h, tm_kv, tm_kvm, tm_o, tm_op, tm_h2, tm_act, tm_x1, tm_out;
    CUtensorMap tm_wq, tm_wk, tm_wv, tm_wo, tm_wg, tm_wu, tm_wd;
    const bf16 *x, *c, *w_mod;
    int qmask;
};

constexpr int R_NST = 3;
constexpr uint32_t R_WV = 0, R_MEM = 65536, R_KX = 73728, R_VX = R_KX + R_NST * 4096,
                   R_KMS = R_VX + R_NST * 4096  , R_VMS = R_KMS + 1024,
                   R_QS = R_KMS + 4096, R_OS = R_QS + 1024, R_SX = R_OS + 1024, R_BAR = R_SX + 2560,
                   R_RS = 107520  , R_VP = R_RS + 8192  ,
                   R_STG = R_VP + 8192  , R_SMEM = R_STG + 98304;
static_assert((R_KMS & 4095) == 0, "smem");
static_assert(R_BAR + 64 <= R_RS, "smem");
constexpr uint32_t RB_SX = R_BAR, RB_V = R_BAR + 8, RB_E = R_BAR + 16, RB_A = R_BAR + 24, RB_ROLE = R_BAR + 32, RB_A1 = R_BAR + 40;
constexpr int W_NST = 3;
constexpr uint32_t W_STAGE = 49152, W_STG = W_NST * W_STAGE, W_END = W_STG + 65536;
constexpr uint32_t SM_BAR = W_END;
constexpr uint32_t SMEM_BYTES = W_END + 1024 + 2048;
constexpr uint32_t B_FULL = 0, B_EMPTY = 32, B_STGFREE = 64, B_REQ = 80, B_RSP = 88, B_NEXT = 96, B_RING = 128;
#define PICK_AHEAD 3

constexpr int NB_X = 11  , NB_Y = 1, NB_M = 5, NB_K = 5, NB_B = 2, NB_C = 3, NB_D = 4, NB_W0 = 6  , NB_ST = 9  ;

__device__ __forceinline__ int pos_of_d(int d) {
    const int rem = d & 31;
    return (d & ~31) + ((rem & 7) >> 1) * 8 + (rem & 1) * 4 + (rem >> 3);
}

#define PROF(i) do {} while (0)
#define PROFG(i) do {} while (0)
#define OPAQUE(x) asm volatile("" : "+r"(x))
#define FENCE_SCHED(x) do { if ((x) == 0u) asm volatile("trap;"); } while (0)
#define VK0_ 4
constexpr int VK0 = VK0_;
constexpr int NOFF = 8;
#define VDELAY -1
#define POLL_GAP 110

struct RecParams { const bf16 *mem0, *wq, *wk, *wv, *wo; int ncl; };

__device__ __forceinline__ void rec_qk(const RecParams& p, const uint32_t sb, const int cta, const int warp, int lane, const int sel) {
    const int crank = cta & 15, cl = cta >> 4, rank = cta & 1;
    const int kh = warp >> 2, aa = warp & 3;
    uint32_t wa[2][16][4];
    const uint32_t stg = sb + R_STG + kh * 32768;
    {
        const int t128 = aa * 32 + lane;
        const int row = (lane >> 4) * 8 + (lane & 7);
        const int ch = t128 & 7;
        const size_t goff = (size_t)kh * 256 * HD_ + cta * 64 + ch * 8;
#pragma unroll 4
        for (int dd = 0; dd < 16; dd++) {
            const int d = dd * 16 + (t128 >> 3), pp = pos_of_d(d);
            cp_async16(sb + R_WV + kh * 32768 + pp * 128 + ((ch ^ (pp & 7)) << 4), p.wv + goff + (size_t)d * HD_);
        }
        cp_async_commit();
#pragma unroll 4
        for (int dd = 0; dd < 16; dd++) {
            const int d = dd * 16 + (t128 >> 3), pp = pos_of_d(d);
            cp_async16(stg + pp * 128 + ((ch ^ (pp & 7)) << 4), p.wq + goff + (size_t)d * HD_);
        }
        cp_async_commit();
        {
            const int i0 = (warp * 32 + lane) * 16, tok = i0 >> 9;
            const uint4 m0 = __ldg((const uint4*)(p.mem0 + i0)), m1 = __ldg((const uint4*)(p.mem0 + i0 + 8));
            const uint32_t mw[8] = {m0.x, m0.y, m0.z, m0.w, m1.x, m1.y, m1.z, m1.w};
#pragma unroll
            for (int e = 0; e < 16; e++) {
                const int pp = pos_of_d((i0 & 511) + e);
                const unsigned short v = (unsigned short)(mw[e >> 1] >> ((e & 1) * 16));
                asm volatile("st.shared.u16 [%0], %1;" :: "r"(sb + R_MEM + (pp >> 3) * 128 + tok * 16 + (pp & 7) * 2), "h"(v) : "memory");
            }
        }
        cp_async_wait<1>();
        bar_sync(NB_W0 + kh, 128);
        const uint32_t fv = row * 128 + (((2 * aa + ((lane >> 3) & 1)) ^ (row & 7)) << 4);
#pragma unroll
        for (int ks = 0; ks < 16; ks++) ldsm4t(wa[0][ks][0], wa[0][ks][1], wa[0][ks][2], wa[0][ks][3], sb + R_WV + kh * 32768 + fv + ks * 2048);
        bar_sync(NB_W0 + kh, 128);
#pragma unroll
        for (int ks = 0; ks < 16; ks++)
            sts128(sb + R_WV + kh * 32768 + (aa * 16 + ks) * 512 + lane * 16, make_uint4(wa[0][ks][0], wa[0][ks][1], wa[0][ks][2], wa[0][ks][3]));
        const uint32_t fo = stg + row * 128 + (((4 * (aa & 1) + ((lane >> 3) & 1)) ^ (row & 7)) << 4);
#pragma unroll 1
        for (int m = 0; m < 2; m++) {
            cp_async_wait<0>();
            bar_sync(NB_W0 + kh, 128);
            if ((aa >> 1) == m) {
#pragma unroll
                for (int ks = 0; ks < 16; ks++) {
                    ldsm4t(wa[0][ks][0], wa[0][ks][1], wa[0][ks][2], wa[0][ks][3], fo + ks * 2048);
                    ldsm4t(wa[1][ks][0], wa[1][ks][1], wa[1][ks][2], wa[1][ks][3], (fo ^ 32) + ks * 2048);
                }
            }
            bar_sync(NB_W0 + kh, 128);
            if (m == 0) {
#pragma unroll 4
                for (int dd = 0; dd < 16; dd++) {
                    const int d = dd * 16 + (t128 >> 3), pp = pos_of_d(d);
                    cp_async16(stg + pp * 128 + ((ch ^ (pp & 7)) << 4), p.wk + goff + (size_t)d * HD_);
                }
                cp_async_commit();
            }
        }
    }
    const uint32_t tab = stg + (aa * 32 + lane) * 16;
    {
        const uint32_t l7 = lane & 7, l8 = lane >> 3, g = lane >> 2, t = lane & 3;
        const uint32_t t0 = l7 * 128 + ((l8 ^ l7) << 4);
        const uint32_t tq = l7 * 128 + (((l8 >> 1) ^ l7) << 4);
        const uint32_t bq = warp >> 1, tp = warp & 1;
        uint4 v;
        v.x = sb + (aa < 2 ? R_QS : R_KMS) + l7 * 128 + (((4 * (aa & 1) + 2 * kh + (l8 & 1)) ^ l7) << 4);
        v.y = sb + R_QS + tq;
        v.z = sb + (warp == 0 ? R_KMS : R_KX + (warp - 1) * 1024) + t0;
        v.w = mapa_u32(sb + R_SX + (rank * 5 + warp) * 256 + lane * 8, crank ^ 1);
        sts128(tab, v);
        sts128(tab + 2048, make_uint4(sb + lane * 16 + R_MEM + kh * 4096, sb + lane * 16 + R_WV + warp * 8192,
                                      sb + lane * 16 + R_VP + warp * 512, sb + lane * 16 + R_VP + 4096 + (warp ^ 4) * 512));
        const uint32_t src = (l8 >> 1) * 8 + l7;
        const uint32_t L = bq * 8 + 2 * tp + (l8 & 1);
        const uint32_t d0 = (crank + ((t >> 1) | (g & 6))) & 15;
        v.x = sb + R_RS + src * 512 + ((L ^ (src & 7)) << 4);
        v.y = mapa_u32(sb + R_MEM + (crank * 4 + bq) * 128 + (4 * tp + 2 * (t & 1) + (g & 1)) * 16, d0);
        v.z = mapa_u32(sb + ((crank & 2) ? RB_A1 : RB_A), d0);
        v.w = lane;
        sts128(tab + 4096, v);
        const uint64_t wr = (uint64_t)(g_F + ((crank * 2 + ((crank ^ (crank >> 3) ^ sel) & 1)) * 1024 + warp * 128 + cl * 32 + lane));
        sts128(tab + 6144, make_uint4((uint32_t)wr, (uint32_t)(wr >> 32), (uint32_t)((((cl + 1) & 3) - cl) * 128), (uint32_t)((((cl + 2) & 3) - cl) * 128)));
        sts32(tab + 8192, (uint32_t)((((cl + 3) & 3) - cl) * 128));
#pragma unroll
        for (int i = 0; i < NOFF; i++)
            sts128(tab + 10240 + i * 2048, make_uint4(wa[i & 1][i >> 1][0], wa[i & 1][i >> 1][1], wa[i & 1][i >> 1][2], wa[i & 1][i >> 1][3]));
    }
    bar_sync(NB_D, 384);
    uint32_t slot_off = 0;
    const uint32_t slot_inc = warp == 0 ? 2048 : 4096, slot_last = warp == 0 ? 2048 : (R_NST - 1) * 4096;
    const uint32_t sx_bar_rem = (sb + RB_SX) ^ (1u << 24);
    uint4 tb = lds128(tab + 2048);
#pragma unroll 1
    for (int s = 0; s < NSEG; s++) {
        if (s > 0) mbar_wait(sb + RB_A, (s - 1) & 1);
        if (warp == 0) { PROF(0); PROFG(13); }
        uint4 ta;
        const uint32_t km_tog = aa >= 2 ? (s & 1) * 2048 : 0;
        {
            float acc[5][4];
#pragma unroll
            for (int c = 0; c < 5; c++) { acc[c][0] = acc[c][1] = acc[c][2] = acc[c][3] = 0.f; }
            uint32_t b[8][4];
            uint4 av[16];
            static_assert(VK0 == 4, "order below assumes the V/O warps cover slices 0,1");
            ldsm4(b[0][0], b[0][1], b[0][2], b[0][3], tb.x);
            ldsm4(b[1][0], b[1][1], b[1][2], b[1][3], tb.x + 512);
            ldsm4(b[4][0], b[4][1], b[4][2], b[4][3], tb.x + 2048);
            ldsm4(b[5][0], b[5][1], b[5][2], b[5][3], tb.x + 2560);
#pragma unroll
            for (int kk = 0; kk < 8; kk++) {
                const int k2 = kk < 2 ? kk : (kk < 4 ? kk + 2 : (kk < 6 ? kk - 2 : kk));
                if (kk == 4) {
                    if (s > 0) mbar_wait(sb + RB_A1, (s - 1) & 1);
                    ldsm4(b[2][0], b[2][1], b[2][2], b[2][3], tb.x + 1024);
                    ldsm4(b[3][0], b[3][1], b[3][2], b[3][3], tb.x + 1536);
                    ldsm4(b[6][0], b[6][1], b[6][2], b[6][3], tb.x + 3072);
                    ldsm4(b[7][0], b[7][1], b[7][2], b[7][3], tb.x + 3584);
#pragma unroll
                    for (int i = 12; i < 16; i++) av[i] = lds128(tb.y + i * 512);
                    ta = lds128(tab);
                }
                mma16816(acc[0], wa[0][2 * k2][0], wa[0][2 * k2][1], wa[0][2 * k2][2], wa[0][2 * k2][3], b[k2][0], b[k2][1]);
                mma16816(acc[1], wa[1][2 * k2][0], wa[1][2 * k2][1], wa[1][2 * k2][2], wa[1][2 * k2][3], b[k2][0], b[k2][1]);
                mma16816(acc[3], wa[0][2 * k2 + 1][0], wa[0][2 * k2 + 1][1], wa[0][2 * k2 + 1][2], wa[0][2 * k2 + 1][3], b[k2][2], b[k2][3]);
                mma16816(acc[4], wa[1][2 * k2 + 1][0], wa[1][2 * k2 + 1][1], wa[1][2 * k2 + 1][2], wa[1][2 * k2 + 1][3], b[k2][2], b[k2][3]);
                if (2 * k2 >= VK0) {
                    mma16816(acc[2], av[2 * k2].x, av[2 * k2].y, av[2 * k2].z, av[2 * k2].w, b[k2][0], b[k2][1]);
                    mma16816(acc[2], av[2 * k2 + 1].x, av[2 * k2 + 1].y, av[2 * k2 + 1].z, av[2 * k2 + 1].w, b[k2][2], b[k2][3]);
                }
                if (kk == 0) { av[8] = lds128(tb.y + 8 * 512); av[9] = lds128(tb.y + 9 * 512); }
                if (kk == 1) { av[10] = lds128(tb.y + 10 * 512); av[11] = lds128(tb.y + 11 * 512); }
                if (kk == 2) { av[4] = lds128(tb.y + 4 * 512); av[5] = lds128(tb.y + 5 * 512); }
                if (kk == 3) { av[6] = lds128(tb.y + 6 * 512); av[7] = lds128(tb.y + 7 * 512); }
            }
#pragma unroll
            for (int i = 0; i < 4; i++) { acc[0][i] += acc[3][i]; acc[1][i] += acc[4][i]; }
            const float g0 = kh ? acc[0][0] : acc[1][0], g1 = kh ? acc[0][1] : acc[1][1], g2 = kh ? acc[0][2] : acc[1][2], g3 = kh ? acc[0][3] : acc[1][3];
            sts128(tb.w, make_uint4(__float_as_uint(g0), __float_as_uint(g1), __float_as_uint(g2), __float_as_uint(g3)));
            const float k0 = kh ? acc[1][0] : acc[0][0], k1 = kh ? acc[1][1] : acc[0][1], k2_ = kh ? acc[1][2] : acc[0][2], k3 = kh ? acc[1][3] : acc[0][3];
            if (warp == 0) PROF(1);
            bar_sync(NB_X + aa, 64);
            const uint4 o = lds128(tb.z + 4096);
            stsm2t(ta.x ^ km_tog, pack2(k0 + __uint_as_float(o.x), k1 + __uint_as_float(o.y)), pack2(k2_ + __uint_as_float(o.z), k3 + __uint_as_float(o.w)));
            sts128(tb.z, make_uint4(__float_as_uint(acc[2][0]), __float_as_uint(acc[2][1]), __float_as_uint(acc[2][2]), __float_as_uint(acc[2][3])));
        }
        const uint32_t kb = ta.z + slot_off;
        if (warp == 0) PROF(14);
        bar_sync(NB_B, 256);
        if (warp < 5) {
            uint32_t q[16], k0, k1, k2, k3, k4, k5, k6, k7;
            float sa[4] = {0.f, 0.f, 0.f, 0.f}, sc[4] = {0.f, 0.f, 0.f, 0.f};
            ldsm4(q[0], q[1], q[2], q[3], ta.y);
            ldsm4(k0, k1, k2, k3, kb);
            ldsm4(q[4], q[5], q[6], q[7], ta.y ^ 32);
            ldsm4(q[8], q[9], q[10], q[11], ta.y ^ 64);
            ldsm4(k4, k5, k6, k7, kb ^ 64);
            ldsm4(q[12], q[13], q[14], q[15], ta.y ^ 96);
            mma16816(sa, q[0], q[1], q[2], q[3], k0, k1);
            bar_arrive(NB_Y, 288);
            mma16816(sc, q[4], q[5], q[6], q[7], k2, k3);
            mma16816(sa, q[8], q[9], q[10], q[11], k4, k5);
            mma16816(sc, q[12], q[13], q[14], q[15], k6, k7);
            const float scl = 0.08838834764831845f * 1.4426950408889634f;
            const float r0 = (sa[0] + sc[0]) * scl, r1 = (sa[1] + sc[1]) * scl;
            if (s != NSEG - 1) {
                st_async_v2(ta.w, r0, r1, sx_bar_rem);
                st_async_v2(ta.w ^ (1u << 24), r0, r1, sx_bar_rem ^ (1u << 24));
            }
            if (warp == 0) PROF(2);
        } else if (s > 0 && warp == 7 && lane == 0) {
            mbar_expect_tx(sb + RB_A, 4096);
            mbar_expect_tx(sb + RB_A1, 4096);
        } else if (s > 0 && (s & 3) == 0 && warp == 6) {
            bar_sync(NB_K, 160);
            if (lane == 0) red_release(&g_flags[F_MEM + (s >> 2) - 1], 1);
            __syncwarp();
        }
        if (s == NSEG - 1) {
            const uint4 td = lds128(tab + 6144);
            stg_relaxed32((uint32_t*)(((uint64_t)td.y << 32) | (td.x ^ 0x21000)), 0u);
            break;
        }
        slot_off = slot_off == slot_last ? 0 : slot_off + slot_inc;
        const uint4 tc = lds128(tab + 4096), td = lds128(tab + 6144);
        const uint32_t te = lds32(tab + 8192);
        uint32_t* wr = (uint32_t*)(((uint64_t)td.y << 32) | (td.x ^ ((s & 1) * 0x21000)));
        const uint32_t* r1p = (const uint32_t*)((const char*)wr + (int)td.z);
        const uint32_t* r2p = (const uint32_t*)((const char*)wr + (int)td.w);
        const uint32_t* r3p = (const uint32_t*)((const char*)wr + (int)te);
        const uint32_t tag = ((s >> 1) + 1) & 1;
        mbar_wait(sb + RB_E, s & 1);
        if (warp == 0) PROF(7);
        {
            uint32_t a0, a1, a2, a3, a4, a5, a6, a7;
            ldsm4t(a0, a1, a2, a3, tc.x);
            ldsm4t(a4, a5, a6, a7, tc.x ^ 64);
            const uint32_t one = 0x3F803F80u;
            float d0_[4] = {0.f, 0.f, 0.f, 0.f}, d1_[4] = {0.f, 0.f, 0.f, 0.f};
            mma16816(d0_, a0, a1, a2, a3, one, one);
            mma16816(d1_, a4, a5, a6, a7, one, one);
            const bool t1 = tc.w & 1, t2 = tc.w & 2;
            const float x = t2 ? (t1 ? d1_[2] : d1_[0]) : (t1 ? d0_[2] : d0_[0]);
            const uint32_t own = (__float_as_uint(x) & ~1u) | tag;
            stg_relaxed32(wr, own);
            const uint32_t tq = clk32();
            if (warp == 0) PROF(8);
            PROFG(16 + warp);
            while ((int)(clk32() - tq) < POLL_GAP) {}
            uint32_t f1 = ldg_relaxed32(r1p), f2 = ldg_relaxed32(r2p), f3 = ldg_relaxed32(r3p);
#pragma unroll
            for (int i = 0; i < NOFF; i++) {
                const uint4 f0 = lds128(tab + 10240 + i * 2048);
                wa[i & 1][i >> 1][0] = f0.x; wa[i & 1][i >> 1][1] = f0.y; wa[i & 1][i >> 1][2] = f0.z; wa[i & 1][i >> 1][3] = f0.w;
            }
            tb = lds128(tab + 2048);
            int gg = 0;
#pragma unroll 1
            while (!__all_sync(~0u, (((f1 ^ tag) | (f2 ^ tag) | (f3 ^ tag)) & 1) == 0)) {
                f1 = ldg_relaxed32(r1p); f2 = ldg_relaxed32(r2p); f3 = ldg_relaxed32(r3p);
                if (++gg > 16 * SPIN_LIMIT) { TIMEOUT(3, s); break; }
            }
            if (warp == 0) PROF(9);
            const float v = (__uint_as_float(own) + __uint_as_float(f2)) + (__uint_as_float(f1) + __uint_as_float(f3));
            const bool b8 = tc.w & 8, b16 = tc.w & 16;
            const float recv = __shfl_xor_sync(~0u, v, 8);
            const uint32_t word = b8 ? pack2(recv, v) : pack2(v, recv);
            const uint32_t oth = __shfl_xor_sync(~0u, word, 16);
            const uint32_t wl = b16 ? oth : word, wh = b16 ? word : oth;
            const uint32_t p0 = __shfl_xor_sync(~0u, wl, 2), p1 = __shfl_xor_sync(~0u, wh, 2);
            const uint4 item = t2 ? make_uint4(p0, p1, wl, wh) : make_uint4(wl, wh, p0, p1);
            st_async_v4(tc.y, item, tc.z);
            st_async_v4(tc.y ^ (8u << 24), item, tc.z ^ (8u << 24));
            if (tc.w == 0 && warp == 7) mbar_expect_tx(sb + RB_E, 8192);
            if (warp == 0) PROF(10);
            PROF(40 + warp);
        }
        bar_sync(NB_D, 384);
    }
}

__device__ __forceinline__ void rec_load_kv(uint32_t sb, int col0, int s, uint32_t slot_off, int t128) {
    const int row = t128 >> 2, c2 = (t128 & 3) * 2;
    const bf16* src = g_kv + ((size_t)(s * 32 + row) * (2 * HD_) + col0 + c2 * 8);
    const uint32_t d0 = sb + R_KX + slot_off + row * 128 + ((c2 ^ (row & 7)) << 4);
    cp_async16(d0, src);
    cp_async16(d0 ^ 16, src + 8);
    cp_async16(d0 + (R_VX - R_KX), src + HD_);
    cp_async16((d0 ^ 16) + (R_VX - R_KX), src + HD_ + 8);
}

__device__ __forceinline__ void rec_store_kvm(uint32_t sb, int col0, int s, int w, int lane) {
    const int tok = (w & 1) * 4 + (lane >> 3);
    const uint4 v = lds128(sb + R_KMS + (s & 1) * 2048 + (w >> 1) * 1024 + tok * 128 + (((lane & 7) ^ tok) << 4));
    *(uint4*)(g_kvm + ((s * 8 + tok) * (2 * HD_) + (w >> 1) * HD_ + col0 + (lane & 7) * 8)) = v;
}

__device__ __forceinline__ void rec_vo(const RecParams& p, const uint32_t sb, const int cta, const int warp, int lane) {
    const int w = warp - 8, crank = cta & 15;
    const int col0 = cta * 64;
    uint32_t wo[8][4][4];
    {
        const int t128 = w * 32 + lane;
        const bf16* Wo = p.wo + (size_t)col0 * D_;
        const uint32_t stg = sb + R_STG + 2 * 32768;
#pragma unroll
        for (int half = 0; half < 2; half++) {
#pragma unroll 4
            for (int i = t128; i < 2048; i += 128) {
                const int e = i >> 6, ch = i & 63;
                cp_async16(stg + e * 1024 + ((ch ^ (e & 7)) << 4), Wo + (size_t)(half * 32 + e) * D_ + ch * 8);
            }
            cp_async_commit();
            cp_async_wait<0>();
            bar_sync(NB_W0 + 2, 128);
#pragma unroll
            for (int j = 0; j < 8; j++)
#pragma unroll
                for (int kk = 0; kk < 2; kk++) {
                    const int e = kk * 16 + (lane >> 4) * 8 + (lane & 7);
                    const int ch = (w * 8 + j) * 2 + ((lane >> 3) & 1);
                    ldsm4t(wo[j][half * 2 + kk][0], wo[j][half * 2 + kk][1], wo[j][half * 2 + kk][2], wo[j][half * 2 + kk][3],
                           stg + e * 1024 + ((ch ^ (e & 7)) << 4));
                }
            bar_sync(NB_W0 + 2, 128);
        }
        if (lane == 0) wait_flag(F_KV + 0, 64);
        __syncwarp();
        rec_load_kv(sb, col0, 0, 0, t128); cp_async_commit();
        rec_load_kv(sb, col0, 1, 4096, t128); cp_async_commit();
        cp_async_wait<1>();
    }
    const uint32_t tab = sb + R_STG + 2 * 32768 + (w * 32 + lane) * 16;
    {
        const uint32_t l7 = lane & 7, l8 = lane >> 3, g = lane >> 2;
        uint4 v;
        v.x = sb + R_VX + ((l8 & 1) * 8 + l7) * 128 + (((2 * w + (l8 >> 1)) ^ l7) << 4);
        v.y = sb + R_OS + g * 128 + (((2 * w) ^ g) << 4) + (lane & 3) * 4;
        v.z = sb + R_VMS + l7 * 128 + (((2 * w + (l8 & 1)) ^ l7) << 4);
        v.w = sb + R_OS + l7 * 128 + ((l8 ^ l7) << 4);
        sts128(tab, v);
        v.x = mapa_u32(sb + R_RS + crank * 512 + ((lane ^ (crank & 7)) << 4), w * 4);
        v.y = mapa_u32(sb + RB_E, w * 4);
        v.z = sb + R_VP + w * 512 + lane * 16;
        v.w = sb + R_SX + lane * 8;
        sts128(tab + 2048, v);
#pragma unroll
        for (int i = 0; i < 8; i++) sts128(tab + 4096 + i * 2048, make_uint4(wo[i][0][0], wo[i][0][1], wo[i][0][2], wo[i][0][3]));
        const int tok = (w & 1) * 4 + (lane >> 3), row = (w * 32 + lane) >> 2, c2 = (lane & 3) * 2;
        const uint64_t kd = (uint64_t)(g_kvm + (tok * (2 * HD_) + (w >> 1) * HD_ + col0 + (lane & 7) * 8));
        const uint64_t ks = (uint64_t)(g_kv + ((size_t)row * (2 * HD_) + col0 + c2 * 8));
        sts128(tab + 20480, make_uint4((uint32_t)kd, (uint32_t)(kd >> 32), (uint32_t)ks, (uint32_t)(ks >> 32)));
        sts128(tab + 22528, make_uint4(sb + R_KMS + (w >> 1) * 1024 + tok * 128 + (((lane & 7) ^ tok) << 4),
                                       sb + R_KX + row * 128 + ((c2 ^ (row & 7)) << 4), lane, 0));
    }
    bar_sync(NB_D, 384);
    const uint32_t lane16 = lds32(tab + 2048 + 8) - R_VP - w * 512;
    uint4 av[2 * VK0];
#pragma unroll
    for (int i = 0; i < 2 * VK0; i++) av[i] = lds128(lane16 + R_WV + (i / VK0) * 32768 + (w * 16 + i % VK0) * 512);
    uint32_t slot_off = 0;
#pragma unroll 1
    for (int s = 0; s < NSEG; s++) {
        if (s > 0) {
            mbar_wait(sb + RB_A, (s - 1) & 1);
            const uint4 tp = lds128(tab + 20480), tq = lds128(tab + 22528);
            const uint4 kvm = lds128(tq.x + ((s - 1) & 1) * 2048);
            *(uint4*)((((uint64_t)tp.y << 32) | tp.x) + (uint64_t)(s - 1) * (8 * 2 * HD_ * 2)) = kvm;
            if ((s & 3) == 0) bar_arrive(NB_K, 160);
            if (s + 1 < NSEG - 1) {
                if (((s + 1) & 3) == 0) { if (tq.z == 0) wait_flag(F_KV + ((s + 1) >> 2), 64); __syncwarp(); }
                const char* src = (const char*)((((uint64_t)tp.w << 32) | tp.z) + (uint64_t)(s + 1) * (32 * 2 * HD_ * 2));
                const uint32_t d0 = tq.y + (slot_off == (R_NST - 1) * 4096 ? 0 : slot_off + 4096);
                cp_async16(d0, src);
                cp_async16(d0 ^ 16, src + 16);
                cp_async16(d0 + (R_VX - R_KX), src + HD_ * 2);
                cp_async16((d0 ^ 16) + (R_VX - R_KX), src + HD_ * 2 + 16);
            }
            cp_async_commit();
        }
        bar_sync(NB_Y, 288);
        uint32_t vb0, vb1;
        {
            float va[4] = {0.f, 0.f, 0.f, 0.f}, vc[4] = {0.f, 0.f, 0.f, 0.f};
            uint32_t bb[VK0][4];
#pragma unroll
            for (int k2 = 0; k2 < VK0; k2++) ldsm4(bb[k2][0], bb[k2][1], bb[k2][2], bb[k2][3], lane16 + R_MEM + (k2 / (VK0 / 2)) * 4096 + (k2 % (VK0 / 2)) * 512);
#pragma unroll
            for (int k2 = 0; k2 < VK0; k2++) {
                mma16816(va, av[2 * k2].x, av[2 * k2].y, av[2 * k2].z, av[2 * k2].w, bb[k2][0], bb[k2][1]);
                mma16816(vc, av[2 * k2 + 1].x, av[2 * k2 + 1].y, av[2 * k2 + 1].z, av[2 * k2 + 1].w, bb[k2][2], bb[k2][3]);
            }
            const uint4 a = lds128(lane16 + R_VP + w * 512), b = lds128(lane16 + R_VP + 2048 + w * 512);
            vb0 = pack2((va[0] + vc[0]) + (__uint_as_float(a.x) + __uint_as_float(b.x)), (va[1] + vc[1]) + (__uint_as_float(a.y) + __uint_as_float(b.y)));
            vb1 = pack2((va[2] + vc[2]) + (__uint_as_float(a.z) + __uint_as_float(b.z)), (va[3] + vc[3]) + (__uint_as_float(a.w) + __uint_as_float(b.w)));
        }
        const uint4 ta = lds128(tab), tb = lds128(tab + 2048);
        uint32_t vx[8];
        ldsm4t(vx[0], vx[1], vx[2], vx[3], ta.x + slot_off);
        ldsm4t(vx[4], vx[5], vx[6], vx[7], ta.x + slot_off + 2048);
#pragma unroll
        for (int i = 0; i < 4; i++) {
            const uint4 f0 = lds128(tab + 4096 + i * 2048);
            wo[i][0][0] = f0.x; wo[i][0][1] = f0.y; wo[i][0][2] = f0.z; wo[i][0][3] = f0.w;
        }
        if (w == 0) PROF(11);
        uint32_t pf[5];
        float oa[2][4] = {{0.f, 0.f, 0.f, 0.f}, {0.f, 0.f, 0.f, 0.f}}, ob_[2][4] = {{0.f, 0.f, 0.f, 0.f}, {0.f, 0.f, 0.f, 0.f}};
        float sm0[4] = {0.f, 0.f, 0.f, 0.f}, sm1[4] = {0.f, 0.f, 0.f, 0.f};
        if (s != NSEG - 1) {
            mbar_wait(sb + RB_SX, s & 1);
            if (w == 0) PROF(4);
            float sv[10];
#pragma unroll
            for (int n = 0; n < 5; n++) {
                const float2 a = lds64f(tb.w + n * 256), b = lds64f(tb.w + (5 + n) * 256);
                sv[2 * n] = a.x + b.x; sv[2 * n + 1] = a.y + b.y;
            }
            float mx = fmaxf(fmaxf(fmaxf(sv[0], sv[1]), fmaxf(sv[2], sv[3])), fmaxf(fmaxf(sv[4], sv[5]), fmaxf(sv[6], sv[7])));
            mx = fmaxf(mx, fmaxf(sv[8], sv[9]));
            mx = fmaxf(mx, __shfl_xor_sync(~0u, mx, 1));
            mx = fmaxf(mx, __shfl_xor_sync(~0u, mx, 2));
#pragma unroll
            for (int n = 1; n < 5; n++) pf[n] = pack2(ex2(sv[2 * n] - mx), ex2(sv[2 * n + 1] - mx));
            pf[0] = pack2(ex2(sv[0] - mx), ex2(sv[1] - mx));
            if (w == 0) PROF(12);
            const uint32_t one = 0x3F803F80u;
            mma16816h(sm0, pf[1], pf[2], one, one);
            mma16816h(oa[0], pf[1], pf[2], vx[0], vx[1]);
            mma16816h(oa[1], pf[1], pf[2], vx[2], vx[3]);
            mma16816h(sm1, pf[3], pf[4], one, one);
            mma16816h(ob_[0], pf[3], pf[4], vx[4], vx[5]);
            mma16816h(ob_[1], pf[3], pf[4], vx[6], vx[7]);
            mma1688h(sm0, pf[0], one);
            mma1688h(oa[0], pf[0], vb0);
            mma1688h(oa[1], pf[0], vb1);
            float inv;
            asm("rcp.approx.ftz.f32 %0, %1;" : "=f"(inv) : "f"(sm0[0] + sm1[0]));
            oa[0][0] += ob_[0][0]; oa[0][1] += ob_[0][1]; oa[1][0] += ob_[1][0]; oa[1][1] += ob_[1][1];
            sts32(ta.y, pack2(oa[0][0] * inv, oa[0][1] * inv));
            sts32(ta.y ^ 16, pack2(oa[1][0] * inv, oa[1][1] * inv));
            const uint32_t oa2 = ta.w ^ 64;
            bar_sync(NB_C, 128);
            if (w == 0) PROF(5);
            uint32_t ob[8];
            ldsm4(ob[0], ob[1], ob[2], ob[3], ta.w);
            ldsm4(ob[4], ob[5], ob[6], ob[7], oa2);
#pragma unroll
            for (int i = 4; i < 8; i++) {
                const uint4 f0 = lds128(tab + 4096 + i * 2048);
                wo[i][0][0] = f0.x; wo[i][0][1] = f0.y; wo[i][0][2] = f0.z; wo[i][0][3] = f0.w;
            }
#pragma unroll
            for (int jj = 0; jj < 2; jj++) {
                if (jj == 1 && tb.w == 0) break;
                float acc[4][4];
#pragma unroll
                for (int c = 0; c < 4; c++) { acc[c][0] = acc[c][1] = acc[c][2] = acc[c][3] = 0.f; }
#pragma unroll
                for (int ks = 0; ks < 4; ks++)
#pragma unroll
                    for (int c = 0; c < 4; c++)
                        mma16816(acc[c], wo[jj * 4 + c][ks][0], wo[jj * 4 + c][ks][1], wo[jj * 4 + c][ks][2], wo[jj * 4 + c][ks][3], ob[2 * ks], ob[2 * ks + 1]);
#pragma unroll
                for (int pr = 0; pr < 2; pr++) {
                    uint4 v;
                    v.x = pack2(acc[2 * pr][0], acc[2 * pr][1]);
                    v.y = pack2(acc[2 * pr][2], acc[2 * pr][3]);
                    v.z = pack2(acc[2 * pr + 1][0], acc[2 * pr + 1][1]);
                    v.w = pack2(acc[2 * pr + 1][2], acc[2 * pr + 1][3]);
                    st_async_v4(tb.x + ((jj * 2 + pr) << 24), v, tb.y + ((jj * 2 + pr) << 24));
                }
            }
            if (w == 0) PROF(6);
        }
        stsm2t(ta.z + (s & 1) * 2048, vb0, vb1);
        cp_async_wait<0>();
        bar_sync(NB_C, 128);
        if (w == 0 && lane == 0 && s != NSEG - 1) mbar_expect_tx(sb + RB_SX, 2560);
        if (s != NSEG - 1) bar_arrive(NB_D, 384);
#pragma unroll
        for (int i = 0; i < 2 * VK0; i++) av[i] = lds128(lane16 + R_WV + (i / VK0) * 32768 + (w * 16 + i % VK0) * 512);
        slot_off = slot_off == (R_NST - 1) * 4096 ? 0 : slot_off + 4096;
    }
    rec_store_kvm(sb, col0, NSEG - 1, w, lane);
    bar_sync(NB_C, 128);
    if (w == 0 && lane == 0) red_release(&g_flags[F_MEM + NRB - 1], 1);
}

__global__ void __launch_bounds__(384, 1) k_rec(const RecParams p) {
    extern __shared__ __align__(1024) unsigned char smem_raw[];
    const uint32_t sb = __shfl_sync(~0u, smem_u32(smem_raw), 0);
    const int warp = __shfl_sync(~0u, threadIdx.x >> 5, 0);
    int lane; asm volatile("mov.u32 %0, %%laneid;" : "=r"(lane));
    const int crank = blockIdx.x & 15, slot = blockIdx.x >> 4;
    asm volatile("griddepcontrol.launch_dependents;");
    if (threadIdx.x == 0) {
        mbar_init(sb + RB_SX, 1); mbar_init(sb + RB_E, 1); mbar_init(sb + RB_A, 1); mbar_init(sb + RB_A1, 1); mbar_init(sb + RB_ROLE, 1);
        asm volatile("fence.mbarrier_init.release.cluster;" ::: "memory");
        mbar_expect_tx(sb + RB_SX, 2560);
        mbar_expect_tx(sb + RB_E, 8192);
        mbar_expect_tx(sb + RB_A, 4096);
        mbar_expect_tx(sb + RB_A1, 4096);
        mbar_expect_tx(sb + RB_ROLE, 4);
    }
    unsigned role = 0;
    if (crank == 0 && threadIdx.x == 0) {
        unsigned x = 0;
        int tm[2] = {0x7fffffff, 0x7fffffff};
#pragma unroll 1
        for (int i = 0; i < 6; i++) {
            const uint32_t t0 = clk32();
            x = atomicAdd(&g_F[65536 + (i & 1) * 1024 + slot * 64 + (x >> 31)], 0u) & 0x7fffffffu;
            if (x == 0x7654321u) sts32(sb + R_BAR + 56, x);
            const int dt = (int)(clk32() - t0);
            if (i >= 2) { if (i & 1) tm[1] = min(tm[1], dt); else tm[0] = min(tm[0], dt); }
        }
        const int side = tm[1] > tm[0];
        const unsigned old = atomicAdd(&g_flags[F_SIDE + side * 32], 1u);
        unsigned c0, c1; int gd = 0;
#pragma unroll 1
        do { c0 = ldg_relaxed32(&g_flags[F_SIDE]); c1 = ldg_relaxed32(&g_flags[F_SIDE + 32]); } while ((int)(c0 + c1) < p.ncl && ++gd < 64 * SPIN_LIMIT);
        const int big = c1 > c0;
        role = side == big ? old : (big ? c1 : c0) + old;
        role |= (big ^ 1) << 8;
    }
    __syncwarp();
    asm volatile("barrier.cluster.arrive.relaxed.aligned;\nbarrier.cluster.wait.aligned;" ::: "memory");
    if (crank == 0 && warp == 0) {
        role = __shfl_sync(~0u, role, 0);
        if (lane < 16)
            asm volatile("st.async.weak.shared::cluster.mbarrier::complete_tx::bytes.u32 [%0], %1, [%2];"
                         :: "r"(mapa_u32(sb + R_BAR + 48, lane)), "r"(role), "r"(mapa_u32(sb + RB_ROLE, lane)) : "memory");
    }
    mbar_wait(sb + RB_ROLE, 0);
    const int rolew = __shfl_sync(~0u, lds32(sb + R_BAR + 48), 0);
    const int cl = rolew & 255;
    if (cl >= 4) return;
    const int cta = cl * 16 + crank;
    if (warp < 8) rec_qk(p, sb, cta, warp, lane, rolew >> 8);
    else rec_vo(p, sb, cta, warp, lane);
}

enum { J_KV = 0, J_QA = 1, J_O = 2, J_LN = 3, J_UP = 4, J_DN = 5, J_LN1 = 6, J_MOD = 7, J_UP2 = 8, J_END = 9 };
constexpr int NJ_O = 2 * OSPLIT, NJ_O2 = 2 * OSPLIT2, NJ_LN = 8, NJ_LN2 = 16, NJ_UP = 14, NJ_UP2 = 28, NJ_DN = 8, NJ_LN1 = 8;
constexpr uint64_t pk8(int a, int b, int c, int d, int e, int f, int g, int h) {
    return (uint64_t)a | ((uint64_t)b << 8) | ((uint64_t)c << 16) | ((uint64_t)d << 24) | ((uint64_t)e << 32) | ((uint64_t)f << 40) | ((uint64_t)g << 48) | ((uint64_t)h << 56);
}
constexpr uint64_t NJ_C = pk8(32, 16, NJ_O, NJ_LN, NJ_UP, NJ_DN, NJ_LN1, 16), NJ_F = pk8(32, 16, NJ_O2, NJ_LN2, NJ_UP2, NJ_DN, NJ_LN1, 0);
constexpr uint64_t TG_C = pk8(2 * NJ_LN1, 64, 32, 2 * NJ_O, 2 * NJ_LN, 2 * NJ_UP, 32, 0), TG_F = pk8(2 * NJ_LN1, 64, 32, 2 * NJ_O2, 2 * NJ_LN2, 2 * NJ_UP2, 32, 0);
constexpr uint64_t PRIO = pk8(4, 10, 9, 8, 7, 6, 3, 0);
__device__ __forceinline__ int pick_job(int lane, int qmask, int& idx) {
    const int rb = lane & 15, half = lane >> 4;
    const uint64_t nj = (rb >= FINE_RB ? NJ_F : (rb < 3 ? NJ_C : NJ_C & ~(0xffull << 56))) >> (8 * half);
    const uint64_t tg = (rb >= FINE_RB ? TG_F : TG_C) >> (8 * half);
    const unsigned* cp = &g_flags[F_CLAIM + half * 32 + rb];
    const unsigned* dp = &g_flags[half * 32 + rb];
    int gd = 0;
#pragma unroll 1
    while (true) {
        const unsigned c0 = ldg_relaxed32(cp), c1 = ldg_relaxed32(cp + 64), c2 = ldg_relaxed32(cp + 128), c3 = ldg_relaxed32(cp + 192);
        const unsigned d0 = ldg_relaxed32(dp - (half ? (rb >= FINE_RB ? 2 : (rb ? 1 : 0)) : 0)), d1 = ldg_relaxed32(dp + 64), d2 = ldg_relaxed32(dp + 128), d3 = ldg_relaxed32(dp + 192 - rb);
        const unsigned cl[4] = {c0, c1, c2, c3}, dv[4] = {d0, d1, d2, d3};
        unsigned key = 0xffffu, key2 = 0xffffu;
        bool pre = false;
#pragma unroll
        for (int i = 0; i < 4; i++) {
            const int q = half + 2 * i;
            const bool have = ((qmask >> q) & 1) && cl[i] < (unsigned)((nj >> (16 * i)) & 255);
            bool ready = have && dv[i] >= (unsigned)((tg >> (16 * i)) & 255);
            unsigned pr = (unsigned)((PRIO >> (8 * q)) & 255);
            if (i == 0 && rb == 0) { ready = have; pr = half ? pr : 2; }
            if (i == 3 && rb == 0) ready = have;
            if (i == 3 && rb == 0 && !half) pr = 1;
            if (i == 3 && rb > 0) pr = 3;
            if (i == 0 && half && rb >= FINE_RB) pr = 5;
            if (ready) key = min(key, (pr << 8) | (rb << 4) | q);
            if (have) key2 = min(key2, rb >= FINE_RB ? (0x100u | (q << 4) | rb) : 0u);
            pre |= have && (i == 3 || (i == 0 && !half));
        }
        const bool anypre = __any_sync(~0u, pre);
        if (anypre && (key & 15) == J_QA) key = 0xffffu;
        key = __reduce_min_sync(~0u, key);
        key2 = __reduce_min_sync(~0u, key2);
        if (key2 == 0xffffu) return J_END;
        int pq, prb;
        if (key != 0xffffu) { pq = key & 15; prb = (key >> 4) & 15; }
        else if (key2 >= 0x120u && key2 < 0x1000u) { pq = (key2 >> 4) & 15; prb = key2 & 15; }
        else {
            __nanosleep(IDLE_NS);
            if (++gd > 16 * SPIN_LIMIT) { TIMEOUT(5, 0); return J_END; }
            continue;
        }
        int c = 0;
        if (lane == 0) c = (int)atomicAdd(&g_flags[F_CLAIM + pq * 32 + prb], 1u);
        c = __shfl_sync(~0u, c, 0);
        if (c < (int)(((prb >= FINE_RB ? NJ_F : NJ_C) >> (8 * pq)) & 255)) {
            idx = pq * 512 + prb * 32 + c;
            int acq = 0;
            if (pq != J_QA && pq < J_LN1) {
                if (lane == 0 && ld_acquire(&g_flags[pq * 32 + prb]) >= (unsigned)(((prb >= FINE_RB ? TG_F : TG_C) >> (8 * pq)) & 255)) {
                    asm volatile("fence.proxy.async.global;" ::: "memory");
                    acq = 1 << 24;
                }
            }
            return (pq == J_UP && prb >= FINE_RB ? J_UP2 : pq) | (prb << 8) | (c << 16) | acq;
        }
    }
}
__device__ __forceinline__ int op_row(int rb, int split) {
    return rb < FINE_RB ? split * S_ + rb * 128 : OSPLIT * S_ + (split * (NRB - FINE_RB) + rb - FINE_RB) * 128;
}

struct Pipe { uint32_t stage, phase; };
__device__ __forceinline__ void pipe_next(Pipe& p) { if (++p.stage == W_NST) { p.stage = 0; p.phase ^= 1; } }

__device__ __forceinline__ void scheduler(const Params& p, uint32_t sb, int lane) {
    const uint32_t bars = sb + SM_BAR;
    uint32_t ph = 0;
#pragma unroll 1
    while (true) {
        mbar_wait(bars + B_REQ, ph);
        int j = 4095;
        const int jd = pick_job(lane, p.qmask, j);
        if (lane == 0) { sts32(bars + B_NEXT, (uint32_t)jd); sts32(bars + B_NEXT + 4, (uint32_t)j); mbar_arrive(bars + B_RSP); }
        ph ^= 1;
        if (jd == J_END) break;
        __syncwarp();
    }
}

__device__ __forceinline__ void producer(const Params& p, uint32_t sb) {
    Pipe pp{0, 1};
    const uint32_t bars = sb + SM_BAR;
    uint32_t seq = 0, h_seen = 0;
    mbar_arrive(bars + B_REQ);
#pragma unroll 1
    while (true) {
        mbar_wait(bars + B_RSP, seq & 1);
        const int jd = (int)lds32(bars + B_NEXT), j = (int)lds32(bars + B_NEXT + 4);
        int left = (jd & 255) == J_DN ? 15 : ((jd & 255) == J_QA ? 12 : ((jd & 255) == J_O ? (((jd >> 8) & 255) >= FINE_RB ? 64 / OSPLIT2 : 64 / OSPLIT) : ((jd & 255) == J_LN || (jd & 255) == J_LN1 || (jd & 255) == J_MOD ? 1 : 8)));
        left = max(left - PICK_AHEAD, 1);
        TR(j, 1);
        const int type = jd & 255, rb = (jd >> 8) & 255, cb = (jd >> 16) & 255;
        const bool fine = rb >= FINE_RB, acquired = (jd >> 24) & 1;
        bool first = true;
        auto begin_stage = [&](uint32_t bytes) -> uint32_t {
            mbar_wait(bars + B_EMPTY + pp.stage * 8, pp.phase);
            if (first) { sts32(bars + B_RING + (seq & 7) * 4, (uint32_t)jd); sts32(bars + B_RING + 32 + (seq & 7) * 4, (uint32_t)j); first = false; }
            const uint32_t fb = bars + B_FULL + pp.stage * 8;
            if (bytes) mbar_expect_tx(fb, bytes); else mbar_arrive(fb);
            if (--left == 0 && type != J_END) mbar_arrive(bars + B_REQ);
            return fb;
        };
        if (type == J_END || type == J_LN || type == J_LN1 || type == J_MOD) {
            if (type == J_LN) { if (!acquired) wait_flag(F_OP + rb, 2 * (fine ? NJ_O2 : NJ_O)); if (!(h_seen >> 31)) { wait_flag(F_MOD + 1, 32); wait_flag(F_MOD + 2, 32); h_seen |= 1u << 31; } }

            TR(j, 2);
            begin_stage(0); pipe_next(pp);
            seq++;
            if (type == J_END) break;
            continue;
        }
        const CUtensorMap *ta, *tb0, *tb1;
        int k0 = 0, nk = 8, n0 = cb * 256, n1 = n0 + 128, nb = 4, dep = -1;
        unsigned tgt = 0;
        switch (type) {
            case J_KV: ta = &p.tm_h; tb0 = tb1 = cb < 16 ? &p.tm_wk : &p.tm_wv; n0 = (cb & 15) * 256; n1 = n0 + 128; dep = F_H + rb; tgt = 2 * NJ_LN1; break;
            case J_QA: ta = &p.tm_h; tb0 = tb1 = &p.tm_wq; dep = F_H + rb; tgt = 2 * NJ_LN1; break;
            case J_O: ta = &p.tm_o; tb0 = tb1 = &p.tm_wo; n0 = (cb & 1) * 256; n1 = n0 + 128; nk = fine ? 64 / OSPLIT2 : 64 / OSPLIT; k0 = (cb >> 1) * nk * 64;
                      dep = F_O + rb; tgt = 32; break;
            case J_UP: ta = &p.tm_h2; tb0 = &p.tm_wg; tb1 = &p.tm_wu; n0 = n1 = cb * 128; dep = F_H2 + rb; tgt = 2 * NJ_LN; break;
            case J_UP2: ta = &p.tm_h2; tb0 = &p.tm_wg; tb1 = &p.tm_wu; n0 = n1 = cb * 64; nb = 2; dep = F_H2 + rb; tgt = 2 * NJ_LN2; break;
            default: ta = &p.tm_act; tb0 = tb1 = &p.tm_wd; n0 = cb * 64; nk = 0; break;
        }
        const int m0 = rb * 128;
        if (type == J_DN) {
#pragma unroll 1
            for (int kb = 0; kb < 14; kb++) {
                const uint32_t fb = begin_stage(49152);
                const uint32_t st = sb + pp.stage * W_STAGE;
                const int k = kb * 128;
                tma_load2d(st + 32768, tb0, n0, k, fb);
                tma_load2d(st + 40960, tb0, n0, k + 64, fb);
                if (kb == 0) { if (!acquired) { wait_flag(F_ACT + rb, 2 * (fine ? NJ_UP2 : NJ_UP)); asm volatile("fence.proxy.async.global;" ::: "memory"); } TR(j, 2); }
                tma_load2d(st, ta, k, m0, fb);
                tma_load2d(st + 8192, ta, k, m0 + 64, fb);
                tma_load2d(st + 16384, ta, k + 64, m0, fb);
                tma_load2d(st + 24576, ta, k + 64, m0 + 64, fb);
                pipe_next(pp);
            }
        }
#pragma unroll 1
        for (int kb = 0; kb < nk; kb++) {
            const uint32_t fb = begin_stage(16384 + nb * 8192);
            const uint32_t st = sb + pp.stage * W_STAGE;
            const int k = k0 + kb * 64;
            tma_load2d(st + 16384, tb0, n0, k, fb);
            if (nb == 4) {
                tma_load2d(st + 16384 + 8192, tb0, n0 + 64, k, fb);
                tma_load2d(st + 16384 + 16384, tb1, n1, k, fb);
                tma_load2d(st + 16384 + 24576, tb1, n1 + 64, k, fb);
            } else if (nb == 2) {
                tma_load2d(st + 16384 + 8192, tb1, n1, k, fb);
            }
            if (kb == 0) {
                if (acquired && dep < 16) h_seen |= 1u << dep;
                if (dep >= 0 && !acquired && !(dep < 16 && ((h_seen >> dep) & 1))) {
                    wait_flag(dep, tgt);
                    if (type != J_O) asm volatile("fence.proxy.async.global;" ::: "memory");
                    if (dep < 16) h_seen |= 1u << dep;
                }
                TR(j, 2);
            }
            tma_load2d(st, ta, k, m0, fb);
            tma_load2d(st + 8192, ta, k, m0 + 64, fb);
            pipe_next(pp);
        }
        if (type == J_QA) {
            wait_flag(F_KV + rb, 64);
#pragma unroll 1
            for (int i = 0; i < 4; i++) {
                const uint32_t fb = begin_stage(40960);
                const uint32_t st = sb + pp.stage * W_STAGE;
                const int col = (i & 1) * HD_ + (cb * 2 + (i >> 1)) * DH_;
                tma_load2d(st, &p.tm_kv, col, m0, fb);
                tma_load2d(st + 8192, &p.tm_kv, col, m0 + 64, fb);
                tma_load2d(st + 16384, &p.tm_kv, col + 64, m0, fb);
                tma_load2d(st + 24576, &p.tm_kv, col + 64, m0 + 64, fb);
                if (i == 0) { wait_flag(F_MEM + rb, 64); asm volatile("fence.proxy.async.global;" ::: "memory"); }
                tma_load2d(st + 32768, &p.tm_kvm, col, rb * 32, fb);
                tma_load2d(st + 36864, &p.tm_kvm, col + 64, rb * 32, fb);
                pipe_next(pp);
            }
        } else if (type == J_DN) {
            const uint32_t fb = begin_stage(16384);
            const uint32_t st = sb + pp.stage * W_STAGE;
            tma_load2d(st, &p.tm_x1, n0, m0, fb);
            tma_load2d(st + 8192, &p.tm_x1, n0, m0 + 64, fb);
            pipe_next(pp);
        }
        seq++;
    }
}

__device__ __forceinline__ void store_warp(const Params& p, uint32_t sb, int wg, int lane) {
    const uint32_t bars = sb + SM_BAR;
    uint32_t seq = 0;
#pragma unroll 1
    while (true) {
        bar_sync(NB_ST + wg, 160);
        const uint32_t jd = lds32(bars + B_RING + (seq & 7) * 4);
        seq++;
        const int type = jd & 255, rb = (jd >> 8) & 255, cb = (jd >> 16) & 255;
        if (type == J_END) break;
        if (lane == 0) {
            const uint32_t src = sb + W_STG + wg * 32768;
            const CUtensorMap* tm = nullptr; int n0 = cb * 256, nbox = 4, mrow = rb * 128 + wg * 64, flag = 0;
            switch (type) {
                case J_KV: tm = &p.tm_kv; flag = F_KV + rb; break;
                case J_QA: tm = &p.tm_o; flag = F_O + rb; break;
                case J_O: tm = &p.tm_op; n0 = (cb & 1) * 256; mrow = op_row(rb, cb >> 1) + wg * 64; flag = F_OP + rb; break;
                case J_LN: flag = F_H2 + rb; nbox = 0; break;
                case J_LN1: flag = F_H + rb; nbox = 0; break;
                case J_MOD: flag = F_MOD + rb; nbox = 0; break;
                case J_UP: tm = &p.tm_act; n0 = cb * 128; nbox = 2; flag = F_ACT + rb; break;
                case J_UP2: tm = &p.tm_act; n0 = cb * 64; nbox = 1; flag = F_ACT + rb; break;
                default: tm = &p.tm_out; n0 = cb * 64; nbox = 1; flag = -1; break;
            }
#pragma unroll 1
            for (int b = 0; b < nbox; b++) tma_store2d(tm, src + b * 8192, n0 + b * 64, mrow);
            bulk_commit();
            bulk_wait0();
            mbar_arrive(bars + B_STGFREE + wg * 8);
            if (flag >= 0) red_release(&g_flags[flag], 1);
        }
        __syncwarp();
    }
}

__device__ __forceinline__ float gelu_tanh(float x) {
    const float t = x * fmaf(-0.10294324397f, x * x, -2.30220819814f);
    float r; asm("rcp.approx.ftz.f32 %0, %1;" : "=f"(r) : "f"(1.f + ex2(t)));
    return x * r;
}

#define CTR(i) do {} while (0)

template <int NSPLIT>
__device__ __forceinline__ void ln2_row(const Params& p, int rb, int r, int lane) {
    const int row = rb * 128 + r;
    uint4 u[2 * NSPLIT];
#pragma unroll
    for (int sp = 0; sp < NSPLIT; sp++) {
        const uint4* src = (const uint4*)(g_op + (size_t)(op_row(rb, sp) + r) * D_);
        u[2 * sp] = __ldcg(src + lane); u[2 * sp + 1] = __ldcg(src + 32 + lane);
    }
    const uint4* xr = (const uint4*)(p.x + (size_t)row * D_);
    const uint4 xa = __ldg(xr + lane), xb = __ldg(xr + 32 + lane);
    uint32_t ga[8], c1[8], sm[8];
    load_mod8(g_mod + 2 * D_, lane, ga);
    load_mod8(g_mod + 4 * D_, lane, c1);
    load_mod8(g_mod + 3 * D_, lane, sm);
    float a[16];
#pragma unroll
    for (int i = 0; i < 16; i++) a[i] = 0.f;
#pragma unroll
    for (int sp = 0; sp < 2 * NSPLIT; sp++) {
        float* q = a + (sp & 1) * 8;
        q[0] += bflo(u[sp].x); q[1] += bfhi(u[sp].x); q[2] += bflo(u[sp].y); q[3] += bfhi(u[sp].y);
        q[4] += bflo(u[sp].z); q[5] += bfhi(u[sp].z); q[6] += bflo(u[sp].w); q[7] += bfhi(u[sp].w);
    }
    const uint32_t xv[8] = {xa.x, xa.y, xa.z, xa.w, xb.x, xb.y, xb.z, xb.w};
    uint32_t v[8], r8[8];
#pragma unroll
    for (int i = 0; i < 8; i++) v[i] = hadd2(xv[i], hmul2(ga[i], pack2(a[2 * i], a[2 * i + 1])));
    uint4* x1r = (uint4*)(g_x1 + (size_t)row * D_);
    x1r[lane] = make_uint4(v[0], v[1], v[2], v[3]); x1r[32 + lane] = make_uint4(v[4], v[5], v[6], v[7]);
    uint32_t mu2; float rden;
    ln_stats(v, mu2, rden);
#pragma unroll
    for (int i = 0; i < 8; i++) c1[i] = hadd2(c1[i], 0x3F803F80u);
    ln_apply(v, mu2, rden, c1, sm, r8);
    uint4* hr = (uint4*)(g_h2 + (size_t)row * D_);
    hr[lane] = make_uint4(r8[0], r8[1], r8[2], r8[3]); hr[32 + lane] = make_uint4(r8[4], r8[5], r8[6], r8[7]);
}

__device__ __forceinline__ void consumer(const Params& p, uint32_t sb, int warp, int lane) {
    const uint32_t bars = sb + SM_BAR;
    const int wg = warp >> 2, wl = warp & 3;
    const uint32_t l7 = lane & 7, l8 = lane >> 3, g = lane >> 2, t = lane & 3;
    Pipe pp{0, 0};
    uint32_t seq = 0, stg_phase = 1;
    const int srow = wl * 16 + l7 + (l8 & 1) * 8;
    const uint32_t stg_base = sb + W_STG + wg * 32768 + srow * 128;
    const uint32_t sx = ((lane >> 4) ^ (srow & 7)) << 4;
#pragma unroll 1
    while (true) {
        mbar_wait(bars + B_FULL + pp.stage * 8, pp.phase);
        const uint32_t jd = lds32(bars + B_RING + (seq & 7) * 4);
        CTR(3);
        seq++;
        const int type = jd & 255, rb = (jd >> 8) & 255, cb = (jd >> 16) & 255;
        if (type == J_END) { mbar_wait(bars + B_STGFREE + wg * 8, stg_phase); bar_arrive(NB_ST + wg, 160); break; }
        if (type == J_MOD) {
            __syncwarp();
            if (lane == 0) mbar_arrive(bars + B_EMPTY + pp.stage * 8);
            pipe_next(pp);
            const int rg = warp * 4 + l8, col = rb * 1024 + cb * 64;
            uint4 wv[16];
#pragma unroll
            for (int i = 0; i < 16; i++) wv[i] = __ldg((const uint4*)(p.w_mod + (size_t)(rg * 16 + i) * (6 * D_) + col + l7 * 8));
            const uint32_t cw = __ldg((const uint32_t*)(p.c + rg * 16) + l7);
            const float cl = bflo(cw), ch = bfhi(cw);
            const uint32_t sw = pack2(__fdividef(cl, 1.f + __expf(-cl)), __fdividef(ch, 1.f + __expf(-ch)));
            float a[8];
#pragma unroll
            for (int i = 0; i < 8; i++) a[i] = 0.f;
#pragma unroll
            for (int i = 0; i < 16; i++) {
                const uint32_t sv = __shfl_sync(~0u, sw, (lane & 24) + (i >> 1));
                const float cv = (i & 1) ? bfhi(sv) : bflo(sv);
                a[0] = fmaf(cv, bflo(wv[i].x), a[0]); a[1] = fmaf(cv, bfhi(wv[i].x), a[1]); a[2] = fmaf(cv, bflo(wv[i].y), a[2]); a[3] = fmaf(cv, bfhi(wv[i].y), a[3]);
                a[4] = fmaf(cv, bflo(wv[i].z), a[4]); a[5] = fmaf(cv, bfhi(wv[i].z), a[5]); a[6] = fmaf(cv, bflo(wv[i].w), a[6]); a[7] = fmaf(cv, bfhi(wv[i].w), a[7]);
            }
#pragma unroll
            for (int i = 0; i < 8; i++) { a[i] += __shfl_xor_sync(~0u, a[i], 8); a[i] += __shfl_xor_sync(~0u, a[i], 16); }
            const uint32_t red = sb + SM_BAR + 1024;
            bar_sync(NB_M, 256);
            if (lane < 8) {
                sts128(red + warp * 256 + lane * 32, make_uint4(__float_as_uint(a[0]), __float_as_uint(a[1]), __float_as_uint(a[2]), __float_as_uint(a[3])));
                sts128(red + warp * 256 + lane * 32 + 16, make_uint4(__float_as_uint(a[4]), __float_as_uint(a[5]), __float_as_uint(a[6]), __float_as_uint(a[7])));
            }
            bar_sync(NB_M, 256);
            if (wl == 0) {
                const uint32_t ra = red + (wg * 32 + lane) * 4;
                float v = 0.f;
#pragma unroll
                for (int i = 0; i < 8; i++) v += lds32f(ra + i * 256);
                g_mod[col + wg * 32 + lane] = __float2bfloat16_rn(v);
            }
            mbar_wait(bars + B_STGFREE + wg * 8, stg_phase); stg_phase ^= 1;
            CTR(4); CTR(5);
            bar_arrive(NB_ST + wg, 160);
            continue;
        }
        if (type == J_LN || type == J_LN1) {
            __syncwarp();
            if (lane == 0) mbar_arrive(bars + B_EMPTY + pp.stage * 8);
            pipe_next(pp);
            if (type == J_LN1) {
                const int row = rb * 128 + cb * 16 + warp * 2;
                const uint4* xr = (const uint4*)(p.x + (size_t)row * D_);
                const uint4 xa[4] = {__ldg(xr + lane), __ldg(xr + 32 + lane), __ldg(xr + 64 + lane), __ldg(xr + 96 + lane)};
                uint32_t c1[8], sm[8], mu2[2];
                float rden[2];
#pragma unroll
                for (int rr = 0; rr < 2; rr++) {
                    const uint32_t v[8] = {xa[2 * rr].x, xa[2 * rr].y, xa[2 * rr].z, xa[2 * rr].w, xa[2 * rr + 1].x, xa[2 * rr + 1].y, xa[2 * rr + 1].z, xa[2 * rr + 1].w};
                    ln_stats(v, mu2[rr], rden[rr]);
                }
                if (lane == 0) wait_flag(F_MOD, 32);
                __syncwarp();
                load_mod8(g_mod + D_, lane, c1);
                load_mod8(g_mod, lane, sm);
#pragma unroll
                for (int i = 0; i < 8; i++) c1[i] = hadd2(c1[i], 0x3F803F80u);
#pragma unroll
                for (int rr = 0; rr < 2; rr++) {
                    const uint32_t v[8] = {xa[2 * rr].x, xa[2 * rr].y, xa[2 * rr].z, xa[2 * rr].w, xa[2 * rr + 1].x, xa[2 * rr + 1].y, xa[2 * rr + 1].z, xa[2 * rr + 1].w};
                    uint32_t r[8];
                    ln_apply(v, mu2[rr], rden[rr], c1, sm, r);
                    uint4* hr = (uint4*)(g_h + (size_t)(row + rr) * D_);
                    hr[lane] = make_uint4(r[0], r[1], r[2], r[3]); hr[32 + lane] = make_uint4(r[4], r[5], r[6], r[7]);
                }
            } else if (rb >= FINE_RB) ln2_row<OSPLIT2>(p, rb, cb * 8 + warp, lane);
            else {
#pragma unroll 1
                for (int rr = 0; rr < 2; rr++) ln2_row<OSPLIT>(p, rb, cb * 16 + warp * 2 + rr, lane);
            }
            mbar_wait(bars + B_STGFREE + wg * 8, stg_phase); stg_phase ^= 1;
            CTR(4); CTR(5);
            bar_arrive(NB_ST + wg, 160);
            continue;
        }
        if (type == J_DN || type == J_UP2) {
            float acc[64];
#pragma unroll
            for (int i = 0; i < 64; i++) acc[i] = 0.f;
            if (type == J_DN) {
#pragma unroll 1
                for (int kb = 0; kb < 14; kb++) {
                    if (kb) mbar_wait(bars + B_FULL + pp.stage * 8, pp.phase);
                    const uint32_t st = sb + pp.stage * W_STAGE;
                    const uint64_t da = mkdesc(st + wg * 8192, 16, 1024), db = mkdesc(st + 32768, 8192, 1024);
                    wg_fence();
#pragma unroll
                    for (int ks = 0; ks < 8; ks++) wgmma_n64(acc, da + (ks >> 2) * 1024 + (ks & 3) * 2, db + ks * 128);
                    wg_commit();
                    wg_wait0();
                    if (lane == 0) mbar_arrive(bars + B_EMPTY + pp.stage * 8);
                    pipe_next(pp);
                }
            } else {
#pragma unroll 1
                for (int kb = 0; kb < 8; kb++) {
                    if (kb) mbar_wait(bars + B_FULL + pp.stage * 8, pp.phase);
                    const uint32_t st = sb + pp.stage * W_STAGE;
                    const uint64_t da = mkdesc(st + wg * 8192, 16, 1024), db = mkdesc(st + 16384, 8192, 1024);
                    wg_fence();
#pragma unroll
                    for (int ks = 0; ks < 4; ks++) wgmma_n128(acc, da + ks * 2, db + ks * 128, 1);
                    wg_commit();
                    wg_wait0();
                    if (lane == 0) mbar_arrive(bars + B_EMPTY + pp.stage * 8);
                    pipe_next(pp);
                }
            }
            CTR(4);
            if (type == J_UP2) {
                mbar_wait(bars + B_STGFREE + wg * 8, stg_phase); stg_phase ^= 1;
#pragma unroll
                for (int j = 0; j < 4; j++) {
                    uint32_t r[4];
#pragma unroll
                    for (int q = 0; q < 4; q++) {
                        const uint32_t gw = pack2(acc[8 * j + 2 * q], acc[8 * j + 2 * q + 1]);
                        const uint32_t uw = pack2(acc[32 + 8 * j + 2 * q], acc[32 + 8 * j + 2 * q + 1]);
                        r[q] = hmul2(pack2(gelu_tanh(bflo(gw)), gelu_tanh(bfhi(gw))), uw);
                    }
                    stsm4(stg_base + (sx ^ (j << 5)), r[0], r[1], r[2], r[3]);
                }
            } else {
                mbar_wait(bars + B_FULL + pp.stage * 8, pp.phase);
                const uint32_t st = sb + pp.stage * W_STAGE;
                mbar_wait(bars + B_STGFREE + wg * 8, stg_phase); stg_phase ^= 1;
                const uint32_t* gb = (const uint32_t*)(g_mod + 5 * D_ + cb * 64) + t;
                const uint32_t xa = st + wg * 8192 + (wl * 16 + g) * 128 + (g << 4) + t * 4;
#pragma unroll
                for (int j = 0; j < 4; j++) {
                    uint32_t r[4];
#pragma unroll
                    for (int q = 0; q < 4; q++) {
                        const int nt = 2 * j + (q >> 1);
                        const uint32_t xw = lds32((xa ^ ((nt & 7) << 4)) + (nt >> 3) * 16384 + (q & 1) * 1024);
                        r[q] = hadd2(xw, hmul2(__ldcg(gb + nt * 4), pack2(acc[8 * j + 2 * q], acc[8 * j + 2 * q + 1])));
                    }
                    stsm4(stg_base + (j >> 2) * 8192 + (sx ^ ((2 * j & 7) << 4)), r[0], r[1], r[2], r[3]);
                }
                __syncwarp();
                if (lane == 0) mbar_arrive(bars + B_EMPTY + pp.stage * 8);
                pipe_next(pp);
            }
            fence_async_smem();
            CTR(5);
            bar_arrive(NB_ST + wg, 160);
            continue;
        }
        float acc[128];
#pragma unroll
        for (int i = 0; i < 128; i++) acc[i] = 0.f;
        const int nk = type == J_O ? (rb >= FINE_RB ? 64 / OSPLIT2 : 64 / OSPLIT) : 8;
#pragma unroll 1
        for (int kb = 0; kb < nk; kb++) {
            if (kb) mbar_wait(bars + B_FULL + pp.stage * 8, pp.phase);
            const uint32_t st = sb + pp.stage * W_STAGE;
            const uint64_t da = mkdesc(st + wg * 8192, 16, 1024), db = mkdesc(st + 16384, 8192, 1024);
            wg_fence();
#pragma unroll
            for (int ks = 0; ks < 4; ks++) wgmma_n256(acc, da + ks * 2, db + ks * 128, 1);
            wg_commit();
            wg_wait0();
            if (lane == 0) mbar_arrive(bars + B_EMPTY + pp.stage * 8);
            pipe_next(pp);
        }
        CTR(4);
        if (type == J_QA) {
            uint32_t qf[64];
#pragma unroll
            for (int i = 0; i < 64; i++) qf[i] = pack2(acc[2 * i], acc[2 * i + 1]);
            const int sg = warp >> 1, half = warp & 1;
            const float sc = 0.08838834764831845f * 1.4426950408889634f;
            const uint32_t xoff = (sg >> 1) * 8192 + ((sg & 1) * 32 + l7) * 128;
            const uint32_t moff = 32768 + (sg * 8 + l7) * 128;
            const uint32_t kch = (l8 ^ l7) << 4;
            const uint32_t vch = ((l8 & 1) ^ l7) << 4;
            mbar_wait(bars + B_STGFREE + wg * 8, stg_phase); stg_phase ^= 1;
#pragma unroll 1
            for (int hh = 0; hh < 2; hh++) {
                mbar_wait(bars + B_FULL + pp.stage * 8, pp.phase);
                uint32_t st = sb + pp.stage * W_STAGE;
                float sa[5][4];
#pragma unroll
                for (int n = 0; n < 5; n++) sa[n][0] = sa[n][1] = sa[n][2] = sa[n][3] = 0.f;
#pragma unroll
                for (int i = 0; i < 4; i++) {
                    const uint32_t* q = qf + i * 8;
                    uint32_t kk[5][4];
                    ldsm4(kk[0][0], kk[0][1], kk[0][2], kk[0][3], st + moff + (i >> 1) * 4096 + (kch ^ ((i & 1) * 64)));
#pragma unroll
                    for (int n = 1; n < 5; n++)
                        ldsm4(kk[n][0], kk[n][1], kk[n][2], kk[n][3], st + xoff + (n - 1) * 1024 + (i >> 1) * 16384 + (kch ^ ((i & 1) * 64)));
#pragma unroll
                    for (int n = 0; n < 5; n++) mma16816(sa[n], q[0], q[1], q[2], q[3], kk[n][0], kk[n][1]);
#pragma unroll
                    for (int n = 0; n < 5; n++) mma16816(sa[n], q[4], q[5], q[6], q[7], kk[n][2], kk[n][3]);
                }
                __syncwarp();
                if (lane == 0) mbar_arrive(bars + B_EMPTY + pp.stage * 8);
                pipe_next(pp);
                const int iq0 = half * 16 + g - 2 * t, iq1 = iq0 + 8;
                float m0 = fmaxf(sa[0][0], sa[0][1]), m1 = fmaxf(sa[0][2], sa[0][3]);
#pragma unroll
                for (int n = 1; n < 5; n++) {
#pragma unroll
                    for (int e = 0; e < 2; e++) {
                        const int jx = (n - 1) * 8 + e;
                        if (jx > iq0) sa[n][e] = -3.0e38f;
                        if (jx > iq1) sa[n][2 + e] = -3.0e38f;
                        m0 = fmaxf(m0, sa[n][e]); m1 = fmaxf(m1, sa[n][2 + e]);
                    }
                }
                m0 = fmaxf(m0, __shfl_xor_sync(~0u, m0, 1)); m1 = fmaxf(m1, __shfl_xor_sync(~0u, m1, 1));
                m0 = fmaxf(m0, __shfl_xor_sync(~0u, m0, 2)); m1 = fmaxf(m1, __shfl_xor_sync(~0u, m1, 2));
                m0 *= -sc; m1 *= -sc;
                float l0 = 0.f, l1 = 0.f;
                uint32_t p0[5], p1[5];
#pragma unroll
                for (int n = 0; n < 5; n++) {
                    const float e0 = ex2(fmaf(sa[n][0], sc, m0)), e1 = ex2(fmaf(sa[n][1], sc, m0));
                    const float e2 = ex2(fmaf(sa[n][2], sc, m1)), e3 = ex2(fmaf(sa[n][3], sc, m1));
                    l0 += e0 + e1; l1 += e2 + e3;
                    p0[n] = pack2(e0, e1); p1[n] = pack2(e2, e3);
                }
                l0 += __shfl_xor_sync(~0u, l0, 1); l1 += __shfl_xor_sync(~0u, l1, 1);
                l0 += __shfl_xor_sync(~0u, l0, 2); l1 += __shfl_xor_sync(~0u, l1, 2);
                const float i0 = __fdividef(1.f, l0), i1 = __fdividef(1.f, l1);
                mbar_wait(bars + B_FULL + pp.stage * 8, pp.phase);
                st = sb + pp.stage * W_STAGE;
#pragma unroll
                for (int i = 0; i < 32; i++) qf[i] = qf[32 + i];
#pragma unroll 1
                for (int bx = 0; bx < 2; bx++) {
                    float o[8][4];
                    uint32_t vm[8], v0[4][4], v1[4][4];
#pragma unroll
                    for (int ep = 0; ep < 4; ep++) {
                        ldsm2t(vm[2 * ep], vm[2 * ep + 1], st + moff + bx * 4096 + (vch ^ (ep << 5)));
                        const uint32_t va = st + xoff + (l8 >> 1) * 1024 + bx * 16384 + (vch ^ (ep << 5));
                        ldsm4t(v0[ep][0], v0[ep][1], v0[ep][2], v0[ep][3], va);
                        ldsm4t(v1[ep][0], v1[ep][1], v1[ep][2], v1[ep][3], va + 2048);
                    }
#pragma unroll
                    for (int n = 0; n < 8; n++) { o[n][0] = o[n][1] = o[n][2] = o[n][3] = 0.f; mma16816(o[n], p0[0], p1[0], p0[1], p1[1], vm[n], v0[n >> 1][n & 1]); }
#pragma unroll
                    for (int n = 0; n < 8; n++) mma16816(o[n], p0[2], p1[2], p0[3], p1[3], v0[n >> 1][2 + (n & 1)], v1[n >> 1][n & 1]);
#pragma unroll
                    for (int n = 0; n < 8; n++) mma1688(o[n], p0[4], p1[4], v1[n >> 1][2 + (n & 1)]);
#pragma unroll
                    for (int ep = 0; ep < 4; ep++)
                        stsm4(stg_base + (hh * 2 + bx) * 8192 + (sx ^ (ep << 5)),
                              pack2(o[2 * ep][0] * i0, o[2 * ep][1] * i0), pack2(o[2 * ep][2] * i1, o[2 * ep][3] * i1),
                              pack2(o[2 * ep + 1][0] * i0, o[2 * ep + 1][1] * i0), pack2(o[2 * ep + 1][2] * i1, o[2 * ep + 1][3] * i1));
                }
                __syncwarp();
                if (lane == 0) mbar_arrive(bars + B_EMPTY + pp.stage * 8);
                pipe_next(pp);
            }
        } else if (type == J_UP) {
            mbar_wait(bars + B_STGFREE + wg * 8, stg_phase); stg_phase ^= 1;
#pragma unroll
            for (int j = 0; j < 8; j++) {
                uint32_t r[4];
#pragma unroll
                for (int q = 0; q < 4; q++) {
                    const uint32_t gw = pack2(acc[8 * j + 2 * q], acc[8 * j + 2 * q + 1]);
                    const uint32_t uw = pack2(acc[64 + 8 * j + 2 * q], acc[64 + 8 * j + 2 * q + 1]);
                    r[q] = hmul2(pack2(gelu_tanh(bflo(gw)), gelu_tanh(bfhi(gw))), uw);
                }
                stsm4(stg_base + (j >> 2) * 8192 + (sx ^ ((2 * j & 7) << 4)), r[0], r[1], r[2], r[3]);
            }
        } else {
            mbar_wait(bars + B_STGFREE + wg * 8, stg_phase); stg_phase ^= 1;
#pragma unroll
            for (int j = 0; j < 16; j++)
                stsm4(stg_base + (j >> 2) * 8192 + (sx ^ ((2 * j & 7) << 4)),
                      pack2(acc[8 * j], acc[8 * j + 1]), pack2(acc[8 * j + 2], acc[8 * j + 3]),
                      pack2(acc[8 * j + 4], acc[8 * j + 5]), pack2(acc[8 * j + 6], acc[8 * j + 7]));
        }
        fence_async_smem();
        CTR(5);
        bar_arrive(NB_ST + wg, 160);
    }
}

__global__ void __launch_bounds__(384, 1) k_work(const __grid_constant__ Params p) {
    extern __shared__ __align__(1024) unsigned char smem_raw[];
    const uint32_t sb = smem_u32(smem_raw);
    if (sb & 1023) __trap();
    const int warp = __shfl_sync(~0u, threadIdx.x >> 5, 0);
    int lane; asm volatile("mov.u32 %0, %%laneid;" : "=r"(lane));
    if (threadIdx.x == 0) {
        const uint32_t bars = sb + SM_BAR;
        for (int i = 0; i < W_NST; i++) { mbar_init(bars + B_FULL + i * 8, 1); mbar_init(bars + B_EMPTY + i * 8, 8); }
        mbar_init(bars + B_STGFREE, 1); mbar_init(bars + B_STGFREE + 8, 1); mbar_init(bars + B_REQ, 1); mbar_init(bars + B_RSP, 1);
        asm volatile("fence.mbarrier_init.release.cluster;" ::: "memory");
    }
    __syncthreads();
    if (warp < 8) {
        asm volatile("setmaxnreg.inc.sync.aligned.u32 224;");
        consumer(p, sb, warp, lane);
    } else {
        asm volatile("setmaxnreg.dec.sync.aligned.u32 56;");
        if (warp == 8) { if (lane == 0) producer(p, sb); }
        else if (warp < 11) store_warp(p, sb, warp - 9, lane);
        else scheduler(p, sb, lane);
        __syncwarp();
        bar_sync(NB_W0, 128);
        if (warp == 8 && p.qmask == 0xff) {
            unsigned last = 0;
            if (lane == 0) { __threadfence(); last = atomicAdd(&g_flags[F_DONE], 1u) == gridDim.x - 1; }
            if (__shfl_sync(~0u, last, 0))
                for (int i = lane; i < F_TOTAL; i += 32) g_flags[i] = 0;
        }
    }
}

typedef CUresult (*EncodeFn)(CUtensorMap*, CUtensorMapDataType, cuuint32_t, void*, const cuuint64_t*, const cuuint64_t*,
                             const cuuint32_t*, const cuuint32_t*, CUtensorMapInterleave, CUtensorMapSwizzle,
                             CUtensorMapL2promotion, CUtensorMapFloatOOBfill);

static void make_map(EncodeFn enc, CUtensorMap* m, const void* ptr, uint64_t rows, uint64_t cols, uint32_t box_rows) {
    cuuint64_t dims[2] = {cols, rows};
    cuuint64_t strides[1] = {cols * 2};
    cuuint32_t box[2] = {64, box_rows};
    cuuint32_t es[2] = {1, 1};
    enc(m, CU_TENSOR_MAP_DATA_TYPE_BFLOAT16, 2, const_cast<void*>(ptr), dims, strides, box, es, CU_TENSOR_MAP_INTERLEAVE_NONE,
        CU_TENSOR_MAP_SWIZZLE_128B, CU_TENSOR_MAP_L2_PROMOTION_L2_256B, CU_TENSOR_MAP_FLOAT_OOB_FILL_NONE);
}
template <typename T> static void* sym_addr(T& sym) { void* p = nullptr; cudaGetSymbolAddress(&p, sym); return p; }

extern "C" void kernel_launch(void* const* d_in, const int* in_sizes, int n_in, void* d_out, int out_size) {
    static Params prm;
    static RecParams rp;
    static bool ready = false;
    static const void* key[14];
    bool same = ready;
    for (int i = 0; i < 13 && same; i++) same = key[i] == d_in[i];
    same = same && key[13] == d_out;
    if (!same) {
        void* fn = nullptr;
        cudaDriverEntryPointQueryResult qr;
        cudaGetDriverEntryPoint("cuTensorMapEncodeTiled", &fn, cudaEnableDefault, &qr);
        EncodeFn enc = (EncodeFn)fn;
        make_map(enc, &prm.tm_h, sym_addr(g_h), S_, D_, 64);
        make_map(enc, &prm.tm_kv, sym_addr(g_kv), S_, 2 * HD_, 64);
        make_map(enc, &prm.tm_kvm, sym_addr(g_kvm), NSEG * 8, 2 * HD_, 32);
        make_map(enc, &prm.tm_o, sym_addr(g_o), S_, HD_, 64);
        make_map(enc, &prm.tm_op, sym_addr(g_op), OP_ROWS, D_, 64);
        make_map(enc, &prm.tm_h2, sym_addr(g_h2), S_, D_, 64);
        make_map(enc, &prm.tm_act, sym_addr(g_act), S_, DF_, 64);
        make_map(enc, &prm.tm_x1, sym_addr(g_x1), S_, D_, 64);
        make_map(enc, &prm.tm_out, d_out, S_, D_, 64);
        make_map(enc, &prm.tm_wq, d_in[2], D_, HD_, 64);
        make_map(enc, &prm.tm_wk, d_in[3], D_, HD_, 64);
        make_map(enc, &prm.tm_wv, d_in[4], D_, HD_, 64);
        make_map(enc, &prm.tm_wo, d_in[5], HD_, D_, 64);
        make_map(enc, &prm.tm_wg, d_in[8], D_, DF_, 64);
        make_map(enc, &prm.tm_wu, d_in[9], D_, DF_, 64);
        make_map(enc, &prm.tm_wd, d_in[10], DF_, D_, 64);
        prm.x = (const bf16*)d_in[0]; prm.c = (const bf16*)d_in[11]; prm.w_mod = (const bf16*)d_in[12];
        rp.mem0 = (const bf16*)d_in[1];
        rp.wq = (const bf16*)d_in[2]; rp.wk = (const bf16*)d_in[3]; rp.wv = (const bf16*)d_in[4]; rp.wo = (const bf16*)d_in[5];
        cudaFuncSetAttribute(k_work, cudaFuncAttributeMaxDynamicSharedMemorySize, SMEM_BYTES);
        cudaFuncSetAttribute(k_rec, cudaFuncAttributeMaxDynamicSharedMemorySize, R_SMEM);
        cudaFuncSetAttribute(k_rec, cudaFuncAttributeNonPortableClusterSizeAllowed, 1);
        {
            cudaLaunchConfig_t cfg = {};
            cfg.gridDim = dim3(128); cfg.blockDim = dim3(384); cfg.dynamicSmemBytes = R_SMEM;
            cudaLaunchAttribute at[1];
            at[0].id = cudaLaunchAttributeClusterDimension; at[0].val.clusterDim.x = 16; at[0].val.clusterDim.y = 1; at[0].val.clusterDim.z = 1;
            cfg.attrs = at; cfg.numAttrs = 1;
            int n = 0;
            cudaOccupancyMaxActiveClusters(&n, k_rec, &cfg);
            rp.ncl = n < 4 ? 4 : (n > 8 ? 8 : n);
        }
        for (int i = 0; i < 13; i++) key[i] = d_in[i];
        key[13] = d_out;
        ready = true;
    }
    cudaStream_t st = cudaStreamPerThread;
    auto launch_rec = [&]() {
        cudaLaunchConfig_t cfg = {};
        cfg.gridDim = dim3(16 * rp.ncl); cfg.blockDim = dim3(384); cfg.dynamicSmemBytes = R_SMEM; cfg.stream = st;
        cudaLaunchAttribute at[1];
        at[0].id = cudaLaunchAttributeClusterDimension; at[0].val.clusterDim.x = 16; at[0].val.clusterDim.y = 1; at[0].val.clusterDim.z = 1;
        cfg.attrs = at; cfg.numAttrs = 1;
        cudaLaunchKernelEx(&cfg, k_rec, rp);
    };
    auto launch_work = [&](int qmask, int pdl) {
        prm.qmask = qmask;
        cudaLaunchConfig_t cfg = {};
        cfg.gridDim = dim3(132); cfg.blockDim = dim3(384); cfg.dynamicSmemBytes = SMEM_BYTES; cfg.stream = st;
        cudaLaunchAttribute at[1];
        at[0].id = cudaLaunchAttributeProgrammaticStreamSerialization; at[0].val.programmaticStreamSerializationAllowed = 1;
        cfg.attrs = at; cfg.numAttrs = pdl;
        cudaLaunchKernelEx(&cfg, k_work, prm);
    };
    launch_rec();
    launch_work(0xff, 1);
}
```

```cpp
#include <cuda_runtime.h>
#include <cuda_bf16.h>
#include <cuda.h>
#include <stdint.h>

typedef __nv_bfloat16 bf16;
#define IDLE_NS 150
#define FLAG_NS 20

constexpr int S_ = 2048, D_ = 512, H_ = 32, DH_ = 128, HD_ = 4096, NSEG = 64, DF_ = 1792;
constexpr int NRB = 16;
constexpr int OSPLIT = 4;

__device__ __align__(1024) bf16 g_h[S_ * D_];
__device__ __align__(1024) bf16 g_kv[S_ * 2 * HD_];
__device__ __align__(1024) bf16 g_kvm[NSEG * 8 * 2 * HD_];
__device__ __align__(1024) bf16 g_o[S_ * HD_];
#define FINE_RB_ 12
constexpr int FINE_RB = FINE_RB_;
#define OSPLIT2_ 8
constexpr int OSPLIT2 = OSPLIT2_;
constexpr int OP_ROWS = OSPLIT * S_ + OSPLIT2 * (NRB - FINE_RB) * 128;
__device__ __align__(1024) bf16 g_op[OP_ROWS * D_];
__device__ __align__(1024) bf16 g_x1[S_ * D_];
__device__ __align__(1024) bf16 g_h2[S_ * D_];
__device__ __align__(1024) bf16 g_act[S_ * DF_];
__device__ __align__(1024) bf16 g_mod[6 * D_];
__device__ uint32_t g_Fraw[131072 + 65536 + 2048];
#define g_F ((uint32_t*)(((uint64_t)g_Fraw + 0x7FFFFull) & ~0x7FFFFull))
constexpr int F_H = 0, F_MEM = 32, F_O = 64, F_OP = 96, F_H2 = 128, F_ACT = 160, F_MOD = 192, F_KV = 224, F_CLAIM = 256  ,
              F_SIDE = 512  , F_DONE = 576, F_TOTAL = 608;
__device__ __align__(128) unsigned int g_flags[F_TOTAL];
#define TR(j, i) do {} while (0)

__device__ __forceinline__ uint32_t smem_u32(const void* p) { return (uint32_t)__cvta_generic_to_shared(p); }
__device__ __forceinline__ uint32_t clk32() { uint32_t c; asm volatile("mov.u32 %0, %%clock;" : "=r"(c)); return c; }
__device__ __forceinline__ uint32_t mapa_u32(uint32_t addr, uint32_t rank) {
    uint32_t r; asm volatile("mapa.shared::cluster.u32 %0, %1, %2;" : "=r"(r) : "r"(addr), "r"(rank)); return r;
}
__device__ __forceinline__ void mbar_init(uint32_t bar, uint32_t cnt) {
    asm volatile("mbarrier.init.shared::cta.b64 [%0], %1;" :: "r"(bar), "r"(cnt) : "memory");
}
__device__ __forceinline__ void mbar_inval(uint32_t bar) {
    asm volatile("mbarrier.inval.shared::cta.b64 [%0];" :: "r"(bar) : "memory");
}
__device__ __forceinline__ void mbar_expect_tx(uint32_t bar, uint32_t bytes) {
    asm volatile("mbarrier.arrive.expect_tx.shared::cta.b64 _, [%0], %1;" :: "r"(bar), "r"(bytes) : "memory");
}
__device__ __forceinline__ void mbar_arrive(uint32_t bar) {
    asm volatile("mbarrier.arrive.shared::cta.b64 _, [%0];" :: "r"(bar) : "memory");
}
__device__ __forceinline__ bool mbar_try_wait(uint32_t bar, uint32_t parity) {
    uint32_t ok;
    asm volatile("{\n.reg .pred p;\nmbarrier.try_wait.parity.shared::cta.b64 p, [%1], %2;\nselp.u32 %0, 1, 0, p;\n}"
                 : "=r"(ok) : "r"(bar), "r"(parity) : "memory");
    return ok;
}
__device__ __forceinline__ bool mbar_try_wait_cluster(uint32_t bar, uint32_t parity) {
    uint32_t ok;
    asm volatile("{\n.reg .pred p;\nmbarrier.try_wait.parity.acquire.cluster.shared::cta.b64 p, [%1], %2;\nselp.u32 %0, 1, 0, p;\n}"
                 : "=r"(ok) : "r"(bar), "r"(parity) : "memory");
    return ok;
}
constexpr int SPIN_LIMIT = 1 << 18;
#define TIMEOUT(code, info) do {} while (0)
__device__ __forceinline__ void mbar_wait(uint32_t bar, uint32_t parity) {
    int g = 0;
#pragma unroll 1
    while (!mbar_try_wait(bar, parity)) { if (++g >= SPIN_LIMIT) { TIMEOUT(0, bar & 255); break; } }
}
__device__ __forceinline__ void mbar_wait_cluster(uint32_t bar, uint32_t parity) {
    int g = 0;
#pragma unroll 1
    while (!mbar_try_wait_cluster(bar, parity)) { if (++g >= SPIN_LIMIT) { TIMEOUT(1, bar & 255); break; } }
}
__device__ __forceinline__ void bar_sync(int id, int n) { asm volatile("bar.sync %0, %1;" :: "r"(id), "r"(n) : "memory"); }
__device__ __forceinline__ void bar_arrive(int id, int n) { asm volatile("bar.arrive %0, %1;" :: "r"(id), "r"(n) : "memory"); }
__device__ __forceinline__ void cluster_sync_all() {
    asm volatile("barrier.cluster.arrive.aligned;\nbarrier.cluster.wait.aligned;" ::: "memory");
}
__device__ __forceinline__ void st_async_v2(uint32_t addr, float a, float b, uint32_t bar) {
    asm volatile("st.async.weak.shared::cluster.mbarrier::complete_tx::bytes.v2.f32 [%0], {%1,%2}, [%3];"
                 :: "r"(addr), "f"(a), "f"(b), "r"(bar) : "memory");
}
__device__ __forceinline__ void st_async_v4(uint32_t addr, uint4 v, uint32_t bar) {
    asm volatile("st.async.weak.shared::cluster.mbarrier::complete_tx::bytes.v4.b32 [%0], {%1,%2,%3,%4}, [%5];"
                 :: "r"(addr), "r"(v.x), "r"(v.y), "r"(v.z), "r"(v.w), "r"(bar) : "memory");
}
__device__ __forceinline__ uint2 ldg_relaxed2(const uint2* p) {
    uint2 v;
    asm volatile("ld.relaxed.gpu.global.v2.b32 {%0,%1}, [%2];" : "=r"(v.x), "=r"(v.y) : "l"(p) : "memory");
    return v;
}
__device__ __forceinline__ void stg_relaxed2(uint2* p, uint2 v) {
    asm volatile("st.relaxed.gpu.global.v2.b32 [%0], {%1,%2};" :: "l"(p), "r"(v.x), "r"(v.y) : "memory");
}
__device__ __forceinline__ uint4 ldg_relaxed(const uint4* p) {
    uint4 v;
    asm volatile("ld.relaxed.gpu.global.v4.b32 {%0,%1,%2,%3}, [%4];" : "=r"(v.x), "=r"(v.y), "=r"(v.z), "=r"(v.w) : "l"(p) : "memory");
    return v;
}
__device__ __forceinline__ void stg_relaxed(uint4* p, uint4 v) {
    asm volatile("st.relaxed.gpu.global.v4.b32 [%0], {%1,%2,%3,%4};" :: "l"(p), "r"(v.x), "r"(v.y), "r"(v.z), "r"(v.w) : "memory");
}
__device__ __forceinline__ void stg_relaxed32(uint32_t* p, uint32_t v) {
    asm volatile("st.relaxed.gpu.global.b32 [%0], %1;" :: "l"(p), "r"(v) : "memory");
}
__device__ __forceinline__ uint32_t ldg_relaxed32(const uint32_t* p) {
    uint32_t v; asm volatile("ld.relaxed.gpu.global.b32 %0, [%1];" : "=r"(v) : "l"(p) : "memory"); return v;
}
__device__ __forceinline__ unsigned int ld_acquire(const unsigned int* p) {
    unsigned int v; asm volatile("ld.acquire.gpu.global.u32 %0, [%1];" : "=r"(v) : "l"(p) : "memory"); return v;
}
__device__ __forceinline__ void red_release(unsigned int* p, unsigned int v) {
    asm volatile("red.release.gpu.global.add.u32 [%0], %1;" :: "l"(p), "r"(v) : "memory");
}
__device__ __forceinline__ void wait_flag(int idx, unsigned int target) {
    const unsigned int* p = &g_flags[idx];
    int g = 0;
#pragma unroll 1
    while (ld_acquire(p) < target) { __nanosleep(FLAG_NS); if (++g >= 64 * SPIN_LIMIT) { TIMEOUT(2, idx); break; } }
}
__device__ __forceinline__ void cp_async16(uint32_t dst, const void* src) {
    asm volatile("cp.async.cg.shared.global [%0], [%1], 16;" :: "r"(dst), "l"(src) : "memory");
}
__device__ __forceinline__ void cp_async_commit() { asm volatile("cp.async.commit_group;" ::: "memory"); }
template <int N> __device__ __forceinline__ void cp_async_wait() { asm volatile("cp.async.wait_group %0;" :: "n"(N) : "memory"); }
__device__ __forceinline__ void ldsm4(uint32_t& r0, uint32_t& r1, uint32_t& r2, uint32_t& r3, uint32_t addr) {
    asm volatile("ldmatrix.sync.aligned.m8n8.x4.shared.b16 {%0,%1,%2,%3}, [%4];" : "=r"(r0), "=r"(r1), "=r"(r2), "=r"(r3) : "r"(addr) : "memory");
}
__device__ __forceinline__ void ldsm4t(uint32_t& r0, uint32_t& r1, uint32_t& r2, uint32_t& r3, uint32_t addr) {
    asm volatile("ldmatrix.sync.aligned.m8n8.x4.trans.shared.b16 {%0,%1,%2,%3}, [%4];" : "=r"(r0), "=r"(r1), "=r"(r2), "=r"(r3) : "r"(addr) : "memory");
}
__device__ __forceinline__ void ldsm2t(uint32_t& r0, uint32_t& r1, uint32_t addr) {
    asm volatile("ldmatrix.sync.aligned.m8n8.x2.trans.shared.b16 {%0,%1}, [%2];" : "=r"(r0), "=r"(r1) : "r"(addr) : "memory");
}
__device__ __forceinline__ void stsm4(uint32_t addr, uint32_t r0, uint32_t r1, uint32_t r2, uint32_t r3) {
    asm volatile("stmatrix.sync.aligned.m8n8.x4.shared.b16 [%0], {%1,%2,%3,%4};" :: "r"(addr), "r"(r0), "r"(r1), "r"(r2), "r"(r3) : "memory");
}
__device__ __forceinline__ void stsm2t(uint32_t addr, uint32_t r0, uint32_t r1) {
    asm volatile("stmatrix.sync.aligned.m8n8.x2.trans.shared.b16 [%0], {%1,%2};" :: "r"(addr), "r"(r0), "r"(r1) : "memory");
}
__device__ __forceinline__ void mma16816(float* d, uint32_t a0, uint32_t a1, uint32_t a2, uint32_t a3, uint32_t b0, uint32_t b1) {
    asm volatile("mma.sync.aligned.m16n8k16.row.col.f32.bf16.bf16.f32 {%0,%1,%2,%3}, {%4,%5,%6,%7}, {%8,%9}, {%0,%1,%2,%3};"
                 : "+f"(d[0]), "+f"(d[1]), "+f"(d[2]), "+f"(d[3]) : "r"(a0), "r"(a1), "r"(a2), "r"(a3), "r"(b0), "r"(b1));
}
__device__ __forceinline__ void mma1688(float* d, uint32_t a0, uint32_t a1, uint32_t b0) {
    asm volatile("mma.sync.aligned.m16n8k8.row.col.f32.bf16.bf16.f32 {%0,%1,%2,%3}, {%4,%5}, {%6}, {%0,%1,%2,%3};"
                 : "+f"(d[0]), "+f"(d[1]), "+f"(d[2]), "+f"(d[3]) : "r"(a0), "r"(a1), "r"(b0));
}
__device__ __forceinline__ void mma16816h(float* d, uint32_t a0, uint32_t a2, uint32_t b0, uint32_t b1) {
    asm volatile("{\n.reg .b32 ju, jv;\nmma.sync.aligned.m16n8k16.row.col.f32.bf16.bf16.f32 {%0,%1,%2,%3}, {%4,ju,%5,jv}, {%6,%7}, {%0,%1,%2,%3};\n}"
                 : "+f"(d[0]), "+f"(d[1]), "+f"(d[2]), "+f"(d[3]) : "r"(a0), "r"(a2), "r"(b0), "r"(b1));
}
__device__ __forceinline__ void mma1688h(float* d, uint32_t a0, uint32_t b0) {
    asm volatile("{\n.reg .b32 ju;\nmma.sync.aligned.m16n8k8.row.col.f32.bf16.bf16.f32 {%0,%1,%2,%3}, {%4,ju}, {%5}, {%0,%1,%2,%3};\n}"
                 : "+f"(d[0]), "+f"(d[1]), "+f"(d[2]), "+f"(d[3]) : "r"(a0), "r"(b0));
}
__device__ __forceinline__ uint32_t pack2(float lo, float hi) {
    uint32_t r; asm("cvt.rn.bf16x2.f32 %0, %1, %2;" : "=r"(r) : "f"(hi), "f"(lo)); return r;
}
__device__ __forceinline__ float bflo(uint32_t w) { return __uint_as_float(w << 16); }
__device__ __forceinline__ float bfhi(uint32_t w) { return __uint_as_float(w & 0xffff0000u); }
__device__ __forceinline__ float rbf(float x) { return __bfloat162float(__float2bfloat16_rn(x)); }
__device__ __forceinline__ float ex2(float x) { float y; asm("ex2.approx.ftz.f32 %0, %1;" : "=f"(y) : "f"(x)); return y; }
__device__ __forceinline__ void sts128(uint32_t addr, uint4 v) {
    asm volatile("st.shared.v4.b32 [%0], {%1,%2,%3,%4};" :: "r"(addr), "r"(v.x), "r"(v.y), "r"(v.z), "r"(v.w) : "memory");
}
__device__ __forceinline__ uint4 lds128(uint32_t addr) {
    uint4 v; asm volatile("ld.shared.v4.b32 {%0,%1,%2,%3}, [%4];" : "=r"(v.x), "=r"(v.y), "=r"(v.z), "=r"(v.w) : "r"(addr) : "memory"); return v;
}
__device__ __forceinline__ float2 lds64f(uint32_t addr) {
    float2 v; asm volatile("ld.shared.v2.f32 {%0,%1}, [%2];" : "=f"(v.x), "=f"(v.y) : "r"(addr) : "memory"); return v;
}
__device__ __forceinline__ float lds32f(uint32_t addr) {
    float v; asm volatile("ld.shared.f32 %0, [%1];" : "=f"(v) : "r"(addr) : "memory"); return v;
}
__device__ __forceinline__ uint32_t lds32(uint32_t addr) {
    uint32_t v; asm volatile("ld.shared.b32 %0, [%1];" : "=r"(v) : "r"(addr) : "memory"); return v;
}
__device__ __forceinline__ void sts32(uint32_t addr, uint32_t v) { asm volatile("st.shared.b32 [%0], %1;" :: "r"(addr), "r"(v) : "memory"); }
__device__ __forceinline__ void sts64f(uint32_t addr, float a, float b) { asm volatile("st.shared.v2.f32 [%0], {%1,%2};" :: "r"(addr), "f"(a), "f"(b) : "memory"); }

__device__ __forceinline__ void tma_load2d(uint32_t dst, const CUtensorMap* tm, int c0, int c1, uint32_t bar) {
    asm volatile("cp.async.bulk.tensor.2d.shared::cluster.global.mbarrier::complete_tx::bytes [%0], [%1, {%3, %4}], [%2];"
                 :: "r"(dst), "l"(tm), "r"(bar), "r"(c0), "r"(c1) : "memory");
}
__device__ __forceinline__ void tma_store2d(const CUtensorMap* tm, uint32_t src, int c0, int c1) {
    asm volatile("cp.async.bulk.tensor.2d.global.shared::cta.bulk_group [%0, {%2, %3}], [%1];"
                 :: "l"(tm), "r"(src), "r"(c0), "r"(c1) : "memory");
}
__device__ __forceinline__ void bulk_commit() { asm volatile("cp.async.bulk.commit_group;" ::: "memory"); }
__device__ __forceinline__ void bulk_wait0() { asm volatile("cp.async.bulk.wait_group 0;" ::: "memory"); }
__device__ __forceinline__ void fence_async_smem() { asm volatile("fence.proxy.async.shared::cta;" ::: "memory"); }
__device__ __forceinline__ void fence_async_all() { asm volatile("fence.proxy.async;" ::: "memory"); }

__device__ __forceinline__ void wg_fence() { asm volatile("wgmma.fence.sync.aligned;" ::: "memory"); }
__device__ __forceinline__ void wg_commit() { asm volatile("wgmma.commit_group.sync.aligned;" ::: "memory"); }
__device__ __forceinline__ void wg_wait0() { asm volatile("wgmma.wait_group.sync.aligned 0;" ::: "memory"); }
__device__ __forceinline__ uint64_t mkdesc(uint32_t saddr, uint32_t lbo, uint32_t sbo) {
    return (uint64_t)((saddr & 0x3FFFF) >> 4) | ((uint64_t)(lbo >> 4) << 16) | ((uint64_t)(sbo >> 4) << 32) | (1ull << 62);
}
#define ACC8(i) "+f"(d[i]), "+f"(d[i + 1]), "+f"(d[i + 2]), "+f"(d[i + 3]), "+f"(d[i + 4]), "+f"(d[i + 5]), "+f"(d[i + 6]), "+f"(d[i + 7])
__device__ __forceinline__ void wgmma_n256(float* d, uint64_t da, uint64_t db, int scale_d) {
    asm volatile(
        "{\n.reg .pred p;\nsetp.ne.b32 p, %130, 0;\n"
        "wgmma.mma_async.sync.aligned.m64n256k16.f32.bf16.bf16 "
        "{%0,%1,%2,%3,%4,%5,%6,%7,%8,%9,%10,%11,%12,%13,%14,%15,%16,%17,%18,%19,%20,%21,%22,%23,%24,%25,%26,%27,%28,%29,%30,%31,"
        "%32,%33,%34,%35,%36,%37,%38,%39,%40,%41,%42,%43,%44,%45,%46,%47,%48,%49,%50,%51,%52,%53,%54,%55,%56,%57,%58,%59,%60,%61,%62,%63,"
        "%64,%65,%66,%67,%68,%69,%70,%71,%72,%73,%74,%75,%76,%77,%78,%79,%80,%81,%82,%83,%84,%85,%86,%87,%88,%89,%90,%91,%92,%93,%94,%95,"
        "%96,%97,%98,%99,%100,%101,%102,%103,%104,%105,%106,%107,%108,%109,%110,%111,%112,%113,%114,%115,%116,%117,%118,%119,%120,%121,%122,%123,%124,%125,%126,%127}, "
        "%128, %129, p, 1, 1, 0, 1;\n}"
        : ACC8(0), ACC8(8), ACC8(16), ACC8(24), ACC8(32), ACC8(40), ACC8(48), ACC8(56),
          ACC8(64), ACC8(72), ACC8(80), ACC8(88), ACC8(96), ACC8(104), ACC8(112), ACC8(120)
        : "l"(da), "l"(db), "r"(scale_d));
}
__device__ __forceinline__ void wgmma_n128(float* d, uint64_t da, uint64_t db, int scale_d) {
    asm volatile(
        "{\n.reg .pred p;\nsetp.ne.b32 p, %66, 0;\n"
        "wgmma.mma_async.sync.aligned.m64n128k16.f32.bf16.bf16 "
        "{%0,%1,%2,%3,%4,%5,%6,%7,%8,%9,%10,%11,%12,%13,%14,%15,%16,%17,%18,%19,%20,%21,%22,%23,%24,%25,%26,%27,%28,%29,%30,%31,"
        "%32,%33,%34,%35,%36,%37,%38,%39,%40,%41,%42,%43,%44,%45,%46,%47,%48,%49,%50,%51,%52,%53,%54,%55,%56,%57,%58,%59,%60,%61,%62,%63}, "
        "%64, %65, p, 1, 1, 0, 1;\n}"
        : ACC8(0), ACC8(8), ACC8(16), ACC8(24), ACC8(32), ACC8(40), ACC8(48), ACC8(56)
        : "l"(da), "l"(db), "r"(scale_d));
}

__device__ __forceinline__ void wgmma_n64(float* d, uint64_t da, uint64_t db) {
    asm volatile(
        "wgmma.mma_async.sync.aligned.m64n64k16.f32.bf16.bf16 "
        "{%0,%1,%2,%3,%4,%5,%6,%7,%8,%9,%10,%11,%12,%13,%14,%15,%16,%17,%18,%19,%20,%21,%22,%23,%24,%25,%26,%27,%28,%29,%30,%31}, "
        "%32, %33, 1, 1, 1, 0, 1;"
        : ACC8(0), ACC8(8), ACC8(16), ACC8(24)
        : "l"(da), "l"(db));
}
__device__ __forceinline__ void wgmma_n8_ta(float* d, uint64_t da, uint64_t db, int scale_d) {
    asm volatile(
        "{\n.reg .pred p;\nsetp.ne.b32 p, %6, 0;\n"
        "wgmma.mma_async.sync.aligned.m64n8k16.f32.bf16.bf16 {%0,%1,%2,%3}, %4, %5, p, 1, 1, 1, 0;\n}"
        : "+f"(d[0]), "+f"(d[1]), "+f"(d[2]), "+f"(d[3]) : "l"(da), "l"(db), "r"(scale_d));
}

__device__ __forceinline__ uint32_t hadd2(uint32_t a, uint32_t b) { uint32_t r; asm("add.rn.bf16x2 %0, %1, %2;" : "=r"(r) : "r"(a), "r"(b)); return r; }
__device__ __forceinline__ uint32_t hsub2(uint32_t a, uint32_t b) { uint32_t r; asm("sub.rn.bf16x2 %0, %1, %2;" : "=r"(r) : "r"(a), "r"(b)); return r; }
__device__ __forceinline__ uint32_t hmul2(uint32_t a, uint32_t b) { uint32_t r; asm("mul.rn.bf16x2 %0, %1, %2;" : "=r"(r) : "r"(a), "r"(b)); return r; }
__device__ __forceinline__ void load_mod8(const bf16* m, int lane, uint32_t* v) {
    const uint4 a = __ldcg((const uint4*)m + lane), b = __ldcg((const uint4*)m + 32 + lane);
    v[0] = a.x; v[1] = a.y; v[2] = a.z; v[3] = a.w; v[4] = b.x; v[5] = b.y; v[6] = b.z; v[7] = b.w;
}
__device__ __forceinline__ void ln_stats(const uint32_t* x, uint32_t& mu2, float& rden) {
    float s = 0.f;
#pragma unroll
    for (int i = 0; i < 8; i++) s += bflo(x[i]) + bfhi(x[i]);
#pragma unroll
    for (int o = 16; o > 0; o >>= 1) s += __shfl_xor_sync(~0u, s, o);
    const float mean = s * (1.f / D_);
    float q = 0.f;
#pragma unroll
    for (int i = 0; i < 8; i++) { const float d0 = bflo(x[i]) - mean, d1 = bfhi(x[i]) - mean; q = fmaf(d0, d0, q); q = fmaf(d1, d1, q); }
#pragma unroll
    for (int o = 16; o > 0; o >>= 1) q += __shfl_xor_sync(~0u, q, o);
    mu2 = pack2(mean, mean);
    rden = __frcp_rn(rbf(__fsqrt_rn(rbf(rbf(q * (1.f / D_)) + 1e-5f))));
}
__device__ __forceinline__ void ln_apply(const uint32_t* x, uint32_t mu2, float rden, const uint32_t* c1, const uint32_t* sm, uint32_t* r) {
#pragma unroll
    for (int i = 0; i < 8; i++) {
        const uint32_t d = hsub2(x[i], mu2);
        r[i] = hadd2(hmul2(pack2(bflo(d) * rden, bfhi(d) * rden), c1[i]), sm[i]);
    }
}

struct __align__(64) Params {
    CUtensorMap tm_h, tm_kv, tm_kvm, tm_o, tm_op, tm_h2, tm_act, tm_x1, tm_out;
    CUtensorMap tm_wq, tm_wk, tm_wv, tm_wo, tm_wg, tm_wu, tm_wd;
    const bf16 *x, *c, *w_mod;
    int qmask;
};

constexpr int R_NST = 3;
constexpr uint32_t R_WV = 0, R_MEM = 65536, R_KX = 73728, R_VX = R_KX + R_NST * 4096,
                   R_KMS = R_VX + R_NST * 4096  , R_VMS = R_KMS + 1024,
                   R_QS = R_KMS + 4096, R_OS = R_QS + 1024, R_SX = R_OS + 1024, R_BAR = R_SX + 2560,
                   R_RS = 107520  , R_VP = R_RS + 8192  ,
                   R_STG = R_VP + 8192  , R_SMEM = R_STG + 98304;
static_assert((R_KMS & 4095) == 0, "smem");
static_assert(R_BAR + 64 <= R_RS, "smem");
constexpr uint32_t RB_SX = R_BAR, RB_V = R_BAR + 8, RB_E = R_BAR + 16, RB_A = R_BAR + 24, RB_ROLE = R_BAR + 32, RB_A1 = R_BAR + 40;
constexpr int W_NST = 4;
constexpr uint32_t W_STAGE = 49152, W_STG = W_NST * W_STAGE  , W_END = W_STG + 32768;
constexpr uint32_t SM_BAR = W_END;
constexpr uint32_t SMEM_BYTES = W_END + 1024 + 2048;
constexpr uint32_t B_FULL = 0, B_EMPTY = 32, B_STGFREE = 64, B_REQ = 80, B_RSP = 88, B_NEXT = 96, B_RING = 128;
#define PICK_AHEAD 3

constexpr int NB_X = 11  , NB_Y = 1, NB_M = 5, NB_K = 5, NB_B = 2, NB_C = 3, NB_D = 4, NB_W0 = 6  , NB_ST = 9  ;

__device__ __forceinline__ int pos_of_d(int d) {
    const int rem = d & 31;
    return (d & ~31) + ((rem & 7) >> 1) * 8 + (rem & 1) * 4 + (rem >> 3);
}

#define PROF(i) do {} while (0)
#define PROFG(i) do {} while (0)
#define OPAQUE(x) asm volatile("" : "+r"(x))
#define FENCE_SCHED(x) do { if ((x) == 0u) asm volatile("trap;"); } while (0)
#define VK0_ 4
constexpr int VK0 = VK0_;
constexpr int NOFF = 8;
#define VDELAY -1
#define POLL_GAP 110

struct RecParams { const bf16 *mem0, *wq, *wk, *wv, *wo; int ncl; };

__device__ __forceinline__ void rec_qk(const RecParams& p, const uint32_t sb, const int cta, const int warp, int lane, const int sel) {
    const int crank = cta & 15, cl = cta >> 4, rank = cta & 1;
    const int kh = warp >> 2, aa = warp & 3;
    uint32_t wa[2][16][4];
    const uint32_t stg = sb + R_STG + kh * 32768;
    {
        const int t128 = aa * 32 + lane;
        const int row = (lane >> 4) * 8 + (lane & 7);
        const int ch = t128 & 7;
        const size_t goff = (size_t)kh * 256 * HD_ + cta * 64 + ch * 8;
#pragma unroll 4
        for (int dd = 0; dd < 16; dd++) {
            const int d = dd * 16 + (t128 >> 3), pp = pos_of_d(d);
            cp_async16(sb + R_WV + kh * 32768 + pp * 128 + ((ch ^ (pp & 7)) << 4), p.wv + goff + (size_t)d * HD_);
        }
        cp_async_commit();
#pragma unroll 4
        for (int dd = 0; dd < 16; dd++) {
            const int d = dd * 16 + (t128 >> 3), pp = pos_of_d(d);
            cp_async16(stg + pp * 128 + ((ch ^ (pp & 7)) << 4), p.wq + goff + (size_t)d * HD_);
        }
        cp_async_commit();
        {
            const int i0 = (warp * 32 + lane) * 16, tok = i0 >> 9;
            const uint4 m0 = __ldg((const uint4*)(p.mem0 + i0)), m1 = __ldg((const uint4*)(p.mem0 + i0 + 8));
            const uint32_t mw[8] = {m0.x, m0.y, m0.z, m0.w, m1.x, m1.y, m1.z, m1.w};
#pragma unroll
            for (int e = 0; e < 16; e++) {
                const int pp = pos_of_d((i0 & 511) + e);
                const unsigned short v = (unsigned short)(mw[e >> 1] >> ((e & 1) * 16));
                asm volatile("st.shared.u16 [%0], %1;" :: "r"(sb + R_MEM + (pp >> 3) * 128 + tok * 16 + (pp & 7) * 2), "h"(v) : "memory");
            }
        }
        cp_async_wait<1>();
        bar_sync(NB_W0 + kh, 128);
        const uint32_t fv = row * 128 + (((2 * aa + ((lane >> 3) & 1)) ^ (row & 7)) << 4);
#pragma unroll
        for (int ks = 0; ks < 16; ks++) ldsm4t(wa[0][ks][0], wa[0][ks][1], wa[0][ks][2], wa[0][ks][3], sb + R_WV + kh * 32768 + fv + ks * 2048);
        bar_sync(NB_W0 + kh, 128);
#pragma unroll
        for (int ks = 0; ks < 16; ks++)
            sts128(sb + R_WV + kh * 32768 + (aa * 16 + ks) * 512 + lane * 16, make_uint4(wa[0][ks][0], wa[0][ks][1], wa[0][ks][2], wa[0][ks][3]));
        const uint32_t fo = stg + row * 128 + (((4 * (aa & 1) + ((lane >> 3) & 1)) ^ (row & 7)) << 4);
#pragma unroll 1
        for (int m = 0; m < 2; m++) {
            cp_async_wait<0>();
            bar_sync(NB_W0 + kh, 128);
            if ((aa >> 1) == m) {
#pragma unroll
                for (int ks = 0; ks < 16; ks++) {
                    ldsm4t(wa[0][ks][0], wa[0][ks][1], wa[0][ks][2], wa[0][ks][3], fo + ks * 2048);
                    ldsm4t(wa[1][ks][0], wa[1][ks][1], wa[1][ks][2], wa[1][ks][3], (fo ^ 32) + ks * 2048);
                }
            }
            bar_sync(NB_W0 + kh, 128);
            if (m == 0) {
#pragma unroll 4
                for (int dd = 0; dd < 16; dd++) {
                    const int d = dd * 16 + (t128 >> 3), pp = pos_of_d(d);
                    cp_async16(stg + pp * 128 + ((ch ^ (pp & 7)) << 4), p.wk + goff + (size_t)d * HD_);
                }
                cp_async_commit();
            }
        }
    }
    const uint32_t tab = stg + (aa * 32 + lane) * 16;
    {
        const uint32_t l7 = lane & 7, l8 = lane >> 3, g = lane >> 2, t = lane & 3;
        const uint32_t t0 = l7 * 128 + ((l8 ^ l7) << 4);
        const uint32_t tq = l7 * 128 + (((l8 >> 1) ^ l7) << 4);
        const uint32_t bq = warp >> 1, tp = warp & 1;
        uint4 v;
        v.x = sb + (aa < 2 ? R_QS : R_KMS) + l7 * 128 + (((4 * (aa & 1) + 2 * kh + (l8 & 1)) ^ l7) << 4);
        v.y = sb + R_QS + tq;
        v.z = sb + (warp == 0 ? R_KMS : R_KX + (warp - 1) * 1024) + t0;
        v.w = mapa_u32(sb + R_SX + (rank * 5 + warp) * 256 + lane * 8, crank ^ 1);
        sts128(tab, v);
        sts128(tab + 2048, make_uint4(sb + lane * 16 + R_MEM + kh * 4096, sb + lane * 16 + R_WV + warp * 8192,
                                      sb + lane * 16 + R_VP + warp * 512, sb + lane * 16 + R_VP + 4096 + (warp ^ 4) * 512));
        const uint32_t src = (l8 >> 1) * 8 + l7;
        const uint32_t L = bq * 8 + 2 * tp + (l8 & 1);
        const uint32_t d0 = (crank + ((t >> 1) | (g & 6))) & 15;
        v.x = sb + R_RS + src * 512 + ((L ^ (src & 7)) << 4);
        v.y = mapa_u32(sb + R_MEM + (crank * 4 + bq) * 128 + (4 * tp + 2 * (t & 1) + (g & 1)) * 16, d0);
        v.z = mapa_u32(sb + ((crank & 2) ? RB_A1 : RB_A), d0);
        v.w = lane;
        sts128(tab + 4096, v);
        const uint64_t wr = (uint64_t)(g_F + ((crank * 2 + ((crank ^ (crank >> 3) ^ sel) & 1)) * 1024 + warp * 128 + cl * 32 + lane));
        sts128(tab + 6144, make_uint4((uint32_t)wr, (uint32_t)(wr >> 32), (uint32_t)((((cl + 1) & 3) - cl) * 128), (uint32_t)((((cl + 2) & 3) - cl) * 128)));
        sts32(tab + 8192, (uint32_t)((((cl + 3) & 3) - cl) * 128));
#pragma unroll
        for (int i = 0; i < NOFF; i++)
            sts128(tab + 10240 + i * 2048, make_uint4(wa[i & 1][i >> 1][0], wa[i & 1][i >> 1][1], wa[i & 1][i >> 1][2], wa[i & 1][i >> 1][3]));
    }
    bar_sync(NB_D, 384);
    uint32_t slot_off = 0;
    const uint32_t slot_inc = warp == 0 ? 2048 : 4096, slot_last = warp == 0 ? 2048 : (R_NST - 1) * 4096;
    const uint32_t sx_bar_rem = (sb + RB_SX) ^ (1u << 24);
    uint4 tb = lds128(tab + 2048);
#pragma unroll 1
    for (int s = 0; s < NSEG; s++) {
        if (s > 0) mbar_wait(sb + RB_A, (s - 1) & 1);
        if (warp == 0) { PROF(0); PROFG(13); }
        uint4 ta;
        const uint32_t km_tog = aa >= 2 ? (s & 1) * 2048 : 0;
        {
            float acc[5][4];
#pragma unroll
            for (int c = 0; c < 5; c++) { acc[c][0] = acc[c][1] = acc[c][2] = acc[c][3] = 0.f; }
            uint32_t b[8][4];
            uint4 av[16];
            static_assert(VK0 == 4, "order below assumes the V/O warps cover slices 0,1");
            ldsm4(b[0][0], b[0][1], b[0][2], b[0][3], tb.x);
            ldsm4(b[1][0], b[1][1], b[1][2], b[1][3], tb.x + 512);
            ldsm4(b[4][0], b[4][1], b[4][2], b[4][3], tb.x + 2048);
            ldsm4(b[5][0], b[5][1], b[5][2], b[5][3], tb.x + 2560);
#pragma unroll
            for (int kk = 0; kk < 8; kk++) {
                const int k2 = kk < 2 ? kk : (kk < 4 ? kk + 2 : (kk < 6 ? kk - 2 : kk));
                if (kk == 4) {
                    if (s > 0) mbar_wait(sb + RB_A1, (s - 1) & 1);
                    ldsm4(b[2][0], b[2][1], b[2][2], b[2][3], tb.x + 1024);
                    ldsm4(b[3][0], b[3][1], b[3][2], b[3][3], tb.x + 1536);
                    ldsm4(b[6][0], b[6][1], b[6][2], b[6][3], tb.x + 3072);
                    ldsm4(b[7][0], b[7][1], b[7][2], b[7][3], tb.x + 3584);
#pragma unroll
                    for (int i = 12; i < 16; i++) av[i] = lds128(tb.y + i * 512);
                    ta = lds128(tab);
                }
                mma16816(acc[0], wa[0][2 * k2][0], wa[0][2 * k2][1], wa[0][2 * k2][2], wa[0][2 * k2][3], b[k2][0], b[k2][1]);
                mma16816(acc[1], wa[1][2 * k2][0], wa[1][2 * k2][1], wa[1][2 * k2][2], wa[1][2 * k2][3], b[k2][0], b[k2][1]);
                mma16816(acc[3], wa[0][2 * k2 + 1][0], wa[0][2 * k2 + 1][1], wa[0][2 * k2 + 1][2], wa[0][2 * k2 + 1][3], b[k2][2], b[k2][3]);
                mma16816(acc[4], wa[1][2 * k2 + 1][0], wa[1][2 * k2 + 1][1], wa[1][2 * k2 + 1][2], wa[1][2 * k2 + 1][3], b[k2][2], b[k2][3]);
                if (2 * k2 >= VK0) {
                    mma16816(acc[2], av[2 * k2].x, av[2 * k2].y, av[2 * k2].z, av[2 * k2].w, b[k2][0], b[k2][1]);
                    mma16816(acc[2], av[2 * k2 + 1].x, av[2 * k2 + 1].y, av[2 * k2 + 1].z, av[2 * k2 + 1].w, b[k2][2], b[k2][3]);
                }
                if (kk == 0) { av[8] = lds128(tb.y + 8 * 512); av[9] = lds128(tb.y + 9 * 512); }
                if (kk == 1) { av[10] = lds128(tb.y + 10 * 512); av[11] = lds128(tb.y + 11 * 512); }
                if (kk == 2) { av[4] = lds128(tb.y + 4 * 512); av[5] = lds128(tb.y + 5 * 512); }
                if (kk == 3) { av[6] = lds128(tb.y + 6 * 512); av[7] = lds128(tb.y + 7 * 512); }
            }
#pragma unroll
            for (int i = 0; i < 4; i++) { acc[0][i] += acc[3][i]; acc[1][i] += acc[4][i]; }
            const float g0 = kh ? acc[0][0] : acc[1][0], g1 = kh ? acc[0][1] : acc[1][1], g2 = kh ? acc[0][2] : acc[1][2], g3 = kh ? acc[0][3] : acc[1][3];
            sts128(tb.w, make_uint4(__float_as_uint(g0), __float_as_uint(g1), __float_as_uint(g2), __float_as_uint(g3)));
            const float k0 = kh ? acc[1][0] : acc[0][0], k1 = kh ? acc[1][1] : acc[0][1], k2_ = kh ? acc[1][2] : acc[0][2], k3 = kh ? acc[1][3] : acc[0][3];
            if (warp == 0) PROF(1);
            bar_sync(NB_X + aa, 64);
            const uint4 o = lds128(tb.z + 4096);
            stsm2t(ta.x ^ km_tog, pack2(k0 + __uint_as_float(o.x), k1 + __uint_as_float(o.y)), pack2(k2_ + __uint_as_float(o.z), k3 + __uint_as_float(o.w)));
            sts128(tb.z, make_uint4(__float_as_uint(acc[2][0]), __float_as_uint(acc[2][1]), __float_as_uint(acc[2][2]), __float_as_uint(acc[2][3])));
        }
        const uint32_t kb = ta.z + slot_off;
        if (warp == 0) PROF(14);
        bar_sync(NB_B, 256);
        if (warp < 5) {
            uint32_t q[16], k0, k1, k2, k3, k4, k5, k6, k7;
            float sa[4] = {0.f, 0.f, 0.f, 0.f}, sc[4] = {0.f, 0.f, 0.f, 0.f};
            ldsm4(q[0], q[1], q[2], q[3], ta.y);
            ldsm4(k0, k1, k2, k3, kb);
            ldsm4(q[4], q[5], q[6], q[7], ta.y ^ 32);
            ldsm4(q[8], q[9], q[10], q[11], ta.y ^ 64);
            ldsm4(k4, k5, k6, k7, kb ^ 64);
            ldsm4(q[12], q[13], q[14], q[15], ta.y ^ 96);
            mma16816(sa, q[0], q[1], q[2], q[3], k0, k1);
            bar_arrive(NB_Y, 288);
            mma16816(sc, q[4], q[5], q[6], q[7], k2, k3);
            mma16816(sa, q[8], q[9], q[10], q[11], k4, k5);
            mma16816(sc, q[12], q[13], q[14], q[15], k6, k7);
            const float scl = 0.08838834764831845f * 1.4426950408889634f;
            const float r0 = (sa[0] + sc[0]) * scl, r1 = (sa[1] + sc[1]) * scl;
            if (s != NSEG - 1) {
                st_async_v2(ta.w, r0, r1, sx_bar_rem);
                st_async_v2(ta.w ^ (1u << 24), r0, r1, sx_bar_rem ^ (1u << 24));
            }
            if (warp == 0) PROF(2);
        } else if (s > 0 && warp == 7 && lane == 0) {
            mbar_expect_tx(sb + RB_A, 4096);
            mbar_expect_tx(sb + RB_A1, 4096);
        } else if (s > 0 && (s & 3) == 0 && warp == 6) {
            bar_sync(NB_K, 160);
            if (lane == 0) red_release(&g_flags[F_MEM + (s >> 2) - 1], 1);
            __syncwarp();
        }
        if (s == NSEG - 1) {
            const uint4 td = lds128(tab + 6144);
            stg_relaxed32((uint32_t*)(((uint64_t)td.y << 32) | (td.x ^ 0x21000)), 0u);
            break;
        }
        slot_off = slot_off == slot_last ? 0 : slot_off + slot_inc;
        const uint4 tc = lds128(tab + 4096), td = lds128(tab + 6144);
        const uint32_t te = lds32(tab + 8192);
        uint32_t* wr = (uint32_t*)(((uint64_t)td.y << 32) | (td.x ^ ((s & 1) * 0x21000)));
        const uint32_t* r1p = (const uint32_t*)((const char*)wr + (int)td.z);
        const uint32_t* r2p = (const uint32_t*)((const char*)wr + (int)td.w);
        const uint32_t* r3p = (const uint32_t*)((const char*)wr + (int)te);
        const uint32_t tag = ((s >> 1) + 1) & 1;
        mbar_wait(sb + RB_E, s & 1);
        if (warp == 0) PROF(7);
        {
            uint32_t a0, a1, a2, a3, a4, a5, a6, a7;
            ldsm4t(a0, a1, a2, a3, tc.x);
            ldsm4t(a4, a5, a6, a7, tc.x ^ 64);
            const uint32_t one = 0x3F803F80u;
            float d0_[4] = {0.f, 0.f, 0.f, 0.f}, d1_[4] = {0.f, 0.f, 0.f, 0.f};
            mma16816(d0_, a0, a1, a2, a3, one, one);
            mma16816(d1_, a4, a5, a6, a7, one, one);
            const bool t1 = tc.w & 1, t2 = tc.w & 2;
            const float x = t2 ? (t1 ? d1_[2] : d1_[0]) : (t1 ? d0_[2] : d0_[0]);
            const uint32_t own = (__float_as_uint(x) & ~1u) | tag;
            stg_relaxed32(wr, own);
            const uint32_t tq = clk32();
            if (warp == 0) PROF(8);
            PROFG(16 + warp);
            while ((int)(clk32() - tq) < POLL_GAP) {}
            uint32_t f1 = ldg_relaxed32(r1p), f2 = ldg_relaxed32(r2p), f3 = ldg_relaxed32(r3p);
#pragma unroll
            for (int i = 0; i < NOFF; i++) {
                const uint4 f0 = lds128(tab + 10240 + i * 2048);
                wa[i & 1][i >> 1][0] = f0.x; wa[i & 1][i >> 1][1] = f0.y; wa[i & 1][i >> 1][2] = f0.z; wa[i & 1][i >> 1][3] = f0.w;
            }
            tb = lds128(tab + 2048);
            int gg = 0;
#pragma unroll 1
            while (!__all_sync(~0u, (((f1 ^ tag) | (f2 ^ tag) | (f3 ^ tag)) & 1) == 0)) {
                f1 = ldg_relaxed32(r1p); f2 = ldg_relaxed32(r2p); f3 = ldg_relaxed32(r3p);
                if (++gg > 16 * SPIN_LIMIT) { TIMEOUT(3, s); break; }
            }
            if (warp == 0) PROF(9);
            const float v = (__uint_as_float(own) + __uint_as_float(f2)) + (__uint_as_float(f1) + __uint_as_float(f3));
            const bool b8 = tc.w & 8, b16 = tc.w & 16;
            const float recv = __shfl_xor_sync(~0u, v, 8);
            const uint32_t word = b8 ? pack2(recv, v) : pack2(v, recv);
            const uint32_t oth = __shfl_xor_sync(~0u, word, 16);
            const uint32_t wl = b16 ? oth : word, wh = b16 ? word : oth;
            const uint32_t p0 = __shfl_xor_sync(~0u, wl, 2), p1 = __shfl_xor_sync(~0u, wh, 2);
            const uint4 item = t2 ? make_uint4(p0, p1, wl, wh) : make_uint4(wl, wh, p0, p1);
            st_async_v4(tc.y, item, tc.z);
            st_async_v4(tc.y ^ (8u << 24), item, tc.z ^ (8u << 24));
            if (tc.w == 0 && warp == 7) mbar_expect_tx(sb + RB_E, 8192);
            if (warp == 0) PROF(10);
            PROF(40 + warp);
        }
        bar_sync(NB_D, 384);
    }
}

__device__ __forceinline__ void rec_load_kv(uint32_t sb, int col0, int s, uint32_t slot_off, int t128) {
    const int row = t128 >> 2, c2 = (t128 & 3) * 2;
    const bf16* src = g_kv + ((size_t)(s * 32 + row) * (2 * HD_) + col0 + c2 * 8);
    const uint32_t d0 = sb + R_KX + slot_off + row * 128 + ((c2 ^ (row & 7)) << 4);
    cp_async16(d0, src);
    cp_async16(d0 ^ 16, src + 8);
    cp_async16(d0 + (R_VX - R_KX), src + HD_);
    cp_async16((d0 ^ 16) + (R_VX - R_KX), src + HD_ + 8);
}

__device__ __forceinline__ void rec_store_kvm(uint32_t sb, int col0, int s, int w, int lane) {
    const int tok = (w & 1) * 4 + (lane >> 3);
    const uint4 v = lds128(sb + R_KMS + (s & 1) * 2048 + (w >> 1) * 1024 + tok * 128 + (((lane & 7) ^ tok) << 4));
    *(uint4*)(g_kvm + ((s * 8 + tok) * (2 * HD_) + (w >> 1) * HD_ + col0 + (lane & 7) * 8)) = v;
}

__device__ __forceinline__ void rec_vo(const RecParams& p, const uint32_t sb, const int cta, const int warp, int lane) {
    const int w = warp - 8, crank = cta & 15;
    const int col0 = cta * 64;
    uint32_t wo[8][4][4];
    {
        const int t128 = w * 32 + lane;
        const bf16* Wo = p.wo + (size_t)col0 * D_;
        const uint32_t stg = sb + R_STG + 2 * 32768;
#pragma unroll
        for (int half = 0; half < 2; half++) {
#pragma unroll 4
            for (int i = t128; i < 2048; i += 128) {
                const int e = i >> 6, ch = i & 63;
                cp_async16(stg + e * 1024 + ((ch ^ (e & 7)) << 4), Wo + (size_t)(half * 32 + e) * D_ + ch * 8);
            }
            cp_async_commit();
            cp_async_wait<0>();
            bar_sync(NB_W0 + 2, 128);
#pragma unroll
            for (int j = 0; j < 8; j++)
#pragma unroll
                for (int kk = 0; kk < 2; kk++) {
                    const int e = kk * 16 + (lane >> 4) * 8 + (lane & 7);
                    const int ch = (w * 8 + j) * 2 + ((lane >> 3) & 1);
                    ldsm4t(wo[j][half * 2 + kk][0], wo[j][half * 2 + kk][1], wo[j][half * 2 + kk][2], wo[j][half * 2 + kk][3],
                           stg + e * 1024 + ((ch ^ (e & 7)) << 4));
                }
            bar_sync(NB_W0 + 2, 128);
        }
        if (lane == 0) wait_flag(F_KV + 0, 64);
        __syncwarp();
        rec_load_kv(sb, col0, 0, 0, t128); cp_async_commit();
        rec_load_kv(sb, col0, 1, 4096, t128); cp_async_commit();
        cp_async_wait<1>();
    }
    const uint32_t tab = sb + R_STG + 2 * 32768 + (w * 32 + lane) * 16;
    {
        const uint32_t l7 = lane & 7, l8 = lane >> 3, g = lane >> 2;
        uint4 v;
        v.x = sb + R_VX + ((l8 & 1) * 8 + l7) * 128 + (((2 * w + (l8 >> 1)) ^ l7) << 4);
        v.y = sb + R_OS + g * 128 + (((2 * w) ^ g) << 4) + (lane & 3) * 4;
        v.z = sb + R_VMS + l7 * 128 + (((2 * w + (l8 & 1)) ^ l7) << 4);
        v.w = sb + R_OS + l7 * 128 + ((l8 ^ l7) << 4);
        sts128(tab, v);
        v.x = mapa_u32(sb + R_RS + crank * 512 + ((lane ^ (crank & 7)) << 4), w * 4);
        v.y = mapa_u32(sb + RB_E, w * 4);
        v.z = sb + R_VP + w * 512 + lane * 16;
        v.w = sb + R_SX + lane * 8;
        sts128(tab + 2048, v);
#pragma unroll
        for (int i = 0; i < 8; i++) sts128(tab + 4096 + i * 2048, make_uint4(wo[i][0][0], wo[i][0][1], wo[i][0][2], wo[i][0][3]));
        const int tok = (w & 1) * 4 + (lane >> 3), row = (w * 32 + lane) >> 2, c2 = (lane & 3) * 2;
        const uint64_t kd = (uint64_t)(g_kvm + (tok * (2 * HD_) + (w >> 1) * HD_ + col0 + (lane & 7) * 8));
        const uint64_t ks = (uint64_t)(g_kv + ((size_t)row * (2 * HD_) + col0 + c2 * 8));
        sts128(tab + 20480, make_uint4((uint32_t)kd, (uint32_t)(kd >> 32), (uint32_t)ks, (uint32_t)(ks >> 32)));
        sts128(tab + 22528, make_uint4(sb + R_KMS + (w >> 1) * 1024 + tok * 128 + (((lane & 7) ^ tok) << 4),
                                       sb + R_KX + row * 128 + ((c2 ^ (row & 7)) << 4), lane, 0));
    }
    bar_sync(NB_D, 384);
    const uint32_t lane16 = lds32(tab + 2048 + 8) - R_VP - w * 512;
    uint4 av[2 * VK0];
#pragma unroll
    for (int i = 0; i < 2 * VK0; i++) av[i] = lds128(lane16 + R_WV + (i / VK0) * 32768 + (w * 16 + i % VK0) * 512);
    uint32_t slot_off = 0;
#pragma unroll 1
    for (int s = 0; s < NSEG; s++) {
        if (s > 0) {
            mbar_wait(sb + RB_A, (s - 1) & 1);
            const uint4 tp = lds128(tab + 20480), tq = lds128(tab + 22528);
            const uint4 kvm = lds128(tq.x + ((s - 1) & 1) * 2048);
            *(uint4*)((((uint64_t)tp.y << 32) | tp.x) + (uint64_t)(s - 1) * (8 * 2 * HD_ * 2)) = kvm;
            if ((s & 3) == 0) bar_arrive(NB_K, 160);
            if (s + 1 < NSEG - 1) {
                if (((s + 1) & 3) == 0) { if (tq.z == 0) wait_flag(F_KV + ((s + 1) >> 2), 64); __syncwarp(); }
                const char* src = (const char*)((((uint64_t)tp.w << 32) | tp.z) + (uint64_t)(s + 1) * (32 * 2 * HD_ * 2));
                const uint32_t d0 = tq.y + (slot_off == (R_NST - 1) * 4096 ? 0 : slot_off + 4096);
                cp_async16(d0, src);
                cp_async16(d0 ^ 16, src + 16);
                cp_async16(d0 + (R_VX - R_KX), src + HD_ * 2);
                cp_async16((d0 ^ 16) + (R_VX - R_KX), src + HD_ * 2 + 16);
            }
            cp_async_commit();
        }
        bar_sync(NB_Y, 288);
        uint32_t vb0, vb1;
        {
            float va[4] = {0.f, 0.f, 0.f, 0.f}, vc[4] = {0.f, 0.f, 0.f, 0.f};
            uint32_t bb[VK0][4];
#pragma unroll
            for (int k2 = 0; k2 < VK0; k2++) ldsm4(bb[k2][0], bb[k2][1], bb[k2][2], bb[k2][3], lane16 + R_MEM + (k2 / (VK0 / 2)) * 4096 + (k2 % (VK0 / 2)) * 512);
#pragma unroll
            for (int k2 = 0; k2 < VK0; k2++) {
                mma16816(va, av[2 * k2].x, av[2 * k2].y, av[2 * k2].z, av[2 * k2].w, bb[k2][0], bb[k2][1]);
                mma16816(vc, av[2 * k2 + 1].x, av[2 * k2 + 1].y, av[2 * k2 + 1].z, av[2 * k2 + 1].w, bb[k2][2], bb[k2][3]);
            }
            const uint4 a = lds128(lane16 + R_VP + w * 512), b = lds128(lane16 + R_VP + 2048 + w * 512);
            vb0 = pack2((va[0] + vc[0]) + (__uint_as_float(a.x) + __uint_as_float(b.x)), (va[1] + vc[1]) + (__uint_as_float(a.y) + __uint_as_float(b.y)));
            vb1 = pack2((va[2] + vc[2]) + (__uint_as_float(a.z) + __uint_as_float(b.z)), (va[3] + vc[3]) + (__uint_as_float(a.w) + __uint_as_float(b.w)));
        }
        const uint4 ta = lds128(tab), tb = lds128(tab + 2048);
        uint32_t vx[8];
        ldsm4t(vx[0], vx[1], vx[2], vx[3], ta.x + slot_off);
        ldsm4t(vx[4], vx[5], vx[6], vx[7], ta.x + slot_off + 2048);
#pragma unroll
        for (int i = 0; i < 4; i++) {
            const uint4 f0 = lds128(tab + 4096 + i * 2048);
            wo[i][0][0] = f0.x; wo[i][0][1] = f0.y; wo[i][0][2] = f0.z; wo[i][0][3] = f0.w;
        }
        if (w == 0) PROF(11);
        uint32_t pf[5];
        float oa[2][4] = {{0.f, 0.f, 0.f, 0.f}, {0.f, 0.f, 0.f, 0.f}}, ob_[2][4] = {{0.f, 0.f, 0.f, 0.f}, {0.f, 0.f, 0.f, 0.f}};
        float sm0[4] = {0.f, 0.f, 0.f, 0.f}, sm1[4] = {0.f, 0.f, 0.f, 0.f};
        if (s != NSEG - 1) {
            mbar_wait(sb + RB_SX, s & 1);
            if (w == 0) PROF(4);
            float sv[10];
#pragma unroll
            for (int n = 0; n < 5; n++) {
                const float2 a = lds64f(tb.w + n * 256), b = lds64f(tb.w + (5 + n) * 256);
                sv[2 * n] = a.x + b.x; sv[2 * n + 1] = a.y + b.y;
            }
            float mx = fmaxf(fmaxf(fmaxf(sv[0], sv[1]), fmaxf(sv[2], sv[3])), fmaxf(fmaxf(sv[4], sv[5]), fmaxf(sv[6], sv[7])));
            mx = fmaxf(mx, fmaxf(sv[8], sv[9]));
            mx = fmaxf(mx, __shfl_xor_sync(~0u, mx, 1));
            mx = fmaxf(mx, __shfl_xor_sync(~0u, mx, 2));
#pragma unroll
            for (int n = 1; n < 5; n++) pf[n] = pack2(ex2(sv[2 * n] - mx), ex2(sv[2 * n + 1] - mx));
            pf[0] = pack2(ex2(sv[0] - mx), ex2(sv[1] - mx));
            if (w == 0) PROF(12);
            const uint32_t one = 0x3F803F80u;
            mma16816h(sm0, pf[1], pf[2], one, one);
            mma16816h(oa[0], pf[1], pf[2], vx[0], vx[1]);
            mma16816h(oa[1], pf[1], pf[2], vx[2], vx[3]);
            mma16816h(sm1, pf[3], pf[4], one, one);
            mma16816h(ob_[0], pf[3], pf[4], vx[4], vx[5]);
            mma16816h(ob_[1], pf[3], pf[4], vx[6], vx[7]);
            mma1688h(sm0, pf[0], one);
            mma1688h(oa[0], pf[0], vb0);
            mma1688h(oa[1], pf[0], vb1);
            float inv;
            asm("rcp.approx.ftz.f32 %0, %1;" : "=f"(inv) : "f"(sm0[0] + sm1[0]));
            oa[0][0] += ob_[0][0]; oa[0][1] += ob_[0][1]; oa[1][0] += ob_[1][0]; oa[1][1] += ob_[1][1];
            sts32(ta.y, pack2(oa[0][0] * inv, oa[0][1] * inv));
            sts32(ta.y ^ 16, pack2(oa[1][0] * inv, oa[1][1] * inv));
            const uint32_t oa2 = ta.w ^ 64;
            bar_sync(NB_C, 128);
            if (w == 0) PROF(5);
            uint32_t ob[8];
            ldsm4(ob[0], ob[1], ob[2], ob[3], ta.w);
            ldsm4(ob[4], ob[5], ob[6], ob[7], oa2);
#pragma unroll
            for (int i = 4; i < 8; i++) {
                const uint4 f0 = lds128(tab + 4096 + i * 2048);
                wo[i][0][0] = f0.x; wo[i][0][1] = f0.y; wo[i][0][2] = f0.z; wo[i][0][3] = f0.w;
            }
#pragma unroll
            for (int jj = 0; jj < 2; jj++) {
                if (jj == 1 && tb.w == 0) break;
                float acc[4][4];
#pragma unroll
                for (int c = 0; c < 4; c++) { acc[c][0] = acc[c][1] = acc[c][2] = acc[c][3] = 0.f; }
#pragma unroll
                for (int ks = 0; ks < 4; ks++)
#pragma unroll
                    for (int c = 0; c < 4; c++)
                        mma16816(acc[c], wo[jj * 4 + c][ks][0], wo[jj * 4 + c][ks][1], wo[jj * 4 + c][ks][2], wo[jj * 4 + c][ks][3], ob[2 * ks], ob[2 * ks + 1]);
#pragma unroll
                for (int pr = 0; pr < 2; pr++) {
                    uint4 v;
                    v.x = pack2(acc[2 * pr][0], acc[2 * pr][1]);
                    v.y = pack2(acc[2 * pr][2], acc[2 * pr][3]);
                    v.z = pack2(acc[2 * pr + 1][0], acc[2 * pr + 1][1]);
                    v.w = pack2(acc[2 * pr + 1][2], acc[2 * pr + 1][3]);
                    st_async_v4(tb.x + ((jj * 2 + pr) << 24), v, tb.y + ((jj * 2 + pr) << 24));
                }
            }
            if (w == 0) PROF(6);
        }
        stsm2t(ta.z + (s & 1) * 2048, vb0, vb1);
        cp_async_wait<0>();
        bar_sync(NB_C, 128);
        if (w == 0 && lane == 0 && s != NSEG - 1) mbar_expect_tx(sb + RB_SX, 2560);
        if (s != NSEG - 1) bar_arrive(NB_D, 384);
#pragma unroll
        for (int i = 0; i < 2 * VK0; i++) av[i] = lds128(lane16 + R_WV + (i / VK0) * 32768 + (w * 16 + i % VK0) * 512);
        slot_off = slot_off == (R_NST - 1) * 4096 ? 0 : slot_off + 4096;
    }
    rec_store_kvm(sb, col0, NSEG - 1, w, lane);
    bar_sync(NB_C, 128);
    if (w == 0 && lane == 0) red_release(&g_flags[F_MEM + NRB - 1], 1);
}

__global__ void __launch_bounds__(384, 1) k_rec(const RecParams p) {
    extern __shared__ __align__(1024) unsigned char smem_raw[];
    const uint32_t sb = __shfl_sync(~0u, smem_u32(smem_raw), 0);
    const int warp = __shfl_sync(~0u, threadIdx.x >> 5, 0);
    int lane; asm volatile("mov.u32 %0, %%laneid;" : "=r"(lane));
    const int crank = blockIdx.x & 15, slot = blockIdx.x >> 4;
    asm volatile("griddepcontrol.launch_dependents;");
    if (threadIdx.x == 0) {
        mbar_init(sb + RB_SX, 1); mbar_init(sb + RB_E, 1); mbar_init(sb + RB_A, 1); mbar_init(sb + RB_A1, 1); mbar_init(sb + RB_ROLE, 1);
        asm volatile("fence.mbarrier_init.release.cluster;" ::: "memory");
        mbar_expect_tx(sb + RB_SX, 2560);
        mbar_expect_tx(sb + RB_E, 8192);
        mbar_expect_tx(sb + RB_A, 4096);
        mbar_expect_tx(sb + RB_A1, 4096);
        mbar_expect_tx(sb + RB_ROLE, 4);
    }
    unsigned role = 0;
    if (crank == 0 && threadIdx.x == 0) {
        unsigned x = 0;
        int tm[2] = {0x7fffffff, 0x7fffffff};
#pragma unroll 1
        for (int i = 0; i < 6; i++) {
            const uint32_t t0 = clk32();
            x = atomicAdd(&g_F[65536 + (i & 1) * 1024 + slot * 64 + (x >> 31)], 0u) & 0x7fffffffu;
            if (x == 0x7654321u) sts32(sb + R_BAR + 56, x);
            const int dt = (int)(clk32() - t0);
            if (i >= 2) { if (i & 1) tm[1] = min(tm[1], dt); else tm[0] = min(tm[0], dt); }
        }
        const int side = tm[1] > tm[0];
        const unsigned old = atomicAdd(&g_flags[F_SIDE + side * 32], 1u);
        unsigned c0, c1; int gd = 0;
#pragma unroll 1
        do { c0 = ldg_relaxed32(&g_flags[F_SIDE]); c1 = ldg_relaxed32(&g_flags[F_SIDE + 32]); } while ((int)(c0 + c1) < p.ncl && ++gd < 64 * SPIN_LIMIT);
        const int big = c1 > c0;
        role = side == big ? old : (big ? c1 : c0) + old;
        role |= (big ^ 1) << 8;
    }
    __syncwarp();
    asm volatile("barrier.cluster.arrive.relaxed.aligned;\nbarrier.cluster.wait.aligned;" ::: "memory");
    if (crank == 0 && warp == 0) {
        role = __shfl_sync(~0u, role, 0);
        if (lane < 16)
            asm volatile("st.async.weak.shared::cluster.mbarrier::complete_tx::bytes.u32 [%0], %1, [%2];"
                         :: "r"(mapa_u32(sb + R_BAR + 48, lane)), "r"(role), "r"(mapa_u32(sb + RB_ROLE, lane)) : "memory");
    }
    mbar_wait(sb + RB_ROLE, 0);
    const int rolew = __shfl_sync(~0u, lds32(sb + R_BAR + 48), 0);
    const int cl = rolew & 255;
    if (cl >= 4) return;
    const int cta = cl * 16 + crank;
    if (warp < 8) rec_qk(p, sb, cta, warp, lane, rolew >> 8);
    else rec_vo(p, sb, cta, warp, lane);
}

enum { J_KV = 0, J_QA = 1, J_O = 2, J_LN = 3, J_UP = 4, J_DN = 5, J_LN1 = 6, J_MOD = 7, J_UP2 = 8, J_END = 9 };
constexpr int NJ_O = 2 * OSPLIT, NJ_O2 = 2 * OSPLIT2, NJ_LN = 8, NJ_LN2 = 16, NJ_UP = 14, NJ_UP2 = 28, NJ_DN = 8, NJ_LN1 = 8;
constexpr uint64_t pk8(int a, int b, int c, int d, int e, int f, int g, int h) {
    return (uint64_t)a | ((uint64_t)b << 8) | ((uint64_t)c << 16) | ((uint64_t)d << 24) | ((uint64_t)e << 32) | ((uint64_t)f << 40) | ((uint64_t)g << 48) | ((uint64_t)h << 56);
}
constexpr uint64_t NJ_C = pk8(32, 16, NJ_O, NJ_LN, NJ_UP, NJ_DN, NJ_LN1, 16), NJ_F = pk8(32, 16, NJ_O2, NJ_LN2, NJ_UP2, NJ_DN, NJ_LN1, 0);
constexpr uint64_t TG_C = pk8(2 * NJ_LN1, 64, 32, 2 * NJ_O, 2 * NJ_LN, 2 * NJ_UP, 32, 0), TG_F = pk8(2 * NJ_LN1, 64, 32, 2 * NJ_O2, 2 * NJ_LN2, 2 * NJ_UP2, 32, 0);
constexpr uint64_t PRIO = pk8(4, 10, 9, 8, 7, 6, 3, 0);
__device__ __forceinline__ int pick_job(int lane, int qmask, int& idx) {
    const int rb = lane & 15, half = lane >> 4;
    const uint64_t nj = (rb >= FINE_RB ? NJ_F : (rb < 3 ? NJ_C : NJ_C & ~(0xffull << 56))) >> (8 * half);
    const uint64_t tg = (rb >= FINE_RB ? TG_F : TG_C) >> (8 * half);
    const unsigned* cp = &g_flags[F_CLAIM + half * 32 + rb];
    const unsigned* dp = &g_flags[half * 32 + rb];
    int gd = 0;
#pragma unroll 1
    while (true) {
        const unsigned c0 = ldg_relaxed32(cp), c1 = ldg_relaxed32(cp + 64), c2 = ldg_relaxed32(cp + 128), c3 = ldg_relaxed32(cp + 192);
        const unsigned d0 = ldg_relaxed32(dp - (half ? (rb >= FINE_RB ? 2 : (rb ? 1 : 0)) : 0)), d1 = ldg_relaxed32(dp + 64), d2 = ldg_relaxed32(dp + 128), d3 = ldg_relaxed32(dp + 192 - rb);
        const unsigned cl[4] = {c0, c1, c2, c3}, dv[4] = {d0, d1, d2, d3};
        unsigned key = 0xffffu, key2 = 0xffffu;
        bool pre = false;
#pragma unroll
        for (int i = 0; i < 4; i++) {
            const int q = half + 2 * i;
            const bool have = ((qmask >> q) & 1) && cl[i] < (unsigned)((nj >> (16 * i)) & 255);
            bool ready = have && dv[i] >= (unsigned)((tg >> (16 * i)) & 255);
            unsigned pr = (unsigned)((PRIO >> (8 * q)) & 255);
            if (i == 0 && rb == 0) { ready = have; pr = half ? pr : 2; }
            if (i == 3 && rb == 0) ready = have;
            if (i == 3 && rb == 0 && !half) pr = 1;
            if (i == 3 && rb > 0) pr = 3;
            if (i == 0 && half && rb >= FINE_RB) pr = 5;
            if (ready) key = min(key, (pr << 8) | (rb << 4) | q);
            if (have) key2 = min(key2, rb >= FINE_RB ? (0x100u | (q << 4) | rb) : (i == 0 || i == 3 ? 0u : 0x1000u));
            pre |= have && (i == 3 || (i == 0 && !half));
        }
        const bool anypre = __any_sync(~0u, pre);
        if (anypre && (key & 15) == J_QA) key = 0xffffu;
        key = __reduce_min_sync(~0u, key);
        key2 = __reduce_min_sync(~0u, key2);
        if (key2 == 0xffffu) return J_END;
        int pq, prb;
        if (key != 0xffffu) { pq = key & 15; prb = (key >> 4) & 15; }
        else if (key2 >= 0x120u && key2 < 0x1000u) { pq = (key2 >> 4) & 15; prb = key2 & 15; }
        else {
            __nanosleep(IDLE_NS);
            if (++gd > 16 * SPIN_LIMIT) { TIMEOUT(5, 0); return J_END; }
            continue;
        }
        int c = 0;
        if (lane == 0) c = (int)atomicAdd(&g_flags[F_CLAIM + pq * 32 + prb], 1u);
        c = __shfl_sync(~0u, c, 0);
        if (c < (int)(((prb >= FINE_RB ? NJ_F : NJ_C) >> (8 * pq)) & 255)) {
            idx = pq * 512 + prb * 32 + c;
            int acq = 0;
            if (pq != J_QA && pq < J_LN1) {
                if (lane == 0 && ld_acquire(&g_flags[pq * 32 + prb]) >= (unsigned)(((prb >= FINE_RB ? TG_F : TG_C) >> (8 * pq)) & 255)) {
                    asm volatile("fence.proxy.async.global;" ::: "memory");
                    acq = 1 << 24;
                }
            }
            return (pq == J_UP && prb >= FINE_RB ? J_UP2 : pq) | (prb << 8) | (c << 16) | acq;
        }
    }
}
__device__ __forceinline__ int op_row(int rb, int split) {
    return rb < FINE_RB ? split * S_ + rb * 128 : OSPLIT * S_ + (split * (NRB - FINE_RB) + rb - FINE_RB) * 128;
}

struct Pipe { uint32_t stage, phase; };
__device__ __forceinline__ void pipe_next(Pipe& p) { if (++p.stage == W_NST) { p.stage = 0; p.phase ^= 1; } }

__device__ __forceinline__ void scheduler(const Params& p, uint32_t sb, int lane) {
    const uint32_t bars = sb + SM_BAR;
    uint32_t ph = 0;
#pragma unroll 1
    while (true) {
        mbar_wait(bars + B_REQ, ph);
        int j = 4095;
        const int jd = pick_job(lane, p.qmask, j);
        if (lane == 0) { sts32(bars + B_NEXT, (uint32_t)jd); sts32(bars + B_NEXT + 4, (uint32_t)j); mbar_arrive(bars + B_RSP); }
        ph ^= 1;
        if (jd == J_END) break;
        __syncwarp();
    }
}

__device__ __forceinline__ void producer(const Params& p, uint32_t sb) {
    Pipe pp{0, 1};
    const uint32_t bars = sb + SM_BAR;
    uint32_t seq = 0, h_seen = 0;
    mbar_arrive(bars + B_REQ);
#pragma unroll 1
    while (true) {
        mbar_wait(bars + B_RSP, seq & 1);
        const int jd = (int)lds32(bars + B_NEXT), j = (int)lds32(bars + B_NEXT + 4);
        int left = (jd & 255) == J_DN ? 15 : ((jd & 255) == J_QA ? 12 : ((jd & 255) == J_O ? (((jd >> 8) & 255) >= FINE_RB ? 64 / OSPLIT2 : 64 / OSPLIT) : ((jd & 255) == J_LN || (jd & 255) == J_LN1 || (jd & 255) == J_MOD ? 1 : 8)));
        left = max(left - PICK_AHEAD, 1);
        TR(j, 1);
        const int type = jd & 255, rb = (jd >> 8) & 255, cb = (jd >> 16) & 255;
        const bool fine = rb >= FINE_RB, acquired = (jd >> 24) & 1;
        bool first = true;
        auto begin_stage = [&](uint32_t bytes) -> uint32_t {
            mbar_wait(bars + B_EMPTY + pp.stage * 8, pp.phase);
            if (first) { sts32(bars + B_RING + (seq & 7) * 4, (uint32_t)jd); sts32(bars + B_RING + 32 + (seq & 7) * 4, (uint32_t)j); first = false; }
            const uint32_t fb = bars + B_FULL + pp.stage * 8;
            if (bytes) mbar_expect_tx(fb, bytes); else mbar_arrive(fb);
            if (--left == 0 && type != J_END) mbar_arrive(bars + B_REQ);
            return fb;
        };
        if (type == J_END || type == J_LN || type == J_LN1 || type == J_MOD) {
            if (type == J_LN) { if (!acquired) wait_flag(F_OP + rb, 2 * (fine ? NJ_O2 : NJ_O)); if (!(h_seen >> 31)) { wait_flag(F_MOD + 1, 32); wait_flag(F_MOD + 2, 32); h_seen |= 1u << 31; } }

            TR(j, 2);
            begin_stage(0); pipe_next(pp);
            seq++;
            if (type == J_END) break;
            continue;
        }
        const CUtensorMap *ta, *tb0, *tb1;
        int k0 = 0, nk = 8, n0 = cb * 256, n1 = n0 + 128, nb = 4, dep = -1;
        unsigned tgt = 0;
        switch (type) {
            case J_KV: ta = &p.tm_h; tb0 = tb1 = cb < 16 ? &p.tm_wk : &p.tm_wv; n0 = (cb & 15) * 256; n1 = n0 + 128; dep = F_H + rb; tgt = 2 * NJ_LN1; break;
            case J_QA: ta = &p.tm_h; tb0 = tb1 = &p.tm_wq; dep = F_H + rb; tgt = 2 * NJ_LN1; break;
            case J_O: ta = &p.tm_o; tb0 = tb1 = &p.tm_wo; n0 = (cb & 1) * 256; n1 = n0 + 128; nk = fine ? 64 / OSPLIT2 : 64 / OSPLIT; k0 = (cb >> 1) * nk * 64;
                      dep = F_O + rb; tgt = 32; break;
            case J_UP: ta = &p.tm_h2; tb0 = &p.tm_wg; tb1 = &p.tm_wu; n0 = n1 = cb * 128; dep = F_H2 + rb; tgt = 2 * NJ_LN; break;
            case J_UP2: ta = &p.tm_h2; tb0 = &p.tm_wg; tb1 = &p.tm_wu; n0 = n1 = cb * 64; nb = 2; dep = F_H2 + rb; tgt = 2 * NJ_LN2; break;
            default: ta = &p.tm_act; tb0 = tb1 = &p.tm_wd; n0 = cb * 64; nk = 0; break;
        }
        const int m0 = rb * 128;
        if (type == J_DN) {
#pragma unroll 1
            for (int kb = 0; kb < 14; kb++) {
                const uint32_t fb = begin_stage(49152);
                const uint32_t st = sb + pp.stage * W_STAGE;
                const int k = kb * 128;
                tma_load2d(st + 32768, tb0, n0, k, fb);
                tma_load2d(st + 40960, tb0, n0, k + 64, fb);
                if (kb == 0) { if (!acquired) { wait_flag(F_ACT + rb, 2 * (fine ? NJ_UP2 : NJ_UP)); asm volatile("fence.proxy.async.global;" ::: "memory"); } TR(j, 2); }
                tma_load2d(st, ta, k, m0, fb);
                tma_load2d(st + 8192, ta, k, m0 + 64, fb);
                tma_load2d(st + 16384, ta, k + 64, m0, fb);
                tma_load2d(st + 24576, ta, k + 64, m0 + 64, fb);
                pipe_next(pp);
            }
        }
#pragma unroll 1
        for (int kb = 0; kb < nk; kb++) {
            const uint32_t fb = begin_stage(16384 + nb * 8192);
            const uint32_t st = sb + pp.stage * W_STAGE;
            const int k = k0 + kb * 64;
            tma_load2d(st + 16384, tb0, n0, k, fb);
            if (nb == 4) {
                tma_load2d(st + 16384 + 8192, tb0, n0 + 64, k, fb);
                tma_load2d(st + 16384 + 16384, tb1, n1, k, fb);
                tma_load2d(st + 16384 + 24576, tb1, n1 + 64, k, fb);
            } else if (nb == 2) {
                tma_load2d(st + 16384 + 8192, tb1, n1, k, fb);
            }
            if (kb == 0) {
                if (acquired && dep < 16) h_seen |= 1u << dep;
                if (dep >= 0 && !acquired && !(dep < 16 && ((h_seen >> dep) & 1))) {
                    wait_flag(dep, tgt);
                    if (type != J_O) asm volatile("fence.proxy.async.global;" ::: "memory");
                    if (dep < 16) h_seen |= 1u << dep;
                }
                TR(j, 2);
            }
            tma_load2d(st, ta, k, m0, fb);
            tma_load2d(st + 8192, ta, k, m0 + 64, fb);
            pipe_next(pp);
        }
        if (type == J_QA) {
            wait_flag(F_KV + rb, 64);
#pragma unroll 1
            for (int i = 0; i < 4; i++) {
                const uint32_t fb = begin_stage(40960);
                const uint32_t st = sb + pp.stage * W_STAGE;
                const int col = (i & 1) * HD_ + (cb * 2 + (i >> 1)) * DH_;
                tma_load2d(st, &p.tm_kv, col, m0, fb);
                tma_load2d(st + 8192, &p.tm_kv, col, m0 + 64, fb);
                tma_load2d(st + 16384, &p.tm_kv, col + 64, m0, fb);
                tma_load2d(st + 24576, &p.tm_kv, col + 64, m0 + 64, fb);
                if (i == 0) { wait_flag(F_MEM + rb, 64); asm volatile("fence.proxy.async.global;" ::: "memory"); }
                tma_load2d(st + 32768, &p.tm_kvm, col, rb * 32, fb);
                tma_load2d(st + 36864, &p.tm_kvm, col + 64, rb * 32, fb);
                pipe_next(pp);
            }
        } else if (type == J_DN) {
            const uint32_t fb = begin_stage(16384);
            const uint32_t st = sb + pp.stage * W_STAGE;
            tma_load2d(st, &p.tm_x1, n0, m0, fb);
            tma_load2d(st + 8192, &p.tm_x1, n0, m0 + 64, fb);
            pipe_next(pp);
        }
        seq++;
    }
}

__device__ __forceinline__ void store_warp(const Params& p, uint32_t sb, int wg, int lane) {
    const uint32_t bars = sb + SM_BAR;
    uint32_t seq = 0;
#pragma unroll 1
    while (true) {
        bar_sync(NB_ST + wg, 160);
        const uint32_t jd = lds32(bars + B_RING + (seq & 7) * 4);
        seq++;
        const int type = jd & 255, rb = (jd >> 8) & 255, cb = (jd >> 16) & 255;
        if (type == J_END) break;
        const uint32_t src = sb + W_STG + wg * 16384;
        const CUtensorMap* tm = nullptr; int n0 = cb * 256, nbox = 4, mrow = rb * 128 + wg * 64, flag = 0;
        switch (type) {
            case J_KV: tm = &p.tm_kv; flag = F_KV + rb; break;
            case J_QA: tm = &p.tm_o; flag = F_O + rb; break;
            case J_O: tm = &p.tm_op; n0 = (cb & 1) * 256; mrow = op_row(rb, cb >> 1) + wg * 64; flag = F_OP + rb; break;
            case J_LN: flag = F_H2 + rb; nbox = 0; break;
            case J_LN1: flag = F_H + rb; nbox = 0; break;
            case J_MOD: flag = F_MOD + rb; nbox = 0; break;
            case J_UP: tm = &p.tm_act; n0 = cb * 128; nbox = 2; flag = F_ACT + rb; break;
            case J_UP2: tm = &p.tm_act; n0 = cb * 64; nbox = 1; flag = F_ACT + rb; break;
            default: tm = &p.tm_out; n0 = cb * 64; nbox = 1; flag = -1; break;
        }
        if (nbox == 4) {
            if (lane == 0) {
                tma_store2d(tm, src, n0, mrow);
                tma_store2d(tm, src + 8192, n0 + 64, mrow);
                bulk_commit();
                asm volatile("cp.async.bulk.wait_group.read 0;" ::: "memory");
                mbar_arrive(bars + B_STGFREE + wg * 8);
            }
            __syncwarp();
            bar_sync(NB_ST + wg, 160);
            n0 += 128; nbox = 2;
        }
        if (lane == 0) {
            if (nbox) {
                tma_store2d(tm, src, n0, mrow);
                if (nbox == 2) tma_store2d(tm, src + 8192, n0 + 64, mrow);
                bulk_commit();
                asm volatile("cp.async.bulk.wait_group.read 0;" ::: "memory");
                mbar_arrive(bars + B_STGFREE + wg * 8);
                bulk_wait0();
                if (flag >= 0) asm volatile("red.relaxed.gpu.global.add.u32 [%0], 1;" :: "l"(&g_flags[flag]) : "memory");
            } else {
                mbar_arrive(bars + B_STGFREE + wg * 8);
                red_release(&g_flags[flag], 1);
            }
        }
        __syncwarp();
    }
}

__device__ __forceinline__ float gelu_tanh(float x) {
    const float t = x * fmaf(-0.10294324397f, x * x, -2.30220819814f);
    float r; asm("rcp.approx.ftz.f32 %0, %1;" : "=f"(r) : "f"(1.f + ex2(t)));
    return x * r;
}

#define CTR(i) do {} while (0)

template <int NSPLIT>
__device__ __forceinline__ void ln2_row(const Params& p, int rb, int r, int lane) {
    const int row = rb * 128 + r;
    uint4 u[2 * NSPLIT];
#pragma unroll
    for (int sp = 0; sp < NSPLIT; sp++) {
        const uint4* src = (const uint4*)(g_op + (size_t)(op_row(rb, sp) + r) * D_);
        u[2 * sp] = __ldcg(src + lane); u[2 * sp + 1] = __ldcg(src + 32 + lane);
    }
    const uint4* xr = (const uint4*)(p.x + (size_t)row * D_);
    const uint4 xa = __ldg(xr + lane), xb = __ldg(xr + 32 + lane);
    uint32_t ga[8], c1[8], sm[8];
    load_mod8(g_mod + 2 * D_, lane, ga);
    load_mod8(g_mod + 4 * D_, lane, c1);
    load_mod8(g_mod + 3 * D_, lane, sm);
    float a[16];
#pragma unroll
    for (int i = 0; i < 16; i++) a[i] = 0.f;
#pragma unroll
    for (int sp = 0; sp < 2 * NSPLIT; sp++) {
        float* q = a + (sp & 1) * 8;
        q[0] += bflo(u[sp].x); q[1] += bfhi(u[sp].x); q[2] += bflo(u[sp].y); q[3] += bfhi(u[sp].y);
        q[4] += bflo(u[sp].z); q[5] += bfhi(u[sp].z); q[6] += bflo(u[sp].w); q[7] += bfhi(u[sp].w);
    }
    const uint32_t xv[8] = {xa.x, xa.y, xa.z, xa.w, xb.x, xb.y, xb.z, xb.w};
    uint32_t v[8], r8[8];
#pragma unroll
    for (int i = 0; i < 8; i++) v[i] = hadd2(xv[i], hmul2(ga[i], pack2(a[2 * i], a[2 * i + 1])));
    uint4* x1r = (uint4*)(g_x1 + (size_t)row * D_);
    x1r[lane] = make_uint4(v[0], v[1], v[2], v[3]); x1r[32 + lane] = make_uint4(v[4], v[5], v[6], v[7]);
    uint32_t mu2; float rden;
    ln_stats(v, mu2, rden);
#pragma unroll
    for (int i = 0; i < 8; i++) c1[i] = hadd2(c1[i], 0x3F803F80u);
    ln_apply(v, mu2, rden, c1, sm, r8);
    uint4* hr = (uint4*)(g_h2 + (size_t)row * D_);
    hr[lane] = make_uint4(r8[0], r8[1], r8[2], r8[3]); hr[32 + lane] = make_uint4(r8[4], r8[5], r8[6], r8[7]);
}

__device__ __forceinline__ void consumer(const Params& p, uint32_t sb, int warp, int lane) {
    const uint32_t bars = sb + SM_BAR;
    const int wg = warp >> 2, wl = warp & 3;
    const uint32_t l7 = lane & 7, l8 = lane >> 3, g = lane >> 2, t = lane & 3;
    Pipe pp{0, 0};
    uint32_t seq = 0, stg_phase = 1;
    const int srow = wl * 16 + l7 + (l8 & 1) * 8;
    const uint32_t stg_base = sb + W_STG + wg * 16384 + srow * 128;
    const uint32_t sx = ((lane >> 4) ^ (srow & 7)) << 4;
#pragma unroll 1
    while (true) {
        mbar_wait(bars + B_FULL + pp.stage * 8, pp.phase);
        const uint32_t jd = lds32(bars + B_RING + (seq & 7) * 4);
        CTR(3);
        seq++;
        const int type = jd & 255, rb = (jd >> 8) & 255, cb = (jd >> 16) & 255;
        if (type == J_END) { mbar_wait(bars + B_STGFREE + wg * 8, stg_phase); bar_arrive(NB_ST + wg, 160); break; }
        if (type == J_MOD) {
            __syncwarp();
            if (lane == 0) mbar_arrive(bars + B_EMPTY + pp.stage * 8);
            pipe_next(pp);
            const int rg = warp * 4 + l8, col = rb * 1024 + cb * 64;
            uint4 wv[16];
#pragma unroll
            for (int i = 0; i < 16; i++) wv[i] = __ldg((const uint4*)(p.w_mod + (size_t)(rg * 16 + i) * (6 * D_) + col + l7 * 8));
            const uint32_t cw = __ldg((const uint32_t*)(p.c + rg * 16) + l7);
            const float cl = bflo(cw), ch = bfhi(cw);
            const uint32_t sw = pack2(__fdividef(cl, 1.f + __expf(-cl)), __fdividef(ch, 1.f + __expf(-ch)));
            float a[8];
#pragma unroll
            for (int i = 0; i < 8; i++) a[i] = 0.f;
#pragma unroll
            for (int i = 0; i < 16; i++) {
                const uint32_t sv = __shfl_sync(~0u, sw, (lane & 24) + (i >> 1));
                const float cv = (i & 1) ? bfhi(sv) : bflo(sv);
                a[0] = fmaf(cv, bflo(wv[i].x), a[0]); a[1] = fmaf(cv, bfhi(wv[i].x), a[1]); a[2] = fmaf(cv, bflo(wv[i].y), a[2]); a[3] = fmaf(cv, bfhi(wv[i].y), a[3]);
                a[4] = fmaf(cv, bflo(wv[i].z), a[4]); a[5] = fmaf(cv, bfhi(wv[i].z), a[5]); a[6] = fmaf(cv, bflo(wv[i].w), a[6]); a[7] = fmaf(cv, bfhi(wv[i].w), a[7]);
            }
#pragma unroll
            for (int i = 0; i < 8; i++) { a[i] += __shfl_xor_sync(~0u, a[i], 8); a[i] += __shfl_xor_sync(~0u, a[i], 16); }
            const uint32_t red = sb + SM_BAR + 1024;
            bar_sync(NB_M, 256);
            if (lane < 8) {
                sts128(red + warp * 256 + lane * 32, make_uint4(__float_as_uint(a[0]), __float_as_uint(a[1]), __float_as_uint(a[2]), __float_as_uint(a[3])));
                sts128(red + warp * 256 + lane * 32 + 16, make_uint4(__float_as_uint(a[4]), __float_as_uint(a[5]), __float_as_uint(a[6]), __float_as_uint(a[7])));
            }
            bar_sync(NB_M, 256);
            if (wl == 0) {
                const uint32_t ra = red + (wg * 32 + lane) * 4;
                float v = 0.f;
#pragma unroll
                for (int i = 0; i < 8; i++) v += lds32f(ra + i * 256);
                g_mod[col + wg * 32 + lane] = __float2bfloat16_rn(v);
            }
            mbar_wait(bars + B_STGFREE + wg * 8, stg_phase); stg_phase ^= 1;
            CTR(4); CTR(5);
            bar_arrive(NB_ST + wg, 160);
            continue;
        }
        if (type == J_LN || type == J_LN1) {
            __syncwarp();
            if (lane == 0) mbar_arrive(bars + B_EMPTY + pp.stage * 8);
            pipe_next(pp);
            if (type == J_LN1) {
                const int row = rb * 128 + cb * 16 + warp * 2;
                const uint4* xr = (const uint4*)(p.x + (size_t)row * D_);
                const uint4 xa[4] = {__ldg(xr + lane), __ldg(xr + 32 + lane), __ldg(xr + 64 + lane), __ldg(xr + 96 + lane)};
                uint32_t c1[8], sm[8], mu2[2];
                float rden[2];
#pragma unroll
                for (int rr = 0; rr < 2; rr++) {
                    const uint32_t v[8] = {xa[2 * rr].x, xa[2 * rr].y, xa[2 * rr].z, xa[2 * rr].w, xa[2 * rr + 1].x, xa[2 * rr + 1].y, xa[2 * rr + 1].z, xa[2 * rr + 1].w};
                    ln_stats(v, mu2[rr], rden[rr]);
                }
                if (lane == 0) wait_flag(F_MOD, 32);
                __syncwarp();
                load_mod8(g_mod + D_, lane, c1);
                load_mod8(g_mod, lane, sm);
#pragma unroll
                for (int i = 0; i < 8; i++) c1[i] = hadd2(c1[i], 0x3F803F80u);
#pragma unroll
                for (int rr = 0; rr < 2; rr++) {
                    const uint32_t v[8] = {xa[2 * rr].x, xa[2 * rr].y, xa[2 * rr].z, xa[2 * rr].w, xa[2 * rr + 1].x, xa[2 * rr + 1].y, xa[2 * rr + 1].z, xa[2 * rr + 1].w};
                    uint32_t r[8];
                    ln_apply(v, mu2[rr], rden[rr], c1, sm, r);
                    uint4* hr = (uint4*)(g_h + (size_t)(row + rr) * D_);
                    hr[lane] = make_uint4(r[0], r[1], r[2], r[3]); hr[32 + lane] = make_uint4(r[4], r[5], r[6], r[7]);
                }
            } else if (rb >= FINE_RB) ln2_row<OSPLIT2>(p, rb, cb * 8 + warp, lane);
            else {
#pragma unroll 1
                for (int rr = 0; rr < 2; rr++) ln2_row<OSPLIT>(p, rb, cb * 16 + warp * 2 + rr, lane);
            }
            mbar_wait(bars + B_STGFREE + wg * 8, stg_phase); stg_phase ^= 1;
            CTR(4); CTR(5);
            bar_arrive(NB_ST + wg, 160);
            continue;
        }
        if (type == J_DN || type == J_UP2) {
            float acc[64];
#pragma unroll
            for (int i = 0; i < 64; i++) acc[i] = 0.f;
            if (type == J_DN) {
#pragma unroll 1
                for (int kb = 0; kb < 14; kb++) {
                    if (kb) mbar_wait(bars + B_FULL + pp.stage * 8, pp.phase);
                    const uint32_t st = sb + pp.stage * W_STAGE;
                    const uint64_t da = mkdesc(st + wg * 8192, 16, 1024), db = mkdesc(st + 32768, 8192, 1024);
                    wg_fence();
#pragma unroll
                    for (int ks = 0; ks < 8; ks++) wgmma_n64(acc, da + (ks >> 2) * 1024 + (ks & 3) * 2, db + ks * 128);
                    wg_commit();
                    wg_wait0();
                    if (lane == 0) mbar_arrive(bars + B_EMPTY + pp.stage * 8);
                    pipe_next(pp);
                }
            } else {
#pragma unroll 1
                for (int kb = 0; kb < 8; kb++) {
                    if (kb) mbar_wait(bars + B_FULL + pp.stage * 8, pp.phase);
                    const uint32_t st = sb + pp.stage * W_STAGE;
                    const uint64_t da = mkdesc(st + wg * 8192, 16, 1024), db = mkdesc(st + 16384, 8192, 1024);
                    wg_fence();
#pragma unroll
                    for (int ks = 0; ks < 4; ks++) wgmma_n128(acc, da + ks * 2, db + ks * 128, 1);
                    wg_commit();
                    wg_wait0();
                    if (lane == 0) mbar_arrive(bars + B_EMPTY + pp.stage * 8);
                    pipe_next(pp);
                }
            }
            CTR(4);
            if (type == J_UP2) {
                mbar_wait(bars + B_STGFREE + wg * 8, stg_phase); stg_phase ^= 1;
#pragma unroll
                for (int j = 0; j < 4; j++) {
                    uint32_t r[4];
#pragma unroll
                    for (int q = 0; q < 4; q++) {
                        const uint32_t gw = pack2(acc[8 * j + 2 * q], acc[8 * j + 2 * q + 1]);
                        const uint32_t uw = pack2(acc[32 + 8 * j + 2 * q], acc[32 + 8 * j + 2 * q + 1]);
                        r[q] = hmul2(pack2(gelu_tanh(bflo(gw)), gelu_tanh(bfhi(gw))), uw);
                    }
                    stsm4(stg_base + (sx ^ (j << 5)), r[0], r[1], r[2], r[3]);
                }
            } else {
                mbar_wait(bars + B_FULL + pp.stage * 8, pp.phase);
                const uint32_t st = sb + pp.stage * W_STAGE;
                mbar_wait(bars + B_STGFREE + wg * 8, stg_phase); stg_phase ^= 1;
                const uint32_t* gb = (const uint32_t*)(g_mod + 5 * D_ + cb * 64) + t;
                const uint32_t xa = st + wg * 8192 + (wl * 16 + g) * 128 + (g << 4) + t * 4;
#pragma unroll
                for (int j = 0; j < 4; j++) {
                    uint32_t r[4];
#pragma unroll
                    for (int q = 0; q < 4; q++) {
                        const int nt = 2 * j + (q >> 1);
                        const uint32_t xw = lds32((xa ^ ((nt & 7) << 4)) + (nt >> 3) * 16384 + (q & 1) * 1024);
                        r[q] = hadd2(xw, hmul2(__ldcg(gb + nt * 4), pack2(acc[8 * j + 2 * q], acc[8 * j + 2 * q + 1])));
                    }
                    stsm4(stg_base + (j >> 2) * 8192 + (sx ^ ((2 * j & 7) << 4)), r[0], r[1], r[2], r[3]);
                }
                __syncwarp();
                if (lane == 0) mbar_arrive(bars + B_EMPTY + pp.stage * 8);
                pipe_next(pp);
            }
            fence_async_smem();
            CTR(5);
            bar_arrive(NB_ST + wg, 160);
            continue;
        }
        float acc[128];
#pragma unroll
        for (int i = 0; i < 128; i++) acc[i] = 0.f;
        const int nk = type == J_O ? (rb >= FINE_RB ? 64 / OSPLIT2 : 64 / OSPLIT) : 8;
#pragma unroll 1
        for (int kb = 0; kb < nk; kb++) {
            if (kb) mbar_wait(bars + B_FULL + pp.stage * 8, pp.phase);
            const uint32_t st = sb + pp.stage * W_STAGE;
            const uint64_t da = mkdesc(st + wg * 8192, 16, 1024), db = mkdesc(st + 16384, 8192, 1024);
            wg_fence();
#pragma unroll
            for (int ks = 0; ks < 4; ks++) wgmma_n256(acc, da + ks * 2, db + ks * 128, 1);
            wg_commit();
            wg_wait0();
            if (lane == 0) mbar_arrive(bars + B_EMPTY + pp.stage * 8);
            pipe_next(pp);
        }
        CTR(4);
        if (type == J_QA) {
            uint32_t qf[64];
#pragma unroll
            for (int i = 0; i < 64; i++) qf[i] = pack2(acc[2 * i], acc[2 * i + 1]);
            const int sg = warp >> 1, half = warp & 1;
            const float sc = 0.08838834764831845f * 1.4426950408889634f;
            const uint32_t xoff = (sg >> 1) * 8192 + ((sg & 1) * 32 + l7) * 128;
            const uint32_t moff = 32768 + (sg * 8 + l7) * 128;
            const uint32_t kch = (l8 ^ l7) << 4;
            const uint32_t vch = ((l8 & 1) ^ l7) << 4;
#pragma unroll 1
            for (int hh = 0; hh < 2; hh++) {
                mbar_wait(bars + B_FULL + pp.stage * 8, pp.phase);
                uint32_t st = sb + pp.stage * W_STAGE;
                float sa[5][4];
#pragma unroll
                for (int n = 0; n < 5; n++) sa[n][0] = sa[n][1] = sa[n][2] = sa[n][3] = 0.f;
#pragma unroll
                for (int i = 0; i < 4; i++) {
                    const uint32_t* q = qf + i * 8;
                    uint32_t kk[5][4];
                    ldsm4(kk[0][0], kk[0][1], kk[0][2], kk[0][3], st + moff + (i >> 1) * 4096 + (kch ^ ((i & 1) * 64)));
#pragma unroll
                    for (int n = 1; n < 5; n++)
                        ldsm4(kk[n][0], kk[n][1], kk[n][2], kk[n][3], st + xoff + (n - 1) * 1024 + (i >> 1) * 16384 + (kch ^ ((i & 1) * 64)));
#pragma unroll
                    for (int n = 0; n < 5; n++) mma16816(sa[n], q[0], q[1], q[2], q[3], kk[n][0], kk[n][1]);
#pragma unroll
                    for (int n = 0; n < 5; n++) mma16816(sa[n], q[4], q[5], q[6], q[7], kk[n][2], kk[n][3]);
                }
                __syncwarp();
                if (lane == 0) mbar_arrive(bars + B_EMPTY + pp.stage * 8);
                pipe_next(pp);
                const int iq0 = half * 16 + g - 2 * t, iq1 = iq0 + 8;
                float m0 = fmaxf(sa[0][0], sa[0][1]), m1 = fmaxf(sa[0][2], sa[0][3]);
#pragma unroll
                for (int n = 1; n < 5; n++) {
#pragma unroll
                    for (int e = 0; e < 2; e++) {
                        const int jx = (n - 1) * 8 + e;
                        if (jx > iq0) sa[n][e] = -3.0e38f;
                        if (jx > iq1) sa[n][2 + e] = -3.0e38f;
                        m0 = fmaxf(m0, sa[n][e]); m1 = fmaxf(m1, sa[n][2 + e]);
                    }
                }
                m0 = fmaxf(m0, __shfl_xor_sync(~0u, m0, 1)); m1 = fmaxf(m1, __shfl_xor_sync(~0u, m1, 1));
                m0 = fmaxf(m0, __shfl_xor_sync(~0u, m0, 2)); m1 = fmaxf(m1, __shfl_xor_sync(~0u, m1, 2));
                m0 *= -sc; m1 *= -sc;
                float l0 = 0.f, l1 = 0.f;
                uint32_t p0[5], p1[5];
#pragma unroll
                for (int n = 0; n < 5; n++) {
                    const float e0 = ex2(fmaf(sa[n][0], sc, m0)), e1 = ex2(fmaf(sa[n][1], sc, m0));
                    const float e2 = ex2(fmaf(sa[n][2], sc, m1)), e3 = ex2(fmaf(sa[n][3], sc, m1));
                    l0 += e0 + e1; l1 += e2 + e3;
                    p0[n] = pack2(e0, e1); p1[n] = pack2(e2, e3);
                }
                l0 += __shfl_xor_sync(~0u, l0, 1); l1 += __shfl_xor_sync(~0u, l1, 1);
                l0 += __shfl_xor_sync(~0u, l0, 2); l1 += __shfl_xor_sync(~0u, l1, 2);
                const float i0 = __fdividef(1.f, l0), i1 = __fdividef(1.f, l1);
                mbar_wait(bars + B_FULL + pp.stage * 8, pp.phase);
                st = sb + pp.stage * W_STAGE;
                mbar_wait(bars + B_STGFREE + wg * 8, stg_phase); stg_phase ^= 1;
#pragma unroll
                for (int i = 0; i < 32; i++) qf[i] = qf[32 + i];
#pragma unroll 1
                for (int bx = 0; bx < 2; bx++) {
                    float o[8][4];
                    uint32_t vm[8], v0[4][4], v1[4][4];
#pragma unroll
                    for (int ep = 0; ep < 4; ep++) {
                        ldsm2t(vm[2 * ep], vm[2 * ep + 1], st + moff + bx * 4096 + (vch ^ (ep << 5)));
                        const uint32_t va = st + xoff + (l8 >> 1) * 1024 + bx * 16384 + (vch ^ (ep << 5));
                        ldsm4t(v0[ep][0], v0[ep][1], v0[ep][2], v0[ep][3], va);
                        ldsm4t(v1[ep][0], v1[ep][1], v1[ep][2], v1[ep][3], va + 2048);
                    }
#pragma unroll
                    for (int n = 0; n < 8; n++) { o[n][0] = o[n][1] = o[n][2] = o[n][3] = 0.f; mma16816(o[n], p0[0], p1[0], p0[1], p1[1], vm[n], v0[n >> 1][n & 1]); }
#pragma unroll
                    for (int n = 0; n < 8; n++) mma16816(o[n], p0[2], p1[2], p0[3], p1[3], v0[n >> 1][2 + (n & 1)], v1[n >> 1][n & 1]);
#pragma unroll
                    for (int n = 0; n < 8; n++) mma1688(o[n], p0[4], p1[4], v1[n >> 1][2 + (n & 1)]);
#pragma unroll
                    for (int ep = 0; ep < 4; ep++)
                        stsm4(stg_base + bx * 8192 + (sx ^ (ep << 5)),
                              pack2(o[2 * ep][0] * i0, o[2 * ep][1] * i0), pack2(o[2 * ep][2] * i1, o[2 * ep][3] * i1),
                              pack2(o[2 * ep + 1][0] * i0, o[2 * ep + 1][1] * i0), pack2(o[2 * ep + 1][2] * i1, o[2 * ep + 1][3] * i1));
                }
                __syncwarp();
                if (lane == 0) mbar_arrive(bars + B_EMPTY + pp.stage * 8);
                pipe_next(pp);
                if (hh == 0) { fence_async_smem(); bar_arrive(NB_ST + wg, 160); }
            }
        } else if (type == J_UP) {
            mbar_wait(bars + B_STGFREE + wg * 8, stg_phase); stg_phase ^= 1;
#pragma unroll
            for (int j = 0; j < 8; j++) {
                uint32_t r[4];
#pragma unroll
                for (int q = 0; q < 4; q++) {
                    const uint32_t gw = pack2(acc[8 * j + 2 * q], acc[8 * j + 2 * q + 1]);
                    const uint32_t uw = pack2(acc[64 + 8 * j + 2 * q], acc[64 + 8 * j + 2 * q + 1]);
                    r[q] = hmul2(pack2(gelu_tanh(bflo(gw)), gelu_tanh(bfhi(gw))), uw);
                }
                stsm4(stg_base + (j >> 2) * 8192 + (sx ^ ((2 * j & 7) << 4)), r[0], r[1], r[2], r[3]);
            }
        } else {
#pragma unroll
            for (int rd = 0; rd < 2; rd++) {
                mbar_wait(bars + B_STGFREE + wg * 8, stg_phase); stg_phase ^= 1;
#pragma unroll
                for (int j = rd * 8; j < rd * 8 + 8; j++)
                    stsm4(stg_base + ((j >> 2) & 1) * 8192 + (sx ^ ((2 * j & 7) << 4)),
                          pack2(acc[8 * j], acc[8 * j + 1]), pack2(acc[8 * j + 2], acc[8 * j + 3]),
                          pack2(acc[8 * j + 4], acc[8 * j + 5]), pack2(acc[8 * j + 6], acc[8 * j + 7]));
                if (rd == 0) { fence_async_smem(); bar_arrive(NB_ST + wg, 160); }
            }
        }
        fence_async_smem();
        CTR(5);
        bar_arrive(NB_ST + wg, 160);
    }
}

__global__ void __launch_bounds__(384, 1) k_work(const __grid_constant__ Params p) {
    extern __shared__ __align__(1024) unsigned char smem_raw[];
    const uint32_t sb = smem_u32(smem_raw);
    if (sb & 1023) __trap();
    const int warp = __shfl_sync(~0u, threadIdx.x >> 5, 0);
    int lane; asm volatile("mov.u32 %0, %%laneid;" : "=r"(lane));
    if (threadIdx.x == 0) {
        const uint32_t bars = sb + SM_BAR;
        for (int i = 0; i < W_NST; i++) { mbar_init(bars + B_FULL + i * 8, 1); mbar_init(bars + B_EMPTY + i * 8, 8); }
        mbar_init(bars + B_STGFREE, 1); mbar_init(bars + B_STGFREE + 8, 1); mbar_init(bars + B_REQ, 1); mbar_init(bars + B_RSP, 1);
        asm volatile("fence.mbarrier_init.release.cluster;" ::: "memory");
    }
    __syncthreads();
    if (warp < 8) {
        asm volatile("setmaxnreg.inc.sync.aligned.u32 224;");
        consumer(p, sb, warp, lane);
    } else {
        asm volatile("setmaxnreg.dec.sync.aligned.u32 56;");
        if (warp == 8) { if (lane == 0) producer(p, sb); }
        else if (warp < 11) store_warp(p, sb, warp - 9, lane);
        else scheduler(p, sb, lane);
        __syncwarp();
        bar_sync(NB_W0, 128);
        if (warp == 8 && p.qmask == 0xff) {
            unsigned last = 0;
            if (lane == 0) { __threadfence(); last = atomicAdd(&g_flags[F_DONE], 1u) == gridDim.x - 1; }
            if (__shfl_sync(~0u, last, 0))
                for (int i = lane; i < F_TOTAL; i += 32) g_flags[i] = 0;
        }
    }
}

typedef CUresult (*EncodeFn)(CUtensorMap*, CUtensorMapDataType, cuuint32_t, void*, const cuuint64_t*, const cuuint64_t*,
                             const cuuint32_t*, const cuuint32_t*, CUtensorMapInterleave, CUtensorMapSwizzle,
                             CUtensorMapL2promotion, CUtensorMapFloatOOBfill);

static void make_map(EncodeFn enc, CUtensorMap* m, const void* ptr, uint64_t rows, uint64_t cols, uint32_t box_rows) {
    cuuint64_t dims[2] = {cols, rows};
    cuuint64_t strides[1] = {cols * 2};
    cuuint32_t box[2] = {64, box_rows};
    cuuint32_t es[2] = {1, 1};
    enc(m, CU_TENSOR_MAP_DATA_TYPE_BFLOAT16, 2, const_cast<void*>(ptr), dims, strides, box, es, CU_TENSOR_MAP_INTERLEAVE_NONE,
        CU_TENSOR_MAP_SWIZZLE_128B, CU_TENSOR_MAP_L2_PROMOTION_L2_256B, CU_TENSOR_MAP_FLOAT_OOB_FILL_NONE);
}
template <typename T> static void* sym_addr(T& sym) { void* p = nullptr; cudaGetSymbolAddress(&p, sym); return p; }

extern "C" void kernel_launch(void* const* d_in, const int* in_sizes, int n_in, void* d_out, int out_size) {
    static Params prm;
    static RecParams rp;
    static bool ready = false;
    static const void* key[14];
    bool same = ready;
    for (int i = 0; i < 13 && same; i++) same = key[i] == d_in[i];
    same = same && key[13] == d_out;
    if (!same) {
        void* fn = nullptr;
        cudaDriverEntryPointQueryResult qr;
        cudaGetDriverEntryPoint("cuTensorMapEncodeTiled", &fn, cudaEnableDefault, &qr);
        EncodeFn enc = (EncodeFn)fn;
        make_map(enc, &prm.tm_h, sym_addr(g_h), S_, D_, 64);
        make_map(enc, &prm.tm_kv, sym_addr(g_kv), S_, 2 * HD_, 64);
        make_map(enc, &prm.tm_kvm, sym_addr(g_kvm), NSEG * 8, 2 * HD_, 32);
        make_map(enc, &prm.tm_o, sym_addr(g_o), S_, HD_, 64);
        make_map(enc, &prm.tm_op, sym_addr(g_op), OP_ROWS, D_, 64);
        make_map(enc, &prm.tm_h2, sym_addr(g_h2), S_, D_, 64);
        make_map(enc, &prm.tm_act, sym_addr(g_act), S_, DF_, 64);
        make_map(enc, &prm.tm_x1, sym_addr(g_x1), S_, D_, 64);
        make_map(enc, &prm.tm_out, d_out, S_, D_, 64);
        make_map(enc, &prm.tm_wq, d_in[2], D_, HD_, 64);
        make_map(enc, &prm.tm_wk, d_in[3], D_, HD_, 64);
        make_map(enc, &prm.tm_wv, d_in[4], D_, HD_, 64);
        make_map(enc, &prm.tm_wo, d_in[5], HD_, D_, 64);
        make_map(enc, &prm.tm_wg, d_in[8], D_, DF_, 64);
        make_map(enc, &prm.tm_wu, d_in[9], D_, DF_, 64);
        make_map(enc, &prm.tm_wd, d_in[10], DF_, D_, 64);
        prm.x = (const bf16*)d_in[0]; prm.c = (const bf16*)d_in[11]; prm.w_mod = (const bf16*)d_in[12];
        rp.mem0 = (const bf16*)d_in[1];
        rp.wq = (const bf16*)d_in[2]; rp.wk = (const bf16*)d_in[3]; rp.wv = (const bf16*)d_in[4]; rp.wo = (const bf16*)d_in[5];
        cudaFuncSetAttribute(k_work, cudaFuncAttributeMaxDynamicSharedMemorySize, SMEM_BYTES);
        cudaFuncSetAttribute(k_rec, cudaFuncAttributeMaxDynamicSharedMemorySize, R_SMEM);
        cudaFuncSetAttribute(k_rec, cudaFuncAttributeNonPortableClusterSizeAllowed, 1);
        {
            cudaLaunchConfig_t cfg = {};
            cfg.gridDim = dim3(128); cfg.blockDim = dim3(384); cfg.dynamicSmemBytes = R_SMEM;
            cudaLaunchAttribute at[1];
            at[0].id = cudaLaunchAttributeClusterDimension; at[0].val.clusterDim.x = 16; at[0].val.clusterDim.y = 1; at[0].val.clusterDim.z = 1;
            cfg.attrs = at; cfg.numAttrs = 1;
            int n = 0;
            cudaOccupancyMaxActiveClusters(&n, k_rec, &cfg);
            rp.ncl = n < 4 ? 4 : (n > 8 ? 8 : n);
        }
        for (int i = 0; i < 13; i++) key[i] = d_in[i];
        key[13] = d_out;
        ready = true;
    }
    cudaStream_t st = cudaStreamPerThread;
    auto launch_rec = [&]() {
        cudaLaunchConfig_t cfg = {};
        cfg.gridDim = dim3(16 * rp.ncl); cfg.blockDim = dim3(384); cfg.dynamicSmemBytes = R_SMEM; cfg.stream = st;
        cudaLaunchAttribute at[1];
        at[0].id = cudaLaunchAttributeClusterDimension; at[0].val.clusterDim.x = 16; at[0].val.clusterDim.y = 1; at[0].val.clusterDim.z = 1;
        cfg.attrs = at; cfg.numAttrs = 1;
        cudaLaunchKernelEx(&cfg, k_rec, rp);
    };
    auto launch_work = [&](int qmask, int pdl) {
        prm.qmask = qmask;
        cudaLaunchConfig_t cfg = {};
        cfg.gridDim = dim3(132); cfg.blockDim = dim3(384); cfg.dynamicSmemBytes = SMEM_BYTES; cfg.stream = st;
        cudaLaunchAttribute at[1];
        at[0].id = cudaLaunchAttributeProgrammaticStreamSerialization; at[0].val.programmaticStreamSerializationAllowed = 1;
        cfg.attrs = at; cfg.numAttrs = pdl;
        cudaLaunchKernelEx(&cfg, k_work, prm);
    };
    launch_rec();
    launch_work(0xff, 1);
}
```

```cpp
#include <cuda_runtime.h>
#include <cuda_bf16.h>
#include <cuda.h>
#include <stdint.h>

typedef __nv_bfloat16 bf16;
#define IDLE_NS 150
#define FLAG_NS 20

constexpr int S_ = 2048, D_ = 512, H_ = 32, DH_ = 128, HD_ = 4096, NSEG = 64, DF_ = 1792;
constexpr int NRB = 16;
constexpr int OSPLIT = 4;

__device__ __align__(1024) bf16 g_h[S_ * D_];
__device__ __align__(1024) bf16 g_kv[S_ * 2 * HD_];
__device__ __align__(1024) bf16 g_kvm[NSEG * 8 * 2 * HD_];
__device__ __align__(1024) bf16 g_o[S_ * HD_];
#define FINE_RB_ 12
constexpr int FINE_RB = FINE_RB_;
#define OSPLIT2_ 8
constexpr int OSPLIT2 = OSPLIT2_;
constexpr int OP_ROWS = OSPLIT * S_ + OSPLIT2 * (NRB - FINE_RB) * 128;
__device__ __align__(1024) bf16 g_op[OP_ROWS * D_];
__device__ __align__(1024) bf16 g_x1[S_ * D_];
__device__ __align__(1024) bf16 g_h2[S_ * D_];
__device__ __align__(1024) bf16 g_act[S_ * DF_];
__device__ __align__(1024) bf16 g_mod[6 * D_];
__device__ uint32_t g_Fraw[131072 + 65536 + 2048];
#define g_F ((uint32_t*)(((uint64_t)g_Fraw + 0x7FFFFull) & ~0x7FFFFull))
constexpr int F_H = 0, F_MEM = 32, F_O = 64, F_OP = 96, F_H2 = 128, F_ACT = 160, F_MOD = 192, F_KV = 224, F_CLAIM = 256  ,
              F_SIDE = 512  , F_DONE = 576, F_TOTAL = 608;
__device__ __align__(128) unsigned int g_flags[F_TOTAL];
#define TR(j, i) do {} while (0)

__device__ __forceinline__ uint32_t smem_u32(const void* p) { return (uint32_t)__cvta_generic_to_shared(p); }
__device__ __forceinline__ uint32_t clk32() { uint32_t c; asm volatile("mov.u32 %0, %%clock;" : "=r"(c)); return c; }
__device__ __forceinline__ uint32_t mapa_u32(uint32_t addr, uint32_t rank) {
    uint32_t r; asm volatile("mapa.shared::cluster.u32 %0, %1, %2;" : "=r"(r) : "r"(addr), "r"(rank)); return r;
}
__device__ __forceinline__ void mbar_init(uint32_t bar, uint32_t cnt) {
    asm volatile("mbarrier.init.shared::cta.b64 [%0], %1;" :: "r"(bar), "r"(cnt) : "memory");
}
__device__ __forceinline__ void mbar_inval(uint32_t bar) {
    asm volatile("mbarrier.inval.shared::cta.b64 [%0];" :: "r"(bar) : "memory");
}
__device__ __forceinline__ void mbar_expect_tx(uint32_t bar, uint32_t bytes) {
    asm volatile("mbarrier.arrive.expect_tx.shared::cta.b64 _, [%0], %1;" :: "r"(bar), "r"(bytes) : "memory");
}
__device__ __forceinline__ void mbar_arrive(uint32_t bar) {
    asm volatile("mbarrier.arrive.shared::cta.b64 _, [%0];" :: "r"(bar) : "memory");
}
__device__ __forceinline__ bool mbar_try_wait(uint32_t bar, uint32_t parity) {
    uint32_t ok;
    asm volatile("{\n.reg .pred p;\nmbarrier.try_wait.parity.shared::cta.b64 p, [%1], %2;\nselp.u32 %0, 1, 0, p;\n}"
                 : "=r"(ok) : "r"(bar), "r"(parity) : "memory");
    return ok;
}
__device__ __forceinline__ bool mbar_try_wait_cluster(uint32_t bar, uint32_t parity) {
    uint32_t ok;
    asm volatile("{\n.reg .pred p;\nmbarrier.try_wait.parity.acquire.cluster.shared::cta.b64 p, [%1], %2;\nselp.u32 %0, 1, 0, p;\n}"
                 : "=r"(ok) : "r"(bar), "r"(parity) : "memory");
    return ok;
}
constexpr int SPIN_LIMIT = 1 << 18;
#define TIMEOUT(code, info) do {} while (0)
__device__ __forceinline__ void mbar_wait(uint32_t bar, uint32_t parity) {
    int g = 0;
#pragma unroll 1
    while (!mbar_try_wait(bar, parity)) { if (++g >= SPIN_LIMIT) { TIMEOUT(0, bar & 255); break; } }
}
__device__ __forceinline__ void mbar_wait_cluster(uint32_t bar, uint32_t parity) {
    int g = 0;
#pragma unroll 1
    while (!mbar_try_wait_cluster(bar, parity)) { if (++g >= SPIN_LIMIT) { TIMEOUT(1, bar & 255); break; } }
}
__device__ __forceinline__ void bar_sync(int id, int n) { asm volatile("bar.sync %0, %1;" :: "r"(id), "r"(n) : "memory"); }
__device__ __forceinline__ void bar_arrive(int id, int n) { asm volatile("bar.arrive %0, %1;" :: "r"(id), "r"(n) : "memory"); }
__device__ __forceinline__ void cluster_sync_all() {
    asm volatile("barrier.cluster.arrive.aligned;\nbarrier.cluster.wait.aligned;" ::: "memory");
}
__device__ __forceinline__ void st_async_v2(uint32_t addr, float a, float b, uint32_t bar) {
    asm volatile("st.async.weak.shared::cluster.mbarrier::complete_tx::bytes.v2.f32 [%0], {%1,%2}, [%3];"
                 :: "r"(addr), "f"(a), "f"(b), "r"(bar) : "memory");
}
__device__ __forceinline__ void st_async_v4(uint32_t addr, uint4 v, uint32_t bar) {
    asm volatile("st.async.weak.shared::cluster.mbarrier::complete_tx::bytes.v4.b32 [%0], {%1,%2,%3,%4}, [%5];"
                 :: "r"(addr), "r"(v.x), "r"(v.y), "r"(v.z), "r"(v.w), "r"(bar) : "memory");
}
__device__ __forceinline__ uint2 ldg_relaxed2(const uint2* p) {
    uint2 v;
    asm volatile("ld.relaxed.gpu.global.v2.b32 {%0,%1}, [%2];" : "=r"(v.x), "=r"(v.y) : "l"(p) : "memory");
    return v;
}
__device__ __forceinline__ void stg_relaxed2(uint2* p, uint2 v) {
    asm volatile("st.relaxed.gpu.global.v2.b32 [%0], {%1,%2};" :: "l"(p), "r"(v.x), "r"(v.y) : "memory");
}
__device__ __forceinline__ uint4 ldg_relaxed(const uint4* p) {
    uint4 v;
    asm volatile("ld.relaxed.gpu.global.v4.b32 {%0,%1,%2,%3}, [%4];" : "=r"(v.x), "=r"(v.y), "=r"(v.z), "=r"(v.w) : "l"(p) : "memory");
    return v;
}
__device__ __forceinline__ void stg_relaxed(uint4* p, uint4 v) {
    asm volatile("st.relaxed.gpu.global.v4.b32 [%0], {%1,%2,%3,%4};" :: "l"(p), "r"(v.x), "r"(v.y), "r"(v.z), "r"(v.w) : "memory");
}
__device__ __forceinline__ void stg_relaxed32(uint32_t* p, uint32_t v) {
    asm volatile("st.relaxed.gpu.global.b32 [%0], %1;" :: "l"(p), "r"(v) : "memory");
}
__device__ __forceinline__ uint32_t ldg_relaxed32(const uint32_t* p) {
    uint32_t v; asm volatile("ld.relaxed.gpu.global.b32 %0, [%1];" : "=r"(v) : "l"(p) : "memory"); return v;
}
__device__ __forceinline__ unsigned int ld_acquire(const unsigned int* p) {
    unsigned int v; asm volatile("ld.acquire.gpu.global.u32 %0, [%1];" : "=r"(v) : "l"(p) : "memory"); return v;
}
__device__ __forceinline__ void red_release(unsigned int* p, unsigned int v) {
    asm volatile("red.release.gpu.global.add.u32 [%0], %1;" :: "l"(p), "r"(v) : "memory");
}
__device__ __forceinline__ void wait_flag(int idx, unsigned int target) {
    const unsigned int* p = &g_flags[idx];
    int g = 0;
#pragma unroll 1
    while (ld_acquire(p) < target) { __nanosleep(FLAG_NS); if (++g >= 64 * SPIN_LIMIT) { TIMEOUT(2, idx); break; } }
}
__device__ __forceinline__ void cp_async16(uint32_t dst, const void* src) {
    asm volatile("cp.async.cg.shared.global [%0], [%1], 16;" :: "r"(dst), "l"(src) : "memory");
}
__device__ __forceinline__ void cp_async_commit() { asm volatile("cp.async.commit_group;" ::: "memory"); }
template <int N> __device__ __forceinline__ void cp_async_wait() { asm volatile("cp.async.wait_group %0;" :: "n"(N) : "memory"); }
__device__ __forceinline__ void ldsm4(uint32_t& r0, uint32_t& r1, uint32_t& r2, uint32_t& r3, uint32_t addr) {
    asm volatile("ldmatrix.sync.aligned.m8n8.x4.shared.b16 {%0,%1,%2,%3}, [%4];" : "=r"(r0), "=r"(r1), "=r"(r2), "=r"(r3) : "r"(addr) : "memory");
}
__device__ __forceinline__ void ldsm4t(uint32_t& r0, uint32_t& r1, uint32_t& r2, uint32_t& r3, uint32_t addr) {
    asm volatile("ldmatrix.sync.aligned.m8n8.x4.trans.shared.b16 {%0,%1,%2,%3}, [%4];" : "=r"(r0), "=r"(r1), "=r"(r2), "=r"(r3) : "r"(addr) : "memory");
}
__device__ __forceinline__ void ldsm2t(uint32_t& r0, uint32_t& r1, uint32_t addr) {
    asm volatile("ldmatrix.sync.aligned.m8n8.x2.trans.shared.b16 {%0,%1}, [%2];" : "=r"(r0), "=r"(r1) : "r"(addr) : "memory");
}
__device__ __forceinline__ void stsm4(uint32_t addr, uint32_t r0, uint32_t r1, uint32_t r2, uint32_t r3) {
    asm volatile("stmatrix.sync.aligned.m8n8.x4.shared.b16 [%0], {%1,%2,%3,%4};" :: "r"(addr), "r"(r0), "r"(r1), "r"(r2), "r"(r3) : "memory");
}
__device__ __forceinline__ void stsm2t(uint32_t addr, uint32_t r0, uint32_t r1) {
    asm volatile("stmatrix.sync.aligned.m8n8.x2.trans.shared.b16 [%0], {%1,%2};" :: "r"(addr), "r"(r0), "r"(r1) : "memory");
}
__device__ __forceinline__ void mma16816(float* d, uint32_t a0, uint32_t a1, uint32_t a2, uint32_t a3, uint32_t b0, uint32_t b1) {
    asm volatile("mma.sync.aligned.m16n8k16.row.col.f32.bf16.bf16.f32 {%0,%1,%2,%3}, {%4,%5,%6,%7}, {%8,%9}, {%0,%1,%2,%3};"
                 : "+f"(d[0]), "+f"(d[1]), "+f"(d[2]), "+f"(d[3]) : "r"(a0), "r"(a1), "r"(a2), "r"(a3), "r"(b0), "r"(b1));
}
__device__ __forceinline__ void mma1688(float* d, uint32_t a0, uint32_t a1, uint32_t b0) {
    asm volatile("mma.sync.aligned.m16n8k8.row.col.f32.bf16.bf16.f32 {%0,%1,%2,%3}, {%4,%5}, {%6}, {%0,%1,%2,%3};"
                 : "+f"(d[0]), "+f"(d[1]), "+f"(d[2]), "+f"(d[3]) : "r"(a0), "r"(a1), "r"(b0));
}
__device__ __forceinline__ void mma16816h(float* d, uint32_t a0, uint32_t a2, uint32_t b0, uint32_t b1) {
    asm volatile("{\n.reg .b32 ju, jv;\nmma.sync.aligned.m16n8k16.row.col.f32.bf16.bf16.f32 {%0,%1,%2,%3}, {%4,ju,%5,jv}, {%6,%7}, {%0,%1,%2,%3};\n}"
                 : "+f"(d[0]), "+f"(d[1]), "+f"(d[2]), "+f"(d[3]) : "r"(a0), "r"(a2), "r"(b0), "r"(b1));
}
__device__ __forceinline__ void mma1688h(float* d, uint32_t a0, uint32_t b0) {
    asm volatile("{\n.reg .b32 ju;\nmma.sync.aligned.m16n8k8.row.col.f32.bf16.bf16.f32 {%0,%1,%2,%3}, {%4,ju}, {%5}, {%0,%1,%2,%3};\n}"
                 : "+f"(d[0]), "+f"(d[1]), "+f"(d[2]), "+f"(d[3]) : "r"(a0), "r"(b0));
}
__device__ __forceinline__ uint32_t pack2(float lo, float hi) {
    uint32_t r; asm("cvt.rn.bf16x2.f32 %0, %1, %2;" : "=r"(r) : "f"(hi), "f"(lo)); return r;
}
__device__ __forceinline__ float bflo(uint32_t w) { return __uint_as_float(w << 16); }
__device__ __forceinline__ float bfhi(uint32_t w) { return __uint_as_float(w & 0xffff0000u); }
__device__ __forceinline__ float rbf(float x) { return __bfloat162float(__float2bfloat16_rn(x)); }
__device__ __forceinline__ float ex2(float x) { float y; asm("ex2.approx.ftz.f32 %0, %1;" : "=f"(y) : "f"(x)); return y; }
__device__ __forceinline__ void sts128(uint32_t addr, uint4 v) {
    asm volatile("st.shared.v4.b32 [%0], {%1,%2,%3,%4};" :: "r"(addr), "r"(v.x), "r"(v.y), "r"(v.z), "r"(v.w) : "memory");
}
__device__ __forceinline__ uint4 lds128(uint32_t addr) {
    uint4 v; asm volatile("ld.shared.v4.b32 {%0,%1,%2,%3}, [%4];" : "=r"(v.x), "=r"(v.y), "=r"(v.z), "=r"(v.w) : "r"(addr) : "memory"); return v;
}
__device__ __forceinline__ float2 lds64f(uint32_t addr) {
    float2 v; asm volatile("ld.shared.v2.f32 {%0,%1}, [%2];" : "=f"(v.x), "=f"(v.y) : "r"(addr) : "memory"); return v;
}
__device__ __forceinline__ float lds32f(uint32_t addr) {
    float v; asm volatile("ld.shared.f32 %0, [%1];" : "=f"(v) : "r"(addr) : "memory"); return v;
}
__device__ __forceinline__ uint32_t lds32(uint32_t addr) {
    uint32_t v; asm volatile("ld.shared.b32 %0, [%1];" : "=r"(v) : "r"(addr) : "memory"); return v;
}
__device__ __forceinline__ void sts32(uint32_t addr, uint32_t v) { asm volatile("st.shared.b32 [%0], %1;" :: "r"(addr), "r"(v) : "memory"); }
__device__ __forceinline__ void sts64f(uint32_t addr, float a, float b) { asm volatile("st.shared.v2.f32 [%0], {%1,%2};" :: "r"(addr), "f"(a), "f"(b) : "memory"); }

__device__ __forceinline__ void tma_load2d(uint32_t dst, const CUtensorMap* tm, int c0, int c1, uint32_t bar) {
    asm volatile("cp.async.bulk.tensor.2d.shared::cluster.global.mbarrier::complete_tx::bytes [%0], [%1, {%3, %4}], [%2];"
                 :: "r"(dst), "l"(tm), "r"(bar), "r"(c0), "r"(c1) : "memory");
}
__device__ __forceinline__ void tma_store2d(const CUtensorMap* tm, uint32_t src, int c0, int c1) {
    asm volatile("cp.async.bulk.tensor.2d.global.shared::cta.bulk_group [%0, {%2, %3}], [%1];"
                 :: "l"(tm), "r"(src), "r"(c0), "r"(c1) : "memory");
}
__device__ __forceinline__ void bulk_commit() { asm volatile("cp.async.bulk.commit_group;" ::: "memory"); }
__device__ __forceinline__ void bulk_wait0() { asm volatile("cp.async.bulk.wait_group 0;" ::: "memory"); }
__device__ __forceinline__ void fence_async_smem() { asm volatile("fence.proxy.async.shared::cta;" ::: "memory"); }
__device__ __forceinline__ void fence_async_all() { asm volatile("fence.proxy.async;" ::: "memory"); }

__device__ __forceinline__ void wg_fence() { asm volatile("wgmma.fence.sync.aligned;" ::: "memory"); }
__device__ __forceinline__ void wg_commit() { asm volatile("wgmma.commit_group.sync.aligned;" ::: "memory"); }
__device__ __forceinline__ void wg_wait0() { asm volatile("wgmma.wait_group.sync.aligned 0;" ::: "memory"); }
__device__ __forceinline__ uint64_t mkdesc(uint32_t saddr, uint32_t lbo, uint32_t sbo) {
    return (uint64_t)((saddr & 0x3FFFF) >> 4) | ((uint64_t)(lbo >> 4) << 16) | ((uint64_t)(sbo >> 4) << 32) | (1ull << 62);
}
#define ACC8(i) "+f"(d[i]), "+f"(d[i + 1]), "+f"(d[i + 2]), "+f"(d[i + 3]), "+f"(d[i + 4]), "+f"(d[i + 5]), "+f"(d[i + 6]), "+f"(d[i + 7])
__device__ __forceinline__ void wgmma_n256(float* d, uint64_t da, uint64_t db, int scale_d) {
    asm volatile(
        "{\n.reg .pred p;\nsetp.ne.b32 p, %130, 0;\n"
        "wgmma.mma_async.sync.aligned.m64n256k16.f32.bf16.bf16 "
        "{%0,%1,%2,%3,%4,%5,%6,%7,%8,%9,%10,%11,%12,%13,%14,%15,%16,%17,%18,%19,%20,%21,%22,%23,%24,%25,%26,%27,%28,%29,%30,%31,"
        "%32,%33,%34,%35,%36,%37,%38,%39,%40,%41,%42,%43,%44,%45,%46,%47,%48,%49,%50,%51,%52,%53,%54,%55,%56,%57,%58,%59,%60,%61,%62,%63,"
        "%64,%65,%66,%67,%68,%69,%70,%71,%72,%73,%74,%75,%76,%77,%78,%79,%80,%81,%82,%83,%84,%85,%86,%87,%88,%89,%90,%91,%92,%93,%94,%95,"
        "%96,%97,%98,%99,%100,%101,%102,%103,%104,%105,%106,%107,%108,%109,%110,%111,%112,%113,%114,%115,%116,%117,%118,%119,%120,%121,%122,%123,%124,%125,%126,%127}, "
        "%128, %129, p, 1, 1, 0, 1;\n}"
        : ACC8(0), ACC8(8), ACC8(16), ACC8(24), ACC8(32), ACC8(40), ACC8(48), ACC8(56),
          ACC8(64), ACC8(72), ACC8(80), ACC8(88), ACC8(96), ACC8(104), ACC8(112), ACC8(120)
        : "l"(da), "l"(db), "r"(scale_d));
}
__device__ __forceinline__ void wgmma_n128(float* d, uint64_t da, uint64_t db, int scale_d) {
    asm volatile(
        "{\n.reg .pred p;\nsetp.ne.b32 p, %66, 0;\n"
        "wgmma.mma_async.sync.aligned.m64n128k16.f32.bf16.bf16 "
        "{%0,%1,%2,%3,%4,%5,%6,%7,%8,%9,%10,%11,%12,%13,%14,%15,%16,%17,%18,%19,%20,%21,%22,%23,%24,%25,%26,%27,%28,%29,%30,%31,"
        "%32,%33,%34,%35,%36,%37,%38,%39,%40,%41,%42,%43,%44,%45,%46,%47,%48,%49,%50,%51,%52,%53,%54,%55,%56,%57,%58,%59,%60,%61,%62,%63}, "
        "%64, %65, p, 1, 1, 0, 1;\n}"
        : ACC8(0), ACC8(8), ACC8(16), ACC8(24), ACC8(32), ACC8(40), ACC8(48), ACC8(56)
        : "l"(da), "l"(db), "r"(scale_d));
}

__device__ __forceinline__ void wgmma_n64(float* d, uint64_t da, uint64_t db) {
    asm volatile(
        "wgmma.mma_async.sync.aligned.m64n64k16.f32.bf16.bf16 "
        "{%0,%1,%2,%3,%4,%5,%6,%7,%8,%9,%10,%11,%12,%13,%14,%15,%16,%17,%18,%19,%20,%21,%22,%23,%24,%25,%26,%27,%28,%29,%30,%31}, "
        "%32, %33, 1, 1, 1, 0, 1;"
        : ACC8(0), ACC8(8), ACC8(16), ACC8(24)
        : "l"(da), "l"(db));
}
__device__ __forceinline__ void wgmma_n8_ta(float* d, uint64_t da, uint64_t db, int scale_d) {
    asm volatile(
        "{\n.reg .pred p;\nsetp.ne.b32 p, %6, 0;\n"
        "wgmma.mma_async.sync.aligned.m64n8k16.f32.bf16.bf16 {%0,%1,%2,%3}, %4, %5, p, 1, 1, 1, 0;\n}"
        : "+f"(d[0]), "+f"(d[1]), "+f"(d[2]), "+f"(d[3]) : "l"(da), "l"(db), "r"(scale_d));
}

__device__ __forceinline__ uint32_t hadd2(uint32_t a, uint32_t b) { uint32_t r; asm("add.rn.bf16x2 %0, %1, %2;" : "=r"(r) : "r"(a), "r"(b)); return r; }
__device__ __forceinline__ uint32_t hsub2(uint32_t a, uint32_t b) { uint32_t r; asm("sub.rn.bf16x2 %0, %1, %2;" : "=r"(r) : "r"(a), "r"(b)); return r; }
__device__ __forceinline__ uint32_t hmul2(uint32_t a, uint32_t b) { uint32_t r; asm("mul.rn.bf16x2 %0, %1, %2;" : "=r"(r) : "r"(a), "r"(b)); return r; }
__device__ __forceinline__ void load_mod8(const bf16* m, int lane, uint32_t* v) {
    const uint4 a = __ldcg((const uint4*)m + lane), b = __ldcg((const uint4*)m + 32 + lane);
    v[0] = a.x; v[1] = a.y; v[2] = a.z; v[3] = a.w; v[4] = b.x; v[5] = b.y; v[6] = b.z; v[7] = b.w;
}
__device__ __forceinline__ void ln_stats(const uint32_t* x, uint32_t& mu2, float& rden) {
    float s = 0.f;
#pragma unroll
    for (int i = 0; i < 8; i++) s += bflo(x[i]) + bfhi(x[i]);
#pragma unroll
    for (int o = 16; o > 0; o >>= 1) s += __shfl_xor_sync(~0u, s, o);
    const float mean = s * (1.f / D_);
    float q = 0.f;
#pragma unroll
    for (int i = 0; i < 8; i++) { const float d0 = bflo(x[i]) - mean, d1 = bfhi(x[i]) - mean; q = fmaf(d0, d0, q); q = fmaf(d1, d1, q); }
#pragma unroll
    for (int o = 16; o > 0; o >>= 1) q += __shfl_xor_sync(~0u, q, o);
    mu2 = pack2(mean, mean);
    rden = __frcp_rn(rbf(__fsqrt_rn(rbf(rbf(q * (1.f / D_)) + 1e-5f))));
}
__device__ __forceinline__ void ln_apply(const uint32_t* x, uint32_t mu2, float rden, const uint32_t* c1, const uint32_t* sm, uint32_t* r) {
#pragma unroll
    for (int i = 0; i < 8; i++) {
        const uint32_t d = hsub2(x[i], mu2);
        r[i] = hadd2(hmul2(pack2(bflo(d) * rden, bfhi(d) * rden), c1[i]), sm[i]);
    }
}

struct __align__(64) Params {
    CUtensorMap tm_h, tm_kv, tm_kvm, tm_o, tm_op, tm_h2, tm_act, tm_x1, tm_out;
    CUtensorMap tm_wq, tm_wk, tm_wv, tm_wo, tm_wg, tm_wu, tm_wd;
    const bf16 *x, *c, *w_mod;
    int qmask;
};

constexpr int R_NST = 3;
constexpr uint32_t R_WV = 0, R_MEM = 65536, R_KX = 73728, R_VX = R_KX + R_NST * 4096,
                   R_KMS = R_VX + R_NST * 4096  , R_VMS = R_KMS + 1024,
                   R_QS = R_KMS + 4096, R_OS = R_QS + 1024, R_SX = R_OS + 1024, R_BAR = R_SX + 2560,
                   R_RS = 107520  , R_VP = R_RS + 8192  ,
                   R_STG = R_VP + 8192  , R_SMEM = R_STG + 98304;
static_assert((R_KMS & 4095) == 0, "smem");
static_assert(R_BAR + 64 <= R_RS, "smem");
constexpr uint32_t RB_SX = R_BAR, RB_V = R_BAR + 8, RB_E = R_BAR + 16, RB_A = R_BAR + 24, RB_ROLE = R_BAR + 32, RB_A1 = R_BAR + 40;
constexpr int W_NST = 4;
constexpr uint32_t W_STAGE = 49152, W_STG = W_NST * W_STAGE  , W_END = W_STG + 32768;
constexpr uint32_t SM_BAR = W_END;
constexpr uint32_t SMEM_BYTES = W_END + 1024 + 2048;
constexpr uint32_t B_FULL = 0, B_EMPTY = 32, B_STGFREE = 64, B_REQ = 80, B_RSP = 88, B_NEXT = 96, B_RING = 128;
#define PICK_AHEAD 3

constexpr int NB_X = 11  , NB_Y = 1, NB_M = 5, NB_K = 5, NB_B = 2, NB_C = 3, NB_D = 4, NB_W0 = 6  , NB_ST = 9  ;

__device__ __forceinline__ int pos_of_d(int d) {
    const int rem = d & 31;
    return (d & ~31) + ((rem & 7) >> 1) * 8 + (rem & 1) * 4 + (rem >> 3);
}

#define PROF(i) do {} while (0)
#define PROFG(i) do {} while (0)
#define OPAQUE(x) asm volatile("" : "+r"(x))
#define FENCE_SCHED(x) do { if ((x) == 0u) asm volatile("trap;"); } while (0)
#define VK0_ 4
constexpr int VK0 = VK0_;
constexpr int NOFF = 8;
#define VDELAY -1
#define POLL_GAP 110

struct RecParams { const bf16 *mem0, *wq, *wk, *wv, *wo, *x, *c, *w_mod; int ncl, only_pre; };

__device__ __forceinline__ void rec_qk(const RecParams& p, const uint32_t sb, const int cta, const int warp, int lane, const int sel) {
    const int crank = cta & 15, cl = cta >> 4, rank = cta & 1;
    const int kh = warp >> 2, aa = warp & 3;
    uint32_t wa[2][16][4];
    const uint32_t stg = sb + R_STG + kh * 32768;
    {
        const int t128 = aa * 32 + lane;
        const int row = (lane >> 4) * 8 + (lane & 7);
        const int ch = t128 & 7;
        const size_t goff = (size_t)kh * 256 * HD_ + cta * 64 + ch * 8;
#pragma unroll 4
        for (int dd = 0; dd < 16; dd++) {
            const int d = dd * 16 + (t128 >> 3), pp = pos_of_d(d);
            cp_async16(sb + R_WV + kh * 32768 + pp * 128 + ((ch ^ (pp & 7)) << 4), p.wv + goff + (size_t)d * HD_);
        }
        cp_async_commit();
#pragma unroll 4
        for (int dd = 0; dd < 16; dd++) {
            const int d = dd * 16 + (t128 >> 3), pp = pos_of_d(d);
            cp_async16(stg + pp * 128 + ((ch ^ (pp & 7)) << 4), p.wq + goff + (size_t)d * HD_);
        }
        cp_async_commit();
        {
            const int i0 = (warp * 32 + lane) * 16, tok = i0 >> 9;
            const uint4 m0 = __ldg((const uint4*)(p.mem0 + i0)), m1 = __ldg((const uint4*)(p.mem0 + i0 + 8));
            const uint32_t mw[8] = {m0.x, m0.y, m0.z, m0.w, m1.x, m1.y, m1.z, m1.w};
#pragma unroll
            for (int e = 0; e < 16; e++) {
                const int pp = pos_of_d((i0 & 511) + e);
                const unsigned short v = (unsigned short)(mw[e >> 1] >> ((e & 1) * 16));
                asm volatile("st.shared.u16 [%0], %1;" :: "r"(sb + R_MEM + (pp >> 3) * 128 + tok * 16 + (pp & 7) * 2), "h"(v) : "memory");
            }
        }
        cp_async_wait<1>();
        bar_sync(NB_W0 + kh, 128);
        const uint32_t fv = row * 128 + (((2 * aa + ((lane >> 3) & 1)) ^ (row & 7)) << 4);
#pragma unroll
        for (int ks = 0; ks < 16; ks++) ldsm4t(wa[0][ks][0], wa[0][ks][1], wa[0][ks][2], wa[0][ks][3], sb + R_WV + kh * 32768 + fv + ks * 2048);
        bar_sync(NB_W0 + kh, 128);
#pragma unroll
        for (int ks = 0; ks < 16; ks++)
            sts128(sb + R_WV + kh * 32768 + (aa * 16 + ks) * 512 + lane * 16, make_uint4(wa[0][ks][0], wa[0][ks][1], wa[0][ks][2], wa[0][ks][3]));
        const uint32_t fo = stg + row * 128 + (((4 * (aa & 1) + ((lane >> 3) & 1)) ^ (row & 7)) << 4);
#pragma unroll 1
        for (int m = 0; m < 2; m++) {
            cp_async_wait<0>();
            bar_sync(NB_W0 + kh, 128);
            if ((aa >> 1) == m) {
#pragma unroll
                for (int ks = 0; ks < 16; ks++) {
                    ldsm4t(wa[0][ks][0], wa[0][ks][1], wa[0][ks][2], wa[0][ks][3], fo + ks * 2048);
                    ldsm4t(wa[1][ks][0], wa[1][ks][1], wa[1][ks][2], wa[1][ks][3], (fo ^ 32) + ks * 2048);
                }
            }
            bar_sync(NB_W0 + kh, 128);
            if (m == 0) {
#pragma unroll 4
                for (int dd = 0; dd < 16; dd++) {
                    const int d = dd * 16 + (t128 >> 3), pp = pos_of_d(d);
                    cp_async16(stg + pp * 128 + ((ch ^ (pp & 7)) << 4), p.wk + goff + (size_t)d * HD_);
                }
                cp_async_commit();
            }
        }
    }
    const uint32_t tab = stg + (aa * 32 + lane) * 16;
    {
        const uint32_t l7 = lane & 7, l8 = lane >> 3, g = lane >> 2, t = lane & 3;
        const uint32_t t0 = l7 * 128 + ((l8 ^ l7) << 4);
        const uint32_t tq = l7 * 128 + (((l8 >> 1) ^ l7) << 4);
        const uint32_t bq = warp >> 1, tp = warp & 1;
        uint4 v;
        v.x = sb + (aa < 2 ? R_QS : R_KMS) + l7 * 128 + (((4 * (aa & 1) + 2 * kh + (l8 & 1)) ^ l7) << 4);
        v.y = sb + R_QS + tq;
        v.z = sb + (warp == 0 ? R_KMS : R_KX + (warp - 1) * 1024) + t0;
        v.w = mapa_u32(sb + R_SX + (rank * 5 + warp) * 256 + lane * 8, crank ^ 1);
        sts128(tab, v);
        sts128(tab + 2048, make_uint4(sb + lane * 16 + R_MEM + kh * 4096, sb + lane * 16 + R_WV + warp * 8192,
                                      sb + lane * 16 + R_VP + warp * 512, sb + lane * 16 + R_VP + 4096 + (warp ^ 4) * 512));
        const uint32_t src = (l8 >> 1) * 8 + l7;
        const uint32_t L = bq * 8 + 2 * tp + (l8 & 1);
        const uint32_t d0 = (crank + ((t >> 1) | (g & 6))) & 15;
        v.x = sb + R_RS + src * 512 + ((L ^ (src & 7)) << 4);
        v.y = mapa_u32(sb + R_MEM + (crank * 4 + bq) * 128 + (4 * tp + 2 * (t & 1) + (g & 1)) * 16, d0);
        v.z = mapa_u32(sb + ((crank & 2) ? RB_A1 : RB_A), d0);
        v.w = lane;
        sts128(tab + 4096, v);
        const uint64_t wr = (uint64_t)(g_F + ((crank * 2 + ((crank ^ (crank >> 3) ^ sel) & 1)) * 1024 + warp * 128 + cl * 32 + lane));
        sts128(tab + 6144, make_uint4((uint32_t)wr, (uint32_t)(wr >> 32), (uint32_t)((((cl + 1) & 3) - cl) * 128), (uint32_t)((((cl + 2) & 3) - cl) * 128)));
        sts32(tab + 8192, (uint32_t)((((cl + 3) & 3) - cl) * 128));
#pragma unroll
        for (int i = 0; i < NOFF; i++)
            sts128(tab + 10240 + i * 2048, make_uint4(wa[i & 1][i >> 1][0], wa[i & 1][i >> 1][1], wa[i & 1][i >> 1][2], wa[i & 1][i >> 1][3]));
    }
    bar_sync(NB_D, 384);
    uint32_t slot_off = 0;
    const uint32_t slot_inc = warp == 0 ? 2048 : 4096, slot_last = warp == 0 ? 2048 : (R_NST - 1) * 4096;
    const uint32_t sx_bar_rem = (sb + RB_SX) ^ (1u << 24);
    uint4 tb = lds128(tab + 2048);
#pragma unroll 1
    for (int s = 0; s < NSEG; s++) {
        if (s > 0) mbar_wait(sb + RB_A, (s - 1) & 1);
        if (warp == 0) { PROF(0); PROFG(13); }
        uint4 ta;
        const uint32_t km_tog = aa >= 2 ? (s & 1) * 2048 : 0;
        {
            float acc[5][4];
#pragma unroll
            for (int c = 0; c < 5; c++) { acc[c][0] = acc[c][1] = acc[c][2] = acc[c][3] = 0.f; }
            uint32_t b[8][4];
            uint4 av[16];
            static_assert(VK0 == 4, "order below assumes the V/O warps cover slices 0,1");
            ldsm4(b[0][0], b[0][1], b[0][2], b[0][3], tb.x);
            ldsm4(b[1][0], b[1][1], b[1][2], b[1][3], tb.x + 512);
            ldsm4(b[4][0], b[4][1], b[4][2], b[4][3], tb.x + 2048);
            ldsm4(b[5][0], b[5][1], b[5][2], b[5][3], tb.x + 2560);
#pragma unroll
            for (int kk = 0; kk < 8; kk++) {
                const int k2 = kk < 2 ? kk : (kk < 4 ? kk + 2 : (kk < 6 ? kk - 2 : kk));
                if (kk == 4) {
                    if (s > 0) mbar_wait(sb + RB_A1, (s - 1) & 1);
                    ldsm4(b[2][0], b[2][1], b[2][2], b[2][3], tb.x + 1024);
                    ldsm4(b[3][0], b[3][1], b[3][2], b[3][3], tb.x + 1536);
                    ldsm4(b[6][0], b[6][1], b[6][2], b[6][3], tb.x + 3072);
                    ldsm4(b[7][0], b[7][1], b[7][2], b[7][3], tb.x + 3584);
#pragma unroll
                    for (int i = 12; i < 16; i++) av[i] = lds128(tb.y + i * 512);
                    ta = lds128(tab);
                }
                mma16816(acc[0], wa[0][2 * k2][0], wa[0][2 * k2][1], wa[0][2 * k2][2], wa[0][2 * k2][3], b[k2][0], b[k2][1]);
                mma16816(acc[1], wa[1][2 * k2][0], wa[1][2 * k2][1], wa[1][2 * k2][2], wa[1][2 * k2][3], b[k2][0], b[k2][1]);
                mma16816(acc[3], wa[0][2 * k2 + 1][0], wa[0][2 * k2 + 1][1], wa[0][2 * k2 + 1][2], wa[0][2 * k2 + 1][3], b[k2][2], b[k2][3]);
                mma16816(acc[4], wa[1][2 * k2 + 1][0], wa[1][2 * k2 + 1][1], wa[1][2 * k2 + 1][2], wa[1][2 * k2 + 1][3], b[k2][2], b[k2][3]);
                if (2 * k2 >= VK0) {
                    mma16816(acc[2], av[2 * k2].x, av[2 * k2].y, av[2 * k2].z, av[2 * k2].w, b[k2][0], b[k2][1]);
                    mma16816(acc[2], av[2 * k2 + 1].x, av[2 * k2 + 1].y, av[2 * k2 + 1].z, av[2 * k2 + 1].w, b[k2][2], b[k2][3]);
                }
                if (kk == 0) { av[8] = lds128(tb.y + 8 * 512); av[9] = lds128(tb.y + 9 * 512); }
                if (kk == 1) { av[10] = lds128(tb.y + 10 * 512); av[11] = lds128(tb.y + 11 * 512); }
                if (kk == 2) { av[4] = lds128(tb.y + 4 * 512); av[5] = lds128(tb.y + 5 * 512); }
                if (kk == 3) { av[6] = lds128(tb.y + 6 * 512); av[7] = lds128(tb.y + 7 * 512); }
            }
#pragma unroll
            for (int i = 0; i < 4; i++) { acc[0][i] += acc[3][i]; acc[1][i] += acc[4][i]; }
            const float g0 = kh ? acc[0][0] : acc[1][0], g1 = kh ? acc[0][1] : acc[1][1], g2 = kh ? acc[0][2] : acc[1][2], g3 = kh ? acc[0][3] : acc[1][3];
            sts128(tb.w, make_uint4(__float_as_uint(g0), __float_as_uint(g1), __float_as_uint(g2), __float_as_uint(g3)));
            const float k0 = kh ? acc[1][0] : acc[0][0], k1 = kh ? acc[1][1] : acc[0][1], k2_ = kh ? acc[1][2] : acc[0][2], k3 = kh ? acc[1][3] : acc[0][3];
            if (warp == 0) PROF(1);
            bar_sync(NB_X + aa, 64);
            const uint4 o = lds128(tb.z + 4096);
            stsm2t(ta.x ^ km_tog, pack2(k0 + __uint_as_float(o.x), k1 + __uint_as_float(o.y)), pack2(k2_ + __uint_as_float(o.z), k3 + __uint_as_float(o.w)));
            sts128(tb.z, make_uint4(__float_as_uint(acc[2][0]), __float_as_uint(acc[2][1]), __float_as_uint(acc[2][2]), __float_as_uint(acc[2][3])));
        }
        const uint32_t kb = ta.z + slot_off;
        if (warp == 0) PROF(14);
        bar_sync(NB_B, 256);
        if (warp < 5) {
            uint32_t q[16], k0, k1, k2, k3, k4, k5, k6, k7;
            float sa[4] = {0.f, 0.f, 0.f, 0.f}, sc[4] = {0.f, 0.f, 0.f, 0.f};
            ldsm4(q[0], q[1], q[2], q[3], ta.y);
            ldsm4(k0, k1, k2, k3, kb);
            ldsm4(q[4], q[5], q[6], q[7], ta.y ^ 32);
            ldsm4(q[8], q[9], q[10], q[11], ta.y ^ 64);
            ldsm4(k4, k5, k6, k7, kb ^ 64);
            ldsm4(q[12], q[13], q[14], q[15], ta.y ^ 96);
            mma16816(sa, q[0], q[1], q[2], q[3], k0, k1);
            bar_arrive(NB_Y, 288);
            mma16816(sc, q[4], q[5], q[6], q[7], k2, k3);
            mma16816(sa, q[8], q[9], q[10], q[11], k4, k5);
            mma16816(sc, q[12], q[13], q[14], q[15], k6, k7);
            const float scl = 0.08838834764831845f * 1.4426950408889634f;
            const float r0 = (sa[0] + sc[0]) * scl, r1 = (sa[1] + sc[1]) * scl;
            if (s != NSEG - 1) {
                st_async_v2(ta.w, r0, r1, sx_bar_rem);
                st_async_v2(ta.w ^ (1u << 24), r0, r1, sx_bar_rem ^ (1u << 24));
            }
            if (warp == 0) PROF(2);
        } else if (s > 0 && warp == 7 && lane == 0) {
            mbar_expect_tx(sb + RB_A, 4096);
            mbar_expect_tx(sb + RB_A1, 4096);
        } else if (s > 0 && (s & 3) == 0 && warp == 6) {
            bar_sync(NB_K, 160);
            if (lane == 0) red_release(&g_flags[F_MEM + (s >> 2) - 1], 1);
            __syncwarp();
        }
        if (s == NSEG - 1) {
            const uint4 td = lds128(tab + 6144);
            stg_relaxed32((uint32_t*)(((uint64_t)td.y << 32) | (td.x ^ 0x21000)), 0u);
            break;
        }
        slot_off = slot_off == slot_last ? 0 : slot_off + slot_inc;
        const uint4 tc = lds128(tab + 4096), td = lds128(tab + 6144);
        const uint32_t te = lds32(tab + 8192);
        uint32_t* wr = (uint32_t*)(((uint64_t)td.y << 32) | (td.x ^ ((s & 1) * 0x21000)));
        const uint32_t* r1p = (const uint32_t*)((const char*)wr + (int)td.z);
        const uint32_t* r2p = (const uint32_t*)((const char*)wr + (int)td.w);
        const uint32_t* r3p = (const uint32_t*)((const char*)wr + (int)te);
        const uint32_t tag = ((s >> 1) + 1) & 1;
        mbar_wait(sb + RB_E, s & 1);
        if (warp == 0) PROF(7);
        {
            uint32_t a0, a1, a2, a3, a4, a5, a6, a7;
            ldsm4t(a0, a1, a2, a3, tc.x);
            ldsm4t(a4, a5, a6, a7, tc.x ^ 64);
            const uint32_t one = 0x3F803F80u;
            float d0_[4] = {0.f, 0.f, 0.f, 0.f}, d1_[4] = {0.f, 0.f, 0.f, 0.f};
            mma16816(d0_, a0, a1, a2, a3, one, one);
            mma16816(d1_, a4, a5, a6, a7, one, one);
            const bool t1 = tc.w & 1, t2 = tc.w & 2;
            const float x = t2 ? (t1 ? d1_[2] : d1_[0]) : (t1 ? d0_[2] : d0_[0]);
            const uint32_t own = (__float_as_uint(x) & ~1u) | tag;
            stg_relaxed32(wr, own);
            const uint32_t tq = clk32();
            if (warp == 0) PROF(8);
            PROFG(16 + warp);
            while ((int)(clk32() - tq) < POLL_GAP) {}
            uint32_t f1 = ldg_relaxed32(r1p), f2 = ldg_relaxed32(r2p), f3 = ldg_relaxed32(r3p);
#pragma unroll
            for (int i = 0; i < NOFF; i++) {
                const uint4 f0 = lds128(tab + 10240 + i * 2048);
                wa[i & 1][i >> 1][0] = f0.x; wa[i & 1][i >> 1][1] = f0.y; wa[i & 1][i >> 1][2] = f0.z; wa[i & 1][i >> 1][3] = f0.w;
            }
            tb = lds128(tab + 2048);
            int gg = 0;
#pragma unroll 1
            while (!__all_sync(~0u, (((f1 ^ tag) | (f2 ^ tag) | (f3 ^ tag)) & 1) == 0)) {
                f1 = ldg_relaxed32(r1p); f2 = ldg_relaxed32(r2p); f3 = ldg_relaxed32(r3p);
                if (++gg > 16 * SPIN_LIMIT) { TIMEOUT(3, s); break; }
            }
            if (warp == 0) PROF(9);
            const float v = (__uint_as_float(own) + __uint_as_float(f2)) + (__uint_as_float(f1) + __uint_as_float(f3));
            const bool b8 = tc.w & 8, b16 = tc.w & 16;
            const float recv = __shfl_xor_sync(~0u, v, 8);
            const uint32_t word = b8 ? pack2(recv, v) : pack2(v, recv);
            const uint32_t oth = __shfl_xor_sync(~0u, word, 16);
            const uint32_t wl = b16 ? oth : word, wh = b16 ? word : oth;
            const uint32_t p0 = __shfl_xor_sync(~0u, wl, 2), p1 = __shfl_xor_sync(~0u, wh, 2);
            const uint4 item = t2 ? make_uint4(p0, p1, wl, wh) : make_uint4(wl, wh, p0, p1);
            st_async_v4(tc.y, item, tc.z);
            st_async_v4(tc.y ^ (8u << 24), item, tc.z ^ (8u << 24));
            if (tc.w == 0 && warp == 7) mbar_expect_tx(sb + RB_E, 8192);
            if (warp == 0) PROF(10);
            PROF(40 + warp);
        }
        bar_sync(NB_D, 384);
    }
}

__device__ __forceinline__ void rec_load_kv(uint32_t sb, int col0, int s, uint32_t slot_off, int t128) {
    const int row = t128 >> 2, c2 = (t128 & 3) * 2;
    const bf16* src = g_kv + ((size_t)(s * 32 + row) * (2 * HD_) + col0 + c2 * 8);
    const uint32_t d0 = sb + R_KX + slot_off + row * 128 + ((c2 ^ (row & 7)) << 4);
    cp_async16(d0, src);
    cp_async16(d0 ^ 16, src + 8);
    cp_async16(d0 + (R_VX - R_KX), src + HD_);
    cp_async16((d0 ^ 16) + (R_VX - R_KX), src + HD_ + 8);
}

__device__ __forceinline__ void rec_store_kvm(uint32_t sb, int col0, int s, int w, int lane) {
    const int tok = (w & 1) * 4 + (lane >> 3);
    const uint4 v = lds128(sb + R_KMS + (s & 1) * 2048 + (w >> 1) * 1024 + tok * 128 + (((lane & 7) ^ tok) << 4));
    *(uint4*)(g_kvm + ((s * 8 + tok) * (2 * HD_) + (w >> 1) * HD_ + col0 + (lane & 7) * 8)) = v;
}

__device__ __forceinline__ void rec_vo(const RecParams& p, const uint32_t sb, const int cta, const int warp, int lane) {
    const int w = warp - 8, crank = cta & 15;
    const int col0 = cta * 64;
    uint32_t wo[8][4][4];
    {
        const int t128 = w * 32 + lane;
        const bf16* Wo = p.wo + (size_t)col0 * D_;
        const uint32_t stg = sb + R_STG + 2 * 32768;
#pragma unroll
        for (int half = 0; half < 2; half++) {
#pragma unroll 4
            for (int i = t128; i < 2048; i += 128) {
                const int e = i >> 6, ch = i & 63;
                cp_async16(stg + e * 1024 + ((ch ^ (e & 7)) << 4), Wo + (size_t)(half * 32 + e) * D_ + ch * 8);
            }
            cp_async_commit();
            cp_async_wait<0>();
            bar_sync(NB_W0 + 2, 128);
#pragma unroll
            for (int j = 0; j < 8; j++)
#pragma unroll
                for (int kk = 0; kk < 2; kk++) {
                    const int e = kk * 16 + (lane >> 4) * 8 + (lane & 7);
                    const int ch = (w * 8 + j) * 2 + ((lane >> 3) & 1);
                    ldsm4t(wo[j][half * 2 + kk][0], wo[j][half * 2 + kk][1], wo[j][half * 2 + kk][2], wo[j][half * 2 + kk][3],
                           stg + e * 1024 + ((ch ^ (e & 7)) << 4));
                }
            bar_sync(NB_W0 + 2, 128);
        }
        if (lane == 0) wait_flag(F_KV + 0, 64);
        __syncwarp();
        rec_load_kv(sb, col0, 0, 0, t128); cp_async_commit();
        rec_load_kv(sb, col0, 1, 4096, t128); cp_async_commit();
        cp_async_wait<1>();
    }
    const uint32_t tab = sb + R_STG + 2 * 32768 + (w * 32 + lane) * 16;
    {
        const uint32_t l7 = lane & 7, l8 = lane >> 3, g = lane >> 2;
        uint4 v;
        v.x = sb + R_VX + ((l8 & 1) * 8 + l7) * 128 + (((2 * w + (l8 >> 1)) ^ l7) << 4);
        v.y = sb + R_OS + g * 128 + (((2 * w) ^ g) << 4) + (lane & 3) * 4;
        v.z = sb + R_VMS + l7 * 128 + (((2 * w + (l8 & 1)) ^ l7) << 4);
        v.w = sb + R_OS + l7 * 128 + ((l8 ^ l7) << 4);
        sts128(tab, v);
        v.x = mapa_u32(sb + R_RS + crank * 512 + ((lane ^ (crank & 7)) << 4), w * 4);
        v.y = mapa_u32(sb + RB_E, w * 4);
        v.z = sb + R_VP + w * 512 + lane * 16;
        v.w = sb + R_SX + lane * 8;
        sts128(tab + 2048, v);
#pragma unroll
        for (int i = 0; i < 8; i++) sts128(tab + 4096 + i * 2048, make_uint4(wo[i][0][0], wo[i][0][1], wo[i][0][2], wo[i][0][3]));
        const int tok = (w & 1) * 4 + (lane >> 3), row = (w * 32 + lane) >> 2, c2 = (lane & 3) * 2;
        const uint64_t kd = (uint64_t)(g_kvm + (tok * (2 * HD_) + (w >> 1) * HD_ + col0 + (lane & 7) * 8));
        const uint64_t ks = (uint64_t)(g_kv + ((size_t)row * (2 * HD_) + col0 + c2 * 8));
        sts128(tab + 20480, make_uint4((uint32_t)kd, (uint32_t)(kd >> 32), (uint32_t)ks, (uint32_t)(ks >> 32)));
        sts128(tab + 22528, make_uint4(sb + R_KMS + (w >> 1) * 1024 + tok * 128 + (((lane & 7) ^ tok) << 4),
                                       sb + R_KX + row * 128 + ((c2 ^ (row & 7)) << 4), lane, 0));
    }
    bar_sync(NB_D, 384);
    const uint32_t lane16 = lds32(tab + 2048 + 8) - R_VP - w * 512;
    uint4 av[2 * VK0];
#pragma unroll
    for (int i = 0; i < 2 * VK0; i++) av[i] = lds128(lane16 + R_WV + (i / VK0) * 32768 + (w * 16 + i % VK0) * 512);
    uint32_t slot_off = 0;
#pragma unroll 1
    for (int s = 0; s < NSEG; s++) {
        if (s > 0) {
            mbar_wait(sb + RB_A, (s - 1) & 1);
            const uint4 tp = lds128(tab + 20480), tq = lds128(tab + 22528);
            const uint4 kvm = lds128(tq.x + ((s - 1) & 1) * 2048);
            *(uint4*)((((uint64_t)tp.y << 32) | tp.x) + (uint64_t)(s - 1) * (8 * 2 * HD_ * 2)) = kvm;
            if ((s & 3) == 0) bar_arrive(NB_K, 160);
            if (s + 1 < NSEG - 1) {
                if (((s + 1) & 3) == 0) { if (tq.z == 0) wait_flag(F_KV + ((s + 1) >> 2), 64); __syncwarp(); }
                const char* src = (const char*)((((uint64_t)tp.w << 32) | tp.z) + (uint64_t)(s + 1) * (32 * 2 * HD_ * 2));
                const uint32_t d0 = tq.y + (slot_off == (R_NST - 1) * 4096 ? 0 : slot_off + 4096);
                cp_async16(d0, src);
                cp_async16(d0 ^ 16, src + 16);
                cp_async16(d0 + (R_VX - R_KX), src + HD_ * 2);
                cp_async16((d0 ^ 16) + (R_VX - R_KX), src + HD_ * 2 + 16);
            }
            cp_async_commit();
        }
        bar_sync(NB_Y, 288);
        uint32_t vb0, vb1;
        {
            float va[4] = {0.f, 0.f, 0.f, 0.f}, vc[4] = {0.f, 0.f, 0.f, 0.f};
            uint32_t bb[VK0][4];
#pragma unroll
            for (int k2 = 0; k2 < VK0; k2++) ldsm4(bb[k2][0], bb[k2][1], bb[k2][2], bb[k2][3], lane16 + R_MEM + (k2 / (VK0 / 2)) * 4096 + (k2 % (VK0 / 2)) * 512);
#pragma unroll
            for (int k2 = 0; k2 < VK0; k2++) {
                mma16816(va, av[2 * k2].x, av[2 * k2].y, av[2 * k2].z, av[2 * k2].w, bb[k2][0], bb[k2][1]);
                mma16816(vc, av[2 * k2 + 1].x, av[2 * k2 + 1].y, av[2 * k2 + 1].z, av[2 * k2 + 1].w, bb[k2][2], bb[k2][3]);
            }
            const uint4 a = lds128(lane16 + R_VP + w * 512), b = lds128(lane16 + R_VP + 2048 + w * 512);
            vb0 = pack2((va[0] + vc[0]) + (__uint_as_float(a.x) + __uint_as_float(b.x)), (va[1] + vc[1]) + (__uint_as_float(a.y) + __uint_as_float(b.y)));
            vb1 = pack2((va[2] + vc[2]) + (__uint_as_float(a.z) + __uint_as_float(b.z)), (va[3] + vc[3]) + (__uint_as_float(a.w) + __uint_as_float(b.w)));
        }
        const uint4 ta = lds128(tab), tb = lds128(tab + 2048);
        uint32_t vx[8];
        ldsm4t(vx[0], vx[1], vx[2], vx[3], ta.x + slot_off);
        ldsm4t(vx[4], vx[5], vx[6], vx[7], ta.x + slot_off + 2048);
#pragma unroll
        for (int i = 0; i < 4; i++) {
            const uint4 f0 = lds128(tab + 4096 + i * 2048);
            wo[i][0][0] = f0.x; wo[i][0][1] = f0.y; wo[i][0][2] = f0.z; wo[i][0][3] = f0.w;
        }
        if (w == 0) PROF(11);
        uint32_t pf[5];
        float oa[2][4] = {{0.f, 0.f, 0.f, 0.f}, {0.f, 0.f, 0.f, 0.f}}, ob_[2][4] = {{0.f, 0.f, 0.f, 0.f}, {0.f, 0.f, 0.f, 0.f}};
        float sm0[4] = {0.f, 0.f, 0.f, 0.f}, sm1[4] = {0.f, 0.f, 0.f, 0.f};
        if (s != NSEG - 1) {
            mbar_wait(sb + RB_SX, s & 1);
            if (w == 0) PROF(4);
            float sv[10];
#pragma unroll
            for (int n = 0; n < 5; n++) {
                const float2 a = lds64f(tb.w + n * 256), b = lds64f(tb.w + (5 + n) * 256);
                sv[2 * n] = a.x + b.x; sv[2 * n + 1] = a.y + b.y;
            }
            float mx = fmaxf(fmaxf(fmaxf(sv[0], sv[1]), fmaxf(sv[2], sv[3])), fmaxf(fmaxf(sv[4], sv[5]), fmaxf(sv[6], sv[7])));
            mx = fmaxf(mx, fmaxf(sv[8], sv[9]));
            mx = fmaxf(mx, __shfl_xor_sync(~0u, mx, 1));
            mx = fmaxf(mx, __shfl_xor_sync(~0u, mx, 2));
#pragma unroll
            for (int n = 1; n < 5; n++) pf[n] = pack2(ex2(sv[2 * n] - mx), ex2(sv[2 * n + 1] - mx));
            pf[0] = pack2(ex2(sv[0] - mx), ex2(sv[1] - mx));
            if (w == 0) PROF(12);
            const uint32_t one = 0x3F803F80u;
            mma16816h(sm0, pf[1], pf[2], one, one);
            mma16816h(oa[0], pf[1], pf[2], vx[0], vx[1]);
            mma16816h(oa[1], pf[1], pf[2], vx[2], vx[3]);
            mma16816h(sm1, pf[3], pf[4], one, one);
            mma16816h(ob_[0], pf[3], pf[4], vx[4], vx[5]);
            mma16816h(ob_[1], pf[3], pf[4], vx[6], vx[7]);
            mma1688h(sm0, pf[0], one);
            mma1688h(oa[0], pf[0], vb0);
            mma1688h(oa[1], pf[0], vb1);
            float inv;
            asm("rcp.approx.ftz.f32 %0, %1;" : "=f"(inv) : "f"(sm0[0] + sm1[0]));
            oa[0][0] += ob_[0][0]; oa[0][1] += ob_[0][1]; oa[1][0] += ob_[1][0]; oa[1][1] += ob_[1][1];
            sts32(ta.y, pack2(oa[0][0] * inv, oa[0][1] * inv));
            sts32(ta.y ^ 16, pack2(oa[1][0] * inv, oa[1][1] * inv));
            const uint32_t oa2 = ta.w ^ 64;
            bar_sync(NB_C, 128);
            if (w == 0) PROF(5);
            uint32_t ob[8];
            ldsm4(ob[0], ob[1], ob[2], ob[3], ta.w);
            ldsm4(ob[4], ob[5], ob[6], ob[7], oa2);
#pragma unroll
            for (int i = 4; i < 8; i++) {
                const uint4 f0 = lds128(tab + 4096 + i * 2048);
                wo[i][0][0] = f0.x; wo[i][0][1] = f0.y; wo[i][0][2] = f0.z; wo[i][0][3] = f0.w;
            }
#pragma unroll
            for (int jj = 0; jj < 2; jj++) {
                if (jj == 1 && tb.w == 0) break;
                float acc[4][4];
#pragma unroll
                for (int c = 0; c < 4; c++) { acc[c][0] = acc[c][1] = acc[c][2] = acc[c][3] = 0.f; }
#pragma unroll
                for (int ks = 0; ks < 4; ks++)
#pragma unroll
                    for (int c = 0; c < 4; c++)
                        mma16816(acc[c], wo[jj * 4 + c][ks][0], wo[jj * 4 + c][ks][1], wo[jj * 4 + c][ks][2], wo[jj * 4 + c][ks][3], ob[2 * ks], ob[2 * ks + 1]);
#pragma unroll
                for (int pr = 0; pr < 2; pr++) {
                    uint4 v;
                    v.x = pack2(acc[2 * pr][0], acc[2 * pr][1]);
                    v.y = pack2(acc[2 * pr][2], acc[2 * pr][3]);
                    v.z = pack2(acc[2 * pr + 1][0], acc[2 * pr + 1][1]);
                    v.w = pack2(acc[2 * pr + 1][2], acc[2 * pr + 1][3]);
                    st_async_v4(tb.x + ((jj * 2 + pr) << 24), v, tb.y + ((jj * 2 + pr) << 24));
                }
            }
            if (w == 0) PROF(6);
        }
        stsm2t(ta.z + (s & 1) * 2048, vb0, vb1);
        cp_async_wait<0>();
        bar_sync(NB_C, 128);
        if (w == 0 && lane == 0 && s != NSEG - 1) mbar_expect_tx(sb + RB_SX, 2560);
        if (s != NSEG - 1) bar_arrive(NB_D, 384);
#pragma unroll
        for (int i = 0; i < 2 * VK0; i++) av[i] = lds128(lane16 + R_WV + (i / VK0) * 32768 + (w * 16 + i % VK0) * 512);
        slot_off = slot_off == (R_NST - 1) * 4096 ? 0 : slot_off + 4096;
    }
    rec_store_kvm(sb, col0, NSEG - 1, w, lane);
    bar_sync(NB_C, 128);
    if (w == 0 && lane == 0) red_release(&g_flags[F_MEM + NRB - 1], 1);
}

__global__ void __launch_bounds__(384, 1) k_rec(const RecParams p) {
    extern __shared__ __align__(1024) unsigned char smem_raw[];
    const uint32_t sb = __shfl_sync(~0u, smem_u32(smem_raw), 0);
    const int warp = __shfl_sync(~0u, threadIdx.x >> 5, 0);
    int lane; asm volatile("mov.u32 %0, %%laneid;" : "=r"(lane));
    const int crank = blockIdx.x & 15, slot = blockIdx.x >> 4;
    asm volatile("griddepcontrol.launch_dependents;");
    if (threadIdx.x == 0) {
        mbar_init(sb + RB_SX, 1); mbar_init(sb + RB_E, 1); mbar_init(sb + RB_A, 1); mbar_init(sb + RB_A1, 1); mbar_init(sb + RB_ROLE, 1);
        asm volatile("fence.mbarrier_init.release.cluster;" ::: "memory");
        mbar_expect_tx(sb + RB_SX, 2560);
        mbar_expect_tx(sb + RB_E, 8192);
        mbar_expect_tx(sb + RB_A, 4096);
        mbar_expect_tx(sb + RB_A1, 4096);
        mbar_expect_tx(sb + RB_ROLE, 4);
    }
    if (warp >= 4) {
        const int w8 = warp - 4, nblk = gridDim.x;
        const int cq = lane & 3, rg = w8 * 8 + (lane >> 2);
        const uint32_t red = sb + R_STG;
        const int row0 = blockIdx.x * 8 + w8;
        const uint4* xr = (const uint4*)(p.x + (size_t)row0 * D_);
        uint4 xa = __ldg(xr + lane), xb = __ldg(xr + 32 + lane);
#pragma unroll 1
        for (int sl = blockIdx.x; sl < 96; sl += nblk) {
            uint4 wv[8];
#pragma unroll
            for (int i = 0; i < 8; i++) wv[i] = __ldg((const uint4*)(p.w_mod + (size_t)(rg * 8 + i) * (6 * D_) + sl * 32 + cq * 8));
            const uint32_t cw = __ldg((const uint32_t*)(p.c + rg * 8) + cq);
            const float cl = bflo(cw), ch = bfhi(cw);
            const uint32_t sw = pack2(__fdividef(cl, 1.f + __expf(-cl)), __fdividef(ch, 1.f + __expf(-ch)));
            float a[8];
#pragma unroll
            for (int i = 0; i < 8; i++) a[i] = 0.f;
#pragma unroll
            for (int i = 0; i < 8; i++) {
                const uint32_t sv = __shfl_sync(~0u, sw, (lane & 28) + (i >> 1));
                const float cv = (i & 1) ? bfhi(sv) : bflo(sv);
                a[0] = fmaf(cv, bflo(wv[i].x), a[0]); a[1] = fmaf(cv, bfhi(wv[i].x), a[1]); a[2] = fmaf(cv, bflo(wv[i].y), a[2]); a[3] = fmaf(cv, bfhi(wv[i].y), a[3]);
                a[4] = fmaf(cv, bflo(wv[i].z), a[4]); a[5] = fmaf(cv, bfhi(wv[i].z), a[5]); a[6] = fmaf(cv, bflo(wv[i].w), a[6]); a[7] = fmaf(cv, bfhi(wv[i].w), a[7]);
            }
#pragma unroll
            for (int i = 0; i < 8; i++) { a[i] += __shfl_xor_sync(~0u, a[i], 4); a[i] += __shfl_xor_sync(~0u, a[i], 8); a[i] += __shfl_xor_sync(~0u, a[i], 16); }
            if (lane < 4) {
                sts128(red + w8 * 128 + lane * 32, make_uint4(__float_as_uint(a[0]), __float_as_uint(a[1]), __float_as_uint(a[2]), __float_as_uint(a[3])));
                sts128(red + w8 * 128 + lane * 32 + 16, make_uint4(__float_as_uint(a[4]), __float_as_uint(a[5]), __float_as_uint(a[6]), __float_as_uint(a[7])));
            }
            bar_sync(NB_B, 256);
            if (w8 == 0) {
                float v = 0.f;
#pragma unroll
                for (int i = 0; i < 8; i++) v += lds32f(red + i * 128 + lane * 4);
                g_mod[sl * 32 + lane] = __float2bfloat16_rn(v);
                __syncwarp();
                if (lane == 0) red_release(&g_flags[F_MOD + (sl >= 32)], 1);
            }
            bar_sync(NB_B, 256);
        }
        uint32_t c1[8], sm[8];
#pragma unroll 1
        for (int row = row0; row < S_; row += nblk * 8) {
            const uint32_t v[8] = {xa.x, xa.y, xa.z, xa.w, xb.x, xb.y, xb.z, xb.w};
            if (row + nblk * 8 < S_) { xr += (size_t)nblk * 8 * (D_ / 8); xa = __ldg(xr + lane); xb = __ldg(xr + 32 + lane); }
            uint32_t mu2, r[8]; float rden;
            ln_stats(v, mu2, rden);
            if (row == row0) {
                if (lane == 0) wait_flag(F_MOD, 32);
                __syncwarp();
                load_mod8(g_mod + D_, lane, c1);
                load_mod8(g_mod, lane, sm);
#pragma unroll
                for (int i = 0; i < 8; i++) c1[i] = hadd2(c1[i], 0x3F803F80u);
            }
            ln_apply(v, mu2, rden, c1, sm, r);
            uint4* hr = (uint4*)(g_h + (size_t)row * D_);
            hr[lane] = make_uint4(r[0], r[1], r[2], r[3]); hr[32 + lane] = make_uint4(r[4], r[5], r[6], r[7]);
            bar_sync(NB_B, 256);
            if (w8 == (row >> 7 & 7) && lane == 0) red_release(&g_flags[F_H + (row >> 7)], 1);
            __syncwarp();
        }
    }
    if (p.only_pre) return;
    unsigned role = 0;
    if (crank == 0 && threadIdx.x == 0) {
        unsigned x = 0;
        int tm[2] = {0x7fffffff, 0x7fffffff};
#pragma unroll 1
        for (int i = 0; i < 6; i++) {
            const uint32_t t0 = clk32();
            x = atomicAdd(&g_F[65536 + (i & 1) * 1024 + slot * 64 + (x >> 31)], 0u) & 0x7fffffffu;
            if (x == 0x7654321u) sts32(sb + R_BAR + 56, x);
            const int dt = (int)(clk32() - t0);
            if (i >= 2) { if (i & 1) tm[1] = min(tm[1], dt); else tm[0] = min(tm[0], dt); }
        }
        const int side = tm[1] > tm[0];
        const unsigned old = atomicAdd(&g_flags[F_SIDE + side * 32], 1u);
        unsigned c0, c1; int gd = 0;
#pragma unroll 1
        do { c0 = ldg_relaxed32(&g_flags[F_SIDE]); c1 = ldg_relaxed32(&g_flags[F_SIDE + 32]); } while ((int)(c0 + c1) < p.ncl && ++gd < 64 * SPIN_LIMIT);
        const int big = c1 > c0;
        role = side == big ? old : (big ? c1 : c0) + old;
        role |= (big ^ 1) << 8;
    }
    __syncwarp();
    asm volatile("barrier.cluster.arrive.relaxed.aligned;\nbarrier.cluster.wait.aligned;" ::: "memory");
    if (crank == 0 && warp == 0) {
        role = __shfl_sync(~0u, role, 0);
        if (lane < 16)
            asm volatile("st.async.weak.shared::cluster.mbarrier::complete_tx::bytes.u32 [%0], %1, [%2];"
                         :: "r"(mapa_u32(sb + R_BAR + 48, lane)), "r"(role), "r"(mapa_u32(sb + RB_ROLE, lane)) : "memory");
    }
    mbar_wait(sb + RB_ROLE, 0);
    const int rolew = __shfl_sync(~0u, lds32(sb + R_BAR + 48), 0);
    const int cl = rolew & 255;
    if (cl >= 4) return;
    const int cta = cl * 16 + crank;
    if (warp < 8) rec_qk(p, sb, cta, warp, lane, rolew >> 8);
    else rec_vo(p, sb, cta, warp, lane);
}

enum { J_KV = 0, J_QA = 1, J_O = 2, J_LN = 3, J_UP = 4, J_DN = 5, J_LN1 = 6, J_MOD = 7, J_UP2 = 8, J_END = 9 };
constexpr int NJ_O = 2 * OSPLIT, NJ_O2 = 2 * OSPLIT2, NJ_LN = 8, NJ_LN2 = 16, NJ_UP = 14, NJ_UP2 = 28, NJ_DN = 8, NJ_LN1 = 8;
constexpr uint64_t pk8(int a, int b, int c, int d, int e, int f, int g, int h) {
    return (uint64_t)a | ((uint64_t)b << 8) | ((uint64_t)c << 16) | ((uint64_t)d << 24) | ((uint64_t)e << 32) | ((uint64_t)f << 40) | ((uint64_t)g << 48) | ((uint64_t)h << 56);
}
constexpr uint64_t NJ_C = pk8(32, 16, NJ_O, NJ_LN, NJ_UP, NJ_DN, 0, 0), NJ_F = pk8(32, 16, NJ_O2, NJ_LN2, NJ_UP2, NJ_DN, 0, 0);
constexpr uint64_t TG_C = pk8(2 * NJ_LN1, 64, 32, 2 * NJ_O, 2 * NJ_LN, 2 * NJ_UP, 32, 0), TG_F = pk8(2 * NJ_LN1, 64, 32, 2 * NJ_O2, 2 * NJ_LN2, 2 * NJ_UP2, 32, 0);
constexpr uint64_t PRIO = pk8(4, 10, 9, 8, 7, 6, 3, 0);
__device__ __forceinline__ int pick_job(int lane, int qmask, int& idx) {
    const int rb = lane & 15, half = lane >> 4;
    const uint64_t nj = (rb >= FINE_RB ? NJ_F : NJ_C) >> (8 * half);
    const uint64_t tg = (rb >= FINE_RB ? TG_F : TG_C) >> (8 * half);
    const unsigned* cp = &g_flags[F_CLAIM + half * 32 + rb];
    const unsigned* dp = &g_flags[half * 32 + rb];
    int gd = 0;
#pragma unroll 1
    while (true) {
        const unsigned c0 = ldg_relaxed32(cp), c1 = ldg_relaxed32(cp + 64), c2 = ldg_relaxed32(cp + 128);
        const unsigned d0 = ldg_relaxed32(dp - (half ? (rb >= FINE_RB ? 2 : (rb ? 1 : 0)) : 0)), d1 = ldg_relaxed32(dp + 64), d2 = ldg_relaxed32(dp + 128);
        const unsigned cl[3] = {c0, c1, c2}, dv[3] = {d0, d1, d2};
        unsigned key = 0xffffu, key2 = 0xffffu;
        bool pre = false;
#pragma unroll
        for (int i = 0; i < 3; i++) {
            const int q = half + 2 * i;
            const bool have = ((qmask >> q) & 1) && cl[i] < (unsigned)((nj >> (16 * i)) & 255);
            bool ready = have && dv[i] >= (unsigned)((tg >> (16 * i)) & 255);
            unsigned pr = (unsigned)((PRIO >> (8 * q)) & 255);
            if (i == 0 && rb <= 1 - half) ready = have;
            if (i == 0 && half && rb >= FINE_RB) pr = 5;
            if (ready) key = min(key, (pr << 8) | (rb << 4) | q);
            if (have) key2 = min(key2, rb >= FINE_RB ? (0x100u | (q << 4) | rb) : (i == 0 ? 0u : 0x1000u));
            pre |= have && i == 0 && !half;
        }
        const bool anypre = __any_sync(~0u, pre);
        if (anypre && (key & 15) == J_QA) key = 0xffffu;
        key = __reduce_min_sync(~0u, key);
        key2 = __reduce_min_sync(~0u, key2);
        if (key2 == 0xffffu) return J_END;
        int pq, prb;
        if (key != 0xffffu) { pq = key & 15; prb = (key >> 4) & 15; }
        else if (key2 >= 0x120u && key2 < 0x1000u) { pq = (key2 >> 4) & 15; prb = key2 & 15; }
        else {
            __nanosleep(IDLE_NS);
            if (++gd > 16 * SPIN_LIMIT) { TIMEOUT(5, 0); return J_END; }
            continue;
        }
        int c = 0;
        if (lane == 0) c = (int)atomicAdd(&g_flags[F_CLAIM + pq * 32 + prb], 1u);
        c = __shfl_sync(~0u, c, 0);
        if (c < (int)(((prb >= FINE_RB ? NJ_F : NJ_C) >> (8 * pq)) & 255)) {
            idx = pq * 512 + prb * 32 + c;
            int acq = 0;
            if (pq != J_QA && pq < J_LN1) {
                if (lane == 0 && ld_acquire(&g_flags[pq * 32 + prb]) >= (unsigned)(((prb >= FINE_RB ? TG_F : TG_C) >> (8 * pq)) & 255)) {
                    asm volatile("fence.proxy.async.global;" ::: "memory");
                    acq = 1 << 24;
                }
            }
            return (pq == J_UP && prb >= FINE_RB ? J_UP2 : pq) | (prb << 8) | (c << 16) | acq;
        }
    }
}
__device__ __forceinline__ int op_row(int rb, int split) {
    return rb < FINE_RB ? split * S_ + rb * 128 : OSPLIT * S_ + (split * (NRB - FINE_RB) + rb - FINE_RB) * 128;
}

struct Pipe { uint32_t stage, phase; };
__device__ __forceinline__ void pipe_next(Pipe& p) { if (++p.stage == W_NST) { p.stage = 0; p.phase ^= 1; } }

__device__ __forceinline__ void scheduler(const Params& p, uint32_t sb, int lane) {
    const uint32_t bars = sb + SM_BAR;
    uint32_t ph = 0;
#pragma unroll 1
    while (true) {
        mbar_wait(bars + B_REQ, ph);
        int j = 4095;
        const int jd = pick_job(lane, p.qmask, j);
        if (lane == 0) { sts32(bars + B_NEXT, (uint32_t)jd); sts32(bars + B_NEXT + 4, (uint32_t)j); mbar_arrive(bars + B_RSP); }
        ph ^= 1;
        if (jd == J_END) break;
        __syncwarp();
    }
}

__device__ __forceinline__ void producer(const Params& p, uint32_t sb) {
    Pipe pp{0, 1};
    const uint32_t bars = sb + SM_BAR;
    uint32_t seq = 0, h_seen = 0;
    mbar_arrive(bars + B_REQ);
#pragma unroll 1
    while (true) {
        mbar_wait(bars + B_RSP, seq & 1);
        const int jd = (int)lds32(bars + B_NEXT), j = (int)lds32(bars + B_NEXT + 4);
        int left = (jd & 255) == J_DN ? 15 : ((jd & 255) == J_QA ? 12 : ((jd & 255) == J_O ? (((jd >> 8) & 255) >= FINE_RB ? 64 / OSPLIT2 : 64 / OSPLIT) : ((jd & 255) == J_LN || (jd & 255) == J_LN1 || (jd & 255) == J_MOD ? 1 : 8)));
        left = max(left - PICK_AHEAD, 1);
        TR(j, 1);
        const int type = jd & 255, rb = (jd >> 8) & 255, cb = (jd >> 16) & 255;
        const bool fine = rb >= FINE_RB, acquired = (jd >> 24) & 1;
        bool first = true;
        auto begin_stage = [&](uint32_t bytes) -> uint32_t {
            mbar_wait(bars + B_EMPTY + pp.stage * 8, pp.phase);
            if (first) { sts32(bars + B_RING + (seq & 7) * 4, (uint32_t)jd); sts32(bars + B_RING + 32 + (seq & 7) * 4, (uint32_t)j); first = false; }
            const uint32_t fb = bars + B_FULL + pp.stage * 8;
            if (bytes) mbar_expect_tx(fb, bytes); else mbar_arrive(fb);
            if (--left == 0 && type != J_END) mbar_arrive(bars + B_REQ);
            return fb;
        };
        if (type == J_END || type == J_LN || type == J_LN1 || type == J_MOD) {
            if (type == J_LN) { if (!acquired) wait_flag(F_OP + rb, 2 * (fine ? NJ_O2 : NJ_O)); if (!(h_seen >> 31)) { wait_flag(F_MOD + 1, 64); h_seen |= 1u << 31; } }

            TR(j, 2);
            begin_stage(0); pipe_next(pp);
            seq++;
            if (type == J_END) break;
            continue;
        }
        const CUtensorMap *ta, *tb0, *tb1;
        int k0 = 0, nk = 8, n0 = cb * 256, n1 = n0 + 128, nb = 4, dep = -1;
        unsigned tgt = 0;
        switch (type) {
            case J_KV: ta = &p.tm_h; tb0 = tb1 = cb < 16 ? &p.tm_wk : &p.tm_wv; n0 = (cb & 15) * 256; n1 = n0 + 128; dep = F_H + rb; tgt = 2 * NJ_LN1; break;
            case J_QA: ta = &p.tm_h; tb0 = tb1 = &p.tm_wq; dep = F_H + rb; tgt = 2 * NJ_LN1; break;
            case J_O: ta = &p.tm_o; tb0 = tb1 = &p.tm_wo; n0 = (cb & 1) * 256; n1 = n0 + 128; nk = fine ? 64 / OSPLIT2 : 64 / OSPLIT; k0 = (cb >> 1) * nk * 64;
                      dep = F_O + rb; tgt = 32; break;
            case J_UP: ta = &p.tm_h2; tb0 = &p.tm_wg; tb1 = &p.tm_wu; n0 = n1 = cb * 128; dep = F_H2 + rb; tgt = 2 * NJ_LN; break;
            case J_UP2: ta = &p.tm_h2; tb0 = &p.tm_wg; tb1 = &p.tm_wu; n0 = n1 = cb * 64; nb = 2; dep = F_H2 + rb; tgt = 2 * NJ_LN2; break;
            default: ta = &p.tm_act; tb0 = tb1 = &p.tm_wd; n0 = cb * 64; nk = 0; break;
        }
        const int m0 = rb * 128;
        if (type == J_DN) {
#pragma unroll 1
            for (int kb = 0; kb < 14; kb++) {
                const uint32_t fb = begin_stage(49152);
                const uint32_t st = sb + pp.stage * W_STAGE;
                const int k = kb * 128;
                tma_load2d(st + 32768, tb0, n0, k, fb);
                tma_load2d(st + 40960, tb0, n0, k + 64, fb);
                if (kb == 0) { if (!acquired) { wait_flag(F_ACT + rb, 2 * (fine ? NJ_UP2 : NJ_UP)); asm volatile("fence.proxy.async.global;" ::: "memory"); } TR(j, 2); }
                tma_load2d(st, ta, k, m0, fb);
                tma_load2d(st + 8192, ta, k, m0 + 64, fb);
                tma_load2d(st + 16384, ta, k + 64, m0, fb);
                tma_load2d(st + 24576, ta, k + 64, m0 + 64, fb);
                pipe_next(pp);
            }
        }
#pragma unroll 1
        for (int kb = 0; kb < nk; kb++) {
            const uint32_t fb = begin_stage(16384 + nb * 8192);
            const uint32_t st = sb + pp.stage * W_STAGE;
            const int k = k0 + kb * 64;
            tma_load2d(st + 16384, tb0, n0, k, fb);
            if (nb == 4) {
                tma_load2d(st + 16384 + 8192, tb0, n0 + 64, k, fb);
                tma_load2d(st + 16384 + 16384, tb1, n1, k, fb);
                tma_load2d(st + 16384 + 24576, tb1, n1 + 64, k, fb);
            } else if (nb == 2) {
                tma_load2d(st + 16384 + 8192, tb1, n1, k, fb);
            }
            if (kb == 0) {
                if (acquired && dep < 16) h_seen |= 1u << dep;
                if (dep >= 0 && !acquired && !(dep < 16 && ((h_seen >> dep) & 1))) {
                    wait_flag(dep, tgt);
                    if (type != J_O) asm volatile("fence.proxy.async.global;" ::: "memory");
                    if (dep < 16) h_seen |= 1u << dep;
                }
                TR(j, 2);
            }
            tma_load2d(st, ta, k, m0, fb);
            tma_load2d(st + 8192, ta, k, m0 + 64, fb);
            pipe_next(pp);
        }
        if (type == J_QA) {
            wait_flag(F_KV + rb, 64);
#pragma unroll 1
            for (int i = 0; i < 4; i++) {
                const uint32_t fb = begin_stage(40960);
                const uint32_t st = sb + pp.stage * W_STAGE;
                const int col = (i & 1) * HD_ + (cb * 2 + (i >> 1)) * DH_;
                tma_load2d(st, &p.tm_kv, col, m0, fb);
                tma_load2d(st + 8192, &p.tm_kv, col, m0 + 64, fb);
                tma_load2d(st + 16384, &p.tm_kv, col + 64, m0, fb);
                tma_load2d(st + 24576, &p.tm_kv, col + 64, m0 + 64, fb);
                if (i == 0) { wait_flag(F_MEM + rb, 64); asm volatile("fence.proxy.async.global;" ::: "memory"); }
                tma_load2d(st + 32768, &p.tm_kvm, col, rb * 32, fb);
                tma_load2d(st + 36864, &p.tm_kvm, col + 64, rb * 32, fb);
                pipe_next(pp);
            }
        } else if (type == J_DN) {
            const uint32_t fb = begin_stage(16384);
            const uint32_t st = sb + pp.stage * W_STAGE;
            tma_load2d(st, &p.tm_x1, n0, m0, fb);
            tma_load2d(st + 8192, &p.tm_x1, n0, m0 + 64, fb);
            pipe_next(pp);
        }
        seq++;
    }
}

__device__ __forceinline__ void store_warp(const Params& p, uint32_t sb, int wg, int lane) {
    const uint32_t bars = sb + SM_BAR;
    uint32_t seq = 0;
#pragma unroll 1
    while (true) {
        bar_sync(NB_ST + wg, 160);
        const uint32_t jd = lds32(bars + B_RING + (seq & 7) * 4);
        seq++;
        const int type = jd & 255, rb = (jd >> 8) & 255, cb = (jd >> 16) & 255;
        if (type == J_END) break;
        const uint32_t src = sb + W_STG + wg * 16384;
        const CUtensorMap* tm = nullptr; int n0 = cb * 256, nbox = 4, mrow = rb * 128 + wg * 64, flag = 0;
        switch (type) {
            case J_KV: tm = &p.tm_kv; flag = F_KV + rb; break;
            case J_QA: tm = &p.tm_o; flag = F_O + rb; break;
            case J_O: tm = &p.tm_op; n0 = (cb & 1) * 256; mrow = op_row(rb, cb >> 1) + wg * 64; flag = F_OP + rb; break;
            case J_LN: flag = F_H2 + rb; nbox = 0; break;
            case J_LN1: flag = F_H + rb; nbox = 0; break;
            case J_MOD: flag = F_MOD + rb; nbox = 0; break;
            case J_UP: tm = &p.tm_act; n0 = cb * 128; nbox = 2; flag = F_ACT + rb; break;
            case J_UP2: tm = &p.tm_act; n0 = cb * 64; nbox = 1; flag = F_ACT + rb; break;
            default: tm = &p.tm_out; n0 = cb * 64; nbox = 1; flag = -1; break;
        }
        if (nbox == 4) {
            if (lane == 0) {
                tma_store2d(tm, src, n0, mrow);
                tma_store2d(tm, src + 8192, n0 + 64, mrow);
                bulk_commit();
                asm volatile("cp.async.bulk.wait_group.read 0;" ::: "memory");
                mbar_arrive(bars + B_STGFREE + wg * 8);
            }
            __syncwarp();
            bar_sync(NB_ST + wg, 160);
            n0 += 128; nbox = 2;
        }
        if (lane == 0) {
            if (nbox) {
                tma_store2d(tm, src, n0, mrow);
                if (nbox == 2) tma_store2d(tm, src + 8192, n0 + 64, mrow);
                bulk_commit();
                asm volatile("cp.async.bulk.wait_group.read 0;" ::: "memory");
                mbar_arrive(bars + B_STGFREE + wg * 8);
                bulk_wait0();
                if (flag >= 0) asm volatile("red.relaxed.gpu.global.add.u32 [%0], 1;" :: "l"(&g_flags[flag]) : "memory");
            } else {
                mbar_arrive(bars + B_STGFREE + wg * 8);
                red_release(&g_flags[flag], 1);
            }
        }
        __syncwarp();
    }
}

__device__ __forceinline__ float gelu_tanh(float x) {
    const float t = x * fmaf(-0.10294324397f, x * x, -2.30220819814f);
    float r; asm("rcp.approx.ftz.f32 %0, %1;" : "=f"(r) : "f"(1.f + ex2(t)));
    return x * r;
}

#define CTR(i) do {} while (0)

template <int NSPLIT>
__device__ __forceinline__ void ln2_row(const Params& p, int rb, int r, int lane) {
    const int row = rb * 128 + r;
    uint4 u[2 * NSPLIT];
#pragma unroll
    for (int sp = 0; sp < NSPLIT; sp++) {
        const uint4* src = (const uint4*)(g_op + (size_t)(op_row(rb, sp) + r) * D_);
        u[2 * sp] = __ldcg(src + lane); u[2 * sp + 1] = __ldcg(src + 32 + lane);
    }
    const uint4* xr = (const uint4*)(p.x + (size_t)row * D_);
    const uint4 xa = __ldg(xr + lane), xb = __ldg(xr + 32 + lane);
    uint32_t ga[8], c1[8], sm[8];
    load_mod8(g_mod + 2 * D_, lane, ga);
    load_mod8(g_mod + 4 * D_, lane, c1);
    load_mod8(g_mod + 3 * D_, lane, sm);
    float a[16];
#pragma unroll
    for (int i = 0; i < 16; i++) a[i] = 0.f;
#pragma unroll
    for (int sp = 0; sp < 2 * NSPLIT; sp++) {
        float* q = a + (sp & 1) * 8;
        q[0] += bflo(u[sp].x); q[1] += bfhi(u[sp].x); q[2] += bflo(u[sp].y); q[3] += bfhi(u[sp].y);
        q[4] += bflo(u[sp].z); q[5] += bfhi(u[sp].z); q[6] += bflo(u[sp].w); q[7] += bfhi(u[sp].w);
    }
    const uint32_t xv[8] = {xa.x, xa.y, xa.z, xa.w, xb.x, xb.y, xb.z, xb.w};
    uint32_t v[8], r8[8];
#pragma unroll
    for (int i = 0; i < 8; i++) v[i] = hadd2(xv[i], hmul2(ga[i], pack2(a[2 * i], a[2 * i + 1])));
    uint4* x1r = (uint4*)(g_x1 + (size_t)row * D_);
    x1r[lane] = make_uint4(v[0], v[1], v[2], v[3]); x1r[32 + lane] = make_uint4(v[4], v[5], v[6], v[7]);
    uint32_t mu2; float rden;
    ln_stats(v, mu2, rden);
#pragma unroll
    for (int i = 0; i < 8; i++) c1[i] = hadd2(c1[i], 0x3F803F80u);
    ln_apply(v, mu2, rden, c1, sm, r8);
    uint4* hr = (uint4*)(g_h2 + (size_t)row * D_);
    hr[lane] = make_uint4(r8[0], r8[1], r8[2], r8[3]); hr[32 + lane] = make_uint4(r8[4], r8[5], r8[6], r8[7]);
}

__device__ __forceinline__ void consumer(const Params& p, uint32_t sb, int warp, int lane) {
    const uint32_t bars = sb + SM_BAR;
    const int wg = warp >> 2, wl = warp & 3;
    const uint32_t l7 = lane & 7, l8 = lane >> 3, g = lane >> 2, t = lane & 3;
    Pipe pp{0, 0};
    uint32_t seq = 0, stg_phase = 1;
    const int srow = wl * 16 + l7 + (l8 & 1) * 8;
    const uint32_t stg_base = sb + W_STG + wg * 16384 + srow * 128;
    const uint32_t sx = ((lane >> 4) ^ (srow & 7)) << 4;
#pragma unroll 1
    while (true) {
        mbar_wait(bars + B_FULL + pp.stage * 8, pp.phase);
        const uint32_t jd = lds32(bars + B_RING + (seq & 7) * 4);
        CTR(3);
        seq++;
        const int type = jd & 255, rb = (jd >> 8) & 255, cb = (jd >> 16) & 255;
        if (type == J_END) { mbar_wait(bars + B_STGFREE + wg * 8, stg_phase); bar_arrive(NB_ST + wg, 160); break; }
        if (type == J_LN) {
            __syncwarp();
            if (lane == 0) mbar_arrive(bars + B_EMPTY + pp.stage * 8);
            pipe_next(pp);
            if (rb >= FINE_RB) ln2_row<OSPLIT2>(p, rb, cb * 8 + warp, lane);
            else {
#pragma unroll 1
                for (int rr = 0; rr < 2; rr++) ln2_row<OSPLIT>(p, rb, cb * 16 + warp * 2 + rr, lane);
            }
            mbar_wait(bars + B_STGFREE + wg * 8, stg_phase); stg_phase ^= 1;
            CTR(4); CTR(5);
            bar_arrive(NB_ST + wg, 160);
            continue;
        }
        if (type == J_DN || type == J_UP2) {
            float acc[64];
#pragma unroll
            for (int i = 0; i < 64; i++) acc[i] = 0.f;
            if (type == J_DN) {
#pragma unroll 1
                for (int kb = 0; kb < 14; kb++) {
                    if (kb) mbar_wait(bars + B_FULL + pp.stage * 8, pp.phase);
                    const uint32_t st = sb + pp.stage * W_STAGE;
                    const uint64_t da = mkdesc(st + wg * 8192, 16, 1024), db = mkdesc(st + 32768, 8192, 1024);
                    wg_fence();
#pragma unroll
                    for (int ks = 0; ks < 8; ks++) wgmma_n64(acc, da + (ks >> 2) * 1024 + (ks & 3) * 2, db + ks * 128);
                    wg_commit();
                    wg_wait0();
                    if (lane == 0) mbar_arrive(bars + B_EMPTY + pp.stage * 8);
                    pipe_next(pp);
                }
            } else {
#pragma unroll 1
                for (int kb = 0; kb < 8; kb++) {
                    if (kb) mbar_wait(bars + B_FULL + pp.stage * 8, pp.phase);
                    const uint32_t st = sb + pp.stage * W_STAGE;
                    const uint64_t da = mkdesc(st + wg * 8192, 16, 1024), db = mkdesc(st + 16384, 8192, 1024);
                    wg_fence();
#pragma unroll
                    for (int ks = 0; ks < 4; ks++) wgmma_n128(acc, da + ks * 2, db + ks * 128, 1);
                    wg_commit();
                    wg_wait0();
                    if (lane == 0) mbar_arrive(bars + B_EMPTY + pp.stage * 8);
                    pipe_next(pp);
                }
            }
            CTR(4);
            if (type == J_UP2) {
                mbar_wait(bars + B_STGFREE + wg * 8, stg_phase); stg_phase ^= 1;
#pragma unroll
                for (int j = 0; j < 4; j++) {
                    uint32_t r[4];
#pragma unroll
                    for (int q = 0; q < 4; q++) {
                        const uint32_t gw = pack2(acc[8 * j + 2 * q], acc[8 * j + 2 * q + 1]);
                        const uint32_t uw = pack2(acc[32 + 8 * j + 2 * q], acc[32 + 8 * j + 2 * q + 1]);
                        r[q] = hmul2(pack2(gelu_tanh(bflo(gw)), gelu_tanh(bfhi(gw))), uw);
                    }
                    stsm4(stg_base + (sx ^ (j << 5)), r[0], r[1], r[2], r[3]);
                }
            } else {
                mbar_wait(bars + B_FULL + pp.stage * 8, pp.phase);
                const uint32_t st = sb + pp.stage * W_STAGE;
                mbar_wait(bars + B_STGFREE + wg * 8, stg_phase); stg_phase ^= 1;
                const uint32_t* gb = (const uint32_t*)(g_mod + 5 * D_ + cb * 64) + t;
                const uint32_t xa = st + wg * 8192 + (wl * 16 + g) * 128 + (g << 4) + t * 4;
#pragma unroll
                for (int j = 0; j < 4; j++) {
                    uint32_t r[4];
#pragma unroll
                    for (int q = 0; q < 4; q++) {
                        const int nt = 2 * j + (q >> 1);
                        const uint32_t xw = lds32((xa ^ ((nt & 7) << 4)) + (nt >> 3) * 16384 + (q & 1) * 1024);
                        r[q] = hadd2(xw, hmul2(__ldcg(gb + nt * 4), pack2(acc[8 * j + 2 * q], acc[8 * j + 2 * q + 1])));
                    }
                    stsm4(stg_base + (j >> 2) * 8192 + (sx ^ ((2 * j & 7) << 4)), r[0], r[1], r[2], r[3]);
                }
                __syncwarp();
                if (lane == 0) mbar_arrive(bars + B_EMPTY + pp.stage * 8);
                pipe_next(pp);
            }
            fence_async_smem();
            CTR(5);
            bar_arrive(NB_ST + wg, 160);
            continue;
        }
        float acc[128];
#pragma unroll
        for (int i = 0; i < 128; i++) acc[i] = 0.f;
        const int nk = type == J_O ? (rb >= FINE_RB ? 64 / OSPLIT2 : 64 / OSPLIT) : 8;
#pragma unroll 1
        for (int kb = 0; kb < nk; kb++) {
            if (kb) mbar_wait(bars + B_FULL + pp.stage * 8, pp.phase);
            const uint32_t st = sb + pp.stage * W_STAGE;
            const uint64_t da = mkdesc(st + wg * 8192, 16, 1024), db = mkdesc(st + 16384, 8192, 1024);
            wg_fence();
#pragma unroll
            for (int ks = 0; ks < 4; ks++) wgmma_n256(acc, da + ks * 2, db + ks * 128, 1);
            wg_commit();
            wg_wait0();
            if (lane == 0) mbar_arrive(bars + B_EMPTY + pp.stage * 8);
            pipe_next(pp);
        }
        CTR(4);
        if (type == J_QA) {
            uint32_t qf[64];
#pragma unroll
            for (int i = 0; i < 64; i++) qf[i] = pack2(acc[2 * i], acc[2 * i + 1]);
            const int sg = warp >> 1, half = warp & 1;
            const float sc = 0.08838834764831845f * 1.4426950408889634f;
            const uint32_t xoff = (sg >> 1) * 8192 + ((sg & 1) * 32 + l7) * 128;
            const uint32_t moff = 32768 + (sg * 8 + l7) * 128;
            const uint32_t kch = (l8 ^ l7) << 4;
            const uint32_t vch = ((l8 & 1) ^ l7) << 4;
#pragma unroll 1
            for (int hh = 0; hh < 2; hh++) {
                mbar_wait(bars + B_FULL + pp.stage * 8, pp.phase);
                uint32_t st = sb + pp.stage * W_STAGE;
                float sa[5][4];
#pragma unroll
                for (int n = 0; n < 5; n++) sa[n][0] = sa[n][1] = sa[n][2] = sa[n][3] = 0.f;
#pragma unroll
                for (int i = 0; i < 4; i++) {
                    const uint32_t* q = qf + i * 8;
                    uint32_t kk[5][4];
                    ldsm4(kk[0][0], kk[0][1], kk[0][2], kk[0][3], st + moff + (i >> 1) * 4096 + (kch ^ ((i & 1) * 64)));
#pragma unroll
                    for (int n = 1; n < 5; n++)
                        ldsm4(kk[n][0], kk[n][1], kk[n][2], kk[n][3], st + xoff + (n - 1) * 1024 + (i >> 1) * 16384 + (kch ^ ((i & 1) * 64)));
#pragma unroll
                    for (int n = 0; n < 5; n++) mma16816(sa[n], q[0], q[1], q[2], q[3], kk[n][0], kk[n][1]);
#pragma unroll
                    for (int n = 0; n < 5; n++) mma16816(sa[n], q[4], q[5], q[6], q[7], kk[n][2], kk[n][3]);
                }
                __syncwarp();
                if (lane == 0) mbar_arrive(bars + B_EMPTY + pp.stage * 8);
                pipe_next(pp);
                const int iq0 = half * 16 + g - 2 * t, iq1 = iq0 + 8;
                float m0 = fmaxf(sa[0][0], sa[0][1]), m1 = fmaxf(sa[0][2], sa[0][3]);
#pragma unroll
                for (int n = 1; n < 5; n++) {
#pragma unroll
                    for (int e = 0; e < 2; e++) {
                        const int jx = (n - 1) * 8 + e;
                        if (jx > iq0) sa[n][e] = -3.0e38f;
                        if (jx > iq1) sa[n][2 + e] = -3.0e38f;
                        m0 = fmaxf(m0, sa[n][e]); m1 = fmaxf(m1, sa[n][2 + e]);
                    }
                }
                m0 = fmaxf(m0, __shfl_xor_sync(~0u, m0, 1)); m1 = fmaxf(m1, __shfl_xor_sync(~0u, m1, 1));
                m0 = fmaxf(m0, __shfl_xor_sync(~0u, m0, 2)); m1 = fmaxf(m1, __shfl_xor_sync(~0u, m1, 2));
                m0 *= -sc; m1 *= -sc;
                float l0 = 0.f, l1 = 0.f;
                uint32_t p0[5], p1[5];
#pragma unroll
                for (int n = 0; n < 5; n++) {
                    const float e0 = ex2(fmaf(sa[n][0], sc, m0)), e1 = ex2(fmaf(sa[n][1], sc, m0));
                    const float e2 = ex2(fmaf(sa[n][2], sc, m1)), e3 = ex2(fmaf(sa[n][3], sc, m1));
                    l0 += e0 + e1; l1 += e2 + e3;
                    p0[n] = pack2(e0, e1); p1[n] = pack2(e2, e3);
                }
                l0 += __shfl_xor_sync(~0u, l0, 1); l1 += __shfl_xor_sync(~0u, l1, 1);
                l0 += __shfl_xor_sync(~0u, l0, 2); l1 += __shfl_xor_sync(~0u, l1, 2);
                const float i0 = __fdividef(1.f, l0), i1 = __fdividef(1.f, l1);
                mbar_wait(bars + B_FULL + pp.stage * 8, pp.phase);
                st = sb + pp.stage * W_STAGE;
                mbar_wait(bars + B_STGFREE + wg * 8, stg_phase); stg_phase ^= 1;
#pragma unroll
                for (int i = 0; i < 32; i++) qf[i] = qf[32 + i];
#pragma unroll 1
                for (int bx = 0; bx < 2; bx++) {
                    float o[8][4];
                    uint32_t vm[8], v0[4][4], v1[4][4];
#pragma unroll
                    for (int ep = 0; ep < 4; ep++) {
                        ldsm2t(vm[2 * ep], vm[2 * ep + 1], st + moff + bx * 4096 + (vch ^ (ep << 5)));
                        const uint32_t va = st + xoff + (l8 >> 1) * 1024 + bx * 16384 + (vch ^ (ep << 5));
                        ldsm4t(v0[ep][0], v0[ep][1], v0[ep][2], v0[ep][3], va);
                        ldsm4t(v1[ep][0], v1[ep][1], v1[ep][2], v1[ep][3], va + 2048);
                    }
#pragma unroll
                    for (int n = 0; n < 8; n++) { o[n][0] = o[n][1] = o[n][2] = o[n][3] = 0.f; mma16816(o[n], p0[0], p1[0], p0[1], p1[1], vm[n], v0[n >> 1][n & 1]); }
#pragma unroll
                    for (int n = 0; n < 8; n++) mma16816(o[n], p0[2], p1[2], p0[3], p1[3], v0[n >> 1][2 + (n & 1)], v1[n >> 1][n & 1]);
#pragma unroll
                    for (int n = 0; n < 8; n++) mma1688(o[n], p0[4], p1[4], v1[n >> 1][2 + (n & 1)]);
#pragma unroll
                    for (int ep = 0; ep < 4; ep++)
                        stsm4(stg_base + bx * 8192 + (sx ^ (ep << 5)),
                              pack2(o[2 * ep][0] * i0, o[2 * ep][1] * i0), pack2(o[2 * ep][2] * i1, o[2 * ep][3] * i1),
                              pack2(o[2 * ep + 1][0] * i0, o[2 * ep + 1][1] * i0), pack2(o[2 * ep + 1][2] * i1, o[2 * ep + 1][3] * i1));
                }
                __syncwarp();
                if (lane == 0) mbar_arrive(bars + B_EMPTY + pp.stage * 8);
                pipe_next(pp);
                if (hh == 0) { fence_async_smem(); bar_arrive(NB_ST + wg, 160); }
            }
        } else if (type == J_UP) {
            mbar_wait(bars + B_STGFREE + wg * 8, stg_phase); stg_phase ^= 1;
#pragma unroll
            for (int j = 0; j < 8; j++) {
                uint32_t r[4];
#pragma unroll
                for (int q = 0; q < 4; q++) {
                    const uint32_t gw = pack2(acc[8 * j + 2 * q], acc[8 * j + 2 * q + 1]);
                    const uint32_t uw = pack2(acc[64 + 8 * j + 2 * q], acc[64 + 8 * j + 2 * q + 1]);
                    r[q] = hmul2(pack2(gelu_tanh(bflo(gw)), gelu_tanh(bfhi(gw))), uw);
                }
                stsm4(stg_base + (j >> 2) * 8192 + (sx ^ ((2 * j & 7) << 4)), r[0], r[1], r[2], r[3]);
            }
        } else {
#pragma unroll
            for (int rd = 0; rd < 2; rd++) {
                mbar_wait(bars + B_STGFREE + wg * 8, stg_phase); stg_phase ^= 1;
#pragma unroll
                for (int j = rd * 8; j < rd * 8 + 8; j++)
                    stsm4(stg_base + ((j >> 2) & 1) * 8192 + (sx ^ ((2 * j & 7) << 4)),
                          pack2(acc[8 * j], acc[8 * j + 1]), pack2(acc[8 * j + 2], acc[8 * j + 3]),
                          pack2(acc[8 * j + 4], acc[8 * j + 5]), pack2(acc[8 * j + 6], acc[8 * j + 7]));
                if (rd == 0) { fence_async_smem(); bar_arrive(NB_ST + wg, 160); }
            }
        }
        fence_async_smem();
        CTR(5);
        bar_arrive(NB_ST + wg, 160);
    }
}

__global__ void __launch_bounds__(384, 1) k_work(const __grid_constant__ Params p) {
    extern __shared__ __align__(1024) unsigned char smem_raw[];
    const uint32_t sb = smem_u32(smem_raw);
    if (sb & 1023) __trap();
    const int warp = __shfl_sync(~0u, threadIdx.x >> 5, 0);
    int lane; asm volatile("mov.u32 %0, %%laneid;" : "=r"(lane));
    if (threadIdx.x == 0) {
        const uint32_t bars = sb + SM_BAR;
        for (int i = 0; i < W_NST; i++) { mbar_init(bars + B_FULL + i * 8, 1); mbar_init(bars + B_EMPTY + i * 8, 8); }
        mbar_init(bars + B_STGFREE, 1); mbar_init(bars + B_STGFREE + 8, 1); mbar_init(bars + B_REQ, 1); mbar_init(bars + B_RSP, 1);
        asm volatile("fence.mbarrier_init.release.cluster;" ::: "memory");
    }
    __syncthreads();
    if (warp < 8) {
        asm volatile("setmaxnreg.inc.sync.aligned.u32 224;");
        consumer(p, sb, warp, lane);
    } else {
        asm volatile("setmaxnreg.dec.sync.aligned.u32 56;");
        if (warp == 8) { if (lane == 0) producer(p, sb); }
        else if (warp < 11) store_warp(p, sb, warp - 9, lane);
        else scheduler(p, sb, lane);
        __syncwarp();
        bar_sync(NB_W0, 128);
        if (warp == 8 && p.qmask == 0xff) {
            unsigned last = 0;
            if (lane == 0) { __threadfence(); last = atomicAdd(&g_flags[F_DONE], 1u) == gridDim.x - 1; }
            if (__shfl_sync(~0u, last, 0))
                for (int i = lane; i < F_TOTAL; i += 32) g_flags[i] = 0;
        }
    }
}

typedef CUresult (*EncodeFn)(CUtensorMap*, CUtensorMapDataType, cuuint32_t, void*, const cuuint64_t*, const cuuint64_t*,
                             const cuuint32_t*, const cuuint32_t*, CUtensorMapInterleave, CUtensorMapSwizzle,
                             CUtensorMapL2promotion, CUtensorMapFloatOOBfill);

static void make_map(EncodeFn enc, CUtensorMap* m, const void* ptr, uint64_t rows, uint64_t cols, uint32_t box_rows) {
    cuuint64_t dims[2] = {cols, rows};
    cuuint64_t strides[1] = {cols * 2};
    cuuint32_t box[2] = {64, box_rows};
    cuuint32_t es[2] = {1, 1};
    enc(m, CU_TENSOR_MAP_DATA_TYPE_BFLOAT16, 2, const_cast<void*>(ptr), dims, strides, box, es, CU_TENSOR_MAP_INTERLEAVE_NONE,
        CU_TENSOR_MAP_SWIZZLE_128B, CU_TENSOR_MAP_L2_PROMOTION_L2_256B, CU_TENSOR_MAP_FLOAT_OOB_FILL_NONE);
}
template <typename T> static void* sym_addr(T& sym) { void* p = nullptr; cudaGetSymbolAddress(&p, sym); return p; }

extern "C" void kernel_launch(void* const* d_in, const int* in_sizes, int n_in, void* d_out, int out_size) {
    static Params prm;
    static RecParams rp;
    static bool ready = false;
    static const void* key[14];
    bool same = ready;
    for (int i = 0; i < 13 && same; i++) same = key[i] == d_in[i];
    same = same && key[13] == d_out;
    if (!same) {
        void* fn = nullptr;
        cudaDriverEntryPointQueryResult qr;
        cudaGetDriverEntryPoint("cuTensorMapEncodeTiled", &fn, cudaEnableDefault, &qr);
        EncodeFn enc = (EncodeFn)fn;
        make_map(enc, &prm.tm_h, sym_addr(g_h), S_, D_, 64);
        make_map(enc, &prm.tm_kv, sym_addr(g_kv), S_, 2 * HD_, 64);
        make_map(enc, &prm.tm_kvm, sym_addr(g_kvm), NSEG * 8, 2 * HD_, 32);
        make_map(enc, &prm.tm_o, sym_addr(g_o), S_, HD_, 64);
        make_map(enc, &prm.tm_op, sym_addr(g_op), OP_ROWS, D_, 64);
        make_map(enc, &prm.tm_h2, sym_addr(g_h2), S_, D_, 64);
        make_map(enc, &prm.tm_act, sym_addr(g_act), S_, DF_, 64);
        make_map(enc, &prm.tm_x1, sym_addr(g_x1), S_, D_, 64);
        make_map(enc, &prm.tm_out, d_out, S_, D_, 64);
        make_map(enc, &prm.tm_wq, d_in[2], D_, HD_, 64);
        make_map(enc, &prm.tm_wk, d_in[3], D_, HD_, 64);
        make_map(enc, &prm.tm_wv, d_in[4], D_, HD_, 64);
        make_map(enc, &prm.tm_wo, d_in[5], HD_, D_, 64);
        make_map(enc, &prm.tm_wg, d_in[8], D_, DF_, 64);
        make_map(enc, &prm.tm_wu, d_in[9], D_, DF_, 64);
        make_map(enc, &prm.tm_wd, d_in[10], DF_, D_, 64);
        prm.x = (const bf16*)d_in[0]; prm.c = (const bf16*)d_in[11]; prm.w_mod = (const bf16*)d_in[12];
        rp.mem0 = (const bf16*)d_in[1]; rp.x = prm.x; rp.c = prm.c; rp.w_mod = prm.w_mod;
        rp.wq = (const bf16*)d_in[2]; rp.wk = (const bf16*)d_in[3]; rp.wv = (const bf16*)d_in[4]; rp.wo = (const bf16*)d_in[5];
        cudaFuncSetAttribute(k_work, cudaFuncAttributeMaxDynamicSharedMemorySize, SMEM_BYTES);
        cudaFuncSetAttribute(k_rec, cudaFuncAttributeMaxDynamicSharedMemorySize, R_SMEM);
        cudaFuncSetAttribute(k_rec, cudaFuncAttributeNonPortableClusterSizeAllowed, 1);
        {
            cudaLaunchConfig_t cfg = {};
            cfg.gridDim = dim3(128); cfg.blockDim = dim3(384); cfg.dynamicSmemBytes = R_SMEM;
            cudaLaunchAttribute at[1];
            at[0].id = cudaLaunchAttributeClusterDimension; at[0].val.clusterDim.x = 16; at[0].val.clusterDim.y = 1; at[0].val.clusterDim.z = 1;
            cfg.attrs = at; cfg.numAttrs = 1;
            int n = 0;
            cudaOccupancyMaxActiveClusters(&n, k_rec, &cfg);
            rp.ncl = n < 4 ? 4 : (n > 8 ? 8 : n);
        }
        for (int i = 0; i < 13; i++) key[i] = d_in[i];
        key[13] = d_out;
        ready = true;
    }
    cudaStream_t st = cudaStreamPerThread;
    auto launch_rec = [&]() {
        cudaLaunchConfig_t cfg = {};
        cfg.gridDim = dim3(16 * rp.ncl); cfg.blockDim = dim3(384); cfg.dynamicSmemBytes = R_SMEM; cfg.stream = st;
        cudaLaunchAttribute at[1];
        at[0].id = cudaLaunchAttributeClusterDimension; at[0].val.clusterDim.x = 16; at[0].val.clusterDim.y = 1; at[0].val.clusterDim.z = 1;
        cfg.attrs = at; cfg.numAttrs = 1;
        cudaLaunchKernelEx(&cfg, k_rec, rp);
    };
    auto launch_work = [&](int qmask, int pdl) {
        prm.qmask = qmask;
        cudaLaunchConfig_t cfg = {};
        cfg.gridDim = dim3(132); cfg.blockDim = dim3(384); cfg.dynamicSmemBytes = SMEM_BYTES; cfg.stream = st;
        cudaLaunchAttribute at[1];
        at[0].id = cudaLaunchAttributeProgrammaticStreamSerialization; at[0].val.programmaticStreamSerializationAllowed = 1;
        cfg.attrs = at; cfg.numAttrs = pdl;
        cudaLaunchKernelEx(&cfg, k_work, prm);
    };
    launch_rec();
    launch_work(0xff, 1);
}
```

```cpp
#include <cuda_runtime.h>
#include <cuda_bf16.h>
#include <cuda.h>
#include <stdint.h>

typedef __nv_bfloat16 bf16;
#define IDLE_NS 150
#define FLAG_NS 20

constexpr int S_ = 2048, D_ = 512, H_ = 32, DH_ = 128, HD_ = 4096, NSEG = 64, DF_ = 1792;
constexpr int NRB = 16;
constexpr int OSPLIT = 4;

__device__ __align__(1024) bf16 g_h[S_ * D_];
__device__ __align__(1024) bf16 g_kv[S_ * 2 * HD_];
__device__ __align__(1024) bf16 g_kvm[NSEG * 8 * 2 * HD_];
__device__ __align__(1024) bf16 g_o[S_ * HD_];
#define FINE_RB_ 12
constexpr int FINE_RB = FINE_RB_;
#define OSPLIT2_ 8
constexpr int OSPLIT2 = OSPLIT2_;
constexpr int OP_ROWS = OSPLIT * S_ + OSPLIT2 * (NRB - FINE_RB) * 128;
__device__ __align__(1024) bf16 g_op[OP_ROWS * D_];
__device__ __align__(1024) bf16 g_x1[S_ * D_];
__device__ __align__(1024) bf16 g_h2[S_ * D_];
__device__ __align__(1024) bf16 g_act[S_ * DF_];
__device__ __align__(1024) bf16 g_mod[6 * D_];
__device__ uint32_t g_Fraw[131072 + 65536 + 2048];
#define g_F ((uint32_t*)(((uint64_t)g_Fraw + 0x7FFFFull) & ~0x7FFFFull))
constexpr int F_H = 0, F_MEM = 32, F_O = 64, F_OP = 96, F_H2 = 128, F_ACT = 160, F_MOD = 192, F_KV = 224, F_CLAIM = 256  ,
              F_SIDE = 512  , F_DONE = 576, F_TOTAL = 608;
__device__ __align__(128) unsigned int g_flags[F_TOTAL];
#define TR(j, i) do {} while (0)

__device__ __forceinline__ uint32_t smem_u32(const void* p) { return (uint32_t)__cvta_generic_to_shared(p); }
__device__ __forceinline__ uint32_t clk32() { uint32_t c; asm volatile("mov.u32 %0, %%clock;" : "=r"(c)); return c; }
__device__ __forceinline__ uint32_t mapa_u32(uint32_t addr, uint32_t rank) {
    uint32_t r; asm volatile("mapa.shared::cluster.u32 %0, %1, %2;" : "=r"(r) : "r"(addr), "r"(rank)); return r;
}
__device__ __forceinline__ void mbar_init(uint32_t bar, uint32_t cnt) {
    asm volatile("mbarrier.init.shared::cta.b64 [%0], %1;" :: "r"(bar), "r"(cnt) : "memory");
}
__device__ __forceinline__ void mbar_inval(uint32_t bar) {
    asm volatile("mbarrier.inval.shared::cta.b64 [%0];" :: "r"(bar) : "memory");
}
__device__ __forceinline__ void mbar_expect_tx(uint32_t bar, uint32_t bytes) {
    asm volatile("mbarrier.arrive.expect_tx.shared::cta.b64 _, [%0], %1;" :: "r"(bar), "r"(bytes) : "memory");
}
__device__ __forceinline__ void mbar_arrive(uint32_t bar) {
    asm volatile("mbarrier.arrive.shared::cta.b64 _, [%0];" :: "r"(bar) : "memory");
}
__device__ __forceinline__ bool mbar_try_wait(uint32_t bar, uint32_t parity) {
    uint32_t ok;
    asm volatile("{\n.reg .pred p;\nmbarrier.try_wait.parity.shared::cta.b64 p, [%1], %2;\nselp.u32 %0, 1, 0, p;\n}"
                 : "=r"(ok) : "r"(bar), "r"(parity) : "memory");
    return ok;
}
__device__ __forceinline__ bool mbar_try_wait_cluster(uint32_t bar, uint32_t parity) {
    uint32_t ok;
    asm volatile("{\n.reg .pred p;\nmbarrier.try_wait.parity.acquire.cluster.shared::cta.b64 p, [%1], %2;\nselp.u32 %0, 1, 0, p;\n}"
                 : "=r"(ok) : "r"(bar), "r"(parity) : "memory");
    return ok;
}
constexpr int SPIN_LIMIT = 1 << 18;
#define TIMEOUT(code, info) do {} while (0)
__device__ __forceinline__ void mbar_wait(uint32_t bar, uint32_t parity) {
    int g = 0;
#pragma unroll 1
    while (!mbar_try_wait(bar, parity)) { if (++g >= SPIN_LIMIT) { TIMEOUT(0, bar & 255); break; } }
}
__device__ __forceinline__ void mbar_wait_cluster(uint32_t bar, uint32_t parity) {
    int g = 0;
#pragma unroll 1
    while (!mbar_try_wait_cluster(bar, parity)) { if (++g >= SPIN_LIMIT) { TIMEOUT(1, bar & 255); break; } }
}
__device__ __forceinline__ void bar_sync(int id, int n) { asm volatile("bar.sync %0, %1;" :: "r"(id), "r"(n) : "memory"); }
__device__ __forceinline__ void bar_arrive(int id, int n) { asm volatile("bar.arrive %0, %1;" :: "r"(id), "r"(n) : "memory"); }
__device__ __forceinline__ void cluster_sync_all() {
    asm volatile("barrier.cluster.arrive.aligned;\nbarrier.cluster.wait.aligned;" ::: "memory");
}
__device__ __forceinline__ void st_async_v2(uint32_t addr, float a, float b, uint32_t bar) {
    asm volatile("st.async.weak.shared::cluster.mbarrier::complete_tx::bytes.v2.f32 [%0], {%1,%2}, [%3];"
                 :: "r"(addr), "f"(a), "f"(b), "r"(bar) : "memory");
}
__device__ __forceinline__ void st_async_v4(uint32_t addr, uint4 v, uint32_t bar) {
    asm volatile("st.async.weak.shared::cluster.mbarrier::complete_tx::bytes.v4.b32 [%0], {%1,%2,%3,%4}, [%5];"
                 :: "r"(addr), "r"(v.x), "r"(v.y), "r"(v.z), "r"(v.w), "r"(bar) : "memory");
}
__device__ __forceinline__ uint2 ldg_relaxed2(const uint2* p) {
    uint2 v;
    asm volatile("ld.relaxed.gpu.global.v2.b32 {%0,%1}, [%2];" : "=r"(v.x), "=r"(v.y) : "l"(p) : "memory");
    return v;
}
__device__ __forceinline__ void stg_relaxed2(uint2* p, uint2 v) {
    asm volatile("st.relaxed.gpu.global.v2.b32 [%0], {%1,%2};" :: "l"(p), "r"(v.x), "r"(v.y) : "memory");
}
__device__ __forceinline__ uint4 ldg_relaxed(const uint4* p) {
    uint4 v;
    asm volatile("ld.relaxed.gpu.global.v4.b32 {%0,%1,%2,%3}, [%4];" : "=r"(v.x), "=r"(v.y), "=r"(v.z), "=r"(v.w) : "l"(p) : "memory");
    return v;
}
__device__ __forceinline__ void stg_relaxed(uint4* p, uint4 v) {
    asm volatile("st.relaxed.gpu.global.v4.b32 [%0], {%1,%2,%3,%4};" :: "l"(p), "r"(v.x), "r"(v.y), "r"(v.z), "r"(v.w) : "memory");
}
__device__ __forceinline__ void stg_relaxed32(uint32_t* p, uint32_t v) {
    asm volatile("st.relaxed.gpu.global.b32 [%0], %1;" :: "l"(p), "r"(v) : "memory");
}
__device__ __forceinline__ uint32_t ldg_relaxed32(const uint32_t* p) {
    uint32_t v; asm volatile("ld.relaxed.gpu.global.b32 %0, [%1];" : "=r"(v) : "l"(p) : "memory"); return v;
}
__device__ __forceinline__ unsigned int ld_acquire(const unsigned int* p) {
    unsigned int v; asm volatile("ld.acquire.gpu.global.u32 %0, [%1];" : "=r"(v) : "l"(p) : "memory"); return v;
}
__device__ __forceinline__ void red_release(unsigned int* p, unsigned int v) {
    asm volatile("red.release.gpu.global.add.u32 [%0], %1;" :: "l"(p), "r"(v) : "memory");
}
__device__ __forceinline__ void wait_flag(int idx, unsigned int target) {
    const unsigned int* p = &g_flags[idx];
    int g = 0;
#pragma unroll 1
    while (ld_acquire(p) < target) { __nanosleep(FLAG_NS); if (++g >= 64 * SPIN_LIMIT) { TIMEOUT(2, idx); break; } }
}
__device__ __forceinline__ void cp_async16(uint32_t dst, const void* src) {
    asm volatile("cp.async.cg.shared.global [%0], [%1], 16;" :: "r"(dst), "l"(src) : "memory");
}
__device__ __forceinline__ void cp_async_commit() { asm volatile("cp.async.commit_group;" ::: "memory"); }
template <int N> __device__ __forceinline__ void cp_async_wait() { asm volatile("cp.async.wait_group %0;" :: "n"(N) : "memory"); }
__device__ __forceinline__ void ldsm4(uint32_t& r0, uint32_t& r1, uint32_t& r2, uint32_t& r3, uint32_t addr) {
    asm volatile("ldmatrix.sync.aligned.m8n8.x4.shared.b16 {%0,%1,%2,%3}, [%4];" : "=r"(r0), "=r"(r1), "=r"(r2), "=r"(r3) : "r"(addr) : "memory");
}
__device__ __forceinline__ void ldsm4t(uint32_t& r0, uint32_t& r1, uint32_t& r2, uint32_t& r3, uint32_t addr) {
    asm volatile("ldmatrix.sync.aligned.m8n8.x4.trans.shared.b16 {%0,%1,%2,%3}, [%4];" : "=r"(r0), "=r"(r1), "=r"(r2), "=r"(r3) : "r"(addr) : "memory");
}
__device__ __forceinline__ void ldsm2t(uint32_t& r0, uint32_t& r1, uint32_t addr) {
    asm volatile("ldmatrix.sync.aligned.m8n8.x2.trans.shared.b16 {%0,%1}, [%2];" : "=r"(r0), "=r"(r1) : "r"(addr) : "memory");
}
__device__ __forceinline__ void stsm4(uint32_t addr, uint32_t r0, uint32_t r1, uint32_t r2, uint32_t r3) {
    asm volatile("stmatrix.sync.aligned.m8n8.x4.shared.b16 [%0], {%1,%2,%3,%4};" :: "r"(addr), "r"(r0), "r"(r1), "r"(r2), "r"(r3) : "memory");
}
__device__ __forceinline__ void stsm2t(uint32_t addr, uint32_t r0, uint32_t r1) {
    asm volatile("stmatrix.sync.aligned.m8n8.x2.trans.shared.b16 [%0], {%1,%2};" :: "r"(addr), "r"(r0), "r"(r1) : "memory");
}
__device__ __forceinline__ void mma16816(float* d, uint32_t a0, uint32_t a1, uint32_t a2, uint32_t a3, uint32_t b0, uint32_t b1) {
    asm volatile("mma.sync.aligned.m16n8k16.row.col.f32.bf16.bf16.f32 {%0,%1,%2,%3}, {%4,%5,%6,%7}, {%8,%9}, {%0,%1,%2,%3};"
                 : "+f"(d[0]), "+f"(d[1]), "+f"(d[2]), "+f"(d[3]) : "r"(a0), "r"(a1), "r"(a2), "r"(a3), "r"(b0), "r"(b1));
}
__device__ __forceinline__ void mma1688(float* d, uint32_t a0, uint32_t a1, uint32_t b0) {
    asm volatile("mma.sync.aligned.m16n8k8.row.col.f32.bf16.bf16.f32 {%0,%1,%2,%3}, {%4,%5}, {%6}, {%0,%1,%2,%3};"
                 : "+f"(d[0]), "+f"(d[1]), "+f"(d[2]), "+f"(d[3]) : "r"(a0), "r"(a1), "r"(b0));
}
__device__ __forceinline__ void mma16816h(float* d, uint32_t a0, uint32_t a2, uint32_t b0, uint32_t b1) {
    asm volatile("{\n.reg .b32 ju, jv;\nmma.sync.aligned.m16n8k16.row.col.f32.bf16.bf16.f32 {%0,%1,%2,%3}, {%4,ju,%5,jv}, {%6,%7}, {%0,%1,%2,%3};\n}"
                 : "+f"(d[0]), "+f"(d[1]), "+f"(d[2]), "+f"(d[3]) : "r"(a0), "r"(a2), "r"(b0), "r"(b1));
}
__device__ __forceinline__ void mma1688h(float* d, uint32_t a0, uint32_t b0) {
    asm volatile("{\n.reg .b32 ju;\nmma.sync.aligned.m16n8k8.row.col.f32.bf16.bf16.f32 {%0,%1,%2,%3}, {%4,ju}, {%5}, {%0,%1,%2,%3};\n}"
                 : "+f"(d[0]), "+f"(d[1]), "+f"(d[2]), "+f"(d[3]) : "r"(a0), "r"(b0));
}
__device__ __forceinline__ uint32_t pack2(float lo, float hi) {
    uint32_t r; asm("cvt.rn.bf16x2.f32 %0, %1, %2;" : "=r"(r) : "f"(hi), "f"(lo)); return r;
}
__device__ __forceinline__ float bflo(uint32_t w) { return __uint_as_float(w << 16); }
__device__ __forceinline__ float bfhi(uint32_t w) { return __uint_as_float(w & 0xffff0000u); }
__device__ __forceinline__ float rbf(float x) { return __bfloat162float(__float2bfloat16_rn(x)); }
__device__ __forceinline__ float ex2(float x) { float y; asm("ex2.approx.ftz.f32 %0, %1;" : "=f"(y) : "f"(x)); return y; }
__device__ __forceinline__ void sts128(uint32_t addr, uint4 v) {
    asm volatile("st.shared.v4.b32 [%0], {%1,%2,%3,%4};" :: "r"(addr), "r"(v.x), "r"(v.y), "r"(v.z), "r"(v.w) : "memory");
}
__device__ __forceinline__ uint4 lds128(uint32_t addr) {
    uint4 v; asm volatile("ld.shared.v4.b32 {%0,%1,%2,%3}, [%4];" : "=r"(v.x), "=r"(v.y), "=r"(v.z), "=r"(v.w) : "r"(addr) : "memory"); return v;
}
__device__ __forceinline__ float2 lds64f(uint32_t addr) {
    float2 v; asm volatile("ld.shared.v2.f32 {%0,%1}, [%2];" : "=f"(v.x), "=f"(v.y) : "r"(addr) : "memory"); return v;
}
__device__ __forceinline__ float lds32f(uint32_t addr) {
    float v; asm volatile("ld.shared.f32 %0, [%1];" : "=f"(v) : "r"(addr) : "memory"); return v;
}
__device__ __forceinline__ uint32_t lds32(uint32_t addr) {
    uint32_t v; asm volatile("ld.shared.b32 %0, [%1];" : "=r"(v) : "r"(addr) : "memory"); return v;
}
__device__ __forceinline__ void sts32(uint32_t addr, uint32_t v) { asm volatile("st.shared.b32 [%0], %1;" :: "r"(addr), "r"(v) : "memory"); }
__device__ __forceinline__ void sts64f(uint32_t addr, float a, float b) { asm volatile("st.shared.v2.f32 [%0], {%1,%2};" :: "r"(addr), "f"(a), "f"(b) : "memory"); }

__device__ __forceinline__ void tma_load2d(uint32_t dst, const CUtensorMap* tm, int c0, int c1, uint32_t bar) {
    asm volatile("cp.async.bulk.tensor.2d.shared::cluster.global.mbarrier::complete_tx::bytes [%0], [%1, {%3, %4}], [%2];"
                 :: "r"(dst), "l"(tm), "r"(bar), "r"(c0), "r"(c1) : "memory");
}
__device__ __forceinline__ void tma_store2d(const CUtensorMap* tm, uint32_t src, int c0, int c1) {
    asm volatile("cp.async.bulk.tensor.2d.global.shared::cta.bulk_group [%0, {%2, %3}], [%1];"
                 :: "l"(tm), "r"(src), "r"(c0), "r"(c1) : "memory");
}
__device__ __forceinline__ void bulk_commit() { asm volatile("cp.async.bulk.commit_group;" ::: "memory"); }
__device__ __forceinline__ void bulk_wait0() { asm volatile("cp.async.bulk.wait_group 0;" ::: "memory"); }
__device__ __forceinline__ void fence_async_smem() { asm volatile("fence.proxy.async.shared::cta;" ::: "memory"); }
__device__ __forceinline__ void fence_async_all() { asm volatile("fence.proxy.async;" ::: "memory"); }

__device__ __forceinline__ void wg_fence() { asm volatile("wgmma.fence.sync.aligned;" ::: "memory"); }
__device__ __forceinline__ void wg_commit() { asm volatile("wgmma.commit_group.sync.aligned;" ::: "memory"); }
__device__ __forceinline__ void wg_wait0() { asm volatile("wgmma.wait_group.sync.aligned 0;" ::: "memory"); }
__device__ __forceinline__ uint64_t mkdesc(uint32_t saddr, uint32_t lbo, uint32_t sbo) {
    return (uint64_t)((saddr & 0x3FFFF) >> 4) | ((uint64_t)(lbo >> 4) << 16) | ((uint64_t)(sbo >> 4) << 32) | (1ull << 62);
}
#define ACC8(i) "+f"(d[i]), "+f"(d[i + 1]), "+f"(d[i + 2]), "+f"(d[i + 3]), "+f"(d[i + 4]), "+f"(d[i + 5]), "+f"(d[i + 6]), "+f"(d[i + 7])
__device__ __forceinline__ void wgmma_n256(float* d, uint64_t da, uint64_t db, int scale_d) {
    asm volatile(
        "{\n.reg .pred p;\nsetp.ne.b32 p, %130, 0;\n"
        "wgmma.mma_async.sync.aligned.m64n256k16.f32.bf16.bf16 "
        "{%0,%1,%2,%3,%4,%5,%6,%7,%8,%9,%10,%11,%12,%13,%14,%15,%16,%17,%18,%19,%20,%21,%22,%23,%24,%25,%26,%27,%28,%29,%30,%31,"
        "%32,%33,%34,%35,%36,%37,%38,%39,%40,%41,%42,%43,%44,%45,%46,%47,%48,%49,%50,%51,%52,%53,%54,%55,%56,%57,%58,%59,%60,%61,%62,%63,"
        "%64,%65,%66,%67,%68,%69,%70,%71,%72,%73,%74,%75,%76,%77,%78,%79,%80,%81,%82,%83,%84,%85,%86,%87,%88,%89,%90,%91,%92,%93,%94,%95,"
        "%96,%97,%98,%99,%100,%101,%102,%103,%104,%105,%106,%107,%108,%109,%110,%111,%112,%113,%114,%115,%116,%117,%118,%119,%120,%121,%122,%123,%124,%125,%126,%127}, "
        "%128, %129, p, 1, 1, 0, 1;\n}"
        : ACC8(0), ACC8(8), ACC8(16), ACC8(24), ACC8(32), ACC8(40), ACC8(48), ACC8(56),
          ACC8(64), ACC8(72), ACC8(80), ACC8(88), ACC8(96), ACC8(104), ACC8(112), ACC8(120)
        : "l"(da), "l"(db), "r"(scale_d));
}
__device__ __forceinline__ void wgmma_n128(float* d, uint64_t da, uint64_t db, int scale_d) {
    asm volatile(
        "{\n.reg .pred p;\nsetp.ne.b32 p, %66, 0;\n"
        "wgmma.mma_async.sync.aligned.m64n128k16.f32.bf16.bf16 "
        "{%0,%1,%2,%3,%4,%5,%6,%7,%8,%9,%10,%11,%12,%13,%14,%15,%16,%17,%18,%19,%20,%21,%22,%23,%24,%25,%26,%27,%28,%29,%30,%31,"
        "%32,%33,%34,%35,%36,%37,%38,%39,%40,%41,%42,%43,%44,%45,%46,%47,%48,%49,%50,%51,%52,%53,%54,%55,%56,%57,%58,%59,%60,%61,%62,%63}, "
        "%64, %65, p, 1, 1, 0, 1;\n}"
        : ACC8(0), ACC8(8), ACC8(16), ACC8(24), ACC8(32), ACC8(40), ACC8(48), ACC8(56)
        : "l"(da), "l"(db), "r"(scale_d));
}

__device__ __forceinline__ void wgmma_n64(float* d, uint64_t da, uint64_t db) {
    asm volatile(
        "wgmma.mma_async.sync.aligned.m64n64k16.f32.bf16.bf16 "
        "{%0,%1,%2,%3,%4,%5,%6,%7,%8,%9,%10,%11,%12,%13,%14,%15,%16,%17,%18,%19,%20,%21,%22,%23,%24,%25,%26,%27,%28,%29,%30,%31}, "
        "%32, %33, 1, 1, 1, 0, 1;"
        : ACC8(0), ACC8(8), ACC8(16), ACC8(24)
        : "l"(da), "l"(db));
}
__device__ __forceinline__ void wgmma_n8_ta(float* d, uint64_t da, uint64_t db, int scale_d) {
    asm volatile(
        "{\n.reg .pred p;\nsetp.ne.b32 p, %6, 0;\n"
        "wgmma.mma_async.sync.aligned.m64n8k16.f32.bf16.bf16 {%0,%1,%2,%3}, %4, %5, p, 1, 1, 1, 0;\n}"
        : "+f"(d[0]), "+f"(d[1]), "+f"(d[2]), "+f"(d[3]) : "l"(da), "l"(db), "r"(scale_d));
}

__device__ __forceinline__ uint32_t hadd2(uint32_t a, uint32_t b) { uint32_t r; asm("add.rn.bf16x2 %0, %1, %2;" : "=r"(r) : "r"(a), "r"(b)); return r; }
__device__ __forceinline__ uint32_t hsub2(uint32_t a, uint32_t b) { uint32_t r; asm("sub.rn.bf16x2 %0, %1, %2;" : "=r"(r) : "r"(a), "r"(b)); return r; }
__device__ __forceinline__ uint32_t hmul2(uint32_t a, uint32_t b) { uint32_t r; asm("mul.rn.bf16x2 %0, %1, %2;" : "=r"(r) : "r"(a), "r"(b)); return r; }
__device__ __forceinline__ void load_mod8(const bf16* m, int lane, uint32_t* v) {
    const uint4 a = __ldcg((const uint4*)m + lane), b = __ldcg((const uint4*)m + 32 + lane);
    v[0] = a.x; v[1] = a.y; v[2] = a.z; v[3] = a.w; v[4] = b.x; v[5] = b.y; v[6] = b.z; v[7] = b.w;
}
__device__ __forceinline__ void ln_stats(const uint32_t* x, uint32_t& mu2, float& rden) {
    float s = 0.f;
#pragma unroll
    for (int i = 0; i < 8; i++) s += bflo(x[i]) + bfhi(x[i]);
#pragma unroll
    for (int o = 16; o > 0; o >>= 1) s += __shfl_xor_sync(~0u, s, o);
    const float mean = s * (1.f / D_);
    float q = 0.f;
#pragma unroll
    for (int i = 0; i < 8; i++) { const float d0 = bflo(x[i]) - mean, d1 = bfhi(x[i]) - mean; q = fmaf(d0, d0, q); q = fmaf(d1, d1, q); }
#pragma unroll
    for (int o = 16; o > 0; o >>= 1) q += __shfl_xor_sync(~0u, q, o);
    mu2 = pack2(mean, mean);
    rden = __frcp_rn(rbf(__fsqrt_rn(rbf(rbf(q * (1.f / D_)) + 1e-5f))));
}
__device__ __forceinline__ void ln_apply(const uint32_t* x, uint32_t mu2, float rden, const uint32_t* c1, const uint32_t* sm, uint32_t* r) {
#pragma unroll
    for (int i = 0; i < 8; i++) {
        const uint32_t d = hsub2(x[i], mu2);
        r[i] = hadd2(hmul2(pack2(bflo(d) * rden, bfhi(d) * rden), c1[i]), sm[i]);
    }
}

struct __align__(64) Params {
    CUtensorMap tm_h, tm_kv, tm_kvm, tm_o, tm_op, tm_h2, tm_act, tm_x1, tm_out;
    CUtensorMap tm_wq, tm_wk, tm_wv, tm_wo, tm_wg, tm_wu, tm_wd;
    const bf16 *x, *c, *w_mod;
    int qmask;
};

constexpr int R_NST = 3;
constexpr uint32_t R_WV = 0, R_MEM = 65536, R_KX = 73728, R_VX = R_KX + R_NST * 4096,
                   R_KMS = R_VX + R_NST * 4096  , R_VMS = R_KMS + 1024,
                   R_QS = R_KMS + 4096, R_OS = R_QS + 1024, R_SX = R_OS + 1024, R_BAR = R_SX + 2560,
                   R_RS = 107520  , R_VP = R_RS + 8192  ,
                   R_STG = R_VP + 8192  , R_SMEM = R_STG + 98304;
static_assert((R_KMS & 4095) == 0, "smem");
static_assert(R_BAR + 64 <= R_RS, "smem");
constexpr uint32_t RB_SX = R_BAR, RB_V = R_BAR + 8, RB_E = R_BAR + 16, RB_A = R_BAR + 24, RB_ROLE = R_BAR + 32, RB_A1 = R_BAR + 40;
constexpr int W_NST = 4;
constexpr uint32_t W_STAGE = 49152, W_STG = W_NST * W_STAGE  , W_END = W_STG + 32768;
constexpr uint32_t SM_BAR = W_END;
constexpr uint32_t SMEM_BYTES = W_END + 1024 + 2048;
constexpr uint32_t B_FULL = 0, B_EMPTY = 32, B_STGFREE = 64, B_REQ = 80, B_RSP = 88, B_NEXT = 96, B_RING = 128;
#define PICK_AHEAD 3

constexpr int NB_X = 11  , NB_Y = 1, NB_M = 5, NB_K = 5, NB_B = 2, NB_C = 3, NB_D = 4, NB_W0 = 6  , NB_ST = 9  ;

__device__ __forceinline__ int pos_of_d(int d) {
    const int rem = d & 31;
    return (d & ~31) + ((rem & 7) >> 1) * 8 + (rem & 1) * 4 + (rem >> 3);
}

#define PROF(i) do {} while (0)
#define PROFG(i) do {} while (0)
#define OPAQUE(x) asm volatile("" : "+r"(x))
#define FENCE_SCHED(x) do { if ((x) == 0u) asm volatile("trap;"); } while (0)
#define QKVAR 2
#define VK0_ 4
constexpr int VK0 = VK0_;
constexpr int NOFF = 8;
#define VDELAY -1
#define POLL_GAP 110

struct RecParams { const bf16 *mem0, *wq, *wk, *wv, *wo, *x, *c, *w_mod; int ncl, only_pre; };

__device__ __forceinline__ void rec_qk(const RecParams& p, const uint32_t sb, const int cta, const int warp, int lane, const int sel) {
    const int crank = cta & 15, cl = cta >> 4, rank = cta & 1;
    const int kh = warp >> 2, aa = warp & 3;
    uint32_t wa[2][16][4];
    const uint32_t stg = sb + R_STG + kh * 32768;
    {
        const int t128 = aa * 32 + lane;
        const int row = (lane >> 4) * 8 + (lane & 7);
        const int ch = t128 & 7;
        const size_t goff = (size_t)kh * 256 * HD_ + cta * 64 + ch * 8;
#pragma unroll 4
        for (int dd = 0; dd < 16; dd++) {
            const int d = dd * 16 + (t128 >> 3), pp = pos_of_d(d);
            cp_async16(sb + R_WV + kh * 32768 + pp * 128 + ((ch ^ (pp & 7)) << 4), p.wv + goff + (size_t)d * HD_);
        }
        cp_async_commit();
#pragma unroll 4
        for (int dd = 0; dd < 16; dd++) {
            const int d = dd * 16 + (t128 >> 3), pp = pos_of_d(d);
            cp_async16(stg + pp * 128 + ((ch ^ (pp & 7)) << 4), p.wq + goff + (size_t)d * HD_);
        }
        cp_async_commit();
        {
            const int i0 = (warp * 32 + lane) * 16, tok = i0 >> 9;
            const uint4 m0 = __ldg((const uint4*)(p.mem0 + i0)), m1 = __ldg((const uint4*)(p.mem0 + i0 + 8));
            const uint32_t mw[8] = {m0.x, m0.y, m0.z, m0.w, m1.x, m1.y, m1.z, m1.w};
#pragma unroll
            for (int e = 0; e < 16; e++) {
                const int pp = pos_of_d((i0 & 511) + e);
                const unsigned short v = (unsigned short)(mw[e >> 1] >> ((e & 1) * 16));
                asm volatile("st.shared.u16 [%0], %1;" :: "r"(sb + R_MEM + (pp >> 3) * 128 + tok * 16 + (pp & 7) * 2), "h"(v) : "memory");
            }
        }
        cp_async_wait<1>();
        bar_sync(NB_W0 + kh, 128);
        const uint32_t fv = row * 128 + (((2 * aa + ((lane >> 3) & 1)) ^ (row & 7)) << 4);
#pragma unroll
        for (int ks = 0; ks < 16; ks++) ldsm4t(wa[0][ks][0], wa[0][ks][1], wa[0][ks][2], wa[0][ks][3], sb + R_WV + kh * 32768 + fv + ks * 2048);
        bar_sync(NB_W0 + kh, 128);
#pragma unroll
        for (int ks = 0; ks < 16; ks++)
            sts128(sb + R_WV + kh * 32768 + (aa * 16 + ks) * 512 + lane * 16, make_uint4(wa[0][ks][0], wa[0][ks][1], wa[0][ks][2], wa[0][ks][3]));
        const uint32_t fo = stg + row * 128 + (((4 * (aa & 1) + ((lane >> 3) & 1)) ^ (row & 7)) << 4);
#pragma unroll 1
        for (int m = 0; m < 2; m++) {
            cp_async_wait<0>();
            bar_sync(NB_W0 + kh, 128);
            if ((aa >> 1) == m) {
#pragma unroll
                for (int ks = 0; ks < 16; ks++) {
                    ldsm4t(wa[0][ks][0], wa[0][ks][1], wa[0][ks][2], wa[0][ks][3], fo + ks * 2048);
                    ldsm4t(wa[1][ks][0], wa[1][ks][1], wa[1][ks][2], wa[1][ks][3], (fo ^ 32) + ks * 2048);
                }
            }
            bar_sync(NB_W0 + kh, 128);
            if (m == 0) {
#pragma unroll 4
                for (int dd = 0; dd < 16; dd++) {
                    const int d = dd * 16 + (t128 >> 3), pp = pos_of_d(d);
                    cp_async16(stg + pp * 128 + ((ch ^ (pp & 7)) << 4), p.wk + goff + (size_t)d * HD_);
                }
                cp_async_commit();
            }
        }
    }
    const uint32_t tab = stg + (aa * 32 + lane) * 16;
    {
        const uint32_t l7 = lane & 7, l8 = lane >> 3, g = lane >> 2, t = lane & 3;
        const uint32_t t0 = l7 * 128 + ((l8 ^ l7) << 4);
        const uint32_t tq = l7 * 128 + (((l8 >> 1) ^ l7) << 4);
        const uint32_t bq = warp >> 1, tp = warp & 1;
        uint4 v;
        v.x = sb + (aa < 2 ? R_QS : R_KMS) + l7 * 128 + (((4 * (aa & 1) + 2 * kh + (l8 & 1)) ^ l7) << 4);
        v.y = sb + R_QS + tq;
        v.z = sb + (warp == 0 ? R_KMS : R_KX + (warp - 1) * 1024) + t0;
        v.w = mapa_u32(sb + R_SX + (rank * 5 + warp) * 256 + lane * 8, crank ^ 1);
        sts128(tab, v);
        sts128(tab + 2048, make_uint4(sb + lane * 16 + R_MEM + kh * 4096, sb + lane * 16 + R_WV + warp * 8192,
                                      sb + lane * 16 + R_VP + warp * 512, sb + lane * 16 + R_VP + 4096 + (warp ^ 4) * 512));
        const uint32_t src = (l8 >> 1) * 8 + l7;
        const uint32_t L = bq * 8 + 2 * tp + (l8 & 1);
        const uint32_t d0 = (crank + ((t >> 1) | (g & 6))) & 15;
        v.x = sb + R_RS + src * 512 + ((L ^ (src & 7)) << 4);
        v.y = mapa_u32(sb + R_MEM + (crank * 4 + bq) * 128 + (4 * tp + 2 * (t & 1) + (g & 1)) * 16, d0);
        v.z = mapa_u32(sb + ((crank & 2) ? RB_A1 : RB_A), d0);
        v.w = lane;
        sts128(tab + 4096, v);
        const uint32_t item = 2 * (t & 1) + (g & 1);
        const uint64_t rd = (uint64_t)(g_F + ((crank * 2 + ((crank ^ (crank >> 3) ^ sel) & 1)) * 1024 + warp * 128 + item * 8));
        sts128(tab + 6144, make_uint4((uint32_t)rd, (uint32_t)(rd >> 32), (uint32_t)(cl * 128 + (4 * (t >> 1) + (g >> 1)) * 4), 0));
#pragma unroll
        for (int i = 0; i < NOFF; i++)
            sts128(tab + 10240 + i * 2048, make_uint4(wa[i & 1][i >> 1][0], wa[i & 1][i >> 1][1], wa[i & 1][i >> 1][2], wa[i & 1][i >> 1][3]));
    }
    bar_sync(NB_D, 384);
    uint32_t slot_off = 0;
    const uint32_t slot_inc = warp == 0 ? 2048 : 4096, slot_last = warp == 0 ? 2048 : (R_NST - 1) * 4096;
    const uint32_t sx_bar_rem = (sb + RB_SX) ^ (1u << 24);
    uint4 tb = lds128(tab + 2048);
#pragma unroll 1
    for (int s = 0; s < NSEG; s++) {
        if (s > 0) mbar_wait(sb + RB_A, (s - 1) & 1);
        if (warp == 0) { PROF(0); PROFG(13); }
        uint4 ta;
        const uint32_t km_tog = aa >= 2 ? (s & 1) * 2048 : 0;
        {
            float acc[5][4];
#pragma unroll
            for (int c = 0; c < 5; c++) { acc[c][0] = acc[c][1] = acc[c][2] = acc[c][3] = 0.f; }
            uint32_t b[8][4];
            uint4 av[16];
            static_assert(VK0 == 4, "order below assumes the V/O warps cover slices 0,1");
#define QK4(k2) do { \
                mma16816(acc[0], wa[0][2 * (k2)][0], wa[0][2 * (k2)][1], wa[0][2 * (k2)][2], wa[0][2 * (k2)][3], b[k2][0], b[k2][1]); \
                mma16816(acc[1], wa[1][2 * (k2)][0], wa[1][2 * (k2)][1], wa[1][2 * (k2)][2], wa[1][2 * (k2)][3], b[k2][0], b[k2][1]); \
                mma16816(acc[3], wa[0][2 * (k2) + 1][0], wa[0][2 * (k2) + 1][1], wa[0][2 * (k2) + 1][2], wa[0][2 * (k2) + 1][3], b[k2][2], b[k2][3]); \
                mma16816(acc[4], wa[1][2 * (k2) + 1][0], wa[1][2 * (k2) + 1][1], wa[1][2 * (k2) + 1][2], wa[1][2 * (k2) + 1][3], b[k2][2], b[k2][3]); } while (0)
#define V2(k2) do { \
                mma16816(acc[2], av[2 * (k2)].x, av[2 * (k2)].y, av[2 * (k2)].z, av[2 * (k2)].w, b[k2][0], b[k2][1]); \
                mma16816(acv, av[2 * (k2) + 1].x, av[2 * (k2) + 1].y, av[2 * (k2) + 1].z, av[2 * (k2) + 1].w, b[k2][2], b[k2][3]); } while (0)
#define LB(k2) ldsm4(b[k2][0], b[k2][1], b[k2][2], b[k2][3], tb.x + (k2) * 512)
#define LV(k2) do { av[2 * (k2)] = lds128(tb.y + 2 * (k2) * 512); av[2 * (k2) + 1] = lds128(tb.y + (2 * (k2) + 1) * 512); } while (0)
            float acv[4] = {0.f, 0.f, 0.f, 0.f};
            LB(0); LB(1); LB(4); LB(5);
            QK4(0); QK4(1); LV(4); LV(5); QK4(4); QK4(5);
            if (s > 0) mbar_wait(sb + RB_A1, (s - 1) & 1);
            LB(2); LB(3); LB(6); LB(7); ta = lds128(tab);
            V2(4); V2(5); LV(2); LV(3);
            QK4(2); QK4(3); QK4(6); QK4(7);
            LV(6); LV(7);
#pragma unroll
            for (int i = 0; i < 4; i++) { acc[0][i] += acc[3][i]; acc[1][i] += acc[4][i]; }
            const float g0 = kh ? acc[0][0] : acc[1][0], g1 = kh ? acc[0][1] : acc[1][1], g2 = kh ? acc[0][2] : acc[1][2], g3 = kh ? acc[0][3] : acc[1][3];
            sts128(tb.w, make_uint4(__float_as_uint(g0), __float_as_uint(g1), __float_as_uint(g2), __float_as_uint(g3)));
            const float k0 = kh ? acc[1][0] : acc[0][0], k1 = kh ? acc[1][1] : acc[0][1], k2_ = kh ? acc[1][2] : acc[0][2], k3 = kh ? acc[1][3] : acc[0][3];
            if (warp == 0) PROF(1);
            V2(2); V2(3);
            bar_sync(NB_X + aa, 64);
            const uint4 o = lds128(tb.z + 4096);
            V2(6); V2(7);
            stsm2t(ta.x ^ km_tog, pack2(k0 + __uint_as_float(o.x), k1 + __uint_as_float(o.y)), pack2(k2_ + __uint_as_float(o.z), k3 + __uint_as_float(o.w)));
            sts128(tb.z, make_uint4(__float_as_uint(acc[2][0] + acv[0]), __float_as_uint(acc[2][1] + acv[1]), __float_as_uint(acc[2][2] + acv[2]), __float_as_uint(acc[2][3] + acv[3])));
        }
        const uint32_t kb = ta.z + slot_off;
        if (warp == 0) PROF(14);
        bar_sync(NB_B, 256);
        if (warp < 5) {
            uint32_t q[16], k0, k1, k2, k3, k4, k5, k6, k7;
            float sa[4] = {0.f, 0.f, 0.f, 0.f}, sc[4] = {0.f, 0.f, 0.f, 0.f};
            ldsm4(q[0], q[1], q[2], q[3], ta.y);
            ldsm4(k0, k1, k2, k3, kb);
            ldsm4(q[4], q[5], q[6], q[7], ta.y ^ 32);
            ldsm4(q[8], q[9], q[10], q[11], ta.y ^ 64);
            ldsm4(k4, k5, k6, k7, kb ^ 64);
            ldsm4(q[12], q[13], q[14], q[15], ta.y ^ 96);
            mma16816(sa, q[0], q[1], q[2], q[3], k0, k1);
            bar_arrive(NB_Y, 288);
            mma16816(sc, q[4], q[5], q[6], q[7], k2, k3);
            mma16816(sa, q[8], q[9], q[10], q[11], k4, k5);
            mma16816(sc, q[12], q[13], q[14], q[15], k6, k7);
            const float scl = 0.08838834764831845f * 1.4426950408889634f;
            const float r0 = (sa[0] + sc[0]) * scl, r1 = (sa[1] + sc[1]) * scl;
            if (s != NSEG - 1) {
                st_async_v2(ta.w, r0, r1, sx_bar_rem);
                st_async_v2(ta.w ^ (1u << 24), r0, r1, sx_bar_rem ^ (1u << 24));
            }
            if (warp == 0) PROF(2);
        } else if (s > 0 && warp == 7 && lane == 0) {
            mbar_expect_tx(sb + RB_A, 4096);
            mbar_expect_tx(sb + RB_A1, 4096);
        } else if (s > 0 && (s & 3) == 0 && warp == 6) {
            bar_sync(NB_K, 160);
            if (lane == 0) red_release(&g_flags[F_MEM + (s >> 2) - 1], 1);
            __syncwarp();
        }
        if (s == NSEG - 1) {
            const uint4 td = lds128(tab + 6144);
            stg_relaxed32((uint32_t*)(((uint64_t)td.y << 32) | ((td.x ^ 0x21000) + td.z)), 0u);
            break;
        }
        slot_off = slot_off == slot_last ? 0 : slot_off + slot_inc;
        const uint4 tc = lds128(tab + 4096), td = lds128(tab + 6144);
        const uint4* rd = (const uint4*)(((uint64_t)td.y << 32) | (td.x ^ ((s & 1) * 0x21000)));
        uint32_t* wr = (uint32_t*)((const char*)rd + td.z);
        const uint32_t tag = ((s >> 1) + 1) & 1;
        mbar_wait(sb + RB_E, s & 1);
        if (warp == 0) PROF(7);
        {
            uint32_t a0, a1, a2, a3, a4, a5, a6, a7;
            ldsm4t(a0, a1, a2, a3, tc.x);
            ldsm4t(a4, a5, a6, a7, tc.x ^ 64);
            const uint32_t one = 0x3F803F80u;
            float d0_[4] = {0.f, 0.f, 0.f, 0.f}, d1_[4] = {0.f, 0.f, 0.f, 0.f};
            mma16816(d0_, a0, a1, a2, a3, one, one);
            mma16816(d1_, a4, a5, a6, a7, one, one);
            const bool t1 = tc.w & 1, t2 = tc.w & 2;
            const float x = t2 ? (t1 ? d1_[2] : d1_[0]) : (t1 ? d0_[2] : d0_[0]);
            const uint32_t own = (__float_as_uint(x) & ~1u) | tag;
            stg_relaxed32(wr, own);
            const uint32_t tq = clk32();
            if (warp == 0) PROF(8);
            PROFG(16 + warp);
            while ((int)(clk32() - tq) < POLL_GAP) {}
            uint4 f[8];
#pragma unroll
            for (int i = 0; i < 8; i++) f[i] = ldg_relaxed(rd + (i >> 1) * 8 + (i & 1));
            int gg = 0;
#pragma unroll 1
            while (true) {
                uint32_t an = ~0u, orr = 0;
#pragma unroll
                for (int i = 0; i < 8; i++) { an &= f[i].x & f[i].y & f[i].z & f[i].w; orr |= f[i].x | f[i].y | f[i].z | f[i].w; }
                if (__all_sync(~0u, (((tag ? an : ~orr) & 1) != 0))) break;
#pragma unroll
                for (int i = 0; i < 8; i++) f[i] = ldg_relaxed(rd + (i >> 1) * 8 + (i & 1));
                if (++gg > 16 * SPIN_LIMIT) { TIMEOUT(3, s); break; }
            }
            if (warp == 0) PROF(9);
#define S4(c, h) ((__uint_as_float(f[h].c) + __uint_as_float(f[2 + h].c)) + (__uint_as_float(f[4 + h].c) + __uint_as_float(f[6 + h].c)))
            const uint4 item = make_uint4(pack2(S4(x, 0), S4(y, 0)), pack2(S4(z, 0), S4(w, 0)), pack2(S4(x, 1), S4(y, 1)), pack2(S4(z, 1), S4(w, 1)));
            st_async_v4(tc.y, item, tc.z);
            st_async_v4(tc.y ^ (8u << 24), item, tc.z ^ (8u << 24));
#pragma unroll
            for (int i = 0; i < NOFF; i++) {
                const uint4 f0 = lds128(tab + 10240 + i * 2048);
                wa[i & 1][i >> 1][0] = f0.x; wa[i & 1][i >> 1][1] = f0.y; wa[i & 1][i >> 1][2] = f0.z; wa[i & 1][i >> 1][3] = f0.w;
            }
            tb = lds128(tab + 2048);
            if (tc.w == 0 && warp == 7) mbar_expect_tx(sb + RB_E, 8192);
            if (warp == 0) PROF(10);
            PROF(40 + warp);
        }
        bar_sync(NB_D, 384);
    }
}

__device__ __forceinline__ void rec_load_kv(uint32_t sb, int col0, int s, uint32_t slot_off, int t128) {
    const int row = t128 >> 2, c2 = (t128 & 3) * 2;
    const bf16* src = g_kv + ((size_t)(s * 32 + row) * (2 * HD_) + col0 + c2 * 8);
    const uint32_t d0 = sb + R_KX + slot_off + row * 128 + ((c2 ^ (row & 7)) << 4);
    cp_async16(d0, src);
    cp_async16(d0 ^ 16, src + 8);
    cp_async16(d0 + (R_VX - R_KX), src + HD_);
    cp_async16((d0 ^ 16) + (R_VX - R_KX), src + HD_ + 8);
}

__device__ __forceinline__ void rec_store_kvm(uint32_t sb, int col0, int s, int w, int lane) {
    const int tok = (w & 1) * 4 + (lane >> 3);
    const uint4 v = lds128(sb + R_KMS + (s & 1) * 2048 + (w >> 1) * 1024 + tok * 128 + (((lane & 7) ^ tok) << 4));
    *(uint4*)(g_kvm + ((s * 8 + tok) * (2 * HD_) + (w >> 1) * HD_ + col0 + (lane & 7) * 8)) = v;
}

__device__ __forceinline__ void rec_vo(const RecParams& p, const uint32_t sb, const int cta, const int warp, int lane) {
    const int w = warp - 8, crank = cta & 15;
    const int col0 = cta * 64;
    uint32_t wo[8][4][4];
    {
        const int t128 = w * 32 + lane;
        const bf16* Wo = p.wo + (size_t)col0 * D_;
        const uint32_t stg = sb + R_STG + 2 * 32768;
#pragma unroll
        for (int half = 0; half < 2; half++) {
#pragma unroll 4
            for (int i = t128; i < 2048; i += 128) {
                const int e = i >> 6, ch = i & 63;
                cp_async16(stg + e * 1024 + ((ch ^ (e & 7)) << 4), Wo + (size_t)(half * 32 + e) * D_ + ch * 8);
            }
            cp_async_commit();
            cp_async_wait<0>();
            bar_sync(NB_W0 + 2, 128);
#pragma unroll
            for (int j = 0; j < 8; j++)
#pragma unroll
                for (int kk = 0; kk < 2; kk++) {
                    const int e = kk * 16 + (lane >> 4) * 8 + (lane & 7);
                    const int ch = (w * 8 + j) * 2 + ((lane >> 3) & 1);
                    ldsm4t(wo[j][half * 2 + kk][0], wo[j][half * 2 + kk][1], wo[j][half * 2 + kk][2], wo[j][half * 2 + kk][3],
                           stg + e * 1024 + ((ch ^ (e & 7)) << 4));
                }
            bar_sync(NB_W0 + 2, 128);
        }
        if (lane == 0) wait_flag(F_KV + 0, 64);
        __syncwarp();
        rec_load_kv(sb, col0, 0, 0, t128); cp_async_commit();
        rec_load_kv(sb, col0, 1, 4096, t128); cp_async_commit();
        cp_async_wait<1>();
    }
    const uint32_t tab = sb + R_STG + 2 * 32768 + (w * 32 + lane) * 16;
    {
        const uint32_t l7 = lane & 7, l8 = lane >> 3, g = lane >> 2;
        uint4 v;
        v.x = sb + R_VX + ((l8 & 1) * 8 + l7) * 128 + (((2 * w + (l8 >> 1)) ^ l7) << 4);
        v.y = sb + R_OS + g * 128 + (((2 * w) ^ g) << 4) + (lane & 3) * 4;
        v.z = sb + R_VMS + l7 * 128 + (((2 * w + (l8 & 1)) ^ l7) << 4);
        v.w = sb + R_OS + l7 * 128 + ((l8 ^ l7) << 4);
        sts128(tab, v);
        v.x = mapa_u32(sb + R_RS + crank * 512 + ((lane ^ (crank & 7)) << 4), w * 4);
        v.y = mapa_u32(sb + RB_E, w * 4);
        v.z = sb + R_VP + w * 512 + lane * 16;
        v.w = sb + R_SX + lane * 8;
        sts128(tab + 2048, v);
#pragma unroll
        for (int i = 0; i < 8; i++) sts128(tab + 4096 + i * 2048, make_uint4(wo[i][0][0], wo[i][0][1], wo[i][0][2], wo[i][0][3]));
        const int tok = (w & 1) * 4 + (lane >> 3), row = (w * 32 + lane) >> 2, c2 = (lane & 3) * 2;
        const uint64_t kd = (uint64_t)(g_kvm + (tok * (2 * HD_) + (w >> 1) * HD_ + col0 + (lane & 7) * 8));
        const uint64_t ks = (uint64_t)(g_kv + ((size_t)row * (2 * HD_) + col0 + c2 * 8));
        sts128(tab + 20480, make_uint4((uint32_t)kd, (uint32_t)(kd >> 32), (uint32_t)ks, (uint32_t)(ks >> 32)));
        sts128(tab + 22528, make_uint4(sb + R_KMS + (w >> 1) * 1024 + tok * 128 + (((lane & 7) ^ tok) << 4),
                                       sb + R_KX + row * 128 + ((c2 ^ (row & 7)) << 4), lane, 0));
    }
    bar_sync(NB_D, 384);
    const uint32_t lane16 = lds32(tab + 2048 + 8) - R_VP - w * 512;
    uint4 av[2 * VK0];
#pragma unroll
    for (int i = 0; i < 2 * VK0; i++) av[i] = lds128(lane16 + R_WV + (i / VK0) * 32768 + (w * 16 + i % VK0) * 512);
    uint32_t slot_off = 0;
#pragma unroll 1
    for (int s = 0; s < NSEG; s++) {
        if (s > 0) {
            mbar_wait(sb + RB_A, (s - 1) & 1);
            const uint4 tp = lds128(tab + 20480), tq = lds128(tab + 22528);
            const uint4 kvm = lds128(tq.x + ((s - 1) & 1) * 2048);
            *(uint4*)((((uint64_t)tp.y << 32) | tp.x) + (uint64_t)(s - 1) * (8 * 2 * HD_ * 2)) = kvm;
            if ((s & 3) == 0) bar_arrive(NB_K, 160);
            if (s + 1 < NSEG - 1) {
                if (((s + 1) & 3) == 0) { if (tq.z == 0) wait_flag(F_KV + ((s + 1) >> 2), 64); __syncwarp(); }
                const char* src = (const char*)((((uint64_t)tp.w << 32) | tp.z) + (uint64_t)(s + 1) * (32 * 2 * HD_ * 2));
                const uint32_t d0 = tq.y + (slot_off == (R_NST - 1) * 4096 ? 0 : slot_off + 4096);
                cp_async16(d0, src);
                cp_async16(d0 ^ 16, src + 16);
                cp_async16(d0 + (R_VX - R_KX), src + HD_ * 2);
                cp_async16((d0 ^ 16) + (R_VX - R_KX), src + HD_ * 2 + 16);
            }
            cp_async_commit();
        }
        bar_sync(NB_Y, 288);
        uint32_t vb0, vb1;
        {
            float va[4] = {0.f, 0.f, 0.f, 0.f}, vc[4] = {0.f, 0.f, 0.f, 0.f};
            uint32_t bb[VK0][4];
#pragma unroll
            for (int k2 = 0; k2 < VK0; k2++) ldsm4(bb[k2][0], bb[k2][1], bb[k2][2], bb[k2][3], lane16 + R_MEM + (k2 / (VK0 / 2)) * 4096 + (k2 % (VK0 / 2)) * 512);
#pragma unroll
            for (int k2 = 0; k2 < VK0; k2++) {
                mma16816(va, av[2 * k2].x, av[2 * k2].y, av[2 * k2].z, av[2 * k2].w, bb[k2][0], bb[k2][1]);
                mma16816(vc, av[2 * k2 + 1].x, av[2 * k2 + 1].y, av[2 * k2 + 1].z, av[2 * k2 + 1].w, bb[k2][2], bb[k2][3]);
            }
            const uint4 a = lds128(lane16 + R_VP + w * 512), b = lds128(lane16 + R_VP + 2048 + w * 512);
            vb0 = pack2((va[0] + vc[0]) + (__uint_as_float(a.x) + __uint_as_float(b.x)), (va[1] + vc[1]) + (__uint_as_float(a.y) + __uint_as_float(b.y)));
            vb1 = pack2((va[2] + vc[2]) + (__uint_as_float(a.z) + __uint_as_float(b.z)), (va[3] + vc[3]) + (__uint_as_float(a.w) + __uint_as_float(b.w)));
        }
        const uint4 ta = lds128(tab), tb = lds128(tab + 2048);
        uint32_t vx[8];
        ldsm4t(vx[0], vx[1], vx[2], vx[3], ta.x + slot_off);
        ldsm4t(vx[4], vx[5], vx[6], vx[7], ta.x + slot_off + 2048);
#pragma unroll
        for (int i = 0; i < 4; i++) {
            const uint4 f0 = lds128(tab + 4096 + i * 2048);
            wo[i][0][0] = f0.x; wo[i][0][1] = f0.y; wo[i][0][2] = f0.z; wo[i][0][3] = f0.w;
        }
        if (w == 0) PROF(11);
        uint32_t pf[5];
        float oa[2][4] = {{0.f, 0.f, 0.f, 0.f}, {0.f, 0.f, 0.f, 0.f}}, ob_[2][4] = {{0.f, 0.f, 0.f, 0.f}, {0.f, 0.f, 0.f, 0.f}};
        float sm0[4] = {0.f, 0.f, 0.f, 0.f}, sm1[4] = {0.f, 0.f, 0.f, 0.f};
        if (s != NSEG - 1) {
            mbar_wait(sb + RB_SX, s & 1);
            if (w == 0) PROF(4);
            float sv[10];
#pragma unroll
            for (int n = 0; n < 5; n++) {
                const float2 a = lds64f(tb.w + n * 256), b = lds64f(tb.w + (5 + n) * 256);
                sv[2 * n] = a.x + b.x; sv[2 * n + 1] = a.y + b.y;
            }
            float mx = fmaxf(fmaxf(fmaxf(sv[0], sv[1]), fmaxf(sv[2], sv[3])), fmaxf(fmaxf(sv[4], sv[5]), fmaxf(sv[6], sv[7])));
            mx = fmaxf(mx, fmaxf(sv[8], sv[9]));
            mx = fmaxf(mx, __shfl_xor_sync(~0u, mx, 1));
            mx = fmaxf(mx, __shfl_xor_sync(~0u, mx, 2));
#pragma unroll
            for (int n = 1; n < 5; n++) pf[n] = pack2(ex2(sv[2 * n] - mx), ex2(sv[2 * n + 1] - mx));
            pf[0] = pack2(ex2(sv[0] - mx), ex2(sv[1] - mx));
            if (w == 0) PROF(12);
            const uint32_t one = 0x3F803F80u;
            mma16816h(sm0, pf[1], pf[2], one, one);
            mma16816h(oa[0], pf[1], pf[2], vx[0], vx[1]);
            mma16816h(oa[1], pf[1], pf[2], vx[2], vx[3]);
            mma16816h(sm1, pf[3], pf[4], one, one);
            mma16816h(ob_[0], pf[3], pf[4], vx[4], vx[5]);
            mma16816h(ob_[1], pf[3], pf[4], vx[6], vx[7]);
            mma1688h(sm0, pf[0], one);
            mma1688h(oa[0], pf[0], vb0);
            mma1688h(oa[1], pf[0], vb1);
            float inv;
            asm("rcp.approx.ftz.f32 %0, %1;" : "=f"(inv) : "f"(sm0[0] + sm1[0]));
            oa[0][0] += ob_[0][0]; oa[0][1] += ob_[0][1]; oa[1][0] += ob_[1][0]; oa[1][1] += ob_[1][1];
            sts32(ta.y, pack2(oa[0][0] * inv, oa[0][1] * inv));
            sts32(ta.y ^ 16, pack2(oa[1][0] * inv, oa[1][1] * inv));
            const uint32_t oa2 = ta.w ^ 64;
            bar_sync(NB_C, 128);
            if (w == 0) PROF(5);
            uint32_t ob[8];
            ldsm4(ob[0], ob[1], ob[2], ob[3], ta.w);
            ldsm4(ob[4], ob[5], ob[6], ob[7], oa2);
#pragma unroll
            for (int i = 4; i < 8; i++) {
                const uint4 f0 = lds128(tab + 4096 + i * 2048);
                wo[i][0][0] = f0.x; wo[i][0][1] = f0.y; wo[i][0][2] = f0.z; wo[i][0][3] = f0.w;
            }
#pragma unroll
            for (int jj = 0; jj < 2; jj++) {
                if (jj == 1 && tb.w == 0) break;
                float acc[4][4];
#pragma unroll
                for (int c = 0; c < 4; c++) { acc[c][0] = acc[c][1] = acc[c][2] = acc[c][3] = 0.f; }
#pragma unroll
                for (int ks = 0; ks < 4; ks++)
#pragma unroll
                    for (int c = 0; c < 4; c++)
                        mma16816(acc[c], wo[jj * 4 + c][ks][0], wo[jj * 4 + c][ks][1], wo[jj * 4 + c][ks][2], wo[jj * 4 + c][ks][3], ob[2 * ks], ob[2 * ks + 1]);
#pragma unroll
                for (int pr = 0; pr < 2; pr++) {
                    uint4 v;
                    v.x = pack2(acc[2 * pr][0], acc[2 * pr][1]);
                    v.y = pack2(acc[2 * pr][2], acc[2 * pr][3]);
                    v.z = pack2(acc[2 * pr + 1][0], acc[2 * pr + 1][1]);
                    v.w = pack2(acc[2 * pr + 1][2], acc[2 * pr + 1][3]);
                    st_async_v4(tb.x + ((jj * 2 + pr) << 24), v, tb.y + ((jj * 2 + pr) << 24));
                }
            }
            if (w == 0) PROF(6);
        }
        stsm2t(ta.z + (s & 1) * 2048, vb0, vb1);
        cp_async_wait<0>();
        bar_sync(NB_C, 128);
        if (w == 0 && lane == 0 && s != NSEG - 1) mbar_expect_tx(sb + RB_SX, 2560);
        if (s != NSEG - 1) bar_arrive(NB_D, 384);
#pragma unroll
        for (int i = 0; i < 2 * VK0; i++) av[i] = lds128(lane16 + R_WV + (i / VK0) * 32768 + (w * 16 + i % VK0) * 512);
        slot_off = slot_off == (R_NST - 1) * 4096 ? 0 : slot_off + 4096;
    }
    rec_store_kvm(sb, col0, NSEG - 1, w, lane);
    bar_sync(NB_C, 128);
    if (w == 0 && lane == 0) red_release(&g_flags[F_MEM + NRB - 1], 1);
}

__global__ void __launch_bounds__(384, 1) k_rec(const RecParams p) {
    extern __shared__ __align__(1024) unsigned char smem_raw[];
    const uint32_t sb = __shfl_sync(~0u, smem_u32(smem_raw), 0);
    const int warp = __shfl_sync(~0u, threadIdx.x >> 5, 0);
    int lane; asm volatile("mov.u32 %0, %%laneid;" : "=r"(lane));
    const int crank = blockIdx.x & 15, slot = blockIdx.x >> 4;
    asm volatile("griddepcontrol.launch_dependents;");
    if (threadIdx.x == 0) {
        mbar_init(sb + RB_SX, 1); mbar_init(sb + RB_E, 1); mbar_init(sb + RB_A, 1); mbar_init(sb + RB_A1, 1); mbar_init(sb + RB_ROLE, 1);
        asm volatile("fence.mbarrier_init.release.cluster;" ::: "memory");
        mbar_expect_tx(sb + RB_SX, 2560);
        mbar_expect_tx(sb + RB_E, 8192);
        mbar_expect_tx(sb + RB_A, 4096);
        mbar_expect_tx(sb + RB_A1, 4096);
        mbar_expect_tx(sb + RB_ROLE, 4);
    }
    if (warp >= 4) {
        const int w8 = warp - 4, nblk = gridDim.x;
        const int cq = lane & 3, rg = w8 * 8 + (lane >> 2);
        const uint32_t red = sb + R_STG;
        const int row0 = blockIdx.x * 8 + w8;
        const uint4* xr = (const uint4*)(p.x + (size_t)row0 * D_);
        uint4 xa = __ldg(xr + lane), xb = __ldg(xr + 32 + lane);
#pragma unroll 1
        for (int sl = blockIdx.x; sl < 96; sl += nblk) {
            uint4 wv[8];
#pragma unroll
            for (int i = 0; i < 8; i++) wv[i] = __ldg((const uint4*)(p.w_mod + (size_t)(rg * 8 + i) * (6 * D_) + sl * 32 + cq * 8));
            const uint32_t cw = __ldg((const uint32_t*)(p.c + rg * 8) + cq);
            const float cl = bflo(cw), ch = bfhi(cw);
            const uint32_t sw = pack2(__fdividef(cl, 1.f + __expf(-cl)), __fdividef(ch, 1.f + __expf(-ch)));
            float a[8];
#pragma unroll
            for (int i = 0; i < 8; i++) a[i] = 0.f;
#pragma unroll
            for (int i = 0; i < 8; i++) {
                const uint32_t sv = __shfl_sync(~0u, sw, (lane & 28) + (i >> 1));
                const float cv = (i & 1) ? bfhi(sv) : bflo(sv);
                a[0] = fmaf(cv, bflo(wv[i].x), a[0]); a[1] = fmaf(cv, bfhi(wv[i].x), a[1]); a[2] = fmaf(cv, bflo(wv[i].y), a[2]); a[3] = fmaf(cv, bfhi(wv[i].y), a[3]);
                a[4] = fmaf(cv, bflo(wv[i].z), a[4]); a[5] = fmaf(cv, bfhi(wv[i].z), a[5]); a[6] = fmaf(cv, bflo(wv[i].w), a[6]); a[7] = fmaf(cv, bfhi(wv[i].w), a[7]);
            }
#pragma unroll
            for (int i = 0; i < 8; i++) { a[i] += __shfl_xor_sync(~0u, a[i], 4); a[i] += __shfl_xor_sync(~0u, a[i], 8); a[i] += __shfl_xor_sync(~0u, a[i], 16); }
            if (lane < 4) {
                sts128(red + w8 * 128 + lane * 32, make_uint4(__float_as_uint(a[0]), __float_as_uint(a[1]), __float_as_uint(a[2]), __float_as_uint(a[3])));
                sts128(red + w8 * 128 + lane * 32 + 16, make_uint4(__float_as_uint(a[4]), __float_as_uint(a[5]), __float_as_uint(a[6]), __float_as_uint(a[7])));
            }
            bar_sync(NB_B, 256);
            if (w8 == 0) {
                float v = 0.f;
#pragma unroll
                for (int i = 0; i < 8; i++) v += lds32f(red + i * 128 + lane * 4);
                g_mod[sl * 32 + lane] = __float2bfloat16_rn(v);
                __syncwarp();
                if (lane == 0) red_release(&g_flags[F_MOD + (sl >= 32)], 1);
            }
            bar_sync(NB_B, 256);
        }
        uint32_t c1[8], sm[8];
#pragma unroll 1
        for (int row = row0; row < S_; row += nblk * 8) {
            const uint32_t v[8] = {xa.x, xa.y, xa.z, xa.w, xb.x, xb.y, xb.z, xb.w};
            if (row + nblk * 8 < S_) { xr += (size_t)nblk * 8 * (D_ / 8); xa = __ldg(xr + lane); xb = __ldg(xr + 32 + lane); }
            uint32_t mu2, r[8]; float rden;
            ln_stats(v, mu2, rden);
            if (row == row0) {
                if (lane == 0) wait_flag(F_MOD, 32);
                __syncwarp();
                load_mod8(g_mod + D_, lane, c1);
                load_mod8(g_mod, lane, sm);
#pragma unroll
                for (int i = 0; i < 8; i++) c1[i] = hadd2(c1[i], 0x3F803F80u);
            }
            ln_apply(v, mu2, rden, c1, sm, r);
            uint4* hr = (uint4*)(g_h + (size_t)row * D_);
            hr[lane] = make_uint4(r[0], r[1], r[2], r[3]); hr[32 + lane] = make_uint4(r[4], r[5], r[6], r[7]);
            bar_sync(NB_B, 256);
            if (w8 == (row >> 7 & 7) && lane == 0) red_release(&g_flags[F_H + (row >> 7)], 1);
            __syncwarp();
        }
    }
    if (p.only_pre) return;
    unsigned role = 0;
    if (crank == 0 && threadIdx.x == 0) {
        unsigned x = 0;
        int tm[2] = {0x7fffffff, 0x7fffffff};
#pragma unroll 1
        for (int i = 0; i < 6; i++) {
            const uint32_t t0 = clk32();
            x = atomicAdd(&g_F[65536 + (i & 1) * 1024 + slot * 64 + (x >> 31)], 0u) & 0x7fffffffu;
            if (x == 0x7654321u) sts32(sb + R_BAR + 56, x);
            const int dt = (int)(clk32() - t0);
            if (i >= 2) { if (i & 1) tm[1] = min(tm[1], dt); else tm[0] = min(tm[0], dt); }
        }
        const int side = tm[1] > tm[0];
        const unsigned old = atomicAdd(&g_flags[F_SIDE + side * 32], 1u);
        unsigned c0, c1; int gd = 0;
#pragma unroll 1
        do { c0 = ldg_relaxed32(&g_flags[F_SIDE]); c1 = ldg_relaxed32(&g_flags[F_SIDE + 32]); } while ((int)(c0 + c1) < p.ncl && ++gd < 64 * SPIN_LIMIT);
        const int big = c1 > c0;
        role = side == big ? old : (big ? c1 : c0) + old;
        role |= (big ^ 1) << 8;
    }
    __syncwarp();
    asm volatile("barrier.cluster.arrive.relaxed.aligned;\nbarrier.cluster.wait.aligned;" ::: "memory");
    if (crank == 0 && warp == 0) {
        role = __shfl_sync(~0u, role, 0);
        if (lane < 16)
            asm volatile("st.async.weak.shared::cluster.mbarrier::complete_tx::bytes.u32 [%0], %1, [%2];"
                         :: "r"(mapa_u32(sb + R_BAR + 48, lane)), "r"(role), "r"(mapa_u32(sb + RB_ROLE, lane)) : "memory");
    }
    mbar_wait(sb + RB_ROLE, 0);
    const int rolew = __shfl_sync(~0u, lds32(sb + R_BAR + 48), 0);
    const int cl = rolew & 255;
    if (cl >= 4) return;
    const int cta = cl * 16 + crank;
    if (warp < 8) rec_qk(p, sb, cta, warp, lane, rolew >> 8);
    else rec_vo(p, sb, cta, warp, lane);
}

enum { J_KV = 0, J_QA = 1, J_O = 2, J_LN = 3, J_UP = 4, J_DN = 5, J_LN1 = 6, J_MOD = 7, J_UP2 = 8, J_END = 9 };
constexpr int NJ_O = 2 * OSPLIT, NJ_O2 = 2 * OSPLIT2, NJ_LN = 8, NJ_LN2 = 16, NJ_UP = 14, NJ_UP2 = 28, NJ_DN = 8, NJ_LN1 = 8;
constexpr uint64_t pk8(int a, int b, int c, int d, int e, int f, int g, int h) {
    return (uint64_t)a | ((uint64_t)b << 8) | ((uint64_t)c << 16) | ((uint64_t)d << 24) | ((uint64_t)e << 32) | ((uint64_t)f << 40) | ((uint64_t)g << 48) | ((uint64_t)h << 56);
}
constexpr uint64_t NJ_C = pk8(32, 16, NJ_O, NJ_LN, NJ_UP, NJ_DN, 0, 0), NJ_F = pk8(32, 16, NJ_O2, NJ_LN2, NJ_UP2, NJ_DN, 0, 0);
constexpr uint64_t TG_C = pk8(2 * NJ_LN1, 64, 32, 2 * NJ_O, 2 * NJ_LN, 2 * NJ_UP, 32, 0), TG_F = pk8(2 * NJ_LN1, 64, 32, 2 * NJ_O2, 2 * NJ_LN2, 2 * NJ_UP2, 32, 0);
constexpr uint64_t PRIO = pk8(4, 10, 9, 8, 7, 6, 3, 0);
__device__ __forceinline__ int pick_job(int lane, int qmask, int& idx) {
    const int rb = lane & 15, half = lane >> 4;
    const uint64_t nj = (rb >= FINE_RB ? NJ_F : NJ_C) >> (8 * half);
    const uint64_t tg = (rb >= FINE_RB ? TG_F : TG_C) >> (8 * half);
    const unsigned* cp = &g_flags[F_CLAIM + half * 32 + rb];
    const unsigned* dp = &g_flags[half * 32 + rb];
    int gd = 0;
#pragma unroll 1
    while (true) {
        const unsigned c0 = ldg_relaxed32(cp), c1 = ldg_relaxed32(cp + 64), c2 = ldg_relaxed32(cp + 128);
        const unsigned d0 = ldg_relaxed32(dp - (half ? (rb >= FINE_RB ? 2 : (rb ? 1 : 0)) : 0)), d1 = ldg_relaxed32(dp + 64), d2 = ldg_relaxed32(dp + 128);
        const unsigned cl[3] = {c0, c1, c2}, dv[3] = {d0, d1, d2};
        unsigned key = 0xffffu, key2 = 0xffffu;
        bool pre = false;
#pragma unroll
        for (int i = 0; i < 3; i++) {
            const int q = half + 2 * i;
            const bool have = ((qmask >> q) & 1) && cl[i] < (unsigned)((nj >> (16 * i)) & 255);
            bool ready = have && dv[i] >= (unsigned)((tg >> (16 * i)) & 255);
            unsigned pr = (unsigned)((PRIO >> (8 * q)) & 255);
            if (i == 0 && rb <= 1 - half) ready = have;
            if (i == 0 && half && rb >= FINE_RB) pr = 5;
            if (ready) key = min(key, (pr << 8) | (rb << 4) | q);
            if (have) key2 = min(key2, rb >= FINE_RB ? (0x100u | (q << 4) | rb) : (i == 0 ? 0u : 0x1000u));
            pre |= have && i == 0 && !half;
        }
        const bool anypre = __any_sync(~0u, pre);
        if (anypre && (key & 15) == J_QA) key = 0xffffu;
        key = __reduce_min_sync(~0u, key);
        key2 = __reduce_min_sync(~0u, key2);
        if (key2 == 0xffffu) return J_END;
        int pq, prb;
        if (key != 0xffffu) { pq = key & 15; prb = (key >> 4) & 15; }
        else if (key2 >= 0x120u && key2 < 0x1000u) { pq = (key2 >> 4) & 15; prb = key2 & 15; }
        else {
            __nanosleep(IDLE_NS);
            if (++gd > 16 * SPIN_LIMIT) { TIMEOUT(5, 0); return J_END; }
            continue;
        }
        int c = 0;
        if (lane == 0) c = (int)atomicAdd(&g_flags[F_CLAIM + pq * 32 + prb], 1u);
        c = __shfl_sync(~0u, c, 0);
        if (c < (int)(((prb >= FINE_RB ? NJ_F : NJ_C) >> (8 * pq)) & 255)) {
            idx = pq * 512 + prb * 32 + c;
            int acq = 0;
            if (pq != J_QA && pq < J_LN1) {
                if (lane == 0 && ld_acquire(&g_flags[pq * 32 + prb]) >= (unsigned)(((prb >= FINE_RB ? TG_F : TG_C) >> (8 * pq)) & 255)) {
                    asm volatile("fence.proxy.async.global;" ::: "memory");
                    acq = 1 << 24;
                }
            }
            return (pq == J_UP && prb >= FINE_RB ? J_UP2 : pq) | (prb << 8) | (c << 16) | acq;
        }
    }
}
__device__ __forceinline__ int op_row(int rb, int split) {
    return rb < FINE_RB ? split * S_ + rb * 128 : OSPLIT * S_ + (split * (NRB - FINE_RB) + rb - FINE_RB) * 128;
}

struct Pipe { uint32_t stage, phase; };
__device__ __forceinline__ void pipe_next(Pipe& p) { if (++p.stage == W_NST) { p.stage = 0; p.phase ^= 1; } }

__device__ __forceinline__ void scheduler(const Params& p, uint32_t sb, int lane) {
    const uint32_t bars = sb + SM_BAR;
    uint32_t ph = 0;
#pragma unroll 1
    while (true) {
        mbar_wait(bars + B_REQ, ph);
        int j = 4095;
        const int jd = pick_job(lane, p.qmask, j);
        if (lane == 0) { sts32(bars + B_NEXT, (uint32_t)jd); sts32(bars + B_NEXT + 4, (uint32_t)j); mbar_arrive(bars + B_RSP); }
        ph ^= 1;
        if (jd == J_END) break;
        __syncwarp();
    }
}

__device__ __forceinline__ void producer(const Params& p, uint32_t sb) {
    Pipe pp{0, 1};
    const uint32_t bars = sb + SM_BAR;
    uint32_t seq = 0, h_seen = 0;
    mbar_arrive(bars + B_REQ);
#pragma unroll 1
    while (true) {
        mbar_wait(bars + B_RSP, seq & 1);
        const int jd = (int)lds32(bars + B_NEXT), j = (int)lds32(bars + B_NEXT + 4);
        int left = (jd & 255) == J_DN ? 15 : ((jd & 255) == J_QA ? 12 : ((jd & 255) == J_O ? (((jd >> 8) & 255) >= FINE_RB ? 64 / OSPLIT2 : 64 / OSPLIT) : ((jd & 255) == J_LN || (jd & 255) == J_LN1 || (jd & 255) == J_MOD ? 1 : 8)));
        left = max(left - PICK_AHEAD, 1);
        TR(j, 1);
        const int type = jd & 255, rb = (jd >> 8) & 255, cb = (jd >> 16) & 255;
        const bool fine = rb >= FINE_RB, acquired = (jd >> 24) & 1;
        bool first = true;
        auto begin_stage = [&](uint32_t bytes) -> uint32_t {
            mbar_wait(bars + B_EMPTY + pp.stage * 8, pp.phase);
            if (first) { sts32(bars + B_RING + (seq & 7) * 4, (uint32_t)jd); sts32(bars + B_RING + 32 + (seq & 7) * 4, (uint32_t)j); first = false; }
            const uint32_t fb = bars + B_FULL + pp.stage * 8;
            if (bytes) mbar_expect_tx(fb, bytes); else mbar_arrive(fb);
            if (--left == 0 && type != J_END) mbar_arrive(bars + B_REQ);
            return fb;
        };
        if (type == J_END || type == J_LN || type == J_LN1 || type == J_MOD) {
            if (type == J_LN) { if (!acquired) wait_flag(F_OP + rb, 2 * (fine ? NJ_O2 : NJ_O)); if (!(h_seen >> 31)) { wait_flag(F_MOD + 1, 64); h_seen |= 1u << 31; } }

            TR(j, 2);
            begin_stage(0); pipe_next(pp);
            seq++;
            if (type == J_END) break;
            continue;
        }
        const CUtensorMap *ta, *tb0, *tb1;
        int k0 = 0, nk = 8, n0 = cb * 256, n1 = n0 + 128, nb = 4, dep = -1;
        unsigned tgt = 0;
        switch (type) {
            case J_KV: ta = &p.tm_h; tb0 = tb1 = cb < 16 ? &p.tm_wk : &p.tm_wv; n0 = (cb & 15) * 256; n1 = n0 + 128; dep = F_H + rb; tgt = 2 * NJ_LN1; break;
            case J_QA: ta = &p.tm_h; tb0 = tb1 = &p.tm_wq; dep = F_H + rb; tgt = 2 * NJ_LN1; break;
            case J_O: ta = &p.tm_o; tb0 = tb1 = &p.tm_wo; n0 = (cb & 1) * 256; n1 = n0 + 128; nk = fine ? 64 / OSPLIT2 : 64 / OSPLIT; k0 = (cb >> 1) * nk * 64;
                      dep = F_O + rb; tgt = 32; break;
            case J_UP: ta = &p.tm_h2; tb0 = &p.tm_wg; tb1 = &p.tm_wu; n0 = n1 = cb * 128; dep = F_H2 + rb; tgt = 2 * NJ_LN; break;
            case J_UP2: ta = &p.tm_h2; tb0 = &p.tm_wg; tb1 = &p.tm_wu; n0 = n1 = cb * 64; nb = 2; dep = F_H2 + rb; tgt = 2 * NJ_LN2; break;
            default: ta = &p.tm_act; tb0 = tb1 = &p.tm_wd; n0 = cb * 64; nk = 0; break;
        }
        const int m0 = rb * 128;
        if (type == J_DN) {
#pragma unroll 1
            for (int kb = 0; kb < 14; kb++) {
                const uint32_t fb = begin_stage(49152);
                const uint32_t st = sb + pp.stage * W_STAGE;
                const int k = kb * 128;
                tma_load2d(st + 32768, tb0, n0, k, fb);
                tma_load2d(st + 40960, tb0, n0, k + 64, fb);
                if (kb == 0) { if (!acquired) { wait_flag(F_ACT + rb, 2 * (fine ? NJ_UP2 : NJ_UP)); asm volatile("fence.proxy.async.global;" ::: "memory"); } TR(j, 2); }
                tma_load2d(st, ta, k, m0, fb);
                tma_load2d(st + 8192, ta, k, m0 + 64, fb);
                tma_load2d(st + 16384, ta, k + 64, m0, fb);
                tma_load2d(st + 24576, ta, k + 64, m0 + 64, fb);
                pipe_next(pp);
            }
        }
#pragma unroll 1
        for (int kb = 0; kb < nk; kb++) {
            const uint32_t fb = begin_stage(16384 + nb * 8192);
            const uint32_t st = sb + pp.stage * W_STAGE;
            const int k = k0 + kb * 64;
            tma_load2d(st + 16384, tb0, n0, k, fb);
            if (nb == 4) {
                tma_load2d(st + 16384 + 8192, tb0, n0 + 64, k, fb);
                tma_load2d(st + 16384 + 16384, tb1, n1, k, fb);
                tma_load2d(st + 16384 + 24576, tb1, n1 + 64, k, fb);
            } else if (nb == 2) {
                tma_load2d(st + 16384 + 8192, tb1, n1, k, fb);
            }
            if (kb == 0) {
                if (acquired && dep < 16) h_seen |= 1u << dep;
                if (dep >= 0 && !acquired && !(dep < 16 && ((h_seen >> dep) & 1))) {
                    wait_flag(dep, tgt);
                    if (type != J_O) asm volatile("fence.proxy.async.global;" ::: "memory");
                    if (dep < 16) h_seen |= 1u << dep;
                }
                TR(j, 2);
            }
            tma_load2d(st, ta, k, m0, fb);
            tma_load2d(st + 8192, ta, k, m0 + 64, fb);
            pipe_next(pp);
        }
        if (type == J_QA) {
            wait_flag(F_KV + rb, 64);
#pragma unroll 1
            for (int i = 0; i < 4; i++) {
                const uint32_t fb = begin_stage(40960);
                const uint32_t st = sb + pp.stage * W_STAGE;
                const int col = (i & 1) * HD_ + (cb * 2 + (i >> 1)) * DH_;
                tma_load2d(st, &p.tm_kv, col, m0, fb);
                tma_load2d(st + 8192, &p.tm_kv, col, m0 + 64, fb);
                tma_load2d(st + 16384, &p.tm_kv, col + 64, m0, fb);
                tma_load2d(st + 24576, &p.tm_kv, col + 64, m0 + 64, fb);
                if (i == 0) { wait_flag(F_MEM + rb, 64); asm volatile("fence.proxy.async.global;" ::: "memory"); }
                tma_load2d(st + 32768, &p.tm_kvm, col, rb * 32, fb);
                tma_load2d(st + 36864, &p.tm_kvm, col + 64, rb * 32, fb);
                pipe_next(pp);
            }
        } else if (type == J_DN) {
            const uint32_t fb = begin_stage(16384);
            const uint32_t st = sb + pp.stage * W_STAGE;
            tma_load2d(st, &p.tm_x1, n0, m0, fb);
            tma_load2d(st + 8192, &p.tm_x1, n0, m0 + 64, fb);
            pipe_next(pp);
        }
        seq++;
    }
}

__device__ __forceinline__ void store_warp(const Params& p, uint32_t sb, int wg, int lane) {
    const uint32_t bars = sb + SM_BAR;
    uint32_t seq = 0;
#pragma unroll 1
    while (true) {
        bar_sync(NB_ST + wg, 160);
        const uint32_t jd = lds32(bars + B_RING + (seq & 7) * 4);
        seq++;
        const int type = jd & 255, rb = (jd >> 8) & 255, cb = (jd >> 16) & 255;
        if (type == J_END) break;
        const uint32_t src = sb + W_STG + wg * 16384;
        const CUtensorMap* tm = nullptr; int n0 = cb * 256, nbox = 4, mrow = rb * 128 + wg * 64, flag = 0;
        switch (type) {
            case J_KV: tm = &p.tm_kv; flag = F_KV + rb; break;
            case J_QA: tm = &p.tm_o; flag = F_O + rb; break;
            case J_O: tm = &p.tm_op; n0 = (cb & 1) * 256; mrow = op_row(rb, cb >> 1) + wg * 64; flag = F_OP + rb; break;
            case J_LN: flag = F_H2 + rb; nbox = 0; break;
            case J_LN1: flag = F_H + rb; nbox = 0; break;
            case J_MOD: flag = F_MOD + rb; nbox = 0; break;
            case J_UP: tm = &p.tm_act; n0 = cb * 128; nbox = 2; flag = F_ACT + rb; break;
            case J_UP2: tm = &p.tm_act; n0 = cb * 64; nbox = 1; flag = F_ACT + rb; break;
            default: tm = &p.tm_out; n0 = cb * 64; nbox = 1; flag = -1; break;
        }
        if (nbox == 4) {
            if (lane == 0) {
                tma_store2d(tm, src, n0, mrow);
                tma_store2d(tm, src + 8192, n0 + 64, mrow);
                bulk_commit();
                asm volatile("cp.async.bulk.wait_group.read 0;" ::: "memory");
                mbar_arrive(bars + B_STGFREE + wg * 8);
            }
            __syncwarp();
            bar_sync(NB_ST + wg, 160);
            n0 += 128; nbox = 2;
        }
        if (lane == 0) {
            if (nbox) {
                tma_store2d(tm, src, n0, mrow);
                if (nbox == 2) tma_store2d(tm, src + 8192, n0 + 64, mrow);
                bulk_commit();
                asm volatile("cp.async.bulk.wait_group.read 0;" ::: "memory");
                mbar_arrive(bars + B_STGFREE + wg * 8);
                bulk_wait0();
                if (flag >= 0) asm volatile("red.relaxed.gpu.global.add.u32 [%0], 1;" :: "l"(&g_flags[flag]) : "memory");
            } else {
                mbar_arrive(bars + B_STGFREE + wg * 8);
                red_release(&g_flags[flag], 1);
            }
        }
        __syncwarp();
    }
}

__device__ __forceinline__ float gelu_tanh(float x) {
    const float t = x * fmaf(-0.10294324397f, x * x, -2.30220819814f);
    float r; asm("rcp.approx.ftz.f32 %0, %1;" : "=f"(r) : "f"(1.f + ex2(t)));
    return x * r;
}

#define CTR(i) do {} while (0)

template <int NSPLIT>
__device__ __forceinline__ void ln2_row(const Params& p, int rb, int r, int lane) {
    const int row = rb * 128 + r;
    uint4 u[2 * NSPLIT];
#pragma unroll
    for (int sp = 0; sp < NSPLIT; sp++) {
        const uint4* src = (const uint4*)(g_op + (size_t)(op_row(rb, sp) + r) * D_);
        u[2 * sp] = __ldcg(src + lane); u[2 * sp + 1] = __ldcg(src + 32 + lane);
    }
    const uint4* xr = (const uint4*)(p.x + (size_t)row * D_);
    const uint4 xa = __ldg(xr + lane), xb = __ldg(xr + 32 + lane);
    uint32_t ga[8], c1[8], sm[8];
    load_mod8(g_mod + 2 * D_, lane, ga);
    load_mod8(g_mod + 4 * D_, lane, c1);
    load_mod8(g_mod + 3 * D_, lane, sm);
    float a[16];
#pragma unroll
    for (int i = 0; i < 16; i++) a[i] = 0.f;
#pragma unroll
    for (int sp = 0; sp < 2 * NSPLIT; sp++) {
        float* q = a + (sp & 1) * 8;
        q[0] += bflo(u[sp].x); q[1] += bfhi(u[sp].x); q[2] += bflo(u[sp].y); q[3] += bfhi(u[sp].y);
        q[4] += bflo(u[sp].z); q[5] += bfhi(u[sp].z); q[6] += bflo(u[sp].w); q[7] += bfhi(u[sp].w);
    }
    const uint32_t xv[8] = {xa.x, xa.y, xa.z, xa.w, xb.x, xb.y, xb.z, xb.w};
    uint32_t v[8], r8[8];
#pragma unroll
    for (int i = 0; i < 8; i++) v[i] = hadd2(xv[i], hmul2(ga[i], pack2(a[2 * i], a[2 * i + 1])));
    uint4* x1r = (uint4*)(g_x1 + (size_t)row * D_);
    x1r[lane] = make_uint4(v[0], v[1], v[2], v[3]); x1r[32 + lane] = make_uint4(v[4], v[5], v[6], v[7]);
    uint32_t mu2; float rden;
    ln_stats(v, mu2, rden);
#pragma unroll
    for (int i = 0; i < 8; i++) c1[i] = hadd2(c1[i], 0x3F803F80u);
    ln_apply(v, mu2, rden, c1, sm, r8);
    uint4* hr = (uint4*)(g_h2 + (size_t)row * D_);
    hr[lane] = make_uint4(r8[0], r8[1], r8[2], r8[3]); hr[32 + lane] = make_uint4(r8[4], r8[5], r8[6], r8[7]);
}

__device__ __forceinline__ void consumer(const Params& p, uint32_t sb, int warp, int lane) {
    const uint32_t bars = sb + SM_BAR;
    const int wg = warp >> 2, wl = warp & 3;
    const uint32_t l7 = lane & 7, l8 = lane >> 3, g = lane >> 2, t = lane & 3;
    Pipe pp{0, 0};
    uint32_t seq = 0, stg_phase = 1;
    const int srow = wl * 16 + l7 + (l8 & 1) * 8;
    const uint32_t stg_base = sb + W_STG + wg * 16384 + srow * 128;
    const uint32_t sx = ((lane >> 4) ^ (srow & 7)) << 4;
#pragma unroll 1
    while (true) {
        mbar_wait(bars + B_FULL + pp.stage * 8, pp.phase);
        const uint32_t jd = lds32(bars + B_RING + (seq & 7) * 4);
        CTR(3);
        seq++;
        const int type = jd & 255, rb = (jd >> 8) & 255, cb = (jd >> 16) & 255;
        if (type == J_END) { mbar_wait(bars + B_STGFREE + wg * 8, stg_phase); bar_arrive(NB_ST + wg, 160); break; }
        if (type == J_LN) {
            __syncwarp();
            if (lane == 0) mbar_arrive(bars + B_EMPTY + pp.stage * 8);
            pipe_next(pp);
            if (rb >= FINE_RB) ln2_row<OSPLIT2>(p, rb, cb * 8 + warp, lane);
            else {
#pragma unroll 1
                for (int rr = 0; rr < 2; rr++) ln2_row<OSPLIT>(p, rb, cb * 16 + warp * 2 + rr, lane);
            }
            mbar_wait(bars + B_STGFREE + wg * 8, stg_phase); stg_phase ^= 1;
            CTR(4); CTR(5);
            bar_arrive(NB_ST + wg, 160);
            continue;
        }
        if (type == J_DN || type == J_UP2) {
            float acc[64];
#pragma unroll
            for (int i = 0; i < 64; i++) acc[i] = 0.f;
            if (type == J_DN) {
#pragma unroll 1
                for (int kb = 0; kb < 14; kb++) {
                    if (kb) mbar_wait(bars + B_FULL + pp.stage * 8, pp.phase);
                    const uint32_t st = sb + pp.stage * W_STAGE;
                    const uint64_t da = mkdesc(st + wg * 8192, 16, 1024), db = mkdesc(st + 32768, 8192, 1024);
                    wg_fence();
#pragma unroll
                    for (int ks = 0; ks < 8; ks++) wgmma_n64(acc, da + (ks >> 2) * 1024 + (ks & 3) * 2, db + ks * 128);
                    wg_commit();
                    wg_wait0();
                    if (lane == 0) mbar_arrive(bars + B_EMPTY + pp.stage * 8);
                    pipe_next(pp);
                }
            } else {
#pragma unroll 1
                for (int kb = 0; kb < 8; kb++) {
                    if (kb) mbar_wait(bars + B_FULL + pp.stage * 8, pp.phase);
                    const uint32_t st = sb + pp.stage * W_STAGE;
                    const uint64_t da = mkdesc(st + wg * 8192, 16, 1024), db = mkdesc(st + 16384, 8192, 1024);
                    wg_fence();
#pragma unroll
                    for (int ks = 0; ks < 4; ks++) wgmma_n128(acc, da + ks * 2, db + ks * 128, 1);
                    wg_commit();
                    wg_wait0();
                    if (lane == 0) mbar_arrive(bars + B_EMPTY + pp.stage * 8);
                    pipe_next(pp);
                }
            }
            CTR(4);
            if (type == J_UP2) {
                mbar_wait(bars + B_STGFREE + wg * 8, stg_phase); stg_phase ^= 1;
#pragma unroll
                for (int j = 0; j < 4; j++) {
                    uint32_t r[4];
#pragma unroll
                    for (int q = 0; q < 4; q++) {
                        const uint32_t gw = pack2(acc[8 * j + 2 * q], acc[8 * j + 2 * q + 1]);
                        const uint32_t uw = pack2(acc[32 + 8 * j + 2 * q], acc[32 + 8 * j + 2 * q + 1]);
                        r[q] = hmul2(pack2(gelu_tanh(bflo(gw)), gelu_tanh(bfhi(gw))), uw);
                    }
                    stsm4(stg_base + (sx ^ (j << 5)), r[0], r[1], r[2], r[3]);
                }
            } else {
                mbar_wait(bars + B_FULL + pp.stage * 8, pp.phase);
                const uint32_t st = sb + pp.stage * W_STAGE;
                mbar_wait(bars + B_STGFREE + wg * 8, stg_phase); stg_phase ^= 1;
                const uint32_t* gb = (const uint32_t*)(g_mod + 5 * D_ + cb * 64) + t;
                const uint32_t xa = st + wg * 8192 + (wl * 16 + g) * 128 + (g << 4) + t * 4;
#pragma unroll
                for (int j = 0; j < 4; j++) {
                    uint32_t r[4];
#pragma unroll
                    for (int q = 0; q < 4; q++) {
                        const int nt = 2 * j + (q >> 1);
                        const uint32_t xw = lds32((xa ^ ((nt & 7) << 4)) + (nt >> 3) * 16384 + (q & 1) * 1024);
                        r[q] = hadd2(xw, hmul2(__ldcg(gb + nt * 4), pack2(acc[8 * j + 2 * q], acc[8 * j + 2 * q + 1])));
                    }
                    stsm4(stg_base + (j >> 2) * 8192 + (sx ^ ((2 * j & 7) << 4)), r[0], r[1], r[2], r[3]);
                }
                __syncwarp();
                if (lane == 0) mbar_arrive(bars + B_EMPTY + pp.stage * 8);
                pipe_next(pp);
            }
            fence_async_smem();
            CTR(5);
            bar_arrive(NB_ST + wg, 160);
            continue;
        }
        float acc[128];
#pragma unroll
        for (int i = 0; i < 128; i++) acc[i] = 0.f;
        const int nk = type == J_O ? (rb >= FINE_RB ? 64 / OSPLIT2 : 64 / OSPLIT) : 8;
#pragma unroll 1
        for (int kb = 0; kb < nk; kb++) {
            if (kb) mbar_wait(bars + B_FULL + pp.stage * 8, pp.phase);
            const uint32_t st = sb + pp.stage * W_STAGE;
            const uint64_t da = mkdesc(st + wg * 8192, 16, 1024), db = mkdesc(st + 16384, 8192, 1024);
            wg_fence();
#pragma unroll
            for (int ks = 0; ks < 4; ks++) wgmma_n256(acc, da + ks * 2, db + ks * 128, 1);
            wg_commit();
            wg_wait0();
            if (lane == 0) mbar_arrive(bars + B_EMPTY + pp.stage * 8);
            pipe_next(pp);
        }
        CTR(4);
        if (type == J_QA) {
            uint32_t qf[64];
#pragma unroll
            for (int i = 0; i < 64; i++) qf[i] = pack2(acc[2 * i], acc[2 * i + 1]);
            const int sg = warp >> 1, half = warp & 1;
            const float sc = 0.08838834764831845f * 1.4426950408889634f;
            const uint32_t xoff = (sg >> 1) * 8192 + ((sg & 1) * 32 + l7) * 128;
            const uint32_t moff = 32768 + (sg * 8 + l7) * 128;
            const uint32_t kch = (l8 ^ l7) << 4;
            const uint32_t vch = ((l8 & 1) ^ l7) << 4;
#pragma unroll 1
            for (int hh = 0; hh < 2; hh++) {
                mbar_wait(bars + B_FULL + pp.stage * 8, pp.phase);
                uint32_t st = sb + pp.stage * W_STAGE;
                float sa[5][4];
#pragma unroll
                for (int n = 0; n < 5; n++) sa[n][0] = sa[n][1] = sa[n][2] = sa[n][3] = 0.f;
#pragma unroll
                for (int i = 0; i < 4; i++) {
                    const uint32_t* q = qf + i * 8;
                    uint32_t kk[5][4];
                    ldsm4(kk[0][0], kk[0][1], kk[0][2], kk[0][3], st + moff + (i >> 1) * 4096 + (kch ^ ((i & 1) * 64)));
#pragma unroll
                    for (int n = 1; n < 5; n++)
                        ldsm4(kk[n][0], kk[n][1], kk[n][2], kk[n][3], st + xoff + (n - 1) * 1024 + (i >> 1) * 16384 + (kch ^ ((i & 1) * 64)));
#pragma unroll
                    for (int n = 0; n < 5; n++) mma16816(sa[n], q[0], q[1], q[2], q[3], kk[n][0], kk[n][1]);
#pragma unroll
                    for (int n = 0; n < 5; n++) mma16816(sa[n], q[4], q[5], q[6], q[7], kk[n][2], kk[n][3]);
                }
                __syncwarp();
                if (lane == 0) mbar_arrive(bars + B_EMPTY + pp.stage * 8);
                pipe_next(pp);
                const int iq0 = half * 16 + g - 2 * t, iq1 = iq0 + 8;
                float m0 = fmaxf(sa[0][0], sa[0][1]), m1 = fmaxf(sa[0][2], sa[0][3]);
#pragma unroll
                for (int n = 1; n < 5; n++) {
#pragma unroll
                    for (int e = 0; e < 2; e++) {
                        const int jx = (n - 1) * 8 + e;
                        if (jx > iq0) sa[n][e] = -3.0e38f;
                        if (jx > iq1) sa[n][2 + e] = -3.0e38f;
                        m0 = fmaxf(m0, sa[n][e]); m1 = fmaxf(m1, sa[n][2 + e]);
                    }
                }
                m0 = fmaxf(m0, __shfl_xor_sync(~0u, m0, 1)); m1 = fmaxf(m1, __shfl_xor_sync(~0u, m1, 1));
                m0 = fmaxf(m0, __shfl_xor_sync(~0u, m0, 2)); m1 = fmaxf(m1, __shfl_xor_sync(~0u, m1, 2));
                m0 *= -sc; m1 *= -sc;
                float l0 = 0.f, l1 = 0.f;
                uint32_t p0[5], p1[5];
#pragma unroll
                for (int n = 0; n < 5; n++) {
                    const float e0 = ex2(fmaf(sa[n][0], sc, m0)), e1 = ex2(fmaf(sa[n][1], sc, m0));
                    const float e2 = ex2(fmaf(sa[n][2], sc, m1)), e3 = ex2(fmaf(sa[n][3], sc, m1));
                    l0 += e0 + e1; l1 += e2 + e3;
                    p0[n] = pack2(e0, e1); p1[n] = pack2(e2, e3);
                }
                l0 += __shfl_xor_sync(~0u, l0, 1); l1 += __shfl_xor_sync(~0u, l1, 1);
                l0 += __shfl_xor_sync(~0u, l0, 2); l1 += __shfl_xor_sync(~0u, l1, 2);
                const float i0 = __fdividef(1.f, l0), i1 = __fdividef(1.f, l1);
                mbar_wait(bars + B_FULL + pp.stage * 8, pp.phase);
                st = sb + pp.stage * W_STAGE;
                mbar_wait(bars + B_STGFREE + wg * 8, stg_phase); stg_phase ^= 1;
#pragma unroll
                for (int i = 0; i < 32; i++) qf[i] = qf[32 + i];
#pragma unroll 1
                for (int bx = 0; bx < 2; bx++) {
                    float o[8][4];
                    uint32_t vm[8], v0[4][4], v1[4][4];
#pragma unroll
                    for (int ep = 0; ep < 4; ep++) {
                        ldsm2t(vm[2 * ep], vm[2 * ep + 1], st + moff + bx * 4096 + (vch ^ (ep << 5)));
                        const uint32_t va = st + xoff + (l8 >> 1) * 1024 + bx * 16384 + (vch ^ (ep << 5));
                        ldsm4t(v0[ep][0], v0[ep][1], v0[ep][2], v0[ep][3], va);
                        ldsm4t(v1[ep][0], v1[ep][1], v1[ep][2], v1[ep][3], va + 2048);
                    }
#pragma unroll
                    for (int n = 0; n < 8; n++) { o[n][0] = o[n][1] = o[n][2] = o[n][3] = 0.f; mma16816(o[n], p0[0], p1[0], p0[1], p1[1], vm[n], v0[n >> 1][n & 1]); }
#pragma unroll
                    for (int n = 0; n < 8; n++) mma16816(o[n], p0[2], p1[2], p0[3], p1[3], v0[n >> 1][2 + (n & 1)], v1[n >> 1][n & 1]);
#pragma unroll
                    for (int n = 0; n < 8; n++) mma1688(o[n], p0[4], p1[4], v1[n >> 1][2 + (n & 1)]);
#pragma unroll
                    for (int ep = 0; ep < 4; ep++)
                        stsm4(stg_base + bx * 8192 + (sx ^ (ep << 5)),
                              pack2(o[2 * ep][0] * i0, o[2 * ep][1] * i0), pack2(o[2 * ep][2] * i1, o[2 * ep][3] * i1),
                              pack2(o[2 * ep + 1][0] * i0, o[2 * ep + 1][1] * i0), pack2(o[2 * ep + 1][2] * i1, o[2 * ep + 1][3] * i1));
                }
                __syncwarp();
                if (lane == 0) mbar_arrive(bars + B_EMPTY + pp.stage * 8);
                pipe_next(pp);
                if (hh == 0) { fence_async_smem(); bar_arrive(NB_ST + wg, 160); }
            }
        } else if (type == J_UP) {
            mbar_wait(bars + B_STGFREE + wg * 8, stg_phase); stg_phase ^= 1;
#pragma unroll
            for (int j = 0; j < 8; j++) {
                uint32_t r[4];
#pragma unroll
                for (int q = 0; q < 4; q++) {
                    const uint32_t gw = pack2(acc[8 * j + 2 * q], acc[8 * j + 2 * q + 1]);
                    const uint32_t uw = pack2(acc[64 + 8 * j + 2 * q], acc[64 + 8 * j + 2 * q + 1]);
                    r[q] = hmul2(pack2(gelu_tanh(bflo(gw)), gelu_tanh(bfhi(gw))), uw);
                }
                stsm4(stg_base + (j >> 2) * 8192 + (sx ^ ((2 * j & 7) << 4)), r[0], r[1], r[2], r[3]);
            }
        } else {
#pragma unroll
            for (int rd = 0; rd < 2; rd++) {
                mbar_wait(bars + B_STGFREE + wg * 8, stg_phase); stg_phase ^= 1;
#pragma unroll
                for (int j = rd * 8; j < rd * 8 + 8; j++)
                    stsm4(stg_base + ((j >> 2) & 1) * 8192 + (sx ^ ((2 * j & 7) << 4)),
                          pack2(acc[8 * j], acc[8 * j + 1]), pack2(acc[8 * j + 2], acc[8 * j + 3]),
                          pack2(acc[8 * j + 4], acc[8 * j + 5]), pack2(acc[8 * j + 6], acc[8 * j + 7]));
                if (rd == 0) { fence_async_smem(); bar_arrive(NB_ST + wg, 160); }
            }
        }
        fence_async_smem();
        CTR(5);
        bar_arrive(NB_ST + wg, 160);
    }
}

__global__ void __launch_bounds__(384, 1) k_work(const __grid_constant__ Params p) {
    extern __shared__ __align__(1024) unsigned char smem_raw[];
    const uint32_t sb = smem_u32(smem_raw);
    if (sb & 1023) __trap();
    const int warp = __shfl_sync(~0u, threadIdx.x >> 5, 0);
    int lane; asm volatile("mov.u32 %0, %%laneid;" : "=r"(lane));
    if (threadIdx.x == 0) {
        const uint32_t bars = sb + SM_BAR;
        for (int i = 0; i < W_NST; i++) { mbar_init(bars + B_FULL + i * 8, 1); mbar_init(bars + B_EMPTY + i * 8, 8); }
        mbar_init(bars + B_STGFREE, 1); mbar_init(bars + B_STGFREE + 8, 1); mbar_init(bars + B_REQ, 1); mbar_init(bars + B_RSP, 1);
        asm volatile("fence.mbarrier_init.release.cluster;" ::: "memory");
    }
    __syncthreads();
    if (warp < 8) {
        asm volatile("setmaxnreg.inc.sync.aligned.u32 224;");
        consumer(p, sb, warp, lane);
    } else {
        asm volatile("setmaxnreg.dec.sync.aligned.u32 56;");
        if (warp == 8) { if (lane == 0) producer(p, sb); }
        else if (warp < 11) store_warp(p, sb, warp - 9, lane);
        else scheduler(p, sb, lane);
        __syncwarp();
        bar_sync(NB_W0, 128);
        if (warp == 8 && p.qmask == 0xff) {
            unsigned last = 0;
            if (lane == 0) { __threadfence(); last = atomicAdd(&g_flags[F_DONE], 1u) == gridDim.x - 1; }
            if (__shfl_sync(~0u, last, 0))
                for (int i = lane; i < F_TOTAL; i += 32) g_flags[i] = 0;
        }
    }
}

typedef CUresult (*EncodeFn)(CUtensorMap*, CUtensorMapDataType, cuuint32_t, void*, const cuuint64_t*, const cuuint64_t*,
                             const cuuint32_t*, const cuuint32_t*, CUtensorMapInterleave, CUtensorMapSwizzle,
                             CUtensorMapL2promotion, CUtensorMapFloatOOBfill);

static void make_map(EncodeFn enc, CUtensorMap* m, const void* ptr, uint64_t rows, uint64_t cols, uint32_t box_rows) {
    cuuint64_t dims[2] = {cols, rows};
    cuuint64_t strides[1] = {cols * 2};
    cuuint32_t box[2] = {64, box_rows};
    cuuint32_t es[2] = {1, 1};
    enc(m, CU_TENSOR_MAP_DATA_TYPE_BFLOAT16, 2, const_cast<void*>(ptr), dims, strides, box, es, CU_TENSOR_MAP_INTERLEAVE_NONE,
        CU_TENSOR_MAP_SWIZZLE_128B, CU_TENSOR_MAP_L2_PROMOTION_L2_256B, CU_TENSOR_MAP_FLOAT_OOB_FILL_NONE);
}
template <typename T> static void* sym_addr(T& sym) { void* p = nullptr; cudaGetSymbolAddress(&p, sym); return p; }

extern "C" void kernel_launch(void* const* d_in, const int* in_sizes, int n_in, void* d_out, int out_size) {
    static Params prm;
    static RecParams rp;
    static bool ready = false;
    static const void* key[14];
    bool same = ready;
    for (int i = 0; i < 13 && same; i++) same = key[i] == d_in[i];
    same = same && key[13] == d_out;
    if (!same) {
        void* fn = nullptr;
        cudaDriverEntryPointQueryResult qr;
        cudaGetDriverEntryPoint("cuTensorMapEncodeTiled", &fn, cudaEnableDefault, &qr);
        EncodeFn enc = (EncodeFn)fn;
        make_map(enc, &prm.tm_h, sym_addr(g_h), S_, D_, 64);
        make_map(enc, &prm.tm_kv, sym_addr(g_kv), S_, 2 * HD_, 64);
        make_map(enc, &prm.tm_kvm, sym_addr(g_kvm), NSEG * 8, 2 * HD_, 32);
        make_map(enc, &prm.tm_o, sym_addr(g_o), S_, HD_, 64);
        make_map(enc, &prm.tm_op, sym_addr(g_op), OP_ROWS, D_, 64);
        make_map(enc, &prm.tm_h2, sym_addr(g_h2), S_, D_, 64);
        make_map(enc, &prm.tm_act, sym_addr(g_act), S_, DF_, 64);
        make_map(enc, &prm.tm_x1, sym_addr(g_x1), S_, D_, 64);
        make_map(enc, &prm.tm_out, d_out, S_, D_, 64);
        make_map(enc, &prm.tm_wq, d_in[2], D_, HD_, 64);
        make_map(enc, &prm.tm_wk, d_in[3], D_, HD_, 64);
        make_map(enc, &prm.tm_wv, d_in[4], D_, HD_, 64);
        make_map(enc, &prm.tm_wo, d_in[5], HD_, D_, 64);
        make_map(enc, &prm.tm_wg, d_in[8], D_, DF_, 64);
        make_map(enc, &prm.tm_wu, d_in[9], D_, DF_, 64);
        make_map(enc, &prm.tm_wd, d_in[10], DF_, D_, 64);
        prm.x = (const bf16*)d_in[0]; prm.c = (const bf16*)d_in[11]; prm.w_mod = (const bf16*)d_in[12];
        rp.mem0 = (const bf16*)d_in[1]; rp.x = prm.x; rp.c = prm.c; rp.w_mod = prm.w_mod;
        rp.wq = (const bf16*)d_in[2]; rp.wk = (const bf16*)d_in[3]; rp.wv = (const bf16*)d_in[4]; rp.wo = (const bf16*)d_in[5];
        cudaFuncSetAttribute(k_work, cudaFuncAttributeMaxDynamicSharedMemorySize, SMEM_BYTES);
        cudaFuncSetAttribute(k_rec, cudaFuncAttributeMaxDynamicSharedMemorySize, R_SMEM);
        cudaFuncSetAttribute(k_rec, cudaFuncAttributeNonPortableClusterSizeAllowed, 1);
        {
            cudaLaunchConfig_t cfg = {};
            cfg.gridDim = dim3(128); cfg.blockDim = dim3(384); cfg.dynamicSmemBytes = R_SMEM;
            cudaLaunchAttribute at[1];
            at[0].id = cudaLaunchAttributeClusterDimension; at[0].val.clusterDim.x = 16; at[0].val.clusterDim.y = 1; at[0].val.clusterDim.z = 1;
            cfg.attrs = at; cfg.numAttrs = 1;
            int n = 0;
            cudaOccupancyMaxActiveClusters(&n, k_rec, &cfg);
            rp.ncl = n < 4 ? 4 : (n > 8 ? 8 : n);
        }
        for (int i = 0; i < 13; i++) key[i] = d_in[i];
        key[13] = d_out;
        ready = true;
    }
    cudaStream_t st = cudaStreamPerThread;
    auto launch_rec = [&]() {
        cudaLaunchConfig_t cfg = {};
        cfg.gridDim = dim3(16 * rp.ncl); cfg.blockDim = dim3(384); cfg.dynamicSmemBytes = R_SMEM; cfg.stream = st;
        cudaLaunchAttribute at[1];
        at[0].id = cudaLaunchAttributeClusterDimension; at[0].val.clusterDim.x = 16; at[0].val.clusterDim.y = 1; at[0].val.clusterDim.z = 1;
        cfg.attrs = at; cfg.numAttrs = 1;
        cudaLaunchKernelEx(&cfg, k_rec, rp);
    };
    auto launch_work = [&](int qmask, int pdl) {
        prm.qmask = qmask;
        cudaLaunchConfig_t cfg = {};
        cfg.gridDim = dim3(132); cfg.blockDim = dim3(384); cfg.dynamicSmemBytes = SMEM_BYTES; cfg.stream = st;
        cudaLaunchAttribute at[1];
        at[0].id = cudaLaunchAttributeProgrammaticStreamSerialization; at[0].val.programmaticStreamSerializationAllowed = 1;
        cfg.attrs = at; cfg.numAttrs = pdl;
        cudaLaunchKernelEx(&cfg, k_work, prm);
    };
    launch_rec();
    launch_work(0xff, 1);
}
```

```cpp
#include <cuda_runtime.h>
#include <cuda_bf16.h>
#include <cuda.h>
#include <stdint.h>

typedef __nv_bfloat16 bf16;
#define IDLE_NS 150
#define FLAG_NS 20

constexpr int S_ = 2048, D_ = 512, H_ = 32, DH_ = 128, HD_ = 4096, NSEG = 64, DF_ = 1792;
constexpr int NRB = 16;
constexpr int OSPLIT = 4;

__device__ __align__(1024) bf16 g_h[S_ * D_];
__device__ __align__(1024) bf16 g_kv[S_ * 2 * HD_];
__device__ __align__(1024) bf16 g_kvm[NSEG * 8 * 2 * HD_];
__device__ __align__(1024) bf16 g_o[S_ * HD_];
#define FINE_RB_ 12
constexpr int FINE_RB = FINE_RB_;
#define OSPLIT2_ 8
constexpr int OSPLIT2 = OSPLIT2_;
constexpr int OSPLIT3 = 16;
constexpr int OP_ROWS = OSPLIT * S_ + OSPLIT2 * (NRB - FINE_RB) * 128 + OSPLIT3 * 128;
__device__ __align__(1024) bf16 g_op[OP_ROWS * D_];
__device__ __align__(1024) bf16 g_x1[S_ * D_];
__device__ __align__(1024) bf16 g_h2[S_ * D_];
__device__ __align__(1024) bf16 g_act[S_ * DF_];
__device__ __align__(1024) bf16 g_mod[6 * D_];
__device__ uint32_t g_Fraw[131072 + 65536 + 2048];
#define g_F ((uint32_t*)(((uint64_t)g_Fraw + 0x7FFFFull) & ~0x7FFFFull))
constexpr int F_H = 0, F_MEM = 32, F_O = 64, F_OP = 96, F_H2 = 128, F_ACT = 160, F_MOD = 192, F_KV = 224, F_CLAIM = 256  ,
              F_SIDE = 512  , F_DONE = 576, F_TOTAL = 608;
__device__ __align__(128) unsigned int g_flags[F_TOTAL];
#define TR(j, i) do {} while (0)

__device__ __forceinline__ uint32_t smem_u32(const void* p) { return (uint32_t)__cvta_generic_to_shared(p); }
__device__ __forceinline__ uint32_t clk32() { uint32_t c; asm volatile("mov.u32 %0, %%clock;" : "=r"(c)); return c; }
__device__ __forceinline__ uint32_t mapa_u32(uint32_t addr, uint32_t rank) {
    uint32_t r; asm volatile("mapa.shared::cluster.u32 %0, %1, %2;" : "=r"(r) : "r"(addr), "r"(rank)); return r;
}
__device__ __forceinline__ void mbar_init(uint32_t bar, uint32_t cnt) {
    asm volatile("mbarrier.init.shared::cta.b64 [%0], %1;" :: "r"(bar), "r"(cnt) : "memory");
}
__device__ __forceinline__ void mbar_inval(uint32_t bar) {
    asm volatile("mbarrier.inval.shared::cta.b64 [%0];" :: "r"(bar) : "memory");
}
__device__ __forceinline__ void mbar_expect_tx(uint32_t bar, uint32_t bytes) {
    asm volatile("mbarrier.arrive.expect_tx.shared::cta.b64 _, [%0], %1;" :: "r"(bar), "r"(bytes) : "memory");
}
__device__ __forceinline__ void mbar_arrive(uint32_t bar) {
    asm volatile("mbarrier.arrive.shared::cta.b64 _, [%0];" :: "r"(bar) : "memory");
}
__device__ __forceinline__ bool mbar_try_wait(uint32_t bar, uint32_t parity) {
    uint32_t ok;
    asm volatile("{\n.reg .pred p;\nmbarrier.try_wait.parity.shared::cta.b64 p, [%1], %2;\nselp.u32 %0, 1, 0, p;\n}"
                 : "=r"(ok) : "r"(bar), "r"(parity) : "memory");
    return ok;
}
__device__ __forceinline__ bool mbar_try_wait_cluster(uint32_t bar, uint32_t parity) {
    uint32_t ok;
    asm volatile("{\n.reg .pred p;\nmbarrier.try_wait.parity.acquire.cluster.shared::cta.b64 p, [%1], %2;\nselp.u32 %0, 1, 0, p;\n}"
                 : "=r"(ok) : "r"(bar), "r"(parity) : "memory");
    return ok;
}
constexpr int SPIN_LIMIT = 1 << 18;
#define TIMEOUT(code, info) do {} while (0)
__device__ __forceinline__ void mbar_wait(uint32_t bar, uint32_t parity) {
    int g = 0;
#pragma unroll 1
    while (!mbar_try_wait(bar, parity)) { if (++g >= SPIN_LIMIT) { TIMEOUT(0, bar & 255); break; } }
}
__device__ __forceinline__ void mbar_wait_cluster(uint32_t bar, uint32_t parity) {
    int g = 0;
#pragma unroll 1
    while (!mbar_try_wait_cluster(bar, parity)) { if (++g >= SPIN_LIMIT) { TIMEOUT(1, bar & 255); break; } }
}
__device__ __forceinline__ void bar_sync(int id, int n) { asm volatile("bar.sync %0, %1;" :: "r"(id), "r"(n) : "memory"); }
__device__ __forceinline__ void bar_arrive(int id, int n) { asm volatile("bar.arrive %0, %1;" :: "r"(id), "r"(n) : "memory"); }
__device__ __forceinline__ void cluster_sync_all() {
    asm volatile("barrier.cluster.arrive.aligned;\nbarrier.cluster.wait.aligned;" ::: "memory");
}
__device__ __forceinline__ void st_async_v2(uint32_t addr, float a, float b, uint32_t bar) {
    asm volatile("st.async.weak.shared::cluster.mbarrier::complete_tx::bytes.v2.f32 [%0], {%1,%2}, [%3];"
                 :: "r"(addr), "f"(a), "f"(b), "r"(bar) : "memory");
}
__device__ __forceinline__ void st_async_v4(uint32_t addr, uint4 v, uint32_t bar) {
    asm volatile("st.async.weak.shared::cluster.mbarrier::complete_tx::bytes.v4.b32 [%0], {%1,%2,%3,%4}, [%5];"
                 :: "r"(addr), "r"(v.x), "r"(v.y), "r"(v.z), "r"(v.w), "r"(bar) : "memory");
}
__device__ __forceinline__ uint2 ldg_relaxed2(const uint2* p) {
    uint2 v;
    asm volatile("ld.relaxed.gpu.global.v2.b32 {%0,%1}, [%2];" : "=r"(v.x), "=r"(v.y) : "l"(p) : "memory");
    return v;
}
__device__ __forceinline__ void stg_relaxed2(uint2* p, uint2 v) {
    asm volatile("st.relaxed.gpu.global.v2.b32 [%0], {%1,%2};" :: "l"(p), "r"(v.x), "r"(v.y) : "memory");
}
__device__ __forceinline__ uint4 ldg_relaxed(const uint4* p) {
    uint4 v;
    asm volatile("ld.relaxed.gpu.global.v4.b32 {%0,%1,%2,%3}, [%4];" : "=r"(v.x), "=r"(v.y), "=r"(v.z), "=r"(v.w) : "l"(p) : "memory");
    return v;
}
__device__ __forceinline__ void stg_relaxed(uint4* p, uint4 v) {
    asm volatile("st.relaxed.gpu.global.v4.b32 [%0], {%1,%2,%3,%4};" :: "l"(p), "r"(v.x), "r"(v.y), "r"(v.z), "r"(v.w) : "memory");
}
__device__ __forceinline__ void stg_relaxed32(uint32_t* p, uint32_t v) {
    asm volatile("st.relaxed.gpu.global.b32 [%0], %1;" :: "l"(p), "r"(v) : "memory");
}
__device__ __forceinline__ uint32_t ldg_relaxed32(const uint32_t* p) {
    uint32_t v; asm volatile("ld.relaxed.gpu.global.b32 %0, [%1];" : "=r"(v) : "l"(p) : "memory"); return v;
}
__device__ __forceinline__ unsigned int ld_acquire(const unsigned int* p) {
    unsigned int v; asm volatile("ld.acquire.gpu.global.u32 %0, [%1];" : "=r"(v) : "l"(p) : "memory"); return v;
}
__device__ __forceinline__ void red_release(unsigned int* p, unsigned int v) {
    asm volatile("red.release.gpu.global.add.u32 [%0], %1;" :: "l"(p), "r"(v) : "memory");
}
__device__ __forceinline__ void wait_flag(int idx, unsigned int target) {
    const unsigned int* p = &g_flags[idx];
    int g = 0;
#pragma unroll 1
    while (ld_acquire(p) < target) { __nanosleep(FLAG_NS); if (++g >= 64 * SPIN_LIMIT) { TIMEOUT(2, idx); break; } }
}
__device__ __forceinline__ void cp_async16(uint32_t dst, const void* src) {
    asm volatile("cp.async.cg.shared.global [%0], [%1], 16;" :: "r"(dst), "l"(src) : "memory");
}
__device__ __forceinline__ void cp_async_commit() { asm volatile("cp.async.commit_group;" ::: "memory"); }
template <int N> __device__ __forceinline__ void cp_async_wait() { asm volatile("cp.async.wait_group %0;" :: "n"(N) : "memory"); }
__device__ __forceinline__ void ldsm4(uint32_t& r0, uint32_t& r1, uint32_t& r2, uint32_t& r3, uint32_t addr) {
    asm volatile("ldmatrix.sync.aligned.m8n8.x4.shared.b16 {%0,%1,%2,%3}, [%4];" : "=r"(r0), "=r"(r1), "=r"(r2), "=r"(r3) : "r"(addr) : "memory");
}
__device__ __forceinline__ void ldsm4t(uint32_t& r0, uint32_t& r1, uint32_t& r2, uint32_t& r3, uint32_t addr) {
    asm volatile("ldmatrix.sync.aligned.m8n8.x4.trans.shared.b16 {%0,%1,%2,%3}, [%4];" : "=r"(r0), "=r"(r1), "=r"(r2), "=r"(r3) : "r"(addr) : "memory");
}
__device__ __forceinline__ void ldsm2t(uint32_t& r0, uint32_t& r1, uint32_t addr) {
    asm volatile("ldmatrix.sync.aligned.m8n8.x2.trans.shared.b16 {%0,%1}, [%2];" : "=r"(r0), "=r"(r1) : "r"(addr) : "memory");
}
__device__ __forceinline__ void stsm4(uint32_t addr, uint32_t r0, uint32_t r1, uint32_t r2, uint32_t r3) {
    asm volatile("stmatrix.sync.aligned.m8n8.x4.shared.b16 [%0], {%1,%2,%3,%4};" :: "r"(addr), "r"(r0), "r"(r1), "r"(r2), "r"(r3) : "memory");
}
__device__ __forceinline__ void stsm2t(uint32_t addr, uint32_t r0, uint32_t r1) {
    asm volatile("stmatrix.sync.aligned.m8n8.x2.trans.shared.b16 [%0], {%1,%2};" :: "r"(addr), "r"(r0), "r"(r1) : "memory");
}
__device__ __forceinline__ void mma16816(float* d, uint32_t a0, uint32_t a1, uint32_t a2, uint32_t a3, uint32_t b0, uint32_t b1) {
    asm volatile("mma.sync.aligned.m16n8k16.row.col.f32.bf16.bf16.f32 {%0,%1,%2,%3}, {%4,%5,%6,%7}, {%8,%9}, {%0,%1,%2,%3};"
                 : "+f"(d[0]), "+f"(d[1]), "+f"(d[2]), "+f"(d[3]) : "r"(a0), "r"(a1), "r"(a2), "r"(a3), "r"(b0), "r"(b1));
}
__device__ __forceinline__ void mma1688(float* d, uint32_t a0, uint32_t a1, uint32_t b0) {
    asm volatile("mma.sync.aligned.m16n8k8.row.col.f32.bf16.bf16.f32 {%0,%1,%2,%3}, {%4,%5}, {%6}, {%0,%1,%2,%3};"
                 : "+f"(d[0]), "+f"(d[1]), "+f"(d[2]), "+f"(d[3]) : "r"(a0), "r"(a1), "r"(b0));
}
__device__ __forceinline__ void mma16816h(float* d, uint32_t a0, uint32_t a2, uint32_t b0, uint32_t b1) {
    asm volatile("{\n.reg .b32 ju, jv;\nmma.sync.aligned.m16n8k16.row.col.f32.bf16.bf16.f32 {%0,%1,%2,%3}, {%4,ju,%5,jv}, {%6,%7}, {%0,%1,%2,%3};\n}"
                 : "+f"(d[0]), "+f"(d[1]), "+f"(d[2]), "+f"(d[3]) : "r"(a0), "r"(a2), "r"(b0), "r"(b1));
}
__device__ __forceinline__ void mma1688h(float* d, uint32_t a0, uint32_t b0) {
    asm volatile("{\n.reg .b32 ju;\nmma.sync.aligned.m16n8k8.row.col.f32.bf16.bf16.f32 {%0,%1,%2,%3}, {%4,ju}, {%5}, {%0,%1,%2,%3};\n}"
                 : "+f"(d[0]), "+f"(d[1]), "+f"(d[2]), "+f"(d[3]) : "r"(a0), "r"(b0));
}
__device__ __forceinline__ uint32_t pack2(float lo, float hi) {
    uint32_t r; asm("cvt.rn.bf16x2.f32 %0, %1, %2;" : "=r"(r) : "f"(hi), "f"(lo)); return r;
}
__device__ __forceinline__ float bflo(uint32_t w) { return __uint_as_float(w << 16); }
__device__ __forceinline__ float bfhi(uint32_t w) { return __uint_as_float(w & 0xffff0000u); }
__device__ __forceinline__ float rbf(float x) { return __bfloat162float(__float2bfloat16_rn(x)); }
__device__ __forceinline__ float ex2(float x) { float y; asm("ex2.approx.ftz.f32 %0, %1;" : "=f"(y) : "f"(x)); return y; }
__device__ __forceinline__ void sts128(uint32_t addr, uint4 v) {
    asm volatile("st.shared.v4.b32 [%0], {%1,%2,%3,%4};" :: "r"(addr), "r"(v.x), "r"(v.y), "r"(v.z), "r"(v.w) : "memory");
}
__device__ __forceinline__ uint4 lds128(uint32_t addr) {
    uint4 v; asm volatile("ld.shared.v4.b32 {%0,%1,%2,%3}, [%4];" : "=r"(v.x), "=r"(v.y), "=r"(v.z), "=r"(v.w) : "r"(addr) : "memory"); return v;
}
__device__ __forceinline__ float2 lds64f(uint32_t addr) {
    float2 v; asm volatile("ld.shared.v2.f32 {%0,%1}, [%2];" : "=f"(v.x), "=f"(v.y) : "r"(addr) : "memory"); return v;
}
__device__ __forceinline__ float lds32f(uint32_t addr) {
    float v; asm volatile("ld.shared.f32 %0, [%1];" : "=f"(v) : "r"(addr) : "memory"); return v;
}
__device__ __forceinline__ uint32_t lds32(uint32_t addr) {
    uint32_t v; asm volatile("ld.shared.b32 %0, [%1];" : "=r"(v) : "r"(addr) : "memory"); return v;
}
__device__ __forceinline__ void sts32(uint32_t addr, uint32_t v) { asm volatile("st.shared.b32 [%0], %1;" :: "r"(addr), "r"(v) : "memory"); }
__device__ __forceinline__ void sts64f(uint32_t addr, float a, float b) { asm volatile("st.shared.v2.f32 [%0], {%1,%2};" :: "r"(addr), "f"(a), "f"(b) : "memory"); }

__device__ __forceinline__ void tma_load2d(uint32_t dst, const CUtensorMap* tm, int c0, int c1, uint32_t bar) {
    asm volatile("cp.async.bulk.tensor.2d.shared::cluster.global.mbarrier::complete_tx::bytes [%0], [%1, {%3, %4}], [%2];"
                 :: "r"(dst), "l"(tm), "r"(bar), "r"(c0), "r"(c1) : "memory");
}
__device__ __forceinline__ void tma_store2d(const CUtensorMap* tm, uint32_t src, int c0, int c1) {
    asm volatile("cp.async.bulk.tensor.2d.global.shared::cta.bulk_group [%0, {%2, %3}], [%1];"
                 :: "l"(tm), "r"(src), "r"(c0), "r"(c1) : "memory");
}
__device__ __forceinline__ void bulk_commit() { asm volatile("cp.async.bulk.commit_group;" ::: "memory"); }
__device__ __forceinline__ void bulk_wait0() { asm volatile("cp.async.bulk.wait_group 0;" ::: "memory"); }
__device__ __forceinline__ void fence_async_smem() { asm volatile("fence.proxy.async.shared::cta;" ::: "memory"); }
__device__ __forceinline__ void fence_async_all() { asm volatile("fence.proxy.async;" ::: "memory"); }

__device__ __forceinline__ void wg_fence() { asm volatile("wgmma.fence.sync.aligned;" ::: "memory"); }
__device__ __forceinline__ void wg_commit() { asm volatile("wgmma.commit_group.sync.aligned;" ::: "memory"); }
__device__ __forceinline__ void wg_wait0() { asm volatile("wgmma.wait_group.sync.aligned 0;" ::: "memory"); }
__device__ __forceinline__ uint64_t mkdesc(uint32_t saddr, uint32_t lbo, uint32_t sbo) {
    return (uint64_t)((saddr & 0x3FFFF) >> 4) | ((uint64_t)(lbo >> 4) << 16) | ((uint64_t)(sbo >> 4) << 32) | (1ull << 62);
}
#define ACC8(i) "+f"(d[i]), "+f"(d[i + 1]), "+f"(d[i + 2]), "+f"(d[i + 3]), "+f"(d[i + 4]), "+f"(d[i + 5]), "+f"(d[i + 6]), "+f"(d[i + 7])
__device__ __forceinline__ void wgmma_n256(float* d, uint64_t da, uint64_t db, int scale_d) {
    asm volatile(
        "{\n.reg .pred p;\nsetp.ne.b32 p, %130, 0;\n"
        "wgmma.mma_async.sync.aligned.m64n256k16.f32.bf16.bf16 "
        "{%0,%1,%2,%3,%4,%5,%6,%7,%8,%9,%10,%11,%12,%13,%14,%15,%16,%17,%18,%19,%20,%21,%22,%23,%24,%25,%26,%27,%28,%29,%30,%31,"
        "%32,%33,%34,%35,%36,%37,%38,%39,%40,%41,%42,%43,%44,%45,%46,%47,%48,%49,%50,%51,%52,%53,%54,%55,%56,%57,%58,%59,%60,%61,%62,%63,"
        "%64,%65,%66,%67,%68,%69,%70,%71,%72,%73,%74,%75,%76,%77,%78,%79,%80,%81,%82,%83,%84,%85,%86,%87,%88,%89,%90,%91,%92,%93,%94,%95,"
        "%96,%97,%98,%99,%100,%101,%102,%103,%104,%105,%106,%107,%108,%109,%110,%111,%112,%113,%114,%115,%116,%117,%118,%119,%120,%121,%122,%123,%124,%125,%126,%127}, "
        "%128, %129, p, 1, 1, 0, 1;\n}"
        : ACC8(0), ACC8(8), ACC8(16), ACC8(24), ACC8(32), ACC8(40), ACC8(48), ACC8(56),
          ACC8(64), ACC8(72), ACC8(80), ACC8(88), ACC8(96), ACC8(104), ACC8(112), ACC8(120)
        : "l"(da), "l"(db), "r"(scale_d));
}
__device__ __forceinline__ void wgmma_n128(float* d, uint64_t da, uint64_t db, int scale_d) {
    asm volatile(
        "{\n.reg .pred p;\nsetp.ne.b32 p, %66, 0;\n"
        "wgmma.mma_async.sync.aligned.m64n128k16.f32.bf16.bf16 "
        "{%0,%1,%2,%3,%4,%5,%6,%7,%8,%9,%10,%11,%12,%13,%14,%15,%16,%17,%18,%19,%20,%21,%22,%23,%24,%25,%26,%27,%28,%29,%30,%31,"
        "%32,%33,%34,%35,%36,%37,%38,%39,%40,%41,%42,%43,%44,%45,%46,%47,%48,%49,%50,%51,%52,%53,%54,%55,%56,%57,%58,%59,%60,%61,%62,%63}, "
        "%64, %65, p, 1, 1, 0, 1;\n}"
        : ACC8(0), ACC8(8), ACC8(16), ACC8(24), ACC8(32), ACC8(40), ACC8(48), ACC8(56)
        : "l"(da), "l"(db), "r"(scale_d));
}

__device__ __forceinline__ void wgmma_n64(float* d, uint64_t da, uint64_t db) {
    asm volatile(
        "wgmma.mma_async.sync.aligned.m64n64k16.f32.bf16.bf16 "
        "{%0,%1,%2,%3,%4,%5,%6,%7,%8,%9,%10,%11,%12,%13,%14,%15,%16,%17,%18,%19,%20,%21,%22,%23,%24,%25,%26,%27,%28,%29,%30,%31}, "
        "%32, %33, 1, 1, 1, 0, 1;"
        : ACC8(0), ACC8(8), ACC8(16), ACC8(24)
        : "l"(da), "l"(db));
}
__device__ __forceinline__ void wgmma_n8_ta(float* d, uint64_t da, uint64_t db, int scale_d) {
    asm volatile(
        "{\n.reg .pred p;\nsetp.ne.b32 p, %6, 0;\n"
        "wgmma.mma_async.sync.aligned.m64n8k16.f32.bf16.bf16 {%0,%1,%2,%3}, %4, %5, p, 1, 1, 1, 0;\n}"
        : "+f"(d[0]), "+f"(d[1]), "+f"(d[2]), "+f"(d[3]) : "l"(da), "l"(db), "r"(scale_d));
}

__device__ __forceinline__ uint32_t hadd2(uint32_t a, uint32_t b) { uint32_t r; asm("add.rn.bf16x2 %0, %1, %2;" : "=r"(r) : "r"(a), "r"(b)); return r; }
__device__ __forceinline__ uint32_t hsub2(uint32_t a, uint32_t b) { uint32_t r; asm("sub.rn.bf16x2 %0, %1, %2;" : "=r"(r) : "r"(a), "r"(b)); return r; }
__device__ __forceinline__ uint32_t hmul2(uint32_t a, uint32_t b) { uint32_t r; asm("mul.rn.bf16x2 %0, %1, %2;" : "=r"(r) : "r"(a), "r"(b)); return r; }
__device__ __forceinline__ void load_mod8(const bf16* m, int lane, uint32_t* v) {
    const uint4 a = __ldcg((const uint4*)m + lane), b = __ldcg((const uint4*)m + 32 + lane);
    v[0] = a.x; v[1] = a.y; v[2] = a.z; v[3] = a.w; v[4] = b.x; v[5] = b.y; v[6] = b.z; v[7] = b.w;
}
__device__ __forceinline__ void ln_stats(const uint32_t* x, uint32_t& mu2, float& rden) {
    float s = 0.f;
#pragma unroll
    for (int i = 0; i < 8; i++) s += bflo(x[i]) + bfhi(x[i]);
#pragma unroll
    for (int o = 16; o > 0; o >>= 1) s += __shfl_xor_sync(~0u, s, o);
    const float mean = s * (1.f / D_);
    float q = 0.f;
#pragma unroll
    for (int i = 0; i < 8; i++) { const float d0 = bflo(x[i]) - mean, d1 = bfhi(x[i]) - mean; q = fmaf(d0, d0, q); q = fmaf(d1, d1, q); }
#pragma unroll
    for (int o = 16; o > 0; o >>= 1) q += __shfl_xor_sync(~0u, q, o);
    mu2 = pack2(mean, mean);
    rden = __frcp_rn(rbf(__fsqrt_rn(rbf(rbf(q * (1.f / D_)) + 1e-5f))));
}
__device__ __forceinline__ void ln_apply(const uint32_t* x, uint32_t mu2, float rden, const uint32_t* c1, const uint32_t* sm, uint32_t* r) {
#pragma unroll
    for (int i = 0; i < 8; i++) {
        const uint32_t d = hsub2(x[i], mu2);
        r[i] = hadd2(hmul2(pack2(bflo(d) * rden, bfhi(d) * rden), c1[i]), sm[i]);
    }
}

struct __align__(64) Params {
    CUtensorMap tm_h, tm_kv, tm_kvm, tm_o, tm_op, tm_h2, tm_act, tm_x1, tm_out;
    CUtensorMap tm_wq, tm_wk, tm_wv, tm_wo, tm_wg, tm_wu, tm_wd;
    const bf16 *x, *c, *w_mod;
    int qmask;
};

constexpr int R_NST = 3;
constexpr uint32_t R_WV = 0, R_MEM = 65536, R_KX = 73728, R_VX = R_KX + R_NST * 4096,
                   R_KMS = R_VX + R_NST * 4096  , R_VMS = R_KMS + 1024,
                   R_QS = R_KMS + 4096, R_OS = R_QS + 1024, R_SX = R_OS + 1024, R_BAR = R_SX + 2560,
                   R_RS = 107520  , R_VP = R_RS + 8192  ,
                   R_STG = R_VP + 8192  , R_SMEM = R_STG + 98304;
static_assert((R_KMS & 4095) == 0, "smem");
static_assert(R_BAR + 64 <= R_RS, "smem");
constexpr uint32_t RB_SX = R_BAR, RB_V = R_BAR + 8, RB_E = R_BAR + 16, RB_A = R_BAR + 24, RB_ROLE = R_BAR + 32, RB_A1 = R_BAR + 40;
constexpr int W_NST = 4;
constexpr uint32_t W_STAGE = 49152, W_STG = W_NST * W_STAGE  , W_END = W_STG + 32768;
constexpr uint32_t SM_BAR = W_END;
constexpr uint32_t SMEM_BYTES = W_END + 1024 + 2048;
constexpr uint32_t B_FULL = 0, B_EMPTY = 32, B_STGFREE = 64, B_REQ = 80, B_RSP = 88, B_NEXT = 96, B_RING = 128;
#define PICK_AHEAD 3

constexpr int NB_X = 11  , NB_Y = 1, NB_M = 5, NB_K = 5, NB_B = 2, NB_C = 3, NB_D = 4, NB_W0 = 6  , NB_ST = 9  ;

__device__ __forceinline__ int pos_of_d(int d) {
    const int rem = d & 31;
    return (d & ~31) + ((rem & 7) >> 1) * 8 + (rem & 1) * 4 + (rem >> 3);
}

#define PROF(i) do {} while (0)
#define PROFG(i) do {} while (0)
#define OPAQUE(x) asm volatile("" : "+r"(x))
#define FENCE_SCHED(x) do { if ((x) == 0u) asm volatile("trap;"); } while (0)
#define QKVAR 2
#define VK0_ 4
constexpr int VK0 = VK0_;
constexpr int NOFF = 8;
#define VDELAY -1
#define POLL_GAP 110

struct RecParams { const bf16 *mem0, *wq, *wk, *wv, *wo, *x, *c, *w_mod; int ncl, only_pre; };

__device__ __forceinline__ void rec_qk(const RecParams& p, const uint32_t sb, const int cta, const int warp, int lane, const int sel) {
    const int crank = cta & 15, cl = cta >> 4, rank = cta & 1;
    const int kh = warp >> 2, aa = warp & 3;
    uint32_t wa[2][16][4];
    const uint32_t stg = sb + R_STG + kh * 32768;
    {
        const int t128 = aa * 32 + lane;
        const int row = (lane >> 4) * 8 + (lane & 7);
        const int ch = t128 & 7;
        const size_t goff = (size_t)kh * 256 * HD_ + cta * 64 + ch * 8;
#pragma unroll 4
        for (int dd = 0; dd < 16; dd++) {
            const int d = dd * 16 + (t128 >> 3), pp = pos_of_d(d);
            cp_async16(sb + R_WV + kh * 32768 + pp * 128 + ((ch ^ (pp & 7)) << 4), p.wv + goff + (size_t)d * HD_);
        }
        cp_async_commit();
#pragma unroll 4
        for (int dd = 0; dd < 16; dd++) {
            const int d = dd * 16 + (t128 >> 3), pp = pos_of_d(d);
            cp_async16(stg + pp * 128 + ((ch ^ (pp & 7)) << 4), p.wq + goff + (size_t)d * HD_);
        }
        cp_async_commit();
        {
            const int i0 = (warp * 32 + lane) * 16, tok = i0 >> 9;
            const uint4 m0 = __ldg((const uint4*)(p.mem0 + i0)), m1 = __ldg((const uint4*)(p.mem0 + i0 + 8));
            const uint32_t mw[8] = {m0.x, m0.y, m0.z, m0.w, m1.x, m1.y, m1.z, m1.w};
#pragma unroll
            for (int e = 0; e < 16; e++) {
                const int pp = pos_of_d((i0 & 511) + e);
                const unsigned short v = (unsigned short)(mw[e >> 1] >> ((e & 1) * 16));
                asm volatile("st.shared.u16 [%0], %1;" :: "r"(sb + R_MEM + (pp >> 3) * 128 + tok * 16 + (pp & 7) * 2), "h"(v) : "memory");
            }
        }
        cp_async_wait<1>();
        bar_sync(NB_W0 + kh, 128);
        const uint32_t fv = row * 128 + (((2 * aa + ((lane >> 3) & 1)) ^ (row & 7)) << 4);
#pragma unroll
        for (int ks = 0; ks < 16; ks++) ldsm4t(wa[0][ks][0], wa[0][ks][1], wa[0][ks][2], wa[0][ks][3], sb + R_WV + kh * 32768 + fv + ks * 2048);
        bar_sync(NB_W0 + kh, 128);
#pragma unroll
        for (int ks = 0; ks < 16; ks++)
            sts128(sb + R_WV + kh * 32768 + (aa * 16 + ks) * 512 + lane * 16, make_uint4(wa[0][ks][0], wa[0][ks][1], wa[0][ks][2], wa[0][ks][3]));
        const uint32_t fo = stg + row * 128 + (((4 * (aa & 1) + ((lane >> 3) & 1)) ^ (row & 7)) << 4);
#pragma unroll 1
        for (int m = 0; m < 2; m++) {
            cp_async_wait<0>();
            bar_sync(NB_W0 + kh, 128);
            if ((aa >> 1) == m) {
#pragma unroll
                for (int ks = 0; ks < 16; ks++) {
                    ldsm4t(wa[0][ks][0], wa[0][ks][1], wa[0][ks][2], wa[0][ks][3], fo + ks * 2048);
                    ldsm4t(wa[1][ks][0], wa[1][ks][1], wa[1][ks][2], wa[1][ks][3], (fo ^ 32) + ks * 2048);
                }
            }
            bar_sync(NB_W0 + kh, 128);
            if (m == 0) {
#pragma unroll 4
                for (int dd = 0; dd < 16; dd++) {
                    const int d = dd * 16 + (t128 >> 3), pp = pos_of_d(d);
                    cp_async16(stg + pp * 128 + ((ch ^ (pp & 7)) << 4), p.wk + goff + (size_t)d * HD_);
                }
                cp_async_commit();
            }
        }
    }
    const uint32_t tab = stg + (aa * 32 + lane) * 16;
    {
        const uint32_t l7 = lane & 7, l8 = lane >> 3, g = lane >> 2, t = lane & 3;
        const uint32_t t0 = l7 * 128 + ((l8 ^ l7) << 4);
        const uint32_t tq = l7 * 128 + (((l8 >> 1) ^ l7) << 4);
        const uint32_t bq = warp >> 1, tp = warp & 1;
        uint4 v;
        v.x = sb + (aa < 2 ? R_QS : R_KMS) + l7 * 128 + (((4 * (aa & 1) + 2 * kh + (l8 & 1)) ^ l7) << 4);
        v.y = sb + R_QS + tq;
        v.z = sb + (warp == 0 ? R_KMS : R_KX + (warp - 1) * 1024) + t0;
        v.w = mapa_u32(sb + R_SX + (rank * 5 + warp) * 256 + lane * 8, crank ^ 1);
        sts128(tab, v);
        sts128(tab + 2048, make_uint4(sb + lane * 16 + R_MEM + kh * 4096, sb + lane * 16 + R_WV + warp * 8192,
                                      sb + lane * 16 + R_VP + warp * 512, sb + lane * 16 + R_VP + 4096 + (warp ^ 4) * 512));
        const uint32_t src = (l8 >> 1) * 8 + l7;
        const uint32_t L = bq * 8 + 2 * tp + (l8 & 1);
        const uint32_t d0 = (crank + ((t >> 1) | (g & 6))) & 15;
        v.x = sb + R_RS + src * 512 + ((L ^ (src & 7)) << 4);
        v.y = mapa_u32(sb + R_MEM + (crank * 4 + bq) * 128 + (4 * tp + 2 * (t & 1) + (g & 1)) * 16, d0);
        v.z = mapa_u32(sb + ((crank & 2) ? RB_A1 : RB_A), d0);
        v.w = lane;
        sts128(tab + 4096, v);
        const uint64_t wr = (uint64_t)(g_F + ((crank * 2 + ((crank ^ (crank >> 3) ^ sel) & 1)) * 1024 + warp * 128 + cl * 32 + lane));
        sts128(tab + 6144, make_uint4((uint32_t)wr, (uint32_t)(wr >> 32), (uint32_t)((((cl + 1) & 3) - cl) * 128), (uint32_t)((((cl + 2) & 3) - cl) * 128)));
        sts32(tab + 8192, (uint32_t)((((cl + 3) & 3) - cl) * 128));
#pragma unroll
        for (int i = 0; i < NOFF; i++)
            sts128(tab + 10240 + i * 2048, make_uint4(wa[i & 1][i >> 1][0], wa[i & 1][i >> 1][1], wa[i & 1][i >> 1][2], wa[i & 1][i >> 1][3]));
    }
    bar_sync(NB_D, 384);
    uint32_t slot_off = 0;
    const uint32_t slot_inc = warp == 0 ? 2048 : 4096, slot_last = warp == 0 ? 2048 : (R_NST - 1) * 4096;
    const uint32_t sx_bar_rem = (sb + RB_SX) ^ (1u << 24);
    uint4 tb = lds128(tab + 2048);
#pragma unroll 1
    for (int s = 0; s < NSEG; s++) {
        if (s > 0) mbar_wait(sb + RB_A, (s - 1) & 1);
        if (warp == 0) { PROF(0); PROFG(13); }
        uint4 ta;
        const uint32_t km_tog = aa >= 2 ? (s & 1) * 2048 : 0;
        {
            float acc[5][4];
#pragma unroll
            for (int c = 0; c < 5; c++) { acc[c][0] = acc[c][1] = acc[c][2] = acc[c][3] = 0.f; }
            uint32_t b[8][4];
            uint4 av[16];
            static_assert(VK0 == 4, "order below assumes the V/O warps cover slices 0,1");
#define QK4(k2) do { \
                mma16816(acc[0], wa[0][2 * (k2)][0], wa[0][2 * (k2)][1], wa[0][2 * (k2)][2], wa[0][2 * (k2)][3], b[k2][0], b[k2][1]); \
                mma16816(acc[1], wa[1][2 * (k2)][0], wa[1][2 * (k2)][1], wa[1][2 * (k2)][2], wa[1][2 * (k2)][3], b[k2][0], b[k2][1]); \
                mma16816(acc[3], wa[0][2 * (k2) + 1][0], wa[0][2 * (k2) + 1][1], wa[0][2 * (k2) + 1][2], wa[0][2 * (k2) + 1][3], b[k2][2], b[k2][3]); \
                mma16816(acc[4], wa[1][2 * (k2) + 1][0], wa[1][2 * (k2) + 1][1], wa[1][2 * (k2) + 1][2], wa[1][2 * (k2) + 1][3], b[k2][2], b[k2][3]); } while (0)
#define V2(k2) do { \
                mma16816(acc[2], av[2 * (k2)].x, av[2 * (k2)].y, av[2 * (k2)].z, av[2 * (k2)].w, b[k2][0], b[k2][1]); \
                mma16816(acv, av[2 * (k2) + 1].x, av[2 * (k2) + 1].y, av[2 * (k2) + 1].z, av[2 * (k2) + 1].w, b[k2][2], b[k2][3]); } while (0)
#define LB(k2) ldsm4(b[k2][0], b[k2][1], b[k2][2], b[k2][3], tb.x + (k2) * 512)
#define LV(k2) do { av[2 * (k2)] = lds128(tb.y + 2 * (k2) * 512); av[2 * (k2) + 1] = lds128(tb.y + (2 * (k2) + 1) * 512); } while (0)
            float acv[4] = {0.f, 0.f, 0.f, 0.f};
            LB(0); LB(1); LB(4); LB(5);
            QK4(0); QK4(1); LV(4); LV(5); QK4(4); QK4(5);
            if (s > 0) mbar_wait(sb + RB_A1, (s - 1) & 1);
            LB(2); LB(3); LB(6); LB(7); ta = lds128(tab);
            V2(4); V2(5); LV(2); LV(3);
            QK4(2); QK4(3); QK4(6); QK4(7);
            LV(6); LV(7);
#pragma unroll
            for (int i = 0; i < 4; i++) { acc[0][i] += acc[3][i]; acc[1][i] += acc[4][i]; }
            const float g0 = kh ? acc[0][0] : acc[1][0], g1 = kh ? acc[0][1] : acc[1][1], g2 = kh ? acc[0][2] : acc[1][2], g3 = kh ? acc[0][3] : acc[1][3];
            sts128(tb.w, make_uint4(__float_as_uint(g0), __float_as_uint(g1), __float_as_uint(g2), __float_as_uint(g3)));
            const float k0 = kh ? acc[1][0] : acc[0][0], k1 = kh ? acc[1][1] : acc[0][1], k2_ = kh ? acc[1][2] : acc[0][2], k3 = kh ? acc[1][3] : acc[0][3];
            if (warp == 0) PROF(1);
            V2(2); V2(3);
            bar_sync(NB_X + aa, 64);
            const uint4 o = lds128(tb.z + 4096);
            V2(6); V2(7);
            stsm2t(ta.x ^ km_tog, pack2(k0 + __uint_as_float(o.x), k1 + __uint_as_float(o.y)), pack2(k2_ + __uint_as_float(o.z), k3 + __uint_as_float(o.w)));
            sts128(tb.z, make_uint4(__float_as_uint(acc[2][0] + acv[0]), __float_as_uint(acc[2][1] + acv[1]), __float_as_uint(acc[2][2] + acv[2]), __float_as_uint(acc[2][3] + acv[3])));
        }
        const uint32_t kb = ta.z + slot_off;
        if (warp == 0) PROF(14);
        bar_sync(NB_B, 256);
        if (warp < 5) {
            uint32_t q[16], k0, k1, k2, k3, k4, k5, k6, k7;
            float sa[4] = {0.f, 0.f, 0.f, 0.f}, sc[4] = {0.f, 0.f, 0.f, 0.f};
            ldsm4(q[0], q[1], q[2], q[3], ta.y);
            ldsm4(k0, k1, k2, k3, kb);
            ldsm4(q[4], q[5], q[6], q[7], ta.y ^ 32);
            ldsm4(q[8], q[9], q[10], q[11], ta.y ^ 64);
            ldsm4(k4, k5, k6, k7, kb ^ 64);
            ldsm4(q[12], q[13], q[14], q[15], ta.y ^ 96);
            mma16816(sa, q[0], q[1], q[2], q[3], k0, k1);
            bar_arrive(NB_Y, 288);
            mma16816(sc, q[4], q[5], q[6], q[7], k2, k3);
            mma16816(sa, q[8], q[9], q[10], q[11], k4, k5);
            mma16816(sc, q[12], q[13], q[14], q[15], k6, k7);
            const float scl = 0.08838834764831845f * 1.4426950408889634f;
            const float r0 = (sa[0] + sc[0]) * scl, r1 = (sa[1] + sc[1]) * scl;
            if (s != NSEG - 1) {
                st_async_v2(ta.w, r0, r1, sx_bar_rem);
                st_async_v2(ta.w ^ (1u << 24), r0, r1, sx_bar_rem ^ (1u << 24));
            }
            if (warp == 0) PROF(2);
        } else if (s > 0 && warp == 7 && lane == 0) {
            mbar_expect_tx(sb + RB_A, 4096);
            mbar_expect_tx(sb + RB_A1, 4096);
        } else if (s > 0 && (s & 3) == 0 && warp == 6) {
            bar_sync(NB_K, 160);
            if (lane == 0) red_release(&g_flags[F_MEM + (s >> 2) - 1], 1);
            __syncwarp();
        }
        if (s == NSEG - 1) {
            const uint4 td = lds128(tab + 6144);
            stg_relaxed32((uint32_t*)(((uint64_t)td.y << 32) | (td.x ^ 0x21000)), 0u);
            break;
        }
        slot_off = slot_off == slot_last ? 0 : slot_off + slot_inc;
        const uint4 tc = lds128(tab + 4096), td = lds128(tab + 6144);
        const uint32_t te = lds32(tab + 8192);
        uint32_t* wr = (uint32_t*)(((uint64_t)td.y << 32) | (td.x ^ ((s & 1) * 0x21000)));
        const uint32_t* r1p = (const uint32_t*)((const char*)wr + (int)td.z);
        const uint32_t* r2p = (const uint32_t*)((const char*)wr + (int)td.w);
        const uint32_t* r3p = (const uint32_t*)((const char*)wr + (int)te);
        const uint32_t tag = ((s >> 1) + 1) & 1;
        mbar_wait(sb + RB_E, s & 1);
        if (warp == 0) PROF(7);
        {
            uint32_t a0, a1, a2, a3, a4, a5, a6, a7;
            ldsm4t(a0, a1, a2, a3, tc.x);
            ldsm4t(a4, a5, a6, a7, tc.x ^ 64);
            const uint32_t one = 0x3F803F80u;
            float d0_[4] = {0.f, 0.f, 0.f, 0.f}, d1_[4] = {0.f, 0.f, 0.f, 0.f};
            mma16816(d0_, a0, a1, a2, a3, one, one);
            mma16816(d1_, a4, a5, a6, a7, one, one);
            const bool t1 = tc.w & 1, t2 = tc.w & 2;
            const float x = t2 ? (t1 ? d1_[2] : d1_[0]) : (t1 ? d0_[2] : d0_[0]);
            const uint32_t own = (__float_as_uint(x) & ~1u) | tag;
            stg_relaxed32(wr, own);
            const uint32_t tq = clk32();
            if (warp == 0) PROF(8);
            PROFG(16 + warp);
            while ((int)(clk32() - tq) < POLL_GAP) {}
            uint32_t f1 = ldg_relaxed32(r1p), f2 = ldg_relaxed32(r2p), f3 = ldg_relaxed32(r3p);
#pragma unroll
            for (int i = 0; i < NOFF; i++) {
                const uint4 f0 = lds128(tab + 10240 + i * 2048);
                wa[i & 1][i >> 1][0] = f0.x; wa[i & 1][i >> 1][1] = f0.y; wa[i & 1][i >> 1][2] = f0.z; wa[i & 1][i >> 1][3] = f0.w;
            }
            tb = lds128(tab + 2048);
            int gg = 0;
#pragma unroll 1
            while (!__all_sync(~0u, (((f1 ^ tag) | (f2 ^ tag) | (f3 ^ tag)) & 1) == 0)) {
                f1 = ldg_relaxed32(r1p); f2 = ldg_relaxed32(r2p); f3 = ldg_relaxed32(r3p);
                if (++gg > 16 * SPIN_LIMIT) { TIMEOUT(3, s); break; }
            }
            if (warp == 0) PROF(9);
            const float v = (__uint_as_float(own) + __uint_as_float(f2)) + (__uint_as_float(f1) + __uint_as_float(f3));
            const bool b8 = tc.w & 8, b16 = tc.w & 16;
            const float recv = __shfl_xor_sync(~0u, v, 8);
            const uint32_t word = b8 ? pack2(recv, v) : pack2(v, recv);
            const uint32_t oth = __shfl_xor_sync(~0u, word, 16);
            const uint32_t wl = b16 ? oth : word, wh = b16 ? word : oth;
            const uint32_t p0 = __shfl_xor_sync(~0u, wl, 2), p1 = __shfl_xor_sync(~0u, wh, 2);
            const uint4 item = t2 ? make_uint4(p0, p1, wl, wh) : make_uint4(wl, wh, p0, p1);
            st_async_v4(tc.y, item, tc.z);
            st_async_v4(tc.y ^ (8u << 24), item, tc.z ^ (8u << 24));
            if (tc.w == 0 && warp == 7) mbar_expect_tx(sb + RB_E, 8192);
            if (warp == 0) PROF(10);
            PROF(40 + warp);
        }
        bar_sync(NB_D, 384);
    }
}

__device__ __forceinline__ void rec_load_kv(uint32_t sb, int col0, int s, uint32_t slot_off, int t128) {
    const int row = t128 >> 2, c2 = (t128 & 3) * 2;
    const bf16* src = g_kv + ((size_t)(s * 32 + row) * (2 * HD_) + col0 + c2 * 8);
    const uint32_t d0 = sb + R_KX + slot_off + row * 128 + ((c2 ^ (row & 7)) << 4);
    cp_async16(d0, src);
    cp_async16(d0 ^ 16, src + 8);
    cp_async16(d0 + (R_VX - R_KX), src + HD_);
    cp_async16((d0 ^ 16) + (R_VX - R_KX), src + HD_ + 8);
}

__device__ __forceinline__ void rec_store_kvm(uint32_t sb, int col0, int s, int w, int lane) {
    const int tok = (w & 1) * 4 + (lane >> 3);
    const uint4 v = lds128(sb + R_KMS + (s & 1) * 2048 + (w >> 1) * 1024 + tok * 128 + (((lane & 7) ^ tok) << 4));
    *(uint4*)(g_kvm + ((s * 8 + tok) * (2 * HD_) + (w >> 1) * HD_ + col0 + (lane & 7) * 8)) = v;
}

__device__ __forceinline__ void rec_vo(const RecParams& p, const uint32_t sb, const int cta, const int warp, int lane) {
    const int w = warp - 8, crank = cta & 15;
    const int col0 = cta * 64;
    uint32_t wo[8][4][4];
    {
        const int t128 = w * 32 + lane;
        const bf16* Wo = p.wo + (size_t)col0 * D_;
        const uint32_t stg = sb + R_STG + 2 * 32768;
#pragma unroll
        for (int half = 0; half < 2; half++) {
#pragma unroll 4
            for (int i = t128; i < 2048; i += 128) {
                const int e = i >> 6, ch = i & 63;
                cp_async16(stg + e * 1024 + ((ch ^ (e & 7)) << 4), Wo + (size_t)(half * 32 + e) * D_ + ch * 8);
            }
            cp_async_commit();
            cp_async_wait<0>();
            bar_sync(NB_W0 + 2, 128);
#pragma unroll
            for (int j = 0; j < 8; j++)
#pragma unroll
                for (int kk = 0; kk < 2; kk++) {
                    const int e = kk * 16 + (lane >> 4) * 8 + (lane & 7);
                    const int ch = (w * 8 + j) * 2 + ((lane >> 3) & 1);
                    ldsm4t(wo[j][half * 2 + kk][0], wo[j][half * 2 + kk][1], wo[j][half * 2 + kk][2], wo[j][half * 2 + kk][3],
                           stg + e * 1024 + ((ch ^ (e & 7)) << 4));
                }
            bar_sync(NB_W0 + 2, 128);
        }
        if (lane == 0) wait_flag(F_KV + 0, 64);
        __syncwarp();
        rec_load_kv(sb, col0, 0, 0, t128); cp_async_commit();
        rec_load_kv(sb, col0, 1, 4096, t128); cp_async_commit();
        cp_async_wait<1>();
    }
    const uint32_t tab = sb + R_STG + 2 * 32768 + (w * 32 + lane) * 16;
    {
        const uint32_t l7 = lane & 7, l8 = lane >> 3, g = lane >> 2;
        uint4 v;
        v.x = sb + R_VX + ((l8 & 1) * 8 + l7) * 128 + (((2 * w + (l8 >> 1)) ^ l7) << 4);
        v.y = sb + R_OS + g * 128 + (((2 * w) ^ g) << 4) + (lane & 3) * 4;
        v.z = sb + R_VMS + l7 * 128 + (((2 * w + (l8 & 1)) ^ l7) << 4);
        v.w = sb + R_OS + l7 * 128 + ((l8 ^ l7) << 4);
        sts128(tab, v);
        v.x = mapa_u32(sb + R_RS + crank * 512 + ((lane ^ (crank & 7)) << 4), w * 4);
        v.y = mapa_u32(sb + RB_E, w * 4);
        v.z = sb + R_VP + w * 512 + lane * 16;
        v.w = sb + R_SX + lane * 8;
        sts128(tab + 2048, v);
#pragma unroll
        for (int i = 0; i < 8; i++) sts128(tab + 4096 + i * 2048, make_uint4(wo[i][0][0], wo[i][0][1], wo[i][0][2], wo[i][0][3]));
        const int tok = (w & 1) * 4 + (lane >> 3), row = (w * 32 + lane) >> 2, c2 = (lane & 3) * 2;
        const uint64_t kd = (uint64_t)(g_kvm + (tok * (2 * HD_) + (w >> 1) * HD_ + col0 + (lane & 7) * 8));
        const uint64_t ks = (uint64_t)(g_kv + ((size_t)row * (2 * HD_) + col0 + c2 * 8));
        sts128(tab + 20480, make_uint4((uint32_t)kd, (uint32_t)(kd >> 32), (uint32_t)ks, (uint32_t)(ks >> 32)));
        sts128(tab + 22528, make_uint4(sb + R_KMS + (w >> 1) * 1024 + tok * 128 + (((lane & 7) ^ tok) << 4),
                                       sb + R_KX + row * 128 + ((c2 ^ (row & 7)) << 4), lane, 0));
    }
    bar_sync(NB_D, 384);
    const uint32_t lane16 = lds32(tab + 2048 + 8) - R_VP - w * 512;
    uint4 av[2 * VK0];
#pragma unroll
    for (int i = 0; i < 2 * VK0; i++) av[i] = lds128(lane16 + R_WV + (i / VK0) * 32768 + (w * 16 + i % VK0) * 512);
    uint32_t slot_off = 0;
#pragma unroll 1
    for (int s = 0; s < NSEG; s++) {
        if (s > 0) {
            mbar_wait(sb + RB_A, (s - 1) & 1);
            const uint4 tp = lds128(tab + 20480), tq = lds128(tab + 22528);
            const uint4 kvm = lds128(tq.x + ((s - 1) & 1) * 2048);
            *(uint4*)((((uint64_t)tp.y << 32) | tp.x) + (uint64_t)(s - 1) * (8 * 2 * HD_ * 2)) = kvm;
            if ((s & 3) == 0) bar_arrive(NB_K, 160);
            if (s + 1 < NSEG - 1) {
                if (((s + 1) & 3) == 0) { if (tq.z == 0) wait_flag(F_KV + ((s + 1) >> 2), 64); __syncwarp(); }
                const char* src = (const char*)((((uint64_t)tp.w << 32) | tp.z) + (uint64_t)(s + 1) * (32 * 2 * HD_ * 2));
                const uint32_t d0 = tq.y + (slot_off == (R_NST - 1) * 4096 ? 0 : slot_off + 4096);
                cp_async16(d0, src);
                cp_async16(d0 ^ 16, src + 16);
                cp_async16(d0 + (R_VX - R_KX), src + HD_ * 2);
                cp_async16((d0 ^ 16) + (R_VX - R_KX), src + HD_ * 2 + 16);
            }
            cp_async_commit();
        }
        bar_sync(NB_Y, 288);
        uint32_t vb0, vb1;
        {
            float va[4] = {0.f, 0.f, 0.f, 0.f}, vc[4] = {0.f, 0.f, 0.f, 0.f};
            uint32_t bb[VK0][4];
#pragma unroll
            for (int k2 = 0; k2 < VK0; k2++) ldsm4(bb[k2][0], bb[k2][1], bb[k2][2], bb[k2][3], lane16 + R_MEM + (k2 / (VK0 / 2)) * 4096 + (k2 % (VK0 / 2)) * 512);
#pragma unroll
            for (int k2 = 0; k2 < VK0; k2++) {
                mma16816(va, av[2 * k2].x, av[2 * k2].y, av[2 * k2].z, av[2 * k2].w, bb[k2][0], bb[k2][1]);
                mma16816(vc, av[2 * k2 + 1].x, av[2 * k2 + 1].y, av[2 * k2 + 1].z, av[2 * k2 + 1].w, bb[k2][2], bb[k2][3]);
            }
            const uint4 a = lds128(lane16 + R_VP + w * 512), b = lds128(lane16 + R_VP + 2048 + w * 512);
            vb0 = pack2((va[0] + vc[0]) + (__uint_as_float(a.x) + __uint_as_float(b.x)), (va[1] + vc[1]) + (__uint_as_float(a.y) + __uint_as_float(b.y)));
            vb1 = pack2((va[2] + vc[2]) + (__uint_as_float(a.z) + __uint_as_float(b.z)), (va[3] + vc[3]) + (__uint_as_float(a.w) + __uint_as_float(b.w)));
        }
        const uint4 ta = lds128(tab), tb = lds128(tab + 2048);
        uint32_t vx[8];
        ldsm4t(vx[0], vx[1], vx[2], vx[3], ta.x + slot_off);
        ldsm4t(vx[4], vx[5], vx[6], vx[7], ta.x + slot_off + 2048);
#pragma unroll
        for (int i = 0; i < 4; i++) {
            const uint4 f0 = lds128(tab + 4096 + i * 2048);
            wo[i][0][0] = f0.x; wo[i][0][1] = f0.y; wo[i][0][2] = f0.z; wo[i][0][3] = f0.w;
        }
        if (w == 0) PROF(11);
        uint32_t pf[5];
        float oa[2][4] = {{0.f, 0.f, 0.f, 0.f}, {0.f, 0.f, 0.f, 0.f}}, ob_[2][4] = {{0.f, 0.f, 0.f, 0.f}, {0.f, 0.f, 0.f, 0.f}};
        float sm0[4] = {0.f, 0.f, 0.f, 0.f}, sm1[4] = {0.f, 0.f, 0.f, 0.f};
        if (s != NSEG - 1) {
            mbar_wait(sb + RB_SX, s & 1);
            if (w == 0) PROF(4);
            float sv[10];
#pragma unroll
            for (int n = 0; n < 5; n++) {
                const float2 a = lds64f(tb.w + n * 256), b = lds64f(tb.w + (5 + n) * 256);
                sv[2 * n] = a.x + b.x; sv[2 * n + 1] = a.y + b.y;
            }
            float mx = fmaxf(fmaxf(fmaxf(sv[0], sv[1]), fmaxf(sv[2], sv[3])), fmaxf(fmaxf(sv[4], sv[5]), fmaxf(sv[6], sv[7])));
            mx = fmaxf(mx, fmaxf(sv[8], sv[9]));
            mx = fmaxf(mx, __shfl_xor_sync(~0u, mx, 1));
            mx = fmaxf(mx, __shfl_xor_sync(~0u, mx, 2));
#pragma unroll
            for (int n = 1; n < 5; n++) pf[n] = pack2(ex2(sv[2 * n] - mx), ex2(sv[2 * n + 1] - mx));
            pf[0] = pack2(ex2(sv[0] - mx), ex2(sv[1] - mx));
            if (w == 0) PROF(12);
            const uint32_t one = 0x3F803F80u;
            mma16816h(sm0, pf[1], pf[2], one, one);
            mma16816h(oa[0], pf[1], pf[2], vx[0], vx[1]);
            mma16816h(oa[1], pf[1], pf[2], vx[2], vx[3]);
            mma16816h(sm1, pf[3], pf[4], one, one);
            mma16816h(ob_[0], pf[3], pf[4], vx[4], vx[5]);
            mma16816h(ob_[1], pf[3], pf[4], vx[6], vx[7]);
            mma1688h(sm0, pf[0], one);
            mma1688h(oa[0], pf[0], vb0);
            mma1688h(oa[1], pf[0], vb1);
            float inv;
            asm("rcp.approx.ftz.f32 %0, %1;" : "=f"(inv) : "f"(sm0[0] + sm1[0]));
            oa[0][0] += ob_[0][0]; oa[0][1] += ob_[0][1]; oa[1][0] += ob_[1][0]; oa[1][1] += ob_[1][1];
            sts32(ta.y, pack2(oa[0][0] * inv, oa[0][1] * inv));
            sts32(ta.y ^ 16, pack2(oa[1][0] * inv, oa[1][1] * inv));
            const uint32_t oa2 = ta.w ^ 64;
            bar_sync(NB_C, 128);
            if (w == 0) PROF(5);
            uint32_t ob[8];
            ldsm4(ob[0], ob[1], ob[2], ob[3], ta.w);
            ldsm4(ob[4], ob[5], ob[6], ob[7], oa2);
#pragma unroll
            for (int i = 4; i < 8; i++) {
                const uint4 f0 = lds128(tab + 4096 + i * 2048);
                wo[i][0][0] = f0.x; wo[i][0][1] = f0.y; wo[i][0][2] = f0.z; wo[i][0][3] = f0.w;
            }
#pragma unroll
            for (int jj = 0; jj < 2; jj++) {
                if (jj == 1 && tb.w == 0) break;
                float acc[4][4];
#pragma unroll
                for (int c = 0; c < 4; c++) { acc[c][0] = acc[c][1] = acc[c][2] = acc[c][3] = 0.f; }
#pragma unroll
                for (int ks = 0; ks < 4; ks++)
#pragma unroll
                    for (int c = 0; c < 4; c++)
                        mma16816(acc[c], wo[jj * 4 + c][ks][0], wo[jj * 4 + c][ks][1], wo[jj * 4 + c][ks][2], wo[jj * 4 + c][ks][3], ob[2 * ks], ob[2 * ks + 1]);
#pragma unroll
                for (int pr = 0; pr < 2; pr++) {
                    uint4 v;
                    v.x = pack2(acc[2 * pr][0], acc[2 * pr][1]);
                    v.y = pack2(acc[2 * pr][2], acc[2 * pr][3]);
                    v.z = pack2(acc[2 * pr + 1][0], acc[2 * pr + 1][1]);
                    v.w = pack2(acc[2 * pr + 1][2], acc[2 * pr + 1][3]);
                    st_async_v4(tb.x + ((jj * 2 + pr) << 24), v, tb.y + ((jj * 2 + pr) << 24));
                }
            }
            if (w == 0) PROF(6);
        }
        stsm2t(ta.z + (s & 1) * 2048, vb0, vb1);
        cp_async_wait<0>();
        bar_sync(NB_C, 128);
        if (w == 0 && lane == 0 && s != NSEG - 1) mbar_expect_tx(sb + RB_SX, 2560);
        if (s != NSEG - 1) bar_arrive(NB_D, 384);
#pragma unroll
        for (int i = 0; i < 2 * VK0; i++) av[i] = lds128(lane16 + R_WV + (i / VK0) * 32768 + (w * 16 + i % VK0) * 512);
        slot_off = slot_off == (R_NST - 1) * 4096 ? 0 : slot_off + 4096;
    }
    rec_store_kvm(sb, col0, NSEG - 1, w, lane);
    bar_sync(NB_C, 128);
    if (w == 0 && lane == 0) red_release(&g_flags[F_MEM + NRB - 1], 1);
}

__global__ void __launch_bounds__(384, 1) k_rec(const RecParams p) {
    extern __shared__ __align__(1024) unsigned char smem_raw[];
    const uint32_t sb = __shfl_sync(~0u, smem_u32(smem_raw), 0);
    const int warp = __shfl_sync(~0u, threadIdx.x >> 5, 0);
    int lane; asm volatile("mov.u32 %0, %%laneid;" : "=r"(lane));
    const int crank = blockIdx.x & 15, slot = blockIdx.x >> 4;
    asm volatile("griddepcontrol.launch_dependents;");
    if (threadIdx.x == 0) {
        mbar_init(sb + RB_SX, 1); mbar_init(sb + RB_E, 1); mbar_init(sb + RB_A, 1); mbar_init(sb + RB_A1, 1); mbar_init(sb + RB_ROLE, 1);
        asm volatile("fence.mbarrier_init.release.cluster;" ::: "memory");
        mbar_expect_tx(sb + RB_SX, 2560);
        mbar_expect_tx(sb + RB_E, 8192);
        mbar_expect_tx(sb + RB_A, 4096);
        mbar_expect_tx(sb + RB_A1, 4096);
        mbar_expect_tx(sb + RB_ROLE, 4);
    }
    asm volatile("barrier.cluster.arrive.relaxed.aligned;\nbarrier.cluster.wait.aligned;" ::: "memory");
    unsigned role = 0;
    if (crank == 0 && threadIdx.x == 0 && !p.only_pre) {
        unsigned x = 0;
        int tm[2] = {0x7fffffff, 0x7fffffff};
#pragma unroll 1
        for (int i = 0; i < 6; i++) {
            const uint32_t t0 = clk32();
            x = atomicAdd(&g_F[65536 + (i & 1) * 1024 + slot * 64 + (x >> 31)], 0u) & 0x7fffffffu;
            if (x == 0x7654321u) sts32(sb + R_BAR + 56, x);
            const int dt = (int)(clk32() - t0);
            if (i >= 2) { if (i & 1) tm[1] = min(tm[1], dt); else tm[0] = min(tm[0], dt); }
        }
        const int side = tm[1] > tm[0];
        const unsigned old = atomicAdd(&g_flags[F_SIDE + side * 32], 1u);
        unsigned c0, c1; int gd = 0;
#pragma unroll 1
        do { c0 = ldg_relaxed32(&g_flags[F_SIDE]); c1 = ldg_relaxed32(&g_flags[F_SIDE + 32]); } while ((int)(c0 + c1) < p.ncl && ++gd < 64 * SPIN_LIMIT);
        const int big = c1 > c0;
        role = side == big ? old : (big ? c1 : c0) + old;
        role |= (big ^ 1) << 8;
    }
    __syncwarp();
    if (crank == 0 && warp == 0 && !p.only_pre) {
        role = __shfl_sync(~0u, role, 0);
        if (lane < 16)
            asm volatile("st.async.weak.shared::cluster.mbarrier::complete_tx::bytes.u32 [%0], %1, [%2];"
                         :: "r"(mapa_u32(sb + R_BAR + 48, lane)), "r"(role), "r"(mapa_u32(sb + RB_ROLE, lane)) : "memory");
    }
    if (warp >= 4) {
        const int w8 = warp - 4, nblk = gridDim.x;
        const int cq = lane & 3, rg = w8 * 8 + (lane >> 2);
        const uint32_t red = sb + R_VP;
        const int row0 = blockIdx.x * 8 + w8;
        const uint4* xr = (const uint4*)(p.x + (size_t)row0 * D_);
        uint4 xa = __ldg(xr + lane), xb = __ldg(xr + 32 + lane);
#pragma unroll 1
        for (int sl = blockIdx.x; sl < 96; sl += nblk) {
            uint4 wv[8];
#pragma unroll
            for (int i = 0; i < 8; i++) wv[i] = __ldg((const uint4*)(p.w_mod + (size_t)(rg * 8 + i) * (6 * D_) + sl * 32 + cq * 8));
            const uint32_t cw = __ldg((const uint32_t*)(p.c + rg * 8) + cq);
            const float cl = bflo(cw), ch = bfhi(cw);
            const uint32_t sw = pack2(__fdividef(cl, 1.f + __expf(-cl)), __fdividef(ch, 1.f + __expf(-ch)));
            float a[8];
#pragma unroll
            for (int i = 0; i < 8; i++) a[i] = 0.f;
#pragma unroll
            for (int i = 0; i < 8; i++) {
                const uint32_t sv = __shfl_sync(~0u, sw, (lane & 28) + (i >> 1));
                const float cv = (i & 1) ? bfhi(sv) : bflo(sv);
                a[0] = fmaf(cv, bflo(wv[i].x), a[0]); a[1] = fmaf(cv, bfhi(wv[i].x), a[1]); a[2] = fmaf(cv, bflo(wv[i].y), a[2]); a[3] = fmaf(cv, bfhi(wv[i].y), a[3]);
                a[4] = fmaf(cv, bflo(wv[i].z), a[4]); a[5] = fmaf(cv, bfhi(wv[i].z), a[5]); a[6] = fmaf(cv, bflo(wv[i].w), a[6]); a[7] = fmaf(cv, bfhi(wv[i].w), a[7]);
            }
#pragma unroll
            for (int i = 0; i < 8; i++) { a[i] += __shfl_xor_sync(~0u, a[i], 4); a[i] += __shfl_xor_sync(~0u, a[i], 8); a[i] += __shfl_xor_sync(~0u, a[i], 16); }
            if (lane < 4) {
                sts128(red + w8 * 128 + lane * 32, make_uint4(__float_as_uint(a[0]), __float_as_uint(a[1]), __float_as_uint(a[2]), __float_as_uint(a[3])));
                sts128(red + w8 * 128 + lane * 32 + 16, make_uint4(__float_as_uint(a[4]), __float_as_uint(a[5]), __float_as_uint(a[6]), __float_as_uint(a[7])));
            }
            bar_sync(NB_B, 256);
            if (w8 == 0) {
                float v = 0.f;
#pragma unroll
                for (int i = 0; i < 8; i++) v += lds32f(red + i * 128 + lane * 4);
                g_mod[sl * 32 + lane] = __float2bfloat16_rn(v);
                __syncwarp();
                if (lane == 0) red_release(&g_flags[F_MOD + (sl >= 32)], 1);
            }
            bar_sync(NB_B, 256);
        }
        uint32_t c1[8], sm[8];
        int row = row0, step = 0;
#pragma unroll 1
        while (true) {
            const uint32_t v[8] = {xa.x, xa.y, xa.z, xa.w, xb.x, xb.y, xb.z, xb.w};
            uint32_t mu2, r[8]; float rden;
            ln_stats(v, mu2, rden);
            int next = row + step;
            if (step == 0) {
                if (!p.only_pre) mbar_wait(sb + RB_ROLE, 0);
                const int cl = p.only_pre ? slot : (int)(lds32(sb + R_BAR + 48) & 255);
                next = cl < 4 ? (nblk + cl * 16 + crank) * 8 + w8 : S_;
                step = 512;
            }
            if (next < S_) { xr = (const uint4*)(p.x + (size_t)next * D_); xa = __ldg(xr + lane); xb = __ldg(xr + 32 + lane); }
            if (row == row0) {
                if (lane == 0) wait_flag(F_MOD, 32);
                __syncwarp();
                load_mod8(g_mod + D_, lane, c1);
                load_mod8(g_mod, lane, sm);
#pragma unroll
                for (int i = 0; i < 8; i++) c1[i] = hadd2(c1[i], 0x3F803F80u);
            }
            ln_apply(v, mu2, rden, c1, sm, r);
            uint4* hr = (uint4*)(g_h + (size_t)row * D_);
            hr[lane] = make_uint4(r[0], r[1], r[2], r[3]); hr[32 + lane] = make_uint4(r[4], r[5], r[6], r[7]);
            bar_sync(NB_B, 256);
            if (w8 == (row >> 7 & 7) && lane == 0) red_release(&g_flags[F_H + (row >> 7)], 1);
            __syncwarp();
            row = next;
            if (row >= S_) break;
        }
    }
    if (p.only_pre) return;
    mbar_wait(sb + RB_ROLE, 0);
    const int rolew = __shfl_sync(~0u, lds32(sb + R_BAR + 48), 0);
    const int cl = rolew & 255;
    if (cl >= 4) return;
    const int cta = cl * 16 + crank;
    if (warp < 8) rec_qk(p, sb, cta, warp, lane, rolew >> 8);
    else rec_vo(p, sb, cta, warp, lane);
}

enum { J_KV = 0, J_QA = 1, J_O = 2, J_LN = 3, J_UP = 4, J_DN = 5, J_LN1 = 6, J_MOD = 7, J_UP2 = 8, J_END = 9 };
constexpr int NJ_O = 2 * OSPLIT, NJ_O2 = 2 * OSPLIT2, NJ_LN = 8, NJ_LN2 = 16, NJ_UP = 14, NJ_UP2 = 28, NJ_DN = 8, NJ_LN1 = 8;
constexpr uint64_t pk8(int a, int b, int c, int d, int e, int f, int g, int h) {
    return (uint64_t)a | ((uint64_t)b << 8) | ((uint64_t)c << 16) | ((uint64_t)d << 24) | ((uint64_t)e << 32) | ((uint64_t)f << 40) | ((uint64_t)g << 48) | ((uint64_t)h << 56);
}
constexpr uint64_t NJ_C = pk8(32, 16, NJ_O, NJ_LN, NJ_UP, NJ_DN, 0, 0), NJ_F = pk8(32, 16, NJ_O2, NJ_LN2, NJ_UP2, NJ_DN, 0, 0);
constexpr uint64_t TG_C = pk8(2 * NJ_LN1, 64, 32, 2 * NJ_O, 2 * NJ_LN, 2 * NJ_UP, 32, 0), TG_F = pk8(2 * NJ_LN1, 64, 32, 2 * NJ_O2, 2 * NJ_LN2, 2 * NJ_UP2, 32, 0);
constexpr uint64_t NJ_L = pk8(32, 32, 2 * OSPLIT3, NJ_LN2, NJ_UP2, NJ_DN, 0, 0), TG_L = pk8(2 * NJ_LN1, 64, 64, 4 * OSPLIT3, 2 * NJ_LN2, 2 * NJ_UP2, 32, 0);
__device__ __forceinline__ uint64_t nj_tab(int rb) { return rb < FINE_RB ? NJ_C : (rb < NRB - 1 ? NJ_F : NJ_L); }
__device__ __forceinline__ uint64_t tg_tab(int rb) { return rb < FINE_RB ? TG_C : (rb < NRB - 1 ? TG_F : TG_L); }
__device__ __forceinline__ int o_nk(int rb) { return rb < FINE_RB ? 64 / OSPLIT : (rb < NRB - 1 ? 64 / OSPLIT2 : 64 / OSPLIT3); }
constexpr uint64_t PRIO = pk8(4, 10, 9, 8, 7, 6, 3, 0);
__device__ __forceinline__ int pick_job(int lane, int qmask, int& idx) {
    const int rb = lane & 15, half = lane >> 4;
    const uint64_t nj = nj_tab(rb) >> (8 * half);
    const uint64_t tg = tg_tab(rb) >> (8 * half);
    const unsigned* cp = &g_flags[F_CLAIM + half * 32 + rb];
    const unsigned* dp = &g_flags[half * 32 + rb];
    int gd = 0;
#pragma unroll 1
    while (true) {
        const unsigned c0 = ldg_relaxed32(cp), c1 = ldg_relaxed32(cp + 64), c2 = ldg_relaxed32(cp + 128);
        const unsigned d0 = ldg_relaxed32(dp - (half ? (rb >= FINE_RB ? 2 : (rb ? 1 : 0)) : 0)), d1 = ldg_relaxed32(dp + 64), d2 = ldg_relaxed32(dp + 128);
        const unsigned cl[3] = {c0, c1, c2}, dv[3] = {d0, d1, d2};
        unsigned key = 0xffffu, key2 = 0xffffu;
        bool pre = false;
#pragma unroll
        for (int i = 0; i < 3; i++) {
            const int q = half + 2 * i;
            const bool have = ((qmask >> q) & 1) && cl[i] < (unsigned)((nj >> (16 * i)) & 255);
            bool ready = have && dv[i] >= (unsigned)((tg >> (16 * i)) & 255);
            unsigned pr = (unsigned)((PRIO >> (8 * q)) & 255);
            if (i == 0 && rb <= 1 - half) ready = have;
            if (i == 0 && half && rb >= FINE_RB) pr = 5;
            if (ready) key = min(key, (pr << 8) | (rb << 4) | q);
            if (have) key2 = min(key2, rb >= FINE_RB ? (0x100u | (q << 4) | rb) : (i == 0 ? 0u : 0x1000u));
            pre |= have && i == 0 && !half;
        }
        const bool anypre = __any_sync(~0u, pre);
        if (anypre && (key & 15) == J_QA) key = 0xffffu;
        key = __reduce_min_sync(~0u, key);
        key2 = __reduce_min_sync(~0u, key2);
        if (key2 == 0xffffu) return J_END;
        int pq, prb;
        if (key != 0xffffu) { pq = key & 15; prb = (key >> 4) & 15; }
        else if (key2 >= 0x120u && key2 < 0x1000u) { pq = (key2 >> 4) & 15; prb = key2 & 15; }
        else {
            __nanosleep(IDLE_NS);
            if (++gd > 16 * SPIN_LIMIT) { TIMEOUT(5, 0); return J_END; }
            continue;
        }
        int c = 0;
        if (lane == 0) c = (int)atomicAdd(&g_flags[F_CLAIM + pq * 32 + prb], 1u);
        c = __shfl_sync(~0u, c, 0);
        if (c < (int)((nj_tab(prb) >> (8 * pq)) & 255)) {
            idx = pq * 512 + prb * 32 + c;
            int acq = 0;
            if (pq != J_QA && pq < J_LN1) {
                if (lane == 0 && ld_acquire(&g_flags[pq * 32 + prb]) >= (unsigned)((tg_tab(prb) >> (8 * pq)) & 255)) {
                    asm volatile("fence.proxy.async.global;" ::: "memory");
                    acq = 1 << 24;
                }
            }
            return (pq == J_UP && prb >= FINE_RB ? J_UP2 : pq) | (prb << 8) | (c << 16) | acq;
        }
    }
}
__device__ __forceinline__ int op_row(int rb, int split) {
    return rb < FINE_RB ? split * S_ + rb * 128
                        : (rb < NRB - 1 ? OSPLIT * S_ + (split * (NRB - FINE_RB) + rb - FINE_RB) * 128 : OSPLIT * S_ + (OSPLIT2 * (NRB - FINE_RB) + split) * 128);
}

struct Pipe { uint32_t stage, phase; };
__device__ __forceinline__ void pipe_next(Pipe& p) { if (++p.stage == W_NST) { p.stage = 0; p.phase ^= 1; } }

__device__ __forceinline__ void scheduler(const Params& p, uint32_t sb, int lane) {
    const uint32_t bars = sb + SM_BAR;
    uint32_t ph = 0;
#pragma unroll 1
    while (true) {
        mbar_wait(bars + B_REQ, ph);
        int j = 4095;
        const int jd = pick_job(lane, p.qmask, j);
        if (lane == 0) { sts32(bars + B_NEXT, (uint32_t)jd); sts32(bars + B_NEXT + 4, (uint32_t)j); mbar_arrive(bars + B_RSP); }
        ph ^= 1;
        if (jd == J_END) break;
        __syncwarp();
    }
}

__device__ __forceinline__ void producer(const Params& p, uint32_t sb) {
    Pipe pp{0, 1};
    const uint32_t bars = sb + SM_BAR;
    uint32_t seq = 0, h_seen = 0;
    mbar_arrive(bars + B_REQ);
#pragma unroll 1
    while (true) {
        mbar_wait(bars + B_RSP, seq & 1);
        const int jd = (int)lds32(bars + B_NEXT), j = (int)lds32(bars + B_NEXT + 4);
        int left = (jd & 255) == J_DN ? 15 : ((jd & 255) == J_QA ? (((jd >> 8) & 255) == NRB - 1 ? 10 : 12) : ((jd & 255) == J_O ? o_nk((jd >> 8) & 255) : ((jd & 255) == J_LN || (jd & 255) == J_LN1 || (jd & 255) == J_MOD ? 1 : 8)));
        left = max(left - PICK_AHEAD, 1);
        TR(j, 1);
        const int type = jd & 255, rb = (jd >> 8) & 255, cb = (jd >> 16) & 255;
        const bool fine = rb >= FINE_RB, acquired = (jd >> 24) & 1;
        bool first = true;
        auto begin_stage = [&](uint32_t bytes) -> uint32_t {
            mbar_wait(bars + B_EMPTY + pp.stage * 8, pp.phase);
            if (first) { sts32(bars + B_RING + (seq & 7) * 4, (uint32_t)jd); sts32(bars + B_RING + 32 + (seq & 7) * 4, (uint32_t)j); first = false; }
            const uint32_t fb = bars + B_FULL + pp.stage * 8;
            if (bytes) mbar_expect_tx(fb, bytes); else mbar_arrive(fb);
            if (--left == 0 && type != J_END) mbar_arrive(bars + B_REQ);
            return fb;
        };
        if (type == J_END || type == J_LN || type == J_LN1 || type == J_MOD) {
            if (type == J_LN) { if (!acquired) wait_flag(F_OP + rb, (unsigned)((tg_tab(rb) >> (8 * J_LN)) & 255)); if (!(h_seen >> 31)) { wait_flag(F_MOD + 1, 64); h_seen |= 1u << 31; } }

            TR(j, 2);
            begin_stage(0); pipe_next(pp);
            seq++;
            if (type == J_END) break;
            continue;
        }
        const CUtensorMap *ta, *tb0, *tb1;
        int k0 = 0, nk = 8, n0 = cb * 256, n1 = n0 + 128, nb = 4, dep = -1;
        unsigned tgt = 0;
        switch (type) {
            case J_KV: ta = &p.tm_h; tb0 = tb1 = cb < 16 ? &p.tm_wk : &p.tm_wv; n0 = (cb & 15) * 256; n1 = n0 + 128; dep = F_H + rb; tgt = 2 * NJ_LN1; break;
            case J_QA: ta = &p.tm_h; tb0 = tb1 = &p.tm_wq; dep = F_H + rb; tgt = 2 * NJ_LN1; if (rb == NRB - 1) { n0 = (cb >> 1) * 256; n1 = n0 + 128; } break;
            case J_O: ta = &p.tm_o; tb0 = tb1 = &p.tm_wo; n0 = (cb & 1) * 256; n1 = n0 + 128; nk = o_nk(rb); k0 = (cb >> 1) * nk * 64;
                      dep = F_O + rb; tgt = rb == NRB - 1 ? 64 : 32; break;
            case J_UP: ta = &p.tm_h2; tb0 = &p.tm_wg; tb1 = &p.tm_wu; n0 = n1 = cb * 128; dep = F_H2 + rb; tgt = 2 * NJ_LN; break;
            case J_UP2: ta = &p.tm_h2; tb0 = &p.tm_wg; tb1 = &p.tm_wu; n0 = n1 = cb * 64; nb = 2; dep = F_H2 + rb; tgt = 2 * NJ_LN2; break;
            default: ta = &p.tm_act; tb0 = tb1 = &p.tm_wd; n0 = cb * 64; nk = 0; break;
        }
        const int m0 = rb * 128;
        if (type == J_DN) {
#pragma unroll 1
            for (int kb = 0; kb < 14; kb++) {
                const uint32_t fb = begin_stage(49152);
                const uint32_t st = sb + pp.stage * W_STAGE;
                const int k = kb * 128;
                tma_load2d(st + 32768, tb0, n0, k, fb);
                tma_load2d(st + 40960, tb0, n0, k + 64, fb);
                if (kb == 0) { if (!acquired) { wait_flag(F_ACT + rb, 2 * (fine ? NJ_UP2 : NJ_UP)); asm volatile("fence.proxy.async.global;" ::: "memory"); } TR(j, 2); }
                tma_load2d(st, ta, k, m0, fb);
                tma_load2d(st + 8192, ta, k, m0 + 64, fb);
                tma_load2d(st + 16384, ta, k + 64, m0, fb);
                tma_load2d(st + 24576, ta, k + 64, m0 + 64, fb);
                pipe_next(pp);
            }
        }
#pragma unroll 1
        for (int kb = 0; kb < nk; kb++) {
            const uint32_t fb = begin_stage(16384 + nb * 8192);
            const uint32_t st = sb + pp.stage * W_STAGE;
            const int k = k0 + kb * 64;
            tma_load2d(st + 16384, tb0, n0, k, fb);
            if (nb == 4) {
                tma_load2d(st + 16384 + 8192, tb0, n0 + 64, k, fb);
                tma_load2d(st + 16384 + 16384, tb1, n1, k, fb);
                tma_load2d(st + 16384 + 24576, tb1, n1 + 64, k, fb);
            } else if (nb == 2) {
                tma_load2d(st + 16384 + 8192, tb1, n1, k, fb);
            }
            if (kb == 0) {
                if (acquired && dep < 16) h_seen |= 1u << dep;
                if (dep >= 0 && !acquired && !(dep < 16 && ((h_seen >> dep) & 1))) {
                    wait_flag(dep, tgt);
                    if (type != J_O) asm volatile("fence.proxy.async.global;" ::: "memory");
                    if (dep < 16) h_seen |= 1u << dep;
                }
                TR(j, 2);
            }
            tma_load2d(st, ta, k, m0, fb);
            tma_load2d(st + 8192, ta, k, m0 + 64, fb);
            pipe_next(pp);
        }
        if (type == J_QA) {
            wait_flag(F_KV + rb, 64);
#pragma unroll 1
            for (int i = 0; i < (rb == NRB - 1 ? 2 : 4); i++) {
                const uint32_t fb = begin_stage(40960);
                const uint32_t st = sb + pp.stage * W_STAGE;
                const int col = (i & 1) * HD_ + (rb == NRB - 1 ? cb : cb * 2 + (i >> 1)) * DH_;
                tma_load2d(st, &p.tm_kv, col, m0, fb);
                tma_load2d(st + 8192, &p.tm_kv, col, m0 + 64, fb);
                tma_load2d(st + 16384, &p.tm_kv, col + 64, m0, fb);
                tma_load2d(st + 24576, &p.tm_kv, col + 64, m0 + 64, fb);
                if (i == 0) { wait_flag(F_MEM + rb, 64); asm volatile("fence.proxy.async.global;" ::: "memory"); }
                tma_load2d(st + 32768, &p.tm_kvm, col, rb * 32, fb);
                tma_load2d(st + 36864, &p.tm_kvm, col + 64, rb * 32, fb);
                pipe_next(pp);
            }
        } else if (type == J_DN) {
            const uint32_t fb = begin_stage(16384);
            const uint32_t st = sb + pp.stage * W_STAGE;
            tma_load2d(st, &p.tm_x1, n0, m0, fb);
            tma_load2d(st + 8192, &p.tm_x1, n0, m0 + 64, fb);
            pipe_next(pp);
        }
        seq++;
    }
}

__device__ __forceinline__ void store_warp(const Params& p, uint32_t sb, int wg, int lane) {
    const uint32_t bars = sb + SM_BAR;
    uint32_t seq = 0;
#pragma unroll 1
    while (true) {
        bar_sync(NB_ST + wg, 160);
        const uint32_t jd = lds32(bars + B_RING + (seq & 7) * 4);
        seq++;
        const int type = jd & 255, rb = (jd >> 8) & 255, cb = (jd >> 16) & 255;
        if (type == J_END) break;
        const uint32_t src = sb + W_STG + wg * 16384;
        const CUtensorMap* tm = nullptr; int n0 = cb * 256, nbox = 4, mrow = rb * 128 + wg * 64, flag = 0;
        switch (type) {
            case J_KV: tm = &p.tm_kv; flag = F_KV + rb; break;
            case J_QA: tm = &p.tm_o; flag = F_O + rb; if (rb == NRB - 1) { n0 = cb * 128; nbox = 2; } break;
            case J_O: tm = &p.tm_op; n0 = (cb & 1) * 256; mrow = op_row(rb, cb >> 1) + wg * 64; flag = F_OP + rb; break;
            case J_LN: flag = F_H2 + rb; nbox = 0; break;
            case J_LN1: flag = F_H + rb; nbox = 0; break;
            case J_MOD: flag = F_MOD + rb; nbox = 0; break;
            case J_UP: tm = &p.tm_act; n0 = cb * 128; nbox = 2; flag = F_ACT + rb; break;
            case J_UP2: tm = &p.tm_act; n0 = cb * 64; nbox = 1; flag = F_ACT + rb; break;
            default: tm = &p.tm_out; n0 = cb * 64; nbox = 1; flag = -1; break;
        }
        if (nbox == 4) {
            if (lane == 0) {
                tma_store2d(tm, src, n0, mrow);
                tma_store2d(tm, src + 8192, n0 + 64, mrow);
                bulk_commit();
                asm volatile("cp.async.bulk.wait_group.read 0;" ::: "memory");
                mbar_arrive(bars + B_STGFREE + wg * 8);
            }
            __syncwarp();
            bar_sync(NB_ST + wg, 160);
            n0 += 128; nbox = 2;
        }
        if (lane == 0) {
            if (nbox) {
                tma_store2d(tm, src, n0, mrow);
                if (nbox == 2) tma_store2d(tm, src + 8192, n0 + 64, mrow);
                bulk_commit();
                asm volatile("cp.async.bulk.wait_group.read 0;" ::: "memory");
                mbar_arrive(bars + B_STGFREE + wg * 8);
                bulk_wait0();
                if (flag >= 0) asm volatile("red.relaxed.gpu.global.add.u32 [%0], 1;" :: "l"(&g_flags[flag]) : "memory");
            } else {
                mbar_arrive(bars + B_STGFREE + wg * 8);
                red_release(&g_flags[flag], 1);
            }
        }
        __syncwarp();
    }
}

__device__ __forceinline__ float gelu_tanh(float x) {
    const float t = x * fmaf(-0.10294324397f, x * x, -2.30220819814f);
    float r; asm("rcp.approx.ftz.f32 %0, %1;" : "=f"(r) : "f"(1.f + ex2(t)));
    return x * r;
}

#define CTR(i) do {} while (0)

template <int NSPLIT>
__device__ __forceinline__ void ln2_row(const Params& p, int rb, int r, int lane) {
    const int row = rb * 128 + r;
    uint4 u[2 * NSPLIT];
#pragma unroll
    for (int sp = 0; sp < NSPLIT; sp++) {
        const uint4* src = (const uint4*)(g_op + (size_t)(op_row(rb, sp) + r) * D_);
        u[2 * sp] = __ldcg(src + lane); u[2 * sp + 1] = __ldcg(src + 32 + lane);
    }
    const uint4* xr = (const uint4*)(p.x + (size_t)row * D_);
    const uint4 xa = __ldg(xr + lane), xb = __ldg(xr + 32 + lane);
    uint32_t ga[8], c1[8], sm[8];
    load_mod8(g_mod + 2 * D_, lane, ga);
    load_mod8(g_mod + 4 * D_, lane, c1);
    load_mod8(g_mod + 3 * D_, lane, sm);
    float a[16];
#pragma unroll
    for (int i = 0; i < 16; i++) a[i] = 0.f;
#pragma unroll
    for (int sp = 0; sp < 2 * NSPLIT; sp++) {
        float* q = a + (sp & 1) * 8;
        q[0] += bflo(u[sp].x); q[1] += bfhi(u[sp].x); q[2] += bflo(u[sp].y); q[3] += bfhi(u[sp].y);
        q[4] += bflo(u[sp].z); q[5] += bfhi(u[sp].z); q[6] += bflo(u[sp].w); q[7] += bfhi(u[sp].w);
    }
    const uint32_t xv[8] = {xa.x, xa.y, xa.z, xa.w, xb.x, xb.y, xb.z, xb.w};
    uint32_t v[8], r8[8];
#pragma unroll
    for (int i = 0; i < 8; i++) v[i] = hadd2(xv[i], hmul2(ga[i], pack2(a[2 * i], a[2 * i + 1])));
    uint4* x1r = (uint4*)(g_x1 + (size_t)row * D_);
    x1r[lane] = make_uint4(v[0], v[1], v[2], v[3]); x1r[32 + lane] = make_uint4(v[4], v[5], v[6], v[7]);
    uint32_t mu2; float rden;
    ln_stats(v, mu2, rden);
#pragma unroll
    for (int i = 0; i < 8; i++) c1[i] = hadd2(c1[i], 0x3F803F80u);
    ln_apply(v, mu2, rden, c1, sm, r8);
    uint4* hr = (uint4*)(g_h2 + (size_t)row * D_);
    hr[lane] = make_uint4(r8[0], r8[1], r8[2], r8[3]); hr[32 + lane] = make_uint4(r8[4], r8[5], r8[6], r8[7]);
}

__device__ __forceinline__ void consumer(const Params& p, uint32_t sb, int warp, int lane) {
    const uint32_t bars = sb + SM_BAR;
    const int wg = warp >> 2, wl = warp & 3;
    const uint32_t l7 = lane & 7, l8 = lane >> 3, g = lane >> 2, t = lane & 3;
    Pipe pp{0, 0};
    uint32_t seq = 0, stg_phase = 1;
    const int srow = wl * 16 + l7 + (l8 & 1) * 8;
    const uint32_t stg_base = sb + W_STG + wg * 16384 + srow * 128;
    const uint32_t sx = ((lane >> 4) ^ (srow & 7)) << 4;
#pragma unroll 1
    while (true) {
        mbar_wait(bars + B_FULL + pp.stage * 8, pp.phase);
        const uint32_t jd = lds32(bars + B_RING + (seq & 7) * 4);
        CTR(3);
        seq++;
        const int type = jd & 255, rb = (jd >> 8) & 255, cb = (jd >> 16) & 255;
        if (type == J_END) { mbar_wait(bars + B_STGFREE + wg * 8, stg_phase); bar_arrive(NB_ST + wg, 160); break; }
        if (type == J_LN) {
            __syncwarp();
            if (lane == 0) mbar_arrive(bars + B_EMPTY + pp.stage * 8);
            pipe_next(pp);
            if (rb == NRB - 1) ln2_row<OSPLIT3>(p, rb, cb * 8 + warp, lane);
            else if (rb >= FINE_RB) ln2_row<OSPLIT2>(p, rb, cb * 8 + warp, lane);
            else {
#pragma unroll 1
                for (int rr = 0; rr < 2; rr++) ln2_row<OSPLIT>(p, rb, cb * 16 + warp * 2 + rr, lane);
            }
            mbar_wait(bars + B_STGFREE + wg * 8, stg_phase); stg_phase ^= 1;
            CTR(4); CTR(5);
            bar_arrive(NB_ST + wg, 160);
            continue;
        }
        if (type == J_DN || type == J_UP2) {
            float acc[64];
#pragma unroll
            for (int i = 0; i < 64; i++) acc[i] = 0.f;
            if (type == J_DN) {
#pragma unroll 1
                for (int kb = 0; kb < 14; kb++) {
                    if (kb) mbar_wait(bars + B_FULL + pp.stage * 8, pp.phase);
                    const uint32_t st = sb + pp.stage * W_STAGE;
                    const uint64_t da = mkdesc(st + wg * 8192, 16, 1024), db = mkdesc(st + 32768, 8192, 1024);
                    wg_fence();
#pragma unroll
                    for (int ks = 0; ks < 8; ks++) wgmma_n64(acc, da + (ks >> 2) * 1024 + (ks & 3) * 2, db + ks * 128);
                    wg_commit();
                    wg_wait0();
                    if (lane == 0) mbar_arrive(bars + B_EMPTY + pp.stage * 8);
                    pipe_next(pp);
                }
            } else {
#pragma unroll 1
                for (int kb = 0; kb < 8; kb++) {
                    if (kb) mbar_wait(bars + B_FULL + pp.stage * 8, pp.phase);
                    const uint32_t st = sb + pp.stage * W_STAGE;
                    const uint64_t da = mkdesc(st + wg * 8192, 16, 1024), db = mkdesc(st + 16384, 8192, 1024);
                    wg_fence();
#pragma unroll
                    for (int ks = 0; ks < 4; ks++) wgmma_n128(acc, da + ks * 2, db + ks * 128, 1);
                    wg_commit();
                    wg_wait0();
                    if (lane == 0) mbar_arrive(bars + B_EMPTY + pp.stage * 8);
                    pipe_next(pp);
                }
            }
            CTR(4);
            if (type == J_UP2) {
                mbar_wait(bars + B_STGFREE + wg * 8, stg_phase); stg_phase ^= 1;
#pragma unroll
                for (int j = 0; j < 4; j++) {
                    uint32_t r[4];
#pragma unroll
                    for (int q = 0; q < 4; q++) {
                        const uint32_t gw = pack2(acc[8 * j + 2 * q], acc[8 * j + 2 * q + 1]);
                        const uint32_t uw = pack2(acc[32 + 8 * j + 2 * q], acc[32 + 8 * j + 2 * q + 1]);
                        r[q] = hmul2(pack2(gelu_tanh(bflo(gw)), gelu_tanh(bfhi(gw))), uw);
                    }
                    stsm4(stg_base + (sx ^ (j << 5)), r[0], r[1], r[2], r[3]);
                }
            } else {
                mbar_wait(bars + B_FULL + pp.stage * 8, pp.phase);
                const uint32_t st = sb + pp.stage * W_STAGE;
                mbar_wait(bars + B_STGFREE + wg * 8, stg_phase); stg_phase ^= 1;
                const uint32_t* gb = (const uint32_t*)(g_mod + 5 * D_ + cb * 64) + t;
                const uint32_t xa = st + wg * 8192 + (wl * 16 + g) * 128 + (g << 4) + t * 4;
#pragma unroll
                for (int j = 0; j < 4; j++) {
                    uint32_t r[4];
#pragma unroll
                    for (int q = 0; q < 4; q++) {
                        const int nt = 2 * j + (q >> 1);
                        const uint32_t xw = lds32((xa ^ ((nt & 7) << 4)) + (nt >> 3) * 16384 + (q & 1) * 1024);
                        r[q] = hadd2(xw, hmul2(__ldcg(gb + nt * 4), pack2(acc[8 * j + 2 * q], acc[8 * j + 2 * q + 1])));
                    }
                    stsm4(stg_base + (j >> 2) * 8192 + (sx ^ ((2 * j & 7) << 4)), r[0], r[1], r[2], r[3]);
                }
                __syncwarp();
                if (lane == 0) mbar_arrive(bars + B_EMPTY + pp.stage * 8);
                pipe_next(pp);
            }
            fence_async_smem();
            CTR(5);
            bar_arrive(NB_ST + wg, 160);
            continue;
        }
        float acc[128];
#pragma unroll
        for (int i = 0; i < 128; i++) acc[i] = 0.f;
        const int nk = type == J_O ? o_nk(rb) : 8;
#pragma unroll 1
        for (int kb = 0; kb < nk; kb++) {
            if (kb) mbar_wait(bars + B_FULL + pp.stage * 8, pp.phase);
            const uint32_t st = sb + pp.stage * W_STAGE;
            const uint64_t da = mkdesc(st + wg * 8192, 16, 1024), db = mkdesc(st + 16384, 8192, 1024);
            wg_fence();
#pragma unroll
            for (int ks = 0; ks < 4; ks++) wgmma_n256(acc, da + ks * 2, db + ks * 128, 1);
            wg_commit();
            wg_wait0();
            if (lane == 0) mbar_arrive(bars + B_EMPTY + pp.stage * 8);
            pipe_next(pp);
        }
        CTR(4);
        if (type == J_QA) {
            uint32_t qf[64];
#pragma unroll
            for (int i = 0; i < 64; i++) qf[i] = pack2(acc[2 * i], acc[2 * i + 1]);
            const int sg = warp >> 1, half = warp & 1;
            const float sc = 0.08838834764831845f * 1.4426950408889634f;
            const uint32_t xoff = (sg >> 1) * 8192 + ((sg & 1) * 32 + l7) * 128;
            const uint32_t moff = 32768 + (sg * 8 + l7) * 128;
            const uint32_t kch = (l8 ^ l7) << 4;
            const uint32_t vch = ((l8 & 1) ^ l7) << 4;
            if (rb == NRB - 1 && (cb & 1)) {
#pragma unroll
                for (int i = 0; i < 32; i++) qf[i] = qf[32 + i];
            }
#pragma unroll 1
            for (int hh = rb == NRB - 1; hh < 2; hh++) {
                mbar_wait(bars + B_FULL + pp.stage * 8, pp.phase);
                uint32_t st = sb + pp.stage * W_STAGE;
                float sa[5][4];
#pragma unroll
                for (int n = 0; n < 5; n++) sa[n][0] = sa[n][1] = sa[n][2] = sa[n][3] = 0.f;
#pragma unroll
                for (int i = 0; i < 4; i++) {
                    const uint32_t* q = qf + i * 8;
                    uint32_t kk[5][4];
                    ldsm4(kk[0][0], kk[0][1], kk[0][2], kk[0][3], st + moff + (i >> 1) * 4096 + (kch ^ ((i & 1) * 64)));
#pragma unroll
                    for (int n = 1; n < 5; n++)
                        ldsm4(kk[n][0], kk[n][1], kk[n][2], kk[n][3], st + xoff + (n - 1) * 1024 + (i >> 1) * 16384 + (kch ^ ((i & 1) * 64)));
#pragma unroll
                    for (int n = 0; n < 5; n++) mma16816(sa[n], q[0], q[1], q[2], q[3], kk[n][0], kk[n][1]);
#pragma unroll
                    for (int n = 0; n < 5; n++) mma16816(sa[n], q[4], q[5], q[6], q[7], kk[n][2], kk[n][3]);
                }
                __syncwarp();
                if (lane == 0) mbar_arrive(bars + B_EMPTY + pp.stage * 8);
                pipe_next(pp);
                const int iq0 = half * 16 + g - 2 * t, iq1 = iq0 + 8;
                float m0 = fmaxf(sa[0][0], sa[0][1]), m1 = fmaxf(sa[0][2], sa[0][3]);
#pragma unroll
                for (int n = 1; n < 5; n++) {
#pragma unroll
                    for (int e = 0; e < 2; e++) {
                        const int jx = (n - 1) * 8 + e;
                        if (jx > iq0) sa[n][e] = -3.0e38f;
                        if (jx > iq1) sa[n][2 + e] = -3.0e38f;
                        m0 = fmaxf(m0, sa[n][e]); m1 = fmaxf(m1, sa[n][2 + e]);
                    }
                }
                m0 = fmaxf(m0, __shfl_xor_sync(~0u, m0, 1)); m1 = fmaxf(m1, __shfl_xor_sync(~0u, m1, 1));
                m0 = fmaxf(m0, __shfl_xor_sync(~0u, m0, 2)); m1 = fmaxf(m1, __shfl_xor_sync(~0u, m1, 2));
                m0 *= -sc; m1 *= -sc;
                float l0 = 0.f, l1 = 0.f;
                uint32_t p0[5], p1[5];
#pragma unroll
                for (int n = 0; n < 5; n++) {
                    const float e0 = ex2(fmaf(sa[n][0], sc, m0)), e1 = ex2(fmaf(sa[n][1], sc, m0));
                    const float e2 = ex2(fmaf(sa[n][2], sc, m1)), e3 = ex2(fmaf(sa[n][3], sc, m1));
                    l0 += e0 + e1; l1 += e2 + e3;
                    p0[n] = pack2(e0, e1); p1[n] = pack2(e2, e3);
                }
                l0 += __shfl_xor_sync(~0u, l0, 1); l1 += __shfl_xor_sync(~0u, l1, 1);
                l0 += __shfl_xor_sync(~0u, l0, 2); l1 += __shfl_xor_sync(~0u, l1, 2);
                const float i0 = __fdividef(1.f, l0), i1 = __fdividef(1.f, l1);
                mbar_wait(bars + B_FULL + pp.stage * 8, pp.phase);
                st = sb + pp.stage * W_STAGE;
                mbar_wait(bars + B_STGFREE + wg * 8, stg_phase); stg_phase ^= 1;
#pragma unroll
                for (int i = 0; i < 32; i++) qf[i] = qf[32 + i];
#pragma unroll 1
                for (int bx = 0; bx < 2; bx++) {
                    float o[8][4];
                    uint32_t vm[8], v0[4][4], v1[4][4];
#pragma unroll
                    for (int ep = 0; ep < 4; ep++) {
                        ldsm2t(vm[2 * ep], vm[2 * ep + 1], st + moff + bx * 4096 + (vch ^ (ep << 5)));
                        const uint32_t va = st + xoff + (l8 >> 1) * 1024 + bx * 16384 + (vch ^ (ep << 5));
                        ldsm4t(v0[ep][0], v0[ep][1], v0[ep][2], v0[ep][3], va);
                        ldsm4t(v1[ep][0], v1[ep][1], v1[ep][2], v1[ep][3], va + 2048);
                    }
#pragma unroll
                    for (int n = 0; n < 8; n++) { o[n][0] = o[n][1] = o[n][2] = o[n][3] = 0.f; mma16816(o[n], p0[0], p1[0], p0[1], p1[1], vm[n], v0[n >> 1][n & 1]); }
#pragma unroll
                    for (int n = 0; n < 8; n++) mma16816(o[n], p0[2], p1[2], p0[3], p1[3], v0[n >> 1][2 + (n & 1)], v1[n >> 1][n & 1]);
#pragma unroll
                    for (int n = 0; n < 8; n++) mma1688(o[n], p0[4], p1[4], v1[n >> 1][2 + (n & 1)]);
#pragma unroll
                    for (int ep = 0; ep < 4; ep++)
                        stsm4(stg_base + bx * 8192 + (sx ^ (ep << 5)),
                              pack2(o[2 * ep][0] * i0, o[2 * ep][1] * i0), pack2(o[2 * ep][2] * i1, o[2 * ep][3] * i1),
                              pack2(o[2 * ep + 1][0] * i0, o[2 * ep + 1][1] * i0), pack2(o[2 * ep + 1][2] * i1, o[2 * ep + 1][3] * i1));
                }
                __syncwarp();
                if (lane == 0) mbar_arrive(bars + B_EMPTY + pp.stage * 8);
                pipe_next(pp);
                if (hh == 0) { fence_async_smem(); bar_arrive(NB_ST + wg, 160); }
            }
        } else if (type == J_UP) {
            mbar_wait(bars + B_STGFREE + wg * 8, stg_phase); stg_phase ^= 1;
#pragma unroll
            for (int j = 0; j < 8; j++) {
                uint32_t r[4];
#pragma unroll
                for (int q = 0; q < 4; q++) {
                    const uint32_t gw = pack2(acc[8 * j + 2 * q], acc[8 * j + 2 * q + 1]);
                    const uint32_t uw = pack2(acc[64 + 8 * j + 2 * q], acc[64 + 8 * j + 2 * q + 1]);
                    r[q] = hmul2(pack2(gelu_tanh(bflo(gw)), gelu_tanh(bfhi(gw))), uw);
                }
                stsm4(stg_base + (j >> 2) * 8192 + (sx ^ ((2 * j & 7) << 4)), r[0], r[1], r[2], r[3]);
            }
        } else {
#pragma unroll
            for (int rd = 0; rd < 2; rd++) {
                mbar_wait(bars + B_STGFREE + wg * 8, stg_phase); stg_phase ^= 1;
#pragma unroll
                for (int j = rd * 8; j < rd * 8 + 8; j++)
                    stsm4(stg_base + ((j >> 2) & 1) * 8192 + (sx ^ ((2 * j & 7) << 4)),
                          pack2(acc[8 * j], acc[8 * j + 1]), pack2(acc[8 * j + 2], acc[8 * j + 3]),
                          pack2(acc[8 * j + 4], acc[8 * j + 5]), pack2(acc[8 * j + 6], acc[8 * j + 7]));
                if (rd == 0) { fence_async_smem(); bar_arrive(NB_ST + wg, 160); }
            }
        }
        fence_async_smem();
        CTR(5);
        bar_arrive(NB_ST + wg, 160);
    }
}

__global__ void __launch_bounds__(384, 1) k_work(const __grid_constant__ Params p) {
    extern __shared__ __align__(1024) unsigned char smem_raw[];
    const uint32_t sb = smem_u32(smem_raw);
    if (sb & 1023) __trap();
    const int warp = __shfl_sync(~0u, threadIdx.x >> 5, 0);
    int lane; asm volatile("mov.u32 %0, %%laneid;" : "=r"(lane));
    if (threadIdx.x == 0) {
        const uint32_t bars = sb + SM_BAR;
        for (int i = 0; i < W_NST; i++) { mbar_init(bars + B_FULL + i * 8, 1); mbar_init(bars + B_EMPTY + i * 8, 8); }
        mbar_init(bars + B_STGFREE, 1); mbar_init(bars + B_STGFREE + 8, 1); mbar_init(bars + B_REQ, 1); mbar_init(bars + B_RSP, 1);
        asm volatile("fence.mbarrier_init.release.cluster;" ::: "memory");
    }
    __syncthreads();
    if (warp < 8) {
        asm volatile("setmaxnreg.inc.sync.aligned.u32 224;");
        consumer(p, sb, warp, lane);
    } else {
        asm volatile("setmaxnreg.dec.sync.aligned.u32 56;");
        if (warp == 8) { if (lane == 0) producer(p, sb); }
        else if (warp < 11) store_warp(p, sb, warp - 9, lane);
        else scheduler(p, sb, lane);
        __syncwarp();
        bar_sync(NB_W0, 128);
        if (warp == 8 && p.qmask == 0xff) {
            unsigned last = 0;
            if (lane == 0) { __threadfence(); last = atomicAdd(&g_flags[F_DONE], 1u) == gridDim.x - 1; }
            if (__shfl_sync(~0u, last, 0))
                for (int i = lane; i < F_TOTAL; i += 32) g_flags[i] = 0;
        }
    }
}

typedef CUresult (*EncodeFn)(CUtensorMap*, CUtensorMapDataType, cuuint32_t, void*, const cuuint64_t*, const cuuint64_t*,
                             const cuuint32_t*, const cuuint32_t*, CUtensorMapInterleave, CUtensorMapSwizzle,
                             CUtensorMapL2promotion, CUtensorMapFloatOOBfill);

static void make_map(EncodeFn enc, CUtensorMap* m, const void* ptr, uint64_t rows, uint64_t cols, uint32_t box_rows) {
    cuuint64_t dims[2] = {cols, rows};
    cuuint64_t strides[1] = {cols * 2};
    cuuint32_t box[2] = {64, box_rows};
    cuuint32_t es[2] = {1, 1};
    enc(m, CU_TENSOR_MAP_DATA_TYPE_BFLOAT16, 2, const_cast<void*>(ptr), dims, strides, box, es, CU_TENSOR_MAP_INTERLEAVE_NONE,
        CU_TENSOR_MAP_SWIZZLE_128B, CU_TENSOR_MAP_L2_PROMOTION_L2_256B, CU_TENSOR_MAP_FLOAT_OOB_FILL_NONE);
}
template <typename T> static void* sym_addr(T& sym) { void* p = nullptr; cudaGetSymbolAddress(&p, sym); return p; }

extern "C" void kernel_launch(void* const* d_in, const int* in_sizes, int n_in, void* d_out, int out_size) {
    static Params prm;
    static RecParams rp;
    static bool ready = false;
    static const void* key[14];
    bool same = ready;
    for (int i = 0; i < 13 && same; i++) same = key[i] == d_in[i];
    same = same && key[13] == d_out;
    if (!same) {
        void* fn = nullptr;
        cudaDriverEntryPointQueryResult qr;
        cudaGetDriverEntryPoint("cuTensorMapEncodeTiled", &fn, cudaEnableDefault, &qr);
        EncodeFn enc = (EncodeFn)fn;
        make_map(enc, &prm.tm_h, sym_addr(g_h), S_, D_, 64);
        make_map(enc, &prm.tm_kv, sym_addr(g_kv), S_, 2 * HD_, 64);
        make_map(enc, &prm.tm_kvm, sym_addr(g_kvm), NSEG * 8, 2 * HD_, 32);
        make_map(enc, &prm.tm_o, sym_addr(g_o), S_, HD_, 64);
        make_map(enc, &prm.tm_op, sym_addr(g_op), OP_ROWS, D_, 64);
        make_map(enc, &prm.tm_h2, sym_addr(g_h2), S_, D_, 64);
        make_map(enc, &prm.tm_act, sym_addr(g_act), S_, DF_, 64);
        make_map(enc, &prm.tm_x1, sym_addr(g_x1), S_, D_, 64);
        make_map(enc, &prm.tm_out, d_out, S_, D_, 64);
        make_map(enc, &prm.tm_wq, d_in[2], D_, HD_, 64);
        make_map(enc, &prm.tm_wk, d_in[3], D_, HD_, 64);
        make_map(enc, &prm.tm_wv, d_in[4], D_, HD_, 64);
        make_map(enc, &prm.tm_wo, d_in[5], HD_, D_, 64);
        make_map(enc, &prm.tm_wg, d_in[8], D_, DF_, 64);
        make_map(enc, &prm.tm_wu, d_in[9], D_, DF_, 64);
        make_map(enc, &prm.tm_wd, d_in[10], DF_, D_, 64);
        prm.x = (const bf16*)d_in[0]; prm.c = (const bf16*)d_in[11]; prm.w_mod = (const bf16*)d_in[12];
        rp.mem0 = (const bf16*)d_in[1]; rp.x = prm.x; rp.c = prm.c; rp.w_mod = prm.w_mod;
        rp.wq = (const bf16*)d_in[2]; rp.wk = (const bf16*)d_in[3]; rp.wv = (const bf16*)d_in[4]; rp.wo = (const bf16*)d_in[5];
        cudaFuncSetAttribute(k_work, cudaFuncAttributeMaxDynamicSharedMemorySize, SMEM_BYTES);
        cudaFuncSetAttribute(k_rec, cudaFuncAttributeMaxDynamicSharedMemorySize, R_SMEM);
        cudaFuncSetAttribute(k_rec, cudaFuncAttributeNonPortableClusterSizeAllowed, 1);
        {
            cudaLaunchConfig_t cfg = {};
            cfg.gridDim = dim3(128); cfg.blockDim = dim3(384); cfg.dynamicSmemBytes = R_SMEM;
            cudaLaunchAttribute at[1];
            at[0].id = cudaLaunchAttributeClusterDimension; at[0].val.clusterDim.x = 16; at[0].val.clusterDim.y = 1; at[0].val.clusterDim.z = 1;
            cfg.attrs = at; cfg.numAttrs = 1;
            int n = 0;
            cudaOccupancyMaxActiveClusters(&n, k_rec, &cfg);
            rp.ncl = n < 4 ? 4 : (n > 8 ? 8 : n);
        }
        for (int i = 0; i < 13; i++) key[i] = d_in[i];
        key[13] = d_out;
        ready = true;
    }
    cudaStream_t st = cudaStreamPerThread;
    auto launch_rec = [&]() {
        cudaLaunchConfig_t cfg = {};
        cfg.gridDim = dim3(16 * rp.ncl); cfg.blockDim = dim3(384); cfg.dynamicSmemBytes = R_SMEM; cfg.stream = st;
        cudaLaunchAttribute at[1];
        at[0].id = cudaLaunchAttributeClusterDimension; at[0].val.clusterDim.x = 16; at[0].val.clusterDim.y = 1; at[0].val.clusterDim.z = 1;
        cfg.attrs = at; cfg.numAttrs = 1;
        cudaLaunchKernelEx(&cfg, k_rec, rp);
    };
    auto launch_work = [&](int qmask, int pdl) {
        prm.qmask = qmask;
        cudaLaunchConfig_t cfg = {};
        cfg.gridDim = dim3(132); cfg.blockDim = dim3(384); cfg.dynamicSmemBytes = SMEM_BYTES; cfg.stream = st;
        cudaLaunchAttribute at[1];
        at[0].id = cudaLaunchAttributeProgrammaticStreamSerialization; at[0].val.programmaticStreamSerializationAllowed = 1;
        cfg.attrs = at; cfg.numAttrs = pdl;
        cudaLaunchKernelEx(&cfg, k_work, prm);
    };
    launch_rec();
    launch_work(0xff, 1);
}
```

```cpp
#include <cuda_runtime.h>
#include <cuda_bf16.h>
#include <cuda.h>
#include <stdint.h>

typedef __nv_bfloat16 bf16;
#define IDLE_NS 150
#define FLAG_NS 20

constexpr int S_ = 2048, D_ = 512, H_ = 32, DH_ = 128, HD_ = 4096, NSEG = 64, DF_ = 1792;
constexpr int NRB = 16;
constexpr int OSPLIT = 4;

__device__ __align__(1024) bf16 g_h[S_ * D_];
__device__ __align__(1024) bf16 g_kv[S_ * 2 * HD_];
__device__ __align__(1024) bf16 g_kvm[NSEG * 8 * 2 * HD_];
__device__ __align__(1024) bf16 g_o[S_ * HD_];
#define FINE_RB_ 12
constexpr int FINE_RB = FINE_RB_;
#define OSPLIT2_ 8
constexpr int OSPLIT2 = OSPLIT2_;
constexpr int OSPLIT3 = 16;
constexpr int OP_ROWS = OSPLIT * S_ + OSPLIT2 * (NRB - FINE_RB) * 128 + OSPLIT3 * 128;
__device__ __align__(1024) bf16 g_op[OP_ROWS * D_];
__device__ __align__(1024) bf16 g_x1[S_ * D_];
__device__ __align__(1024) bf16 g_h2[S_ * D_];
__device__ __align__(1024) bf16 g_act[S_ * DF_];
__device__ __align__(1024) bf16 g_mod[6 * D_];
__device__ uint32_t g_Fraw[131072 + 65536 + 2048];
#define g_F ((uint32_t*)(((uint64_t)g_Fraw + 0x7FFFFull) & ~0x7FFFFull))
constexpr int F_H = 0, F_MEM = 32, F_O = 64, F_OP = 96, F_H2 = 128, F_ACT = 160, F_MOD = 192, F_KV = 224, F_CLAIM = 256  ,
              F_SIDE = 512  , F_DONE = 576, F_TOTAL = 608;
__device__ __align__(128) unsigned int g_flags[F_TOTAL];
#define TR(j, i) do {} while (0)

__device__ __forceinline__ uint32_t smem_u32(const void* p) { return (uint32_t)__cvta_generic_to_shared(p); }
__device__ __forceinline__ uint32_t clk32() { uint32_t c; asm volatile("mov.u32 %0, %%clock;" : "=r"(c)); return c; }
__device__ __forceinline__ uint32_t mapa_u32(uint32_t addr, uint32_t rank) {
    uint32_t r; asm volatile("mapa.shared::cluster.u32 %0, %1, %2;" : "=r"(r) : "r"(addr), "r"(rank)); return r;
}
__device__ __forceinline__ void mbar_init(uint32_t bar, uint32_t cnt) {
    asm volatile("mbarrier.init.shared::cta.b64 [%0], %1;" :: "r"(bar), "r"(cnt) : "memory");
}
__device__ __forceinline__ void mbar_inval(uint32_t bar) {
    asm volatile("mbarrier.inval.shared::cta.b64 [%0];" :: "r"(bar) : "memory");
}
__device__ __forceinline__ void mbar_expect_tx(uint32_t bar, uint32_t bytes) {
    asm volatile("mbarrier.arrive.expect_tx.shared::cta.b64 _, [%0], %1;" :: "r"(bar), "r"(bytes) : "memory");
}
__device__ __forceinline__ void mbar_arrive(uint32_t bar) {
    asm volatile("mbarrier.arrive.shared::cta.b64 _, [%0];" :: "r"(bar) : "memory");
}
__device__ __forceinline__ bool mbar_try_wait(uint32_t bar, uint32_t parity) {
    uint32_t ok;
    asm volatile("{\n.reg .pred p;\nmbarrier.try_wait.parity.shared::cta.b64 p, [%1], %2;\nselp.u32 %0, 1, 0, p;\n}"
                 : "=r"(ok) : "r"(bar), "r"(parity) : "memory");
    return ok;
}
__device__ __forceinline__ bool mbar_try_wait_cluster(uint32_t bar, uint32_t parity) {
    uint32_t ok;
    asm volatile("{\n.reg .pred p;\nmbarrier.try_wait.parity.acquire.cluster.shared::cta.b64 p, [%1], %2;\nselp.u32 %0, 1, 0, p;\n}"
                 : "=r"(ok) : "r"(bar), "r"(parity) : "memory");
    return ok;
}
constexpr int SPIN_LIMIT = 1 << 18;
#define TIMEOUT(code, info) do {} while (0)
__device__ __forceinline__ void mbar_wait(uint32_t bar, uint32_t parity) {
    int g = 0;
#pragma unroll 1
    while (!mbar_try_wait(bar, parity)) { if (++g >= SPIN_LIMIT) { TIMEOUT(0, bar & 255); break; } }
}
__device__ __forceinline__ void mbar_wait_cluster(uint32_t bar, uint32_t parity) {
    int g = 0;
#pragma unroll 1
    while (!mbar_try_wait_cluster(bar, parity)) { if (++g >= SPIN_LIMIT) { TIMEOUT(1, bar & 255); break; } }
}
__device__ __forceinline__ void bar_sync(int id, int n) { asm volatile("bar.sync %0, %1;" :: "r"(id), "r"(n) : "memory"); }
__device__ __forceinline__ void bar_arrive(int id, int n) { asm volatile("bar.arrive %0, %1;" :: "r"(id), "r"(n) : "memory"); }
__device__ __forceinline__ void cluster_sync_all() {
    asm volatile("barrier.cluster.arrive.aligned;\nbarrier.cluster.wait.aligned;" ::: "memory");
}
__device__ __forceinline__ void st_async_v2(uint32_t addr, float a, float b, uint32_t bar) {
    asm volatile("st.async.weak.shared::cluster.mbarrier::complete_tx::bytes.v2.f32 [%0], {%1,%2}, [%3];"
                 :: "r"(addr), "f"(a), "f"(b), "r"(bar) : "memory");
}
__device__ __forceinline__ void st_async_v4(uint32_t addr, uint4 v, uint32_t bar) {
    asm volatile("st.async.weak.shared::cluster.mbarrier::complete_tx::bytes.v4.b32 [%0], {%1,%2,%3,%4}, [%5];"
                 :: "r"(addr), "r"(v.x), "r"(v.y), "r"(v.z), "r"(v.w), "r"(bar) : "memory");
}
__device__ __forceinline__ uint2 ldg_relaxed2(const uint2* p) {
    uint2 v;
    asm volatile("ld.relaxed.gpu.global.v2.b32 {%0,%1}, [%2];" : "=r"(v.x), "=r"(v.y) : "l"(p) : "memory");
    return v;
}
__device__ __forceinline__ void stg_relaxed2(uint2* p, uint2 v) {
    asm volatile("st.relaxed.gpu.global.v2.b32 [%0], {%1,%2};" :: "l"(p), "r"(v.x), "r"(v.y) : "memory");
}
__device__ __forceinline__ uint4 ldg_relaxed(const uint4* p) {
    uint4 v;
    asm volatile("ld.relaxed.gpu.global.v4.b32 {%0,%1,%2,%3}, [%4];" : "=r"(v.x), "=r"(v.y), "=r"(v.z), "=r"(v.w) : "l"(p) : "memory");
    return v;
}
__device__ __forceinline__ void stg_relaxed(uint4* p, uint4 v) {
    asm volatile("st.relaxed.gpu.global.v4.b32 [%0], {%1,%2,%3,%4};" :: "l"(p), "r"(v.x), "r"(v.y), "r"(v.z), "r"(v.w) : "memory");
}
__device__ __forceinline__ void stg_relaxed32(uint32_t* p, uint32_t v) {
    asm volatile("st.relaxed.gpu.global.b32 [%0], %1;" :: "l"(p), "r"(v) : "memory");
}
__device__ __forceinline__ uint32_t ldg_relaxed32(const uint32_t* p) {
    uint32_t v; asm volatile("ld.relaxed.gpu.global.b32 %0, [%1];" : "=r"(v) : "l"(p) : "memory"); return v;
}
__device__ __forceinline__ unsigned int ld_acquire(const unsigned int* p) {
    unsigned int v; asm volatile("ld.acquire.gpu.global.u32 %0, [%1];" : "=r"(v) : "l"(p) : "memory"); return v;
}
__device__ __forceinline__ void red_release(unsigned int* p, unsigned int v) {
    asm volatile("red.release.gpu.global.add.u32 [%0], %1;" :: "l"(p), "r"(v) : "memory");
}
__device__ __forceinline__ void wait_flag(int idx, unsigned int target) {
    const unsigned int* p = &g_flags[idx];
    int g = 0;
#pragma unroll 1
    while (ld_acquire(p) < target) { __nanosleep(FLAG_NS); if (++g >= 64 * SPIN_LIMIT) { TIMEOUT(2, idx); break; } }
}
__device__ __forceinline__ void cp_async16(uint32_t dst, const void* src) {
    asm volatile("cp.async.cg.shared.global [%0], [%1], 16;" :: "r"(dst), "l"(src) : "memory");
}
__device__ __forceinline__ void cp_async_commit() { asm volatile("cp.async.commit_group;" ::: "memory"); }
template <int N> __device__ __forceinline__ void cp_async_wait() { asm volatile("cp.async.wait_group %0;" :: "n"(N) : "memory"); }
__device__ __forceinline__ void ldsm4(uint32_t& r0, uint32_t& r1, uint32_t& r2, uint32_t& r3, uint32_t addr) {
    asm volatile("ldmatrix.sync.aligned.m8n8.x4.shared.b16 {%0,%1,%2,%3}, [%4];" : "=r"(r0), "=r"(r1), "=r"(r2), "=r"(r3) : "r"(addr) : "memory");
}
__device__ __forceinline__ void ldsm4t(uint32_t& r0, uint32_t& r1, uint32_t& r2, uint32_t& r3, uint32_t addr) {
    asm volatile("ldmatrix.sync.aligned.m8n8.x4.trans.shared.b16 {%0,%1,%2,%3}, [%4];" : "=r"(r0), "=r"(r1), "=r"(r2), "=r"(r3) : "r"(addr) : "memory");
}
__device__ __forceinline__ void ldsm2t(uint32_t& r0, uint32_t& r1, uint32_t addr) {
    asm volatile("ldmatrix.sync.aligned.m8n8.x2.trans.shared.b16 {%0,%1}, [%2];" : "=r"(r0), "=r"(r1) : "r"(addr) : "memory");
}
__device__ __forceinline__ void stsm4(uint32_t addr, uint32_t r0, uint32_t r1, uint32_t r2, uint32_t r3) {
    asm volatile("stmatrix.sync.aligned.m8n8.x4.shared.b16 [%0], {%1,%2,%3,%4};" :: "r"(addr), "r"(r0), "r"(r1), "r"(r2), "r"(r3) : "memory");
}
__device__ __forceinline__ void stsm2t(uint32_t addr, uint32_t r0, uint32_t r1) {
    asm volatile("stmatrix.sync.aligned.m8n8.x2.trans.shared.b16 [%0], {%1,%2};" :: "r"(addr), "r"(r0), "r"(r1) : "memory");
}
__device__ __forceinline__ void mma16816(float* d, uint32_t a0, uint32_t a1, uint32_t a2, uint32_t a3, uint32_t b0, uint32_t b1) {
    asm volatile("mma.sync.aligned.m16n8k16.row.col.f32.bf16.bf16.f32 {%0,%1,%2,%3}, {%4,%5,%6,%7}, {%8,%9}, {%0,%1,%2,%3};"
                 : "+f"(d[0]), "+f"(d[1]), "+f"(d[2]), "+f"(d[3]) : "r"(a0), "r"(a1), "r"(a2), "r"(a3), "r"(b0), "r"(b1));
}
__device__ __forceinline__ void mma1688(float* d, uint32_t a0, uint32_t a1, uint32_t b0) {
    asm volatile("mma.sync.aligned.m16n8k8.row.col.f32.bf16.bf16.f32 {%0,%1,%2,%3}, {%4,%5}, {%6}, {%0,%1,%2,%3};"
                 : "+f"(d[0]), "+f"(d[1]), "+f"(d[2]), "+f"(d[3]) : "r"(a0), "r"(a1), "r"(b0));
}
__device__ __forceinline__ void mma16816h(float* d, uint32_t a0, uint32_t a2, uint32_t b0, uint32_t b1) {
    asm volatile("{\n.reg .b32 ju, jv;\nmma.sync.aligned.m16n8k16.row.col.f32.bf16.bf16.f32 {%0,%1,%2,%3}, {%4,ju,%5,jv}, {%6,%7}, {%0,%1,%2,%3};\n}"
                 : "+f"(d[0]), "+f"(d[1]), "+f"(d[2]), "+f"(d[3]) : "r"(a0), "r"(a2), "r"(b0), "r"(b1));
}
__device__ __forceinline__ void mma1688h(float* d, uint32_t a0, uint32_t b0) {
    asm volatile("{\n.reg .b32 ju;\nmma.sync.aligned.m16n8k8.row.col.f32.bf16.bf16.f32 {%0,%1,%2,%3}, {%4,ju}, {%5}, {%0,%1,%2,%3};\n}"
                 : "+f"(d[0]), "+f"(d[1]), "+f"(d[2]), "+f"(d[3]) : "r"(a0), "r"(b0));
}
__device__ __forceinline__ uint32_t pack2(float lo, float hi) {
    uint32_t r; asm("cvt.rn.bf16x2.f32 %0, %1, %2;" : "=r"(r) : "f"(hi), "f"(lo)); return r;
}
__device__ __forceinline__ float bflo(uint32_t w) { return __uint_as_float(w << 16); }
__device__ __forceinline__ float bfhi(uint32_t w) { return __uint_as_float(w & 0xffff0000u); }
__device__ __forceinline__ float rbf(float x) { return __bfloat162float(__float2bfloat16_rn(x)); }
__device__ __forceinline__ float ex2(float x) { float y; asm("ex2.approx.ftz.f32 %0, %1;" : "=f"(y) : "f"(x)); return y; }
__device__ __forceinline__ void sts128(uint32_t addr, uint4 v) {
    asm volatile("st.shared.v4.b32 [%0], {%1,%2,%3,%4};" :: "r"(addr), "r"(v.x), "r"(v.y), "r"(v.z), "r"(v.w) : "memory");
}
__device__ __forceinline__ uint4 lds128(uint32_t addr) {
    uint4 v; asm volatile("ld.shared.v4.b32 {%0,%1,%2,%3}, [%4];" : "=r"(v.x), "=r"(v.y), "=r"(v.z), "=r"(v.w) : "r"(addr) : "memory"); return v;
}
__device__ __forceinline__ float2 lds64f(uint32_t addr) {
    float2 v; asm volatile("ld.shared.v2.f32 {%0,%1}, [%2];" : "=f"(v.x), "=f"(v.y) : "r"(addr) : "memory"); return v;
}
__device__ __forceinline__ float lds32f(uint32_t addr) {
    float v; asm volatile("ld.shared.f32 %0, [%1];" : "=f"(v) : "r"(addr) : "memory"); return v;
}
__device__ __forceinline__ uint32_t lds32(uint32_t addr) {
    uint32_t v; asm volatile("ld.shared.b32 %0, [%1];" : "=r"(v) : "r"(addr) : "memory"); return v;
}
__device__ __forceinline__ void sts32(uint32_t addr, uint32_t v) { asm volatile("st.shared.b32 [%0], %1;" :: "r"(addr), "r"(v) : "memory"); }
__device__ __forceinline__ void sts64f(uint32_t addr, float a, float b) { asm volatile("st.shared.v2.f32 [%0], {%1,%2};" :: "r"(addr), "f"(a), "f"(b) : "memory"); }

__device__ __forceinline__ void tma_load2d(uint32_t dst, const CUtensorMap* tm, int c0, int c1, uint32_t bar) {
    asm volatile("cp.async.bulk.tensor.2d.shared::cluster.global.mbarrier::complete_tx::bytes [%0], [%1, {%3, %4}], [%2];"
                 :: "r"(dst), "l"(tm), "r"(bar), "r"(c0), "r"(c1) : "memory");
}
__device__ __forceinline__ void tma_store2d(const CUtensorMap* tm, uint32_t src, int c0, int c1) {
    asm volatile("cp.async.bulk.tensor.2d.global.shared::cta.bulk_group [%0, {%2, %3}], [%1];"
                 :: "l"(tm), "r"(src), "r"(c0), "r"(c1) : "memory");
}
__device__ __forceinline__ void bulk_commit() { asm volatile("cp.async.bulk.commit_group;" ::: "memory"); }
__device__ __forceinline__ void bulk_wait0() { asm volatile("cp.async.bulk.wait_group 0;" ::: "memory"); }
__device__ __forceinline__ void fence_async_smem() { asm volatile("fence.proxy.async.shared::cta;" ::: "memory"); }
__device__ __forceinline__ void fence_async_all() { asm volatile("fence.proxy.async;" ::: "memory"); }

__device__ __forceinline__ void wg_fence() { asm volatile("wgmma.fence.sync.aligned;" ::: "memory"); }
__device__ __forceinline__ void wg_commit() { asm volatile("wgmma.commit_group.sync.aligned;" ::: "memory"); }
__device__ __forceinline__ void wg_wait0() { asm volatile("wgmma.wait_group.sync.aligned 0;" ::: "memory"); }
__device__ __forceinline__ uint64_t mkdesc(uint32_t saddr, uint32_t lbo, uint32_t sbo) {
    return (uint64_t)((saddr & 0x3FFFF) >> 4) | ((uint64_t)(lbo >> 4) << 16) | ((uint64_t)(sbo >> 4) << 32) | (1ull << 62);
}
#define ACC8(i) "+f"(d[i]), "+f"(d[i + 1]), "+f"(d[i + 2]), "+f"(d[i + 3]), "+f"(d[i + 4]), "+f"(d[i + 5]), "+f"(d[i + 6]), "+f"(d[i + 7])
__device__ __forceinline__ void wgmma_n256(float* d, uint64_t da, uint64_t db, int scale_d) {
    asm volatile(
        "{\n.reg .pred p;\nsetp.ne.b32 p, %130, 0;\n"
        "wgmma.mma_async.sync.aligned.m64n256k16.f32.bf16.bf16 "
        "{%0,%1,%2,%3,%4,%5,%6,%7,%8,%9,%10,%11,%12,%13,%14,%15,%16,%17,%18,%19,%20,%21,%22,%23,%24,%25,%26,%27,%28,%29,%30,%31,"
        "%32,%33,%34,%35,%36,%37,%38,%39,%40,%41,%42,%43,%44,%45,%46,%47,%48,%49,%50,%51,%52,%53,%54,%55,%56,%57,%58,%59,%60,%61,%62,%63,"
        "%64,%65,%66,%67,%68,%69,%70,%71,%72,%73,%74,%75,%76,%77,%78,%79,%80,%81,%82,%83,%84,%85,%86,%87,%88,%89,%90,%91,%92,%93,%94,%95,"
        "%96,%97,%98,%99,%100,%101,%102,%103,%104,%105,%106,%107,%108,%109,%110,%111,%112,%113,%114,%115,%116,%117,%118,%119,%120,%121,%122,%123,%124,%125,%126,%127}, "
        "%128, %129, p, 1, 1, 0, 1;\n}"
        : ACC8(0), ACC8(8), ACC8(16), ACC8(24), ACC8(32), ACC8(40), ACC8(48), ACC8(56),
          ACC8(64), ACC8(72), ACC8(80), ACC8(88), ACC8(96), ACC8(104), ACC8(112), ACC8(120)
        : "l"(da), "l"(db), "r"(scale_d));
}
__device__ __forceinline__ void wgmma_n128(float* d, uint64_t da, uint64_t db, int scale_d) {
    asm volatile(
        "{\n.reg .pred p;\nsetp.ne.b32 p, %66, 0;\n"
        "wgmma.mma_async.sync.aligned.m64n128k16.f32.bf16.bf16 "
        "{%0,%1,%2,%3,%4,%5,%6,%7,%8,%9,%10,%11,%12,%13,%14,%15,%16,%17,%18,%19,%20,%21,%22,%23,%24,%25,%26,%27,%28,%29,%30,%31,"
        "%32,%33,%34,%35,%36,%37,%38,%39,%40,%41,%42,%43,%44,%45,%46,%47,%48,%49,%50,%51,%52,%53,%54,%55,%56,%57,%58,%59,%60,%61,%62,%63}, "
        "%64, %65, p, 1, 1, 0, 1;\n}"
        : ACC8(0), ACC8(8), ACC8(16), ACC8(24), ACC8(32), ACC8(40), ACC8(48), ACC8(56)
        : "l"(da), "l"(db), "r"(scale_d));
}

__device__ __forceinline__ void wgmma_n64(float* d, uint64_t da, uint64_t db) {
    asm volatile(
        "wgmma.mma_async.sync.aligned.m64n64k16.f32.bf16.bf16 "
        "{%0,%1,%2,%3,%4,%5,%6,%7,%8,%9,%10,%11,%12,%13,%14,%15,%16,%17,%18,%19,%20,%21,%22,%23,%24,%25,%26,%27,%28,%29,%30,%31}, "
        "%32, %33, 1, 1, 1, 0, 1;"
        : ACC8(0), ACC8(8), ACC8(16), ACC8(24)
        : "l"(da), "l"(db));
}
__device__ __forceinline__ void wgmma_n8_ta(float* d, uint64_t da, uint64_t db, int scale_d) {
    asm volatile(
        "{\n.reg .pred p;\nsetp.ne.b32 p, %6, 0;\n"
        "wgmma.mma_async.sync.aligned.m64n8k16.f32.bf16.bf16 {%0,%1,%2,%3}, %4, %5, p, 1, 1, 1, 0;\n}"
        : "+f"(d[0]), "+f"(d[1]), "+f"(d[2]), "+f"(d[3]) : "l"(da), "l"(db), "r"(scale_d));
}

__device__ __forceinline__ uint32_t hadd2(uint32_t a, uint32_t b) { uint32_t r; asm("add.rn.bf16x2 %0, %1, %2;" : "=r"(r) : "r"(a), "r"(b)); return r; }
__device__ __forceinline__ uint32_t hsub2(uint32_t a, uint32_t b) { uint32_t r; asm("sub.rn.bf16x2 %0, %1, %2;" : "=r"(r) : "r"(a), "r"(b)); return r; }
__device__ __forceinline__ uint32_t hmul2(uint32_t a, uint32_t b) { uint32_t r; asm("mul.rn.bf16x2 %0, %1, %2;" : "=r"(r) : "r"(a), "r"(b)); return r; }
__device__ __forceinline__ void load_mod8(const bf16* m, int lane, uint32_t* v) {
    const uint4 a = __ldcg((const uint4*)m + lane), b = __ldcg((const uint4*)m + 32 + lane);
    v[0] = a.x; v[1] = a.y; v[2] = a.z; v[3] = a.w; v[4] = b.x; v[5] = b.y; v[6] = b.z; v[7] = b.w;
}
__device__ __forceinline__ void ln_stats(const uint32_t* x, uint32_t& mu2, float& rden) {
    float s = 0.f;
#pragma unroll
    for (int i = 0; i < 8; i++) s += bflo(x[i]) + bfhi(x[i]);
#pragma unroll
    for (int o = 16; o > 0; o >>= 1) s += __shfl_xor_sync(~0u, s, o);
    const float mean = s * (1.f / D_);
    float q = 0.f;
#pragma unroll
    for (int i = 0; i < 8; i++) { const float d0 = bflo(x[i]) - mean, d1 = bfhi(x[i]) - mean; q = fmaf(d0, d0, q); q = fmaf(d1, d1, q); }
#pragma unroll
    for (int o = 16; o > 0; o >>= 1) q += __shfl_xor_sync(~0u, q, o);
    mu2 = pack2(mean, mean);
    rden = __frcp_rn(rbf(__fsqrt_rn(rbf(rbf(q * (1.f / D_)) + 1e-5f))));
}
__device__ __forceinline__ void ln_apply(const uint32_t* x, uint32_t mu2, float rden, const uint32_t* c1, const uint32_t* sm, uint32_t* r) {
#pragma unroll
    for (int i = 0; i < 8; i++) {
        const uint32_t d = hsub2(x[i], mu2);
        r[i] = hadd2(hmul2(pack2(bflo(d) * rden, bfhi(d) * rden), c1[i]), sm[i]);
    }
}

struct __align__(64) Params {
    CUtensorMap tm_h, tm_kv, tm_kvm, tm_o, tm_op, tm_h2, tm_act, tm_x1, tm_out;
    CUtensorMap tm_wq, tm_wk, tm_wv, tm_wo, tm_wg, tm_wu, tm_wd;
    const bf16 *x, *c, *w_mod;
    int qmask;
};

constexpr int R_NST = 3;
constexpr uint32_t R_WV = 0, R_MEM = 65536, R_KX = 73728, R_VX = R_KX + R_NST * 4096,
                   R_KMS = R_VX + R_NST * 4096  , R_VMS = R_KMS + 1024,
                   R_QS = R_KMS + 4096, R_OS = R_QS + 1024, R_SX = R_OS + 1024, R_BAR = R_SX + 2560,
                   R_RS = 107520  , R_VP = R_RS + 8192  ,
                   R_STG = R_VP + 8192  , R_SMEM = R_STG + 98304;
static_assert((R_KMS & 4095) == 0, "smem");
static_assert(R_BAR + 64 <= R_RS, "smem");
constexpr uint32_t RB_SX = R_BAR, RB_V = R_BAR + 8, RB_E = R_BAR + 16, RB_A = R_BAR + 24, RB_ROLE = R_BAR + 32, RB_A1 = R_BAR + 40;
constexpr int W_NST = 4;
constexpr uint32_t W_STAGE = 49152, W_STG = W_NST * W_STAGE  , W_END = W_STG + 32768;
constexpr uint32_t SM_BAR = W_END;
constexpr uint32_t SMEM_BYTES = W_END + 1024 + 2048;
constexpr uint32_t B_FULL = 0, B_EMPTY = 32, B_STGFREE = 64, B_REQ = 80, B_RSP = 88, B_NEXT = 96, B_RING = 128;
#define PICK_AHEAD 3

constexpr int NB_X = 11  , NB_Y = 1, NB_M = 5, NB_K = 5, NB_B = 2, NB_C = 3, NB_D = 4, NB_W0 = 6  , NB_ST = 9  ;

__device__ __forceinline__ int pos_of_d(int d) {
    const int rem = d & 31;
    return (d & ~31) + ((rem & 7) >> 1) * 8 + (rem & 1) * 4 + (rem >> 3);
}

#define PROF(i) do {} while (0)
#define PROFG(i) do {} while (0)
#define OPAQUE(x) asm volatile("" : "+r"(x))
#define FENCE_SCHED(x) do { if ((x) == 0u) asm volatile("trap;"); } while (0)
#define QKVAR 2
#define VK0_ 4
constexpr int VK0 = VK0_;
constexpr int NOFF = 8;
#define VDELAY -1
#define POLL_GAP 110

struct RecParams { const bf16 *mem0, *wq, *wk, *wv, *wo, *x, *c, *w_mod; int ncl, only_pre; };

__device__ __forceinline__ void rec_qk(const RecParams& p, const uint32_t sb, const int cta, const int warp, int lane, const int sel) {
    const int crank = cta & 15, cl = cta >> 4, rank = cta & 1;
    const int kh = warp >> 2, aa = warp & 3;
    uint32_t wa[2][16][4];
    const uint32_t stg = sb + R_STG + kh * 32768;
    {
        const int t128 = aa * 32 + lane;
        const int row = (lane >> 4) * 8 + (lane & 7);
        const int ch = t128 & 7;
        const size_t goff = (size_t)kh * 256 * HD_ + cta * 64 + ch * 8;
#pragma unroll 4
        for (int dd = 0; dd < 16; dd++) {
            const int d = dd * 16 + (t128 >> 3), pp = pos_of_d(d);
            cp_async16(sb + R_WV + kh * 32768 + pp * 128 + ((ch ^ (pp & 7)) << 4), p.wv + goff + (size_t)d * HD_);
        }
        cp_async_commit();
#pragma unroll 4
        for (int dd = 0; dd < 16; dd++) {
            const int d = dd * 16 + (t128 >> 3), pp = pos_of_d(d);
            cp_async16(stg + pp * 128 + ((ch ^ (pp & 7)) << 4), p.wq + goff + (size_t)d * HD_);
        }
        cp_async_commit();
        {
            const int i0 = (warp * 32 + lane) * 16, tok = i0 >> 9;
            const uint4 m0 = __ldg((const uint4*)(p.mem0 + i0)), m1 = __ldg((const uint4*)(p.mem0 + i0 + 8));
            const uint32_t mw[8] = {m0.x, m0.y, m0.z, m0.w, m1.x, m1.y, m1.z, m1.w};
#pragma unroll
            for (int e = 0; e < 16; e++) {
                const int pp = pos_of_d((i0 & 511) + e);
                const unsigned short v = (unsigned short)(mw[e >> 1] >> ((e & 1) * 16));
                asm volatile("st.shared.u16 [%0], %1;" :: "r"(sb + R_MEM + (pp >> 3) * 128 + tok * 16 + (pp & 7) * 2), "h"(v) : "memory");
            }
        }
        cp_async_wait<1>();
        bar_sync(NB_W0 + kh, 128);
        const uint32_t fv = row * 128 + (((2 * aa + ((lane >> 3) & 1)) ^ (row & 7)) << 4);
#pragma unroll
        for (int ks = 0; ks < 16; ks++) ldsm4t(wa[0][ks][0], wa[0][ks][1], wa[0][ks][2], wa[0][ks][3], sb + R_WV + kh * 32768 + fv + ks * 2048);
        bar_sync(NB_W0 + kh, 128);
#pragma unroll
        for (int ks = 0; ks < 16; ks++)
            sts128(sb + R_WV + kh * 32768 + (aa * 16 + ks) * 512 + lane * 16, make_uint4(wa[0][ks][0], wa[0][ks][1], wa[0][ks][2], wa[0][ks][3]));
        const uint32_t fo = stg + row * 128 + (((4 * (aa & 1) + ((lane >> 3) & 1)) ^ (row & 7)) << 4);
#pragma unroll 1
        for (int m = 0; m < 2; m++) {
            cp_async_wait<0>();
            bar_sync(NB_W0 + kh, 128);
            if ((aa >> 1) == m) {
#pragma unroll
                for (int ks = 0; ks < 16; ks++) {
                    ldsm4t(wa[0][ks][0], wa[0][ks][1], wa[0][ks][2], wa[0][ks][3], fo + ks * 2048);
                    ldsm4t(wa[1][ks][0], wa[1][ks][1], wa[1][ks][2], wa[1][ks][3], (fo ^ 32) + ks * 2048);
                }
            }
            bar_sync(NB_W0 + kh, 128);
            if (m == 0) {
#pragma unroll 4
                for (int dd = 0; dd < 16; dd++) {
                    const int d = dd * 16 + (t128 >> 3), pp = pos_of_d(d);
                    cp_async16(stg + pp * 128 + ((ch ^ (pp & 7)) << 4), p.wk + goff + (size_t)d * HD_);
                }
                cp_async_commit();
            }
        }
    }
    const uint32_t tab = stg + (aa * 32 + lane) * 16;
    {
        const uint32_t l7 = lane & 7, l8 = lane >> 3, g = lane >> 2, t = lane & 3;
        const uint32_t t0 = l7 * 128 + ((l8 ^ l7) << 4);
        const uint32_t tq = l7 * 128 + (((l8 >> 1) ^ l7) << 4);
        const uint32_t bq = warp >> 1, tp = warp & 1;
        uint4 v;
        v.x = sb + (aa < 2 ? R_QS : R_KMS) + l7 * 128 + (((4 * (aa & 1) + 2 * kh + (l8 & 1)) ^ l7) << 4);
        v.y = sb + R_QS + tq;
        v.z = sb + (warp == 0 ? R_KMS : R_KX + (warp - 1) * 1024) + t0;
        v.w = mapa_u32(sb + R_SX + (rank * 5 + warp) * 256 + lane * 8, crank ^ 1);
        sts128(tab, v);
        sts128(tab + 2048, make_uint4(sb + lane * 16 + R_MEM + kh * 4096, sb + lane * 16 + R_WV + warp * 8192,
                                      sb + lane * 16 + R_VP + warp * 512, sb + lane * 16 + R_VP + 4096 + (warp ^ 4) * 512));
        const uint32_t src = (l8 >> 1) * 8 + l7;
        const uint32_t L = bq * 8 + 2 * tp + (l8 & 1);
        const uint32_t d0 = (crank + ((t >> 1) | (g & 6))) & 15;
        v.x = sb + R_RS + src * 512 + ((L ^ (src & 7)) << 4);
        v.y = mapa_u32(sb + R_MEM + (crank * 4 + bq) * 128 + (4 * tp + 2 * (t & 1) + (g & 1)) * 16, d0);
        v.z = mapa_u32(sb + ((crank & 2) ? RB_A1 : RB_A), d0);
        v.w = lane;
        sts128(tab + 4096, v);
        const uint64_t wr = (uint64_t)(g_F + ((crank * 2 + ((crank ^ (crank >> 3) ^ sel) & 1)) * 1024 + warp * 128 + cl * 32 + lane));
        sts128(tab + 6144, make_uint4((uint32_t)wr, (uint32_t)(wr >> 32), (uint32_t)((((cl + 1) & 3) - cl) * 128), (uint32_t)((((cl + 2) & 3) - cl) * 128)));
        sts32(tab + 8192, (uint32_t)((((cl + 3) & 3) - cl) * 128));
#pragma unroll
        for (int i = 0; i < NOFF; i++)
            sts128(tab + 10240 + i * 2048, make_uint4(wa[i & 1][i >> 1][0], wa[i & 1][i >> 1][1], wa[i & 1][i >> 1][2], wa[i & 1][i >> 1][3]));
    }
    bar_sync(NB_D, 384);
    uint32_t slot_off = 0;
    const uint32_t slot_inc = warp == 0 ? 2048 : 4096, slot_last = warp == 0 ? 2048 : (R_NST - 1) * 4096;
    const uint32_t sx_bar_rem = (sb + RB_SX) ^ (1u << 24);
    uint4 tb = lds128(tab + 2048);
#pragma unroll 1
    for (int s = 0; s < NSEG; s++) {
        if (s > 0) mbar_wait(sb + RB_A, (s - 1) & 1);
        if (warp == 0) { PROF(0); PROFG(13); }
        uint4 ta;
        const uint32_t km_tog = aa >= 2 ? (s & 1) * 2048 : 0;
        {
            float acc[5][4];
#pragma unroll
            for (int c = 0; c < 5; c++) { acc[c][0] = acc[c][1] = acc[c][2] = acc[c][3] = 0.f; }
            uint32_t b[8][4];
            uint4 av[16];
            static_assert(VK0 == 4, "order below assumes the V/O warps cover slices 0,1");
#define QK4(k2) do { \
                mma16816(acc[0], wa[0][2 * (k2)][0], wa[0][2 * (k2)][1], wa[0][2 * (k2)][2], wa[0][2 * (k2)][3], b[k2][0], b[k2][1]); \
                mma16816(acc[1], wa[1][2 * (k2)][0], wa[1][2 * (k2)][1], wa[1][2 * (k2)][2], wa[1][2 * (k2)][3], b[k2][0], b[k2][1]); \
                mma16816(acc[3], wa[0][2 * (k2) + 1][0], wa[0][2 * (k2) + 1][1], wa[0][2 * (k2) + 1][2], wa[0][2 * (k2) + 1][3], b[k2][2], b[k2][3]); \
                mma16816(acc[4], wa[1][2 * (k2) + 1][0], wa[1][2 * (k2) + 1][1], wa[1][2 * (k2) + 1][2], wa[1][2 * (k2) + 1][3], b[k2][2], b[k2][3]); } while (0)
#define V2(k2) do { \
                mma16816(acc[2], av[2 * (k2)].x, av[2 * (k2)].y, av[2 * (k2)].z, av[2 * (k2)].w, b[k2][0], b[k2][1]); \
                mma16816(acv, av[2 * (k2) + 1].x, av[2 * (k2) + 1].y, av[2 * (k2) + 1].z, av[2 * (k2) + 1].w, b[k2][2], b[k2][3]); } while (0)
#define LB(k2) ldsm4(b[k2][0], b[k2][1], b[k2][2], b[k2][3], tb.x + (k2) * 512)
#define LV(k2) do { av[2 * (k2)] = lds128(tb.y + 2 * (k2) * 512); av[2 * (k2) + 1] = lds128(tb.y + (2 * (k2) + 1) * 512); } while (0)
            float acv[4] = {0.f, 0.f, 0.f, 0.f};
            LB(0); LB(1); LB(4); LB(5);
            QK4(0); QK4(1); LV(4); LV(5); QK4(4); QK4(5);
            if (s > 0) mbar_wait(sb + RB_A1, (s - 1) & 1);
            LB(2); LB(3); LB(6); LB(7); ta = lds128(tab);
            V2(4); V2(5); LV(2); LV(3);
            QK4(2); QK4(3); QK4(6); QK4(7);
            LV(6); LV(7);
#pragma unroll
            for (int i = 0; i < 4; i++) { acc[0][i] += acc[3][i]; acc[1][i] += acc[4][i]; }
            const float g0 = kh ? acc[0][0] : acc[1][0], g1 = kh ? acc[0][1] : acc[1][1], g2 = kh ? acc[0][2] : acc[1][2], g3 = kh ? acc[0][3] : acc[1][3];
            sts128(tb.w, make_uint4(__float_as_uint(g0), __float_as_uint(g1), __float_as_uint(g2), __float_as_uint(g3)));
            const float k0 = kh ? acc[1][0] : acc[0][0], k1 = kh ? acc[1][1] : acc[0][1], k2_ = kh ? acc[1][2] : acc[0][2], k3 = kh ? acc[1][3] : acc[0][3];
            if (warp == 0) PROF(1);
            V2(2); V2(3);
            bar_sync(NB_X + aa, 64);
            const uint4 o = lds128(tb.z + 4096);
            V2(6); V2(7);
            stsm2t(ta.x ^ km_tog, pack2(k0 + __uint_as_float(o.x), k1 + __uint_as_float(o.y)), pack2(k2_ + __uint_as_float(o.z), k3 + __uint_as_float(o.w)));
            sts128(tb.z, make_uint4(__float_as_uint(acc[2][0] + acv[0]), __float_as_uint(acc[2][1] + acv[1]), __float_as_uint(acc[2][2] + acv[2]), __float_as_uint(acc[2][3] + acv[3])));
        }
        const uint32_t kb = ta.z + slot_off;
        if (warp == 0) PROF(14);
        bar_sync(NB_B, 256);
        if (warp < 5) {
            uint32_t q[16], k0, k1, k2, k3, k4, k5, k6, k7;
            float sa[4] = {0.f, 0.f, 0.f, 0.f}, sc[4] = {0.f, 0.f, 0.f, 0.f};
            ldsm4(q[0], q[1], q[2], q[3], ta.y);
            ldsm4(k0, k1, k2, k3, kb);
            ldsm4(q[4], q[5], q[6], q[7], ta.y ^ 32);
            ldsm4(q[8], q[9], q[10], q[11], ta.y ^ 64);
            ldsm4(k4, k5, k6, k7, kb ^ 64);
            ldsm4(q[12], q[13], q[14], q[15], ta.y ^ 96);
            mma16816(sa, q[0], q[1], q[2], q[3], k0, k1);
            bar_arrive(NB_Y, 288);
            mma16816(sc, q[4], q[5], q[6], q[7], k2, k3);
            mma16816(sa, q[8], q[9], q[10], q[11], k4, k5);
            mma16816(sc, q[12], q[13], q[14], q[15], k6, k7);
            const float scl = 0.08838834764831845f * 1.4426950408889634f;
            const float r0 = (sa[0] + sc[0]) * scl, r1 = (sa[1] + sc[1]) * scl;
            if (s != NSEG - 1) {
                st_async_v2(ta.w, r0, r1, sx_bar_rem);
                st_async_v2(ta.w ^ (1u << 24), r0, r1, sx_bar_rem ^ (1u << 24));
            }
            if (warp == 0) PROF(2);
        } else if (s > 0 && warp == 7 && lane == 0) {
            mbar_expect_tx(sb + RB_A, 4096);
            mbar_expect_tx(sb + RB_A1, 4096);
        } else if (s > 0 && (s & 3) == 0 && warp == 6) {
            bar_sync(NB_K, 160);
            if (lane == 0) red_release(&g_flags[F_MEM + (s >> 2) - 1], 1);
            __syncwarp();
        }
        if (s == NSEG - 1) {
            const uint4 td = lds128(tab + 6144);
            stg_relaxed32((uint32_t*)(((uint64_t)td.y << 32) | (td.x ^ 0x21000)), 0u);
            break;
        }
        slot_off = slot_off == slot_last ? 0 : slot_off + slot_inc;
        const uint4 tc = lds128(tab + 4096), td = lds128(tab + 6144);
        const uint32_t te = lds32(tab + 8192);
        uint32_t* wr = (uint32_t*)(((uint64_t)td.y << 32) | (td.x ^ ((s & 1) * 0x21000)));
        const uint32_t* r1p = (const uint32_t*)((const char*)wr + (int)td.z);
        const uint32_t* r2p = (const uint32_t*)((const char*)wr + (int)td.w);
        const uint32_t* r3p = (const uint32_t*)((const char*)wr + (int)te);
        const uint32_t tag = ((s >> 1) + 1) & 1;
        mbar_wait(sb + RB_E, s & 1);
        if (warp == 0) PROF(7);
        {
            uint32_t a0, a1, a2, a3, a4, a5, a6, a7;
            ldsm4t(a0, a1, a2, a3, tc.x);
            ldsm4t(a4, a5, a6, a7, tc.x ^ 64);
            const uint32_t one = 0x3F803F80u;
            float d0_[4] = {0.f, 0.f, 0.f, 0.f}, d1_[4] = {0.f, 0.f, 0.f, 0.f};
            mma16816(d0_, a0, a1, a2, a3, one, one);
            mma16816(d1_, a4, a5, a6, a7, one, one);
            const bool t1 = tc.w & 1, t2 = tc.w & 2;
            const float x = t2 ? (t1 ? d1_[2] : d1_[0]) : (t1 ? d0_[2] : d0_[0]);
            const uint32_t own = (__float_as_uint(x) & ~1u) | tag;
            stg_relaxed32(wr, own);
            const uint32_t tq = clk32();
            if (warp == 0) PROF(8);
            PROFG(16 + warp);
            while ((int)(clk32() - tq) < POLL_GAP) {}
            uint32_t f1 = ldg_relaxed32(r1p), f2 = ldg_relaxed32(r2p), f3 = ldg_relaxed32(r3p);
#pragma unroll
            for (int i = 0; i < NOFF; i++) {
                const uint4 f0 = lds128(tab + 10240 + i * 2048);
                wa[i & 1][i >> 1][0] = f0.x; wa[i & 1][i >> 1][1] = f0.y; wa[i & 1][i >> 1][2] = f0.z; wa[i & 1][i >> 1][3] = f0.w;
            }
            tb = lds128(tab + 2048);
            int gg = 0;
#pragma unroll 1
            while (!__all_sync(~0u, (((f1 ^ tag) | (f2 ^ tag) | (f3 ^ tag)) & 1) == 0)) {
                f1 = ldg_relaxed32(r1p); f2 = ldg_relaxed32(r2p); f3 = ldg_relaxed32(r3p);
                if (++gg > 16 * SPIN_LIMIT) { TIMEOUT(3, s); break; }
            }
            if (warp == 0) PROF(9);
            const float v = (__uint_as_float(own) + __uint_as_float(f2)) + (__uint_as_float(f1) + __uint_as_float(f3));
            const bool b8 = tc.w & 8, b16 = tc.w & 16;
            const float recv = __shfl_xor_sync(~0u, v, 8);
            const uint32_t word = b8 ? pack2(recv, v) : pack2(v, recv);
            const uint32_t oth = __shfl_xor_sync(~0u, word, 16);
            const uint32_t wl = b16 ? oth : word, wh = b16 ? word : oth;
            const uint32_t p0 = __shfl_xor_sync(~0u, wl, 2), p1 = __shfl_xor_sync(~0u, wh, 2);
            const uint4 item = t2 ? make_uint4(p0, p1, wl, wh) : make_uint4(wl, wh, p0, p1);
            st_async_v4(tc.y, item, tc.z);
            st_async_v4(tc.y ^ (8u << 24), item, tc.z ^ (8u << 24));
            if (tc.w == 0 && warp == 7) mbar_expect_tx(sb + RB_E, 8192);
            if (warp == 0) PROF(10);
            PROF(40 + warp);
        }
        bar_sync(NB_D, 384);
    }
}

__device__ __forceinline__ void rec_load_kv(uint32_t sb, int col0, int s, uint32_t slot_off, int t128) {
    const int row = t128 >> 2, c2 = (t128 & 3) * 2;
    const bf16* src = g_kv + ((size_t)(s * 32 + row) * (2 * HD_) + col0 + c2 * 8);
    const uint32_t d0 = sb + R_KX + slot_off + row * 128 + ((c2 ^ (row & 7)) << 4);
    cp_async16(d0, src);
    cp_async16(d0 ^ 16, src + 8);
    cp_async16(d0 + (R_VX - R_KX), src + HD_);
    cp_async16((d0 ^ 16) + (R_VX - R_KX), src + HD_ + 8);
}

__device__ __forceinline__ void rec_store_kvm(uint32_t sb, int col0, int s, int w, int lane) {
    const int tok = (w & 1) * 4 + (lane >> 3);
    const uint4 v = lds128(sb + R_KMS + (s & 1) * 2048 + (w >> 1) * 1024 + tok * 128 + (((lane & 7) ^ tok) << 4));
    *(uint4*)(g_kvm + ((s * 8 + tok) * (2 * HD_) + (w >> 1) * HD_ + col0 + (lane & 7) * 8)) = v;
}

__device__ __forceinline__ void rec_vo(const RecParams& p, const uint32_t sb, const int cta, const int warp, int lane) {
    const int w = warp - 8, crank = cta & 15;
    const int col0 = cta * 64;
    uint32_t wo[8][4][4];
    {
        const int t128 = w * 32 + lane;
        const bf16* Wo = p.wo + (size_t)col0 * D_;
        const uint32_t stg = sb + R_STG + 2 * 32768;
#pragma unroll
        for (int half = 0; half < 2; half++) {
#pragma unroll 4
            for (int i = t128; i < 2048; i += 128) {
                const int e = i >> 6, ch = i & 63;
                cp_async16(stg + e * 1024 + ((ch ^ (e & 7)) << 4), Wo + (size_t)(half * 32 + e) * D_ + ch * 8);
            }
            cp_async_commit();
            cp_async_wait<0>();
            bar_sync(NB_W0 + 2, 128);
#pragma unroll
            for (int j = 0; j < 8; j++)
#pragma unroll
                for (int kk = 0; kk < 2; kk++) {
                    const int e = kk * 16 + (lane >> 4) * 8 + (lane & 7);
                    const int ch = (w * 8 + j) * 2 + ((lane >> 3) & 1);
                    ldsm4t(wo[j][half * 2 + kk][0], wo[j][half * 2 + kk][1], wo[j][half * 2 + kk][2], wo[j][half * 2 + kk][3],
                           stg + e * 1024 + ((ch ^ (e & 7)) << 4));
                }
            bar_sync(NB_W0 + 2, 128);
        }
        if (lane == 0) wait_flag(F_KV + 0, 64);
        __syncwarp();
        rec_load_kv(sb, col0, 0, 0, t128); cp_async_commit();
        rec_load_kv(sb, col0, 1, 4096, t128); cp_async_commit();
        cp_async_wait<1>();
    }
    const uint32_t tab = sb + R_STG + 2 * 32768 + (w * 32 + lane) * 16;
    {
        const uint32_t l7 = lane & 7, l8 = lane >> 3, g = lane >> 2;
        uint4 v;
        v.x = sb + R_VX + ((l8 & 1) * 8 + l7) * 128 + (((2 * w + (l8 >> 1)) ^ l7) << 4);
        v.y = sb + R_OS + g * 128 + (((2 * w) ^ g) << 4) + (lane & 3) * 4;
        v.z = sb + R_VMS + l7 * 128 + (((2 * w + (l8 & 1)) ^ l7) << 4);
        v.w = sb + R_OS + l7 * 128 + ((l8 ^ l7) << 4);
        sts128(tab, v);
        v.x = mapa_u32(sb + R_RS + crank * 512 + ((lane ^ (crank & 7)) << 4), w * 4);
        v.y = mapa_u32(sb + RB_E, w * 4);
        v.z = sb + R_VP + w * 512 + lane * 16;
        v.w = sb + R_SX + lane * 8;
        sts128(tab + 2048, v);
#pragma unroll
        for (int i = 0; i < 8; i++) sts128(tab + 4096 + i * 2048, make_uint4(wo[i][0][0], wo[i][0][1], wo[i][0][2], wo[i][0][3]));
        const int tok = (w & 1) * 4 + (lane >> 3), row = (w * 32 + lane) >> 2, c2 = (lane & 3) * 2;
        const uint64_t kd = (uint64_t)(g_kvm + (tok * (2 * HD_) + (w >> 1) * HD_ + col0 + (lane & 7) * 8));
        const uint64_t ks = (uint64_t)(g_kv + ((size_t)row * (2 * HD_) + col0 + c2 * 8));
        sts128(tab + 20480, make_uint4((uint32_t)kd, (uint32_t)(kd >> 32), (uint32_t)ks, (uint32_t)(ks >> 32)));
        sts128(tab + 22528, make_uint4(sb + R_KMS + (w >> 1) * 1024 + tok * 128 + (((lane & 7) ^ tok) << 4),
                                       sb + R_KX + row * 128 + ((c2 ^ (row & 7)) << 4), lane, 0));
    }
    bar_sync(NB_D, 384);
    const uint32_t lane16 = lds32(tab + 2048 + 8) - R_VP - w * 512;
    uint4 av[2 * VK0];
#pragma unroll
    for (int i = 0; i < 2 * VK0; i++) av[i] = lds128(lane16 + R_WV + (i / VK0) * 32768 + (w * 16 + i % VK0) * 512);
    uint32_t slot_off = 0;
#pragma unroll 1
    for (int s = 0; s < NSEG; s++) {
        if (s > 0) {
            mbar_wait(sb + RB_A, (s - 1) & 1);
            const uint4 tp = lds128(tab + 20480), tq = lds128(tab + 22528);
            const uint4 kvm = lds128(tq.x + ((s - 1) & 1) * 2048);
            *(uint4*)((((uint64_t)tp.y << 32) | tp.x) + (uint64_t)(s - 1) * (8 * 2 * HD_ * 2)) = kvm;
            if ((s & 3) == 0) bar_arrive(NB_K, 160);
            if (s + 1 < NSEG - 1) {
                if (((s + 1) & 3) == 0) { if (tq.z == 0) wait_flag(F_KV + ((s + 1) >> 2), 64); __syncwarp(); }
                const char* src = (const char*)((((uint64_t)tp.w << 32) | tp.z) + (uint64_t)(s + 1) * (32 * 2 * HD_ * 2));
                const uint32_t d0 = tq.y + (slot_off == (R_NST - 1) * 4096 ? 0 : slot_off + 4096);
                cp_async16(d0, src);
                cp_async16(d0 ^ 16, src + 16);
                cp_async16(d0 + (R_VX - R_KX), src + HD_ * 2);
                cp_async16((d0 ^ 16) + (R_VX - R_KX), src + HD_ * 2 + 16);
            }
            cp_async_commit();
        }
        bar_sync(NB_Y, 288);
        uint32_t vb0, vb1;
        {
            float va[4] = {0.f, 0.f, 0.f, 0.f}, vc[4] = {0.f, 0.f, 0.f, 0.f};
            uint32_t bb[VK0][4];
#pragma unroll
            for (int k2 = 0; k2 < VK0; k2++) ldsm4(bb[k2][0], bb[k2][1], bb[k2][2], bb[k2][3], lane16 + R_MEM + (k2 / (VK0 / 2)) * 4096 + (k2 % (VK0 / 2)) * 512);
#pragma unroll
            for (int k2 = 0; k2 < VK0; k2++) {
                mma16816(va, av[2 * k2].x, av[2 * k2].y, av[2 * k2].z, av[2 * k2].w, bb[k2][0], bb[k2][1]);
                mma16816(vc, av[2 * k2 + 1].x, av[2 * k2 + 1].y, av[2 * k2 + 1].z, av[2 * k2 + 1].w, bb[k2][2], bb[k2][3]);
            }
            const uint4 a = lds128(lane16 + R_VP + w * 512), b = lds128(lane16 + R_VP + 2048 + w * 512);
            vb0 = pack2((va[0] + vc[0]) + (__uint_as_float(a.x) + __uint_as_float(b.x)), (va[1] + vc[1]) + (__uint_as_float(a.y) + __uint_as_float(b.y)));
            vb1 = pack2((va[2] + vc[2]) + (__uint_as_float(a.z) + __uint_as_float(b.z)), (va[3] + vc[3]) + (__uint_as_float(a.w) + __uint_as_float(b.w)));
        }
        const uint4 ta = lds128(tab), tb = lds128(tab + 2048);
        uint32_t vx[8];
        ldsm4t(vx[0], vx[1], vx[2], vx[3], ta.x + slot_off);
        ldsm4t(vx[4], vx[5], vx[6], vx[7], ta.x + slot_off + 2048);
#pragma unroll
        for (int i = 0; i < 4; i++) {
            const uint4 f0 = lds128(tab + 4096 + i * 2048);
            wo[i][0][0] = f0.x; wo[i][0][1] = f0.y; wo[i][0][2] = f0.z; wo[i][0][3] = f0.w;
        }
        if (w == 0) PROF(11);
        uint32_t pf[5];
        float oa[2][4] = {{0.f, 0.f, 0.f, 0.f}, {0.f, 0.f, 0.f, 0.f}}, ob_[2][4] = {{0.f, 0.f, 0.f, 0.f}, {0.f, 0.f, 0.f, 0.f}};
        float sm0[4] = {0.f, 0.f, 0.f, 0.f}, sm1[4] = {0.f, 0.f, 0.f, 0.f};
        if (s != NSEG - 1) {
            mbar_wait(sb + RB_SX, s & 1);
            if (w == 0) PROF(4);
            float sv[10];
#pragma unroll
            for (int n = 0; n < 5; n++) {
                const float2 a = lds64f(tb.w + n * 256), b = lds64f(tb.w + (5 + n) * 256);
                sv[2 * n] = a.x + b.x; sv[2 * n + 1] = a.y + b.y;
            }
            float mx = fmaxf(fmaxf(fmaxf(sv[0], sv[1]), fmaxf(sv[2], sv[3])), fmaxf(fmaxf(sv[4], sv[5]), fmaxf(sv[6], sv[7])));
            mx = fmaxf(mx, fmaxf(sv[8], sv[9]));
            mx = fmaxf(mx, __shfl_xor_sync(~0u, mx, 1));
            mx = fmaxf(mx, __shfl_xor_sync(~0u, mx, 2));
#pragma unroll
            for (int n = 1; n < 5; n++) pf[n] = pack2(ex2(sv[2 * n] - mx), ex2(sv[2 * n + 1] - mx));
            pf[0] = pack2(ex2(sv[0] - mx), ex2(sv[1] - mx));
            if (w == 0) PROF(12);
            const uint32_t one = 0x3F803F80u;
            mma16816h(sm0, pf[1], pf[2], one, one);
            mma16816h(oa[0], pf[1], pf[2], vx[0], vx[1]);
            mma16816h(oa[1], pf[1], pf[2], vx[2], vx[3]);
            mma16816h(sm1, pf[3], pf[4], one, one);
            mma16816h(ob_[0], pf[3], pf[4], vx[4], vx[5]);
            mma16816h(ob_[1], pf[3], pf[4], vx[6], vx[7]);
            mma1688h(sm0, pf[0], one);
            mma1688h(oa[0], pf[0], vb0);
            mma1688h(oa[1], pf[0], vb1);
            float inv;
            asm("rcp.approx.ftz.f32 %0, %1;" : "=f"(inv) : "f"(sm0[0] + sm1[0]));
            oa[0][0] += ob_[0][0]; oa[0][1] += ob_[0][1]; oa[1][0] += ob_[1][0]; oa[1][1] += ob_[1][1];
            sts32(ta.y, pack2(oa[0][0] * inv, oa[0][1] * inv));
            sts32(ta.y ^ 16, pack2(oa[1][0] * inv, oa[1][1] * inv));
            const uint32_t oa2 = ta.w ^ 64;
            bar_sync(NB_C, 128);
            if (w == 0) PROF(5);
            uint32_t ob[8];
            ldsm4(ob[0], ob[1], ob[2], ob[3], ta.w);
            ldsm4(ob[4], ob[5], ob[6], ob[7], oa2);
#pragma unroll
            for (int i = 4; i < 8; i++) {
                const uint4 f0 = lds128(tab + 4096 + i * 2048);
                wo[i][0][0] = f0.x; wo[i][0][1] = f0.y; wo[i][0][2] = f0.z; wo[i][0][3] = f0.w;
            }
#pragma unroll
            for (int jj = 0; jj < 2; jj++) {
                if (jj == 1 && tb.w == 0) break;
                float acc[4][4];
#pragma unroll
                for (int c = 0; c < 4; c++) { acc[c][0] = acc[c][1] = acc[c][2] = acc[c][3] = 0.f; }
#pragma unroll
                for (int ks = 0; ks < 4; ks++)
#pragma unroll
                    for (int c = 0; c < 4; c++)
                        mma16816(acc[c], wo[jj * 4 + c][ks][0], wo[jj * 4 + c][ks][1], wo[jj * 4 + c][ks][2], wo[jj * 4 + c][ks][3], ob[2 * ks], ob[2 * ks + 1]);
#pragma unroll
                for (int pr = 0; pr < 2; pr++) {
                    uint4 v;
                    v.x = pack2(acc[2 * pr][0], acc[2 * pr][1]);
                    v.y = pack2(acc[2 * pr][2], acc[2 * pr][3]);
                    v.z = pack2(acc[2 * pr + 1][0], acc[2 * pr + 1][1]);
                    v.w = pack2(acc[2 * pr + 1][2], acc[2 * pr + 1][3]);
                    st_async_v4(tb.x + ((jj * 2 + pr) << 24), v, tb.y + ((jj * 2 + pr) << 24));
                }
            }
            if (w == 0) PROF(6);
        }
        stsm2t(ta.z + (s & 1) * 2048, vb0, vb1);
        cp_async_wait<0>();
        bar_sync(NB_C, 128);
        if (w == 0 && lane == 0 && s != NSEG - 1) mbar_expect_tx(sb + RB_SX, 2560);
        if (s != NSEG - 1) bar_arrive(NB_D, 384);
#pragma unroll
        for (int i = 0; i < 2 * VK0; i++) av[i] = lds128(lane16 + R_WV + (i / VK0) * 32768 + (w * 16 + i % VK0) * 512);
        slot_off = slot_off == (R_NST - 1) * 4096 ? 0 : slot_off + 4096;
    }
    rec_store_kvm(sb, col0, NSEG - 1, w, lane);
    bar_sync(NB_C, 128);
    if (w == 0 && lane == 0) red_release(&g_flags[F_MEM + NRB - 1], 1);
}

__global__ void __launch_bounds__(384, 1) k_rec(const RecParams p) {
    extern __shared__ __align__(1024) unsigned char smem_raw[];
    const uint32_t sb = __shfl_sync(~0u, smem_u32(smem_raw), 0);
    const int warp = __shfl_sync(~0u, threadIdx.x >> 5, 0);
    int lane; asm volatile("mov.u32 %0, %%laneid;" : "=r"(lane));
    const int crank = blockIdx.x & 15, slot = blockIdx.x >> 4;
    asm volatile("griddepcontrol.launch_dependents;");
    if (threadIdx.x == 0) {
        mbar_init(sb + RB_SX, 1); mbar_init(sb + RB_E, 1); mbar_init(sb + RB_A, 1); mbar_init(sb + RB_A1, 1); mbar_init(sb + RB_ROLE, 1);
        asm volatile("fence.mbarrier_init.release.cluster;" ::: "memory");
        mbar_expect_tx(sb + RB_SX, 2560);
        mbar_expect_tx(sb + RB_E, 8192);
        mbar_expect_tx(sb + RB_A, 4096);
        mbar_expect_tx(sb + RB_A1, 4096);
        mbar_expect_tx(sb + RB_ROLE, 4);
    }
    asm volatile("barrier.cluster.arrive.relaxed.aligned;\nbarrier.cluster.wait.aligned;" ::: "memory");
    unsigned role = 0;
    if (crank == 0 && threadIdx.x == 0 && !p.only_pre) {
        unsigned x = 0;
        int tm[2] = {0x7fffffff, 0x7fffffff};
#pragma unroll 1
        for (int i = 0; i < 6; i++) {
            const uint32_t t0 = clk32();
            x = atomicAdd(&g_F[65536 + (i & 1) * 1024 + slot * 64 + (x >> 31)], 0u) & 0x7fffffffu;
            if (x == 0x7654321u) sts32(sb + R_BAR + 56, x);
            const int dt = (int)(clk32() - t0);
            if (i >= 2) { if (i & 1) tm[1] = min(tm[1], dt); else tm[0] = min(tm[0], dt); }
        }
        const int side = tm[1] > tm[0];
        const unsigned old = atomicAdd(&g_flags[F_SIDE + side * 32], 1u);
        unsigned c0, c1; int gd = 0;
#pragma unroll 1
        do { c0 = ldg_relaxed32(&g_flags[F_SIDE]); c1 = ldg_relaxed32(&g_flags[F_SIDE + 32]); } while ((int)(c0 + c1) < p.ncl && ++gd < 64 * SPIN_LIMIT);
        const int big = c1 > c0;
        role = side == big ? old : (big ? c1 : c0) + old;
        role |= (big ^ 1) << 8;
    }
    __syncwarp();
    if (crank == 0 && warp == 0 && !p.only_pre) {
        role = __shfl_sync(~0u, role, 0);
        if (lane < 16)
            asm volatile("st.async.weak.shared::cluster.mbarrier::complete_tx::bytes.u32 [%0], %1, [%2];"
                         :: "r"(mapa_u32(sb + R_BAR + 48, lane)), "r"(role), "r"(mapa_u32(sb + RB_ROLE, lane)) : "memory");
    }
    if (warp >= 4) {
        const int w8 = warp - 4, nblk = gridDim.x;
        const int cq = lane & 3, rg = w8 * 8 + (lane >> 2);
        const uint32_t red = sb + R_VP;
        const int row0 = blockIdx.x * 8 + w8;
        const uint4* xr = (const uint4*)(p.x + (size_t)row0 * D_);
        uint4 xa = __ldg(xr + lane), xb = __ldg(xr + 32 + lane);
#pragma unroll 1
        for (int sl = blockIdx.x; sl < 96; sl += nblk) {
            uint4 wv[8];
#pragma unroll
            for (int i = 0; i < 8; i++) wv[i] = __ldg((const uint4*)(p.w_mod + (size_t)(rg * 8 + i) * (6 * D_) + sl * 32 + cq * 8));
            const uint32_t cw = __ldg((const uint32_t*)(p.c + rg * 8) + cq);
            const float cl = bflo(cw), ch = bfhi(cw);
            const uint32_t sw = pack2(__fdividef(cl, 1.f + __expf(-cl)), __fdividef(ch, 1.f + __expf(-ch)));
            float a[8];
#pragma unroll
            for (int i = 0; i < 8; i++) a[i] = 0.f;
#pragma unroll
            for (int i = 0; i < 8; i++) {
                const uint32_t sv = __shfl_sync(~0u, sw, (lane & 28) + (i >> 1));
                const float cv = (i & 1) ? bfhi(sv) : bflo(sv);
                a[0] = fmaf(cv, bflo(wv[i].x), a[0]); a[1] = fmaf(cv, bfhi(wv[i].x), a[1]); a[2] = fmaf(cv, bflo(wv[i].y), a[2]); a[3] = fmaf(cv, bfhi(wv[i].y), a[3]);
                a[4] = fmaf(cv, bflo(wv[i].z), a[4]); a[5] = fmaf(cv, bfhi(wv[i].z), a[5]); a[6] = fmaf(cv, bflo(wv[i].w), a[6]); a[7] = fmaf(cv, bfhi(wv[i].w), a[7]);
            }
#pragma unroll
            for (int i = 0; i < 8; i++) { a[i] += __shfl_xor_sync(~0u, a[i], 4); a[i] += __shfl_xor_sync(~0u, a[i], 8); a[i] += __shfl_xor_sync(~0u, a[i], 16); }
            if (lane < 4) {
                sts128(red + w8 * 128 + lane * 32, make_uint4(__float_as_uint(a[0]), __float_as_uint(a[1]), __float_as_uint(a[2]), __float_as_uint(a[3])));
                sts128(red + w8 * 128 + lane * 32 + 16, make_uint4(__float_as_uint(a[4]), __float_as_uint(a[5]), __float_as_uint(a[6]), __float_as_uint(a[7])));
            }
            bar_sync(NB_B, 256);
            if (w8 == 0) {
                float v = 0.f;
#pragma unroll
                for (int i = 0; i < 8; i++) v += lds32f(red + i * 128 + lane * 4);
                g_mod[sl * 32 + lane] = __float2bfloat16_rn(v);
                __syncwarp();
                if (lane == 0) red_release(&g_flags[F_MOD + (sl >= 32)], 1);
            }
            bar_sync(NB_B, 256);
        }
        uint32_t c1[8], sm[8];
        int row = row0;
#pragma unroll 1
        while (true) {
            const uint32_t v[8] = {xa.x, xa.y, xa.z, xa.w, xb.x, xb.y, xb.z, xb.w};
            uint32_t mu2, r[8]; float rden;
            ln_stats(v, mu2, rden);
            if (row == row0) {
                if (lane == 0) wait_flag(F_MOD, 32);
                __syncwarp();
                load_mod8(g_mod + D_, lane, c1);
                load_mod8(g_mod, lane, sm);
#pragma unroll
                for (int i = 0; i < 8; i++) c1[i] = hadd2(c1[i], 0x3F803F80u);
            } else if (row + 512 < S_) {
                xr = (const uint4*)(p.x + (size_t)(row + 512) * D_); xa = __ldg(xr + lane); xb = __ldg(xr + 32 + lane);
            }
            ln_apply(v, mu2, rden, c1, sm, r);
            uint4* hr = (uint4*)(g_h + (size_t)row * D_);
            hr[lane] = make_uint4(r[0], r[1], r[2], r[3]); hr[32 + lane] = make_uint4(r[4], r[5], r[6], r[7]);
            bar_sync(NB_B, 256);
            if (w8 == (row >> 7 & 7) && lane == 0) red_release(&g_flags[F_H + (row >> 7)], 1);
            __syncwarp();
            if (row == row0) {
                if (!p.only_pre) mbar_wait(sb + RB_ROLE, 0);
                const int cl = p.only_pre ? slot : (int)(lds32(sb + R_BAR + 48) & 255);
                row = cl < 4 ? (nblk + cl * 16 + crank) * 8 + w8 : S_;
                if (row < S_) { xr = (const uint4*)(p.x + (size_t)row * D_); xa = __ldg(xr + lane); xb = __ldg(xr + 32 + lane); }
            } else {
                row += 512;
            }
            if (row >= S_) break;
        }
    }
    if (p.only_pre) return;
    mbar_wait(sb + RB_ROLE, 0);
    const int rolew = __shfl_sync(~0u, lds32(sb + R_BAR + 48), 0);
    const int cl = rolew & 255;
    if (cl >= 4) return;
    const int cta = cl * 16 + crank;
    if (warp < 8) rec_qk(p, sb, cta, warp, lane, rolew >> 8);
    else rec_vo(p, sb, cta, warp, lane);
}

enum { J_KV = 0, J_QA = 1, J_O = 2, J_LN = 3, J_UP = 4, J_DN = 5, J_LN1 = 6, J_MOD = 7, J_UP2 = 8, J_END = 9 };
constexpr int NJ_O = 2 * OSPLIT, NJ_O2 = 2 * OSPLIT2, NJ_LN = 8, NJ_LN2 = 16, NJ_UP = 14, NJ_UP2 = 28, NJ_DN = 8, NJ_LN1 = 8;
constexpr uint64_t pk8(int a, int b, int c, int d, int e, int f, int g, int h) {
    return (uint64_t)a | ((uint64_t)b << 8) | ((uint64_t)c << 16) | ((uint64_t)d << 24) | ((uint64_t)e << 32) | ((uint64_t)f << 40) | ((uint64_t)g << 48) | ((uint64_t)h << 56);
}
constexpr uint64_t NJ_C = pk8(32, 16, NJ_O, NJ_LN, NJ_UP, NJ_DN, 0, 0), NJ_F = pk8(32, 16, NJ_O2, NJ_LN2, NJ_UP2, NJ_DN, 0, 0);
constexpr uint64_t TG_C = pk8(2 * NJ_LN1, 64, 32, 2 * NJ_O, 2 * NJ_LN, 2 * NJ_UP, 32, 0), TG_F = pk8(2 * NJ_LN1, 64, 32, 2 * NJ_O2, 2 * NJ_LN2, 2 * NJ_UP2, 32, 0);
constexpr uint64_t NJ_L = pk8(32, 32, 2 * OSPLIT3, NJ_LN2, NJ_UP2, NJ_DN, 0, 0), TG_L = pk8(2 * NJ_LN1, 64, 64, 4 * OSPLIT3, 2 * NJ_LN2, 2 * NJ_UP2, 32, 0);
__device__ __forceinline__ uint64_t nj_tab(int rb) { return rb < FINE_RB ? NJ_C : (rb < NRB - 1 ? NJ_F : NJ_L); }
__device__ __forceinline__ uint64_t tg_tab(int rb) { return rb < FINE_RB ? TG_C : (rb < NRB - 1 ? TG_F : TG_L); }
__device__ __forceinline__ int o_nk(int rb) { return rb < FINE_RB ? 64 / OSPLIT : (rb < NRB - 1 ? 64 / OSPLIT2 : 64 / OSPLIT3); }
constexpr uint64_t PRIO = pk8(4, 10, 9, 8, 7, 6, 3, 0);
__device__ __forceinline__ int pick_job(int lane, int qmask, int& idx) {
    const int rb = lane & 15, half = lane >> 4;
    const uint64_t nj = nj_tab(rb) >> (8 * half);
    const uint64_t tg = tg_tab(rb) >> (8 * half);
    const unsigned* cp = &g_flags[F_CLAIM + half * 32 + rb];
    const unsigned* dp = &g_flags[half * 32 + rb];
    int gd = 0;
#pragma unroll 1
    while (true) {
        const unsigned c0 = ldg_relaxed32(cp), c1 = ldg_relaxed32(cp + 64), c2 = ldg_relaxed32(cp + 128);
        const unsigned d0 = ldg_relaxed32(dp - (half && rb ? 1 : 0)), d1 = ldg_relaxed32(dp + 64), d2 = ldg_relaxed32(dp + 128);
        const unsigned cl[3] = {c0, c1, c2}, dv[3] = {d0, d1, d2};
        unsigned key = 0xffffu, key2 = 0xffffu;
        bool pre = false;
#pragma unroll
        for (int i = 0; i < 3; i++) {
            const int q = half + 2 * i;
            const bool have = ((qmask >> q) & 1) && cl[i] < (unsigned)((nj >> (16 * i)) & 255);
            bool ready = have && dv[i] >= (unsigned)((tg >> (16 * i)) & 255);
            unsigned pr = (unsigned)((PRIO >> (8 * q)) & 255);
            if (i == 0 && rb <= 1 - half) ready = have;
            if (i == 0 && half && rb >= FINE_RB) pr = 5;
            if (ready) key = min(key, (pr << 8) | (rb << 4) | q);
            if (have) key2 = min(key2, rb >= FINE_RB ? (0x100u | (q << 4) | rb) : (i == 0 ? 0u : 0x1000u));
            pre |= have && i == 0 && !half;
        }
        const bool anypre = __any_sync(~0u, pre);
        if (anypre && (key & 15) == J_QA) key = 0xffffu;
        key = __reduce_min_sync(~0u, key);
        key2 = __reduce_min_sync(~0u, key2);
        if (key2 == 0xffffu) return J_END;
        int pq, prb;
        if (key != 0xffffu) { pq = key & 15; prb = (key >> 4) & 15; }
        else if (key2 >= 0x120u && key2 < 0x1000u) { pq = (key2 >> 4) & 15; prb = key2 & 15; }
        else {
            __nanosleep(IDLE_NS);
            if (++gd > 16 * SPIN_LIMIT) { TIMEOUT(5, 0); return J_END; }
            continue;
        }
        int c = 0;
        if (lane == 0) c = (int)atomicAdd(&g_flags[F_CLAIM + pq * 32 + prb], 1u);
        c = __shfl_sync(~0u, c, 0);
        if (c < (int)((nj_tab(prb) >> (8 * pq)) & 255)) {
            idx = pq * 512 + prb * 32 + c;
            int acq = 0;
            if (pq != J_QA && pq < J_LN1) {
                if (lane == 0 && ld_acquire(&g_flags[pq * 32 + prb]) >= (unsigned)((tg_tab(prb) >> (8 * pq)) & 255)) {
                    asm volatile("fence.proxy.async.global;" ::: "memory");
                    acq = 1 << 24;
                }
            }
            return (pq == J_UP && prb >= FINE_RB ? J_UP2 : pq) | (prb << 8) | (c << 16) | acq;
        }
    }
}
__device__ __forceinline__ int op_row(int rb, int split) {
    return rb < FINE_RB ? split * S_ + rb * 128
                        : (rb < NRB - 1 ? OSPLIT * S_ + (split * (NRB - FINE_RB) + rb - FINE_RB) * 128 : OSPLIT * S_ + (OSPLIT2 * (NRB - FINE_RB) + split) * 128);
}

struct Pipe { uint32_t stage, phase; };
__device__ __forceinline__ void pipe_next(Pipe& p) { if (++p.stage == W_NST) { p.stage = 0; p.phase ^= 1; } }

__device__ __forceinline__ void scheduler(const Params& p, uint32_t sb, int lane) {
    const uint32_t bars = sb + SM_BAR;
    uint32_t ph = 0;
#pragma unroll 1
    while (true) {
        mbar_wait(bars + B_REQ, ph);
        int j = 4095;
        const int jd = pick_job(lane, p.qmask, j);
        if (lane == 0) { sts32(bars + B_NEXT, (uint32_t)jd); sts32(bars + B_NEXT + 4, (uint32_t)j); mbar_arrive(bars + B_RSP); }
        ph ^= 1;
        if (jd == J_END) break;
        __syncwarp();
    }
}

__device__ __forceinline__ void producer(const Params& p, uint32_t sb) {
    Pipe pp{0, 1};
    const uint32_t bars = sb + SM_BAR;
    uint32_t seq = 0, h_seen = 0;
    mbar_arrive(bars + B_REQ);
#pragma unroll 1
    while (true) {
        mbar_wait(bars + B_RSP, seq & 1);
        const int jd = (int)lds32(bars + B_NEXT), j = (int)lds32(bars + B_NEXT + 4);
        int left = (jd & 255) == J_DN ? 15 : ((jd & 255) == J_QA ? (((jd >> 8) & 255) == NRB - 1 ? 10 : 12) : ((jd & 255) == J_O ? o_nk((jd >> 8) & 255) : ((jd & 255) == J_LN || (jd & 255) == J_LN1 || (jd & 255) == J_MOD ? 1 : 8)));
        left = max(left - PICK_AHEAD, 1);
        TR(j, 1);
        const int type = jd & 255, rb = (jd >> 8) & 255, cb = (jd >> 16) & 255;
        const bool fine = rb >= FINE_RB, acquired = (jd >> 24) & 1;
        bool first = true;
        auto begin_stage = [&](uint32_t bytes) -> uint32_t {
            mbar_wait(bars + B_EMPTY + pp.stage * 8, pp.phase);
            if (first) { sts32(bars + B_RING + (seq & 7) * 4, (uint32_t)jd); sts32(bars + B_RING + 32 + (seq & 7) * 4, (uint32_t)j); first = false; }
            const uint32_t fb = bars + B_FULL + pp.stage * 8;
            if (bytes) mbar_expect_tx(fb, bytes); else mbar_arrive(fb);
            if (--left == 0 && type != J_END) mbar_arrive(bars + B_REQ);
            return fb;
        };
        if (type == J_END || type == J_LN || type == J_LN1 || type == J_MOD) {
            if (type == J_LN) { if (!acquired) wait_flag(F_OP + rb, (unsigned)((tg_tab(rb) >> (8 * J_LN)) & 255)); if (!(h_seen >> 31)) { wait_flag(F_MOD + 1, 64); h_seen |= 1u << 31; } }

            TR(j, 2);
            begin_stage(0); pipe_next(pp);
            seq++;
            if (type == J_END) break;
            continue;
        }
        const CUtensorMap *ta, *tb0, *tb1;
        int k0 = 0, nk = 8, n0 = cb * 256, n1 = n0 + 128, nb = 4, dep = -1;
        unsigned tgt = 0;
        switch (type) {
            case J_KV: ta = &p.tm_h; tb0 = tb1 = cb < 16 ? &p.tm_wk : &p.tm_wv; n0 = (cb & 15) * 256; n1 = n0 + 128; dep = F_H + rb; tgt = 2 * NJ_LN1; break;
            case J_QA: ta = &p.tm_h; tb0 = tb1 = &p.tm_wq; dep = F_H + rb; tgt = 2 * NJ_LN1; if (rb == NRB - 1) { n0 = (cb >> 1) * 256; n1 = n0 + 128; } break;
            case J_O: ta = &p.tm_o; tb0 = tb1 = &p.tm_wo; n0 = (cb & 1) * 256; n1 = n0 + 128; nk = o_nk(rb); k0 = (cb >> 1) * nk * 64;
                      dep = F_O + rb; tgt = rb == NRB - 1 ? 64 : 32; break;
            case J_UP: ta = &p.tm_h2; tb0 = &p.tm_wg; tb1 = &p.tm_wu; n0 = n1 = cb * 128; dep = F_H2 + rb; tgt = 2 * NJ_LN; break;
            case J_UP2: ta = &p.tm_h2; tb0 = &p.tm_wg; tb1 = &p.tm_wu; n0 = n1 = cb * 64; nb = 2; dep = F_H2 + rb; tgt = 2 * NJ_LN2; break;
            default: ta = &p.tm_act; tb0 = tb1 = &p.tm_wd; n0 = cb * 64; nk = 0; break;
        }
        const int m0 = rb * 128;
        if (type == J_DN) {
#pragma unroll 1
            for (int kb = 0; kb < 14; kb++) {
                const uint32_t fb = begin_stage(49152);
                const uint32_t st = sb + pp.stage * W_STAGE;
                const int k = kb * 128;
                tma_load2d(st + 32768, tb0, n0, k, fb);
                tma_load2d(st + 40960, tb0, n0, k + 64, fb);
                if (kb == 0) { if (!acquired) { wait_flag(F_ACT + rb, 2 * (fine ? NJ_UP2 : NJ_UP)); asm volatile("fence.proxy.async.global;" ::: "memory"); } TR(j, 2); }
                tma_load2d(st, ta, k, m0, fb);
                tma_load2d(st + 8192, ta, k, m0 + 64, fb);
                tma_load2d(st + 16384, ta, k + 64, m0, fb);
                tma_load2d(st + 24576, ta, k + 64, m0 + 64, fb);
                pipe_next(pp);
            }
        }
#pragma unroll 1
        for (int kb = 0; kb < nk; kb++) {
            const uint32_t fb = begin_stage(16384 + nb * 8192);
            const uint32_t st = sb + pp.stage * W_STAGE;
            const int k = k0 + kb * 64;
            tma_load2d(st + 16384, tb0, n0, k, fb);
            if (nb == 4) {
                tma_load2d(st + 16384 + 8192, tb0, n0 + 64, k, fb);
                tma_load2d(st + 16384 + 16384, tb1, n1, k, fb);
                tma_load2d(st + 16384 + 24576, tb1, n1 + 64, k, fb);
            } else if (nb == 2) {
                tma_load2d(st + 16384 + 8192, tb1, n1, k, fb);
            }
            if (kb == 0) {
                if (acquired && dep < 16) h_seen |= 1u << dep;
                if (dep >= 0 && !acquired && !(dep < 16 && ((h_seen >> dep) & 1))) {
                    wait_flag(dep, tgt);
                    if (type != J_O) asm volatile("fence.proxy.async.global;" ::: "memory");
                    if (dep < 16) h_seen |= 1u << dep;
                }
                TR(j, 2);
            }
            tma_load2d(st, ta, k, m0, fb);
            tma_load2d(st + 8192, ta, k, m0 + 64, fb);
            pipe_next(pp);
        }
        if (type == J_QA) {
            wait_flag(F_KV + rb, 64);
#pragma unroll 1
            for (int i = 0; i < (rb == NRB - 1 ? 2 : 4); i++) {
                const uint32_t fb = begin_stage(40960);
                const uint32_t st = sb + pp.stage * W_STAGE;
                const int col = (i & 1) * HD_ + (rb == NRB - 1 ? cb : cb * 2 + (i >> 1)) * DH_;
                tma_load2d(st, &p.tm_kv, col, m0, fb);
                tma_load2d(st + 8192, &p.tm_kv, col, m0 + 64, fb);
                tma_load2d(st + 16384, &p.tm_kv, col + 64, m0, fb);
                tma_load2d(st + 24576, &p.tm_kv, col + 64, m0 + 64, fb);
                if (i == 0) { wait_flag(F_MEM + rb, 64); asm volatile("fence.proxy.async.global;" ::: "memory"); }
                tma_load2d(st + 32768, &p.tm_kvm, col, rb * 32, fb);
                tma_load2d(st + 36864, &p.tm_kvm, col + 64, rb * 32, fb);
                pipe_next(pp);
            }
        } else if (type == J_DN) {
            const uint32_t fb = begin_stage(16384);
            const uint32_t st = sb + pp.stage * W_STAGE;
            tma_load2d(st, &p.tm_x1, n0, m0, fb);
            tma_load2d(st + 8192, &p.tm_x1, n0, m0 + 64, fb);
            pipe_next(pp);
        }
        seq++;
    }
}

__device__ __forceinline__ void store_warp(const Params& p, uint32_t sb, int wg, int lane) {
    const uint32_t bars = sb + SM_BAR;
    uint32_t seq = 0;
#pragma unroll 1
    while (true) {
        bar_sync(NB_ST + wg, 160);
        const uint32_t jd = lds32(bars + B_RING + (seq & 7) * 4);
        seq++;
        const int type = jd & 255, rb = (jd >> 8) & 255, cb = (jd >> 16) & 255;
        if (type == J_END) break;
        const uint32_t src = sb + W_STG + wg * 16384;
        const CUtensorMap* tm = nullptr; int n0 = cb * 256, nbox = 4, mrow = rb * 128 + wg * 64, flag = 0;
        switch (type) {
            case J_KV: tm = &p.tm_kv; flag = F_KV + rb; break;
            case J_QA: tm = &p.tm_o; flag = F_O + rb; if (rb == NRB - 1) { n0 = cb * 128; nbox = 2; } break;
            case J_O: tm = &p.tm_op; n0 = (cb & 1) * 256; mrow = op_row(rb, cb >> 1) + wg * 64; flag = F_OP + rb; break;
            case J_LN: flag = F_H2 + rb; nbox = 0; break;
            case J_LN1: flag = F_H + rb; nbox = 0; break;
            case J_MOD: flag = F_MOD + rb; nbox = 0; break;
            case J_UP: tm = &p.tm_act; n0 = cb * 128; nbox = 2; flag = F_ACT + rb; break;
            case J_UP2: tm = &p.tm_act; n0 = cb * 64; nbox = 1; flag = F_ACT + rb; break;
            default: tm = &p.tm_out; n0 = cb * 64; nbox = 1; flag = -1; break;
        }
        if (nbox == 4) {
            if (lane == 0) {
                tma_store2d(tm, src, n0, mrow);
                tma_store2d(tm, src + 8192, n0 + 64, mrow);
                bulk_commit();
                asm volatile("cp.async.bulk.wait_group.read 0;" ::: "memory");
                mbar_arrive(bars + B_STGFREE + wg * 8);
            }
            __syncwarp();
            bar_sync(NB_ST + wg, 160);
            n0 += 128; nbox = 2;
        }
        if (lane == 0) {
            if (nbox) {
                tma_store2d(tm, src, n0, mrow);
                if (nbox == 2) tma_store2d(tm, src + 8192, n0 + 64, mrow);
                bulk_commit();
                asm volatile("cp.async.bulk.wait_group.read 0;" ::: "memory");
                mbar_arrive(bars + B_STGFREE + wg * 8);
                bulk_wait0();
                if (flag >= 0) asm volatile("red.relaxed.gpu.global.add.u32 [%0], 1;" :: "l"(&g_flags[flag]) : "memory");
            } else {
                mbar_arrive(bars + B_STGFREE + wg * 8);
                red_release(&g_flags[flag], 1);
            }
        }
        __syncwarp();
    }
}

__device__ __forceinline__ float gelu_tanh(float x) {
    const float t = x * fmaf(-0.10294324397f, x * x, -2.30220819814f);
    float r; asm("rcp.approx.ftz.f32 %0, %1;" : "=f"(r) : "f"(1.f + ex2(t)));
    return x * r;
}

#define CTR(i) do {} while (0)

template <int NSPLIT>
__device__ __forceinline__ void ln2_row(const Params& p, int rb, int r, int lane) {
    const int row = rb * 128 + r;
    uint4 u[2 * NSPLIT];
#pragma unroll
    for (int sp = 0; sp < NSPLIT; sp++) {
        const uint4* src = (const uint4*)(g_op + (size_t)(op_row(rb, sp) + r) * D_);
        u[2 * sp] = __ldcg(src + lane); u[2 * sp + 1] = __ldcg(src + 32 + lane);
    }
    const uint4* xr = (const uint4*)(p.x + (size_t)row * D_);
    const uint4 xa = __ldg(xr + lane), xb = __ldg(xr + 32 + lane);
    uint32_t ga[8], c1[8], sm[8];
    load_mod8(g_mod + 2 * D_, lane, ga);
    load_mod8(g_mod + 4 * D_, lane, c1);
    load_mod8(g_mod + 3 * D_, lane, sm);
    float a[16];
#pragma unroll
    for (int i = 0; i < 16; i++) a[i] = 0.f;
#pragma unroll
    for (int sp = 0; sp < 2 * NSPLIT; sp++) {
        float* q = a + (sp & 1) * 8;
        q[0] += bflo(u[sp].x); q[1] += bfhi(u[sp].x); q[2] += bflo(u[sp].y); q[3] += bfhi(u[sp].y);
        q[4] += bflo(u[sp].z); q[5] += bfhi(u[sp].z); q[6] += bflo(u[sp].w); q[7] += bfhi(u[sp].w);
    }
    const uint32_t xv[8] = {xa.x, xa.y, xa.z, xa.w, xb.x, xb.y, xb.z, xb.w};
    uint32_t v[8], r8[8];
#pragma unroll
    for (int i = 0; i < 8; i++) v[i] = hadd2(xv[i], hmul2(ga[i], pack2(a[2 * i], a[2 * i + 1])));
    uint4* x1r = (uint4*)(g_x1 + (size_t)row * D_);
    x1r[lane] = make_uint4(v[0], v[1], v[2], v[3]); x1r[32 + lane] = make_uint4(v[4], v[5], v[6], v[7]);
    uint32_t mu2; float rden;
    ln_stats(v, mu2, rden);
#pragma unroll
    for (int i = 0; i < 8; i++) c1[i] = hadd2(c1[i], 0x3F803F80u);
    ln_apply(v, mu2, rden, c1, sm, r8);
    uint4* hr = (uint4*)(g_h2 + (size_t)row * D_);
    hr[lane] = make_uint4(r8[0], r8[1], r8[2], r8[3]); hr[32 + lane] = make_uint4(r8[4], r8[5], r8[6], r8[7]);
}

__device__ __forceinline__ void consumer(const Params& p, uint32_t sb, int warp, int lane) {
    const uint32_t bars = sb + SM_BAR;
    const int wg = warp >> 2, wl = warp & 3;
    const uint32_t l7 = lane & 7, l8 = lane >> 3, g = lane >> 2, t = lane & 3;
    Pipe pp{0, 0};
    uint32_t seq = 0, stg_phase = 1;
    const int srow = wl * 16 + l7 + (l8 & 1) * 8;
    const uint32_t stg_base = sb + W_STG + wg * 16384 + srow * 128;
    const uint32_t sx = ((lane >> 4) ^ (srow & 7)) << 4;
#pragma unroll 1
    while (true) {
        mbar_wait(bars + B_FULL + pp.stage * 8, pp.phase);
        const uint32_t jd = lds32(bars + B_RING + (seq & 7) * 4);
        CTR(3);
        seq++;
        const int type = jd & 255, rb = (jd >> 8) & 255, cb = (jd >> 16) & 255;
        if (type == J_END) { mbar_wait(bars + B_STGFREE + wg * 8, stg_phase); bar_arrive(NB_ST + wg, 160); break; }
        if (type == J_LN) {
            __syncwarp();
            if (lane == 0) mbar_arrive(bars + B_EMPTY + pp.stage * 8);
            pipe_next(pp);
            if (rb == NRB - 1) ln2_row<OSPLIT3>(p, rb, cb * 8 + warp, lane);
            else if (rb >= FINE_RB) ln2_row<OSPLIT2>(p, rb, cb * 8 + warp, lane);
            else {
#pragma unroll 1
                for (int rr = 0; rr < 2; rr++) ln2_row<OSPLIT>(p, rb, cb * 16 + warp * 2 + rr, lane);
            }
            mbar_wait(bars + B_STGFREE + wg * 8, stg_phase); stg_phase ^= 1;
            CTR(4); CTR(5);
            bar_arrive(NB_ST + wg, 160);
            continue;
        }
        if (type == J_DN || type == J_UP2) {
            float acc[64];
#pragma unroll
            for (int i = 0; i < 64; i++) acc[i] = 0.f;
            if (type == J_DN) {
#pragma unroll 1
                for (int kb = 0; kb < 14; kb++) {
                    if (kb) mbar_wait(bars + B_FULL + pp.stage * 8, pp.phase);
                    const uint32_t st = sb + pp.stage * W_STAGE;
                    const uint64_t da = mkdesc(st + wg * 8192, 16, 1024), db = mkdesc(st + 32768, 8192, 1024);
                    wg_fence();
#pragma unroll
                    for (int ks = 0; ks < 8; ks++) wgmma_n64(acc, da + (ks >> 2) * 1024 + (ks & 3) * 2, db + ks * 128);
                    wg_commit();
                    wg_wait0();
                    if (lane == 0) mbar_arrive(bars + B_EMPTY + pp.stage * 8);
                    pipe_next(pp);
                }
            } else {
#pragma unroll 1
                for (int kb = 0; kb < 8; kb++) {
                    if (kb) mbar_wait(bars + B_FULL + pp.stage * 8, pp.phase);
                    const uint32_t st = sb + pp.stage * W_STAGE;
                    const uint64_t da = mkdesc(st + wg * 8192, 16, 1024), db = mkdesc(st + 16384, 8192, 1024);
                    wg_fence();
#pragma unroll
                    for (int ks = 0; ks < 4; ks++) wgmma_n128(acc, da + ks * 2, db + ks * 128, 1);
                    wg_commit();
                    wg_wait0();
                    if (lane == 0) mbar_arrive(bars + B_EMPTY + pp.stage * 8);
                    pipe_next(pp);
                }
            }
            CTR(4);
            if (type == J_UP2) {
                mbar_wait(bars + B_STGFREE + wg * 8, stg_phase); stg_phase ^= 1;
#pragma unroll
                for (int j = 0; j < 4; j++) {
                    uint32_t r[4];
#pragma unroll
                    for (int q = 0; q < 4; q++) {
                        const uint32_t gw = pack2(acc[8 * j + 2 * q], acc[8 * j + 2 * q + 1]);
                        const uint32_t uw = pack2(acc[32 + 8 * j + 2 * q], acc[32 + 8 * j + 2 * q + 1]);
                        r[q] = hmul2(pack2(gelu_tanh(bflo(gw)), gelu_tanh(bfhi(gw))), uw);
                    }
                    stsm4(stg_base + (sx ^ (j << 5)), r[0], r[1], r[2], r[3]);
                }
            } else {
                mbar_wait(bars + B_FULL + pp.stage * 8, pp.phase);
                const uint32_t st = sb + pp.stage * W_STAGE;
                mbar_wait(bars + B_STGFREE + wg * 8, stg_phase); stg_phase ^= 1;
                const uint32_t* gb = (const uint32_t*)(g_mod + 5 * D_ + cb * 64) + t;
                const uint32_t xa = st + wg * 8192 + (wl * 16 + g) * 128 + (g << 4) + t * 4;
#pragma unroll
                for (int j = 0; j < 4; j++) {
                    uint32_t r[4];
#pragma unroll
                    for (int q = 0; q < 4; q++) {
                        const int nt = 2 * j + (q >> 1);
                        const uint32_t xw = lds32((xa ^ ((nt & 7) << 4)) + (nt >> 3) * 16384 + (q & 1) * 1024);
                        r[q] = hadd2(xw, hmul2(__ldcg(gb + nt * 4), pack2(acc[8 * j + 2 * q], acc[8 * j + 2 * q + 1])));
                    }
                    stsm4(stg_base + (j >> 2) * 8192 + (sx ^ ((2 * j & 7) << 4)), r[0], r[1], r[2], r[3]);
                }
                __syncwarp();
                if (lane == 0) mbar_arrive(bars + B_EMPTY + pp.stage * 8);
                pipe_next(pp);
            }
            fence_async_smem();
            CTR(5);
            bar_arrive(NB_ST + wg, 160);
            continue;
        }
        float acc[128];
#pragma unroll
        for (int i = 0; i < 128; i++) acc[i] = 0.f;
        const int nk = type == J_O ? o_nk(rb) : 8;
#pragma unroll 1
        for (int kb = 0; kb < nk; kb++) {
            if (kb) mbar_wait(bars + B_FULL + pp.stage * 8, pp.phase);
            const uint32_t st = sb + pp.stage * W_STAGE;
            const uint64_t da = mkdesc(st + wg * 8192, 16, 1024), db = mkdesc(st + 16384, 8192, 1024);
            wg_fence();
#pragma unroll
            for (int ks = 0; ks < 4; ks++) wgmma_n256(acc, da + ks * 2, db + ks * 128, 1);
            wg_commit();
            wg_wait0();
            if (lane == 0) mbar_arrive(bars + B_EMPTY + pp.stage * 8);
            pipe_next(pp);
        }
        CTR(4);
        if (type == J_QA) {
            uint32_t qf[64];
#pragma unroll
            for (int i = 0; i < 64; i++) qf[i] = pack2(acc[2 * i], acc[2 * i + 1]);
            const int sg = warp >> 1, half = warp & 1;
            const float sc = 0.08838834764831845f * 1.4426950408889634f;
            const uint32_t xoff = (sg >> 1) * 8192 + ((sg & 1) * 32 + l7) * 128;
            const uint32_t moff = 32768 + (sg * 8 + l7) * 128;
            const uint32_t kch = (l8 ^ l7) << 4;
            const uint32_t vch = ((l8 & 1) ^ l7) << 4;
            if (rb == NRB - 1 && (cb & 1)) {
#pragma unroll
                for (int i = 0; i < 32; i++) qf[i] = qf[32 + i];
            }
#pragma unroll 1
            for (int hh = rb == NRB - 1; hh < 2; hh++) {
                mbar_wait(bars + B_FULL + pp.stage * 8, pp.phase);
                uint32_t st = sb + pp.stage * W_STAGE;
                float sa[5][4];
#pragma unroll
                for (int n = 0; n < 5; n++) sa[n][0] = sa[n][1] = sa[n][2] = sa[n][3] = 0.f;
#pragma unroll
                for (int i = 0; i < 4; i++) {
                    const uint32_t* q = qf + i * 8;
                    uint32_t kk[5][4];
                    ldsm4(kk[0][0], kk[0][1], kk[0][2], kk[0][3], st + moff + (i >> 1) * 4096 + (kch ^ ((i & 1) * 64)));
#pragma unroll
                    for (int n = 1; n < 5; n++)
                        ldsm4(kk[n][0], kk[n][1], kk[n][2], kk[n][3], st + xoff + (n - 1) * 1024 + (i >> 1) * 16384 + (kch ^ ((i & 1) * 64)));
#pragma unroll
                    for (int n = 0; n < 5; n++) mma16816(sa[n], q[0], q[1], q[2], q[3], kk[n][0], kk[n][1]);
#pragma unroll
                    for (int n = 0; n < 5; n++) mma16816(sa[n], q[4], q[5], q[6], q[7], kk[n][2], kk[n][3]);
                }
                __syncwarp();
                if (lane == 0) mbar_arrive(bars + B_EMPTY + pp.stage * 8);
                pipe_next(pp);
                const int iq0 = half * 16 + g - 2 * t, iq1 = iq0 + 8;
                float m0 = fmaxf(sa[0][0], sa[0][1]), m1 = fmaxf(sa[0][2], sa[0][3]);
#pragma unroll
                for (int n = 1; n < 5; n++) {
#pragma unroll
                    for (int e = 0; e < 2; e++) {
                        const int jx = (n - 1) * 8 + e;
                        if (jx > iq0) sa[n][e] = -3.0e38f;
                        if (jx > iq1) sa[n][2 + e] = -3.0e38f;
                        m0 = fmaxf(m0, sa[n][e]); m1 = fmaxf(m1, sa[n][2 + e]);
                    }
                }
                m0 = fmaxf(m0, __shfl_xor_sync(~0u, m0, 1)); m1 = fmaxf(m1, __shfl_xor_sync(~0u, m1, 1));
                m0 = fmaxf(m0, __shfl_xor_sync(~0u, m0, 2)); m1 = fmaxf(m1, __shfl_xor_sync(~0u, m1, 2));
                m0 *= -sc; m1 *= -sc;
                float l0 = 0.f, l1 = 0.f;
                uint32_t p0[5], p1[5];
#pragma unroll
                for (int n = 0; n < 5; n++) {
                    const float e0 = ex2(fmaf(sa[n][0], sc, m0)), e1 = ex2(fmaf(sa[n][1], sc, m0));
                    const float e2 = ex2(fmaf(sa[n][2], sc, m1)), e3 = ex2(fmaf(sa[n][3], sc, m1));
                    l0 += e0 + e1; l1 += e2 + e3;
                    p0[n] = pack2(e0, e1); p1[n] = pack2(e2, e3);
                }
                l0 += __shfl_xor_sync(~0u, l0, 1); l1 += __shfl_xor_sync(~0u, l1, 1);
                l0 += __shfl_xor_sync(~0u, l0, 2); l1 += __shfl_xor_sync(~0u, l1, 2);
                const float i0 = __fdividef(1.f, l0), i1 = __fdividef(1.f, l1);
                mbar_wait(bars + B_FULL + pp.stage * 8, pp.phase);
                st = sb + pp.stage * W_STAGE;
                mbar_wait(bars + B_STGFREE + wg * 8, stg_phase); stg_phase ^= 1;
#pragma unroll
                for (int i = 0; i < 32; i++) qf[i] = qf[32 + i];
#pragma unroll 1
                for (int bx = 0; bx < 2; bx++) {
                    float o[8][4];
                    uint32_t vm[8], v0[4][4], v1[4][4];
#pragma unroll
                    for (int ep = 0; ep < 4; ep++) {
                        ldsm2t(vm[2 * ep], vm[2 * ep + 1], st + moff + bx * 4096 + (vch ^ (ep << 5)));
                        const uint32_t va = st + xoff + (l8 >> 1) * 1024 + bx * 16384 + (vch ^ (ep << 5));
                        ldsm4t(v0[ep][0], v0[ep][1], v0[ep][2], v0[ep][3], va);
                        ldsm4t(v1[ep][0], v1[ep][1], v1[ep][2], v1[ep][3], va + 2048);
                    }
#pragma unroll
                    for (int n = 0; n < 8; n++) { o[n][0] = o[n][1] = o[n][2] = o[n][3] = 0.f; mma16816(o[n], p0[0], p1[0], p0[1], p1[1], vm[n], v0[n >> 1][n & 1]); }
#pragma unroll
                    for (int n = 0; n < 8; n++) mma16816(o[n], p0[2], p1[2], p0[3], p1[3], v0[n >> 1][2 + (n & 1)], v1[n >> 1][n & 1]);
#pragma unroll
                    for (int n = 0; n < 8; n++) mma1688(o[n], p0[4], p1[4], v1[n >> 1][2 + (n & 1)]);
#pragma unroll
                    for (int ep = 0; ep < 4; ep++)
                        stsm4(stg_base + bx * 8192 + (sx ^ (ep << 5)),
                              pack2(o[2 * ep][0] * i0, o[2 * ep][1] * i0), pack2(o[2 * ep][2] * i1, o[2 * ep][3] * i1),
                              pack2(o[2 * ep + 1][0] * i0, o[2 * ep + 1][1] * i0), pack2(o[2 * ep + 1][2] * i1, o[2 * ep + 1][3] * i1));
                }
                __syncwarp();
                if (lane == 0) mbar_arrive(bars + B_EMPTY + pp.stage * 8);
                pipe_next(pp);
                if (hh == 0) { fence_async_smem(); bar_arrive(NB_ST + wg, 160); }
            }
        } else if (type == J_UP) {
            mbar_wait(bars + B_STGFREE + wg * 8, stg_phase); stg_phase ^= 1;
#pragma unroll
            for (int j = 0; j < 8; j++) {
                uint32_t r[4];
#pragma unroll
                for (int q = 0; q < 4; q++) {
                    const uint32_t gw = pack2(acc[8 * j + 2 * q], acc[8 * j + 2 * q + 1]);
                    const uint32_t uw = pack2(acc[64 + 8 * j + 2 * q], acc[64 + 8 * j + 2 * q + 1]);
                    r[q] = hmul2(pack2(gelu_tanh(bflo(gw)), gelu_tanh(bfhi(gw))), uw);
                }
                stsm4(stg_base + (j >> 2) * 8192 + (sx ^ ((2 * j & 7) << 4)), r[0], r[1], r[2], r[3]);
            }
        } else {
#pragma unroll
            for (int rd = 0; rd < 2; rd++) {
                mbar_wait(bars + B_STGFREE + wg * 8, stg_phase); stg_phase ^= 1;
#pragma unroll
                for (int j = rd * 8; j < rd * 8 + 8; j++)
                    stsm4(stg_base + ((j >> 2) & 1) * 8192 + (sx ^ ((2 * j & 7) << 4)),
                          pack2(acc[8 * j], acc[8 * j + 1]), pack2(acc[8 * j + 2], acc[8 * j + 3]),
                          pack2(acc[8 * j + 4], acc[8 * j + 5]), pack2(acc[8 * j + 6], acc[8 * j + 7]));
                if (rd == 0) { fence_async_smem(); bar_arrive(NB_ST + wg, 160); }
            }
        }
        fence_async_smem();
        CTR(5);
        bar_arrive(NB_ST + wg, 160);
    }
}

__global__ void __launch_bounds__(384, 1) k_work(const __grid_constant__ Params p) {
    extern __shared__ __align__(1024) unsigned char smem_raw[];
    const uint32_t sb = smem_u32(smem_raw);
    if (sb & 1023) __trap();
    const int warp = __shfl_sync(~0u, threadIdx.x >> 5, 0);
    int lane; asm volatile("mov.u32 %0, %%laneid;" : "=r"(lane));
    if (threadIdx.x == 0) {
        const uint32_t bars = sb + SM_BAR;
        for (int i = 0; i < W_NST; i++) { mbar_init(bars + B_FULL + i * 8, 1); mbar_init(bars + B_EMPTY + i * 8, 8); }
        mbar_init(bars + B_STGFREE, 1); mbar_init(bars + B_STGFREE + 8, 1); mbar_init(bars + B_REQ, 1); mbar_init(bars + B_RSP, 1);
        asm volatile("fence.mbarrier_init.release.cluster;" ::: "memory");
    }
    __syncthreads();
    if (warp < 8) {
        asm volatile("setmaxnreg.inc.sync.aligned.u32 224;");
        consumer(p, sb, warp, lane);
    } else {
        asm volatile("setmaxnreg.dec.sync.aligned.u32 56;");
        if (warp == 8) { if (lane == 0) producer(p, sb); }
        else if (warp < 11) store_warp(p, sb, warp - 9, lane);
        else scheduler(p, sb, lane);
        __syncwarp();
        bar_sync(NB_W0, 128);
        if (warp == 8 && p.qmask == 0xff) {
            unsigned last = 0;
            if (lane == 0) { __threadfence(); last = atomicAdd(&g_flags[F_DONE], 1u) == gridDim.x - 1; }
            if (__shfl_sync(~0u, last, 0))
                for (int i = lane; i < F_TOTAL; i += 32) g_flags[i] = 0;
        }
    }
}

typedef CUresult (*EncodeFn)(CUtensorMap*, CUtensorMapDataType, cuuint32_t, void*, const cuuint64_t*, const cuuint64_t*,
                             const cuuint32_t*, const cuuint32_t*, CUtensorMapInterleave, CUtensorMapSwizzle,
                             CUtensorMapL2promotion, CUtensorMapFloatOOBfill);

static void make_map(EncodeFn enc, CUtensorMap* m, const void* ptr, uint64_t rows, uint64_t cols, uint32_t box_rows) {
    cuuint64_t dims[2] = {cols, rows};
    cuuint64_t strides[1] = {cols * 2};
    cuuint32_t box[2] = {64, box_rows};
    cuuint32_t es[2] = {1, 1};
    enc(m, CU_TENSOR_MAP_DATA_TYPE_BFLOAT16, 2, const_cast<void*>(ptr), dims, strides, box, es, CU_TENSOR_MAP_INTERLEAVE_NONE,
        CU_TENSOR_MAP_SWIZZLE_128B, CU_TENSOR_MAP_L2_PROMOTION_L2_256B, CU_TENSOR_MAP_FLOAT_OOB_FILL_NONE);
}
template <typename T> static void* sym_addr(T& sym) { void* p = nullptr; cudaGetSymbolAddress(&p, sym); return p; }

extern "C" void kernel_launch(void* const* d_in, const int* in_sizes, int n_in, void* d_out, int out_size) {
    static Params prm;
    static RecParams rp;
    static bool ready = false;
    static const void* key[14];
    bool same = ready;
    for (int i = 0; i < 13 && same; i++) same = key[i] == d_in[i];
    same = same && key[13] == d_out;
    if (!same) {
        void* fn = nullptr;
        cudaDriverEntryPointQueryResult qr;
        cudaGetDriverEntryPoint("cuTensorMapEncodeTiled", &fn, cudaEnableDefault, &qr);
        EncodeFn enc = (EncodeFn)fn;
        make_map(enc, &prm.tm_h, sym_addr(g_h), S_, D_, 64);
        make_map(enc, &prm.tm_kv, sym_addr(g_kv), S_, 2 * HD_, 64);
        make_map(enc, &prm.tm_kvm, sym_addr(g_kvm), NSEG * 8, 2 * HD_, 32);
        make_map(enc, &prm.tm_o, sym_addr(g_o), S_, HD_, 64);
        make_map(enc, &prm.tm_op, sym_addr(g_op), OP_ROWS, D_, 64);
        make_map(enc, &prm.tm_h2, sym_addr(g_h2), S_, D_, 64);
        make_map(enc, &prm.tm_act, sym_addr(g_act), S_, DF_, 64);
        make_map(enc, &prm.tm_x1, sym_addr(g_x1), S_, D_, 64);
        make_map(enc, &prm.tm_out, d_out, S_, D_, 64);
        make_map(enc, &prm.tm_wq, d_in[2], D_, HD_, 64);
        make_map(enc, &prm.tm_wk, d_in[3], D_, HD_, 64);
        make_map(enc, &prm.tm_wv, d_in[4], D_, HD_, 64);
        make_map(enc, &prm.tm_wo, d_in[5], HD_, D_, 64);
        make_map(enc, &prm.tm_wg, d_in[8], D_, DF_, 64);
        make_map(enc, &prm.tm_wu, d_in[9], D_, DF_, 64);
        make_map(enc, &prm.tm_wd, d_in[10], DF_, D_, 64);
        prm.x = (const bf16*)d_in[0]; prm.c = (const bf16*)d_in[11]; prm.w_mod = (const bf16*)d_in[12];
        rp.mem0 = (const bf16*)d_in[1]; rp.x = prm.x; rp.c = prm.c; rp.w_mod = prm.w_mod;
        rp.wq = (const bf16*)d_in[2]; rp.wk = (const bf16*)d_in[3]; rp.wv = (const bf16*)d_in[4]; rp.wo = (const bf16*)d_in[5];
        cudaFuncSetAttribute(k_work, cudaFuncAttributeMaxDynamicSharedMemorySize, SMEM_BYTES);
        cudaFuncSetAttribute(k_rec, cudaFuncAttributeMaxDynamicSharedMemorySize, R_SMEM);
        cudaFuncSetAttribute(k_rec, cudaFuncAttributeNonPortableClusterSizeAllowed, 1);
        {
            cudaLaunchConfig_t cfg = {};
            cfg.gridDim = dim3(128); cfg.blockDim = dim3(384); cfg.dynamicSmemBytes = R_SMEM;
            cudaLaunchAttribute at[1];
            at[0].id = cudaLaunchAttributeClusterDimension; at[0].val.clusterDim.x = 16; at[0].val.clusterDim.y = 1; at[0].val.clusterDim.z = 1;
            cfg.attrs = at; cfg.numAttrs = 1;
            int n = 0;
            cudaOccupancyMaxActiveClusters(&n, k_rec, &cfg);
            rp.ncl = n < 4 ? 4 : (n > 8 ? 8 : n);
        }
        for (int i = 0; i < 13; i++) key[i] = d_in[i];
        key[13] = d_out;
        ready = true;
    }
    cudaStream_t st = cudaStreamPerThread;
    auto launch_rec = [&]() {
        cudaLaunchConfig_t cfg = {};
        cfg.gridDim = dim3(16 * rp.ncl); cfg.blockDim = dim3(384); cfg.dynamicSmemBytes = R_SMEM; cfg.stream = st;
        cudaLaunchAttribute at[1];
        at[0].id = cudaLaunchAttributeClusterDimension; at[0].val.clusterDim.x = 16; at[0].val.clusterDim.y = 1; at[0].val.clusterDim.z = 1;
        cfg.attrs = at; cfg.numAttrs = 1;
        cudaLaunchKernelEx(&cfg, k_rec, rp);
    };
    auto launch_work = [&](int qmask, int pdl) {
        prm.qmask = qmask;
        cudaLaunchConfig_t cfg = {};
        cfg.gridDim = dim3(132); cfg.blockDim = dim3(384); cfg.dynamicSmemBytes = SMEM_BYTES; cfg.stream = st;
        cudaLaunchAttribute at[1];
        at[0].id = cudaLaunchAttributeProgrammaticStreamSerialization; at[0].val.programmaticStreamSerializationAllowed = 1;
        cfg.attrs = at; cfg.numAttrs = pdl;
        cudaLaunchKernelEx(&cfg, k_work, prm);
    };
    launch_rec();
    launch_work(0xff, 1);
}
```

```cpp
#include <cuda_runtime.h>
#include <cuda_bf16.h>
#include <cuda.h>
#include <stdint.h>

typedef __nv_bfloat16 bf16;
#define PF_NS 500
#define IDLE_NS 150
#define FLAG_NS 20

constexpr int S_ = 2048, D_ = 512, H_ = 32, DH_ = 128, HD_ = 4096, NSEG = 64, DF_ = 1792;
constexpr int NRB = 16;
constexpr int OSPLIT = 4;

__device__ __align__(1024) bf16 g_h[S_ * D_];
__device__ __align__(1024) bf16 g_kv[S_ * 2 * HD_];
__device__ __align__(1024) bf16 g_kvm[NSEG * 8 * 2 * HD_];
__device__ __align__(1024) bf16 g_o[S_ * HD_];
#define FINE_RB_ 12
constexpr int FINE_RB = FINE_RB_;
#define OSPLIT2_ 8
constexpr int OSPLIT2 = OSPLIT2_;
constexpr int OSPLIT3 = 16;
constexpr int OP_ROWS = OSPLIT * S_ + OSPLIT2 * (NRB - FINE_RB) * 128 + OSPLIT3 * 128;
__device__ __align__(1024) bf16 g_op[OP_ROWS * D_];
__device__ __align__(1024) bf16 g_x1[S_ * D_];
__device__ __align__(1024) bf16 g_h2[S_ * D_];
__device__ __align__(1024) bf16 g_act[S_ * DF_];
__device__ __align__(1024) bf16 g_mod[6 * D_];
__device__ uint32_t g_Fraw[131072 + 65536 + 2048];
#define g_F ((uint32_t*)(((uint64_t)g_Fraw + 0x7FFFFull) & ~0x7FFFFull))
constexpr int F_H = 0, F_MEM = 32, F_O = 64, F_OP = 96, F_H2 = 128, F_ACT = 160, F_MOD = 192, F_KV = 224, F_CLAIM = 256  ,
              F_SIDE = 512  , F_DONE = 576, F_TOTAL = 608;
__device__ __align__(128) unsigned int g_flags[F_TOTAL];
#define TR(j, i) do {} while (0)

__device__ __forceinline__ uint32_t smem_u32(const void* p) { return (uint32_t)__cvta_generic_to_shared(p); }
__device__ __forceinline__ uint32_t clk32() { uint32_t c; asm volatile("mov.u32 %0, %%clock;" : "=r"(c)); return c; }
__device__ __forceinline__ uint32_t mapa_u32(uint32_t addr, uint32_t rank) {
    uint32_t r; asm volatile("mapa.shared::cluster.u32 %0, %1, %2;" : "=r"(r) : "r"(addr), "r"(rank)); return r;
}
__device__ __forceinline__ void mbar_init(uint32_t bar, uint32_t cnt) {
    asm volatile("mbarrier.init.shared::cta.b64 [%0], %1;" :: "r"(bar), "r"(cnt) : "memory");
}
__device__ __forceinline__ void mbar_inval(uint32_t bar) {
    asm volatile("mbarrier.inval.shared::cta.b64 [%0];" :: "r"(bar) : "memory");
}
__device__ __forceinline__ void mbar_expect_tx(uint32_t bar, uint32_t bytes) {
    asm volatile("mbarrier.arrive.expect_tx.shared::cta.b64 _, [%0], %1;" :: "r"(bar), "r"(bytes) : "memory");
}
__device__ __forceinline__ void mbar_arrive(uint32_t bar) {
    asm volatile("mbarrier.arrive.shared::cta.b64 _, [%0];" :: "r"(bar) : "memory");
}
__device__ __forceinline__ bool mbar_try_wait(uint32_t bar, uint32_t parity) {
    uint32_t ok;
    asm volatile("{\n.reg .pred p;\nmbarrier.try_wait.parity.shared::cta.b64 p, [%1], %2;\nselp.u32 %0, 1, 0, p;\n}"
                 : "=r"(ok) : "r"(bar), "r"(parity) : "memory");
    return ok;
}
__device__ __forceinline__ bool mbar_try_wait_cluster(uint32_t bar, uint32_t parity) {
    uint32_t ok;
    asm volatile("{\n.reg .pred p;\nmbarrier.try_wait.parity.acquire.cluster.shared::cta.b64 p, [%1], %2;\nselp.u32 %0, 1, 0, p;\n}"
                 : "=r"(ok) : "r"(bar), "r"(parity) : "memory");
    return ok;
}
constexpr int SPIN_LIMIT = 1 << 18;
#define TIMEOUT(code, info) do {} while (0)
__device__ __forceinline__ void mbar_wait(uint32_t bar, uint32_t parity) {
    int g = 0;
#pragma unroll 1
    while (!mbar_try_wait(bar, parity)) { if (++g >= SPIN_LIMIT) { TIMEOUT(0, bar & 255); break; } }
}
__device__ __forceinline__ void mbar_wait_cluster(uint32_t bar, uint32_t parity) {
    int g = 0;
#pragma unroll 1
    while (!mbar_try_wait_cluster(bar, parity)) { if (++g >= SPIN_LIMIT) { TIMEOUT(1, bar & 255); break; } }
}
__device__ __forceinline__ void bar_sync(int id, int n) { asm volatile("bar.sync %0, %1;" :: "r"(id), "r"(n) : "memory"); }
__device__ __forceinline__ void bar_arrive(int id, int n) { asm volatile("bar.arrive %0, %1;" :: "r"(id), "r"(n) : "memory"); }
__device__ __forceinline__ void cluster_sync_all() {
    asm volatile("barrier.cluster.arrive.aligned;\nbarrier.cluster.wait.aligned;" ::: "memory");
}
__device__ __forceinline__ void st_async_v2(uint32_t addr, float a, float b, uint32_t bar) {
    asm volatile("st.async.weak.shared::cluster.mbarrier::complete_tx::bytes.v2.f32 [%0], {%1,%2}, [%3];"
                 :: "r"(addr), "f"(a), "f"(b), "r"(bar) : "memory");
}
__device__ __forceinline__ void st_async_v4(uint32_t addr, uint4 v, uint32_t bar) {
    asm volatile("st.async.weak.shared::cluster.mbarrier::complete_tx::bytes.v4.b32 [%0], {%1,%2,%3,%4}, [%5];"
                 :: "r"(addr), "r"(v.x), "r"(v.y), "r"(v.z), "r"(v.w), "r"(bar) : "memory");
}
__device__ __forceinline__ uint2 ldg_relaxed2(const uint2* p) {
    uint2 v;
    asm volatile("ld.relaxed.gpu.global.v2.b32 {%0,%1}, [%2];" : "=r"(v.x), "=r"(v.y) : "l"(p) : "memory");
    return v;
}
__device__ __forceinline__ void stg_relaxed2(uint2* p, uint2 v) {
    asm volatile("st.relaxed.gpu.global.v2.b32 [%0], {%1,%2};" :: "l"(p), "r"(v.x), "r"(v.y) : "memory");
}
__device__ __forceinline__ uint4 ldg_relaxed(const uint4* p) {
    uint4 v;
    asm volatile("ld.relaxed.gpu.global.v4.b32 {%0,%1,%2,%3}, [%4];" : "=r"(v.x), "=r"(v.y), "=r"(v.z), "=r"(v.w) : "l"(p) : "memory");
    return v;
}
__device__ __forceinline__ void stg_relaxed(uint4* p, uint4 v) {
    asm volatile("st.relaxed.gpu.global.v4.b32 [%0], {%1,%2,%3,%4};" :: "l"(p), "r"(v.x), "r"(v.y), "r"(v.z), "r"(v.w) : "memory");
}
__device__ __forceinline__ void stg_relaxed32(uint32_t* p, uint32_t v) {
    asm volatile("st.relaxed.gpu.global.b32 [%0], %1;" :: "l"(p), "r"(v) : "memory");
}
__device__ __forceinline__ uint32_t ldg_relaxed32(const uint32_t* p) {
    uint32_t v; asm volatile("ld.relaxed.gpu.global.b32 %0, [%1];" : "=r"(v) : "l"(p) : "memory"); return v;
}
__device__ __forceinline__ unsigned int ld_acquire(const unsigned int* p) {
    unsigned int v; asm volatile("ld.acquire.gpu.global.u32 %0, [%1];" : "=r"(v) : "l"(p) : "memory"); return v;
}
__device__ __forceinline__ void red_release(unsigned int* p, unsigned int v) {
    asm volatile("red.release.gpu.global.add.u32 [%0], %1;" :: "l"(p), "r"(v) : "memory");
}
__device__ __forceinline__ void wait_flag(int idx, unsigned int target) {
    const unsigned int* p = &g_flags[idx];
    int g = 0;
#pragma unroll 1
    while (ld_acquire(p) < target) { __nanosleep(FLAG_NS); if (++g >= 64 * SPIN_LIMIT) { TIMEOUT(2, idx); break; } }
}
__device__ __forceinline__ void cp_async16(uint32_t dst, const void* src) {
    asm volatile("cp.async.cg.shared.global [%0], [%1], 16;" :: "r"(dst), "l"(src) : "memory");
}
__device__ __forceinline__ void cp_async_commit() { asm volatile("cp.async.commit_group;" ::: "memory"); }
template <int N> __device__ __forceinline__ void cp_async_wait() { asm volatile("cp.async.wait_group %0;" :: "n"(N) : "memory"); }
__device__ __forceinline__ void ldsm4(uint32_t& r0, uint32_t& r1, uint32_t& r2, uint32_t& r3, uint32_t addr) {
    asm volatile("ldmatrix.sync.aligned.m8n8.x4.shared.b16 {%0,%1,%2,%3}, [%4];" : "=r"(r0), "=r"(r1), "=r"(r2), "=r"(r3) : "r"(addr) : "memory");
}
__device__ __forceinline__ void ldsm4t(uint32_t& r0, uint32_t& r1, uint32_t& r2, uint32_t& r3, uint32_t addr) {
    asm volatile("ldmatrix.sync.aligned.m8n8.x4.trans.shared.b16 {%0,%1,%2,%3}, [%4];" : "=r"(r0), "=r"(r1), "=r"(r2), "=r"(r3) : "r"(addr) : "memory");
}
__device__ __forceinline__ void ldsm2t(uint32_t& r0, uint32_t& r1, uint32_t addr) {
    asm volatile("ldmatrix.sync.aligned.m8n8.x2.trans.shared.b16 {%0,%1}, [%2];" : "=r"(r0), "=r"(r1) : "r"(addr) : "memory");
}
__device__ __forceinline__ void stsm4(uint32_t addr, uint32_t r0, uint32_t r1, uint32_t r2, uint32_t r3) {
    asm volatile("stmatrix.sync.aligned.m8n8.x4.shared.b16 [%0], {%1,%2,%3,%4};" :: "r"(addr), "r"(r0), "r"(r1), "r"(r2), "r"(r3) : "memory");
}
__device__ __forceinline__ void stsm2t(uint32_t addr, uint32_t r0, uint32_t r1) {
    asm volatile("stmatrix.sync.aligned.m8n8.x2.trans.shared.b16 [%0], {%1,%2};" :: "r"(addr), "r"(r0), "r"(r1) : "memory");
}
__device__ __forceinline__ void mma16816(float* d, uint32_t a0, uint32_t a1, uint32_t a2, uint32_t a3, uint32_t b0, uint32_t b1) {
    asm volatile("mma.sync.aligned.m16n8k16.row.col.f32.bf16.bf16.f32 {%0,%1,%2,%3}, {%4,%5,%6,%7}, {%8,%9}, {%0,%1,%2,%3};"
                 : "+f"(d[0]), "+f"(d[1]), "+f"(d[2]), "+f"(d[3]) : "r"(a0), "r"(a1), "r"(a2), "r"(a3), "r"(b0), "r"(b1));
}
__device__ __forceinline__ void mma1688(float* d, uint32_t a0, uint32_t a1, uint32_t b0) {
    asm volatile("mma.sync.aligned.m16n8k8.row.col.f32.bf16.bf16.f32 {%0,%1,%2,%3}, {%4,%5}, {%6}, {%0,%1,%2,%3};"
                 : "+f"(d[0]), "+f"(d[1]), "+f"(d[2]), "+f"(d[3]) : "r"(a0), "r"(a1), "r"(b0));
}
__device__ __forceinline__ void mma16816h(float* d, uint32_t a0, uint32_t a2, uint32_t b0, uint32_t b1) {
    asm volatile("{\n.reg .b32 ju, jv;\nmma.sync.aligned.m16n8k16.row.col.f32.bf16.bf16.f32 {%0,%1,%2,%3}, {%4,ju,%5,jv}, {%6,%7}, {%0,%1,%2,%3};\n}"
                 : "+f"(d[0]), "+f"(d[1]), "+f"(d[2]), "+f"(d[3]) : "r"(a0), "r"(a2), "r"(b0), "r"(b1));
}
__device__ __forceinline__ void mma1688h(float* d, uint32_t a0, uint32_t b0) {
    asm volatile("{\n.reg .b32 ju;\nmma.sync.aligned.m16n8k8.row.col.f32.bf16.bf16.f32 {%0,%1,%2,%3}, {%4,ju}, {%5}, {%0,%1,%2,%3};\n}"
                 : "+f"(d[0]), "+f"(d[1]), "+f"(d[2]), "+f"(d[3]) : "r"(a0), "r"(b0));
}
__device__ __forceinline__ uint32_t pack2(float lo, float hi) {
    uint32_t r; asm("cvt.rn.bf16x2.f32 %0, %1, %2;" : "=r"(r) : "f"(hi), "f"(lo)); return r;
}
__device__ __forceinline__ float bflo(uint32_t w) { return __uint_as_float(w << 16); }
__device__ __forceinline__ float bfhi(uint32_t w) { return __uint_as_float(w & 0xffff0000u); }
__device__ __forceinline__ float rbf(float x) { return __bfloat162float(__float2bfloat16_rn(x)); }
__device__ __forceinline__ float ex2(float x) { float y; asm("ex2.approx.ftz.f32 %0, %1;" : "=f"(y) : "f"(x)); return y; }
__device__ __forceinline__ void sts128(uint32_t addr, uint4 v) {
    asm volatile("st.shared.v4.b32 [%0], {%1,%2,%3,%4};" :: "r"(addr), "r"(v.x), "r"(v.y), "r"(v.z), "r"(v.w) : "memory");
}
__device__ __forceinline__ uint4 lds128(uint32_t addr) {
    uint4 v; asm volatile("ld.shared.v4.b32 {%0,%1,%2,%3}, [%4];" : "=r"(v.x), "=r"(v.y), "=r"(v.z), "=r"(v.w) : "r"(addr) : "memory"); return v;
}
__device__ __forceinline__ float2 lds64f(uint32_t addr) {
    float2 v; asm volatile("ld.shared.v2.f32 {%0,%1}, [%2];" : "=f"(v.x), "=f"(v.y) : "r"(addr) : "memory"); return v;
}
__device__ __forceinline__ float lds32f(uint32_t addr) {
    float v; asm volatile("ld.shared.f32 %0, [%1];" : "=f"(v) : "r"(addr) : "memory"); return v;
}
__device__ __forceinline__ uint32_t lds32(uint32_t addr) {
    uint32_t v; asm volatile("ld.shared.b32 %0, [%1];" : "=r"(v) : "r"(addr) : "memory"); return v;
}
__device__ __forceinline__ void sts32(uint32_t addr, uint32_t v) { asm volatile("st.shared.b32 [%0], %1;" :: "r"(addr), "r"(v) : "memory"); }
__device__ __forceinline__ void sts64f(uint32_t addr, float a, float b) { asm volatile("st.shared.v2.f32 [%0], {%1,%2};" :: "r"(addr), "f"(a), "f"(b) : "memory"); }

__device__ __forceinline__ void tma_load2d(uint32_t dst, const CUtensorMap* tm, int c0, int c1, uint32_t bar) {
    asm volatile("cp.async.bulk.tensor.2d.shared::cluster.global.mbarrier::complete_tx::bytes [%0], [%1, {%3, %4}], [%2];"
                 :: "r"(dst), "l"(tm), "r"(bar), "r"(c0), "r"(c1) : "memory");
}
__device__ __forceinline__ void tma_store2d(const CUtensorMap* tm, uint32_t src, int c0, int c1) {
    asm volatile("cp.async.bulk.tensor.2d.global.shared::cta.bulk_group [%0, {%2, %3}], [%1];"
                 :: "l"(tm), "r"(src), "r"(c0), "r"(c1) : "memory");
}
__device__ __forceinline__ void bulk_commit() { asm volatile("cp.async.bulk.commit_group;" ::: "memory"); }
__device__ __forceinline__ void bulk_wait0() { asm volatile("cp.async.bulk.wait_group 0;" ::: "memory"); }
__device__ __forceinline__ void fence_async_smem() { asm volatile("fence.proxy.async.shared::cta;" ::: "memory"); }
__device__ __forceinline__ void fence_async_all() { asm volatile("fence.proxy.async;" ::: "memory"); }

__device__ __forceinline__ void wg_fence() { asm volatile("wgmma.fence.sync.aligned;" ::: "memory"); }
__device__ __forceinline__ void wg_commit() { asm volatile("wgmma.commit_group.sync.aligned;" ::: "memory"); }
__device__ __forceinline__ void wg_wait0() { asm volatile("wgmma.wait_group.sync.aligned 0;" ::: "memory"); }
__device__ __forceinline__ uint64_t mkdesc(uint32_t saddr, uint32_t lbo, uint32_t sbo) {
    return (uint64_t)((saddr & 0x3FFFF) >> 4) | ((uint64_t)(lbo >> 4) << 16) | ((uint64_t)(sbo >> 4) << 32) | (1ull << 62);
}
#define ACC8(i) "+f"(d[i]), "+f"(d[i + 1]), "+f"(d[i + 2]), "+f"(d[i + 3]), "+f"(d[i + 4]), "+f"(d[i + 5]), "+f"(d[i + 6]), "+f"(d[i + 7])
__device__ __forceinline__ void wgmma_n256(float* d, uint64_t da, uint64_t db, int scale_d) {
    asm volatile(
        "{\n.reg .pred p;\nsetp.ne.b32 p, %130, 0;\n"
        "wgmma.mma_async.sync.aligned.m64n256k16.f32.bf16.bf16 "
        "{%0,%1,%2,%3,%4,%5,%6,%7,%8,%9,%10,%11,%12,%13,%14,%15,%16,%17,%18,%19,%20,%21,%22,%23,%24,%25,%26,%27,%28,%29,%30,%31,"
        "%32,%33,%34,%35,%36,%37,%38,%39,%40,%41,%42,%43,%44,%45,%46,%47,%48,%49,%50,%51,%52,%53,%54,%55,%56,%57,%58,%59,%60,%61,%62,%63,"
        "%64,%65,%66,%67,%68,%69,%70,%71,%72,%73,%74,%75,%76,%77,%78,%79,%80,%81,%82,%83,%84,%85,%86,%87,%88,%89,%90,%91,%92,%93,%94,%95,"
        "%96,%97,%98,%99,%100,%101,%102,%103,%104,%105,%106,%107,%108,%109,%110,%111,%112,%113,%114,%115,%116,%117,%118,%119,%120,%121,%122,%123,%124,%125,%126,%127}, "
        "%128, %129, p, 1, 1, 0, 1;\n}"
        : ACC8(0), ACC8(8), ACC8(16), ACC8(24), ACC8(32), ACC8(40), ACC8(48), ACC8(56),
          ACC8(64), ACC8(72), ACC8(80), ACC8(88), ACC8(96), ACC8(104), ACC8(112), ACC8(120)
        : "l"(da), "l"(db), "r"(scale_d));
}
__device__ __forceinline__ void wgmma_n128(float* d, uint64_t da, uint64_t db, int scale_d) {
    asm volatile(
        "{\n.reg .pred p;\nsetp.ne.b32 p, %66, 0;\n"
        "wgmma.mma_async.sync.aligned.m64n128k16.f32.bf16.bf16 "
        "{%0,%1,%2,%3,%4,%5,%6,%7,%8,%9,%10,%11,%12,%13,%14,%15,%16,%17,%18,%19,%20,%21,%22,%23,%24,%25,%26,%27,%28,%29,%30,%31,"
        "%32,%33,%34,%35,%36,%37,%38,%39,%40,%41,%42,%43,%44,%45,%46,%47,%48,%49,%50,%51,%52,%53,%54,%55,%56,%57,%58,%59,%60,%61,%62,%63}, "
        "%64, %65, p, 1, 1, 0, 1;\n}"
        : ACC8(0), ACC8(8), ACC8(16), ACC8(24), ACC8(32), ACC8(40), ACC8(48), ACC8(56)
        : "l"(da), "l"(db), "r"(scale_d));
}

__device__ __forceinline__ void wgmma_n64(float* d, uint64_t da, uint64_t db) {
    asm volatile(
        "wgmma.mma_async.sync.aligned.m64n64k16.f32.bf16.bf16 "
        "{%0,%1,%2,%3,%4,%5,%6,%7,%8,%9,%10,%11,%12,%13,%14,%15,%16,%17,%18,%19,%20,%21,%22,%23,%24,%25,%26,%27,%28,%29,%30,%31}, "
        "%32, %33, 1, 1, 1, 0, 1;"
        : ACC8(0), ACC8(8), ACC8(16), ACC8(24)
        : "l"(da), "l"(db));
}
__device__ __forceinline__ void wgmma_n8_ta(float* d, uint64_t da, uint64_t db, int scale_d) {
    asm volatile(
        "{\n.reg .pred p;\nsetp.ne.b32 p, %6, 0;\n"
        "wgmma.mma_async.sync.aligned.m64n8k16.f32.bf16.bf16 {%0,%1,%2,%3}, %4, %5, p, 1, 1, 1, 0;\n}"
        : "+f"(d[0]), "+f"(d[1]), "+f"(d[2]), "+f"(d[3]) : "l"(da), "l"(db), "r"(scale_d));
}

__device__ __forceinline__ uint32_t hadd2(uint32_t a, uint32_t b) { uint32_t r; asm("add.rn.bf16x2 %0, %1, %2;" : "=r"(r) : "r"(a), "r"(b)); return r; }
__device__ __forceinline__ uint32_t hsub2(uint32_t a, uint32_t b) { uint32_t r; asm("sub.rn.bf16x2 %0, %1, %2;" : "=r"(r) : "r"(a), "r"(b)); return r; }
__device__ __forceinline__ uint32_t hmul2(uint32_t a, uint32_t b) { uint32_t r; asm("mul.rn.bf16x2 %0, %1, %2;" : "=r"(r) : "r"(a), "r"(b)); return r; }
__device__ __forceinline__ void load_mod8(const bf16* m, int lane, uint32_t* v) {
    const uint4 a = __ldcg((const uint4*)m + lane), b = __ldcg((const uint4*)m + 32 + lane);
    v[0] = a.x; v[1] = a.y; v[2] = a.z; v[3] = a.w; v[4] = b.x; v[5] = b.y; v[6] = b.z; v[7] = b.w;
}
__device__ __forceinline__ void ln_stats(const uint32_t* x, uint32_t& mu2, float& rden) {
    float s = 0.f;
#pragma unroll
    for (int i = 0; i < 8; i++) s += bflo(x[i]) + bfhi(x[i]);
#pragma unroll
    for (int o = 16; o > 0; o >>= 1) s += __shfl_xor_sync(~0u, s, o);
    const float mean = s * (1.f / D_);
    float q = 0.f;
#pragma unroll
    for (int i = 0; i < 8; i++) { const float d0 = bflo(x[i]) - mean, d1 = bfhi(x[i]) - mean; q = fmaf(d0, d0, q); q = fmaf(d1, d1, q); }
#pragma unroll
    for (int o = 16; o > 0; o >>= 1) q += __shfl_xor_sync(~0u, q, o);
    mu2 = pack2(mean, mean);
    rden = __frcp_rn(rbf(__fsqrt_rn(rbf(rbf(q * (1.f / D_)) + 1e-5f))));
}
__device__ __forceinline__ void ln_apply(const uint32_t* x, uint32_t mu2, float rden, const uint32_t* c1, const uint32_t* sm, uint32_t* r) {
#pragma unroll
    for (int i = 0; i < 8; i++) {
        const uint32_t d = hsub2(x[i], mu2);
        r[i] = hadd2(hmul2(pack2(bflo(d) * rden, bfhi(d) * rden), c1[i]), sm[i]);
    }
}

struct __align__(64) Params {
    CUtensorMap tm_h, tm_kv, tm_kvm, tm_o, tm_op, tm_h2, tm_act, tm_x1, tm_out;
    CUtensorMap tm_wq, tm_wk, tm_wv, tm_wo, tm_wg, tm_wu, tm_wd;
    const bf16 *x, *c, *w_mod;
    int qmask;
};

constexpr int R_NST = 3;
constexpr uint32_t R_WV = 0, R_MEM = 65536, R_KX = 73728, R_VX = R_KX + R_NST * 4096,
                   R_KMS = R_VX + R_NST * 4096  , R_VMS = R_KMS + 1024,
                   R_QS = R_KMS + 4096, R_OS = R_QS + 1024, R_SX = R_OS + 1024, R_BAR = R_SX + 2560,
                   R_RS = 107520  , R_VP = R_RS + 8192  ,
                   R_STG = R_VP + 8192  , R_SMEM = R_STG + 98304;
static_assert((R_KMS & 4095) == 0, "smem");
static_assert(R_BAR + 64 <= R_RS, "smem");
constexpr uint32_t RB_SX = R_BAR, RB_V = R_BAR + 8, RB_E = R_BAR + 16, RB_A = R_BAR + 24, RB_ROLE = R_BAR + 32, RB_A1 = R_BAR + 40;
constexpr int W_NST = 4;
constexpr uint32_t W_STAGE = 49152, W_STG = W_NST * W_STAGE  , W_END = W_STG + 32768;
constexpr uint32_t SM_BAR = W_END;
constexpr uint32_t SMEM_BYTES = W_END + 1024 + 2048;
constexpr uint32_t B_FULL = 0, B_EMPTY = 32, B_STGFREE = 64, B_REQ = 80, B_RSP = 88, B_NEXT = 96, B_RING = 128;
#define PICK_AHEAD 3

constexpr int NB_X = 11  , NB_Y = 1, NB_M = 5, NB_K = 5, NB_B = 2, NB_C = 3, NB_D = 4, NB_W0 = 6  , NB_ST = 9  ;

__device__ __forceinline__ int pos_of_d(int d) {
    const int rem = d & 31;
    return (d & ~31) + ((rem & 7) >> 1) * 8 + (rem & 1) * 4 + (rem >> 3);
}

#define PROF(i) do {} while (0)
#define PROFG(i) do {} while (0)
#define OPAQUE(x) asm volatile("" : "+r"(x))
#define FENCE_SCHED(x) do { if ((x) == 0u) asm volatile("trap;"); } while (0)
#define QKVAR 2
#define VK0_ 4
constexpr int VK0 = VK0_;
constexpr int NOFF = 8;
#define VDELAY -1
#define POLL_GAP 110

struct RecParams { const bf16 *mem0, *wq, *wk, *wv, *wo, *x, *c, *w_mod; int ncl, only_pre; };

__device__ __forceinline__ void rec_qk(const RecParams& p, const uint32_t sb, const int cta, const int warp, int lane, const int sel) {
    const int crank = cta & 15, cl = cta >> 4, rank = cta & 1;
    const int kh = warp >> 2, aa = warp & 3;
    uint32_t wa[2][16][4];
    const uint32_t stg = sb + R_STG + kh * 32768;
    {
        const int t128 = aa * 32 + lane;
        const int row = (lane >> 4) * 8 + (lane & 7);
        const int ch = t128 & 7;
        const size_t goff = (size_t)kh * 256 * HD_ + cta * 64 + ch * 8;
#pragma unroll 4
        for (int dd = 0; dd < 16; dd++) {
            const int d = dd * 16 + (t128 >> 3), pp = pos_of_d(d);
            cp_async16(sb + R_WV + kh * 32768 + pp * 128 + ((ch ^ (pp & 7)) << 4), p.wv + goff + (size_t)d * HD_);
        }
        cp_async_commit();
#pragma unroll 4
        for (int dd = 0; dd < 16; dd++) {
            const int d = dd * 16 + (t128 >> 3), pp = pos_of_d(d);
            cp_async16(stg + pp * 128 + ((ch ^ (pp & 7)) << 4), p.wq + goff + (size_t)d * HD_);
        }
        cp_async_commit();
        {
            const int i0 = (warp * 32 + lane) * 16, tok = i0 >> 9;
            const uint4 m0 = __ldg((const uint4*)(p.mem0 + i0)), m1 = __ldg((const uint4*)(p.mem0 + i0 + 8));
            const uint32_t mw[8] = {m0.x, m0.y, m0.z, m0.w, m1.x, m1.y, m1.z, m1.w};
#pragma unroll
            for (int e = 0; e < 16; e++) {
                const int pp = pos_of_d((i0 & 511) + e);
                const unsigned short v = (unsigned short)(mw[e >> 1] >> ((e & 1) * 16));
                asm volatile("st.shared.u16 [%0], %1;" :: "r"(sb + R_MEM + (pp >> 3) * 128 + tok * 16 + (pp & 7) * 2), "h"(v) : "memory");
            }
        }
        cp_async_wait<1>();
        bar_sync(NB_W0 + kh, 128);
        const uint32_t fv = row * 128 + (((2 * aa + ((lane >> 3) & 1)) ^ (row & 7)) << 4);
#pragma unroll
        for (int ks = 0; ks < 16; ks++) ldsm4t(wa[0][ks][0], wa[0][ks][1], wa[0][ks][2], wa[0][ks][3], sb + R_WV + kh * 32768 + fv + ks * 2048);
        bar_sync(NB_W0 + kh, 128);
#pragma unroll
        for (int ks = 0; ks < 16; ks++)
            sts128(sb + R_WV + kh * 32768 + (aa * 16 + ks) * 512 + lane * 16, make_uint4(wa[0][ks][0], wa[0][ks][1], wa[0][ks][2], wa[0][ks][3]));
        const uint32_t fo = stg + row * 128 + (((4 * (aa & 1) + ((lane >> 3) & 1)) ^ (row & 7)) << 4);
#pragma unroll 1
        for (int m = 0; m < 2; m++) {
            cp_async_wait<0>();
            bar_sync(NB_W0 + kh, 128);
            if ((aa >> 1) == m) {
#pragma unroll
                for (int ks = 0; ks < 16; ks++) {
                    ldsm4t(wa[0][ks][0], wa[0][ks][1], wa[0][ks][2], wa[0][ks][3], fo + ks * 2048);
                    ldsm4t(wa[1][ks][0], wa[1][ks][1], wa[1][ks][2], wa[1][ks][3], (fo ^ 32) + ks * 2048);
                }
            }
            bar_sync(NB_W0 + kh, 128);
            if (m == 0) {
#pragma unroll 4
                for (int dd = 0; dd < 16; dd++) {
                    const int d = dd * 16 + (t128 >> 3), pp = pos_of_d(d);
                    cp_async16(stg + pp * 128 + ((ch ^ (pp & 7)) << 4), p.wk + goff + (size_t)d * HD_);
                }
                cp_async_commit();
            }
        }
    }
    const uint32_t tab = stg + (aa * 32 + lane) * 16;
    {
        const uint32_t l7 = lane & 7, l8 = lane >> 3, g = lane >> 2, t = lane & 3;
        const uint32_t t0 = l7 * 128 + ((l8 ^ l7) << 4);
        const uint32_t tq = l7 * 128 + (((l8 >> 1) ^ l7) << 4);
        const uint32_t bq = warp >> 1, tp = warp & 1;
        uint4 v;
        v.x = sb + (aa < 2 ? R_QS : R_KMS) + l7 * 128 + (((4 * (aa & 1) + 2 * kh + (l8 & 1)) ^ l7) << 4);
        v.y = sb + R_QS + tq;
        v.z = sb + (warp == 0 ? R_KMS : R_KX + (warp - 1) * 1024) + t0;
        v.w = mapa_u32(sb + R_SX + (rank * 5 + warp) * 256 + lane * 8, crank ^ 1);
        sts128(tab, v);
        sts128(tab + 2048, make_uint4(sb + lane * 16 + R_MEM + kh * 4096, sb + lane * 16 + R_WV + warp * 8192,
                                      sb + lane * 16 + R_VP + warp * 512, sb + lane * 16 + R_VP + 4096 + (warp ^ 4) * 512));
        const uint32_t src = (l8 >> 1) * 8 + l7;
        const uint32_t L = bq * 8 + 2 * tp + (l8 & 1);
        const uint32_t d0 = (crank + ((t >> 1) | (g & 6))) & 15;
        v.x = sb + R_RS + src * 512 + ((L ^ (src & 7)) << 4);
        v.y = mapa_u32(sb + R_MEM + (crank * 4 + bq) * 128 + (4 * tp + 2 * (t & 1) + (g & 1)) * 16, d0);
        v.z = mapa_u32(sb + ((crank & 2) ? RB_A1 : RB_A), d0);
        v.w = lane;
        sts128(tab + 4096, v);
        const uint64_t wr = (uint64_t)(g_F + ((crank * 2 + ((crank ^ (crank >> 3) ^ sel) & 1)) * 1024 + warp * 128 + cl * 32 + lane));
        sts128(tab + 6144, make_uint4((uint32_t)wr, (uint32_t)(wr >> 32), (uint32_t)((((cl + 1) & 3) - cl) * 128), (uint32_t)((((cl + 2) & 3) - cl) * 128)));
        sts32(tab + 8192, (uint32_t)((((cl + 3) & 3) - cl) * 128));
#pragma unroll
        for (int i = 0; i < NOFF; i++)
            sts128(tab + 10240 + i * 2048, make_uint4(wa[i & 1][i >> 1][0], wa[i & 1][i >> 1][1], wa[i & 1][i >> 1][2], wa[i & 1][i >> 1][3]));
    }
    bar_sync(NB_D, 384);
    uint32_t slot_off = 0;
    const uint32_t slot_inc = warp == 0 ? 2048 : 4096, slot_last = warp == 0 ? 2048 : (R_NST - 1) * 4096;
    const uint32_t sx_bar_rem = (sb + RB_SX) ^ (1u << 24);
    uint4 tb = lds128(tab + 2048);
#pragma unroll 1
    for (int s = 0; s < NSEG; s++) {
        if (s > 0) mbar_wait(sb + RB_A, (s - 1) & 1);
        if (warp == 0) { PROF(0); PROFG(13); }
        uint4 ta;
        const uint32_t km_tog = aa >= 2 ? (s & 1) * 2048 : 0;
        {
            float acc[5][4];
#pragma unroll
            for (int c = 0; c < 5; c++) { acc[c][0] = acc[c][1] = acc[c][2] = acc[c][3] = 0.f; }
            uint32_t b[8][4];
            uint4 av[16];
            static_assert(VK0 == 4, "order below assumes the V/O warps cover slices 0,1");
#define QK4(k2) do { \
                mma16816(acc[0], wa[0][2 * (k2)][0], wa[0][2 * (k2)][1], wa[0][2 * (k2)][2], wa[0][2 * (k2)][3], b[k2][0], b[k2][1]); \
                mma16816(acc[1], wa[1][2 * (k2)][0], wa[1][2 * (k2)][1], wa[1][2 * (k2)][2], wa[1][2 * (k2)][3], b[k2][0], b[k2][1]); \
                mma16816(acc[3], wa[0][2 * (k2) + 1][0], wa[0][2 * (k2) + 1][1], wa[0][2 * (k2) + 1][2], wa[0][2 * (k2) + 1][3], b[k2][2], b[k2][3]); \
                mma16816(acc[4], wa[1][2 * (k2) + 1][0], wa[1][2 * (k2) + 1][1], wa[1][2 * (k2) + 1][2], wa[1][2 * (k2) + 1][3], b[k2][2], b[k2][3]); } while (0)
#define V2(k2) do { \
                mma16816(acc[2], av[2 * (k2)].x, av[2 * (k2)].y, av[2 * (k2)].z, av[2 * (k2)].w, b[k2][0], b[k2][1]); \
                mma16816(acv, av[2 * (k2) + 1].x, av[2 * (k2) + 1].y, av[2 * (k2) + 1].z, av[2 * (k2) + 1].w, b[k2][2], b[k2][3]); } while (0)
#define LB(k2) ldsm4(b[k2][0], b[k2][1], b[k2][2], b[k2][3], tb.x + (k2) * 512)
#define LV(k2) do { av[2 * (k2)] = lds128(tb.y + 2 * (k2) * 512); av[2 * (k2) + 1] = lds128(tb.y + (2 * (k2) + 1) * 512); } while (0)
            float acv[4] = {0.f, 0.f, 0.f, 0.f};
            LB(0); LB(1); LB(4); LB(5);
            QK4(0); QK4(1); LV(4); LV(5); QK4(4); QK4(5);
            if (s > 0) mbar_wait(sb + RB_A1, (s - 1) & 1);
            LB(2); LB(3); LB(6); LB(7); ta = lds128(tab);
            V2(4); V2(5); LV(2); LV(3);
            QK4(2); QK4(3); QK4(6); QK4(7);
            LV(6); LV(7);
#pragma unroll
            for (int i = 0; i < 4; i++) { acc[0][i] += acc[3][i]; acc[1][i] += acc[4][i]; }
            const float g0 = kh ? acc[0][0] : acc[1][0], g1 = kh ? acc[0][1] : acc[1][1], g2 = kh ? acc[0][2] : acc[1][2], g3 = kh ? acc[0][3] : acc[1][3];
            sts128(tb.w, make_uint4(__float_as_uint(g0), __float_as_uint(g1), __float_as_uint(g2), __float_as_uint(g3)));
            const float k0 = kh ? acc[1][0] : acc[0][0], k1 = kh ? acc[1][1] : acc[0][1], k2_ = kh ? acc[1][2] : acc[0][2], k3 = kh ? acc[1][3] : acc[0][3];
            if (warp == 0) PROF(1);
            V2(2); V2(3);
            bar_sync(NB_X + aa, 64);
            const uint4 o = lds128(tb.z + 4096);
            V2(6); V2(7);
            stsm2t(ta.x ^ km_tog, pack2(k0 + __uint_as_float(o.x), k1 + __uint_as_float(o.y)), pack2(k2_ + __uint_as_float(o.z), k3 + __uint_as_float(o.w)));
            sts128(tb.z, make_uint4(__float_as_uint(acc[2][0] + acv[0]), __float_as_uint(acc[2][1] + acv[1]), __float_as_uint(acc[2][2] + acv[2]), __float_as_uint(acc[2][3] + acv[3])));
        }
        const uint32_t kb = ta.z + slot_off;
        if (warp == 0) PROF(14);
        bar_sync(NB_B, 256);
        if (warp < 5) {
            uint32_t q[16], k0, k1, k2, k3, k4, k5, k6, k7;
            float sa[4] = {0.f, 0.f, 0.f, 0.f}, sc[4] = {0.f, 0.f, 0.f, 0.f};
            ldsm4(q[0], q[1], q[2], q[3], ta.y);
            ldsm4(k0, k1, k2, k3, kb);
            ldsm4(q[4], q[5], q[6], q[7], ta.y ^ 32);
            ldsm4(q[8], q[9], q[10], q[11], ta.y ^ 64);
            ldsm4(k4, k5, k6, k7, kb ^ 64);
            ldsm4(q[12], q[13], q[14], q[15], ta.y ^ 96);
            mma16816(sa, q[0], q[1], q[2], q[3], k0, k1);
            bar_arrive(NB_Y, 288);
            mma16816(sc, q[4], q[5], q[6], q[7], k2, k3);
            mma16816(sa, q[8], q[9], q[10], q[11], k4, k5);
            mma16816(sc, q[12], q[13], q[14], q[15], k6, k7);
            const float scl = 0.08838834764831845f * 1.4426950408889634f;
            const float r0 = (sa[0] + sc[0]) * scl, r1 = (sa[1] + sc[1]) * scl;
            if (s != NSEG - 1) {
                st_async_v2(ta.w, r0, r1, sx_bar_rem);
                st_async_v2(ta.w ^ (1u << 24), r0, r1, sx_bar_rem ^ (1u << 24));
            }
            if (warp == 0) PROF(2);
        } else if (s > 0 && warp == 7 && lane == 0) {
            mbar_expect_tx(sb + RB_A, 4096);
            mbar_expect_tx(sb + RB_A1, 4096);
        } else if (s > 0 && (s & 3) == 0 && warp == 6) {
            bar_sync(NB_K, 160);
            if (lane == 0) red_release(&g_flags[F_MEM + (s >> 2) - 1], 1);
            __syncwarp();
        }
        if (s == NSEG - 1) {
            const uint4 td = lds128(tab + 6144);
            stg_relaxed32((uint32_t*)(((uint64_t)td.y << 32) | (td.x ^ 0x21000)), 0u);
            break;
        }
        slot_off = slot_off == slot_last ? 0 : slot_off + slot_inc;
        const uint4 tc = lds128(tab + 4096), td = lds128(tab + 6144);
        const uint32_t te = lds32(tab + 8192);
        uint32_t* wr = (uint32_t*)(((uint64_t)td.y << 32) | (td.x ^ ((s & 1) * 0x21000)));
        const uint32_t* r1p = (const uint32_t*)((const char*)wr + (int)td.z);
        const uint32_t* r2p = (const uint32_t*)((const char*)wr + (int)td.w);
        const uint32_t* r3p = (const uint32_t*)((const char*)wr + (int)te);
        const uint32_t tag = ((s >> 1) + 1) & 1;
        mbar_wait(sb + RB_E, s & 1);
        if (warp == 0) PROF(7);
        {
            uint32_t a0, a1, a2, a3, a4, a5, a6, a7;
            ldsm4t(a0, a1, a2, a3, tc.x);
            ldsm4t(a4, a5, a6, a7, tc.x ^ 64);
            const uint32_t one = 0x3F803F80u;
            float d0_[4] = {0.f, 0.f, 0.f, 0.f}, d1_[4] = {0.f, 0.f, 0.f, 0.f};
            mma16816(d0_, a0, a1, a2, a3, one, one);
            mma16816(d1_, a4, a5, a6, a7, one, one);
            const bool t1 = tc.w & 1, t2 = tc.w & 2;
            const float x = t2 ? (t1 ? d1_[2] : d1_[0]) : (t1 ? d0_[2] : d0_[0]);
            const uint32_t own = (__float_as_uint(x) & ~1u) | tag;
            stg_relaxed32(wr, own);
            const uint32_t tq = clk32();
            if (warp == 0) PROF(8);
            PROFG(16 + warp);
            while ((int)(clk32() - tq) < POLL_GAP) {}
            uint32_t f1 = ldg_relaxed32(r1p), f2 = ldg_relaxed32(r2p), f3 = ldg_relaxed32(r3p);
#pragma unroll
            for (int i = 0; i < NOFF; i++) {
                const uint4 f0 = lds128(tab + 10240 + i * 2048);
                wa[i & 1][i >> 1][0] = f0.x; wa[i & 1][i >> 1][1] = f0.y; wa[i & 1][i >> 1][2] = f0.z; wa[i & 1][i >> 1][3] = f0.w;
            }
            tb = lds128(tab + 2048);
            int gg = 0;
#pragma unroll 1
            while (!__all_sync(~0u, (((f1 ^ tag) | (f2 ^ tag) | (f3 ^ tag)) & 1) == 0)) {
                f1 = ldg_relaxed32(r1p); f2 = ldg_relaxed32(r2p); f3 = ldg_relaxed32(r3p);
                if (++gg > 16 * SPIN_LIMIT) { TIMEOUT(3, s); break; }
            }
            if (warp == 0) PROF(9);
            const float v = (__uint_as_float(own) + __uint_as_float(f2)) + (__uint_as_float(f1) + __uint_as_float(f3));
            const bool b8 = tc.w & 8, b16 = tc.w & 16;
            const float recv = __shfl_xor_sync(~0u, v, 8);
            const uint32_t word = b8 ? pack2(recv, v) : pack2(v, recv);
            const uint32_t oth = __shfl_xor_sync(~0u, word, 16);
            const uint32_t wl = b16 ? oth : word, wh = b16 ? word : oth;
            const uint32_t p0 = __shfl_xor_sync(~0u, wl, 2), p1 = __shfl_xor_sync(~0u, wh, 2);
            const uint4 item = t2 ? make_uint4(p0, p1, wl, wh) : make_uint4(wl, wh, p0, p1);
            st_async_v4(tc.y, item, tc.z);
            st_async_v4(tc.y ^ (8u << 24), item, tc.z ^ (8u << 24));
            if (tc.w == 0 && warp == 7) mbar_expect_tx(sb + RB_E, 8192);
            if (warp == 0) PROF(10);
            PROF(40 + warp);
        }
        bar_sync(NB_D, 384);
    }
}

__device__ __forceinline__ void rec_load_kv(uint32_t sb, int col0, int s, uint32_t slot_off, int t128) {
    const int row = t128 >> 2, c2 = (t128 & 3) * 2;
    const bf16* src = g_kv + ((size_t)(s * 32 + row) * (2 * HD_) + col0 + c2 * 8);
    const uint32_t d0 = sb + R_KX + slot_off + row * 128 + ((c2 ^ (row & 7)) << 4);
    cp_async16(d0, src);
    cp_async16(d0 ^ 16, src + 8);
    cp_async16(d0 + (R_VX - R_KX), src + HD_);
    cp_async16((d0 ^ 16) + (R_VX - R_KX), src + HD_ + 8);
}

__device__ __forceinline__ void rec_store_kvm(uint32_t sb, int col0, int s, int w, int lane) {
    const int tok = (w & 1) * 4 + (lane >> 3);
    const uint4 v = lds128(sb + R_KMS + (s & 1) * 2048 + (w >> 1) * 1024 + tok * 128 + (((lane & 7) ^ tok) << 4));
    *(uint4*)(g_kvm + ((s * 8 + tok) * (2 * HD_) + (w >> 1) * HD_ + col0 + (lane & 7) * 8)) = v;
}

__device__ __forceinline__ void rec_vo(const RecParams& p, const uint32_t sb, const int cta, const int warp, int lane) {
    const int w = warp - 8, crank = cta & 15;
    const int col0 = cta * 64;
    uint32_t wo[8][4][4];
    {
        const int t128 = w * 32 + lane;
        const bf16* Wo = p.wo + (size_t)col0 * D_;
        const uint32_t stg = sb + R_STG + 2 * 32768;
#pragma unroll
        for (int half = 0; half < 2; half++) {
#pragma unroll 4
            for (int i = t128; i < 2048; i += 128) {
                const int e = i >> 6, ch = i & 63;
                cp_async16(stg + e * 1024 + ((ch ^ (e & 7)) << 4), Wo + (size_t)(half * 32 + e) * D_ + ch * 8);
            }
            cp_async_commit();
            cp_async_wait<0>();
            bar_sync(NB_W0 + 2, 128);
#pragma unroll
            for (int j = 0; j < 8; j++)
#pragma unroll
                for (int kk = 0; kk < 2; kk++) {
                    const int e = kk * 16 + (lane >> 4) * 8 + (lane & 7);
                    const int ch = (w * 8 + j) * 2 + ((lane >> 3) & 1);
                    ldsm4t(wo[j][half * 2 + kk][0], wo[j][half * 2 + kk][1], wo[j][half * 2 + kk][2], wo[j][half * 2 + kk][3],
                           stg + e * 1024 + ((ch ^ (e & 7)) << 4));
                }
            bar_sync(NB_W0 + 2, 128);
        }
        if (lane == 0) wait_flag(F_KV + 0, 64);
        __syncwarp();
        rec_load_kv(sb, col0, 0, 0, t128); cp_async_commit();
        rec_load_kv(sb, col0, 1, 4096, t128); cp_async_commit();
        cp_async_wait<1>();
    }
    const uint32_t tab = sb + R_STG + 2 * 32768 + (w * 32 + lane) * 16;
    {
        const uint32_t l7 = lane & 7, l8 = lane >> 3, g = lane >> 2;
        uint4 v;
        v.x = sb + R_VX + ((l8 & 1) * 8 + l7) * 128 + (((2 * w + (l8 >> 1)) ^ l7) << 4);
        v.y = sb + R_OS + g * 128 + (((2 * w) ^ g) << 4) + (lane & 3) * 4;
        v.z = sb + R_VMS + l7 * 128 + (((2 * w + (l8 & 1)) ^ l7) << 4);
        v.w = sb + R_OS + l7 * 128 + ((l8 ^ l7) << 4);
        sts128(tab, v);
        v.x = mapa_u32(sb + R_RS + crank * 512 + ((lane ^ (crank & 7)) << 4), w * 4);
        v.y = mapa_u32(sb + RB_E, w * 4);
        v.z = sb + R_VP + w * 512 + lane * 16;
        v.w = sb + R_SX + lane * 8;
        sts128(tab + 2048, v);
#pragma unroll
        for (int i = 0; i < 8; i++) sts128(tab + 4096 + i * 2048, make_uint4(wo[i][0][0], wo[i][0][1], wo[i][0][2], wo[i][0][3]));
        const int tok = (w & 1) * 4 + (lane >> 3), row = (w * 32 + lane) >> 2, c2 = (lane & 3) * 2;
        const uint64_t kd = (uint64_t)(g_kvm + (tok * (2 * HD_) + (w >> 1) * HD_ + col0 + (lane & 7) * 8));
        const uint64_t ks = (uint64_t)(g_kv + ((size_t)row * (2 * HD_) + col0 + c2 * 8));
        sts128(tab + 20480, make_uint4((uint32_t)kd, (uint32_t)(kd >> 32), (uint32_t)ks, (uint32_t)(ks >> 32)));
        sts128(tab + 22528, make_uint4(sb + R_KMS + (w >> 1) * 1024 + tok * 128 + (((lane & 7) ^ tok) << 4),
                                       sb + R_KX + row * 128 + ((c2 ^ (row & 7)) << 4), lane, 0));
    }
    bar_sync(NB_D, 384);
    const uint32_t lane16 = lds32(tab + 2048 + 8) - R_VP - w * 512;
    uint4 av[2 * VK0];
#pragma unroll
    for (int i = 0; i < 2 * VK0; i++) av[i] = lds128(lane16 + R_WV + (i / VK0) * 32768 + (w * 16 + i % VK0) * 512);
    uint32_t slot_off = 0;
#pragma unroll 1
    for (int s = 0; s < NSEG; s++) {
        if (s > 0) {
            mbar_wait(sb + RB_A, (s - 1) & 1);
            const uint4 tp = lds128(tab + 20480), tq = lds128(tab + 22528);
            const uint4 kvm = lds128(tq.x + ((s - 1) & 1) * 2048);
            *(uint4*)((((uint64_t)tp.y << 32) | tp.x) + (uint64_t)(s - 1) * (8 * 2 * HD_ * 2)) = kvm;
            if ((s & 3) == 0) bar_arrive(NB_K, 160);
            if (s + 1 < NSEG - 1) {
                if (((s + 1) & 3) == 0) { if (tq.z == 0) wait_flag(F_KV + ((s + 1) >> 2), 64); __syncwarp(); }
                const char* src = (const char*)((((uint64_t)tp.w << 32) | tp.z) + (uint64_t)(s + 1) * (32 * 2 * HD_ * 2));
                const uint32_t d0 = tq.y + (slot_off == (R_NST - 1) * 4096 ? 0 : slot_off + 4096);
                cp_async16(d0, src);
                cp_async16(d0 ^ 16, src + 16);
                cp_async16(d0 + (R_VX - R_KX), src + HD_ * 2);
                cp_async16((d0 ^ 16) + (R_VX - R_KX), src + HD_ * 2 + 16);
            }
            cp_async_commit();
        }
        bar_sync(NB_Y, 288);
        uint32_t vb0, vb1;
        {
            float va[4] = {0.f, 0.f, 0.f, 0.f}, vc[4] = {0.f, 0.f, 0.f, 0.f};
            uint32_t bb[VK0][4];
#pragma unroll
            for (int k2 = 0; k2 < VK0; k2++) ldsm4(bb[k2][0], bb[k2][1], bb[k2][2], bb[k2][3], lane16 + R_MEM + (k2 / (VK0 / 2)) * 4096 + (k2 % (VK0 / 2)) * 512);
#pragma unroll
            for (int k2 = 0; k2 < VK0; k2++) {
                mma16816(va, av[2 * k2].x, av[2 * k2].y, av[2 * k2].z, av[2 * k2].w, bb[k2][0], bb[k2][1]);
                mma16816(vc, av[2 * k2 + 1].x, av[2 * k2 + 1].y, av[2 * k2 + 1].z, av[2 * k2 + 1].w, bb[k2][2], bb[k2][3]);
            }
            const uint4 a = lds128(lane16 + R_VP + w * 512), b = lds128(lane16 + R_VP + 2048 + w * 512);
            vb0 = pack2((va[0] + vc[0]) + (__uint_as_float(a.x) + __uint_as_float(b.x)), (va[1] + vc[1]) + (__uint_as_float(a.y) + __uint_as_float(b.y)));
            vb1 = pack2((va[2] + vc[2]) + (__uint_as_float(a.z) + __uint_as_float(b.z)), (va[3] + vc[3]) + (__uint_as_float(a.w) + __uint_as_float(b.w)));
        }
        const uint4 ta = lds128(tab), tb = lds128(tab + 2048);
        uint32_t vx[8];
        ldsm4t(vx[0], vx[1], vx[2], vx[3], ta.x + slot_off);
        ldsm4t(vx[4], vx[5], vx[6], vx[7], ta.x + slot_off + 2048);
#pragma unroll
        for (int i = 0; i < 4; i++) {
            const uint4 f0 = lds128(tab + 4096 + i * 2048);
            wo[i][0][0] = f0.x; wo[i][0][1] = f0.y; wo[i][0][2] = f0.z; wo[i][0][3] = f0.w;
        }
        if (w == 0) PROF(11);
        uint32_t pf[5];
        float oa[2][4] = {{0.f, 0.f, 0.f, 0.f}, {0.f, 0.f, 0.f, 0.f}}, ob_[2][4] = {{0.f, 0.f, 0.f, 0.f}, {0.f, 0.f, 0.f, 0.f}};
        float sm0[4] = {0.f, 0.f, 0.f, 0.f}, sm1[4] = {0.f, 0.f, 0.f, 0.f};
        if (s != NSEG - 1) {
            mbar_wait(sb + RB_SX, s & 1);
            if (w == 0) PROF(4);
            float sv[10];
#pragma unroll
            for (int n = 0; n < 5; n++) {
                const float2 a = lds64f(tb.w + n * 256), b = lds64f(tb.w + (5 + n) * 256);
                sv[2 * n] = a.x + b.x; sv[2 * n + 1] = a.y + b.y;
            }
            float mx = fmaxf(fmaxf(fmaxf(sv[0], sv[1]), fmaxf(sv[2], sv[3])), fmaxf(fmaxf(sv[4], sv[5]), fmaxf(sv[6], sv[7])));
            mx = fmaxf(mx, fmaxf(sv[8], sv[9]));
            mx = fmaxf(mx, __shfl_xor_sync(~0u, mx, 1));
            mx = fmaxf(mx, __shfl_xor_sync(~0u, mx, 2));
#pragma unroll
            for (int n = 1; n < 5; n++) pf[n] = pack2(ex2(sv[2 * n] - mx), ex2(sv[2 * n + 1] - mx));
            pf[0] = pack2(ex2(sv[0] - mx), ex2(sv[1] - mx));
            if (w == 0) PROF(12);
            const uint32_t one = 0x3F803F80u;
            mma16816h(sm0, pf[1], pf[2], one, one);
            mma16816h(oa[0], pf[1], pf[2], vx[0], vx[1]);
            mma16816h(oa[1], pf[1], pf[2], vx[2], vx[3]);
            mma16816h(sm1, pf[3], pf[4], one, one);
            mma16816h(ob_[0], pf[3], pf[4], vx[4], vx[5]);
            mma16816h(ob_[1], pf[3], pf[4], vx[6], vx[7]);
            mma1688h(sm0, pf[0], one);
            mma1688h(oa[0], pf[0], vb0);
            mma1688h(oa[1], pf[0], vb1);
            float inv;
            asm("rcp.approx.ftz.f32 %0, %1;" : "=f"(inv) : "f"(sm0[0] + sm1[0]));
            oa[0][0] += ob_[0][0]; oa[0][1] += ob_[0][1]; oa[1][0] += ob_[1][0]; oa[1][1] += ob_[1][1];
            sts32(ta.y, pack2(oa[0][0] * inv, oa[0][1] * inv));
            sts32(ta.y ^ 16, pack2(oa[1][0] * inv, oa[1][1] * inv));
            const uint32_t oa2 = ta.w ^ 64;
            bar_sync(NB_C, 128);
            if (w == 0) PROF(5);
            uint32_t ob[8];
            ldsm4(ob[0], ob[1], ob[2], ob[3], ta.w);
            ldsm4(ob[4], ob[5], ob[6], ob[7], oa2);
#pragma unroll
            for (int i = 4; i < 8; i++) {
                const uint4 f0 = lds128(tab + 4096 + i * 2048);
                wo[i][0][0] = f0.x; wo[i][0][1] = f0.y; wo[i][0][2] = f0.z; wo[i][0][3] = f0.w;
            }
#pragma unroll
            for (int jj = 0; jj < 2; jj++) {
                if (jj == 1 && tb.w == 0) break;
                float acc[4][4];
#pragma unroll
                for (int c = 0; c < 4; c++) { acc[c][0] = acc[c][1] = acc[c][2] = acc[c][3] = 0.f; }
#pragma unroll
                for (int ks = 0; ks < 4; ks++)
#pragma unroll
                    for (int c = 0; c < 4; c++)
                        mma16816(acc[c], wo[jj * 4 + c][ks][0], wo[jj * 4 + c][ks][1], wo[jj * 4 + c][ks][2], wo[jj * 4 + c][ks][3], ob[2 * ks], ob[2 * ks + 1]);
#pragma unroll
                for (int pr = 0; pr < 2; pr++) {
                    uint4 v;
                    v.x = pack2(acc[2 * pr][0], acc[2 * pr][1]);
                    v.y = pack2(acc[2 * pr][2], acc[2 * pr][3]);
                    v.z = pack2(acc[2 * pr + 1][0], acc[2 * pr + 1][1]);
                    v.w = pack2(acc[2 * pr + 1][2], acc[2 * pr + 1][3]);
                    st_async_v4(tb.x + ((jj * 2 + pr) << 24), v, tb.y + ((jj * 2 + pr) << 24));
                }
            }
            if (w == 0) PROF(6);
        }
        stsm2t(ta.z + (s & 1) * 2048, vb0, vb1);
        cp_async_wait<0>();
        bar_sync(NB_C, 128);
        if (w == 0 && lane == 0 && s != NSEG - 1) mbar_expect_tx(sb + RB_SX, 2560);
        if (s != NSEG - 1) bar_arrive(NB_D, 384);
#pragma unroll
        for (int i = 0; i < 2 * VK0; i++) av[i] = lds128(lane16 + R_WV + (i / VK0) * 32768 + (w * 16 + i % VK0) * 512);
        slot_off = slot_off == (R_NST - 1) * 4096 ? 0 : slot_off + 4096;
    }
    rec_store_kvm(sb, col0, NSEG - 1, w, lane);
    bar_sync(NB_C, 128);
    if (w == 0 && lane == 0) red_release(&g_flags[F_MEM + NRB - 1], 1);
}

__global__ void __launch_bounds__(384, 1) k_rec(const RecParams p) {
    extern __shared__ __align__(1024) unsigned char smem_raw[];
    const uint32_t sb = __shfl_sync(~0u, smem_u32(smem_raw), 0);
    const int warp = __shfl_sync(~0u, threadIdx.x >> 5, 0);
    int lane; asm volatile("mov.u32 %0, %%laneid;" : "=r"(lane));
    const int crank = blockIdx.x & 15, slot = blockIdx.x >> 4;
    asm volatile("griddepcontrol.launch_dependents;");
    if (crank == 0 && warp == 1 && lane < 4) {
        const unsigned int* q = lane < 2 ? &g_F[65536 + lane * 1024 + slot * 64] : &g_flags[F_SIDE + (lane - 2) * 32];
        asm volatile("prefetch.global.L2 [%0];" :: "l"(q));
    }
    if (threadIdx.x == 0) {
        mbar_init(sb + RB_SX, 1); mbar_init(sb + RB_E, 1); mbar_init(sb + RB_A, 1); mbar_init(sb + RB_A1, 1); mbar_init(sb + RB_ROLE, 1);
        asm volatile("fence.mbarrier_init.release.cluster;" ::: "memory");
        mbar_expect_tx(sb + RB_SX, 2560);
        mbar_expect_tx(sb + RB_E, 8192);
        mbar_expect_tx(sb + RB_A, 4096);
        mbar_expect_tx(sb + RB_A1, 4096);
        mbar_expect_tx(sb + RB_ROLE, 4);
    }
    asm volatile("barrier.cluster.arrive.relaxed.aligned;\nbarrier.cluster.wait.aligned;" ::: "memory");
    if (warp == 2 && lane < 16) {
        __nanosleep(PF_NS);
        const int i = lane * gridDim.x + blockIdx.x;
        if (i < 1024) {
            const bf16* W = (i >> 8) == 0 ? p.wk : ((i >> 8) == 1 ? p.wv : ((i >> 8) == 2 ? p.wq : p.wo));
            asm volatile("cp.async.bulk.prefetch.L2.global [%0], %1;" :: "l"(W + (size_t)(i & 255) * 8192), "r"(16384) : "memory");
        }
    }
    unsigned role = 0;
    if (crank == 0 && threadIdx.x == 0 && !p.only_pre) {
        unsigned x = 0;
        int tm[2] = {0x7fffffff, 0x7fffffff};
#pragma unroll 1
        for (int i = 0; i < 6; i++) {
            const uint32_t t0 = clk32();
            x = atomicAdd(&g_F[65536 + (i & 1) * 1024 + slot * 64 + (x >> 31)], 0u) & 0x7fffffffu;
            if (x == 0x7654321u) sts32(sb + R_BAR + 56, x);
            const int dt = (int)(clk32() - t0);
            if (i >= 2) { if (i & 1) tm[1] = min(tm[1], dt); else tm[0] = min(tm[0], dt); }
        }
        const int side = tm[1] > tm[0];
        const unsigned old = atomicAdd(&g_flags[F_SIDE + side * 32], 1u);
        unsigned c0, c1; int gd = 0;
#pragma unroll 1
        do { c0 = ldg_relaxed32(&g_flags[F_SIDE]); c1 = ldg_relaxed32(&g_flags[F_SIDE + 32]); } while ((int)(c0 + c1) < p.ncl && ++gd < 64 * SPIN_LIMIT);
        const int big = c1 > c0;
        role = side == big ? old : (big ? c1 : c0) + old;
        role |= (big ^ 1) << 8;
    }
    __syncwarp();
    if (crank == 0 && warp == 0 && !p.only_pre) {
        role = __shfl_sync(~0u, role, 0);
        if (lane < 16)
            asm volatile("st.async.weak.shared::cluster.mbarrier::complete_tx::bytes.u32 [%0], %1, [%2];"
                         :: "r"(mapa_u32(sb + R_BAR + 48, lane)), "r"(role), "r"(mapa_u32(sb + RB_ROLE, lane)) : "memory");
    }
    if (warp >= 4) {
        const int w8 = warp - 4, nblk = gridDim.x;
        const int cq = lane & 3, rg = w8 * 8 + (lane >> 2);
        const uint32_t red = sb + R_VP;
        const int row0 = blockIdx.x * 8 + w8;
        const uint4* xr = (const uint4*)(p.x + (size_t)row0 * D_);
        uint4 xa = __ldg(xr + lane), xb = __ldg(xr + 32 + lane);
#pragma unroll 1
        for (int sl = blockIdx.x; sl < 96; sl += nblk) {
            uint4 wv[8];
#pragma unroll
            for (int i = 0; i < 8; i++) wv[i] = __ldg((const uint4*)(p.w_mod + (size_t)(rg * 8 + i) * (6 * D_) + sl * 32 + cq * 8));
            const uint32_t cw = __ldg((const uint32_t*)(p.c + rg * 8) + cq);
            const float cl = bflo(cw), ch = bfhi(cw);
            const uint32_t sw = pack2(__fdividef(cl, 1.f + __expf(-cl)), __fdividef(ch, 1.f + __expf(-ch)));
            float a[8];
#pragma unroll
            for (int i = 0; i < 8; i++) a[i] = 0.f;
#pragma unroll
            for (int i = 0; i < 8; i++) {
                const uint32_t sv = __shfl_sync(~0u, sw, (lane & 28) + (i >> 1));
                const float cv = (i & 1) ? bfhi(sv) : bflo(sv);
                a[0] = fmaf(cv, bflo(wv[i].x), a[0]); a[1] = fmaf(cv, bfhi(wv[i].x), a[1]); a[2] = fmaf(cv, bflo(wv[i].y), a[2]); a[3] = fmaf(cv, bfhi(wv[i].y), a[3]);
                a[4] = fmaf(cv, bflo(wv[i].z), a[4]); a[5] = fmaf(cv, bfhi(wv[i].z), a[5]); a[6] = fmaf(cv, bflo(wv[i].w), a[6]); a[7] = fmaf(cv, bfhi(wv[i].w), a[7]);
            }
#pragma unroll
            for (int i = 0; i < 8; i++) { a[i] += __shfl_xor_sync(~0u, a[i], 4); a[i] += __shfl_xor_sync(~0u, a[i], 8); a[i] += __shfl_xor_sync(~0u, a[i], 16); }
            if (lane < 4) {
                sts128(red + w8 * 128 + lane * 32, make_uint4(__float_as_uint(a[0]), __float_as_uint(a[1]), __float_as_uint(a[2]), __float_as_uint(a[3])));
                sts128(red + w8 * 128 + lane * 32 + 16, make_uint4(__float_as_uint(a[4]), __float_as_uint(a[5]), __float_as_uint(a[6]), __float_as_uint(a[7])));
            }
            bar_sync(NB_B, 256);
            if (w8 == 0) {
                float v = 0.f;
#pragma unroll
                for (int i = 0; i < 8; i++) v += lds32f(red + i * 128 + lane * 4);
                g_mod[sl * 32 + lane] = __float2bfloat16_rn(v);
                __syncwarp();
                if (lane == 0) red_release(&g_flags[F_MOD + (sl >= 32)], 1);
            }
            bar_sync(NB_B, 256);
        }
        uint32_t c1[8], sm[8];
        int row = row0;
#pragma unroll 1
        while (true) {
            const uint32_t v[8] = {xa.x, xa.y, xa.z, xa.w, xb.x, xb.y, xb.z, xb.w};
            uint32_t mu2, r[8]; float rden;
            ln_stats(v, mu2, rden);
            if (row == row0) {
                if (lane == 0) wait_flag(F_MOD, 32);
                __syncwarp();
                load_mod8(g_mod + D_, lane, c1);
                load_mod8(g_mod, lane, sm);
#pragma unroll
                for (int i = 0; i < 8; i++) c1[i] = hadd2(c1[i], 0x3F803F80u);
            } else if (row + 512 < S_) {
                xr = (const uint4*)(p.x + (size_t)(row + 512) * D_); xa = __ldg(xr + lane); xb = __ldg(xr + 32 + lane);
            }
            ln_apply(v, mu2, rden, c1, sm, r);
            uint4* hr = (uint4*)(g_h + (size_t)row * D_);
            hr[lane] = make_uint4(r[0], r[1], r[2], r[3]); hr[32 + lane] = make_uint4(r[4], r[5], r[6], r[7]);
            bar_sync(NB_B, 256);
            if (w8 == (row >> 7 & 7) && lane == 0) red_release(&g_flags[F_H + (row >> 7)], 1);
            __syncwarp();
            if (row == row0) {
                if (!p.only_pre) mbar_wait(sb + RB_ROLE, 0);
                const int cl = p.only_pre ? slot : (int)(lds32(sb + R_BAR + 48) & 255);
                row = cl < 4 ? (nblk + cl * 16 + crank) * 8 + w8 : S_;
                if (row < S_) { xr = (const uint4*)(p.x + (size_t)row * D_); xa = __ldg(xr + lane); xb = __ldg(xr + 32 + lane); }
            } else {
                row += 512;
            }
            if (row >= S_) break;
        }
    }
    if (p.only_pre) return;
    mbar_wait(sb + RB_ROLE, 0);
    const int rolew = __shfl_sync(~0u, lds32(sb + R_BAR + 48), 0);
    const int cl = rolew & 255;
    if (cl >= 4) return;
    const int cta = cl * 16 + crank;
    if (warp < 8) rec_qk(p, sb, cta, warp, lane, rolew >> 8);
    else rec_vo(p, sb, cta, warp, lane);
}

enum { J_KV = 0, J_QA = 1, J_O = 2, J_LN = 3, J_UP = 4, J_DN = 5, J_LN1 = 6, J_MOD = 7, J_UP2 = 8, J_END = 9 };
constexpr int NJ_O = 2 * OSPLIT, NJ_O2 = 2 * OSPLIT2, NJ_LN = 8, NJ_LN2 = 16, NJ_UP = 14, NJ_UP2 = 28, NJ_DN = 8, NJ_LN1 = 8;
constexpr uint64_t pk8(int a, int b, int c, int d, int e, int f, int g, int h) {
    return (uint64_t)a | ((uint64_t)b << 8) | ((uint64_t)c << 16) | ((uint64_t)d << 24) | ((uint64_t)e << 32) | ((uint64_t)f << 40) | ((uint64_t)g << 48) | ((uint64_t)h << 56);
}
constexpr uint64_t NJ_C = pk8(32, 16, NJ_O, NJ_LN, NJ_UP, NJ_DN, 0, 0), NJ_F = pk8(32, 16, NJ_O2, NJ_LN2, NJ_UP2, NJ_DN, 0, 0);
constexpr uint64_t TG_C = pk8(2 * NJ_LN1, 64, 32, 2 * NJ_O, 2 * NJ_LN, 2 * NJ_UP, 32, 0), TG_F = pk8(2 * NJ_LN1, 64, 32, 2 * NJ_O2, 2 * NJ_LN2, 2 * NJ_UP2, 32, 0);
constexpr uint64_t NJ_L = pk8(32, 32, 2 * OSPLIT3, NJ_LN2, NJ_UP2, NJ_DN, 0, 0), TG_L = pk8(2 * NJ_LN1, 64, 64, 4 * OSPLIT3, 2 * NJ_LN2, 2 * NJ_UP2, 32, 0);
__device__ __forceinline__ uint64_t nj_tab(int rb) { return rb < FINE_RB ? NJ_C : (rb < NRB - 1 ? NJ_F : NJ_L); }
__device__ __forceinline__ uint64_t tg_tab(int rb) { return rb < FINE_RB ? TG_C : (rb < NRB - 1 ? TG_F : TG_L); }
__device__ __forceinline__ int o_nk(int rb) { return rb < FINE_RB ? 64 / OSPLIT : (rb < NRB - 1 ? 64 / OSPLIT2 : 64 / OSPLIT3); }
constexpr uint64_t PRIO = pk8(4, 10, 9, 8, 7, 6, 3, 0);
__device__ __forceinline__ int pick_job(int lane, int qmask, int& idx) {
    const int rb = lane & 15, half = lane >> 4;
    const uint64_t nj = nj_tab(rb) >> (8 * half);
    const uint64_t tg = tg_tab(rb) >> (8 * half);
    const unsigned* cp = &g_flags[F_CLAIM + half * 32 + rb];
    const unsigned* dp = &g_flags[half * 32 + rb];
    int gd = 0;
#pragma unroll 1
    while (true) {
        const unsigned c0 = ldg_relaxed32(cp), c1 = ldg_relaxed32(cp + 64), c2 = ldg_relaxed32(cp + 128);
        const unsigned d0 = ldg_relaxed32(dp - (half && rb ? 1 : 0)), d1 = ldg_relaxed32(dp + 64), d2 = ldg_relaxed32(dp + 128);
        const unsigned cl[3] = {c0, c1, c2}, dv[3] = {d0, d1, d2};
        unsigned key = 0xffffu, key2 = 0xffffu;
        bool pre = false;
#pragma unroll
        for (int i = 0; i < 3; i++) {
            const int q = half + 2 * i;
            const bool have = ((qmask >> q) & 1) && cl[i] < (unsigned)((nj >> (16 * i)) & 255);
            bool ready = have && dv[i] >= (unsigned)((tg >> (16 * i)) & 255);
            unsigned pr = (unsigned)((PRIO >> (8 * q)) & 255);
            if (i == 0 && rb <= 1 - half) ready = have;
            if (i == 0 && half && rb >= FINE_RB) pr = 5;
            if (ready) key = min(key, (pr << 8) | (rb << 4) | q);
            if (have) key2 = min(key2, rb >= FINE_RB ? (0x100u | (q << 4) | rb) : (i == 0 ? 0u : 0x1000u));
            pre |= have && i == 0 && !half;
        }
        const bool anypre = __any_sync(~0u, pre);
        if (anypre && (key & 15) == J_QA) key = 0xffffu;
        key = __reduce_min_sync(~0u, key);
        key2 = __reduce_min_sync(~0u, key2);
        if (key2 == 0xffffu) return J_END;
        int pq, prb;
        if (key != 0xffffu) { pq = key & 15; prb = (key >> 4) & 15; }
        else if (key2 >= 0x120u && key2 < 0x1000u) { pq = (key2 >> 4) & 15; prb = key2 & 15; }
        else {
            __nanosleep(IDLE_NS);
            if (++gd > 16 * SPIN_LIMIT) { TIMEOUT(5, 0); return J_END; }
            continue;
        }
        int c = 0;
        if (lane == 0) c = (int)atomicAdd(&g_flags[F_CLAIM + pq * 32 + prb], 1u);
        c = __shfl_sync(~0u, c, 0);
        if (c < (int)((nj_tab(prb) >> (8 * pq)) & 255)) {
            idx = pq * 512 + prb * 32 + c;
            int acq = 0;
            if (pq != J_QA && pq < J_LN1) {
                if (lane == 0 && ld_acquire(&g_flags[pq * 32 + prb]) >= (unsigned)((tg_tab(prb) >> (8 * pq)) & 255)) {
                    asm volatile("fence.proxy.async.global;" ::: "memory");
                    acq = 1 << 24;
                }
            }
            return (pq == J_UP && prb >= FINE_RB ? J_UP2 : pq) | (prb << 8) | (c << 16) | acq;
        }
    }
}
__device__ __forceinline__ int op_row(int rb, int split) {
    return rb < FINE_RB ? split * S_ + rb * 128
                        : (rb < NRB - 1 ? OSPLIT * S_ + (split * (NRB - FINE_RB) + rb - FINE_RB) * 128 : OSPLIT * S_ + (OSPLIT2 * (NRB - FINE_RB) + split) * 128);
}

struct Pipe { uint32_t stage, phase; };
__device__ __forceinline__ void pipe_next(Pipe& p) { if (++p.stage == W_NST) { p.stage = 0; p.phase ^= 1; } }

__device__ __forceinline__ void scheduler(const Params& p, uint32_t sb, int lane) {
    const uint32_t bars = sb + SM_BAR;
    uint32_t ph = 0;
#pragma unroll 1
    while (true) {
        mbar_wait(bars + B_REQ, ph);
        int j = 4095;
        const int jd = pick_job(lane, p.qmask, j);
        if (lane == 0) { sts32(bars + B_NEXT, (uint32_t)jd); sts32(bars + B_NEXT + 4, (uint32_t)j); mbar_arrive(bars + B_RSP); }
        ph ^= 1;
        if (jd == J_END) break;
        __syncwarp();
    }
}

__device__ __forceinline__ void producer(const Params& p, uint32_t sb) {
    Pipe pp{0, 1};
    const uint32_t bars = sb + SM_BAR;
    uint32_t seq = 0, h_seen = 0;
    mbar_arrive(bars + B_REQ);
#pragma unroll 1
    while (true) {
        mbar_wait(bars + B_RSP, seq & 1);
        const int jd = (int)lds32(bars + B_NEXT), j = (int)lds32(bars + B_NEXT + 4);
        int left = (jd & 255) == J_DN ? 15 : ((jd & 255) == J_QA ? (((jd >> 8) & 255) == NRB - 1 ? 10 : 12) : ((jd & 255) == J_O ? o_nk((jd >> 8) & 255) : ((jd & 255) == J_LN || (jd & 255) == J_LN1 || (jd & 255) == J_MOD ? 1 : 8)));
        left = max(left - PICK_AHEAD, 1);
        TR(j, 1);
        const int type = jd & 255, rb = (jd >> 8) & 255, cb = (jd >> 16) & 255;
        const bool fine = rb >= FINE_RB, acquired = (jd >> 24) & 1;
        bool first = true;
        auto begin_stage = [&](uint32_t bytes) -> uint32_t {
            mbar_wait(bars + B_EMPTY + pp.stage * 8, pp.phase);
            if (first) { sts32(bars + B_RING + (seq & 7) * 4, (uint32_t)jd); sts32(bars + B_RING + 32 + (seq & 7) * 4, (uint32_t)j); first = false; }
            const uint32_t fb = bars + B_FULL + pp.stage * 8;
            if (bytes) mbar_expect_tx(fb, bytes); else mbar_arrive(fb);
            if (--left == 0 && type != J_END) mbar_arrive(bars + B_REQ);
            return fb;
        };
        if (type == J_END || type == J_LN || type == J_LN1 || type == J_MOD) {
            if (type == J_LN) { if (!acquired) wait_flag(F_OP + rb, (unsigned)((tg_tab(rb) >> (8 * J_LN)) & 255)); if (!(h_seen >> 31)) { wait_flag(F_MOD + 1, 64); h_seen |= 1u << 31; } }

            TR(j, 2);
            begin_stage(0); pipe_next(pp);
            seq++;
            if (type == J_END) break;
            continue;
        }
        const CUtensorMap *ta, *tb0, *tb1;
        int k0 = 0, nk = 8, n0 = cb * 256, n1 = n0 + 128, nb = 4, dep = -1;
        unsigned tgt = 0;
        switch (type) {
            case J_KV: ta = &p.tm_h; tb0 = tb1 = cb < 16 ? &p.tm_wk : &p.tm_wv; n0 = (cb & 15) * 256; n1 = n0 + 128; dep = F_H + rb; tgt = 2 * NJ_LN1; break;
            case J_QA: ta = &p.tm_h; tb0 = tb1 = &p.tm_wq; dep = F_H + rb; tgt = 2 * NJ_LN1; if (rb == NRB - 1) { n0 = (cb >> 1) * 256; n1 = n0 + 128; } break;
            case J_O: ta = &p.tm_o; tb0 = tb1 = &p.tm_wo; n0 = (cb & 1) * 256; n1 = n0 + 128; nk = o_nk(rb); k0 = (cb >> 1) * nk * 64;
                      dep = F_O + rb; tgt = rb == NRB - 1 ? 64 : 32; break;
            case J_UP: ta = &p.tm_h2; tb0 = &p.tm_wg; tb1 = &p.tm_wu; n0 = n1 = cb * 128; dep = F_H2 + rb; tgt = 2 * NJ_LN; break;
            case J_UP2: ta = &p.tm_h2; tb0 = &p.tm_wg; tb1 = &p.tm_wu; n0 = n1 = cb * 64; nb = 2; dep = F_H2 + rb; tgt = 2 * NJ_LN2; break;
            default: ta = &p.tm_act; tb0 = tb1 = &p.tm_wd; n0 = cb * 64; nk = 0; break;
        }
        const int m0 = rb * 128;
        if (type == J_DN) {
#pragma unroll 1
            for (int kb = 0; kb < 14; kb++) {
                const uint32_t fb = begin_stage(49152);
                const uint32_t st = sb + pp.stage * W_STAGE;
                const int k = kb * 128;
                tma_load2d(st + 32768, tb0, n0, k, fb);
                tma_load2d(st + 40960, tb0, n0, k + 64, fb);
                if (kb == 0) { if (!acquired) { wait_flag(F_ACT + rb, 2 * (fine ? NJ_UP2 : NJ_UP)); asm volatile("fence.proxy.async.global;" ::: "memory"); } TR(j, 2); }
                tma_load2d(st, ta, k, m0, fb);
                tma_load2d(st + 8192, ta, k, m0 + 64, fb);
                tma_load2d(st + 16384, ta, k + 64, m0, fb);
                tma_load2d(st + 24576, ta, k + 64, m0 + 64, fb);
                pipe_next(pp);
            }
        }
#pragma unroll 1
        for (int kb = 0; kb < nk; kb++) {
            const uint32_t fb = begin_stage(16384 + nb * 8192);
            const uint32_t st = sb + pp.stage * W_STAGE;
            const int k = k0 + kb * 64;
            tma_load2d(st + 16384, tb0, n0, k, fb);
            if (nb == 4) {
                tma_load2d(st + 16384 + 8192, tb0, n0 + 64, k, fb);
                tma_load2d(st + 16384 + 16384, tb1, n1, k, fb);
                tma_load2d(st + 16384 + 24576, tb1, n1 + 64, k, fb);
            } else if (nb == 2) {
                tma_load2d(st + 16384 + 8192, tb1, n1, k, fb);
            }
            if (kb == 0) {
                if (acquired && dep < 16) h_seen |= 1u << dep;
                if (dep >= 0 && !acquired && !(dep < 16 && ((h_seen >> dep) & 1))) {
                    wait_flag(dep, tgt);
                    if (type != J_O) asm volatile("fence.proxy.async.global;" ::: "memory");
                    if (dep < 16) h_seen |= 1u << dep;
                }
                TR(j, 2);
            }
            tma_load2d(st, ta, k, m0, fb);
            tma_load2d(st + 8192, ta, k, m0 + 64, fb);
            pipe_next(pp);
        }
        if (type == J_QA) {
            wait_flag(F_KV + rb, 64);
#pragma unroll 1
            for (int i = 0; i < (rb == NRB - 1 ? 2 : 4); i++) {
                const uint32_t fb = begin_stage(40960);
                const uint32_t st = sb + pp.stage * W_STAGE;
                const int col = (i & 1) * HD_ + (rb == NRB - 1 ? cb : cb * 2 + (i >> 1)) * DH_;
                tma_load2d(st, &p.tm_kv, col, m0, fb);
                tma_load2d(st + 8192, &p.tm_kv, col, m0 + 64, fb);
                tma_load2d(st + 16384, &p.tm_kv, col + 64, m0, fb);
                tma_load2d(st + 24576, &p.tm_kv, col + 64, m0 + 64, fb);
                if (i == 0) { wait_flag(F_MEM + rb, 64); asm volatile("fence.proxy.async.global;" ::: "memory"); }
                tma_load2d(st + 32768, &p.tm_kvm, col, rb * 32, fb);
                tma_load2d(st + 36864, &p.tm_kvm, col + 64, rb * 32, fb);
                pipe_next(pp);
            }
        } else if (type == J_DN) {
            const uint32_t fb = begin_stage(16384);
            const uint32_t st = sb + pp.stage * W_STAGE;
            tma_load2d(st, &p.tm_x1, n0, m0, fb);
            tma_load2d(st + 8192, &p.tm_x1, n0, m0 + 64, fb);
            pipe_next(pp);
        }
        seq++;
    }
}

__device__ __forceinline__ void store_warp(const Params& p, uint32_t sb, int wg, int lane) {
    const uint32_t bars = sb + SM_BAR;
    uint32_t seq = 0;
#pragma unroll 1
    while (true) {
        bar_sync(NB_ST + wg, 160);
        const uint32_t jd = lds32(bars + B_RING + (seq & 7) * 4);
        seq++;
        const int type = jd & 255, rb = (jd >> 8) & 255, cb = (jd >> 16) & 255;
        if (type == J_END) break;
        const uint32_t src = sb + W_STG + wg * 16384;
        const CUtensorMap* tm = nullptr; int n0 = cb * 256, nbox = 4, mrow = rb * 128 + wg * 64, flag = 0;
        switch (type) {
            case J_KV: tm = &p.tm_kv; flag = F_KV + rb; break;
            case J_QA: tm = &p.tm_o; flag = F_O + rb; if (rb == NRB - 1) { n0 = cb * 128; nbox = 2; } break;
            case J_O: tm = &p.tm_op; n0 = (cb & 1) * 256; mrow = op_row(rb, cb >> 1) + wg * 64; flag = F_OP + rb; break;
            case J_LN: flag = F_H2 + rb; nbox = 0; break;
            case J_LN1: flag = F_H + rb; nbox = 0; break;
            case J_MOD: flag = F_MOD + rb; nbox = 0; break;
            case J_UP: tm = &p.tm_act; n0 = cb * 128; nbox = 2; flag = F_ACT + rb; break;
            case J_UP2: tm = &p.tm_act; n0 = cb * 64; nbox = 1; flag = F_ACT + rb; break;
            default: tm = &p.tm_out; n0 = cb * 64; nbox = 1; flag = -1; break;
        }
        if (nbox == 4) {
            if (lane == 0) {
                tma_store2d(tm, src, n0, mrow);
                tma_store2d(tm, src + 8192, n0 + 64, mrow);
                bulk_commit();
                asm volatile("cp.async.bulk.wait_group.read 0;" ::: "memory");
                mbar_arrive(bars + B_STGFREE + wg * 8);
            }
            __syncwarp();
            bar_sync(NB_ST + wg, 160);
            n0 += 128; nbox = 2;
        }
        if (lane == 0) {
            if (nbox) {
                tma_store2d(tm, src, n0, mrow);
                if (nbox == 2) tma_store2d(tm, src + 8192, n0 + 64, mrow);
                bulk_commit();
                asm volatile("cp.async.bulk.wait_group.read 0;" ::: "memory");
                mbar_arrive(bars + B_STGFREE + wg * 8);
                bulk_wait0();
                if (flag >= 0) asm volatile("red.relaxed.gpu.global.add.u32 [%0], 1;" :: "l"(&g_flags[flag]) : "memory");
            } else {
                mbar_arrive(bars + B_STGFREE + wg * 8);
                red_release(&g_flags[flag], 1);
            }
        }
        __syncwarp();
    }
}

__device__ __forceinline__ float gelu_tanh(float x) {
    const float t = x * fmaf(-0.10294324397f, x * x, -2.30220819814f);
    float r; asm("rcp.approx.ftz.f32 %0, %1;" : "=f"(r) : "f"(1.f + ex2(t)));
    return x * r;
}

#define CTR(i) do {} while (0)

__device__ __forceinline__ void ln2_row(const Params& p, int rb, int r, int lane) {
    const int row = rb * 128 + r, nsplit = 64 / o_nk(rb);
    const uint4* xr = (const uint4*)(p.x + (size_t)row * D_);
    const uint4 xa = __ldg(xr + lane), xb = __ldg(xr + 32 + lane);
    uint32_t ga[8], c1[8], sm[8];
    load_mod8(g_mod + 2 * D_, lane, ga);
    load_mod8(g_mod + 4 * D_, lane, c1);
    load_mod8(g_mod + 3 * D_, lane, sm);
    float a[16];
#pragma unroll
    for (int i = 0; i < 16; i++) a[i] = 0.f;
    const uint4* src = (const uint4*)(g_op + (size_t)(op_row(rb, 0) + r) * D_) + lane;
    const int sstride = (op_row(rb, 1) - op_row(rb, 0)) * (D_ / 8);
    uint4 u[2][8];
#pragma unroll
    for (int sp = 0; sp < 4; sp++) { u[0][2 * sp] = __ldcg(src + sp * sstride); u[0][2 * sp + 1] = __ldcg(src + sp * sstride + 32); }
    if (nsplit > 4) {
#pragma unroll
        for (int sp = 0; sp < 4; sp++) { u[1][2 * sp] = __ldcg(src + (4 + sp) * sstride); u[1][2 * sp + 1] = __ldcg(src + (4 + sp) * sstride + 32); }
    }
#pragma unroll 1
    for (int s0 = 0; s0 < nsplit; s0 += 4) {
#pragma unroll
        for (int sp = 0; sp < 8; sp++) {
            float* q = a + (sp & 1) * 8;
            const uint4 w = u[0][sp];
            q[0] += bflo(w.x); q[1] += bfhi(w.x); q[2] += bflo(w.y); q[3] += bfhi(w.y);
            q[4] += bflo(w.z); q[5] += bfhi(w.z); q[6] += bflo(w.w); q[7] += bfhi(w.w);
            u[0][sp] = u[1][sp];
        }
        if (s0 + 8 < nsplit) {
#pragma unroll
            for (int sp = 0; sp < 4; sp++) { u[1][2 * sp] = __ldcg(src + (s0 + 8 + sp) * sstride); u[1][2 * sp + 1] = __ldcg(src + (s0 + 8 + sp) * sstride + 32); }
        }
    }
    const uint32_t xv[8] = {xa.x, xa.y, xa.z, xa.w, xb.x, xb.y, xb.z, xb.w};
    uint32_t v[8], r8[8];
#pragma unroll
    for (int i = 0; i < 8; i++) v[i] = hadd2(xv[i], hmul2(ga[i], pack2(a[2 * i], a[2 * i + 1])));
    uint4* x1r = (uint4*)(g_x1 + (size_t)row * D_);
    x1r[lane] = make_uint4(v[0], v[1], v[2], v[3]); x1r[32 + lane] = make_uint4(v[4], v[5], v[6], v[7]);
    uint32_t mu2; float rden;
    ln_stats(v, mu2, rden);
#pragma unroll
    for (int i = 0; i < 8; i++) c1[i] = hadd2(c1[i], 0x3F803F80u);
    ln_apply(v, mu2, rden, c1, sm, r8);
    uint4* hr = (uint4*)(g_h2 + (size_t)row * D_);
    hr[lane] = make_uint4(r8[0], r8[1], r8[2], r8[3]); hr[32 + lane] = make_uint4(r8[4], r8[5], r8[6], r8[7]);
}

__device__ __forceinline__ void consumer(const Params& p, uint32_t sb, int warp, int lane) {
    const uint32_t bars = sb + SM_BAR;
    const int wg = warp >> 2, wl = warp & 3;
    const uint32_t l7 = lane & 7, l8 = lane >> 3, g = lane >> 2, t = lane & 3;
    Pipe pp{0, 0};
    uint32_t seq = 0, stg_phase = 1;
    const int srow = wl * 16 + l7 + (l8 & 1) * 8;
    const uint32_t stg_base = sb + W_STG + wg * 16384 + srow * 128;
    const uint32_t sx = ((lane >> 4) ^ (srow & 7)) << 4;
#pragma unroll 1
    while (true) {
        mbar_wait(bars + B_FULL + pp.stage * 8, pp.phase);
        const uint32_t jd = lds32(bars + B_RING + (seq & 7) * 4);
        CTR(3);
        seq++;
        const int type = jd & 255, rb = (jd >> 8) & 255, cb = (jd >> 16) & 255;
        if (type == J_END) { mbar_wait(bars + B_STGFREE + wg * 8, stg_phase); bar_arrive(NB_ST + wg, 160); break; }
        if (type == J_LN) {
            __syncwarp();
            if (lane == 0) mbar_arrive(bars + B_EMPTY + pp.stage * 8);
            pipe_next(pp);
            const int nr = rb >= FINE_RB ? 1 : 2;
#pragma unroll 1
            for (int rr = 0; rr < nr; rr++) ln2_row(p, rb, (cb * 8 + warp) * nr + rr, lane);
            mbar_wait(bars + B_STGFREE + wg * 8, stg_phase); stg_phase ^= 1;
            CTR(4); CTR(5);
            bar_arrive(NB_ST + wg, 160);
            continue;
        }
        if (type == J_DN || type == J_UP2) {
            float acc[64];
#pragma unroll
            for (int i = 0; i < 64; i++) acc[i] = 0.f;
            if (type == J_DN) {
#pragma unroll 1
                for (int kb = 0; kb < 14; kb++) {
                    if (kb) mbar_wait(bars + B_FULL + pp.stage * 8, pp.phase);
                    const uint32_t st = sb + pp.stage * W_STAGE;
                    const uint64_t da = mkdesc(st + wg * 8192, 16, 1024), db = mkdesc(st + 32768, 8192, 1024);
                    wg_fence();
#pragma unroll
                    for (int ks = 0; ks < 8; ks++) wgmma_n64(acc, da + (ks >> 2) * 1024 + (ks & 3) * 2, db + ks * 128);
                    wg_commit();
                    wg_wait0();
                    if (lane == 0) mbar_arrive(bars + B_EMPTY + pp.stage * 8);
                    pipe_next(pp);
                }
            } else {
#pragma unroll 1
                for (int kb = 0; kb < 8; kb++) {
                    if (kb) mbar_wait(bars + B_FULL + pp.stage * 8, pp.phase);
                    const uint32_t st = sb + pp.stage * W_STAGE;
                    const uint64_t da = mkdesc(st + wg * 8192, 16, 1024), db = mkdesc(st + 16384, 8192, 1024);
                    wg_fence();
#pragma unroll
                    for (int ks = 0; ks < 4; ks++) wgmma_n128(acc, da + ks * 2, db + ks * 128, 1);
                    wg_commit();
                    wg_wait0();
                    if (lane == 0) mbar_arrive(bars + B_EMPTY + pp.stage * 8);
                    pipe_next(pp);
                }
            }
            CTR(4);
            if (type == J_UP2) {
                mbar_wait(bars + B_STGFREE + wg * 8, stg_phase); stg_phase ^= 1;
#pragma unroll
                for (int j = 0; j < 4; j++) {
                    uint32_t r[4];
#pragma unroll
                    for (int q = 0; q < 4; q++) {
                        const uint32_t gw = pack2(acc[8 * j + 2 * q], acc[8 * j + 2 * q + 1]);
                        const uint32_t uw = pack2(acc[32 + 8 * j + 2 * q], acc[32 + 8 * j + 2 * q + 1]);
                        r[q] = hmul2(pack2(gelu_tanh(bflo(gw)), gelu_tanh(bfhi(gw))), uw);
                    }
                    stsm4(stg_base + (sx ^ (j << 5)), r[0], r[1], r[2], r[3]);
                }
            } else {
                mbar_wait(bars + B_FULL + pp.stage * 8, pp.phase);
                const uint32_t st = sb + pp.stage * W_STAGE;
                mbar_wait(bars + B_STGFREE + wg * 8, stg_phase); stg_phase ^= 1;
                const uint32_t* gb = (const uint32_t*)(g_mod + 5 * D_ + cb * 64) + t;
                const uint32_t xa = st + wg * 8192 + (wl * 16 + g) * 128 + (g << 4) + t * 4;
#pragma unroll
                for (int j = 0; j < 4; j++) {
                    uint32_t r[4];
#pragma unroll
                    for (int q = 0; q < 4; q++) {
                        const int nt = 2 * j + (q >> 1);
                        const uint32_t xw = lds32((xa ^ ((nt & 7) << 4)) + (nt >> 3) * 16384 + (q & 1) * 1024);
                        r[q] = hadd2(xw, hmul2(__ldcg(gb + nt * 4), pack2(acc[8 * j + 2 * q], acc[8 * j + 2 * q + 1])));
                    }
                    stsm4(stg_base + (j >> 2) * 8192 + (sx ^ ((2 * j & 7) << 4)), r[0], r[1], r[2], r[3]);
                }
                __syncwarp();
                if (lane == 0) mbar_arrive(bars + B_EMPTY + pp.stage * 8);
                pipe_next(pp);
            }
            fence_async_smem();
            CTR(5);
            bar_arrive(NB_ST + wg, 160);
            continue;
        }
        float acc[128];
#pragma unroll
        for (int i = 0; i < 128; i++) acc[i] = 0.f;
        const int nk = type == J_O ? o_nk(rb) : 8;
#pragma unroll 1
        for (int kb = 0; kb < nk; kb++) {
            if (kb) mbar_wait(bars + B_FULL + pp.stage * 8, pp.phase);
            const uint32_t st = sb + pp.stage * W_STAGE;
            const uint64_t da = mkdesc(st + wg * 8192, 16, 1024), db = mkdesc(st + 16384, 8192, 1024);
            wg_fence();
#pragma unroll
            for (int ks = 0; ks < 4; ks++) wgmma_n256(acc, da + ks * 2, db + ks * 128, 1);
            wg_commit();
            wg_wait0();
            if (lane == 0) mbar_arrive(bars + B_EMPTY + pp.stage * 8);
            pipe_next(pp);
        }
        CTR(4);
        if (type == J_QA) {
            uint32_t qf[64];
#pragma unroll
            for (int i = 0; i < 64; i++) qf[i] = pack2(acc[2 * i], acc[2 * i + 1]);
            const int sg = warp >> 1, half = warp & 1;
            const float sc = 0.08838834764831845f * 1.4426950408889634f;
            const uint32_t xoff = (sg >> 1) * 8192 + ((sg & 1) * 32 + l7) * 128;
            const uint32_t moff = 32768 + (sg * 8 + l7) * 128;
            const uint32_t kch = (l8 ^ l7) << 4;
            const uint32_t vch = ((l8 & 1) ^ l7) << 4;
            if (rb == NRB - 1 && (cb & 1)) {
#pragma unroll
                for (int i = 0; i < 32; i++) qf[i] = qf[32 + i];
            }
#pragma unroll 1
            for (int hh = rb == NRB - 1; hh < 2; hh++) {
                mbar_wait(bars + B_FULL + pp.stage * 8, pp.phase);
                uint32_t st = sb + pp.stage * W_STAGE;
                float sa[5][4];
#pragma unroll
                for (int n = 0; n < 5; n++) sa[n][0] = sa[n][1] = sa[n][2] = sa[n][3] = 0.f;
#pragma unroll
                for (int i = 0; i < 4; i++) {
                    const uint32_t* q = qf + i * 8;
                    uint32_t kk[5][4];
                    ldsm4(kk[0][0], kk[0][1], kk[0][2], kk[0][3], st + moff + (i >> 1) * 4096 + (kch ^ ((i & 1) * 64)));
#pragma unroll
                    for (int n = 1; n < 5; n++)
                        ldsm4(kk[n][0], kk[n][1], kk[n][2], kk[n][3], st + xoff + (n - 1) * 1024 + (i >> 1) * 16384 + (kch ^ ((i & 1) * 64)));
#pragma unroll
                    for (int n = 0; n < 5; n++) mma16816(sa[n], q[0], q[1], q[2], q[3], kk[n][0], kk[n][1]);
#pragma unroll
                    for (int n = 0; n < 5; n++) mma16816(sa[n], q[4], q[5], q[6], q[7], kk[n][2], kk[n][3]);
                }
                __syncwarp();
                if (lane == 0) mbar_arrive(bars + B_EMPTY + pp.stage * 8);
                pipe_next(pp);
                const int iq0 = half * 16 + g - 2 * t, iq1 = iq0 + 8;
                float m0 = fmaxf(sa[0][0], sa[0][1]), m1 = fmaxf(sa[0][2], sa[0][3]);
#pragma unroll
                for (int n = 1; n < 5; n++) {
#pragma unroll
                    for (int e = 0; e < 2; e++) {
                        const int jx = (n - 1) * 8 + e;
                        if (jx > iq0) sa[n][e] = -3.0e38f;
                        if (jx > iq1) sa[n][2 + e] = -3.0e38f;
                        m0 = fmaxf(m0, sa[n][e]); m1 = fmaxf(m1, sa[n][2 + e]);
                    }
                }
                m0 = fmaxf(m0, __shfl_xor_sync(~0u, m0, 1)); m1 = fmaxf(m1, __shfl_xor_sync(~0u, m1, 1));
                m0 = fmaxf(m0, __shfl_xor_sync(~0u, m0, 2)); m1 = fmaxf(m1, __shfl_xor_sync(~0u, m1, 2));
                m0 *= -sc; m1 *= -sc;
                float l0 = 0.f, l1 = 0.f;
                uint32_t p0[5], p1[5];
#pragma unroll
                for (int n = 0; n < 5; n++) {
                    const float e0 = ex2(fmaf(sa[n][0], sc, m0)), e1 = ex2(fmaf(sa[n][1], sc, m0));
                    const float e2 = ex2(fmaf(sa[n][2], sc, m1)), e3 = ex2(fmaf(sa[n][3], sc, m1));
                    l0 += e0 + e1; l1 += e2 + e3;
                    p0[n] = pack2(e0, e1); p1[n] = pack2(e2, e3);
                }
                l0 += __shfl_xor_sync(~0u, l0, 1); l1 += __shfl_xor_sync(~0u, l1, 1);
                l0 += __shfl_xor_sync(~0u, l0, 2); l1 += __shfl_xor_sync(~0u, l1, 2);
                const float i0 = __fdividef(1.f, l0), i1 = __fdividef(1.f, l1);
                mbar_wait(bars + B_FULL + pp.stage * 8, pp.phase);
                st = sb + pp.stage * W_STAGE;
                mbar_wait(bars + B_STGFREE + wg * 8, stg_phase); stg_phase ^= 1;
#pragma unroll
                for (int i = 0; i < 32; i++) qf[i] = qf[32 + i];
#pragma unroll 1
                for (int bx = 0; bx < 2; bx++) {
                    float o[8][4];
                    uint32_t vm[8], v0[4][4], v1[4][4];
#pragma unroll
                    for (int ep = 0; ep < 4; ep++) {
                        ldsm2t(vm[2 * ep], vm[2 * ep + 1], st + moff + bx * 4096 + (vch ^ (ep << 5)));
                        const uint32_t va = st + xoff + (l8 >> 1) * 1024 + bx * 16384 + (vch ^ (ep << 5));
                        ldsm4t(v0[ep][0], v0[ep][1], v0[ep][2], v0[ep][3], va);
                        ldsm4t(v1[ep][0], v1[ep][1], v1[ep][2], v1[ep][3], va + 2048);
                    }
#pragma unroll
                    for (int n = 0; n < 8; n++) { o[n][0] = o[n][1] = o[n][2] = o[n][3] = 0.f; mma16816(o[n], p0[0], p1[0], p0[1], p1[1], vm[n], v0[n >> 1][n & 1]); }
#pragma unroll
                    for (int n = 0; n < 8; n++) mma16816(o[n], p0[2], p1[2], p0[3], p1[3], v0[n >> 1][2 + (n & 1)], v1[n >> 1][n & 1]);
#pragma unroll
                    for (int n = 0; n < 8; n++) mma1688(o[n], p0[4], p1[4], v1[n >> 1][2 + (n & 1)]);
#pragma unroll
                    for (int ep = 0; ep < 4; ep++)
                        stsm4(stg_base + bx * 8192 + (sx ^ (ep << 5)),
                              pack2(o[2 * ep][0] * i0, o[2 * ep][1] * i0), pack2(o[2 * ep][2] * i1, o[2 * ep][3] * i1),
                              pack2(o[2 * ep + 1][0] * i0, o[2 * ep + 1][1] * i0), pack2(o[2 * ep + 1][2] * i1, o[2 * ep + 1][3] * i1));
                }
                __syncwarp();
                if (lane == 0) mbar_arrive(bars + B_EMPTY + pp.stage * 8);
                pipe_next(pp);
                if (hh == 0) { fence_async_smem(); bar_arrive(NB_ST + wg, 160); }
            }
        } else if (type == J_UP) {
            mbar_wait(bars + B_STGFREE + wg * 8, stg_phase); stg_phase ^= 1;
#pragma unroll
            for (int j = 0; j < 8; j++) {
                uint32_t r[4];
#pragma unroll
                for (int q = 0; q < 4; q++) {
                    const uint32_t gw = pack2(acc[8 * j + 2 * q], acc[8 * j + 2 * q + 1]);
                    const uint32_t uw = pack2(acc[64 + 8 * j + 2 * q], acc[64 + 8 * j + 2 * q + 1]);
                    r[q] = hmul2(pack2(gelu_tanh(bflo(gw)), gelu_tanh(bfhi(gw))), uw);
                }
                stsm4(stg_base + (j >> 2) * 8192 + (sx ^ ((2 * j & 7) << 4)), r[0], r[1], r[2], r[3]);
            }
        } else {
#pragma unroll
            for (int rd = 0; rd < 2; rd++) {
                mbar_wait(bars + B_STGFREE + wg * 8, stg_phase); stg_phase ^= 1;
#pragma unroll
                for (int j = rd * 8; j < rd * 8 + 8; j++)
                    stsm4(stg_base + ((j >> 2) & 1) * 8192 + (sx ^ ((2 * j & 7) << 4)),
                          pack2(acc[8 * j], acc[8 * j + 1]), pack2(acc[8 * j + 2], acc[8 * j + 3]),
                          pack2(acc[8 * j + 4], acc[8 * j + 5]), pack2(acc[8 * j + 6], acc[8 * j + 7]));
                if (rd == 0) { fence_async_smem(); bar_arrive(NB_ST + wg, 160); }
            }
        }
        fence_async_smem();
        CTR(5);
        bar_arrive(NB_ST + wg, 160);
    }
}

__global__ void __launch_bounds__(384, 1) k_work(const __grid_constant__ Params p) {
    extern __shared__ __align__(1024) unsigned char smem_raw[];
    const uint32_t sb = smem_u32(smem_raw);
    if (sb & 1023) __trap();
    const int warp = __shfl_sync(~0u, threadIdx.x >> 5, 0);
    int lane; asm volatile("mov.u32 %0, %%laneid;" : "=r"(lane));
    if (threadIdx.x == 0) {
        const uint32_t bars = sb + SM_BAR;
        for (int i = 0; i < W_NST; i++) { mbar_init(bars + B_FULL + i * 8, 1); mbar_init(bars + B_EMPTY + i * 8, 8); }
        mbar_init(bars + B_STGFREE, 1); mbar_init(bars + B_STGFREE + 8, 1); mbar_init(bars + B_REQ, 1); mbar_init(bars + B_RSP, 1);
        asm volatile("fence.mbarrier_init.release.cluster;" ::: "memory");
    }
    __syncthreads();
    if (warp < 8) {
        asm volatile("setmaxnreg.inc.sync.aligned.u32 224;");
        consumer(p, sb, warp, lane);
    } else {
        asm volatile("setmaxnreg.dec.sync.aligned.u32 56;");
        if (warp == 8) { if (lane == 0) producer(p, sb); }
        else if (warp < 11) store_warp(p, sb, warp - 9, lane);
        else scheduler(p, sb, lane);
        __syncwarp();
        bar_sync(NB_W0, 128);
        if (warp == 8 && p.qmask == 0xff) {
            unsigned last = 0;
            if (lane == 0) { __threadfence(); last = atomicAdd(&g_flags[F_DONE], 1u) == gridDim.x - 1; }
            if (__shfl_sync(~0u, last, 0))
                for (int i = lane; i < F_TOTAL; i += 32) g_flags[i] = 0;
        }
    }
}

typedef CUresult (*EncodeFn)(CUtensorMap*, CUtensorMapDataType, cuuint32_t, void*, const cuuint64_t*, const cuuint64_t*,
                             const cuuint32_t*, const cuuint32_t*, CUtensorMapInterleave, CUtensorMapSwizzle,
                             CUtensorMapL2promotion, CUtensorMapFloatOOBfill);

static void make_map(EncodeFn enc, CUtensorMap* m, const void* ptr, uint64_t rows, uint64_t cols, uint32_t box_rows) {
    cuuint64_t dims[2] = {cols, rows};
    cuuint64_t strides[1] = {cols * 2};
    cuuint32_t box[2] = {64, box_rows};
    cuuint32_t es[2] = {1, 1};
    enc(m, CU_TENSOR_MAP_DATA_TYPE_BFLOAT16, 2, const_cast<void*>(ptr), dims, strides, box, es, CU_TENSOR_MAP_INTERLEAVE_NONE,
        CU_TENSOR_MAP_SWIZZLE_128B, CU_TENSOR_MAP_L2_PROMOTION_L2_256B, CU_TENSOR_MAP_FLOAT_OOB_FILL_NONE);
}
template <typename T> static void* sym_addr(T& sym) { void* p = nullptr; cudaGetSymbolAddress(&p, sym); return p; }

extern "C" void kernel_launch(void* const* d_in, const int* in_sizes, int n_in, void* d_out, int out_size) {
    static Params prm;
    static RecParams rp;
    static bool ready = false;
    static const void* key[14];
    bool same = ready;
    for (int i = 0; i < 13 && same; i++) same = key[i] == d_in[i];
    same = same && key[13] == d_out;
    if (!same) {
        void* fn = nullptr;
        cudaDriverEntryPointQueryResult qr;
        cudaGetDriverEntryPoint("cuTensorMapEncodeTiled", &fn, cudaEnableDefault, &qr);
        EncodeFn enc = (EncodeFn)fn;
        make_map(enc, &prm.tm_h, sym_addr(g_h), S_, D_, 64);
        make_map(enc, &prm.tm_kv, sym_addr(g_kv), S_, 2 * HD_, 64);
        make_map(enc, &prm.tm_kvm, sym_addr(g_kvm), NSEG * 8, 2 * HD_, 32);
        make_map(enc, &prm.tm_o, sym_addr(g_o), S_, HD_, 64);
        make_map(enc, &prm.tm_op, sym_addr(g_op), OP_ROWS, D_, 64);
        make_map(enc, &prm.tm_h2, sym_addr(g_h2), S_, D_, 64);
        make_map(enc, &prm.tm_act, sym_addr(g_act), S_, DF_, 64);
        make_map(enc, &prm.tm_x1, sym_addr(g_x1), S_, D_, 64);
        make_map(enc, &prm.tm_out, d_out, S_, D_, 64);
        make_map(enc, &prm.tm_wq, d_in[2], D_, HD_, 64);
        make_map(enc, &prm.tm_wk, d_in[3], D_, HD_, 64);
        make_map(enc, &prm.tm_wv, d_in[4], D_, HD_, 64);
        make_map(enc, &prm.tm_wo, d_in[5], HD_, D_, 64);
        make_map(enc, &prm.tm_wg, d_in[8], D_, DF_, 64);
        make_map(enc, &prm.tm_wu, d_in[9], D_, DF_, 64);
        make_map(enc, &prm.tm_wd, d_in[10], DF_, D_, 64);
        prm.x = (const bf16*)d_in[0]; prm.c = (const bf16*)d_in[11]; prm.w_mod = (const bf16*)d_in[12];
        rp.mem0 = (const bf16*)d_in[1]; rp.x = prm.x; rp.c = prm.c; rp.w_mod = prm.w_mod;
        rp.wq = (const bf16*)d_in[2]; rp.wk = (const bf16*)d_in[3]; rp.wv = (const bf16*)d_in[4]; rp.wo = (const bf16*)d_in[5];
        cudaFuncSetAttribute(k_work, cudaFuncAttributeMaxDynamicSharedMemorySize, SMEM_BYTES);
        cudaFuncSetAttribute(k_rec, cudaFuncAttributeMaxDynamicSharedMemorySize, R_SMEM);
        cudaFuncSetAttribute(k_rec, cudaFuncAttributeNonPortableClusterSizeAllowed, 1);
        {
            cudaLaunchConfig_t cfg = {};
            cfg.gridDim = dim3(128); cfg.blockDim = dim3(384); cfg.dynamicSmemBytes = R_SMEM;
            cudaLaunchAttribute at[1];
            at[0].id = cudaLaunchAttributeClusterDimension; at[0].val.clusterDim.x = 16; at[0].val.clusterDim.y = 1; at[0].val.clusterDim.z = 1;
            cfg.attrs = at; cfg.numAttrs = 1;
            int n = 0;
            cudaOccupancyMaxActiveClusters(&n, k_rec, &cfg);
            rp.ncl = n < 4 ? 4 : (n > 8 ? 8 : n);
        }
        for (int i = 0; i < 13; i++) key[i] = d_in[i];
        key[13] = d_out;
        ready = true;
    }
    cudaStream_t st = cudaStreamPerThread;
    auto launch_rec = [&]() {
        cudaLaunchConfig_t cfg = {};
        cfg.gridDim = dim3(16 * rp.ncl); cfg.blockDim = dim3(384); cfg.dynamicSmemBytes = R_SMEM; cfg.stream = st;
        cudaLaunchAttribute at[1];
        at[0].id = cudaLaunchAttributeClusterDimension; at[0].val.clusterDim.x = 16; at[0].val.clusterDim.y = 1; at[0].val.clusterDim.z = 1;
        cfg.attrs = at; cfg.numAttrs = 1;
        cudaLaunchKernelEx(&cfg, k_rec, rp);
    };
    auto launch_work = [&](int qmask, int pdl) {
        prm.qmask = qmask;
        cudaLaunchConfig_t cfg = {};
        cfg.gridDim = dim3(132); cfg.blockDim = dim3(384); cfg.dynamicSmemBytes = SMEM_BYTES; cfg.stream = st;
        cudaLaunchAttribute at[1];
        at[0].id = cudaLaunchAttributeProgrammaticStreamSerialization; at[0].val.programmaticStreamSerializationAllowed = 1;
        cfg.attrs = at; cfg.numAttrs = pdl;
        cudaLaunchKernelEx(&cfg, k_work, prm);
    };
    launch_rec();
    launch_work(0xff, 1);
}
```

```cpp
#include <cuda_runtime.h>
#include <cuda_bf16.h>
#include <cuda.h>
#include <stdint.h>

typedef __nv_bfloat16 bf16;
#define PF_NS 500
#define IDLE_NS 150
#define FLAG_NS 20

constexpr int S_ = 2048, D_ = 512, H_ = 32, DH_ = 128, HD_ = 4096, NSEG = 64, DF_ = 1792;
constexpr int NRB = 16;
constexpr int OSPLIT = 4;

__device__ __align__(1024) bf16 g_h[S_ * D_];
__device__ __align__(1024) bf16 g_kv[S_ * 2 * HD_];
__device__ __align__(1024) bf16 g_kvm[NSEG * 8 * 2 * HD_];
__device__ __align__(1024) bf16 g_o[S_ * HD_];
#define FINE_RB_ 12
constexpr int FINE_RB = FINE_RB_;
#define OSPLIT2_ 8
constexpr int OSPLIT2 = OSPLIT2_;
constexpr int OSPLIT3 = 16;
constexpr int OP_ROWS = OSPLIT * S_ + OSPLIT2 * (NRB - FINE_RB) * 128 + OSPLIT3 * 128;
__device__ __align__(1024) bf16 g_op[OP_ROWS * D_];
__device__ __align__(1024) bf16 g_x1[S_ * D_];
__device__ __align__(1024) bf16 g_h2[S_ * D_];
__device__ __align__(1024) bf16 g_act[S_ * DF_];
__device__ __align__(1024) bf16 g_mod[6 * D_];
__device__ uint32_t g_Fraw[131072 + 65536 + 2048];
#define g_F ((uint32_t*)(((uint64_t)g_Fraw + 0x7FFFFull) & ~0x7FFFFull))
constexpr int F_H = 0, F_MEM = 32, F_O = 64, F_OP = 96, F_H2 = 128, F_ACT = 160, F_MOD = 192, F_KV = 224, F_CLAIM = 256  ,
              F_SIDE = 512  , F_DONE = 576, F_TOTAL = 608;
__device__ __align__(128) unsigned int g_flags[F_TOTAL];
#define TR(j, i) do {} while (0)

__device__ __forceinline__ uint32_t smem_u32(const void* p) { return (uint32_t)__cvta_generic_to_shared(p); }
__device__ __forceinline__ uint32_t clk32() { uint32_t c; asm volatile("mov.u32 %0, %%clock;" : "=r"(c)); return c; }
__device__ __forceinline__ uint32_t mapa_u32(uint32_t addr, uint32_t rank) {
    uint32_t r; asm volatile("mapa.shared::cluster.u32 %0, %1, %2;" : "=r"(r) : "r"(addr), "r"(rank)); return r;
}
__device__ __forceinline__ void mbar_init(uint32_t bar, uint32_t cnt) {
    asm volatile("mbarrier.init.shared::cta.b64 [%0], %1;" :: "r"(bar), "r"(cnt) : "memory");
}
__device__ __forceinline__ void mbar_inval(uint32_t bar) {
    asm volatile("mbarrier.inval.shared::cta.b64 [%0];" :: "r"(bar) : "memory");
}
__device__ __forceinline__ void mbar_expect_tx(uint32_t bar, uint32_t bytes) {
    asm volatile("mbarrier.arrive.expect_tx.shared::cta.b64 _, [%0], %1;" :: "r"(bar), "r"(bytes) : "memory");
}
__device__ __forceinline__ void mbar_arrive(uint32_t bar) {
    asm volatile("mbarrier.arrive.shared::cta.b64 _, [%0];" :: "r"(bar) : "memory");
}
__device__ __forceinline__ bool mbar_try_wait(uint32_t bar, uint32_t parity) {
    uint32_t ok;
    asm volatile("{\n.reg .pred p;\nmbarrier.try_wait.parity.shared::cta.b64 p, [%1], %2;\nselp.u32 %0, 1, 0, p;\n}"
                 : "=r"(ok) : "r"(bar), "r"(parity) : "memory");
    return ok;
}
__device__ __forceinline__ bool mbar_try_wait_cluster(uint32_t bar, uint32_t parity) {
    uint32_t ok;
    asm volatile("{\n.reg .pred p;\nmbarrier.try_wait.parity.acquire.cluster.shared::cta.b64 p, [%1], %2;\nselp.u32 %0, 1, 0, p;\n}"
                 : "=r"(ok) : "r"(bar), "r"(parity) : "memory");
    return ok;
}
constexpr int SPIN_LIMIT = 1 << 18;
#define TIMEOUT(code, info) do {} while (0)
__device__ __forceinline__ void mbar_wait(uint32_t bar, uint32_t parity) {
    int g = 0;
#pragma unroll 1
    while (!mbar_try_wait(bar, parity)) { if (++g >= SPIN_LIMIT) { TIMEOUT(0, bar & 255); break; } }
}
__device__ __forceinline__ void mbar_wait_cluster(uint32_t bar, uint32_t parity) {
    int g = 0;
#pragma unroll 1
    while (!mbar_try_wait_cluster(bar, parity)) { if (++g >= SPIN_LIMIT) { TIMEOUT(1, bar & 255); break; } }
}
__device__ __forceinline__ void bar_sync(int id, int n) { asm volatile("bar.sync %0, %1;" :: "r"(id), "r"(n) : "memory"); }
__device__ __forceinline__ void bar_arrive(int id, int n) { asm volatile("bar.arrive %0, %1;" :: "r"(id), "r"(n) : "memory"); }
__device__ __forceinline__ void cluster_sync_all() {
    asm volatile("barrier.cluster.arrive.aligned;\nbarrier.cluster.wait.aligned;" ::: "memory");
}
__device__ __forceinline__ void st_async_v2(uint32_t addr, float a, float b, uint32_t bar) {
    asm volatile("st.async.weak.shared::cluster.mbarrier::complete_tx::bytes.v2.f32 [%0], {%1,%2}, [%3];"
                 :: "r"(addr), "f"(a), "f"(b), "r"(bar) : "memory");
}
__device__ __forceinline__ void st_async_v4(uint32_t addr, uint4 v, uint32_t bar) {
    asm volatile("st.async.weak.shared::cluster.mbarrier::complete_tx::bytes.v4.b32 [%0], {%1,%2,%3,%4}, [%5];"
                 :: "r"(addr), "r"(v.x), "r"(v.y), "r"(v.z), "r"(v.w), "r"(bar) : "memory");
}
__device__ __forceinline__ uint2 ldg_relaxed2(const uint2* p) {
    uint2 v;
    asm volatile("ld.relaxed.gpu.global.v2.b32 {%0,%1}, [%2];" : "=r"(v.x), "=r"(v.y) : "l"(p) : "memory");
    return v;
}
__device__ __forceinline__ void stg_relaxed2(uint2* p, uint2 v) {
    asm volatile("st.relaxed.gpu.global.v2.b32 [%0], {%1,%2};" :: "l"(p), "r"(v.x), "r"(v.y) : "memory");
}
__device__ __forceinline__ uint4 ldg_relaxed(const uint4* p) {
    uint4 v;
    asm volatile("ld.relaxed.gpu.global.v4.b32 {%0,%1,%2,%3}, [%4];" : "=r"(v.x), "=r"(v.y), "=r"(v.z), "=r"(v.w) : "l"(p) : "memory");
    return v;
}
__device__ __forceinline__ void stg_relaxed(uint4* p, uint4 v) {
    asm volatile("st.relaxed.gpu.global.v4.b32 [%0], {%1,%2,%3,%4};" :: "l"(p), "r"(v.x), "r"(v.y), "r"(v.z), "r"(v.w) : "memory");
}
__device__ __forceinline__ void stg_relaxed32(uint32_t* p, uint32_t v) {
    asm volatile("st.relaxed.gpu.global.b32 [%0], %1;" :: "l"(p), "r"(v) : "memory");
}
__device__ __forceinline__ uint32_t ldg_relaxed32(const uint32_t* p) {
    uint32_t v; asm volatile("ld.relaxed.gpu.global.b32 %0, [%1];" : "=r"(v) : "l"(p) : "memory"); return v;
}
__device__ __forceinline__ unsigned int ld_acquire(const unsigned int* p) {
    unsigned int v; asm volatile("ld.acquire.gpu.global.u32 %0, [%1];" : "=r"(v) : "l"(p) : "memory"); return v;
}
__device__ __forceinline__ void red_release(unsigned int* p, unsigned int v) {
    asm volatile("red.release.gpu.global.add.u32 [%0], %1;" :: "l"(p), "r"(v) : "memory");
}
__device__ __forceinline__ void wait_flag(int idx, unsigned int target) {
    const unsigned int* p = &g_flags[idx];
    int g = 0;
#pragma unroll 1
    while (ld_acquire(p) < target) { __nanosleep(FLAG_NS); if (++g >= 64 * SPIN_LIMIT) { TIMEOUT(2, idx); break; } }
}
__device__ __forceinline__ void cp_async16(uint32_t dst, const void* src) {
    asm volatile("cp.async.cg.shared.global [%0], [%1], 16;" :: "r"(dst), "l"(src) : "memory");
}
__device__ __forceinline__ void cp_async_commit() { asm volatile("cp.async.commit_group;" ::: "memory"); }
template <int N> __device__ __forceinline__ void cp_async_wait() { asm volatile("cp.async.wait_group %0;" :: "n"(N) : "memory"); }
__device__ __forceinline__ void ldsm4(uint32_t& r0, uint32_t& r1, uint32_t& r2, uint32_t& r3, uint32_t addr) {
    asm volatile("ldmatrix.sync.aligned.m8n8.x4.shared.b16 {%0,%1,%2,%3}, [%4];" : "=r"(r0), "=r"(r1), "=r"(r2), "=r"(r3) : "r"(addr) : "memory");
}
__device__ __forceinline__ void ldsm4t(uint32_t& r0, uint32_t& r1, uint32_t& r2, uint32_t& r3, uint32_t addr) {
    asm volatile("ldmatrix.sync.aligned.m8n8.x4.trans.shared.b16 {%0,%1,%2,%3}, [%4];" : "=r"(r0), "=r"(r1), "=r"(r2), "=r"(r3) : "r"(addr) : "memory");
}
__device__ __forceinline__ void ldsm2t(uint32_t& r0, uint32_t& r1, uint32_t addr) {
    asm volatile("ldmatrix.sync.aligned.m8n8.x2.trans.shared.b16 {%0,%1}, [%2];" : "=r"(r0), "=r"(r1) : "r"(addr) : "memory");
}
__device__ __forceinline__ void stsm4(uint32_t addr, uint32_t r0, uint32_t r1, uint32_t r2, uint32_t r3) {
    asm volatile("stmatrix.sync.aligned.m8n8.x4.shared.b16 [%0], {%1,%2,%3,%4};" :: "r"(addr), "r"(r0), "r"(r1), "r"(r2), "r"(r3) : "memory");
}
__device__ __forceinline__ void stsm2t(uint32_t addr, uint32_t r0, uint32_t r1) {
    asm volatile("stmatrix.sync.aligned.m8n8.x2.trans.shared.b16 [%0], {%1,%2};" :: "r"(addr), "r"(r0), "r"(r1) : "memory");
}
__device__ __forceinline__ void mma16816(float* d, uint32_t a0, uint32_t a1, uint32_t a2, uint32_t a3, uint32_t b0, uint32_t b1) {
    asm volatile("mma.sync.aligned.m16n8k16.row.col.f32.bf16.bf16.f32 {%0,%1,%2,%3}, {%4,%5,%6,%7}, {%8,%9}, {%0,%1,%2,%3};"
                 : "+f"(d[0]), "+f"(d[1]), "+f"(d[2]), "+f"(d[3]) : "r"(a0), "r"(a1), "r"(a2), "r"(a3), "r"(b0), "r"(b1));
}
__device__ __forceinline__ void mma1688(float* d, uint32_t a0, uint32_t a1, uint32_t b0) {
    asm volatile("mma.sync.aligned.m16n8k8.row.col.f32.bf16.bf16.f32 {%0,%1,%2,%3}, {%4,%5}, {%6}, {%0,%1,%2,%3};"
                 : "+f"(d[0]), "+f"(d[1]), "+f"(d[2]), "+f"(d[3]) : "r"(a0), "r"(a1), "r"(b0));
}
__device__ __forceinline__ void mma16816h(float* d, uint32_t a0, uint32_t a2, uint32_t b0, uint32_t b1) {
    asm volatile("{\n.reg .b32 ju, jv;\nmma.sync.aligned.m16n8k16.row.col.f32.bf16.bf16.f32 {%0,%1,%2,%3}, {%4,ju,%5,jv}, {%6,%7}, {%0,%1,%2,%3};\n}"
                 : "+f"(d[0]), "+f"(d[1]), "+f"(d[2]), "+f"(d[3]) : "r"(a0), "r"(a2), "r"(b0), "r"(b1));
}
__device__ __forceinline__ void mma1688h(float* d, uint32_t a0, uint32_t b0) {
    asm volatile("{\n.reg .b32 ju;\nmma.sync.aligned.m16n8k8.row.col.f32.bf16.bf16.f32 {%0,%1,%2,%3}, {%4,ju}, {%5}, {%0,%1,%2,%3};\n}"
                 : "+f"(d[0]), "+f"(d[1]), "+f"(d[2]), "+f"(d[3]) : "r"(a0), "r"(b0));
}
__device__ __forceinline__ uint32_t pack2(float lo, float hi) {
    uint32_t r; asm("cvt.rn.bf16x2.f32 %0, %1, %2;" : "=r"(r) : "f"(hi), "f"(lo)); return r;
}
__device__ __forceinline__ float bflo(uint32_t w) { return __uint_as_float(w << 16); }
__device__ __forceinline__ float bfhi(uint32_t w) { return __uint_as_float(w & 0xffff0000u); }
__device__ __forceinline__ float rbf(float x) { return __bfloat162float(__float2bfloat16_rn(x)); }
__device__ __forceinline__ float ex2(float x) { float y; asm("ex2.approx.ftz.f32 %0, %1;" : "=f"(y) : "f"(x)); return y; }
__device__ __forceinline__ void sts128(uint32_t addr, uint4 v) {
    asm volatile("st.shared.v4.b32 [%0], {%1,%2,%3,%4};" :: "r"(addr), "r"(v.x), "r"(v.y), "r"(v.z), "r"(v.w) : "memory");
}
__device__ __forceinline__ uint4 lds128(uint32_t addr) {
    uint4 v; asm volatile("ld.shared.v4.b32 {%0,%1,%2,%3}, [%4];" : "=r"(v.x), "=r"(v.y), "=r"(v.z), "=r"(v.w) : "r"(addr) : "memory"); return v;
}
__device__ __forceinline__ float2 lds64f(uint32_t addr) {
    float2 v; asm volatile("ld.shared.v2.f32 {%0,%1}, [%2];" : "=f"(v.x), "=f"(v.y) : "r"(addr) : "memory"); return v;
}
__device__ __forceinline__ float lds32f(uint32_t addr) {
    float v; asm volatile("ld.shared.f32 %0, [%1];" : "=f"(v) : "r"(addr) : "memory"); return v;
}
__device__ __forceinline__ uint32_t lds32(uint32_t addr) {
    uint32_t v; asm volatile("ld.shared.b32 %0, [%1];" : "=r"(v) : "r"(addr) : "memory"); return v;
}
__device__ __forceinline__ void sts32(uint32_t addr, uint32_t v) { asm volatile("st.shared.b32 [%0], %1;" :: "r"(addr), "r"(v) : "memory"); }
__device__ __forceinline__ void sts64f(uint32_t addr, float a, float b) { asm volatile("st.shared.v2.f32 [%0], {%1,%2};" :: "r"(addr), "f"(a), "f"(b) : "memory"); }

__device__ __forceinline__ void tma_load2d(uint32_t dst, const CUtensorMap* tm, int c0, int c1, uint32_t bar) {
    asm volatile("cp.async.bulk.tensor.2d.shared::cluster.global.mbarrier::complete_tx::bytes [%0], [%1, {%3, %4}], [%2];"
                 :: "r"(dst), "l"(tm), "r"(bar), "r"(c0), "r"(c1) : "memory");
}
__device__ __forceinline__ void tma_store2d(const CUtensorMap* tm, uint32_t src, int c0, int c1) {
    asm volatile("cp.async.bulk.tensor.2d.global.shared::cta.bulk_group [%0, {%2, %3}], [%1];"
                 :: "l"(tm), "r"(src), "r"(c0), "r"(c1) : "memory");
}
__device__ __forceinline__ void bulk_commit() { asm volatile("cp.async.bulk.commit_group;" ::: "memory"); }
__device__ __forceinline__ void bulk_wait0() { asm volatile("cp.async.bulk.wait_group 0;" ::: "memory"); }
__device__ __forceinline__ void fence_async_smem() { asm volatile("fence.proxy.async.shared::cta;" ::: "memory"); }
__device__ __forceinline__ void fence_async_all() { asm volatile("fence.proxy.async;" ::: "memory"); }

__device__ __forceinline__ void wg_fence() { asm volatile("wgmma.fence.sync.aligned;" ::: "memory"); }
__device__ __forceinline__ void wg_commit() { asm volatile("wgmma.commit_group.sync.aligned;" ::: "memory"); }
__device__ __forceinline__ void wg_wait0() { asm volatile("wgmma.wait_group.sync.aligned 0;" ::: "memory"); }
__device__ __forceinline__ uint64_t mkdesc(uint32_t saddr, uint32_t lbo, uint32_t sbo) {
    return (uint64_t)((saddr & 0x3FFFF) >> 4) | ((uint64_t)(lbo >> 4) << 16) | ((uint64_t)(sbo >> 4) << 32) | (1ull << 62);
}
#define ACC8(i) "+f"(d[i]), "+f"(d[i + 1]), "+f"(d[i + 2]), "+f"(d[i + 3]), "+f"(d[i + 4]), "+f"(d[i + 5]), "+f"(d[i + 6]), "+f"(d[i + 7])
__device__ __forceinline__ void wgmma_n256(float* d, uint64_t da, uint64_t db, int scale_d) {
    asm volatile(
        "{\n.reg .pred p;\nsetp.ne.b32 p, %130, 0;\n"
        "wgmma.mma_async.sync.aligned.m64n256k16.f32.bf16.bf16 "
        "{%0,%1,%2,%3,%4,%5,%6,%7,%8,%9,%10,%11,%12,%13,%14,%15,%16,%17,%18,%19,%20,%21,%22,%23,%24,%25,%26,%27,%28,%29,%30,%31,"
        "%32,%33,%34,%35,%36,%37,%38,%39,%40,%41,%42,%43,%44,%45,%46,%47,%48,%49,%50,%51,%52,%53,%54,%55,%56,%57,%58,%59,%60,%61,%62,%63,"
        "%64,%65,%66,%67,%68,%69,%70,%71,%72,%73,%74,%75,%76,%77,%78,%79,%80,%81,%82,%83,%84,%85,%86,%87,%88,%89,%90,%91,%92,%93,%94,%95,"
        "%96,%97,%98,%99,%100,%101,%102,%103,%104,%105,%106,%107,%108,%109,%110,%111,%112,%113,%114,%115,%116,%117,%118,%119,%120,%121,%122,%123,%124,%125,%126,%127}, "
        "%128, %129, p, 1, 1, 0, 1;\n}"
        : ACC8(0), ACC8(8), ACC8(16), ACC8(24), ACC8(32), ACC8(40), ACC8(48), ACC8(56),
          ACC8(64), ACC8(72), ACC8(80), ACC8(88), ACC8(96), ACC8(104), ACC8(112), ACC8(120)
        : "l"(da), "l"(db), "r"(scale_d));
}
__device__ __forceinline__ void wgmma_n128(float* d, uint64_t da, uint64_t db, int scale_d) {
    asm volatile(
        "{\n.reg .pred p;\nsetp.ne.b32 p, %66, 0;\n"
        "wgmma.mma_async.sync.aligned.m64n128k16.f32.bf16.bf16 "
        "{%0,%1,%2,%3,%4,%5,%6,%7,%8,%9,%10,%11,%12,%13,%14,%15,%16,%17,%18,%19,%20,%21,%22,%23,%24,%25,%26,%27,%28,%29,%30,%31,"
        "%32,%33,%34,%35,%36,%37,%38,%39,%40,%41,%42,%43,%44,%45,%46,%47,%48,%49,%50,%51,%52,%53,%54,%55,%56,%57,%58,%59,%60,%61,%62,%63}, "
        "%64, %65, p, 1, 1, 0, 1;\n}"
        : ACC8(0), ACC8(8), ACC8(16), ACC8(24), ACC8(32), ACC8(40), ACC8(48), ACC8(56)
        : "l"(da), "l"(db), "r"(scale_d));
}

__device__ __forceinline__ void wgmma_n64(float* d, uint64_t da, uint64_t db) {
    asm volatile(
        "wgmma.mma_async.sync.aligned.m64n64k16.f32.bf16.bf16 "
        "{%0,%1,%2,%3,%4,%5,%6,%7,%8,%9,%10,%11,%12,%13,%14,%15,%16,%17,%18,%19,%20,%21,%22,%23,%24,%25,%26,%27,%28,%29,%30,%31}, "
        "%32, %33, 1, 1, 1, 0, 1;"
        : ACC8(0), ACC8(8), ACC8(16), ACC8(24)
        : "l"(da), "l"(db));
}
__device__ __forceinline__ void wgmma_n8_ta(float* d, uint64_t da, uint64_t db, int scale_d) {
    asm volatile(
        "{\n.reg .pred p;\nsetp.ne.b32 p, %6, 0;\n"
        "wgmma.mma_async.sync.aligned.m64n8k16.f32.bf16.bf16 {%0,%1,%2,%3}, %4, %5, p, 1, 1, 1, 0;\n}"
        : "+f"(d[0]), "+f"(d[1]), "+f"(d[2]), "+f"(d[3]) : "l"(da), "l"(db), "r"(scale_d));
}

__device__ __forceinline__ uint32_t hadd2(uint32_t a, uint32_t b) { uint32_t r; asm("add.rn.bf16x2 %0, %1, %2;" : "=r"(r) : "r"(a), "r"(b)); return r; }
__device__ __forceinline__ uint32_t hsub2(uint32_t a, uint32_t b) { uint32_t r; asm("sub.rn.bf16x2 %0, %1, %2;" : "=r"(r) : "r"(a), "r"(b)); return r; }
__device__ __forceinline__ uint32_t hmul2(uint32_t a, uint32_t b) { uint32_t r; asm("mul.rn.bf16x2 %0, %1, %2;" : "=r"(r) : "r"(a), "r"(b)); return r; }
__device__ __forceinline__ void load_mod8(const bf16* m, int lane, uint32_t* v) {
    const uint4 a = __ldcg((const uint4*)m + lane), b = __ldcg((const uint4*)m + 32 + lane);
    v[0] = a.x; v[1] = a.y; v[2] = a.z; v[3] = a.w; v[4] = b.x; v[5] = b.y; v[6] = b.z; v[7] = b.w;
}
__device__ __forceinline__ void ln_stats(const uint32_t* x, uint32_t& mu2, float& rden) {
    float s = 0.f;
#pragma unroll
    for (int i = 0; i < 8; i++) s += bflo(x[i]) + bfhi(x[i]);
#pragma unroll
    for (int o = 16; o > 0; o >>= 1) s += __shfl_xor_sync(~0u, s, o);
    const float mean = s * (1.f / D_);
    float q = 0.f;
#pragma unroll
    for (int i = 0; i < 8; i++) { const float d0 = bflo(x[i]) - mean, d1 = bfhi(x[i]) - mean; q = fmaf(d0, d0, q); q = fmaf(d1, d1, q); }
#pragma unroll
    for (int o = 16; o > 0; o >>= 1) q += __shfl_xor_sync(~0u, q, o);
    mu2 = pack2(mean, mean);
    rden = __frcp_rn(rbf(__fsqrt_rn(rbf(rbf(q * (1.f / D_)) + 1e-5f))));
}
__device__ __forceinline__ void ln_apply(const uint32_t* x, uint32_t mu2, float rden, const uint32_t* c1, const uint32_t* sm, uint32_t* r) {
#pragma unroll
    for (int i = 0; i < 8; i++) {
        const uint32_t d = hsub2(x[i], mu2);
        r[i] = hadd2(hmul2(pack2(bflo(d) * rden, bfhi(d) * rden), c1[i]), sm[i]);
    }
}

struct __align__(64) Params {
    CUtensorMap tm_h, tm_kv, tm_kvm, tm_o, tm_op, tm_h2, tm_act, tm_x1, tm_out;
    CUtensorMap tm_wq, tm_wk, tm_wv, tm_wo, tm_wg, tm_wu, tm_wd;
    const bf16 *x, *c, *w_mod;
    int qmask;
};

constexpr uint32_t R_WV = 0, R_MEM = 65536, R_KX = 73728  , R_VX = R_KX + 8192  ,
                   R_KMS = R_VX + 16384  , R_VMS = R_KMS + 1024,
                   R_QS = R_KMS + 4096, R_OS = R_QS + 1024  , R_SX = R_OS + 2048, R_BAR = R_SX + 2560,
                   R_RS = 108544  , R_VB = R_RS + 4096  , R_VP = R_VB + 2048  ,
                   R_STG = R_VP + 8192  , R_SMEM = R_STG + 98304;
static_assert((R_KMS & 4095) == 0, "smem");
static_assert(R_BAR + 64 <= R_RS, "smem");
constexpr uint32_t RB_SX = R_BAR, RB_V = R_BAR + 8, RB_E = R_BAR + 16, RB_A = R_BAR + 24, RB_ROLE = R_BAR + 32, RB_A1 = R_BAR + 40;
constexpr int W_NST = 4;
constexpr uint32_t W_STAGE = 49152, W_STG = W_NST * W_STAGE  , W_END = W_STG + 32768;
constexpr uint32_t SM_BAR = W_END;
constexpr uint32_t SMEM_BYTES = W_END + 1024 + 2048;
constexpr uint32_t B_FULL = 0, B_EMPTY = 32, B_STGFREE = 64, B_REQ = 80, B_RSP = 88, B_NEXT = 96, B_RING = 128;
#define PICK_AHEAD 3

constexpr int NB_X = 11  , NB_Y = 1, NB_M = 5, NB_K = 5, NB_B = 2, NB_C = 3, NB_D = 4, NB_W0 = 6  , NB_ST = 9  ;

__device__ __forceinline__ int pos_of_d(int d) {
    const int rem = d & 31;
    return (d & ~31) + ((rem & 7) >> 1) * 8 + (rem & 1) * 4 + (rem >> 3);
}

#define PROF(i) do {} while (0)
#define PROFG(i) do {} while (0)
#define OPAQUE(x) asm volatile("" : "+r"(x))
#define FENCE_SCHED(x) do { if ((x) == 0u) asm volatile("trap;"); } while (0)
#define QKVAR 2
#define VK0_ 4
constexpr int VK0 = VK0_;
constexpr int NOFF = 8;
#define OFFKS(i) (((i) >> 1) < 2 ? ((i) >> 1) : ((i) >> 1) + 2)
#define VDELAY -1
#define POLL_GAP 110

struct RecParams { const bf16 *mem0, *wq, *wk, *wv, *wo, *x, *c, *w_mod; int ncl, only_pre; };

__device__ __forceinline__ void rec_qk(const RecParams& p, const uint32_t sb, const int cta, const int warp, int lane, const int sel) {
    const int crank = cta & 15, cl = cta >> 4, rank = cta & 1;
    const int kh = warp >> 2, aa = warp & 3;
    uint32_t wa[2][16][4];
    const uint32_t stg = sb + R_STG + kh * 32768;
    {
        const int t128 = aa * 32 + lane;
        const int row = (lane >> 4) * 8 + (lane & 7);
        const int ch = t128 & 7;
        const size_t goff = (size_t)kh * 256 * HD_ + cta * 64 + ch * 8;
#pragma unroll 4
        for (int dd = 0; dd < 16; dd++) {
            const int d = dd * 16 + (t128 >> 3), pp = pos_of_d(d);
            cp_async16(sb + R_WV + kh * 32768 + pp * 128 + ((ch ^ (pp & 7)) << 4), p.wv + goff + (size_t)d * HD_);
        }
        cp_async_commit();
#pragma unroll 4
        for (int dd = 0; dd < 16; dd++) {
            const int d = dd * 16 + (t128 >> 3), pp = pos_of_d(d);
            cp_async16(stg + pp * 128 + ((ch ^ (pp & 7)) << 4), p.wq + goff + (size_t)d * HD_);
        }
        cp_async_commit();
        {
            const int i0 = (warp * 32 + lane) * 16, tok = i0 >> 9;
            const uint4 m0 = __ldg((const uint4*)(p.mem0 + i0)), m1 = __ldg((const uint4*)(p.mem0 + i0 + 8));
            const uint32_t mw[8] = {m0.x, m0.y, m0.z, m0.w, m1.x, m1.y, m1.z, m1.w};
#pragma unroll
            for (int e = 0; e < 16; e++) {
                const int pp = pos_of_d((i0 & 511) + e);
                const unsigned short v = (unsigned short)(mw[e >> 1] >> ((e & 1) * 16));
                asm volatile("st.shared.u16 [%0], %1;" :: "r"(sb + R_MEM + (pp >> 3) * 128 + tok * 16 + (pp & 7) * 2), "h"(v) : "memory");
            }
        }
        cp_async_wait<1>();
        bar_sync(NB_W0 + kh, 128);
        const uint32_t fv = row * 128 + (((2 * aa + ((lane >> 3) & 1)) ^ (row & 7)) << 4);
#pragma unroll
        for (int ks = 0; ks < 16; ks++) ldsm4t(wa[0][ks][0], wa[0][ks][1], wa[0][ks][2], wa[0][ks][3], sb + R_WV + kh * 32768 + fv + ks * 2048);
        bar_sync(NB_W0 + kh, 128);
#pragma unroll
        for (int ks = 0; ks < 16; ks++)
            sts128(sb + R_WV + kh * 32768 + (aa * 16 + ks) * 512 + lane * 16, make_uint4(wa[0][ks][0], wa[0][ks][1], wa[0][ks][2], wa[0][ks][3]));
        const uint32_t fo = stg + row * 128 + (((4 * (aa & 1) + ((lane >> 3) & 1)) ^ (row & 7)) << 4);
#pragma unroll 1
        for (int m = 0; m < 2; m++) {
            cp_async_wait<0>();
            bar_sync(NB_W0 + kh, 128);
            if ((aa >> 1) == m) {
#pragma unroll
                for (int ks = 0; ks < 16; ks++) {
                    ldsm4t(wa[0][ks][0], wa[0][ks][1], wa[0][ks][2], wa[0][ks][3], fo + ks * 2048);
                    ldsm4t(wa[1][ks][0], wa[1][ks][1], wa[1][ks][2], wa[1][ks][3], (fo ^ 32) + ks * 2048);
                }
            }
            bar_sync(NB_W0 + kh, 128);
            if (m == 0) {
#pragma unroll 4
                for (int dd = 0; dd < 16; dd++) {
                    const int d = dd * 16 + (t128 >> 3), pp = pos_of_d(d);
                    cp_async16(stg + pp * 128 + ((ch ^ (pp & 7)) << 4), p.wk + goff + (size_t)d * HD_);
                }
                cp_async_commit();
            }
        }
    }
    const uint32_t tab = stg + (aa * 32 + lane) * 16;
    {
        const uint32_t l7 = lane & 7, l8 = lane >> 3, g = lane >> 2, t = lane & 3;
        const uint32_t t0 = l7 * 128 + ((l8 ^ l7) << 4);
        const uint32_t tq = l7 * 128 + (((l8 >> 1) ^ l7) << 4);
        const uint32_t bq = warp >> 1, tp = warp & 1;
        uint4 v;
        v.x = sb + (aa < 2 ? R_QS : R_KMS) + l7 * 128 + (((4 * (aa & 1) + 2 * kh + (l8 & 1)) ^ l7) << 4);
        v.y = sb + R_QS + tq;
        v.z = sb + (warp == 0 ? R_KMS : R_KX + (warp - 1) * 1024) + t0;
        v.w = mapa_u32(sb + R_SX + (rank * 5 + warp) * 256 + lane * 8, crank ^ 1);
        sts128(tab, v);
        sts128(tab + 2048, make_uint4(sb + lane * 16 + R_MEM + kh * 4096, sb + lane * 16 + R_WV + warp * 8192,
                                      sb + lane * 16 + R_VP + warp * 512, sb + lane * 16 + R_VP + 4096 + (warp ^ 4) * 512));
        const uint32_t src = l7;
        const uint32_t L = bq * 8 + 2 * tp + (l8 & 1) + 4 * (l8 >> 1);
        const uint32_t d0 = (crank + ((t >> 1) | (g & 6))) & 15;
        v.x = sb + R_RS + src * 512 + ((L ^ (src & 7)) << 4);
        v.y = mapa_u32(sb + R_MEM + (crank * 4 + bq) * 128 + (4 * tp + 2 * (t & 1) + (g & 1)) * 16, d0);
        v.z = mapa_u32(sb + ((crank & 1) ? RB_A1 : RB_A), d0);
        v.w = lane;
        sts128(tab + 4096, v);
        const uint64_t wr = (uint64_t)(g_F + ((crank * 2 + ((crank ^ (crank >> 3) ^ sel) & 1)) * 1024 + warp * 128 + cl * 32 + lane));
        sts128(tab + 6144, make_uint4((uint32_t)wr, (uint32_t)(wr >> 32), (uint32_t)((((cl + 1) & 3) - cl) * 128), (uint32_t)((((cl + 2) & 3) - cl) * 128)));
        sts32(tab + 8192, (uint32_t)((((cl + 3) & 3) - cl) * 128));
#pragma unroll
        for (int i = 0; i < NOFF; i++)
            sts128(tab + 10240 + i * 2048, make_uint4(wa[i & 1][OFFKS(i)][0], wa[i & 1][OFFKS(i)][1], wa[i & 1][OFFKS(i)][2], wa[i & 1][OFFKS(i)][3]));
    }
    bar_sync(NB_D, 384);
    uint32_t slot_off = 0;
    const uint32_t slot_inc = warp == 0 ? 2048 : 4096;
    const uint32_t sx_bar_rem = (sb + RB_SX) ^ (1u << 24);
    uint4 tb = lds128(tab + 2048);
#pragma unroll 1
    for (int s = 0; s < NSEG; s++) {
        if (s > 0) mbar_wait(sb + RB_A, (s - 1) & 1);
        if (warp == 0) { PROF(0); PROFG(13); }
        uint4 ta;
        const uint32_t km_tog = aa >= 2 ? (s & 1) * 2048 : 0;
        {
            float acc[5][4];
#pragma unroll
            for (int c = 0; c < 5; c++) { acc[c][0] = acc[c][1] = acc[c][2] = acc[c][3] = 0.f; }
            uint32_t b[8][4];
            uint4 av[16];
            static_assert(VK0 == 4, "order below assumes the V/O warps cover slices 0,1");
#define QK4(k2) do { \
                mma16816(acc[0], wa[0][2 * (k2)][0], wa[0][2 * (k2)][1], wa[0][2 * (k2)][2], wa[0][2 * (k2)][3], b[k2][0], b[k2][1]); \
                mma16816(acc[1], wa[1][2 * (k2)][0], wa[1][2 * (k2)][1], wa[1][2 * (k2)][2], wa[1][2 * (k2)][3], b[k2][0], b[k2][1]); \
                mma16816(acc[3], wa[0][2 * (k2) + 1][0], wa[0][2 * (k2) + 1][1], wa[0][2 * (k2) + 1][2], wa[0][2 * (k2) + 1][3], b[k2][2], b[k2][3]); \
                mma16816(acc[4], wa[1][2 * (k2) + 1][0], wa[1][2 * (k2) + 1][1], wa[1][2 * (k2) + 1][2], wa[1][2 * (k2) + 1][3], b[k2][2], b[k2][3]); } while (0)
#define V2(k2) do { \
                mma16816(acc[2], av[2 * (k2)].x, av[2 * (k2)].y, av[2 * (k2)].z, av[2 * (k2)].w, b[k2][0], b[k2][1]); \
                mma16816(acv, av[2 * (k2) + 1].x, av[2 * (k2) + 1].y, av[2 * (k2) + 1].z, av[2 * (k2) + 1].w, b[k2][2], b[k2][3]); } while (0)
#define LB(k2) ldsm4(b[k2][0], b[k2][1], b[k2][2], b[k2][3], tb.x + (k2) * 512)
#define LV(k2) do { av[2 * (k2)] = lds128(tb.y + 2 * (k2) * 512); av[2 * (k2) + 1] = lds128(tb.y + (2 * (k2) + 1) * 512); } while (0)
            float acv[4] = {0.f, 0.f, 0.f, 0.f};
            LB(0); LB(2); LB(4); LB(6);
            QK4(0); QK4(2); LV(2); LV(4); QK4(4); QK4(6);
            if (s > 0) mbar_wait(sb + RB_A1, (s - 1) & 1);
            LB(1); LB(3); LB(5); LB(7); ta = lds128(tab);
            V2(2); V2(4); LV(6); LV(3);
            QK4(1); QK4(3); QK4(5); QK4(7);
            LV(5); LV(7);
#pragma unroll
            for (int i = 0; i < 4; i++) { acc[0][i] += acc[3][i]; acc[1][i] += acc[4][i]; }
            const float g0 = kh ? acc[0][0] : acc[1][0], g1 = kh ? acc[0][1] : acc[1][1], g2 = kh ? acc[0][2] : acc[1][2], g3 = kh ? acc[0][3] : acc[1][3];
            sts128(tb.w, make_uint4(__float_as_uint(g0), __float_as_uint(g1), __float_as_uint(g2), __float_as_uint(g3)));
            const float k0 = kh ? acc[1][0] : acc[0][0], k1 = kh ? acc[1][1] : acc[0][1], k2_ = kh ? acc[1][2] : acc[0][2], k3 = kh ? acc[1][3] : acc[0][3];
            if (warp == 0) PROF(1);
            V2(6); V2(3);
            bar_sync(NB_X + aa, 64);
            const uint4 o = lds128(tb.z + 4096);
            V2(5); V2(7);
            stsm2t(ta.x ^ km_tog, pack2(k0 + __uint_as_float(o.x), k1 + __uint_as_float(o.y)), pack2(k2_ + __uint_as_float(o.z), k3 + __uint_as_float(o.w)));
            sts128(tb.z, make_uint4(__float_as_uint(acc[2][0] + acv[0]), __float_as_uint(acc[2][1] + acv[1]), __float_as_uint(acc[2][2] + acv[2]), __float_as_uint(acc[2][3] + acv[3])));
        }
        const uint32_t kb = ta.z + slot_off;
        if (warp == 0) PROF(14);
        bar_sync(NB_B, 256);
        if (warp < 5) {
            uint32_t q[16], k0, k1, k2, k3, k4, k5, k6, k7;
            float sa[4] = {0.f, 0.f, 0.f, 0.f}, sc[4] = {0.f, 0.f, 0.f, 0.f};
            ldsm4(q[0], q[1], q[2], q[3], ta.y);
            ldsm4(k0, k1, k2, k3, kb);
            ldsm4(q[4], q[5], q[6], q[7], ta.y ^ 32);
            ldsm4(q[8], q[9], q[10], q[11], ta.y ^ 64);
            ldsm4(k4, k5, k6, k7, kb ^ 64);
            ldsm4(q[12], q[13], q[14], q[15], ta.y ^ 96);
            mma16816(sa, q[0], q[1], q[2], q[3], k0, k1);
            bar_arrive(NB_Y, 288);
            mma16816(sc, q[4], q[5], q[6], q[7], k2, k3);
            mma16816(sa, q[8], q[9], q[10], q[11], k4, k5);
            mma16816(sc, q[12], q[13], q[14], q[15], k6, k7);
            const float scl = 0.08838834764831845f * 1.4426950408889634f;
            const float r0 = (sa[0] + sc[0]) * scl, r1 = (sa[1] + sc[1]) * scl;
            if (s != NSEG - 1) {
                st_async_v2(ta.w, r0, r1, sx_bar_rem);
                st_async_v2(ta.w ^ (1u << 24), r0, r1, sx_bar_rem ^ (1u << 24));
            }
            if (warp == 0) PROF(2);
        } else if (s > 0 && warp == 7 && lane == 0) {
            mbar_expect_tx(sb + RB_A, 4096);
            mbar_expect_tx(sb + RB_A1, 4096);
        } else if (s > 0 && (s & 3) == 0 && warp == 6) {
            bar_sync(NB_K, 160);
            if (lane == 0) red_release(&g_flags[F_MEM + (s >> 2) - 1], 1);
            __syncwarp();
        }
        if (s == NSEG - 1) {
            const uint4 td = lds128(tab + 6144);
            stg_relaxed32((uint32_t*)(((uint64_t)td.y << 32) | (td.x ^ 0x21000)), 0u);
            break;
        }
        slot_off ^= slot_inc;
        const uint4 tc = lds128(tab + 4096), td = lds128(tab + 6144);
        const uint32_t te = lds32(tab + 8192);
        uint32_t* wr = (uint32_t*)(((uint64_t)td.y << 32) | (td.x ^ ((s & 1) * 0x21000)));
        const uint32_t* r1p = (const uint32_t*)((const char*)wr + (int)td.z);
        const uint32_t* r2p = (const uint32_t*)((const char*)wr + (int)td.w);
        const uint32_t* r3p = (const uint32_t*)((const char*)wr + (int)te);
        const uint32_t tag = ((s >> 1) + 1) & 1;
        mbar_wait(sb + RB_E, s & 1);
        if (warp == 0) PROF(7);
        {
            uint32_t a0, a1, a2, a3;
            ldsm4t(a0, a1, a2, a3, tc.x);
            const uint32_t one = 0x3F803F80u;
            float d0_[4] = {0.f, 0.f, 0.f, 0.f}, d1_[4] = {0.f, 0.f, 0.f, 0.f};
            mma1688(d0_, a0, a1, one);
            mma1688(d1_, a2, a3, one);
            const bool t1 = tc.w & 1, t2 = tc.w & 2;
            const float x = t2 ? (t1 ? d1_[2] : d1_[0]) : (t1 ? d0_[2] : d0_[0]);
            const uint32_t own = (__float_as_uint(x) & ~1u) | tag;
            stg_relaxed32(wr, own);
            const uint32_t tq = clk32();
            if (warp == 0) PROF(8);
            PROFG(16 + warp);
            while ((int)(clk32() - tq) < POLL_GAP) {}
            uint32_t f1 = ldg_relaxed32(r1p), f2 = ldg_relaxed32(r2p), f3 = ldg_relaxed32(r3p);
#pragma unroll
            for (int i = 0; i < NOFF; i++) {
                const uint4 f0 = lds128(tab + 10240 + i * 2048);
                wa[i & 1][OFFKS(i)][0] = f0.x; wa[i & 1][OFFKS(i)][1] = f0.y; wa[i & 1][OFFKS(i)][2] = f0.z; wa[i & 1][OFFKS(i)][3] = f0.w;
            }
            tb = lds128(tab + 2048);
            int gg = 0;
#pragma unroll 1
            while (!__all_sync(~0u, (((f1 ^ tag) | (f2 ^ tag) | (f3 ^ tag)) & 1) == 0)) {
                f1 = ldg_relaxed32(r1p); f2 = ldg_relaxed32(r2p); f3 = ldg_relaxed32(r3p);
                if (++gg > 16 * SPIN_LIMIT) { TIMEOUT(3, s); break; }
            }
            if (warp == 0) PROF(9);
            const float v = (__uint_as_float(own) + __uint_as_float(f2)) + (__uint_as_float(f1) + __uint_as_float(f3));
            const bool b8 = tc.w & 8, b16 = tc.w & 16;
            const float recv = __shfl_xor_sync(~0u, v, 8);
            const uint32_t word = b8 ? pack2(recv, v) : pack2(v, recv);
            const uint32_t oth = __shfl_xor_sync(~0u, word, 16);
            const uint32_t wl = b16 ? oth : word, wh = b16 ? word : oth;
            const uint32_t p0 = __shfl_xor_sync(~0u, wl, 2), p1 = __shfl_xor_sync(~0u, wh, 2);
            const uint4 item = t2 ? make_uint4(p0, p1, wl, wh) : make_uint4(wl, wh, p0, p1);
            st_async_v4(tc.y, item, tc.z);
            st_async_v4(tc.y ^ (8u << 24), item, tc.z ^ (8u << 24));
            if (tc.w == 0 && warp == 7) mbar_expect_tx(sb + RB_E, 4096);
            if (warp == 0) PROF(10);
            PROF(40 + warp);
        }
        bar_sync(NB_D, 384);
    }
}

__device__ __forceinline__ void rec_load_kv(uint32_t dk, const char* src, int rank) {
    cp_async16(dk, src);
    cp_async16(dk ^ 16, src + 16);
}
__device__ __forceinline__ void rec_load_v(uint32_t dv, const char* src) {
    cp_async16(dv, src);
    cp_async16(dv ^ 16, src + 16);
    cp_async16(dv + 4096, src + 128);
    cp_async16((dv ^ 16) + 4096, src + 128 + 16);
}

__device__ __forceinline__ void rec_vo(const RecParams& p, const uint32_t sb, const int cta, const int warp, int lane) {
    const int w = warp - 8, crank = cta & 15, rank = cta & 1;
    const int col0 = cta * 64;
    uint32_t wo[4][8][4];
    const uint32_t tab = sb + R_STG + 2 * 32768 + (w * 32 + lane) * 16;
    {
        const int t128 = w * 32 + lane;
        const bf16* Wo = p.wo + (size_t)(cta >> 1) * DH_ * D_ + rank * 256;
        const uint32_t stg = sb + R_STG + 2 * 32768;
#pragma unroll
        for (int half = 0; half < 2; half++) {
#pragma unroll 4
            for (int i = t128; i < 2048; i += 128) {
                const int e = i >> 5, ch = i & 31;
                cp_async16(stg + e * 512 + ((ch ^ (e & 7)) << 4), Wo + (size_t)(half * 64 + e) * D_ + ch * 8);
            }
            cp_async_commit();
            cp_async_wait<0>();
            bar_sync(NB_W0 + 2, 128);
#pragma unroll
            for (int j = 0; j < 4; j++)
#pragma unroll
                for (int kk = 0; kk < 4; kk++) {
                    const int e = kk * 16 + (lane >> 4) * 8 + (lane & 7);
                    const int ch = (w * 4 + j) * 2 + ((lane >> 3) & 1);
                    ldsm4t(wo[j][half * 4 + kk][0], wo[j][half * 4 + kk][1], wo[j][half * 4 + kk][2], wo[j][half * 4 + kk][3],
                           stg + e * 512 + ((ch ^ (e & 7)) << 4));
                }
            bar_sync(NB_W0 + 2, 128);
        }
        const uint32_t l7 = lane & 7, l8 = lane >> 3, g = lane >> 2;
        uint4 v;
        v.x = sb + R_VX + (w >> 1) * 4096 + ((l8 & 1) * 8 + l7) * 128 + (((4 * (w & 1) + (l8 >> 1)) ^ l7) << 4);
        v.y = sb + R_OS + (w >> 1) * 1024 + g * 128 + (((4 * (w & 1)) ^ g) << 4) + (lane & 3) * 4;
        v.z = sb + R_VMS + l7 * 128 + (((2 * w + (l8 & 1)) ^ l7) << 4);
        v.w = sb + R_OS + l7 * 128 + ((l8 ^ l7) << 4);
        sts128(tab, v);
        v.x = mapa_u32(sb + R_RS + (crank >> 1) * 512 + ((lane ^ (crank >> 1)) << 4), rank * 8 + w * 2);
        v.y = mapa_u32(sb + RB_E, rank * 8 + w * 2);
        v.z = sb + R_VB + ((w >> 1) * 4 + 2 * (w & 1)) * 256 + lane * 8;
        v.w = sb + R_SX + lane * 8;
        sts128(tab + 2048, v);
#pragma unroll
        for (int i = 0; i < 8; i++)
            sts128(tab + 4096 + i * 2048, make_uint4(wo[i >> 1][(i & 1) * 4][0], wo[i >> 1][(i & 1) * 4][1], wo[i >> 1][(i & 1) * 4][2], wo[i >> 1][(i & 1) * 4][3]));
        const int tok = (w & 1) * 4 + (lane >> 3), row = t128 >> 2, c2 = (lane & 3) * 2;
        const uint64_t kd = (uint64_t)(g_kvm + (tok * (2 * HD_) + (w >> 1) * HD_ + col0 + (lane & 7) * 8));
        const uint64_t ks = (uint64_t)(g_kv + ((size_t)row * (2 * HD_) + col0 + c2 * 8));
        const uint32_t dk = sb + R_KX + row * 128 + ((c2 ^ (row & 7)) << 4);
        sts128(tab + 20480, make_uint4((uint32_t)kd, (uint32_t)(kd >> 32), (uint32_t)ks, (uint32_t)(ks >> 32)));
        sts128(tab + 22528, make_uint4(sb + R_KMS + (w >> 1) * 1024 + tok * 128 + (((lane & 7) ^ tok) << 4), dk, lane, sb + lane * 16));
        if (lane == 0) wait_flag(F_KV + 0, 64);
        __syncwarp();
        rec_load_kv(dk, (const char*)ks, rank);
        rec_load_v(dk + (R_VX - R_KX), (const char*)ks + HD_ * 2 - rank * 128);
        cp_async_commit();
        cp_async_wait<0>();
    }
    bar_sync(NB_D, 384);
    const uint32_t lane16 = lds32(tab + 22528 + 12);
    const uint32_t vb_dst = (lane16 - sb) / 2 + sb + R_VB + (rank * 4 + w) * 256;
    uint4 av[2 * VK0];
#pragma unroll
    for (int i = 0; i < 2 * VK0; i++) av[i] = lds128(lane16 + R_WV + (i / VK0) * 32768 + (w * 16 + i % VK0) * 512);
#pragma unroll 1
    for (int s = 0; s < NSEG; s++) {
        {
            if (s > 0) mbar_wait(sb + RB_A, (s - 1) & 1);
            const uint4 tp = lds128(tab + 20480), tq = lds128(tab + 22528);
            if (s > 0) {
                const uint4 kvm = lds128(tq.x + ((s - 1) & 1) * 2048);
                *(uint4*)((((uint64_t)tp.y << 32) | tp.x) + (uint64_t)(s - 1) * (8 * 2 * HD_ * 2)) = kvm;
                if ((s & 3) == 0) bar_arrive(NB_K, 160);
            }
            if (s + 1 < NSEG - 1) {
                if (((s + 1) & 3) == 0) { if (tq.z == 0) wait_flag(F_KV + ((s + 1) >> 2), 64); __syncwarp(); }
                const char* src = (const char*)((((uint64_t)tp.w << 32) | tp.z) + (uint64_t)(s + 1) * (32 * 2 * HD_ * 2));
                rec_load_kv(tq.y + ((s + 1) & 1) * 4096, src, rank);
                rec_load_v(tq.y + (R_VX - R_KX) + ((s + 1) & 1) * 8192, src + HD_ * 2 - rank * 128);
            }
            cp_async_commit();
        }
        bar_sync(NB_Y, 288);
        uint32_t vb0, vb1;
        {
            float va[4] = {0.f, 0.f, 0.f, 0.f}, vc[4] = {0.f, 0.f, 0.f, 0.f};
            uint32_t bb[VK0][4];
#pragma unroll
            for (int k2 = 0; k2 < VK0; k2++) ldsm4(bb[k2][0], bb[k2][1], bb[k2][2], bb[k2][3], lane16 + R_MEM + (k2 / (VK0 / 2)) * 4096 + (k2 % (VK0 / 2)) * 512);
            const uint4 a = lds128(lane16 + R_VP + w * 512), b = lds128(lane16 + R_VP + 2048 + w * 512);
#pragma unroll
            for (int k2 = 0; k2 < VK0; k2++) {
                mma16816(va, av[2 * k2].x, av[2 * k2].y, av[2 * k2].z, av[2 * k2].w, bb[k2][0], bb[k2][1]);
                mma16816(vc, av[2 * k2 + 1].x, av[2 * k2 + 1].y, av[2 * k2 + 1].z, av[2 * k2 + 1].w, bb[k2][2], bb[k2][3]);
            }
            vb0 = pack2((va[0] + vc[0]) + (__uint_as_float(a.x) + __uint_as_float(b.x)), (va[1] + vc[1]) + (__uint_as_float(a.y) + __uint_as_float(b.y)));
            vb1 = pack2((va[2] + vc[2]) + (__uint_as_float(a.z) + __uint_as_float(b.z)), (va[3] + vc[3]) + (__uint_as_float(a.w) + __uint_as_float(b.w)));
            if (s != NSEG - 1) {
                st_async_v2(vb_dst ^ (1u << 24), __uint_as_float(vb0), __uint_as_float(vb1), (sb + RB_V) ^ (1u << 24));
                st_async_v2(vb_dst, __uint_as_float(vb0), __uint_as_float(vb1), sb + RB_V);
            }
        }
        const uint4 ta = lds128(tab), tb = lds128(tab + 2048);
        stsm2t(ta.z + (s & 1) * 2048, vb0, vb1);
        if (w == 0) PROF(11);
        if (s != NSEG - 1) {
            uint32_t vx[16];
            const uint32_t vxa = ta.x + (s & 1) * 8192;
            ldsm4t(vx[0], vx[1], vx[2], vx[3], vxa);
            ldsm4t(vx[4], vx[5], vx[6], vx[7], vxa ^ 32);
            ldsm4t(vx[8], vx[9], vx[10], vx[11], vxa + 2048);
            ldsm4t(vx[12], vx[13], vx[14], vx[15], (vxa ^ 32) + 2048);
#pragma unroll
            for (int i = 0; i < 4; i++) {
                const uint4 f0 = lds128(tab + 4096 + i * 2048);
                wo[i >> 1][(i & 1) * 4][0] = f0.x; wo[i >> 1][(i & 1) * 4][1] = f0.y; wo[i >> 1][(i & 1) * 4][2] = f0.z; wo[i >> 1][(i & 1) * 4][3] = f0.w;
            }
            mbar_wait(sb + RB_SX, s & 1);
            if (w == 0) PROF(4);
            float sv[10];
#pragma unroll
            for (int n = 0; n < 5; n++) {
                const float2 a = lds64f(tb.w + n * 256), b = lds64f(tb.w + (5 + n) * 256);
                sv[2 * n] = a.x + b.x; sv[2 * n + 1] = a.y + b.y;
            }
            float mx = fmaxf(fmaxf(fmaxf(sv[0], sv[1]), fmaxf(sv[2], sv[3])), fmaxf(fmaxf(sv[4], sv[5]), fmaxf(sv[6], sv[7])));
            mx = fmaxf(mx, fmaxf(sv[8], sv[9]));
            mx = fmaxf(mx, __shfl_xor_sync(~0u, mx, 1));
            mx = fmaxf(mx, __shfl_xor_sync(~0u, mx, 2));
            mbar_wait(sb + RB_V, s & 1);
            const float2 m0 = lds64f(tb.z), m1 = lds64f(tb.z + 256);
            uint32_t pf[5];
#pragma unroll
            for (int n = 0; n < 5; n++) pf[n] = pack2(ex2(sv[2 * n] - mx), ex2(sv[2 * n + 1] - mx));
            if (w == 0) PROF(12);
            float oa[4][4] = {{0.f, 0.f, 0.f, 0.f}, {0.f, 0.f, 0.f, 0.f}, {0.f, 0.f, 0.f, 0.f}, {0.f, 0.f, 0.f, 0.f}}, sm[4] = {0.f, 0.f, 0.f, 0.f};
            const uint32_t one = 0x3F803F80u;
            mma1688h(sm, pf[0], one);
            mma1688h(oa[0], pf[0], __float_as_uint(m0.x));
            mma1688h(oa[1], pf[0], __float_as_uint(m0.y));
            mma1688h(oa[2], pf[0], __float_as_uint(m1.x));
            mma1688h(oa[3], pf[0], __float_as_uint(m1.y));
            mma16816h(sm, pf[1], pf[2], one, one);
#pragma unroll
            for (int n = 0; n < 4; n++) mma16816h(oa[n], pf[1], pf[2], vx[2 * n], vx[2 * n + 1]);
            mma16816h(sm, pf[3], pf[4], one, one);
#pragma unroll
            for (int n = 0; n < 4; n++) mma16816h(oa[n], pf[3], pf[4], vx[8 + 2 * n], vx[8 + 2 * n + 1]);
            float inv;
            asm("rcp.approx.ftz.f32 %0, %1;" : "=f"(inv) : "f"(sm[0]));
#pragma unroll
            for (int n = 0; n < 4; n++) sts32(ta.y ^ (n << 4), pack2(oa[n][0] * inv, oa[n][1] * inv));
            bar_sync(NB_C, 128);
            if (w == 0) PROF(5);
            uint32_t ob[16];
            ldsm4(ob[0], ob[1], ob[2], ob[3], ta.w);
            ldsm4(ob[8], ob[9], ob[10], ob[11], ta.w + 1024);
            ldsm4(ob[4], ob[5], ob[6], ob[7], ta.w ^ 64);
            ldsm4(ob[12], ob[13], ob[14], ob[15], (ta.w ^ 64) + 1024);
#pragma unroll
            for (int i = 4; i < 8; i++) {
                const uint4 f0 = lds128(tab + 4096 + i * 2048);
                wo[i >> 1][(i & 1) * 4][0] = f0.x; wo[i >> 1][(i & 1) * 4][1] = f0.y; wo[i >> 1][(i & 1) * 4][2] = f0.z; wo[i >> 1][(i & 1) * 4][3] = f0.w;
            }
#pragma unroll
            for (int jj = 0; jj < 2; jj++) {
                if (jj == 1 && tb.w == 0) break;
                float acc[4][4];
#pragma unroll
                for (int c = 0; c < 4; c++) { acc[c][0] = acc[c][1] = acc[c][2] = acc[c][3] = 0.f; }
#pragma unroll
                for (int k4 = 0; k4 < 4; k4++)
#pragma unroll
                    for (int c = 0; c < 4; c++) {
                        const int tl = jj * 2 + (c >> 1), ks = (c & 1) * 4 + k4;
                        mma16816(acc[c], wo[tl][ks][0], wo[tl][ks][1], wo[tl][ks][2], wo[tl][ks][3], ob[2 * ks], ob[2 * ks + 1]);
                    }
                uint4 v;
                v.x = pack2(acc[0][0] + acc[1][0], acc[0][1] + acc[1][1]);
                v.y = pack2(acc[0][2] + acc[1][2], acc[0][3] + acc[1][3]);
                v.z = pack2(acc[2][0] + acc[3][0], acc[2][1] + acc[3][1]);
                v.w = pack2(acc[2][2] + acc[3][2], acc[2][3] + acc[3][3]);
                st_async_v4(tb.x + (jj << 24), v, tb.y + (jj << 24));
            }
            if (w == 0) PROF(6);
        }
        cp_async_wait<0>();
        bar_sync(NB_C, 128);
        if (s != NSEG - 1) {
            if (w == 0 && lane == 0) { mbar_expect_tx(sb + RB_SX, 2560); mbar_expect_tx(sb + RB_V, 2048); }
            bar_arrive(NB_D, 384);
        }
#pragma unroll
        for (int i = 0; i < 2 * VK0; i++) av[i] = lds128(lane16 + R_WV + (i / VK0) * 32768 + (w * 16 + i % VK0) * 512);
    }
    {
        const uint4 tp = lds128(tab + 20480), tq = lds128(tab + 22528);
        *(uint4*)((((uint64_t)tp.y << 32) | tp.x) + (uint64_t)(NSEG - 1) * (8 * 2 * HD_ * 2)) = lds128(tq.x + 2048);
    }
    bar_sync(NB_C, 128);
    if (w == 0 && lane == 0) red_release(&g_flags[F_MEM + NRB - 1], 1);
}

__global__ void __launch_bounds__(384, 1) k_rec(const RecParams p) {
    extern __shared__ __align__(1024) unsigned char smem_raw[];
    const uint32_t sb = __shfl_sync(~0u, smem_u32(smem_raw), 0);
    const int warp = __shfl_sync(~0u, threadIdx.x >> 5, 0);
    int lane; asm volatile("mov.u32 %0, %%laneid;" : "=r"(lane));
    const int crank = blockIdx.x & 15, slot = blockIdx.x >> 4;
    asm volatile("griddepcontrol.launch_dependents;");
    if (crank == 0 && warp == 1 && lane < 4) {
        const unsigned int* q = lane < 2 ? &g_F[65536 + lane * 1024 + slot * 64] : &g_flags[F_SIDE + (lane - 2) * 32];
        asm volatile("prefetch.global.L2 [%0];" :: "l"(q));
    }
    if (threadIdx.x == 0) {
        mbar_init(sb + RB_SX, 1); mbar_init(sb + RB_V, 1); mbar_init(sb + RB_E, 1); mbar_init(sb + RB_A, 1); mbar_init(sb + RB_A1, 1); mbar_init(sb + RB_ROLE, 1);
        asm volatile("fence.mbarrier_init.release.cluster;" ::: "memory");
        mbar_expect_tx(sb + RB_SX, 2560);
        mbar_expect_tx(sb + RB_E, 4096);
        mbar_expect_tx(sb + RB_V, 2048);
        mbar_expect_tx(sb + RB_A, 4096);
        mbar_expect_tx(sb + RB_A1, 4096);
        mbar_expect_tx(sb + RB_ROLE, 4);
    }
    asm volatile("barrier.cluster.arrive.relaxed.aligned;\nbarrier.cluster.wait.aligned;" ::: "memory");
    unsigned role = 0;
    if (crank == 0 && threadIdx.x == 0 && !p.only_pre) {
        unsigned x = 0;
        int tm[2] = {0x7fffffff, 0x7fffffff};
#pragma unroll 1
        for (int i = 0; i < 6; i++) {
            const uint32_t t0 = clk32();
            x = atomicAdd(&g_F[65536 + (i & 1) * 1024 + slot * 64 + (x >> 31)], 0u) & 0x7fffffffu;
            if (x == 0x7654321u) sts32(sb + R_BAR + 56, x);
            const int dt = (int)(clk32() - t0);
            if (i >= 2) { if (i & 1) tm[1] = min(tm[1], dt); else tm[0] = min(tm[0], dt); }
        }
        const int side = tm[1] > tm[0];
        const unsigned old = atomicAdd(&g_flags[F_SIDE + side * 32], 1u);
        unsigned c0, c1; int gd = 0;
#pragma unroll 1
        do { c0 = ldg_relaxed32(&g_flags[F_SIDE]); c1 = ldg_relaxed32(&g_flags[F_SIDE + 32]); } while ((int)(c0 + c1) < p.ncl && ++gd < 64 * SPIN_LIMIT);
        const int big = c1 > c0;
        role = side == big ? old : (big ? c1 : c0) + old;
        role |= (big ^ 1) << 8;
    }
    __syncwarp();
    if (crank == 0 && warp == 0 && !p.only_pre) {
        role = __shfl_sync(~0u, role, 0);
        if (lane < 16)
            asm volatile("st.async.weak.shared::cluster.mbarrier::complete_tx::bytes.u32 [%0], %1, [%2];"
                         :: "r"(mapa_u32(sb + R_BAR + 48, lane)), "r"(role), "r"(mapa_u32(sb + RB_ROLE, lane)) : "memory");
    }
    if (warp >= 4) {
        const int w8 = warp - 4, nblk = gridDim.x;
        const int cq = lane & 3, rg = w8 * 8 + (lane >> 2);
        const uint32_t red = sb + R_VP;
        const int row0 = blockIdx.x * 8 + w8;
        const uint4* xr = (const uint4*)(p.x + (size_t)row0 * D_);
        uint4 xa = __ldg(xr + lane), xb = __ldg(xr + 32 + lane);
#pragma unroll 1
        for (int sl = blockIdx.x; sl < 96; sl += nblk) {
            uint4 wv[8];
#pragma unroll
            for (int i = 0; i < 8; i++) wv[i] = __ldg((const uint4*)(p.w_mod + (size_t)(rg * 8 + i) * (6 * D_) + sl * 32 + cq * 8));
            const uint32_t cw = __ldg((const uint32_t*)(p.c + rg * 8) + cq);
            const float cl = bflo(cw), ch = bfhi(cw);
            const uint32_t sw = pack2(__fdividef(cl, 1.f + __expf(-cl)), __fdividef(ch, 1.f + __expf(-ch)));
            float a[8];
#pragma unroll
            for (int i = 0; i < 8; i++) a[i] = 0.f;
#pragma unroll
            for (int i = 0; i < 8; i++) {
                const uint32_t sv = __shfl_sync(~0u, sw, (lane & 28) + (i >> 1));
                const float cv = (i & 1) ? bfhi(sv) : bflo(sv);
                a[0] = fmaf(cv, bflo(wv[i].x), a[0]); a[1] = fmaf(cv, bfhi(wv[i].x), a[1]); a[2] = fmaf(cv, bflo(wv[i].y), a[2]); a[3] = fmaf(cv, bfhi(wv[i].y), a[3]);
                a[4] = fmaf(cv, bflo(wv[i].z), a[4]); a[5] = fmaf(cv, bfhi(wv[i].z), a[5]); a[6] = fmaf(cv, bflo(wv[i].w), a[6]); a[7] = fmaf(cv, bfhi(wv[i].w), a[7]);
            }
#pragma unroll
            for (int i = 0; i < 8; i++) { a[i] += __shfl_xor_sync(~0u, a[i], 4); a[i] += __shfl_xor_sync(~0u, a[i], 8); a[i] += __shfl_xor_sync(~0u, a[i], 16); }
            if (lane < 4) {
                sts128(red + w8 * 128 + lane * 32, make_uint4(__float_as_uint(a[0]), __float_as_uint(a[1]), __float_as_uint(a[2]), __float_as_uint(a[3])));
                sts128(red + w8 * 128 + lane * 32 + 16, make_uint4(__float_as_uint(a[4]), __float_as_uint(a[5]), __float_as_uint(a[6]), __float_as_uint(a[7])));
            }
            bar_sync(NB_B, 256);
            if (w8 == 0) {
                float v = 0.f;
#pragma unroll
                for (int i = 0; i < 8; i++) v += lds32f(red + i * 128 + lane * 4);
                g_mod[sl * 32 + lane] = __float2bfloat16_rn(v);
                __syncwarp();
                if (lane == 0) red_release(&g_flags[F_MOD + (sl >= 32)], 1);
            }
            bar_sync(NB_B, 256);
        }
        uint32_t c1[8], sm[8];
        int row = row0;
#pragma unroll 1
        while (true) {
            const uint32_t v[8] = {xa.x, xa.y, xa.z, xa.w, xb.x, xb.y, xb.z, xb.w};
            uint32_t mu2, r[8]; float rden;
            ln_stats(v, mu2, rden);
            if (row == row0) {
                if (lane == 0) wait_flag(F_MOD, 32);
                __syncwarp();
                load_mod8(g_mod + D_, lane, c1);
                load_mod8(g_mod, lane, sm);
#pragma unroll
                for (int i = 0; i < 8; i++) c1[i] = hadd2(c1[i], 0x3F803F80u);
            } else if (row + 512 < S_) {
                xr = (const uint4*)(p.x + (size_t)(row + 512) * D_); xa = __ldg(xr + lane); xb = __ldg(xr + 32 + lane);
            }
            ln_apply(v, mu2, rden, c1, sm, r);
            uint4* hr = (uint4*)(g_h + (size_t)row * D_);
            hr[lane] = make_uint4(r[0], r[1], r[2], r[3]); hr[32 + lane] = make_uint4(r[4], r[5], r[6], r[7]);
            bar_sync(NB_B, 256);
            if (w8 == (row >> 7 & 7) && lane == 0) red_release(&g_flags[F_H + (row >> 7)], 1);
            __syncwarp();
            if (row == row0) {
                if (!p.only_pre) mbar_wait(sb + RB_ROLE, 0);
                const int cl = p.only_pre ? slot : (int)(lds32(sb + R_BAR + 48) & 255);
                row = cl < 4 ? (nblk + cl * 16 + crank) * 8 + w8 : S_;
                if (row < S_) { xr = (const uint4*)(p.x + (size_t)row * D_); xa = __ldg(xr + lane); xb = __ldg(xr + 32 + lane); }
            } else {
                row += 512;
            }
            if (row >= S_) break;
        }
    }
    if (p.only_pre) return;
    mbar_wait(sb + RB_ROLE, 0);
    const int rolew = __shfl_sync(~0u, lds32(sb + R_BAR + 48), 0);
    const int cl = rolew & 255;
    if (cl >= 4) return;
    const int cta = cl * 16 + crank;
    if (warp < 8) rec_qk(p, sb, cta, warp, lane, rolew >> 8);
    else rec_vo(p, sb, cta, warp, lane);
}

enum { J_KV = 0, J_QA = 1, J_O = 2, J_LN = 3, J_UP = 4, J_DN = 5, J_LN1 = 6, J_MOD = 7, J_UP2 = 8, J_END = 9 };
constexpr int NJ_O = 2 * OSPLIT, NJ_O2 = 2 * OSPLIT2, NJ_LN = 8, NJ_LN2 = 16, NJ_UP = 14, NJ_UP2 = 28, NJ_DN = 8, NJ_LN1 = 8;
constexpr uint64_t pk8(int a, int b, int c, int d, int e, int f, int g, int h) {
    return (uint64_t)a | ((uint64_t)b << 8) | ((uint64_t)c << 16) | ((uint64_t)d << 24) | ((uint64_t)e << 32) | ((uint64_t)f << 40) | ((uint64_t)g << 48) | ((uint64_t)h << 56);
}
constexpr uint64_t NJ_C = pk8(32, 16, NJ_O, NJ_LN, NJ_UP, NJ_DN, 0, 0), NJ_F = pk8(32, 16, NJ_O2, NJ_LN2, NJ_UP2, NJ_DN, 0, 0);
constexpr uint64_t TG_C = pk8(2 * NJ_LN1, 64, 32, 2 * NJ_O, 2 * NJ_LN, 2 * NJ_UP, 32, 0), TG_F = pk8(2 * NJ_LN1, 64, 32, 2 * NJ_O2, 2 * NJ_LN2, 2 * NJ_UP2, 32, 0);
constexpr uint64_t NJ_L = pk8(32, 32, 2 * OSPLIT3, NJ_LN2, NJ_UP2, NJ_DN, 0, 0), TG_L = pk8(2 * NJ_LN1, 64, 64, 4 * OSPLIT3, 2 * NJ_LN2, 2 * NJ_UP2, 32, 0);
__device__ __forceinline__ uint64_t nj_tab(int rb) { return rb < FINE_RB ? NJ_C : (rb < NRB - 1 ? NJ_F : NJ_L); }
__device__ __forceinline__ uint64_t tg_tab(int rb) { return rb < FINE_RB ? TG_C : (rb < NRB - 1 ? TG_F : TG_L); }
__device__ __forceinline__ int o_nk(int rb) { return rb < FINE_RB ? 64 / OSPLIT : (rb < NRB - 1 ? 64 / OSPLIT2 : 64 / OSPLIT3); }
constexpr uint64_t PRIO = pk8(4, 10, 9, 8, 7, 6, 3, 0);
__device__ __forceinline__ int pick_job(int lane, int qmask, int& idx) {
    const int rb = lane & 15, half = lane >> 4;
    const uint64_t nj = nj_tab(rb) >> (8 * half);
    const uint64_t tg = tg_tab(rb) >> (8 * half);
    const unsigned* cp = &g_flags[F_CLAIM + half * 32 + rb];
    const unsigned* dp = &g_flags[half * 32 + rb];
    int gd = 0;
#pragma unroll 1
    while (true) {
        const unsigned c0 = ldg_relaxed32(cp), c1 = ldg_relaxed32(cp + 64), c2 = ldg_relaxed32(cp + 128);
        const unsigned d0 = ldg_relaxed32(dp - (half && rb ? 1 : 0)), d1 = ldg_relaxed32(dp + 64), d2 = ldg_relaxed32(dp + 128);
        const unsigned cl[3] = {c0, c1, c2}, dv[3] = {d0, d1, d2};
        unsigned key = 0xffffu, key2 = 0xffffu;
        bool pre = false;
#pragma unroll
        for (int i = 0; i < 3; i++) {
            const int q = half + 2 * i;
            const bool have = ((qmask >> q) & 1) && cl[i] < (unsigned)((nj >> (16 * i)) & 255);
            bool ready = have && dv[i] >= (unsigned)((tg >> (16 * i)) & 255);
            unsigned pr = (unsigned)((PRIO >> (8 * q)) & 255);
            if (i == 0 && rb <= 1 - half) ready = have;
            if (i == 0 && half && rb >= FINE_RB) pr = 5;
            if (ready) key = min(key, (pr << 8) | (rb << 4) | q);
            if (have) key2 = min(key2, rb >= FINE_RB ? (0x100u | (q << 4) | rb) : (i == 0 ? 0u : 0x1000u));
            pre |= have && i == 0 && !half;
        }
        const bool anypre = __any_sync(~0u, pre);
        if (anypre && (key & 15) == J_QA) key = 0xffffu;
        key = __reduce_min_sync(~0u, key);
        key2 = __reduce_min_sync(~0u, key2);
        if (key2 == 0xffffu) return J_END;
        int pq, prb;
        if (key != 0xffffu) { pq = key & 15; prb = (key >> 4) & 15; }
        else if (key2 >= 0x120u && key2 < 0x1000u) { pq = (key2 >> 4) & 15; prb = key2 & 15; }
        else {
            __nanosleep(IDLE_NS);
            if (++gd > 16 * SPIN_LIMIT) { TIMEOUT(5, 0); return J_END; }
            continue;
        }
        int c = 0;
        if (lane == 0) c = (int)atomicAdd(&g_flags[F_CLAIM + pq * 32 + prb], 1u);
        c = __shfl_sync(~0u, c, 0);
        if (c < (int)((nj_tab(prb) >> (8 * pq)) & 255)) {
            idx = pq * 512 + prb * 32 + c;
            int acq = 0;
            if (pq != J_QA && pq < J_LN1) {
                if (lane == 0 && ld_acquire(&g_flags[pq * 32 + prb]) >= (unsigned)((tg_tab(prb) >> (8 * pq)) & 255)) {
                    asm volatile("fence.proxy.async.global;" ::: "memory");
                    acq = 1 << 24;
                }
            }
            return (pq == J_UP && prb >= FINE_RB ? J_UP2 : pq) | (prb << 8) | (c << 16) | acq;
        }
    }
}
__device__ __forceinline__ int op_row(int rb, int split) {
    return rb < FINE_RB ? split * S_ + rb * 128
                        : (rb < NRB - 1 ? OSPLIT * S_ + (split * (NRB - FINE_RB) + rb - FINE_RB) * 128 : OSPLIT * S_ + (OSPLIT2 * (NRB - FINE_RB) + split) * 128);
}

struct Pipe { uint32_t stage, phase; };
__device__ __forceinline__ void pipe_next(Pipe& p) { if (++p.stage == W_NST) { p.stage = 0; p.phase ^= 1; } }

__device__ __forceinline__ void scheduler(const Params& p, uint32_t sb, int lane) {
    const uint32_t bars = sb + SM_BAR;
    uint32_t ph = 0;
#pragma unroll 1
    while (true) {
        mbar_wait(bars + B_REQ, ph);
        int j = 4095;
        const int jd = pick_job(lane, p.qmask, j);
        if (lane == 0) { sts32(bars + B_NEXT, (uint32_t)jd); sts32(bars + B_NEXT + 4, (uint32_t)j); mbar_arrive(bars + B_RSP); }
        ph ^= 1;
        if (jd == J_END) break;
        __syncwarp();
    }
}

__device__ __forceinline__ void producer(const Params& p, uint32_t sb) {
    Pipe pp{0, 1};
    const uint32_t bars = sb + SM_BAR;
    uint32_t seq = 0, h_seen = 0;
    mbar_arrive(bars + B_REQ);
#pragma unroll 1
    while (true) {
        mbar_wait(bars + B_RSP, seq & 1);
        const int jd = (int)lds32(bars + B_NEXT), j = (int)lds32(bars + B_NEXT + 4);
        int left = (jd & 255) == J_DN ? 15 : ((jd & 255) == J_QA ? (((jd >> 8) & 255) == NRB - 1 ? 10 : 12) : ((jd & 255) == J_O ? o_nk((jd >> 8) & 255) : ((jd & 255) == J_LN || (jd & 255) == J_LN1 || (jd & 255) == J_MOD ? 1 : 8)));
        left = max(left - PICK_AHEAD, 1);
        TR(j, 1);
        const int type = jd & 255, rb = (jd >> 8) & 255, cb = (jd >> 16) & 255;
        const bool fine = rb >= FINE_RB, acquired = (jd >> 24) & 1;
        bool first = true;
        auto begin_stage = [&](uint32_t bytes) -> uint32_t {
            mbar_wait(bars + B_EMPTY + pp.stage * 8, pp.phase);
            if (first) { sts32(bars + B_RING + (seq & 7) * 4, (uint32_t)jd); sts32(bars + B_RING + 32 + (seq & 7) * 4, (uint32_t)j); first = false; }
            const uint32_t fb = bars + B_FULL + pp.stage * 8;
            if (bytes) mbar_expect_tx(fb, bytes); else mbar_arrive(fb);
            if (--left == 0 && type != J_END) mbar_arrive(bars + B_REQ);
            return fb;
        };
        if (type == J_END || type == J_LN || type == J_LN1 || type == J_MOD) {
            if (type == J_LN) { if (!acquired) wait_flag(F_OP + rb, (unsigned)((tg_tab(rb) >> (8 * J_LN)) & 255)); if (!(h_seen >> 31)) { wait_flag(F_MOD + 1, 64); h_seen |= 1u << 31; } }

            TR(j, 2);
            begin_stage(0); pipe_next(pp);
            seq++;
            if (type == J_END) break;
            continue;
        }
        const CUtensorMap *ta, *tb0, *tb1;
        int k0 = 0, nk = 8, n0 = cb * 256, n1 = n0 + 128, nb = 4, dep = -1;
        unsigned tgt = 0;
        switch (type) {
            case J_KV: ta = &p.tm_h; tb0 = tb1 = cb < 16 ? &p.tm_wk : &p.tm_wv; n0 = (cb & 15) * 256; n1 = n0 + 128; dep = F_H + rb; tgt = 2 * NJ_LN1; break;
            case J_QA: ta = &p.tm_h; tb0 = tb1 = &p.tm_wq; dep = F_H + rb; tgt = 2 * NJ_LN1; if (rb == NRB - 1) { n0 = (cb >> 1) * 256; n1 = n0 + 128; } break;
            case J_O: ta = &p.tm_o; tb0 = tb1 = &p.tm_wo; n0 = (cb & 1) * 256; n1 = n0 + 128; nk = o_nk(rb); k0 = (cb >> 1) * nk * 64;
                      dep = F_O + rb; tgt = rb == NRB - 1 ? 64 : 32; break;
            case J_UP: ta = &p.tm_h2; tb0 = &p.tm_wg; tb1 = &p.tm_wu; n0 = n1 = cb * 128; dep = F_H2 + rb; tgt = 2 * NJ_LN; break;
            case J_UP2: ta = &p.tm_h2; tb0 = &p.tm_wg; tb1 = &p.tm_wu; n0 = n1 = cb * 64; nb = 2; dep = F_H2 + rb; tgt = 2 * NJ_LN2; break;
            default: ta = &p.tm_act; tb0 = tb1 = &p.tm_wd; n0 = cb * 64; nk = 0; break;
        }
        const int m0 = rb * 128;
        if (type == J_DN) {
#pragma unroll 1
            for (int kb = 0; kb < 14; kb++) {
                const uint32_t fb = begin_stage(49152);
                const uint32_t st = sb + pp.stage * W_STAGE;
                const int k = kb * 128;
                tma_load2d(st + 32768, tb0, n0, k, fb);
                tma_load2d(st + 40960, tb0, n0, k + 64, fb);
                if (kb == 0) { if (!acquired) { wait_flag(F_ACT + rb, 2 * (fine ? NJ_UP2 : NJ_UP)); asm volatile("fence.proxy.async.global;" ::: "memory"); } TR(j, 2); }
                tma_load2d(st, ta, k, m0, fb);
                tma_load2d(st + 8192, ta, k, m0 + 64, fb);
                tma_load2d(st + 16384, ta, k + 64, m0, fb);
                tma_load2d(st + 24576, ta, k + 64, m0 + 64, fb);
                pipe_next(pp);
            }
        }
#pragma unroll 1
        for (int kb = 0; kb < nk; kb++) {
            const uint32_t fb = begin_stage(16384 + nb * 8192);
            const uint32_t st = sb + pp.stage * W_STAGE;
            const int k = k0 + kb * 64;
            tma_load2d(st + 16384, tb0, n0, k, fb);
            if (nb == 4) {
                tma_load2d(st + 16384 + 8192, tb0, n0 + 64, k, fb);
                tma_load2d(st + 16384 + 16384, tb1, n1, k, fb);
                tma_load2d(st + 16384 + 24576, tb1, n1 + 64, k, fb);
            } else if (nb == 2) {
                tma_load2d(st + 16384 + 8192, tb1, n1, k, fb);
            }
            if (kb == 0) {
                if (acquired && dep < 16) h_seen |= 1u << dep;
                if (dep >= 0 && !acquired && !(dep < 16 && ((h_seen >> dep) & 1))) {
                    wait_flag(dep, tgt);
                    if (type != J_O) asm volatile("fence.proxy.async.global;" ::: "memory");
                    if (dep < 16) h_seen |= 1u << dep;
                }
                TR(j, 2);
            }
            tma_load2d(st, ta, k, m0, fb);
            tma_load2d(st + 8192, ta, k, m0 + 64, fb);
            pipe_next(pp);
        }
        if (type == J_QA) {
            wait_flag(F_KV + rb, 64);
#pragma unroll 1
            for (int i = 0; i < (rb == NRB - 1 ? 2 : 4); i++) {
                const uint32_t fb = begin_stage(40960);
                const uint32_t st = sb + pp.stage * W_STAGE;
                const int col = (i & 1) * HD_ + (rb == NRB - 1 ? cb : cb * 2 + (i >> 1)) * DH_;
                tma_load2d(st, &p.tm_kv, col, m0, fb);
                tma_load2d(st + 8192, &p.tm_kv, col, m0 + 64, fb);
                tma_load2d(st + 16384, &p.tm_kv, col + 64, m0, fb);
                tma_load2d(st + 24576, &p.tm_kv, col + 64, m0 + 64, fb);
                if (i == 0) { wait_flag(F_MEM + rb, 64); asm volatile("fence.proxy.async.global;" ::: "memory"); }
                tma_load2d(st + 32768, &p.tm_kvm, col, rb * 32, fb);
                tma_load2d(st + 36864, &p.tm_kvm, col + 64, rb * 32, fb);
                pipe_next(pp);
            }
        } else if (type == J_DN) {
            const uint32_t fb = begin_stage(16384);
            const uint32_t st = sb + pp.stage * W_STAGE;
            tma_load2d(st, &p.tm_x1, n0, m0, fb);
            tma_load2d(st + 8192, &p.tm_x1, n0, m0 + 64, fb);
            pipe_next(pp);
        }
        seq++;
    }
}

__device__ __forceinline__ void store_warp(const Params& p, uint32_t sb, int wg, int lane) {
    const uint32_t bars = sb + SM_BAR;
    uint32_t seq = 0;
#pragma unroll 1
    while (true) {
        bar_sync(NB_ST + wg, 160);
        const uint32_t jd = lds32(bars + B_RING + (seq & 7) * 4);
        seq++;
        const int type = jd & 255, rb = (jd >> 8) & 255, cb = (jd >> 16) & 255;
        if (type == J_END) break;
        const uint32_t src = sb + W_STG + wg * 16384;
        const CUtensorMap* tm = nullptr; int n0 = cb * 256, nbox = 4, mrow = rb * 128 + wg * 64, flag = 0;
        switch (type) {
            case J_KV: tm = &p.tm_kv; flag = F_KV + rb; break;
            case J_QA: tm = &p.tm_o; flag = F_O + rb; if (rb == NRB - 1) { n0 = cb * 128; nbox = 2; } break;
            case J_O: tm = &p.tm_op; n0 = (cb & 1) * 256; mrow = op_row(rb, cb >> 1) + wg * 64; flag = F_OP + rb; break;
            case J_LN: flag = F_H2 + rb; nbox = 0; break;
            case J_LN1: flag = F_H + rb; nbox = 0; break;
            case J_MOD: flag = F_MOD + rb; nbox = 0; break;
            case J_UP: tm = &p.tm_act; n0 = cb * 128; nbox = 2; flag = F_ACT + rb; break;
            case J_UP2: tm = &p.tm_act; n0 = cb * 64; nbox = 1; flag = F_ACT + rb; break;
            default: tm = &p.tm_out; n0 = cb * 64; nbox = 1; flag = -1; break;
        }
        if (nbox == 4) {
            if (lane == 0) {
                tma_store2d(tm, src, n0, mrow);
                tma_store2d(tm, src + 8192, n0 + 64, mrow);
                bulk_commit();
                asm volatile("cp.async.bulk.wait_group.read 0;" ::: "memory");
                mbar_arrive(bars + B_STGFREE + wg * 8);
            }
            __syncwarp();
            bar_sync(NB_ST + wg, 160);
            n0 += 128; nbox = 2;
        }
        if (lane == 0) {
            if (nbox) {
                tma_store2d(tm, src, n0, mrow);
                if (nbox == 2) tma_store2d(tm, src + 8192, n0 + 64, mrow);
                bulk_commit();
                asm volatile("cp.async.bulk.wait_group.read 0;" ::: "memory");
                mbar_arrive(bars + B_STGFREE + wg * 8);
                bulk_wait0();
                if (flag >= 0) asm volatile("red.relaxed.gpu.global.add.u32 [%0], 1;" :: "l"(&g_flags[flag]) : "memory");
            } else {
                mbar_arrive(bars + B_STGFREE + wg * 8);
                red_release(&g_flags[flag], 1);
            }
        }
        __syncwarp();
    }
}

__device__ __forceinline__ float gelu_tanh(float x) {
    const float t = x * fmaf(-0.10294324397f, x * x, -2.30220819814f);
    float r; asm("rcp.approx.ftz.f32 %0, %1;" : "=f"(r) : "f"(1.f + ex2(t)));
    return x * r;
}

#define CTR(i) do {} while (0)

__device__ __forceinline__ void ln2_row(const Params& p, int rb, int r, int lane) {
    const int row = rb * 128 + r, nsplit = 64 / o_nk(rb);
    const uint4* xr = (const uint4*)(p.x + (size_t)row * D_);
    const uint4 xa = __ldg(xr + lane), xb = __ldg(xr + 32 + lane);
    uint32_t ga[8], c1[8], sm[8];
    load_mod8(g_mod + 2 * D_, lane, ga);
    load_mod8(g_mod + 4 * D_, lane, c1);
    load_mod8(g_mod + 3 * D_, lane, sm);
    float a[16];
#pragma unroll
    for (int i = 0; i < 16; i++) a[i] = 0.f;
    const uint4* src = (const uint4*)(g_op + (size_t)(op_row(rb, 0) + r) * D_) + lane;
    const int sstride = (op_row(rb, 1) - op_row(rb, 0)) * (D_ / 8);
    uint4 u[2][8];
#pragma unroll
    for (int sp = 0; sp < 4; sp++) { u[0][2 * sp] = __ldcg(src + sp * sstride); u[0][2 * sp + 1] = __ldcg(src + sp * sstride + 32); }
    if (nsplit > 4) {
#pragma unroll
        for (int sp = 0; sp < 4; sp++) { u[1][2 * sp] = __ldcg(src + (4 + sp) * sstride); u[1][2 * sp + 1] = __ldcg(src + (4 + sp) * sstride + 32); }
    }
#pragma unroll 1
    for (int s0 = 0; s0 < nsplit; s0 += 4) {
#pragma unroll
        for (int sp = 0; sp < 8; sp++) {
            float* q = a + (sp & 1) * 8;
            const uint4 w = u[0][sp];
            q[0] += bflo(w.x); q[1] += bfhi(w.x); q[2] += bflo(w.y); q[3] += bfhi(w.y);
            q[4] += bflo(w.z); q[5] += bfhi(w.z); q[6] += bflo(w.w); q[7] += bfhi(w.w);
            u[0][sp] = u[1][sp];
        }
        if (s0 + 8 < nsplit) {
#pragma unroll
            for (int sp = 0; sp < 4; sp++) { u[1][2 * sp] = __ldcg(src + (s0 + 8 + sp) * sstride); u[1][2 * sp + 1] = __ldcg(src + (s0 + 8 + sp) * sstride + 32); }
        }
    }
    const uint32_t xv[8] = {xa.x, xa.y, xa.z, xa.w, xb.x, xb.y, xb.z, xb.w};
    uint32_t v[8], r8[8];
#pragma unroll
    for (int i = 0; i < 8; i++) v[i] = hadd2(xv[i], hmul2(ga[i], pack2(a[2 * i], a[2 * i + 1])));
    uint4* x1r = (uint4*)(g_x1 + (size_t)row * D_);
    x1r[lane] = make_uint4(v[0], v[1], v[2], v[3]); x1r[32 + lane] = make_uint4(v[4], v[5], v[6], v[7]);
    uint32_t mu2; float rden;
    ln_stats(v, mu2, rden);
#pragma unroll
    for (int i = 0; i < 8; i++) c1[i] = hadd2(c1[i], 0x3F803F80u);
    ln_apply(v, mu2, rden, c1, sm, r8);
    uint4* hr = (uint4*)(g_h2 + (size_t)row * D_);
    hr[lane] = make_uint4(r8[0], r8[1], r8[2], r8[3]); hr[32 + lane] = make_uint4(r8[4], r8[5], r8[6], r8[7]);
}

__device__ __forceinline__ void consumer(const Params& p, uint32_t sb, int warp, int lane) {
    const uint32_t bars = sb + SM_BAR;
    const int wg = warp >> 2, wl = warp & 3;
    const uint32_t l7 = lane & 7, l8 = lane >> 3, g = lane >> 2, t = lane & 3;
    Pipe pp{0, 0};
    uint32_t seq = 0, stg_phase = 1;
    const int srow = wl * 16 + l7 + (l8 & 1) * 8;
    const uint32_t stg_base = sb + W_STG + wg * 16384 + srow * 128;
    const uint32_t sx = ((lane >> 4) ^ (srow & 7)) << 4;
#pragma unroll 1
    while (true) {
        mbar_wait(bars + B_FULL + pp.stage * 8, pp.phase);
        const uint32_t jd = lds32(bars + B_RING + (seq & 7) * 4);
        CTR(3);
        seq++;
        const int type = jd & 255, rb = (jd >> 8) & 255, cb = (jd >> 16) & 255;
        if (type == J_END) { mbar_wait(bars + B_STGFREE + wg * 8, stg_phase); bar_arrive(NB_ST + wg, 160); break; }
        if (type == J_LN) {
            __syncwarp();
            if (lane == 0) mbar_arrive(bars + B_EMPTY + pp.stage * 8);
            pipe_next(pp);
            const int nr = rb >= FINE_RB ? 1 : 2;
#pragma unroll 1
            for (int rr = 0; rr < nr; rr++) ln2_row(p, rb, (cb * 8 + warp) * nr + rr, lane);
            mbar_wait(bars + B_STGFREE + wg * 8, stg_phase); stg_phase ^= 1;
            CTR(4); CTR(5);
            bar_arrive(NB_ST + wg, 160);
            continue;
        }
        if (type == J_DN || type == J_UP2) {
            float acc[64];
#pragma unroll
            for (int i = 0; i < 64; i++) acc[i] = 0.f;
            if (type == J_DN) {
#pragma unroll 1
                for (int kb = 0; kb < 14; kb++) {
                    if (kb) mbar_wait(bars + B_FULL + pp.stage * 8, pp.phase);
                    const uint32_t st = sb + pp.stage * W_STAGE;
                    const uint64_t da = mkdesc(st + wg * 8192, 16, 1024), db = mkdesc(st + 32768, 8192, 1024);
                    wg_fence();
#pragma unroll
                    for (int ks = 0; ks < 8; ks++) wgmma_n64(acc, da + (ks >> 2) * 1024 + (ks & 3) * 2, db + ks * 128);
                    wg_commit();
                    wg_wait0();
                    if (lane == 0) mbar_arrive(bars + B_EMPTY + pp.stage * 8);
                    pipe_next(pp);
                }
            } else {
#pragma unroll 1
                for (int kb = 0; kb < 8; kb++) {
                    if (kb) mbar_wait(bars + B_FULL + pp.stage * 8, pp.phase);
                    const uint32_t st = sb + pp.stage * W_STAGE;
                    const uint64_t da = mkdesc(st + wg * 8192, 16, 1024), db = mkdesc(st + 16384, 8192, 1024);
                    wg_fence();
#pragma unroll
                    for (int ks = 0; ks < 4; ks++) wgmma_n128(acc, da + ks * 2, db + ks * 128, 1);
                    wg_commit();
                    wg_wait0();
                    if (lane == 0) mbar_arrive(bars + B_EMPTY + pp.stage * 8);
                    pipe_next(pp);
                }
            }
            CTR(4);
            if (type == J_UP2) {
                mbar_wait(bars + B_STGFREE + wg * 8, stg_phase); stg_phase ^= 1;
#pragma unroll
                for (int j = 0; j < 4; j++) {
                    uint32_t r[4];
#pragma unroll
                    for (int q = 0; q < 4; q++) {
                        const uint32_t gw = pack2(acc[8 * j + 2 * q], acc[8 * j + 2 * q + 1]);
                        const uint32_t uw = pack2(acc[32 + 8 * j + 2 * q], acc[32 + 8 * j + 2 * q + 1]);
                        r[q] = hmul2(pack2(gelu_tanh(bflo(gw)), gelu_tanh(bfhi(gw))), uw);
                    }
                    stsm4(stg_base + (sx ^ (j << 5)), r[0], r[1], r[2], r[3]);
                }
            } else {
                mbar_wait(bars + B_FULL + pp.stage * 8, pp.phase);
                const uint32_t st = sb + pp.stage * W_STAGE;
                mbar_wait(bars + B_STGFREE + wg * 8, stg_phase); stg_phase ^= 1;
                const uint32_t* gb = (const uint32_t*)(g_mod + 5 * D_ + cb * 64) + t;
                const uint32_t xa = st + wg * 8192 + (wl * 16 + g) * 128 + (g << 4) + t * 4;
#pragma unroll
                for (int j = 0; j < 4; j++) {
                    uint32_t r[4];
#pragma unroll
                    for (int q = 0; q < 4; q++) {
                        const int nt = 2 * j + (q >> 1);
                        const uint32_t xw = lds32((xa ^ ((nt & 7) << 4)) + (nt >> 3) * 16384 + (q & 1) * 1024);
                        r[q] = hadd2(xw, hmul2(__ldcg(gb + nt * 4), pack2(acc[8 * j + 2 * q], acc[8 * j + 2 * q + 1])));
                    }
                    stsm4(stg_base + (j >> 2) * 8192 + (sx ^ ((2 * j & 7) << 4)), r[0], r[1], r[2], r[3]);
                }
                __syncwarp();
                if (lane == 0) mbar_arrive(bars + B_EMPTY + pp.stage * 8);
                pipe_next(pp);
            }
            fence_async_smem();
            CTR(5);
            bar_arrive(NB_ST + wg, 160);
            continue;
        }
        float acc[128];
#pragma unroll
        for (int i = 0; i < 128; i++) acc[i] = 0.f;
        const int nk = type == J_O ? o_nk(rb) : 8;
#pragma unroll 1
        for (int kb = 0; kb < nk; kb++) {
            if (kb) mbar_wait(bars + B_FULL + pp.stage * 8, pp.phase);
            const uint32_t st = sb + pp.stage * W_STAGE;
            const uint64_t da = mkdesc(st + wg * 8192, 16, 1024), db = mkdesc(st + 16384, 8192, 1024);
            wg_fence();
#pragma unroll
            for (int ks = 0; ks < 4; ks++) wgmma_n256(acc, da + ks * 2, db + ks * 128, 1);
            wg_commit();
            wg_wait0();
            if (lane == 0) mbar_arrive(bars + B_EMPTY + pp.stage * 8);
            pipe_next(pp);
        }
        CTR(4);
        if (type == J_QA) {
            uint32_t qf[64];
#pragma unroll
            for (int i = 0; i < 64; i++) qf[i] = pack2(acc[2 * i], acc[2 * i + 1]);
            const int sg = warp >> 1, half = warp & 1;
            const float sc = 0.08838834764831845f * 1.4426950408889634f;
            const uint32_t xoff = (sg >> 1) * 8192 + ((sg & 1) * 32 + l7) * 128;
            const uint32_t moff = 32768 + (sg * 8 + l7) * 128;
            const uint32_t kch = (l8 ^ l7) << 4;
            const uint32_t vch = ((l8 & 1) ^ l7) << 4;
            if (rb == NRB - 1 && (cb & 1)) {
#pragma unroll
                for (int i = 0; i < 32; i++) qf[i] = qf[32 + i];
            }
#pragma unroll 1
            for (int hh = rb == NRB - 1; hh < 2; hh++) {
                mbar_wait(bars + B_FULL + pp.stage * 8, pp.phase);
                uint32_t st = sb + pp.stage * W_STAGE;
                float sa[5][4];
#pragma unroll
                for (int n = 0; n < 5; n++) sa[n][0] = sa[n][1] = sa[n][2] = sa[n][3] = 0.f;
#pragma unroll
                for (int i = 0; i < 4; i++) {
                    const uint32_t* q = qf + i * 8;
                    uint32_t kk[5][4];
                    ldsm4(kk[0][0], kk[0][1], kk[0][2], kk[0][3], st + moff + (i >> 1) * 4096 + (kch ^ ((i & 1) * 64)));
#pragma unroll
                    for (int n = 1; n < 5; n++)
                        ldsm4(kk[n][0], kk[n][1], kk[n][2], kk[n][3], st + xoff + (n - 1) * 1024 + (i >> 1) * 16384 + (kch ^ ((i & 1) * 64)));
#pragma unroll
                    for (int n = 0; n < 5; n++) mma16816(sa[n], q[0], q[1], q[2], q[3], kk[n][0], kk[n][1]);
#pragma unroll
                    for (int n = 0; n < 5; n++) mma16816(sa[n], q[4], q[5], q[6], q[7], kk[n][2], kk[n][3]);
                }
                __syncwarp();
                if (lane == 0) mbar_arrive(bars + B_EMPTY + pp.stage * 8);
                pipe_next(pp);
                const int iq0 = half * 16 + g - 2 * t, iq1 = iq0 + 8;
                float m0 = fmaxf(sa[0][0], sa[0][1]), m1 = fmaxf(sa[0][2], sa[0][3]);
#pragma unroll
                for (int n = 1; n < 5; n++) {
#pragma unroll
                    for (int e = 0; e < 2; e++) {
                        const int jx = (n - 1) * 8 + e;
                        if (jx > iq0) sa[n][e] = -3.0e38f;
                        if (jx > iq1) sa[n][2 + e] = -3.0e38f;
                        m0 = fmaxf(m0, sa[n][e]); m1 = fmaxf(m1, sa[n][2 + e]);
                    }
                }
                m0 = fmaxf(m0, __shfl_xor_sync(~0u, m0, 1)); m1 = fmaxf(m1, __shfl_xor_sync(~0u, m1, 1));
                m0 = fmaxf(m0, __shfl_xor_sync(~0u, m0, 2)); m1 = fmaxf(m1, __shfl_xor_sync(~0u, m1, 2));
                m0 *= -sc; m1 *= -sc;
                float l0 = 0.f, l1 = 0.f;
                uint32_t p0[5], p1[5];
#pragma unroll
                for (int n = 0; n < 5; n++) {
                    const float e0 = ex2(fmaf(sa[n][0], sc, m0)), e1 = ex2(fmaf(sa[n][1], sc, m0));
                    const float e2 = ex2(fmaf(sa[n][2], sc, m1)), e3 = ex2(fmaf(sa[n][3], sc, m1));
                    l0 += e0 + e1; l1 += e2 + e3;
                    p0[n] = pack2(e0, e1); p1[n] = pack2(e2, e3);
                }
                l0 += __shfl_xor_sync(~0u, l0, 1); l1 += __shfl_xor_sync(~0u, l1, 1);
                l0 += __shfl_xor_sync(~0u, l0, 2); l1 += __shfl_xor_sync(~0u, l1, 2);
                const float i0 = __fdividef(1.f, l0), i1 = __fdividef(1.f, l1);
                mbar_wait(bars + B_FULL + pp.stage * 8, pp.phase);
                st = sb + pp.stage * W_STAGE;
                mbar_wait(bars + B_STGFREE + wg * 8, stg_phase); stg_phase ^= 1;
#pragma unroll
                for (int i = 0; i < 32; i++) qf[i] = qf[32 + i];
#pragma unroll 1
                for (int bx = 0; bx < 2; bx++) {
                    float o[8][4];
                    uint32_t vm[8], v0[4][4], v1[4][4];
#pragma unroll
                    for (int ep = 0; ep < 4; ep++) {
                        ldsm2t(vm[2 * ep], vm[2 * ep + 1], st + moff + bx * 4096 + (vch ^ (ep << 5)));
                        const uint32_t va = st + xoff + (l8 >> 1) * 1024 + bx * 16384 + (vch ^ (ep << 5));
                        ldsm4t(v0[ep][0], v0[ep][1], v0[ep][2], v0[ep][3], va);
                        ldsm4t(v1[ep][0], v1[ep][1], v1[ep][2], v1[ep][3], va + 2048);
                    }
#pragma unroll
                    for (int n = 0; n < 8; n++) { o[n][0] = o[n][1] = o[n][2] = o[n][3] = 0.f; mma16816(o[n], p0[0], p1[0], p0[1], p1[1], vm[n], v0[n >> 1][n & 1]); }
#pragma unroll
                    for (int n = 0; n < 8; n++) mma16816(o[n], p0[2], p1[2], p0[3], p1[3], v0[n >> 1][2 + (n & 1)], v1[n >> 1][n & 1]);
#pragma unroll
                    for (int n = 0; n < 8; n++) mma1688(o[n], p0[4], p1[4], v1[n >> 1][2 + (n & 1)]);
#pragma unroll
                    for (int ep = 0; ep < 4; ep++)
                        stsm4(stg_base + bx * 8192 + (sx ^ (ep << 5)),
                              pack2(o[2 * ep][0] * i0, o[2 * ep][1] * i0), pack2(o[2 * ep][2] * i1, o[2 * ep][3] * i1),
                              pack2(o[2 * ep + 1][0] * i0, o[2 * ep + 1][1] * i0), pack2(o[2 * ep + 1][2] * i1, o[2 * ep + 1][3] * i1));
                }
                __syncwarp();
                if (lane == 0) mbar_arrive(bars + B_EMPTY + pp.stage * 8);
                pipe_next(pp);
                if (hh == 0) { fence_async_smem(); bar_arrive(NB_ST + wg, 160); }
            }
        } else if (type == J_UP) {
            mbar_wait(bars + B_STGFREE + wg * 8, stg_phase); stg_phase ^= 1;
#pragma unroll
            for (int j = 0; j < 8; j++) {
                uint32_t r[4];
#pragma unroll
                for (int q = 0; q < 4; q++) {
                    const uint32_t gw = pack2(acc[8 * j + 2 * q], acc[8 * j + 2 * q + 1]);
                    const uint32_t uw = pack2(acc[64 + 8 * j + 2 * q], acc[64 + 8 * j + 2 * q + 1]);
                    r[q] = hmul2(pack2(gelu_tanh(bflo(gw)), gelu_tanh(bfhi(gw))), uw);
                }
                stsm4(stg_base + (j >> 2) * 8192 + (sx ^ ((2 * j & 7) << 4)), r[0], r[1], r[2], r[3]);
            }
        } else {
#pragma unroll
            for (int rd = 0; rd < 2; rd++) {
                mbar_wait(bars + B_STGFREE + wg * 8, stg_phase); stg_phase ^= 1;
#pragma unroll
                for (int j = rd * 8; j < rd * 8 + 8; j++)
                    stsm4(stg_base + ((j >> 2) & 1) * 8192 + (sx ^ ((2 * j & 7) << 4)),
                          pack2(acc[8 * j], acc[8 * j + 1]), pack2(acc[8 * j + 2], acc[8 * j + 3]),
                          pack2(acc[8 * j + 4], acc[8 * j + 5]), pack2(acc[8 * j + 6], acc[8 * j + 7]));
                if (rd == 0) { fence_async_smem(); bar_arrive(NB_ST + wg, 160); }
            }
        }
        fence_async_smem();
        CTR(5);
        bar_arrive(NB_ST + wg, 160);
    }
}

__global__ void __launch_bounds__(384, 1) k_work(const __grid_constant__ Params p) {
    extern __shared__ __align__(1024) unsigned char smem_raw[];
    const uint32_t sb = smem_u32(smem_raw);
    if (sb & 1023) __trap();
    const int warp = __shfl_sync(~0u, threadIdx.x >> 5, 0);
    int lane; asm volatile("mov.u32 %0, %%laneid;" : "=r"(lane));
    if (threadIdx.x == 0) {
        const uint32_t bars = sb + SM_BAR;
        for (int i = 0; i < W_NST; i++) { mbar_init(bars + B_FULL + i * 8, 1); mbar_init(bars + B_EMPTY + i * 8, 8); }
        mbar_init(bars + B_STGFREE, 1); mbar_init(bars + B_STGFREE + 8, 1); mbar_init(bars + B_REQ, 1); mbar_init(bars + B_RSP, 1);
        asm volatile("fence.mbarrier_init.release.cluster;" ::: "memory");
    }
    __syncthreads();
    if (warp < 8) {
        asm volatile("setmaxnreg.inc.sync.aligned.u32 224;");
        consumer(p, sb, warp, lane);
    } else {
        asm volatile("setmaxnreg.dec.sync.aligned.u32 56;");
        if (warp == 8) { if (lane == 0) producer(p, sb); }
        else if (warp < 11) store_warp(p, sb, warp - 9, lane);
        else scheduler(p, sb, lane);
        __syncwarp();
        bar_sync(NB_W0, 128);
        if (warp == 8 && p.qmask == 0xff) {
            unsigned last = 0;
            if (lane == 0) { __threadfence(); last = atomicAdd(&g_flags[F_DONE], 1u) == gridDim.x - 1; }
            if (__shfl_sync(~0u, last, 0))
                for (int i = lane; i < F_TOTAL; i += 32) g_flags[i] = 0;
        }
    }
}

typedef CUresult (*EncodeFn)(CUtensorMap*, CUtensorMapDataType, cuuint32_t, void*, const cuuint64_t*, const cuuint64_t*,
                             const cuuint32_t*, const cuuint32_t*, CUtensorMapInterleave, CUtensorMapSwizzle,
                             CUtensorMapL2promotion, CUtensorMapFloatOOBfill);

static void make_map(EncodeFn enc, CUtensorMap* m, const void* ptr, uint64_t rows, uint64_t cols, uint32_t box_rows) {
    cuuint64_t dims[2] = {cols, rows};
    cuuint64_t strides[1] = {cols * 2};
    cuuint32_t box[2] = {64, box_rows};
    cuuint32_t es[2] = {1, 1};
    enc(m, CU_TENSOR_MAP_DATA_TYPE_BFLOAT16, 2, const_cast<void*>(ptr), dims, strides, box, es, CU_TENSOR_MAP_INTERLEAVE_NONE,
        CU_TENSOR_MAP_SWIZZLE_128B, CU_TENSOR_MAP_L2_PROMOTION_L2_256B, CU_TENSOR_MAP_FLOAT_OOB_FILL_NONE);
}
template <typename T> static void* sym_addr(T& sym) { void* p = nullptr; cudaGetSymbolAddress(&p, sym); return p; }

extern "C" void kernel_launch(void* const* d_in, const int* in_sizes, int n_in, void* d_out, int out_size) {
    static Params prm;
    static RecParams rp;
    static bool ready = false;
    static const void* key[14];
    bool same = ready;
    for (int i = 0; i < 13 && same; i++) same = key[i] == d_in[i];
    same = same && key[13] == d_out;
    if (!same) {
        void* fn = nullptr;
        cudaDriverEntryPointQueryResult qr;
        cudaGetDriverEntryPoint("cuTensorMapEncodeTiled", &fn, cudaEnableDefault, &qr);
        EncodeFn enc = (EncodeFn)fn;
        make_map(enc, &prm.tm_h, sym_addr(g_h), S_, D_, 64);
        make_map(enc, &prm.tm_kv, sym_addr(g_kv), S_, 2 * HD_, 64);
        make_map(enc, &prm.tm_kvm, sym_addr(g_kvm), NSEG * 8, 2 * HD_, 32);
        make_map(enc, &prm.tm_o, sym_addr(g_o), S_, HD_, 64);
        make_map(enc, &prm.tm_op, sym_addr(g_op), OP_ROWS, D_, 64);
        make_map(enc, &prm.tm_h2, sym_addr(g_h2), S_, D_, 64);
        make_map(enc, &prm.tm_act, sym_addr(g_act), S_, DF_, 64);
        make_map(enc, &prm.tm_x1, sym_addr(g_x1), S_, D_, 64);
        make_map(enc, &prm.tm_out, d_out, S_, D_, 64);
        make_map(enc, &prm.tm_wq, d_in[2], D_, HD_, 64);
        make_map(enc, &prm.tm_wk, d_in[3], D_, HD_, 64);
        make_map(enc, &prm.tm_wv, d_in[4], D_, HD_, 64);
        make_map(enc, &prm.tm_wo, d_in[5], HD_, D_, 64);
        make_map(enc, &prm.tm_wg, d_in[8], D_, DF_, 64);
        make_map(enc, &prm.tm_wu, d_in[9], D_, DF_, 64);
        make_map(enc, &prm.tm_wd, d_in[10], DF_, D_, 64);
        prm.x = (const bf16*)d_in[0]; prm.c = (const bf16*)d_in[11]; prm.w_mod = (const bf16*)d_in[12];
        rp.mem0 = (const bf16*)d_in[1]; rp.x = prm.x; rp.c = prm.c; rp.w_mod = prm.w_mod;
        rp.wq = (const bf16*)d_in[2]; rp.wk = (const bf16*)d_in[3]; rp.wv = (const bf16*)d_in[4]; rp.wo = (const bf16*)d_in[5];
        cudaFuncSetAttribute(k_work, cudaFuncAttributeMaxDynamicSharedMemorySize, SMEM_BYTES);
        cudaFuncSetAttribute(k_rec, cudaFuncAttributeMaxDynamicSharedMemorySize, R_SMEM);
        cudaFuncSetAttribute(k_rec, cudaFuncAttributeNonPortableClusterSizeAllowed, 1);
        {
            cudaLaunchConfig_t cfg = {};
            cfg.gridDim = dim3(128); cfg.blockDim = dim3(384); cfg.dynamicSmemBytes = R_SMEM;
            cudaLaunchAttribute at[1];
            at[0].id = cudaLaunchAttributeClusterDimension; at[0].val.clusterDim.x = 16; at[0].val.clusterDim.y = 1; at[0].val.clusterDim.z = 1;
            cfg.attrs = at; cfg.numAttrs = 1;
            int n = 0;
            cudaOccupancyMaxActiveClusters(&n, k_rec, &cfg);
            rp.ncl = n < 4 ? 4 : (n > 8 ? 8 : n);
        }
        for (int i = 0; i < 13; i++) key[i] = d_in[i];
        key[13] = d_out;
        ready = true;
    }
    cudaStream_t st = cudaStreamPerThread;
    auto launch_rec = [&]() {
        cudaLaunchConfig_t cfg = {};
        cfg.gridDim = dim3(16 * rp.ncl); cfg.blockDim = dim3(384); cfg.dynamicSmemBytes = R_SMEM; cfg.stream = st;
        cudaLaunchAttribute at[1];
        at[0].id = cudaLaunchAttributeClusterDimension; at[0].val.clusterDim.x = 16; at[0].val.clusterDim.y = 1; at[0].val.clusterDim.z = 1;
        cfg.attrs = at; cfg.numAttrs = 1;
        cudaLaunchKernelEx(&cfg, k_rec, rp);
    };
    auto launch_work = [&](int qmask, int pdl) {
        prm.qmask = qmask;
        cudaLaunchConfig_t cfg = {};
        cfg.gridDim = dim3(132); cfg.blockDim = dim3(384); cfg.dynamicSmemBytes = SMEM_BYTES; cfg.stream = st;
        cudaLaunchAttribute at[1];
        at[0].id = cudaLaunchAttributeProgrammaticStreamSerialization; at[0].val.programmaticStreamSerializationAllowed = 1;
        cfg.attrs = at; cfg.numAttrs = pdl;
        cudaLaunchKernelEx(&cfg, k_work, prm);
    };
    launch_rec();
    launch_work(0xff, 1);
}
```

```cpp
#include <cuda_runtime.h>
#include <cuda_bf16.h>
#include <cuda.h>
#include <stdint.h>

typedef __nv_bfloat16 bf16;
#define PF_NS 500
#define IDLE_NS 150
#define FLAG_NS 20

constexpr int S_ = 2048, D_ = 512, H_ = 32, DH_ = 128, HD_ = 4096, NSEG = 64, DF_ = 1792;
constexpr int NRB = 16;
constexpr int OSPLIT = 4;

__device__ __align__(1024) bf16 g_h[S_ * D_];
__device__ __align__(1024) bf16 g_kv[S_ * 2 * HD_];
__device__ __align__(1024) bf16 g_kvm[NSEG * 8 * 2 * HD_];
__device__ __align__(1024) bf16 g_o[S_ * HD_];
#define FINE_RB_ 12
constexpr int FINE_RB = FINE_RB_;
#define OSPLIT2_ 8
constexpr int OSPLIT2 = OSPLIT2_;
constexpr int OSPLIT3 = 16;
constexpr int OP_ROWS = OSPLIT * S_ + OSPLIT2 * (NRB - FINE_RB) * 128 + OSPLIT3 * 128;
__device__ __align__(1024) bf16 g_op[OP_ROWS * D_];
__device__ __align__(1024) bf16 g_x1[S_ * D_];
__device__ __align__(1024) bf16 g_h2[S_ * D_];
__device__ __align__(1024) bf16 g_act[S_ * DF_];
__device__ __align__(1024) bf16 g_mod[6 * D_];
__device__ uint32_t g_Fraw[131072 + 65536 + 2048];
#define g_F ((uint32_t*)(((uint64_t)g_Fraw + 0x7FFFFull) & ~0x7FFFFull))
constexpr int F_H = 0, F_MEM = 32, F_O = 64, F_OP = 96, F_H2 = 128, F_ACT = 160, F_MOD = 192, F_KV = 224, F_CLAIM = 256  ,
              F_SIDE = 512  , F_DONE = 576, F_TOTAL = 608;
__device__ __align__(128) unsigned int g_flags[F_TOTAL];
#define TR(j, i) do {} while (0)

__device__ __forceinline__ uint32_t smem_u32(const void* p) { return (uint32_t)__cvta_generic_to_shared(p); }
__device__ __forceinline__ uint32_t clk32() { uint32_t c; asm volatile("mov.u32 %0, %%clock;" : "=r"(c)); return c; }
__device__ __forceinline__ uint32_t mapa_u32(uint32_t addr, uint32_t rank) {
    uint32_t r; asm volatile("mapa.shared::cluster.u32 %0, %1, %2;" : "=r"(r) : "r"(addr), "r"(rank)); return r;
}
__device__ __forceinline__ void mbar_init(uint32_t bar, uint32_t cnt) {
    asm volatile("mbarrier.init.shared::cta.b64 [%0], %1;" :: "r"(bar), "r"(cnt) : "memory");
}
__device__ __forceinline__ void mbar_inval(uint32_t bar) {
    asm volatile("mbarrier.inval.shared::cta.b64 [%0];" :: "r"(bar) : "memory");
}
__device__ __forceinline__ void mbar_expect_tx(uint32_t bar, uint32_t bytes) {
    asm volatile("mbarrier.arrive.expect_tx.shared::cta.b64 _, [%0], %1;" :: "r"(bar), "r"(bytes) : "memory");
}
__device__ __forceinline__ void mbar_arrive(uint32_t bar) {
    asm volatile("mbarrier.arrive.shared::cta.b64 _, [%0];" :: "r"(bar) : "memory");
}
__device__ __forceinline__ bool mbar_try_wait(uint32_t bar, uint32_t parity) {
    uint32_t ok;
    asm volatile("{\n.reg .pred p;\nmbarrier.try_wait.parity.shared::cta.b64 p, [%1], %2;\nselp.u32 %0, 1, 0, p;\n}"
                 : "=r"(ok) : "r"(bar), "r"(parity) : "memory");
    return ok;
}
__device__ __forceinline__ bool mbar_try_wait_cluster(uint32_t bar, uint32_t parity) {
    uint32_t ok;
    asm volatile("{\n.reg .pred p;\nmbarrier.try_wait.parity.acquire.cluster.shared::cta.b64 p, [%1], %2;\nselp.u32 %0, 1, 0, p;\n}"
                 : "=r"(ok) : "r"(bar), "r"(parity) : "memory");
    return ok;
}
constexpr int SPIN_LIMIT = 1 << 18;
#define TIMEOUT(code, info) do {} while (0)
__device__ __forceinline__ void mbar_wait(uint32_t bar, uint32_t parity) {
    int g = 0;
#pragma unroll 1
    while (!mbar_try_wait(bar, parity)) { if (++g >= SPIN_LIMIT) { TIMEOUT(0, bar & 255); break; } }
}
__device__ __forceinline__ void mbar_wait_cluster(uint32_t bar, uint32_t parity) {
    int g = 0;
#pragma unroll 1
    while (!mbar_try_wait_cluster(bar, parity)) { if (++g >= SPIN_LIMIT) { TIMEOUT(1, bar & 255); break; } }
}
__device__ __forceinline__ void bar_sync(int id, int n) { asm volatile("bar.sync %0, %1;" :: "r"(id), "r"(n) : "memory"); }
__device__ __forceinline__ void bar_arrive(int id, int n) { asm volatile("bar.arrive %0, %1;" :: "r"(id), "r"(n) : "memory"); }
__device__ __forceinline__ void cluster_sync_all() {
    asm volatile("barrier.cluster.arrive.aligned;\nbarrier.cluster.wait.aligned;" ::: "memory");
}
__device__ __forceinline__ void st_async_v2(uint32_t addr, float a, float b, uint32_t bar) {
    asm volatile("st.async.weak.shared::cluster.mbarrier::complete_tx::bytes.v2.f32 [%0], {%1,%2}, [%3];"
                 :: "r"(addr), "f"(a), "f"(b), "r"(bar) : "memory");
}
__device__ __forceinline__ void st_async_v4(uint32_t addr, uint4 v, uint32_t bar) {
    asm volatile("st.async.weak.shared::cluster.mbarrier::complete_tx::bytes.v4.b32 [%0], {%1,%2,%3,%4}, [%5];"
                 :: "r"(addr), "r"(v.x), "r"(v.y), "r"(v.z), "r"(v.w), "r"(bar) : "memory");
}
__device__ __forceinline__ uint2 ldg_relaxed2(const uint2* p) {
    uint2 v;
    asm volatile("ld.relaxed.gpu.global.v2.b32 {%0,%1}, [%2];" : "=r"(v.x), "=r"(v.y) : "l"(p) : "memory");
    return v;
}
__device__ __forceinline__ void stg_relaxed2(uint2* p, uint2 v) {
    asm volatile("st.relaxed.gpu.global.v2.b32 [%0], {%1,%2};" :: "l"(p), "r"(v.x), "r"(v.y) : "memory");
}
__device__ __forceinline__ uint4 ldg_relaxed(const uint4* p) {
    uint4 v;
    asm volatile("ld.relaxed.gpu.global.v4.b32 {%0,%1,%2,%3}, [%4];" : "=r"(v.x), "=r"(v.y), "=r"(v.z), "=r"(v.w) : "l"(p) : "memory");
    return v;
}
__device__ __forceinline__ void stg_relaxed(uint4* p, uint4 v) {
    asm volatile("st.relaxed.gpu.global.v4.b32 [%0], {%1,%2,%3,%4};" :: "l"(p), "r"(v.x), "r"(v.y), "r"(v.z), "r"(v.w) : "memory");
}
__device__ __forceinline__ void stg_relaxed32(uint32_t* p, uint32_t v) {
    asm volatile("st.relaxed.gpu.global.b32 [%0], %1;" :: "l"(p), "r"(v) : "memory");
}
__device__ __forceinline__ uint32_t ldg_relaxed32(const uint32_t* p) {
    uint32_t v; asm volatile("ld.relaxed.gpu.global.b32 %0, [%1];" : "=r"(v) : "l"(p) : "memory"); return v;
}
__device__ __forceinline__ unsigned int ld_acquire(const unsigned int* p) {
    unsigned int v; asm volatile("ld.acquire.gpu.global.u32 %0, [%1];" : "=r"(v) : "l"(p) : "memory"); return v;
}
__device__ __forceinline__ void red_release(unsigned int* p, unsigned int v) {
    asm volatile("red.release.gpu.global.add.u32 [%0], %1;" :: "l"(p), "r"(v) : "memory");
}
__device__ __forceinline__ void wait_flag(int idx, unsigned int target) {
    const unsigned int* p = &g_flags[idx];
    int g = 0;
#pragma unroll 1
    while (ld_acquire(p) < target) { __nanosleep(FLAG_NS); if (++g >= 64 * SPIN_LIMIT) { TIMEOUT(2, idx); break; } }
}
__device__ __forceinline__ void cp_async16(uint32_t dst, const void* src) {
    asm volatile("cp.async.cg.shared.global [%0], [%1], 16;" :: "r"(dst), "l"(src) : "memory");
}
__device__ __forceinline__ void cp_async_commit() { asm volatile("cp.async.commit_group;" ::: "memory"); }
template <int N> __device__ __forceinline__ void cp_async_wait() { asm volatile("cp.async.wait_group %0;" :: "n"(N) : "memory"); }
__device__ __forceinline__ void ldsm4(uint32_t& r0, uint32_t& r1, uint32_t& r2, uint32_t& r3, uint32_t addr) {
    asm volatile("ldmatrix.sync.aligned.m8n8.x4.shared.b16 {%0,%1,%2,%3}, [%4];" : "=r"(r0), "=r"(r1), "=r"(r2), "=r"(r3) : "r"(addr) : "memory");
}
__device__ __forceinline__ void ldsm4t(uint32_t& r0, uint32_t& r1, uint32_t& r2, uint32_t& r3, uint32_t addr) {
    asm volatile("ldmatrix.sync.aligned.m8n8.x4.trans.shared.b16 {%0,%1,%2,%3}, [%4];" : "=r"(r0), "=r"(r1), "=r"(r2), "=r"(r3) : "r"(addr) : "memory");
}
__device__ __forceinline__ void ldsm2t(uint32_t& r0, uint32_t& r1, uint32_t addr) {
    asm volatile("ldmatrix.sync.aligned.m8n8.x2.trans.shared.b16 {%0,%1}, [%2];" : "=r"(r0), "=r"(r1) : "r"(addr) : "memory");
}
__device__ __forceinline__ void stsm4(uint32_t addr, uint32_t r0, uint32_t r1, uint32_t r2, uint32_t r3) {
    asm volatile("stmatrix.sync.aligned.m8n8.x4.shared.b16 [%0], {%1,%2,%3,%4};" :: "r"(addr), "r"(r0), "r"(r1), "r"(r2), "r"(r3) : "memory");
}
__device__ __forceinline__ void stsm2t(uint32_t addr, uint32_t r0, uint32_t r1) {
    asm volatile("stmatrix.sync.aligned.m8n8.x2.trans.shared.b16 [%0], {%1,%2};" :: "r"(addr), "r"(r0), "r"(r1) : "memory");
}
__device__ __forceinline__ void mma16816(float* d, uint32_t a0, uint32_t a1, uint32_t a2, uint32_t a3, uint32_t b0, uint32_t b1) {
    asm volatile("mma.sync.aligned.m16n8k16.row.col.f32.bf16.bf16.f32 {%0,%1,%2,%3}, {%4,%5,%6,%7}, {%8,%9}, {%0,%1,%2,%3};"
                 : "+f"(d[0]), "+f"(d[1]), "+f"(d[2]), "+f"(d[3]) : "r"(a0), "r"(a1), "r"(a2), "r"(a3), "r"(b0), "r"(b1));
}
__device__ __forceinline__ void mma1688(float* d, uint32_t a0, uint32_t a1, uint32_t b0) {
    asm volatile("mma.sync.aligned.m16n8k8.row.col.f32.bf16.bf16.f32 {%0,%1,%2,%3}, {%4,%5}, {%6}, {%0,%1,%2,%3};"
                 : "+f"(d[0]), "+f"(d[1]), "+f"(d[2]), "+f"(d[3]) : "r"(a0), "r"(a1), "r"(b0));
}
__device__ __forceinline__ void mma16816h(float* d, uint32_t a0, uint32_t a2, uint32_t b0, uint32_t b1) {
    asm volatile("{\n.reg .b32 ju, jv;\nmma.sync.aligned.m16n8k16.row.col.f32.bf16.bf16.f32 {%0,%1,%2,%3}, {%4,ju,%5,jv}, {%6,%7}, {%0,%1,%2,%3};\n}"
                 : "+f"(d[0]), "+f"(d[1]), "+f"(d[2]), "+f"(d[3]) : "r"(a0), "r"(a2), "r"(b0), "r"(b1));
}
__device__ __forceinline__ void mma1688h(float* d, uint32_t a0, uint32_t b0) {
    asm volatile("{\n.reg .b32 ju;\nmma.sync.aligned.m16n8k8.row.col.f32.bf16.bf16.f32 {%0,%1,%2,%3}, {%4,ju}, {%5}, {%0,%1,%2,%3};\n}"
                 : "+f"(d[0]), "+f"(d[1]), "+f"(d[2]), "+f"(d[3]) : "r"(a0), "r"(b0));
}
__device__ __forceinline__ uint32_t pack2(float lo, float hi) {
    uint32_t r; asm("cvt.rn.bf16x2.f32 %0, %1, %2;" : "=r"(r) : "f"(hi), "f"(lo)); return r;
}
__device__ __forceinline__ float bflo(uint32_t w) { return __uint_as_float(w << 16); }
__device__ __forceinline__ float bfhi(uint32_t w) { return __uint_as_float(w & 0xffff0000u); }
__device__ __forceinline__ float rbf(float x) { return __bfloat162float(__float2bfloat16_rn(x)); }
__device__ __forceinline__ float ex2(float x) { float y; asm("ex2.approx.ftz.f32 %0, %1;" : "=f"(y) : "f"(x)); return y; }
__device__ __forceinline__ void sts128(uint32_t addr, uint4 v) {
    asm volatile("st.shared.v4.b32 [%0], {%1,%2,%3,%4};" :: "r"(addr), "r"(v.x), "r"(v.y), "r"(v.z), "r"(v.w) : "memory");
}
__device__ __forceinline__ uint4 lds128(uint32_t addr) {
    uint4 v; asm volatile("ld.shared.v4.b32 {%0,%1,%2,%3}, [%4];" : "=r"(v.x), "=r"(v.y), "=r"(v.z), "=r"(v.w) : "r"(addr) : "memory"); return v;
}
__device__ __forceinline__ float2 lds64f(uint32_t addr) {
    float2 v; asm volatile("ld.shared.v2.f32 {%0,%1}, [%2];" : "=f"(v.x), "=f"(v.y) : "r"(addr) : "memory"); return v;
}
__device__ __forceinline__ float lds32f(uint32_t addr) {
    float v; asm volatile("ld.shared.f32 %0, [%1];" : "=f"(v) : "r"(addr) : "memory"); return v;
}
__device__ __forceinline__ uint32_t lds32(uint32_t addr) {
    uint32_t v; asm volatile("ld.shared.b32 %0, [%1];" : "=r"(v) : "r"(addr) : "memory"); return v;
}
__device__ __forceinline__ void sts32(uint32_t addr, uint32_t v) { asm volatile("st.shared.b32 [%0], %1;" :: "r"(addr), "r"(v) : "memory"); }
__device__ __forceinline__ void sts64f(uint32_t addr, float a, float b) { asm volatile("st.shared.v2.f32 [%0], {%1,%2};" :: "r"(addr), "f"(a), "f"(b) : "memory"); }

__device__ __forceinline__ void tma_load2d(uint32_t dst, const CUtensorMap* tm, int c0, int c1, uint32_t bar) {
    asm volatile("cp.async.bulk.tensor.2d.shared::cluster.global.mbarrier::complete_tx::bytes [%0], [%1, {%3, %4}], [%2];"
                 :: "r"(dst), "l"(tm), "r"(bar), "r"(c0), "r"(c1) : "memory");
}
__device__ __forceinline__ void tma_store2d(const CUtensorMap* tm, uint32_t src, int c0, int c1) {
    asm volatile("cp.async.bulk.tensor.2d.global.shared::cta.bulk_group [%0, {%2, %3}], [%1];"
                 :: "l"(tm), "r"(src), "r"(c0), "r"(c1) : "memory");
}
__device__ __forceinline__ void bulk_commit() { asm volatile("cp.async.bulk.commit_group;" ::: "memory"); }
__device__ __forceinline__ void bulk_wait0() { asm volatile("cp.async.bulk.wait_group 0;" ::: "memory"); }
__device__ __forceinline__ void fence_async_smem() { asm volatile("fence.proxy.async.shared::cta;" ::: "memory"); }
__device__ __forceinline__ void fence_async_all() { asm volatile("fence.proxy.async;" ::: "memory"); }

__device__ __forceinline__ void wg_fence() { asm volatile("wgmma.fence.sync.aligned;" ::: "memory"); }
__device__ __forceinline__ void wg_commit() { asm volatile("wgmma.commit_group.sync.aligned;" ::: "memory"); }
__device__ __forceinline__ void wg_wait0() { asm volatile("wgmma.wait_group.sync.aligned 0;" ::: "memory"); }
__device__ __forceinline__ uint64_t mkdesc(uint32_t saddr, uint32_t lbo, uint32_t sbo) {
    return (uint64_t)((saddr & 0x3FFFF) >> 4) | ((uint64_t)(lbo >> 4) << 16) | ((uint64_t)(sbo >> 4) << 32) | (1ull << 62);
}
#define ACC8(i) "+f"(d[i]), "+f"(d[i + 1]), "+f"(d[i + 2]), "+f"(d[i + 3]), "+f"(d[i + 4]), "+f"(d[i + 5]), "+f"(d[i + 6]), "+f"(d[i + 7])
__device__ __forceinline__ void wgmma_n256(float* d, uint64_t da, uint64_t db, int scale_d) {
    asm volatile(
        "{\n.reg .pred p;\nsetp.ne.b32 p, %130, 0;\n"
        "wgmma.mma_async.sync.aligned.m64n256k16.f32.bf16.bf16 "
        "{%0,%1,%2,%3,%4,%5,%6,%7,%8,%9,%10,%11,%12,%13,%14,%15,%16,%17,%18,%19,%20,%21,%22,%23,%24,%25,%26,%27,%28,%29,%30,%31,"
        "%32,%33,%34,%35,%36,%37,%38,%39,%40,%41,%42,%43,%44,%45,%46,%47,%48,%49,%50,%51,%52,%53,%54,%55,%56,%57,%58,%59,%60,%61,%62,%63,"
        "%64,%65,%66,%67,%68,%69,%70,%71,%72,%73,%74,%75,%76,%77,%78,%79,%80,%81,%82,%83,%84,%85,%86,%87,%88,%89,%90,%91,%92,%93,%94,%95,"
        "%96,%97,%98,%99,%100,%101,%102,%103,%104,%105,%106,%107,%108,%109,%110,%111,%112,%113,%114,%115,%116,%117,%118,%119,%120,%121,%122,%123,%124,%125,%126,%127}, "
        "%128, %129, p, 1, 1, 0, 1;\n}"
        : ACC8(0), ACC8(8), ACC8(16), ACC8(24), ACC8(32), ACC8(40), ACC8(48), ACC8(56),
          ACC8(64), ACC8(72), ACC8(80), ACC8(88), ACC8(96), ACC8(104), ACC8(112), ACC8(120)
        : "l"(da), "l"(db), "r"(scale_d));
}
__device__ __forceinline__ void wgmma_n128(float* d, uint64_t da, uint64_t db, int scale_d) {
    asm volatile(
        "{\n.reg .pred p;\nsetp.ne.b32 p, %66, 0;\n"
        "wgmma.mma_async.sync.aligned.m64n128k16.f32.bf16.bf16 "
        "{%0,%1,%2,%3,%4,%5,%6,%7,%8,%9,%10,%11,%12,%13,%14,%15,%16,%17,%18,%19,%20,%21,%22,%23,%24,%25,%26,%27,%28,%29,%30,%31,"
        "%32,%33,%34,%35,%36,%37,%38,%39,%40,%41,%42,%43,%44,%45,%46,%47,%48,%49,%50,%51,%52,%53,%54,%55,%56,%57,%58,%59,%60,%61,%62,%63}, "
        "%64, %65, p, 1, 1, 0, 1;\n}"
        : ACC8(0), ACC8(8), ACC8(16), ACC8(24), ACC8(32), ACC8(40), ACC8(48), ACC8(56)
        : "l"(da), "l"(db), "r"(scale_d));
}

__device__ __forceinline__ void wgmma_n64(float* d, uint64_t da, uint64_t db) {
    asm volatile(
        "wgmma.mma_async.sync.aligned.m64n64k16.f32.bf16.bf16 "
        "{%0,%1,%2,%3,%4,%5,%6,%7,%8,%9,%10,%11,%12,%13,%14,%15,%16,%17,%18,%19,%20,%21,%22,%23,%24,%25,%26,%27,%28,%29,%30,%31}, "
        "%32, %33, 1, 1, 1, 0, 1;"
        : ACC8(0), ACC8(8), ACC8(16), ACC8(24)
        : "l"(da), "l"(db));
}
__device__ __forceinline__ void wgmma_n8_ta(float* d, uint64_t da, uint64_t db, int scale_d) {
    asm volatile(
        "{\n.reg .pred p;\nsetp.ne.b32 p, %6, 0;\n"
        "wgmma.mma_async.sync.aligned.m64n8k16.f32.bf16.bf16 {%0,%1,%2,%3}, %4, %5, p, 1, 1, 1, 0;\n}"
        : "+f"(d[0]), "+f"(d[1]), "+f"(d[2]), "+f"(d[3]) : "l"(da), "l"(db), "r"(scale_d));
}

__device__ __forceinline__ uint32_t hadd2(uint32_t a, uint32_t b) { uint32_t r; asm("add.rn.bf16x2 %0, %1, %2;" : "=r"(r) : "r"(a), "r"(b)); return r; }
__device__ __forceinline__ uint32_t hsub2(uint32_t a, uint32_t b) { uint32_t r; asm("sub.rn.bf16x2 %0, %1, %2;" : "=r"(r) : "r"(a), "r"(b)); return r; }
__device__ __forceinline__ uint32_t hmul2(uint32_t a, uint32_t b) { uint32_t r; asm("mul.rn.bf16x2 %0, %1, %2;" : "=r"(r) : "r"(a), "r"(b)); return r; }
__device__ __forceinline__ void load_mod8(const bf16* m, int lane, uint32_t* v) {
    const uint4 a = __ldcg((const uint4*)m + lane), b = __ldcg((const uint4*)m + 32 + lane);
    v[0] = a.x; v[1] = a.y; v[2] = a.z; v[3] = a.w; v[4] = b.x; v[5] = b.y; v[6] = b.z; v[7] = b.w;
}
__device__ __forceinline__ void ln_stats(const uint32_t* x, uint32_t& mu2, float& rden) {
    float s = 0.f;
#pragma unroll
    for (int i = 0; i < 8; i++) s += bflo(x[i]) + bfhi(x[i]);
#pragma unroll
    for (int o = 16; o > 0; o >>= 1) s += __shfl_xor_sync(~0u, s, o);
    const float mean = s * (1.f / D_);
    float q = 0.f;
#pragma unroll
    for (int i = 0; i < 8; i++) { const float d0 = bflo(x[i]) - mean, d1 = bfhi(x[i]) - mean; q = fmaf(d0, d0, q); q = fmaf(d1, d1, q); }
#pragma unroll
    for (int o = 16; o > 0; o >>= 1) q += __shfl_xor_sync(~0u, q, o);
    mu2 = pack2(mean, mean);
    rden = __frcp_rn(rbf(__fsqrt_rn(rbf(rbf(q * (1.f / D_)) + 1e-5f))));
}
__device__ __forceinline__ void ln_apply(const uint32_t* x, uint32_t mu2, float rden, const uint32_t* c1, const uint32_t* sm, uint32_t* r) {
#pragma unroll
    for (int i = 0; i < 8; i++) {
        const uint32_t d = hsub2(x[i], mu2);
        r[i] = hadd2(hmul2(pack2(bflo(d) * rden, bfhi(d) * rden), c1[i]), sm[i]);
    }
}

struct __align__(64) Params {
    CUtensorMap tm_h, tm_kv, tm_kvm, tm_o, tm_op, tm_h2, tm_act, tm_x1, tm_out;
    CUtensorMap tm_wq, tm_wk, tm_wv, tm_wo, tm_wg, tm_wu, tm_wd;
    const bf16 *x, *c, *w_mod;
    int qmask;
};

constexpr uint32_t R_WV = 0, R_MEM = 65536, R_KX = 73728  , R_VX = R_KX + 8192  ,
                   R_KMS = R_VX + 16384  , R_VMS = R_KMS + 1024,
                   R_QS = R_KMS + 4096, R_OS = R_QS + 1024  , R_SX = R_OS + 2048, R_BAR = R_SX + 2560,
                   R_RS = 108544  , R_VB = R_RS + 4096  , R_VP = R_VB + 2048  ,
                   R_STG = R_VP + 8192  , R_SMEM = R_STG + 98304;
static_assert((R_KMS & 4095) == 0, "smem");
static_assert(R_BAR + 64 <= R_RS, "smem");
constexpr uint32_t RB_SX = R_BAR, RB_V = R_BAR + 8, RB_E = R_BAR + 16, RB_A = R_BAR + 24, RB_ROLE = R_BAR + 32, RB_A1 = R_BAR + 40;
constexpr int W_NST = 4;
constexpr uint32_t W_STAGE = 49152, W_STG = W_NST * W_STAGE  , W_END = W_STG + 32768;
constexpr uint32_t SM_BAR = W_END;
constexpr uint32_t SMEM_BYTES = W_END + 1024 + 2048;
constexpr uint32_t B_FULL = 0, B_EMPTY = 32, B_STGFREE = 64, B_REQ = 80, B_RSP = 88, B_NEXT = 96, B_RING = 128;
#define PICK_AHEAD 3

constexpr int NB_X = 11  , NB_Y = 1, NB_M = 5, NB_K = 5, NB_B = 2, NB_C = 3, NB_D = 4, NB_W0 = 6  , NB_ST = 9  ;

__device__ __forceinline__ int pos_of_d(int d) {
    const int rem = d & 31;
    return (d & ~31) + ((rem & 7) >> 1) * 8 + (rem & 1) * 4 + (rem >> 3);
}

#define PROF(i) do {} while (0)
#define PROFG(i) do {} while (0)
#define OPAQUE(x) asm volatile("" : "+r"(x))
#define FENCE_SCHED(x) do { if ((x) == 0u) asm volatile("trap;"); } while (0)
#define QKVAR 2
#define VK0_ 4
constexpr int VK0 = VK0_;
constexpr int NOFF = 8;
#define OFFKS(i) (((i) >> 1) < 2 ? ((i) >> 1) : ((i) >> 1) + 2)
#define VDELAY -1
#define POLL_GAP 110

struct RecParams { const bf16 *mem0, *wq, *wk, *wv, *wo, *x, *c, *w_mod; int ncl, only_pre; };

__device__ __forceinline__ void rec_qk(const RecParams& p, const uint32_t sb, const int cta, const int warp, int lane, const int sel) {
    const int crank = cta & 15, cl = cta >> 4, rank = cta & 1;
    const int kh = warp >> 2, aa = warp & 3;
    uint32_t wa[2][16][4];
    const uint32_t stg = sb + R_STG + kh * 32768;
    {
        const int t128 = aa * 32 + lane;
        const int row = (lane >> 4) * 8 + (lane & 7);
        const int ch = t128 & 7;
        const size_t goff = (size_t)kh * 256 * HD_ + cta * 64 + ch * 8;
#pragma unroll 4
        for (int dd = 0; dd < 16; dd++) {
            const int d = dd * 16 + (t128 >> 3), pp = pos_of_d(d);
            cp_async16(sb + R_WV + kh * 32768 + pp * 128 + ((ch ^ (pp & 7)) << 4), p.wv + goff + (size_t)d * HD_);
        }
        cp_async_commit();
#pragma unroll 4
        for (int dd = 0; dd < 16; dd++) {
            const int d = dd * 16 + (t128 >> 3), pp = pos_of_d(d);
            cp_async16(stg + pp * 128 + ((ch ^ (pp & 7)) << 4), p.wq + goff + (size_t)d * HD_);
        }
        cp_async_commit();
        {
            const int i0 = (warp * 32 + lane) * 16, tok = i0 >> 9;
            const uint4 m0 = __ldg((const uint4*)(p.mem0 + i0)), m1 = __ldg((const uint4*)(p.mem0 + i0 + 8));
            const uint32_t mw[8] = {m0.x, m0.y, m0.z, m0.w, m1.x, m1.y, m1.z, m1.w};
#pragma unroll
            for (int e = 0; e < 16; e++) {
                const int pp = pos_of_d((i0 & 511) + e);
                const unsigned short v = (unsigned short)(mw[e >> 1] >> ((e & 1) * 16));
                asm volatile("st.shared.u16 [%0], %1;" :: "r"(sb + R_MEM + (pp >> 3) * 128 + tok * 16 + (pp & 7) * 2), "h"(v) : "memory");
            }
        }
        cp_async_wait<1>();
        bar_sync(NB_W0 + kh, 128);
        const uint32_t fv = row * 128 + (((2 * aa + ((lane >> 3) & 1)) ^ (row & 7)) << 4);
#pragma unroll
        for (int ks = 0; ks < 16; ks++) ldsm4t(wa[0][ks][0], wa[0][ks][1], wa[0][ks][2], wa[0][ks][3], sb + R_WV + kh * 32768 + fv + ks * 2048);
        bar_sync(NB_W0 + kh, 128);
#pragma unroll
        for (int ks = 0; ks < 16; ks++)
            sts128(sb + R_WV + kh * 32768 + (aa * 16 + ks) * 512 + lane * 16, make_uint4(wa[0][ks][0], wa[0][ks][1], wa[0][ks][2], wa[0][ks][3]));
        const uint32_t fo = stg + row * 128 + (((4 * (aa & 1) + ((lane >> 3) & 1)) ^ (row & 7)) << 4);
#pragma unroll 1
        for (int m = 0; m < 2; m++) {
            cp_async_wait<0>();
            bar_sync(NB_W0 + kh, 128);
            if ((aa >> 1) == m) {
#pragma unroll
                for (int ks = 0; ks < 16; ks++) {
                    ldsm4t(wa[0][ks][0], wa[0][ks][1], wa[0][ks][2], wa[0][ks][3], fo + ks * 2048);
                    ldsm4t(wa[1][ks][0], wa[1][ks][1], wa[1][ks][2], wa[1][ks][3], (fo ^ 32) + ks * 2048);
                }
            }
            bar_sync(NB_W0 + kh, 128);
            if (m == 0) {
#pragma unroll 4
                for (int dd = 0; dd < 16; dd++) {
                    const int d = dd * 16 + (t128 >> 3), pp = pos_of_d(d);
                    cp_async16(stg + pp * 128 + ((ch ^ (pp & 7)) << 4), p.wk + goff + (size_t)d * HD_);
                }
                cp_async_commit();
            }
        }
    }
    const uint32_t tab = stg + (aa * 32 + lane) * 16;
    {
        const uint32_t l7 = lane & 7, l8 = lane >> 3, g = lane >> 2, t = lane & 3;
        const uint32_t t0 = l7 * 128 + ((l8 ^ l7) << 4);
        const uint32_t tq = l7 * 128 + (((l8 >> 1) ^ l7) << 4);
        const uint32_t bq = warp >> 1, tp = warp & 1;
        uint4 v;
        v.x = sb + (aa < 2 ? R_QS : R_KMS) + l7 * 128 + (((4 * (aa & 1) + 2 * kh + (l8 & 1)) ^ l7) << 4);
        v.y = sb + R_QS + tq;
        v.z = sb + (warp == 0 ? R_KMS : R_KX + (warp - 1) * 1024) + t0;
        v.w = mapa_u32(sb + R_SX + (rank * 5 + warp) * 256 + lane * 8, crank ^ 1);
        sts128(tab, v);
        sts128(tab + 2048, make_uint4(sb + lane * 16 + R_MEM + kh * 4096, sb + lane * 16 + R_WV + warp * 8192,
                                      sb + lane * 16 + R_VP + warp * 512, sb + lane * 16 + R_VP + 4096 + (warp ^ 4) * 512));
        const uint32_t src = l7;
        const uint32_t L = bq * 8 + 2 * tp + (l8 & 1) + 4 * (l8 >> 1);
        const uint32_t d0 = (crank + ((t >> 1) | (g & 6))) & 15;
        v.x = sb + R_RS + src * 512 + ((L ^ (src & 7)) << 4);
        v.y = mapa_u32(sb + R_MEM + (crank * 4 + bq) * 128 + (4 * tp + 2 * (t & 1) + (g & 1)) * 16, d0);
        v.z = mapa_u32(sb + ((crank & 1) ? RB_A1 : RB_A), d0);
        v.w = lane;
        sts128(tab + 4096, v);
        const uint64_t wr = (uint64_t)(g_F + ((crank * 2 + ((crank ^ (crank >> 3) ^ sel) & 1)) * 1024 + warp * 128 + cl * 32 + lane));
        sts128(tab + 6144, make_uint4((uint32_t)wr, (uint32_t)(wr >> 32), (uint32_t)((((cl + 1) & 3) - cl) * 128), (uint32_t)((((cl + 2) & 3) - cl) * 128)));
        sts32(tab + 8192, (uint32_t)((((cl + 3) & 3) - cl) * 128));
#pragma unroll
        for (int i = 0; i < NOFF; i++)
            sts128(tab + 10240 + i * 2048, make_uint4(wa[i & 1][OFFKS(i)][0], wa[i & 1][OFFKS(i)][1], wa[i & 1][OFFKS(i)][2], wa[i & 1][OFFKS(i)][3]));
    }
    bar_sync(NB_D, 384);
    uint32_t slot_off = 0;
    const uint32_t slot_inc = warp == 0 ? 2048 : 4096;
    const uint32_t sx_bar_rem = (sb + RB_SX) ^ (1u << 24);
    uint4 tb = lds128(tab + 2048);
#pragma unroll 1
    for (int s = 0; s < NSEG; s++) {
        if (s > 0) mbar_wait(sb + RB_A, (s - 1) & 1);
        if (warp == 0) { PROF(0); PROFG(13); }
        uint4 ta;
        const uint32_t km_tog = aa >= 2 ? (s & 1) * 2048 : 0;
        {
            float acc[5][4];
#pragma unroll
            for (int c = 0; c < 5; c++) { acc[c][0] = acc[c][1] = acc[c][2] = acc[c][3] = 0.f; }
            uint32_t b[8][4];
            uint4 av[16];
            static_assert(VK0 == 4, "order below assumes the V/O warps cover slices 0,1");
#define QK4(k2) do { \
                mma16816(acc[0], wa[0][2 * (k2)][0], wa[0][2 * (k2)][1], wa[0][2 * (k2)][2], wa[0][2 * (k2)][3], b[k2][0], b[k2][1]); \
                mma16816(acc[1], wa[1][2 * (k2)][0], wa[1][2 * (k2)][1], wa[1][2 * (k2)][2], wa[1][2 * (k2)][3], b[k2][0], b[k2][1]); \
                mma16816(acc[3], wa[0][2 * (k2) + 1][0], wa[0][2 * (k2) + 1][1], wa[0][2 * (k2) + 1][2], wa[0][2 * (k2) + 1][3], b[k2][2], b[k2][3]); \
                mma16816(acc[4], wa[1][2 * (k2) + 1][0], wa[1][2 * (k2) + 1][1], wa[1][2 * (k2) + 1][2], wa[1][2 * (k2) + 1][3], b[k2][2], b[k2][3]); } while (0)
#define V2(k2) do { \
                mma16816(acc[2], av[2 * (k2)].x, av[2 * (k2)].y, av[2 * (k2)].z, av[2 * (k2)].w, b[k2][0], b[k2][1]); \
                mma16816(acv, av[2 * (k2) + 1].x, av[2 * (k2) + 1].y, av[2 * (k2) + 1].z, av[2 * (k2) + 1].w, b[k2][2], b[k2][3]); } while (0)
#define LB(k2) ldsm4(b[k2][0], b[k2][1], b[k2][2], b[k2][3], tb.x + (k2) * 512)
#define LV(k2) do { av[2 * (k2)] = lds128(tb.y + 2 * (k2) * 512); av[2 * (k2) + 1] = lds128(tb.y + (2 * (k2) + 1) * 512); } while (0)
            float acv[4] = {0.f, 0.f, 0.f, 0.f};
            LB(0); LB(2); LB(4); LB(6);
            QK4(0); QK4(2); LV(4); LV(6); QK4(4); QK4(6);
            if (s > 0) mbar_wait(sb + RB_A1, (s - 1) & 1);
            LB(1); LB(3); LB(5); LB(7); ta = lds128(tab);
            V2(4); V2(6); LV(1); LV(3);
            QK4(1); QK4(3); QK4(5); QK4(7);
            LV(5); LV(7);
#pragma unroll
            for (int i = 0; i < 4; i++) { acc[0][i] += acc[3][i]; acc[1][i] += acc[4][i]; }
            const float g0 = kh ? acc[0][0] : acc[1][0], g1 = kh ? acc[0][1] : acc[1][1], g2 = kh ? acc[0][2] : acc[1][2], g3 = kh ? acc[0][3] : acc[1][3];
            sts128(tb.w, make_uint4(__float_as_uint(g0), __float_as_uint(g1), __float_as_uint(g2), __float_as_uint(g3)));
            const float k0 = kh ? acc[1][0] : acc[0][0], k1 = kh ? acc[1][1] : acc[0][1], k2_ = kh ? acc[1][2] : acc[0][2], k3 = kh ? acc[1][3] : acc[0][3];
            if (warp == 0) PROF(1);
            V2(1); V2(3);
            bar_sync(NB_X + aa, 64);
            const uint4 o = lds128(tb.z + 4096);
            V2(5); V2(7);
            stsm2t(ta.x ^ km_tog, pack2(k0 + __uint_as_float(o.x), k1 + __uint_as_float(o.y)), pack2(k2_ + __uint_as_float(o.z), k3 + __uint_as_float(o.w)));
            sts128(tb.z, make_uint4(__float_as_uint(acc[2][0] + acv[0]), __float_as_uint(acc[2][1] + acv[1]), __float_as_uint(acc[2][2] + acv[2]), __float_as_uint(acc[2][3] + acv[3])));
        }
        const uint32_t kb = ta.z + slot_off;
        if (warp == 0) PROF(14);
        bar_sync(NB_B, 256);
        if (warp < 5) {
            uint32_t q[16], k0, k1, k2, k3, k4, k5, k6, k7;
            float sa[4] = {0.f, 0.f, 0.f, 0.f}, sc[4] = {0.f, 0.f, 0.f, 0.f};
            ldsm4(q[0], q[1], q[2], q[3], ta.y);
            ldsm4(k0, k1, k2, k3, kb);
            ldsm4(q[4], q[5], q[6], q[7], ta.y ^ 32);
            ldsm4(q[8], q[9], q[10], q[11], ta.y ^ 64);
            ldsm4(k4, k5, k6, k7, kb ^ 64);
            ldsm4(q[12], q[13], q[14], q[15], ta.y ^ 96);
            mma16816(sa, q[0], q[1], q[2], q[3], k0, k1);
            bar_arrive(NB_Y, 288);
            mma16816(sc, q[4], q[5], q[6], q[7], k2, k3);
            mma16816(sa, q[8], q[9], q[10], q[11], k4, k5);
            mma16816(sc, q[12], q[13], q[14], q[15], k6, k7);
            const float scl = 0.08838834764831845f * 1.4426950408889634f;
            const float r0 = (sa[0] + sc[0]) * scl, r1 = (sa[1] + sc[1]) * scl;
            if (s != NSEG - 1) {
                st_async_v2(ta.w, r0, r1, sx_bar_rem);
                st_async_v2(ta.w ^ (1u << 24), r0, r1, sx_bar_rem ^ (1u << 24));
            }
            if (warp == 0) PROF(2);
        } else if (s > 0 && warp == 7 && lane == 0) {
            mbar_expect_tx(sb + RB_A, 4096);
            mbar_expect_tx(sb + RB_A1, 4096);
        } else if (s > 0 && (s & 3) == 0 && warp == 6) {
            bar_sync(NB_K, 160);
            if (lane == 0) red_release(&g_flags[F_MEM + (s >> 2) - 1], 1);
            __syncwarp();
        }
        if (s == NSEG - 1) {
            const uint4 td = lds128(tab + 6144);
            stg_relaxed32((uint32_t*)(((uint64_t)td.y << 32) | (td.x ^ 0x21000)), 0u);
            break;
        }
        slot_off ^= slot_inc;
        const uint4 tc = lds128(tab + 4096), td = lds128(tab + 6144);
        const uint32_t te = lds32(tab + 8192);
        uint32_t* wr = (uint32_t*)(((uint64_t)td.y << 32) | (td.x ^ ((s & 1) * 0x21000)));
        const uint32_t* r1p = (const uint32_t*)((const char*)wr + (int)td.z);
        const uint32_t* r2p = (const uint32_t*)((const char*)wr + (int)td.w);
        const uint32_t* r3p = (const uint32_t*)((const char*)wr + (int)te);
        const uint32_t tag = ((s >> 1) + 1) & 1;
        mbar_wait(sb + RB_E, s & 1);
        if (warp == 0) PROF(7);
        {
            uint32_t a0, a1, a2, a3;
            ldsm4t(a0, a1, a2, a3, tc.x);
            const uint32_t one = 0x3F803F80u;
            float d0_[4] = {0.f, 0.f, 0.f, 0.f}, d1_[4] = {0.f, 0.f, 0.f, 0.f};
            mma1688(d0_, a0, a1, one);
            mma1688(d1_, a2, a3, one);
            const bool t1 = tc.w & 1, t2 = tc.w & 2;
            const float x = t2 ? (t1 ? d1_[2] : d1_[0]) : (t1 ? d0_[2] : d0_[0]);
            const uint32_t own = (__float_as_uint(x) & ~1u) | tag;
            stg_relaxed32(wr, own);
            const uint32_t tq = clk32();
            if (warp == 0) PROF(8);
            PROFG(16 + warp);
            while ((int)(clk32() - tq) < POLL_GAP) {}
            uint32_t f1 = ldg_relaxed32(r1p), f2 = ldg_relaxed32(r2p), f3 = ldg_relaxed32(r3p);
#pragma unroll
            for (int i = 0; i < NOFF; i++) {
                const uint4 f0 = lds128(tab + 10240 + i * 2048);
                wa[i & 1][OFFKS(i)][0] = f0.x; wa[i & 1][OFFKS(i)][1] = f0.y; wa[i & 1][OFFKS(i)][2] = f0.z; wa[i & 1][OFFKS(i)][3] = f0.w;
            }
            tb = lds128(tab + 2048);
            int gg = 0;
#pragma unroll 1
            while (!__all_sync(~0u, (((f1 ^ tag) | (f2 ^ tag) | (f3 ^ tag)) & 1) == 0)) {
                f1 = ldg_relaxed32(r1p); f2 = ldg_relaxed32(r2p); f3 = ldg_relaxed32(r3p);
                if (++gg > 16 * SPIN_LIMIT) { TIMEOUT(3, s); break; }
            }
            if (warp == 0) PROF(9);
            const float v = (__uint_as_float(own) + __uint_as_float(f2)) + (__uint_as_float(f1) + __uint_as_float(f3));
            const bool b8 = tc.w & 8, b16 = tc.w & 16;
            const float recv = __shfl_xor_sync(~0u, v, 8);
            const uint32_t word = b8 ? pack2(recv, v) : pack2(v, recv);
            const uint32_t oth = __shfl_xor_sync(~0u, word, 16);
            const uint32_t wl = b16 ? oth : word, wh = b16 ? word : oth;
            const uint32_t p0 = __shfl_xor_sync(~0u, wl, 2), p1 = __shfl_xor_sync(~0u, wh, 2);
            const uint4 item = t2 ? make_uint4(p0, p1, wl, wh) : make_uint4(wl, wh, p0, p1);
            st_async_v4(tc.y, item, tc.z);
            st_async_v4(tc.y ^ (8u << 24), item, tc.z ^ (8u << 24));
            if (tc.w == 0 && warp == 7) mbar_expect_tx(sb + RB_E, 4096);
            if (warp == 0) PROF(10);
            PROF(40 + warp);
        }
        bar_sync(NB_D, 384);
    }
}

__device__ __forceinline__ void rec_load_kv(uint32_t dk, const char* src, int rank) {
    cp_async16(dk, src);
    cp_async16(dk ^ 16, src + 16);
}
__device__ __forceinline__ void rec_load_v(uint32_t dv, const char* src) {
    cp_async16(dv, src);
    cp_async16(dv ^ 16, src + 16);
    cp_async16(dv + 4096, src + 128);
    cp_async16((dv ^ 16) + 4096, src + 128 + 16);
}

__device__ __forceinline__ void rec_vo(const RecParams& p, const uint32_t sb, const int cta, const int warp, int lane) {
    const int w = warp - 8, crank = cta & 15, rank = cta & 1;
    const int col0 = cta * 64;
    uint32_t wo[4][8][4];
    const uint32_t tab = sb + R_STG + 2 * 32768 + (w * 32 + lane) * 16;
    {
        const int t128 = w * 32 + lane;
        const bf16* Wo = p.wo + (size_t)(cta >> 1) * DH_ * D_ + rank * 256;
        const uint32_t stg = sb + R_STG + 2 * 32768;
#pragma unroll
        for (int half = 0; half < 2; half++) {
#pragma unroll 4
            for (int i = t128; i < 2048; i += 128) {
                const int e = i >> 5, ch = i & 31;
                cp_async16(stg + e * 512 + ((ch ^ (e & 7)) << 4), Wo + (size_t)(half * 64 + e) * D_ + ch * 8);
            }
            cp_async_commit();
            cp_async_wait<0>();
            bar_sync(NB_W0 + 2, 128);
#pragma unroll
            for (int j = 0; j < 4; j++)
#pragma unroll
                for (int kk = 0; kk < 4; kk++) {
                    const int e = kk * 16 + (lane >> 4) * 8 + (lane & 7);
                    const int ch = (w * 4 + j) * 2 + ((lane >> 3) & 1);
                    ldsm4t(wo[j][half * 4 + kk][0], wo[j][half * 4 + kk][1], wo[j][half * 4 + kk][2], wo[j][half * 4 + kk][3],
                           stg + e * 512 + ((ch ^ (e & 7)) << 4));
                }
            bar_sync(NB_W0 + 2, 128);
        }
        const uint32_t l7 = lane & 7, l8 = lane >> 3, g = lane >> 2;
        uint4 v;
        v.x = sb + R_VX + (w >> 1) * 4096 + ((l8 & 1) * 8 + l7) * 128 + (((4 * (w & 1) + (l8 >> 1)) ^ l7) << 4);
        v.y = sb + R_OS + (w >> 1) * 1024 + g * 128 + (((4 * (w & 1)) ^ g) << 4) + (lane & 3) * 4;
        v.z = sb + R_VMS + l7 * 128 + (((2 * w + (l8 & 1)) ^ l7) << 4);
        v.w = sb + R_OS + l7 * 128 + ((l8 ^ l7) << 4);
        sts128(tab, v);
        v.x = mapa_u32(sb + R_RS + (crank >> 1) * 512 + ((lane ^ (crank >> 1)) << 4), rank * 8 + w * 2);
        v.y = mapa_u32(sb + RB_E, rank * 8 + w * 2);
        v.z = sb + R_VB + ((w >> 1) * 4 + 2 * (w & 1)) * 256 + lane * 8;
        v.w = sb + R_SX + lane * 8;
        sts128(tab + 2048, v);
#pragma unroll
        for (int i = 0; i < 8; i++)
            sts128(tab + 4096 + i * 2048, make_uint4(wo[i >> 1][(i & 1) * 4][0], wo[i >> 1][(i & 1) * 4][1], wo[i >> 1][(i & 1) * 4][2], wo[i >> 1][(i & 1) * 4][3]));
        const int tok = (w & 1) * 4 + (lane >> 3), row = t128 >> 2, c2 = (lane & 3) * 2;
        const uint64_t kd = (uint64_t)(g_kvm + (tok * (2 * HD_) + (w >> 1) * HD_ + col0 + (lane & 7) * 8));
        const uint64_t ks = (uint64_t)(g_kv + ((size_t)row * (2 * HD_) + col0 + c2 * 8));
        const uint32_t dk = sb + R_KX + row * 128 + ((c2 ^ (row & 7)) << 4);
        sts128(tab + 20480, make_uint4((uint32_t)kd, (uint32_t)(kd >> 32), (uint32_t)ks, (uint32_t)(ks >> 32)));
        sts128(tab + 22528, make_uint4(sb + R_KMS + (w >> 1) * 1024 + tok * 128 + (((lane & 7) ^ tok) << 4), dk, lane, sb + lane * 16));
        if (lane == 0) wait_flag(F_KV + 0, 64);
        __syncwarp();
        rec_load_kv(dk, (const char*)ks, rank);
        rec_load_v(dk + (R_VX - R_KX), (const char*)ks + HD_ * 2 - rank * 128);
        cp_async_commit();
        cp_async_wait<0>();
    }
    bar_sync(NB_D, 384);
    const uint32_t lane16 = lds32(tab + 22528 + 12);
    const uint32_t vb_dst = (lane16 - sb) / 2 + sb + R_VB + (rank * 4 + w) * 256;
    uint4 av[2 * VK0];
#pragma unroll
    for (int i = 0; i < 2 * VK0; i++) av[i] = lds128(lane16 + R_WV + (i / VK0) * 32768 + (w * 16 + (i & 1) + (i & 2) * 2) * 512);
#pragma unroll 1
    for (int s = 0; s < NSEG; s++) {
        {
            if (s > 0) mbar_wait(sb + RB_A, (s - 1) & 1);
            const uint4 tp = lds128(tab + 20480), tq = lds128(tab + 22528);
            if (s > 0) {
                const uint4 kvm = lds128(tq.x + ((s - 1) & 1) * 2048);
                *(uint4*)((((uint64_t)tp.y << 32) | tp.x) + (uint64_t)(s - 1) * (8 * 2 * HD_ * 2)) = kvm;
                if ((s & 3) == 0) bar_arrive(NB_K, 160);
            }
            if (s + 1 < NSEG - 1) {
                if (((s + 1) & 3) == 0) { if (tq.z == 0) wait_flag(F_KV + ((s + 1) >> 2), 64); __syncwarp(); }
                const char* src = (const char*)((((uint64_t)tp.w << 32) | tp.z) + (uint64_t)(s + 1) * (32 * 2 * HD_ * 2));
                rec_load_kv(tq.y + ((s + 1) & 1) * 4096, src, rank);
                rec_load_v(tq.y + (R_VX - R_KX) + ((s + 1) & 1) * 8192, src + HD_ * 2 - rank * 128);
            }
            cp_async_commit();
        }
        uint32_t vb0, vb1;
        {
            float va[4] = {0.f, 0.f, 0.f, 0.f}, vc[4] = {0.f, 0.f, 0.f, 0.f};
            uint32_t bb[VK0][4];
#pragma unroll
            for (int k2 = 0; k2 < VK0; k2++) ldsm4(bb[k2][0], bb[k2][1], bb[k2][2], bb[k2][3], lane16 + R_MEM + (k2 >> 1) * 4096 + (k2 & 1) * 1024);
#pragma unroll
            for (int k2 = 0; k2 < VK0; k2++) {
                mma16816(va, av[2 * k2].x, av[2 * k2].y, av[2 * k2].z, av[2 * k2].w, bb[k2][0], bb[k2][1]);
                mma16816(vc, av[2 * k2 + 1].x, av[2 * k2 + 1].y, av[2 * k2 + 1].z, av[2 * k2 + 1].w, bb[k2][2], bb[k2][3]);
            }
            bar_sync(NB_Y, 288);
            const uint4 a = lds128(lane16 + R_VP + w * 512), b = lds128(lane16 + R_VP + 2048 + w * 512);
            vb0 = pack2((va[0] + vc[0]) + (__uint_as_float(a.x) + __uint_as_float(b.x)), (va[1] + vc[1]) + (__uint_as_float(a.y) + __uint_as_float(b.y)));
            vb1 = pack2((va[2] + vc[2]) + (__uint_as_float(a.z) + __uint_as_float(b.z)), (va[3] + vc[3]) + (__uint_as_float(a.w) + __uint_as_float(b.w)));
            if (s != NSEG - 1) {
                st_async_v2(vb_dst ^ (1u << 24), __uint_as_float(vb0), __uint_as_float(vb1), (sb + RB_SX) ^ (1u << 24));
                st_async_v2(vb_dst, __uint_as_float(vb0), __uint_as_float(vb1), sb + RB_SX);
            }
        }
        const uint4 ta = lds128(tab), tb = lds128(tab + 2048);
        stsm2t(ta.z + (s & 1) * 2048, vb0, vb1);
        if (w == 0) PROF(11);
        if (s != NSEG - 1) {
            uint32_t vx[16];
            const uint32_t vxa = ta.x + (s & 1) * 8192;
            ldsm4t(vx[0], vx[1], vx[2], vx[3], vxa);
            ldsm4t(vx[4], vx[5], vx[6], vx[7], vxa ^ 32);
            ldsm4t(vx[8], vx[9], vx[10], vx[11], vxa + 2048);
            ldsm4t(vx[12], vx[13], vx[14], vx[15], (vxa ^ 32) + 2048);
#pragma unroll
            for (int i = 0; i < 4; i++) {
                const uint4 f0 = lds128(tab + 4096 + i * 2048);
                wo[i >> 1][(i & 1) * 4][0] = f0.x; wo[i >> 1][(i & 1) * 4][1] = f0.y; wo[i >> 1][(i & 1) * 4][2] = f0.z; wo[i >> 1][(i & 1) * 4][3] = f0.w;
            }
            mbar_wait(sb + RB_SX, s & 1);
            if (w == 0) PROF(4);
            float sv[10];
#pragma unroll
            for (int n = 0; n < 5; n++) {
                const float2 a = lds64f(tb.w + n * 256), b = lds64f(tb.w + (5 + n) * 256);
                sv[2 * n] = a.x + b.x; sv[2 * n + 1] = a.y + b.y;
            }
            const float2 m0 = lds64f(tb.z), m1 = lds64f(tb.z + 256);
            float mx = fmaxf(fmaxf(fmaxf(sv[0], sv[1]), fmaxf(sv[2], sv[3])), fmaxf(fmaxf(sv[4], sv[5]), fmaxf(sv[6], sv[7])));
            mx = fmaxf(mx, fmaxf(sv[8], sv[9]));
            mx = fmaxf(mx, __shfl_xor_sync(~0u, mx, 1));
            mx = fmaxf(mx, __shfl_xor_sync(~0u, mx, 2));
            uint32_t pf[5];
#pragma unroll
            for (int n = 0; n < 5; n++) pf[n] = pack2(ex2(sv[2 * n] - mx), ex2(sv[2 * n + 1] - mx));
            if (w == 0) PROF(12);
            float oa[4][4] = {{0.f, 0.f, 0.f, 0.f}, {0.f, 0.f, 0.f, 0.f}, {0.f, 0.f, 0.f, 0.f}, {0.f, 0.f, 0.f, 0.f}}, sm[4] = {0.f, 0.f, 0.f, 0.f};
            const uint32_t one = 0x3F803F80u;
            mma1688h(sm, pf[0], one);
            mma1688h(oa[0], pf[0], __float_as_uint(m0.x));
            mma1688h(oa[1], pf[0], __float_as_uint(m0.y));
            mma1688h(oa[2], pf[0], __float_as_uint(m1.x));
            mma1688h(oa[3], pf[0], __float_as_uint(m1.y));
            mma16816h(sm, pf[1], pf[2], one, one);
#pragma unroll
            for (int n = 0; n < 4; n++) mma16816h(oa[n], pf[1], pf[2], vx[2 * n], vx[2 * n + 1]);
            mma16816h(sm, pf[3], pf[4], one, one);
#pragma unroll
            for (int n = 0; n < 4; n++) mma16816h(oa[n], pf[3], pf[4], vx[8 + 2 * n], vx[8 + 2 * n + 1]);
            float inv;
            asm("rcp.approx.ftz.f32 %0, %1;" : "=f"(inv) : "f"(sm[0]));
#pragma unroll
            for (int n = 0; n < 4; n++) sts32(ta.y ^ (n << 4), pack2(oa[n][0] * inv, oa[n][1] * inv));
            bar_sync(NB_C, 128);
            if (w == 0) PROF(5);
            uint32_t ob[16];
            ldsm4(ob[0], ob[1], ob[2], ob[3], ta.w);
            ldsm4(ob[8], ob[9], ob[10], ob[11], ta.w + 1024);
            ldsm4(ob[4], ob[5], ob[6], ob[7], ta.w ^ 64);
            ldsm4(ob[12], ob[13], ob[14], ob[15], (ta.w ^ 64) + 1024);
#pragma unroll
            for (int i = 4; i < 8; i++) {
                const uint4 f0 = lds128(tab + 4096 + i * 2048);
                wo[i >> 1][(i & 1) * 4][0] = f0.x; wo[i >> 1][(i & 1) * 4][1] = f0.y; wo[i >> 1][(i & 1) * 4][2] = f0.z; wo[i >> 1][(i & 1) * 4][3] = f0.w;
            }
#pragma unroll
            for (int jj = 0; jj < 2; jj++) {
                if (jj == 1 && tb.w == 0) break;
                float acc[4][4];
#pragma unroll
                for (int c = 0; c < 4; c++) { acc[c][0] = acc[c][1] = acc[c][2] = acc[c][3] = 0.f; }
#pragma unroll
                for (int k4 = 0; k4 < 4; k4++)
#pragma unroll
                    for (int c = 0; c < 4; c++) {
                        const int tl = jj * 2 + (c >> 1), ks = (c & 1) * 4 + k4;
                        mma16816(acc[c], wo[tl][ks][0], wo[tl][ks][1], wo[tl][ks][2], wo[tl][ks][3], ob[2 * ks], ob[2 * ks + 1]);
                    }
                uint4 v;
                v.x = pack2(acc[0][0] + acc[1][0], acc[0][1] + acc[1][1]);
                v.y = pack2(acc[0][2] + acc[1][2], acc[0][3] + acc[1][3]);
                v.z = pack2(acc[2][0] + acc[3][0], acc[2][1] + acc[3][1]);
                v.w = pack2(acc[2][2] + acc[3][2], acc[2][3] + acc[3][3]);
                st_async_v4(tb.x + (jj << 24), v, tb.y + (jj << 24));
            }
            if (w == 0) PROF(6);
        }
        cp_async_wait<0>();
        bar_sync(NB_C, 128);
        if (s != NSEG - 1) {
            if (w == 0 && lane == 0) mbar_expect_tx(sb + RB_SX, 4608);
            bar_arrive(NB_D, 384);
        }
#pragma unroll
        for (int i = 0; i < 2 * VK0; i++) av[i] = lds128(lane16 + R_WV + (i / VK0) * 32768 + (w * 16 + (i & 1) + (i & 2) * 2) * 512);
    }
    {
        const uint4 tp = lds128(tab + 20480), tq = lds128(tab + 22528);
        *(uint4*)((((uint64_t)tp.y << 32) | tp.x) + (uint64_t)(NSEG - 1) * (8 * 2 * HD_ * 2)) = lds128(tq.x + 2048);
    }
    bar_sync(NB_C, 128);
    if (w == 0 && lane == 0) red_release(&g_flags[F_MEM + NRB - 1], 1);
}

__global__ void __launch_bounds__(384, 1) k_rec(const RecParams p) {
    extern __shared__ __align__(1024) unsigned char smem_raw[];
    const uint32_t sb = __shfl_sync(~0u, smem_u32(smem_raw), 0);
    const int warp = __shfl_sync(~0u, threadIdx.x >> 5, 0);
    int lane; asm volatile("mov.u32 %0, %%laneid;" : "=r"(lane));
    const int crank = blockIdx.x & 15, slot = blockIdx.x >> 4;
    asm volatile("griddepcontrol.launch_dependents;");
    if (crank == 0 && warp == 1 && lane < 4) {
        const unsigned int* q = lane < 2 ? &g_F[65536 + lane * 1024 + slot * 64] : &g_flags[F_SIDE + (lane - 2) * 32];
        asm volatile("prefetch.global.L2 [%0];" :: "l"(q));
    }
    if (threadIdx.x == 0) {
        mbar_init(sb + RB_SX, 1); mbar_init(sb + RB_E, 1); mbar_init(sb + RB_A, 1); mbar_init(sb + RB_A1, 1); mbar_init(sb + RB_ROLE, 1);
        asm volatile("fence.mbarrier_init.release.cluster;" ::: "memory");
        mbar_expect_tx(sb + RB_SX, 4608);
        mbar_expect_tx(sb + RB_E, 4096);
        mbar_expect_tx(sb + RB_A, 4096);
        mbar_expect_tx(sb + RB_A1, 4096);
        mbar_expect_tx(sb + RB_ROLE, 4);
    }
    asm volatile("barrier.cluster.arrive.relaxed.aligned;\nbarrier.cluster.wait.aligned;" ::: "memory");
    unsigned role = 0;
    if (crank == 0 && threadIdx.x == 0 && !p.only_pre) {
        unsigned x = 0;
        int tm[2] = {0x7fffffff, 0x7fffffff};
#pragma unroll 1
        for (int i = 0; i < 6; i++) {
            const uint32_t t0 = clk32();
            x = atomicAdd(&g_F[65536 + (i & 1) * 1024 + slot * 64 + (x >> 31)], 0u) & 0x7fffffffu;
            if (x == 0x7654321u) sts32(sb + R_BAR + 56, x);
            const int dt = (int)(clk32() - t0);
            if (i >= 2) { if (i & 1) tm[1] = min(tm[1], dt); else tm[0] = min(tm[0], dt); }
        }
        const int side = tm[1] > tm[0];
        const unsigned old = atomicAdd(&g_flags[F_SIDE + side * 32], 1u);
        unsigned c0, c1; int gd = 0;
#pragma unroll 1
        do { c0 = ldg_relaxed32(&g_flags[F_SIDE]); c1 = ldg_relaxed32(&g_flags[F_SIDE + 32]); } while ((int)(c0 + c1) < p.ncl && ++gd < 64 * SPIN_LIMIT);
        const int big = c1 > c0;
        role = side == big ? old : (big ? c1 : c0) + old;
        role |= (big ^ 1) << 8;
    }
    __syncwarp();
    if (crank == 0 && warp == 0 && !p.only_pre) {
        role = __shfl_sync(~0u, role, 0);
        if (lane < 16)
            asm volatile("st.async.weak.shared::cluster.mbarrier::complete_tx::bytes.u32 [%0], %1, [%2];"
                         :: "r"(mapa_u32(sb + R_BAR + 48, lane)), "r"(role), "r"(mapa_u32(sb + RB_ROLE, lane)) : "memory");
    }
    if (warp >= 4) {
        const int w8 = warp - 4, nblk = gridDim.x;
        const int cq = lane & 3, rg = w8 * 8 + (lane >> 2);
        const uint32_t red = sb + R_VP;
        const int row0 = blockIdx.x * 8 + w8;
        const uint4* xr = (const uint4*)(p.x + (size_t)row0 * D_);
        uint4 xa = __ldg(xr + lane), xb = __ldg(xr + 32 + lane);
#pragma unroll 1
        for (int sl = blockIdx.x; sl < 96; sl += nblk) {
            uint4 wv[8];
#pragma unroll
            for (int i = 0; i < 8; i++) wv[i] = __ldg((const uint4*)(p.w_mod + (size_t)(rg * 8 + i) * (6 * D_) + sl * 32 + cq * 8));
            const uint32_t cw = __ldg((const uint32_t*)(p.c + rg * 8) + cq);
            const float cl = bflo(cw), ch = bfhi(cw);
            const uint32_t sw = pack2(__fdividef(cl, 1.f + __expf(-cl)), __fdividef(ch, 1.f + __expf(-ch)));
            float a[8];
#pragma unroll
            for (int i = 0; i < 8; i++) a[i] = 0.f;
#pragma unroll
            for (int i = 0; i < 8; i++) {
                const uint32_t sv = __shfl_sync(~0u, sw, (lane & 28) + (i >> 1));
                const float cv = (i & 1) ? bfhi(sv) : bflo(sv);
                a[0] = fmaf(cv, bflo(wv[i].x), a[0]); a[1] = fmaf(cv, bfhi(wv[i].x), a[1]); a[2] = fmaf(cv, bflo(wv[i].y), a[2]); a[3] = fmaf(cv, bfhi(wv[i].y), a[3]);
                a[4] = fmaf(cv, bflo(wv[i].z), a[4]); a[5] = fmaf(cv, bfhi(wv[i].z), a[5]); a[6] = fmaf(cv, bflo(wv[i].w), a[6]); a[7] = fmaf(cv, bfhi(wv[i].w), a[7]);
            }
#pragma unroll
            for (int i = 0; i < 8; i++) { a[i] += __shfl_xor_sync(~0u, a[i], 4); a[i] += __shfl_xor_sync(~0u, a[i], 8); a[i] += __shfl_xor_sync(~0u, a[i], 16); }
            if (lane < 4) {
                sts128(red + w8 * 128 + lane * 32, make_uint4(__float_as_uint(a[0]), __float_as_uint(a[1]), __float_as_uint(a[2]), __float_as_uint(a[3])));
                sts128(red + w8 * 128 + lane * 32 + 16, make_uint4(__float_as_uint(a[4]), __float_as_uint(a[5]), __float_as_uint(a[6]), __float_as_uint(a[7])));
            }
            bar_sync(NB_B, 256);
            if (w8 == 0) {
                float v = 0.f;
#pragma unroll
                for (int i = 0; i < 8; i++) v += lds32f(red + i * 128 + lane * 4);
                g_mod[sl * 32 + lane] = __float2bfloat16_rn(v);
                __syncwarp();
                if (lane == 0) red_release(&g_flags[F_MOD + (sl >= 32)], 1);
            }
            bar_sync(NB_B, 256);
        }
        uint32_t c1[8], sm[8];
        int row = row0;
#pragma unroll 1
        while (true) {
            const uint32_t v[8] = {xa.x, xa.y, xa.z, xa.w, xb.x, xb.y, xb.z, xb.w};
            uint32_t mu2, r[8]; float rden;
            ln_stats(v, mu2, rden);
            if (row == row0) {
                if (lane == 0) wait_flag(F_MOD, 32);
                __syncwarp();
                load_mod8(g_mod + D_, lane, c1);
                load_mod8(g_mod, lane, sm);
#pragma unroll
                for (int i = 0; i < 8; i++) c1[i] = hadd2(c1[i], 0x3F803F80u);
            } else if (row + 512 < S_) {
                xr = (const uint4*)(p.x + (size_t)(row + 512) * D_); xa = __ldg(xr + lane); xb = __ldg(xr + 32 + lane);
            }
            ln_apply(v, mu2, rden, c1, sm, r);
            uint4* hr = (uint4*)(g_h + (size_t)row * D_);
            hr[lane] = make_uint4(r[0], r[1], r[2], r[3]); hr[32 + lane] = make_uint4(r[4], r[5], r[6], r[7]);
            bar_sync(NB_B, 256);
            if (w8 == (row >> 7 & 7) && lane == 0) red_release(&g_flags[F_H + (row >> 7)], 1);
            __syncwarp();
            if (row == row0) {
                if (!p.only_pre) mbar_wait(sb + RB_ROLE, 0);
                const int cl = p.only_pre ? slot : (int)(lds32(sb + R_BAR + 48) & 255);
                row = cl < 4 ? (nblk + cl * 16 + crank) * 8 + w8 : S_;
                if (row < S_) { xr = (const uint4*)(p.x + (size_t)row * D_); xa = __ldg(xr + lane); xb = __ldg(xr + 32 + lane); }
            } else {
                row += 512;
            }
            if (row >= S_) break;
        }
    }
    if (p.only_pre) return;
    mbar_wait(sb + RB_ROLE, 0);
    const int rolew = __shfl_sync(~0u, lds32(sb + R_BAR + 48), 0);
    const int cl = rolew & 255;
    if (cl >= 4) return;
    const int cta = cl * 16 + crank;
    if (warp < 8) rec_qk(p, sb, cta, warp, lane, rolew >> 8);
    else rec_vo(p, sb, cta, warp, lane);
}

enum { J_KV = 0, J_QA = 1, J_O = 2, J_LN = 3, J_UP = 4, J_DN = 5, J_LN1 = 6, J_MOD = 7, J_UP2 = 8, J_END = 9 };
constexpr int NJ_O = 2 * OSPLIT, NJ_O2 = 2 * OSPLIT2, NJ_LN = 8, NJ_LN2 = 16, NJ_UP = 14, NJ_UP2 = 28, NJ_DN = 8, NJ_LN1 = 8;
constexpr uint64_t pk8(int a, int b, int c, int d, int e, int f, int g, int h) {
    return (uint64_t)a | ((uint64_t)b << 8) | ((uint64_t)c << 16) | ((uint64_t)d << 24) | ((uint64_t)e << 32) | ((uint64_t)f << 40) | ((uint64_t)g << 48) | ((uint64_t)h << 56);
}
constexpr uint64_t NJ_C = pk8(32, 16, NJ_O, NJ_LN, NJ_UP, NJ_DN, 0, 0), NJ_F = pk8(32, 16, NJ_O2, NJ_LN2, NJ_UP2, NJ_DN, 0, 0);
constexpr uint64_t TG_C = pk8(2 * NJ_LN1, 64, 32, 2 * NJ_O, 2 * NJ_LN, 2 * NJ_UP, 32, 0), TG_F = pk8(2 * NJ_LN1, 64, 32, 2 * NJ_O2, 2 * NJ_LN2, 2 * NJ_UP2, 32, 0);
constexpr uint64_t NJ_L = pk8(32, 32, 2 * OSPLIT3, NJ_LN2, NJ_UP2, NJ_DN, 0, 0), TG_L = pk8(2 * NJ_LN1, 64, 64, 4 * OSPLIT3, 2 * NJ_LN2, 2 * NJ_UP2, 32, 0);
__device__ __forceinline__ uint64_t nj_tab(int rb) { return rb < FINE_RB ? NJ_C : (rb < NRB - 1 ? NJ_F : NJ_L); }
__device__ __forceinline__ uint64_t tg_tab(int rb) { return rb < FINE_RB ? TG_C : (rb < NRB - 1 ? TG_F : TG_L); }
__device__ __forceinline__ int o_nk(int rb) { return rb < FINE_RB ? 64 / OSPLIT : (rb < NRB - 1 ? 64 / OSPLIT2 : 64 / OSPLIT3); }
constexpr uint64_t PRIO = pk8(4, 10, 9, 8, 7, 6, 3, 0);
__device__ __forceinline__ int pick_job(int lane, int qmask, int& idx) {
    const int rb = lane & 15, half = lane >> 4;
    const uint64_t nj = nj_tab(rb) >> (8 * half);
    const uint64_t tg = tg_tab(rb) >> (8 * half);
    const unsigned* cp = &g_flags[F_CLAIM + half * 32 + rb];
    const unsigned* dp = &g_flags[half * 32 + rb];
    int gd = 0;
#pragma unroll 1
    while (true) {
        const unsigned c0 = ldg_relaxed32(cp), c1 = ldg_relaxed32(cp + 64), c2 = ldg_relaxed32(cp + 128);
        const unsigned d0 = ldg_relaxed32(dp - (half && rb ? 1 : 0)), d1 = ldg_relaxed32(dp + 64), d2 = ldg_relaxed32(dp + 128);
        const unsigned cl[3] = {c0, c1, c2}, dv[3] = {d0, d1, d2};
        unsigned key = 0xffffu, key2 = 0xffffu;
        bool pre = false;
#pragma unroll
        for (int i = 0; i < 3; i++) {
            const int q = half + 2 * i;
            const bool have = ((qmask >> q) & 1) && cl[i] < (unsigned)((nj >> (16 * i)) & 255);
            bool ready = have && dv[i] >= (unsigned)((tg >> (16 * i)) & 255);
            unsigned pr = (unsigned)((PRIO >> (8 * q)) & 255);
            if (i == 0 && rb <= 1 - half) ready = have;
            if (i == 0 && half && rb >= FINE_RB) pr = 5;
            if (ready) key = min(key, (pr << 8) | (rb << 4) | q);
            if (have) key2 = min(key2, rb >= FINE_RB ? (0x100u | (q << 4) | rb) : (i == 0 ? 0u : 0x1000u));
            pre |= have && i == 0 && !half;
        }
        const bool anypre = __any_sync(~0u, pre);
        if (anypre && (key & 15) == J_QA) key = 0xffffu;
        key = __reduce_min_sync(~0u, key);
        key2 = __reduce_min_sync(~0u, key2);
        if (key2 == 0xffffu) return J_END;
        int pq, prb;
        if (key != 0xffffu) { pq = key & 15; prb = (key >> 4) & 15; }
        else if (key2 >= 0x120u && key2 < 0x1000u) { pq = (key2 >> 4) & 15; prb = key2 & 15; }
        else {
            __nanosleep(IDLE_NS);
            if (++gd > 16 * SPIN_LIMIT) { TIMEOUT(5, 0); return J_END; }
            continue;
        }
        int c = 0;
        if (lane == 0) c = (int)atomicAdd(&g_flags[F_CLAIM + pq * 32 + prb], 1u);
        c = __shfl_sync(~0u, c, 0);
        if (c < (int)((nj_tab(prb) >> (8 * pq)) & 255)) {
            idx = pq * 512 + prb * 32 + c;
            int acq = 0;
            if (pq != J_QA && pq < J_LN1) {
                if (lane == 0 && ld_acquire(&g_flags[pq * 32 + prb]) >= (unsigned)((tg_tab(prb) >> (8 * pq)) & 255)) {
                    asm volatile("fence.proxy.async.global;" ::: "memory");
                    acq = 1 << 24;
                }
            }
            return (pq == J_UP && prb >= FINE_RB ? J_UP2 : pq) | (prb << 8) | (c << 16) | acq;
        }
    }
}
__device__ __forceinline__ int op_row(int rb, int split) {
    return rb < FINE_RB ? split * S_ + rb * 128
                        : (rb < NRB - 1 ? OSPLIT * S_ + (split * (NRB - FINE_RB) + rb - FINE_RB) * 128 : OSPLIT * S_ + (OSPLIT2 * (NRB - FINE_RB) + split) * 128);
}

struct Pipe { uint32_t stage, phase; };
__device__ __forceinline__ void pipe_next(Pipe& p) { if (++p.stage == W_NST) { p.stage = 0; p.phase ^= 1; } }

__device__ __forceinline__ void scheduler(const Params& p, uint32_t sb, int lane) {
    const uint32_t bars = sb + SM_BAR;
    uint32_t ph = 0;
#pragma unroll 1
    while (true) {
        mbar_wait(bars + B_REQ, ph);
        int j = 4095;
        const int jd = pick_job(lane, p.qmask, j);
        if (lane == 0) { sts32(bars + B_NEXT, (uint32_t)jd); sts32(bars + B_NEXT + 4, (uint32_t)j); mbar_arrive(bars + B_RSP); }
        ph ^= 1;
        if (jd == J_END) break;
        __syncwarp();
    }
}

__device__ __forceinline__ void producer(const Params& p, uint32_t sb) {
    Pipe pp{0, 1};
    const uint32_t bars = sb + SM_BAR;
    uint32_t seq = 0, h_seen = 0;
    mbar_arrive(bars + B_REQ);
#pragma unroll 1
    while (true) {
        mbar_wait(bars + B_RSP, seq & 1);
        const int jd = (int)lds32(bars + B_NEXT), j = (int)lds32(bars + B_NEXT + 4);
        int left = (jd & 255) == J_DN ? 15 : ((jd & 255) == J_QA ? (((jd >> 8) & 255) == NRB - 1 ? 10 : 12) : ((jd & 255) == J_O ? o_nk((jd >> 8) & 255) : ((jd & 255) == J_LN || (jd & 255) == J_LN1 || (jd & 255) == J_MOD ? 1 : 8)));
        left = max(left - PICK_AHEAD, 1);
        TR(j, 1);
        const int type = jd & 255, rb = (jd >> 8) & 255, cb = (jd >> 16) & 255;
        const bool fine = rb >= FINE_RB, acquired = (jd >> 24) & 1;
        bool first = true;
        auto begin_stage = [&](uint32_t bytes) -> uint32_t {
            mbar_wait(bars + B_EMPTY + pp.stage * 8, pp.phase);
            if (first) { sts32(bars + B_RING + (seq & 7) * 4, (uint32_t)jd); sts32(bars + B_RING + 32 + (seq & 7) * 4, (uint32_t)j); first = false; }
            const uint32_t fb = bars + B_FULL + pp.stage * 8;
            if (bytes) mbar_expect_tx(fb, bytes); else mbar_arrive(fb);
            if (--left == 0 && type != J_END) mbar_arrive(bars + B_REQ);
            return fb;
        };
        if (type == J_END || type == J_LN || type == J_LN1 || type == J_MOD) {
            if (type == J_LN) { if (!acquired) wait_flag(F_OP + rb, (unsigned)((tg_tab(rb) >> (8 * J_LN)) & 255)); if (!(h_seen >> 31)) { wait_flag(F_MOD + 1, 64); h_seen |= 1u << 31; } }

            TR(j, 2);
            begin_stage(0); pipe_next(pp);
            seq++;
            if (type == J_END) break;
            continue;
        }
        const CUtensorMap *ta, *tb0, *tb1;
        int k0 = 0, nk = 8, n0 = cb * 256, n1 = n0 + 128, nb = 4, dep = -1;
        unsigned tgt = 0;
        switch (type) {
            case J_KV: ta = &p.tm_h; tb0 = tb1 = cb < 16 ? &p.tm_wk : &p.tm_wv; n0 = (cb & 15) * 256; n1 = n0 + 128; dep = F_H + rb; tgt = 2 * NJ_LN1; break;
            case J_QA: ta = &p.tm_h; tb0 = tb1 = &p.tm_wq; dep = F_H + rb; tgt = 2 * NJ_LN1; if (rb == NRB - 1) { n0 = (cb >> 1) * 256; n1 = n0 + 128; } break;
            case J_O: ta = &p.tm_o; tb0 = tb1 = &p.tm_wo; n0 = (cb & 1) * 256; n1 = n0 + 128; nk = o_nk(rb); k0 = (cb >> 1) * nk * 64;
                      dep = F_O + rb; tgt = rb == NRB - 1 ? 64 : 32; break;
            case J_UP: ta = &p.tm_h2; tb0 = &p.tm_wg; tb1 = &p.tm_wu; n0 = n1 = cb * 128; dep = F_H2 + rb; tgt = 2 * NJ_LN; break;
            case J_UP2: ta = &p.tm_h2; tb0 = &p.tm_wg; tb1 = &p.tm_wu; n0 = n1 = cb * 64; nb = 2; dep = F_H2 + rb; tgt = 2 * NJ_LN2; break;
            default: ta = &p.tm_act; tb0 = tb1 = &p.tm_wd; n0 = cb * 64; nk = 0; break;
        }
        const int m0 = rb * 128;
        if (type == J_DN) {
#pragma unroll 1
            for (int kb = 0; kb < 14; kb++) {
                const uint32_t fb = begin_stage(49152);
                const uint32_t st = sb + pp.stage * W_STAGE;
                const int k = kb * 128;
                tma_load2d(st + 32768, tb0, n0, k, fb);
                tma_load2d(st + 40960, tb0, n0, k + 64, fb);
                if (kb == 0) { if (!acquired) { wait_flag(F_ACT + rb, 2 * (fine ? NJ_UP2 : NJ_UP)); asm volatile("fence.proxy.async.global;" ::: "memory"); } TR(j, 2); }
                tma_load2d(st, ta, k, m0, fb);
                tma_load2d(st + 8192, ta, k, m0 + 64, fb);
                tma_load2d(st + 16384, ta, k + 64, m0, fb);
                tma_load2d(st + 24576, ta, k + 64, m0 + 64, fb);
                pipe_next(pp);
            }
        }
#pragma unroll 1
        for (int kb = 0; kb < nk; kb++) {
            const uint32_t fb = begin_stage(16384 + nb * 8192);
            const uint32_t st = sb + pp.stage * W_STAGE;
            const int k = k0 + kb * 64;
            tma_load2d(st + 16384, tb0, n0, k, fb);
            if (nb == 4) {
                tma_load2d(st + 16384 + 8192, tb0, n0 + 64, k, fb);
                tma_load2d(st + 16384 + 16384, tb1, n1, k, fb);
                tma_load2d(st + 16384 + 24576, tb1, n1 + 64, k, fb);
            } else if (nb == 2) {
                tma_load2d(st + 16384 + 8192, tb1, n1, k, fb);
            }
            if (kb == 0) {
                if (acquired && dep < 16) h_seen |= 1u << dep;
                if (dep >= 0 && !acquired && !(dep < 16 && ((h_seen >> dep) & 1))) {
                    wait_flag(dep, tgt);
                    if (type != J_O) asm volatile("fence.proxy.async.global;" ::: "memory");
                    if (dep < 16) h_seen |= 1u << dep;
                }
                TR(j, 2);
            }
            tma_load2d(st, ta, k, m0, fb);
            tma_load2d(st + 8192, ta, k, m0 + 64, fb);
            pipe_next(pp);
        }
        if (type == J_QA) {
            wait_flag(F_KV + rb, 64);
#pragma unroll 1
            for (int i = 0; i < (rb == NRB - 1 ? 2 : 4); i++) {
                const uint32_t fb = begin_stage(40960);
                const uint32_t st = sb + pp.stage * W_STAGE;
                const int col = (i & 1) * HD_ + (rb == NRB - 1 ? cb : cb * 2 + (i >> 1)) * DH_;
                tma_load2d(st, &p.tm_kv, col, m0, fb);
                tma_load2d(st + 8192, &p.tm_kv, col, m0 + 64, fb);
                tma_load2d(st + 16384, &p.tm_kv, col + 64, m0, fb);
                tma_load2d(st + 24576, &p.tm_kv, col + 64, m0 + 64, fb);
                if (i == 0) { wait_flag(F_MEM + rb, 64); asm volatile("fence.proxy.async.global;" ::: "memory"); }
                tma_load2d(st + 32768, &p.tm_kvm, col, rb * 32, fb);
                tma_load2d(st + 36864, &p.tm_kvm, col + 64, rb * 32, fb);
                pipe_next(pp);
            }
        } else if (type == J_DN) {
            const uint32_t fb = begin_stage(16384);
            const uint32_t st = sb + pp.stage * W_STAGE;
            tma_load2d(st, &p.tm_x1, n0, m0, fb);
            tma_load2d(st + 8192, &p.tm_x1, n0, m0 + 64, fb);
            pipe_next(pp);
        }
        seq++;
    }
}

__device__ __forceinline__ void store_warp(const Params& p, uint32_t sb, int wg, int lane) {
    const uint32_t bars = sb + SM_BAR;
    uint32_t seq = 0;
#pragma unroll 1
    while (true) {
        bar_sync(NB_ST + wg, 160);
        const uint32_t jd = lds32(bars + B_RING + (seq & 7) * 4);
        seq++;
        const int type = jd & 255, rb = (jd >> 8) & 255, cb = (jd >> 16) & 255;
        if (type == J_END) break;
        const uint32_t src = sb + W_STG + wg * 16384;
        const CUtensorMap* tm = nullptr; int n0 = cb * 256, nbox = 4, mrow = rb * 128 + wg * 64, flag = 0;
        switch (type) {
            case J_KV: tm = &p.tm_kv; flag = F_KV + rb; break;
            case J_QA: tm = &p.tm_o; flag = F_O + rb; if (rb == NRB - 1) { n0 = cb * 128; nbox = 2; } break;
            case J_O: tm = &p.tm_op; n0 = (cb & 1) * 256; mrow = op_row(rb, cb >> 1) + wg * 64; flag = F_OP + rb; break;
            case J_LN: flag = F_H2 + rb; nbox = 0; break;
            case J_LN1: flag = F_H + rb; nbox = 0; break;
            case J_MOD: flag = F_MOD + rb; nbox = 0; break;
            case J_UP: tm = &p.tm_act; n0 = cb * 128; nbox = 2; flag = F_ACT + rb; break;
            case J_UP2: tm = &p.tm_act; n0 = cb * 64; nbox = 1; flag = F_ACT + rb; break;
            default: tm = &p.tm_out; n0 = cb * 64; nbox = 1; flag = -1; break;
        }
        if (nbox == 4) {
            if (lane == 0) {
                tma_store2d(tm, src, n0, mrow);
                tma_store2d(tm, src + 8192, n0 + 64, mrow);
                bulk_commit();
                asm volatile("cp.async.bulk.wait_group.read 0;" ::: "memory");
                mbar_arrive(bars + B_STGFREE + wg * 8);
            }
            __syncwarp();
            bar_sync(NB_ST + wg, 160);
            n0 += 128; nbox = 2;
        }
        if (lane == 0) {
            if (nbox) {
                tma_store2d(tm, src, n0, mrow);
                if (nbox == 2) tma_store2d(tm, src + 8192, n0 + 64, mrow);
                bulk_commit();
                asm volatile("cp.async.bulk.wait_group.read 0;" ::: "memory");
                mbar_arrive(bars + B_STGFREE + wg * 8);
                bulk_wait0();
                if (flag >= 0) asm volatile("red.relaxed.gpu.global.add.u32 [%0], 1;" :: "l"(&g_flags[flag]) : "memory");
            } else {
                mbar_arrive(bars + B_STGFREE + wg * 8);
                red_release(&g_flags[flag], 1);
            }
        }
        __syncwarp();
    }
}

__device__ __forceinline__ float gelu_tanh(float x) {
    const float t = x * fmaf(-0.10294324397f, x * x, -2.30220819814f);
    float r; asm("rcp.approx.ftz.f32 %0, %1;" : "=f"(r) : "f"(1.f + ex2(t)));
    return x * r;
}

#define CTR(i) do {} while (0)

__device__ __forceinline__ void ln2_row(const Params& p, int rb, int r, int lane) {
    const int row = rb * 128 + r, nsplit = 64 / o_nk(rb);
    const uint4* xr = (const uint4*)(p.x + (size_t)row * D_);
    const uint4 xa = __ldg(xr + lane), xb = __ldg(xr + 32 + lane);
    uint32_t ga[8], c1[8], sm[8];
    load_mod8(g_mod + 2 * D_, lane, ga);
    load_mod8(g_mod + 4 * D_, lane, c1);
    load_mod8(g_mod + 3 * D_, lane, sm);
    float a[16];
#pragma unroll
    for (int i = 0; i < 16; i++) a[i] = 0.f;
    const uint4* src = (const uint4*)(g_op + (size_t)(op_row(rb, 0) + r) * D_) + lane;
    const int sstride = (op_row(rb, 1) - op_row(rb, 0)) * (D_ / 8);
    uint4 u[2][8];
#pragma unroll
    for (int sp = 0; sp < 4; sp++) { u[0][2 * sp] = __ldcg(src + sp * sstride); u[0][2 * sp + 1] = __ldcg(src + sp * sstride + 32); }
    if (nsplit > 4) {
#pragma unroll
        for (int sp = 0; sp < 4; sp++) { u[1][2 * sp] = __ldcg(src + (4 + sp) * sstride); u[1][2 * sp + 1] = __ldcg(src + (4 + sp) * sstride + 32); }
    }
#pragma unroll 1
    for (int s0 = 0; s0 < nsplit; s0 += 4) {
#pragma unroll
        for (int sp = 0; sp < 8; sp++) {
            float* q = a + (sp & 1) * 8;
            const uint4 w = u[0][sp];
            q[0] += bflo(w.x); q[1] += bfhi(w.x); q[2] += bflo(w.y); q[3] += bfhi(w.y);
            q[4] += bflo(w.z); q[5] += bfhi(w.z); q[6] += bflo(w.w); q[7] += bfhi(w.w);
            u[0][sp] = u[1][sp];
        }
        if (s0 + 8 < nsplit) {
#pragma unroll
            for (int sp = 0; sp < 4; sp++) { u[1][2 * sp] = __ldcg(src + (s0 + 8 + sp) * sstride); u[1][2 * sp + 1] = __ldcg(src + (s0 + 8 + sp) * sstride + 32); }
        }
    }
    const uint32_t xv[8] = {xa.x, xa.y, xa.z, xa.w, xb.x, xb.y, xb.z, xb.w};
    uint32_t v[8], r8[8];
#pragma unroll
    for (int i = 0; i < 8; i++) v[i] = hadd2(xv[i], hmul2(ga[i], pack2(a[2 * i], a[2 * i + 1])));
    uint4* x1r = (uint4*)(g_x1 + (size_t)row * D_);
    x1r[lane] = make_uint4(v[0], v[1], v[2], v[3]); x1r[32 + lane] = make_uint4(v[4], v[5], v[6], v[7]);
    uint32_t mu2; float rden;
    ln_stats(v, mu2, rden);
#pragma unroll
    for (int i = 0; i < 8; i++) c1[i] = hadd2(c1[i], 0x3F803F80u);
    ln_apply(v, mu2, rden, c1, sm, r8);
    uint4* hr = (uint4*)(g_h2 + (size_t)row * D_);
    hr[lane] = make_uint4(r8[0], r8[1], r8[2], r8[3]); hr[32 + lane] = make_uint4(r8[4], r8[5], r8[6], r8[7]);
}

__device__ __forceinline__ void consumer(const Params& p, uint32_t sb, int warp, int lane) {
    const uint32_t bars = sb + SM_BAR;
    const int wg = warp >> 2, wl = warp & 3;
    const uint32_t l7 = lane & 7, l8 = lane >> 3, g = lane >> 2, t = lane & 3;
    Pipe pp{0, 0};
    uint32_t seq = 0, stg_phase = 1;
    const int srow = wl * 16 + l7 + (l8 & 1) * 8;
    const uint32_t stg_base = sb + W_STG + wg * 16384 + srow * 128;
    const uint32_t sx = ((lane >> 4) ^ (srow & 7)) << 4;
#pragma unroll 1
    while (true) {
        mbar_wait(bars + B_FULL + pp.stage * 8, pp.phase);
        const uint32_t jd = lds32(bars + B_RING + (seq & 7) * 4);
        CTR(3);
        seq++;
        const int type = jd & 255, rb = (jd >> 8) & 255, cb = (jd >> 16) & 255;
        if (type == J_END) { mbar_wait(bars + B_STGFREE + wg * 8, stg_phase); bar_arrive(NB_ST + wg, 160); break; }
        if (type == J_LN) {
            __syncwarp();
            if (lane == 0) mbar_arrive(bars + B_EMPTY + pp.stage * 8);
            pipe_next(pp);
            const int nr = rb >= FINE_RB ? 1 : 2;
#pragma unroll 1
            for (int rr = 0; rr < nr; rr++) ln2_row(p, rb, (cb * 8 + warp) * nr + rr, lane);
            mbar_wait(bars + B_STGFREE + wg * 8, stg_phase); stg_phase ^= 1;
            CTR(4); CTR(5);
            bar_arrive(NB_ST + wg, 160);
            continue;
        }
        if (type == J_DN || type == J_UP2) {
            float acc[64];
#pragma unroll
            for (int i = 0; i < 64; i++) acc[i] = 0.f;
            if (type == J_DN) {
#pragma unroll 1
                for (int kb = 0; kb < 14; kb++) {
                    if (kb) mbar_wait(bars + B_FULL + pp.stage * 8, pp.phase);
                    const uint32_t st = sb + pp.stage * W_STAGE;
                    const uint64_t da = mkdesc(st + wg * 8192, 16, 1024), db = mkdesc(st + 32768, 8192, 1024);
                    wg_fence();
#pragma unroll
                    for (int ks = 0; ks < 8; ks++) wgmma_n64(acc, da + (ks >> 2) * 1024 + (ks & 3) * 2, db + ks * 128);
                    wg_commit();
                    wg_wait0();
                    if (lane == 0) mbar_arrive(bars + B_EMPTY + pp.stage * 8);
                    pipe_next(pp);
                }
            } else {
#pragma unroll 1
                for (int kb = 0; kb < 8; kb++) {
                    if (kb) mbar_wait(bars + B_FULL + pp.stage * 8, pp.phase);
                    const uint32_t st = sb + pp.stage * W_STAGE;
                    const uint64_t da = mkdesc(st + wg * 8192, 16, 1024), db = mkdesc(st + 16384, 8192, 1024);
                    wg_fence();
#pragma unroll
                    for (int ks = 0; ks < 4; ks++) wgmma_n128(acc, da + ks * 2, db + ks * 128, 1);
                    wg_commit();
                    wg_wait0();
                    if (lane == 0) mbar_arrive(bars + B_EMPTY + pp.stage * 8);
                    pipe_next(pp);
                }
            }
            CTR(4);
            if (type == J_UP2) {
                mbar_wait(bars + B_STGFREE + wg * 8, stg_phase); stg_phase ^= 1;
#pragma unroll
                for (int j = 0; j < 4; j++) {
                    uint32_t r[4];
#pragma unroll
                    for (int q = 0; q < 4; q++) {
                        const uint32_t gw = pack2(acc[8 * j + 2 * q], acc[8 * j + 2 * q + 1]);
                        const uint32_t uw = pack2(acc[32 + 8 * j + 2 * q], acc[32 + 8 * j + 2 * q + 1]);
                        r[q] = hmul2(pack2(gelu_tanh(bflo(gw)), gelu_tanh(bfhi(gw))), uw);
                    }
                    stsm4(stg_base + (sx ^ (j << 5)), r[0], r[1], r[2], r[3]);
                }
            } else {
                mbar_wait(bars + B_FULL + pp.stage * 8, pp.phase);
                const uint32_t st = sb + pp.stage * W_STAGE;
                mbar_wait(bars + B_STGFREE + wg * 8, stg_phase); stg_phase ^= 1;
                const uint32_t* gb = (const uint32_t*)(g_mod + 5 * D_ + cb * 64) + t;
                const uint32_t xa = st + wg * 8192 + (wl * 16 + g) * 128 + (g << 4) + t * 4;
#pragma unroll
                for (int j = 0; j < 4; j++) {
                    uint32_t r[4];
#pragma unroll
                    for (int q = 0; q < 4; q++) {
                        const int nt = 2 * j + (q >> 1);
                        const uint32_t xw = lds32((xa ^ ((nt & 7) << 4)) + (nt >> 3) * 16384 + (q & 1) * 1024);
                        r[q] = hadd2(xw, hmul2(__ldcg(gb + nt * 4), pack2(acc[8 * j + 2 * q], acc[8 * j + 2 * q + 1])));
                    }
                    stsm4(stg_base + (j >> 2) * 8192 + (sx ^ ((2 * j & 7) << 4)), r[0], r[1], r[2], r[3]);
                }
                __syncwarp();
                if (lane == 0) mbar_arrive(bars + B_EMPTY + pp.stage * 8);
                pipe_next(pp);
            }
            fence_async_smem();
            CTR(5);
            bar_arrive(NB_ST + wg, 160);
            continue;
        }
        float acc[128];
#pragma unroll
        for (int i = 0; i < 128; i++) acc[i] = 0.f;
        const int nk = type == J_O ? o_nk(rb) : 8;
#pragma unroll 1
        for (int kb = 0; kb < nk; kb++) {
            if (kb) mbar_wait(bars + B_FULL + pp.stage * 8, pp.phase);
            const uint32_t st = sb + pp.stage * W_STAGE;
            const uint64_t da = mkdesc(st + wg * 8192, 16, 1024), db = mkdesc(st + 16384, 8192, 1024);
            wg_fence();
#pragma unroll
            for (int ks = 0; ks < 4; ks++) wgmma_n256(acc, da + ks * 2, db + ks * 128, 1);
            wg_commit();
            wg_wait0();
            if (lane == 0) mbar_arrive(bars + B_EMPTY + pp.stage * 8);
            pipe_next(pp);
        }
        CTR(4);
        if (type == J_QA) {
            uint32_t qf[64];
#pragma unroll
            for (int i = 0; i < 64; i++) qf[i] = pack2(acc[2 * i], acc[2 * i + 1]);
            const int sg = warp >> 1, half = warp & 1;
            const float sc = 0.08838834764831845f * 1.4426950408889634f;
            const uint32_t xoff = (sg >> 1) * 8192 + ((sg & 1) * 32 + l7) * 128;
            const uint32_t moff = 32768 + (sg * 8 + l7) * 128;
            const uint32_t kch = (l8 ^ l7) << 4;
            const uint32_t vch = ((l8 & 1) ^ l7) << 4;
            if (rb == NRB - 1 && (cb & 1)) {
#pragma unroll
                for (int i = 0; i < 32; i++) qf[i] = qf[32 + i];
            }
#pragma unroll 1
            for (int hh = rb == NRB - 1; hh < 2; hh++) {
                mbar_wait(bars + B_FULL + pp.stage * 8, pp.phase);
                uint32_t st = sb + pp.stage * W_STAGE;
                float sa[5][4];
#pragma unroll
                for (int n = 0; n < 5; n++) sa[n][0] = sa[n][1] = sa[n][2] = sa[n][3] = 0.f;
#pragma unroll
                for (int i = 0; i < 4; i++) {
                    const uint32_t* q = qf + i * 8;
                    uint32_t kk[5][4];
                    ldsm4(kk[0][0], kk[0][1], kk[0][2], kk[0][3], st + moff + (i >> 1) * 4096 + (kch ^ ((i & 1) * 64)));
#pragma unroll
                    for (int n = 1; n < 5; n++)
                        ldsm4(kk[n][0], kk[n][1], kk[n][2], kk[n][3], st + xoff + (n - 1) * 1024 + (i >> 1) * 16384 + (kch ^ ((i & 1) * 64)));
#pragma unroll
                    for (int n = 0; n < 5; n++) mma16816(sa[n], q[0], q[1], q[2], q[3], kk[n][0], kk[n][1]);
#pragma unroll
                    for (int n = 0; n < 5; n++) mma16816(sa[n], q[4], q[5], q[6], q[7], kk[n][2], kk[n][3]);
                }
                __syncwarp();
                if (lane == 0) mbar_arrive(bars + B_EMPTY + pp.stage * 8);
                pipe_next(pp);
                const int iq0 = half * 16 + g - 2 * t, iq1 = iq0 + 8;
                float m0 = fmaxf(sa[0][0], sa[0][1]), m1 = fmaxf(sa[0][2], sa[0][3]);
#pragma unroll
                for (int n = 1; n < 5; n++) {
#pragma unroll
                    for (int e = 0; e < 2; e++) {
                        const int jx = (n - 1) * 8 + e;
                        if (jx > iq0) sa[n][e] = -3.0e38f;
                        if (jx > iq1) sa[n][2 + e] = -3.0e38f;
                        m0 = fmaxf(m0, sa[n][e]); m1 = fmaxf(m1, sa[n][2 + e]);
                    }
                }
                m0 = fmaxf(m0, __shfl_xor_sync(~0u, m0, 1)); m1 = fmaxf(m1, __shfl_xor_sync(~0u, m1, 1));
                m0 = fmaxf(m0, __shfl_xor_sync(~0u, m0, 2)); m1 = fmaxf(m1, __shfl_xor_sync(~0u, m1, 2));
                m0 *= -sc; m1 *= -sc;
                float l0 = 0.f, l1 = 0.f;
                uint32_t p0[5], p1[5];
#pragma unroll
                for (int n = 0; n < 5; n++) {
                    const float e0 = ex2(fmaf(sa[n][0], sc, m0)), e1 = ex2(fmaf(sa[n][1], sc, m0));
                    const float e2 = ex2(fmaf(sa[n][2], sc, m1)), e3 = ex2(fmaf(sa[n][3], sc, m1));
                    l0 += e0 + e1; l1 += e2 + e3;
                    p0[n] = pack2(e0, e1); p1[n] = pack2(e2, e3);
                }
                l0 += __shfl_xor_sync(~0u, l0, 1); l1 += __shfl_xor_sync(~0u, l1, 1);
                l0 += __shfl_xor_sync(~0u, l0, 2); l1 += __shfl_xor_sync(~0u, l1, 2);
                const float i0 = __fdividef(1.f, l0), i1 = __fdividef(1.f, l1);
                mbar_wait(bars + B_FULL + pp.stage * 8, pp.phase);
                st = sb + pp.stage * W_STAGE;
                mbar_wait(bars + B_STGFREE + wg * 8, stg_phase); stg_phase ^= 1;
#pragma unroll
                for (int i = 0; i < 32; i++) qf[i] = qf[32 + i];
#pragma unroll 1
                for (int bx = 0; bx < 2; bx++) {
                    float o[8][4];
                    uint32_t vm[8], v0[4][4], v1[4][4];
#pragma unroll
                    for (int ep = 0; ep < 4; ep++) {
                        ldsm2t(vm[2 * ep], vm[2 * ep + 1], st + moff + bx * 4096 + (vch ^ (ep << 5)));
                        const uint32_t va = st + xoff + (l8 >> 1) * 1024 + bx * 16384 + (vch ^ (ep << 5));
                        ldsm4t(v0[ep][0], v0[ep][1], v0[ep][2], v0[ep][3], va);
                        ldsm4t(v1[ep][0], v1[ep][1], v1[ep][2], v1[ep][3], va + 2048);
                    }
#pragma unroll
                    for (int n = 0; n < 8; n++) { o[n][0] = o[n][1] = o[n][2] = o[n][3] = 0.f; mma16816(o[n], p0[0], p1[0], p0[1], p1[1], vm[n], v0[n >> 1][n & 1]); }
#pragma unroll
                    for (int n = 0; n < 8; n++) mma16816(o[n], p0[2], p1[2], p0[3], p1[3], v0[n >> 1][2 + (n & 1)], v1[n >> 1][n & 1]);
#pragma unroll
                    for (int n = 0; n < 8; n++) mma1688(o[n], p0[4], p1[4], v1[n >> 1][2 + (n & 1)]);
#pragma unroll
                    for (int ep = 0; ep < 4; ep++)
                        stsm4(stg_base + bx * 8192 + (sx ^ (ep << 5)),
                              pack2(o[2 * ep][0] * i0, o[2 * ep][1] * i0), pack2(o[2 * ep][2] * i1, o[2 * ep][3] * i1),
                              pack2(o[2 * ep + 1][0] * i0, o[2 * ep + 1][1] * i0), pack2(o[2 * ep + 1][2] * i1, o[2 * ep + 1][3] * i1));
                }
                __syncwarp();
                if (lane == 0) mbar_arrive(bars + B_EMPTY + pp.stage * 8);
                pipe_next(pp);
                if (hh == 0) { fence_async_smem(); bar_arrive(NB_ST + wg, 160); }
            }
        } else if (type == J_UP) {
            mbar_wait(bars + B_STGFREE + wg * 8, stg_phase); stg_phase ^= 1;
#pragma unroll
            for (int j = 0; j < 8; j++) {
                uint32_t r[4];
#pragma unroll
                for (int q = 0; q < 4; q++) {
                    const uint32_t gw = pack2(acc[8 * j + 2 * q], acc[8 * j + 2 * q + 1]);
                    const uint32_t uw = pack2(acc[64 + 8 * j + 2 * q], acc[64 + 8 * j + 2 * q + 1]);
                    r[q] = hmul2(pack2(gelu_tanh(bflo(gw)), gelu_tanh(bfhi(gw))), uw);
                }
                stsm4(stg_base + (j >> 2) * 8192 + (sx ^ ((2 * j & 7) << 4)), r[0], r[1], r[2], r[3]);
            }
        } else {
#pragma unroll
            for (int rd = 0; rd < 2; rd++) {
                mbar_wait(bars + B_STGFREE + wg * 8, stg_phase); stg_phase ^= 1;
#pragma unroll
                for (int j = rd * 8; j < rd * 8 + 8; j++)
                    stsm4(stg_base + ((j >> 2) & 1) * 8192 + (sx ^ ((2 * j & 7) << 4)),
                          pack2(acc[8 * j], acc[8 * j + 1]), pack2(acc[8 * j + 2], acc[8 * j + 3]),
                          pack2(acc[8 * j + 4], acc[8 * j + 5]), pack2(acc[8 * j + 6], acc[8 * j + 7]));
                if (rd == 0) { fence_async_smem(); bar_arrive(NB_ST + wg, 160); }
            }
        }
        fence_async_smem();
        CTR(5);
        bar_arrive(NB_ST + wg, 160);
    }
}

__global__ void __launch_bounds__(384, 1) k_work(const __grid_constant__ Params p) {
    extern __shared__ __align__(1024) unsigned char smem_raw[];
    const uint32_t sb = smem_u32(smem_raw);
    if (sb & 1023) __trap();
    const int warp = __shfl_sync(~0u, threadIdx.x >> 5, 0);
    int lane; asm volatile("mov.u32 %0, %%laneid;" : "=r"(lane));
    if (threadIdx.x == 0) {
        const uint32_t bars = sb + SM_BAR;
        for (int i = 0; i < W_NST; i++) { mbar_init(bars + B_FULL + i * 8, 1); mbar_init(bars + B_EMPTY + i * 8, 8); }
        mbar_init(bars + B_STGFREE, 1); mbar_init(bars + B_STGFREE + 8, 1); mbar_init(bars + B_REQ, 1); mbar_init(bars + B_RSP, 1);
        asm volatile("fence.mbarrier_init.release.cluster;" ::: "memory");
    }
    __syncthreads();
    if (warp < 8) {
        asm volatile("setmaxnreg.inc.sync.aligned.u32 224;");
        consumer(p, sb, warp, lane);
    } else {
        asm volatile("setmaxnreg.dec.sync.aligned.u32 56;");
        if (warp == 8) { if (lane == 0) producer(p, sb); }
        else if (warp < 11) store_warp(p, sb, warp - 9, lane);
        else scheduler(p, sb, lane);
        __syncwarp();
        bar_sync(NB_W0, 128);
        if (warp == 8 && p.qmask == 0xff) {
            unsigned last = 0;
            if (lane == 0) { __threadfence(); last = atomicAdd(&g_flags[F_DONE], 1u) == gridDim.x - 1; }
            if (__shfl_sync(~0u, last, 0))
                for (int i = lane; i < F_TOTAL; i += 32) g_flags[i] = 0;
        }
    }
}

typedef CUresult (*EncodeFn)(CUtensorMap*, CUtensorMapDataType, cuuint32_t, void*, const cuuint64_t*, const cuuint64_t*,
                             const cuuint32_t*, const cuuint32_t*, CUtensorMapInterleave, CUtensorMapSwizzle,
                             CUtensorMapL2promotion, CUtensorMapFloatOOBfill);

static void make_map(EncodeFn enc, CUtensorMap* m, const void* ptr, uint64_t rows, uint64_t cols, uint32_t box_rows) {
    cuuint64_t dims[2] = {cols, rows};
    cuuint64_t strides[1] = {cols * 2};
    cuuint32_t box[2] = {64, box_rows};
    cuuint32_t es[2] = {1, 1};
    enc(m, CU_TENSOR_MAP_DATA_TYPE_BFLOAT16, 2, const_cast<void*>(ptr), dims, strides, box, es, CU_TENSOR_MAP_INTERLEAVE_NONE,
        CU_TENSOR_MAP_SWIZZLE_128B, CU_TENSOR_MAP_L2_PROMOTION_L2_256B, CU_TENSOR_MAP_FLOAT_OOB_FILL_NONE);
}
template <typename T> static void* sym_addr(T& sym) { void* p = nullptr; cudaGetSymbolAddress(&p, sym); return p; }

extern "C" void kernel_launch(void* const* d_in, const int* in_sizes, int n_in, void* d_out, int out_size) {
    static Params prm;
    static RecParams rp;
    static bool ready = false;
    static const void* key[14];
    bool same = ready;
    for (int i = 0; i < 13 && same; i++) same = key[i] == d_in[i];
    same = same && key[13] == d_out;
    if (!same) {
        void* fn = nullptr;
        cudaDriverEntryPointQueryResult qr;
        cudaGetDriverEntryPoint("cuTensorMapEncodeTiled", &fn, cudaEnableDefault, &qr);
        EncodeFn enc = (EncodeFn)fn;
        make_map(enc, &prm.tm_h, sym_addr(g_h), S_, D_, 64);
        make_map(enc, &prm.tm_kv, sym_addr(g_kv), S_, 2 * HD_, 64);
        make_map(enc, &prm.tm_kvm, sym_addr(g_kvm), NSEG * 8, 2 * HD_, 32);
        make_map(enc, &prm.tm_o, sym_addr(g_o), S_, HD_, 64);
        make_map(enc, &prm.tm_op, sym_addr(g_op), OP_ROWS, D_, 64);
        make_map(enc, &prm.tm_h2, sym_addr(g_h2), S_, D_, 64);
        make_map(enc, &prm.tm_act, sym_addr(g_act), S_, DF_, 64);
        make_map(enc, &prm.tm_x1, sym_addr(g_x1), S_, D_, 64);
        make_map(enc, &prm.tm_out, d_out, S_, D_, 64);
        make_map(enc, &prm.tm_wq, d_in[2], D_, HD_, 64);
        make_map(enc, &prm.tm_wk, d_in[3], D_, HD_, 64);
        make_map(enc, &prm.tm_wv, d_in[4], D_, HD_, 64);
        make_map(enc, &prm.tm_wo, d_in[5], HD_, D_, 64);
        make_map(enc, &prm.tm_wg, d_in[8], D_, DF_, 64);
        make_map(enc, &prm.tm_wu, d_in[9], D_, DF_, 64);
        make_map(enc, &prm.tm_wd, d_in[10], DF_, D_, 64);
        prm.x = (const bf16*)d_in[0]; prm.c = (const bf16*)d_in[11]; prm.w_mod = (const bf16*)d_in[12];
        rp.mem0 = (const bf16*)d_in[1]; rp.x = prm.x; rp.c = prm.c; rp.w_mod = prm.w_mod;
        rp.wq = (const bf16*)d_in[2]; rp.wk = (const bf16*)d_in[3]; rp.wv = (const bf16*)d_in[4]; rp.wo = (const bf16*)d_in[5];
        cudaFuncSetAttribute(k_work, cudaFuncAttributeMaxDynamicSharedMemorySize, SMEM_BYTES);
        cudaFuncSetAttribute(k_rec, cudaFuncAttributeMaxDynamicSharedMemorySize, R_SMEM);
        cudaFuncSetAttribute(k_rec, cudaFuncAttributeNonPortableClusterSizeAllowed, 1);
        {
            cudaLaunchConfig_t cfg = {};
            cfg.gridDim = dim3(128); cfg.blockDim = dim3(384); cfg.dynamicSmemBytes = R_SMEM;
            cudaLaunchAttribute at[1];
            at[0].id = cudaLaunchAttributeClusterDimension; at[0].val.clusterDim.x = 16; at[0].val.clusterDim.y = 1; at[0].val.clusterDim.z = 1;
            cfg.attrs = at; cfg.numAttrs = 1;
            int n = 0;
            cudaOccupancyMaxActiveClusters(&n, k_rec, &cfg);
            rp.ncl = n < 4 ? 4 : (n > 8 ? 8 : n);
        }
        for (int i = 0; i < 13; i++) key[i] = d_in[i];
        key[13] = d_out;
        ready = true;
    }
    cudaStream_t st = cudaStreamPerThread;
    auto launch_rec = [&]() {
        cudaLaunchConfig_t cfg = {};
        cfg.gridDim = dim3(16 * rp.ncl); cfg.blockDim = dim3(384); cfg.dynamicSmemBytes = R_SMEM; cfg.stream = st;
        cudaLaunchAttribute at[1];
        at[0].id = cudaLaunchAttributeClusterDimension; at[0].val.clusterDim.x = 16; at[0].val.clusterDim.y = 1; at[0].val.clusterDim.z = 1;
        cfg.attrs = at; cfg.numAttrs = 1;
        cudaLaunchKernelEx(&cfg, k_rec, rp);
    };
    auto launch_work = [&](int qmask, int pdl) {
        prm.qmask = qmask;
        cudaLaunchConfig_t cfg = {};
        cfg.gridDim = dim3(132); cfg.blockDim = dim3(384); cfg.dynamicSmemBytes = SMEM_BYTES; cfg.stream = st;
        cudaLaunchAttribute at[1];
        at[0].id = cudaLaunchAttributeProgrammaticStreamSerialization; at[0].val.programmaticStreamSerializationAllowed = 1;
        cfg.attrs = at; cfg.numAttrs = pdl;
        cudaLaunchKernelEx(&cfg, k_work, prm);
    };
    launch_rec();
    launch_work(0xff, 1);
}
```

```cpp
#include <cuda_runtime.h>
#include <cuda_bf16.h>
#include <cuda.h>
#include <stdint.h>

typedef __nv_bfloat16 bf16;
#define PF_NS 500
#define IDLE_NS 150
#define FLAG_NS 20

constexpr int S_ = 2048, D_ = 512, H_ = 32, DH_ = 128, HD_ = 4096, NSEG = 64, DF_ = 1792;
constexpr int NRB = 16;
constexpr int OSPLIT = 4;

__device__ __align__(1024) bf16 g_h[S_ * D_];
__device__ __align__(1024) bf16 g_kv[S_ * 2 * HD_];
__device__ __align__(1024) bf16 g_kvm[NSEG * 8 * 2 * HD_];
__device__ __align__(1024) bf16 g_o[S_ * HD_];
#define FINE_RB_ 12
constexpr int FINE_RB = FINE_RB_;
#define OSPLIT2_ 8
constexpr int OSPLIT2 = OSPLIT2_;
constexpr int OSPLIT3 = 16;
constexpr int OP_ROWS = OSPLIT * S_ + OSPLIT2 * (NRB - FINE_RB) * 128 + OSPLIT3 * 128;
__device__ __align__(1024) bf16 g_op[OP_ROWS * D_];
__device__ __align__(1024) bf16 g_x1[S_ * D_];
__device__ __align__(1024) bf16 g_h2[S_ * D_];
__device__ __align__(1024) bf16 g_act[S_ * DF_];
__device__ __align__(1024) bf16 g_mod[6 * D_];
__device__ uint32_t g_Fraw[131072 + 65536 + 2048];
#define g_F ((uint32_t*)(((uint64_t)g_Fraw + 0x7FFFFull) & ~0x7FFFFull))
constexpr int F_H = 0, F_MEM = 32, F_O = 64, F_OP = 96, F_H2 = 128, F_ACT = 160, F_MOD = 192, F_KV = 224, F_CLAIM = 256  ,
              F_SIDE = 512  , F_DONE = 576, F_TOTAL = 608;
__device__ __align__(128) unsigned int g_flags[F_TOTAL];
#define TR(j, i) do {} while (0)

__device__ __forceinline__ uint32_t smem_u32(const void* p) { return (uint32_t)__cvta_generic_to_shared(p); }
__device__ __forceinline__ uint32_t clk32() { uint32_t c; asm volatile("mov.u32 %0, %%clock;" : "=r"(c)); return c; }
__device__ __forceinline__ uint32_t mapa_u32(uint32_t addr, uint32_t rank) {
    uint32_t r; asm volatile("mapa.shared::cluster.u32 %0, %1, %2;" : "=r"(r) : "r"(addr), "r"(rank)); return r;
}
__device__ __forceinline__ void mbar_init(uint32_t bar, uint32_t cnt) {
    asm volatile("mbarrier.init.shared::cta.b64 [%0], %1;" :: "r"(bar), "r"(cnt) : "memory");
}
__device__ __forceinline__ void mbar_inval(uint32_t bar) {
    asm volatile("mbarrier.inval.shared::cta.b64 [%0];" :: "r"(bar) : "memory");
}
__device__ __forceinline__ void mbar_expect_tx(uint32_t bar, uint32_t bytes) {
    asm volatile("mbarrier.arrive.expect_tx.shared::cta.b64 _, [%0], %1;" :: "r"(bar), "r"(bytes) : "memory");
}
__device__ __forceinline__ void mbar_arrive(uint32_t bar) {
    asm volatile("mbarrier.arrive.shared::cta.b64 _, [%0];" :: "r"(bar) : "memory");
}
__device__ __forceinline__ bool mbar_try_wait(uint32_t bar, uint32_t parity) {
    uint32_t ok;
    asm volatile("{\n.reg .pred p;\nmbarrier.try_wait.parity.shared::cta.b64 p, [%1], %2;\nselp.u32 %0, 1, 0, p;\n}"
                 : "=r"(ok) : "r"(bar), "r"(parity) : "memory");
    return ok;
}
__device__ __forceinline__ bool mbar_try_wait_cluster(uint32_t bar, uint32_t parity) {
    uint32_t ok;
    asm volatile("{\n.reg .pred p;\nmbarrier.try_wait.parity.acquire.cluster.shared::cta.b64 p, [%1], %2;\nselp.u32 %0, 1, 0, p;\n}"
                 : "=r"(ok) : "r"(bar), "r"(parity) : "memory");
    return ok;
}
constexpr int SPIN_LIMIT = 1 << 18;
#define TIMEOUT(code, info) do {} while (0)
__device__ __forceinline__ void mbar_wait(uint32_t bar, uint32_t parity) {
    int g = 0;
#pragma unroll 1
    while (!mbar_try_wait(bar, parity)) { if (++g >= SPIN_LIMIT) { TIMEOUT(0, bar & 255); break; } }
}
__device__ __forceinline__ void mbar_wait_cluster(uint32_t bar, uint32_t parity) {
    int g = 0;
#pragma unroll 1
    while (!mbar_try_wait_cluster(bar, parity)) { if (++g >= SPIN_LIMIT) { TIMEOUT(1, bar & 255); break; } }
}
__device__ __forceinline__ void bar_sync(int id, int n) { asm volatile("bar.sync %0, %1;" :: "r"(id), "r"(n) : "memory"); }
__device__ __forceinline__ void bar_arrive(int id, int n) { asm volatile("bar.arrive %0, %1;" :: "r"(id), "r"(n) : "memory"); }
__device__ __forceinline__ void cluster_sync_all() {
    asm volatile("barrier.cluster.arrive.aligned;\nbarrier.cluster.wait.aligned;" ::: "memory");
}
__device__ __forceinline__ void st_async_v2(uint32_t addr, float a, float b, uint32_t bar) {
    asm volatile("st.async.weak.shared::cluster.mbarrier::complete_tx::bytes.v2.f32 [%0], {%1,%2}, [%3];"
                 :: "r"(addr), "f"(a), "f"(b), "r"(bar) : "memory");
}
__device__ __forceinline__ void st_async_v4(uint32_t addr, uint4 v, uint32_t bar) {
    asm volatile("st.async.weak.shared::cluster.mbarrier::complete_tx::bytes.v4.b32 [%0], {%1,%2,%3,%4}, [%5];"
                 :: "r"(addr), "r"(v.x), "r"(v.y), "r"(v.z), "r"(v.w), "r"(bar) : "memory");
}
__device__ __forceinline__ uint2 ldg_relaxed2(const uint2* p) {
    uint2 v;
    asm volatile("ld.relaxed.gpu.global.v2.b32 {%0,%1}, [%2];" : "=r"(v.x), "=r"(v.y) : "l"(p) : "memory");
    return v;
}
__device__ __forceinline__ void stg_relaxed2(uint2* p, uint2 v) {
    asm volatile("st.relaxed.gpu.global.v2.b32 [%0], {%1,%2};" :: "l"(p), "r"(v.x), "r"(v.y) : "memory");
}
__device__ __forceinline__ uint4 ldg_relaxed(const uint4* p) {
    uint4 v;
    asm volatile("ld.relaxed.gpu.global.v4.b32 {%0,%1,%2,%3}, [%4];" : "=r"(v.x), "=r"(v.y), "=r"(v.z), "=r"(v.w) : "l"(p) : "memory");
    return v;
}
__device__ __forceinline__ void stg_relaxed(uint4* p, uint4 v) {
    asm volatile("st.relaxed.gpu.global.v4.b32 [%0], {%1,%2,%3,%4};" :: "l"(p), "r"(v.x), "r"(v.y), "r"(v.z), "r"(v.w) : "memory");
}
__device__ __forceinline__ void stg_relaxed32(uint32_t* p, uint32_t v) {
    asm volatile("st.relaxed.gpu.global.b32 [%0], %1;" :: "l"(p), "r"(v) : "memory");
}
__device__ __forceinline__ uint32_t ldg_relaxed32(const uint32_t* p) {
    uint32_t v; asm volatile("ld.relaxed.gpu.global.b32 %0, [%1];" : "=r"(v) : "l"(p) : "memory"); return v;
}
__device__ __forceinline__ unsigned int ld_acquire(const unsigned int* p) {
    unsigned int v; asm volatile("ld.acquire.gpu.global.u32 %0, [%1];" : "=r"(v) : "l"(p) : "memory"); return v;
}
__device__ __forceinline__ void red_release(unsigned int* p, unsigned int v) {
    asm volatile("red.release.gpu.global.add.u32 [%0], %1;" :: "l"(p), "r"(v) : "memory");
}
__device__ __forceinline__ void wait_flag(int idx, unsigned int target) {
    const unsigned int* p = &g_flags[idx];
    int g = 0;
#pragma unroll 1
    while (ld_acquire(p) < target) { __nanosleep(FLAG_NS); if (++g >= 64 * SPIN_LIMIT) { TIMEOUT(2, idx); break; } }
}
__device__ __forceinline__ void cp_async16(uint32_t dst, const void* src) {
    asm volatile("cp.async.cg.shared.global [%0], [%1], 16;" :: "r"(dst), "l"(src) : "memory");
}
__device__ __forceinline__ void cp_async_commit() { asm volatile("cp.async.commit_group;" ::: "memory"); }
template <int N> __device__ __forceinline__ void cp_async_wait() { asm volatile("cp.async.wait_group %0;" :: "n"(N) : "memory"); }
__device__ __forceinline__ void ldsm4(uint32_t& r0, uint32_t& r1, uint32_t& r2, uint32_t& r3, uint32_t addr) {
    asm volatile("ldmatrix.sync.aligned.m8n8.x4.shared.b16 {%0,%1,%2,%3}, [%4];" : "=r"(r0), "=r"(r1), "=r"(r2), "=r"(r3) : "r"(addr) : "memory");
}
__device__ __forceinline__ void ldsm4t(uint32_t& r0, uint32_t& r1, uint32_t& r2, uint32_t& r3, uint32_t addr) {
    asm volatile("ldmatrix.sync.aligned.m8n8.x4.trans.shared.b16 {%0,%1,%2,%3}, [%4];" : "=r"(r0), "=r"(r1), "=r"(r2), "=r"(r3) : "r"(addr) : "memory");
}
__device__ __forceinline__ void ldsm2t(uint32_t& r0, uint32_t& r1, uint32_t addr) {
    asm volatile("ldmatrix.sync.aligned.m8n8.x2.trans.shared.b16 {%0,%1}, [%2];" : "=r"(r0), "=r"(r1) : "r"(addr) : "memory");
}
__device__ __forceinline__ void stsm4(uint32_t addr, uint32_t r0, uint32_t r1, uint32_t r2, uint32_t r3) {
    asm volatile("stmatrix.sync.aligned.m8n8.x4.shared.b16 [%0], {%1,%2,%3,%4};" :: "r"(addr), "r"(r0), "r"(r1), "r"(r2), "r"(r3) : "memory");
}
__device__ __forceinline__ void stsm2t(uint32_t addr, uint32_t r0, uint32_t r1) {
    asm volatile("stmatrix.sync.aligned.m8n8.x2.trans.shared.b16 [%0], {%1,%2};" :: "r"(addr), "r"(r0), "r"(r1) : "memory");
}
__device__ __forceinline__ void mma16816(float* d, uint32_t a0, uint32_t a1, uint32_t a2, uint32_t a3, uint32_t b0, uint32_t b1) {
    asm volatile("mma.sync.aligned.m16n8k16.row.col.f32.bf16.bf16.f32 {%0,%1,%2,%3}, {%4,%5,%6,%7}, {%8,%9}, {%0,%1,%2,%3};"
                 : "+f"(d[0]), "+f"(d[1]), "+f"(d[2]), "+f"(d[3]) : "r"(a0), "r"(a1), "r"(a2), "r"(a3), "r"(b0), "r"(b1));
}
__device__ __forceinline__ void mma1688(float* d, uint32_t a0, uint32_t a1, uint32_t b0) {
    asm volatile("mma.sync.aligned.m16n8k8.row.col.f32.bf16.bf16.f32 {%0,%1,%2,%3}, {%4,%5}, {%6}, {%0,%1,%2,%3};"
                 : "+f"(d[0]), "+f"(d[1]), "+f"(d[2]), "+f"(d[3]) : "r"(a0), "r"(a1), "r"(b0));
}
__device__ __forceinline__ void mma16816h(float* d, uint32_t a0, uint32_t a2, uint32_t b0, uint32_t b1) {
    asm volatile("{\n.reg .b32 ju, jv;\nmma.sync.aligned.m16n8k16.row.col.f32.bf16.bf16.f32 {%0,%1,%2,%3}, {%4,ju,%5,jv}, {%6,%7}, {%0,%1,%2,%3};\n}"
                 : "+f"(d[0]), "+f"(d[1]), "+f"(d[2]), "+f"(d[3]) : "r"(a0), "r"(a2), "r"(b0), "r"(b1));
}
__device__ __forceinline__ void mma1688h(float* d, uint32_t a0, uint32_t b0) {
    asm volatile("{\n.reg .b32 ju;\nmma.sync.aligned.m16n8k8.row.col.f32.bf16.bf16.f32 {%0,%1,%2,%3}, {%4,ju}, {%5}, {%0,%1,%2,%3};\n}"
                 : "+f"(d[0]), "+f"(d[1]), "+f"(d[2]), "+f"(d[3]) : "r"(a0), "r"(b0));
}
__device__ __forceinline__ uint32_t pack2(float lo, float hi) {
    uint32_t r; asm("cvt.rn.bf16x2.f32 %0, %1, %2;" : "=r"(r) : "f"(hi), "f"(lo)); return r;
}
__device__ __forceinline__ float bflo(uint32_t w) { return __uint_as_float(w << 16); }
__device__ __forceinline__ float bfhi(uint32_t w) { return __uint_as_float(w & 0xffff0000u); }
__device__ __forceinline__ float rbf(float x) { return __bfloat162float(__float2bfloat16_rn(x)); }
__device__ __forceinline__ float ex2(float x) { float y; asm("ex2.approx.ftz.f32 %0, %1;" : "=f"(y) : "f"(x)); return y; }
__device__ __forceinline__ void sts128(uint32_t addr, uint4 v) {
    asm volatile("st.shared.v4.b32 [%0], {%1,%2,%3,%4};" :: "r"(addr), "r"(v.x), "r"(v.y), "r"(v.z), "r"(v.w) : "memory");
}
__device__ __forceinline__ uint4 lds128(uint32_t addr) {
    uint4 v; asm volatile("ld.shared.v4.b32 {%0,%1,%2,%3}, [%4];" : "=r"(v.x), "=r"(v.y), "=r"(v.z), "=r"(v.w) : "r"(addr) : "memory"); return v;
}
__device__ __forceinline__ float2 lds64f(uint32_t addr) {
    float2 v; asm volatile("ld.shared.v2.f32 {%0,%1}, [%2];" : "=f"(v.x), "=f"(v.y) : "r"(addr) : "memory"); return v;
}
__device__ __forceinline__ float lds32f(uint32_t addr) {
    float v; asm volatile("ld.shared.f32 %0, [%1];" : "=f"(v) : "r"(addr) : "memory"); return v;
}
__device__ __forceinline__ uint32_t lds32(uint32_t addr) {
    uint32_t v; asm volatile("ld.shared.b32 %0, [%1];" : "=r"(v) : "r"(addr) : "memory"); return v;
}
__device__ __forceinline__ void sts32(uint32_t addr, uint32_t v) { asm volatile("st.shared.b32 [%0], %1;" :: "r"(addr), "r"(v) : "memory"); }
__device__ __forceinline__ void sts64f(uint32_t addr, float a, float b) { asm volatile("st.shared.v2.f32 [%0], {%1,%2};" :: "r"(addr), "f"(a), "f"(b) : "memory"); }

__device__ __forceinline__ void tma_load2d(uint32_t dst, const CUtensorMap* tm, int c0, int c1, uint32_t bar) {
    asm volatile("cp.async.bulk.tensor.2d.shared::cluster.global.mbarrier::complete_tx::bytes [%0], [%1, {%3, %4}], [%2];"
                 :: "r"(dst), "l"(tm), "r"(bar), "r"(c0), "r"(c1) : "memory");
}
__device__ __forceinline__ void tma_store2d(const CUtensorMap* tm, uint32_t src, int c0, int c1) {
    asm volatile("cp.async.bulk.tensor.2d.global.shared::cta.bulk_group [%0, {%2, %3}], [%1];"
                 :: "l"(tm), "r"(src), "r"(c0), "r"(c1) : "memory");
}
__device__ __forceinline__ void bulk_commit() { asm volatile("cp.async.bulk.commit_group;" ::: "memory"); }
__device__ __forceinline__ void bulk_wait0() { asm volatile("cp.async.bulk.wait_group 0;" ::: "memory"); }
__device__ __forceinline__ void fence_async_smem() { asm volatile("fence.proxy.async.shared::cta;" ::: "memory"); }
__device__ __forceinline__ void fence_async_all() { asm volatile("fence.proxy.async;" ::: "memory"); }

__device__ __forceinline__ void wg_fence() { asm volatile("wgmma.fence.sync.aligned;" ::: "memory"); }
__device__ __forceinline__ void wg_commit() { asm volatile("wgmma.commit_group.sync.aligned;" ::: "memory"); }
__device__ __forceinline__ void wg_wait0() { asm volatile("wgmma.wait_group.sync.aligned 0;" ::: "memory"); }
__device__ __forceinline__ uint64_t mkdesc(uint32_t saddr, uint32_t lbo, uint32_t sbo) {
    return (uint64_t)((saddr & 0x3FFFF) >> 4) | ((uint64_t)(lbo >> 4) << 16) | ((uint64_t)(sbo >> 4) << 32) | (1ull << 62);
}
#define ACC8(i) "+f"(d[i]), "+f"(d[i + 1]), "+f"(d[i + 2]), "+f"(d[i + 3]), "+f"(d[i + 4]), "+f"(d[i + 5]), "+f"(d[i + 6]), "+f"(d[i + 7])
__device__ __forceinline__ void wgmma_n256(float* d, uint64_t da, uint64_t db, int scale_d) {
    asm volatile(
        "{\n.reg .pred p;\nsetp.ne.b32 p, %130, 0;\n"
        "wgmma.mma_async.sync.aligned.m64n256k16.f32.bf16.bf16 "
        "{%0,%1,%2,%3,%4,%5,%6,%7,%8,%9,%10,%11,%12,%13,%14,%15,%16,%17,%18,%19,%20,%21,%22,%23,%24,%25,%26,%27,%28,%29,%30,%31,"
        "%32,%33,%34,%35,%36,%37,%38,%39,%40,%41,%42,%43,%44,%45,%46,%47,%48,%49,%50,%51,%52,%53,%54,%55,%56,%57,%58,%59,%60,%61,%62,%63,"
        "%64,%65,%66,%67,%68,%69,%70,%71,%72,%73,%74,%75,%76,%77,%78,%79,%80,%81,%82,%83,%84,%85,%86,%87,%88,%89,%90,%91,%92,%93,%94,%95,"
        "%96,%97,%98,%99,%100,%101,%102,%103,%104,%105,%106,%107,%108,%109,%110,%111,%112,%113,%114,%115,%116,%117,%118,%119,%120,%121,%122,%123,%124,%125,%126,%127}, "
        "%128, %129, p, 1, 1, 0, 1;\n}"
        : ACC8(0), ACC8(8), ACC8(16), ACC8(24), ACC8(32), ACC8(40), ACC8(48), ACC8(56),
          ACC8(64), ACC8(72), ACC8(80), ACC8(88), ACC8(96), ACC8(104), ACC8(112), ACC8(120)
        : "l"(da), "l"(db), "r"(scale_d));
}
__device__ __forceinline__ void wgmma_n128(float* d, uint64_t da, uint64_t db, int scale_d) {
    asm volatile(
        "{\n.reg .pred p;\nsetp.ne.b32 p, %66, 0;\n"
        "wgmma.mma_async.sync.aligned.m64n128k16.f32.bf16.bf16 "
        "{%0,%1,%2,%3,%4,%5,%6,%7,%8,%9,%10,%11,%12,%13,%14,%15,%16,%17,%18,%19,%20,%21,%22,%23,%24,%25,%26,%27,%28,%29,%30,%31,"
        "%32,%33,%34,%35,%36,%37,%38,%39,%40,%41,%42,%43,%44,%45,%46,%47,%48,%49,%50,%51,%52,%53,%54,%55,%56,%57,%58,%59,%60,%61,%62,%63}, "
        "%64, %65, p, 1, 1, 0, 1;\n}"
        : ACC8(0), ACC8(8), ACC8(16), ACC8(24), ACC8(32), ACC8(40), ACC8(48), ACC8(56)
        : "l"(da), "l"(db), "r"(scale_d));
}

__device__ __forceinline__ void wgmma_n64(float* d, uint64_t da, uint64_t db) {
    asm volatile(
        "wgmma.mma_async.sync.aligned.m64n64k16.f32.bf16.bf16 "
        "{%0,%1,%2,%3,%4,%5,%6,%7,%8,%9,%10,%11,%12,%13,%14,%15,%16,%17,%18,%19,%20,%21,%22,%23,%24,%25,%26,%27,%28,%29,%30,%31}, "
        "%32, %33, 1, 1, 1, 0, 1;"
        : ACC8(0), ACC8(8), ACC8(16), ACC8(24)
        : "l"(da), "l"(db));
}
__device__ __forceinline__ void wgmma_n8_ta(float* d, uint64_t da, uint64_t db, int scale_d) {
    asm volatile(
        "{\n.reg .pred p;\nsetp.ne.b32 p, %6, 0;\n"
        "wgmma.mma_async.sync.aligned.m64n8k16.f32.bf16.bf16 {%0,%1,%2,%3}, %4, %5, p, 1, 1, 1, 0;\n}"
        : "+f"(d[0]), "+f"(d[1]), "+f"(d[2]), "+f"(d[3]) : "l"(da), "l"(db), "r"(scale_d));
}

__device__ __forceinline__ uint32_t hadd2(uint32_t a, uint32_t b) { uint32_t r; asm("add.rn.bf16x2 %0, %1, %2;" : "=r"(r) : "r"(a), "r"(b)); return r; }
__device__ __forceinline__ uint32_t hsub2(uint32_t a, uint32_t b) { uint32_t r; asm("sub.rn.bf16x2 %0, %1, %2;" : "=r"(r) : "r"(a), "r"(b)); return r; }
__device__ __forceinline__ uint32_t hmul2(uint32_t a, uint32_t b) { uint32_t r; asm("mul.rn.bf16x2 %0, %1, %2;" : "=r"(r) : "r"(a), "r"(b)); return r; }
__device__ __forceinline__ void load_mod8(const bf16* m, int lane, uint32_t* v) {
    const uint4 a = __ldcg((const uint4*)m + lane), b = __ldcg((const uint4*)m + 32 + lane);
    v[0] = a.x; v[1] = a.y; v[2] = a.z; v[3] = a.w; v[4] = b.x; v[5] = b.y; v[6] = b.z; v[7] = b.w;
}
__device__ __forceinline__ void ln_stats(const uint32_t* x, uint32_t& mu2, float& rden) {
    float s = 0.f;
#pragma unroll
    for (int i = 0; i < 8; i++) s += bflo(x[i]) + bfhi(x[i]);
#pragma unroll
    for (int o = 16; o > 0; o >>= 1) s += __shfl_xor_sync(~0u, s, o);
    const float mean = s * (1.f / D_);
    float q = 0.f;
#pragma unroll
    for (int i = 0; i < 8; i++) { const float d0 = bflo(x[i]) - mean, d1 = bfhi(x[i]) - mean; q = fmaf(d0, d0, q); q = fmaf(d1, d1, q); }
#pragma unroll
    for (int o = 16; o > 0; o >>= 1) q += __shfl_xor_sync(~0u, q, o);
    mu2 = pack2(mean, mean);
    rden = __frcp_rn(rbf(__fsqrt_rn(rbf(rbf(q * (1.f / D_)) + 1e-5f))));
}
__device__ __forceinline__ void ln_apply(const uint32_t* x, uint32_t mu2, float rden, const uint32_t* c1, const uint32_t* sm, uint32_t* r) {
#pragma unroll
    for (int i = 0; i < 8; i++) {
        const uint32_t d = hsub2(x[i], mu2);
        r[i] = hadd2(hmul2(pack2(bflo(d) * rden, bfhi(d) * rden), c1[i]), sm[i]);
    }
}

struct __align__(64) Params {
    CUtensorMap tm_h, tm_kv, tm_kvm, tm_o, tm_op, tm_h2, tm_act, tm_x1, tm_out;
    CUtensorMap tm_wq, tm_wk, tm_wv, tm_wo, tm_wg, tm_wu, tm_wd;
    const bf16 *x, *c, *w_mod;
    int qmask;
};

constexpr int R_NST = 3;
constexpr uint32_t R_WV = 0, R_MEM = 65536, R_KX = 73728, R_VX = R_KX + R_NST * 4096,
                   R_KMS = R_VX + R_NST * 4096  , R_VMS = R_KMS + 1024,
                   R_QS = R_KMS + 4096, R_OS = R_QS + 1024, R_SX = R_OS + 1024, R_BAR = R_SX + 2560,
                   R_RS = 107520  , R_VP = R_RS + 8192  ,
                   R_STG = R_VP + 8192  , R_SMEM = R_STG + 98304;
static_assert((R_KMS & 4095) == 0, "smem");
static_assert(R_BAR + 64 <= R_RS, "smem");
constexpr uint32_t RB_SX = R_BAR, RB_V = R_BAR + 8, RB_E = R_BAR + 16, RB_A = R_BAR + 24, RB_ROLE = R_BAR + 32, RB_A1 = R_BAR + 40;
constexpr int W_NST = 4;
constexpr uint32_t W_STAGE = 49152, W_STG = W_NST * W_STAGE  , W_END = W_STG + 32768;
constexpr uint32_t SM_BAR = W_END;
constexpr uint32_t SMEM_BYTES = W_END + 1024 + 2048;
constexpr uint32_t B_FULL = 0, B_EMPTY = 32, B_STGFREE = 64, B_REQ = 80, B_RSP = 88, B_NEXT = 96, B_RING = 128;
#define PICK_AHEAD 3

constexpr int NB_X = 11  , NB_Y = 1, NB_M = 5, NB_K = 5, NB_B = 2, NB_C = 3, NB_D = 4, NB_W0 = 6  , NB_ST = 9  ;

__device__ __forceinline__ int pos_of_d(int d) {
    const int rem = d & 31;
    return (d & ~31) + ((rem & 7) >> 1) * 8 + (rem & 1) * 4 + (rem >> 3);
}

#define PROF(i) do {} while (0)
#define PROFG(i) do {} while (0)
#define OPAQUE(x) asm volatile("" : "+r"(x))
#define FENCE_SCHED(x) do { if ((x) == 0u) asm volatile("trap;"); } while (0)
#define QKVAR 2
#define VK0_ 4
constexpr int VK0 = VK0_;
constexpr int NOFF = 8;
#define VDELAY -1
#define POLL_GAP 110

struct RecParams { const bf16 *mem0, *wq, *wk, *wv, *wo, *x, *c, *w_mod; int ncl, only_pre; };

__device__ __forceinline__ void rec_qk(const RecParams& p, const uint32_t sb, const int cta, const int warp, int lane, const int sel) {
    const int crank = cta & 15, cl = cta >> 4, rank = cta & 1;
    const int kh = warp >> 2, aa = warp & 3;
    uint32_t wa[2][16][4];
    const uint32_t stg = sb + R_STG + kh * 32768;
    {
        const int t128 = aa * 32 + lane;
        const int row = (lane >> 4) * 8 + (lane & 7);
        const int ch = t128 & 7;
        const size_t goff = (size_t)kh * 256 * HD_ + cta * 64 + ch * 8;
#pragma unroll 4
        for (int dd = 0; dd < 16; dd++) {
            const int d = dd * 16 + (t128 >> 3), pp = pos_of_d(d);
            cp_async16(sb + R_WV + kh * 32768 + pp * 128 + ((ch ^ (pp & 7)) << 4), p.wv + goff + (size_t)d * HD_);
        }
        cp_async_commit();
#pragma unroll 4
        for (int dd = 0; dd < 16; dd++) {
            const int d = dd * 16 + (t128 >> 3), pp = pos_of_d(d);
            cp_async16(stg + pp * 128 + ((ch ^ (pp & 7)) << 4), p.wq + goff + (size_t)d * HD_);
        }
        cp_async_commit();
        {
            const int i0 = (warp * 32 + lane) * 16, tok = i0 >> 9;
            const uint4 m0 = __ldg((const uint4*)(p.mem0 + i0)), m1 = __ldg((const uint4*)(p.mem0 + i0 + 8));
            const uint32_t mw[8] = {m0.x, m0.y, m0.z, m0.w, m1.x, m1.y, m1.z, m1.w};
#pragma unroll
            for (int e = 0; e < 16; e++) {
                const int pp = pos_of_d((i0 & 511) + e);
                const unsigned short v = (unsigned short)(mw[e >> 1] >> ((e & 1) * 16));
                asm volatile("st.shared.u16 [%0], %1;" :: "r"(sb + R_MEM + (pp >> 3) * 128 + tok * 16 + (pp & 7) * 2), "h"(v) : "memory");
            }
        }
        cp_async_wait<1>();
        bar_sync(NB_W0 + kh, 128);
        const uint32_t fv = row * 128 + (((2 * aa + ((lane >> 3) & 1)) ^ (row & 7)) << 4);
#pragma unroll
        for (int ks = 0; ks < 16; ks++) ldsm4t(wa[0][ks][0], wa[0][ks][1], wa[0][ks][2], wa[0][ks][3], sb + R_WV + kh * 32768 + fv + ks * 2048);
        bar_sync(NB_W0 + kh, 128);
#pragma unroll
        for (int ks = 0; ks < 16; ks++)
            sts128(sb + R_WV + kh * 32768 + (aa * 16 + ks) * 512 + lane * 16, make_uint4(wa[0][ks][0], wa[0][ks][1], wa[0][ks][2], wa[0][ks][3]));
        const uint32_t fo = stg + row * 128 + (((4 * (aa & 1) + ((lane >> 3) & 1)) ^ (row & 7)) << 4);
#pragma unroll 1
        for (int m = 0; m < 2; m++) {
            cp_async_wait<0>();
            bar_sync(NB_W0 + kh, 128);
            if ((aa >> 1) == m) {
#pragma unroll
                for (int ks = 0; ks < 16; ks++) {
                    ldsm4t(wa[0][ks][0], wa[0][ks][1], wa[0][ks][2], wa[0][ks][3], fo + ks * 2048);
                    ldsm4t(wa[1][ks][0], wa[1][ks][1], wa[1][ks][2], wa[1][ks][3], (fo ^ 32) + ks * 2048);
                }
            }
            bar_sync(NB_W0 + kh, 128);
            if (m == 0) {
#pragma unroll 4
                for (int dd = 0; dd < 16; dd++) {
                    const int d = dd * 16 + (t128 >> 3), pp = pos_of_d(d);
                    cp_async16(stg + pp * 128 + ((ch ^ (pp & 7)) << 4), p.wk + goff + (size_t)d * HD_);
                }
                cp_async_commit();
            }
        }
    }
    const uint32_t tab = stg + (aa * 32 + lane) * 16;
    {
        const uint32_t l7 = lane & 7, l8 = lane >> 3, g = lane >> 2, t = lane & 3;
        const uint32_t t0 = l7 * 128 + ((l8 ^ l7) << 4);
        const uint32_t tq = l7 * 128 + (((l8 >> 1) ^ l7) << 4);
        const uint32_t bq = warp >> 1, tp = warp & 1;
        uint4 v;
        v.x = sb + (aa < 2 ? R_QS : R_KMS) + l7 * 128 + (((4 * (aa & 1) + 2 * kh + (l8 & 1)) ^ l7) << 4);
        v.y = sb + R_QS + tq;
        v.z = sb + (warp == 0 ? R_KMS : R_KX + (warp - 1) * 1024) + t0;
        v.w = mapa_u32(sb + R_SX + (rank * 5 + warp) * 256 + lane * 8, crank ^ 1);
        sts128(tab, v);
        sts128(tab + 2048, make_uint4(sb + lane * 16 + R_MEM + kh * 4096, sb + lane * 16 + R_WV + warp * 8192,
                                      sb + lane * 16 + R_VP + warp * 512, sb + lane * 16 + R_VP + 4096 + (warp ^ 4) * 512));
        const uint32_t src = (l8 >> 1) * 8 + l7;
        const uint32_t L = bq * 8 + 2 * tp + (l8 & 1);
        const uint32_t d0 = (crank + ((t >> 1) | (g & 6))) & 15;
        v.x = sb + R_RS + src * 512 + ((L ^ (src & 7)) << 4);
        v.y = mapa_u32(sb + R_MEM + (crank * 4 + bq) * 128 + (4 * tp + 2 * (t & 1) + (g & 1)) * 16, d0);
        v.z = mapa_u32(sb + ((crank & 2) ? RB_A1 : RB_A), d0);
        v.w = lane;
        sts128(tab + 4096, v);
        const uint64_t wr = (uint64_t)(g_F + ((crank * 2 + ((crank ^ (crank >> 3) ^ sel) & 1)) * 1024 + warp * 128 + cl * 32 + lane));
        sts128(tab + 6144, make_uint4((uint32_t)wr, (uint32_t)(wr >> 32), (uint32_t)((((cl + 1) & 3) - cl) * 128), (uint32_t)((((cl + 2) & 3) - cl) * 128)));
        sts32(tab + 8192, (uint32_t)((((cl + 3) & 3) - cl) * 128));
#pragma unroll
        for (int i = 0; i < NOFF; i++)
            sts128(tab + 10240 + i * 2048, make_uint4(wa[i & 1][i >> 1][0], wa[i & 1][i >> 1][1], wa[i & 1][i >> 1][2], wa[i & 1][i >> 1][3]));
    }
    bar_sync(NB_D, 384);
    uint32_t slot_off = 0;
    const uint32_t slot_inc = warp == 0 ? 2048 : 4096, slot_last = warp == 0 ? 2048 : (R_NST - 1) * 4096;
    const uint32_t sx_bar_rem = (sb + RB_SX) ^ (1u << 24);
    uint4 tb = lds128(tab + 2048);
#pragma unroll 1
    for (int s = 0; s < NSEG; s++) {
        if (s > 0) mbar_wait(sb + RB_A, (s - 1) & 1);
        if (warp == 0) { PROF(0); PROFG(13); }
        uint4 ta;
        const uint32_t km_tog = aa >= 2 ? (s & 1) * 2048 : 0;
        {
            float acc[5][4];
#pragma unroll
            for (int c = 0; c < 5; c++) { acc[c][0] = acc[c][1] = acc[c][2] = acc[c][3] = 0.f; }
            uint32_t b[8][4];
            uint4 av[16];
            static_assert(VK0 == 4, "order below assumes the V/O warps cover slices 0,1");
#define QK4(k2) do { \
                mma16816(acc[0], wa[0][2 * (k2)][0], wa[0][2 * (k2)][1], wa[0][2 * (k2)][2], wa[0][2 * (k2)][3], b[k2][0], b[k2][1]); \
                mma16816(acc[1], wa[1][2 * (k2)][0], wa[1][2 * (k2)][1], wa[1][2 * (k2)][2], wa[1][2 * (k2)][3], b[k2][0], b[k2][1]); \
                mma16816(acc[3], wa[0][2 * (k2) + 1][0], wa[0][2 * (k2) + 1][1], wa[0][2 * (k2) + 1][2], wa[0][2 * (k2) + 1][3], b[k2][2], b[k2][3]); \
                mma16816(acc[4], wa[1][2 * (k2) + 1][0], wa[1][2 * (k2) + 1][1], wa[1][2 * (k2) + 1][2], wa[1][2 * (k2) + 1][3], b[k2][2], b[k2][3]); } while (0)
#define V2(k2) do { \
                mma16816(acc[2], av[2 * (k2)].x, av[2 * (k2)].y, av[2 * (k2)].z, av[2 * (k2)].w, b[k2][0], b[k2][1]); \
                mma16816(acv, av[2 * (k2) + 1].x, av[2 * (k2) + 1].y, av[2 * (k2) + 1].z, av[2 * (k2) + 1].w, b[k2][2], b[k2][3]); } while (0)
#define LB(k2) ldsm4(b[k2][0], b[k2][1], b[k2][2], b[k2][3], tb.x + (k2) * 512)
#define LV(k2) do { av[2 * (k2)] = lds128(tb.y + 2 * (k2) * 512); av[2 * (k2) + 1] = lds128(tb.y + (2 * (k2) + 1) * 512); } while (0)
            float acv[4] = {0.f, 0.f, 0.f, 0.f};
            LB(0); LB(1); LB(4); LB(5);
            QK4(0); QK4(1); LV(4); LV(5); QK4(4); QK4(5);
            if (s > 0) mbar_wait(sb + RB_A1, (s - 1) & 1);
            LB(2); LB(3); LB(6); LB(7); ta = lds128(tab);
            V2(4); V2(5); LV(2); LV(3);
            QK4(2); QK4(3); QK4(6); QK4(7);
            LV(6); LV(7);
#pragma unroll
            for (int i = 0; i < 4; i++) { acc[0][i] += acc[3][i]; acc[1][i] += acc[4][i]; }
            const float g0 = kh ? acc[0][0] : acc[1][0], g1 = kh ? acc[0][1] : acc[1][1], g2 = kh ? acc[0][2] : acc[1][2], g3 = kh ? acc[0][3] : acc[1][3];
            sts128(tb.w, make_uint4(__float_as_uint(g0), __float_as_uint(g1), __float_as_uint(g2), __float_as_uint(g3)));
            const float k0 = kh ? acc[1][0] : acc[0][0], k1 = kh ? acc[1][1] : acc[0][1], k2_ = kh ? acc[1][2] : acc[0][2], k3 = kh ? acc[1][3] : acc[0][3];
            if (warp == 0) PROF(1);
            V2(2); V2(3);
            bar_sync(NB_X + aa, 64);
            const uint4 o = lds128(tb.z + 4096);
            V2(6); V2(7);
            stsm2t(ta.x ^ km_tog, pack2(k0 + __uint_as_float(o.x), k1 + __uint_as_float(o.y)), pack2(k2_ + __uint_as_float(o.z), k3 + __uint_as_float(o.w)));
            sts128(tb.z, make_uint4(__float_as_uint(acc[2][0] + acv[0]), __float_as_uint(acc[2][1] + acv[1]), __float_as_uint(acc[2][2] + acv[2]), __float_as_uint(acc[2][3] + acv[3])));
        }
        const uint32_t kb = ta.z + slot_off;
        if (warp == 0) PROF(14);
        bar_sync(NB_B, 256);
        if (warp < 5) {
            uint32_t q[16], k0, k1, k2, k3, k4, k5, k6, k7;
            float sa[4] = {0.f, 0.f, 0.f, 0.f}, sc[4] = {0.f, 0.f, 0.f, 0.f};
            ldsm4(q[0], q[1], q[2], q[3], ta.y);
            ldsm4(k0, k1, k2, k3, kb);
            ldsm4(q[4], q[5], q[6], q[7], ta.y ^ 32);
            ldsm4(q[8], q[9], q[10], q[11], ta.y ^ 64);
            ldsm4(k4, k5, k6, k7, kb ^ 64);
            ldsm4(q[12], q[13], q[14], q[15], ta.y ^ 96);
            mma16816(sa, q[0], q[1], q[2], q[3], k0, k1);
            bar_arrive(NB_Y, 288);
            mma16816(sc, q[4], q[5], q[6], q[7], k2, k3);
            mma16816(sa, q[8], q[9], q[10], q[11], k4, k5);
            mma16816(sc, q[12], q[13], q[14], q[15], k6, k7);
            const float scl = 0.08838834764831845f * 1.4426950408889634f;
            const float r0 = (sa[0] + sc[0]) * scl, r1 = (sa[1] + sc[1]) * scl;
            if (s != NSEG - 1) {
                st_async_v2(ta.w, r0, r1, sx_bar_rem);
                st_async_v2(ta.w ^ (1u << 24), r0, r1, sx_bar_rem ^ (1u << 24));
            }
            if (warp == 0) PROF(2);
        } else if (s > 0 && warp == 7 && lane == 0) {
            mbar_expect_tx(sb + RB_A, 4096);
            mbar_expect_tx(sb + RB_A1, 4096);
        } else if (s > 0 && (s & 3) == 0 && warp == 6) {
            bar_sync(NB_K, 160);
            if (lane == 0) red_release(&g_flags[F_MEM + (s >> 2) - 1], 1);
            __syncwarp();
        }
        if (s == NSEG - 1) {
            const uint4 td = lds128(tab + 6144);
            stg_relaxed32((uint32_t*)(((uint64_t)td.y << 32) | (td.x ^ 0x21000)), 0u);
            break;
        }
        slot_off = slot_off == slot_last ? 0 : slot_off + slot_inc;
        const uint4 tc = lds128(tab + 4096), td = lds128(tab + 6144);
        const uint32_t te = lds32(tab + 8192);
        uint32_t* wr = (uint32_t*)(((uint64_t)td.y << 32) | (td.x ^ ((s & 1) * 0x21000)));
        const uint32_t* r1p = (const uint32_t*)((const char*)wr + (int)td.z);
        const uint32_t* r2p = (const uint32_t*)((const char*)wr + (int)td.w);
        const uint32_t* r3p = (const uint32_t*)((const char*)wr + (int)te);
        const uint32_t tag = ((s >> 1) + 1) & 1;
        mbar_wait(sb + RB_E, s & 1);
        if (warp == 0) PROF(7);
        {
            uint32_t a0, a1, a2, a3, a4, a5, a6, a7;
            ldsm4t(a0, a1, a2, a3, tc.x);
            ldsm4t(a4, a5, a6, a7, tc.x ^ 64);
            const uint32_t one = 0x3F803F80u;
            float d0_[4] = {0.f, 0.f, 0.f, 0.f}, d1_[4] = {0.f, 0.f, 0.f, 0.f};
            mma16816(d0_, a0, a1, a2, a3, one, one);
            mma16816(d1_, a4, a5, a6, a7, one, one);
            const bool t1 = tc.w & 1, t2 = tc.w & 2;
            const float x = t2 ? (t1 ? d1_[2] : d1_[0]) : (t1 ? d0_[2] : d0_[0]);
            const uint32_t own = (__float_as_uint(x) & ~1u) | tag;
            stg_relaxed32(wr, own);
            const uint32_t tq = clk32();
            if (warp == 0) PROF(8);
            PROFG(16 + warp);
            while ((int)(clk32() - tq) < POLL_GAP) {}
            uint32_t f1 = ldg_relaxed32(r1p), f2 = ldg_relaxed32(r2p), f3 = ldg_relaxed32(r3p);
#pragma unroll
            for (int i = 0; i < NOFF; i++) {
                const uint4 f0 = lds128(tab + 10240 + i * 2048);
                wa[i & 1][i >> 1][0] = f0.x; wa[i & 1][i >> 1][1] = f0.y; wa[i & 1][i >> 1][2] = f0.z; wa[i & 1][i >> 1][3] = f0.w;
            }
            tb = lds128(tab + 2048);
            int gg = 0;
#pragma unroll 1
            while (!__all_sync(~0u, (((f1 ^ tag) | (f2 ^ tag) | (f3 ^ tag)) & 1) == 0)) {
                f1 = ldg_relaxed32(r1p); f2 = ldg_relaxed32(r2p); f3 = ldg_relaxed32(r3p);
                if (++gg > 16 * SPIN_LIMIT) { TIMEOUT(3, s); break; }
            }
            if (warp == 0) PROF(9);
            const float v = (__uint_as_float(own) + __uint_as_float(f2)) + (__uint_as_float(f1) + __uint_as_float(f3));
            const bool b8 = tc.w & 8, b16 = tc.w & 16;
            const float recv = __shfl_xor_sync(~0u, v, 8);
            const uint32_t word = b8 ? pack2(recv, v) : pack2(v, recv);
            const uint32_t oth = __shfl_xor_sync(~0u, word, 16);
            const uint32_t wl = b16 ? oth : word, wh = b16 ? word : oth;
            const uint32_t p0 = __shfl_xor_sync(~0u, wl, 2), p1 = __shfl_xor_sync(~0u, wh, 2);
            const uint4 item = t2 ? make_uint4(p0, p1, wl, wh) : make_uint4(wl, wh, p0, p1);
            st_async_v4(tc.y, item, tc.z);
            st_async_v4(tc.y ^ (8u << 24), item, tc.z ^ (8u << 24));
            if (tc.w == 0 && warp == 7) mbar_expect_tx(sb + RB_E, 8192);
            if (warp == 0) PROF(10);
            PROF(40 + warp);
        }
        bar_sync(NB_D, 384);
    }
}

__device__ __forceinline__ void rec_load_kv(uint32_t sb, int col0, int s, uint32_t slot_off, int t128) {
    const int row = t128 >> 2, c2 = (t128 & 3) * 2;
    const bf16* src = g_kv + ((size_t)(s * 32 + row) * (2 * HD_) + col0 + c2 * 8);
    const uint32_t d0 = sb + R_KX + slot_off + row * 128 + ((c2 ^ (row & 7)) << 4);
    cp_async16(d0, src);
    cp_async16(d0 ^ 16, src + 8);
    cp_async16(d0 + (R_VX - R_KX), src + HD_);
    cp_async16((d0 ^ 16) + (R_VX - R_KX), src + HD_ + 8);
}

__device__ __forceinline__ void rec_store_kvm(uint32_t sb, int col0, int s, int w, int lane) {
    const int tok = (w & 1) * 4 + (lane >> 3);
    const uint4 v = lds128(sb + R_KMS + (s & 1) * 2048 + (w >> 1) * 1024 + tok * 128 + (((lane & 7) ^ tok) << 4));
    *(uint4*)(g_kvm + ((s * 8 + tok) * (2 * HD_) + (w >> 1) * HD_ + col0 + (lane & 7) * 8)) = v;
}

__device__ __forceinline__ void rec_vo(const RecParams& p, const uint32_t sb, const int cta, const int warp, int lane) {
    const int w = warp - 8, crank = cta & 15;
    const int col0 = cta * 64;
    uint32_t wo[8][4][4];
    {
        const int t128 = w * 32 + lane;
        const bf16* Wo = p.wo + (size_t)col0 * D_;
        const uint32_t stg = sb + R_STG + 2 * 32768;
#pragma unroll
        for (int half = 0; half < 2; half++) {
#pragma unroll 4
            for (int i = t128; i < 2048; i += 128) {
                const int e = i >> 6, ch = i & 63;
                cp_async16(stg + e * 1024 + ((ch ^ (e & 7)) << 4), Wo + (size_t)(half * 32 + e) * D_ + ch * 8);
            }
            cp_async_commit();
            cp_async_wait<0>();
            bar_sync(NB_W0 + 2, 128);
#pragma unroll
            for (int j = 0; j < 8; j++)
#pragma unroll
                for (int kk = 0; kk < 2; kk++) {
                    const int e = kk * 16 + (lane >> 4) * 8 + (lane & 7);
                    const int ch = (w * 8 + j) * 2 + ((lane >> 3) & 1);
                    ldsm4t(wo[j][half * 2 + kk][0], wo[j][half * 2 + kk][1], wo[j][half * 2 + kk][2], wo[j][half * 2 + kk][3],
                           stg + e * 1024 + ((ch ^ (e & 7)) << 4));
                }
            bar_sync(NB_W0 + 2, 128);
        }
        if (lane == 0) wait_flag(F_KV + 0, 64);
        __syncwarp();
        rec_load_kv(sb, col0, 0, 0, t128); cp_async_commit();
        rec_load_kv(sb, col0, 1, 4096, t128); cp_async_commit();
        cp_async_wait<1>();
    }
    const uint32_t tab = sb + R_STG + 2 * 32768 + (w * 32 + lane) * 16;
    {
        const uint32_t l7 = lane & 7, l8 = lane >> 3, g = lane >> 2;
        uint4 v;
        v.x = sb + R_VX + ((l8 & 1) * 8 + l7) * 128 + (((2 * w + (l8 >> 1)) ^ l7) << 4);
        v.y = sb + R_OS + g * 128 + (((2 * w) ^ g) << 4) + (lane & 3) * 4;
        v.z = sb + R_VMS + l7 * 128 + (((2 * w + (l8 & 1)) ^ l7) << 4);
        v.w = sb + R_OS + l7 * 128 + ((l8 ^ l7) << 4);
        sts128(tab, v);
        v.x = mapa_u32(sb + R_RS + crank * 512 + ((lane ^ (crank & 7)) << 4), w * 4);
        v.y = mapa_u32(sb + RB_E, w * 4);
        v.z = sb + R_VP + w * 512 + lane * 16;
        v.w = sb + R_SX + lane * 8;
        sts128(tab + 2048, v);
#pragma unroll
        for (int i = 0; i < 8; i++) sts128(tab + 4096 + i * 2048, make_uint4(wo[i][0][0], wo[i][0][1], wo[i][0][2], wo[i][0][3]));
        const int tok = (w & 1) * 4 + (lane >> 3), row = (w * 32 + lane) >> 2, c2 = (lane & 3) * 2;
        const uint64_t kd = (uint64_t)(g_kvm + (tok * (2 * HD_) + (w >> 1) * HD_ + col0 + (lane & 7) * 8));
        const uint64_t ks = (uint64_t)(g_kv + ((size_t)row * (2 * HD_) + col0 + c2 * 8));
        sts128(tab + 20480, make_uint4((uint32_t)kd, (uint32_t)(kd >> 32), (uint32_t)ks, (uint32_t)(ks >> 32)));
        sts128(tab + 22528, make_uint4(sb + R_KMS + (w >> 1) * 1024 + tok * 128 + (((lane & 7) ^ tok) << 4),
                                       sb + R_KX + row * 128 + ((c2 ^ (row & 7)) << 4), lane, 0));
    }
    bar_sync(NB_D, 384);
    const uint32_t lane16 = lds32(tab + 2048 + 8) - R_VP - w * 512;
    uint4 av[2 * VK0];
#pragma unroll
    for (int i = 0; i < 2 * VK0; i++) av[i] = lds128(lane16 + R_WV + (i / VK0) * 32768 + (w * 16 + i % VK0) * 512);
    uint32_t slot_off = 0;
#pragma unroll 1
    for (int s = 0; s < NSEG; s++) {
        if (s > 0) {
            mbar_wait(sb + RB_A, (s - 1) & 1);
            const uint4 tp = lds128(tab + 20480), tq = lds128(tab + 22528);
            const uint4 kvm = lds128(tq.x + ((s - 1) & 1) * 2048);
            *(uint4*)((((uint64_t)tp.y << 32) | tp.x) + (uint64_t)(s - 1) * (8 * 2 * HD_ * 2)) = kvm;
            if ((s & 3) == 0) bar_arrive(NB_K, 160);
            if (s + 1 < NSEG - 1) {
                if (((s + 1) & 3) == 0) { if (tq.z == 0) wait_flag(F_KV + ((s + 1) >> 2), 64); __syncwarp(); }
                const char* src = (const char*)((((uint64_t)tp.w << 32) | tp.z) + (uint64_t)(s + 1) * (32 * 2 * HD_ * 2));
                const uint32_t d0 = tq.y + (slot_off == (R_NST - 1) * 4096 ? 0 : slot_off + 4096);
                cp_async16(d0, src);
                cp_async16(d0 ^ 16, src + 16);
                cp_async16(d0 + (R_VX - R_KX), src + HD_ * 2);
                cp_async16((d0 ^ 16) + (R_VX - R_KX), src + HD_ * 2 + 16);
            }
            cp_async_commit();
        }
        bar_sync(NB_Y, 288);
        uint32_t vb0, vb1;
        {
            float va[4] = {0.f, 0.f, 0.f, 0.f}, vc[4] = {0.f, 0.f, 0.f, 0.f};
            uint32_t bb[VK0][4];
#pragma unroll
            for (int k2 = 0; k2 < VK0; k2++) ldsm4(bb[k2][0], bb[k2][1], bb[k2][2], bb[k2][3], lane16 + R_MEM + (k2 / (VK0 / 2)) * 4096 + (k2 % (VK0 / 2)) * 512);
#pragma unroll
            for (int k2 = 0; k2 < VK0; k2++) {
                mma16816(va, av[2 * k2].x, av[2 * k2].y, av[2 * k2].z, av[2 * k2].w, bb[k2][0], bb[k2][1]);
                mma16816(vc, av[2 * k2 + 1].x, av[2 * k2 + 1].y, av[2 * k2 + 1].z, av[2 * k2 + 1].w, bb[k2][2], bb[k2][3]);
            }
            const uint4 a = lds128(lane16 + R_VP + w * 512), b = lds128(lane16 + R_VP + 2048 + w * 512);
            vb0 = pack2((va[0] + vc[0]) + (__uint_as_float(a.x) + __uint_as_float(b.x)), (va[1] + vc[1]) + (__uint_as_float(a.y) + __uint_as_float(b.y)));
            vb1 = pack2((va[2] + vc[2]) + (__uint_as_float(a.z) + __uint_as_float(b.z)), (va[3] + vc[3]) + (__uint_as_float(a.w) + __uint_as_float(b.w)));
        }
        const uint4 ta = lds128(tab), tb = lds128(tab + 2048);
        uint32_t vx[8];
        ldsm4t(vx[0], vx[1], vx[2], vx[3], ta.x + slot_off);
        ldsm4t(vx[4], vx[5], vx[6], vx[7], ta.x + slot_off + 2048);
#pragma unroll
        for (int i = 0; i < 4; i++) {
            const uint4 f0 = lds128(tab + 4096 + i * 2048);
            wo[i][0][0] = f0.x; wo[i][0][1] = f0.y; wo[i][0][2] = f0.z; wo[i][0][3] = f0.w;
        }
        if (w == 0) PROF(11);
        uint32_t pf[5];
        float oa[2][4] = {{0.f, 0.f, 0.f, 0.f}, {0.f, 0.f, 0.f, 0.f}}, ob_[2][4] = {{0.f, 0.f, 0.f, 0.f}, {0.f, 0.f, 0.f, 0.f}};
        float sm0[4] = {0.f, 0.f, 0.f, 0.f}, sm1[4] = {0.f, 0.f, 0.f, 0.f};
        if (s != NSEG - 1) {
            mbar_wait(sb + RB_SX, s & 1);
            if (w == 0) PROF(4);
            float sv[10];
#pragma unroll
            for (int n = 0; n < 5; n++) {
                const float2 a = lds64f(tb.w + n * 256), b = lds64f(tb.w + (5 + n) * 256);
                sv[2 * n] = a.x + b.x; sv[2 * n + 1] = a.y + b.y;
            }
            float mx = fmaxf(fmaxf(fmaxf(sv[0], sv[1]), fmaxf(sv[2], sv[3])), fmaxf(fmaxf(sv[4], sv[5]), fmaxf(sv[6], sv[7])));
            mx = fmaxf(mx, fmaxf(sv[8], sv[9]));
            mx = fmaxf(mx, __shfl_xor_sync(~0u, mx, 1));
            mx = fmaxf(mx, __shfl_xor_sync(~0u, mx, 2));
#pragma unroll
            for (int n = 1; n < 5; n++) pf[n] = pack2(ex2(sv[2 * n] - mx), ex2(sv[2 * n + 1] - mx));
            pf[0] = pack2(ex2(sv[0] - mx), ex2(sv[1] - mx));
            if (w == 0) PROF(12);
            const uint32_t one = 0x3F803F80u;
            mma16816h(sm0, pf[1], pf[2], one, one);
            mma16816h(oa[0], pf[1], pf[2], vx[0], vx[1]);
            mma16816h(oa[1], pf[1], pf[2], vx[2], vx[3]);
            mma16816h(sm1, pf[3], pf[4], one, one);
            mma16816h(ob_[0], pf[3], pf[4], vx[4], vx[5]);
            mma16816h(ob_[1], pf[3], pf[4], vx[6], vx[7]);
            mma1688h(sm0, pf[0], one);
            mma1688h(oa[0], pf[0], vb0);
            mma1688h(oa[1], pf[0], vb1);
            float inv;
            asm("rcp.approx.ftz.f32 %0, %1;" : "=f"(inv) : "f"(sm0[0] + sm1[0]));
            oa[0][0] += ob_[0][0]; oa[0][1] += ob_[0][1]; oa[1][0] += ob_[1][0]; oa[1][1] += ob_[1][1];
            sts32(ta.y, pack2(oa[0][0] * inv, oa[0][1] * inv));
            sts32(ta.y ^ 16, pack2(oa[1][0] * inv, oa[1][1] * inv));
            const uint32_t oa2 = ta.w ^ 64;
            bar_sync(NB_C, 128);
            if (w == 0) PROF(5);
            uint32_t ob[8];
            ldsm4(ob[0], ob[1], ob[2], ob[3], ta.w);
            ldsm4(ob[4], ob[5], ob[6], ob[7], oa2);
#pragma unroll
            for (int i = 4; i < 8; i++) {
                const uint4 f0 = lds128(tab + 4096 + i * 2048);
                wo[i][0][0] = f0.x; wo[i][0][1] = f0.y; wo[i][0][2] = f0.z; wo[i][0][3] = f0.w;
            }
#pragma unroll
            for (int jj = 0; jj < 2; jj++) {
                if (jj == 1 && tb.w == 0) break;
                float acc[4][4];
#pragma unroll
                for (int c = 0; c < 4; c++) { acc[c][0] = acc[c][1] = acc[c][2] = acc[c][3] = 0.f; }
#pragma unroll
                for (int ks = 0; ks < 4; ks++)
#pragma unroll
                    for (int c = 0; c < 4; c++)
                        mma16816(acc[c], wo[jj * 4 + c][ks][0], wo[jj * 4 + c][ks][1], wo[jj * 4 + c][ks][2], wo[jj * 4 + c][ks][3], ob[2 * ks], ob[2 * ks + 1]);
#pragma unroll
                for (int pr = 0; pr < 2; pr++) {
                    uint4 v;
                    v.x = pack2(acc[2 * pr][0], acc[2 * pr][1]);
                    v.y = pack2(acc[2 * pr][2], acc[2 * pr][3]);
                    v.z = pack2(acc[2 * pr + 1][0], acc[2 * pr + 1][1]);
                    v.w = pack2(acc[2 * pr + 1][2], acc[2 * pr + 1][3]);
                    st_async_v4(tb.x + ((jj * 2 + pr) << 24), v, tb.y + ((jj * 2 + pr) << 24));
                }
            }
            if (w == 0) PROF(6);
        }
        stsm2t(ta.z + (s & 1) * 2048, vb0, vb1);
        cp_async_wait<0>();
        bar_sync(NB_C, 128);
        if (w == 0 && lane == 0 && s != NSEG - 1) mbar_expect_tx(sb + RB_SX, 2560);
        if (s != NSEG - 1) bar_arrive(NB_D, 384);
#pragma unroll
        for (int i = 0; i < 2 * VK0; i++) av[i] = lds128(lane16 + R_WV + (i / VK0) * 32768 + (w * 16 + i % VK0) * 512);
        slot_off = slot_off == (R_NST - 1) * 4096 ? 0 : slot_off + 4096;
    }
    rec_store_kvm(sb, col0, NSEG - 1, w, lane);
    bar_sync(NB_C, 128);
    if (w == 0 && lane == 0) red_release(&g_flags[F_MEM + NRB - 1], 1);
}

__global__ void __launch_bounds__(384, 1) k_rec(const RecParams p) {
    extern __shared__ __align__(1024) unsigned char smem_raw[];
    const uint32_t sb = __shfl_sync(~0u, smem_u32(smem_raw), 0);
    const int warp = __shfl_sync(~0u, threadIdx.x >> 5, 0);
    int lane; asm volatile("mov.u32 %0, %%laneid;" : "=r"(lane));
    const int crank = blockIdx.x & 15, slot = blockIdx.x >> 4;
    asm volatile("griddepcontrol.launch_dependents;");
    if (crank == 0 && warp == 1 && lane < 4) {
        const unsigned int* q = lane < 2 ? &g_F[65536 + lane * 1024 + slot * 64] : &g_flags[F_SIDE + (lane - 2) * 32];
        asm volatile("prefetch.global.L2 [%0];" :: "l"(q));
    }
    if (threadIdx.x == 0) {
        mbar_init(sb + RB_SX, 1); mbar_init(sb + RB_E, 1); mbar_init(sb + RB_A, 1); mbar_init(sb + RB_A1, 1); mbar_init(sb + RB_ROLE, 1);
        asm volatile("fence.mbarrier_init.release.cluster;" ::: "memory");
        mbar_expect_tx(sb + RB_SX, 2560);
        mbar_expect_tx(sb + RB_E, 8192);
        mbar_expect_tx(sb + RB_A, 4096);
        mbar_expect_tx(sb + RB_A1, 4096);
        mbar_expect_tx(sb + RB_ROLE, 4);
    }
    asm volatile("barrier.cluster.arrive.relaxed.aligned;\nbarrier.cluster.wait.aligned;" ::: "memory");
    unsigned role = 0;
    if (crank == 0 && threadIdx.x == 0 && !p.only_pre) {
        unsigned x = 0;
        int tm[2] = {0x7fffffff, 0x7fffffff};
#pragma unroll 1
        for (int i = 0; i < 6; i++) {
            const uint32_t t0 = clk32();
            x = atomicAdd(&g_F[65536 + (i & 1) * 1024 + slot * 64 + (x >> 31)], 0u) & 0x7fffffffu;
            if (x == 0x7654321u) sts32(sb + R_BAR + 56, x);
            const int dt = (int)(clk32() - t0);
            if (i >= 2) { if (i & 1) tm[1] = min(tm[1], dt); else tm[0] = min(tm[0], dt); }
        }
        const int side = tm[1] > tm[0];
        const unsigned old = atomicAdd(&g_flags[F_SIDE + side * 32], 1u);
        unsigned c0, c1; int gd = 0;
#pragma unroll 1
        do { c0 = ldg_relaxed32(&g_flags[F_SIDE]); c1 = ldg_relaxed32(&g_flags[F_SIDE + 32]); } while ((int)(c0 + c1) < p.ncl && ++gd < 64 * SPIN_LIMIT);
        const int big = c1 > c0;
        role = side == big ? old : (big ? c1 : c0) + old;
        role |= (big ^ 1) << 8;
    }
    __syncwarp();
    if (crank == 0 && warp == 0 && !p.only_pre) {
        role = __shfl_sync(~0u, role, 0);
        if (lane < 16)
            asm volatile("st.async.weak.shared::cluster.mbarrier::complete_tx::bytes.u32 [%0], %1, [%2];"
                         :: "r"(mapa_u32(sb + R_BAR + 48, lane)), "r"(role), "r"(mapa_u32(sb + RB_ROLE, lane)) : "memory");
    }
    if (warp >= 4) {
        const int w8 = warp - 4, nblk = gridDim.x;
        const int cq = lane & 3, rg = w8 * 8 + (lane >> 2);
        const uint32_t red = sb + R_VP;
        const int row0 = blockIdx.x * 8 + w8;
        const uint4* xr = (const uint4*)(p.x + (size_t)row0 * D_);
        uint4 xa = __ldg(xr + lane), xb = __ldg(xr + 32 + lane);
#pragma unroll 1
        for (int sl = blockIdx.x; sl < 96; sl += nblk) {
            uint4 wv[8];
#pragma unroll
            for (int i = 0; i < 8; i++) wv[i] = __ldg((const uint4*)(p.w_mod + (size_t)(rg * 8 + i) * (6 * D_) + sl * 32 + cq * 8));
            const uint32_t cw = __ldg((const uint32_t*)(p.c + rg * 8) + cq);
            const float cl = bflo(cw), ch = bfhi(cw);
            const uint32_t sw = pack2(__fdividef(cl, 1.f + __expf(-cl)), __fdividef(ch, 1.f + __expf(-ch)));
            float a[8];
#pragma unroll
            for (int i = 0; i < 8; i++) a[i] = 0.f;
#pragma unroll
            for (int i = 0; i < 8; i++) {
                const uint32_t sv = __shfl_sync(~0u, sw, (lane & 28) + (i >> 1));
                const float cv = (i & 1) ? bfhi(sv) : bflo(sv);
                a[0] = fmaf(cv, bflo(wv[i].x), a[0]); a[1] = fmaf(cv, bfhi(wv[i].x), a[1]); a[2] = fmaf(cv, bflo(wv[i].y), a[2]); a[3] = fmaf(cv, bfhi(wv[i].y), a[3]);
                a[4] = fmaf(cv, bflo(wv[i].z), a[4]); a[5] = fmaf(cv, bfhi(wv[i].z), a[5]); a[6] = fmaf(cv, bflo(wv[i].w), a[6]); a[7] = fmaf(cv, bfhi(wv[i].w), a[7]);
            }
#pragma unroll
            for (int i = 0; i < 8; i++) { a[i] += __shfl_xor_sync(~0u, a[i], 4); a[i] += __shfl_xor_sync(~0u, a[i], 8); a[i] += __shfl_xor_sync(~0u, a[i], 16); }
            if (lane < 4) {
                sts128(red + w8 * 128 + lane * 32, make_uint4(__float_as_uint(a[0]), __float_as_uint(a[1]), __float_as_uint(a[2]), __float_as_uint(a[3])));
                sts128(red + w8 * 128 + lane * 32 + 16, make_uint4(__float_as_uint(a[4]), __float_as_uint(a[5]), __float_as_uint(a[6]), __float_as_uint(a[7])));
            }
            bar_sync(NB_B, 256);
            if (w8 == 0) {
                float v = 0.f;
#pragma unroll
                for (int i = 0; i < 8; i++) v += lds32f(red + i * 128 + lane * 4);
                g_mod[sl * 32 + lane] = __float2bfloat16_rn(v);
                __syncwarp();
                if (lane == 0) red_release(&g_flags[F_MOD + (sl >= 32)], 1);
            }
            bar_sync(NB_B, 256);
        }
        uint32_t c1[8], sm[8];
        int row = row0;
#pragma unroll 1
        while (true) {
            const uint32_t v[8] = {xa.x, xa.y, xa.z, xa.w, xb.x, xb.y, xb.z, xb.w};
            uint32_t mu2, r[8]; float rden;
            ln_stats(v, mu2, rden);
            if (row == row0) {
                if (lane == 0) wait_flag(F_MOD, 32);
                __syncwarp();
                load_mod8(g_mod + D_, lane, c1);
                load_mod8(g_mod, lane, sm);
#pragma unroll
                for (int i = 0; i < 8; i++) c1[i] = hadd2(c1[i], 0x3F803F80u);
            } else if (row + 512 < S_) {
                xr = (const uint4*)(p.x + (size_t)(row + 512) * D_); xa = __ldg(xr + lane); xb = __ldg(xr + 32 + lane);
            }
            ln_apply(v, mu2, rden, c1, sm, r);
            uint4* hr = (uint4*)(g_h + (size_t)row * D_);
            hr[lane] = make_uint4(r[0], r[1], r[2], r[3]); hr[32 + lane] = make_uint4(r[4], r[5], r[6], r[7]);
            bar_sync(NB_B, 256);
            if (w8 == (row >> 7 & 7) && lane == 0) red_release(&g_flags[F_H + (row >> 7)], 1);
            __syncwarp();
            if (row == row0) {
                if (!p.only_pre) mbar_wait(sb + RB_ROLE, 0);
                const int cl = p.only_pre ? slot : (int)(lds32(sb + R_BAR + 48) & 255);
                row = cl < 4 ? (nblk + cl * 16 + crank) * 8 + w8 : S_;
                if (row < S_) { xr = (const uint4*)(p.x + (size_t)row * D_); xa = __ldg(xr + lane); xb = __ldg(xr + 32 + lane); }
            } else {
                row += 512;
            }
            if (row >= S_) break;
        }
    }
    if (p.only_pre) return;
    mbar_wait(sb + RB_ROLE, 0);
    const int rolew = __shfl_sync(~0u, lds32(sb + R_BAR + 48), 0);
    const int cl = rolew & 255;
    if (cl >= 4) return;
    const int cta = cl * 16 + crank;
    if (warp < 8) rec_qk(p, sb, cta, warp, lane, rolew >> 8);
    else rec_vo(p, sb, cta, warp, lane);
}

enum { J_KV = 0, J_QA = 1, J_O = 2, J_LN = 3, J_UP = 4, J_DN = 5, J_LN1 = 6, J_MOD = 7, J_UP2 = 8, J_END = 9 };
constexpr int NJ_O = 2 * OSPLIT, NJ_O2 = 2 * OSPLIT2, NJ_LN = 8, NJ_LN2 = 16, NJ_UP = 14, NJ_UP2 = 28, NJ_DN = 8, NJ_LN1 = 8;
constexpr uint64_t pk8(int a, int b, int c, int d, int e, int f, int g, int h) {
    return (uint64_t)a | ((uint64_t)b << 8) | ((uint64_t)c << 16) | ((uint64_t)d << 24) | ((uint64_t)e << 32) | ((uint64_t)f << 40) | ((uint64_t)g << 48) | ((uint64_t)h << 56);
}
constexpr uint64_t NJ_C = pk8(32, 16, NJ_O, NJ_LN, NJ_UP, NJ_DN, 0, 0), NJ_F = pk8(32, 16, NJ_O2, NJ_LN2, NJ_UP2, NJ_DN, 0, 0);
constexpr uint64_t TG_C = pk8(2 * NJ_LN1, 64, 32, 2 * NJ_O, 2 * NJ_LN, 2 * NJ_UP, 32, 0), TG_F = pk8(2 * NJ_LN1, 64, 32, 2 * NJ_O2, 2 * NJ_LN2, 2 * NJ_UP2, 32, 0);
constexpr uint64_t NJ_L = pk8(32, 32, 2 * OSPLIT3, NJ_LN2, NJ_UP2, 2 * NJ_DN, 0, 0), TG_L = pk8(2 * NJ_LN1, 64, 64, 4 * OSPLIT3, 2 * NJ_LN2, 2 * NJ_UP2, 32, 0);
__device__ __forceinline__ uint64_t nj_tab(int rb) { return rb < FINE_RB ? NJ_C : (rb < NRB - 1 ? NJ_F : NJ_L); }
__device__ __forceinline__ uint64_t tg_tab(int rb) { return rb < FINE_RB ? TG_C : (rb < NRB - 1 ? TG_F : TG_L); }
__device__ __forceinline__ int o_nk(int rb) { return rb < FINE_RB ? 64 / OSPLIT : (rb < NRB - 1 ? 64 / OSPLIT2 : 64 / OSPLIT3); }
constexpr uint64_t PRIO = pk8(4, 10, 9, 8, 7, 6, 3, 0);
__device__ __forceinline__ int pick_job(int lane, int qmask, int& idx) {
    const int rb = lane & 15, half = lane >> 4;
    const uint64_t nj = nj_tab(rb) >> (8 * half);
    const uint64_t tg = tg_tab(rb) >> (8 * half);
    const unsigned* cp = &g_flags[F_CLAIM + half * 32 + rb];
    const unsigned* dp = &g_flags[half * 32 + rb];
    int gd = 0;
#pragma unroll 1
    while (true) {
        const unsigned c0 = ldg_relaxed32(cp), c1 = ldg_relaxed32(cp + 64), c2 = ldg_relaxed32(cp + 128);
        const unsigned d0 = ldg_relaxed32(dp - (half && rb ? 1 : 0)), d1 = ldg_relaxed32(dp + 64), d2 = ldg_relaxed32(dp + 128);
        const unsigned cl[3] = {c0, c1, c2}, dv[3] = {d0, d1, d2};
        unsigned key = 0xffffu, key2 = 0xffffu;
        bool pre = false;
#pragma unroll
        for (int i = 0; i < 3; i++) {
            const int q = half + 2 * i;
            const bool have = ((qmask >> q) & 1) && cl[i] < (unsigned)((nj >> (16 * i)) & 255);
            bool ready = have && dv[i] >= (unsigned)((tg >> (16 * i)) & 255);
            unsigned pr = (unsigned)((PRIO >> (8 * q)) & 255);
            if (i == 0 && rb <= 1 - half) ready = have;
            if (i == 0 && half && rb >= FINE_RB) pr = 5;
            if (ready) key = min(key, (pr << 8) | (rb << 4) | q);
            if (have) key2 = min(key2, rb >= FINE_RB ? (0x100u | (q << 4) | rb) : (i == 0 ? 0u : 0x1000u));
            pre |= have && i == 0 && !half;
        }
        const bool anypre = __any_sync(~0u, pre);
        if (anypre && (key & 15) == J_QA) key = 0xffffu;
        key = __reduce_min_sync(~0u, key);
        key2 = __reduce_min_sync(~0u, key2);
        if (key2 == 0xffffu) return J_END;
        int pq, prb;
        if (key != 0xffffu) { pq = key & 15; prb = (key >> 4) & 15; }
        else if (key2 >= 0x120u && key2 < 0x1000u) { pq = (key2 >> 4) & 15; prb = key2 & 15; }
        else {
            __nanosleep(IDLE_NS);
            if (++gd > 16 * SPIN_LIMIT) { TIMEOUT(5, 0); return J_END; }
            continue;
        }
        int c = 0;
        if (lane == 0) c = (int)atomicAdd(&g_flags[F_CLAIM + pq * 32 + prb], 1u);
        c = __shfl_sync(~0u, c, 0);
        if (c < (int)((nj_tab(prb) >> (8 * pq)) & 255)) {
            idx = pq * 512 + prb * 32 + c;
            int acq = 0;
            if (pq != J_QA && pq < J_LN1) {
                if (lane == 0 && ld_acquire(&g_flags[pq * 32 + prb]) >= (unsigned)((tg_tab(prb) >> (8 * pq)) & 255)) {
                    asm volatile("fence.proxy.async.global;" ::: "memory");
                    acq = 1 << 24;
                }
            }
            return (pq == J_UP && prb >= FINE_RB ? J_UP2 : pq) | (prb << 8) | (c << 16) | acq;
        }
    }
}
__device__ __forceinline__ int op_row(int rb, int split) {
    return rb < FINE_RB ? split * S_ + rb * 128
                        : (rb < NRB - 1 ? OSPLIT * S_ + (split * (NRB - FINE_RB) + rb - FINE_RB) * 128 : OSPLIT * S_ + (OSPLIT2 * (NRB - FINE_RB) + split) * 128);
}

struct Pipe { uint32_t stage, phase; };
__device__ __forceinline__ void pipe_next(Pipe& p) { if (++p.stage == W_NST) { p.stage = 0; p.phase ^= 1; } }

__device__ __forceinline__ void scheduler(const Params& p, uint32_t sb, int lane) {
    const uint32_t bars = sb + SM_BAR;
    uint32_t ph = 0;
#pragma unroll 1
    while (true) {
        mbar_wait(bars + B_REQ, ph);
        int j = 4095;
        const int jd = pick_job(lane, p.qmask, j);
        if (lane == 0) { sts32(bars + B_NEXT, (uint32_t)jd); sts32(bars + B_NEXT + 4, (uint32_t)j); mbar_arrive(bars + B_RSP); }
        ph ^= 1;
        if (jd == J_END) break;
        __syncwarp();
    }
}

__device__ __forceinline__ void producer(const Params& p, uint32_t sb) {
    Pipe pp{0, 1};
    const uint32_t bars = sb + SM_BAR;
    uint32_t seq = 0, h_seen = 0;
    mbar_arrive(bars + B_REQ);
#pragma unroll 1
    while (true) {
        mbar_wait(bars + B_RSP, seq & 1);
        const int jd = (int)lds32(bars + B_NEXT), j = (int)lds32(bars + B_NEXT + 4);
        int left = (jd & 255) == J_DN ? 15 : ((jd & 255) == J_QA ? (((jd >> 8) & 255) == NRB - 1 ? 10 : 12) : ((jd & 255) == J_O ? o_nk((jd >> 8) & 255) : ((jd & 255) == J_LN || (jd & 255) == J_LN1 || (jd & 255) == J_MOD ? 1 : 8)));
        left = max(left - PICK_AHEAD, 1);
        TR(j, 1);
        const int type = jd & 255, rb = (jd >> 8) & 255, cb = (jd >> 16) & 255;
        const bool fine = rb >= FINE_RB, acquired = (jd >> 24) & 1;
        bool first = true;
        auto begin_stage = [&](uint32_t bytes) -> uint32_t {
            mbar_wait(bars + B_EMPTY + pp.stage * 8, pp.phase);
            if (first) { sts32(bars + B_RING + (seq & 7) * 4, (uint32_t)jd); sts32(bars + B_RING + 32 + (seq & 7) * 4, (uint32_t)j); first = false; }
            const uint32_t fb = bars + B_FULL + pp.stage * 8;
            if (bytes) mbar_expect_tx(fb, bytes); else mbar_arrive(fb);
            if (--left == 0 && type != J_END) mbar_arrive(bars + B_REQ);
            return fb;
        };
        if (type == J_END || type == J_LN || type == J_LN1 || type == J_MOD) {
            if (type == J_LN && !(h_seen >> 31)) { wait_flag(F_MOD + 1, 64); h_seen |= 1u << 31; }

            TR(j, 2);
            begin_stage(0); pipe_next(pp);
            seq++;
            if (type == J_END) break;
            continue;
        }
        const CUtensorMap *ta, *tb0, *tb1;
        int k0 = 0, nk = 8, n0 = cb * 256, n1 = n0 + 128, nb = 4, dep = -1;
        unsigned tgt = 0;
        switch (type) {
            case J_KV: ta = &p.tm_h; tb0 = tb1 = cb < 16 ? &p.tm_wk : &p.tm_wv; n0 = (cb & 15) * 256; n1 = n0 + 128; dep = F_H + rb; tgt = 2 * NJ_LN1; break;
            case J_QA: ta = &p.tm_h; tb0 = tb1 = &p.tm_wq; dep = F_H + rb; tgt = 2 * NJ_LN1; if (rb == NRB - 1) { n0 = (cb >> 1) * 256; n1 = n0 + 128; } break;
            case J_O: ta = &p.tm_o; tb0 = tb1 = &p.tm_wo; n0 = (cb & 1) * 256; n1 = n0 + 128; nk = o_nk(rb); k0 = (cb >> 1) * nk * 64;
                      dep = F_O + rb; tgt = rb == NRB - 1 ? 64 : 32; break;
            case J_UP: ta = &p.tm_h2; tb0 = &p.tm_wg; tb1 = &p.tm_wu; n0 = n1 = cb * 128; dep = F_H2 + rb; tgt = 2 * NJ_LN; break;
            case J_UP2: ta = &p.tm_h2; tb0 = &p.tm_wg; tb1 = &p.tm_wu; n0 = n1 = cb * 64; nb = 2; dep = F_H2 + rb; tgt = 2 * NJ_LN2; break;
            default: ta = &p.tm_act; tb0 = tb1 = &p.tm_wd; n0 = cb * 64; nk = 0; break;
        }
        const int m0 = rb * 128;
        if (type == J_DN && rb == NRB - 1) {
            n0 = (cb >> 1) * 64;
            const int mh = m0 + (cb & 1) * 64;
#pragma unroll 1
            for (int kb = 0; kb < 14; kb++) {
                const uint32_t fb = begin_stage(32768);
                const uint32_t st = sb + pp.stage * W_STAGE;
                const int k = kb * 128;
                tma_load2d(st + 32768, tb0, n0, k, fb);
                tma_load2d(st + 40960, tb0, n0, k + 64, fb);
                if (kb == 0) { if (!acquired) { wait_flag(F_ACT + rb, 2 * NJ_UP2); asm volatile("fence.proxy.async.global;" ::: "memory"); } TR(j, 2); }
                tma_load2d(st, ta, k, mh, fb);
                tma_load2d(st + 8192, ta, k + 64, mh, fb);
                pipe_next(pp);
            }
            const uint32_t fb = begin_stage(8192);
            tma_load2d(sb + pp.stage * W_STAGE, &p.tm_x1, n0, mh, fb);
            pipe_next(pp);
            seq++;
            continue;
        }
        if (type == J_DN) {
#pragma unroll 1
            for (int kb = 0; kb < 14; kb++) {
                const uint32_t fb = begin_stage(49152);
                const uint32_t st = sb + pp.stage * W_STAGE;
                const int k = kb * 128;
                tma_load2d(st + 32768, tb0, n0, k, fb);
                tma_load2d(st + 40960, tb0, n0, k + 64, fb);
                if (kb == 0) { if (!acquired) { wait_flag(F_ACT + rb, 2 * (fine ? NJ_UP2 : NJ_UP)); asm volatile("fence.proxy.async.global;" ::: "memory"); } TR(j, 2); }
                tma_load2d(st, ta, k, m0, fb);
                tma_load2d(st + 8192, ta, k, m0 + 64, fb);
                tma_load2d(st + 16384, ta, k + 64, m0, fb);
                tma_load2d(st + 24576, ta, k + 64, m0 + 64, fb);
                pipe_next(pp);
            }
        }
#pragma unroll 1
        for (int kb = 0; kb < nk; kb++) {
            const uint32_t fb = begin_stage(16384 + nb * 8192);
            const uint32_t st = sb + pp.stage * W_STAGE;
            const int k = k0 + kb * 64;
            tma_load2d(st + 16384, tb0, n0, k, fb);
            if (nb == 4) {
                tma_load2d(st + 16384 + 8192, tb0, n0 + 64, k, fb);
                tma_load2d(st + 16384 + 16384, tb1, n1, k, fb);
                tma_load2d(st + 16384 + 24576, tb1, n1 + 64, k, fb);
            } else if (nb == 2) {
                tma_load2d(st + 16384 + 8192, tb1, n1, k, fb);
            }
            if (kb == 0) {
                if (acquired && dep < 16) h_seen |= 1u << dep;
                if (dep >= 0 && !acquired && !(dep < 16 && ((h_seen >> dep) & 1))) {
                    wait_flag(dep, tgt);
                    if (type != J_O) asm volatile("fence.proxy.async.global;" ::: "memory");
                    if (dep < 16) h_seen |= 1u << dep;
                }
                TR(j, 2);
            }
            tma_load2d(st, ta, k, m0, fb);
            tma_load2d(st + 8192, ta, k, m0 + 64, fb);
            pipe_next(pp);
        }
        if (type == J_QA) {
            wait_flag(F_KV + rb, 64);
#pragma unroll 1
            for (int i = 0; i < (rb == NRB - 1 ? 2 : 4); i++) {
                const uint32_t fb = begin_stage(40960);
                const uint32_t st = sb + pp.stage * W_STAGE;
                const int col = (i & 1) * HD_ + (rb == NRB - 1 ? cb : cb * 2 + (i >> 1)) * DH_;
                tma_load2d(st, &p.tm_kv, col, m0, fb);
                tma_load2d(st + 8192, &p.tm_kv, col, m0 + 64, fb);
                tma_load2d(st + 16384, &p.tm_kv, col + 64, m0, fb);
                tma_load2d(st + 24576, &p.tm_kv, col + 64, m0 + 64, fb);
                if (i == 0) { wait_flag(F_MEM + rb, 64); asm volatile("fence.proxy.async.global;" ::: "memory"); }
                tma_load2d(st + 32768, &p.tm_kvm, col, rb * 32, fb);
                tma_load2d(st + 36864, &p.tm_kvm, col + 64, rb * 32, fb);
                pipe_next(pp);
            }
        } else if (type == J_DN) {
            const uint32_t fb = begin_stage(16384);
            const uint32_t st = sb + pp.stage * W_STAGE;
            tma_load2d(st, &p.tm_x1, n0, m0, fb);
            tma_load2d(st + 8192, &p.tm_x1, n0, m0 + 64, fb);
            pipe_next(pp);
        }
        seq++;
    }
}

__device__ __forceinline__ void store_warp(const Params& p, uint32_t sb, int wg, int lane) {
    const uint32_t bars = sb + SM_BAR;
    uint32_t seq = 0;
#pragma unroll 1
    while (true) {
        bar_sync(NB_ST + wg, 160);
        const uint32_t jd = lds32(bars + B_RING + (seq & 7) * 4);
        seq++;
        const int type = jd & 255, rb = (jd >> 8) & 255, cb = (jd >> 16) & 255;
        if (type == J_END) break;
        const uint32_t src = sb + W_STG + wg * 16384;
        const CUtensorMap* tm = nullptr; int n0 = cb * 256, nbox = 4, mrow = rb * 128 + wg * 64, flag = 0;
        switch (type) {
            case J_KV: tm = &p.tm_kv; flag = F_KV + rb; break;
            case J_QA: tm = &p.tm_o; flag = F_O + rb; if (rb == NRB - 1) { n0 = cb * 128; nbox = 2; } break;
            case J_O: tm = &p.tm_op; n0 = (cb & 1) * 256; mrow = op_row(rb, cb >> 1) + wg * 64; flag = F_OP + rb; break;
            case J_LN: flag = F_H2 + rb; nbox = 0; break;
            case J_LN1: flag = F_H + rb; nbox = 0; break;
            case J_MOD: flag = F_MOD + rb; nbox = 0; break;
            case J_UP: tm = &p.tm_act; n0 = cb * 128; nbox = 2; flag = F_ACT + rb; break;
            case J_UP2: tm = &p.tm_act; n0 = cb * 64; nbox = 1; flag = F_ACT + rb; break;
            default: tm = &p.tm_out; n0 = cb * 64; nbox = 1; flag = -1;
                     if (rb == NRB - 1) { n0 = (cb >> 1) * 64; mrow = rb * 128 + (cb & 1) * 64; nbox = wg == 0; } break;
        }
        if (nbox == 4) {
            if (lane == 0) {
                tma_store2d(tm, src, n0, mrow);
                tma_store2d(tm, src + 8192, n0 + 64, mrow);
                bulk_commit();
                asm volatile("cp.async.bulk.wait_group.read 0;" ::: "memory");
                mbar_arrive(bars + B_STGFREE + wg * 8);
            }
            __syncwarp();
            bar_sync(NB_ST + wg, 160);
            n0 += 128; nbox = 2;
        }
        if (lane == 0) {
            if (nbox) {
                tma_store2d(tm, src, n0, mrow);
                if (nbox == 2) tma_store2d(tm, src + 8192, n0 + 64, mrow);
                bulk_commit();
                asm volatile("cp.async.bulk.wait_group.read 0;" ::: "memory");
                mbar_arrive(bars + B_STGFREE + wg * 8);
                bulk_wait0();
                if (flag >= 0) asm volatile("red.relaxed.gpu.global.add.u32 [%0], 1;" :: "l"(&g_flags[flag]) : "memory");
            } else {
                mbar_arrive(bars + B_STGFREE + wg * 8);
                if (flag >= 0) red_release(&g_flags[flag], 1);
            }
        }
        __syncwarp();
    }
}

__device__ __forceinline__ float gelu_tanh(float x) {
    const float t = x * fmaf(-0.10294324397f, x * x, -2.30220819814f);
    float r; asm("rcp.approx.ftz.f32 %0, %1;" : "=f"(r) : "f"(1.f + ex2(t)));
    return x * r;
}

#define CTR(i) do {} while (0)

__device__ __forceinline__ void ln2_row(const Params& p, int rb, int r, int lane, bool wait) {
    const int row = rb * 128 + r, nsplit = 64 / o_nk(rb);
    const uint4* xr = (const uint4*)(p.x + (size_t)row * D_);
    const uint4 xa = __ldg(xr + lane), xb = __ldg(xr + 32 + lane);
    uint32_t ga[8], c1[8], sm[8];
    load_mod8(g_mod + 2 * D_, lane, ga);
    load_mod8(g_mod + 4 * D_, lane, c1);
    load_mod8(g_mod + 3 * D_, lane, sm);
    float a[16];
#pragma unroll
    for (int i = 0; i < 16; i++) a[i] = 0.f;
    const uint4* src = (const uint4*)(g_op + (size_t)(op_row(rb, 0) + r) * D_) + lane;
    const int sstride = (op_row(rb, 1) - op_row(rb, 0)) * (D_ / 8);
    if (wait) { if (lane == 0) wait_flag(F_OP + rb, 4 * nsplit); __syncwarp(); }
    uint4 u[2][8];
#pragma unroll
    for (int sp = 0; sp < 4; sp++) { u[0][2 * sp] = __ldcg(src + sp * sstride); u[0][2 * sp + 1] = __ldcg(src + sp * sstride + 32); }
    if (nsplit > 4) {
#pragma unroll
        for (int sp = 0; sp < 4; sp++) { u[1][2 * sp] = __ldcg(src + (4 + sp) * sstride); u[1][2 * sp + 1] = __ldcg(src + (4 + sp) * sstride + 32); }
    }
#pragma unroll 1
    for (int s0 = 0; s0 < nsplit; s0 += 4) {
#pragma unroll
        for (int sp = 0; sp < 8; sp++) {
            float* q = a + (sp & 1) * 8;
            const uint4 w = u[0][sp];
            q[0] += bflo(w.x); q[1] += bfhi(w.x); q[2] += bflo(w.y); q[3] += bfhi(w.y);
            q[4] += bflo(w.z); q[5] += bfhi(w.z); q[6] += bflo(w.w); q[7] += bfhi(w.w);
            u[0][sp] = u[1][sp];
        }
        if (s0 + 8 < nsplit) {
#pragma unroll
            for (int sp = 0; sp < 4; sp++) { u[1][2 * sp] = __ldcg(src + (s0 + 8 + sp) * sstride); u[1][2 * sp + 1] = __ldcg(src + (s0 + 8 + sp) * sstride + 32); }
        }
    }
    const uint32_t xv[8] = {xa.x, xa.y, xa.z, xa.w, xb.x, xb.y, xb.z, xb.w};
    uint32_t v[8], r8[8];
#pragma unroll
    for (int i = 0; i < 8; i++) v[i] = hadd2(xv[i], hmul2(ga[i], pack2(a[2 * i], a[2 * i + 1])));
    uint4* x1r = (uint4*)(g_x1 + (size_t)row * D_);
    x1r[lane] = make_uint4(v[0], v[1], v[2], v[3]); x1r[32 + lane] = make_uint4(v[4], v[5], v[6], v[7]);
    uint32_t mu2; float rden;
    ln_stats(v, mu2, rden);
#pragma unroll
    for (int i = 0; i < 8; i++) c1[i] = hadd2(c1[i], 0x3F803F80u);
    ln_apply(v, mu2, rden, c1, sm, r8);
    uint4* hr = (uint4*)(g_h2 + (size_t)row * D_);
    hr[lane] = make_uint4(r8[0], r8[1], r8[2], r8[3]); hr[32 + lane] = make_uint4(r8[4], r8[5], r8[6], r8[7]);
}

__device__ __forceinline__ void consumer(const Params& p, uint32_t sb, int warp, int lane) {
    const uint32_t bars = sb + SM_BAR;
    const int wg = warp >> 2, wl = warp & 3;
    const uint32_t l7 = lane & 7, l8 = lane >> 3, g = lane >> 2, t = lane & 3;
    Pipe pp{0, 0};
    uint32_t seq = 0, stg_phase = 1;
    const int srow = wl * 16 + l7 + (l8 & 1) * 8;
    const uint32_t stg_base = sb + W_STG + wg * 16384 + srow * 128;
    const uint32_t sx = ((lane >> 4) ^ (srow & 7)) << 4;
#pragma unroll 1
    while (true) {
        mbar_wait(bars + B_FULL + pp.stage * 8, pp.phase);
        const uint32_t jd = lds32(bars + B_RING + (seq & 7) * 4);
        CTR(3);
        seq++;
        const int type = jd & 255, rb = (jd >> 8) & 255, cb = (jd >> 16) & 255;
        if (type == J_END) { mbar_wait(bars + B_STGFREE + wg * 8, stg_phase); bar_arrive(NB_ST + wg, 160); break; }
        if (type == J_LN) {
            __syncwarp();
            if (lane == 0) mbar_arrive(bars + B_EMPTY + pp.stage * 8);
            pipe_next(pp);
            const int nr = rb >= FINE_RB ? 1 : 2;
#pragma unroll 1
            for (int rr = 0; rr < nr; rr++) ln2_row(p, rb, (cb * 8 + warp) * nr + rr, lane, !((jd >> 24) & 1) && rr == 0);
            mbar_wait(bars + B_STGFREE + wg * 8, stg_phase); stg_phase ^= 1;
            CTR(4); CTR(5);
            bar_arrive(NB_ST + wg, 160);
            continue;
        }
        if (type == J_DN || type == J_UP2) {
            float acc[64];
#pragma unroll
            for (int i = 0; i < 64; i++) acc[i] = 0.f;
            const bool ksplit = type == J_DN && rb == NRB - 1;
            if (ksplit) {
#pragma unroll 1
                for (int kb = 0; kb < 14; kb++) {
                    if (kb) mbar_wait(bars + B_FULL + pp.stage * 8, pp.phase);
                    const uint32_t st = sb + pp.stage * W_STAGE;
                    const uint64_t da = mkdesc(st + wg * 8192, 16, 1024), db = mkdesc(st + 32768 + wg * 8192, 8192, 1024);
                    wg_fence();
#pragma unroll
                    for (int ks = 0; ks < 4; ks++) wgmma_n64(acc, da + ks * 2, db + ks * 128);
                    wg_commit();
                    wg_wait0();
                    if (lane == 0) mbar_arrive(bars + B_EMPTY + pp.stage * 8);
                    pipe_next(pp);
                }
                const uint32_t xb = sb + W_STG + 16384 + (wl * 32 + lane) * 16;
                if (wg == 1) {
                    mbar_wait(bars + B_STGFREE + 8, stg_phase);
#pragma unroll
                    for (int i = 0; i < 8; i++)
                        sts128(xb + i * 2048, make_uint4(__float_as_uint(acc[4 * i]), __float_as_uint(acc[4 * i + 1]), __float_as_uint(acc[4 * i + 2]), __float_as_uint(acc[4 * i + 3])));
                }
                bar_sync(NB_M, 256);
                if (wg == 0) {
#pragma unroll
                    for (int i = 0; i < 8; i++) {
                        const uint4 o = lds128(xb + i * 2048);
                        acc[4 * i] += __uint_as_float(o.x); acc[4 * i + 1] += __uint_as_float(o.y); acc[4 * i + 2] += __uint_as_float(o.z); acc[4 * i + 3] += __uint_as_float(o.w);
                    }
                }
                bar_sync(NB_M, 256);
            } else if (type == J_DN) {
#pragma unroll 1
                for (int kb = 0; kb < 14; kb++) {
                    if (kb) mbar_wait(bars + B_FULL + pp.stage * 8, pp.phase);
                    const uint32_t st = sb + pp.stage * W_STAGE;
                    const uint64_t da = mkdesc(st + wg * 8192, 16, 1024), db = mkdesc(st + 32768, 8192, 1024);
                    wg_fence();
#pragma unroll
                    for (int ks = 0; ks < 8; ks++) wgmma_n64(acc, da + (ks >> 2) * 1024 + (ks & 3) * 2, db + ks * 128);
                    wg_commit();
                    wg_wait0();
                    if (lane == 0) mbar_arrive(bars + B_EMPTY + pp.stage * 8);
                    pipe_next(pp);
                }
            } else {
#pragma unroll 1
                for (int kb = 0; kb < 8; kb++) {
                    if (kb) mbar_wait(bars + B_FULL + pp.stage * 8, pp.phase);
                    const uint32_t st = sb + pp.stage * W_STAGE;
                    const uint64_t da = mkdesc(st + wg * 8192, 16, 1024), db = mkdesc(st + 16384, 8192, 1024);
                    wg_fence();
#pragma unroll
                    for (int ks = 0; ks < 4; ks++) wgmma_n128(acc, da + ks * 2, db + ks * 128, 1);
                    wg_commit();
                    wg_wait0();
                    if (lane == 0) mbar_arrive(bars + B_EMPTY + pp.stage * 8);
                    pipe_next(pp);
                }
            }
            CTR(4);
            if (type == J_UP2) {
                mbar_wait(bars + B_STGFREE + wg * 8, stg_phase); stg_phase ^= 1;
#pragma unroll
                for (int j = 0; j < 4; j++) {
                    uint32_t r[4];
#pragma unroll
                    for (int q = 0; q < 4; q++) {
                        const uint32_t gw = pack2(acc[8 * j + 2 * q], acc[8 * j + 2 * q + 1]);
                        const uint32_t uw = pack2(acc[32 + 8 * j + 2 * q], acc[32 + 8 * j + 2 * q + 1]);
                        r[q] = hmul2(pack2(gelu_tanh(bflo(gw)), gelu_tanh(bfhi(gw))), uw);
                    }
                    stsm4(stg_base + (sx ^ (j << 5)), r[0], r[1], r[2], r[3]);
                }
            } else {
                mbar_wait(bars + B_FULL + pp.stage * 8, pp.phase);
                const uint32_t st = sb + pp.stage * W_STAGE;
                mbar_wait(bars + B_STGFREE + wg * 8, stg_phase); stg_phase ^= 1;
                const uint32_t* gb = (const uint32_t*)(g_mod + 5 * D_ + (ksplit ? cb >> 1 : cb) * 64) + t;
                const uint32_t xa = st + (ksplit ? 0 : wg * 8192) + (wl * 16 + g) * 128 + (g << 4) + t * 4;
#pragma unroll
                for (int j = 0; j < 4; j++) {
                    uint32_t r[4];
#pragma unroll
                    for (int q = 0; q < 4; q++) {
                        const int nt = 2 * j + (q >> 1);
                        const uint32_t xw = lds32((xa ^ ((nt & 7) << 4)) + (nt >> 3) * 16384 + (q & 1) * 1024);
                        r[q] = hadd2(xw, hmul2(__ldcg(gb + nt * 4), pack2(acc[8 * j + 2 * q], acc[8 * j + 2 * q + 1])));
                    }
                    stsm4(stg_base + (j >> 2) * 8192 + (sx ^ ((2 * j & 7) << 4)), r[0], r[1], r[2], r[3]);
                }
                __syncwarp();
                if (lane == 0) mbar_arrive(bars + B_EMPTY + pp.stage * 8);
                pipe_next(pp);
            }
            fence_async_smem();
            CTR(5);
            bar_arrive(NB_ST + wg, 160);
            continue;
        }
        float acc[128];
#pragma unroll
        for (int i = 0; i < 128; i++) acc[i] = 0.f;
        const int nk = type == J_O ? o_nk(rb) : 8;
#pragma unroll 1
        for (int kb = 0; kb < nk; kb++) {
            if (kb) mbar_wait(bars + B_FULL + pp.stage * 8, pp.phase);
            const uint32_t st = sb + pp.stage * W_STAGE;
            const uint64_t da = mkdesc(st + wg * 8192, 16, 1024), db = mkdesc(st + 16384, 8192, 1024);
            wg_fence();
#pragma unroll
            for (int ks = 0; ks < 4; ks++) wgmma_n256(acc, da + ks * 2, db + ks * 128, 1);
            wg_commit();
            wg_wait0();
            if (lane == 0) mbar_arrive(bars + B_EMPTY + pp.stage * 8);
            pipe_next(pp);
        }
        CTR(4);
        if (type == J_QA) {
            uint32_t qf[64];
#pragma unroll
            for (int i = 0; i < 64; i++) qf[i] = pack2(acc[2 * i], acc[2 * i + 1]);
            const int sg = warp >> 1, half = warp & 1;
            const float sc = 0.08838834764831845f * 1.4426950408889634f;
            const uint32_t xoff = (sg >> 1) * 8192 + ((sg & 1) * 32 + l7) * 128;
            const uint32_t moff = 32768 + (sg * 8 + l7) * 128;
            const uint32_t kch = (l8 ^ l7) << 4;
            const uint32_t vch = ((l8 & 1) ^ l7) << 4;
            if (rb == NRB - 1 && (cb & 1)) {
#pragma unroll
                for (int i = 0; i < 32; i++) qf[i] = qf[32 + i];
            }
#pragma unroll 1
            for (int hh = rb == NRB - 1; hh < 2; hh++) {
                mbar_wait(bars + B_FULL + pp.stage * 8, pp.phase);
                uint32_t st = sb + pp.stage * W_STAGE;
                float sa[5][4];
#pragma unroll
                for (int n = 0; n < 5; n++) sa[n][0] = sa[n][1] = sa[n][2] = sa[n][3] = 0.f;
#pragma unroll
                for (int i = 0; i < 4; i++) {
                    const uint32_t* q = qf + i * 8;
                    uint32_t kk[5][4];
                    ldsm4(kk[0][0], kk[0][1], kk[0][2], kk[0][3], st + moff + (i >> 1) * 4096 + (kch ^ ((i & 1) * 64)));
#pragma unroll
                    for (int n = 1; n < 5; n++)
                        ldsm4(kk[n][0], kk[n][1], kk[n][2], kk[n][3], st + xoff + (n - 1) * 1024 + (i >> 1) * 16384 + (kch ^ ((i & 1) * 64)));
#pragma unroll
                    for (int n = 0; n < 5; n++) mma16816(sa[n], q[0], q[1], q[2], q[3], kk[n][0], kk[n][1]);
#pragma unroll
                    for (int n = 0; n < 5; n++) mma16816(sa[n], q[4], q[5], q[6], q[7], kk[n][2], kk[n][3]);
                }
                __syncwarp();
                if (lane == 0) mbar_arrive(bars + B_EMPTY + pp.stage * 8);
                pipe_next(pp);
                const int iq0 = half * 16 + g - 2 * t, iq1 = iq0 + 8;
                float m0 = fmaxf(sa[0][0], sa[0][1]), m1 = fmaxf(sa[0][2], sa[0][3]);
#pragma unroll
                for (int n = 1; n < 5; n++) {
#pragma unroll
                    for (int e = 0; e < 2; e++) {
                        const int jx = (n - 1) * 8 + e;
                        if (jx > iq0) sa[n][e] = -3.0e38f;
                        if (jx > iq1) sa[n][2 + e] = -3.0e38f;
                        m0 = fmaxf(m0, sa[n][e]); m1 = fmaxf(m1, sa[n][2 + e]);
                    }
                }
                m0 = fmaxf(m0, __shfl_xor_sync(~0u, m0, 1)); m1 = fmaxf(m1, __shfl_xor_sync(~0u, m1, 1));
                m0 = fmaxf(m0, __shfl_xor_sync(~0u, m0, 2)); m1 = fmaxf(m1, __shfl_xor_sync(~0u, m1, 2));
                m0 *= -sc; m1 *= -sc;
                float l0 = 0.f, l1 = 0.f;
                uint32_t p0[5], p1[5];
#pragma unroll
                for (int n = 0; n < 5; n++) {
                    const float e0 = ex2(fmaf(sa[n][0], sc, m0)), e1 = ex2(fmaf(sa[n][1], sc, m0));
                    const float e2 = ex2(fmaf(sa[n][2], sc, m1)), e3 = ex2(fmaf(sa[n][3], sc, m1));
                    l0 += e0 + e1; l1 += e2 + e3;
                    p0[n] = pack2(e0, e1); p1[n] = pack2(e2, e3);
                }
                l0 += __shfl_xor_sync(~0u, l0, 1); l1 += __shfl_xor_sync(~0u, l1, 1);
                l0 += __shfl_xor_sync(~0u, l0, 2); l1 += __shfl_xor_sync(~0u, l1, 2);
                const float i0 = __fdividef(1.f, l0), i1 = __fdividef(1.f, l1);
                mbar_wait(bars + B_FULL + pp.stage * 8, pp.phase);
                st = sb + pp.stage * W_STAGE;
                mbar_wait(bars + B_STGFREE + wg * 8, stg_phase); stg_phase ^= 1;
#pragma unroll
                for (int i = 0; i < 32; i++) qf[i] = qf[32 + i];
#pragma unroll 1
                for (int bx = 0; bx < 2; bx++) {
                    float o[8][4];
                    uint32_t vm[8], v0[4][4], v1[4][4];
#pragma unroll
                    for (int ep = 0; ep < 4; ep++) {
                        ldsm2t(vm[2 * ep], vm[2 * ep + 1], st + moff + bx * 4096 + (vch ^ (ep << 5)));
                        const uint32_t va = st + xoff + (l8 >> 1) * 1024 + bx * 16384 + (vch ^ (ep << 5));
                        ldsm4t(v0[ep][0], v0[ep][1], v0[ep][2], v0[ep][3], va);
                        ldsm4t(v1[ep][0], v1[ep][1], v1[ep][2], v1[ep][3], va + 2048);
                    }
#pragma unroll
                    for (int n = 0; n < 8; n++) { o[n][0] = o[n][1] = o[n][2] = o[n][3] = 0.f; mma16816(o[n], p0[0], p1[0], p0[1], p1[1], vm[n], v0[n >> 1][n & 1]); }
#pragma unroll
                    for (int n = 0; n < 8; n++) mma16816(o[n], p0[2], p1[2], p0[3], p1[3], v0[n >> 1][2 + (n & 1)], v1[n >> 1][n & 1]);
#pragma unroll
                    for (int n = 0; n < 8; n++) mma1688(o[n], p0[4], p1[4], v1[n >> 1][2 + (n & 1)]);
#pragma unroll
                    for (int ep = 0; ep < 4; ep++)
                        stsm4(stg_base + bx * 8192 + (sx ^ (ep << 5)),
                              pack2(o[2 * ep][0] * i0, o[2 * ep][1] * i0), pack2(o[2 * ep][2] * i1, o[2 * ep][3] * i1),
                              pack2(o[2 * ep + 1][0] * i0, o[2 * ep + 1][1] * i0), pack2(o[2 * ep + 1][2] * i1, o[2 * ep + 1][3] * i1));
                }
                __syncwarp();
                if (lane == 0) mbar_arrive(bars + B_EMPTY + pp.stage * 8);
                pipe_next(pp);
                if (hh == 0) { fence_async_smem(); bar_arrive(NB_ST + wg, 160); }
            }
        } else if (type == J_UP) {
            mbar_wait(bars + B_STGFREE + wg * 8, stg_phase); stg_phase ^= 1;
#pragma unroll
            for (int j = 0; j < 8; j++) {
                uint32_t r[4];
#pragma unroll
                for (int q = 0; q < 4; q++) {
                    const uint32_t gw = pack2(acc[8 * j + 2 * q], acc[8 * j + 2 * q + 1]);
                    const uint32_t uw = pack2(acc[64 + 8 * j + 2 * q], acc[64 + 8 * j + 2 * q + 1]);
                    r[q] = hmul2(pack2(gelu_tanh(bflo(gw)), gelu_tanh(bfhi(gw))), uw);
                }
                stsm4(stg_base + (j >> 2) * 8192 + (sx ^ ((2 * j & 7) << 4)), r[0], r[1], r[2], r[3]);
            }
        } else {
#pragma unroll
            for (int rd = 0; rd < 2; rd++) {
                mbar_wait(bars + B_STGFREE + wg * 8, stg_phase); stg_phase ^= 1;
#pragma unroll
                for (int j = rd * 8; j < rd * 8 + 8; j++)
                    stsm4(stg_base + ((j >> 2) & 1) * 8192 + (sx ^ ((2 * j & 7) << 4)),
                          pack2(acc[8 * j], acc[8 * j + 1]), pack2(acc[8 * j + 2], acc[8 * j + 3]),
                          pack2(acc[8 * j + 4], acc[8 * j + 5]), pack2(acc[8 * j + 6], acc[8 * j + 7]));
                if (rd == 0) { fence_async_smem(); bar_arrive(NB_ST + wg, 160); }
            }
        }
        fence_async_smem();
        CTR(5);
        bar_arrive(NB_ST + wg, 160);
    }
}

__global__ void __launch_bounds__(384, 1) k_work(const __grid_constant__ Params p) {
    extern __shared__ __align__(1024) unsigned char smem_raw[];
    const uint32_t sb = smem_u32(smem_raw);
    if (sb & 1023) __trap();
    const int warp = __shfl_sync(~0u, threadIdx.x >> 5, 0);
    int lane; asm volatile("mov.u32 %0, %%laneid;" : "=r"(lane));
    if (threadIdx.x == 0) {
        const uint32_t bars = sb + SM_BAR;
        for (int i = 0; i < W_NST; i++) { mbar_init(bars + B_FULL + i * 8, 1); mbar_init(bars + B_EMPTY + i * 8, 8); }
        mbar_init(bars + B_STGFREE, 1); mbar_init(bars + B_STGFREE + 8, 1); mbar_init(bars + B_REQ, 1); mbar_init(bars + B_RSP, 1);
        asm volatile("fence.mbarrier_init.release.cluster;" ::: "memory");
    }
    __syncthreads();
    if (warp < 8) {
        asm volatile("setmaxnreg.inc.sync.aligned.u32 224;");
        consumer(p, sb, warp, lane);
    } else {
        asm volatile("setmaxnreg.dec.sync.aligned.u32 56;");
        if (warp == 8) { if (lane == 0) producer(p, sb); }
        else if (warp < 11) store_warp(p, sb, warp - 9, lane);
        else scheduler(p, sb, lane);
        __syncwarp();
        bar_sync(NB_W0, 128);
        if (warp == 8 && p.qmask == 0xff) {
            unsigned last = 0;
            if (lane == 0) { __threadfence(); last = atomicAdd(&g_flags[F_DONE], 1u) == gridDim.x - 1; }
            if (__shfl_sync(~0u, last, 0))
                for (int i = lane; i < F_TOTAL; i += 32) g_flags[i] = 0;
        }
    }
}

typedef CUresult (*EncodeFn)(CUtensorMap*, CUtensorMapDataType, cuuint32_t, void*, const cuuint64_t*, const cuuint64_t*,
                             const cuuint32_t*, const cuuint32_t*, CUtensorMapInterleave, CUtensorMapSwizzle,
                             CUtensorMapL2promotion, CUtensorMapFloatOOBfill);

static void make_map(EncodeFn enc, CUtensorMap* m, const void* ptr, uint64_t rows, uint64_t cols, uint32_t box_rows) {
    cuuint64_t dims[2] = {cols, rows};
    cuuint64_t strides[1] = {cols * 2};
    cuuint32_t box[2] = {64, box_rows};
    cuuint32_t es[2] = {1, 1};
    enc(m, CU_TENSOR_MAP_DATA_TYPE_BFLOAT16, 2, const_cast<void*>(ptr), dims, strides, box, es, CU_TENSOR_MAP_INTERLEAVE_NONE,
        CU_TENSOR_MAP_SWIZZLE_128B, CU_TENSOR_MAP_L2_PROMOTION_L2_256B, CU_TENSOR_MAP_FLOAT_OOB_FILL_NONE);
}
template <typename T> static void* sym_addr(T& sym) { void* p = nullptr; cudaGetSymbolAddress(&p, sym); return p; }

extern "C" void kernel_launch(void* const* d_in, const int* in_sizes, int n_in, void* d_out, int out_size) {
    static Params prm;
    static RecParams rp;
    static bool ready = false;
    static const void* key[14];
    bool same = ready;
    for (int i = 0; i < 13 && same; i++) same = key[i] == d_in[i];
    same = same && key[13] == d_out;
    if (!same) {
        void* fn = nullptr;
        cudaDriverEntryPointQueryResult qr;
        cudaGetDriverEntryPoint("cuTensorMapEncodeTiled", &fn, cudaEnableDefault, &qr);
        EncodeFn enc = (EncodeFn)fn;
        make_map(enc, &prm.tm_h, sym_addr(g_h), S_, D_, 64);
        make_map(enc, &prm.tm_kv, sym_addr(g_kv), S_, 2 * HD_, 64);
        make_map(enc, &prm.tm_kvm, sym_addr(g_kvm), NSEG * 8, 2 * HD_, 32);
        make_map(enc, &prm.tm_o, sym_addr(g_o), S_, HD_, 64);
        make_map(enc, &prm.tm_op, sym_addr(g_op), OP_ROWS, D_, 64);
        make_map(enc, &prm.tm_h2, sym_addr(g_h2), S_, D_, 64);
        make_map(enc, &prm.tm_act, sym_addr(g_act), S_, DF_, 64);
        make_map(enc, &prm.tm_x1, sym_addr(g_x1), S_, D_, 64);
        make_map(enc, &prm.tm_out, d_out, S_, D_, 64);
        make_map(enc, &prm.tm_wq, d_in[2], D_, HD_, 64);
        make_map(enc, &prm.tm_wk, d_in[3], D_, HD_, 64);
        make_map(enc, &prm.tm_wv, d_in[4], D_, HD_, 64);
        make_map(enc, &prm.tm_wo, d_in[5], HD_, D_, 64);
        make_map(enc, &prm.tm_wg, d_in[8], D_, DF_, 64);
        make_map(enc, &prm.tm_wu, d_in[9], D_, DF_, 64);
        make_map(enc, &prm.tm_wd, d_in[10], DF_, D_, 64);
        prm.x = (const bf16*)d_in[0]; prm.c = (const bf16*)d_in[11]; prm.w_mod = (const bf16*)d_in[12];
        rp.mem0 = (const bf16*)d_in[1]; rp.x = prm.x; rp.c = prm.c; rp.w_mod = prm.w_mod;
        rp.wq = (const bf16*)d_in[2]; rp.wk = (const bf16*)d_in[3]; rp.wv = (const bf16*)d_in[4]; rp.wo = (const bf16*)d_in[5];
        cudaFuncSetAttribute(k_work, cudaFuncAttributeMaxDynamicSharedMemorySize, SMEM_BYTES);
        cudaFuncSetAttribute(k_rec, cudaFuncAttributeMaxDynamicSharedMemorySize, R_SMEM);
        cudaFuncSetAttribute(k_rec, cudaFuncAttributeNonPortableClusterSizeAllowed, 1);
        {
            cudaLaunchConfig_t cfg = {};
            cfg.gridDim = dim3(128); cfg.blockDim = dim3(384); cfg.dynamicSmemBytes = R_SMEM;
            cudaLaunchAttribute at[1];
            at[0].id = cudaLaunchAttributeClusterDimension; at[0].val.clusterDim.x = 16; at[0].val.clusterDim.y = 1; at[0].val.clusterDim.z = 1;
            cfg.attrs = at; cfg.numAttrs = 1;
            int n = 0;
            cudaOccupancyMaxActiveClusters(&n, k_rec, &cfg);
            rp.ncl = n < 4 ? 4 : (n > 8 ? 8 : n);
        }
        for (int i = 0; i < 13; i++) key[i] = d_in[i];
        key[13] = d_out;
        ready = true;
    }
    cudaStream_t st = cudaStreamPerThread;
    auto launch_rec = [&]() {
        cudaLaunchConfig_t cfg = {};
        cfg.gridDim = dim3(16 * rp.ncl); cfg.blockDim = dim3(384); cfg.dynamicSmemBytes = R_SMEM; cfg.stream = st;
        cudaLaunchAttribute at[1];
        at[0].id = cudaLaunchAttributeClusterDimension; at[0].val.clusterDim.x = 16; at[0].val.clusterDim.y = 1; at[0].val.clusterDim.z = 1;
        cfg.attrs = at; cfg.numAttrs = 1;
        cudaLaunchKernelEx(&cfg, k_rec, rp);
    };
    auto launch_work = [&](int qmask, int pdl) {
        prm.qmask = qmask;
        cudaLaunchConfig_t cfg = {};
        cfg.gridDim = dim3(132); cfg.blockDim = dim3(384); cfg.dynamicSmemBytes = SMEM_BYTES; cfg.stream = st;
        cudaLaunchAttribute at[1];
        at[0].id = cudaLaunchAttributeProgrammaticStreamSerialization; at[0].val.programmaticStreamSerializationAllowed = 1;
        cfg.attrs = at; cfg.numAttrs = pdl;
        cudaLaunchKernelEx(&cfg, k_work, prm);
    };
    launch_rec();
    launch_work(0xff, 1);
}
```

```cpp
#include <cuda_runtime.h>
#include <cuda_bf16.h>
#include <cuda.h>
#include <stdint.h>

typedef __nv_bfloat16 bf16;
#define PF_NS 500
#define IDLE_NS 150
#define FLAG_NS 20

constexpr int S_ = 2048, D_ = 512, H_ = 32, DH_ = 128, HD_ = 4096, NSEG = 64, DF_ = 1792;
constexpr int NRB = 16;
constexpr int OSPLIT = 4;

__device__ __align__(1024) bf16 g_h[S_ * D_];
__device__ __align__(1024) bf16 g_kv[S_ * 2 * HD_];
__device__ __align__(1024) bf16 g_kvm[NSEG * 8 * 2 * HD_];
__device__ __align__(1024) bf16 g_o[S_ * HD_];
#define FINE_RB_ 12
constexpr int FINE_RB = FINE_RB_;
#define OSPLIT2_ 8
constexpr int OSPLIT2 = OSPLIT2_;
constexpr int OSPLIT3 = 16;
constexpr int OP_ROWS = OSPLIT * S_ + OSPLIT2 * (NRB - FINE_RB) * 128 + OSPLIT3 * 128;
__device__ __align__(1024) bf16 g_op[OP_ROWS * D_];
__device__ __align__(1024) bf16 g_x1[S_ * D_];
__device__ __align__(1024) bf16 g_h2[S_ * D_];
__device__ __align__(1024) bf16 g_act[S_ * DF_];
__device__ __align__(1024) bf16 g_mod[6 * D_];
__device__ uint32_t g_Fraw[131072 + 65536 + 2048];
#define g_F ((uint32_t*)(((uint64_t)g_Fraw + 0x7FFFFull) & ~0x7FFFFull))
constexpr int F_H = 0, F_MEM = 32, F_O = 64, F_OP = 96, F_H2 = 128, F_ACT = 160, F_MOD = 192, F_KV = 224, F_CLAIM = 256  ,
              F_SIDE = 512  , F_DONE = 576, F_TOTAL = 608;
__device__ __align__(128) unsigned int g_flags[F_TOTAL];
#define TR(j, i) do {} while (0)

__device__ __forceinline__ uint32_t smem_u32(const void* p) { return (uint32_t)__cvta_generic_to_shared(p); }
__device__ __forceinline__ uint32_t clk32() { uint32_t c; asm volatile("mov.u32 %0, %%clock;" : "=r"(c)); return c; }
__device__ __forceinline__ uint32_t mapa_u32(uint32_t addr, uint32_t rank) {
    uint32_t r; asm volatile("mapa.shared::cluster.u32 %0, %1, %2;" : "=r"(r) : "r"(addr), "r"(rank)); return r;
}
__device__ __forceinline__ void mbar_init(uint32_t bar, uint32_t cnt) {
    asm volatile("mbarrier.init.shared::cta.b64 [%0], %1;" :: "r"(bar), "r"(cnt) : "memory");
}
__device__ __forceinline__ void mbar_inval(uint32_t bar) {
    asm volatile("mbarrier.inval.shared::cta.b64 [%0];" :: "r"(bar) : "memory");
}
__device__ __forceinline__ void mbar_expect_tx(uint32_t bar, uint32_t bytes) {
    asm volatile("mbarrier.arrive.expect_tx.shared::cta.b64 _, [%0], %1;" :: "r"(bar), "r"(bytes) : "memory");
}
__device__ __forceinline__ void mbar_arrive(uint32_t bar) {
    asm volatile("mbarrier.arrive.shared::cta.b64 _, [%0];" :: "r"(bar) : "memory");
}
__device__ __forceinline__ bool mbar_try_wait(uint32_t bar, uint32_t parity) {
    uint32_t ok;
    asm volatile("{\n.reg .pred p;\nmbarrier.try_wait.parity.shared::cta.b64 p, [%1], %2;\nselp.u32 %0, 1, 0, p;\n}"
                 : "=r"(ok) : "r"(bar), "r"(parity) : "memory");
    return ok;
}
__device__ __forceinline__ bool mbar_try_wait_cluster(uint32_t bar, uint32_t parity) {
    uint32_t ok;
    asm volatile("{\n.reg .pred p;\nmbarrier.try_wait.parity.acquire.cluster.shared::cta.b64 p, [%1], %2;\nselp.u32 %0, 1, 0, p;\n}"
                 : "=r"(ok) : "r"(bar), "r"(parity) : "memory");
    return ok;
}
constexpr int SPIN_LIMIT = 1 << 18;
#define TIMEOUT(code, info) do {} while (0)
__device__ __forceinline__ void mbar_wait(uint32_t bar, uint32_t parity) {
    int g = 0;
#pragma unroll 1
    while (!mbar_try_wait(bar, parity)) { if (++g >= SPIN_LIMIT) { TIMEOUT(0, bar & 255); break; } }
}
__device__ __forceinline__ void mbar_wait_cluster(uint32_t bar, uint32_t parity) {
    int g = 0;
#pragma unroll 1
    while (!mbar_try_wait_cluster(bar, parity)) { if (++g >= SPIN_LIMIT) { TIMEOUT(1, bar & 255); break; } }
}
__device__ __forceinline__ void bar_sync(int id, int n) { asm volatile("bar.sync %0, %1;" :: "r"(id), "r"(n) : "memory"); }
__device__ __forceinline__ void bar_arrive(int id, int n) { asm volatile("bar.arrive %0, %1;" :: "r"(id), "r"(n) : "memory"); }
__device__ __forceinline__ void cluster_sync_all() {
    asm volatile("barrier.cluster.arrive.aligned;\nbarrier.cluster.wait.aligned;" ::: "memory");
}
__device__ __forceinline__ void st_async_v2(uint32_t addr, float a, float b, uint32_t bar) {
    asm volatile("st.async.weak.shared::cluster.mbarrier::complete_tx::bytes.v2.f32 [%0], {%1,%2}, [%3];"
                 :: "r"(addr), "f"(a), "f"(b), "r"(bar) : "memory");
}
__device__ __forceinline__ void st_async_v4(uint32_t addr, uint4 v, uint32_t bar) {
    asm volatile("st.async.weak.shared::cluster.mbarrier::complete_tx::bytes.v4.b32 [%0], {%1,%2,%3,%4}, [%5];"
                 :: "r"(addr), "r"(v.x), "r"(v.y), "r"(v.z), "r"(v.w), "r"(bar) : "memory");
}
__device__ __forceinline__ uint2 ldg_relaxed2(const uint2* p) {
    uint2 v;
    asm volatile("ld.relaxed.gpu.global.v2.b32 {%0,%1}, [%2];" : "=r"(v.x), "=r"(v.y) : "l"(p) : "memory");
    return v;
}
__device__ __forceinline__ void stg_relaxed2(uint2* p, uint2 v) {
    asm volatile("st.relaxed.gpu.global.v2.b32 [%0], {%1,%2};" :: "l"(p), "r"(v.x), "r"(v.y) : "memory");
}
__device__ __forceinline__ uint4 ldg_relaxed(const uint4* p) {
    uint4 v;
    asm volatile("ld.relaxed.gpu.global.v4.b32 {%0,%1,%2,%3}, [%4];" : "=r"(v.x), "=r"(v.y), "=r"(v.z), "=r"(v.w) : "l"(p) : "memory");
    return v;
}
__device__ __forceinline__ void stg_relaxed(uint4* p, uint4 v) {
    asm volatile("st.relaxed.gpu.global.v4.b32 [%0], {%1,%2,%3,%4};" :: "l"(p), "r"(v.x), "r"(v.y), "r"(v.z), "r"(v.w) : "memory");
}
__device__ __forceinline__ void stg_relaxed32(uint32_t* p, uint32_t v) {
    asm volatile("st.relaxed.gpu.global.b32 [%0], %1;" :: "l"(p), "r"(v) : "memory");
}
__device__ __forceinline__ uint32_t ldg_relaxed32(const uint32_t* p) {
    uint32_t v; asm volatile("ld.relaxed.gpu.global.b32 %0, [%1];" : "=r"(v) : "l"(p) : "memory"); return v;
}
__device__ __forceinline__ unsigned int ld_acquire(const unsigned int* p) {
    unsigned int v; asm volatile("ld.acquire.gpu.global.u32 %0, [%1];" : "=r"(v) : "l"(p) : "memory"); return v;
}
__device__ __forceinline__ void red_release(unsigned int* p, unsigned int v) {
    asm volatile("red.release.gpu.global.add.u32 [%0], %1;" :: "l"(p), "r"(v) : "memory");
}
__device__ __forceinline__ void wait_flag(int idx, unsigned int target) {
    const unsigned int* p = &g_flags[idx];
    int g = 0;
#pragma unroll 1
    while (ld_acquire(p) < target) { __nanosleep(FLAG_NS); if (++g >= 64 * SPIN_LIMIT) { TIMEOUT(2, idx); break; } }
}
__device__ __forceinline__ void cp_async16(uint32_t dst, const void* src) {
    asm volatile("cp.async.cg.shared.global [%0], [%1], 16;" :: "r"(dst), "l"(src) : "memory");
}
__device__ __forceinline__ void cp_async_commit() { asm volatile("cp.async.commit_group;" ::: "memory"); }
template <int N> __device__ __forceinline__ void cp_async_wait() { asm volatile("cp.async.wait_group %0;" :: "n"(N) : "memory"); }
__device__ __forceinline__ void ldsm4(uint32_t& r0, uint32_t& r1, uint32_t& r2, uint32_t& r3, uint32_t addr) {
    asm volatile("ldmatrix.sync.aligned.m8n8.x4.shared.b16 {%0,%1,%2,%3}, [%4];" : "=r"(r0), "=r"(r1), "=r"(r2), "=r"(r3) : "r"(addr) : "memory");
}
__device__ __forceinline__ void ldsm4t(uint32_t& r0, uint32_t& r1, uint32_t& r2, uint32_t& r3, uint32_t addr) {
    asm volatile("ldmatrix.sync.aligned.m8n8.x4.trans.shared.b16 {%0,%1,%2,%3}, [%4];" : "=r"(r0), "=r"(r1), "=r"(r2), "=r"(r3) : "r"(addr) : "memory");
}
__device__ __forceinline__ void ldsm2t(uint32_t& r0, uint32_t& r1, uint32_t addr) {
    asm volatile("ldmatrix.sync.aligned.m8n8.x2.trans.shared.b16 {%0,%1}, [%2];" : "=r"(r0), "=r"(r1) : "r"(addr) : "memory");
}
__device__ __forceinline__ void stsm4(uint32_t addr, uint32_t r0, uint32_t r1, uint32_t r2, uint32_t r3) {
    asm volatile("stmatrix.sync.aligned.m8n8.x4.shared.b16 [%0], {%1,%2,%3,%4};" :: "r"(addr), "r"(r0), "r"(r1), "r"(r2), "r"(r3) : "memory");
}
__device__ __forceinline__ void stsm4t(uint32_t addr, uint32_t r0, uint32_t r1, uint32_t r2, uint32_t r3) {
    asm volatile("stmatrix.sync.aligned.m8n8.x4.trans.shared.b16 [%0], {%1,%2,%3,%4};" :: "r"(addr), "r"(r0), "r"(r1), "r"(r2), "r"(r3) : "memory");
}
__device__ __forceinline__ void stsm2t(uint32_t addr, uint32_t r0, uint32_t r1) {
    asm volatile("stmatrix.sync.aligned.m8n8.x2.trans.shared.b16 [%0], {%1,%2};" :: "r"(addr), "r"(r0), "r"(r1) : "memory");
}
__device__ __forceinline__ void mma16816(float* d, uint32_t a0, uint32_t a1, uint32_t a2, uint32_t a3, uint32_t b0, uint32_t b1) {
    asm volatile("mma.sync.aligned.m16n8k16.row.col.f32.bf16.bf16.f32 {%0,%1,%2,%3}, {%4,%5,%6,%7}, {%8,%9}, {%0,%1,%2,%3};"
                 : "+f"(d[0]), "+f"(d[1]), "+f"(d[2]), "+f"(d[3]) : "r"(a0), "r"(a1), "r"(a2), "r"(a3), "r"(b0), "r"(b1));
}
__device__ __forceinline__ void mma1688(float* d, uint32_t a0, uint32_t a1, uint32_t b0) {
    asm volatile("mma.sync.aligned.m16n8k8.row.col.f32.bf16.bf16.f32 {%0,%1,%2,%3}, {%4,%5}, {%6}, {%0,%1,%2,%3};"
                 : "+f"(d[0]), "+f"(d[1]), "+f"(d[2]), "+f"(d[3]) : "r"(a0), "r"(a1), "r"(b0));
}
__device__ __forceinline__ void mma16816h(float* d, uint32_t a0, uint32_t a2, uint32_t b0, uint32_t b1) {
    asm volatile("{\n.reg .b32 ju, jv;\nmma.sync.aligned.m16n8k16.row.col.f32.bf16.bf16.f32 {%0,%1,%2,%3}, {%4,ju,%5,jv}, {%6,%7}, {%0,%1,%2,%3};\n}"
                 : "+f"(d[0]), "+f"(d[1]), "+f"(d[2]), "+f"(d[3]) : "r"(a0), "r"(a2), "r"(b0), "r"(b1));
}
__device__ __forceinline__ void mma1688h(float* d, uint32_t a0, uint32_t b0) {
    asm volatile("{\n.reg .b32 ju;\nmma.sync.aligned.m16n8k8.row.col.f32.bf16.bf16.f32 {%0,%1,%2,%3}, {%4,ju}, {%5}, {%0,%1,%2,%3};\n}"
                 : "+f"(d[0]), "+f"(d[1]), "+f"(d[2]), "+f"(d[3]) : "r"(a0), "r"(b0));
}
__device__ __forceinline__ uint32_t pack2(float lo, float hi) {
    uint32_t r; asm("cvt.rn.bf16x2.f32 %0, %1, %2;" : "=r"(r) : "f"(hi), "f"(lo)); return r;
}
__device__ __forceinline__ float bflo(uint32_t w) { return __uint_as_float(w << 16); }
__device__ __forceinline__ float bfhi(uint32_t w) { return __uint_as_float(w & 0xffff0000u); }
__device__ __forceinline__ float rbf(float x) { return __bfloat162float(__float2bfloat16_rn(x)); }
__device__ __forceinline__ float ex2(float x) { float y; asm("ex2.approx.ftz.f32 %0, %1;" : "=f"(y) : "f"(x)); return y; }
__device__ __forceinline__ void sts128(uint32_t addr, uint4 v) {
    asm volatile("st.shared.v4.b32 [%0], {%1,%2,%3,%4};" :: "r"(addr), "r"(v.x), "r"(v.y), "r"(v.z), "r"(v.w) : "memory");
}
__device__ __forceinline__ uint4 lds128(uint32_t addr) {
    uint4 v; asm volatile("ld.shared.v4.b32 {%0,%1,%2,%3}, [%4];" : "=r"(v.x), "=r"(v.y), "=r"(v.z), "=r"(v.w) : "r"(addr) : "memory"); return v;
}
__device__ __forceinline__ float2 lds64f(uint32_t addr) {
    float2 v; asm volatile("ld.shared.v2.f32 {%0,%1}, [%2];" : "=f"(v.x), "=f"(v.y) : "r"(addr) : "memory"); return v;
}
__device__ __forceinline__ float lds32f(uint32_t addr) {
    float v; asm volatile("ld.shared.f32 %0, [%1];" : "=f"(v) : "r"(addr) : "memory"); return v;
}
__device__ __forceinline__ uint32_t lds32(uint32_t addr) {
    uint32_t v; asm volatile("ld.shared.b32 %0, [%1];" : "=r"(v) : "r"(addr) : "memory"); return v;
}
__device__ __forceinline__ void sts32(uint32_t addr, uint32_t v) { asm volatile("st.shared.b32 [%0], %1;" :: "r"(addr), "r"(v) : "memory"); }
__device__ __forceinline__ void sts64f(uint32_t addr, float a, float b) { asm volatile("st.shared.v2.f32 [%0], {%1,%2};" :: "r"(addr), "f"(a), "f"(b) : "memory"); }

__device__ __forceinline__ void tma_load2d(uint32_t dst, const CUtensorMap* tm, int c0, int c1, uint32_t bar) {
    asm volatile("cp.async.bulk.tensor.2d.shared::cluster.global.mbarrier::complete_tx::bytes [%0], [%1, {%3, %4}], [%2];"
                 :: "r"(dst), "l"(tm), "r"(bar), "r"(c0), "r"(c1) : "memory");
}
__device__ __forceinline__ void tma_store2d(const CUtensorMap* tm, uint32_t src, int c0, int c1) {
    asm volatile("cp.async.bulk.tensor.2d.global.shared::cta.bulk_group [%0, {%2, %3}], [%1];"
                 :: "l"(tm), "r"(src), "r"(c0), "r"(c1) : "memory");
}
__device__ __forceinline__ void bulk_commit() { asm volatile("cp.async.bulk.commit_group;" ::: "memory"); }
__device__ __forceinline__ void bulk_wait0() { asm volatile("cp.async.bulk.wait_group 0;" ::: "memory"); }
__device__ __forceinline__ void fence_async_smem() { asm volatile("fence.proxy.async.shared::cta;" ::: "memory"); }
__device__ __forceinline__ void fence_async_all() { asm volatile("fence.proxy.async;" ::: "memory"); }

__device__ __forceinline__ void wg_fence() { asm volatile("wgmma.fence.sync.aligned;" ::: "memory"); }
__device__ __forceinline__ void wg_commit() { asm volatile("wgmma.commit_group.sync.aligned;" ::: "memory"); }
__device__ __forceinline__ void wg_wait0() { asm volatile("wgmma.wait_group.sync.aligned 0;" ::: "memory"); }
__device__ __forceinline__ uint64_t mkdesc(uint32_t saddr, uint32_t lbo, uint32_t sbo) {
    return (uint64_t)((saddr & 0x3FFFF) >> 4) | ((uint64_t)(lbo >> 4) << 16) | ((uint64_t)(sbo >> 4) << 32) | (1ull << 62);
}
#define ACC8(i) "+f"(d[i]), "+f"(d[i + 1]), "+f"(d[i + 2]), "+f"(d[i + 3]), "+f"(d[i + 4]), "+f"(d[i + 5]), "+f"(d[i + 6]), "+f"(d[i + 7])
__device__ __forceinline__ void wgmma_n256(float* d, uint64_t da, uint64_t db, int scale_d) {
    asm volatile(
        "{\n.reg .pred p;\nsetp.ne.b32 p, %130, 0;\n"
        "wgmma.mma_async.sync.aligned.m64n256k16.f32.bf16.bf16 "
        "{%0,%1,%2,%3,%4,%5,%6,%7,%8,%9,%10,%11,%12,%13,%14,%15,%16,%17,%18,%19,%20,%21,%22,%23,%24,%25,%26,%27,%28,%29,%30,%31,"
        "%32,%33,%34,%35,%36,%37,%38,%39,%40,%41,%42,%43,%44,%45,%46,%47,%48,%49,%50,%51,%52,%53,%54,%55,%56,%57,%58,%59,%60,%61,%62,%63,"
        "%64,%65,%66,%67,%68,%69,%70,%71,%72,%73,%74,%75,%76,%77,%78,%79,%80,%81,%82,%83,%84,%85,%86,%87,%88,%89,%90,%91,%92,%93,%94,%95,"
        "%96,%97,%98,%99,%100,%101,%102,%103,%104,%105,%106,%107,%108,%109,%110,%111,%112,%113,%114,%115,%116,%117,%118,%119,%120,%121,%122,%123,%124,%125,%126,%127}, "
        "%128, %129, p, 1, 1, 0, 1;\n}"
        : ACC8(0), ACC8(8), ACC8(16), ACC8(24), ACC8(32), ACC8(40), ACC8(48), ACC8(56),
          ACC8(64), ACC8(72), ACC8(80), ACC8(88), ACC8(96), ACC8(104), ACC8(112), ACC8(120)
        : "l"(da), "l"(db), "r"(scale_d));
}
__device__ __forceinline__ void wgmma_n128(float* d, uint64_t da, uint64_t db, int scale_d) {
    asm volatile(
        "{\n.reg .pred p;\nsetp.ne.b32 p, %66, 0;\n"
        "wgmma.mma_async.sync.aligned.m64n128k16.f32.bf16.bf16 "
        "{%0,%1,%2,%3,%4,%5,%6,%7,%8,%9,%10,%11,%12,%13,%14,%15,%16,%17,%18,%19,%20,%21,%22,%23,%24,%25,%26,%27,%28,%29,%30,%31,"
        "%32,%33,%34,%35,%36,%37,%38,%39,%40,%41,%42,%43,%44,%45,%46,%47,%48,%49,%50,%51,%52,%53,%54,%55,%56,%57,%58,%59,%60,%61,%62,%63}, "
        "%64, %65, p, 1, 1, 0, 1;\n}"
        : ACC8(0), ACC8(8), ACC8(16), ACC8(24), ACC8(32), ACC8(40), ACC8(48), ACC8(56)
        : "l"(da), "l"(db), "r"(scale_d));
}

__device__ __forceinline__ void wgmma_n64(float* d, uint64_t da, uint64_t db) {
    asm volatile(
        "wgmma.mma_async.sync.aligned.m64n64k16.f32.bf16.bf16 "
        "{%0,%1,%2,%3,%4,%5,%6,%7,%8,%9,%10,%11,%12,%13,%14,%15,%16,%17,%18,%19,%20,%21,%22,%23,%24,%25,%26,%27,%28,%29,%30,%31}, "
        "%32, %33, 1, 1, 1, 0, 1;"
        : ACC8(0), ACC8(8), ACC8(16), ACC8(24)
        : "l"(da), "l"(db));
}
__device__ __forceinline__ void wgmma_n8_ta(float* d, uint64_t da, uint64_t db, int scale_d) {
    asm volatile(
        "{\n.reg .pred p;\nsetp.ne.b32 p, %6, 0;\n"
        "wgmma.mma_async.sync.aligned.m64n8k16.f32.bf16.bf16 {%0,%1,%2,%3}, %4, %5, p, 1, 1, 1, 0;\n}"
        : "+f"(d[0]), "+f"(d[1]), "+f"(d[2]), "+f"(d[3]) : "l"(da), "l"(db), "r"(scale_d));
}

__device__ __forceinline__ uint32_t hadd2(uint32_t a, uint32_t b) { uint32_t r; asm("add.rn.bf16x2 %0, %1, %2;" : "=r"(r) : "r"(a), "r"(b)); return r; }
__device__ __forceinline__ uint32_t hsub2(uint32_t a, uint32_t b) { uint32_t r; asm("sub.rn.bf16x2 %0, %1, %2;" : "=r"(r) : "r"(a), "r"(b)); return r; }
__device__ __forceinline__ uint32_t hmul2(uint32_t a, uint32_t b) { uint32_t r; asm("mul.rn.bf16x2 %0, %1, %2;" : "=r"(r) : "r"(a), "r"(b)); return r; }
__device__ __forceinline__ void load_mod8(const bf16* m, int lane, uint32_t* v) {
    const uint4 a = __ldcg((const uint4*)m + lane), b = __ldcg((const uint4*)m + 32 + lane);
    v[0] = a.x; v[1] = a.y; v[2] = a.z; v[3] = a.w; v[4] = b.x; v[5] = b.y; v[6] = b.z; v[7] = b.w;
}
__device__ __forceinline__ void ln_stats(const uint32_t* x, uint32_t& mu2, float& rden) {
    float s = 0.f;
#pragma unroll
    for (int i = 0; i < 8; i++) s += bflo(x[i]) + bfhi(x[i]);
#pragma unroll
    for (int o = 16; o > 0; o >>= 1) s += __shfl_xor_sync(~0u, s, o);
    const float mean = s * (1.f / D_);
    float q = 0.f;
#pragma unroll
    for (int i = 0; i < 8; i++) { const float d0 = bflo(x[i]) - mean, d1 = bfhi(x[i]) - mean; q = fmaf(d0, d0, q); q = fmaf(d1, d1, q); }
#pragma unroll
    for (int o = 16; o > 0; o >>= 1) q += __shfl_xor_sync(~0u, q, o);
    mu2 = pack2(mean, mean);
    rden = __frcp_rn(rbf(__fsqrt_rn(rbf(rbf(q * (1.f / D_)) + 1e-5f))));
}
__device__ __forceinline__ void ln_apply(const uint32_t* x, uint32_t mu2, float rden, const uint32_t* c1, const uint32_t* sm, uint32_t* r) {
#pragma unroll
    for (int i = 0; i < 8; i++) {
        const uint32_t d = hsub2(x[i], mu2);
        r[i] = hadd2(hmul2(pack2(bflo(d) * rden, bfhi(d) * rden), c1[i]), sm[i]);
    }
}

struct __align__(64) Params {
    CUtensorMap tm_h, tm_kv, tm_kvm, tm_o, tm_op, tm_h2, tm_act, tm_x1, tm_out;
    CUtensorMap tm_wq, tm_wk, tm_wv, tm_wo, tm_wg, tm_wu, tm_wd;
    const bf16 *x, *c, *w_mod;
    int qmask;
};

constexpr int R_NST = 3;
constexpr uint32_t R_WV = 0, R_MEM = 65536, R_KX = 73728, R_VX = R_KX + R_NST * 4096,
                   R_KMS = R_VX + R_NST * 4096, R_VMS = R_KMS + 1024, R_QS = R_KMS + 5120,
                   R_OS = R_KMS + 8192, R_SX = R_OS + 1024, R_BAR = R_SX + 2560,
                   R_RS = 110592  , R_VP = R_RS + 8192  ,
                   R_STG = R_VP + 4096  , R_SMEM = R_STG + 98304;
static_assert((R_KMS & 4095) == 0, "smem");
static_assert(R_BAR + 64 <= R_RS, "smem");
constexpr uint32_t RB_SX = R_BAR, RB_Q = R_BAR + 8, RB_E = R_BAR + 16, RB_A = R_BAR + 24, RB_ROLE = R_BAR + 32, RB_A1 = R_BAR + 40;
constexpr int W_NST = 4;
constexpr uint32_t W_STAGE = 49152, W_STG = W_NST * W_STAGE  , W_END = W_STG + 32768;
constexpr uint32_t SM_BAR = W_END;
constexpr uint32_t SMEM_BYTES = W_END + 1024 + 2048;
constexpr uint32_t B_FULL = 0, B_EMPTY = 32, B_STGFREE = 64, B_REQ = 80, B_RSP = 88, B_NEXT = 96, B_RING = 128;
#define PICK_AHEAD 3

constexpr int NB_X = 11  , NB_Y = 1, NB_M = 5, NB_K = 5, NB_B = 2, NB_C = 3, NB_D = 4, NB_W0 = 6  , NB_ST = 9  ;

__device__ __forceinline__ int pos_of_d(int d) {
    const int rem = d & 31;
    return (d & ~31) + ((rem & 7) >> 1) * 8 + (rem & 1) * 4 + (rem >> 3);
}

#define PROF(i) do {} while (0)
#define PROFG(i) do {} while (0)
#define OPAQUE(x) asm volatile("" : "+r"(x))
#define FENCE_SCHED(x) do { if ((x) == 0u) asm volatile("trap;"); } while (0)
#define QKVAR 2
#define VK0_ 4
constexpr int VK0 = VK0_;
constexpr int NOFF = 8;
#define VDELAY -1
#define POLL_GAP 110

struct RecParams { const bf16 *mem0, *wq, *wk, *wv, *wo, *x, *c, *w_mod; int ncl, only_pre; };

__device__ __forceinline__ void rec_qk(const RecParams& p, const uint32_t sb, const int cta, const int warp, int lane, const int sel) {
    const int crank = cta & 15, cl = cta >> 4, rank = cta & 1;
    const int kh = warp >> 2, aa = warp & 3;
    uint32_t wa[2][16][4];
    const uint32_t stg = sb + R_STG + kh * 32768;
    {
        const int t128 = aa * 32 + lane;
        const int row = (lane >> 4) * 8 + (lane & 7);
        const int ch = t128 & 7;
        const size_t goff = (size_t)kh * 256 * HD_ + cta * 64 + ch * 8;
#pragma unroll 4
        for (int dd = 0; dd < 16; dd++) {
            const int d = dd * 16 + (t128 >> 3), pp = pos_of_d(d);
            cp_async16(sb + R_WV + kh * 32768 + pp * 128 + ((ch ^ (pp & 7)) << 4), p.wv + goff + (size_t)d * HD_);
        }
        cp_async_commit();
#pragma unroll 4
        for (int dd = 0; dd < 16; dd++) {
            const int d = dd * 16 + (t128 >> 3), pp = pos_of_d(d);
            cp_async16(stg + pp * 128 + ((ch ^ (pp & 7)) << 4), p.wq + goff + (size_t)d * HD_);
        }
        cp_async_commit();
        {
            const int i0 = (warp * 32 + lane) * 16, tok = i0 >> 9;
            const uint4 m0 = __ldg((const uint4*)(p.mem0 + i0)), m1 = __ldg((const uint4*)(p.mem0 + i0 + 8));
            const uint32_t mw[8] = {m0.x, m0.y, m0.z, m0.w, m1.x, m1.y, m1.z, m1.w};
#pragma unroll
            for (int e = 0; e < 16; e++) {
                const int pp = pos_of_d((i0 & 511) + e);
                const unsigned short v = (unsigned short)(mw[e >> 1] >> ((e & 1) * 16));
                asm volatile("st.shared.u16 [%0], %1;" :: "r"(sb + R_MEM + (pp >> 3) * 128 + tok * 16 + (pp & 7) * 2), "h"(v) : "memory");
            }
        }
        cp_async_wait<1>();
        bar_sync(NB_W0 + kh, 128);
        const uint32_t fv = row * 128 + (((2 * aa + ((lane >> 3) & 1)) ^ (row & 7)) << 4);
#pragma unroll
        for (int ks = 0; ks < 16; ks++) ldsm4t(wa[0][ks][0], wa[0][ks][1], wa[0][ks][2], wa[0][ks][3], sb + R_WV + kh * 32768 + fv + ks * 2048);
        bar_sync(NB_W0 + kh, 128);
#pragma unroll
        for (int ks = 0; ks < 16; ks++)
            sts128(sb + R_WV + kh * 32768 + (aa * 16 + ks) * 512 + lane * 16, make_uint4(wa[0][ks][0], wa[0][ks][1], wa[0][ks][2], wa[0][ks][3]));
        const uint32_t fo = stg + row * 128 + (((4 * (aa & 1) + ((lane >> 3) & 1)) ^ (row & 7)) << 4);
#pragma unroll 1
        for (int m = 0; m < 2; m++) {
            cp_async_wait<0>();
            bar_sync(NB_W0 + kh, 128);
            if ((aa >> 1) == m) {
#pragma unroll
                for (int ks = 0; ks < 16; ks++) {
                    ldsm4t(wa[0][ks][0], wa[0][ks][1], wa[0][ks][2], wa[0][ks][3], fo + ks * 2048);
                    ldsm4t(wa[1][ks][0], wa[1][ks][1], wa[1][ks][2], wa[1][ks][3], (fo ^ 32) + ks * 2048);
                }
            }
            bar_sync(NB_W0 + kh, 128);
            if (m == 0) {
#pragma unroll 4
                for (int dd = 0; dd < 16; dd++) {
                    const int d = dd * 16 + (t128 >> 3), pp = pos_of_d(d);
                    cp_async16(stg + pp * 128 + ((ch ^ (pp & 7)) << 4), p.wk + goff + (size_t)d * HD_);
                }
                cp_async_commit();
            }
        }
    }
    const uint32_t tab = stg + (aa * 32 + lane) * 16;
    {
        const uint32_t l7 = lane & 7, l8 = lane >> 3, g = lane >> 2, t = lane & 3;
        const uint32_t t0 = l7 * 128 + ((l8 ^ l7) << 4);
        const uint32_t bq = warp >> 1, tp = warp & 1;
        uint4 v;
        v.x = sb + (aa < 2 ? R_QS + kh * 2048 : R_KMS + kh * 4096) + l7 * 128 + (((4 * (aa & 1) + l8) ^ l7) << 4);
        v.y = sb + R_QS + t0;
        v.z = sb + (warp == 0 ? R_KMS : R_KX + (warp - 1) * 1024) + t0;
        v.w = mapa_u32(sb + R_SX + (rank * 5 + warp) * 256 + lane * 8, crank ^ 1);
        sts128(tab, v);
        sts128(tab + 2048, make_uint4(sb + lane * 16 + R_MEM + kh * 4096, sb + lane * 16 + R_WV + warp * 8192,
                                      sb + lane * 16 + R_VP + warp * 512, 0));
        const uint32_t src = (l8 >> 1) * 8 + l7;
        const uint32_t L = bq * 8 + 2 * tp + (l8 & 1);
        const uint32_t d0 = (crank + ((t >> 1) | (g & 6))) & 15;
        v.x = sb + R_RS + src * 512 + ((L ^ (src & 7)) << 4);
        v.y = mapa_u32(sb + R_MEM + (crank * 4 + bq) * 128 + (4 * tp + 2 * (t & 1) + (g & 1)) * 16, d0);
        v.z = mapa_u32(sb + ((crank & 2) ? RB_A1 : RB_A), d0);
        v.w = lane;
        sts128(tab + 4096, v);
        const uint64_t wr = (uint64_t)(g_F + ((crank * 2 + ((crank ^ (crank >> 3) ^ sel) & 1)) * 1024 + warp * 128 + cl * 32 + lane));
        sts128(tab + 6144, make_uint4((uint32_t)wr, (uint32_t)(wr >> 32), (uint32_t)((((cl + 1) & 3) - cl) * 128), (uint32_t)((((cl + 2) & 3) - cl) * 128)));
        sts32(tab + 8192, (uint32_t)((((cl + 3) & 3) - cl) * 128));
#pragma unroll
        for (int i = 0; i < NOFF; i++)
            sts128(tab + 10240 + i * 2048, make_uint4(wa[i & 1][i >> 1][0], wa[i & 1][i >> 1][1], wa[i & 1][i >> 1][2], wa[i & 1][i >> 1][3]));
    }
    bar_sync(NB_D, 384);
    uint32_t slot_off = 0;
    const uint32_t slot_inc = warp == 0 ? 2048 : 4096, slot_last = warp == 0 ? 2048 : (R_NST - 1) * 4096;
    const uint32_t sx_bar_rem = (sb + RB_SX) ^ (1u << 24);
    uint4 tb = lds128(tab + 2048);
#pragma unroll 1
    for (int s = 0; s < NSEG; s++) {
        if (s > 0) mbar_wait(sb + RB_A, (s - 1) & 1);
        if (warp == 0) { PROF(0); PROFG(13); }
        uint4 ta;
        const uint32_t km_tog = aa >= 2 ? (s & 1) * 2048 : 0;
        {
            float acc[5][4];
#pragma unroll
            for (int c = 0; c < 5; c++) { acc[c][0] = acc[c][1] = acc[c][2] = acc[c][3] = 0.f; }
            uint32_t b[8][4];
            uint4 av[16];
            static_assert(VK0 == 4, "order below assumes the V/O warps cover slices 0,1");
#define QK4(k2) do { \
                mma16816(acc[0], wa[0][2 * (k2)][0], wa[0][2 * (k2)][1], wa[0][2 * (k2)][2], wa[0][2 * (k2)][3], b[k2][0], b[k2][1]); \
                mma16816(acc[1], wa[1][2 * (k2)][0], wa[1][2 * (k2)][1], wa[1][2 * (k2)][2], wa[1][2 * (k2)][3], b[k2][0], b[k2][1]); \
                mma16816(acc[3], wa[0][2 * (k2) + 1][0], wa[0][2 * (k2) + 1][1], wa[0][2 * (k2) + 1][2], wa[0][2 * (k2) + 1][3], b[k2][2], b[k2][3]); \
                mma16816(acc[4], wa[1][2 * (k2) + 1][0], wa[1][2 * (k2) + 1][1], wa[1][2 * (k2) + 1][2], wa[1][2 * (k2) + 1][3], b[k2][2], b[k2][3]); } while (0)
#define V2(k2) do { \
                mma16816(acc[2], av[2 * (k2)].x, av[2 * (k2)].y, av[2 * (k2)].z, av[2 * (k2)].w, b[k2][0], b[k2][1]); \
                mma16816(acv, av[2 * (k2) + 1].x, av[2 * (k2) + 1].y, av[2 * (k2) + 1].z, av[2 * (k2) + 1].w, b[k2][2], b[k2][3]); } while (0)
#define LB(k2) ldsm4(b[k2][0], b[k2][1], b[k2][2], b[k2][3], tb.x + (k2) * 512)
#define LV(k2) do { av[2 * (k2)] = lds128(tb.y + 2 * (k2) * 512); av[2 * (k2) + 1] = lds128(tb.y + (2 * (k2) + 1) * 512); } while (0)
            float acv[4] = {0.f, 0.f, 0.f, 0.f};
            LB(0); LB(1); LB(4); LB(5);
            QK4(0); QK4(1); LV(4); LV(5); QK4(4); QK4(5);
            if (s > 0) mbar_wait(sb + RB_A1, (s - 1) & 1);
            LB(2); LB(3); LB(6); LB(7); ta = lds128(tab);
            V2(4); V2(5); LV(2); LV(3);
            QK4(2); QK4(3); QK4(6); QK4(7);
            LV(6); LV(7);
#pragma unroll
            for (int i = 0; i < 4; i++) { acc[0][i] += acc[3][i]; acc[1][i] += acc[4][i]; }
            stsm4t(ta.x ^ km_tog, pack2(acc[0][0], acc[0][1]), pack2(acc[0][2], acc[0][3]), pack2(acc[1][0], acc[1][1]), pack2(acc[1][2], acc[1][3]));
            if (warp == 0) PROF(1);
            __syncwarp();
            if (lane == 0) mbar_arrive(sb + RB_Q);
            V2(2); V2(3); V2(6); V2(7);
            sts128(tb.z, make_uint4(__float_as_uint(acc[2][0] + acv[0]), __float_as_uint(acc[2][1] + acv[1]), __float_as_uint(acc[2][2] + acv[2]), __float_as_uint(acc[2][3] + acv[3])));
        }
        const uint32_t kb = ta.z + slot_off;
        if (warp == 0) PROF(14);
        bar_arrive(NB_Y, 384);
        if (warp < 5) {
            mbar_wait(sb + RB_Q, s & 1);
            uint32_t q[8], q1[8], k[8];
            float sa[4] = {0.f, 0.f, 0.f, 0.f}, sc[4] = {0.f, 0.f, 0.f, 0.f};
            ldsm4(q[0], q[1], q[2], q[3], ta.y);
            ldsm4(q1[0], q1[1], q1[2], q1[3], ta.y + 2048);
            ldsm4(k[0], k[1], k[2], k[3], kb);
            ldsm4(q[4], q[5], q[6], q[7], ta.y ^ 64);
            ldsm4(q1[4], q1[5], q1[6], q1[7], (ta.y ^ 64) + 2048);
            ldsm4(k[4], k[5], k[6], k[7], kb ^ 64);
            if (warp == 0) {
                uint32_t k1[8];
                ldsm4(k1[0], k1[1], k1[2], k1[3], kb + 4096);
                ldsm4(k1[4], k1[5], k1[6], k1[7], (kb ^ 64) + 4096);
#pragma unroll
                for (int i = 0; i < 8; i++) k[i] = hadd2(k[i], k1[i]);
            }
#pragma unroll
            for (int i = 0; i < 8; i++) q[i] = hadd2(q[i], q1[i]);
            bar_arrive(NB_X, 288);
            mma16816h(sa, q[0], q[1], k[0], k[1]);
            mma16816h(sc, q[2], q[3], k[2], k[3]);
            mma16816h(sa, q[4], q[5], k[4], k[5]);
            mma16816h(sc, q[6], q[7], k[6], k[7]);
            const float scl = 0.08838834764831845f * 1.4426950408889634f;
            const float r0 = (sa[0] + sc[0]) * scl, r1 = (sa[1] + sc[1]) * scl;
            if (s != NSEG - 1) {
                st_async_v2(ta.w, r0, r1, sx_bar_rem);
                st_async_v2(ta.w ^ (1u << 24), r0, r1, sx_bar_rem ^ (1u << 24));
            }
            if (warp == 0) PROF(2);
        } else if (s > 0 && warp == 7 && lane == 0) {
            mbar_expect_tx(sb + RB_A, 4096);
            mbar_expect_tx(sb + RB_A1, 4096);
        } else if (s > 0 && (s & 3) == 0 && warp == 6) {
            bar_sync(NB_K, 160);
            if (lane == 0) red_release(&g_flags[F_MEM + (s >> 2) - 1], 1);
            __syncwarp();
        }
        if (s == NSEG - 1) {
            const uint4 td = lds128(tab + 6144);
            stg_relaxed32((uint32_t*)(((uint64_t)td.y << 32) | (td.x ^ 0x21000)), 0u);
            break;
        }
        slot_off = slot_off == slot_last ? 0 : slot_off + slot_inc;
        const uint4 tc = lds128(tab + 4096), td = lds128(tab + 6144);
        const uint32_t te = lds32(tab + 8192);
        uint32_t* wr = (uint32_t*)(((uint64_t)td.y << 32) | (td.x ^ ((s & 1) * 0x21000)));
        const uint32_t* r1p = (const uint32_t*)((const char*)wr + (int)td.z);
        const uint32_t* r2p = (const uint32_t*)((const char*)wr + (int)td.w);
        const uint32_t* r3p = (const uint32_t*)((const char*)wr + (int)te);
        const uint32_t tag = ((s >> 1) + 1) & 1;
        mbar_wait(sb + RB_E, s & 1);
        if (warp == 0) PROF(7);
        {
            uint32_t a0, a1, a2, a3, a4, a5, a6, a7;
            ldsm4t(a0, a1, a2, a3, tc.x);
            ldsm4t(a4, a5, a6, a7, tc.x ^ 64);
            const uint32_t one = 0x3F803F80u;
            float d0_[4] = {0.f, 0.f, 0.f, 0.f}, d1_[4] = {0.f, 0.f, 0.f, 0.f};
            mma16816(d0_, a0, a1, a2, a3, one, one);
            mma16816(d1_, a4, a5, a6, a7, one, one);
            const bool t1 = tc.w & 1, t2 = tc.w & 2;
            const float x = t2 ? (t1 ? d1_[2] : d1_[0]) : (t1 ? d0_[2] : d0_[0]);
            const uint32_t own = (__float_as_uint(x) & ~1u) | tag;
            stg_relaxed32(wr, own);
            const uint32_t tq = clk32();
            if (warp == 0) PROF(8);
            PROFG(16 + warp);
            while ((int)(clk32() - tq) < POLL_GAP) {}
            uint32_t f1 = ldg_relaxed32(r1p), f2 = ldg_relaxed32(r2p), f3 = ldg_relaxed32(r3p);
#pragma unroll
            for (int i = 0; i < NOFF; i++) {
                const uint4 f0 = lds128(tab + 10240 + i * 2048);
                wa[i & 1][i >> 1][0] = f0.x; wa[i & 1][i >> 1][1] = f0.y; wa[i & 1][i >> 1][2] = f0.z; wa[i & 1][i >> 1][3] = f0.w;
            }
            tb = lds128(tab + 2048);
            int gg = 0;
#pragma unroll 1
            while (!__all_sync(~0u, (((f1 ^ tag) | (f2 ^ tag) | (f3 ^ tag)) & 1) == 0)) {
                f1 = ldg_relaxed32(r1p); f2 = ldg_relaxed32(r2p); f3 = ldg_relaxed32(r3p);
                if (++gg > 16 * SPIN_LIMIT) { TIMEOUT(3, s); break; }
            }
            if (warp == 0) PROF(9);
            const float v = (__uint_as_float(own) + __uint_as_float(f2)) + (__uint_as_float(f1) + __uint_as_float(f3));
            const bool b8 = tc.w & 8, b16 = tc.w & 16;
            const float recv = __shfl_xor_sync(~0u, v, 8);
            const uint32_t word = b8 ? pack2(recv, v) : pack2(v, recv);
            const uint32_t oth = __shfl_xor_sync(~0u, word, 16);
            const uint32_t wl = b16 ? oth : word, wh = b16 ? word : oth;
            const uint32_t p0 = __shfl_xor_sync(~0u, wl, 2), p1 = __shfl_xor_sync(~0u, wh, 2);
            const uint4 item = t2 ? make_uint4(p0, p1, wl, wh) : make_uint4(wl, wh, p0, p1);
            st_async_v4(tc.y, item, tc.z);
            st_async_v4(tc.y ^ (8u << 24), item, tc.z ^ (8u << 24));
            if (tc.w == 0 && warp == 7) mbar_expect_tx(sb + RB_E, 8192);
            if (warp == 0) PROF(10);
            PROF(40 + warp);
        }
        bar_sync(NB_D, 384);
    }
}

__device__ __forceinline__ void rec_load_kv(uint32_t sb, int col0, int s, uint32_t slot_off, int t128) {
    const int row = t128 >> 2, c2 = (t128 & 3) * 2;
    const bf16* src = g_kv + ((size_t)(s * 32 + row) * (2 * HD_) + col0 + c2 * 8);
    const uint32_t d0 = sb + R_KX + slot_off + row * 128 + ((c2 ^ (row & 7)) << 4);
    cp_async16(d0, src);
    cp_async16(d0 ^ 16, src + 8);
    cp_async16(d0 + (R_VX - R_KX), src + HD_);
    cp_async16((d0 ^ 16) + (R_VX - R_KX), src + HD_ + 8);
}

__device__ __forceinline__ void rec_store_kvm(uint32_t sb, int col0, int s, int w, int lane) {
    const int tok = (w & 1) * 4 + (lane >> 3);
    const uint32_t a = sb + R_KMS + (s & 1) * 2048 + (w >> 1) * 1024 + tok * 128 + (((lane & 7) ^ tok) << 4);
    uint4 v = lds128(a);
    if (w < 2) {
        const uint4 k1 = lds128(a + 4096);
        v = make_uint4(hadd2(v.x, k1.x), hadd2(v.y, k1.y), hadd2(v.z, k1.z), hadd2(v.w, k1.w));
    }
    *(uint4*)(g_kvm + ((s * 8 + tok) * (2 * HD_) + (w >> 1) * HD_ + col0 + (lane & 7) * 8)) = v;
}

__device__ __forceinline__ void rec_vo(const RecParams& p, const uint32_t sb, const int cta, const int warp, int lane) {
    const int w = warp - 8, crank = cta & 15;
    const int col0 = cta * 64;
    uint32_t wo[8][4][4];
    {
        const int t128 = w * 32 + lane;
        const bf16* Wo = p.wo + (size_t)col0 * D_;
        const uint32_t stg = sb + R_STG + 2 * 32768;
#pragma unroll
        for (int half = 0; half < 2; half++) {
#pragma unroll 4
            for (int i = t128; i < 2048; i += 128) {
                const int e = i >> 6, ch = i & 63;
                cp_async16(stg + e * 1024 + ((ch ^ (e & 7)) << 4), Wo + (size_t)(half * 32 + e) * D_ + ch * 8);
            }
            cp_async_commit();
            cp_async_wait<0>();
            bar_sync(NB_W0 + 2, 128);
#pragma unroll
            for (int j = 0; j < 8; j++)
#pragma unroll
                for (int kk = 0; kk < 2; kk++) {
                    const int e = kk * 16 + (lane >> 4) * 8 + (lane & 7);
                    const int ch = (w * 8 + j) * 2 + ((lane >> 3) & 1);
                    ldsm4t(wo[j][half * 2 + kk][0], wo[j][half * 2 + kk][1], wo[j][half * 2 + kk][2], wo[j][half * 2 + kk][3],
                           stg + e * 1024 + ((ch ^ (e & 7)) << 4));
                }
            bar_sync(NB_W0 + 2, 128);
        }
        if (lane == 0) wait_flag(F_KV + 0, 64);
        __syncwarp();
        rec_load_kv(sb, col0, 0, 0, t128); cp_async_commit();
        rec_load_kv(sb, col0, 1, 4096, t128); cp_async_commit();
        cp_async_wait<1>();
    }
    const uint32_t tab = sb + R_STG + 2 * 32768 + (w * 32 + lane) * 16;
    {
        const uint32_t l7 = lane & 7, l8 = lane >> 3, g = lane >> 2;
        uint4 v;
        v.x = sb + R_VX + ((l8 & 1) * 8 + l7) * 128 + (((2 * w + (l8 >> 1)) ^ l7) << 4);
        v.y = sb + R_OS + g * 128 + (((2 * w) ^ g) << 4) + (lane & 3) * 4;
        v.z = sb + R_VMS + l7 * 128 + (((2 * w + (l8 & 1)) ^ l7) << 4);
        v.w = sb + R_OS + l7 * 128 + ((l8 ^ l7) << 4);
        sts128(tab, v);
        v.x = mapa_u32(sb + R_RS + crank * 512 + ((lane ^ (crank & 7)) << 4), w * 4);
        v.y = mapa_u32(sb + RB_E, w * 4);
        v.z = sb + R_VP + w * 512 + lane * 16;
        v.w = sb + R_SX + lane * 8;
        sts128(tab + 2048, v);
#pragma unroll
        for (int i = 0; i < 8; i++) sts128(tab + 4096 + i * 2048, make_uint4(wo[i][0][0], wo[i][0][1], wo[i][0][2], wo[i][0][3]));
        const int tok = (w & 1) * 4 + (lane >> 3), row = (w * 32 + lane) >> 2, c2 = (lane & 3) * 2;
        const uint64_t kd = (uint64_t)(g_kvm + (tok * (2 * HD_) + (w >> 1) * HD_ + col0 + (lane & 7) * 8));
        const uint64_t ks = (uint64_t)(g_kv + ((size_t)row * (2 * HD_) + col0 + c2 * 8));
        sts128(tab + 20480, make_uint4((uint32_t)kd, (uint32_t)(kd >> 32), (uint32_t)ks, (uint32_t)(ks >> 32)));
        sts128(tab + 22528, make_uint4(sb + R_KMS + (w >> 1) * 1024 + tok * 128 + (((lane & 7) ^ tok) << 4),
                                       sb + R_KX + row * 128 + ((c2 ^ (row & 7)) << 4), lane, 0));
    }
    bar_sync(NB_D, 384);
    const uint32_t lane16 = lds32(tab + 2048 + 8) - R_VP - w * 512;
    uint4 av[2 * VK0];
#pragma unroll
    for (int i = 0; i < 2 * VK0; i++) av[i] = lds128(lane16 + R_WV + (i / VK0) * 32768 + (w * 16 + i % VK0) * 512);
    uint32_t slot_off = 0;
#pragma unroll 1
    for (int s = 0; s < NSEG; s++) {
        if (s > 0) {
            mbar_wait(sb + RB_A, (s - 1) & 1);
            const uint4 tp = lds128(tab + 20480), tq = lds128(tab + 22528);
            uint4 kvm = lds128(tq.x + ((s - 1) & 1) * 2048);
            if (w < 2) {
                const uint4 k1 = lds128(tq.x + ((s - 1) & 1) * 2048 + 4096);
                kvm = make_uint4(hadd2(kvm.x, k1.x), hadd2(kvm.y, k1.y), hadd2(kvm.z, k1.z), hadd2(kvm.w, k1.w));
            }
            *(uint4*)((((uint64_t)tp.y << 32) | tp.x) + (uint64_t)(s - 1) * (8 * 2 * HD_ * 2)) = kvm;
            if ((s & 3) == 0) bar_arrive(NB_K, 160);
            if (s + 1 < NSEG - 1) {
                if (((s + 1) & 3) == 0) { if (tq.z == 0) wait_flag(F_KV + ((s + 1) >> 2), 64); __syncwarp(); }
                const char* src = (const char*)((((uint64_t)tp.w << 32) | tp.z) + (uint64_t)(s + 1) * (32 * 2 * HD_ * 2));
                const uint32_t d0 = tq.y + (slot_off == (R_NST - 1) * 4096 ? 0 : slot_off + 4096);
                cp_async16(d0, src);
                cp_async16(d0 ^ 16, src + 16);
                cp_async16(d0 + (R_VX - R_KX), src + HD_ * 2);
                cp_async16((d0 ^ 16) + (R_VX - R_KX), src + HD_ * 2 + 16);
            }
            cp_async_commit();
        }
        bar_sync(NB_Y, 384);
        bar_sync(NB_X, 288);
        uint32_t vb0, vb1;
        {
            float va[4] = {0.f, 0.f, 0.f, 0.f}, vc[4] = {0.f, 0.f, 0.f, 0.f};
            uint32_t bb[VK0][4];
#pragma unroll
            for (int k2 = 0; k2 < VK0; k2++) ldsm4(bb[k2][0], bb[k2][1], bb[k2][2], bb[k2][3], lane16 + R_MEM + (k2 / (VK0 / 2)) * 4096 + (k2 % (VK0 / 2)) * 512);
#pragma unroll
            for (int k2 = 0; k2 < VK0; k2++) {
                mma16816(va, av[2 * k2].x, av[2 * k2].y, av[2 * k2].z, av[2 * k2].w, bb[k2][0], bb[k2][1]);
                mma16816(vc, av[2 * k2 + 1].x, av[2 * k2 + 1].y, av[2 * k2 + 1].z, av[2 * k2 + 1].w, bb[k2][2], bb[k2][3]);
            }
            const uint4 a = lds128(lane16 + R_VP + w * 512), b = lds128(lane16 + R_VP + 2048 + w * 512);
            vb0 = pack2((va[0] + vc[0]) + (__uint_as_float(a.x) + __uint_as_float(b.x)), (va[1] + vc[1]) + (__uint_as_float(a.y) + __uint_as_float(b.y)));
            vb1 = pack2((va[2] + vc[2]) + (__uint_as_float(a.z) + __uint_as_float(b.z)), (va[3] + vc[3]) + (__uint_as_float(a.w) + __uint_as_float(b.w)));
        }
        const uint4 ta = lds128(tab), tb = lds128(tab + 2048);
        uint32_t vx[8];
        ldsm4t(vx[0], vx[1], vx[2], vx[3], ta.x + slot_off);
        ldsm4t(vx[4], vx[5], vx[6], vx[7], ta.x + slot_off + 2048);
#pragma unroll
        for (int i = 0; i < 4; i++) {
            const uint4 f0 = lds128(tab + 4096 + i * 2048);
            wo[i][0][0] = f0.x; wo[i][0][1] = f0.y; wo[i][0][2] = f0.z; wo[i][0][3] = f0.w;
        }
        if (w == 0) PROF(11);
        uint32_t pf[5];
        float oa[2][4] = {{0.f, 0.f, 0.f, 0.f}, {0.f, 0.f, 0.f, 0.f}}, ob_[2][4] = {{0.f, 0.f, 0.f, 0.f}, {0.f, 0.f, 0.f, 0.f}};
        float sm0[4] = {0.f, 0.f, 0.f, 0.f}, sm1[4] = {0.f, 0.f, 0.f, 0.f};
        if (s != NSEG - 1) {
            mbar_wait(sb + RB_SX, s & 1);
            if (w == 0) PROF(4);
            float sv[10];
#pragma unroll
            for (int n = 0; n < 5; n++) {
                const float2 a = lds64f(tb.w + n * 256), b = lds64f(tb.w + (5 + n) * 256);
                sv[2 * n] = a.x + b.x; sv[2 * n + 1] = a.y + b.y;
            }
            float mx = fmaxf(fmaxf(fmaxf(sv[0], sv[1]), fmaxf(sv[2], sv[3])), fmaxf(fmaxf(sv[4], sv[5]), fmaxf(sv[6], sv[7])));
            mx = fmaxf(mx, fmaxf(sv[8], sv[9]));
            mx = fmaxf(mx, __shfl_xor_sync(~0u, mx, 1));
            mx = fmaxf(mx, __shfl_xor_sync(~0u, mx, 2));
#pragma unroll
            for (int n = 1; n < 5; n++) pf[n] = pack2(ex2(sv[2 * n] - mx), ex2(sv[2 * n + 1] - mx));
            pf[0] = pack2(ex2(sv[0] - mx), ex2(sv[1] - mx));
            if (w == 0) PROF(12);
            const uint32_t one = 0x3F803F80u;
            mma16816h(sm0, pf[1], pf[2], one, one);
            mma16816h(oa[0], pf[1], pf[2], vx[0], vx[1]);
            mma16816h(oa[1], pf[1], pf[2], vx[2], vx[3]);
            mma16816h(sm1, pf[3], pf[4], one, one);
            mma16816h(ob_[0], pf[3], pf[4], vx[4], vx[5]);
            mma16816h(ob_[1], pf[3], pf[4], vx[6], vx[7]);
            mma1688h(sm0, pf[0], one);
            mma1688h(oa[0], pf[0], vb0);
            mma1688h(oa[1], pf[0], vb1);
            float inv;
            asm("rcp.approx.ftz.f32 %0, %1;" : "=f"(inv) : "f"(sm0[0] + sm1[0]));
            oa[0][0] += ob_[0][0]; oa[0][1] += ob_[0][1]; oa[1][0] += ob_[1][0]; oa[1][1] += ob_[1][1];
            sts32(ta.y, pack2(oa[0][0] * inv, oa[0][1] * inv));
            sts32(ta.y ^ 16, pack2(oa[1][0] * inv, oa[1][1] * inv));
            const uint32_t oa2 = ta.w ^ 64;
            bar_sync(NB_C, 128);
            if (w == 0) PROF(5);
            uint32_t ob[8];
            ldsm4(ob[0], ob[1], ob[2], ob[3], ta.w);
            ldsm4(ob[4], ob[5], ob[6], ob[7], oa2);
#pragma unroll
            for (int i = 4; i < 8; i++) {
                const uint4 f0 = lds128(tab + 4096 + i * 2048);
                wo[i][0][0] = f0.x; wo[i][0][1] = f0.y; wo[i][0][2] = f0.z; wo[i][0][3] = f0.w;
            }
#pragma unroll
            for (int jj = 0; jj < 2; jj++) {
                if (jj == 1 && tb.w == 0) break;
                float acc[4][4];
#pragma unroll
                for (int c = 0; c < 4; c++) { acc[c][0] = acc[c][1] = acc[c][2] = acc[c][3] = 0.f; }
#pragma unroll
                for (int ks = 0; ks < 4; ks++)
#pragma unroll
                    for (int c = 0; c < 4; c++)
                        mma16816(acc[c], wo[jj * 4 + c][ks][0], wo[jj * 4 + c][ks][1], wo[jj * 4 + c][ks][2], wo[jj * 4 + c][ks][3], ob[2 * ks], ob[2 * ks + 1]);
#pragma unroll
                for (int pr = 0; pr < 2; pr++) {
                    uint4 v;
                    v.x = pack2(acc[2 * pr][0], acc[2 * pr][1]);
                    v.y = pack2(acc[2 * pr][2], acc[2 * pr][3]);
                    v.z = pack2(acc[2 * pr + 1][0], acc[2 * pr + 1][1]);
                    v.w = pack2(acc[2 * pr + 1][2], acc[2 * pr + 1][3]);
                    st_async_v4(tb.x + ((jj * 2 + pr) << 24), v, tb.y + ((jj * 2 + pr) << 24));
                }
            }
            if (w == 0) PROF(6);
        }
        stsm2t(ta.z + (s & 1) * 2048, vb0, vb1);
        cp_async_wait<0>();
        bar_sync(NB_C, 128);
        if (w == 0 && lane == 0 && s != NSEG - 1) mbar_expect_tx(sb + RB_SX, 2560);
        if (s != NSEG - 1) bar_arrive(NB_D, 384);
#pragma unroll
        for (int i = 0; i < 2 * VK0; i++) av[i] = lds128(lane16 + R_WV + (i / VK0) * 32768 + (w * 16 + i % VK0) * 512);
        slot_off = slot_off == (R_NST - 1) * 4096 ? 0 : slot_off + 4096;
    }
    rec_store_kvm(sb, col0, NSEG - 1, w, lane);
    bar_sync(NB_C, 128);
    if (w == 0 && lane == 0) red_release(&g_flags[F_MEM + NRB - 1], 1);
}

__global__ void __launch_bounds__(384, 1) k_rec(const RecParams p) {
    extern __shared__ __align__(1024) unsigned char smem_raw[];
    const uint32_t sb = __shfl_sync(~0u, smem_u32(smem_raw), 0);
    const int warp = __shfl_sync(~0u, threadIdx.x >> 5, 0);
    int lane; asm volatile("mov.u32 %0, %%laneid;" : "=r"(lane));
    const int crank = blockIdx.x & 15, slot = blockIdx.x >> 4;
    asm volatile("griddepcontrol.launch_dependents;");
    if (crank == 0 && warp == 1 && lane < 4) {
        const unsigned int* q = lane < 2 ? &g_F[65536 + lane * 1024 + slot * 64] : &g_flags[F_SIDE + (lane - 2) * 32];
        asm volatile("prefetch.global.L2 [%0];" :: "l"(q));
    }
    if (threadIdx.x == 0) {
        mbar_init(sb + RB_SX, 1); mbar_init(sb + RB_Q, 8); mbar_init(sb + RB_E, 1); mbar_init(sb + RB_A, 1); mbar_init(sb + RB_A1, 1); mbar_init(sb + RB_ROLE, 1);
        asm volatile("fence.mbarrier_init.release.cluster;" ::: "memory");
        mbar_expect_tx(sb + RB_SX, 2560);
        mbar_expect_tx(sb + RB_E, 8192);
        mbar_expect_tx(sb + RB_A, 4096);
        mbar_expect_tx(sb + RB_A1, 4096);
        mbar_expect_tx(sb + RB_ROLE, 4);
    }
    asm volatile("barrier.cluster.arrive.relaxed.aligned;\nbarrier.cluster.wait.aligned;" ::: "memory");
    unsigned role = 0;
    if (crank == 0 && threadIdx.x == 0 && !p.only_pre) {
        unsigned x = 0;
        int tm[2] = {0x7fffffff, 0x7fffffff};
#pragma unroll 1
        for (int i = 0; i < 6; i++) {
            const uint32_t t0 = clk32();
            x = atomicAdd(&g_F[65536 + (i & 1) * 1024 + slot * 64 + (x >> 31)], 0u) & 0x7fffffffu;
            if (x == 0x7654321u) sts32(sb + R_BAR + 56, x);
            const int dt = (int)(clk32() - t0);
            if (i >= 2) { if (i & 1) tm[1] = min(tm[1], dt); else tm[0] = min(tm[0], dt); }
        }
        const int side = tm[1] > tm[0];
        const unsigned old = atomicAdd(&g_flags[F_SIDE + side * 32], 1u);
        unsigned c0, c1; int gd = 0;
#pragma unroll 1
        do { c0 = ldg_relaxed32(&g_flags[F_SIDE]); c1 = ldg_relaxed32(&g_flags[F_SIDE + 32]); } while ((int)(c0 + c1) < p.ncl && ++gd < 64 * SPIN_LIMIT);
        const int big = c1 > c0;
        role = side == big ? old : (big ? c1 : c0) + old;
        role |= (big ^ 1) << 8;
    }
    __syncwarp();
    if (crank == 0 && warp == 0 && !p.only_pre) {
        role = __shfl_sync(~0u, role, 0);
        if (lane < 16)
            asm volatile("st.async.weak.shared::cluster.mbarrier::complete_tx::bytes.u32 [%0], %1, [%2];"
                         :: "r"(mapa_u32(sb + R_BAR + 48, lane)), "r"(role), "r"(mapa_u32(sb + RB_ROLE, lane)) : "memory");
    }
    if (warp >= 4) {
        const int w8 = warp - 4, nblk = gridDim.x;
        const int cq = lane & 3, rg = w8 * 8 + (lane >> 2);
        const uint32_t red = sb + R_VP;
        const int row0 = blockIdx.x * 8 + w8;
        const uint4* xr = (const uint4*)(p.x + (size_t)row0 * D_);
        uint4 xa = __ldg(xr + lane), xb = __ldg(xr + 32 + lane);
#pragma unroll 1
        for (int sl = blockIdx.x; sl < 96; sl += nblk) {
            uint4 wv[8];
#pragma unroll
            for (int i = 0; i < 8; i++) wv[i] = __ldg((const uint4*)(p.w_mod + (size_t)(rg * 8 + i) * (6 * D_) + sl * 32 + cq * 8));
            const uint32_t cw = __ldg((const uint32_t*)(p.c + rg * 8) + cq);
            const float cl = bflo(cw), ch = bfhi(cw);
            const uint32_t sw = pack2(__fdividef(cl, 1.f + __expf(-cl)), __fdividef(ch, 1.f + __expf(-ch)));
            float a[8];
#pragma unroll
            for (int i = 0; i < 8; i++) a[i] = 0.f;
#pragma unroll
            for (int i = 0; i < 8; i++) {
                const uint32_t sv = __shfl_sync(~0u, sw, (lane & 28) + (i >> 1));
                const float cv = (i & 1) ? bfhi(sv) : bflo(sv);
                a[0] = fmaf(cv, bflo(wv[i].x), a[0]); a[1] = fmaf(cv, bfhi(wv[i].x), a[1]); a[2] = fmaf(cv, bflo(wv[i].y), a[2]); a[3] = fmaf(cv, bfhi(wv[i].y), a[3]);
                a[4] = fmaf(cv, bflo(wv[i].z), a[4]); a[5] = fmaf(cv, bfhi(wv[i].z), a[5]); a[6] = fmaf(cv, bflo(wv[i].w), a[6]); a[7] = fmaf(cv, bfhi(wv[i].w), a[7]);
            }
#pragma unroll
            for (int i = 0; i < 8; i++) { a[i] += __shfl_xor_sync(~0u, a[i], 4); a[i] += __shfl_xor_sync(~0u, a[i], 8); a[i] += __shfl_xor_sync(~0u, a[i], 16); }
            if (lane < 4) {
                sts128(red + w8 * 128 + lane * 32, make_uint4(__float_as_uint(a[0]), __float_as_uint(a[1]), __float_as_uint(a[2]), __float_as_uint(a[3])));
                sts128(red + w8 * 128 + lane * 32 + 16, make_uint4(__float_as_uint(a[4]), __float_as_uint(a[5]), __float_as_uint(a[6]), __float_as_uint(a[7])));
            }
            bar_sync(NB_B, 256);
            if (w8 == 0) {
                float v = 0.f;
#pragma unroll
                for (int i = 0; i < 8; i++) v += lds32f(red + i * 128 + lane * 4);
                g_mod[sl * 32 + lane] = __float2bfloat16_rn(v);
                __syncwarp();
                if (lane == 0) red_release(&g_flags[F_MOD + (sl >= 32)], 1);
            }
            bar_sync(NB_B, 256);
        }
        uint32_t c1[8], sm[8];
        int row = row0;
#pragma unroll 1
        while (true) {
            const uint32_t v[8] = {xa.x, xa.y, xa.z, xa.w, xb.x, xb.y, xb.z, xb.w};
            uint32_t mu2, r[8]; float rden;
            ln_stats(v, mu2, rden);
            if (row == row0) {
                if (lane == 0) wait_flag(F_MOD, 32);
                __syncwarp();
                load_mod8(g_mod + D_, lane, c1);
                load_mod8(g_mod, lane, sm);
#pragma unroll
                for (int i = 0; i < 8; i++) c1[i] = hadd2(c1[i], 0x3F803F80u);
            } else if (row + 512 < S_) {
                xr = (const uint4*)(p.x + (size_t)(row + 512) * D_); xa = __ldg(xr + lane); xb = __ldg(xr + 32 + lane);
            }
            ln_apply(v, mu2, rden, c1, sm, r);
            uint4* hr = (uint4*)(g_h + (size_t)row * D_);
            hr[lane] = make_uint4(r[0], r[1], r[2], r[3]); hr[32 + lane] = make_uint4(r[4], r[5], r[6], r[7]);
            bar_sync(NB_B, 256);
            if (w8 == (row >> 7 & 7) && lane == 0) red_release(&g_flags[F_H + (row >> 7)], 1);
            __syncwarp();
            if (row == row0) {
                if (!p.only_pre) mbar_wait(sb + RB_ROLE, 0);
                const int cl = p.only_pre ? slot : (int)(lds32(sb + R_BAR + 48) & 255);
                row = cl < 4 ? (nblk + cl * 16 + crank) * 8 + w8 : S_;
                if (row < S_) { xr = (const uint4*)(p.x + (size_t)row * D_); xa = __ldg(xr + lane); xb = __ldg(xr + 32 + lane); }
            } else {
                row += 512;
            }
            if (row >= S_) break;
        }
    }
    if (p.only_pre) return;
    mbar_wait(sb + RB_ROLE, 0);
    const int rolew = __shfl_sync(~0u, lds32(sb + R_BAR + 48), 0);
    const int cl = rolew & 255;
    if (cl >= 4) return;
    const int cta = cl * 16 + crank;
    if (warp < 8) rec_qk(p, sb, cta, warp, lane, rolew >> 8);
    else rec_vo(p, sb, cta, warp, lane);
}

enum { J_KV = 0, J_QA = 1, J_O = 2, J_LN = 3, J_UP = 4, J_DN = 5, J_LN1 = 6, J_MOD = 7, J_UP2 = 8, J_END = 9 };
constexpr int NJ_O = 2 * OSPLIT, NJ_O2 = 2 * OSPLIT2, NJ_LN = 8, NJ_LN2 = 16, NJ_UP = 14, NJ_UP2 = 28, NJ_DN = 8, NJ_LN1 = 8;
constexpr uint64_t pk8(int a, int b, int c, int d, int e, int f, int g, int h) {
    return (uint64_t)a | ((uint64_t)b << 8) | ((uint64_t)c << 16) | ((uint64_t)d << 24) | ((uint64_t)e << 32) | ((uint64_t)f << 40) | ((uint64_t)g << 48) | ((uint64_t)h << 56);
}
constexpr uint64_t NJ_C = pk8(32, 16, NJ_O, NJ_LN, NJ_UP, NJ_DN, 0, 0), NJ_F = pk8(32, 16, NJ_O2, NJ_LN2, NJ_UP2, NJ_DN, 0, 0);
constexpr uint64_t TG_C = pk8(2 * NJ_LN1, 64, 32, 2 * NJ_O, 2 * NJ_LN, 2 * NJ_UP, 32, 0), TG_F = pk8(2 * NJ_LN1, 64, 32, 2 * NJ_O2, 2 * NJ_LN2, 2 * NJ_UP2, 32, 0);
constexpr uint64_t NJ_L = pk8(32, 32, 2 * OSPLIT3, NJ_LN2, NJ_UP2, 2 * NJ_DN, 0, 0), TG_L = pk8(2 * NJ_LN1, 64, 64, 4 * OSPLIT3, 2 * NJ_LN2, 2 * NJ_UP2, 32, 0);
__device__ __forceinline__ uint64_t nj_tab(int rb) { return rb < FINE_RB ? NJ_C : (rb < NRB - 1 ? NJ_F : NJ_L); }
__device__ __forceinline__ uint64_t tg_tab(int rb) { return rb < FINE_RB ? TG_C : (rb < NRB - 1 ? TG_F : TG_L); }
__device__ __forceinline__ int o_nk(int rb) { return rb < FINE_RB ? 64 / OSPLIT : (rb < NRB - 1 ? 64 / OSPLIT2 : 64 / OSPLIT3); }
constexpr uint64_t PRIO = pk8(4, 10, 9, 8, 7, 6, 3, 0);
__device__ __forceinline__ int pick_job(int lane, int qmask, int& idx) {
    const int rb = lane & 15, half = lane >> 4;
    const uint64_t nj = nj_tab(rb) >> (8 * half);
    const uint64_t tg = tg_tab(rb) >> (8 * half);
    const unsigned* cp = &g_flags[F_CLAIM + half * 32 + rb];
    const unsigned* dp = &g_flags[half * 32 + rb];
    int gd = 0;
#pragma unroll 1
    while (true) {
        const unsigned c0 = ldg_relaxed32(cp), c1 = ldg_relaxed32(cp + 64), c2 = ldg_relaxed32(cp + 128);
        const unsigned d0 = ldg_relaxed32(dp - (half && rb ? 1 : 0)), d1 = ldg_relaxed32(dp + 64), d2 = ldg_relaxed32(dp + 128);
        const unsigned cl[3] = {c0, c1, c2}, dv[3] = {d0, d1, d2};
        unsigned key = 0xffffu, key2 = 0xffffu;
        bool pre = false;
#pragma unroll
        for (int i = 0; i < 3; i++) {
            const int q = half + 2 * i;
            const bool have = ((qmask >> q) & 1) && cl[i] < (unsigned)((nj >> (16 * i)) & 255);
            bool ready = have && dv[i] >= (unsigned)((tg >> (16 * i)) & 255);
            unsigned pr = (unsigned)((PRIO >> (8 * q)) & 255);
            if (i == 0 && rb <= 1 - half) ready = have;
            if (i == 0 && half && rb >= FINE_RB) pr = 5;
            if (ready) key = min(key, (pr << 8) | (rb << 4) | q);
            if (have) key2 = min(key2, rb >= FINE_RB ? (0x100u | (q << 4) | rb) : (i == 0 ? 0u : 0x1000u));
            pre |= have && i == 0 && !half;
        }
        const bool anypre = __any_sync(~0u, pre);
        if (anypre && (key & 15) == J_QA) key = 0xffffu;
        key = __reduce_min_sync(~0u, key);
        key2 = __reduce_min_sync(~0u, key2);
        if (key2 == 0xffffu) return J_END;
        int pq, prb;
        if (key != 0xffffu) { pq = key & 15; prb = (key >> 4) & 15; }
        else if (key2 >= 0x120u && key2 < 0x1000u) { pq = (key2 >> 4) & 15; prb = key2 & 15; }
        else {
            __nanosleep(IDLE_NS);
            if (++gd > 16 * SPIN_LIMIT) { TIMEOUT(5, 0); return J_END; }
            continue;
        }
        int c = 0;
        if (lane == 0) c = (int)atomicAdd(&g_flags[F_CLAIM + pq * 32 + prb], 1u);
        c = __shfl_sync(~0u, c, 0);
        if (c < (int)((nj_tab(prb) >> (8 * pq)) & 255)) {
            idx = pq * 512 + prb * 32 + c;
            int acq = 0;
            if (pq != J_QA && pq < J_LN1) {
                if (lane == 0 && ld_acquire(&g_flags[pq * 32 + prb]) >= (unsigned)((tg_tab(prb) >> (8 * pq)) & 255)) {
                    asm volatile("fence.proxy.async.global;" ::: "memory");
                    acq = 1 << 24;
                }
            }
            return (pq == J_UP && prb >= FINE_RB ? J_UP2 : pq) | (prb << 8) | (c << 16) | acq;
        }
    }
}
__device__ __forceinline__ int op_row(int rb, int split) {
    return rb < FINE_RB ? split * S_ + rb * 128
                        : (rb < NRB - 1 ? OSPLIT * S_ + (split * (NRB - FINE_RB) + rb - FINE_RB) * 128 : OSPLIT * S_ + (OSPLIT2 * (NRB - FINE_RB) + split) * 128);
}

struct Pipe { uint32_t stage, phase; };
__device__ __forceinline__ void pipe_next(Pipe& p) { if (++p.stage == W_NST) { p.stage = 0; p.phase ^= 1; } }

__device__ __forceinline__ void scheduler(const Params& p, uint32_t sb, int lane) {
    const uint32_t bars = sb + SM_BAR;
    uint32_t ph = 0;
#pragma unroll 1
    while (true) {
        mbar_wait(bars + B_REQ, ph);
        int j = 4095;
        const int jd = pick_job(lane, p.qmask, j);
        if (lane == 0) { sts32(bars + B_NEXT, (uint32_t)jd); sts32(bars + B_NEXT + 4, (uint32_t)j); mbar_arrive(bars + B_RSP); }
        ph ^= 1;
        if (jd == J_END) break;
        __syncwarp();
    }
}

__device__ __forceinline__ void producer(const Params& p, uint32_t sb) {
    Pipe pp{0, 1};
    const uint32_t bars = sb + SM_BAR;
    uint32_t seq = 0, h_seen = 0;
    mbar_arrive(bars + B_REQ);
#pragma unroll 1
    while (true) {
        mbar_wait(bars + B_RSP, seq & 1);
        const int jd = (int)lds32(bars + B_NEXT), j = (int)lds32(bars + B_NEXT + 4);
        int left = (jd & 255) == J_DN ? 15 : ((jd & 255) == J_QA ? (((jd >> 8) & 255) == NRB - 1 ? 10 : 12) : ((jd & 255) == J_O ? o_nk((jd >> 8) & 255) : ((jd & 255) == J_LN || (jd & 255) == J_LN1 || (jd & 255) == J_MOD ? 1 : 8)));
        left = max(left - PICK_AHEAD, 1);
        TR(j, 1);
        const int type = jd & 255, rb = (jd >> 8) & 255, cb = (jd >> 16) & 255;
        const bool fine = rb >= FINE_RB, acquired = (jd >> 24) & 1;
        bool first = true;
        auto begin_stage = [&](uint32_t bytes) -> uint32_t {
            mbar_wait(bars + B_EMPTY + pp.stage * 8, pp.phase);
            if (first) { sts32(bars + B_RING + (seq & 7) * 4, (uint32_t)jd); sts32(bars + B_RING + 32 + (seq & 7) * 4, (uint32_t)j); first = false; }
            const uint32_t fb = bars + B_FULL + pp.stage * 8;
            if (bytes) mbar_expect_tx(fb, bytes); else mbar_arrive(fb);
            if (--left == 0 && type != J_END) mbar_arrive(bars + B_REQ);
            return fb;
        };
        if (type == J_END || type == J_LN || type == J_LN1 || type == J_MOD) {
            if (type == J_LN && !(h_seen >> 31)) { wait_flag(F_MOD + 1, 64); h_seen |= 1u << 31; }

            TR(j, 2);
            begin_stage(0); pipe_next(pp);
            seq++;
            if (type == J_END) break;
            continue;
        }
        const CUtensorMap *ta, *tb0, *tb1;
        int k0 = 0, nk = 8, n0 = cb * 256, n1 = n0 + 128, nb = 4, dep = -1;
        unsigned tgt = 0;
        switch (type) {
            case J_KV: ta = &p.tm_h; tb0 = tb1 = cb < 16 ? &p.tm_wk : &p.tm_wv; n0 = (cb & 15) * 256; n1 = n0 + 128; dep = F_H + rb; tgt = 2 * NJ_LN1; break;
            case J_QA: ta = &p.tm_h; tb0 = tb1 = &p.tm_wq; dep = F_H + rb; tgt = 2 * NJ_LN1; if (rb == NRB - 1) { n0 = (cb >> 1) * 256; n1 = n0 + 128; } break;
            case J_O: ta = &p.tm_o; tb0 = tb1 = &p.tm_wo; n0 = (cb & 1) * 256; n1 = n0 + 128; nk = o_nk(rb); k0 = (cb >> 1) * nk * 64;
                      dep = F_O + rb; tgt = rb == NRB - 1 ? 64 : 32; break;
            case J_UP: ta = &p.tm_h2; tb0 = &p.tm_wg; tb1 = &p.tm_wu; n0 = n1 = cb * 128; dep = F_H2 + rb; tgt = 2 * NJ_LN; break;
            case J_UP2: ta = &p.tm_h2; tb0 = &p.tm_wg; tb1 = &p.tm_wu; n0 = n1 = cb * 64; nb = 2; dep = F_H2 + rb; tgt = 2 * NJ_LN2; break;
            default: ta = &p.tm_act; tb0 = tb1 = &p.tm_wd; n0 = cb * 64; nk = 0; break;
        }
        const int m0 = rb * 128;
        if (type == J_DN && rb == NRB - 1) {
            n0 = (cb >> 1) * 64;
            const int mh = m0 + (cb & 1) * 64;
#pragma unroll 1
            for (int kb = 0; kb < 14; kb++) {
                const uint32_t fb = begin_stage(32768);
                const uint32_t st = sb + pp.stage * W_STAGE;
                const int k = kb * 128;
                tma_load2d(st + 32768, tb0, n0, k, fb);
                tma_load2d(st + 40960, tb0, n0, k + 64, fb);
                if (kb == 0) { if (!acquired) { wait_flag(F_ACT + rb, 2 * NJ_UP2); asm volatile("fence.proxy.async.global;" ::: "memory"); } TR(j, 2); }
                tma_load2d(st, ta, k, mh, fb);
                tma_load2d(st + 8192, ta, k + 64, mh, fb);
                pipe_next(pp);
            }
            const uint32_t fb = begin_stage(8192);
            tma_load2d(sb + pp.stage * W_STAGE, &p.tm_x1, n0, mh, fb);
            pipe_next(pp);
            seq++;
            continue;
        }
        if (type == J_DN) {
#pragma unroll 1
            for (int kb = 0; kb < 14; kb++) {
                const uint32_t fb = begin_stage(49152);
                const uint32_t st = sb + pp.stage * W_STAGE;
                const int k = kb * 128;
                tma_load2d(st + 32768, tb0, n0, k, fb);
                tma_load2d(st + 40960, tb0, n0, k + 64, fb);
                if (kb == 0) { if (!acquired) { wait_flag(F_ACT + rb, 2 * (fine ? NJ_UP2 : NJ_UP)); asm volatile("fence.proxy.async.global;" ::: "memory"); } TR(j, 2); }
                tma_load2d(st, ta, k, m0, fb);
                tma_load2d(st + 8192, ta, k, m0 + 64, fb);
                tma_load2d(st + 16384, ta, k + 64, m0, fb);
                tma_load2d(st + 24576, ta, k + 64, m0 + 64, fb);
                pipe_next(pp);
            }
        }
#pragma unroll 1
        for (int kb = 0; kb < nk; kb++) {
            const uint32_t fb = begin_stage(16384 + nb * 8192);
            const uint32_t st = sb + pp.stage * W_STAGE;
            const int k = k0 + kb * 64;
            tma_load2d(st + 16384, tb0, n0, k, fb);
            if (nb == 4) {
                tma_load2d(st + 16384 + 8192, tb0, n0 + 64, k, fb);
                tma_load2d(st + 16384 + 16384, tb1, n1, k, fb);
                tma_load2d(st + 16384 + 24576, tb1, n1 + 64, k, fb);
            } else if (nb == 2) {
                tma_load2d(st + 16384 + 8192, tb1, n1, k, fb);
            }
            if (kb == 0) {
                if (acquired && dep < 16) h_seen |= 1u << dep;
                if (dep >= 0 && !acquired && !(dep < 16 && ((h_seen >> dep) & 1))) {
                    wait_flag(dep, tgt);
                    if (type != J_O) asm volatile("fence.proxy.async.global;" ::: "memory");
                    if (dep < 16) h_seen |= 1u << dep;
                }
                TR(j, 2);
            }
            tma_load2d(st, ta, k, m0, fb);
            tma_load2d(st + 8192, ta, k, m0 + 64, fb);
            pipe_next(pp);
        }
        if (type == J_QA) {
            wait_flag(F_KV + rb, 64);
#pragma unroll 1
            for (int i = 0; i < (rb == NRB - 1 ? 2 : 4); i++) {
                const uint32_t fb = begin_stage(40960);
                const uint32_t st = sb + pp.stage * W_STAGE;
                const int col = (i & 1) * HD_ + (rb == NRB - 1 ? cb : cb * 2 + (i >> 1)) * DH_;
                tma_load2d(st, &p.tm_kv, col, m0, fb);
                tma_load2d(st + 8192, &p.tm_kv, col, m0 + 64, fb);
                tma_load2d(st + 16384, &p.tm_kv, col + 64, m0, fb);
                tma_load2d(st + 24576, &p.tm_kv, col + 64, m0 + 64, fb);
                if (i == 0) { wait_flag(F_MEM + rb, 64); asm volatile("fence.proxy.async.global;" ::: "memory"); }
                tma_load2d(st + 32768, &p.tm_kvm, col, rb * 32, fb);
                tma_load2d(st + 36864, &p.tm_kvm, col + 64, rb * 32, fb);
                pipe_next(pp);
            }
        } else if (type == J_DN) {
            const uint32_t fb = begin_stage(16384);
            const uint32_t st = sb + pp.stage * W_STAGE;
            tma_load2d(st, &p.tm_x1, n0, m0, fb);
            tma_load2d(st + 8192, &p.tm_x1, n0, m0 + 64, fb);
            pipe_next(pp);
        }
        seq++;
    }
}

__device__ __forceinline__ void store_warp(const Params& p, uint32_t sb, int wg, int lane) {
    const uint32_t bars = sb + SM_BAR;
    uint32_t seq = 0;
#pragma unroll 1
    while (true) {
        bar_sync(NB_ST + wg, 160);
        const uint32_t jd = lds32(bars + B_RING + (seq & 7) * 4);
        seq++;
        const int type = jd & 255, rb = (jd >> 8) & 255, cb = (jd >> 16) & 255;
        if (type == J_END) break;
        const uint32_t src = sb + W_STG + wg * 16384;
        const CUtensorMap* tm = nullptr; int n0 = cb * 256, nbox = 4, mrow = rb * 128 + wg * 64, flag = 0;
        switch (type) {
            case J_KV: tm = &p.tm_kv; flag = F_KV + rb; break;
            case J_QA: tm = &p.tm_o; flag = F_O + rb; if (rb == NRB - 1) { n0 = cb * 128; nbox = 2; } break;
            case J_O: tm = &p.tm_op; n0 = (cb & 1) * 256; mrow = op_row(rb, cb >> 1) + wg * 64; flag = F_OP + rb; break;
            case J_LN: flag = F_H2 + rb; nbox = 0; break;
            case J_LN1: flag = F_H + rb; nbox = 0; break;
            case J_MOD: flag = F_MOD + rb; nbox = 0; break;
            case J_UP: tm = &p.tm_act; n0 = cb * 128; nbox = 2; flag = F_ACT + rb; break;
            case J_UP2: tm = &p.tm_act; n0 = cb * 64; nbox = 1; flag = F_ACT + rb; break;
            default: tm = &p.tm_out; n0 = cb * 64; nbox = 1; flag = -1;
                     if (rb == NRB - 1) { n0 = (cb >> 1) * 64; mrow = rb * 128 + (cb & 1) * 64; nbox = wg == 0; } break;
        }
        if (nbox == 4) {
            if (lane == 0) {
                tma_store2d(tm, src, n0, mrow);
                tma_store2d(tm, src + 8192, n0 + 64, mrow);
                bulk_commit();
                asm volatile("cp.async.bulk.wait_group.read 0;" ::: "memory");
                mbar_arrive(bars + B_STGFREE + wg * 8);
            }
            __syncwarp();
            bar_sync(NB_ST + wg, 160);
            n0 += 128; nbox = 2;
        }
        if (lane == 0) {
            if (nbox) {
                tma_store2d(tm, src, n0, mrow);
                if (nbox == 2) tma_store2d(tm, src + 8192, n0 + 64, mrow);
                bulk_commit();
                asm volatile("cp.async.bulk.wait_group.read 0;" ::: "memory");
                mbar_arrive(bars + B_STGFREE + wg * 8);
                bulk_wait0();
                if (flag >= 0) asm volatile("red.relaxed.gpu.global.add.u32 [%0], 1;" :: "l"(&g_flags[flag]) : "memory");
            } else {
                mbar_arrive(bars + B_STGFREE + wg * 8);
                if (flag >= 0) red_release(&g_flags[flag], 1);
            }
        }
        __syncwarp();
    }
}

__device__ __forceinline__ float gelu_tanh(float x) {
    const float t = x * fmaf(-0.10294324397f, x * x, -2.30220819814f);
    float r; asm("rcp.approx.ftz.f32 %0, %1;" : "=f"(r) : "f"(1.f + ex2(t)));
    return x * r;
}

#define CTR(i) do {} while (0)

__device__ __forceinline__ void ln2_row(const Params& p, int rb, int r, int lane, bool wait) {
    const int row = rb * 128 + r, nsplit = 64 / o_nk(rb);
    const uint4* xr = (const uint4*)(p.x + (size_t)row * D_);
    const uint4 xa = __ldg(xr + lane), xb = __ldg(xr + 32 + lane);
    uint32_t ga[8], c1[8], sm[8];
    load_mod8(g_mod + 2 * D_, lane, ga);
    load_mod8(g_mod + 4 * D_, lane, c1);
    load_mod8(g_mod + 3 * D_, lane, sm);
    float a[16];
#pragma unroll
    for (int i = 0; i < 16; i++) a[i] = 0.f;
    const uint4* src = (const uint4*)(g_op + (size_t)(op_row(rb, 0) + r) * D_) + lane;
    const int sstride = (op_row(rb, 1) - op_row(rb, 0)) * (D_ / 8);
    if (wait) { if (lane == 0) wait_flag(F_OP + rb, 4 * nsplit); __syncwarp(); }
    uint4 u[2][8];
#pragma unroll
    for (int sp = 0; sp < 4; sp++) { u[0][2 * sp] = __ldcg(src + sp * sstride); u[0][2 * sp + 1] = __ldcg(src + sp * sstride + 32); }
    if (nsplit > 4) {
#pragma unroll
        for (int sp = 0; sp < 4; sp++) { u[1][2 * sp] = __ldcg(src + (4 + sp) * sstride); u[1][2 * sp + 1] = __ldcg(src + (4 + sp) * sstride + 32); }
    }
#pragma unroll 1
    for (int s0 = 0; s0 < nsplit; s0 += 4) {
#pragma unroll
        for (int sp = 0; sp < 8; sp++) {
            float* q = a + (sp & 1) * 8;
            const uint4 w = u[0][sp];
            q[0] += bflo(w.x); q[1] += bfhi(w.x); q[2] += bflo(w.y); q[3] += bfhi(w.y);
            q[4] += bflo(w.z); q[5] += bfhi(w.z); q[6] += bflo(w.w); q[7] += bfhi(w.w);
            u[0][sp] = u[1][sp];
        }
        if (s0 + 8 < nsplit) {
#pragma unroll
            for (int sp = 0; sp < 4; sp++) { u[1][2 * sp] = __ldcg(src + (s0 + 8 + sp) * sstride); u[1][2 * sp + 1] = __ldcg(src + (s0 + 8 + sp) * sstride + 32); }
        }
    }
    const uint32_t xv[8] = {xa.x, xa.y, xa.z, xa.w, xb.x, xb.y, xb.z, xb.w};
    uint32_t v[8], r8[8];
#pragma unroll
    for (int i = 0; i < 8; i++) v[i] = hadd2(xv[i], hmul2(ga[i], pack2(a[2 * i], a[2 * i + 1])));
    uint4* x1r = (uint4*)(g_x1 + (size_t)row * D_);
    x1r[lane] = make_uint4(v[0], v[1], v[2], v[3]); x1r[32 + lane] = make_uint4(v[4], v[5], v[6], v[7]);
    uint32_t mu2; float rden;
    ln_stats(v, mu2, rden);
#pragma unroll
    for (int i = 0; i < 8; i++) c1[i] = hadd2(c1[i], 0x3F803F80u);
    ln_apply(v, mu2, rden, c1, sm, r8);
    uint4* hr = (uint4*)(g_h2 + (size_t)row * D_);
    hr[lane] = make_uint4(r8[0], r8[1], r8[2], r8[3]); hr[32 + lane] = make_uint4(r8[4], r8[5], r8[6], r8[7]);
}

__device__ __forceinline__ void consumer(const Params& p, uint32_t sb, int warp, int lane) {
    const uint32_t bars = sb + SM_BAR;
    const int wg = warp >> 2, wl = warp & 3;
    const uint32_t l7 = lane & 7, l8 = lane >> 3, g = lane >> 2, t = lane & 3;
    Pipe pp{0, 0};
    uint32_t seq = 0, stg_phase = 1;
    const int srow = wl * 16 + l7 + (l8 & 1) * 8;
    const uint32_t stg_base = sb + W_STG + wg * 16384 + srow * 128;
    const uint32_t sx = ((lane >> 4) ^ (srow & 7)) << 4;
#pragma unroll 1
    while (true) {
        mbar_wait(bars + B_FULL + pp.stage * 8, pp.phase);
        const uint32_t jd = lds32(bars + B_RING + (seq & 7) * 4);
        CTR(3);
        seq++;
        const int type = jd & 255, rb = (jd >> 8) & 255, cb = (jd >> 16) & 255;
        if (type == J_END) { mbar_wait(bars + B_STGFREE + wg * 8, stg_phase); bar_arrive(NB_ST + wg, 160); break; }
        if (type == J_LN) {
            __syncwarp();
            if (lane == 0) mbar_arrive(bars + B_EMPTY + pp.stage * 8);
            pipe_next(pp);
            const int nr = rb >= FINE_RB ? 1 : 2;
#pragma unroll 1
            for (int rr = 0; rr < nr; rr++) ln2_row(p, rb, (cb * 8 + warp) * nr + rr, lane, !((jd >> 24) & 1) && rr == 0);
            mbar_wait(bars + B_STGFREE + wg * 8, stg_phase); stg_phase ^= 1;
            CTR(4); CTR(5);
            bar_arrive(NB_ST + wg, 160);
            continue;
        }
        if (type == J_DN || type == J_UP2) {
            float acc[64];
#pragma unroll
            for (int i = 0; i < 64; i++) acc[i] = 0.f;
            const bool ksplit = type == J_DN && rb == NRB - 1;
            if (ksplit) {
#pragma unroll 1
                for (int kb = 0; kb < 14; kb++) {
                    if (kb) mbar_wait(bars + B_FULL + pp.stage * 8, pp.phase);
                    const uint32_t st = sb + pp.stage * W_STAGE;
                    const uint64_t da = mkdesc(st + wg * 8192, 16, 1024), db = mkdesc(st + 32768 + wg * 8192, 8192, 1024);
                    wg_fence();
#pragma unroll
                    for (int ks = 0; ks < 4; ks++) wgmma_n64(acc, da + ks * 2, db + ks * 128);
                    wg_commit();
                    wg_wait0();
                    if (lane == 0) mbar_arrive(bars + B_EMPTY + pp.stage * 8);
                    pipe_next(pp);
                }
                const uint32_t xb = sb + W_STG + 16384 + (wl * 32 + lane) * 16;
                if (wg == 1) {
                    mbar_wait(bars + B_STGFREE + 8, stg_phase);
#pragma unroll
                    for (int i = 0; i < 8; i++)
                        sts128(xb + i * 2048, make_uint4(__float_as_uint(acc[4 * i]), __float_as_uint(acc[4 * i + 1]), __float_as_uint(acc[4 * i + 2]), __float_as_uint(acc[4 * i + 3])));
                }
                bar_sync(NB_M, 256);
                if (wg == 0) {
#pragma unroll
                    for (int i = 0; i < 8; i++) {
                        const uint4 o = lds128(xb + i * 2048);
                        acc[4 * i] += __uint_as_float(o.x); acc[4 * i + 1] += __uint_as_float(o.y); acc[4 * i + 2] += __uint_as_float(o.z); acc[4 * i + 3] += __uint_as_float(o.w);
                    }
                }
                bar_sync(NB_M, 256);
            } else if (type == J_DN) {
#pragma unroll 1
                for (int kb = 0; kb < 14; kb++) {
                    if (kb) mbar_wait(bars + B_FULL + pp.stage * 8, pp.phase);
                    const uint32_t st = sb + pp.stage * W_STAGE;
                    const uint64_t da = mkdesc(st + wg * 8192, 16, 1024), db = mkdesc(st + 32768, 8192, 1024);
                    wg_fence();
#pragma unroll
                    for (int ks = 0; ks < 8; ks++) wgmma_n64(acc, da + (ks >> 2) * 1024 + (ks & 3) * 2, db + ks * 128);
                    wg_commit();
                    wg_wait0();
                    if (lane == 0) mbar_arrive(bars + B_EMPTY + pp.stage * 8);
                    pipe_next(pp);
                }
            } else {
#pragma unroll 1
                for (int kb = 0; kb < 8; kb++) {
                    if (kb) mbar_wait(bars + B_FULL + pp.stage * 8, pp.phase);
                    const uint32_t st = sb + pp.stage * W_STAGE;
                    const uint64_t da = mkdesc(st + wg * 8192, 16, 1024), db = mkdesc(st + 16384, 8192, 1024);
                    wg_fence();
#pragma unroll
                    for (int ks = 0; ks < 4; ks++) wgmma_n128(acc, da + ks * 2, db + ks * 128, 1);
                    wg_commit();
                    wg_wait0();
                    if (lane == 0) mbar_arrive(bars + B_EMPTY + pp.stage * 8);
                    pipe_next(pp);
                }
            }
            CTR(4);
            if (type == J_UP2) {
                mbar_wait(bars + B_STGFREE + wg * 8, stg_phase); stg_phase ^= 1;
#pragma unroll
                for (int j = 0; j < 4; j++) {
                    uint32_t r[4];
#pragma unroll
                    for (int q = 0; q < 4; q++) {
                        const uint32_t gw = pack2(acc[8 * j + 2 * q], acc[8 * j + 2 * q + 1]);
                        const uint32_t uw = pack2(acc[32 + 8 * j + 2 * q], acc[32 + 8 * j + 2 * q + 1]);
                        r[q] = hmul2(pack2(gelu_tanh(bflo(gw)), gelu_tanh(bfhi(gw))), uw);
                    }
                    stsm4(stg_base + (sx ^ (j << 5)), r[0], r[1], r[2], r[3]);
                }
            } else {
                mbar_wait(bars + B_FULL + pp.stage * 8, pp.phase);
                const uint32_t st = sb + pp.stage * W_STAGE;
                mbar_wait(bars + B_STGFREE + wg * 8, stg_phase); stg_phase ^= 1;
                const uint32_t* gb = (const uint32_t*)(g_mod + 5 * D_ + (ksplit ? cb >> 1 : cb) * 64) + t;
                const uint32_t xa = st + (ksplit ? 0 : wg * 8192) + (wl * 16 + g) * 128 + (g << 4) + t * 4;
#pragma unroll
                for (int j = 0; j < 4; j++) {
                    uint32_t r[4];
#pragma unroll
                    for (int q = 0; q < 4; q++) {
                        const int nt = 2 * j + (q >> 1);
                        const uint32_t xw = lds32((xa ^ ((nt & 7) << 4)) + (nt >> 3) * 16384 + (q & 1) * 1024);
                        r[q] = hadd2(xw, hmul2(__ldcg(gb + nt * 4), pack2(acc[8 * j + 2 * q], acc[8 * j + 2 * q + 1])));
                    }
                    stsm4(stg_base + (j >> 2) * 8192 + (sx ^ ((2 * j & 7) << 4)), r[0], r[1], r[2], r[3]);
                }
                __syncwarp();
                if (lane == 0) mbar_arrive(bars + B_EMPTY + pp.stage * 8);
                pipe_next(pp);
            }
            fence_async_smem();
            CTR(5);
            bar_arrive(NB_ST + wg, 160);
            continue;
        }
        float acc[128];
#pragma unroll
        for (int i = 0; i < 128; i++) acc[i] = 0.f;
        const int nk = type == J_O ? o_nk(rb) : 8;
#pragma unroll 1
        for (int kb = 0; kb < nk; kb++) {
            if (kb) mbar_wait(bars + B_FULL + pp.stage * 8, pp.phase);
            const uint32_t st = sb + pp.stage * W_STAGE;
            const uint64_t da = mkdesc(st + wg * 8192, 16, 1024), db = mkdesc(st + 16384, 8192, 1024);
            wg_fence();
#pragma unroll
            for (int ks = 0; ks < 4; ks++) wgmma_n256(acc, da + ks * 2, db + ks * 128, 1);
            wg_commit();
            wg_wait0();
            if (lane == 0) mbar_arrive(bars + B_EMPTY + pp.stage * 8);
            pipe_next(pp);
        }
        CTR(4);
        if (type == J_QA) {
            uint32_t qf[64];
#pragma unroll
            for (int i = 0; i < 64; i++) qf[i] = pack2(acc[2 * i], acc[2 * i + 1]);
            const int sg = warp >> 1, half = warp & 1;
            const float sc = 0.08838834764831845f * 1.4426950408889634f;
            const uint32_t xoff = (sg >> 1) * 8192 + ((sg & 1) * 32 + l7) * 128;
            const uint32_t moff = 32768 + (sg * 8 + l7) * 128;
            const uint32_t kch = (l8 ^ l7) << 4;
            const uint32_t vch = ((l8 & 1) ^ l7) << 4;
            if (rb == NRB - 1 && (cb & 1)) {
#pragma unroll
                for (int i = 0; i < 32; i++) qf[i] = qf[32 + i];
            }
#pragma unroll 1
            for (int hh = rb == NRB - 1; hh < 2; hh++) {
                mbar_wait(bars + B_FULL + pp.stage * 8, pp.phase);
                uint32_t st = sb + pp.stage * W_STAGE;
                float sa[5][4];
#pragma unroll
                for (int n = 0; n < 5; n++) sa[n][0] = sa[n][1] = sa[n][2] = sa[n][3] = 0.f;
#pragma unroll
                for (int i = 0; i < 4; i++) {
                    const uint32_t* q = qf + i * 8;
                    uint32_t kk[5][4];
                    ldsm4(kk[0][0], kk[0][1], kk[0][2], kk[0][3], st + moff + (i >> 1) * 4096 + (kch ^ ((i & 1) * 64)));
#pragma unroll
                    for (int n = 1; n < 5; n++)
                        ldsm4(kk[n][0], kk[n][1], kk[n][2], kk[n][3], st + xoff + (n - 1) * 1024 + (i >> 1) * 16384 + (kch ^ ((i & 1) * 64)));
#pragma unroll
                    for (int n = 0; n < 5; n++) mma16816(sa[n], q[0], q[1], q[2], q[3], kk[n][0], kk[n][1]);
#pragma unroll
                    for (int n = 0; n < 5; n++) mma16816(sa[n], q[4], q[5], q[6], q[7], kk[n][2], kk[n][3]);
                }
                __syncwarp();
                if (lane == 0) mbar_arrive(bars + B_EMPTY + pp.stage * 8);
                pipe_next(pp);
                const int iq0 = half * 16 + g - 2 * t, iq1 = iq0 + 8;
                float m0 = fmaxf(sa[0][0], sa[0][1]), m1 = fmaxf(sa[0][2], sa[0][3]);
#pragma unroll
                for (int n = 1; n < 5; n++) {
#pragma unroll
                    for (int e = 0; e < 2; e++) {
                        const int jx = (n - 1) * 8 + e;
                        if (jx > iq0) sa[n][e] = -3.0e38f;
                        if (jx > iq1) sa[n][2 + e] = -3.0e38f;
                        m0 = fmaxf(m0, sa[n][e]); m1 = fmaxf(m1, sa[n][2 + e]);
                    }
                }
                m0 = fmaxf(m0, __shfl_xor_sync(~0u, m0, 1)); m1 = fmaxf(m1, __shfl_xor_sync(~0u, m1, 1));
                m0 = fmaxf(m0, __shfl_xor_sync(~0u, m0, 2)); m1 = fmaxf(m1, __shfl_xor_sync(~0u, m1, 2));
                m0 *= -sc; m1 *= -sc;
                float l0 = 0.f, l1 = 0.f;
                uint32_t p0[5], p1[5];
#pragma unroll
                for (int n = 0; n < 5; n++) {
                    const float e0 = ex2(fmaf(sa[n][0], sc, m0)), e1 = ex2(fmaf(sa[n][1], sc, m0));
                    const float e2 = ex2(fmaf(sa[n][2], sc, m1)), e3 = ex2(fmaf(sa[n][3], sc, m1));
                    l0 += e0 + e1; l1 += e2 + e3;
                    p0[n] = pack2(e0, e1); p1[n] = pack2(e2, e3);
                }
                l0 += __shfl_xor_sync(~0u, l0, 1); l1 += __shfl_xor_sync(~0u, l1, 1);
                l0 += __shfl_xor_sync(~0u, l0, 2); l1 += __shfl_xor_sync(~0u, l1, 2);
                const float i0 = __fdividef(1.f, l0), i1 = __fdividef(1.f, l1);
                mbar_wait(bars + B_FULL + pp.stage * 8, pp.phase);
                st = sb + pp.stage * W_STAGE;
                mbar_wait(bars + B_STGFREE + wg * 8, stg_phase); stg_phase ^= 1;
#pragma unroll
                for (int i = 0; i < 32; i++) qf[i] = qf[32 + i];
#pragma unroll 1
                for (int bx = 0; bx < 2; bx++) {
                    float o[8][4];
                    uint32_t vm[8], v0[4][4], v1[4][4];
#pragma unroll
                    for (int ep = 0; ep < 4; ep++) {
                        ldsm2t(vm[2 * ep], vm[2 * ep + 1], st + moff + bx * 4096 + (vch ^ (ep << 5)));
                        const uint32_t va = st + xoff + (l8 >> 1) * 1024 + bx * 16384 + (vch ^ (ep << 5));
                        ldsm4t(v0[ep][0], v0[ep][1], v0[ep][2], v0[ep][3], va);
                        ldsm4t(v1[ep][0], v1[ep][1], v1[ep][2], v1[ep][3], va + 2048);
                    }
#pragma unroll
                    for (int n = 0; n < 8; n++) { o[n][0] = o[n][1] = o[n][2] = o[n][3] = 0.f; mma16816(o[n], p0[0], p1[0], p0[1], p1[1], vm[n], v0[n >> 1][n & 1]); }
#pragma unroll
                    for (int n = 0; n < 8; n++) mma16816(o[n], p0[2], p1[2], p0[3], p1[3], v0[n >> 1][2 + (n & 1)], v1[n >> 1][n & 1]);
#pragma unroll
                    for (int n = 0; n < 8; n++) mma1688(o[n], p0[4], p1[4], v1[n >> 1][2 + (n & 1)]);
#pragma unroll
                    for (int ep = 0; ep < 4; ep++)
                        stsm4(stg_base + bx * 8192 + (sx ^ (ep << 5)),
                              pack2(o[2 * ep][0] * i0, o[2 * ep][1] * i0), pack2(o[2 * ep][2] * i1, o[2 * ep][3] * i1),
                              pack2(o[2 * ep + 1][0] * i0, o[2 * ep + 1][1] * i0), pack2(o[2 * ep + 1][2] * i1, o[2 * ep + 1][3] * i1));
                }
                __syncwarp();
                if (lane == 0) mbar_arrive(bars + B_EMPTY + pp.stage * 8);
                pipe_next(pp);
                if (hh == 0) { fence_async_smem(); bar_arrive(NB_ST + wg, 160); }
            }
        } else if (type == J_UP) {
            mbar_wait(bars + B_STGFREE + wg * 8, stg_phase); stg_phase ^= 1;
#pragma unroll
            for (int j = 0; j < 8; j++) {
                uint32_t r[4];
#pragma unroll
                for (int q = 0; q < 4; q++) {
                    const uint32_t gw = pack2(acc[8 * j + 2 * q], acc[8 * j + 2 * q + 1]);
                    const uint32_t uw = pack2(acc[64 + 8 * j + 2 * q], acc[64 + 8 * j + 2 * q + 1]);
                    r[q] = hmul2(pack2(gelu_tanh(bflo(gw)), gelu_tanh(bfhi(gw))), uw);
                }
                stsm4(stg_base + (j >> 2) * 8192 + (sx ^ ((2 * j & 7) << 4)), r[0], r[1], r[2], r[3]);
            }
        } else {
#pragma unroll
            for (int rd = 0; rd < 2; rd++) {
                mbar_wait(bars + B_STGFREE + wg * 8, stg_phase); stg_phase ^= 1;
#pragma unroll
                for (int j = rd * 8; j < rd * 8 + 8; j++)
                    stsm4(stg_base + ((j >> 2) & 1) * 8192 + (sx ^ ((2 * j & 7) << 4)),
                          pack2(acc[8 * j], acc[8 * j + 1]), pack2(acc[8 * j + 2], acc[8 * j + 3]),
                          pack2(acc[8 * j + 4], acc[8 * j + 5]), pack2(acc[8 * j + 6], acc[8 * j + 7]));
                if (rd == 0) { fence_async_smem(); bar_arrive(NB_ST + wg, 160); }
            }
        }
        fence_async_smem();
        CTR(5);
        bar_arrive(NB_ST + wg, 160);
    }
}

__global__ void __launch_bounds__(384, 1) k_work(const __grid_constant__ Params p) {
    extern __shared__ __align__(1024) unsigned char smem_raw[];
    const uint32_t sb = smem_u32(smem_raw);
    if (sb & 1023) __trap();
    const int warp = __shfl_sync(~0u, threadIdx.x >> 5, 0);
    int lane; asm volatile("mov.u32 %0, %%laneid;" : "=r"(lane));
    if (threadIdx.x == 0) {
        const uint32_t bars = sb + SM_BAR;
        for (int i = 0; i < W_NST; i++) { mbar_init(bars + B_FULL + i * 8, 1); mbar_init(bars + B_EMPTY + i * 8, 8); }
        mbar_init(bars + B_STGFREE, 1); mbar_init(bars + B_STGFREE + 8, 1); mbar_init(bars + B_REQ, 1); mbar_init(bars + B_RSP, 1);
        asm volatile("fence.mbarrier_init.release.cluster;" ::: "memory");
    }
    __syncthreads();
    if (warp < 8) {
        asm volatile("setmaxnreg.inc.sync.aligned.u32 224;");
        consumer(p, sb, warp, lane);
    } else {
        asm volatile("setmaxnreg.dec.sync.aligned.u32 56;");
        if (warp == 8) { if (lane == 0) producer(p, sb); }
        else if (warp < 11) store_warp(p, sb, warp - 9, lane);
        else scheduler(p, sb, lane);
        __syncwarp();
        bar_sync(NB_W0, 128);
        if (warp == 8 && p.qmask == 0xff) {
            unsigned last = 0;
            if (lane == 0) { __threadfence(); last = atomicAdd(&g_flags[F_DONE], 1u) == gridDim.x - 1; }
            if (__shfl_sync(~0u, last, 0))
                for (int i = lane; i < F_TOTAL; i += 32) g_flags[i] = 0;
        }
    }
}

typedef CUresult (*EncodeFn)(CUtensorMap*, CUtensorMapDataType, cuuint32_t, void*, const cuuint64_t*, const cuuint64_t*,
                             const cuuint32_t*, const cuuint32_t*, CUtensorMapInterleave, CUtensorMapSwizzle,
                             CUtensorMapL2promotion, CUtensorMapFloatOOBfill);

static void make_map(EncodeFn enc, CUtensorMap* m, const void* ptr, uint64_t rows, uint64_t cols, uint32_t box_rows) {
    cuuint64_t dims[2] = {cols, rows};
    cuuint64_t strides[1] = {cols * 2};
    cuuint32_t box[2] = {64, box_rows};
    cuuint32_t es[2] = {1, 1};
    enc(m, CU_TENSOR_MAP_DATA_TYPE_BFLOAT16, 2, const_cast<void*>(ptr), dims, strides, box, es, CU_TENSOR_MAP_INTERLEAVE_NONE,
        CU_TENSOR_MAP_SWIZZLE_128B, CU_TENSOR_MAP_L2_PROMOTION_L2_256B, CU_TENSOR_MAP_FLOAT_OOB_FILL_NONE);
}
template <typename T> static void* sym_addr(T& sym) { void* p = nullptr; cudaGetSymbolAddress(&p, sym); return p; }

extern "C" void kernel_launch(void* const* d_in, const int* in_sizes, int n_in, void* d_out, int out_size) {
    static Params prm;
    static RecParams rp;
    static bool ready = false;
    static const void* key[14];
    bool same = ready;
    for (int i = 0; i < 13 && same; i++) same = key[i] == d_in[i];
    same = same && key[13] == d_out;
    if (!same) {
        void* fn = nullptr;
        cudaDriverEntryPointQueryResult qr;
        cudaGetDriverEntryPoint("cuTensorMapEncodeTiled", &fn, cudaEnableDefault, &qr);
        EncodeFn enc = (EncodeFn)fn;
        make_map(enc, &prm.tm_h, sym_addr(g_h), S_, D_, 64);
        make_map(enc, &prm.tm_kv, sym_addr(g_kv), S_, 2 * HD_, 64);
        make_map(enc, &prm.tm_kvm, sym_addr(g_kvm), NSEG * 8, 2 * HD_, 32);
        make_map(enc, &prm.tm_o, sym_addr(g_o), S_, HD_, 64);
        make_map(enc, &prm.tm_op, sym_addr(g_op), OP_ROWS, D_, 64);
        make_map(enc, &prm.tm_h2, sym_addr(g_h2), S_, D_, 64);
        make_map(enc, &prm.tm_act, sym_addr(g_act), S_, DF_, 64);
        make_map(enc, &prm.tm_x1, sym_addr(g_x1), S_, D_, 64);
        make_map(enc, &prm.tm_out, d_out, S_, D_, 64);
        make_map(enc, &prm.tm_wq, d_in[2], D_, HD_, 64);
        make_map(enc, &prm.tm_wk, d_in[3], D_, HD_, 64);
        make_map(enc, &prm.tm_wv, d_in[4], D_, HD_, 64);
        make_map(enc, &prm.tm_wo, d_in[5], HD_, D_, 64);
        make_map(enc, &prm.tm_wg, d_in[8], D_, DF_, 64);
        make_map(enc, &prm.tm_wu, d_in[9], D_, DF_, 64);
        make_map(enc, &prm.tm_wd, d_in[10], DF_, D_, 64);
        prm.x = (const bf16*)d_in[0]; prm.c = (const bf16*)d_in[11]; prm.w_mod = (const bf16*)d_in[12];
        rp.mem0 = (const bf16*)d_in[1]; rp.x = prm.x; rp.c = prm.c; rp.w_mod = prm.w_mod;
        rp.wq = (const bf16*)d_in[2]; rp.wk = (const bf16*)d_in[3]; rp.wv = (const bf16*)d_in[4]; rp.wo = (const bf16*)d_in[5];
        cudaFuncSetAttribute(k_work, cudaFuncAttributeMaxDynamicSharedMemorySize, SMEM_BYTES);
        cudaFuncSetAttribute(k_rec, cudaFuncAttributeMaxDynamicSharedMemorySize, R_SMEM);
        cudaFuncSetAttribute(k_rec, cudaFuncAttributeNonPortableClusterSizeAllowed, 1);
        {
            cudaLaunchConfig_t cfg = {};
            cfg.gridDim = dim3(128); cfg.blockDim = dim3(384); cfg.dynamicSmemBytes = R_SMEM;
            cudaLaunchAttribute at[1];
            at[0].id = cudaLaunchAttributeClusterDimension; at[0].val.clusterDim.x = 16; at[0].val.clusterDim.y = 1; at[0].val.clusterDim.z = 1;
            cfg.attrs = at; cfg.numAttrs = 1;
            int n = 0;
            cudaOccupancyMaxActiveClusters(&n, k_rec, &cfg);
            rp.ncl = n < 4 ? 4 : (n > 8 ? 8 : n);
        }
        for (int i = 0; i < 13; i++) key[i] = d_in[i];
        key[13] = d_out;
        ready = true;
    }
    cudaStream_t st = cudaStreamPerThread;
    auto launch_rec = [&]() {
        cudaLaunchConfig_t cfg = {};
        cfg.gridDim = dim3(16 * rp.ncl); cfg.blockDim = dim3(384); cfg.dynamicSmemBytes = R_SMEM; cfg.stream = st;
        cudaLaunchAttribute at[1];
        at[0].id = cudaLaunchAttributeClusterDimension; at[0].val.clusterDim.x = 16; at[0].val.clusterDim.y = 1; at[0].val.clusterDim.z = 1;
        cfg.attrs = at; cfg.numAttrs = 1;
        cudaLaunchKernelEx(&cfg, k_rec, rp);
    };
    auto launch_work = [&](int qmask, int pdl) {
        prm.qmask = qmask;
        cudaLaunchConfig_t cfg = {};
        cfg.gridDim = dim3(132); cfg.blockDim = dim3(384); cfg.dynamicSmemBytes = SMEM_BYTES; cfg.stream = st;
        cudaLaunchAttribute at[1];
        at[0].id = cudaLaunchAttributeProgrammaticStreamSerialization; at[0].val.programmaticStreamSerializationAllowed = 1;
        cfg.attrs = at; cfg.numAttrs = pdl;
        cudaLaunchKernelEx(&cfg, k_work, prm);
    };
    launch_rec();
    launch_work(0xff, 1);
}
```

```cpp
#include <cuda_runtime.h>
#include <cuda_bf16.h>
#include <cuda.h>
#include <stdint.h>

typedef __nv_bfloat16 bf16;
#define IDLE_NS 150
#define FLAG_NS 20

constexpr int S_ = 2048, D_ = 512, H_ = 32, DH_ = 128, HD_ = 4096, NSEG = 64, DF_ = 1792;
constexpr int NRB = 16;
constexpr int OSPLIT = 4;

__device__ __align__(1024) bf16 g_h[S_ * D_];
__device__ __align__(1024) bf16 g_kv[S_ * 2 * HD_];
__device__ __align__(1024) bf16 g_kvm[NSEG * 8 * 2 * HD_];
__device__ __align__(1024) bf16 g_o[S_ * HD_];
#define FINE_RB_ 12
constexpr int FINE_RB = FINE_RB_;
#define OSPLIT2_ 8
constexpr int OSPLIT2 = OSPLIT2_;
constexpr int OSPLIT3 = 16;
constexpr int OP_ROWS = OSPLIT * S_ + OSPLIT2 * (NRB - FINE_RB) * 128 + OSPLIT3 * 128;
__device__ __align__(1024) bf16 g_op[OP_ROWS * D_];
__device__ __align__(1024) bf16 g_x1[S_ * D_];
__device__ __align__(1024) bf16 g_h2[S_ * D_];
__device__ __align__(1024) bf16 g_act[S_ * DF_];
__device__ __align__(1024) bf16 g_mod[6 * D_];
__device__ uint32_t g_Fraw[131072 + 65536 + 2048];
#define g_F ((uint32_t*)(((uint64_t)g_Fraw + 0x7FFFFull) & ~0x7FFFFull))
constexpr int F_H = 0, F_MEM = 32, F_O = 64, F_OP = 96, F_H2 = 128, F_ACT = 160, F_MOD = 192, F_KV = 224, F_CLAIM = 256  ,
              F_SIDE = 512  , F_DONE = 576, F_TOTAL = 608;
__device__ __align__(128) unsigned int g_flags[F_TOTAL];
#define TR(j, i) do {} while (0)

__device__ __forceinline__ uint32_t smem_u32(const void* p) { return (uint32_t)__cvta_generic_to_shared(p); }
__device__ __forceinline__ uint32_t clk32() { uint32_t c; asm volatile("mov.u32 %0, %%clock;" : "=r"(c)); return c; }
__device__ __forceinline__ uint32_t mapa_u32(uint32_t addr, uint32_t rank) {
    uint32_t r; asm volatile("mapa.shared::cluster.u32 %0, %1, %2;" : "=r"(r) : "r"(addr), "r"(rank)); return r;
}
__device__ __forceinline__ void mbar_init(uint32_t bar, uint32_t cnt) {
    asm volatile("mbarrier.init.shared::cta.b64 [%0], %1;" :: "r"(bar), "r"(cnt) : "memory");
}
__device__ __forceinline__ void mbar_expect_tx(uint32_t bar, uint32_t bytes) {
    asm volatile("mbarrier.arrive.expect_tx.shared::cta.b64 _, [%0], %1;" :: "r"(bar), "r"(bytes) : "memory");
}
__device__ __forceinline__ void mbar_arrive(uint32_t bar) {
    asm volatile("mbarrier.arrive.shared::cta.b64 _, [%0];" :: "r"(bar) : "memory");
}
__device__ __forceinline__ bool mbar_try_wait(uint32_t bar, uint32_t parity) {
    uint32_t ok;
    asm volatile("{\n.reg .pred p;\nmbarrier.try_wait.parity.shared::cta.b64 p, [%1], %2;\nselp.u32 %0, 1, 0, p;\n}"
                 : "=r"(ok) : "r"(bar), "r"(parity) : "memory");
    return ok;
}
constexpr int SPIN_LIMIT = 1 << 18;
#define TIMEOUT(code, info) do {} while (0)
__device__ __forceinline__ void mbar_wait(uint32_t bar, uint32_t parity) {
    int g = 0;
#pragma unroll 1
    while (!mbar_try_wait(bar, parity)) { if (++g >= SPIN_LIMIT) { TIMEOUT(0, bar & 255); break; } }
}
__device__ __forceinline__ void bar_sync(int id, int n) { asm volatile("bar.sync %0, %1;" :: "r"(id), "r"(n) : "memory"); }
__device__ __forceinline__ void bar_arrive(int id, int n) { asm volatile("bar.arrive %0, %1;" :: "r"(id), "r"(n) : "memory"); }
__device__ __forceinline__ void st_async_v2(uint32_t addr, float a, float b, uint32_t bar) {
    asm volatile("st.async.weak.shared::cluster.mbarrier::complete_tx::bytes.v2.f32 [%0], {%1,%2}, [%3];"
                 :: "r"(addr), "f"(a), "f"(b), "r"(bar) : "memory");
}
__device__ __forceinline__ void st_async_v4(uint32_t addr, uint4 v, uint32_t bar) {
    asm volatile("st.async.weak.shared::cluster.mbarrier::complete_tx::bytes.v4.b32 [%0], {%1,%2,%3,%4}, [%5];"
                 :: "r"(addr), "r"(v.x), "r"(v.y), "r"(v.z), "r"(v.w), "r"(bar) : "memory");
}
__device__ __forceinline__ void stg_relaxed32(uint32_t* p, uint32_t v) {
    asm volatile("st.relaxed.gpu.global.b32 [%0], %1;" :: "l"(p), "r"(v) : "memory");
}
__device__ __forceinline__ uint32_t ldg_relaxed32(const uint32_t* p) {
    uint32_t v; asm volatile("ld.relaxed.gpu.global.b32 %0, [%1];" : "=r"(v) : "l"(p) : "memory"); return v;
}
__device__ __forceinline__ unsigned int ld_acquire(const unsigned int* p) {
    unsigned int v; asm volatile("ld.acquire.gpu.global.u32 %0, [%1];" : "=r"(v) : "l"(p) : "memory"); return v;
}
__device__ __forceinline__ void red_release(unsigned int* p, unsigned int v) {
    asm volatile("red.release.gpu.global.add.u32 [%0], %1;" :: "l"(p), "r"(v) : "memory");
}
__device__ __forceinline__ void wait_flag(int idx, unsigned int target) {
    const unsigned int* p = &g_flags[idx];
    int g = 0;
#pragma unroll 1
    while (ld_acquire(p) < target) { __nanosleep(FLAG_NS); if (++g >= 64 * SPIN_LIMIT) { TIMEOUT(2, idx); break; } }
}
__device__ __forceinline__ void cp_async16(uint32_t dst, const void* src) {
    asm volatile("cp.async.cg.shared.global [%0], [%1], 16;" :: "r"(dst), "l"(src) : "memory");
}
__device__ __forceinline__ void cp_async_commit() { asm volatile("cp.async.commit_group;" ::: "memory"); }
template <int N> __device__ __forceinline__ void cp_async_wait() { asm volatile("cp.async.wait_group %0;" :: "n"(N) : "memory"); }
__device__ __forceinline__ void ldsm4(uint32_t& r0, uint32_t& r1, uint32_t& r2, uint32_t& r3, uint32_t addr) {
    asm volatile("ldmatrix.sync.aligned.m8n8.x4.shared.b16 {%0,%1,%2,%3}, [%4];" : "=r"(r0), "=r"(r1), "=r"(r2), "=r"(r3) : "r"(addr) : "memory");
}
__device__ __forceinline__ void ldsm4t(uint32_t& r0, uint32_t& r1, uint32_t& r2, uint32_t& r3, uint32_t addr) {
    asm volatile("ldmatrix.sync.aligned.m8n8.x4.trans.shared.b16 {%0,%1,%2,%3}, [%4];" : "=r"(r0), "=r"(r1), "=r"(r2), "=r"(r3) : "r"(addr) : "memory");
}
__device__ __forceinline__ void ldsm2t(uint32_t& r0, uint32_t& r1, uint32_t addr) {
    asm volatile("ldmatrix.sync.aligned.m8n8.x2.trans.shared.b16 {%0,%1}, [%2];" : "=r"(r0), "=r"(r1) : "r"(addr) : "memory");
}
__device__ __forceinline__ void stsm4(uint32_t addr, uint32_t r0, uint32_t r1, uint32_t r2, uint32_t r3) {
    asm volatile("stmatrix.sync.aligned.m8n8.x4.shared.b16 [%0], {%1,%2,%3,%4};" :: "r"(addr), "r"(r0), "r"(r1), "r"(r2), "r"(r3) : "memory");
}
__device__ __forceinline__ void stsm2t(uint32_t addr, uint32_t r0, uint32_t r1) {
    asm volatile("stmatrix.sync.aligned.m8n8.x2.trans.shared.b16 [%0], {%1,%2};" :: "r"(addr), "r"(r0), "r"(r1) : "memory");
}
__device__ __forceinline__ void mma16816(float* d, uint32_t a0, uint32_t a1, uint32_t a2, uint32_t a3, uint32_t b0, uint32_t b1) {
    asm volatile("mma.sync.aligned.m16n8k16.row.col.f32.bf16.bf16.f32 {%0,%1,%2,%3}, {%4,%5,%6,%7}, {%8,%9}, {%0,%1,%2,%3};"
                 : "+f"(d[0]), "+f"(d[1]), "+f"(d[2]), "+f"(d[3]) : "r"(a0), "r"(a1), "r"(a2), "r"(a3), "r"(b0), "r"(b1));
}
__device__ __forceinline__ void mma1688(float* d, uint32_t a0, uint32_t a1, uint32_t b0) {
    asm volatile("mma.sync.aligned.m16n8k8.row.col.f32.bf16.bf16.f32 {%0,%1,%2,%3}, {%4,%5}, {%6}, {%0,%1,%2,%3};"
                 : "+f"(d[0]), "+f"(d[1]), "+f"(d[2]), "+f"(d[3]) : "r"(a0), "r"(a1), "r"(b0));
}
__device__ __forceinline__ void mma16816h(float* d, uint32_t a0, uint32_t a2, uint32_t b0, uint32_t b1) {
    asm volatile("{\n.reg .b32 ju, jv;\nmma.sync.aligned.m16n8k16.row.col.f32.bf16.bf16.f32 {%0,%1,%2,%3}, {%4,ju,%5,jv}, {%6,%7}, {%0,%1,%2,%3};\n}"
                 : "+f"(d[0]), "+f"(d[1]), "+f"(d[2]), "+f"(d[3]) : "r"(a0), "r"(a2), "r"(b0), "r"(b1));
}
__device__ __forceinline__ void mma1688h(float* d, uint32_t a0, uint32_t b0) {
    asm volatile("{\n.reg .b32 ju;\nmma.sync.aligned.m16n8k8.row.col.f32.bf16.bf16.f32 {%0,%1,%2,%3}, {%4,ju}, {%5}, {%0,%1,%2,%3};\n}"
                 : "+f"(d[0]), "+f"(d[1]), "+f"(d[2]), "+f"(d[3]) : "r"(a0), "r"(b0));
}
__device__ __forceinline__ uint32_t pack2(float lo, float hi) {
    uint32_t r; asm("cvt.rn.bf16x2.f32 %0, %1, %2;" : "=r"(r) : "f"(hi), "f"(lo)); return r;
}
__device__ __forceinline__ float bflo(uint32_t w) { return __uint_as_float(w << 16); }
__device__ __forceinline__ float bfhi(uint32_t w) { return __uint_as_float(w & 0xffff0000u); }
__device__ __forceinline__ float rbf(float x) { return __bfloat162float(__float2bfloat16_rn(x)); }
__device__ __forceinline__ float ex2(float x) { float y; asm("ex2.approx.ftz.f32 %0, %1;" : "=f"(y) : "f"(x)); return y; }
__device__ __forceinline__ void sts128(uint32_t addr, uint4 v) {
    asm volatile("st.shared.v4.b32 [%0], {%1,%2,%3,%4};" :: "r"(addr), "r"(v.x), "r"(v.y), "r"(v.z), "r"(v.w) : "memory");
}
__device__ __forceinline__ uint4 lds128(uint32_t addr) {
    uint4 v; asm volatile("ld.shared.v4.b32 {%0,%1,%2,%3}, [%4];" : "=r"(v.x), "=r"(v.y), "=r"(v.z), "=r"(v.w) : "r"(addr) : "memory"); return v;
}
__device__ __forceinline__ float2 lds64f(uint32_t addr) {
    float2 v; asm volatile("ld.shared.v2.f32 {%0,%1}, [%2];" : "=f"(v.x), "=f"(v.y) : "r"(addr) : "memory"); return v;
}
__device__ __forceinline__ float lds32f(uint32_t addr) {
    float v; asm volatile("ld.shared.f32 %0, [%1];" : "=f"(v) : "r"(addr) : "memory"); return v;
}
__device__ __forceinline__ uint32_t lds32(uint32_t addr) {
    uint32_t v; asm volatile("ld.shared.b32 %0, [%1];" : "=r"(v) : "r"(addr) : "memory"); return v;
}
__device__ __forceinline__ void sts32(uint32_t addr, uint32_t v) { asm volatile("st.shared.b32 [%0], %1;" :: "r"(addr), "r"(v) : "memory"); }
__device__ __forceinline__ void sts64f(uint32_t addr, float a, float b) { asm volatile("st.shared.v2.f32 [%0], {%1,%2};" :: "r"(addr), "f"(a), "f"(b) : "memory"); }

__device__ __forceinline__ void tma_load2d(uint32_t dst, const CUtensorMap* tm, int c0, int c1, uint32_t bar) {
    asm volatile("cp.async.bulk.tensor.2d.shared::cluster.global.mbarrier::complete_tx::bytes [%0], [%1, {%3, %4}], [%2];"
                 :: "r"(dst), "l"(tm), "r"(bar), "r"(c0), "r"(c1) : "memory");
}
__device__ __forceinline__ void tma_store2d(const CUtensorMap* tm, uint32_t src, int c0, int c1) {
    asm volatile("cp.async.bulk.tensor.2d.global.shared::cta.bulk_group [%0, {%2, %3}], [%1];"
                 :: "l"(tm), "r"(src), "r"(c0), "r"(c1) : "memory");
}
__device__ __forceinline__ void bulk_commit() { asm volatile("cp.async.bulk.commit_group;" ::: "memory"); }
__device__ __forceinline__ void bulk_wait0() { asm volatile("cp.async.bulk.wait_group 0;" ::: "memory"); }
__device__ __forceinline__ void fence_async_smem() { asm volatile("fence.proxy.async.shared::cta;" ::: "memory"); }
__device__ __forceinline__ void fence_async_all() { asm volatile("fence.proxy.async;" ::: "memory"); }

__device__ __forceinline__ void wg_fence() { asm volatile("wgmma.fence.sync.aligned;" ::: "memory"); }
__device__ __forceinline__ void wg_commit() { asm volatile("wgmma.commit_group.sync.aligned;" ::: "memory"); }
__device__ __forceinline__ void wg_wait0() { asm volatile("wgmma.wait_group.sync.aligned 0;" ::: "memory"); }
__device__ __forceinline__ uint64_t mkdesc(uint32_t saddr, uint32_t lbo, uint32_t sbo) {
    return (uint64_t)((saddr & 0x3FFFF) >> 4) | ((uint64_t)(lbo >> 4) << 16) | ((uint64_t)(sbo >> 4) << 32) | (1ull << 62);
}
#define ACC8(i) "+f"(d[i]), "+f"(d[i + 1]), "+f"(d[i + 2]), "+f"(d[i + 3]), "+f"(d[i + 4]), "+f"(d[i + 5]), "+f"(d[i + 6]), "+f"(d[i + 7])
__device__ __forceinline__ void wgmma_n256(float* d, uint64_t da, uint64_t db, int scale_d) {
    asm volatile(
        "{\n.reg .pred p;\nsetp.ne.b32 p, %130, 0;\n"
        "wgmma.mma_async.sync.aligned.m64n256k16.f32.bf16.bf16 "
        "{%0,%1,%2,%3,%4,%5,%6,%7,%8,%9,%10,%11,%12,%13,%14,%15,%16,%17,%18,%19,%20,%21,%22,%23,%24,%25,%26,%27,%28,%29,%30,%31,"
        "%32,%33,%34,%35,%36,%37,%38,%39,%40,%41,%42,%43,%44,%45,%46,%47,%48,%49,%50,%51,%52,%53,%54,%55,%56,%57,%58,%59,%60,%61,%62,%63,"
        "%64,%65,%66,%67,%68,%69,%70,%71,%72,%73,%74,%75,%76,%77,%78,%79,%80,%81,%82,%83,%84,%85,%86,%87,%88,%89,%90,%91,%92,%93,%94,%95,"
        "%96,%97,%98,%99,%100,%101,%102,%103,%104,%105,%106,%107,%108,%109,%110,%111,%112,%113,%114,%115,%116,%117,%118,%119,%120,%121,%122,%123,%124,%125,%126,%127}, "
        "%128, %129, p, 1, 1, 0, 1;\n}"
        : ACC8(0), ACC8(8), ACC8(16), ACC8(24), ACC8(32), ACC8(40), ACC8(48), ACC8(56),
          ACC8(64), ACC8(72), ACC8(80), ACC8(88), ACC8(96), ACC8(104), ACC8(112), ACC8(120)
        : "l"(da), "l"(db), "r"(scale_d));
}
__device__ __forceinline__ void wgmma_n128(float* d, uint64_t da, uint64_t db, int scale_d) {
    asm volatile(
        "{\n.reg .pred p;\nsetp.ne.b32 p, %66, 0;\n"
        "wgmma.mma_async.sync.aligned.m64n128k16.f32.bf16.bf16 "
        "{%0,%1,%2,%3,%4,%5,%6,%7,%8,%9,%10,%11,%12,%13,%14,%15,%16,%17,%18,%19,%20,%21,%22,%23,%24,%25,%26,%27,%28,%29,%30,%31,"
        "%32,%33,%34,%35,%36,%37,%38,%39,%40,%41,%42,%43,%44,%45,%46,%47,%48,%49,%50,%51,%52,%53,%54,%55,%56,%57,%58,%59,%60,%61,%62,%63}, "
        "%64, %65, p, 1, 1, 0, 1;\n}"
        : ACC8(0), ACC8(8), ACC8(16), ACC8(24), ACC8(32), ACC8(40), ACC8(48), ACC8(56)
        : "l"(da), "l"(db), "r"(scale_d));
}

__device__ __forceinline__ void wgmma_n64(float* d, uint64_t da, uint64_t db) {
    asm volatile(
        "wgmma.mma_async.sync.aligned.m64n64k16.f32.bf16.bf16 "
        "{%0,%1,%2,%3,%4,%5,%6,%7,%8,%9,%10,%11,%12,%13,%14,%15,%16,%17,%18,%19,%20,%21,%22,%23,%24,%25,%26,%27,%28,%29,%30,%31}, "
        "%32, %33, 1, 1, 1, 0, 1;"
        : ACC8(0), ACC8(8), ACC8(16), ACC8(24)
        : "l"(da), "l"(db));
}
__device__ __forceinline__ uint32_t hadd2(uint32_t a, uint32_t b) { uint32_t r; asm("add.rn.bf16x2 %0, %1, %2;" : "=r"(r) : "r"(a), "r"(b)); return r; }
__device__ __forceinline__ uint32_t hsub2(uint32_t a, uint32_t b) { uint32_t r; asm("sub.rn.bf16x2 %0, %1, %2;" : "=r"(r) : "r"(a), "r"(b)); return r; }
__device__ __forceinline__ uint32_t hmul2(uint32_t a, uint32_t b) { uint32_t r; asm("mul.rn.bf16x2 %0, %1, %2;" : "=r"(r) : "r"(a), "r"(b)); return r; }
__device__ __forceinline__ void load_mod8(const bf16* m, int lane, uint32_t* v) {
    const uint4 a = __ldcg((const uint4*)m + lane), b = __ldcg((const uint4*)m + 32 + lane);
    v[0] = a.x; v[1] = a.y; v[2] = a.z; v[3] = a.w; v[4] = b.x; v[5] = b.y; v[6] = b.z; v[7] = b.w;
}
__device__ __forceinline__ void ln_stats(const uint32_t* x, uint32_t& mu2, float& rden) {
    float s = 0.f;
#pragma unroll
    for (int i = 0; i < 8; i++) s += bflo(x[i]) + bfhi(x[i]);
#pragma unroll
    for (int o = 16; o > 0; o >>= 1) s += __shfl_xor_sync(~0u, s, o);
    const float mean = s * (1.f / D_);
    float q = 0.f;
#pragma unroll
    for (int i = 0; i < 8; i++) { const float d0 = bflo(x[i]) - mean, d1 = bfhi(x[i]) - mean; q = fmaf(d0, d0, q); q = fmaf(d1, d1, q); }
#pragma unroll
    for (int o = 16; o > 0; o >>= 1) q += __shfl_xor_sync(~0u, q, o);
    mu2 = pack2(mean, mean);
    rden = __frcp_rn(rbf(__fsqrt_rn(rbf(rbf(q * (1.f / D_)) + 1e-5f))));
}
__device__ __forceinline__ void ln_apply(const uint32_t* x, uint32_t mu2, float rden, const uint32_t* c1, const uint32_t* sm, uint32_t* r) {
#pragma unroll
    for (int i = 0; i < 8; i++) {
        const uint32_t d = hsub2(x[i], mu2);
        r[i] = hadd2(hmul2(pack2(bflo(d) * rden, bfhi(d) * rden), c1[i]), sm[i]);
    }
}

struct __align__(64) Params {
    CUtensorMap tm_h, tm_kv, tm_kvm, tm_o, tm_op, tm_h2, tm_act, tm_x1, tm_out;
    CUtensorMap tm_wq, tm_wk, tm_wv, tm_wo, tm_wg, tm_wu, tm_wd;
    const bf16 *x, *c, *w_mod;
    int qmask;
};

constexpr int R_NST = 3;
constexpr uint32_t R_WV = 0, R_MEM = 65536, R_KX = 73728, R_VX = R_KX + R_NST * 4096,
                   R_KMS = R_VX + R_NST * 4096  , R_VMS = R_KMS + 1024,
                   R_QS = R_KMS + 4096, R_OS = R_QS + 1024, R_SX = R_OS + 1024, R_BAR = R_SX + 2560,
                   R_RS = 107520  , R_VP = R_RS + 8192  ,
                   R_STG = R_VP + 8192  , R_SMEM = R_STG + 98304;
static_assert((R_KMS & 4095) == 0, "smem");
static_assert(R_BAR + 64 <= R_RS, "smem");
constexpr uint32_t RB_SX = R_BAR, RB_V = R_BAR + 8, RB_E = R_BAR + 16, RB_A = R_BAR + 24, RB_ROLE = R_BAR + 32, RB_A1 = R_BAR + 40;
constexpr int W_NST = 4;
constexpr uint32_t W_STAGE = 49152, W_STG = W_NST * W_STAGE  , W_END = W_STG + 32768;
constexpr uint32_t SM_BAR = W_END;
constexpr uint32_t SMEM_BYTES = W_END + 1024 + 2048;
constexpr uint32_t B_FULL = 0, B_EMPTY = 32, B_STGFREE = 64, B_REQ = 80, B_RSP = 88, B_NEXT = 96, B_RING = 128;
#define PICK_AHEAD 3

constexpr int NB_X = 11  , NB_Y = 1, NB_M = 5, NB_K = 5, NB_B = 2, NB_C = 3, NB_D = 4, NB_W0 = 6  , NB_ST = 9  ;

__device__ __forceinline__ int pos_of_d(int d) {
    const int rem = d & 31;
    return (d & ~31) + ((rem & 7) >> 1) * 8 + (rem & 1) * 4 + (rem >> 3);
}

#define PROF(i) do {} while (0)
#define PROFG(i) do {} while (0)
#define VK0_ 4
constexpr int VK0 = VK0_;
constexpr int NOFF = 8;
#define POLL_GAP 110

struct RecParams { const bf16 *mem0, *wq, *wk, *wv, *wo, *x, *c, *w_mod; int ncl, only_pre; };

__device__ __forceinline__ void rec_qk(const RecParams& p, const uint32_t sb, const int cta, const int warp, int lane, const int sel) {
    const int crank = cta & 15, cl = cta >> 4, rank = cta & 1;
    const int kh = warp >> 2, aa = warp & 3;
    uint32_t wa[2][16][4];
    const uint32_t stg = sb + R_STG + kh * 32768;
    {
        const int t128 = aa * 32 + lane;
        const int row = (lane >> 4) * 8 + (lane & 7);
        const int ch = t128 & 7;
        const size_t goff = (size_t)kh * 256 * HD_ + cta * 64 + ch * 8;
#pragma unroll 4
        for (int dd = 0; dd < 16; dd++) {
            const int d = dd * 16 + (t128 >> 3), pp = pos_of_d(d);
            cp_async16(sb + R_WV + kh * 32768 + pp * 128 + ((ch ^ (pp & 7)) << 4), p.wv + goff + (size_t)d * HD_);
        }
        cp_async_commit();
#pragma unroll 4
        for (int dd = 0; dd < 16; dd++) {
            const int d = dd * 16 + (t128 >> 3), pp = pos_of_d(d);
            cp_async16(stg + pp * 128 + ((ch ^ (pp & 7)) << 4), p.wq + goff + (size_t)d * HD_);
        }
        cp_async_commit();
        {
            const int i0 = (warp * 32 + lane) * 16, tok = i0 >> 9;
            const uint4 m0 = __ldg((const uint4*)(p.mem0 + i0)), m1 = __ldg((const uint4*)(p.mem0 + i0 + 8));
            const uint32_t mw[8] = {m0.x, m0.y, m0.z, m0.w, m1.x, m1.y, m1.z, m1.w};
#pragma unroll
            for (int e = 0; e < 16; e++) {
                const int pp = pos_of_d((i0 & 511) + e);
                const unsigned short v = (unsigned short)(mw[e >> 1] >> ((e & 1) * 16));
                asm volatile("st.shared.u16 [%0], %1;" :: "r"(sb + R_MEM + (pp >> 3) * 128 + tok * 16 + (pp & 7) * 2), "h"(v) : "memory");
            }
        }
        cp_async_wait<1>();
        bar_sync(NB_W0 + kh, 128);
        const uint32_t fv = row * 128 + (((2 * aa + ((lane >> 3) & 1)) ^ (row & 7)) << 4);
#pragma unroll
        for (int ks = 0; ks < 16; ks++) ldsm4t(wa[0][ks][0], wa[0][ks][1], wa[0][ks][2], wa[0][ks][3], sb + R_WV + kh * 32768 + fv + ks * 2048);
        bar_sync(NB_W0 + kh, 128);
#pragma unroll
        for (int ks = 0; ks < 16; ks++)
            sts128(sb + R_WV + kh * 32768 + (aa * 16 + ks) * 512 + lane * 16, make_uint4(wa[0][ks][0], wa[0][ks][1], wa[0][ks][2], wa[0][ks][3]));
        const uint32_t fo = stg + row * 128 + (((4 * (aa & 1) + ((lane >> 3) & 1)) ^ (row & 7)) << 4);
#pragma unroll 1
        for (int m = 0; m < 2; m++) {
            cp_async_wait<0>();
            bar_sync(NB_W0 + kh, 128);
            if ((aa >> 1) == m) {
#pragma unroll
                for (int ks = 0; ks < 16; ks++) {
                    ldsm4t(wa[0][ks][0], wa[0][ks][1], wa[0][ks][2], wa[0][ks][3], fo + ks * 2048);
                    ldsm4t(wa[1][ks][0], wa[1][ks][1], wa[1][ks][2], wa[1][ks][3], (fo ^ 32) + ks * 2048);
                }
            }
            bar_sync(NB_W0 + kh, 128);
            if (m == 0) {
#pragma unroll 4
                for (int dd = 0; dd < 16; dd++) {
                    const int d = dd * 16 + (t128 >> 3), pp = pos_of_d(d);
                    cp_async16(stg + pp * 128 + ((ch ^ (pp & 7)) << 4), p.wk + goff + (size_t)d * HD_);
                }
                cp_async_commit();
            }
        }
    }
    const uint32_t tab = stg + (aa * 32 + lane) * 16;
    {
        const uint32_t l7 = lane & 7, l8 = lane >> 3, g = lane >> 2, t = lane & 3;
        const uint32_t t0 = l7 * 128 + ((l8 ^ l7) << 4);
        const uint32_t tq = l7 * 128 + (((l8 >> 1) ^ l7) << 4);
        const uint32_t bq = warp >> 1, tp = warp & 1;
        uint4 v;
        v.x = sb + (aa < 2 ? R_QS : R_KMS) + l7 * 128 + (((4 * (aa & 1) + 2 * kh + (l8 & 1)) ^ l7) << 4);
        v.y = sb + R_QS + tq;
        v.z = sb + (warp == 0 ? R_KMS : R_KX + (warp - 1) * 1024) + t0;
        v.w = mapa_u32(sb + R_SX + (rank * 5 + warp) * 256 + lane * 8, crank ^ 1);
        sts128(tab, v);
        sts128(tab + 2048, make_uint4(sb + lane * 16 + R_MEM + kh * 4096, sb + lane * 16 + R_WV + warp * 8192,
                                      sb + lane * 16 + R_VP + warp * 512, sb + lane * 16 + R_VP + 4096 + (warp ^ 4) * 512));
        const uint32_t src = (l8 >> 1) * 8 + l7;
        const uint32_t L = bq * 8 + 2 * tp + (l8 & 1);
        const uint32_t d0 = (crank + ((t >> 1) | (g & 6))) & 15;
        v.x = sb + R_RS + src * 512 + ((L ^ (src & 7)) << 4);
        v.y = mapa_u32(sb + R_MEM + (crank * 4 + bq) * 128 + (4 * tp + 2 * (t & 1) + (g & 1)) * 16, d0);
        v.z = mapa_u32(sb + ((crank & 2) ? RB_A1 : RB_A), d0);
        v.w = lane;
        sts128(tab + 4096, v);
        const uint64_t wr = (uint64_t)(g_F + ((crank * 2 + ((crank ^ (crank >> 3) ^ sel) & 1)) * 1024 + warp * 128 + cl * 32 + lane));
        sts128(tab + 6144, make_uint4((uint32_t)wr, (uint32_t)(wr >> 32), (uint32_t)((((cl + 1) & 3) - cl) * 128), (uint32_t)((((cl + 2) & 3) - cl) * 128)));
        sts32(tab + 8192, (uint32_t)((((cl + 3) & 3) - cl) * 128));
#pragma unroll
        for (int i = 0; i < NOFF; i++)
            sts128(tab + 10240 + i * 2048, make_uint4(wa[i & 1][i >> 1][0], wa[i & 1][i >> 1][1], wa[i & 1][i >> 1][2], wa[i & 1][i >> 1][3]));
    }
    bar_sync(NB_D, 384);
    uint32_t slot_off = 0;
    const uint32_t slot_inc = warp == 0 ? 2048 : 4096, slot_last = warp == 0 ? 2048 : (R_NST - 1) * 4096;
    const uint32_t sx_bar_rem = (sb + RB_SX) ^ (1u << 24);
    uint4 tb = lds128(tab + 2048);
#pragma unroll 1
    for (int s = 0; s < NSEG; s++) {
        if (s > 0) mbar_wait(sb + RB_A, (s - 1) & 1);
        if (warp == 0) { PROF(0); PROFG(13); }
        uint4 ta;
        const uint32_t km_tog = aa >= 2 ? (s & 1) * 2048 : 0;
        {
            float acc[5][4];
#pragma unroll
            for (int c = 0; c < 5; c++) { acc[c][0] = acc[c][1] = acc[c][2] = acc[c][3] = 0.f; }
            uint32_t b[8][4];
            uint4 av[16];
            static_assert(VK0 == 4, "order below assumes the V/O warps cover slices 0,1");
#define QK4(k2) do { \
                mma16816(acc[0], wa[0][2 * (k2)][0], wa[0][2 * (k2)][1], wa[0][2 * (k2)][2], wa[0][2 * (k2)][3], b[k2][0], b[k2][1]); \
                mma16816(acc[1], wa[1][2 * (k2)][0], wa[1][2 * (k2)][1], wa[1][2 * (k2)][2], wa[1][2 * (k2)][3], b[k2][0], b[k2][1]); \
                mma16816(acc[3], wa[0][2 * (k2) + 1][0], wa[0][2 * (k2) + 1][1], wa[0][2 * (k2) + 1][2], wa[0][2 * (k2) + 1][3], b[k2][2], b[k2][3]); \
                mma16816(acc[4], wa[1][2 * (k2) + 1][0], wa[1][2 * (k2) + 1][1], wa[1][2 * (k2) + 1][2], wa[1][2 * (k2) + 1][3], b[k2][2], b[k2][3]); } while (0)
#define V2(k2) do { \
                mma16816(acc[2], av[2 * (k2)].x, av[2 * (k2)].y, av[2 * (k2)].z, av[2 * (k2)].w, b[k2][0], b[k2][1]); \
                mma16816(acv, av[2 * (k2) + 1].x, av[2 * (k2) + 1].y, av[2 * (k2) + 1].z, av[2 * (k2) + 1].w, b[k2][2], b[k2][3]); } while (0)
#define LB(k2) ldsm4(b[k2][0], b[k2][1], b[k2][2], b[k2][3], tb.x + (k2) * 512)
#define LV(k2) do { av[2 * (k2)] = lds128(tb.y + 2 * (k2) * 512); av[2 * (k2) + 1] = lds128(tb.y + (2 * (k2) + 1) * 512); } while (0)
            float acv[4] = {0.f, 0.f, 0.f, 0.f};
            LB(0); LB(1); LB(4); LB(5);
            QK4(0); QK4(1); LV(4); LV(5); QK4(4); QK4(5);
            if (s > 0) mbar_wait(sb + RB_A1, (s - 1) & 1);
            LB(2); LB(3); LB(6); LB(7); ta = lds128(tab);
            V2(4); V2(5); LV(2); LV(3);
            QK4(2); QK4(3); QK4(6); QK4(7);
            LV(6); LV(7);
#pragma unroll
            for (int i = 0; i < 4; i++) { acc[0][i] += acc[3][i]; acc[1][i] += acc[4][i]; }
            const float g0 = kh ? acc[0][0] : acc[1][0], g1 = kh ? acc[0][1] : acc[1][1], g2 = kh ? acc[0][2] : acc[1][2], g3 = kh ? acc[0][3] : acc[1][3];
            sts128(tb.w, make_uint4(__float_as_uint(g0), __float_as_uint(g1), __float_as_uint(g2), __float_as_uint(g3)));
            const float k0 = kh ? acc[1][0] : acc[0][0], k1 = kh ? acc[1][1] : acc[0][1], k2_ = kh ? acc[1][2] : acc[0][2], k3 = kh ? acc[1][3] : acc[0][3];
            if (warp == 0) PROF(1);
            V2(2); V2(3);
            bar_sync(NB_X + aa, 64);
            const uint4 o = lds128(tb.z + 4096);
            V2(6); V2(7);
            stsm2t(ta.x ^ km_tog, pack2(k0 + __uint_as_float(o.x), k1 + __uint_as_float(o.y)), pack2(k2_ + __uint_as_float(o.z), k3 + __uint_as_float(o.w)));
            sts128(tb.z, make_uint4(__float_as_uint(acc[2][0] + acv[0]), __float_as_uint(acc[2][1] + acv[1]), __float_as_uint(acc[2][2] + acv[2]), __float_as_uint(acc[2][3] + acv[3])));
        }
        const uint32_t kb = ta.z + slot_off;
        if (warp == 0) PROF(14);
        bar_sync(NB_B, 256);
        if (warp < 5) {
            uint32_t q[16], k0, k1, k2, k3, k4, k5, k6, k7;
            float sa[4] = {0.f, 0.f, 0.f, 0.f}, sc[4] = {0.f, 0.f, 0.f, 0.f};
            ldsm4(q[0], q[1], q[2], q[3], ta.y);
            ldsm4(k0, k1, k2, k3, kb);
            ldsm4(q[4], q[5], q[6], q[7], ta.y ^ 32);
            ldsm4(q[8], q[9], q[10], q[11], ta.y ^ 64);
            ldsm4(k4, k5, k6, k7, kb ^ 64);
            ldsm4(q[12], q[13], q[14], q[15], ta.y ^ 96);
            mma16816(sa, q[0], q[1], q[2], q[3], k0, k1);
            bar_arrive(NB_Y, 288);
            mma16816(sc, q[4], q[5], q[6], q[7], k2, k3);
            mma16816(sa, q[8], q[9], q[10], q[11], k4, k5);
            mma16816(sc, q[12], q[13], q[14], q[15], k6, k7);
            const float scl = 0.08838834764831845f * 1.4426950408889634f;
            const float r0 = (sa[0] + sc[0]) * scl, r1 = (sa[1] + sc[1]) * scl;
            if (s != NSEG - 1) {
                st_async_v2(ta.w, r0, r1, sx_bar_rem);
                st_async_v2(ta.w ^ (1u << 24), r0, r1, sx_bar_rem ^ (1u << 24));
            }
            if (warp == 0) PROF(2);
        } else if (s > 0 && warp == 7 && lane == 0) {
            mbar_expect_tx(sb + RB_A, 4096);
            mbar_expect_tx(sb + RB_A1, 4096);
        } else if (s > 0 && (s & 3) == 0 && warp == 6) {
            bar_sync(NB_K, 160);
            if (lane == 0) red_release(&g_flags[F_MEM + (s >> 2) - 1], 1);
            __syncwarp();
        }
        if (s == NSEG - 1) {
            const uint4 td = lds128(tab + 6144);
            stg_relaxed32((uint32_t*)(((uint64_t)td.y << 32) | (td.x ^ 0x21000)), 0u);
            break;
        }
        slot_off = slot_off == slot_last ? 0 : slot_off + slot_inc;
        const uint4 tc = lds128(tab + 4096), td = lds128(tab + 6144);
        const uint32_t te = lds32(tab + 8192);
        uint32_t* wr = (uint32_t*)(((uint64_t)td.y << 32) | (td.x ^ ((s & 1) * 0x21000)));
        const uint32_t* r1p = (const uint32_t*)((const char*)wr + (int)td.z);
        const uint32_t* r2p = (const uint32_t*)((const char*)wr + (int)td.w);
        const uint32_t* r3p = (const uint32_t*)((const char*)wr + (int)te);
        const uint32_t tag = ((s >> 1) + 1) & 1;
        mbar_wait(sb + RB_E, s & 1);
        if (warp == 0) PROF(7);
        {
            uint32_t a0, a1, a2, a3, a4, a5, a6, a7;
            ldsm4t(a0, a1, a2, a3, tc.x);
            ldsm4t(a4, a5, a6, a7, tc.x ^ 64);
            const uint32_t one = 0x3F803F80u;
            float d0_[4] = {0.f, 0.f, 0.f, 0.f}, d1_[4] = {0.f, 0.f, 0.f, 0.f};
            mma16816(d0_, a0, a1, a2, a3, one, one);
            mma16816(d1_, a4, a5, a6, a7, one, one);
            const bool t1 = tc.w & 1, t2 = tc.w & 2;
            const float x = t2 ? (t1 ? d1_[2] : d1_[0]) : (t1 ? d0_[2] : d0_[0]);
            const uint32_t own = (__float_as_uint(x) & ~1u) | tag;
            stg_relaxed32(wr, own);
            const uint32_t tq = clk32();
            if (warp == 0) PROF(8);
            PROFG(16 + warp);
            while ((int)(clk32() - tq) < POLL_GAP) {}
            uint32_t f1 = ldg_relaxed32(r1p), f2 = ldg_relaxed32(r2p), f3 = ldg_relaxed32(r3p);
#pragma unroll
            for (int i = 0; i < NOFF; i++) {
                const uint4 f0 = lds128(tab + 10240 + i * 2048);
                wa[i & 1][i >> 1][0] = f0.x; wa[i & 1][i >> 1][1] = f0.y; wa[i & 1][i >> 1][2] = f0.z; wa[i & 1][i >> 1][3] = f0.w;
            }
            tb = lds128(tab + 2048);
            int gg = 0;
#pragma unroll 1
            while (!__all_sync(~0u, (((f1 ^ tag) | (f2 ^ tag) | (f3 ^ tag)) & 1) == 0)) {
                f1 = ldg_relaxed32(r1p); f2 = ldg_relaxed32(r2p); f3 = ldg_relaxed32(r3p);
                if (++gg > 16 * SPIN_LIMIT) { TIMEOUT(3, s); break; }
            }
            if (warp == 0) PROF(9);
            const float v = (__uint_as_float(own) + __uint_as_float(f2)) + (__uint_as_float(f1) + __uint_as_float(f3));
            const bool b8 = tc.w & 8, b16 = tc.w & 16;
            const float recv = __shfl_xor_sync(~0u, v, 8);
            const uint32_t word = b8 ? pack2(recv, v) : pack2(v, recv);
            const uint32_t oth = __shfl_xor_sync(~0u, word, 16);
            const uint32_t wl = b16 ? oth : word, wh = b16 ? word : oth;
            const uint32_t p0 = __shfl_xor_sync(~0u, wl, 2), p1 = __shfl_xor_sync(~0u, wh, 2);
            const uint4 item = t2 ? make_uint4(p0, p1, wl, wh) : make_uint4(wl, wh, p0, p1);
            st_async_v4(tc.y, item, tc.z);
            st_async_v4(tc.y ^ (8u << 24), item, tc.z ^ (8u << 24));
            if (tc.w == 0 && warp == 7) mbar_expect_tx(sb + RB_E, 8192);
            if (warp == 0) PROF(10);
            PROF(40 + warp);
        }
        bar_sync(NB_D, 384);
    }
}

__device__ __forceinline__ void rec_load_kv(uint32_t sb, int col0, int s, uint32_t slot_off, int t128) {
    const int row = t128 >> 2, c2 = (t128 & 3) * 2;
    const bf16* src = g_kv + ((size_t)(s * 32 + row) * (2 * HD_) + col0 + c2 * 8);
    const uint32_t d0 = sb + R_KX + slot_off + row * 128 + ((c2 ^ (row & 7)) << 4);
    cp_async16(d0, src);
    cp_async16(d0 ^ 16, src + 8);
    cp_async16(d0 + (R_VX - R_KX), src + HD_);
    cp_async16((d0 ^ 16) + (R_VX - R_KX), src + HD_ + 8);
}

__device__ __forceinline__ void rec_store_kvm(uint32_t sb, int col0, int s, int w, int lane) {
    const int tok = (w & 1) * 4 + (lane >> 3);
    const uint4 v = lds128(sb + R_KMS + (s & 1) * 2048 + (w >> 1) * 1024 + tok * 128 + (((lane & 7) ^ tok) << 4));
    *(uint4*)(g_kvm + ((s * 8 + tok) * (2 * HD_) + (w >> 1) * HD_ + col0 + (lane & 7) * 8)) = v;
}

__device__ __forceinline__ void rec_vo(const RecParams& p, const uint32_t sb, const int cta, const int warp, int lane) {
    const int w = warp - 8, crank = cta & 15;
    const int col0 = cta * 64;
    uint32_t wo[8][4][4];
    {
        const int t128 = w * 32 + lane;
        const bf16* Wo = p.wo + (size_t)col0 * D_;
        const uint32_t stg = sb + R_STG + 2 * 32768;
#pragma unroll
        for (int half = 0; half < 2; half++) {
#pragma unroll 4
            for (int i = t128; i < 2048; i += 128) {
                const int e = i >> 6, ch = i & 63;
                cp_async16(stg + e * 1024 + ((ch ^ (e & 7)) << 4), Wo + (size_t)(half * 32 + e) * D_ + ch * 8);
            }
            cp_async_commit();
            cp_async_wait<0>();
            bar_sync(NB_W0 + 2, 128);
#pragma unroll
            for (int j = 0; j < 8; j++)
#pragma unroll
                for (int kk = 0; kk < 2; kk++) {
                    const int e = kk * 16 + (lane >> 4) * 8 + (lane & 7);
                    const int ch = (w * 8 + j) * 2 + ((lane >> 3) & 1);
                    ldsm4t(wo[j][half * 2 + kk][0], wo[j][half * 2 + kk][1], wo[j][half * 2 + kk][2], wo[j][half * 2 + kk][3],
                           stg + e * 1024 + ((ch ^ (e & 7)) << 4));
                }
            bar_sync(NB_W0 + 2, 128);
        }
        if (lane == 0) wait_flag(F_KV + 0, 64);
        __syncwarp();
        rec_load_kv(sb, col0, 0, 0, t128); cp_async_commit();
        rec_load_kv(sb, col0, 1, 4096, t128); cp_async_commit();
        cp_async_wait<1>();
    }
    const uint32_t tab = sb + R_STG + 2 * 32768 + (w * 32 + lane) * 16;
    {
        const uint32_t l7 = lane & 7, l8 = lane >> 3, g = lane >> 2;
        uint4 v;
        v.x = sb + R_VX + ((l8 & 1) * 8 + l7) * 128 + (((2 * w + (l8 >> 1)) ^ l7) << 4);
        v.y = sb + R_OS + g * 128 + (((2 * w) ^ g) << 4) + (lane & 3) * 4;
        v.z = sb + R_VMS + l7 * 128 + (((2 * w + (l8 & 1)) ^ l7) << 4);
        v.w = sb + R_OS + l7 * 128 + ((l8 ^ l7) << 4);
        sts128(tab, v);
        v.x = mapa_u32(sb + R_RS + crank * 512 + ((lane ^ (crank & 7)) << 4), w * 4);
        v.y = mapa_u32(sb + RB_E, w * 4);
        v.z = sb + R_VP + w * 512 + lane * 16;
        v.w = sb + R_SX + lane * 8;
        sts128(tab + 2048, v);
#pragma unroll
        for (int i = 0; i < 8; i++) sts128(tab + 4096 + i * 2048, make_uint4(wo[i][0][0], wo[i][0][1], wo[i][0][2], wo[i][0][3]));
        const int tok = (w & 1) * 4 + (lane >> 3), row = (w * 32 + lane) >> 2, c2 = (lane & 3) * 2;
        const uint64_t kd = (uint64_t)(g_kvm + (tok * (2 * HD_) + (w >> 1) * HD_ + col0 + (lane & 7) * 8));
        const uint64_t ks = (uint64_t)(g_kv + ((size_t)row * (2 * HD_) + col0 + c2 * 8));
        sts128(tab + 20480, make_uint4((uint32_t)kd, (uint32_t)(kd >> 32), (uint32_t)ks, (uint32_t)(ks >> 32)));
        sts128(tab + 22528, make_uint4(sb + R_KMS + (w >> 1) * 1024 + tok * 128 + (((lane & 7) ^ tok) << 4),
                                       sb + R_KX + row * 128 + ((c2 ^ (row & 7)) << 4), lane, 0));
    }
    bar_sync(NB_D, 384);
    const uint32_t lane16 = lds32(tab + 2048 + 8) - R_VP - w * 512;
    uint4 av[2 * VK0];
#pragma unroll
    for (int i = 0; i < 2 * VK0; i++) av[i] = lds128(lane16 + R_WV + (i / VK0) * 32768 + (w * 16 + i % VK0) * 512);
    uint32_t slot_off = 0;
#pragma unroll 1
    for (int s = 0; s < NSEG; s++) {
        if (s > 0) {
            mbar_wait(sb + RB_A, (s - 1) & 1);
            const uint4 tp = lds128(tab + 20480), tq = lds128(tab + 22528);
            const uint4 kvm = lds128(tq.x + ((s - 1) & 1) * 2048);
            *(uint4*)((((uint64_t)tp.y << 32) | tp.x) + (uint64_t)(s - 1) * (8 * 2 * HD_ * 2)) = kvm;
            if ((s & 3) == 0) bar_arrive(NB_K, 160);
            if (s + 1 < NSEG - 1) {
                if (((s + 1) & 3) == 0) { if (tq.z == 0) wait_flag(F_KV + ((s + 1) >> 2), 64); __syncwarp(); }
                const char* src = (const char*)((((uint64_t)tp.w << 32) | tp.z) + (uint64_t)(s + 1) * (32 * 2 * HD_ * 2));
                const uint32_t d0 = tq.y + (slot_off == (R_NST - 1) * 4096 ? 0 : slot_off + 4096);
                cp_async16(d0, src);
                cp_async16(d0 ^ 16, src + 16);
                cp_async16(d0 + (R_VX - R_KX), src + HD_ * 2);
                cp_async16((d0 ^ 16) + (R_VX - R_KX), src + HD_ * 2 + 16);
            }
            cp_async_commit();
        }
        bar_sync(NB_Y, 288);
        uint32_t vb0, vb1;
        {
            float va[4] = {0.f, 0.f, 0.f, 0.f}, vc[4] = {0.f, 0.f, 0.f, 0.f};
            uint32_t bb[VK0][4];
#pragma unroll
            for (int k2 = 0; k2 < VK0; k2++) ldsm4(bb[k2][0], bb[k2][1], bb[k2][2], bb[k2][3], lane16 + R_MEM + (k2 / (VK0 / 2)) * 4096 + (k2 % (VK0 / 2)) * 512);
#pragma unroll
            for (int k2 = 0; k2 < VK0; k2++) {
                mma16816(va, av[2 * k2].x, av[2 * k2].y, av[2 * k2].z, av[2 * k2].w, bb[k2][0], bb[k2][1]);
                mma16816(vc, av[2 * k2 + 1].x, av[2 * k2 + 1].y, av[2 * k2 + 1].z, av[2 * k2 + 1].w, bb[k2][2], bb[k2][3]);
            }
            const uint4 a = lds128(lane16 + R_VP + w * 512), b = lds128(lane16 + R_VP + 2048 + w * 512);
            vb0 = pack2((va[0] + vc[0]) + (__uint_as_float(a.x) + __uint_as_float(b.x)), (va[1] + vc[1]) + (__uint_as_float(a.y) + __uint_as_float(b.y)));
            vb1 = pack2((va[2] + vc[2]) + (__uint_as_float(a.z) + __uint_as_float(b.z)), (va[3] + vc[3]) + (__uint_as_float(a.w) + __uint_as_float(b.w)));
        }
        const uint4 ta = lds128(tab), tb = lds128(tab + 2048);
        uint32_t vx[8];
        ldsm4t(vx[0], vx[1], vx[2], vx[3], ta.x + slot_off);
        ldsm4t(vx[4], vx[5], vx[6], vx[7], ta.x + slot_off + 2048);
#pragma unroll
        for (int i = 0; i < 4; i++) {
            const uint4 f0 = lds128(tab + 4096 + i * 2048);
            wo[i][0][0] = f0.x; wo[i][0][1] = f0.y; wo[i][0][2] = f0.z; wo[i][0][3] = f0.w;
        }
        if (w == 0) PROF(11);
        uint32_t pf[5];
        float oa[2][4] = {{0.f, 0.f, 0.f, 0.f}, {0.f, 0.f, 0.f, 0.f}}, ob_[2][4] = {{0.f, 0.f, 0.f, 0.f}, {0.f, 0.f, 0.f, 0.f}};
        float sm0[4] = {0.f, 0.f, 0.f, 0.f}, sm1[4] = {0.f, 0.f, 0.f, 0.f};
        if (s != NSEG - 1) {
            mbar_wait(sb + RB_SX, s & 1);
            if (w == 0) PROF(4);
            float sv[10];
#pragma unroll
            for (int n = 0; n < 5; n++) {
                const float2 a = lds64f(tb.w + n * 256), b = lds64f(tb.w + (5 + n) * 256);
                sv[2 * n] = a.x + b.x; sv[2 * n + 1] = a.y + b.y;
            }
            float mx = fmaxf(fmaxf(fmaxf(sv[0], sv[1]), fmaxf(sv[2], sv[3])), fmaxf(fmaxf(sv[4], sv[5]), fmaxf(sv[6], sv[7])));
            mx = fmaxf(mx, fmaxf(sv[8], sv[9]));
            mx = fmaxf(mx, __shfl_xor_sync(~0u, mx, 1));
            mx = fmaxf(mx, __shfl_xor_sync(~0u, mx, 2));
#pragma unroll
            for (int n = 1; n < 5; n++) pf[n] = pack2(ex2(sv[2 * n] - mx), ex2(sv[2 * n + 1] - mx));
            pf[0] = pack2(ex2(sv[0] - mx), ex2(sv[1] - mx));
            if (w == 0) PROF(12);
            const uint32_t one = 0x3F803F80u;
            mma16816h(sm0, pf[1], pf[2], one, one);
            mma16816h(oa[0], pf[1], pf[2], vx[0], vx[1]);
            mma16816h(oa[1], pf[1], pf[2], vx[2], vx[3]);
            mma16816h(sm1, pf[3], pf[4], one, one);
            mma16816h(ob_[0], pf[3], pf[4], vx[4], vx[5]);
            mma16816h(ob_[1], pf[3], pf[4], vx[6], vx[7]);
            mma1688h(sm0, pf[0], one);
            mma1688h(oa[0], pf[0], vb0);
            mma1688h(oa[1], pf[0], vb1);
            float inv;
            asm("rcp.approx.ftz.f32 %0, %1;" : "=f"(inv) : "f"(sm0[0] + sm1[0]));
            oa[0][0] += ob_[0][0]; oa[0][1] += ob_[0][1]; oa[1][0] += ob_[1][0]; oa[1][1] += ob_[1][1];
            sts32(ta.y, pack2(oa[0][0] * inv, oa[0][1] * inv));
            sts32(ta.y ^ 16, pack2(oa[1][0] * inv, oa[1][1] * inv));
            const uint32_t oa2 = ta.w ^ 64;
            bar_sync(NB_C, 128);
            if (w == 0) PROF(5);
            uint32_t ob[8];
            ldsm4(ob[0], ob[1], ob[2], ob[3], ta.w);
            ldsm4(ob[4], ob[5], ob[6], ob[7], oa2);
#pragma unroll
            for (int i = 4; i < 8; i++) {
                const uint4 f0 = lds128(tab + 4096 + i * 2048);
                wo[i][0][0] = f0.x; wo[i][0][1] = f0.y; wo[i][0][2] = f0.z; wo[i][0][3] = f0.w;
            }
#pragma unroll
            for (int jj = 0; jj < 2; jj++) {
                if (jj == 1 && tb.w == 0) break;
                float acc[4][4];
#pragma unroll
                for (int c = 0; c < 4; c++) { acc[c][0] = acc[c][1] = acc[c][2] = acc[c][3] = 0.f; }
#pragma unroll
                for (int ks = 0; ks < 4; ks++)
#pragma unroll
                    for (int c = 0; c < 4; c++)
                        mma16816(acc[c], wo[jj * 4 + c][ks][0], wo[jj * 4 + c][ks][1], wo[jj * 4 + c][ks][2], wo[jj * 4 + c][ks][3], ob[2 * ks], ob[2 * ks + 1]);
#pragma unroll
                for (int pr = 0; pr < 2; pr++) {
                    uint4 v;
                    v.x = pack2(acc[2 * pr][0], acc[2 * pr][1]);
                    v.y = pack2(acc[2 * pr][2], acc[2 * pr][3]);
                    v.z = pack2(acc[2 * pr + 1][0], acc[2 * pr + 1][1]);
                    v.w = pack2(acc[2 * pr + 1][2], acc[2 * pr + 1][3]);
                    st_async_v4(tb.x + ((jj * 2 + pr) << 24), v, tb.y + ((jj * 2 + pr) << 24));
                }
            }
            if (w == 0) PROF(6);
        }
        stsm2t(ta.z + (s & 1) * 2048, vb0, vb1);
        cp_async_wait<0>();
        bar_sync(NB_C, 128);
        if (w == 0 && lane == 0 && s != NSEG - 1) mbar_expect_tx(sb + RB_SX, 2560);
        if (s != NSEG - 1) bar_arrive(NB_D, 384);
#pragma unroll
        for (int i = 0; i < 2 * VK0; i++) av[i] = lds128(lane16 + R_WV + (i / VK0) * 32768 + (w * 16 + i % VK0) * 512);
        slot_off = slot_off == (R_NST - 1) * 4096 ? 0 : slot_off + 4096;
    }
    rec_store_kvm(sb, col0, NSEG - 1, w, lane);
    bar_sync(NB_C, 128);
    if (w == 0 && lane == 0) red_release(&g_flags[F_MEM + NRB - 1], 1);
}

__global__ void __launch_bounds__(384, 1) k_rec(const RecParams p) {
    extern __shared__ __align__(1024) unsigned char smem_raw[];
    const uint32_t sb = __shfl_sync(~0u, smem_u32(smem_raw), 0);
    const int warp = __shfl_sync(~0u, threadIdx.x >> 5, 0);
    int lane; asm volatile("mov.u32 %0, %%laneid;" : "=r"(lane));
    const int crank = blockIdx.x & 15, slot = blockIdx.x >> 4;
    asm volatile("griddepcontrol.launch_dependents;");
    if (crank == 0 && threadIdx.x == 0) {
        stg_relaxed32(&g_F[65536 + slot * 64], 0u);
        stg_relaxed32(&g_F[65536 + 1024 + slot * 64], 0u);
    }
    if (threadIdx.x == 0) {
        mbar_init(sb + RB_SX, 1); mbar_init(sb + RB_E, 1); mbar_init(sb + RB_A, 1); mbar_init(sb + RB_A1, 1); mbar_init(sb + RB_ROLE, 1);
        asm volatile("fence.mbarrier_init.release.cluster;" ::: "memory");
        mbar_expect_tx(sb + RB_SX, 2560);
        mbar_expect_tx(sb + RB_E, 8192);
        mbar_expect_tx(sb + RB_A, 4096);
        mbar_expect_tx(sb + RB_A1, 4096);
        mbar_expect_tx(sb + RB_ROLE, 4);
    }
    asm volatile("barrier.cluster.arrive.relaxed.aligned;\nbarrier.cluster.wait.aligned;" ::: "memory");
    unsigned role = 0;
    if (crank == 0 && threadIdx.x == 0 && !p.only_pre) {
        unsigned x = 0;
        int tm[2] = {0x7fffffff, 0x7fffffff};
#pragma unroll 1
        for (int i = 0; i < 6; i++) {
            const uint32_t t0 = clk32();
            x = atomicAdd(&g_F[65536 + (i & 1) * 1024 + slot * 64 + (x >> 31)], 1u);
            if (x != (unsigned)(i >> 1)) sts32(sb + R_BAR + 56, x);
            const int dt = (int)(clk32() - t0);
            if (i >= 2) { if (i & 1) tm[1] = min(tm[1], dt); else tm[0] = min(tm[0], dt); }
        }
        const int side = tm[1] > tm[0];
        const unsigned old = atomicAdd(&g_flags[F_SIDE + side * 32], 1u);
        unsigned c0, c1; int gd = 0;
#pragma unroll 1
        do { c0 = ldg_relaxed32(&g_flags[F_SIDE]); c1 = ldg_relaxed32(&g_flags[F_SIDE + 32]); } while ((int)(c0 + c1) < p.ncl && ++gd < 64 * SPIN_LIMIT);
        const int big = c1 > c0;
        role = side == big ? old : (big ? c1 : c0) + old;
        role |= (big ^ 1) << 8;
    }
    __syncwarp();
    if (crank == 0 && warp == 0 && !p.only_pre) {
        role = __shfl_sync(~0u, role, 0);
        if (lane < 16)
            asm volatile("st.async.weak.shared::cluster.mbarrier::complete_tx::bytes.u32 [%0], %1, [%2];"
                         :: "r"(mapa_u32(sb + R_BAR + 48, lane)), "r"(role), "r"(mapa_u32(sb + RB_ROLE, lane)) : "memory");
    }
    if (warp >= 4) {
        const int w8 = warp - 4, nblk = gridDim.x;
        const int cq = lane & 3, rg = w8 * 8 + (lane >> 2);
        const uint32_t red = sb + R_VP;
        const int row0 = blockIdx.x * 8 + w8;
        const uint4* xr = (const uint4*)(p.x + (size_t)row0 * D_);
        uint4 xa = __ldg(xr + lane), xb = __ldg(xr + 32 + lane);
#pragma unroll 1
        for (int sl = blockIdx.x; sl < 96; sl += nblk) {
            uint4 wv[8];
#pragma unroll
            for (int i = 0; i < 8; i++) wv[i] = __ldg((const uint4*)(p.w_mod + (size_t)(rg * 8 + i) * (6 * D_) + sl * 32 + cq * 8));
            const uint32_t cw = __ldg((const uint32_t*)(p.c + rg * 8) + cq);
            const float cl = bflo(cw), ch = bfhi(cw);
            const uint32_t sw = pack2(__fdividef(cl, 1.f + __expf(-cl)), __fdividef(ch, 1.f + __expf(-ch)));
            float a[8];
#pragma unroll
            for (int i = 0; i < 8; i++) a[i] = 0.f;
#pragma unroll
            for (int i = 0; i < 8; i++) {
                const uint32_t sv = __shfl_sync(~0u, sw, (lane & 28) + (i >> 1));
                const float cv = (i & 1) ? bfhi(sv) : bflo(sv);
                a[0] = fmaf(cv, bflo(wv[i].x), a[0]); a[1] = fmaf(cv, bfhi(wv[i].x), a[1]); a[2] = fmaf(cv, bflo(wv[i].y), a[2]); a[3] = fmaf(cv, bfhi(wv[i].y), a[3]);
                a[4] = fmaf(cv, bflo(wv[i].z), a[4]); a[5] = fmaf(cv, bfhi(wv[i].z), a[5]); a[6] = fmaf(cv, bflo(wv[i].w), a[6]); a[7] = fmaf(cv, bfhi(wv[i].w), a[7]);
            }
#pragma unroll
            for (int i = 0; i < 8; i++) { a[i] += __shfl_xor_sync(~0u, a[i], 4); a[i] += __shfl_xor_sync(~0u, a[i], 8); a[i] += __shfl_xor_sync(~0u, a[i], 16); }
            if (lane < 4) {
                sts128(red + w8 * 128 + lane * 32, make_uint4(__float_as_uint(a[0]), __float_as_uint(a[1]), __float_as_uint(a[2]), __float_as_uint(a[3])));
                sts128(red + w8 * 128 + lane * 32 + 16, make_uint4(__float_as_uint(a[4]), __float_as_uint(a[5]), __float_as_uint(a[6]), __float_as_uint(a[7])));
            }
            bar_sync(NB_B, 256);
            if (w8 == 0) {
                float v = 0.f;
#pragma unroll
                for (int i = 0; i < 8; i++) v += lds32f(red + i * 128 + lane * 4);
                g_mod[sl * 32 + lane] = __float2bfloat16_rn(v);
                __syncwarp();
                if (lane == 0) red_release(&g_flags[F_MOD + (sl >= 32)], 1);
            }
            bar_sync(NB_B, 256);
        }
        uint32_t c1[8], sm[8];
        int row = row0;
#pragma unroll 1
        while (true) {
            const uint32_t v[8] = {xa.x, xa.y, xa.z, xa.w, xb.x, xb.y, xb.z, xb.w};
            uint32_t mu2, r[8]; float rden;
            ln_stats(v, mu2, rden);
            if (row == row0) {
                if (lane == 0) wait_flag(F_MOD, 32);
                __syncwarp();
                load_mod8(g_mod + D_, lane, c1);
                load_mod8(g_mod, lane, sm);
#pragma unroll
                for (int i = 0; i < 8; i++) c1[i] = hadd2(c1[i], 0x3F803F80u);
            } else if (row + 512 < S_) {
                xr = (const uint4*)(p.x + (size_t)(row + 512) * D_); xa = __ldg(xr + lane); xb = __ldg(xr + 32 + lane);
            }
            ln_apply(v, mu2, rden, c1, sm, r);
            uint4* hr = (uint4*)(g_h + (size_t)row * D_);
            hr[lane] = make_uint4(r[0], r[1], r[2], r[3]); hr[32 + lane] = make_uint4(r[4], r[5], r[6], r[7]);
            bar_sync(NB_B, 256);
            if (w8 == (row >> 7 & 7) && lane == 0) red_release(&g_flags[F_H + (row >> 7)], 1);
            __syncwarp();
            if (row == row0) {
                if (!p.only_pre) mbar_wait(sb + RB_ROLE, 0);
                const int cl = p.only_pre ? slot : (int)(lds32(sb + R_BAR + 48) & 255);
                row = cl < 4 ? (nblk + cl * 16 + crank) * 8 + w8 : S_;
                if (row < S_) { xr = (const uint4*)(p.x + (size_t)row * D_); xa = __ldg(xr + lane); xb = __ldg(xr + 32 + lane); }
            } else {
                row += 512;
            }
            if (row >= S_) break;
        }
    }
    if (p.only_pre) return;
    mbar_wait(sb + RB_ROLE, 0);
    const int rolew = __shfl_sync(~0u, lds32(sb + R_BAR + 48), 0);
    const int cl = rolew & 255;
    if (cl >= 4) return;
    const int cta = cl * 16 + crank;
    if (warp < 8) rec_qk(p, sb, cta, warp, lane, rolew >> 8);
    else rec_vo(p, sb, cta, warp, lane);
}

enum { J_KV = 0, J_QA = 1, J_O = 2, J_LN = 3, J_UP = 4, J_DN = 5, J_LN1 = 6, J_MOD = 7, J_UP2 = 8, J_END = 9 };
constexpr int NJ_O = 2 * OSPLIT, NJ_O2 = 2 * OSPLIT2, NJ_LN = 8, NJ_LN2 = 16, NJ_UP = 14, NJ_UP2 = 28, NJ_DN = 8, NJ_LN1 = 8;
constexpr uint64_t pk8(int a, int b, int c, int d, int e, int f, int g, int h) {
    return (uint64_t)a | ((uint64_t)b << 8) | ((uint64_t)c << 16) | ((uint64_t)d << 24) | ((uint64_t)e << 32) | ((uint64_t)f << 40) | ((uint64_t)g << 48) | ((uint64_t)h << 56);
}
constexpr uint64_t NJ_C = pk8(32, 16, NJ_O, NJ_LN, NJ_UP, NJ_DN, 0, 0), NJ_F = pk8(32, 16, NJ_O2, NJ_LN2, NJ_UP2, NJ_DN, 0, 0);
constexpr uint64_t TG_C = pk8(2 * NJ_LN1, 64, 32, 2 * NJ_O, 2 * NJ_LN, 2 * NJ_UP, 32, 0), TG_F = pk8(2 * NJ_LN1, 64, 32, 2 * NJ_O2, 2 * NJ_LN2, 2 * NJ_UP2, 32, 0);
constexpr uint64_t NJ_L = pk8(32, 32, 2 * OSPLIT3, NJ_LN2, NJ_UP2, 2 * NJ_DN, 0, 0), TG_L = pk8(2 * NJ_LN1, 64, 64, 4 * OSPLIT3, 2 * NJ_LN2, 2 * NJ_UP2, 32, 0);
__device__ __forceinline__ uint64_t nj_tab(int rb) { return rb < FINE_RB ? NJ_C : (rb < NRB - 1 ? NJ_F : NJ_L); }
__device__ __forceinline__ uint64_t tg_tab(int rb) { return rb < FINE_RB ? TG_C : (rb < NRB - 1 ? TG_F : TG_L); }
__device__ __forceinline__ int o_nk(int rb) { return rb < FINE_RB ? 64 / OSPLIT : (rb < NRB - 1 ? 64 / OSPLIT2 : 64 / OSPLIT3); }
constexpr uint64_t PRIO = pk8(4, 10, 9, 8, 7, 6, 3, 0);
__device__ __forceinline__ int pick_job(int lane, int qmask, int& idx) {
    const int rb = lane & 15, half = lane >> 4;
    const uint64_t nj = nj_tab(rb) >> (8 * half);
    const uint64_t tg = tg_tab(rb) >> (8 * half);
    const unsigned* cp = &g_flags[F_CLAIM + half * 32 + rb];
    const unsigned* dp = &g_flags[half * 32 + rb];
    int gd = 0;
#pragma unroll 1
    while (true) {
        const unsigned c0 = ldg_relaxed32(cp), c1 = ldg_relaxed32(cp + 64), c2 = ldg_relaxed32(cp + 128);
        const unsigned d0 = ldg_relaxed32(dp - (half && rb ? 1 : 0)), d1 = ldg_relaxed32(dp + 64), d2 = ldg_relaxed32(dp + 128);
        const unsigned cl[3] = {c0, c1, c2}, dv[3] = {d0, d1, d2};
        unsigned key = 0xffffu, key2 = 0xffffu;
        bool pre = false;
#pragma unroll
        for (int i = 0; i < 3; i++) {
            const int q = half + 2 * i;
            const bool have = ((qmask >> q) & 1) && cl[i] < (unsigned)((nj >> (16 * i)) & 255);
            bool ready = have && dv[i] >= (unsigned)((tg >> (16 * i)) & 255);
            unsigned pr = (unsigned)((PRIO >> (8 * q)) & 255);
            if (i == 0 && rb <= 1 - half) ready = have;
            if (i == 0 && half && rb >= FINE_RB) pr = 5;
            if (ready) key = min(key, (pr << 8) | (rb << 4) | q);
            if (have) key2 = min(key2, rb >= FINE_RB ? (0x100u | (q << 4) | rb) : (i == 0 ? 0u : 0x1000u));
            pre |= have && i == 0 && !half;
        }
        const bool anypre = __any_sync(~0u, pre);
        if (anypre && (key & 15) == J_QA) key = 0xffffu;
        key = __reduce_min_sync(~0u, key);
        key2 = __reduce_min_sync(~0u, key2);
        if (key2 == 0xffffu) return J_END;
        int pq, prb;
        if (key != 0xffffu) { pq = key & 15; prb = (key >> 4) & 15; }
        else if (key2 >= 0x120u && key2 < 0x1000u) { pq = (key2 >> 4) & 15; prb = key2 & 15; }
        else {
            __nanosleep(IDLE_NS);
            if (++gd > 16 * SPIN_LIMIT) { TIMEOUT(5, 0); return J_END; }
            continue;
        }
        int c = 0;
        if (lane == 0) c = (int)atomicAdd(&g_flags[F_CLAIM + pq * 32 + prb], 1u);
        c = __shfl_sync(~0u, c, 0);
        if (c < (int)((nj_tab(prb) >> (8 * pq)) & 255)) {
            idx = pq * 512 + prb * 32 + c;
            int acq = 0;
            if (pq != J_QA && pq < J_LN1) {
                if (lane == 0 && ld_acquire(&g_flags[pq * 32 + prb]) >= (unsigned)((tg_tab(prb) >> (8 * pq)) & 255)) {
                    asm volatile("fence.proxy.async.global;" ::: "memory");
                    acq = 1 << 24;
                }
            }
            return (pq == J_UP && prb >= FINE_RB ? J_UP2 : pq) | (prb << 8) | (c << 16) | acq;
        }
    }
}
__device__ __forceinline__ int op_row(int rb, int split) {
    return rb < FINE_RB ? split * S_ + rb * 128
                        : (rb < NRB - 1 ? OSPLIT * S_ + (split * (NRB - FINE_RB) + rb - FINE_RB) * 128 : OSPLIT * S_ + (OSPLIT2 * (NRB - FINE_RB) + split) * 128);
}

struct Pipe { uint32_t stage, phase; };
__device__ __forceinline__ void pipe_next(Pipe& p) { if (++p.stage == W_NST) { p.stage = 0; p.phase ^= 1; } }

__device__ __forceinline__ void scheduler(const Params& p, uint32_t sb, int lane) {
    const uint32_t bars = sb + SM_BAR;
    uint32_t ph = 0;
#pragma unroll 1
    while (true) {
        mbar_wait(bars + B_REQ, ph);
        int j = 4095;
        const int jd = pick_job(lane, p.qmask, j);
        if (lane == 0) { sts32(bars + B_NEXT, (uint32_t)jd); sts32(bars + B_NEXT + 4, (uint32_t)j); mbar_arrive(bars + B_RSP); }
        ph ^= 1;
        if (jd == J_END) break;
        __syncwarp();
    }
}

__device__ __forceinline__ void producer(const Params& p, uint32_t sb) {
    Pipe pp{0, 1};
    const uint32_t bars = sb + SM_BAR;
    uint32_t seq = 0, h_seen = 0;
    mbar_arrive(bars + B_REQ);
#pragma unroll 1
    while (true) {
        mbar_wait(bars + B_RSP, seq & 1);
        const int jd = (int)lds32(bars + B_NEXT), j = (int)lds32(bars + B_NEXT + 4);
        int left = (jd & 255) == J_DN ? 15 : ((jd & 255) == J_QA ? (((jd >> 8) & 255) == NRB - 1 ? 10 : 12) : ((jd & 255) == J_O ? o_nk((jd >> 8) & 255) : ((jd & 255) == J_LN || (jd & 255) == J_LN1 || (jd & 255) == J_MOD ? 1 : 8)));
        left = max(left - PICK_AHEAD, 1);
        TR(j, 1);
        const int type = jd & 255, rb = (jd >> 8) & 255, cb = (jd >> 16) & 255;
        const bool fine = rb >= FINE_RB, acquired = (jd >> 24) & 1;
        bool first = true;
        auto begin_stage = [&](uint32_t bytes) -> uint32_t {
            mbar_wait(bars + B_EMPTY + pp.stage * 8, pp.phase);
            if (first) { sts32(bars + B_RING + (seq & 7) * 4, (uint32_t)jd); sts32(bars + B_RING + 32 + (seq & 7) * 4, (uint32_t)j); first = false; }
            const uint32_t fb = bars + B_FULL + pp.stage * 8;
            if (bytes) mbar_expect_tx(fb, bytes); else mbar_arrive(fb);
            if (--left == 0 && type != J_END) mbar_arrive(bars + B_REQ);
            return fb;
        };
        if (type == J_END || type == J_LN || type == J_LN1 || type == J_MOD) {
            if (type == J_LN && !(h_seen >> 31)) { wait_flag(F_MOD + 1, 64); h_seen |= 1u << 31; }

            TR(j, 2);
            begin_stage(0); pipe_next(pp);
            seq++;
            if (type == J_END) break;
            continue;
        }
        const CUtensorMap *ta, *tb0, *tb1;
        int k0 = 0, nk = 8, n0 = cb * 256, n1 = n0 + 128, nb = 4, dep = -1;
        unsigned tgt = 0;
        switch (type) {
            case J_KV: ta = &p.tm_h; tb0 = tb1 = cb < 16 ? &p.tm_wk : &p.tm_wv; n0 = (cb & 15) * 256; n1 = n0 + 128; dep = F_H + rb; tgt = 2 * NJ_LN1; break;
            case J_QA: ta = &p.tm_h; tb0 = tb1 = &p.tm_wq; dep = F_H + rb; tgt = 2 * NJ_LN1; if (rb == NRB - 1) { n0 = (cb >> 1) * 256; n1 = n0 + 128; } break;
            case J_O: ta = &p.tm_o; tb0 = tb1 = &p.tm_wo; n0 = (cb & 1) * 256; n1 = n0 + 128; nk = o_nk(rb); k0 = (cb >> 1) * nk * 64;
                      dep = F_O + rb; tgt = rb == NRB - 1 ? 64 : 32; break;
            case J_UP: ta = &p.tm_h2; tb0 = &p.tm_wg; tb1 = &p.tm_wu; n0 = n1 = cb * 128; dep = F_H2 + rb; tgt = 2 * NJ_LN; break;
            case J_UP2: ta = &p.tm_h2; tb0 = &p.tm_wg; tb1 = &p.tm_wu; n0 = n1 = cb * 64; nb = 2; dep = F_H2 + rb; tgt = 2 * NJ_LN2; break;
            default: ta = &p.tm_act; tb0 = tb1 = &p.tm_wd; n0 = cb * 64; nk = 0; break;
        }
        const int m0 = rb * 128;
        if (type == J_DN && rb == NRB - 1) {
            n0 = (cb >> 1) * 64;
            const int mh = m0 + (cb & 1) * 64;
#pragma unroll 1
            for (int kb = 0; kb < 14; kb++) {
                const uint32_t fb = begin_stage(32768);
                const uint32_t st = sb + pp.stage * W_STAGE;
                const int k = kb * 128;
                tma_load2d(st + 32768, tb0, n0, k, fb);
                tma_load2d(st + 40960, tb0, n0, k + 64, fb);
                if (kb == 0) { if (!acquired) { wait_flag(F_ACT + rb, 2 * NJ_UP2); asm volatile("fence.proxy.async.global;" ::: "memory"); } TR(j, 2); }
                tma_load2d(st, ta, k, mh, fb);
                tma_load2d(st + 8192, ta, k + 64, mh, fb);
                pipe_next(pp);
            }
            const uint32_t fb = begin_stage(8192);
            tma_load2d(sb + pp.stage * W_STAGE, &p.tm_x1, n0, mh, fb);
            pipe_next(pp);
            seq++;
            continue;
        }
        if (type == J_DN) {
#pragma unroll 1
            for (int kb = 0; kb < 14; kb++) {
                const uint32_t fb = begin_stage(49152);
                const uint32_t st = sb + pp.stage * W_STAGE;
                const int k = kb * 128;
                tma_load2d(st + 32768, tb0, n0, k, fb);
                tma_load2d(st + 40960, tb0, n0, k + 64, fb);
                if (kb == 0) { if (!acquired) { wait_flag(F_ACT + rb, 2 * (fine ? NJ_UP2 : NJ_UP)); asm volatile("fence.proxy.async.global;" ::: "memory"); } TR(j, 2); }
                tma_load2d(st, ta, k, m0, fb);
                tma_load2d(st + 8192, ta, k, m0 + 64, fb);
                tma_load2d(st + 16384, ta, k + 64, m0, fb);
                tma_load2d(st + 24576, ta, k + 64, m0 + 64, fb);
                pipe_next(pp);
            }
        }
#pragma unroll 1
        for (int kb = 0; kb < nk; kb++) {
            const uint32_t fb = begin_stage(16384 + nb * 8192);
            const uint32_t st = sb + pp.stage * W_STAGE;
            const int k = k0 + kb * 64;
            tma_load2d(st + 16384, tb0, n0, k, fb);
            if (nb == 4) {
                tma_load2d(st + 16384 + 8192, tb0, n0 + 64, k, fb);
                tma_load2d(st + 16384 + 16384, tb1, n1, k, fb);
                tma_load2d(st + 16384 + 24576, tb1, n1 + 64, k, fb);
            } else if (nb == 2) {
                tma_load2d(st + 16384 + 8192, tb1, n1, k, fb);
            }
            if (kb == 0) {
                if (acquired && dep < 16) h_seen |= 1u << dep;
                if (dep >= 0 && !acquired && !(dep < 16 && ((h_seen >> dep) & 1))) {
                    wait_flag(dep, tgt);
                    if (type != J_O) asm volatile("fence.proxy.async.global;" ::: "memory");
                    if (dep < 16) h_seen |= 1u << dep;
                }
                TR(j, 2);
            }
            tma_load2d(st, ta, k, m0, fb);
            tma_load2d(st + 8192, ta, k, m0 + 64, fb);
            pipe_next(pp);
        }
        if (type == J_QA) {
            wait_flag(F_KV + rb, 64);
#pragma unroll 1
            for (int i = 0; i < (rb == NRB - 1 ? 2 : 4); i++) {
                const uint32_t fb = begin_stage(40960);
                const uint32_t st = sb + pp.stage * W_STAGE;
                const int col = (i & 1) * HD_ + (rb == NRB - 1 ? cb : cb * 2 + (i >> 1)) * DH_;
                tma_load2d(st, &p.tm_kv, col, m0, fb);
                tma_load2d(st + 8192, &p.tm_kv, col, m0 + 64, fb);
                tma_load2d(st + 16384, &p.tm_kv, col + 64, m0, fb);
                tma_load2d(st + 24576, &p.tm_kv, col + 64, m0 + 64, fb);
                if (i == 0) { wait_flag(F_MEM + rb, 64); asm volatile("fence.proxy.async.global;" ::: "memory"); }
                tma_load2d(st + 32768, &p.tm_kvm, col, rb * 32, fb);
                tma_load2d(st + 36864, &p.tm_kvm, col + 64, rb * 32, fb);
                pipe_next(pp);
            }
        } else if (type == J_DN) {
            const uint32_t fb = begin_stage(16384);
            const uint32_t st = sb + pp.stage * W_STAGE;
            tma_load2d(st, &p.tm_x1, n0, m0, fb);
            tma_load2d(st + 8192, &p.tm_x1, n0, m0 + 64, fb);
            pipe_next(pp);
        }
        seq++;
    }
}

__device__ __forceinline__ void store_warp(const Params& p, uint32_t sb, int wg, int lane) {
    const uint32_t bars = sb + SM_BAR;
    uint32_t seq = 0;
#pragma unroll 1
    while (true) {
        bar_sync(NB_ST + wg, 160);
        const uint32_t jd = lds32(bars + B_RING + (seq & 7) * 4);
        seq++;
        const int type = jd & 255, rb = (jd >> 8) & 255, cb = (jd >> 16) & 255;
        if (type == J_END) break;
        const uint32_t src = sb + W_STG + wg * 16384;
        const CUtensorMap* tm = nullptr; int n0 = cb * 256, nbox = 4, mrow = rb * 128 + wg * 64, flag = 0;
        switch (type) {
            case J_KV: tm = &p.tm_kv; flag = F_KV + rb; break;
            case J_QA: tm = &p.tm_o; flag = F_O + rb; if (rb == NRB - 1) { n0 = cb * 128; nbox = 2; } break;
            case J_O: tm = &p.tm_op; n0 = (cb & 1) * 256; mrow = op_row(rb, cb >> 1) + wg * 64; flag = F_OP + rb; break;
            case J_LN: flag = F_H2 + rb; nbox = 0; break;
            case J_LN1: flag = F_H + rb; nbox = 0; break;
            case J_MOD: flag = F_MOD + rb; nbox = 0; break;
            case J_UP: tm = &p.tm_act; n0 = cb * 128; nbox = 2; flag = F_ACT + rb; break;
            case J_UP2: tm = &p.tm_act; n0 = cb * 64; nbox = 1; flag = F_ACT + rb; break;
            default: tm = &p.tm_out; n0 = cb * 64; nbox = 1; flag = -1;
                     if (rb == NRB - 1) { n0 = (cb >> 1) * 64; mrow = rb * 128 + (cb & 1) * 64; nbox = wg == 0; } break;
        }
        if (nbox == 4) {
            if (lane == 0) {
                tma_store2d(tm, src, n0, mrow);
                tma_store2d(tm, src + 8192, n0 + 64, mrow);
                bulk_commit();
                asm volatile("cp.async.bulk.wait_group.read 0;" ::: "memory");
                mbar_arrive(bars + B_STGFREE + wg * 8);
            }
            __syncwarp();
            bar_sync(NB_ST + wg, 160);
            n0 += 128; nbox = 2;
        }
        if (lane == 0) {
            if (nbox) {
                tma_store2d(tm, src, n0, mrow);
                if (nbox == 2) tma_store2d(tm, src + 8192, n0 + 64, mrow);
                bulk_commit();
                asm volatile("cp.async.bulk.wait_group.read 0;" ::: "memory");
                mbar_arrive(bars + B_STGFREE + wg * 8);
                bulk_wait0();
                if (flag >= 0) asm volatile("red.relaxed.gpu.global.add.u32 [%0], 1;" :: "l"(&g_flags[flag]) : "memory");
            } else {
                mbar_arrive(bars + B_STGFREE + wg * 8);
                if (flag >= 0) red_release(&g_flags[flag], 1);
            }
        }
        __syncwarp();
    }
}

__device__ __forceinline__ float gelu_tanh(float x) {
    const float t = x * fmaf(-0.10294324397f, x * x, -2.30220819814f);
    float r; asm("rcp.approx.ftz.f32 %0, %1;" : "=f"(r) : "f"(1.f + ex2(t)));
    return x * r;
}

#define CTR(i) do {} while (0)

__device__ __forceinline__ void ln2_row(const Params& p, int rb, int r, int lane, bool wait) {
    const int row = rb * 128 + r, nsplit = 64 / o_nk(rb);
    const uint4* xr = (const uint4*)(p.x + (size_t)row * D_);
    const uint4 xa = __ldg(xr + lane), xb = __ldg(xr + 32 + lane);
    uint32_t ga[8], c1[8], sm[8];
    load_mod8(g_mod + 2 * D_, lane, ga);
    load_mod8(g_mod + 4 * D_, lane, c1);
    load_mod8(g_mod + 3 * D_, lane, sm);
    float a[16];
#pragma unroll
    for (int i = 0; i < 16; i++) a[i] = 0.f;
    const uint4* src = (const uint4*)(g_op + (size_t)(op_row(rb, 0) + r) * D_) + lane;
    const int sstride = (op_row(rb, 1) - op_row(rb, 0)) * (D_ / 8);
    if (wait) { if (lane == 0) wait_flag(F_OP + rb, 4 * nsplit); __syncwarp(); }
    uint4 u[2][8];
#pragma unroll
    for (int sp = 0; sp < 4; sp++) { u[0][2 * sp] = __ldcg(src + sp * sstride); u[0][2 * sp + 1] = __ldcg(src + sp * sstride + 32); }
    if (nsplit > 4) {
#pragma unroll
        for (int sp = 0; sp < 4; sp++) { u[1][2 * sp] = __ldcg(src + (4 + sp) * sstride); u[1][2 * sp + 1] = __ldcg(src + (4 + sp) * sstride + 32); }
    }
#pragma unroll 1
    for (int s0 = 0; s0 < nsplit; s0 += 4) {
#pragma unroll
        for (int sp = 0; sp < 8; sp++) {
            float* q = a + (sp & 1) * 8;
            const uint4 w = u[0][sp];
            q[0] += bflo(w.x); q[1] += bfhi(w.x); q[2] += bflo(w.y); q[3] += bfhi(w.y);
            q[4] += bflo(w.z); q[5] += bfhi(w.z); q[6] += bflo(w.w); q[7] += bfhi(w.w);
            u[0][sp] = u[1][sp];
        }
        if (s0 + 8 < nsplit) {
#pragma unroll
            for (int sp = 0; sp < 4; sp++) { u[1][2 * sp] = __ldcg(src + (s0 + 8 + sp) * sstride); u[1][2 * sp + 1] = __ldcg(src + (s0 + 8 + sp) * sstride + 32); }
        }
    }
    const uint32_t xv[8] = {xa.x, xa.y, xa.z, xa.w, xb.x, xb.y, xb.z, xb.w};
    uint32_t v[8], r8[8];
#pragma unroll
    for (int i = 0; i < 8; i++) v[i] = hadd2(xv[i], hmul2(ga[i], pack2(a[2 * i], a[2 * i + 1])));
    uint4* x1r = (uint4*)(g_x1 + (size_t)row * D_);
    x1r[lane] = make_uint4(v[0], v[1], v[2], v[3]); x1r[32 + lane] = make_uint4(v[4], v[5], v[6], v[7]);
    uint32_t mu2; float rden;
    ln_stats(v, mu2, rden);
#pragma unroll
    for (int i = 0; i < 8; i++) c1[i] = hadd2(c1[i], 0x3F803F80u);
    ln_apply(v, mu2, rden, c1, sm, r8);
    uint4* hr = (uint4*)(g_h2 + (size_t)row * D_);
    hr[lane] = make_uint4(r8[0], r8[1], r8[2], r8[3]); hr[32 + lane] = make_uint4(r8[4], r8[5], r8[6], r8[7]);
}

__device__ __forceinline__ void consumer(const Params& p, uint32_t sb, int warp, int lane) {
    const uint32_t bars = sb + SM_BAR;
    const int wg = warp >> 2, wl = warp & 3;
    const uint32_t l7 = lane & 7, l8 = lane >> 3, g = lane >> 2, t = lane & 3;
    Pipe pp{0, 0};
    uint32_t seq = 0, stg_phase = 1;
    const int srow = wl * 16 + l7 + (l8 & 1) * 8;
    const uint32_t stg_base = sb + W_STG + wg * 16384 + srow * 128;
    const uint32_t sx = ((lane >> 4) ^ (srow & 7)) << 4;
#pragma unroll 1
    while (true) {
        mbar_wait(bars + B_FULL + pp.stage * 8, pp.phase);
        const uint32_t jd = lds32(bars + B_RING + (seq & 7) * 4);
        CTR(3);
        seq++;
        const int type = jd & 255, rb = (jd >> 8) & 255, cb = (jd >> 16) & 255;
        if (type == J_END) { mbar_wait(bars + B_STGFREE + wg * 8, stg_phase); bar_arrive(NB_ST + wg, 160); break; }
        if (type == J_LN) {
            __syncwarp();
            if (lane == 0) mbar_arrive(bars + B_EMPTY + pp.stage * 8);
            pipe_next(pp);
            const int nr = rb >= FINE_RB ? 1 : 2;
#pragma unroll 1
            for (int rr = 0; rr < nr; rr++) ln2_row(p, rb, (cb * 8 + warp) * nr + rr, lane, !((jd >> 24) & 1) && rr == 0);
            mbar_wait(bars + B_STGFREE + wg * 8, stg_phase); stg_phase ^= 1;
            CTR(4); CTR(5);
            bar_arrive(NB_ST + wg, 160);
            continue;
        }
        if (type == J_DN || type == J_UP2) {
            float acc[64];
#pragma unroll
            for (int i = 0; i < 64; i++) acc[i] = 0.f;
            const bool ksplit = type == J_DN && rb == NRB - 1;
            if (ksplit) {
#pragma unroll 1
                for (int kb = 0; kb < 14; kb++) {
                    if (kb) mbar_wait(bars + B_FULL + pp.stage * 8, pp.phase);
                    const uint32_t st = sb + pp.stage * W_STAGE;
                    const uint64_t da = mkdesc(st + wg * 8192, 16, 1024), db = mkdesc(st + 32768 + wg * 8192, 8192, 1024);
                    wg_fence();
#pragma unroll
                    for (int ks = 0; ks < 4; ks++) wgmma_n64(acc, da + ks * 2, db + ks * 128);
                    wg_commit();
                    wg_wait0();
                    if (lane == 0) mbar_arrive(bars + B_EMPTY + pp.stage * 8);
                    pipe_next(pp);
                }
                const uint32_t xb = sb + W_STG + 16384 + (wl * 32 + lane) * 16;
                if (wg == 1) {
                    mbar_wait(bars + B_STGFREE + 8, stg_phase);
#pragma unroll
                    for (int i = 0; i < 8; i++)
                        sts128(xb + i * 2048, make_uint4(__float_as_uint(acc[4 * i]), __float_as_uint(acc[4 * i + 1]), __float_as_uint(acc[4 * i + 2]), __float_as_uint(acc[4 * i + 3])));
                }
                bar_sync(NB_M, 256);
                if (wg == 0) {
#pragma unroll
                    for (int i = 0; i < 8; i++) {
                        const uint4 o = lds128(xb + i * 2048);
                        acc[4 * i] += __uint_as_float(o.x); acc[4 * i + 1] += __uint_as_float(o.y); acc[4 * i + 2] += __uint_as_float(o.z); acc[4 * i + 3] += __uint_as_float(o.w);
                    }
                }
                bar_sync(NB_M, 256);
            } else if (type == J_DN) {
#pragma unroll 1
                for (int kb = 0; kb < 14; kb++) {
                    if (kb) mbar_wait(bars + B_FULL + pp.stage * 8, pp.phase);
                    const uint32_t st = sb + pp.stage * W_STAGE;
                    const uint64_t da = mkdesc(st + wg * 8192, 16, 1024), db = mkdesc(st + 32768, 8192, 1024);
                    wg_fence();
#pragma unroll
                    for (int ks = 0; ks < 8; ks++) wgmma_n64(acc, da + (ks >> 2) * 1024 + (ks & 3) * 2, db + ks * 128);
                    wg_commit();
                    wg_wait0();
                    if (lane == 0) mbar_arrive(bars + B_EMPTY + pp.stage * 8);
                    pipe_next(pp);
                }
            } else {
#pragma unroll 1
                for (int kb = 0; kb < 8; kb++) {
                    if (kb) mbar_wait(bars + B_FULL + pp.stage * 8, pp.phase);
                    const uint32_t st = sb + pp.stage * W_STAGE;
                    const uint64_t da = mkdesc(st + wg * 8192, 16, 1024), db = mkdesc(st + 16384, 8192, 1024);
                    wg_fence();
#pragma unroll
                    for (int ks = 0; ks < 4; ks++) wgmma_n128(acc, da + ks * 2, db + ks * 128, 1);
                    wg_commit();
                    wg_wait0();
                    if (lane == 0) mbar_arrive(bars + B_EMPTY + pp.stage * 8);
                    pipe_next(pp);
                }
            }
            CTR(4);
            if (type == J_UP2) {
                mbar_wait(bars + B_STGFREE + wg * 8, stg_phase); stg_phase ^= 1;
#pragma unroll
                for (int j = 0; j < 4; j++) {
                    uint32_t r[4];
#pragma unroll
                    for (int q = 0; q < 4; q++) {
                        const uint32_t gw = pack2(acc[8 * j + 2 * q], acc[8 * j + 2 * q + 1]);
                        const uint32_t uw = pack2(acc[32 + 8 * j + 2 * q], acc[32 + 8 * j + 2 * q + 1]);
                        r[q] = hmul2(pack2(gelu_tanh(bflo(gw)), gelu_tanh(bfhi(gw))), uw);
                    }
                    stsm4(stg_base + (sx ^ (j << 5)), r[0], r[1], r[2], r[3]);
                }
            } else {
                mbar_wait(bars + B_FULL + pp.stage * 8, pp.phase);
                const uint32_t st = sb + pp.stage * W_STAGE;
                mbar_wait(bars + B_STGFREE + wg * 8, stg_phase); stg_phase ^= 1;
                const uint32_t* gb = (const uint32_t*)(g_mod + 5 * D_ + (ksplit ? cb >> 1 : cb) * 64) + t;
                const uint32_t xa = st + (ksplit ? 0 : wg * 8192) + (wl * 16 + g) * 128 + (g << 4) + t * 4;
#pragma unroll
                for (int j = 0; j < 4; j++) {
                    uint32_t r[4];
#pragma unroll
                    for (int q = 0; q < 4; q++) {
                        const int nt = 2 * j + (q >> 1);
                        const uint32_t xw = lds32((xa ^ ((nt & 7) << 4)) + (nt >> 3) * 16384 + (q & 1) * 1024);
                        r[q] = hadd2(xw, hmul2(__ldcg(gb + nt * 4), pack2(acc[8 * j + 2 * q], acc[8 * j + 2 * q + 1])));
                    }
                    stsm4(stg_base + (j >> 2) * 8192 + (sx ^ ((2 * j & 7) << 4)), r[0], r[1], r[2], r[3]);
                }
                __syncwarp();
                if (lane == 0) mbar_arrive(bars + B_EMPTY + pp.stage * 8);
                pipe_next(pp);
            }
            fence_async_smem();
            CTR(5);
            bar_arrive(NB_ST + wg, 160);
            continue;
        }
        float acc[128];
#pragma unroll
        for (int i = 0; i < 128; i++) acc[i] = 0.f;
        const int nk = type == J_O ? o_nk(rb) : 8;
#pragma unroll 1
        for (int kb = 0; kb < nk; kb++) {
            if (kb) mbar_wait(bars + B_FULL + pp.stage * 8, pp.phase);
            const uint32_t st = sb + pp.stage * W_STAGE;
            const uint64_t da = mkdesc(st + wg * 8192, 16, 1024), db = mkdesc(st + 16384, 8192, 1024);
            wg_fence();
#pragma unroll
            for (int ks = 0; ks < 4; ks++) wgmma_n256(acc, da + ks * 2, db + ks * 128, 1);
            wg_commit();
            wg_wait0();
            if (lane == 0) mbar_arrive(bars + B_EMPTY + pp.stage * 8);
            pipe_next(pp);
        }
        CTR(4);
        if (type == J_QA) {
            uint32_t qf[64];
#pragma unroll
            for (int i = 0; i < 64; i++) qf[i] = pack2(acc[2 * i], acc[2 * i + 1]);
            const int sg = warp >> 1, half = warp & 1;
            const float sc = 0.08838834764831845f * 1.4426950408889634f;
            const uint32_t xoff = (sg >> 1) * 8192 + ((sg & 1) * 32 + l7) * 128;
            const uint32_t moff = 32768 + (sg * 8 + l7) * 128;
            const uint32_t kch = (l8 ^ l7) << 4;
            const uint32_t vch = ((l8 & 1) ^ l7) << 4;
            if (rb == NRB - 1 && (cb & 1)) {
#pragma unroll
                for (int i = 0; i < 32; i++) qf[i] = qf[32 + i];
            }
#pragma unroll 1
            for (int hh = rb == NRB - 1; hh < 2; hh++) {
                mbar_wait(bars + B_FULL + pp.stage * 8, pp.phase);
                uint32_t st = sb + pp.stage * W_STAGE;
                float sa[5][4];
#pragma unroll
                for (int n = 0; n < 5; n++) sa[n][0] = sa[n][1] = sa[n][2] = sa[n][3] = 0.f;
#pragma unroll
                for (int i = 0; i < 4; i++) {
                    const uint32_t* q = qf + i * 8;
                    uint32_t kk[5][4];
                    ldsm4(kk[0][0], kk[0][1], kk[0][2], kk[0][3], st + moff + (i >> 1) * 4096 + (kch ^ ((i & 1) * 64)));
#pragma unroll
                    for (int n = 1; n < 5; n++)
                        ldsm4(kk[n][0], kk[n][1], kk[n][2], kk[n][3], st + xoff + (n - 1) * 1024 + (i >> 1) * 16384 + (kch ^ ((i & 1) * 64)));
#pragma unroll
                    for (int n = 0; n < 5; n++) mma16816(sa[n], q[0], q[1], q[2], q[3], kk[n][0], kk[n][1]);
#pragma unroll
                    for (int n = 0; n < 5; n++) mma16816(sa[n], q[4], q[5], q[6], q[7], kk[n][2], kk[n][3]);
                }
                __syncwarp();
                if (lane == 0) mbar_arrive(bars + B_EMPTY + pp.stage * 8);
                pipe_next(pp);
                const int iq0 = half * 16 + g - 2 * t, iq1 = iq0 + 8;
                float m0 = fmaxf(sa[0][0], sa[0][1]), m1 = fmaxf(sa[0][2], sa[0][3]);
#pragma unroll
                for (int n = 1; n < 5; n++) {
#pragma unroll
                    for (int e = 0; e < 2; e++) {
                        const int jx = (n - 1) * 8 + e;
                        if (jx > iq0) sa[n][e] = -3.0e38f;
                        if (jx > iq1) sa[n][2 + e] = -3.0e38f;
                        m0 = fmaxf(m0, sa[n][e]); m1 = fmaxf(m1, sa[n][2 + e]);
                    }
                }
                m0 = fmaxf(m0, __shfl_xor_sync(~0u, m0, 1)); m1 = fmaxf(m1, __shfl_xor_sync(~0u, m1, 1));
                m0 = fmaxf(m0, __shfl_xor_sync(~0u, m0, 2)); m1 = fmaxf(m1, __shfl_xor_sync(~0u, m1, 2));
                m0 *= -sc; m1 *= -sc;
                float l0 = 0.f, l1 = 0.f;
                uint32_t p0[5], p1[5];
#pragma unroll
                for (int n = 0; n < 5; n++) {
                    const float e0 = ex2(fmaf(sa[n][0], sc, m0)), e1 = ex2(fmaf(sa[n][1], sc, m0));
                    const float e2 = ex2(fmaf(sa[n][2], sc, m1)), e3 = ex2(fmaf(sa[n][3], sc, m1));
                    l0 += e0 + e1; l1 += e2 + e3;
                    p0[n] = pack2(e0, e1); p1[n] = pack2(e2, e3);
                }
                l0 += __shfl_xor_sync(~0u, l0, 1); l1 += __shfl_xor_sync(~0u, l1, 1);
                l0 += __shfl_xor_sync(~0u, l0, 2); l1 += __shfl_xor_sync(~0u, l1, 2);
                const float i0 = __fdividef(1.f, l0), i1 = __fdividef(1.f, l1);
                mbar_wait(bars + B_FULL + pp.stage * 8, pp.phase);
                st = sb + pp.stage * W_STAGE;
                mbar_wait(bars + B_STGFREE + wg * 8, stg_phase); stg_phase ^= 1;
#pragma unroll
                for (int i = 0; i < 32; i++) qf[i] = qf[32 + i];
#pragma unroll 1
                for (int bx = 0; bx < 2; bx++) {
                    float o[8][4];
                    uint32_t vm[8], v0[4][4], v1[4][4];
#pragma unroll
                    for (int ep = 0; ep < 4; ep++) {
                        ldsm2t(vm[2 * ep], vm[2 * ep + 1], st + moff + bx * 4096 + (vch ^ (ep << 5)));
                        const uint32_t va = st + xoff + (l8 >> 1) * 1024 + bx * 16384 + (vch ^ (ep << 5));
                        ldsm4t(v0[ep][0], v0[ep][1], v0[ep][2], v0[ep][3], va);
                        ldsm4t(v1[ep][0], v1[ep][1], v1[ep][2], v1[ep][3], va + 2048);
                    }
#pragma unroll
                    for (int n = 0; n < 8; n++) { o[n][0] = o[n][1] = o[n][2] = o[n][3] = 0.f; mma16816(o[n], p0[0], p1[0], p0[1], p1[1], vm[n], v0[n >> 1][n & 1]); }
#pragma unroll
                    for (int n = 0; n < 8; n++) mma16816(o[n], p0[2], p1[2], p0[3], p1[3], v0[n >> 1][2 + (n & 1)], v1[n >> 1][n & 1]);
#pragma unroll
                    for (int n = 0; n < 8; n++) mma1688(o[n], p0[4], p1[4], v1[n >> 1][2 + (n & 1)]);
#pragma unroll
                    for (int ep = 0; ep < 4; ep++)
                        stsm4(stg_base + bx * 8192 + (sx ^ (ep << 5)),
                              pack2(o[2 * ep][0] * i0, o[2 * ep][1] * i0), pack2(o[2 * ep][2] * i1, o[2 * ep][3] * i1),
                              pack2(o[2 * ep + 1][0] * i0, o[2 * ep + 1][1] * i0), pack2(o[2 * ep + 1][2] * i1, o[2 * ep + 1][3] * i1));
                }
                __syncwarp();
                if (lane == 0) mbar_arrive(bars + B_EMPTY + pp.stage * 8);
                pipe_next(pp);
                if (hh == 0) { fence_async_smem(); bar_arrive(NB_ST + wg, 160); }
            }
        } else if (type == J_UP) {
            mbar_wait(bars + B_STGFREE + wg * 8, stg_phase); stg_phase ^= 1;
#pragma unroll
            for (int j = 0; j < 8; j++) {
                uint32_t r[4];
#pragma unroll
                for (int q = 0; q < 4; q++) {
                    const uint32_t gw = pack2(acc[8 * j + 2 * q], acc[8 * j + 2 * q + 1]);
                    const uint32_t uw = pack2(acc[64 + 8 * j + 2 * q], acc[64 + 8 * j + 2 * q + 1]);
                    r[q] = hmul2(pack2(gelu_tanh(bflo(gw)), gelu_tanh(bfhi(gw))), uw);
                }
                stsm4(stg_base + (j >> 2) * 8192 + (sx ^ ((2 * j & 7) << 4)), r[0], r[1], r[2], r[3]);
            }
        } else {
#pragma unroll
            for (int rd = 0; rd < 2; rd++) {
                mbar_wait(bars + B_STGFREE + wg * 8, stg_phase); stg_phase ^= 1;
#pragma unroll
                for (int j = rd * 8; j < rd * 8 + 8; j++)
                    stsm4(stg_base + ((j >> 2) & 1) * 8192 + (sx ^ ((2 * j & 7) << 4)),
                          pack2(acc[8 * j], acc[8 * j + 1]), pack2(acc[8 * j + 2], acc[8 * j + 3]),
                          pack2(acc[8 * j + 4], acc[8 * j + 5]), pack2(acc[8 * j + 6], acc[8 * j + 7]));
                if (rd == 0) { fence_async_smem(); bar_arrive(NB_ST + wg, 160); }
            }
        }
        fence_async_smem();
        CTR(5);
        bar_arrive(NB_ST + wg, 160);
    }
}

__global__ void __launch_bounds__(384, 1) k_work(const __grid_constant__ Params p) {
    extern __shared__ __align__(1024) unsigned char smem_raw[];
    const uint32_t sb = smem_u32(smem_raw);
    if (sb & 1023) __trap();
    const int warp = __shfl_sync(~0u, threadIdx.x >> 5, 0);
    int lane; asm volatile("mov.u32 %0, %%laneid;" : "=r"(lane));
    if (threadIdx.x == 0) {
        const uint32_t bars = sb + SM_BAR;
        for (int i = 0; i < W_NST; i++) { mbar_init(bars + B_FULL + i * 8, 1); mbar_init(bars + B_EMPTY + i * 8, 8); }
        mbar_init(bars + B_STGFREE, 1); mbar_init(bars + B_STGFREE + 8, 1); mbar_init(bars + B_REQ, 1); mbar_init(bars + B_RSP, 1);
        asm volatile("fence.mbarrier_init.release.cluster;" ::: "memory");
    }
    __syncthreads();
    if (warp < 8) {
        asm volatile("setmaxnreg.inc.sync.aligned.u32 224;");
        consumer(p, sb, warp, lane);
    } else {
        asm volatile("setmaxnreg.dec.sync.aligned.u32 56;");
        if (warp == 8) { if (lane == 0) producer(p, sb); }
        else if (warp < 11) store_warp(p, sb, warp - 9, lane);
        else scheduler(p, sb, lane);
        __syncwarp();
        bar_sync(NB_W0, 128);
        if (warp == 8 && p.qmask == 0xff) {
            unsigned last = 0;
            if (lane == 0) { __threadfence(); last = atomicAdd(&g_flags[F_DONE], 1u) == gridDim.x - 1; }
            if (__shfl_sync(~0u, last, 0))
                for (int i = lane; i < F_TOTAL; i += 32) g_flags[i] = 0;
        }
    }
}

typedef CUresult (*EncodeFn)(CUtensorMap*, CUtensorMapDataType, cuuint32_t, void*, const cuuint64_t*, const cuuint64_t*,
                             const cuuint32_t*, const cuuint32_t*, CUtensorMapInterleave, CUtensorMapSwizzle,
                             CUtensorMapL2promotion, CUtensorMapFloatOOBfill);

static void make_map(EncodeFn enc, CUtensorMap* m, const void* ptr, uint64_t rows, uint64_t cols, uint32_t box_rows) {
    cuuint64_t dims[2] = {cols, rows};
    cuuint64_t strides[1] = {cols * 2};
    cuuint32_t box[2] = {64, box_rows};
    cuuint32_t es[2] = {1, 1};
    enc(m, CU_TENSOR_MAP_DATA_TYPE_BFLOAT16, 2, const_cast<void*>(ptr), dims, strides, box, es, CU_TENSOR_MAP_INTERLEAVE_NONE,
        CU_TENSOR_MAP_SWIZZLE_128B, CU_TENSOR_MAP_L2_PROMOTION_L2_256B, CU_TENSOR_MAP_FLOAT_OOB_FILL_NONE);
}
template <typename T> static void* sym_addr(T& sym) { void* p = nullptr; cudaGetSymbolAddress(&p, sym); return p; }

extern "C" void kernel_launch(void* const* d_in, const int* in_sizes, int n_in, void* d_out, int out_size) {
    static Params prm;
    static RecParams rp;
    static int n_sm = 132;
    static bool ready = false;
    static const void* key[14];
    bool same = ready;
    for (int i = 0; i < 13 && same; i++) same = key[i] == d_in[i];
    same = same && key[13] == d_out;
    if (!same) {
        void* fn = nullptr;
        cudaDriverEntryPointQueryResult qr;
        cudaGetDriverEntryPoint("cuTensorMapEncodeTiled", &fn, cudaEnableDefault, &qr);
        EncodeFn enc = (EncodeFn)fn;
        make_map(enc, &prm.tm_h, sym_addr(g_h), S_, D_, 64);
        make_map(enc, &prm.tm_kv, sym_addr(g_kv), S_, 2 * HD_, 64);
        make_map(enc, &prm.tm_kvm, sym_addr(g_kvm), NSEG * 8, 2 * HD_, 32);
        make_map(enc, &prm.tm_o, sym_addr(g_o), S_, HD_, 64);
        make_map(enc, &prm.tm_op, sym_addr(g_op), OP_ROWS, D_, 64);
        make_map(enc, &prm.tm_h2, sym_addr(g_h2), S_, D_, 64);
        make_map(enc, &prm.tm_act, sym_addr(g_act), S_, DF_, 64);
        make_map(enc, &prm.tm_x1, sym_addr(g_x1), S_, D_, 64);
        make_map(enc, &prm.tm_out, d_out, S_, D_, 64);
        make_map(enc, &prm.tm_wq, d_in[2], D_, HD_, 64);
        make_map(enc, &prm.tm_wk, d_in[3], D_, HD_, 64);
        make_map(enc, &prm.tm_wv, d_in[4], D_, HD_, 64);
        make_map(enc, &prm.tm_wo, d_in[5], HD_, D_, 64);
        make_map(enc, &prm.tm_wg, d_in[8], D_, DF_, 64);
        make_map(enc, &prm.tm_wu, d_in[9], D_, DF_, 64);
        make_map(enc, &prm.tm_wd, d_in[10], DF_, D_, 64);
        prm.x = (const bf16*)d_in[0]; prm.c = (const bf16*)d_in[11]; prm.w_mod = (const bf16*)d_in[12];
        rp.mem0 = (const bf16*)d_in[1]; rp.x = prm.x; rp.c = prm.c; rp.w_mod = prm.w_mod;
        rp.wq = (const bf16*)d_in[2]; rp.wk = (const bf16*)d_in[3]; rp.wv = (const bf16*)d_in[4]; rp.wo = (const bf16*)d_in[5];
        cudaDeviceGetAttribute(&n_sm, cudaDevAttrMultiProcessorCount, 0);
        cudaFuncSetAttribute(k_work, cudaFuncAttributeMaxDynamicSharedMemorySize, SMEM_BYTES);
        cudaFuncSetAttribute(k_rec, cudaFuncAttributeMaxDynamicSharedMemorySize, R_SMEM);
        cudaFuncSetAttribute(k_rec, cudaFuncAttributeNonPortableClusterSizeAllowed, 1);
        {
            cudaLaunchConfig_t cfg = {};
            cfg.gridDim = dim3(128); cfg.blockDim = dim3(384); cfg.dynamicSmemBytes = R_SMEM;
            cudaLaunchAttribute at[1];
            at[0].id = cudaLaunchAttributeClusterDimension; at[0].val.clusterDim.x = 16; at[0].val.clusterDim.y = 1; at[0].val.clusterDim.z = 1;
            cfg.attrs = at; cfg.numAttrs = 1;
            int n = 0;
            cudaOccupancyMaxActiveClusters(&n, k_rec, &cfg);
            rp.ncl = n < 4 ? 4 : (n > 8 ? 8 : n);
        }
        for (int i = 0; i < 13; i++) key[i] = d_in[i];
        key[13] = d_out;
        ready = true;
    }
    cudaStream_t st = cudaStreamPerThread;
    auto launch_rec = [&]() {
        cudaLaunchConfig_t cfg = {};
        cfg.gridDim = dim3(16 * rp.ncl); cfg.blockDim = dim3(384); cfg.dynamicSmemBytes = R_SMEM; cfg.stream = st;
        cudaLaunchAttribute at[1];
        at[0].id = cudaLaunchAttributeClusterDimension; at[0].val.clusterDim.x = 16; at[0].val.clusterDim.y = 1; at[0].val.clusterDim.z = 1;
        cfg.attrs = at; cfg.numAttrs = 1;
        cudaLaunchKernelEx(&cfg, k_rec, rp);
    };
    auto launch_work = [&](int qmask, int pdl) {
        prm.qmask = qmask;
        cudaLaunchConfig_t cfg = {};
        cfg.gridDim = dim3(n_sm); cfg.blockDim = dim3(384); cfg.dynamicSmemBytes = SMEM_BYTES; cfg.stream = st;
        cudaLaunchAttribute at[1];
        at[0].id = cudaLaunchAttributeProgrammaticStreamSerialization; at[0].val.programmaticStreamSerializationAllowed = 1;
        cfg.attrs = at; cfg.numAttrs = pdl;
        cudaLaunchKernelEx(&cfg, k_work, prm);
    };
    launch_rec();
    launch_work(0xff, 1);
}
```

```cpp
#include <cuda_runtime.h>
#include <cuda_bf16.h>
#include <cuda.h>
#include <stdint.h>

typedef __nv_bfloat16 bf16;
#define IDLE_NS 150
#define FLAG_NS 20

constexpr int S_ = 2048, D_ = 512, DH_ = 128, HD_ = 4096, NSEG = 64, DF_ = 1792;
constexpr int NRB = 16;
constexpr int OSPLIT = 4;

__device__ __align__(1024) bf16 g_h[S_ * D_];
__device__ __align__(1024) bf16 g_kv[S_ * 2 * HD_];
__device__ __align__(1024) bf16 g_kvm[NSEG * 8 * 2 * HD_];
__device__ __align__(1024) bf16 g_o[S_ * HD_];
#define FINE_RB_ 12
constexpr int FINE_RB = FINE_RB_;
#define OSPLIT2_ 8
constexpr int OSPLIT2 = OSPLIT2_;
constexpr int OSPLIT3 = 16;
constexpr int OP_ROWS = OSPLIT * S_ + OSPLIT2 * (NRB - FINE_RB) * 128 + OSPLIT3 * 128;
__device__ __align__(1024) bf16 g_op[OP_ROWS * D_];
__device__ __align__(1024) bf16 g_x1[S_ * D_];
__device__ __align__(1024) bf16 g_h2[S_ * D_];
__device__ __align__(1024) bf16 g_act[S_ * DF_];
__device__ __align__(1024) bf16 g_mod[6 * D_];
__device__ uint32_t g_Fraw[131072 + 65536 + 2048];
#define g_F ((uint32_t*)(((uint64_t)g_Fraw + 0x7FFFFull) & ~0x7FFFFull))
constexpr int F_H = 0, F_MEM = 32, F_O = 64, F_OP = 96, F_H2 = 128, F_ACT = 160, F_MOD = 192, F_KV = 224, F_CLAIM = 256  ,
              F_SIDE = 512  , F_DONE = 576, F_TOTAL = 608;
__device__ __align__(128) unsigned int g_flags[F_TOTAL];
#define TR(j, i) do {} while (0)

__device__ __forceinline__ uint32_t smem_u32(const void* p) { return (uint32_t)__cvta_generic_to_shared(p); }
__device__ __forceinline__ uint32_t clk32() { uint32_t c; asm volatile("mov.u32 %0, %%clock;" : "=r"(c)); return c; }
__device__ __forceinline__ uint32_t mapa_u32(uint32_t addr, uint32_t rank) {
    uint32_t r; asm volatile("mapa.shared::cluster.u32 %0, %1, %2;" : "=r"(r) : "r"(addr), "r"(rank)); return r;
}
__device__ __forceinline__ void mbar_init(uint32_t bar, uint32_t cnt) {
    asm volatile("mbarrier.init.shared::cta.b64 [%0], %1;" :: "r"(bar), "r"(cnt) : "memory");
}
__device__ __forceinline__ void mbar_expect_tx(uint32_t bar, uint32_t bytes) {
    asm volatile("mbarrier.arrive.expect_tx.shared::cta.b64 _, [%0], %1;" :: "r"(bar), "r"(bytes) : "memory");
}
__device__ __forceinline__ void mbar_arrive(uint32_t bar) {
    asm volatile("mbarrier.arrive.shared::cta.b64 _, [%0];" :: "r"(bar) : "memory");
}
__device__ __forceinline__ bool mbar_try_wait(uint32_t bar, uint32_t parity) {
    uint32_t ok;
    asm volatile("{\n.reg .pred p;\nmbarrier.try_wait.parity.shared::cta.b64 p, [%1], %2;\nselp.u32 %0, 1, 0, p;\n}"
                 : "=r"(ok) : "r"(bar), "r"(parity) : "memory");
    return ok;
}
constexpr int SPIN_LIMIT = 1 << 18;
#define TIMEOUT(code, info) do {} while (0)
__device__ __forceinline__ void mbar_wait(uint32_t bar, uint32_t parity) {
    int g = 0;
#pragma unroll 1
    while (!mbar_try_wait(bar, parity)) { if (++g >= SPIN_LIMIT) { TIMEOUT(0, bar & 255); break; } }
}
__device__ __forceinline__ void bar_sync(int id, int n) { asm volatile("bar.sync %0, %1;" :: "r"(id), "r"(n) : "memory"); }
__device__ __forceinline__ void bar_arrive(int id, int n) { asm volatile("bar.arrive %0, %1;" :: "r"(id), "r"(n) : "memory"); }
__device__ __forceinline__ void st_async_v2(uint32_t addr, float a, float b, uint32_t bar) {
    asm volatile("st.async.weak.shared::cluster.mbarrier::complete_tx::bytes.v2.f32 [%0], {%1,%2}, [%3];"
                 :: "r"(addr), "f"(a), "f"(b), "r"(bar) : "memory");
}
__device__ __forceinline__ void st_async_v4(uint32_t addr, uint4 v, uint32_t bar) {
    asm volatile("st.async.weak.shared::cluster.mbarrier::complete_tx::bytes.v4.b32 [%0], {%1,%2,%3,%4}, [%5];"
                 :: "r"(addr), "r"(v.x), "r"(v.y), "r"(v.z), "r"(v.w), "r"(bar) : "memory");
}
__device__ __forceinline__ void stg_relaxed32(uint32_t* p, uint32_t v) {
    asm volatile("st.relaxed.gpu.global.b32 [%0], %1;" :: "l"(p), "r"(v) : "memory");
}
__device__ __forceinline__ uint32_t ldg_relaxed32(const uint32_t* p) {
    uint32_t v; asm volatile("ld.relaxed.gpu.global.b32 %0, [%1];" : "=r"(v) : "l"(p) : "memory"); return v;
}
__device__ __forceinline__ unsigned int ld_acquire(const unsigned int* p) {
    unsigned int v; asm volatile("ld.acquire.gpu.global.u32 %0, [%1];" : "=r"(v) : "l"(p) : "memory"); return v;
}
__device__ __forceinline__ void red_release(unsigned int* p, unsigned int v) {
    asm volatile("red.release.gpu.global.add.u32 [%0], %1;" :: "l"(p), "r"(v) : "memory");
}
__device__ __forceinline__ void wait_flag(int idx, unsigned int target) {
    const unsigned int* p = &g_flags[idx];
    int g = 0;
#pragma unroll 1
    while (ld_acquire(p) < target) { __nanosleep(FLAG_NS); if (++g >= 64 * SPIN_LIMIT) { TIMEOUT(2, idx); break; } }
}
__device__ __forceinline__ void cp_async16(uint32_t dst, const void* src) {
    asm volatile("cp.async.cg.shared.global [%0], [%1], 16;" :: "r"(dst), "l"(src) : "memory");
}
__device__ __forceinline__ void cp_async_commit() { asm volatile("cp.async.commit_group;" ::: "memory"); }
template <int N> __device__ __forceinline__ void cp_async_wait() { asm volatile("cp.async.wait_group %0;" :: "n"(N) : "memory"); }
__device__ __forceinline__ void ldsm4(uint32_t& r0, uint32_t& r1, uint32_t& r2, uint32_t& r3, uint32_t addr) {
    asm volatile("ldmatrix.sync.aligned.m8n8.x4.shared.b16 {%0,%1,%2,%3}, [%4];" : "=r"(r0), "=r"(r1), "=r"(r2), "=r"(r3) : "r"(addr) : "memory");
}
__device__ __forceinline__ void ldsm4t(uint32_t& r0, uint32_t& r1, uint32_t& r2, uint32_t& r3, uint32_t addr) {
    asm volatile("ldmatrix.sync.aligned.m8n8.x4.trans.shared.b16 {%0,%1,%2,%3}, [%4];" : "=r"(r0), "=r"(r1), "=r"(r2), "=r"(r3) : "r"(addr) : "memory");
}
__device__ __forceinline__ void ldsm2t(uint32_t& r0, uint32_t& r1, uint32_t addr) {
    asm volatile("ldmatrix.sync.aligned.m8n8.x2.trans.shared.b16 {%0,%1}, [%2];" : "=r"(r0), "=r"(r1) : "r"(addr) : "memory");
}
__device__ __forceinline__ void stsm4(uint32_t addr, uint32_t r0, uint32_t r1, uint32_t r2, uint32_t r3) {
    asm volatile("stmatrix.sync.aligned.m8n8.x4.shared.b16 [%0], {%1,%2,%3,%4};" :: "r"(addr), "r"(r0), "r"(r1), "r"(r2), "r"(r3) : "memory");
}
__device__ __forceinline__ void stsm2t(uint32_t addr, uint32_t r0, uint32_t r1) {
    asm volatile("stmatrix.sync.aligned.m8n8.x2.trans.shared.b16 [%0], {%1,%2};" :: "r"(addr), "r"(r0), "r"(r1) : "memory");
}
__device__ __forceinline__ void mma16816(float* d, uint32_t a0, uint32_t a1, uint32_t a2, uint32_t a3, uint32_t b0, uint32_t b1) {
    asm volatile("mma.sync.aligned.m16n8k16.row.col.f32.bf16.bf16.f32 {%0,%1,%2,%3}, {%4,%5,%6,%7}, {%8,%9}, {%0,%1,%2,%3};"
                 : "+f"(d[0]), "+f"(d[1]), "+f"(d[2]), "+f"(d[3]) : "r"(a0), "r"(a1), "r"(a2), "r"(a3), "r"(b0), "r"(b1));
}
__device__ __forceinline__ void mma1688(float* d, uint32_t a0, uint32_t a1, uint32_t b0) {
    asm volatile("mma.sync.aligned.m16n8k8.row.col.f32.bf16.bf16.f32 {%0,%1,%2,%3}, {%4,%5}, {%6}, {%0,%1,%2,%3};"
                 : "+f"(d[0]), "+f"(d[1]), "+f"(d[2]), "+f"(d[3]) : "r"(a0), "r"(a1), "r"(b0));
}
__device__ __forceinline__ void mma16816h(float* d, uint32_t a0, uint32_t a2, uint32_t b0, uint32_t b1) {
    asm volatile("{\n.reg .b32 ju, jv;\nmma.sync.aligned.m16n8k16.row.col.f32.bf16.bf16.f32 {%0,%1,%2,%3}, {%4,ju,%5,jv}, {%6,%7}, {%0,%1,%2,%3};\n}"
                 : "+f"(d[0]), "+f"(d[1]), "+f"(d[2]), "+f"(d[3]) : "r"(a0), "r"(a2), "r"(b0), "r"(b1));
}
__device__ __forceinline__ void mma1688h(float* d, uint32_t a0, uint32_t b0) {
    asm volatile("{\n.reg .b32 ju;\nmma.sync.aligned.m16n8k8.row.col.f32.bf16.bf16.f32 {%0,%1,%2,%3}, {%4,ju}, {%5}, {%0,%1,%2,%3};\n}"
                 : "+f"(d[0]), "+f"(d[1]), "+f"(d[2]), "+f"(d[3]) : "r"(a0), "r"(b0));
}
__device__ __forceinline__ uint32_t pack2(float lo, float hi) {
    uint32_t r; asm("cvt.rn.bf16x2.f32 %0, %1, %2;" : "=r"(r) : "f"(hi), "f"(lo)); return r;
}
__device__ __forceinline__ float bflo(uint32_t w) { return __uint_as_float(w << 16); }
__device__ __forceinline__ float bfhi(uint32_t w) { return __uint_as_float(w & 0xffff0000u); }
__device__ __forceinline__ float rbf(float x) { return __bfloat162float(__float2bfloat16_rn(x)); }
__device__ __forceinline__ float ex2(float x) { float y; asm("ex2.approx.ftz.f32 %0, %1;" : "=f"(y) : "f"(x)); return y; }
__device__ __forceinline__ void sts128(uint32_t addr, uint4 v) {
    asm volatile("st.shared.v4.b32 [%0], {%1,%2,%3,%4};" :: "r"(addr), "r"(v.x), "r"(v.y), "r"(v.z), "r"(v.w) : "memory");
}
__device__ __forceinline__ uint4 lds128(uint32_t addr) {
    uint4 v; asm volatile("ld.shared.v4.b32 {%0,%1,%2,%3}, [%4];" : "=r"(v.x), "=r"(v.y), "=r"(v.z), "=r"(v.w) : "r"(addr) : "memory"); return v;
}
__device__ __forceinline__ float2 lds64f(uint32_t addr) {
    float2 v; asm volatile("ld.shared.v2.f32 {%0,%1}, [%2];" : "=f"(v.x), "=f"(v.y) : "r"(addr) : "memory"); return v;
}
__device__ __forceinline__ float lds32f(uint32_t addr) {
    float v; asm volatile("ld.shared.f32 %0, [%1];" : "=f"(v) : "r"(addr) : "memory"); return v;
}
__device__ __forceinline__ uint32_t lds32(uint32_t addr) {
    uint32_t v; asm volatile("ld.shared.b32 %0, [%1];" : "=r"(v) : "r"(addr) : "memory"); return v;
}
__device__ __forceinline__ void sts32(uint32_t addr, uint32_t v) { asm volatile("st.shared.b32 [%0], %1;" :: "r"(addr), "r"(v) : "memory"); }
__device__ __forceinline__ void sts64f(uint32_t addr, float a, float b) { asm volatile("st.shared.v2.f32 [%0], {%1,%2};" :: "r"(addr), "f"(a), "f"(b) : "memory"); }

__device__ __forceinline__ void tma_load2d(uint32_t dst, const CUtensorMap* tm, int c0, int c1, uint32_t bar) {
    asm volatile("cp.async.bulk.tensor.2d.shared::cluster.global.mbarrier::complete_tx::bytes [%0], [%1, {%3, %4}], [%2];"
                 :: "r"(dst), "l"(tm), "r"(bar), "r"(c0), "r"(c1) : "memory");
}
__device__ __forceinline__ void tma_store2d(const CUtensorMap* tm, uint32_t src, int c0, int c1) {
    asm volatile("cp.async.bulk.tensor.2d.global.shared::cta.bulk_group [%0, {%2, %3}], [%1];"
                 :: "l"(tm), "r"(src), "r"(c0), "r"(c1) : "memory");
}
__device__ __forceinline__ void bulk_commit() { asm volatile("cp.async.bulk.commit_group;" ::: "memory"); }
__device__ __forceinline__ void bulk_wait0() { asm volatile("cp.async.bulk.wait_group 0;" ::: "memory"); }
__device__ __forceinline__ void fence_async_smem() { asm volatile("fence.proxy.async.shared::cta;" ::: "memory"); }
__device__ __forceinline__ void fence_async_all() { asm volatile("fence.proxy.async;" ::: "memory"); }

__device__ __forceinline__ void wg_fence() { asm volatile("wgmma.fence.sync.aligned;" ::: "memory"); }
__device__ __forceinline__ void wg_commit() { asm volatile("wgmma.commit_group.sync.aligned;" ::: "memory"); }
__device__ __forceinline__ void wg_wait0() { asm volatile("wgmma.wait_group.sync.aligned 0;" ::: "memory"); }
__device__ __forceinline__ uint64_t mkdesc(uint32_t saddr, uint32_t lbo, uint32_t sbo) {
    return (uint64_t)((saddr & 0x3FFFF) >> 4) | ((uint64_t)(lbo >> 4) << 16) | ((uint64_t)(sbo >> 4) << 32) | (1ull << 62);
}
#define ACC8(i) "+f"(d[i]), "+f"(d[i + 1]), "+f"(d[i + 2]), "+f"(d[i + 3]), "+f"(d[i + 4]), "+f"(d[i + 5]), "+f"(d[i + 6]), "+f"(d[i + 7])
__device__ __forceinline__ void wgmma_n256(float* d, uint64_t da, uint64_t db, int scale_d) {
    asm volatile(
        "{\n.reg .pred p;\nsetp.ne.b32 p, %130, 0;\n"
        "wgmma.mma_async.sync.aligned.m64n256k16.f32.bf16.bf16 "
        "{%0,%1,%2,%3,%4,%5,%6,%7,%8,%9,%10,%11,%12,%13,%14,%15,%16,%17,%18,%19,%20,%21,%22,%23,%24,%25,%26,%27,%28,%29,%30,%31,"
        "%32,%33,%34,%35,%36,%37,%38,%39,%40,%41,%42,%43,%44,%45,%46,%47,%48,%49,%50,%51,%52,%53,%54,%55,%56,%57,%58,%59,%60,%61,%62,%63,"
        "%64,%65,%66,%67,%68,%69,%70,%71,%72,%73,%74,%75,%76,%77,%78,%79,%80,%81,%82,%83,%84,%85,%86,%87,%88,%89,%90,%91,%92,%93,%94,%95,"
        "%96,%97,%98,%99,%100,%101,%102,%103,%104,%105,%106,%107,%108,%109,%110,%111,%112,%113,%114,%115,%116,%117,%118,%119,%120,%121,%122,%123,%124,%125,%126,%127}, "
        "%128, %129, p, 1, 1, 0, 1;\n}"
        : ACC8(0), ACC8(8), ACC8(16), ACC8(24), ACC8(32), ACC8(40), ACC8(48), ACC8(56),
          ACC8(64), ACC8(72), ACC8(80), ACC8(88), ACC8(96), ACC8(104), ACC8(112), ACC8(120)
        : "l"(da), "l"(db), "r"(scale_d));
}
__device__ __forceinline__ void wgmma_n128(float* d, uint64_t da, uint64_t db, int scale_d) {
    asm volatile(
        "{\n.reg .pred p;\nsetp.ne.b32 p, %66, 0;\n"
        "wgmma.mma_async.sync.aligned.m64n128k16.f32.bf16.bf16 "
        "{%0,%1,%2,%3,%4,%5,%6,%7,%8,%9,%10,%11,%12,%13,%14,%15,%16,%17,%18,%19,%20,%21,%22,%23,%24,%25,%26,%27,%28,%29,%30,%31,"
        "%32,%33,%34,%35,%36,%37,%38,%39,%40,%41,%42,%43,%44,%45,%46,%47,%48,%49,%50,%51,%52,%53,%54,%55,%56,%57,%58,%59,%60,%61,%62,%63}, "
        "%64, %65, p, 1, 1, 0, 1;\n}"
        : ACC8(0), ACC8(8), ACC8(16), ACC8(24), ACC8(32), ACC8(40), ACC8(48), ACC8(56)
        : "l"(da), "l"(db), "r"(scale_d));
}

__device__ __forceinline__ void wgmma_n64(float* d, uint64_t da, uint64_t db) {
    asm volatile(
        "wgmma.mma_async.sync.aligned.m64n64k16.f32.bf16.bf16 "
        "{%0,%1,%2,%3,%4,%5,%6,%7,%8,%9,%10,%11,%12,%13,%14,%15,%16,%17,%18,%19,%20,%21,%22,%23,%24,%25,%26,%27,%28,%29,%30,%31}, "
        "%32, %33, 1, 1, 1, 0, 1;"
        : ACC8(0), ACC8(8), ACC8(16), ACC8(24)
        : "l"(da), "l"(db));
}
__device__ __forceinline__ uint32_t hadd2(uint32_t a, uint32_t b) { uint32_t r; asm("add.rn.bf16x2 %0, %1, %2;" : "=r"(r) : "r"(a), "r"(b)); return r; }
__device__ __forceinline__ uint32_t hsub2(uint32_t a, uint32_t b) { uint32_t r; asm("sub.rn.bf16x2 %0, %1, %2;" : "=r"(r) : "r"(a), "r"(b)); return r; }
__device__ __forceinline__ uint32_t hmul2(uint32_t a, uint32_t b) { uint32_t r; asm("mul.rn.bf16x2 %0, %1, %2;" : "=r"(r) : "r"(a), "r"(b)); return r; }
__device__ __forceinline__ void load_mod8(const bf16* m, int lane, uint32_t* v) {
    const uint4 a = __ldcg((const uint4*)m + lane), b = __ldcg((const uint4*)m + 32 + lane);
    v[0] = a.x; v[1] = a.y; v[2] = a.z; v[3] = a.w; v[4] = b.x; v[5] = b.y; v[6] = b.z; v[7] = b.w;
}
__device__ __forceinline__ void ln_stats(const uint32_t* x, uint32_t& mu2, float& rden) {
    float s = 0.f;
#pragma unroll
    for (int i = 0; i < 8; i++) s += bflo(x[i]) + bfhi(x[i]);
#pragma unroll
    for (int o = 16; o > 0; o >>= 1) s += __shfl_xor_sync(~0u, s, o);
    const float mean = s * (1.f / D_);
    float q = 0.f;
#pragma unroll
    for (int i = 0; i < 8; i++) { const float d0 = bflo(x[i]) - mean, d1 = bfhi(x[i]) - mean; q = fmaf(d0, d0, q); q = fmaf(d1, d1, q); }
#pragma unroll
    for (int o = 16; o > 0; o >>= 1) q += __shfl_xor_sync(~0u, q, o);
    mu2 = pack2(mean, mean);
    rden = __frcp_rn(rbf(__fsqrt_rn(rbf(rbf(q * (1.f / D_)) + 1e-5f))));
}
__device__ __forceinline__ void ln_apply(const uint32_t* x, uint32_t mu2, float rden, const uint32_t* c1, const uint32_t* sm, uint32_t* r) {
#pragma unroll
    for (int i = 0; i < 8; i++) {
        const uint32_t d = hsub2(x[i], mu2);
        r[i] = hadd2(hmul2(pack2(bflo(d) * rden, bfhi(d) * rden), c1[i]), sm[i]);
    }
}

struct __align__(64) Params {
    CUtensorMap tm_h, tm_kv, tm_kvm, tm_o, tm_op, tm_h2, tm_act, tm_x1, tm_out;
    CUtensorMap tm_wq, tm_wk, tm_wv, tm_wo, tm_wg, tm_wu, tm_wd;
    const bf16 *x, *c, *w_mod;
    int qmask;
};

constexpr int R_NST = 3;
constexpr uint32_t R_WV = 0, R_MEM = 65536, R_KX = 73728, R_VX = R_KX + R_NST * 4096,
                   R_KMS = R_VX + R_NST * 4096  , R_VMS = R_KMS + 1024,
                   R_QS = R_KMS + 4096, R_OS = R_QS + 1024, R_SX = R_OS + 1024, R_BAR = R_SX + 2560,
                   R_RS = 107520  , R_VP = R_RS + 8192  ,
                   R_STG = R_VP + 8192  , R_SMEM = R_STG + 98304;
static_assert((R_KMS & 4095) == 0, "smem");
static_assert(R_BAR + 64 <= R_RS, "smem");
constexpr uint32_t RB_SX = R_BAR, RB_E = R_BAR + 16, RB_A = R_BAR + 24, RB_ROLE = R_BAR + 32, RB_A1 = R_BAR + 40;
constexpr int W_NST = 4;
constexpr uint32_t W_STAGE = 49152, W_STG = W_NST * W_STAGE  , W_END = W_STG + 32768;
constexpr uint32_t SM_BAR = W_END;
constexpr uint32_t SMEM_BYTES = W_END + 1024 + 2048;
constexpr uint32_t B_FULL = 0, B_EMPTY = 32, B_STGFREE = 64, B_REQ = 80, B_RSP = 88, B_NEXT = 96, B_RING = 128;
#define PICK_AHEAD 3

constexpr int NB_X = 11  , NB_Y = 1, NB_M = 5, NB_K = 5, NB_B = 2, NB_C = 3, NB_D = 4, NB_W0 = 6  , NB_ST = 9  ;

__device__ __forceinline__ int pos_of_d(int d) {
    const int rem = d & 31;
    return (d & ~31) + ((rem & 7) >> 1) * 8 + (rem & 1) * 4 + (rem >> 3);
}

#define PROF(i) do {} while (0)
#define PROFG(i) do {} while (0)
#define VK0_ 4
constexpr int VK0 = VK0_;
constexpr int NOFF = 8;
#define POLL_GAP 110

struct RecParams { const bf16 *mem0, *wq, *wk, *wv, *wo, *x, *c, *w_mod; int ncl, only_pre; };

__device__ __forceinline__ void rec_qk(const RecParams& p, const uint32_t sb, const int cta, const int warp, int lane, const int sel) {
    const int crank = cta & 15, cl = cta >> 4, rank = cta & 1;
    const int kh = warp >> 2, aa = warp & 3;
    uint32_t wa[2][16][4];
    const uint32_t stg = sb + R_STG + kh * 32768;
    {
        const int t128 = aa * 32 + lane;
        const int row = (lane >> 4) * 8 + (lane & 7);
        const int ch = t128 & 7;
        const size_t goff = (size_t)kh * 256 * HD_ + cta * 64 + ch * 8;
#pragma unroll 4
        for (int dd = 0; dd < 16; dd++) {
            const int d = dd * 16 + (t128 >> 3), pp = pos_of_d(d);
            cp_async16(sb + R_WV + kh * 32768 + pp * 128 + ((ch ^ (pp & 7)) << 4), p.wv + goff + (size_t)d * HD_);
        }
        cp_async_commit();
#pragma unroll 4
        for (int dd = 0; dd < 16; dd++) {
            const int d = dd * 16 + (t128 >> 3), pp = pos_of_d(d);
            cp_async16(stg + pp * 128 + ((ch ^ (pp & 7)) << 4), p.wq + goff + (size_t)d * HD_);
        }
        cp_async_commit();
        {
            const int i0 = (warp * 32 + lane) * 16, tok = i0 >> 9;
            const uint4 m0 = __ldg((const uint4*)(p.mem0 + i0)), m1 = __ldg((const uint4*)(p.mem0 + i0 + 8));
            const uint32_t mw[8] = {m0.x, m0.y, m0.z, m0.w, m1.x, m1.y, m1.z, m1.w};
#pragma unroll
            for (int e = 0; e < 16; e++) {
                const int pp = pos_of_d((i0 & 511) + e);
                const unsigned short v = (unsigned short)(mw[e >> 1] >> ((e & 1) * 16));
                asm volatile("st.shared.u16 [%0], %1;" :: "r"(sb + R_MEM + (pp >> 3) * 128 + tok * 16 + (pp & 7) * 2), "h"(v) : "memory");
            }
        }
        cp_async_wait<1>();
        bar_sync(NB_W0 + kh, 128);
        const uint32_t fv = row * 128 + (((2 * aa + ((lane >> 3) & 1)) ^ (row & 7)) << 4);
#pragma unroll
        for (int ks = 0; ks < 16; ks++) ldsm4t(wa[0][ks][0], wa[0][ks][1], wa[0][ks][2], wa[0][ks][3], sb + R_WV + kh * 32768 + fv + ks * 2048);
        bar_sync(NB_W0 + kh, 128);
#pragma unroll
        for (int ks = 0; ks < 16; ks++)
            sts128(sb + R_WV + kh * 32768 + (aa * 16 + ks) * 512 + lane * 16, make_uint4(wa[0][ks][0], wa[0][ks][1], wa[0][ks][2], wa[0][ks][3]));
        const uint32_t fo = stg + row * 128 + (((4 * (aa & 1) + ((lane >> 3) & 1)) ^ (row & 7)) << 4);
#pragma unroll 1
        for (int m = 0; m < 2; m++) {
            cp_async_wait<0>();
            bar_sync(NB_W0 + kh, 128);
            if ((aa >> 1) == m) {
#pragma unroll
                for (int ks = 0; ks < 16; ks++) {
                    ldsm4t(wa[0][ks][0], wa[0][ks][1], wa[0][ks][2], wa[0][ks][3], fo + ks * 2048);
                    ldsm4t(wa[1][ks][0], wa[1][ks][1], wa[1][ks][2], wa[1][ks][3], (fo ^ 32) + ks * 2048);
                }
            }
            bar_sync(NB_W0 + kh, 128);
            if (m == 0) {
#pragma unroll 4
                for (int dd = 0; dd < 16; dd++) {
                    const int d = dd * 16 + (t128 >> 3), pp = pos_of_d(d);
                    cp_async16(stg + pp * 128 + ((ch ^ (pp & 7)) << 4), p.wk + goff + (size_t)d * HD_);
                }
                cp_async_commit();
            }
        }
    }
    const uint32_t tab = stg + (aa * 32 + lane) * 16;
    {
        const uint32_t l7 = lane & 7, l8 = lane >> 3, g = lane >> 2, t = lane & 3;
        const uint32_t t0 = l7 * 128 + ((l8 ^ l7) << 4);
        const uint32_t tq = l7 * 128 + (((l8 >> 1) ^ l7) << 4);
        const uint32_t bq = warp >> 1, tp = warp & 1;
        uint4 v;
        v.x = sb + (aa < 2 ? R_QS : R_KMS) + l7 * 128 + (((4 * (aa & 1) + 2 * kh + (l8 & 1)) ^ l7) << 4);
        v.y = sb + R_QS + tq;
        v.z = sb + (warp == 0 ? R_KMS : R_KX + (warp - 1) * 1024) + t0;
        v.w = mapa_u32(sb + R_SX + (rank * 5 + warp) * 256 + lane * 8, crank ^ 1);
        sts128(tab, v);
        sts128(tab + 2048, make_uint4(sb + lane * 16 + R_MEM + kh * 4096, sb + lane * 16 + R_WV + warp * 8192,
                                      sb + lane * 16 + R_VP + warp * 512, sb + lane * 16 + R_VP + 4096 + (warp ^ 4) * 512));
        const uint32_t src = (l8 >> 1) * 8 + l7;
        const uint32_t L = bq * 8 + 2 * tp + (l8 & 1);
        const uint32_t d0 = (crank + ((t >> 1) | (g & 6))) & 15;
        v.x = sb + R_RS + src * 512 + ((L ^ (src & 7)) << 4);
        v.y = mapa_u32(sb + R_MEM + (crank * 4 + bq) * 128 + (4 * tp + 2 * (t & 1) + (g & 1)) * 16, d0);
        v.z = mapa_u32(sb + ((crank & 2) ? RB_A1 : RB_A), d0);
        v.w = lane;
        sts128(tab + 4096, v);
        const uint64_t wr = (uint64_t)(g_F + ((crank * 2 + ((crank ^ (crank >> 3) ^ sel) & 1)) * 1024 + warp * 128 + cl * 32 + lane));
        sts128(tab + 6144, make_uint4((uint32_t)wr, (uint32_t)(wr >> 32), (uint32_t)((((cl + 1) & 3) - cl) * 128), (uint32_t)((((cl + 2) & 3) - cl) * 128)));
        sts32(tab + 8192, (uint32_t)((((cl + 3) & 3) - cl) * 128));
#pragma unroll
        for (int i = 0; i < NOFF; i++)
            sts128(tab + 10240 + i * 2048, make_uint4(wa[i & 1][i >> 1][0], wa[i & 1][i >> 1][1], wa[i & 1][i >> 1][2], wa[i & 1][i >> 1][3]));
    }
    bar_sync(NB_D, 384);
    uint32_t slot_off = 0;
    const uint32_t slot_inc = warp == 0 ? 2048 : 4096, slot_last = warp == 0 ? 2048 : (R_NST - 1) * 4096;
    const uint32_t sx_bar_rem = (sb + RB_SX) ^ (1u << 24);
    uint4 tb = lds128(tab + 2048);
#pragma unroll 1
    for (int s = 0; s < NSEG; s++) {
        if (s > 0) mbar_wait(sb + RB_A, (s - 1) & 1);
        if (warp == 0) { PROF(0); PROFG(13); }
        uint4 ta;
        const uint32_t km_tog = aa >= 2 ? (s & 1) * 2048 : 0;
        {
            float acc[5][4];
#pragma unroll
            for (int c = 0; c < 5; c++) { acc[c][0] = acc[c][1] = acc[c][2] = acc[c][3] = 0.f; }
            uint32_t b[8][4];
            uint4 av[16];
            static_assert(VK0 == 4, "order below assumes the V/O warps cover slices 0,1");
#define QK4(k2) do { \
                mma16816(acc[0], wa[0][2 * (k2)][0], wa[0][2 * (k2)][1], wa[0][2 * (k2)][2], wa[0][2 * (k2)][3], b[k2][0], b[k2][1]); \
                mma16816(acc[1], wa[1][2 * (k2)][0], wa[1][2 * (k2)][1], wa[1][2 * (k2)][2], wa[1][2 * (k2)][3], b[k2][0], b[k2][1]); \
                mma16816(acc[3], wa[0][2 * (k2) + 1][0], wa[0][2 * (k2) + 1][1], wa[0][2 * (k2) + 1][2], wa[0][2 * (k2) + 1][3], b[k2][2], b[k2][3]); \
                mma16816(acc[4], wa[1][2 * (k2) + 1][0], wa[1][2 * (k2) + 1][1], wa[1][2 * (k2) + 1][2], wa[1][2 * (k2) + 1][3], b[k2][2], b[k2][3]); } while (0)
#define V2(k2) do { \
                mma16816(acc[2], av[2 * (k2)].x, av[2 * (k2)].y, av[2 * (k2)].z, av[2 * (k2)].w, b[k2][0], b[k2][1]); \
                mma16816(acv, av[2 * (k2) + 1].x, av[2 * (k2) + 1].y, av[2 * (k2) + 1].z, av[2 * (k2) + 1].w, b[k2][2], b[k2][3]); } while (0)
#define LB(k2) ldsm4(b[k2][0], b[k2][1], b[k2][2], b[k2][3], tb.x + (k2) * 512)
#define LV(k2) do { av[2 * (k2)] = lds128(tb.y + 2 * (k2) * 512); av[2 * (k2) + 1] = lds128(tb.y + (2 * (k2) + 1) * 512); } while (0)
            float acv[4] = {0.f, 0.f, 0.f, 0.f};
            LB(0); LB(1); LB(4); LB(5);
            QK4(0); QK4(1); LV(4); LV(5); QK4(4); QK4(5);
            if (s > 0) mbar_wait(sb + RB_A1, (s - 1) & 1);
            LB(2); LB(3); LB(6); LB(7); ta = lds128(tab);
            V2(4); V2(5); LV(2); LV(3);
            QK4(2); QK4(3); QK4(6); QK4(7);
            LV(6); LV(7);
#pragma unroll
            for (int i = 0; i < 4; i++) { acc[0][i] += acc[3][i]; acc[1][i] += acc[4][i]; }
            const float g0 = kh ? acc[0][0] : acc[1][0], g1 = kh ? acc[0][1] : acc[1][1], g2 = kh ? acc[0][2] : acc[1][2], g3 = kh ? acc[0][3] : acc[1][3];
            sts128(tb.w, make_uint4(__float_as_uint(g0), __float_as_uint(g1), __float_as_uint(g2), __float_as_uint(g3)));
            const float k0 = kh ? acc[1][0] : acc[0][0], k1 = kh ? acc[1][1] : acc[0][1], k2_ = kh ? acc[1][2] : acc[0][2], k3 = kh ? acc[1][3] : acc[0][3];
            if (warp == 0) PROF(1);
            V2(2); V2(3);
            bar_sync(NB_X + aa, 64);
            const uint4 o = lds128(tb.z + 4096);
            V2(6); V2(7);
            stsm2t(ta.x ^ km_tog, pack2(k0 + __uint_as_float(o.x), k1 + __uint_as_float(o.y)), pack2(k2_ + __uint_as_float(o.z), k3 + __uint_as_float(o.w)));
            sts128(tb.z, make_uint4(__float_as_uint(acc[2][0] + acv[0]), __float_as_uint(acc[2][1] + acv[1]), __float_as_uint(acc[2][2] + acv[2]), __float_as_uint(acc[2][3] + acv[3])));
        }
        const uint32_t kb = ta.z + slot_off;
        if (warp == 0) PROF(14);
        bar_sync(NB_B, 256);
        if (warp < 5) {
            uint32_t q[16], k0, k1, k2, k3, k4, k5, k6, k7;
            float sa[4] = {0.f, 0.f, 0.f, 0.f}, sc[4] = {0.f, 0.f, 0.f, 0.f};
            ldsm4(q[0], q[1], q[2], q[3], ta.y);
            ldsm4(k0, k1, k2, k3, kb);
            ldsm4(q[4], q[5], q[6], q[7], ta.y ^ 32);
            ldsm4(q[8], q[9], q[10], q[11], ta.y ^ 64);
            ldsm4(k4, k5, k6, k7, kb ^ 64);
            ldsm4(q[12], q[13], q[14], q[15], ta.y ^ 96);
            mma16816(sa, q[0], q[1], q[2], q[3], k0, k1);
            bar_arrive(NB_Y, 288);
            mma16816(sc, q[4], q[5], q[6], q[7], k2, k3);
            mma16816(sa, q[8], q[9], q[10], q[11], k4, k5);
            mma16816(sc, q[12], q[13], q[14], q[15], k6, k7);
            const float scl = 0.08838834764831845f * 1.4426950408889634f;
            const float r0 = (sa[0] + sc[0]) * scl, r1 = (sa[1] + sc[1]) * scl;
            if (s != NSEG - 1) {
                st_async_v2(ta.w, r0, r1, sx_bar_rem);
                st_async_v2(ta.w ^ (1u << 24), r0, r1, sx_bar_rem ^ (1u << 24));
            }
            if (warp == 0) PROF(2);
        } else if (s > 0 && warp == 7 && lane == 0) {
            mbar_expect_tx(sb + RB_A, 4096);
            mbar_expect_tx(sb + RB_A1, 4096);
        } else if (s > 0 && (s & 3) == 0 && warp == 6) {
            bar_sync(NB_K, 160);
            if (lane == 0) red_release(&g_flags[F_MEM + (s >> 2) - 1], 1);
            __syncwarp();
        }
        if (s == NSEG - 1) {
            const uint4 td = lds128(tab + 6144);
            stg_relaxed32((uint32_t*)(((uint64_t)td.y << 32) | (td.x ^ 0x21000)), 0u);
            break;
        }
        slot_off = slot_off == slot_last ? 0 : slot_off + slot_inc;
        const uint4 tc = lds128(tab + 4096), td = lds128(tab + 6144);
        const uint32_t te = lds32(tab + 8192);
        uint32_t* wr = (uint32_t*)(((uint64_t)td.y << 32) | (td.x ^ ((s & 1) * 0x21000)));
        const uint32_t* r1p = (const uint32_t*)((const char*)wr + (int)td.z);
        const uint32_t* r2p = (const uint32_t*)((const char*)wr + (int)td.w);
        const uint32_t* r3p = (const uint32_t*)((const char*)wr + (int)te);
        const uint32_t tag = ((s >> 1) + 1) & 1;
        mbar_wait(sb + RB_E, s & 1);
        if (warp == 0) PROF(7);
        {
            uint32_t a0, a1, a2, a3, a4, a5, a6, a7;
            ldsm4t(a0, a1, a2, a3, tc.x);
            ldsm4t(a4, a5, a6, a7, tc.x ^ 64);
            const uint32_t one = 0x3F803F80u;
            float d0_[4] = {0.f, 0.f, 0.f, 0.f}, d1_[4] = {0.f, 0.f, 0.f, 0.f};
            mma16816(d0_, a0, a1, a2, a3, one, one);
            mma16816(d1_, a4, a5, a6, a7, one, one);
            const bool t1 = tc.w & 1, t2 = tc.w & 2;
            const float x = t2 ? (t1 ? d1_[2] : d1_[0]) : (t1 ? d0_[2] : d0_[0]);
            const uint32_t own = (__float_as_uint(x) & ~1u) | tag;
            stg_relaxed32(wr, own);
            const uint32_t tq = clk32();
            if (warp == 0) PROF(8);
            PROFG(16 + warp);
            while ((int)(clk32() - tq) < POLL_GAP) {}
            uint32_t f1 = ldg_relaxed32(r1p), f2 = ldg_relaxed32(r2p), f3 = ldg_relaxed32(r3p);
#pragma unroll
            for (int i = 0; i < NOFF; i++) {
                const uint4 f0 = lds128(tab + 10240 + i * 2048);
                wa[i & 1][i >> 1][0] = f0.x; wa[i & 1][i >> 1][1] = f0.y; wa[i & 1][i >> 1][2] = f0.z; wa[i & 1][i >> 1][3] = f0.w;
            }
            tb = lds128(tab + 2048);
            int gg = 0;
#pragma unroll 1
            while (!__all_sync(~0u, (((f1 ^ tag) | (f2 ^ tag) | (f3 ^ tag)) & 1) == 0)) {
                f1 = ldg_relaxed32(r1p); f2 = ldg_relaxed32(r2p); f3 = ldg_relaxed32(r3p);
                if (++gg > 16 * SPIN_LIMIT) { TIMEOUT(3, s); break; }
            }
            if (warp == 0) PROF(9);
            const float v = (__uint_as_float(own) + __uint_as_float(f2)) + (__uint_as_float(f1) + __uint_as_float(f3));
            const bool b8 = tc.w & 8, b16 = tc.w & 16;
            const float recv = __shfl_xor_sync(~0u, v, 8);
            const uint32_t word = b8 ? pack2(recv, v) : pack2(v, recv);
            const uint32_t oth = __shfl_xor_sync(~0u, word, 16);
            const uint32_t wl = b16 ? oth : word, wh = b16 ? word : oth;
            const uint32_t p0 = __shfl_xor_sync(~0u, wl, 2), p1 = __shfl_xor_sync(~0u, wh, 2);
            const uint4 item = t2 ? make_uint4(p0, p1, wl, wh) : make_uint4(wl, wh, p0, p1);
            st_async_v4(tc.y, item, tc.z);
            st_async_v4(tc.y ^ (8u << 24), item, tc.z ^ (8u << 24));
            if (tc.w == 0 && warp == 7) mbar_expect_tx(sb + RB_E, 8192);
            if (warp == 0) PROF(10);
            PROF(40 + warp);
        }
        bar_sync(NB_D, 384);
    }
}

__device__ __forceinline__ void rec_load_kv(uint32_t sb, int col0, int s, uint32_t slot_off, int t128) {
    const int row = t128 >> 2, c2 = (t128 & 3) * 2;
    const bf16* src = g_kv + ((size_t)(s * 32 + row) * (2 * HD_) + col0 + c2 * 8);
    const uint32_t d0 = sb + R_KX + slot_off + row * 128 + ((c2 ^ (row & 7)) << 4);
    cp_async16(d0, src);
    cp_async16(d0 ^ 16, src + 8);
    cp_async16(d0 + (R_VX - R_KX), src + HD_);
    cp_async16((d0 ^ 16) + (R_VX - R_KX), src + HD_ + 8);
}

__device__ __forceinline__ void rec_store_kvm(uint32_t sb, int col0, int s, int w, int lane) {
    const int tok = (w & 1) * 4 + (lane >> 3);
    const uint4 v = lds128(sb + R_KMS + (s & 1) * 2048 + (w >> 1) * 1024 + tok * 128 + (((lane & 7) ^ tok) << 4));
    *(uint4*)(g_kvm + ((s * 8 + tok) * (2 * HD_) + (w >> 1) * HD_ + col0 + (lane & 7) * 8)) = v;
}

__device__ __forceinline__ void rec_vo(const RecParams& p, const uint32_t sb, const int cta, const int warp, int lane) {
    const int w = warp - 8, crank = cta & 15;
    const int col0 = cta * 64;
    uint32_t wo[8][4][4];
    {
        const int t128 = w * 32 + lane;
        const bf16* Wo = p.wo + (size_t)col0 * D_;
        const uint32_t stg = sb + R_STG + 2 * 32768;
#pragma unroll
        for (int half = 0; half < 2; half++) {
#pragma unroll 4
            for (int i = t128; i < 2048; i += 128) {
                const int e = i >> 6, ch = i & 63;
                cp_async16(stg + e * 1024 + ((ch ^ (e & 7)) << 4), Wo + (size_t)(half * 32 + e) * D_ + ch * 8);
            }
            cp_async_commit();
            cp_async_wait<0>();
            bar_sync(NB_W0 + 2, 128);
#pragma unroll
            for (int j = 0; j < 8; j++)
#pragma unroll
                for (int kk = 0; kk < 2; kk++) {
                    const int e = kk * 16 + (lane >> 4) * 8 + (lane & 7);
                    const int ch = (w * 8 + j) * 2 + ((lane >> 3) & 1);
                    ldsm4t(wo[j][half * 2 + kk][0], wo[j][half * 2 + kk][1], wo[j][half * 2 + kk][2], wo[j][half * 2 + kk][3],
                           stg + e * 1024 + ((ch ^ (e & 7)) << 4));
                }
            bar_sync(NB_W0 + 2, 128);
        }
        if (lane == 0) wait_flag(F_KV + 0, 64);
        __syncwarp();
        rec_load_kv(sb, col0, 0, 0, t128); cp_async_commit();
        rec_load_kv(sb, col0, 1, 4096, t128); cp_async_commit();
        cp_async_wait<1>();
    }
    const uint32_t tab = sb + R_STG + 2 * 32768 + (w * 32 + lane) * 16;
    {
        const uint32_t l7 = lane & 7, l8 = lane >> 3, g = lane >> 2;
        uint4 v;
        v.x = sb + R_VX + ((l8 & 1) * 8 + l7) * 128 + (((2 * w + (l8 >> 1)) ^ l7) << 4);
        v.y = sb + R_OS + g * 128 + (((2 * w) ^ g) << 4) + (lane & 3) * 4;
        v.z = sb + R_VMS + l7 * 128 + (((2 * w + (l8 & 1)) ^ l7) << 4);
        v.w = sb + R_OS + l7 * 128 + ((l8 ^ l7) << 4);
        sts128(tab, v);
        v.x = mapa_u32(sb + R_RS + crank * 512 + ((lane ^ (crank & 7)) << 4), w * 4);
        v.y = mapa_u32(sb + RB_E, w * 4);
        v.z = sb + R_VP + w * 512 + lane * 16;
        v.w = sb + R_SX + lane * 8;
        sts128(tab + 2048, v);
#pragma unroll
        for (int i = 0; i < 8; i++) sts128(tab + 4096 + i * 2048, make_uint4(wo[i][0][0], wo[i][0][1], wo[i][0][2], wo[i][0][3]));
        const int tok = (w & 1) * 4 + (lane >> 3), row = (w * 32 + lane) >> 2, c2 = (lane & 3) * 2;
        const uint64_t kd = (uint64_t)(g_kvm + (tok * (2 * HD_) + (w >> 1) * HD_ + col0 + (lane & 7) * 8));
        const uint64_t ks = (uint64_t)(g_kv + ((size_t)row * (2 * HD_) + col0 + c2 * 8));
        sts128(tab + 20480, make_uint4((uint32_t)kd, (uint32_t)(kd >> 32), (uint32_t)ks, (uint32_t)(ks >> 32)));
        sts128(tab + 22528, make_uint4(sb + R_KMS + (w >> 1) * 1024 + tok * 128 + (((lane & 7) ^ tok) << 4),
                                       sb + R_KX + row * 128 + ((c2 ^ (row & 7)) << 4), lane, 0));
    }
    bar_sync(NB_D, 384);
    const uint32_t lane16 = lds32(tab + 2048 + 8) - R_VP - w * 512;
    uint4 av[2 * VK0];
#pragma unroll
    for (int i = 0; i < 2 * VK0; i++) av[i] = lds128(lane16 + R_WV + (i / VK0) * 32768 + (w * 16 + i % VK0) * 512);
    uint32_t slot_off = 0;
#pragma unroll 1
    for (int s = 0; s < NSEG; s++) {
        if (s > 0) {
            mbar_wait(sb + RB_A, (s - 1) & 1);
            const uint4 tp = lds128(tab + 20480), tq = lds128(tab + 22528);
            const uint4 kvm = lds128(tq.x + ((s - 1) & 1) * 2048);
            *(uint4*)((((uint64_t)tp.y << 32) | tp.x) + (uint64_t)(s - 1) * (8 * 2 * HD_ * 2)) = kvm;
            if ((s & 3) == 0) bar_arrive(NB_K, 160);
            if (s + 1 < NSEG - 1) {
                if (((s + 1) & 3) == 0) { if (tq.z == 0) wait_flag(F_KV + ((s + 1) >> 2), 64); __syncwarp(); }
                const char* src = (const char*)((((uint64_t)tp.w << 32) | tp.z) + (uint64_t)(s + 1) * (32 * 2 * HD_ * 2));
                const uint32_t d0 = tq.y + (slot_off == (R_NST - 1) * 4096 ? 0 : slot_off + 4096);
                cp_async16(d0, src);
                cp_async16(d0 ^ 16, src + 16);
                cp_async16(d0 + (R_VX - R_KX), src + HD_ * 2);
                cp_async16((d0 ^ 16) + (R_VX - R_KX), src + HD_ * 2 + 16);
            }
            cp_async_commit();
        }
        bar_sync(NB_Y, 288);
        uint32_t vb0, vb1;
        {
            float va[4] = {0.f, 0.f, 0.f, 0.f}, vc[4] = {0.f, 0.f, 0.f, 0.f};
            uint32_t bb[VK0][4];
#pragma unroll
            for (int k2 = 0; k2 < VK0; k2++) ldsm4(bb[k2][0], bb[k2][1], bb[k2][2], bb[k2][3], lane16 + R_MEM + (k2 / (VK0 / 2)) * 4096 + (k2 % (VK0 / 2)) * 512);
#pragma unroll
            for (int k2 = 0; k2 < VK0; k2++) {
                mma16816(va, av[2 * k2].x, av[2 * k2].y, av[2 * k2].z, av[2 * k2].w, bb[k2][0], bb[k2][1]);
                mma16816(vc, av[2 * k2 + 1].x, av[2 * k2 + 1].y, av[2 * k2 + 1].z, av[2 * k2 + 1].w, bb[k2][2], bb[k2][3]);
            }
            const uint4 a = lds128(lane16 + R_VP + w * 512), b = lds128(lane16 + R_VP + 2048 + w * 512);
            vb0 = pack2((va[0] + vc[0]) + (__uint_as_float(a.x) + __uint_as_float(b.x)), (va[1] + vc[1]) + (__uint_as_float(a.y) + __uint_as_float(b.y)));
            vb1 = pack2((va[2] + vc[2]) + (__uint_as_float(a.z) + __uint_as_float(b.z)), (va[3] + vc[3]) + (__uint_as_float(a.w) + __uint_as_float(b.w)));
        }
        const uint4 ta = lds128(tab), tb = lds128(tab + 2048);
        uint32_t vx[8];
        ldsm4t(vx[0], vx[1], vx[2], vx[3], ta.x + slot_off);
        ldsm4t(vx[4], vx[5], vx[6], vx[7], ta.x + slot_off + 2048);
#pragma unroll
        for (int i = 0; i < 4; i++) {
            const uint4 f0 = lds128(tab + 4096 + i * 2048);
            wo[i][0][0] = f0.x; wo[i][0][1] = f0.y; wo[i][0][2] = f0.z; wo[i][0][3] = f0.w;
        }
        if (w == 0) PROF(11);
        uint32_t pf[5];
        float oa[2][4] = {{0.f, 0.f, 0.f, 0.f}, {0.f, 0.f, 0.f, 0.f}}, ob_[2][4] = {{0.f, 0.f, 0.f, 0.f}, {0.f, 0.f, 0.f, 0.f}};
        float sm0[4] = {0.f, 0.f, 0.f, 0.f}, sm1[4] = {0.f, 0.f, 0.f, 0.f};
        if (s != NSEG - 1) {
            mbar_wait(sb + RB_SX, s & 1);
            if (w == 0) PROF(4);
            float sv[10];
#pragma unroll
            for (int n = 0; n < 5; n++) {
                const float2 a = lds64f(tb.w + n * 256), b = lds64f(tb.w + (5 + n) * 256);
                sv[2 * n] = a.x + b.x; sv[2 * n + 1] = a.y + b.y;
            }
            float mx = fmaxf(fmaxf(fmaxf(sv[0], sv[1]), fmaxf(sv[2], sv[3])), fmaxf(fmaxf(sv[4], sv[5]), fmaxf(sv[6], sv[7])));
            mx = fmaxf(mx, fmaxf(sv[8], sv[9]));
            mx = fmaxf(mx, __shfl_xor_sync(~0u, mx, 1));
            mx = fmaxf(mx, __shfl_xor_sync(~0u, mx, 2));
#pragma unroll
            for (int n = 1; n < 5; n++) pf[n] = pack2(ex2(sv[2 * n] - mx), ex2(sv[2 * n + 1] - mx));
            pf[0] = pack2(ex2(sv[0] - mx), ex2(sv[1] - mx));
            if (w == 0) PROF(12);
            const uint32_t one = 0x3F803F80u;
            mma16816h(sm0, pf[1], pf[2], one, one);
            mma16816h(oa[0], pf[1], pf[2], vx[0], vx[1]);
            mma16816h(oa[1], pf[1], pf[2], vx[2], vx[3]);
            mma16816h(sm1, pf[3], pf[4], one, one);
            mma16816h(ob_[0], pf[3], pf[4], vx[4], vx[5]);
            mma16816h(ob_[1], pf[3], pf[4], vx[6], vx[7]);
            mma1688h(sm0, pf[0], one);
            mma1688h(oa[0], pf[0], vb0);
            mma1688h(oa[1], pf[0], vb1);
            float inv;
            asm("rcp.approx.ftz.f32 %0, %1;" : "=f"(inv) : "f"(sm0[0] + sm1[0]));
            oa[0][0] += ob_[0][0]; oa[0][1] += ob_[0][1]; oa[1][0] += ob_[1][0]; oa[1][1] += ob_[1][1];
            sts32(ta.y, pack2(oa[0][0] * inv, oa[0][1] * inv));
            sts32(ta.y ^ 16, pack2(oa[1][0] * inv, oa[1][1] * inv));
            const uint32_t oa2 = ta.w ^ 64;
            bar_sync(NB_C, 128);
            if (w == 0) PROF(5);
            uint32_t ob[8];
            ldsm4(ob[0], ob[1], ob[2], ob[3], ta.w);
            ldsm4(ob[4], ob[5], ob[6], ob[7], oa2);
#pragma unroll
            for (int i = 4; i < 8; i++) {
                const uint4 f0 = lds128(tab + 4096 + i * 2048);
                wo[i][0][0] = f0.x; wo[i][0][1] = f0.y; wo[i][0][2] = f0.z; wo[i][0][3] = f0.w;
            }
#pragma unroll
            for (int jj = 0; jj < 2; jj++) {
                if (jj == 1 && tb.w == 0) break;
                float acc[4][4];
#pragma unroll
                for (int c = 0; c < 4; c++) { acc[c][0] = acc[c][1] = acc[c][2] = acc[c][3] = 0.f; }
#pragma unroll
                for (int ks = 0; ks < 4; ks++)
#pragma unroll
                    for (int c = 0; c < 4; c++)
                        mma16816(acc[c], wo[jj * 4 + c][ks][0], wo[jj * 4 + c][ks][1], wo[jj * 4 + c][ks][2], wo[jj * 4 + c][ks][3], ob[2 * ks], ob[2 * ks + 1]);
#pragma unroll
                for (int pr = 0; pr < 2; pr++) {
                    uint4 v;
                    v.x = pack2(acc[2 * pr][0], acc[2 * pr][1]);
                    v.y = pack2(acc[2 * pr][2], acc[2 * pr][3]);
                    v.z = pack2(acc[2 * pr + 1][0], acc[2 * pr + 1][1]);
                    v.w = pack2(acc[2 * pr + 1][2], acc[2 * pr + 1][3]);
                    st_async_v4(tb.x + ((jj * 2 + pr) << 24), v, tb.y + ((jj * 2 + pr) << 24));
                }
            }
            if (w == 0) PROF(6);
        }
        stsm2t(ta.z + (s & 1) * 2048, vb0, vb1);
        cp_async_wait<0>();
        bar_sync(NB_C, 128);
        if (w == 0 && lane == 0 && s != NSEG - 1) mbar_expect_tx(sb + RB_SX, 2560);
        if (s != NSEG - 1) bar_arrive(NB_D, 384);
#pragma unroll
        for (int i = 0; i < 2 * VK0; i++) av[i] = lds128(lane16 + R_WV + (i / VK0) * 32768 + (w * 16 + i % VK0) * 512);
        slot_off = slot_off == (R_NST - 1) * 4096 ? 0 : slot_off + 4096;
    }
    rec_store_kvm(sb, col0, NSEG - 1, w, lane);
    bar_sync(NB_C, 128);
    if (w == 0 && lane == 0) red_release(&g_flags[F_MEM + NRB - 1], 1);
}

__global__ void __launch_bounds__(384, 1) k_rec(const RecParams p) {
    extern __shared__ __align__(1024) unsigned char smem_raw[];
    const uint32_t sb = __shfl_sync(~0u, smem_u32(smem_raw), 0);
    const int warp = __shfl_sync(~0u, threadIdx.x >> 5, 0);
    int lane; asm volatile("mov.u32 %0, %%laneid;" : "=r"(lane));
    const int crank = blockIdx.x & 15, slot = blockIdx.x >> 4;
    asm volatile("griddepcontrol.launch_dependents;");
    if (crank == 0 && threadIdx.x == 0) {
        stg_relaxed32(&g_F[65536 + slot * 64], 0u);
        stg_relaxed32(&g_F[65536 + 1024 + slot * 64], 0u);
    }
    if (threadIdx.x == 0) {
        mbar_init(sb + RB_SX, 1); mbar_init(sb + RB_E, 1); mbar_init(sb + RB_A, 1); mbar_init(sb + RB_A1, 1); mbar_init(sb + RB_ROLE, 1);
        asm volatile("fence.mbarrier_init.release.cluster;" ::: "memory");
        mbar_expect_tx(sb + RB_SX, 2560);
        mbar_expect_tx(sb + RB_E, 8192);
        mbar_expect_tx(sb + RB_A, 4096);
        mbar_expect_tx(sb + RB_A1, 4096);
        mbar_expect_tx(sb + RB_ROLE, 4);
    }
    asm volatile("barrier.cluster.arrive.relaxed.aligned;\nbarrier.cluster.wait.aligned;" ::: "memory");
    unsigned role = 0;
    if (crank == 0 && threadIdx.x == 0 && !p.only_pre) {
        unsigned x = 0;
        int tm[2] = {0x7fffffff, 0x7fffffff};
#pragma unroll 1
        for (int i = 0; i < 6; i++) {
            const uint32_t t0 = clk32();
            x = atomicAdd(&g_F[65536 + (i & 1) * 1024 + slot * 64 + (x >> 31)], 1u);
            if (x != (unsigned)(i >> 1)) sts32(sb + R_BAR + 56, x);
            const int dt = (int)(clk32() - t0);
            if (i >= 2) { if (i & 1) tm[1] = min(tm[1], dt); else tm[0] = min(tm[0], dt); }
        }
        const int side = tm[1] > tm[0];
        const unsigned old = atomicAdd(&g_flags[F_SIDE + side * 32], 1u);
        unsigned c0, c1; int gd = 0;
#pragma unroll 1
        do { c0 = ldg_relaxed32(&g_flags[F_SIDE]); c1 = ldg_relaxed32(&g_flags[F_SIDE + 32]); } while ((int)(c0 + c1) < p.ncl && ++gd < 64 * SPIN_LIMIT);
        const int big = c1 > c0;
        role = side == big ? old : (big ? c1 : c0) + old;
        role |= (big ^ 1) << 8;
    }
    __syncwarp();
    if (crank == 0 && warp == 0 && !p.only_pre) {
        role = __shfl_sync(~0u, role, 0);
        if (lane < 16)
            asm volatile("st.async.weak.shared::cluster.mbarrier::complete_tx::bytes.u32 [%0], %1, [%2];"
                         :: "r"(mapa_u32(sb + R_BAR + 48, lane)), "r"(role), "r"(mapa_u32(sb + RB_ROLE, lane)) : "memory");
    }
    if (warp >= 4) {
        const int w8 = warp - 4, nblk = gridDim.x;
        const int cq = lane & 3, rg = w8 * 8 + (lane >> 2);
        const uint32_t red = sb + R_VP;
        const int row0 = blockIdx.x * 8 + w8;
        const uint4* xr = (const uint4*)(p.x + (size_t)row0 * D_);
        uint4 xa = __ldg(xr + lane), xb = __ldg(xr + 32 + lane);
#pragma unroll 1
        for (int sl = blockIdx.x; sl < 96; sl += nblk) {
            uint4 wv[8];
#pragma unroll
            for (int i = 0; i < 8; i++) wv[i] = __ldg((const uint4*)(p.w_mod + (size_t)(rg * 8 + i) * (6 * D_) + sl * 32 + cq * 8));
            const uint32_t cw = __ldg((const uint32_t*)(p.c + rg * 8) + cq);
            const float cl = bflo(cw), ch = bfhi(cw);
            const uint32_t sw = pack2(__fdividef(cl, 1.f + __expf(-cl)), __fdividef(ch, 1.f + __expf(-ch)));
            float a[8];
#pragma unroll
            for (int i = 0; i < 8; i++) a[i] = 0.f;
#pragma unroll
            for (int i = 0; i < 8; i++) {
                const uint32_t sv = __shfl_sync(~0u, sw, (lane & 28) + (i >> 1));
                const float cv = (i & 1) ? bfhi(sv) : bflo(sv);
                a[0] = fmaf(cv, bflo(wv[i].x), a[0]); a[1] = fmaf(cv, bfhi(wv[i].x), a[1]); a[2] = fmaf(cv, bflo(wv[i].y), a[2]); a[3] = fmaf(cv, bfhi(wv[i].y), a[3]);
                a[4] = fmaf(cv, bflo(wv[i].z), a[4]); a[5] = fmaf(cv, bfhi(wv[i].z), a[5]); a[6] = fmaf(cv, bflo(wv[i].w), a[6]); a[7] = fmaf(cv, bfhi(wv[i].w), a[7]);
            }
#pragma unroll
            for (int i = 0; i < 8; i++) { a[i] += __shfl_xor_sync(~0u, a[i], 4); a[i] += __shfl_xor_sync(~0u, a[i], 8); a[i] += __shfl_xor_sync(~0u, a[i], 16); }
            if (lane < 4) {
                sts128(red + w8 * 128 + lane * 32, make_uint4(__float_as_uint(a[0]), __float_as_uint(a[1]), __float_as_uint(a[2]), __float_as_uint(a[3])));
                sts128(red + w8 * 128 + lane * 32 + 16, make_uint4(__float_as_uint(a[4]), __float_as_uint(a[5]), __float_as_uint(a[6]), __float_as_uint(a[7])));
            }
            bar_sync(NB_B, 256);
            if (w8 == 0) {
                float v = 0.f;
#pragma unroll
                for (int i = 0; i < 8; i++) v += lds32f(red + i * 128 + lane * 4);
                g_mod[sl * 32 + lane] = __float2bfloat16_rn(v);
                __syncwarp();
                if (lane == 0) red_release(&g_flags[F_MOD + (sl >= 32)], 1);
            }
            bar_sync(NB_B, 256);
        }
        uint32_t c1[8], sm[8];
        int row = row0;
#pragma unroll 1
        while (true) {
            const uint32_t v[8] = {xa.x, xa.y, xa.z, xa.w, xb.x, xb.y, xb.z, xb.w};
            uint32_t mu2, r[8]; float rden;
            ln_stats(v, mu2, rden);
            if (row == row0) {
                if (lane == 0) wait_flag(F_MOD, 32);
                __syncwarp();
                load_mod8(g_mod + D_, lane, c1);
                load_mod8(g_mod, lane, sm);
#pragma unroll
                for (int i = 0; i < 8; i++) c1[i] = hadd2(c1[i], 0x3F803F80u);
            } else if (row + 512 < S_) {
                xr = (const uint4*)(p.x + (size_t)(row + 512) * D_); xa = __ldg(xr + lane); xb = __ldg(xr + 32 + lane);
            }
            ln_apply(v, mu2, rden, c1, sm, r);
            uint4* hr = (uint4*)(g_h + (size_t)row * D_);
            hr[lane] = make_uint4(r[0], r[1], r[2], r[3]); hr[32 + lane] = make_uint4(r[4], r[5], r[6], r[7]);
            bar_sync(NB_B, 256);
            if (w8 == (row >> 7 & 7) && lane == 0) red_release(&g_flags[F_H + (row >> 7)], 1);
            __syncwarp();
            if (row == row0) {
                if (!p.only_pre) mbar_wait(sb + RB_ROLE, 0);
                const int cl = p.only_pre ? slot : (int)(lds32(sb + R_BAR + 48) & 255);
                row = cl < 4 ? (nblk + cl * 16 + crank) * 8 + w8 : S_;
                if (row < S_) { xr = (const uint4*)(p.x + (size_t)row * D_); xa = __ldg(xr + lane); xb = __ldg(xr + 32 + lane); }
            } else {
                row += 512;
            }
            if (row >= S_) break;
        }
    }
    if (p.only_pre) return;
    mbar_wait(sb + RB_ROLE, 0);
    const int rolew = __shfl_sync(~0u, lds32(sb + R_BAR + 48), 0);
    const int cl = rolew & 255;
    if (cl >= 4) return;
    const int cta = cl * 16 + crank;
    if (warp < 8) rec_qk(p, sb, cta, warp, lane, rolew >> 8);
    else rec_vo(p, sb, cta, warp, lane);
}

enum { J_KV = 0, J_QA = 1, J_O = 2, J_LN = 3, J_UP = 4, J_DN = 5, J_UP2 = 8, J_END = 9 };
constexpr int NJ_O = 2 * OSPLIT, NJ_O2 = 2 * OSPLIT2, NJ_LN = 8, NJ_LN2 = 16, NJ_UP = 14, NJ_UP2 = 28, NJ_DN = 8, NJ_LN1 = 8  ;
constexpr uint64_t pk8(int a, int b, int c, int d, int e, int f, int g, int h) {
    return (uint64_t)a | ((uint64_t)b << 8) | ((uint64_t)c << 16) | ((uint64_t)d << 24) | ((uint64_t)e << 32) | ((uint64_t)f << 40) | ((uint64_t)g << 48) | ((uint64_t)h << 56);
}
constexpr uint64_t NJ_C = pk8(32, 16, NJ_O, NJ_LN, NJ_UP, NJ_DN, 0, 0), NJ_F = pk8(32, 16, NJ_O2, NJ_LN2, NJ_UP2, NJ_DN, 0, 0);
constexpr uint64_t TG_C = pk8(2 * NJ_LN1, 64, 32, 2 * NJ_O, 2 * NJ_LN, 2 * NJ_UP, 32, 0), TG_F = pk8(2 * NJ_LN1, 64, 32, 2 * NJ_O2, 2 * NJ_LN2, 2 * NJ_UP2, 32, 0);
constexpr uint64_t NJ_L = pk8(32, 32, 2 * OSPLIT3, NJ_LN2, NJ_UP2, 2 * NJ_DN, 0, 0), TG_L = pk8(2 * NJ_LN1, 64, 64, 4 * OSPLIT3, 2 * NJ_LN2, 2 * NJ_UP2, 32, 0);
__device__ __forceinline__ uint64_t nj_tab(int rb) { return rb < FINE_RB ? NJ_C : (rb < NRB - 1 ? NJ_F : NJ_L); }
__device__ __forceinline__ uint64_t tg_tab(int rb) { return rb < FINE_RB ? TG_C : (rb < NRB - 1 ? TG_F : TG_L); }
__device__ __forceinline__ int o_nk(int rb) { return rb < FINE_RB ? 64 / OSPLIT : (rb < NRB - 1 ? 64 / OSPLIT2 : 64 / OSPLIT3); }
constexpr uint64_t PRIO = pk8(4, 10, 9, 8, 7, 6, 3, 0);
__device__ __forceinline__ int pick_job(int lane, int qmask, int& idx) {
    const int rb = lane & 15, half = lane >> 4;
    const uint64_t nj = nj_tab(rb) >> (8 * half);
    const uint64_t tg = tg_tab(rb) >> (8 * half);
    const unsigned* cp = &g_flags[F_CLAIM + half * 32 + rb];
    const unsigned* dp = &g_flags[half * 32 + rb];
    int gd = 0;
#pragma unroll 1
    while (true) {
        const unsigned c0 = ldg_relaxed32(cp), c1 = ldg_relaxed32(cp + 64), c2 = ldg_relaxed32(cp + 128);
        const unsigned d0 = ldg_relaxed32(dp - (half && rb ? 1 : 0)), d1 = ldg_relaxed32(dp + 64), d2 = ldg_relaxed32(dp + 128);
        const unsigned cl[3] = {c0, c1, c2}, dv[3] = {d0, d1, d2};
        unsigned key = 0xffffu, key2 = 0xffffu;
        bool pre = false;
#pragma unroll
        for (int i = 0; i < 3; i++) {
            const int q = half + 2 * i;
            const bool have = ((qmask >> q) & 1) && cl[i] < (unsigned)((nj >> (16 * i)) & 255);
            bool ready = have && dv[i] >= (unsigned)((tg >> (16 * i)) & 255);
            unsigned pr = (unsigned)((PRIO >> (8 * q)) & 255);
            if (i == 0 && rb <= 1 - half) ready = have;
            if (i == 0 && half && rb >= FINE_RB) pr = 5;
            if (ready) key = min(key, (pr << 8) | (rb << 4) | q);
            if (have) key2 = min(key2, rb >= FINE_RB ? (0x100u | (q << 4) | rb) : (i == 0 ? 0u : 0x1000u));
            pre |= have && i == 0 && !half;
        }
        const bool anypre = __any_sync(~0u, pre);
        if (anypre && (key & 15) == J_QA) key = 0xffffu;
        key = __reduce_min_sync(~0u, key);
        key2 = __reduce_min_sync(~0u, key2);
        if (key2 == 0xffffu) return J_END;
        int pq, prb;
        if (key != 0xffffu) { pq = key & 15; prb = (key >> 4) & 15; }
        else if (key2 >= 0x120u && key2 < 0x1000u) { pq = (key2 >> 4) & 15; prb = key2 & 15; }
        else {
            __nanosleep(IDLE_NS);
            if (++gd > 16 * SPIN_LIMIT) { TIMEOUT(5, 0); return J_END; }
            continue;
        }
        int c = 0;
        if (lane == 0) c = (int)atomicAdd(&g_flags[F_CLAIM + pq * 32 + prb], 1u);
        c = __shfl_sync(~0u, c, 0);
        if (c < (int)((nj_tab(prb) >> (8 * pq)) & 255)) {
            idx = pq * 512 + prb * 32 + c;
            int acq = 0;
            if (pq != J_QA) {
                if (lane == 0 && ld_acquire(&g_flags[pq * 32 + prb]) >= (unsigned)((tg_tab(prb) >> (8 * pq)) & 255)) {
                    asm volatile("fence.proxy.async.global;" ::: "memory");
                    acq = 1 << 24;
                }
            }
            return (pq == J_UP && prb >= FINE_RB ? J_UP2 : pq) | (prb << 8) | (c << 16) | acq;
        }
    }
}
__device__ __forceinline__ int op_row(int rb, int split) {
    return rb < FINE_RB ? split * S_ + rb * 128
                        : (rb < NRB - 1 ? OSPLIT * S_ + (split * (NRB - FINE_RB) + rb - FINE_RB) * 128 : OSPLIT * S_ + (OSPLIT2 * (NRB - FINE_RB) + split) * 128);
}

struct Pipe { uint32_t stage, phase; };
__device__ __forceinline__ void pipe_next(Pipe& p) { if (++p.stage == W_NST) { p.stage = 0; p.phase ^= 1; } }

__device__ __forceinline__ void scheduler(const Params& p, uint32_t sb, int lane) {
    const uint32_t bars = sb + SM_BAR;
    uint32_t ph = 0;
#pragma unroll 1
    while (true) {
        mbar_wait(bars + B_REQ, ph);
        int j = 4095;
        const int jd = pick_job(lane, p.qmask, j);
        if (lane == 0) { sts32(bars + B_NEXT, (uint32_t)jd); sts32(bars + B_NEXT + 4, (uint32_t)j); mbar_arrive(bars + B_RSP); }
        ph ^= 1;
        if (jd == J_END) break;
        __syncwarp();
    }
}

__device__ __forceinline__ void producer(const Params& p, uint32_t sb) {
    Pipe pp{0, 1};
    const uint32_t bars = sb + SM_BAR;
    uint32_t seq = 0, h_seen = 0;
    mbar_arrive(bars + B_REQ);
#pragma unroll 1
    while (true) {
        mbar_wait(bars + B_RSP, seq & 1);
        const int jd = (int)lds32(bars + B_NEXT), j = (int)lds32(bars + B_NEXT + 4);
        int left = (jd & 255) == J_DN ? 15 : ((jd & 255) == J_QA ? (((jd >> 8) & 255) == NRB - 1 ? 10 : 12) : ((jd & 255) == J_O ? o_nk((jd >> 8) & 255) : ((jd & 255) == J_LN ? 1 : 8)));
        left = max(left - PICK_AHEAD, 1);
        TR(j, 1);
        const int type = jd & 255, rb = (jd >> 8) & 255, cb = (jd >> 16) & 255;
        const bool fine = rb >= FINE_RB, acquired = (jd >> 24) & 1;
        bool first = true;
        auto begin_stage = [&](uint32_t bytes) -> uint32_t {
            mbar_wait(bars + B_EMPTY + pp.stage * 8, pp.phase);
            if (first) { sts32(bars + B_RING + (seq & 7) * 4, (uint32_t)jd); sts32(bars + B_RING + 32 + (seq & 7) * 4, (uint32_t)j); first = false; }
            const uint32_t fb = bars + B_FULL + pp.stage * 8;
            if (bytes) mbar_expect_tx(fb, bytes); else mbar_arrive(fb);
            if (--left == 0 && type != J_END) mbar_arrive(bars + B_REQ);
            return fb;
        };
        if (type == J_END || type == J_LN) {
            if (type == J_LN && !(h_seen >> 31)) { wait_flag(F_MOD + 1, 64); h_seen |= 1u << 31; }

            TR(j, 2);
            begin_stage(0); pipe_next(pp);
            seq++;
            if (type == J_END) break;
            continue;
        }
        const CUtensorMap *ta, *tb0, *tb1;
        int k0 = 0, nk = 8, n0 = cb * 256, n1 = n0 + 128, nb = 4, dep = -1;
        unsigned tgt = 0;
        switch (type) {
            case J_KV: ta = &p.tm_h; tb0 = tb1 = cb < 16 ? &p.tm_wk : &p.tm_wv; n0 = (cb & 15) * 256; n1 = n0 + 128; dep = F_H + rb; tgt = 2 * NJ_LN1; break;
            case J_QA: ta = &p.tm_h; tb0 = tb1 = &p.tm_wq; dep = F_H + rb; tgt = 2 * NJ_LN1; if (rb == NRB - 1) { n0 = (cb >> 1) * 256; n1 = n0 + 128; } break;
            case J_O: ta = &p.tm_o; tb0 = tb1 = &p.tm_wo; n0 = (cb & 1) * 256; n1 = n0 + 128; nk = o_nk(rb); k0 = (cb >> 1) * nk * 64;
                      dep = F_O + rb; tgt = rb == NRB - 1 ? 64 : 32; break;
            case J_UP: ta = &p.tm_h2; tb0 = &p.tm_wg; tb1 = &p.tm_wu; n0 = n1 = cb * 128; dep = F_H2 + rb; tgt = 2 * NJ_LN; break;
            case J_UP2: ta = &p.tm_h2; tb0 = &p.tm_wg; tb1 = &p.tm_wu; n0 = n1 = cb * 64; nb = 2; dep = F_H2 + rb; tgt = 2 * NJ_LN2; break;
            default: ta = &p.tm_act; tb0 = tb1 = &p.tm_wd; n0 = cb * 64; nk = 0; break;
        }
        const int m0 = rb * 128;
        if (type == J_DN && rb == NRB - 1) {
            n0 = (cb >> 1) * 64;
            const int mh = m0 + (cb & 1) * 64;
#pragma unroll 1
            for (int kb = 0; kb < 14; kb++) {
                const uint32_t fb = begin_stage(32768);
                const uint32_t st = sb + pp.stage * W_STAGE;
                const int k = kb * 128;
                tma_load2d(st + 32768, tb0, n0, k, fb);
                tma_load2d(st + 40960, tb0, n0, k + 64, fb);
                if (kb == 0) { if (!acquired) { wait_flag(F_ACT + rb, 2 * NJ_UP2); asm volatile("fence.proxy.async.global;" ::: "memory"); } TR(j, 2); }
                tma_load2d(st, ta, k, mh, fb);
                tma_load2d(st + 8192, ta, k + 64, mh, fb);
                pipe_next(pp);
            }
            const uint32_t fb = begin_stage(8192);
            tma_load2d(sb + pp.stage * W_STAGE, &p.tm_x1, n0, mh, fb);
            pipe_next(pp);
            seq++;
            continue;
        }
        if (type == J_DN) {
#pragma unroll 1
            for (int kb = 0; kb < 14; kb++) {
                const uint32_t fb = begin_stage(49152);
                const uint32_t st = sb + pp.stage * W_STAGE;
                const int k = kb * 128;
                tma_load2d(st + 32768, tb0, n0, k, fb);
                tma_load2d(st + 40960, tb0, n0, k + 64, fb);
                if (kb == 0) { if (!acquired) { wait_flag(F_ACT + rb, 2 * (fine ? NJ_UP2 : NJ_UP)); asm volatile("fence.proxy.async.global;" ::: "memory"); } TR(j, 2); }
                tma_load2d(st, ta, k, m0, fb);
                tma_load2d(st + 8192, ta, k, m0 + 64, fb);
                tma_load2d(st + 16384, ta, k + 64, m0, fb);
                tma_load2d(st + 24576, ta, k + 64, m0 + 64, fb);
                pipe_next(pp);
            }
        }
#pragma unroll 1
        for (int kb = 0; kb < nk; kb++) {
            const uint32_t fb = begin_stage(16384 + nb * 8192);
            const uint32_t st = sb + pp.stage * W_STAGE;
            const int k = k0 + kb * 64;
            tma_load2d(st + 16384, tb0, n0, k, fb);
            if (nb == 4) {
                tma_load2d(st + 16384 + 8192, tb0, n0 + 64, k, fb);
                tma_load2d(st + 16384 + 16384, tb1, n1, k, fb);
                tma_load2d(st + 16384 + 24576, tb1, n1 + 64, k, fb);
            } else if (nb == 2) {
                tma_load2d(st + 16384 + 8192, tb1, n1, k, fb);
            }
            if (kb == 0) {
                if (acquired && dep < 16) h_seen |= 1u << dep;
                if (dep >= 0 && !acquired && !(dep < 16 && ((h_seen >> dep) & 1))) {
                    wait_flag(dep, tgt);
                    if (type != J_O) asm volatile("fence.proxy.async.global;" ::: "memory");
                    if (dep < 16) h_seen |= 1u << dep;
                }
                TR(j, 2);
            }
            tma_load2d(st, ta, k, m0, fb);
            tma_load2d(st + 8192, ta, k, m0 + 64, fb);
            pipe_next(pp);
        }
        if (type == J_QA) {
            wait_flag(F_KV + rb, 64);
#pragma unroll 1
            for (int i = 0; i < (rb == NRB - 1 ? 2 : 4); i++) {
                const uint32_t fb = begin_stage(40960);
                const uint32_t st = sb + pp.stage * W_STAGE;
                const int col = (i & 1) * HD_ + (rb == NRB - 1 ? cb : cb * 2 + (i >> 1)) * DH_;
                tma_load2d(st, &p.tm_kv, col, m0, fb);
                tma_load2d(st + 8192, &p.tm_kv, col, m0 + 64, fb);
                tma_load2d(st + 16384, &p.tm_kv, col + 64, m0, fb);
                tma_load2d(st + 24576, &p.tm_kv, col + 64, m0 + 64, fb);
                if (i == 0) { wait_flag(F_MEM + rb, 64); asm volatile("fence.proxy.async.global;" ::: "memory"); }
                tma_load2d(st + 32768, &p.tm_kvm, col, rb * 32, fb);
                tma_load2d(st + 36864, &p.tm_kvm, col + 64, rb * 32, fb);
                pipe_next(pp);
            }
        } else if (type == J_DN) {
            const uint32_t fb = begin_stage(16384);
            const uint32_t st = sb + pp.stage * W_STAGE;
            tma_load2d(st, &p.tm_x1, n0, m0, fb);
            tma_load2d(st + 8192, &p.tm_x1, n0, m0 + 64, fb);
            pipe_next(pp);
        }
        seq++;
    }
}

__device__ __forceinline__ void store_warp(const Params& p, uint32_t sb, int wg, int lane) {
    const uint32_t bars = sb + SM_BAR;
    uint32_t seq = 0;
#pragma unroll 1
    while (true) {
        bar_sync(NB_ST + wg, 160);
        const uint32_t jd = lds32(bars + B_RING + (seq & 7) * 4);
        seq++;
        const int type = jd & 255, rb = (jd >> 8) & 255, cb = (jd >> 16) & 255;
        if (type == J_END) break;
        const uint32_t src = sb + W_STG + wg * 16384;
        const CUtensorMap* tm = nullptr; int n0 = cb * 256, nbox = 4, mrow = rb * 128 + wg * 64, flag = 0;
        switch (type) {
            case J_KV: tm = &p.tm_kv; flag = F_KV + rb; break;
            case J_QA: tm = &p.tm_o; flag = F_O + rb; if (rb == NRB - 1) { n0 = cb * 128; nbox = 2; } break;
            case J_O: tm = &p.tm_op; n0 = (cb & 1) * 256; mrow = op_row(rb, cb >> 1) + wg * 64; flag = F_OP + rb; break;
            case J_LN: flag = F_H2 + rb; nbox = 0; break;
            case J_UP: tm = &p.tm_act; n0 = cb * 128; nbox = 2; flag = F_ACT + rb; break;
            case J_UP2: tm = &p.tm_act; n0 = cb * 64; nbox = 1; flag = F_ACT + rb; break;
            default: tm = &p.tm_out; n0 = cb * 64; nbox = 1; flag = -1;
                     if (rb == NRB - 1) { n0 = (cb >> 1) * 64; mrow = rb * 128 + (cb & 1) * 64; nbox = wg == 0; } break;
        }
        if (nbox == 4) {
            if (lane == 0) {
                tma_store2d(tm, src, n0, mrow);
                tma_store2d(tm, src + 8192, n0 + 64, mrow);
                bulk_commit();
                asm volatile("cp.async.bulk.wait_group.read 0;" ::: "memory");
                mbar_arrive(bars + B_STGFREE + wg * 8);
            }
            __syncwarp();
            bar_sync(NB_ST + wg, 160);
            n0 += 128; nbox = 2;
        }
        if (lane == 0) {
            if (nbox) {
                tma_store2d(tm, src, n0, mrow);
                if (nbox == 2) tma_store2d(tm, src + 8192, n0 + 64, mrow);
                bulk_commit();
                asm volatile("cp.async.bulk.wait_group.read 0;" ::: "memory");
                mbar_arrive(bars + B_STGFREE + wg * 8);
                bulk_wait0();
                if (flag >= 0) asm volatile("red.relaxed.gpu.global.add.u32 [%0], 1;" :: "l"(&g_flags[flag]) : "memory");
            } else {
                mbar_arrive(bars + B_STGFREE + wg * 8);
                if (flag >= 0) red_release(&g_flags[flag], 1);
            }
        }
        __syncwarp();
    }
}

__device__ __forceinline__ float gelu_tanh(float x) {
    const float t = x * fmaf(-0.10294324397f, x * x, -2.30220819814f);
    float r; asm("rcp.approx.ftz.f32 %0, %1;" : "=f"(r) : "f"(1.f + ex2(t)));
    return x * r;
}

#define CTR(i) do {} while (0)

__device__ __forceinline__ void ln2_row(const Params& p, int rb, int r, int lane, bool wait) {
    const int row = rb * 128 + r, nsplit = 64 / o_nk(rb);
    const uint4* xr = (const uint4*)(p.x + (size_t)row * D_);
    const uint4 xa = __ldg(xr + lane), xb = __ldg(xr + 32 + lane);
    uint32_t ga[8], c1[8], sm[8];
    load_mod8(g_mod + 2 * D_, lane, ga);
    load_mod8(g_mod + 4 * D_, lane, c1);
    load_mod8(g_mod + 3 * D_, lane, sm);
    float a[16];
#pragma unroll
    for (int i = 0; i < 16; i++) a[i] = 0.f;
    const uint4* src = (const uint4*)(g_op + (size_t)(op_row(rb, 0) + r) * D_) + lane;
    const int sstride = (op_row(rb, 1) - op_row(rb, 0)) * (D_ / 8);
    if (wait) { if (lane == 0) wait_flag(F_OP + rb, 4 * nsplit); __syncwarp(); }
    uint4 u[2][8];
#pragma unroll
    for (int sp = 0; sp < 4; sp++) { u[0][2 * sp] = __ldcg(src + sp * sstride); u[0][2 * sp + 1] = __ldcg(src + sp * sstride + 32); }
    if (nsplit > 4) {
#pragma unroll
        for (int sp = 0; sp < 4; sp++) { u[1][2 * sp] = __ldcg(src + (4 + sp) * sstride); u[1][2 * sp + 1] = __ldcg(src + (4 + sp) * sstride + 32); }
    }
#pragma unroll 1
    for (int s0 = 0; s0 < nsplit; s0 += 4) {
#pragma unroll
        for (int sp = 0; sp < 8; sp++) {
            float* q = a + (sp & 1) * 8;
            const uint4 w = u[0][sp];
            q[0] += bflo(w.x); q[1] += bfhi(w.x); q[2] += bflo(w.y); q[3] += bfhi(w.y);
            q[4] += bflo(w.z); q[5] += bfhi(w.z); q[6] += bflo(w.w); q[7] += bfhi(w.w);
            u[0][sp] = u[1][sp];
        }
        if (s0 + 8 < nsplit) {
#pragma unroll
            for (int sp = 0; sp < 4; sp++) { u[1][2 * sp] = __ldcg(src + (s0 + 8 + sp) * sstride); u[1][2 * sp + 1] = __ldcg(src + (s0 + 8 + sp) * sstride + 32); }
        }
    }
    const uint32_t xv[8] = {xa.x, xa.y, xa.z, xa.w, xb.x, xb.y, xb.z, xb.w};
    uint32_t v[8], r8[8];
#pragma unroll
    for (int i = 0; i < 8; i++) v[i] = hadd2(xv[i], hmul2(ga[i], pack2(a[2 * i], a[2 * i + 1])));
    uint4* x1r = (uint4*)(g_x1 + (size_t)row * D_);
    x1r[lane] = make_uint4(v[0], v[1], v[2], v[3]); x1r[32 + lane] = make_uint4(v[4], v[5], v[6], v[7]);
    uint32_t mu2; float rden;
    ln_stats(v, mu2, rden);
#pragma unroll
    for (int i = 0; i < 8; i++) c1[i] = hadd2(c1[i], 0x3F803F80u);
    ln_apply(v, mu2, rden, c1, sm, r8);
    uint4* hr = (uint4*)(g_h2 + (size_t)row * D_);
    hr[lane] = make_uint4(r8[0], r8[1], r8[2], r8[3]); hr[32 + lane] = make_uint4(r8[4], r8[5], r8[6], r8[7]);
}

__device__ __forceinline__ void consumer(const Params& p, uint32_t sb, int warp, int lane) {
    const uint32_t bars = sb + SM_BAR;
    const int wg = warp >> 2, wl = warp & 3;
    const uint32_t l7 = lane & 7, l8 = lane >> 3, g = lane >> 2, t = lane & 3;
    Pipe pp{0, 0};
    uint32_t seq = 0, stg_phase = 1;
    const int srow = wl * 16 + l7 + (l8 & 1) * 8;
    const uint32_t stg_base = sb + W_STG + wg * 16384 + srow * 128;
    const uint32_t sx = ((lane >> 4) ^ (srow & 7)) << 4;
#pragma unroll 1
    while (true) {
        mbar_wait(bars + B_FULL + pp.stage * 8, pp.phase);
        const uint32_t jd = lds32(bars + B_RING + (seq & 7) * 4);
        CTR(3);
        seq++;
        const int type = jd & 255, rb = (jd >> 8) & 255, cb = (jd >> 16) & 255;
        if (type == J_END) { mbar_wait(bars + B_STGFREE + wg * 8, stg_phase); bar_arrive(NB_ST + wg, 160); break; }
        if (type == J_LN) {
            __syncwarp();
            if (lane == 0) mbar_arrive(bars + B_EMPTY + pp.stage * 8);
            pipe_next(pp);
            const int nr = rb >= FINE_RB ? 1 : 2;
#pragma unroll 1
            for (int rr = 0; rr < nr; rr++) ln2_row(p, rb, (cb * 8 + warp) * nr + rr, lane, !((jd >> 24) & 1) && rr == 0);
            mbar_wait(bars + B_STGFREE + wg * 8, stg_phase); stg_phase ^= 1;
            CTR(4); CTR(5);
            bar_arrive(NB_ST + wg, 160);
            continue;
        }
        if (type == J_DN || type == J_UP2) {
            float acc[64];
#pragma unroll
            for (int i = 0; i < 64; i++) acc[i] = 0.f;
            const bool ksplit = type == J_DN && rb == NRB - 1;
            if (ksplit) {
#pragma unroll 1
                for (int kb = 0; kb < 14; kb++) {
                    if (kb) mbar_wait(bars + B_FULL + pp.stage * 8, pp.phase);
                    const uint32_t st = sb + pp.stage * W_STAGE;
                    const uint64_t da = mkdesc(st + wg * 8192, 16, 1024), db = mkdesc(st + 32768 + wg * 8192, 8192, 1024);
                    wg_fence();
#pragma unroll
                    for (int ks = 0; ks < 4; ks++) wgmma_n64(acc, da + ks * 2, db + ks * 128);
                    wg_commit();
                    wg_wait0();
                    if (lane == 0) mbar_arrive(bars + B_EMPTY + pp.stage * 8);
                    pipe_next(pp);
                }
                const uint32_t xb = sb + W_STG + 16384 + (wl * 32 + lane) * 16;
                if (wg == 1) {
                    mbar_wait(bars + B_STGFREE + 8, stg_phase);
#pragma unroll
                    for (int i = 0; i < 8; i++)
                        sts128(xb + i * 2048, make_uint4(__float_as_uint(acc[4 * i]), __float_as_uint(acc[4 * i + 1]), __float_as_uint(acc[4 * i + 2]), __float_as_uint(acc[4 * i + 3])));
                }
                bar_sync(NB_M, 256);
                if (wg == 0) {
#pragma unroll
                    for (int i = 0; i < 8; i++) {
                        const uint4 o = lds128(xb + i * 2048);
                        acc[4 * i] += __uint_as_float(o.x); acc[4 * i + 1] += __uint_as_float(o.y); acc[4 * i + 2] += __uint_as_float(o.z); acc[4 * i + 3] += __uint_as_float(o.w);
                    }
                }
                bar_sync(NB_M, 256);
            } else if (type == J_DN) {
#pragma unroll 1
                for (int kb = 0; kb < 14; kb++) {
                    if (kb) mbar_wait(bars + B_FULL + pp.stage * 8, pp.phase);
                    const uint32_t st = sb + pp.stage * W_STAGE;
                    const uint64_t da = mkdesc(st + wg * 8192, 16, 1024), db = mkdesc(st + 32768, 8192, 1024);
                    wg_fence();
#pragma unroll
                    for (int ks = 0; ks < 8; ks++) wgmma_n64(acc, da + (ks >> 2) * 1024 + (ks & 3) * 2, db + ks * 128);
                    wg_commit();
                    wg_wait0();
                    if (lane == 0) mbar_arrive(bars + B_EMPTY + pp.stage * 8);
                    pipe_next(pp);
                }
            } else {
#pragma unroll 1
                for (int kb = 0; kb < 8; kb++) {
                    if (kb) mbar_wait(bars + B_FULL + pp.stage * 8, pp.phase);
                    const uint32_t st = sb + pp.stage * W_STAGE;
                    const uint64_t da = mkdesc(st + wg * 8192, 16, 1024), db = mkdesc(st + 16384, 8192, 1024);
                    wg_fence();
#pragma unroll
                    for (int ks = 0; ks < 4; ks++) wgmma_n128(acc, da + ks * 2, db + ks * 128, 1);
                    wg_commit();
                    wg_wait0();
                    if (lane == 0) mbar_arrive(bars + B_EMPTY + pp.stage * 8);
                    pipe_next(pp);
                }
            }
            CTR(4);
            if (type == J_UP2) {
                mbar_wait(bars + B_STGFREE + wg * 8, stg_phase); stg_phase ^= 1;
#pragma unroll
                for (int j = 0; j < 4; j++) {
                    uint32_t r[4];
#pragma unroll
                    for (int q = 0; q < 4; q++) {
                        const uint32_t gw = pack2(acc[8 * j + 2 * q], acc[8 * j + 2 * q + 1]);
                        const uint32_t uw = pack2(acc[32 + 8 * j + 2 * q], acc[32 + 8 * j + 2 * q + 1]);
                        r[q] = hmul2(pack2(gelu_tanh(bflo(gw)), gelu_tanh(bfhi(gw))), uw);
                    }
                    stsm4(stg_base + (sx ^ (j << 5)), r[0], r[1], r[2], r[3]);
                }
            } else {
                mbar_wait(bars + B_FULL + pp.stage * 8, pp.phase);
                const uint32_t st = sb + pp.stage * W_STAGE;
                mbar_wait(bars + B_STGFREE + wg * 8, stg_phase); stg_phase ^= 1;
                const uint32_t* gb = (const uint32_t*)(g_mod + 5 * D_ + (ksplit ? cb >> 1 : cb) * 64) + t;
                const uint32_t xa = st + (ksplit ? 0 : wg * 8192) + (wl * 16 + g) * 128 + (g << 4) + t * 4;
#pragma unroll
                for (int j = 0; j < 4; j++) {
                    uint32_t r[4];
#pragma unroll
                    for (int q = 0; q < 4; q++) {
                        const int nt = 2 * j + (q >> 1);
                        const uint32_t xw = lds32((xa ^ ((nt & 7) << 4)) + (nt >> 3) * 16384 + (q & 1) * 1024);
                        r[q] = hadd2(xw, hmul2(__ldcg(gb + nt * 4), pack2(acc[8 * j + 2 * q], acc[8 * j + 2 * q + 1])));
                    }
                    stsm4(stg_base + (j >> 2) * 8192 + (sx ^ ((2 * j & 7) << 4)), r[0], r[1], r[2], r[3]);
                }
                __syncwarp();
                if (lane == 0) mbar_arrive(bars + B_EMPTY + pp.stage * 8);
                pipe_next(pp);
            }
            fence_async_smem();
            CTR(5);
            bar_arrive(NB_ST + wg, 160);
            continue;
        }
        float acc[128];
#pragma unroll
        for (int i = 0; i < 128; i++) acc[i] = 0.f;
        const int nk = type == J_O ? o_nk(rb) : 8;
#pragma unroll 1
        for (int kb = 0; kb < nk; kb++) {
            if (kb) mbar_wait(bars + B_FULL + pp.stage * 8, pp.phase);
            const uint32_t st = sb + pp.stage * W_STAGE;
            const uint64_t da = mkdesc(st + wg * 8192, 16, 1024), db = mkdesc(st + 16384, 8192, 1024);
            wg_fence();
#pragma unroll
            for (int ks = 0; ks < 4; ks++) wgmma_n256(acc, da + ks * 2, db + ks * 128, 1);
            wg_commit();
            wg_wait0();
            if (lane == 0) mbar_arrive(bars + B_EMPTY + pp.stage * 8);
            pipe_next(pp);
        }
        CTR(4);
        if (type == J_QA) {
            uint32_t qf[64];
#pragma unroll
            for (int i = 0; i < 64; i++) qf[i] = pack2(acc[2 * i], acc[2 * i + 1]);
            const int sg = warp >> 1, half = warp & 1;
            const float sc = 0.08838834764831845f * 1.4426950408889634f;
            const uint32_t xoff = (sg >> 1) * 8192 + ((sg & 1) * 32 + l7) * 128;
            const uint32_t moff = 32768 + (sg * 8 + l7) * 128;
            const uint32_t kch = (l8 ^ l7) << 4;
            const uint32_t vch = ((l8 & 1) ^ l7) << 4;
            if (rb == NRB - 1 && (cb & 1)) {
#pragma unroll
                for (int i = 0; i < 32; i++) qf[i] = qf[32 + i];
            }
#pragma unroll 1
            for (int hh = rb == NRB - 1; hh < 2; hh++) {
                mbar_wait(bars + B_FULL + pp.stage * 8, pp.phase);
                uint32_t st = sb + pp.stage * W_STAGE;
                float sa[5][4];
#pragma unroll
                for (int n = 0; n < 5; n++) sa[n][0] = sa[n][1] = sa[n][2] = sa[n][3] = 0.f;
#pragma unroll
                for (int i = 0; i < 4; i++) {
                    const uint32_t* q = qf + i * 8;
                    uint32_t kk[5][4];
                    ldsm4(kk[0][0], kk[0][1], kk[0][2], kk[0][3], st + moff + (i >> 1) * 4096 + (kch ^ ((i & 1) * 64)));
#pragma unroll
                    for (int n = 1; n < 5; n++)
                        ldsm4(kk[n][0], kk[n][1], kk[n][2], kk[n][3], st + xoff + (n - 1) * 1024 + (i >> 1) * 16384 + (kch ^ ((i & 1) * 64)));
#pragma unroll
                    for (int n = 0; n < 5; n++) mma16816(sa[n], q[0], q[1], q[2], q[3], kk[n][0], kk[n][1]);
#pragma unroll
                    for (int n = 0; n < 5; n++) mma16816(sa[n], q[4], q[5], q[6], q[7], kk[n][2], kk[n][3]);
                }
                __syncwarp();
                if (lane == 0) mbar_arrive(bars + B_EMPTY + pp.stage * 8);
                pipe_next(pp);
                const int iq0 = half * 16 + g - 2 * t, iq1 = iq0 + 8;
                float m0 = fmaxf(sa[0][0], sa[0][1]), m1 = fmaxf(sa[0][2], sa[0][3]);
#pragma unroll
                for (int n = 1; n < 5; n++) {
#pragma unroll
                    for (int e = 0; e < 2; e++) {
                        const int jx = (n - 1) * 8 + e;
                        if (jx > iq0) sa[n][e] = -3.0e38f;
                        if (jx > iq1) sa[n][2 + e] = -3.0e38f;
                        m0 = fmaxf(m0, sa[n][e]); m1 = fmaxf(m1, sa[n][2 + e]);
                    }
                }
                m0 = fmaxf(m0, __shfl_xor_sync(~0u, m0, 1)); m1 = fmaxf(m1, __shfl_xor_sync(~0u, m1, 1));
                m0 = fmaxf(m0, __shfl_xor_sync(~0u, m0, 2)); m1 = fmaxf(m1, __shfl_xor_sync(~0u, m1, 2));
                m0 *= -sc; m1 *= -sc;
                float l0 = 0.f, l1 = 0.f;
                uint32_t p0[5], p1[5];
#pragma unroll
                for (int n = 0; n < 5; n++) {
                    const float e0 = ex2(fmaf(sa[n][0], sc, m0)), e1 = ex2(fmaf(sa[n][1], sc, m0));
                    const float e2 = ex2(fmaf(sa[n][2], sc, m1)), e3 = ex2(fmaf(sa[n][3], sc, m1));
                    l0 += e0 + e1; l1 += e2 + e3;
                    p0[n] = pack2(e0, e1); p1[n] = pack2(e2, e3);
                }
                l0 += __shfl_xor_sync(~0u, l0, 1); l1 += __shfl_xor_sync(~0u, l1, 1);
                l0 += __shfl_xor_sync(~0u, l0, 2); l1 += __shfl_xor_sync(~0u, l1, 2);
                const float i0 = __fdividef(1.f, l0), i1 = __fdividef(1.f, l1);
                mbar_wait(bars + B_FULL + pp.stage * 8, pp.phase);
                st = sb + pp.stage * W_STAGE;
                mbar_wait(bars + B_STGFREE + wg * 8, stg_phase); stg_phase ^= 1;
#pragma unroll
                for (int i = 0; i < 32; i++) qf[i] = qf[32 + i];
#pragma unroll 1
                for (int bx = 0; bx < 2; bx++) {
                    float o[8][4];
                    uint32_t vm[8], v0[4][4], v1[4][4];
#pragma unroll
                    for (int ep = 0; ep < 4; ep++) {
                        ldsm2t(vm[2 * ep], vm[2 * ep + 1], st + moff + bx * 4096 + (vch ^ (ep << 5)));
                        const uint32_t va = st + xoff + (l8 >> 1) * 1024 + bx * 16384 + (vch ^ (ep << 5));
                        ldsm4t(v0[ep][0], v0[ep][1], v0[ep][2], v0[ep][3], va);
                        ldsm4t(v1[ep][0], v1[ep][1], v1[ep][2], v1[ep][3], va + 2048);
                    }
#pragma unroll
                    for (int n = 0; n < 8; n++) { o[n][0] = o[n][1] = o[n][2] = o[n][3] = 0.f; mma16816(o[n], p0[0], p1[0], p0[1], p1[1], vm[n], v0[n >> 1][n & 1]); }
#pragma unroll
                    for (int n = 0; n < 8; n++) mma16816(o[n], p0[2], p1[2], p0[3], p1[3], v0[n >> 1][2 + (n & 1)], v1[n >> 1][n & 1]);
#pragma unroll
                    for (int n = 0; n < 8; n++) mma1688(o[n], p0[4], p1[4], v1[n >> 1][2 + (n & 1)]);
#pragma unroll
                    for (int ep = 0; ep < 4; ep++)
                        stsm4(stg_base + bx * 8192 + (sx ^ (ep << 5)),
                              pack2(o[2 * ep][0] * i0, o[2 * ep][1] * i0), pack2(o[2 * ep][2] * i1, o[2 * ep][3] * i1),
                              pack2(o[2 * ep + 1][0] * i0, o[2 * ep + 1][1] * i0), pack2(o[2 * ep + 1][2] * i1, o[2 * ep + 1][3] * i1));
                }
                __syncwarp();
                if (lane == 0) mbar_arrive(bars + B_EMPTY + pp.stage * 8);
                pipe_next(pp);
                if (hh == 0) { fence_async_smem(); bar_arrive(NB_ST + wg, 160); }
            }
        } else if (type == J_UP) {
            mbar_wait(bars + B_STGFREE + wg * 8, stg_phase); stg_phase ^= 1;
#pragma unroll
            for (int j = 0; j < 8; j++) {
                uint32_t r[4];
#pragma unroll
                for (int q = 0; q < 4; q++) {
                    const uint32_t gw = pack2(acc[8 * j + 2 * q], acc[8 * j + 2 * q + 1]);
                    const uint32_t uw = pack2(acc[64 + 8 * j + 2 * q], acc[64 + 8 * j + 2 * q + 1]);
                    r[q] = hmul2(pack2(gelu_tanh(bflo(gw)), gelu_tanh(bfhi(gw))), uw);
                }
                stsm4(stg_base + (j >> 2) * 8192 + (sx ^ ((2 * j & 7) << 4)), r[0], r[1], r[2], r[3]);
            }
        } else {
#pragma unroll
            for (int rd = 0; rd < 2; rd++) {
                mbar_wait(bars + B_STGFREE + wg * 8, stg_phase); stg_phase ^= 1;
#pragma unroll
                for (int j = rd * 8; j < rd * 8 + 8; j++)
                    stsm4(stg_base + ((j >> 2) & 1) * 8192 + (sx ^ ((2 * j & 7) << 4)),
                          pack2(acc[8 * j], acc[8 * j + 1]), pack2(acc[8 * j + 2], acc[8 * j + 3]),
                          pack2(acc[8 * j + 4], acc[8 * j + 5]), pack2(acc[8 * j + 6], acc[8 * j + 7]));
                if (rd == 0) { fence_async_smem(); bar_arrive(NB_ST + wg, 160); }
            }
        }
        fence_async_smem();
        CTR(5);
        bar_arrive(NB_ST + wg, 160);
    }
}

__global__ void __launch_bounds__(384, 1) k_work(const __grid_constant__ Params p) {
    extern __shared__ __align__(1024) unsigned char smem_raw[];
    const uint32_t sb = smem_u32(smem_raw);
    if (sb & 1023) __trap();
    const int warp = __shfl_sync(~0u, threadIdx.x >> 5, 0);
    int lane; asm volatile("mov.u32 %0, %%laneid;" : "=r"(lane));
    if (threadIdx.x == 0) {
        const uint32_t bars = sb + SM_BAR;
        for (int i = 0; i < W_NST; i++) { mbar_init(bars + B_FULL + i * 8, 1); mbar_init(bars + B_EMPTY + i * 8, 8); }
        mbar_init(bars + B_STGFREE, 1); mbar_init(bars + B_STGFREE + 8, 1); mbar_init(bars + B_REQ, 1); mbar_init(bars + B_RSP, 1);
        asm volatile("fence.mbarrier_init.release.cluster;" ::: "memory");
    }
    __syncthreads();
    if (warp < 8) {
        asm volatile("setmaxnreg.inc.sync.aligned.u32 224;");
        consumer(p, sb, warp, lane);
    } else {
        asm volatile("setmaxnreg.dec.sync.aligned.u32 56;");
        if (warp == 8) { if (lane == 0) producer(p, sb); }
        else if (warp < 11) store_warp(p, sb, warp - 9, lane);
        else scheduler(p, sb, lane);
        __syncwarp();
        bar_sync(NB_W0, 128);
        if (warp == 8 && p.qmask == 0xff) {
            unsigned last = 0;
            if (lane == 0) { __threadfence(); last = atomicAdd(&g_flags[F_DONE], 1u) == gridDim.x - 1; }
            if (__shfl_sync(~0u, last, 0))
                for (int i = lane; i < F_TOTAL; i += 32) g_flags[i] = 0;
        }
    }
}

typedef CUresult (*EncodeFn)(CUtensorMap*, CUtensorMapDataType, cuuint32_t, void*, const cuuint64_t*, const cuuint64_t*,
                             const cuuint32_t*, const cuuint32_t*, CUtensorMapInterleave, CUtensorMapSwizzle,
                             CUtensorMapL2promotion, CUtensorMapFloatOOBfill);

static void make_map(EncodeFn enc, CUtensorMap* m, const void* ptr, uint64_t rows, uint64_t cols, uint32_t box_rows) {
    cuuint64_t dims[2] = {cols, rows};
    cuuint64_t strides[1] = {cols * 2};
    cuuint32_t box[2] = {64, box_rows};
    cuuint32_t es[2] = {1, 1};
    enc(m, CU_TENSOR_MAP_DATA_TYPE_BFLOAT16, 2, const_cast<void*>(ptr), dims, strides, box, es, CU_TENSOR_MAP_INTERLEAVE_NONE,
        CU_TENSOR_MAP_SWIZZLE_128B, CU_TENSOR_MAP_L2_PROMOTION_L2_256B, CU_TENSOR_MAP_FLOAT_OOB_FILL_NONE);
}
template <typename T> static void* sym_addr(T& sym) { void* p = nullptr; cudaGetSymbolAddress(&p, sym); return p; }

extern "C" void kernel_launch(void* const* d_in, const int* in_sizes, int n_in, void* d_out, int out_size) {
    static Params prm;
    static RecParams rp;
    static int n_sm = 132;
    static bool ready = false;
    static const void* key[14];
    bool same = ready;
    for (int i = 0; i < 13 && same; i++) same = key[i] == d_in[i];
    same = same && key[13] == d_out;
    if (!same) {
        void* fn = nullptr;
        cudaDriverEntryPointQueryResult qr;
        cudaGetDriverEntryPoint("cuTensorMapEncodeTiled", &fn, cudaEnableDefault, &qr);
        EncodeFn enc = (EncodeFn)fn;
        make_map(enc, &prm.tm_h, sym_addr(g_h), S_, D_, 64);
        make_map(enc, &prm.tm_kv, sym_addr(g_kv), S_, 2 * HD_, 64);
        make_map(enc, &prm.tm_kvm, sym_addr(g_kvm), NSEG * 8, 2 * HD_, 32);
        make_map(enc, &prm.tm_o, sym_addr(g_o), S_, HD_, 64);
        make_map(enc, &prm.tm_op, sym_addr(g_op), OP_ROWS, D_, 64);
        make_map(enc, &prm.tm_h2, sym_addr(g_h2), S_, D_, 64);
        make_map(enc, &prm.tm_act, sym_addr(g_act), S_, DF_, 64);
        make_map(enc, &prm.tm_x1, sym_addr(g_x1), S_, D_, 64);
        make_map(enc, &prm.tm_out, d_out, S_, D_, 64);
        make_map(enc, &prm.tm_wq, d_in[2], D_, HD_, 64);
        make_map(enc, &prm.tm_wk, d_in[3], D_, HD_, 64);
        make_map(enc, &prm.tm_wv, d_in[4], D_, HD_, 64);
        make_map(enc, &prm.tm_wo, d_in[5], HD_, D_, 64);
        make_map(enc, &prm.tm_wg, d_in[8], D_, DF_, 64);
        make_map(enc, &prm.tm_wu, d_in[9], D_, DF_, 64);
        make_map(enc, &prm.tm_wd, d_in[10], DF_, D_, 64);
        prm.x = (const bf16*)d_in[0]; prm.c = (const bf16*)d_in[11]; prm.w_mod = (const bf16*)d_in[12];
        rp.mem0 = (const bf16*)d_in[1]; rp.x = prm.x; rp.c = prm.c; rp.w_mod = prm.w_mod;
        rp.wq = (const bf16*)d_in[2]; rp.wk = (const bf16*)d_in[3]; rp.wv = (const bf16*)d_in[4]; rp.wo = (const bf16*)d_in[5];
        cudaDeviceGetAttribute(&n_sm, cudaDevAttrMultiProcessorCount, 0);
        cudaFuncSetAttribute(k_work, cudaFuncAttributeMaxDynamicSharedMemorySize, SMEM_BYTES);
        cudaFuncSetAttribute(k_rec, cudaFuncAttributeMaxDynamicSharedMemorySize, R_SMEM);
        cudaFuncSetAttribute(k_rec, cudaFuncAttributeNonPortableClusterSizeAllowed, 1);
        {
            cudaLaunchConfig_t cfg = {};
            cfg.gridDim = dim3(128); cfg.blockDim = dim3(384); cfg.dynamicSmemBytes = R_SMEM;
            cudaLaunchAttribute at[1];
            at[0].id = cudaLaunchAttributeClusterDimension; at[0].val.clusterDim.x = 16; at[0].val.clusterDim.y = 1; at[0].val.clusterDim.z = 1;
            cfg.attrs = at; cfg.numAttrs = 1;
            int n = 0;
            cudaOccupancyMaxActiveClusters(&n, k_rec, &cfg);
            rp.ncl = n < 4 ? 4 : (n > 8 ? 8 : n);
        }
        for (int i = 0; i < 13; i++) key[i] = d_in[i];
        key[13] = d_out;
        ready = true;
    }
    cudaStream_t st = cudaStreamPerThread;
    auto launch_rec = [&]() {
        cudaLaunchConfig_t cfg = {};
        cfg.gridDim = dim3(16 * rp.ncl); cfg.blockDim = dim3(384); cfg.dynamicSmemBytes = R_SMEM; cfg.stream = st;
        cudaLaunchAttribute at[1];
        at[0].id = cudaLaunchAttributeClusterDimension; at[0].val.clusterDim.x = 16; at[0].val.clusterDim.y = 1; at[0].val.clusterDim.z = 1;
        cfg.attrs = at; cfg.numAttrs = 1;
        cudaLaunchKernelEx(&cfg, k_rec, rp);
    };
    auto launch_work = [&](int qmask, int pdl) {
        prm.qmask = qmask;
        cudaLaunchConfig_t cfg = {};
        cfg.gridDim = dim3(n_sm); cfg.blockDim = dim3(384); cfg.dynamicSmemBytes = SMEM_BYTES; cfg.stream = st;
        cudaLaunchAttribute at[1];
        at[0].id = cudaLaunchAttributeProgrammaticStreamSerialization; at[0].val.programmaticStreamSerializationAllowed = 1;
        cfg.attrs = at; cfg.numAttrs = pdl;
        cudaLaunchKernelEx(&cfg, k_work, prm);
    };
    launch_rec();
    launch_work(0xff, 1);
}
```

```cpp
#include <cuda_runtime.h>
#include <cuda_bf16.h>
#include <cuda.h>
#include <stdint.h>

typedef __nv_bfloat16 bf16;
#define IDLE_NS 150
#define FLAG_NS 20

constexpr int S_ = 2048, D_ = 512, DH_ = 128, HD_ = 4096, NSEG = 64, DF_ = 1792;
constexpr int NRB = 16;
constexpr int OSPLIT = 4;

__device__ __align__(1024) bf16 g_h[S_ * D_];
__device__ __align__(1024) bf16 g_kv[S_ * 2 * HD_];
__device__ __align__(1024) bf16 g_kvm[NSEG * 8 * 2 * HD_];
__device__ __align__(1024) bf16 g_o[S_ * HD_];
#define FINE_RB_ 12
constexpr int FINE_RB = FINE_RB_;
#define OSPLIT2_ 8
constexpr int OSPLIT2 = OSPLIT2_;
constexpr int OSPLIT3 = 16;
constexpr int OP_ROWS = OSPLIT * S_ + OSPLIT2 * (NRB - FINE_RB) * 128 + OSPLIT3 * 128;
__device__ __align__(1024) bf16 g_op[OP_ROWS * D_];
__device__ __align__(1024) bf16 g_x1[S_ * D_];
__device__ __align__(1024) bf16 g_h2[S_ * D_];
__device__ __align__(1024) bf16 g_act[S_ * DF_];
__device__ __align__(1024) bf16 g_mod[6 * D_];
__device__ uint32_t g_Fraw[131072 + 65536 + 2048];
#define g_F ((uint32_t*)(((uint64_t)g_Fraw + 0x7FFFFull) & ~0x7FFFFull))
constexpr int F_H = 0, F_MEM = 32, F_O = 64, F_OP = 96, F_H2 = 128, F_ACT = 160, F_MOD = 192, F_KV = 224, F_CLAIM = 256  ,
              F_SIDE = 512  , F_DONE = 576, F_TOTAL = 608;
__device__ __align__(128) unsigned int g_flags[F_TOTAL];
#define TR(j, i) do {} while (0)

__device__ __forceinline__ uint32_t smem_u32(const void* p) { return (uint32_t)__cvta_generic_to_shared(p); }
__device__ __forceinline__ uint32_t clk32() { uint32_t c; asm volatile("mov.u32 %0, %%clock;" : "=r"(c)); return c; }
__device__ __forceinline__ uint32_t mapa_u32(uint32_t addr, uint32_t rank) {
    uint32_t r; asm volatile("mapa.shared::cluster.u32 %0, %1, %2;" : "=r"(r) : "r"(addr), "r"(rank)); return r;
}
__device__ __forceinline__ void mbar_init(uint32_t bar, uint32_t cnt) {
    asm volatile("mbarrier.init.shared::cta.b64 [%0], %1;" :: "r"(bar), "r"(cnt) : "memory");
}
__device__ __forceinline__ void mbar_expect_tx(uint32_t bar, uint32_t bytes) {
    asm volatile("mbarrier.arrive.expect_tx.shared::cta.b64 _, [%0], %1;" :: "r"(bar), "r"(bytes) : "memory");
}
__device__ __forceinline__ void mbar_arrive(uint32_t bar) {
    asm volatile("mbarrier.arrive.shared::cta.b64 _, [%0];" :: "r"(bar) : "memory");
}
__device__ __forceinline__ bool mbar_try_wait(uint32_t bar, uint32_t parity) {
    uint32_t ok;
    asm volatile("{\n.reg .pred p;\nmbarrier.try_wait.parity.shared::cta.b64 p, [%1], %2;\nselp.u32 %0, 1, 0, p;\n}"
                 : "=r"(ok) : "r"(bar), "r"(parity) : "memory");
    return ok;
}
constexpr int SPIN_LIMIT = 1 << 18;
#define TIMEOUT(code, info) do {} while (0)
__device__ __forceinline__ void mbar_wait(uint32_t bar, uint32_t parity) {
    int g = 0;
#pragma unroll 1
    while (!mbar_try_wait(bar, parity)) { if (++g >= SPIN_LIMIT) { TIMEOUT(0, bar & 255); break; } }
}
__device__ __forceinline__ void bar_sync(int id, int n) { asm volatile("bar.sync %0, %1;" :: "r"(id), "r"(n) : "memory"); }
__device__ __forceinline__ void bar_arrive(int id, int n) { asm volatile("bar.arrive %0, %1;" :: "r"(id), "r"(n) : "memory"); }
__device__ __forceinline__ void st_async_v2(uint32_t addr, float a, float b, uint32_t bar) {
    asm volatile("st.async.weak.shared::cluster.mbarrier::complete_tx::bytes.v2.f32 [%0], {%1,%2}, [%3];"
                 :: "r"(addr), "f"(a), "f"(b), "r"(bar) : "memory");
}
__device__ __forceinline__ void st_async_v4(uint32_t addr, uint4 v, uint32_t bar) {
    asm volatile("st.async.weak.shared::cluster.mbarrier::complete_tx::bytes.v4.b32 [%0], {%1,%2,%3,%4}, [%5];"
                 :: "r"(addr), "r"(v.x), "r"(v.y), "r"(v.z), "r"(v.w), "r"(bar) : "memory");
}
__device__ __forceinline__ void stg_relaxed32(uint32_t* p, uint32_t v) {
    asm volatile("st.relaxed.gpu.global.b32 [%0], %1;" :: "l"(p), "r"(v) : "memory");
}
__device__ __forceinline__ uint32_t ldg_relaxed32(const uint32_t* p) {
    uint32_t v; asm volatile("ld.relaxed.gpu.global.b32 %0, [%1];" : "=r"(v) : "l"(p) : "memory"); return v;
}
__device__ __forceinline__ unsigned int ld_acquire(const unsigned int* p) {
    unsigned int v; asm volatile("ld.acquire.gpu.global.u32 %0, [%1];" : "=r"(v) : "l"(p) : "memory"); return v;
}
__device__ __forceinline__ void red_release(unsigned int* p, unsigned int v) {
    asm volatile("red.release.gpu.global.add.u32 [%0], %1;" :: "l"(p), "r"(v) : "memory");
}
__device__ __forceinline__ void wait_flag(int idx, unsigned int target) {
    const unsigned int* p = &g_flags[idx];
    int g = 0;
#pragma unroll 1
    while (ld_acquire(p) < target) { __nanosleep(FLAG_NS); if (++g >= 64 * SPIN_LIMIT) { TIMEOUT(2, idx); break; } }
}
__device__ __forceinline__ void cp_async16(uint32_t dst, const void* src) {
    asm volatile("cp.async.cg.shared.global [%0], [%1], 16;" :: "r"(dst), "l"(src) : "memory");
}
__device__ __forceinline__ void cp_async_commit() { asm volatile("cp.async.commit_group;" ::: "memory"); }
template <int N> __device__ __forceinline__ void cp_async_wait() { asm volatile("cp.async.wait_group %0;" :: "n"(N) : "memory"); }
__device__ __forceinline__ void ldsm4(uint32_t& r0, uint32_t& r1, uint32_t& r2, uint32_t& r3, uint32_t addr) {
    asm volatile("ldmatrix.sync.aligned.m8n8.x4.shared.b16 {%0,%1,%2,%3}, [%4];" : "=r"(r0), "=r"(r1), "=r"(r2), "=r"(r3) : "r"(addr) : "memory");
}
__device__ __forceinline__ void ldsm4t(uint32_t& r0, uint32_t& r1, uint32_t& r2, uint32_t& r3, uint32_t addr) {
    asm volatile("ldmatrix.sync.aligned.m8n8.x4.trans.shared.b16 {%0,%1,%2,%3}, [%4];" : "=r"(r0), "=r"(r1), "=r"(r2), "=r"(r3) : "r"(addr) : "memory");
}
__device__ __forceinline__ void ldsm2t(uint32_t& r0, uint32_t& r1, uint32_t addr) {
    asm volatile("ldmatrix.sync.aligned.m8n8.x2.trans.shared.b16 {%0,%1}, [%2];" : "=r"(r0), "=r"(r1) : "r"(addr) : "memory");
}
__device__ __forceinline__ void stsm4(uint32_t addr, uint32_t r0, uint32_t r1, uint32_t r2, uint32_t r3) {
    asm volatile("stmatrix.sync.aligned.m8n8.x4.shared.b16 [%0], {%1,%2,%3,%4};" :: "r"(addr), "r"(r0), "r"(r1), "r"(r2), "r"(r3) : "memory");
}
__device__ __forceinline__ void stsm4t(uint32_t addr, uint32_t r0, uint32_t r1, uint32_t r2, uint32_t r3) {
    asm volatile("stmatrix.sync.aligned.m8n8.x4.trans.shared.b16 [%0], {%1,%2,%3,%4};" :: "r"(addr), "r"(r0), "r"(r1), "r"(r2), "r"(r3) : "memory");
}
__device__ __forceinline__ void stsm2t(uint32_t addr, uint32_t r0, uint32_t r1) {
    asm volatile("stmatrix.sync.aligned.m8n8.x2.trans.shared.b16 [%0], {%1,%2};" :: "r"(addr), "r"(r0), "r"(r1) : "memory");
}
__device__ __forceinline__ void mma16816(float* d, uint32_t a0, uint32_t a1, uint32_t a2, uint32_t a3, uint32_t b0, uint32_t b1) {
    asm volatile("mma.sync.aligned.m16n8k16.row.col.f32.bf16.bf16.f32 {%0,%1,%2,%3}, {%4,%5,%6,%7}, {%8,%9}, {%0,%1,%2,%3};"
                 : "+f"(d[0]), "+f"(d[1]), "+f"(d[2]), "+f"(d[3]) : "r"(a0), "r"(a1), "r"(a2), "r"(a3), "r"(b0), "r"(b1));
}
__device__ __forceinline__ void mma1688(float* d, uint32_t a0, uint32_t a1, uint32_t b0) {
    asm volatile("mma.sync.aligned.m16n8k8.row.col.f32.bf16.bf16.f32 {%0,%1,%2,%3}, {%4,%5}, {%6}, {%0,%1,%2,%3};"
                 : "+f"(d[0]), "+f"(d[1]), "+f"(d[2]), "+f"(d[3]) : "r"(a0), "r"(a1), "r"(b0));
}
__device__ __forceinline__ void mma16816h(float* d, uint32_t a0, uint32_t a2, uint32_t b0, uint32_t b1) {
    asm volatile("{\n.reg .b32 ju, jv;\nmma.sync.aligned.m16n8k16.row.col.f32.bf16.bf16.f32 {%0,%1,%2,%3}, {%4,ju,%5,jv}, {%6,%7}, {%0,%1,%2,%3};\n}"
                 : "+f"(d[0]), "+f"(d[1]), "+f"(d[2]), "+f"(d[3]) : "r"(a0), "r"(a2), "r"(b0), "r"(b1));
}
__device__ __forceinline__ void mma1688h(float* d, uint32_t a0, uint32_t b0) {
    asm volatile("{\n.reg .b32 ju;\nmma.sync.aligned.m16n8k8.row.col.f32.bf16.bf16.f32 {%0,%1,%2,%3}, {%4,ju}, {%5}, {%0,%1,%2,%3};\n}"
                 : "+f"(d[0]), "+f"(d[1]), "+f"(d[2]), "+f"(d[3]) : "r"(a0), "r"(b0));
}
__device__ __forceinline__ uint32_t movm(uint32_t a) {
    uint32_t d; asm volatile("movmatrix.sync.aligned.m8n8.trans.b16 %0, %1;" : "=r"(d) : "r"(a)); return d;
}
__device__ __forceinline__ uint32_t pack2(float lo, float hi) {
    uint32_t r; asm("cvt.rn.bf16x2.f32 %0, %1, %2;" : "=r"(r) : "f"(hi), "f"(lo)); return r;
}
__device__ __forceinline__ float bflo(uint32_t w) { return __uint_as_float(w << 16); }
__device__ __forceinline__ float bfhi(uint32_t w) { return __uint_as_float(w & 0xffff0000u); }
__device__ __forceinline__ float rbf(float x) { return __bfloat162float(__float2bfloat16_rn(x)); }
__device__ __forceinline__ float ex2(float x) { float y; asm("ex2.approx.ftz.f32 %0, %1;" : "=f"(y) : "f"(x)); return y; }
__device__ __forceinline__ void sts128(uint32_t addr, uint4 v) {
    asm volatile("st.shared.v4.b32 [%0], {%1,%2,%3,%4};" :: "r"(addr), "r"(v.x), "r"(v.y), "r"(v.z), "r"(v.w) : "memory");
}
__device__ __forceinline__ uint4 lds128(uint32_t addr) {
    uint4 v; asm volatile("ld.shared.v4.b32 {%0,%1,%2,%3}, [%4];" : "=r"(v.x), "=r"(v.y), "=r"(v.z), "=r"(v.w) : "r"(addr) : "memory"); return v;
}
__device__ __forceinline__ float2 lds64f(uint32_t addr) {
    float2 v; asm volatile("ld.shared.v2.f32 {%0,%1}, [%2];" : "=f"(v.x), "=f"(v.y) : "r"(addr) : "memory"); return v;
}
__device__ __forceinline__ float lds32f(uint32_t addr) {
    float v; asm volatile("ld.shared.f32 %0, [%1];" : "=f"(v) : "r"(addr) : "memory"); return v;
}
__device__ __forceinline__ uint32_t lds32(uint32_t addr) {
    uint32_t v; asm volatile("ld.shared.b32 %0, [%1];" : "=r"(v) : "r"(addr) : "memory"); return v;
}
__device__ __forceinline__ void sts32(uint32_t addr, uint32_t v) { asm volatile("st.shared.b32 [%0], %1;" :: "r"(addr), "r"(v) : "memory"); }
__device__ __forceinline__ void sts64f(uint32_t addr, float a, float b) { asm volatile("st.shared.v2.f32 [%0], {%1,%2};" :: "r"(addr), "f"(a), "f"(b) : "memory"); }

__device__ __forceinline__ void tma_load2d(uint32_t dst, const CUtensorMap* tm, int c0, int c1, uint32_t bar) {
    asm volatile("cp.async.bulk.tensor.2d.shared::cluster.global.mbarrier::complete_tx::bytes [%0], [%1, {%3, %4}], [%2];"
                 :: "r"(dst), "l"(tm), "r"(bar), "r"(c0), "r"(c1) : "memory");
}
__device__ __forceinline__ void tma_store2d(const CUtensorMap* tm, uint32_t src, int c0, int c1) {
    asm volatile("cp.async.bulk.tensor.2d.global.shared::cta.bulk_group [%0, {%2, %3}], [%1];"
                 :: "l"(tm), "r"(src), "r"(c0), "r"(c1) : "memory");
}
__device__ __forceinline__ void bulk_commit() { asm volatile("cp.async.bulk.commit_group;" ::: "memory"); }
__device__ __forceinline__ void bulk_wait0() { asm volatile("cp.async.bulk.wait_group 0;" ::: "memory"); }
__device__ __forceinline__ void fence_async_smem() { asm volatile("fence.proxy.async.shared::cta;" ::: "memory"); }
__device__ __forceinline__ void fence_async_all() { asm volatile("fence.proxy.async;" ::: "memory"); }

__device__ __forceinline__ void wg_fence() { asm volatile("wgmma.fence.sync.aligned;" ::: "memory"); }
__device__ __forceinline__ void wg_commit() { asm volatile("wgmma.commit_group.sync.aligned;" ::: "memory"); }
__device__ __forceinline__ void wg_wait0() { asm volatile("wgmma.wait_group.sync.aligned 0;" ::: "memory"); }
__device__ __forceinline__ uint64_t mkdesc(uint32_t saddr, uint32_t lbo, uint32_t sbo) {
    return (uint64_t)((saddr & 0x3FFFF) >> 4) | ((uint64_t)(lbo >> 4) << 16) | ((uint64_t)(sbo >> 4) << 32) | (1ull << 62);
}
#define ACC8(i) "+f"(d[i]), "+f"(d[i + 1]), "+f"(d[i + 2]), "+f"(d[i + 3]), "+f"(d[i + 4]), "+f"(d[i + 5]), "+f"(d[i + 6]), "+f"(d[i + 7])
__device__ __forceinline__ void wgmma_n256(float* d, uint64_t da, uint64_t db, int scale_d) {
    asm volatile(
        "{\n.reg .pred p;\nsetp.ne.b32 p, %130, 0;\n"
        "wgmma.mma_async.sync.aligned.m64n256k16.f32.bf16.bf16 "
        "{%0,%1,%2,%3,%4,%5,%6,%7,%8,%9,%10,%11,%12,%13,%14,%15,%16,%17,%18,%19,%20,%21,%22,%23,%24,%25,%26,%27,%28,%29,%30,%31,"
        "%32,%33,%34,%35,%36,%37,%38,%39,%40,%41,%42,%43,%44,%45,%46,%47,%48,%49,%50,%51,%52,%53,%54,%55,%56,%57,%58,%59,%60,%61,%62,%63,"
        "%64,%65,%66,%67,%68,%69,%70,%71,%72,%73,%74,%75,%76,%77,%78,%79,%80,%81,%82,%83,%84,%85,%86,%87,%88,%89,%90,%91,%92,%93,%94,%95,"
        "%96,%97,%98,%99,%100,%101,%102,%103,%104,%105,%106,%107,%108,%109,%110,%111,%112,%113,%114,%115,%116,%117,%118,%119,%120,%121,%122,%123,%124,%125,%126,%127}, "
        "%128, %129, p, 1, 1, 0, 1;\n}"
        : ACC8(0), ACC8(8), ACC8(16), ACC8(24), ACC8(32), ACC8(40), ACC8(48), ACC8(56),
          ACC8(64), ACC8(72), ACC8(80), ACC8(88), ACC8(96), ACC8(104), ACC8(112), ACC8(120)
        : "l"(da), "l"(db), "r"(scale_d));
}
__device__ __forceinline__ void wgmma_n128(float* d, uint64_t da, uint64_t db, int scale_d) {
    asm volatile(
        "{\n.reg .pred p;\nsetp.ne.b32 p, %66, 0;\n"
        "wgmma.mma_async.sync.aligned.m64n128k16.f32.bf16.bf16 "
        "{%0,%1,%2,%3,%4,%5,%6,%7,%8,%9,%10,%11,%12,%13,%14,%15,%16,%17,%18,%19,%20,%21,%22,%23,%24,%25,%26,%27,%28,%29,%30,%31,"
        "%32,%33,%34,%35,%36,%37,%38,%39,%40,%41,%42,%43,%44,%45,%46,%47,%48,%49,%50,%51,%52,%53,%54,%55,%56,%57,%58,%59,%60,%61,%62,%63}, "
        "%64, %65, p, 1, 1, 0, 1;\n}"
        : ACC8(0), ACC8(8), ACC8(16), ACC8(24), ACC8(32), ACC8(40), ACC8(48), ACC8(56)
        : "l"(da), "l"(db), "r"(scale_d));
}

__device__ __forceinline__ void wgmma_n64(float* d, uint64_t da, uint64_t db) {
    asm volatile(
        "wgmma.mma_async.sync.aligned.m64n64k16.f32.bf16.bf16 "
        "{%0,%1,%2,%3,%4,%5,%6,%7,%8,%9,%10,%11,%12,%13,%14,%15,%16,%17,%18,%19,%20,%21,%22,%23,%24,%25,%26,%27,%28,%29,%30,%31}, "
        "%32, %33, 1, 1, 1, 0, 1;"
        : ACC8(0), ACC8(8), ACC8(16), ACC8(24)
        : "l"(da), "l"(db));
}
__device__ __forceinline__ uint32_t hadd2(uint32_t a, uint32_t b) { uint32_t r; asm("add.rn.bf16x2 %0, %1, %2;" : "=r"(r) : "r"(a), "r"(b)); return r; }
__device__ __forceinline__ uint32_t hsub2(uint32_t a, uint32_t b) { uint32_t r; asm("sub.rn.bf16x2 %0, %1, %2;" : "=r"(r) : "r"(a), "r"(b)); return r; }
__device__ __forceinline__ uint32_t hmul2(uint32_t a, uint32_t b) { uint32_t r; asm("mul.rn.bf16x2 %0, %1, %2;" : "=r"(r) : "r"(a), "r"(b)); return r; }
__device__ __forceinline__ void load_mod8(const bf16* m, int lane, uint32_t* v) {
    const uint4 a = __ldcg((const uint4*)m + lane), b = __ldcg((const uint4*)m + 32 + lane);
    v[0] = a.x; v[1] = a.y; v[2] = a.z; v[3] = a.w; v[4] = b.x; v[5] = b.y; v[6] = b.z; v[7] = b.w;
}
__device__ __forceinline__ void ln_stats(const uint32_t* x, uint32_t& mu2, float& rden) {
    float s = 0.f;
#pragma unroll
    for (int i = 0; i < 8; i++) s += bflo(x[i]) + bfhi(x[i]);
#pragma unroll
    for (int o = 16; o > 0; o >>= 1) s += __shfl_xor_sync(~0u, s, o);
    const float mean = s * (1.f / D_);
    float q = 0.f;
#pragma unroll
    for (int i = 0; i < 8; i++) { const float d0 = bflo(x[i]) - mean, d1 = bfhi(x[i]) - mean; q = fmaf(d0, d0, q); q = fmaf(d1, d1, q); }
#pragma unroll
    for (int o = 16; o > 0; o >>= 1) q += __shfl_xor_sync(~0u, q, o);
    mu2 = pack2(mean, mean);
    rden = __frcp_rn(rbf(__fsqrt_rn(rbf(rbf(q * (1.f / D_)) + 1e-5f))));
}
__device__ __forceinline__ void ln_apply(const uint32_t* x, uint32_t mu2, float rden, const uint32_t* c1, const uint32_t* sm, uint32_t* r) {
#pragma unroll
    for (int i = 0; i < 8; i++) {
        const uint32_t d = hsub2(x[i], mu2);
        r[i] = hadd2(hmul2(pack2(bflo(d) * rden, bfhi(d) * rden), c1[i]), sm[i]);
    }
}

struct __align__(64) Params {
    CUtensorMap tm_h, tm_kv, tm_kvm, tm_o, tm_op, tm_h2, tm_act, tm_x1, tm_out;
    CUtensorMap tm_wq, tm_wk, tm_wv, tm_wo, tm_wg, tm_wu, tm_wd;
    const bf16 *x, *c, *w_mod;
    int qmask;
};

constexpr uint32_t R_WV = 0, R_MEM = 65536  ,
                   R_KX = 69632  , R_VX = R_KX + 8192,
                   R_VMS = R_KX + 32768  , R_OS = R_VMS + 2048  , R_SX = R_OS + 2048  , R_BAR = R_SX + 1536,
                   R_RS = R_BAR + 512  , R_VB = R_RS + 4096  , R_VP = R_VB + 2048  ,
                   R_STG = R_VP + 4096  ,
                   R_TQ = R_STG  , R_TV = R_STG + 53248  , R_QF = R_STG + 77824  ,
                   R_SMEM = R_STG + 98304;
static_assert((R_STG & 1023) == 0 && (R_RS & 511) == 0 && R_QF + 16384 <= R_SMEM, "smem");
constexpr uint32_t RB_Q = R_BAR, RB_V = R_BAR + 8, RB_E = R_BAR + 16, RB_A = R_BAR + 24, RB_ROLE = R_BAR + 32, RB_A1 = R_BAR + 40;
constexpr int W_NST = 4;
constexpr uint32_t W_STAGE = 49152, W_STG = W_NST * W_STAGE  , W_END = W_STG + 32768;
constexpr uint32_t SM_BAR = W_END;
constexpr uint32_t SMEM_BYTES = W_END + 1024 + 2048;
constexpr uint32_t B_FULL = 0, B_EMPTY = 32, B_STGFREE = 64, B_REQ = 80, B_RSP = 88, B_NEXT = 96, B_RING = 128;
#define PICK_AHEAD 3

constexpr int NB_S = 11, NB_Y = 1, NB_M = 5, NB_K = 5, NB_B = 2, NB_C = 3, NB_D = 4, NB_W0 = 6  , NB_ST = 9  ;

__device__ __forceinline__ int pos_of_d(int d) {
    const int rem = d & 31;
    return (d & ~31) + ((rem & 7) >> 1) * 8 + (rem & 1) * 4 + (rem >> 3);
}

#define PROF(i) do {} while (0)
#define PROFG(i) do {} while (0)
#define VK0_ 4
constexpr int VK0 = VK0_;
constexpr int NOFF = 8;
#define OFFKS(i) (((i) >> 1) < 2 ? ((i) >> 1) : ((i) >> 1) + 2)
#define POLL_GAP 110

struct RecParams { const bf16 *mem0, *wq, *wk, *wv, *wo, *x, *c, *w_mod; int ncl, only_pre; };

__device__ __forceinline__ void rec_qk(const RecParams& p, const uint32_t sb, const int cta, const int warp, int lane, const int sel) {
    const int crank = cta & 15, cl = cta >> 4, rank = cta & 1;
    const int wg = warp >> 2, aa = warp & 3;
    uint32_t wa[2][16][4];
    {
        const uint32_t stg = sb + R_STG + wg * 32768;
        const int t128 = aa * 32 + lane;
        const int row = (lane >> 4) * 8 + (lane & 7);
        const int ch = t128 & 7;
        const size_t goff = (size_t)rank * 256 * HD_ + (cta >> 1) * DH_ + ch * 8;
        const bf16* W = (wg == 0 ? p.wq : p.wk) + goff;
#pragma unroll 4
        for (int dd = 0; dd < 16; dd++) {
            const int d = dd * 16 + (t128 >> 3), pp = pos_of_d(d);
            cp_async16(sb + R_WV + wg * 32768 + pp * 128 + ((ch ^ (pp & 7)) << 4), p.wv + goff + wg * 64 + (size_t)d * HD_);
        }
        cp_async_commit();
#pragma unroll 4
        for (int dd = 0; dd < 16; dd++) {
            const int d = dd * 16 + (t128 >> 3), pp = pos_of_d(d);
            cp_async16(stg + pp * 128 + ((ch ^ (pp & 7)) << 4), W + (size_t)d * HD_);
        }
        cp_async_commit();
        {
            const int tok = warp, d0 = lane * 8;
            const uint4 m0 = __ldg((const uint4*)(p.mem0 + tok * D_ + rank * 256 + d0));
            const uint32_t mw[4] = {m0.x, m0.y, m0.z, m0.w};
#pragma unroll
            for (int e = 0; e < 8; e++) {
                const int pp = pos_of_d(d0 + e);
                const unsigned short v = (unsigned short)(mw[e >> 1] >> ((e & 1) * 16));
                asm volatile("st.shared.u16 [%0], %1;" :: "r"(sb + R_MEM + (pp >> 3) * 128 + tok * 16 + (pp & 7) * 2), "h"(v) : "memory");
            }
        }
        cp_async_wait<1>();
        bar_sync(NB_W0 + wg, 128);
        const uint32_t fv = row * 128 + (((2 * aa + ((lane >> 3) & 1)) ^ (row & 7)) << 4);
#pragma unroll
        for (int ks = 0; ks < 16; ks++) ldsm4t(wa[0][ks][0], wa[0][ks][1], wa[0][ks][2], wa[0][ks][3], sb + R_WV + wg * 32768 + fv + ks * 2048);
        bar_sync(NB_W0 + wg, 128);
#pragma unroll
        for (int ks = 0; ks < 16; ks++)
            sts128(sb + R_WV + (warp * 16 + ks) * 512 + lane * 16, make_uint4(wa[0][ks][0], wa[0][ks][1], wa[0][ks][2], wa[0][ks][3]));
        const uint32_t fo = stg + row * 128 + (((4 * (aa & 1) + ((lane >> 3) & 1)) ^ (row & 7)) << 4);
#pragma unroll 1
        for (int m = 0; m < 2; m++) {
            cp_async_wait<0>();
            bar_sync(NB_W0 + wg, 128);
            if ((aa >> 1) == m) {
#pragma unroll
                for (int ks = 0; ks < 16; ks++) {
                    ldsm4t(wa[0][ks][0], wa[0][ks][1], wa[0][ks][2], wa[0][ks][3], fo + ks * 2048);
                    ldsm4t(wa[1][ks][0], wa[1][ks][1], wa[1][ks][2], wa[1][ks][3], (fo ^ 32) + ks * 2048);
                }
            }
            bar_sync(NB_W0 + wg, 128);
            if (m == 0) {
#pragma unroll 4
                for (int dd = 0; dd < 16; dd++) {
                    const int d = dd * 16 + (t128 >> 3), pp = pos_of_d(d);
                    cp_async16(stg + pp * 128 + ((ch ^ (pp & 7)) << 4), W + 64 + (size_t)d * HD_);
                }
                cp_async_commit();
            }
        }
    }
    bar_sync(NB_D, 384);
    const uint32_t tab = sb + R_TQ + wg * 26624 + (aa * 32 + lane) * 16;
    {
        const uint32_t l7 = lane & 7, l8 = lane >> 3, g = lane >> 2, t = lane & 3;
        const uint32_t bq = warp >> 1, tp = warp & 1;
        uint4 v;
        v.x = sb + R_QF + (rank * 8 + warp) * 512 + lane * 16;
        v.y = sb + R_QF + (warp == 5 ? 1024 : 0) + lane * 16;
        v.z = sb + R_KX + ((warp - 1) * 8 + l7) * 128 + ((l8 ^ l7) << 4);
        v.w = sb + R_SX + warp * 256 + lane * 8;
        sts128(tab, v);
        sts128(tab + 2048, make_uint4(sb + lane * 16 + R_MEM, sb + lane * 16 + R_WV + warp * 8192, sb + lane * 16 + R_VP + warp * 512, lane));
        const uint32_t L = bq * 8 + 2 * tp + (l8 & 1) + 4 * (l8 >> 1);
        const uint32_t d0 = (((crank + ((t >> 1) | (g & 6))) & 7) << 1) | (crank >> 3);
        v.x = sb + R_RS + l7 * 512 + ((L ^ l7) << 4);
        v.y = mapa_u32(sb + R_MEM + ((crank & 7) * 4 + bq) * 128 + (4 * tp + 2 * (t & 1) + (g & 1)) * 16, d0);
        v.z = mapa_u32(sb + ((crank & 1) ? RB_A1 : RB_A), d0);
        v.w = lane;
        sts128(tab + 4096, v);
        const uint64_t wr = (uint64_t)(g_F + ((crank * 2 + ((crank ^ (crank >> 3) ^ sel) & 1)) * 1024 + warp * 128 + cl * 32 + lane));
        sts128(tab + 6144, make_uint4((uint32_t)wr, (uint32_t)(wr >> 32), (uint32_t)((((cl + 1) & 3) - cl) * 128), (uint32_t)((((cl + 2) & 3) - cl) * 128)));
        sts32(tab + 8192, (uint32_t)((((cl + 3) & 3) - cl) * 128));
#pragma unroll
        for (int i = 0; i < NOFF; i++)
            sts128(tab + 10240 + i * 2048, make_uint4(wa[i & 1][OFFKS(i)][0], wa[i & 1][OFFKS(i)][1], wa[i & 1][OFFKS(i)][2], wa[i & 1][OFFKS(i)][3]));
    }
    bar_sync(NB_D, 384);
    uint4 tb = lds128(tab + 2048);
#pragma unroll 1
    for (int s = 0; s < NSEG; s++) {
        if (s > 0) mbar_wait(sb + RB_A, (s - 1) & 1);
        if (warp == 0) PROF(0);
        uint4 ta;
        const uint32_t par = (s & 1) * 8192;
        {
            float acc[5][4];
#pragma unroll
            for (int c = 0; c < 5; c++) { acc[c][0] = acc[c][1] = acc[c][2] = acc[c][3] = 0.f; }
            uint32_t b[8][4];
            uint4 av[16];
            static_assert(VK0 == 4, "order below assumes the V/O warps cover slices 0,1");
#define QK4(k2) do { \
                mma16816(acc[0], wa[0][2 * (k2)][0], wa[0][2 * (k2)][1], wa[0][2 * (k2)][2], wa[0][2 * (k2)][3], b[k2][0], b[k2][1]); \
                mma16816(acc[1], wa[1][2 * (k2)][0], wa[1][2 * (k2)][1], wa[1][2 * (k2)][2], wa[1][2 * (k2)][3], b[k2][0], b[k2][1]); \
                mma16816(acc[3], wa[0][2 * (k2) + 1][0], wa[0][2 * (k2) + 1][1], wa[0][2 * (k2) + 1][2], wa[0][2 * (k2) + 1][3], b[k2][2], b[k2][3]); \
                mma16816(acc[4], wa[1][2 * (k2) + 1][0], wa[1][2 * (k2) + 1][1], wa[1][2 * (k2) + 1][2], wa[1][2 * (k2) + 1][3], b[k2][2], b[k2][3]); } while (0)
#define V2(k2) do { \
                mma16816(acc[2], av[2 * (k2)].x, av[2 * (k2)].y, av[2 * (k2)].z, av[2 * (k2)].w, b[k2][0], b[k2][1]); \
                mma16816(acv, av[2 * (k2) + 1].x, av[2 * (k2) + 1].y, av[2 * (k2) + 1].z, av[2 * (k2) + 1].w, b[k2][2], b[k2][3]); } while (0)
#define LB(k2) ldsm4(b[k2][0], b[k2][1], b[k2][2], b[k2][3], tb.x + (k2) * 512)
#define LV(k2) do { av[2 * (k2)] = lds128(tb.y + 2 * (k2) * 512); av[2 * (k2) + 1] = lds128(tb.y + (2 * (k2) + 1) * 512); } while (0)
            float acv[4] = {0.f, 0.f, 0.f, 0.f};
            LB(0); LB(2); LB(4); LB(6);
            QK4(0); QK4(2); LV(2); LV(4); QK4(4); QK4(6);
            if (s > 0) mbar_wait(sb + RB_A1, (s - 1) & 1);
            LB(1); LB(3); LB(5); LB(7); ta = lds128(tab);
            V2(2); V2(4); LV(6); LV(3);
            QK4(1); QK4(3); QK4(5); QK4(7);
            const uint4 f = make_uint4(movm(pack2(acc[0][0] + acc[3][0], acc[0][1] + acc[3][1])), movm(pack2(acc[0][2] + acc[3][2], acc[0][3] + acc[3][3])),
                                       movm(pack2(acc[1][0] + acc[4][0], acc[1][1] + acc[4][1])), movm(pack2(acc[1][2] + acc[4][2], acc[1][3] + acc[4][3])));
            st_async_v4((ta.x + par) ^ (1u << 24), f, (sb + RB_Q) ^ (1u << 24));
            sts128(ta.x + par, f);
            __syncwarp();
            if (tb.w == 0) mbar_arrive(sb + RB_Q);
            if (warp == 0) PROF(1);
            if (tb.x == 0) break;
            LV(5); LV(7);
            V2(6); V2(3); V2(5); V2(7);
            sts128(tb.z, make_uint4(__float_as_uint(acc[2][0] + acv[0]), __float_as_uint(acc[2][1] + acv[1]), __float_as_uint(acc[2][2] + acv[2]), __float_as_uint(acc[2][3] + acv[3])));
            bar_arrive(NB_Y, 384);
        }
        if (warp == 0) PROF(14);
        if (warp < 6 && s != NSEG - 1) {
            float sa[4] = {0.f, 0.f, 0.f, 0.f}, sc[4] = {0.f, 0.f, 0.f, 0.f};
            const uint32_t qa = ta.y + par;
            if (warp == 0 || warp == 5) {
                mbar_wait(sb + RB_Q, s & 1);
                const uint4 q0 = lds128(qa), q1 = lds128(qa + 4096), k0 = lds128(qa + 2048), k1 = lds128(qa + 6144);
                const uint4 q2 = lds128(qa + 512), q3 = lds128(qa + 4608), k2 = lds128(qa + 2560), k3 = lds128(qa + 6656);
                mma16816h(sa, hadd2(q0.x, q1.x), hadd2(q0.y, q1.y), hadd2(k0.x, k1.x), hadd2(k0.y, k1.y));
                mma16816h(sc, hadd2(q0.z, q1.z), hadd2(q0.w, q1.w), hadd2(k0.z, k1.z), hadd2(k0.w, k1.w));
                mma16816h(sa, hadd2(q2.x, q3.x), hadd2(q2.y, q3.y), hadd2(k2.x, k3.x), hadd2(k2.y, k3.y));
                mma16816h(sc, hadd2(q2.z, q3.z), hadd2(q2.w, q3.w), hadd2(k2.z, k3.z), hadd2(k2.w, k3.w));
            } else {
                uint32_t k[16];
                const uint32_t kb = ta.z + 2 * par;
                ldsm4(k[0], k[1], k[2], k[3], kb);
                ldsm4(k[4], k[5], k[6], k[7], kb ^ 64);
                ldsm4(k[8], k[9], k[10], k[11], kb + 4096);
                ldsm4(k[12], k[13], k[14], k[15], (kb ^ 64) + 4096);
                mbar_wait(sb + RB_Q, s & 1);
                uint4 q0[4], q1[4];
#pragma unroll
                for (int i = 0; i < 4; i++) { q0[i] = lds128(qa + i * 512); q1[i] = lds128(qa + 4096 + i * 512); }
                float sd[4] = {0.f, 0.f, 0.f, 0.f}, se[4] = {0.f, 0.f, 0.f, 0.f};
                mma16816h(sa, hadd2(q0[0].x, q1[0].x), hadd2(q0[0].y, q1[0].y), k[0], k[1]);
                mma16816h(sc, hadd2(q0[0].z, q1[0].z), hadd2(q0[0].w, q1[0].w), k[2], k[3]);
                mma16816h(sd, hadd2(q0[1].x, q1[1].x), hadd2(q0[1].y, q1[1].y), k[4], k[5]);
                mma16816h(se, hadd2(q0[1].z, q1[1].z), hadd2(q0[1].w, q1[1].w), k[6], k[7]);
                mma16816h(sa, hadd2(q0[2].x, q1[2].x), hadd2(q0[2].y, q1[2].y), k[8], k[9]);
                mma16816h(sc, hadd2(q0[2].z, q1[2].z), hadd2(q0[2].w, q1[2].w), k[10], k[11]);
                mma16816h(sd, hadd2(q0[3].x, q1[3].x), hadd2(q0[3].y, q1[3].y), k[12], k[13]);
                mma16816h(se, hadd2(q0[3].z, q1[3].z), hadd2(q0[3].w, q1[3].w), k[14], k[15]);
                sa[0] += sd[0]; sa[1] += sd[1]; sc[0] += se[0]; sc[1] += se[1];
            }
            const float scl = 0.08838834764831845f * 1.4426950408889634f;
            sts64f(ta.w, (sa[0] + sc[0]) * scl, (sa[1] + sc[1]) * scl);
            bar_arrive(NB_S, 320);
            if (warp == 0) PROF(2);
        } else if (warp == 7) {
            mbar_wait(sb + RB_Q, s & 1);
            if (lane == 0) {
                mbar_expect_tx(sb + RB_Q, 4096);
                if (s > 0) { mbar_expect_tx(sb + RB_A, 2048); mbar_expect_tx(sb + RB_A1, 2048); }
            }
            __syncwarp();
        } else if (s > 0 && (s & 3) == 0 && warp == 6) {
            bar_sync(NB_K, 160);
            if (lane == 0) red_release(&g_flags[F_MEM + (s >> 2) - 1], 1);
            __syncwarp();
        }
        if (s == NSEG - 1) {
            const uint4 td = lds128(tab + 6144);
            stg_relaxed32((uint32_t*)(((uint64_t)td.y << 32) | (td.x ^ 0x21000)), 0u);
            break;
        }
        const uint4 tc = lds128(tab + 4096), td = lds128(tab + 6144);
        const uint32_t te = lds32(tab + 8192);
        uint32_t* wr = (uint32_t*)(((uint64_t)td.y << 32) | (td.x ^ ((s & 1) * 0x21000)));
        const uint32_t* r1p = (const uint32_t*)((const char*)wr + (int)td.z);
        const uint32_t* r2p = (const uint32_t*)((const char*)wr + (int)td.w);
        const uint32_t* r3p = (const uint32_t*)((const char*)wr + (int)te);
        const uint32_t tag = ((s >> 1) + 1) & 1;
        mbar_wait(sb + RB_E, s & 1);
        if (warp == 0) PROF(7);
        {
            uint32_t a0, a1, a2, a3;
            ldsm4t(a0, a1, a2, a3, tc.x);
            const uint32_t one = 0x3F803F80u;
            float d0_[4] = {0.f, 0.f, 0.f, 0.f}, d1_[4] = {0.f, 0.f, 0.f, 0.f};
            mma1688(d0_, a0, a1, one);
            mma1688(d1_, a2, a3, one);
            const bool t1 = tc.w & 1, t2 = tc.w & 2;
            const float x = t2 ? (t1 ? d1_[2] : d1_[0]) : (t1 ? d0_[2] : d0_[0]);
            const uint32_t own = (__float_as_uint(x) & ~1u) | tag;
            stg_relaxed32(wr, own);
            const uint32_t tq = clk32();
            if (warp == 0) PROF(8);
            while ((int)(clk32() - tq) < POLL_GAP) {}
            uint32_t f1 = ldg_relaxed32(r1p), f2 = ldg_relaxed32(r2p), f3 = ldg_relaxed32(r3p);
#pragma unroll
            for (int i = 0; i < NOFF; i++) {
                const uint4 f0 = lds128(tab + 10240 + i * 2048);
                wa[i & 1][OFFKS(i)][0] = f0.x; wa[i & 1][OFFKS(i)][1] = f0.y; wa[i & 1][OFFKS(i)][2] = f0.z; wa[i & 1][OFFKS(i)][3] = f0.w;
            }
            tb = lds128(tab + 2048);
            int gg = 0;
#pragma unroll 1
            while (!__all_sync(~0u, (((f1 ^ tag) | (f2 ^ tag) | (f3 ^ tag)) & 1) == 0)) {
                f1 = ldg_relaxed32(r1p); f2 = ldg_relaxed32(r2p); f3 = ldg_relaxed32(r3p);
                if (++gg > 16 * SPIN_LIMIT) { TIMEOUT(3, s); break; }
            }
            if (warp == 0) PROF(9);
            const float v = (__uint_as_float(own) + __uint_as_float(f2)) + (__uint_as_float(f1) + __uint_as_float(f3));
            const bool b8 = tc.w & 8, b16 = tc.w & 16;
            const float recv = __shfl_xor_sync(~0u, v, 8);
            const uint32_t word = b8 ? pack2(recv, v) : pack2(v, recv);
            const uint32_t oth = __shfl_xor_sync(~0u, word, 16);
            const uint32_t wl = b16 ? oth : word, wh = b16 ? word : oth;
            const uint32_t p0 = __shfl_xor_sync(~0u, wl, 2), p1 = __shfl_xor_sync(~0u, wh, 2);
            const uint4 item = t2 ? make_uint4(p0, p1, wl, wh) : make_uint4(wl, wh, p0, p1);
            st_async_v4(tc.y, item, tc.z);
            if (tc.w == 0 && warp == 7) mbar_expect_tx(sb + RB_E, 4096);
            if (warp == 0) PROF(10);
        }
        bar_sync(NB_D, 384);
    }
}

__device__ __forceinline__ void rec_load_tile(uint32_t d, const char* src) {
    cp_async16(d, src);
    cp_async16(d ^ 16, src + 16);
    cp_async16(d + 4096, src + 128);
    cp_async16((d ^ 16) + 4096, src + 128 + 16);
}
__device__ __forceinline__ void rec_store_kvm(uint32_t src, char* dst, int s, int w) {
    dst += (size_t)s * (8 * 2 * HD_ * 2);
    if (w < 2) {
        const uint4 a = lds128(src + (s & 1) * 8192), b = lds128(src + (s & 1) * 8192 + 4096);
        *(uint32_t*)dst = hadd2(a.x, b.x); *(uint32_t*)(dst + 16) = hadd2(a.y, b.y);
        *(uint32_t*)(dst + 32) = hadd2(a.z, b.z); *(uint32_t*)(dst + 48) = hadd2(a.w, b.w);
    } else {
        *(uint4*)dst = lds128(src + (s & 1) * 1024);
    }
}

__device__ __forceinline__ void rec_vo(const RecParams& p, const uint32_t sb, const int cta, const int warp, int lane) {
    const int w = warp - 8, crank = cta & 15, rank = cta & 1;
    uint32_t wo[4][8][4];
    const uint32_t tab = sb + R_TV + (w * 32 + lane) * 16;
    {
        const int t128 = w * 32 + lane;
        const bf16* Wo = p.wo + (size_t)(cta >> 1) * DH_ * D_ + rank * 256;
        const uint32_t stg = sb + R_STG + 2 * 32768;
#pragma unroll
        for (int half = 0; half < 2; half++) {
#pragma unroll 4
            for (int i = t128; i < 2048; i += 128) {
                const int e = i >> 5, ch = i & 31;
                cp_async16(stg + e * 512 + ((ch ^ (e & 7)) << 4), Wo + (size_t)(half * 64 + e) * D_ + ch * 8);
            }
            cp_async_commit();
            cp_async_wait<0>();
            bar_sync(NB_W0 + 2, 128);
#pragma unroll
            for (int j = 0; j < 4; j++)
#pragma unroll
                for (int kk = 0; kk < 4; kk++) {
                    const int e = kk * 16 + (lane >> 4) * 8 + (lane & 7);
                    const int ch = (w * 4 + j) * 2 + ((lane >> 3) & 1);
                    ldsm4t(wo[j][half * 4 + kk][0], wo[j][half * 4 + kk][1], wo[j][half * 4 + kk][2], wo[j][half * 4 + kk][3],
                           stg + e * 512 + ((ch ^ (e & 7)) << 4));
                }
            bar_sync(NB_W0 + 2, 128);
        }
        bar_sync(NB_D, 384);
        const uint32_t l7 = lane & 7, l8 = lane >> 3, g = lane >> 2;
        uint4 v;
        v.x = sb + R_VX + (w >> 1) * 4096 + ((l8 & 1) * 8 + l7) * 128 + (((4 * (w & 1) + (l8 >> 1)) ^ l7) << 4);
        v.y = sb + R_OS + (w >> 1) * 1024 + g * 128 + (((4 * (w & 1)) ^ g) << 4) + (lane & 3) * 4;
        v.z = sb + R_VMS + l7 * 128 + (((4 * (w & 1) + l8) ^ l7) << 4);
        v.w = sb + R_OS + l7 * 128 + ((l8 ^ l7) << 4);
        sts128(tab, v);
        v.x = mapa_u32(sb + R_RS + (crank >> 1) * 512 + ((lane ^ (crank >> 1)) << 4), rank * 8 + w * 2);
        v.y = mapa_u32(sb + RB_E, rank * 8 + w * 2);
        v.z = sb + R_VB + w * 512 + lane * 16;
        v.w = sb + R_SX + lane * 8;
        sts128(tab + 2048, v);
#pragma unroll
        for (int i = 0; i < 8; i++)
            sts128(tab + 4096 + i * 2048, make_uint4(wo[i >> 1][(i & 1) * 4][0], wo[i >> 1][(i & 1) * 4][1], wo[i >> 1][(i & 1) * 4][2], wo[i >> 1][(i & 1) * 4][3]));
        const int row = t128 >> 2, c2 = (lane & 3) * 2, tok = (w & 1) * 4 + (lane >> 3);
        const uint64_t kd = w < 2 ? (uint64_t)(g_kvm + (g * (2 * HD_) + cta * 64 + w * 32 + (lane & 3) * 2))
                                  : (uint64_t)(g_kvm + (tok * (2 * HD_) + HD_ + cta * 64 + (lane & 7) * 8));
        const uint32_t ksrc = w < 2 ? sb + R_QF + (4 + 2 * rank + w) * 512 + lane * 16 : sb + R_VMS + tok * 128 + (((lane & 7) ^ tok) << 4);
        const uint64_t ks = (uint64_t)(g_kv + ((size_t)row * (2 * HD_) + (cta >> 1) * DH_ + c2 * 8));
        const uint32_t dk = sb + R_KX + row * 128 + ((c2 ^ (row & 7)) << 4);
        sts128(tab + 20480, make_uint4((uint32_t)kd, (uint32_t)(kd >> 32), (uint32_t)ks, (uint32_t)(ks >> 32)));
        sts128(tab + 22528, make_uint4(ksrc, dk, lane, sb + lane * 16));
        if (lane == 0) wait_flag(F_KV + 0, 64);
        __syncwarp();
        rec_load_tile(dk, (const char*)ks);
        rec_load_tile(dk + 8192, (const char*)ks + HD_ * 2);
        cp_async_commit();
        cp_async_wait<0>();
    }
    bar_sync(NB_D, 384);
    const uint32_t lane16 = lds32(tab + 22528 + 12);
    uint4 av[8];
#pragma unroll
    for (int i = 0; i < 8; i++) av[i] = lds128(lane16 + R_WV + ((2 * w + (i >> 2)) * 16 + (i & 3)) * 512);
#pragma unroll 1
    for (int s = 0; s < NSEG; s++) {
        {
            if (s > 0) mbar_wait(sb + RB_A, (s - 1) & 1);
            const uint4 tp = lds128(tab + 20480), tq = lds128(tab + 22528);
            if (s > 0) {
                rec_store_kvm(tq.x, (char*)(((uint64_t)tp.y << 32) | tp.x), s - 1, w);
                if ((s & 3) == 0) bar_arrive(NB_K, 160);
            }
            if (s + 1 < NSEG - 1) {
                if (((s + 1) & 3) == 0) { if (tq.z == 0) wait_flag(F_KV + ((s + 1) >> 2), 64); __syncwarp(); }
                const char* src = (const char*)((((uint64_t)tp.w << 32) | tp.z) + (uint64_t)(s + 1) * (32 * 2 * HD_ * 2));
                rec_load_tile(tq.y + ((s + 1) & 1) * 16384, src);
                rec_load_tile(tq.y + ((s + 1) & 1) * 16384 + 8192, src + HD_ * 2);
            }
            cp_async_commit();
        }
        bar_sync(NB_Y, 384);
        uint4 vb;
        const uint4 ta = lds128(tab), tb = lds128(tab + 2048);
        {
            uint32_t bb[8];
            ldsm4(bb[0], bb[1], bb[2], bb[3], lane16 + R_MEM);
            ldsm4(bb[4], bb[5], bb[6], bb[7], lane16 + R_MEM + 512);
            const uint4 a = lds128(lane16 + R_VP + w * 1024), b = lds128(lane16 + R_VP + w * 1024 + 512);
            float va[4] = {__uint_as_float(a.x), __uint_as_float(a.y), __uint_as_float(a.z), __uint_as_float(a.w)};
            float vc[4] = {__uint_as_float(b.x), __uint_as_float(b.y), __uint_as_float(b.z), __uint_as_float(b.w)};
            float vd[4] = {0.f, 0.f, 0.f, 0.f}, ve[4] = {0.f, 0.f, 0.f, 0.f};
            mma16816(vd, av[0].x, av[0].y, av[0].z, av[0].w, bb[0], bb[1]);
            mma16816(ve, av[4].x, av[4].y, av[4].z, av[4].w, bb[0], bb[1]);
            mma16816(va, av[1].x, av[1].y, av[1].z, av[1].w, bb[2], bb[3]);
            mma16816(vc, av[5].x, av[5].y, av[5].z, av[5].w, bb[2], bb[3]);
            mma16816(vd, av[2].x, av[2].y, av[2].z, av[2].w, bb[4], bb[5]);
            mma16816(ve, av[6].x, av[6].y, av[6].z, av[6].w, bb[4], bb[5]);
            mma16816(va, av[3].x, av[3].y, av[3].z, av[3].w, bb[6], bb[7]);
            mma16816(vc, av[7].x, av[7].y, av[7].z, av[7].w, bb[6], bb[7]);
            vb = make_uint4(pack2(va[0] + vd[0], va[1] + vd[1]), pack2(va[2] + vd[2], va[3] + vd[3]),
                            pack2(vc[0] + ve[0], vc[1] + ve[1]), pack2(vc[2] + ve[2], vc[3] + ve[3]));
            st_async_v4(tb.z ^ (1u << 24), vb, (sb + RB_V) ^ (1u << 24));
        }
        if (w == 0) PROF(11);
        if (s != NSEG - 1) {
            uint32_t vx[16];
            const uint32_t vxa = ta.x + (s & 1) * 16384;
            ldsm4t(vx[0], vx[1], vx[2], vx[3], vxa);
            ldsm4t(vx[4], vx[5], vx[6], vx[7], vxa ^ 32);
            ldsm4t(vx[8], vx[9], vx[10], vx[11], vxa + 2048);
            ldsm4t(vx[12], vx[13], vx[14], vx[15], (vxa ^ 32) + 2048);
#pragma unroll
            for (int i = 0; i < 4; i++) {
                const uint4 f0 = lds128(tab + 4096 + i * 2048);
                wo[i >> 1][(i & 1) * 4][0] = f0.x; wo[i >> 1][(i & 1) * 4][1] = f0.y; wo[i >> 1][(i & 1) * 4][2] = f0.z; wo[i >> 1][(i & 1) * 4][3] = f0.w;
            }
            mbar_wait(sb + RB_V, s & 1);
            {
                const uint4 o = lds128(tb.z);
                vb = make_uint4(hadd2(vb.x, o.x), hadd2(vb.y, o.y), hadd2(vb.z, o.z), hadd2(vb.w, o.w));
            }
            bar_sync(NB_S, 320);
            if (w == 0) PROF(4);
            float sv[10];
#pragma unroll
            for (int n = 0; n < 5; n++) { const float2 a = lds64f(tb.w + n * 256); sv[2 * n] = a.x; sv[2 * n + 1] = a.y; }
            { const float2 a = lds64f(tb.w + 5 * 256); sv[0] += a.x; sv[1] += a.y; }
            float mx = fmaxf(fmaxf(fmaxf(sv[2], sv[3]), fmaxf(sv[4], sv[5])), fmaxf(fmaxf(sv[6], sv[7]), fmaxf(sv[8], sv[9])));
            mx = fmaxf(mx, fmaxf(sv[0], sv[1]));
            mx = fmaxf(mx, __shfl_xor_sync(~0u, mx, 1));
            mx = fmaxf(mx, __shfl_xor_sync(~0u, mx, 2));
            uint32_t pf[5];
#pragma unroll
            for (int n = 0; n < 5; n++) pf[n] = pack2(ex2(sv[2 * n] - mx), ex2(sv[2 * n + 1] - mx));
            if (w == 0) PROF(12);
            float oa[4][4] = {{0.f, 0.f, 0.f, 0.f}, {0.f, 0.f, 0.f, 0.f}, {0.f, 0.f, 0.f, 0.f}, {0.f, 0.f, 0.f, 0.f}}, sm[4] = {0.f, 0.f, 0.f, 0.f};
            const uint32_t one = 0x3F803F80u;
            mma1688h(sm, pf[0], one);
            mma1688h(oa[0], pf[0], vb.x);
            mma1688h(oa[1], pf[0], vb.y);
            mma1688h(oa[2], pf[0], vb.z);
            mma1688h(oa[3], pf[0], vb.w);
            mma16816h(sm, pf[1], pf[2], one, one);
#pragma unroll
            for (int n = 0; n < 4; n++) mma16816h(oa[n], pf[1], pf[2], vx[2 * n], vx[2 * n + 1]);
            mma16816h(sm, pf[3], pf[4], one, one);
#pragma unroll
            for (int n = 0; n < 4; n++) mma16816h(oa[n], pf[3], pf[4], vx[8 + 2 * n], vx[8 + 2 * n + 1]);
            float inv;
            asm("rcp.approx.ftz.f32 %0, %1;" : "=f"(inv) : "f"(sm[0]));
#pragma unroll
            for (int n = 0; n < 4; n++) sts32(ta.y ^ (n << 4), pack2(oa[n][0] * inv, oa[n][1] * inv));
            bar_sync(NB_C, 128);
            if (w == 0) PROF(5);
            uint32_t ob[16];
            ldsm4(ob[0], ob[1], ob[2], ob[3], ta.w);
            ldsm4(ob[8], ob[9], ob[10], ob[11], ta.w + 1024);
            ldsm4(ob[4], ob[5], ob[6], ob[7], ta.w ^ 64);
            ldsm4(ob[12], ob[13], ob[14], ob[15], (ta.w ^ 64) + 1024);
#pragma unroll
            for (int i = 4; i < 8; i++) {
                const uint4 f0 = lds128(tab + 4096 + i * 2048);
                wo[i >> 1][(i & 1) * 4][0] = f0.x; wo[i >> 1][(i & 1) * 4][1] = f0.y; wo[i >> 1][(i & 1) * 4][2] = f0.z; wo[i >> 1][(i & 1) * 4][3] = f0.w;
            }
#pragma unroll
            for (int jj = 0; jj < 2; jj++) {
                if (jj == 1 && tb.w == 0) break;
                float acc[4][4];
#pragma unroll
                for (int c = 0; c < 4; c++) { acc[c][0] = acc[c][1] = acc[c][2] = acc[c][3] = 0.f; }
#pragma unroll
                for (int k4 = 0; k4 < 4; k4++)
#pragma unroll
                    for (int c = 0; c < 4; c++) {
                        const int tl = jj * 2 + (c >> 1), ks = (c & 1) * 4 + k4;
                        mma16816(acc[c], wo[tl][ks][0], wo[tl][ks][1], wo[tl][ks][2], wo[tl][ks][3], ob[2 * ks], ob[2 * ks + 1]);
                    }
                uint4 v;
                v.x = pack2(acc[0][0] + acc[1][0], acc[0][1] + acc[1][1]);
                v.y = pack2(acc[0][2] + acc[1][2], acc[0][3] + acc[1][3]);
                v.z = pack2(acc[2][0] + acc[3][0], acc[2][1] + acc[3][1]);
                v.w = pack2(acc[2][2] + acc[3][2], acc[2][3] + acc[3][3]);
                st_async_v4(tb.x + (jj << 24), v, tb.y + (jj << 24));
            }
            if (w == 0) PROF(6);
        } else {
            mbar_wait(sb + RB_V, s & 1);
            const uint4 o = lds128(tb.z);
            vb = make_uint4(hadd2(vb.x, o.x), hadd2(vb.y, o.y), hadd2(vb.z, o.z), hadd2(vb.w, o.w));
            mbar_wait(sb + RB_Q, s & 1);
        }
        if ((w >> 1) == rank) stsm4t(ta.z + (s & 1) * 1024, vb.x, vb.y, vb.z, vb.w);
        cp_async_wait<0>();
        bar_sync(NB_C, 128);
        if (s != NSEG - 1) {
            if (w == 0 && lane == 0) mbar_expect_tx(sb + RB_V, 2048);
            bar_arrive(NB_D, 384);
        }
#pragma unroll
        for (int i = 0; i < 8; i++) av[i] = lds128(lane16 + R_WV + ((2 * w + (i >> 2)) * 16 + (i & 3)) * 512);
    }
    {
        const uint4 tp = lds128(tab + 20480), tq = lds128(tab + 22528);
        rec_store_kvm(tq.x, (char*)(((uint64_t)tp.y << 32) | tp.x), NSEG - 1, w);
    }
    bar_sync(NB_C, 128);
    if (w == 0 && lane == 0) red_release(&g_flags[F_MEM + NRB - 1], 1);
}

__global__ void __launch_bounds__(384, 1) k_rec(const RecParams p) {
    extern __shared__ __align__(1024) unsigned char smem_raw[];
    const uint32_t sb = __shfl_sync(~0u, smem_u32(smem_raw), 0);
    const int warp = __shfl_sync(~0u, threadIdx.x >> 5, 0);
    int lane; asm volatile("mov.u32 %0, %%laneid;" : "=r"(lane));
    const int crank = blockIdx.x & 15, slot = blockIdx.x >> 4;
    asm volatile("griddepcontrol.launch_dependents;");
    if (crank == 0 && threadIdx.x == 0) {
        stg_relaxed32(&g_F[65536 + slot * 64], 0u);
        stg_relaxed32(&g_F[65536 + 1024 + slot * 64], 0u);
    }
    if (threadIdx.x == 0) {
        mbar_init(sb + RB_Q, 9); mbar_init(sb + RB_V, 1); mbar_init(sb + RB_E, 1); mbar_init(sb + RB_A, 1); mbar_init(sb + RB_A1, 1); mbar_init(sb + RB_ROLE, 1);
        asm volatile("fence.mbarrier_init.release.cluster;" ::: "memory");
        mbar_expect_tx(sb + RB_Q, 4096);
        mbar_expect_tx(sb + RB_V, 2048);
        mbar_expect_tx(sb + RB_E, 4096);
        mbar_expect_tx(sb + RB_A, 2048);
        mbar_expect_tx(sb + RB_A1, 2048);
        mbar_expect_tx(sb + RB_ROLE, 4);
    }
    asm volatile("barrier.cluster.arrive.relaxed.aligned;\nbarrier.cluster.wait.aligned;" ::: "memory");
    unsigned role = 0;
    if (crank == 0 && threadIdx.x == 0 && !p.only_pre) {
        unsigned x = 0;
        int tm[2] = {0x7fffffff, 0x7fffffff};
#pragma unroll 1
        for (int i = 0; i < 6; i++) {
            const uint32_t t0 = clk32();
            x = atomicAdd(&g_F[65536 + (i & 1) * 1024 + slot * 64 + (x >> 31)], 1u);
            if (x != (unsigned)(i >> 1)) sts32(sb + R_BAR + 56, x);
            const int dt = (int)(clk32() - t0);
            if (i >= 2) { if (i & 1) tm[1] = min(tm[1], dt); else tm[0] = min(tm[0], dt); }
        }
        const int side = tm[1] > tm[0];
        const unsigned old = atomicAdd(&g_flags[F_SIDE + side * 32], 1u);
        unsigned c0, c1; int gd = 0;
#pragma unroll 1
        do { c0 = ldg_relaxed32(&g_flags[F_SIDE]); c1 = ldg_relaxed32(&g_flags[F_SIDE + 32]); } while ((int)(c0 + c1) < p.ncl && ++gd < 64 * SPIN_LIMIT);
        const int big = c1 > c0;
        role = side == big ? old : (big ? c1 : c0) + old;
        role |= (big ^ 1) << 8;
    }
    __syncwarp();
    if (crank == 0 && warp == 0 && !p.only_pre) {
        role = __shfl_sync(~0u, role, 0);
        if (lane < 16)
            asm volatile("st.async.weak.shared::cluster.mbarrier::complete_tx::bytes.u32 [%0], %1, [%2];"
                         :: "r"(mapa_u32(sb + R_BAR + 48, lane)), "r"(role), "r"(mapa_u32(sb + RB_ROLE, lane)) : "memory");
    }
    if (warp >= 4) {
        const int w8 = warp - 4, nblk = gridDim.x;
        const int cq = lane & 3, rg = w8 * 8 + (lane >> 2);
        const uint32_t red = sb + R_VP;
        const int row0 = blockIdx.x * 8 + w8;
        const uint4* xr = (const uint4*)(p.x + (size_t)row0 * D_);
        uint4 xa = __ldg(xr + lane), xb = __ldg(xr + 32 + lane);
#pragma unroll 1
        for (int sl = blockIdx.x; sl < 96; sl += nblk) {
            uint4 wv[8];
#pragma unroll
            for (int i = 0; i < 8; i++) wv[i] = __ldg((const uint4*)(p.w_mod + (size_t)(rg * 8 + i) * (6 * D_) + sl * 32 + cq * 8));
            const uint32_t cw = __ldg((const uint32_t*)(p.c + rg * 8) + cq);
            const float cl = bflo(cw), ch = bfhi(cw);
            const uint32_t sw = pack2(__fdividef(cl, 1.f + __expf(-cl)), __fdividef(ch, 1.f + __expf(-ch)));
            float a[8];
#pragma unroll
            for (int i = 0; i < 8; i++) a[i] = 0.f;
#pragma unroll
            for (int i = 0; i < 8; i++) {
                const uint32_t sv = __shfl_sync(~0u, sw, (lane & 28) + (i >> 1));
                const float cv = (i & 1) ? bfhi(sv) : bflo(sv);
                a[0] = fmaf(cv, bflo(wv[i].x), a[0]); a[1] = fmaf(cv, bfhi(wv[i].x), a[1]); a[2] = fmaf(cv, bflo(wv[i].y), a[2]); a[3] = fmaf(cv, bfhi(wv[i].y), a[3]);
                a[4] = fmaf(cv, bflo(wv[i].z), a[4]); a[5] = fmaf(cv, bfhi(wv[i].z), a[5]); a[6] = fmaf(cv, bflo(wv[i].w), a[6]); a[7] = fmaf(cv, bfhi(wv[i].w), a[7]);
            }
#pragma unroll
            for (int i = 0; i < 8; i++) { a[i] += __shfl_xor_sync(~0u, a[i], 4); a[i] += __shfl_xor_sync(~0u, a[i], 8); a[i] += __shfl_xor_sync(~0u, a[i], 16); }
            if (lane < 4) {
                sts128(red + w8 * 128 + lane * 32, make_uint4(__float_as_uint(a[0]), __float_as_uint(a[1]), __float_as_uint(a[2]), __float_as_uint(a[3])));
                sts128(red + w8 * 128 + lane * 32 + 16, make_uint4(__float_as_uint(a[4]), __float_as_uint(a[5]), __float_as_uint(a[6]), __float_as_uint(a[7])));
            }
            bar_sync(NB_B, 256);
            if (w8 == 0) {
                float v = 0.f;
#pragma unroll
                for (int i = 0; i < 8; i++) v += lds32f(red + i * 128 + lane * 4);
                g_mod[sl * 32 + lane] = __float2bfloat16_rn(v);
                __syncwarp();
                if (lane == 0) red_release(&g_flags[F_MOD + (sl >= 32)], 1);
            }
            bar_sync(NB_B, 256);
        }
        uint32_t c1[8], sm[8];
        int row = row0;
#pragma unroll 1
        while (true) {
            const uint32_t v[8] = {xa.x, xa.y, xa.z, xa.w, xb.x, xb.y, xb.z, xb.w};
            uint32_t mu2, r[8]; float rden;
            ln_stats(v, mu2, rden);
            if (row == row0) {
                if (lane == 0) wait_flag(F_MOD, 32);
                __syncwarp();
                load_mod8(g_mod + D_, lane, c1);
                load_mod8(g_mod, lane, sm);
#pragma unroll
                for (int i = 0; i < 8; i++) c1[i] = hadd2(c1[i], 0x3F803F80u);
            } else if (row + 512 < S_) {
                xr = (const uint4*)(p.x + (size_t)(row + 512) * D_); xa = __ldg(xr + lane); xb = __ldg(xr + 32 + lane);
            }
            ln_apply(v, mu2, rden, c1, sm, r);
            uint4* hr = (uint4*)(g_h + (size_t)row * D_);
            hr[lane] = make_uint4(r[0], r[1], r[2], r[3]); hr[32 + lane] = make_uint4(r[4], r[5], r[6], r[7]);
            bar_sync(NB_B, 256);
            if (w8 == (row >> 7 & 7) && lane == 0) red_release(&g_flags[F_H + (row >> 7)], 1);
            __syncwarp();
            if (row == row0) {
                if (!p.only_pre) mbar_wait(sb + RB_ROLE, 0);
                const int cl = p.only_pre ? slot : (int)(lds32(sb + R_BAR + 48) & 255);
                row = cl < 4 ? (nblk + cl * 16 + crank) * 8 + w8 : S_;
                if (row < S_) { xr = (const uint4*)(p.x + (size_t)row * D_); xa = __ldg(xr + lane); xb = __ldg(xr + 32 + lane); }
            } else {
                row += 512;
            }
            if (row >= S_) break;
        }
    }
    if (p.only_pre) return;
    mbar_wait(sb + RB_ROLE, 0);
    const int rolew = __shfl_sync(~0u, lds32(sb + R_BAR + 48), 0);
    const int cl = rolew & 255;
    if (cl >= 4) return;
    const int cta = cl * 16 + crank;
    if (warp < 8) rec_qk(p, sb, cta, warp, lane, rolew >> 8);
    else rec_vo(p, sb, cta, warp, lane);
}

enum { J_KV = 0, J_QA = 1, J_O = 2, J_LN = 3, J_UP = 4, J_DN = 5, J_UP2 = 8, J_END = 9 };
constexpr int NJ_O = 2 * OSPLIT, NJ_O2 = 2 * OSPLIT2, NJ_LN = 8, NJ_LN2 = 16, NJ_UP = 14, NJ_UP2 = 28, NJ_DN = 8, NJ_LN1 = 8  ;
constexpr uint64_t pk8(int a, int b, int c, int d, int e, int f, int g, int h) {
    return (uint64_t)a | ((uint64_t)b << 8) | ((uint64_t)c << 16) | ((uint64_t)d << 24) | ((uint64_t)e << 32) | ((uint64_t)f << 40) | ((uint64_t)g << 48) | ((uint64_t)h << 56);
}
constexpr uint64_t NJ_C = pk8(32, 16, NJ_O, NJ_LN, NJ_UP, NJ_DN, 0, 0), NJ_F = pk8(32, 16, NJ_O2, NJ_LN2, NJ_UP2, NJ_DN, 0, 0);
constexpr uint64_t TG_C = pk8(2 * NJ_LN1, 64, 32, 2 * NJ_O, 2 * NJ_LN, 2 * NJ_UP, 32, 0), TG_F = pk8(2 * NJ_LN1, 64, 32, 2 * NJ_O2, 2 * NJ_LN2, 2 * NJ_UP2, 32, 0);
constexpr uint64_t NJ_L = pk8(32, 32, 2 * OSPLIT3, NJ_LN2, NJ_UP2, 2 * NJ_DN, 0, 0), TG_L = pk8(2 * NJ_LN1, 64, 64, 4 * OSPLIT3, 2 * NJ_LN2, 2 * NJ_UP2, 32, 0);
__device__ __forceinline__ uint64_t nj_tab(int rb) { return rb < FINE_RB ? NJ_C : (rb < NRB - 1 ? NJ_F : NJ_L); }
__device__ __forceinline__ uint64_t tg_tab(int rb) { return rb < FINE_RB ? TG_C : (rb < NRB - 1 ? TG_F : TG_L); }
__device__ __forceinline__ int o_nk(int rb) { return rb < FINE_RB ? 64 / OSPLIT : (rb < NRB - 1 ? 64 / OSPLIT2 : 64 / OSPLIT3); }
constexpr uint64_t PRIO = pk8(4, 10, 9, 8, 7, 6, 3, 0);
__device__ __forceinline__ int pick_job(int lane, int qmask, int& idx) {
    const int rb = lane & 15, half = lane >> 4;
    const uint64_t nj = nj_tab(rb) >> (8 * half);
    const uint64_t tg = tg_tab(rb) >> (8 * half);
    const unsigned* cp = &g_flags[F_CLAIM + half * 32 + rb];
    const unsigned* dp = &g_flags[half * 32 + rb];
    int gd = 0;
#pragma unroll 1
    while (true) {
        const unsigned c0 = ldg_relaxed32(cp), c1 = ldg_relaxed32(cp + 64), c2 = ldg_relaxed32(cp + 128);
        const unsigned d0 = ldg_relaxed32(dp - (half && rb ? 1 : 0)), d1 = ldg_relaxed32(dp + 64), d2 = ldg_relaxed32(dp + 128);
        const unsigned cl[3] = {c0, c1, c2}, dv[3] = {d0, d1, d2};
        unsigned key = 0xffffu, key2 = 0xffffu;
        bool pre = false;
#pragma unroll
        for (int i = 0; i < 3; i++) {
            const int q = half + 2 * i;
            const bool have = ((qmask >> q) & 1) && cl[i] < (unsigned)((nj >> (16 * i)) & 255);
            bool ready = have && dv[i] >= (unsigned)((tg >> (16 * i)) & 255);
            unsigned pr = (unsigned)((PRIO >> (8 * q)) & 255);
            if (i == 0 && rb <= 1 - half) ready = have;
            if (i == 0 && half && rb >= FINE_RB) pr = 5;
            if (ready) key = min(key, (pr << 8) | (rb << 4) | q);
            if (have) key2 = min(key2, rb >= FINE_RB ? (0x100u | (q << 4) | rb) : (i == 0 ? 0u : 0x1000u));
            pre |= have && i == 0 && !half;
        }
        const bool anypre = __any_sync(~0u, pre);
        if (anypre && (key & 15) == J_QA) key = 0xffffu;
        key = __reduce_min_sync(~0u, key);
        key2 = __reduce_min_sync(~0u, key2);
        if (key2 == 0xffffu) return J_END;
        int pq, prb;
        if (key != 0xffffu) { pq = key & 15; prb = (key >> 4) & 15; }
        else if (key2 >= 0x120u && key2 < 0x1000u) { pq = (key2 >> 4) & 15; prb = key2 & 15; }
        else {
            __nanosleep(IDLE_NS);
            if (++gd > 16 * SPIN_LIMIT) { TIMEOUT(5, 0); return J_END; }
            continue;
        }
        int c = 0;
        if (lane == 0) c = (int)atomicAdd(&g_flags[F_CLAIM + pq * 32 + prb], 1u);
        c = __shfl_sync(~0u, c, 0);
        if (c < (int)((nj_tab(prb) >> (8 * pq)) & 255)) {
            idx = pq * 512 + prb * 32 + c;
            int acq = 0;
            if (pq != J_QA) {
                if (lane == 0 && ld_acquire(&g_flags[pq * 32 + prb]) >= (unsigned)((tg_tab(prb) >> (8 * pq)) & 255)) {
                    asm volatile("fence.proxy.async.global;" ::: "memory");
                    acq = 1 << 24;
                }
            }
            return (pq == J_UP && prb >= FINE_RB ? J_UP2 : pq) | (prb << 8) | (c << 16) | acq;
        }
    }
}
__device__ __forceinline__ int op_row(int rb, int split) {
    return rb < FINE_RB ? split * S_ + rb * 128
                        : (rb < NRB - 1 ? OSPLIT * S_ + (split * (NRB - FINE_RB) + rb - FINE_RB) * 128 : OSPLIT * S_ + (OSPLIT2 * (NRB - FINE_RB) + split) * 128);
}

struct Pipe { uint32_t stage, phase; };
__device__ __forceinline__ void pipe_next(Pipe& p) { if (++p.stage == W_NST) { p.stage = 0; p.phase ^= 1; } }

__device__ __forceinline__ void scheduler(const Params& p, uint32_t sb, int lane) {
    const uint32_t bars = sb + SM_BAR;
    uint32_t ph = 0;
#pragma unroll 1
    while (true) {
        mbar_wait(bars + B_REQ, ph);
        int j = 4095;
        const int jd = pick_job(lane, p.qmask, j);
        if (lane == 0) { sts32(bars + B_NEXT, (uint32_t)jd); sts32(bars + B_NEXT + 4, (uint32_t)j); mbar_arrive(bars + B_RSP); }
        ph ^= 1;
        if (jd == J_END) break;
        __syncwarp();
    }
}

__device__ __forceinline__ void producer(const Params& p, uint32_t sb) {
    Pipe pp{0, 1};
    const uint32_t bars = sb + SM_BAR;
    uint32_t seq = 0, h_seen = 0;
    mbar_arrive(bars + B_REQ);
#pragma unroll 1
    while (true) {
        mbar_wait(bars + B_RSP, seq & 1);
        const int jd = (int)lds32(bars + B_NEXT), j = (int)lds32(bars + B_NEXT + 4);
        int left = (jd & 255) == J_DN ? 15 : ((jd & 255) == J_QA ? (((jd >> 8) & 255) == NRB - 1 ? 10 : 12) : ((jd & 255) == J_O ? o_nk((jd >> 8) & 255) : ((jd & 255) == J_LN ? 1 : 8)));
        left = max(left - PICK_AHEAD, 1);
        TR(j, 1);
        const int type = jd & 255, rb = (jd >> 8) & 255, cb = (jd >> 16) & 255;
        const bool fine = rb >= FINE_RB, acquired = (jd >> 24) & 1;
        bool first = true;
        auto begin_stage = [&](uint32_t bytes) -> uint32_t {
            mbar_wait(bars + B_EMPTY + pp.stage * 8, pp.phase);
            if (first) { sts32(bars + B_RING + (seq & 7) * 4, (uint32_t)jd); sts32(bars + B_RING + 32 + (seq & 7) * 4, (uint32_t)j); first = false; }
            const uint32_t fb = bars + B_FULL + pp.stage * 8;
            if (bytes) mbar_expect_tx(fb, bytes); else mbar_arrive(fb);
            if (--left == 0 && type != J_END) mbar_arrive(bars + B_REQ);
            return fb;
        };
        if (type == J_END || type == J_LN) {
            if (type == J_LN && !(h_seen >> 31)) { wait_flag(F_MOD + 1, 64); h_seen |= 1u << 31; }

            TR(j, 2);
            begin_stage(0); pipe_next(pp);
            seq++;
            if (type == J_END) break;
            continue;
        }
        const CUtensorMap *ta, *tb0, *tb1;
        int k0 = 0, nk = 8, n0 = cb * 256, n1 = n0 + 128, nb = 4, dep = -1;
        unsigned tgt = 0;
        switch (type) {
            case J_KV: ta = &p.tm_h; tb0 = tb1 = cb < 16 ? &p.tm_wk : &p.tm_wv; n0 = (cb & 15) * 256; n1 = n0 + 128; dep = F_H + rb; tgt = 2 * NJ_LN1; break;
            case J_QA: ta = &p.tm_h; tb0 = tb1 = &p.tm_wq; dep = F_H + rb; tgt = 2 * NJ_LN1; if (rb == NRB - 1) { n0 = (cb >> 1) * 256; n1 = n0 + 128; } break;
            case J_O: ta = &p.tm_o; tb0 = tb1 = &p.tm_wo; n0 = (cb & 1) * 256; n1 = n0 + 128; nk = o_nk(rb); k0 = (cb >> 1) * nk * 64;
                      dep = F_O + rb; tgt = rb == NRB - 1 ? 64 : 32; break;
            case J_UP: ta = &p.tm_h2; tb0 = &p.tm_wg; tb1 = &p.tm_wu; n0 = n1 = cb * 128; dep = F_H2 + rb; tgt = 2 * NJ_LN; break;
            case J_UP2: ta = &p.tm_h2; tb0 = &p.tm_wg; tb1 = &p.tm_wu; n0 = n1 = cb * 64; nb = 2; dep = F_H2 + rb; tgt = 2 * NJ_LN2; break;
            default: ta = &p.tm_act; tb0 = tb1 = &p.tm_wd; n0 = cb * 64; nk = 0; break;
        }
        const int m0 = rb * 128;
        if (type == J_DN && rb == NRB - 1) {
            n0 = (cb >> 1) * 64;
            const int mh = m0 + (cb & 1) * 64;
#pragma unroll 1
            for (int kb = 0; kb < 14; kb++) {
                const uint32_t fb = begin_stage(32768);
                const uint32_t st = sb + pp.stage * W_STAGE;
                const int k = kb * 128;
                tma_load2d(st + 32768, tb0, n0, k, fb);
                tma_load2d(st + 40960, tb0, n0, k + 64, fb);
                if (kb == 0) { if (!acquired) { wait_flag(F_ACT + rb, 2 * NJ_UP2); asm volatile("fence.proxy.async.global;" ::: "memory"); } TR(j, 2); }
                tma_load2d(st, ta, k, mh, fb);
                tma_load2d(st + 8192, ta, k + 64, mh, fb);
                pipe_next(pp);
            }
            const uint32_t fb = begin_stage(8192);
            tma_load2d(sb + pp.stage * W_STAGE, &p.tm_x1, n0, mh, fb);
            pipe_next(pp);
            seq++;
            continue;
        }
        if (type == J_DN) {
#pragma unroll 1
            for (int kb = 0; kb < 14; kb++) {
                const uint32_t fb = begin_stage(49152);
                const uint32_t st = sb + pp.stage * W_STAGE;
                const int k = kb * 128;
                tma_load2d(st + 32768, tb0, n0, k, fb);
                tma_load2d(st + 40960, tb0, n0, k + 64, fb);
                if (kb == 0) { if (!acquired) { wait_flag(F_ACT + rb, 2 * (fine ? NJ_UP2 : NJ_UP)); asm volatile("fence.proxy.async.global;" ::: "memory"); } TR(j, 2); }
                tma_load2d(st, ta, k, m0, fb);
                tma_load2d(st + 8192, ta, k, m0 + 64, fb);
                tma_load2d(st + 16384, ta, k + 64, m0, fb);
                tma_load2d(st + 24576, ta, k + 64, m0 + 64, fb);
                pipe_next(pp);
            }
        }
#pragma unroll 1
        for (int kb = 0; kb < nk; kb++) {
            const uint32_t fb = begin_stage(16384 + nb * 8192);
            const uint32_t st = sb + pp.stage * W_STAGE;
            const int k = k0 + kb * 64;
            tma_load2d(st + 16384, tb0, n0, k, fb);
            if (nb == 4) {
                tma_load2d(st + 16384 + 8192, tb0, n0 + 64, k, fb);
                tma_load2d(st + 16384 + 16384, tb1, n1, k, fb);
                tma_load2d(st + 16384 + 24576, tb1, n1 + 64, k, fb);
            } else if (nb == 2) {
                tma_load2d(st + 16384 + 8192, tb1, n1, k, fb);
            }
            if (kb == 0) {
                if (acquired && dep < 16) h_seen |= 1u << dep;
                if (dep >= 0 && !acquired && !(dep < 16 && ((h_seen >> dep) & 1))) {
                    wait_flag(dep, tgt);
                    if (type != J_O) asm volatile("fence.proxy.async.global;" ::: "memory");
                    if (dep < 16) h_seen |= 1u << dep;
                }
                TR(j, 2);
            }
            tma_load2d(st, ta, k, m0, fb);
            tma_load2d(st + 8192, ta, k, m0 + 64, fb);
            pipe_next(pp);
        }
        if (type == J_QA) {
            wait_flag(F_KV + rb, 64);
#pragma unroll 1
            for (int i = 0; i < (rb == NRB - 1 ? 2 : 4); i++) {
                const uint32_t fb = begin_stage(40960);
                const uint32_t st = sb + pp.stage * W_STAGE;
                const int col = (i & 1) * HD_ + (rb == NRB - 1 ? cb : cb * 2 + (i >> 1)) * DH_;
                tma_load2d(st, &p.tm_kv, col, m0, fb);
                tma_load2d(st + 8192, &p.tm_kv, col, m0 + 64, fb);
                tma_load2d(st + 16384, &p.tm_kv, col + 64, m0, fb);
                tma_load2d(st + 24576, &p.tm_kv, col + 64, m0 + 64, fb);
                if (i == 0) { wait_flag(F_MEM + rb, 64); asm volatile("fence.proxy.async.global;" ::: "memory"); }
                tma_load2d(st + 32768, &p.tm_kvm, col, rb * 32, fb);
                tma_load2d(st + 36864, &p.tm_kvm, col + 64, rb * 32, fb);
                pipe_next(pp);
            }
        } else if (type == J_DN) {
            const uint32_t fb = begin_stage(16384);
            const uint32_t st = sb + pp.stage * W_STAGE;
            tma_load2d(st, &p.tm_x1, n0, m0, fb);
            tma_load2d(st + 8192, &p.tm_x1, n0, m0 + 64, fb);
            pipe_next(pp);
        }
        seq++;
    }
}

__device__ __forceinline__ void store_warp(const Params& p, uint32_t sb, int wg, int lane) {
    const uint32_t bars = sb + SM_BAR;
    uint32_t seq = 0;
#pragma unroll 1
    while (true) {
        bar_sync(NB_ST + wg, 160);
        const uint32_t jd = lds32(bars + B_RING + (seq & 7) * 4);
        seq++;
        const int type = jd & 255, rb = (jd >> 8) & 255, cb = (jd >> 16) & 255;
        if (type == J_END) break;
        const uint32_t src = sb + W_STG + wg * 16384;
        const CUtensorMap* tm = nullptr; int n0 = cb * 256, nbox = 4, mrow = rb * 128 + wg * 64, flag = 0;
        switch (type) {
            case J_KV: tm = &p.tm_kv; flag = F_KV + rb; break;
            case J_QA: tm = &p.tm_o; flag = F_O + rb; if (rb == NRB - 1) { n0 = cb * 128; nbox = 2; } break;
            case J_O: tm = &p.tm_op; n0 = (cb & 1) * 256; mrow = op_row(rb, cb >> 1) + wg * 64; flag = F_OP + rb; break;
            case J_LN: flag = F_H2 + rb; nbox = 0; break;
            case J_UP: tm = &p.tm_act; n0 = cb * 128; nbox = 2; flag = F_ACT + rb; break;
            case J_UP2: tm = &p.tm_act; n0 = cb * 64; nbox = 1; flag = F_ACT + rb; break;
            default: tm = &p.tm_out; n0 = cb * 64; nbox = 1; flag = -1;
                     if (rb == NRB - 1) { n0 = (cb >> 1) * 64; mrow = rb * 128 + (cb & 1) * 64; nbox = wg == 0; } break;
        }
        if (nbox == 4) {
            if (lane == 0) {
                tma_store2d(tm, src, n0, mrow);
                tma_store2d(tm, src + 8192, n0 + 64, mrow);
                bulk_commit();
                asm volatile("cp.async.bulk.wait_group.read 0;" ::: "memory");
                mbar_arrive(bars + B_STGFREE + wg * 8);
            }
            __syncwarp();
            bar_sync(NB_ST + wg, 160);
            n0 += 128; nbox = 2;
        }
        if (lane == 0) {
            if (nbox) {
                tma_store2d(tm, src, n0, mrow);
                if (nbox == 2) tma_store2d(tm, src + 8192, n0 + 64, mrow);
                bulk_commit();
                asm volatile("cp.async.bulk.wait_group.read 0;" ::: "memory");
                mbar_arrive(bars + B_STGFREE + wg * 8);
                bulk_wait0();
                if (flag >= 0) asm volatile("red.relaxed.gpu.global.add.u32 [%0], 1;" :: "l"(&g_flags[flag]) : "memory");
            } else {
                mbar_arrive(bars + B_STGFREE + wg * 8);
                if (flag >= 0) red_release(&g_flags[flag], 1);
            }
        }
        __syncwarp();
    }
}

__device__ __forceinline__ float gelu_tanh(float x) {
    const float t = x * fmaf(-0.10294324397f, x * x, -2.30220819814f);
    float r; asm("rcp.approx.ftz.f32 %0, %1;" : "=f"(r) : "f"(1.f + ex2(t)));
    return x * r;
}

#define CTR(i) do {} while (0)

__device__ __forceinline__ void ln2_row(const Params& p, int rb, int r, int lane, bool wait) {
    const int row = rb * 128 + r, nsplit = 64 / o_nk(rb);
    const uint4* xr = (const uint4*)(p.x + (size_t)row * D_);
    const uint4 xa = __ldg(xr + lane), xb = __ldg(xr + 32 + lane);
    uint32_t ga[8], c1[8], sm[8];
    load_mod8(g_mod + 2 * D_, lane, ga);
    load_mod8(g_mod + 4 * D_, lane, c1);
    load_mod8(g_mod + 3 * D_, lane, sm);
    float a[16];
#pragma unroll
    for (int i = 0; i < 16; i++) a[i] = 0.f;
    const uint4* src = (const uint4*)(g_op + (size_t)(op_row(rb, 0) + r) * D_) + lane;
    const int sstride = (op_row(rb, 1) - op_row(rb, 0)) * (D_ / 8);
    if (wait) { if (lane == 0) wait_flag(F_OP + rb, 4 * nsplit); __syncwarp(); }
    uint4 u[2][8];
#pragma unroll
    for (int sp = 0; sp < 4; sp++) { u[0][2 * sp] = __ldcg(src + sp * sstride); u[0][2 * sp + 1] = __ldcg(src + sp * sstride + 32); }
    if (nsplit > 4) {
#pragma unroll
        for (int sp = 0; sp < 4; sp++) { u[1][2 * sp] = __ldcg(src + (4 + sp) * sstride); u[1][2 * sp + 1] = __ldcg(src + (4 + sp) * sstride + 32); }
    }
#pragma unroll 1
    for (int s0 = 0; s0 < nsplit; s0 += 4) {
#pragma unroll
        for (int sp = 0; sp < 8; sp++) {
            float* q = a + (sp & 1) * 8;
            const uint4 w = u[0][sp];
            q[0] += bflo(w.x); q[1] += bfhi(w.x); q[2] += bflo(w.y); q[3] += bfhi(w.y);
            q[4] += bflo(w.z); q[5] += bfhi(w.z); q[6] += bflo(w.w); q[7] += bfhi(w.w);
            u[0][sp] = u[1][sp];
        }
        if (s0 + 8 < nsplit) {
#pragma unroll
            for (int sp = 0; sp < 4; sp++) { u[1][2 * sp] = __ldcg(src + (s0 + 8 + sp) * sstride); u[1][2 * sp + 1] = __ldcg(src + (s0 + 8 + sp) * sstride + 32); }
        }
    }
    const uint32_t xv[8] = {xa.x, xa.y, xa.z, xa.w, xb.x, xb.y, xb.z, xb.w};
    uint32_t v[8], r8[8];
#pragma unroll
    for (int i = 0; i < 8; i++) v[i] = hadd2(xv[i], hmul2(ga[i], pack2(a[2 * i], a[2 * i + 1])));
    uint4* x1r = (uint4*)(g_x1 + (size_t)row * D_);
    x1r[lane] = make_uint4(v[0], v[1], v[2], v[3]); x1r[32 + lane] = make_uint4(v[4], v[5], v[6], v[7]);
    uint32_t mu2; float rden;
    ln_stats(v, mu2, rden);
#pragma unroll
    for (int i = 0; i < 8; i++) c1[i] = hadd2(c1[i], 0x3F803F80u);
    ln_apply(v, mu2, rden, c1, sm, r8);
    uint4* hr = (uint4*)(g_h2 + (size_t)row * D_);
    hr[lane] = make_uint4(r8[0], r8[1], r8[2], r8[3]); hr[32 + lane] = make_uint4(r8[4], r8[5], r8[6], r8[7]);
}

__device__ __forceinline__ void consumer(const Params& p, uint32_t sb, int warp, int lane) {
    const uint32_t bars = sb + SM_BAR;
    const int wg = warp >> 2, wl = warp & 3;
    const uint32_t l7 = lane & 7, l8 = lane >> 3, g = lane >> 2, t = lane & 3;
    Pipe pp{0, 0};
    uint32_t seq = 0, stg_phase = 1;
    const int srow = wl * 16 + l7 + (l8 & 1) * 8;
    const uint32_t stg_base = sb + W_STG + wg * 16384 + srow * 128;
    const uint32_t sx = ((lane >> 4) ^ (srow & 7)) << 4;
#pragma unroll 1
    while (true) {
        mbar_wait(bars + B_FULL + pp.stage * 8, pp.phase);
        const uint32_t jd = lds32(bars + B_RING + (seq & 7) * 4);
        CTR(3);
        seq++;
        const int type = jd & 255, rb = (jd >> 8) & 255, cb = (jd >> 16) & 255;
        if (type == J_END) { mbar_wait(bars + B_STGFREE + wg * 8, stg_phase); bar_arrive(NB_ST + wg, 160); break; }
        if (type == J_LN) {
            __syncwarp();
            if (lane == 0) mbar_arrive(bars + B_EMPTY + pp.stage * 8);
            pipe_next(pp);
            const int nr = rb >= FINE_RB ? 1 : 2;
#pragma unroll 1
            for (int rr = 0; rr < nr; rr++) ln2_row(p, rb, (cb * 8 + warp) * nr + rr, lane, !((jd >> 24) & 1) && rr == 0);
            mbar_wait(bars + B_STGFREE + wg * 8, stg_phase); stg_phase ^= 1;
            CTR(4); CTR(5);
            bar_arrive(NB_ST + wg, 160);
            continue;
        }
        if (type == J_DN || type == J_UP2) {
            float acc[64];
#pragma unroll
            for (int i = 0; i < 64; i++) acc[i] = 0.f;
            const bool ksplit = type == J_DN && rb == NRB - 1;
            if (ksplit) {
#pragma unroll 1
                for (int kb = 0; kb < 14; kb++) {
                    if (kb) mbar_wait(bars + B_FULL + pp.stage * 8, pp.phase);
                    const uint32_t st = sb + pp.stage * W_STAGE;
                    const uint64_t da = mkdesc(st + wg * 8192, 16, 1024), db = mkdesc(st + 32768 + wg * 8192, 8192, 1024);
                    wg_fence();
#pragma unroll
                    for (int ks = 0; ks < 4; ks++) wgmma_n64(acc, da + ks * 2, db + ks * 128);
                    wg_commit();
                    wg_wait0();
                    if (lane == 0) mbar_arrive(bars + B_EMPTY + pp.stage * 8);
                    pipe_next(pp);
                }
                const uint32_t xb = sb + W_STG + 16384 + (wl * 32 + lane) * 16;
                if (wg == 1) {
                    mbar_wait(bars + B_STGFREE + 8, stg_phase);
#pragma unroll
                    for (int i = 0; i < 8; i++)
                        sts128(xb + i * 2048, make_uint4(__float_as_uint(acc[4 * i]), __float_as_uint(acc[4 * i + 1]), __float_as_uint(acc[4 * i + 2]), __float_as_uint(acc[4 * i + 3])));
                }
                bar_sync(NB_M, 256);
                if (wg == 0) {
#pragma unroll
                    for (int i = 0; i < 8; i++) {
                        const uint4 o = lds128(xb + i * 2048);
                        acc[4 * i] += __uint_as_float(o.x); acc[4 * i + 1] += __uint_as_float(o.y); acc[4 * i + 2] += __uint_as_float(o.z); acc[4 * i + 3] += __uint_as_float(o.w);
                    }
                }
                bar_sync(NB_M, 256);
            } else if (type == J_DN) {
#pragma unroll 1
                for (int kb = 0; kb < 14; kb++) {
                    if (kb) mbar_wait(bars + B_FULL + pp.stage * 8, pp.phase);
                    const uint32_t st = sb + pp.stage * W_STAGE;
                    const uint64_t da = mkdesc(st + wg * 8192, 16, 1024), db = mkdesc(st + 32768, 8192, 1024);
                    wg_fence();
#pragma unroll
                    for (int ks = 0; ks < 8; ks++) wgmma_n64(acc, da + (ks >> 2) * 1024 + (ks & 3) * 2, db + ks * 128);
                    wg_commit();
                    wg_wait0();
                    if (lane == 0) mbar_arrive(bars + B_EMPTY + pp.stage * 8);
                    pipe_next(pp);
                }
            } else {
#pragma unroll 1
                for (int kb = 0; kb < 8; kb++) {
                    if (kb) mbar_wait(bars + B_FULL + pp.stage * 8, pp.phase);
                    const uint32_t st = sb + pp.stage * W_STAGE;
                    const uint64_t da = mkdesc(st + wg * 8192, 16, 1024), db = mkdesc(st + 16384, 8192, 1024);
                    wg_fence();
#pragma unroll
                    for (int ks = 0; ks < 4; ks++) wgmma_n128(acc, da + ks * 2, db + ks * 128, 1);
                    wg_commit();
                    wg_wait0();
                    if (lane == 0) mbar_arrive(bars + B_EMPTY + pp.stage * 8);
                    pipe_next(pp);
                }
            }
            CTR(4);
            if (type == J_UP2) {
                mbar_wait(bars + B_STGFREE + wg * 8, stg_phase); stg_phase ^= 1;
#pragma unroll
                for (int j = 0; j < 4; j++) {
                    uint32_t r[4];
#pragma unroll
                    for (int q = 0; q < 4; q++) {
                        const uint32_t gw = pack2(acc[8 * j + 2 * q], acc[8 * j + 2 * q + 1]);
                        const uint32_t uw = pack2(acc[32 + 8 * j + 2 * q], acc[32 + 8 * j + 2 * q + 1]);
                        r[q] = hmul2(pack2(gelu_tanh(bflo(gw)), gelu_tanh(bfhi(gw))), uw);
                    }
                    stsm4(stg_base + (sx ^ (j << 5)), r[0], r[1], r[2], r[3]);
                }
            } else {
                mbar_wait(bars + B_FULL + pp.stage * 8, pp.phase);
                const uint32_t st = sb + pp.stage * W_STAGE;
                mbar_wait(bars + B_STGFREE + wg * 8, stg_phase); stg_phase ^= 1;
                const uint32_t* gb = (const uint32_t*)(g_mod + 5 * D_ + (ksplit ? cb >> 1 : cb) * 64) + t;
                const uint32_t xa = st + (ksplit ? 0 : wg * 8192) + (wl * 16 + g) * 128 + (g << 4) + t * 4;
#pragma unroll
                for (int j = 0; j < 4; j++) {
                    uint32_t r[4];
#pragma unroll
                    for (int q = 0; q < 4; q++) {
                        const int nt = 2 * j + (q >> 1);
                        const uint32_t xw = lds32((xa ^ ((nt & 7) << 4)) + (nt >> 3) * 16384 + (q & 1) * 1024);
                        r[q] = hadd2(xw, hmul2(__ldcg(gb + nt * 4), pack2(acc[8 * j + 2 * q], acc[8 * j + 2 * q + 1])));
                    }
                    stsm4(stg_base + (j >> 2) * 8192 + (sx ^ ((2 * j & 7) << 4)), r[0], r[1], r[2], r[3]);
                }
                __syncwarp();
                if (lane == 0) mbar_arrive(bars + B_EMPTY + pp.stage * 8);
                pipe_next(pp);
            }
            fence_async_smem();
            CTR(5);
            bar_arrive(NB_ST + wg, 160);
            continue;
        }
        float acc[128];
#pragma unroll
        for (int i = 0; i < 128; i++) acc[i] = 0.f;
        const int nk = type == J_O ? o_nk(rb) : 8;
#pragma unroll 1
        for (int kb = 0; kb < nk; kb++) {
            if (kb) mbar_wait(bars + B_FULL + pp.stage * 8, pp.phase);
            const uint32_t st = sb + pp.stage * W_STAGE;
            const uint64_t da = mkdesc(st + wg * 8192, 16, 1024), db = mkdesc(st + 16384, 8192, 1024);
            wg_fence();
#pragma unroll
            for (int ks = 0; ks < 4; ks++) wgmma_n256(acc, da + ks * 2, db + ks * 128, 1);
            wg_commit();
            wg_wait0();
            if (lane == 0) mbar_arrive(bars + B_EMPTY + pp.stage * 8);
            pipe_next(pp);
        }
        CTR(4);
        if (type == J_QA) {
            uint32_t qf[64];
#pragma unroll
            for (int i = 0; i < 64; i++) qf[i] = pack2(acc[2 * i], acc[2 * i + 1]);
            const int sg = warp >> 1, half = warp & 1;
            const float sc = 0.08838834764831845f * 1.4426950408889634f;
            const uint32_t xoff = (sg >> 1) * 8192 + ((sg & 1) * 32 + l7) * 128;
            const uint32_t moff = 32768 + (sg * 8 + l7) * 128;
            const uint32_t kch = (l8 ^ l7) << 4;
            const uint32_t vch = ((l8 & 1) ^ l7) << 4;
            if (rb == NRB - 1 && (cb & 1)) {
#pragma unroll
                for (int i = 0; i < 32; i++) qf[i] = qf[32 + i];
            }
#pragma unroll 1
            for (int hh = rb == NRB - 1; hh < 2; hh++) {
                mbar_wait(bars + B_FULL + pp.stage * 8, pp.phase);
                uint32_t st = sb + pp.stage * W_STAGE;
                float sa[5][4];
#pragma unroll
                for (int n = 0; n < 5; n++) sa[n][0] = sa[n][1] = sa[n][2] = sa[n][3] = 0.f;
#pragma unroll
                for (int i = 0; i < 4; i++) {
                    const uint32_t* q = qf + i * 8;
                    uint32_t kk[5][4];
                    ldsm4(kk[0][0], kk[0][1], kk[0][2], kk[0][3], st + moff + (i >> 1) * 4096 + (kch ^ ((i & 1) * 64)));
#pragma unroll
                    for (int n = 1; n < 5; n++)
                        ldsm4(kk[n][0], kk[n][1], kk[n][2], kk[n][3], st + xoff + (n - 1) * 1024 + (i >> 1) * 16384 + (kch ^ ((i & 1) * 64)));
#pragma unroll
                    for (int n = 0; n < 5; n++) mma16816(sa[n], q[0], q[1], q[2], q[3], kk[n][0], kk[n][1]);
#pragma unroll
                    for (int n = 0; n < 5; n++) mma16816(sa[n], q[4], q[5], q[6], q[7], kk[n][2], kk[n][3]);
                }
                __syncwarp();
                if (lane == 0) mbar_arrive(bars + B_EMPTY + pp.stage * 8);
                pipe_next(pp);
                const int iq0 = half * 16 + g - 2 * t, iq1 = iq0 + 8;
                float m0 = fmaxf(sa[0][0], sa[0][1]), m1 = fmaxf(sa[0][2], sa[0][3]);
#pragma unroll
                for (int n = 1; n < 5; n++) {
#pragma unroll
                    for (int e = 0; e < 2; e++) {
                        const int jx = (n - 1) * 8 + e;
                        if (jx > iq0) sa[n][e] = -3.0e38f;
                        if (jx > iq1) sa[n][2 + e] = -3.0e38f;
                        m0 = fmaxf(m0, sa[n][e]); m1 = fmaxf(m1, sa[n][2 + e]);
                    }
                }
                m0 = fmaxf(m0, __shfl_xor_sync(~0u, m0, 1)); m1 = fmaxf(m1, __shfl_xor_sync(~0u, m1, 1));
                m0 = fmaxf(m0, __shfl_xor_sync(~0u, m0, 2)); m1 = fmaxf(m1, __shfl_xor_sync(~0u, m1, 2));
                m0 *= -sc; m1 *= -sc;
                float l0 = 0.f, l1 = 0.f;
                uint32_t p0[5], p1[5];
#pragma unroll
                for (int n = 0; n < 5; n++) {
                    const float e0 = ex2(fmaf(sa[n][0], sc, m0)), e1 = ex2(fmaf(sa[n][1], sc, m0));
                    const float e2 = ex2(fmaf(sa[n][2], sc, m1)), e3 = ex2(fmaf(sa[n][3], sc, m1));
                    l0 += e0 + e1; l1 += e2 + e3;
                    p0[n] = pack2(e0, e1); p1[n] = pack2(e2, e3);
                }
                l0 += __shfl_xor_sync(~0u, l0, 1); l1 += __shfl_xor_sync(~0u, l1, 1);
                l0 += __shfl_xor_sync(~0u, l0, 2); l1 += __shfl_xor_sync(~0u, l1, 2);
                const float i0 = __fdividef(1.f, l0), i1 = __fdividef(1.f, l1);
                mbar_wait(bars + B_FULL + pp.stage * 8, pp.phase);
                st = sb + pp.stage * W_STAGE;
                mbar_wait(bars + B_STGFREE + wg * 8, stg_phase); stg_phase ^= 1;
#pragma unroll
                for (int i = 0; i < 32; i++) qf[i] = qf[32 + i];
#pragma unroll 1
                for (int bx = 0; bx < 2; bx++) {
                    float o[8][4];
                    uint32_t vm[8], v0[4][4], v1[4][4];
#pragma unroll
                    for (int ep = 0; ep < 4; ep++) {
                        ldsm2t(vm[2 * ep], vm[2 * ep + 1], st + moff + bx * 4096 + (vch ^ (ep << 5)));
                        const uint32_t va = st + xoff + (l8 >> 1) * 1024 + bx * 16384 + (vch ^ (ep << 5));
                        ldsm4t(v0[ep][0], v0[ep][1], v0[ep][2], v0[ep][3], va);
                        ldsm4t(v1[ep][0], v1[ep][1], v1[ep][2], v1[ep][3], va + 2048);
                    }
#pragma unroll
                    for (int n = 0; n < 8; n++) { o[n][0] = o[n][1] = o[n][2] = o[n][3] = 0.f; mma16816(o[n], p0[0], p1[0], p0[1], p1[1], vm[n], v0[n >> 1][n & 1]); }
#pragma unroll
                    for (int n = 0; n < 8; n++) mma16816(o[n], p0[2], p1[2], p0[3], p1[3], v0[n >> 1][2 + (n & 1)], v1[n >> 1][n & 1]);
#pragma unroll
                    for (int n = 0; n < 8; n++) mma1688(o[n], p0[4], p1[4], v1[n >> 1][2 + (n & 1)]);
#pragma unroll
                    for (int ep = 0; ep < 4; ep++)
                        stsm4(stg_base + bx * 8192 + (sx ^ (ep << 5)),
                              pack2(o[2 * ep][0] * i0, o[2 * ep][1] * i0), pack2(o[2 * ep][2] * i1, o[2 * ep][3] * i1),
                              pack2(o[2 * ep + 1][0] * i0, o[2 * ep + 1][1] * i0), pack2(o[2 * ep + 1][2] * i1, o[2 * ep + 1][3] * i1));
                }
                __syncwarp();
                if (lane == 0) mbar_arrive(bars + B_EMPTY + pp.stage * 8);
                pipe_next(pp);
                if (hh == 0) { fence_async_smem(); bar_arrive(NB_ST + wg, 160); }
            }
        } else if (type == J_UP) {
            mbar_wait(bars + B_STGFREE + wg * 8, stg_phase); stg_phase ^= 1;
#pragma unroll
            for (int j = 0; j < 8; j++) {
                uint32_t r[4];
#pragma unroll
                for (int q = 0; q < 4; q++) {
                    const uint32_t gw = pack2(acc[8 * j + 2 * q], acc[8 * j + 2 * q + 1]);
                    const uint32_t uw = pack2(acc[64 + 8 * j + 2 * q], acc[64 + 8 * j + 2 * q + 1]);
                    r[q] = hmul2(pack2(gelu_tanh(bflo(gw)), gelu_tanh(bfhi(gw))), uw);
                }
                stsm4(stg_base + (j >> 2) * 8192 + (sx ^ ((2 * j & 7) << 4)), r[0], r[1], r[2], r[3]);
            }
        } else {
#pragma unroll
            for (int rd = 0; rd < 2; rd++) {
                mbar_wait(bars + B_STGFREE + wg * 8, stg_phase); stg_phase ^= 1;
#pragma unroll
                for (int j = rd * 8; j < rd * 8 + 8; j++)
                    stsm4(stg_base + ((j >> 2) & 1) * 8192 + (sx ^ ((2 * j & 7) << 4)),
                          pack2(acc[8 * j], acc[8 * j + 1]), pack2(acc[8 * j + 2], acc[8 * j + 3]),
                          pack2(acc[8 * j + 4], acc[8 * j + 5]), pack2(acc[8 * j + 6], acc[8 * j + 7]));
                if (rd == 0) { fence_async_smem(); bar_arrive(NB_ST + wg, 160); }
            }
        }
        fence_async_smem();
        CTR(5);
        bar_arrive(NB_ST + wg, 160);
    }
}

__global__ void __launch_bounds__(384, 1) k_work(const __grid_constant__ Params p) {
    extern __shared__ __align__(1024) unsigned char smem_raw[];
    const uint32_t sb = smem_u32(smem_raw);
    if (sb & 1023) __trap();
    const int warp = __shfl_sync(~0u, threadIdx.x >> 5, 0);
    int lane; asm volatile("mov.u32 %0, %%laneid;" : "=r"(lane));
    if (threadIdx.x == 0) {
        const uint32_t bars = sb + SM_BAR;
        for (int i = 0; i < W_NST; i++) { mbar_init(bars + B_FULL + i * 8, 1); mbar_init(bars + B_EMPTY + i * 8, 8); }
        mbar_init(bars + B_STGFREE, 1); mbar_init(bars + B_STGFREE + 8, 1); mbar_init(bars + B_REQ, 1); mbar_init(bars + B_RSP, 1);
        asm volatile("fence.mbarrier_init.release.cluster;" ::: "memory");
    }
    __syncthreads();
    if (warp < 8) {
        asm volatile("setmaxnreg.inc.sync.aligned.u32 224;");
        consumer(p, sb, warp, lane);
    } else {
        asm volatile("setmaxnreg.dec.sync.aligned.u32 56;");
        if (warp == 8) { if (lane == 0) producer(p, sb); }
        else if (warp < 11) store_warp(p, sb, warp - 9, lane);
        else scheduler(p, sb, lane);
        __syncwarp();
        bar_sync(NB_W0, 128);
        if (warp == 8 && p.qmask == 0xff) {
            unsigned last = 0;
            if (lane == 0) { __threadfence(); last = atomicAdd(&g_flags[F_DONE], 1u) == gridDim.x - 1; }
            if (__shfl_sync(~0u, last, 0))
                for (int i = lane; i < F_TOTAL; i += 32) g_flags[i] = 0;
        }
    }
}

typedef CUresult (*EncodeFn)(CUtensorMap*, CUtensorMapDataType, cuuint32_t, void*, const cuuint64_t*, const cuuint64_t*,
                             const cuuint32_t*, const cuuint32_t*, CUtensorMapInterleave, CUtensorMapSwizzle,
                             CUtensorMapL2promotion, CUtensorMapFloatOOBfill);

static void make_map(EncodeFn enc, CUtensorMap* m, const void* ptr, uint64_t rows, uint64_t cols, uint32_t box_rows) {
    cuuint64_t dims[2] = {cols, rows};
    cuuint64_t strides[1] = {cols * 2};
    cuuint32_t box[2] = {64, box_rows};
    cuuint32_t es[2] = {1, 1};
    enc(m, CU_TENSOR_MAP_DATA_TYPE_BFLOAT16, 2, const_cast<void*>(ptr), dims, strides, box, es, CU_TENSOR_MAP_INTERLEAVE_NONE,
        CU_TENSOR_MAP_SWIZZLE_128B, CU_TENSOR_MAP_L2_PROMOTION_L2_256B, CU_TENSOR_MAP_FLOAT_OOB_FILL_NONE);
}
template <typename T> static void* sym_addr(T& sym) { void* p = nullptr; cudaGetSymbolAddress(&p, sym); return p; }

extern "C" void kernel_launch(void* const* d_in, const int* in_sizes, int n_in, void* d_out, int out_size) {
    static Params prm;
    static RecParams rp;
    static int n_sm = 132;
    static bool ready = false;
    static const void* key[14];
    bool same = ready;
    for (int i = 0; i < 13 && same; i++) same = key[i] == d_in[i];
    same = same && key[13] == d_out;
    if (!same) {
        void* fn = nullptr;
        cudaDriverEntryPointQueryResult qr;
        cudaGetDriverEntryPoint("cuTensorMapEncodeTiled", &fn, cudaEnableDefault, &qr);
        EncodeFn enc = (EncodeFn)fn;
        make_map(enc, &prm.tm_h, sym_addr(g_h), S_, D_, 64);
        make_map(enc, &prm.tm_kv, sym_addr(g_kv), S_, 2 * HD_, 64);
        make_map(enc, &prm.tm_kvm, sym_addr(g_kvm), NSEG * 8, 2 * HD_, 32);
        make_map(enc, &prm.tm_o, sym_addr(g_o), S_, HD_, 64);
        make_map(enc, &prm.tm_op, sym_addr(g_op), OP_ROWS, D_, 64);
        make_map(enc, &prm.tm_h2, sym_addr(g_h2), S_, D_, 64);
        make_map(enc, &prm.tm_act, sym_addr(g_act), S_, DF_, 64);
        make_map(enc, &prm.tm_x1, sym_addr(g_x1), S_, D_, 64);
        make_map(enc, &prm.tm_out, d_out, S_, D_, 64);
        make_map(enc, &prm.tm_wq, d_in[2], D_, HD_, 64);
        make_map(enc, &prm.tm_wk, d_in[3], D_, HD_, 64);
        make_map(enc, &prm.tm_wv, d_in[4], D_, HD_, 64);
        make_map(enc, &prm.tm_wo, d_in[5], HD_, D_, 64);
        make_map(enc, &prm.tm_wg, d_in[8], D_, DF_, 64);
        make_map(enc, &prm.tm_wu, d_in[9], D_, DF_, 64);
        make_map(enc, &prm.tm_wd, d_in[10], DF_, D_, 64);
        prm.x = (const bf16*)d_in[0]; prm.c = (const bf16*)d_in[11]; prm.w_mod = (const bf16*)d_in[12];
        rp.mem0 = (const bf16*)d_in[1]; rp.x = prm.x; rp.c = prm.c; rp.w_mod = prm.w_mod;
        rp.wq = (const bf16*)d_in[2]; rp.wk = (const bf16*)d_in[3]; rp.wv = (const bf16*)d_in[4]; rp.wo = (const bf16*)d_in[5];
        cudaDeviceGetAttribute(&n_sm, cudaDevAttrMultiProcessorCount, 0);
        cudaFuncSetAttribute(k_work, cudaFuncAttributeMaxDynamicSharedMemorySize, SMEM_BYTES);
        cudaFuncSetAttribute(k_rec, cudaFuncAttributeMaxDynamicSharedMemorySize, R_SMEM);
        cudaFuncSetAttribute(k_rec, cudaFuncAttributeNonPortableClusterSizeAllowed, 1);
        {
            cudaLaunchConfig_t cfg = {};
            cfg.gridDim = dim3(128); cfg.blockDim = dim3(384); cfg.dynamicSmemBytes = R_SMEM;
            cudaLaunchAttribute at[1];
            at[0].id = cudaLaunchAttributeClusterDimension; at[0].val.clusterDim.x = 16; at[0].val.clusterDim.y = 1; at[0].val.clusterDim.z = 1;
            cfg.attrs = at; cfg.numAttrs = 1;
            int n = 0;
            cudaOccupancyMaxActiveClusters(&n, k_rec, &cfg);
            rp.ncl = n < 4 ? 4 : (n > 8 ? 8 : n);
        }
        for (int i = 0; i < 13; i++) key[i] = d_in[i];
        key[13] = d_out;
        ready = true;
    }
    cudaStream_t st = cudaStreamPerThread;
    auto launch_rec = [&]() {
        cudaLaunchConfig_t cfg = {};
        cfg.gridDim = dim3(16 * rp.ncl); cfg.blockDim = dim3(384); cfg.dynamicSmemBytes = R_SMEM; cfg.stream = st;
        cudaLaunchAttribute at[1];
        at[0].id = cudaLaunchAttributeClusterDimension; at[0].val.clusterDim.x = 16; at[0].val.clusterDim.y = 1; at[0].val.clusterDim.z = 1;
        cfg.attrs = at; cfg.numAttrs = 1;
        cudaLaunchKernelEx(&cfg, k_rec, rp);
    };
    auto launch_work = [&](int qmask, int pdl) {
        prm.qmask = qmask;
        cudaLaunchConfig_t cfg = {};
        cfg.gridDim = dim3(n_sm); cfg.blockDim = dim3(384); cfg.dynamicSmemBytes = SMEM_BYTES; cfg.stream = st;
        cudaLaunchAttribute at[1];
        at[0].id = cudaLaunchAttributeProgrammaticStreamSerialization; at[0].val.programmaticStreamSerializationAllowed = 1;
        cfg.attrs = at; cfg.numAttrs = pdl;
        cudaLaunchKernelEx(&cfg, k_work, prm);
    };
    launch_rec();
    launch_work(0xff, 1);
}
```

```cpp
#include <cuda_runtime.h>
#include <cuda_bf16.h>
#include <cuda.h>
#include <stdint.h>

typedef __nv_bfloat16 bf16;
#define IDLE_NS 150
#define FLAG_NS 20

constexpr int S_ = 2048, D_ = 512, DH_ = 128, HD_ = 4096, NSEG = 64, DF_ = 1792;
constexpr int NRB = 16;
constexpr int OSPLIT = 4;

__device__ __align__(1024) bf16 g_h[S_ * D_];
__device__ __align__(1024) bf16 g_kv[S_ * 2 * HD_];
__device__ __align__(1024) bf16 g_kvm[NSEG * 8 * 2 * HD_];
__device__ __align__(1024) bf16 g_o[S_ * HD_];
#define FINE_RB_ 12
constexpr int FINE_RB = FINE_RB_;
#define OSPLIT2_ 8
constexpr int OSPLIT2 = OSPLIT2_;
constexpr int OSPLIT3 = 16;
constexpr int OP_ROWS = OSPLIT * S_ + OSPLIT2 * (NRB - FINE_RB) * 128 + OSPLIT3 * 128;
__device__ __align__(1024) bf16 g_op[OP_ROWS * D_];
__device__ __align__(1024) bf16 g_x1[S_ * D_];
__device__ __align__(1024) bf16 g_h2[S_ * D_];
__device__ __align__(1024) bf16 g_act[S_ * DF_];
__device__ __align__(1024) bf16 g_mod[6 * D_];
__device__ uint32_t g_Fraw[131072 + 65536 + 2048];
#define g_F ((uint32_t*)(((uint64_t)g_Fraw + 0x7FFFFull) & ~0x7FFFFull))
constexpr int F_H = 0, F_MEM = 32, F_O = 64, F_OP = 96, F_H2 = 128, F_ACT = 160, F_MOD = 192, F_KV = 224, F_CLAIM = 256  ,
              F_SIDE = 512  , F_DONE = 576, F_TOTAL = 608;
__device__ __align__(128) unsigned int g_flags[F_TOTAL];
#define TR(j, i) do {} while (0)

__device__ __forceinline__ uint32_t smem_u32(const void* p) { return (uint32_t)__cvta_generic_to_shared(p); }
__device__ __forceinline__ uint32_t clk32() { uint32_t c; asm volatile("mov.u32 %0, %%clock;" : "=r"(c)); return c; }
__device__ __forceinline__ uint32_t mapa_u32(uint32_t addr, uint32_t rank) {
    uint32_t r; asm volatile("mapa.shared::cluster.u32 %0, %1, %2;" : "=r"(r) : "r"(addr), "r"(rank)); return r;
}
__device__ __forceinline__ void mbar_init(uint32_t bar, uint32_t cnt) {
    asm volatile("mbarrier.init.shared::cta.b64 [%0], %1;" :: "r"(bar), "r"(cnt) : "memory");
}
__device__ __forceinline__ void mbar_expect_tx(uint32_t bar, uint32_t bytes) {
    asm volatile("mbarrier.arrive.expect_tx.shared::cta.b64 _, [%0], %1;" :: "r"(bar), "r"(bytes) : "memory");
}
__device__ __forceinline__ void mbar_arrive(uint32_t bar) {
    asm volatile("mbarrier.arrive.shared::cta.b64 _, [%0];" :: "r"(bar) : "memory");
}
__device__ __forceinline__ bool mbar_try_wait(uint32_t bar, uint32_t parity) {
    uint32_t ok;
    asm volatile("{\n.reg .pred p;\nmbarrier.try_wait.parity.shared::cta.b64 p, [%1], %2;\nselp.u32 %0, 1, 0, p;\n}"
                 : "=r"(ok) : "r"(bar), "r"(parity) : "memory");
    return ok;
}
constexpr int SPIN_LIMIT = 1 << 18;
#define TIMEOUT(code, info) do {} while (0)
__device__ __forceinline__ void mbar_wait(uint32_t bar, uint32_t parity) {
    int g = 0;
#pragma unroll 1
    while (!mbar_try_wait(bar, parity)) { if (++g >= SPIN_LIMIT) { TIMEOUT(0, bar & 255); break; } }
}
__device__ __forceinline__ void bar_sync(int id, int n) { asm volatile("bar.sync %0, %1;" :: "r"(id), "r"(n) : "memory"); }
__device__ __forceinline__ void bar_arrive(int id, int n) { asm volatile("bar.arrive %0, %1;" :: "r"(id), "r"(n) : "memory"); }
__device__ __forceinline__ void st_async_v2(uint32_t addr, float a, float b, uint32_t bar) {
    asm volatile("st.async.weak.shared::cluster.mbarrier::complete_tx::bytes.v2.f32 [%0], {%1,%2}, [%3];"
                 :: "r"(addr), "f"(a), "f"(b), "r"(bar) : "memory");
}
__device__ __forceinline__ void st_async_v4(uint32_t addr, uint4 v, uint32_t bar) {
    asm volatile("st.async.weak.shared::cluster.mbarrier::complete_tx::bytes.v4.b32 [%0], {%1,%2,%3,%4}, [%5];"
                 :: "r"(addr), "r"(v.x), "r"(v.y), "r"(v.z), "r"(v.w), "r"(bar) : "memory");
}
__device__ __forceinline__ void stg_relaxed32(uint32_t* p, uint32_t v) {
    asm volatile("st.relaxed.gpu.global.b32 [%0], %1;" :: "l"(p), "r"(v) : "memory");
}
__device__ __forceinline__ uint32_t ldg_relaxed32(const uint32_t* p) {
    uint32_t v; asm volatile("ld.relaxed.gpu.global.b32 %0, [%1];" : "=r"(v) : "l"(p) : "memory"); return v;
}
__device__ __forceinline__ unsigned int ld_acquire(const unsigned int* p) {
    unsigned int v; asm volatile("ld.acquire.gpu.global.u32 %0, [%1];" : "=r"(v) : "l"(p) : "memory"); return v;
}
__device__ __forceinline__ void red_release(unsigned int* p, unsigned int v) {
    asm volatile("red.release.gpu.global.add.u32 [%0], %1;" :: "l"(p), "r"(v) : "memory");
}
__device__ __forceinline__ void wait_flag(int idx, unsigned int target) {
    const unsigned int* p = &g_flags[idx];
    int g = 0;
#pragma unroll 1
    while (ld_acquire(p) < target) { __nanosleep(FLAG_NS); if (++g >= 64 * SPIN_LIMIT) { TIMEOUT(2, idx); break; } }
}
__device__ __forceinline__ void cp_async16(uint32_t dst, const void* src) {
    asm volatile("cp.async.cg.shared.global [%0], [%1], 16;" :: "r"(dst), "l"(src) : "memory");
}
__device__ __forceinline__ void cp_async_commit() { asm volatile("cp.async.commit_group;" ::: "memory"); }
template <int N> __device__ __forceinline__ void cp_async_wait() { asm volatile("cp.async.wait_group %0;" :: "n"(N) : "memory"); }
__device__ __forceinline__ void ldsm4(uint32_t& r0, uint32_t& r1, uint32_t& r2, uint32_t& r3, uint32_t addr) {
    asm volatile("ldmatrix.sync.aligned.m8n8.x4.shared.b16 {%0,%1,%2,%3}, [%4];" : "=r"(r0), "=r"(r1), "=r"(r2), "=r"(r3) : "r"(addr) : "memory");
}
__device__ __forceinline__ void ldsm4t(uint32_t& r0, uint32_t& r1, uint32_t& r2, uint32_t& r3, uint32_t addr) {
    asm volatile("ldmatrix.sync.aligned.m8n8.x4.trans.shared.b16 {%0,%1,%2,%3}, [%4];" : "=r"(r0), "=r"(r1), "=r"(r2), "=r"(r3) : "r"(addr) : "memory");
}
__device__ __forceinline__ void ldsm2t(uint32_t& r0, uint32_t& r1, uint32_t addr) {
    asm volatile("ldmatrix.sync.aligned.m8n8.x2.trans.shared.b16 {%0,%1}, [%2];" : "=r"(r0), "=r"(r1) : "r"(addr) : "memory");
}
__device__ __forceinline__ void stsm4(uint32_t addr, uint32_t r0, uint32_t r1, uint32_t r2, uint32_t r3) {
    asm volatile("stmatrix.sync.aligned.m8n8.x4.shared.b16 [%0], {%1,%2,%3,%4};" :: "r"(addr), "r"(r0), "r"(r1), "r"(r2), "r"(r3) : "memory");
}
__device__ __forceinline__ void stsm4t(uint32_t addr, uint32_t r0, uint32_t r1, uint32_t r2, uint32_t r3) {
    asm volatile("stmatrix.sync.aligned.m8n8.x4.trans.shared.b16 [%0], {%1,%2,%3,%4};" :: "r"(addr), "r"(r0), "r"(r1), "r"(r2), "r"(r3) : "memory");
}
__device__ __forceinline__ void stsm2t(uint32_t addr, uint32_t r0, uint32_t r1) {
    asm volatile("stmatrix.sync.aligned.m8n8.x2.trans.shared.b16 [%0], {%1,%2};" :: "r"(addr), "r"(r0), "r"(r1) : "memory");
}
__device__ __forceinline__ void mma16816(float* d, uint32_t a0, uint32_t a1, uint32_t a2, uint32_t a3, uint32_t b0, uint32_t b1) {
    asm volatile("mma.sync.aligned.m16n8k16.row.col.f32.bf16.bf16.f32 {%0,%1,%2,%3}, {%4,%5,%6,%7}, {%8,%9}, {%0,%1,%2,%3};"
                 : "+f"(d[0]), "+f"(d[1]), "+f"(d[2]), "+f"(d[3]) : "r"(a0), "r"(a1), "r"(a2), "r"(a3), "r"(b0), "r"(b1));
}
__device__ __forceinline__ void mma1688(float* d, uint32_t a0, uint32_t a1, uint32_t b0) {
    asm volatile("mma.sync.aligned.m16n8k8.row.col.f32.bf16.bf16.f32 {%0,%1,%2,%3}, {%4,%5}, {%6}, {%0,%1,%2,%3};"
                 : "+f"(d[0]), "+f"(d[1]), "+f"(d[2]), "+f"(d[3]) : "r"(a0), "r"(a1), "r"(b0));
}
__device__ __forceinline__ void mma16816h(float* d, uint32_t a0, uint32_t a2, uint32_t b0, uint32_t b1) {
    asm volatile("{\n.reg .b32 ju, jv;\nmma.sync.aligned.m16n8k16.row.col.f32.bf16.bf16.f32 {%0,%1,%2,%3}, {%4,ju,%5,jv}, {%6,%7}, {%0,%1,%2,%3};\n}"
                 : "+f"(d[0]), "+f"(d[1]), "+f"(d[2]), "+f"(d[3]) : "r"(a0), "r"(a2), "r"(b0), "r"(b1));
}
__device__ __forceinline__ void mma1688h(float* d, uint32_t a0, uint32_t b0) {
    asm volatile("{\n.reg .b32 ju;\nmma.sync.aligned.m16n8k8.row.col.f32.bf16.bf16.f32 {%0,%1,%2,%3}, {%4,ju}, {%5}, {%0,%1,%2,%3};\n}"
                 : "+f"(d[0]), "+f"(d[1]), "+f"(d[2]), "+f"(d[3]) : "r"(a0), "r"(b0));
}
__device__ __forceinline__ uint32_t movm(uint32_t a) {
    uint32_t d; asm volatile("movmatrix.sync.aligned.m8n8.trans.b16 %0, %1;" : "=r"(d) : "r"(a)); return d;
}
__device__ __forceinline__ uint32_t pack2(float lo, float hi) {
    uint32_t r; asm("cvt.rn.bf16x2.f32 %0, %1, %2;" : "=r"(r) : "f"(hi), "f"(lo)); return r;
}
__device__ __forceinline__ float bflo(uint32_t w) { return __uint_as_float(w << 16); }
__device__ __forceinline__ float bfhi(uint32_t w) { return __uint_as_float(w & 0xffff0000u); }
__device__ __forceinline__ float rbf(float x) { return __bfloat162float(__float2bfloat16_rn(x)); }
__device__ __forceinline__ float ex2(float x) { float y; asm("ex2.approx.ftz.f32 %0, %1;" : "=f"(y) : "f"(x)); return y; }
__device__ __forceinline__ void sts128(uint32_t addr, uint4 v) {
    asm volatile("st.shared.v4.b32 [%0], {%1,%2,%3,%4};" :: "r"(addr), "r"(v.x), "r"(v.y), "r"(v.z), "r"(v.w) : "memory");
}
__device__ __forceinline__ uint4 lds128(uint32_t addr) {
    uint4 v; asm volatile("ld.shared.v4.b32 {%0,%1,%2,%3}, [%4];" : "=r"(v.x), "=r"(v.y), "=r"(v.z), "=r"(v.w) : "r"(addr) : "memory"); return v;
}
__device__ __forceinline__ float2 lds64f(uint32_t addr) {
    float2 v; asm volatile("ld.shared.v2.f32 {%0,%1}, [%2];" : "=f"(v.x), "=f"(v.y) : "r"(addr) : "memory"); return v;
}
__device__ __forceinline__ float lds32f(uint32_t addr) {
    float v; asm volatile("ld.shared.f32 %0, [%1];" : "=f"(v) : "r"(addr) : "memory"); return v;
}
__device__ __forceinline__ uint32_t lds32(uint32_t addr) {
    uint32_t v; asm volatile("ld.shared.b32 %0, [%1];" : "=r"(v) : "r"(addr) : "memory"); return v;
}
__device__ __forceinline__ void sts32(uint32_t addr, uint32_t v) { asm volatile("st.shared.b32 [%0], %1;" :: "r"(addr), "r"(v) : "memory"); }
__device__ __forceinline__ void sts64f(uint32_t addr, float a, float b) { asm volatile("st.shared.v2.f32 [%0], {%1,%2};" :: "r"(addr), "f"(a), "f"(b) : "memory"); }

__device__ __forceinline__ void tma_load2d(uint32_t dst, const CUtensorMap* tm, int c0, int c1, uint32_t bar) {
    asm volatile("cp.async.bulk.tensor.2d.shared::cluster.global.mbarrier::complete_tx::bytes [%0], [%1, {%3, %4}], [%2];"
                 :: "r"(dst), "l"(tm), "r"(bar), "r"(c0), "r"(c1) : "memory");
}
__device__ __forceinline__ void tma_store2d(const CUtensorMap* tm, uint32_t src, int c0, int c1) {
    asm volatile("cp.async.bulk.tensor.2d.global.shared::cta.bulk_group [%0, {%2, %3}], [%1];"
                 :: "l"(tm), "r"(src), "r"(c0), "r"(c1) : "memory");
}
__device__ __forceinline__ void bulk_commit() { asm volatile("cp.async.bulk.commit_group;" ::: "memory"); }
__device__ __forceinline__ void bulk_wait0() { asm volatile("cp.async.bulk.wait_group 0;" ::: "memory"); }
__device__ __forceinline__ void fence_async_smem() { asm volatile("fence.proxy.async.shared::cta;" ::: "memory"); }
__device__ __forceinline__ void fence_async_all() { asm volatile("fence.proxy.async;" ::: "memory"); }

__device__ __forceinline__ void wg_fence() { asm volatile("wgmma.fence.sync.aligned;" ::: "memory"); }
__device__ __forceinline__ void wg_commit() { asm volatile("wgmma.commit_group.sync.aligned;" ::: "memory"); }
__device__ __forceinline__ void wg_wait0() { asm volatile("wgmma.wait_group.sync.aligned 0;" ::: "memory"); }
__device__ __forceinline__ uint64_t mkdesc(uint32_t saddr, uint32_t lbo, uint32_t sbo) {
    return (uint64_t)((saddr & 0x3FFFF) >> 4) | ((uint64_t)(lbo >> 4) << 16) | ((uint64_t)(sbo >> 4) << 32) | (1ull << 62);
}
#define ACC8(i) "+f"(d[i]), "+f"(d[i + 1]), "+f"(d[i + 2]), "+f"(d[i + 3]), "+f"(d[i + 4]), "+f"(d[i + 5]), "+f"(d[i + 6]), "+f"(d[i + 7])
__device__ __forceinline__ void wgmma_n256(float* d, uint64_t da, uint64_t db, int scale_d) {
    asm volatile(
        "{\n.reg .pred p;\nsetp.ne.b32 p, %130, 0;\n"
        "wgmma.mma_async.sync.aligned.m64n256k16.f32.bf16.bf16 "
        "{%0,%1,%2,%3,%4,%5,%6,%7,%8,%9,%10,%11,%12,%13,%14,%15,%16,%17,%18,%19,%20,%21,%22,%23,%24,%25,%26,%27,%28,%29,%30,%31,"
        "%32,%33,%34,%35,%36,%37,%38,%39,%40,%41,%42,%43,%44,%45,%46,%47,%48,%49,%50,%51,%52,%53,%54,%55,%56,%57,%58,%59,%60,%61,%62,%63,"
        "%64,%65,%66,%67,%68,%69,%70,%71,%72,%73,%74,%75,%76,%77,%78,%79,%80,%81,%82,%83,%84,%85,%86,%87,%88,%89,%90,%91,%92,%93,%94,%95,"
        "%96,%97,%98,%99,%100,%101,%102,%103,%104,%105,%106,%107,%108,%109,%110,%111,%112,%113,%114,%115,%116,%117,%118,%119,%120,%121,%122,%123,%124,%125,%126,%127}, "
        "%128, %129, p, 1, 1, 0, 1;\n}"
        : ACC8(0), ACC8(8), ACC8(16), ACC8(24), ACC8(32), ACC8(40), ACC8(48), ACC8(56),
          ACC8(64), ACC8(72), ACC8(80), ACC8(88), ACC8(96), ACC8(104), ACC8(112), ACC8(120)
        : "l"(da), "l"(db), "r"(scale_d));
}
__device__ __forceinline__ void wgmma_n128(float* d, uint64_t da, uint64_t db, int scale_d) {
    asm volatile(
        "{\n.reg .pred p;\nsetp.ne.b32 p, %66, 0;\n"
        "wgmma.mma_async.sync.aligned.m64n128k16.f32.bf16.bf16 "
        "{%0,%1,%2,%3,%4,%5,%6,%7,%8,%9,%10,%11,%12,%13,%14,%15,%16,%17,%18,%19,%20,%21,%22,%23,%24,%25,%26,%27,%28,%29,%30,%31,"
        "%32,%33,%34,%35,%36,%37,%38,%39,%40,%41,%42,%43,%44,%45,%46,%47,%48,%49,%50,%51,%52,%53,%54,%55,%56,%57,%58,%59,%60,%61,%62,%63}, "
        "%64, %65, p, 1, 1, 0, 1;\n}"
        : ACC8(0), ACC8(8), ACC8(16), ACC8(24), ACC8(32), ACC8(40), ACC8(48), ACC8(56)
        : "l"(da), "l"(db), "r"(scale_d));
}

__device__ __forceinline__ void wgmma_n64(float* d, uint64_t da, uint64_t db) {
    asm volatile(
        "wgmma.mma_async.sync.aligned.m64n64k16.f32.bf16.bf16 "
        "{%0,%1,%2,%3,%4,%5,%6,%7,%8,%9,%10,%11,%12,%13,%14,%15,%16,%17,%18,%19,%20,%21,%22,%23,%24,%25,%26,%27,%28,%29,%30,%31}, "
        "%32, %33, 1, 1, 1, 0, 1;"
        : ACC8(0), ACC8(8), ACC8(16), ACC8(24)
        : "l"(da), "l"(db));
}
__device__ __forceinline__ uint32_t hadd2(uint32_t a, uint32_t b) { uint32_t r; asm("add.rn.bf16x2 %0, %1, %2;" : "=r"(r) : "r"(a), "r"(b)); return r; }
__device__ __forceinline__ uint32_t hsub2(uint32_t a, uint32_t b) { uint32_t r; asm("sub.rn.bf16x2 %0, %1, %2;" : "=r"(r) : "r"(a), "r"(b)); return r; }
__device__ __forceinline__ uint32_t hmul2(uint32_t a, uint32_t b) { uint32_t r; asm("mul.rn.bf16x2 %0, %1, %2;" : "=r"(r) : "r"(a), "r"(b)); return r; }
__device__ __forceinline__ void load_mod8(const bf16* m, int lane, uint32_t* v) {
    const uint4 a = __ldcg((const uint4*)m + lane), b = __ldcg((const uint4*)m + 32 + lane);
    v[0] = a.x; v[1] = a.y; v[2] = a.z; v[3] = a.w; v[4] = b.x; v[5] = b.y; v[6] = b.z; v[7] = b.w;
}
__device__ __forceinline__ void ln_stats(const uint32_t* x, uint32_t& mu2, float& rden) {
    float s = 0.f;
#pragma unroll
    for (int i = 0; i < 8; i++) s += bflo(x[i]) + bfhi(x[i]);
#pragma unroll
    for (int o = 16; o > 0; o >>= 1) s += __shfl_xor_sync(~0u, s, o);
    const float mean = s * (1.f / D_);
    float q = 0.f;
#pragma unroll
    for (int i = 0; i < 8; i++) { const float d0 = bflo(x[i]) - mean, d1 = bfhi(x[i]) - mean; q = fmaf(d0, d0, q); q = fmaf(d1, d1, q); }
#pragma unroll
    for (int o = 16; o > 0; o >>= 1) q += __shfl_xor_sync(~0u, q, o);
    mu2 = pack2(mean, mean);
    rden = __frcp_rn(rbf(__fsqrt_rn(rbf(rbf(q * (1.f / D_)) + 1e-5f))));
}
__device__ __forceinline__ void ln_apply(const uint32_t* x, uint32_t mu2, float rden, const uint32_t* c1, const uint32_t* sm, uint32_t* r) {
#pragma unroll
    for (int i = 0; i < 8; i++) {
        const uint32_t d = hsub2(x[i], mu2);
        r[i] = hadd2(hmul2(pack2(bflo(d) * rden, bfhi(d) * rden), c1[i]), sm[i]);
    }
}

struct __align__(64) Params {
    CUtensorMap tm_h, tm_kv, tm_kvm, tm_o, tm_op, tm_h2, tm_act, tm_x1, tm_out;
    CUtensorMap tm_wq, tm_wk, tm_wv, tm_wo, tm_wg, tm_wu, tm_wd;
    const bf16 *x, *c, *w_mod;
    int qmask;
};

constexpr uint32_t R_WV = 0, R_MEM = 65536  ,
                   R_KX = 69632  , R_VX = R_KX + 8192,
                   R_VMS = R_KX + 32768  , R_OS = R_VMS + 2048  , R_SX = R_OS + 2048  , R_BAR = R_SX + 1536,
                   R_RS = R_BAR + 512  , R_VB = R_RS + 4096  , R_VP = R_VB + 2048  ,
                   R_STG = R_VP + 4096  ,
                   R_TQ = R_STG  , R_TV = R_STG + 53248  , R_QF = R_STG + 77824  ,
                   R_SMEM = R_STG + 98304;
static_assert((R_STG & 1023) == 0 && (R_RS & 511) == 0 && R_QF + 16384 <= R_SMEM, "smem");
constexpr uint32_t RB_Q = R_BAR, RB_V = R_BAR + 8, RB_E = R_BAR + 16, RB_A = R_BAR + 24, RB_ROLE = R_BAR + 32, RB_A1 = R_BAR + 40;
constexpr int W_NST = 4;
constexpr uint32_t W_STAGE = 49152, W_STG = W_NST * W_STAGE  , W_END = W_STG + 32768;
constexpr uint32_t SM_BAR = W_END;
constexpr uint32_t SMEM_BYTES = W_END + 1024 + 2048;
constexpr uint32_t B_FULL = 0, B_EMPTY = 32, B_STGFREE = 64, B_REQ = 80, B_RSP = 88, B_NEXT = 96, B_RING = 128;
#define PICK_AHEAD 3

constexpr int NB_S = 11, NB_Y = 1, NB_M = 5, NB_K = 5, NB_B = 2, NB_C = 3, NB_D = 4, NB_W0 = 6  , NB_ST = 9  ;

__device__ __forceinline__ int pos_of_d(int d) {
    const int rem = d & 31;
    return (d & ~31) + ((rem & 7) >> 1) * 8 + (rem & 1) * 4 + (rem >> 3);
}

#define PROF(i) do {} while (0)
#define PROFG(i) do {} while (0)
#define VK0_ 4
constexpr int VK0 = VK0_;
constexpr int NOFF = 8;
#define OFFKS(i) (((i) >> 1) < 2 ? ((i) >> 1) : ((i) >> 1) + 2)
#define POLL_GAP 110

struct RecParams { const bf16 *mem0, *wq, *wk, *wv, *wo, *x, *c, *w_mod; int ncl, only_pre; };

__device__ __forceinline__ void rec_qk(const RecParams& p, const uint32_t sb, const int cta, const int warp, int lane, const int sel) {
    const int crank = cta & 15, cl = cta >> 4, rank = cta & 1;
    const int wg = warp >> 2, aa = warp & 3;
    uint32_t wa[2][16][4];
    {
        const uint32_t stg = sb + R_STG + wg * 32768;
        const int t128 = aa * 32 + lane;
        const int row = (lane >> 4) * 8 + (lane & 7);
        const int ch = t128 & 7;
        const size_t goff = (size_t)rank * 256 * HD_ + (cta >> 1) * DH_ + ch * 8;
        const bf16* W = (wg == 0 ? p.wq : p.wk) + goff;
#pragma unroll 4
        for (int dd = 0; dd < 16; dd++) {
            const int d = dd * 16 + (t128 >> 3), pp = pos_of_d(d);
            cp_async16(sb + R_WV + wg * 32768 + pp * 128 + ((ch ^ (pp & 7)) << 4), p.wv + goff + wg * 64 + (size_t)d * HD_);
        }
        cp_async_commit();
#pragma unroll 4
        for (int dd = 0; dd < 16; dd++) {
            const int d = dd * 16 + (t128 >> 3), pp = pos_of_d(d);
            cp_async16(stg + pp * 128 + ((ch ^ (pp & 7)) << 4), W + (size_t)d * HD_);
        }
        cp_async_commit();
        {
            const int tok = warp, d0 = lane * 8;
            const uint4 m0 = __ldg((const uint4*)(p.mem0 + tok * D_ + rank * 256 + d0));
            const uint32_t mw[4] = {m0.x, m0.y, m0.z, m0.w};
#pragma unroll
            for (int e = 0; e < 8; e++) {
                const int pp = pos_of_d(d0 + e);
                const unsigned short v = (unsigned short)(mw[e >> 1] >> ((e & 1) * 16));
                asm volatile("st.shared.u16 [%0], %1;" :: "r"(sb + R_MEM + (pp >> 3) * 128 + tok * 16 + (pp & 7) * 2), "h"(v) : "memory");
            }
        }
        cp_async_wait<1>();
        bar_sync(NB_W0 + wg, 128);
        const uint32_t fv = row * 128 + (((2 * aa + ((lane >> 3) & 1)) ^ (row & 7)) << 4);
#pragma unroll
        for (int ks = 0; ks < 16; ks++) ldsm4t(wa[0][ks][0], wa[0][ks][1], wa[0][ks][2], wa[0][ks][3], sb + R_WV + wg * 32768 + fv + ks * 2048);
        bar_sync(NB_W0 + wg, 128);
#pragma unroll
        for (int ks = 0; ks < 16; ks++)
            sts128(sb + R_WV + (warp * 16 + ks) * 512 + lane * 16, make_uint4(wa[0][ks][0], wa[0][ks][1], wa[0][ks][2], wa[0][ks][3]));
        const uint32_t fo = stg + row * 128 + (((4 * (aa & 1) + ((lane >> 3) & 1)) ^ (row & 7)) << 4);
#pragma unroll 1
        for (int m = 0; m < 2; m++) {
            cp_async_wait<0>();
            bar_sync(NB_W0 + wg, 128);
            if ((aa >> 1) == m) {
#pragma unroll
                for (int ks = 0; ks < 16; ks++) {
                    ldsm4t(wa[0][ks][0], wa[0][ks][1], wa[0][ks][2], wa[0][ks][3], fo + ks * 2048);
                    ldsm4t(wa[1][ks][0], wa[1][ks][1], wa[1][ks][2], wa[1][ks][3], (fo ^ 32) + ks * 2048);
                }
            }
            bar_sync(NB_W0 + wg, 128);
            if (m == 0) {
#pragma unroll 4
                for (int dd = 0; dd < 16; dd++) {
                    const int d = dd * 16 + (t128 >> 3), pp = pos_of_d(d);
                    cp_async16(stg + pp * 128 + ((ch ^ (pp & 7)) << 4), W + 64 + (size_t)d * HD_);
                }
                cp_async_commit();
            }
        }
    }
    bar_sync(NB_D, 384);
    const uint32_t tab = sb + R_TQ + wg * 26624 + (aa * 32 + lane) * 16;
    {
        const uint32_t l7 = lane & 7, l8 = lane >> 3, g = lane >> 2, t = lane & 3;
        const uint32_t bq = warp >> 1, tp = warp & 1;
        uint4 v;
        v.x = sb + R_QF + (rank * 8 + warp) * 512 + lane * 16;
        v.y = sb + R_QF + (warp == 5 ? 1024 : 0) + lane * 16;
        v.z = sb + R_KX + ((warp - 1) * 8 + l7) * 128 + ((l8 ^ l7) << 4);
        v.w = sb + R_SX + warp * 256 + lane * 8;
        sts128(tab, v);
        sts128(tab + 2048, make_uint4(sb + lane * 16 + R_MEM, sb + lane * 16 + R_WV + warp * 8192, sb + lane * 16 + R_VP + warp * 512, lane));
        const uint32_t L = bq * 8 + 2 * tp + (l8 & 1) + 4 * (l8 >> 1);
        const uint32_t d0 = (((crank + ((t >> 1) | (g & 6))) & 7) << 1) | (crank >> 3);
        v.x = sb + R_RS + l7 * 512 + ((L ^ l7) << 4);
        v.y = mapa_u32(sb + R_MEM + ((crank & 7) * 4 + bq) * 128 + (4 * tp + 2 * (t & 1) + (g & 1)) * 16, d0);
        v.z = mapa_u32(sb + ((crank & 1) ? RB_A1 : RB_A), d0);
        v.w = lane;
        sts128(tab + 4096, v);
        const uint64_t wr = (uint64_t)(g_F + ((crank * 2 + ((crank ^ (crank >> 3) ^ sel) & 1)) * 1024 + warp * 128 + cl * 32 + lane));
        sts128(tab + 6144, make_uint4((uint32_t)wr, (uint32_t)(wr >> 32), (uint32_t)((((cl + 1) & 3) - cl) * 128), (uint32_t)((((cl + 2) & 3) - cl) * 128)));
        sts32(tab + 8192, (uint32_t)((((cl + 3) & 3) - cl) * 128));
#pragma unroll
        for (int i = 0; i < NOFF; i++)
            sts128(tab + 10240 + i * 2048, make_uint4(wa[i & 1][OFFKS(i)][0], wa[i & 1][OFFKS(i)][1], wa[i & 1][OFFKS(i)][2], wa[i & 1][OFFKS(i)][3]));
    }
    bar_sync(NB_D, 384);
    uint4 tb = lds128(tab + 2048);
#pragma unroll 1
    for (int s = 0; s < NSEG; s++) {
        if (s > 0) mbar_wait(sb + RB_A, (s - 1) & 1);
        if (warp == 0) PROF(0);
        uint4 ta;
        const uint32_t par = (s & 1) * 8192;
        {
            float acc[5][4];
#pragma unroll
            for (int c = 0; c < 5; c++) { acc[c][0] = acc[c][1] = acc[c][2] = acc[c][3] = 0.f; }
            uint32_t b[8][4];
            uint4 av[16];
            static_assert(VK0 == 4, "order below assumes the V/O warps cover slices 0,1");
#define QK4(k2) do { \
                mma16816(acc[0], wa[0][2 * (k2)][0], wa[0][2 * (k2)][1], wa[0][2 * (k2)][2], wa[0][2 * (k2)][3], b[k2][0], b[k2][1]); \
                mma16816(acc[1], wa[1][2 * (k2)][0], wa[1][2 * (k2)][1], wa[1][2 * (k2)][2], wa[1][2 * (k2)][3], b[k2][0], b[k2][1]); \
                mma16816(acc[3], wa[0][2 * (k2) + 1][0], wa[0][2 * (k2) + 1][1], wa[0][2 * (k2) + 1][2], wa[0][2 * (k2) + 1][3], b[k2][2], b[k2][3]); \
                mma16816(acc[4], wa[1][2 * (k2) + 1][0], wa[1][2 * (k2) + 1][1], wa[1][2 * (k2) + 1][2], wa[1][2 * (k2) + 1][3], b[k2][2], b[k2][3]); } while (0)
#define V2(k2) do { \
                mma16816(acc[2], av[2 * (k2)].x, av[2 * (k2)].y, av[2 * (k2)].z, av[2 * (k2)].w, b[k2][0], b[k2][1]); \
                mma16816(acv, av[2 * (k2) + 1].x, av[2 * (k2) + 1].y, av[2 * (k2) + 1].z, av[2 * (k2) + 1].w, b[k2][2], b[k2][3]); } while (0)
#define LB(k2) ldsm4(b[k2][0], b[k2][1], b[k2][2], b[k2][3], tb.x + (k2) * 512)
#define LV(k2) do { av[2 * (k2)] = lds128(tb.y + 2 * (k2) * 512); av[2 * (k2) + 1] = lds128(tb.y + (2 * (k2) + 1) * 512); } while (0)
            float acv[4] = {0.f, 0.f, 0.f, 0.f};
            if (s > 0) mbar_wait(sb + RB_A1, (s - 1) & 1);
            LB(0); LB(2); LB(4); LB(6);
            QK4(0); LB(1); QK4(2); LB(3); LV(2); LV(4); QK4(4); LB(5); QK4(6); LB(7);
            ta = lds128(tab);
            V2(2); V2(4); LV(6); LV(3);
            QK4(1); QK4(3); QK4(5); QK4(7);
            const uint4 f = make_uint4(movm(pack2(acc[0][0] + acc[3][0], acc[0][1] + acc[3][1])), movm(pack2(acc[0][2] + acc[3][2], acc[0][3] + acc[3][3])),
                                       movm(pack2(acc[1][0] + acc[4][0], acc[1][1] + acc[4][1])), movm(pack2(acc[1][2] + acc[4][2], acc[1][3] + acc[4][3])));
            st_async_v4((ta.x + par) ^ (1u << 24), f, (sb + RB_Q) ^ (1u << 24));
            sts128(ta.x + par, f);
            __syncwarp();
            if (tb.w == 0) mbar_arrive(sb + RB_Q);
            if (warp == 0) PROF(1);
            if (tb.x == 0) break;
            LV(5); LV(7);
            V2(6); V2(3); V2(5); V2(7);
            sts128(tb.z, make_uint4(__float_as_uint(acc[2][0] + acv[0]), __float_as_uint(acc[2][1] + acv[1]), __float_as_uint(acc[2][2] + acv[2]), __float_as_uint(acc[2][3] + acv[3])));
            bar_arrive(NB_Y, 384);
        }
        if (warp == 0) PROF(14);
        if (warp < 6 && s != NSEG - 1) {
            float sa[4] = {0.f, 0.f, 0.f, 0.f}, sc[4] = {0.f, 0.f, 0.f, 0.f};
            const uint32_t qa = ta.y + par;
            if (warp == 0 || warp == 5) {
                mbar_wait(sb + RB_Q, s & 1);
                const uint4 q0 = lds128(qa), q1 = lds128(qa + 4096), k0 = lds128(qa + 2048), k1 = lds128(qa + 6144);
                const uint4 q2 = lds128(qa + 512), q3 = lds128(qa + 4608), k2 = lds128(qa + 2560), k3 = lds128(qa + 6656);
                mma16816h(sa, hadd2(q0.x, q1.x), hadd2(q0.y, q1.y), hadd2(k0.x, k1.x), hadd2(k0.y, k1.y));
                mma16816h(sc, hadd2(q0.z, q1.z), hadd2(q0.w, q1.w), hadd2(k0.z, k1.z), hadd2(k0.w, k1.w));
                mma16816h(sa, hadd2(q2.x, q3.x), hadd2(q2.y, q3.y), hadd2(k2.x, k3.x), hadd2(k2.y, k3.y));
                mma16816h(sc, hadd2(q2.z, q3.z), hadd2(q2.w, q3.w), hadd2(k2.z, k3.z), hadd2(k2.w, k3.w));
            } else {
                uint32_t k[16];
                const uint32_t kb = ta.z + 2 * par;
                ldsm4(k[0], k[1], k[2], k[3], kb);
                ldsm4(k[4], k[5], k[6], k[7], kb ^ 64);
                ldsm4(k[8], k[9], k[10], k[11], kb + 4096);
                ldsm4(k[12], k[13], k[14], k[15], (kb ^ 64) + 4096);
                mbar_wait(sb + RB_Q, s & 1);
                uint4 q0[4], q1[4];
#pragma unroll
                for (int i = 0; i < 4; i++) { q0[i] = lds128(qa + i * 512); q1[i] = lds128(qa + 4096 + i * 512); }
                float sd[4] = {0.f, 0.f, 0.f, 0.f}, se[4] = {0.f, 0.f, 0.f, 0.f};
                mma16816h(sa, hadd2(q0[0].x, q1[0].x), hadd2(q0[0].y, q1[0].y), k[0], k[1]);
                mma16816h(sc, hadd2(q0[0].z, q1[0].z), hadd2(q0[0].w, q1[0].w), k[2], k[3]);
                mma16816h(sd, hadd2(q0[1].x, q1[1].x), hadd2(q0[1].y, q1[1].y), k[4], k[5]);
                mma16816h(se, hadd2(q0[1].z, q1[1].z), hadd2(q0[1].w, q1[1].w), k[6], k[7]);
                mma16816h(sa, hadd2(q0[2].x, q1[2].x), hadd2(q0[2].y, q1[2].y), k[8], k[9]);
                mma16816h(sc, hadd2(q0[2].z, q1[2].z), hadd2(q0[2].w, q1[2].w), k[10], k[11]);
                mma16816h(sd, hadd2(q0[3].x, q1[3].x), hadd2(q0[3].y, q1[3].y), k[12], k[13]);
                mma16816h(se, hadd2(q0[3].z, q1[3].z), hadd2(q0[3].w, q1[3].w), k[14], k[15]);
                sa[0] += sd[0]; sa[1] += sd[1]; sc[0] += se[0]; sc[1] += se[1];
            }
            const float scl = 0.08838834764831845f * 1.4426950408889634f;
            sts64f(ta.w, (sa[0] + sc[0]) * scl, (sa[1] + sc[1]) * scl);
            bar_arrive(NB_S, 320);
            if (warp == 0) PROF(2);
        } else if (warp == 7) {
            mbar_wait(sb + RB_Q, s & 1);
            if (lane == 0) {
                mbar_expect_tx(sb + RB_Q, 4096);
                if (s > 0) { mbar_expect_tx(sb + RB_A, 2048); mbar_expect_tx(sb + RB_A1, 2048); }
            }
            __syncwarp();
        } else if (s > 0 && (s & 3) == 0 && warp == 6) {
            bar_sync(NB_K, 160);
            if (lane == 0) red_release(&g_flags[F_MEM + (s >> 2) - 1], 1);
            __syncwarp();
        }
        if (s == NSEG - 1) {
            const uint4 td = lds128(tab + 6144);
            stg_relaxed32((uint32_t*)(((uint64_t)td.y << 32) | (td.x ^ 0x21000)), 0u);
            break;
        }
        const uint4 tc = lds128(tab + 4096), td = lds128(tab + 6144);
        const uint32_t te = lds32(tab + 8192);
        uint32_t* wr = (uint32_t*)(((uint64_t)td.y << 32) | (td.x ^ ((s & 1) * 0x21000)));
        const uint32_t* r1p = (const uint32_t*)((const char*)wr + (int)td.z);
        const uint32_t* r2p = (const uint32_t*)((const char*)wr + (int)td.w);
        const uint32_t* r3p = (const uint32_t*)((const char*)wr + (int)te);
        const uint32_t tag = ((s >> 1) + 1) & 1;
        mbar_wait(sb + RB_E, s & 1);
        if (warp == 0) PROF(7);
        {
            uint32_t a0, a1, a2, a3;
            ldsm4t(a0, a1, a2, a3, tc.x);
            const uint32_t one = 0x3F803F80u;
            float d0_[4] = {0.f, 0.f, 0.f, 0.f}, d1_[4] = {0.f, 0.f, 0.f, 0.f};
            mma1688(d0_, a0, a1, one);
            mma1688(d1_, a2, a3, one);
            const bool t1 = tc.w & 1, t2 = tc.w & 2;
            const float x = t2 ? (t1 ? d1_[2] : d1_[0]) : (t1 ? d0_[2] : d0_[0]);
            const uint32_t own = (__float_as_uint(x) & ~1u) | tag;
            stg_relaxed32(wr, own);
            const uint32_t tq = clk32();
            if (warp == 0) PROF(8);
            while ((int)(clk32() - tq) < POLL_GAP) {}
            uint32_t f1 = ldg_relaxed32(r1p), f2 = ldg_relaxed32(r2p), f3 = ldg_relaxed32(r3p);
#pragma unroll
            for (int i = 0; i < NOFF; i++) {
                const uint4 f0 = lds128(tab + 10240 + i * 2048);
                wa[i & 1][OFFKS(i)][0] = f0.x; wa[i & 1][OFFKS(i)][1] = f0.y; wa[i & 1][OFFKS(i)][2] = f0.z; wa[i & 1][OFFKS(i)][3] = f0.w;
            }
            tb = lds128(tab + 2048);
            int gg = 0;
#pragma unroll 1
            while (!__all_sync(~0u, (((f1 ^ tag) | (f2 ^ tag) | (f3 ^ tag)) & 1) == 0)) {
                f1 = ldg_relaxed32(r1p); f2 = ldg_relaxed32(r2p); f3 = ldg_relaxed32(r3p);
                if (++gg > 16 * SPIN_LIMIT) { TIMEOUT(3, s); break; }
            }
            if (warp == 0) PROF(9);
            const float v = (__uint_as_float(own) + __uint_as_float(f2)) + (__uint_as_float(f1) + __uint_as_float(f3));
            const bool b8 = tc.w & 8, b16 = tc.w & 16;
            const float recv = __shfl_xor_sync(~0u, v, 8);
            const uint32_t word = b8 ? pack2(recv, v) : pack2(v, recv);
            const uint32_t oth = __shfl_xor_sync(~0u, word, 16);
            const uint32_t wl = b16 ? oth : word, wh = b16 ? word : oth;
            const uint32_t p0 = __shfl_xor_sync(~0u, wl, 2), p1 = __shfl_xor_sync(~0u, wh, 2);
            const uint4 item = t2 ? make_uint4(p0, p1, wl, wh) : make_uint4(wl, wh, p0, p1);
            st_async_v4(tc.y, item, tc.z);
            if (tc.w == 0 && warp == 7) mbar_expect_tx(sb + RB_E, 4096);
            if (warp == 0) PROF(10);
        }
        bar_sync(NB_D, 384);
    }
}

__device__ __forceinline__ void rec_load_tile(uint32_t d, const char* src) {
    cp_async16(d, src);
    cp_async16(d ^ 16, src + 16);
    cp_async16(d + 4096, src + 128);
    cp_async16((d ^ 16) + 4096, src + 128 + 16);
}
__device__ __forceinline__ void rec_store_kvm(uint32_t src, char* dst, int s, int w) {
    dst += (size_t)s * (8 * 2 * HD_ * 2);
    if (w < 2) {
        const uint4 a = lds128(src + (s & 1) * 8192), b = lds128(src + (s & 1) * 8192 + 4096);
        *(uint32_t*)dst = hadd2(a.x, b.x); *(uint32_t*)(dst + 16) = hadd2(a.y, b.y);
        *(uint32_t*)(dst + 32) = hadd2(a.z, b.z); *(uint32_t*)(dst + 48) = hadd2(a.w, b.w);
    } else {
        *(uint4*)dst = lds128(src + (s & 1) * 1024);
    }
}

__device__ __forceinline__ void rec_vo(const RecParams& p, const uint32_t sb, const int cta, const int warp, int lane) {
    const int w = warp - 8, crank = cta & 15, rank = cta & 1;
    uint32_t wo[4][8][4];
    const uint32_t tab = sb + R_TV + (w * 32 + lane) * 16;
    {
        const int t128 = w * 32 + lane;
        const bf16* Wo = p.wo + (size_t)(cta >> 1) * DH_ * D_ + rank * 256;
        const uint32_t stg = sb + R_STG + 2 * 32768;
#pragma unroll
        for (int half = 0; half < 2; half++) {
#pragma unroll 4
            for (int i = t128; i < 2048; i += 128) {
                const int e = i >> 5, ch = i & 31;
                cp_async16(stg + e * 512 + ((ch ^ (e & 7)) << 4), Wo + (size_t)(half * 64 + e) * D_ + ch * 8);
            }
            cp_async_commit();
            cp_async_wait<0>();
            bar_sync(NB_W0 + 2, 128);
#pragma unroll
            for (int j = 0; j < 4; j++)
#pragma unroll
                for (int kk = 0; kk < 4; kk++) {
                    const int e = kk * 16 + (lane >> 4) * 8 + (lane & 7);
                    const int ch = (w * 4 + j) * 2 + ((lane >> 3) & 1);
                    ldsm4t(wo[j][half * 4 + kk][0], wo[j][half * 4 + kk][1], wo[j][half * 4 + kk][2], wo[j][half * 4 + kk][3],
                           stg + e * 512 + ((ch ^ (e & 7)) << 4));
                }
            bar_sync(NB_W0 + 2, 128);
        }
        bar_sync(NB_D, 384);
        const uint32_t l7 = lane & 7, l8 = lane >> 3, g = lane >> 2;
        uint4 v;
        v.x = sb + R_VX + (w >> 1) * 4096 + ((l8 & 1) * 8 + l7) * 128 + (((4 * (w & 1) + (l8 >> 1)) ^ l7) << 4);
        v.y = sb + R_OS + (w >> 1) * 1024 + g * 128 + (((4 * (w & 1)) ^ g) << 4) + (lane & 3) * 4;
        v.z = sb + R_VMS + l7 * 128 + (((4 * (w & 1) + l8) ^ l7) << 4);
        v.w = sb + R_OS + l7 * 128 + ((l8 ^ l7) << 4);
        sts128(tab, v);
        v.x = mapa_u32(sb + R_RS + (crank >> 1) * 512 + ((lane ^ (crank >> 1)) << 4), rank * 8 + w * 2);
        v.y = mapa_u32(sb + RB_E, rank * 8 + w * 2);
        v.z = sb + R_VB + w * 512 + lane * 16;
        v.w = sb + R_SX + lane * 8;
        sts128(tab + 2048, v);
#pragma unroll
        for (int i = 0; i < 8; i++)
            sts128(tab + 4096 + i * 2048, make_uint4(wo[i >> 1][(i & 1) * 4][0], wo[i >> 1][(i & 1) * 4][1], wo[i >> 1][(i & 1) * 4][2], wo[i >> 1][(i & 1) * 4][3]));
        const int row = t128 >> 2, c2 = (lane & 3) * 2, tok = (w & 1) * 4 + (lane >> 3);
        const uint64_t kd = w < 2 ? (uint64_t)(g_kvm + (g * (2 * HD_) + cta * 64 + w * 32 + (lane & 3) * 2))
                                  : (uint64_t)(g_kvm + (tok * (2 * HD_) + HD_ + cta * 64 + (lane & 7) * 8));
        const uint32_t ksrc = w < 2 ? sb + R_QF + (4 + 2 * rank + w) * 512 + lane * 16 : sb + R_VMS + tok * 128 + (((lane & 7) ^ tok) << 4);
        const uint64_t ks = (uint64_t)(g_kv + ((size_t)row * (2 * HD_) + (cta >> 1) * DH_ + c2 * 8));
        const uint32_t dk = sb + R_KX + row * 128 + ((c2 ^ (row & 7)) << 4);
        sts128(tab + 20480, make_uint4((uint32_t)kd, (uint32_t)(kd >> 32), (uint32_t)ks, (uint32_t)(ks >> 32)));
        sts128(tab + 22528, make_uint4(ksrc, dk, lane, sb + lane * 16));
        if (lane == 0) wait_flag(F_KV + 0, 64);
        __syncwarp();
        rec_load_tile(dk, (const char*)ks);
        rec_load_tile(dk + 8192, (const char*)ks + HD_ * 2);
        cp_async_commit();
        cp_async_wait<0>();
    }
    bar_sync(NB_D, 384);
    const uint32_t lane16 = lds32(tab + 22528 + 12);
    uint4 av[8];
#pragma unroll
    for (int i = 0; i < 8; i++) av[i] = lds128(lane16 + R_WV + ((2 * w + (i >> 2)) * 16 + (i & 3)) * 512);
#pragma unroll 1
    for (int s = 0; s < NSEG; s++) {
        {
            if (s > 0) mbar_wait(sb + RB_A, (s - 1) & 1);
            const uint4 tp = lds128(tab + 20480), tq = lds128(tab + 22528);
            if (s > 0) {
                rec_store_kvm(tq.x, (char*)(((uint64_t)tp.y << 32) | tp.x), s - 1, w);
                if ((s & 3) == 0) bar_arrive(NB_K, 160);
            }
            if (s + 1 < NSEG - 1) {
                if (((s + 1) & 3) == 0) { if (tq.z == 0) wait_flag(F_KV + ((s + 1) >> 2), 64); __syncwarp(); }
                const char* src = (const char*)((((uint64_t)tp.w << 32) | tp.z) + (uint64_t)(s + 1) * (32 * 2 * HD_ * 2));
                rec_load_tile(tq.y + ((s + 1) & 1) * 16384, src);
                rec_load_tile(tq.y + ((s + 1) & 1) * 16384 + 8192, src + HD_ * 2);
            }
            cp_async_commit();
        }
        uint4 vb;
        const uint4 ta = lds128(tab), tb = lds128(tab + 2048);
        {
            if (s > 0) mbar_wait(sb + RB_A1, (s - 1) & 1);
            uint32_t bb[8];
            ldsm4(bb[0], bb[1], bb[2], bb[3], lane16 + R_MEM);
            ldsm4(bb[4], bb[5], bb[6], bb[7], lane16 + R_MEM + 512);
            float vd[4] = {0.f, 0.f, 0.f, 0.f}, ve[4] = {0.f, 0.f, 0.f, 0.f};
#pragma unroll
            for (int i = 0; i < 4; i++) {
                mma16816(vd, av[i].x, av[i].y, av[i].z, av[i].w, bb[2 * i], bb[2 * i + 1]);
                mma16816(ve, av[4 + i].x, av[4 + i].y, av[4 + i].z, av[4 + i].w, bb[2 * i], bb[2 * i + 1]);
            }
            bar_sync(NB_Y, 384);
            const uint4 a = lds128(lane16 + R_VP + w * 1024), b = lds128(lane16 + R_VP + w * 1024 + 512);
            vb = make_uint4(pack2(__uint_as_float(a.x) + vd[0], __uint_as_float(a.y) + vd[1]), pack2(__uint_as_float(a.z) + vd[2], __uint_as_float(a.w) + vd[3]),
                            pack2(__uint_as_float(b.x) + ve[0], __uint_as_float(b.y) + ve[1]), pack2(__uint_as_float(b.z) + ve[2], __uint_as_float(b.w) + ve[3]));
            st_async_v4(tb.z ^ (1u << 24), vb, (sb + RB_V) ^ (1u << 24));
        }
        if (w == 0) PROF(11);
        if (s != NSEG - 1) {
            uint32_t vx[16];
            const uint32_t vxa = ta.x + (s & 1) * 16384;
            ldsm4t(vx[0], vx[1], vx[2], vx[3], vxa);
            ldsm4t(vx[4], vx[5], vx[6], vx[7], vxa ^ 32);
            ldsm4t(vx[8], vx[9], vx[10], vx[11], vxa + 2048);
            ldsm4t(vx[12], vx[13], vx[14], vx[15], (vxa ^ 32) + 2048);
#pragma unroll
            for (int i = 0; i < 4; i++) {
                const uint4 f0 = lds128(tab + 4096 + i * 2048);
                wo[i >> 1][(i & 1) * 4][0] = f0.x; wo[i >> 1][(i & 1) * 4][1] = f0.y; wo[i >> 1][(i & 1) * 4][2] = f0.z; wo[i >> 1][(i & 1) * 4][3] = f0.w;
            }
            mbar_wait(sb + RB_V, s & 1);
            {
                const uint4 o = lds128(tb.z);
                vb = make_uint4(hadd2(vb.x, o.x), hadd2(vb.y, o.y), hadd2(vb.z, o.z), hadd2(vb.w, o.w));
            }
            bar_sync(NB_S, 320);
            if (w == 0) PROF(4);
            float sv[10];
#pragma unroll
            for (int n = 0; n < 5; n++) { const float2 a = lds64f(tb.w + n * 256); sv[2 * n] = a.x; sv[2 * n + 1] = a.y; }
            { const float2 a = lds64f(tb.w + 5 * 256); sv[0] += a.x; sv[1] += a.y; }
            float mx = fmaxf(fmaxf(fmaxf(sv[2], sv[3]), fmaxf(sv[4], sv[5])), fmaxf(fmaxf(sv[6], sv[7]), fmaxf(sv[8], sv[9])));
            mx = fmaxf(mx, fmaxf(sv[0], sv[1]));
            mx = fmaxf(mx, __shfl_xor_sync(~0u, mx, 1));
            mx = fmaxf(mx, __shfl_xor_sync(~0u, mx, 2));
            uint32_t pf[5];
#pragma unroll
            for (int n = 0; n < 5; n++) pf[n] = pack2(ex2(sv[2 * n] - mx), ex2(sv[2 * n + 1] - mx));
            if (w == 0) PROF(12);
            float oa[4][4] = {{0.f, 0.f, 0.f, 0.f}, {0.f, 0.f, 0.f, 0.f}, {0.f, 0.f, 0.f, 0.f}, {0.f, 0.f, 0.f, 0.f}}, sm[4] = {0.f, 0.f, 0.f, 0.f};
            const uint32_t one = 0x3F803F80u;
            mma1688h(sm, pf[0], one);
            mma1688h(oa[0], pf[0], vb.x);
            mma1688h(oa[1], pf[0], vb.y);
            mma1688h(oa[2], pf[0], vb.z);
            mma1688h(oa[3], pf[0], vb.w);
            mma16816h(sm, pf[1], pf[2], one, one);
#pragma unroll
            for (int n = 0; n < 4; n++) mma16816h(oa[n], pf[1], pf[2], vx[2 * n], vx[2 * n + 1]);
            mma16816h(sm, pf[3], pf[4], one, one);
#pragma unroll
            for (int n = 0; n < 4; n++) mma16816h(oa[n], pf[3], pf[4], vx[8 + 2 * n], vx[8 + 2 * n + 1]);
            float inv;
            asm("rcp.approx.ftz.f32 %0, %1;" : "=f"(inv) : "f"(sm[0]));
#pragma unroll
            for (int n = 0; n < 4; n++) sts32(ta.y ^ (n << 4), pack2(oa[n][0] * inv, oa[n][1] * inv));
            bar_sync(NB_C, 128);
            if (w == 0) PROF(5);
            uint32_t ob[16];
            ldsm4(ob[0], ob[1], ob[2], ob[3], ta.w);
            ldsm4(ob[8], ob[9], ob[10], ob[11], ta.w + 1024);
            ldsm4(ob[4], ob[5], ob[6], ob[7], ta.w ^ 64);
            ldsm4(ob[12], ob[13], ob[14], ob[15], (ta.w ^ 64) + 1024);
#pragma unroll
            for (int i = 4; i < 8; i++) {
                const uint4 f0 = lds128(tab + 4096 + i * 2048);
                wo[i >> 1][(i & 1) * 4][0] = f0.x; wo[i >> 1][(i & 1) * 4][1] = f0.y; wo[i >> 1][(i & 1) * 4][2] = f0.z; wo[i >> 1][(i & 1) * 4][3] = f0.w;
            }
#pragma unroll
            for (int jj = 0; jj < 2; jj++) {
                if (jj == 1 && tb.w == 0) break;
                float acc[4][4];
#pragma unroll
                for (int c = 0; c < 4; c++) { acc[c][0] = acc[c][1] = acc[c][2] = acc[c][3] = 0.f; }
#pragma unroll
                for (int k4 = 0; k4 < 4; k4++)
#pragma unroll
                    for (int c = 0; c < 4; c++) {
                        const int tl = jj * 2 + (c >> 1), ks = (c & 1) * 4 + k4;
                        mma16816(acc[c], wo[tl][ks][0], wo[tl][ks][1], wo[tl][ks][2], wo[tl][ks][3], ob[2 * ks], ob[2 * ks + 1]);
                    }
                uint4 v;
                v.x = pack2(acc[0][0] + acc[1][0], acc[0][1] + acc[1][1]);
                v.y = pack2(acc[0][2] + acc[1][2], acc[0][3] + acc[1][3]);
                v.z = pack2(acc[2][0] + acc[3][0], acc[2][1] + acc[3][1]);
                v.w = pack2(acc[2][2] + acc[3][2], acc[2][3] + acc[3][3]);
                st_async_v4(tb.x + (jj << 24), v, tb.y + (jj << 24));
            }
            if (w == 0) PROF(6);
        } else {
            mbar_wait(sb + RB_V, s & 1);
            const uint4 o = lds128(tb.z);
            vb = make_uint4(hadd2(vb.x, o.x), hadd2(vb.y, o.y), hadd2(vb.z, o.z), hadd2(vb.w, o.w));
            mbar_wait(sb + RB_Q, s & 1);
        }
        if ((w >> 1) == rank) stsm4t(ta.z + (s & 1) * 1024, vb.x, vb.y, vb.z, vb.w);
        cp_async_wait<0>();
        bar_sync(NB_C, 128);
        if (s != NSEG - 1) {
            if (w == 0 && lane == 0) mbar_expect_tx(sb + RB_V, 2048);
            bar_arrive(NB_D, 384);
        }
#pragma unroll
        for (int i = 0; i < 8; i++) av[i] = lds128(lane16 + R_WV + ((2 * w + (i >> 2)) * 16 + (i & 3)) * 512);
    }
    {
        const uint4 tp = lds128(tab + 20480), tq = lds128(tab + 22528);
        rec_store_kvm(tq.x, (char*)(((uint64_t)tp.y << 32) | tp.x), NSEG - 1, w);
    }
    bar_sync(NB_C, 128);
    if (w == 0 && lane == 0) red_release(&g_flags[F_MEM + NRB - 1], 1);
}

__global__ void __launch_bounds__(384, 1) k_rec(const RecParams p) {
    extern __shared__ __align__(1024) unsigned char smem_raw[];
    const uint32_t sb = __shfl_sync(~0u, smem_u32(smem_raw), 0);
    const int warp = __shfl_sync(~0u, threadIdx.x >> 5, 0);
    int lane; asm volatile("mov.u32 %0, %%laneid;" : "=r"(lane));
    const int crank = blockIdx.x & 15, slot = blockIdx.x >> 4;
    asm volatile("griddepcontrol.launch_dependents;");
    if (crank == 0 && threadIdx.x == 0) {
        stg_relaxed32(&g_F[65536 + slot * 64], 0u);
        stg_relaxed32(&g_F[65536 + 1024 + slot * 64], 0u);
    }
    if (threadIdx.x == 0) {
        mbar_init(sb + RB_Q, 9); mbar_init(sb + RB_V, 1); mbar_init(sb + RB_E, 1); mbar_init(sb + RB_A, 1); mbar_init(sb + RB_A1, 1); mbar_init(sb + RB_ROLE, 1);
        asm volatile("fence.mbarrier_init.release.cluster;" ::: "memory");
        mbar_expect_tx(sb + RB_Q, 4096);
        mbar_expect_tx(sb + RB_V, 2048);
        mbar_expect_tx(sb + RB_E, 4096);
        mbar_expect_tx(sb + RB_A, 2048);
        mbar_expect_tx(sb + RB_A1, 2048);
        mbar_expect_tx(sb + RB_ROLE, 4);
    }
    asm volatile("barrier.cluster.arrive.relaxed.aligned;\nbarrier.cluster.wait.aligned;" ::: "memory");
    unsigned role = 0;
    if (crank == 0 && threadIdx.x == 0 && !p.only_pre) {
        unsigned x = 0;
        int tm[2] = {0x7fffffff, 0x7fffffff};
#pragma unroll 1
        for (int i = 0; i < 6; i++) {
            const uint32_t t0 = clk32();
            x = atomicAdd(&g_F[65536 + (i & 1) * 1024 + slot * 64 + (x >> 31)], 1u);
            if (x != (unsigned)(i >> 1)) sts32(sb + R_BAR + 56, x);
            const int dt = (int)(clk32() - t0);
            if (i >= 2) { if (i & 1) tm[1] = min(tm[1], dt); else tm[0] = min(tm[0], dt); }
        }
        const int side = tm[1] > tm[0];
        const unsigned old = atomicAdd(&g_flags[F_SIDE + side * 32], 1u);
        unsigned c0, c1; int gd = 0;
#pragma unroll 1
        do { c0 = ldg_relaxed32(&g_flags[F_SIDE]); c1 = ldg_relaxed32(&g_flags[F_SIDE + 32]); } while ((int)(c0 + c1) < p.ncl && ++gd < 64 * SPIN_LIMIT);
        const int big = c1 > c0;
        role = side == big ? old : (big ? c1 : c0) + old;
        role |= (big ^ 1) << 8;
    }
    __syncwarp();
    if (crank == 0 && warp == 0 && !p.only_pre) {
        role = __shfl_sync(~0u, role, 0);
        if (lane < 16)
            asm volatile("st.async.weak.shared::cluster.mbarrier::complete_tx::bytes.u32 [%0], %1, [%2];"
                         :: "r"(mapa_u32(sb + R_BAR + 48, lane)), "r"(role), "r"(mapa_u32(sb + RB_ROLE, lane)) : "memory");
    }
    if (warp >= 4) {
        const int w8 = warp - 4, nblk = gridDim.x;
        const int cq = lane & 3, rg = w8 * 8 + (lane >> 2);
        const uint32_t red = sb + R_VP;
        const int row0 = blockIdx.x * 8 + w8;
        const uint4* xr = (const uint4*)(p.x + (size_t)row0 * D_);
        uint4 xa = __ldg(xr + lane), xb = __ldg(xr + 32 + lane);
#pragma unroll 1
        for (int sl = blockIdx.x; sl < 96; sl += nblk) {
            uint4 wv[8];
#pragma unroll
            for (int i = 0; i < 8; i++) wv[i] = __ldg((const uint4*)(p.w_mod + (size_t)(rg * 8 + i) * (6 * D_) + sl * 32 + cq * 8));
            const uint32_t cw = __ldg((const uint32_t*)(p.c + rg * 8) + cq);
            const float cl = bflo(cw), ch = bfhi(cw);
            const uint32_t sw = pack2(__fdividef(cl, 1.f + __expf(-cl)), __fdividef(ch, 1.f + __expf(-ch)));
            float a[8];
#pragma unroll
            for (int i = 0; i < 8; i++) a[i] = 0.f;
#pragma unroll
            for (int i = 0; i < 8; i++) {
                const uint32_t sv = __shfl_sync(~0u, sw, (lane & 28) + (i >> 1));
                const float cv = (i & 1) ? bfhi(sv) : bflo(sv);
                a[0] = fmaf(cv, bflo(wv[i].x), a[0]); a[1] = fmaf(cv, bfhi(wv[i].x), a[1]); a[2] = fmaf(cv, bflo(wv[i].y), a[2]); a[3] = fmaf(cv, bfhi(wv[i].y), a[3]);
                a[4] = fmaf(cv, bflo(wv[i].z), a[4]); a[5] = fmaf(cv, bfhi(wv[i].z), a[5]); a[6] = fmaf(cv, bflo(wv[i].w), a[6]); a[7] = fmaf(cv, bfhi(wv[i].w), a[7]);
            }
#pragma unroll
            for (int i = 0; i < 8; i++) { a[i] += __shfl_xor_sync(~0u, a[i], 4); a[i] += __shfl_xor_sync(~0u, a[i], 8); a[i] += __shfl_xor_sync(~0u, a[i], 16); }
            if (lane < 4) {
                sts128(red + w8 * 128 + lane * 32, make_uint4(__float_as_uint(a[0]), __float_as_uint(a[1]), __float_as_uint(a[2]), __float_as_uint(a[3])));
                sts128(red + w8 * 128 + lane * 32 + 16, make_uint4(__float_as_uint(a[4]), __float_as_uint(a[5]), __float_as_uint(a[6]), __float_as_uint(a[7])));
            }
            bar_sync(NB_B, 256);
            if (w8 == 0) {
                float v = 0.f;
#pragma unroll
                for (int i = 0; i < 8; i++) v += lds32f(red + i * 128 + lane * 4);
                g_mod[sl * 32 + lane] = __float2bfloat16_rn(v);
                __syncwarp();
                if (lane == 0) red_release(&g_flags[F_MOD + (sl >= 32)], 1);
            }
            bar_sync(NB_B, 256);
        }
        uint32_t c1[8], sm[8];
        int row = row0;
#pragma unroll 1
        while (true) {
            const uint32_t v[8] = {xa.x, xa.y, xa.z, xa.w, xb.x, xb.y, xb.z, xb.w};
            uint32_t mu2, r[8]; float rden;
            ln_stats(v, mu2, rden);
            if (row == row0) {
                if (lane == 0) wait_flag(F_MOD, 32);
                __syncwarp();
                load_mod8(g_mod + D_, lane, c1);
                load_mod8(g_mod, lane, sm);
#pragma unroll
                for (int i = 0; i < 8; i++) c1[i] = hadd2(c1[i], 0x3F803F80u);
            } else if (row + 512 < S_) {
                xr = (const uint4*)(p.x + (size_t)(row + 512) * D_); xa = __ldg(xr + lane); xb = __ldg(xr + 32 + lane);
            }
            ln_apply(v, mu2, rden, c1, sm, r);
            uint4* hr = (uint4*)(g_h + (size_t)row * D_);
            hr[lane] = make_uint4(r[0], r[1], r[2], r[3]); hr[32 + lane] = make_uint4(r[4], r[5], r[6], r[7]);
            bar_sync(NB_B, 256);
            if (w8 == (row >> 7 & 7) && lane == 0) red_release(&g_flags[F_H + (row >> 7)], 1);
            __syncwarp();
            if (row == row0) {
                if (!p.only_pre) mbar_wait(sb + RB_ROLE, 0);
                const int cl = p.only_pre ? slot : (int)(lds32(sb + R_BAR + 48) & 255);
                row = cl < 4 ? (nblk + cl * 16 + crank) * 8 + w8 : S_;
                if (row < S_) { xr = (const uint4*)(p.x + (size_t)row * D_); xa = __ldg(xr + lane); xb = __ldg(xr + 32 + lane); }
            } else {
                row += 512;
            }
            if (row >= S_) break;
        }
    }
    if (p.only_pre) return;
    mbar_wait(sb + RB_ROLE, 0);
    const int rolew = __shfl_sync(~0u, lds32(sb + R_BAR + 48), 0);
    const int cl = rolew & 255;
    if (cl >= 4) return;
    const int cta = cl * 16 + crank;
    if (warp < 8) rec_qk(p, sb, cta, warp, lane, rolew >> 8);
    else rec_vo(p, sb, cta, warp, lane);
}

enum { J_KV = 0, J_QA = 1, J_O = 2, J_LN = 3, J_UP = 4, J_DN = 5, J_UP2 = 8, J_END = 9 };
constexpr int NJ_O = 2 * OSPLIT, NJ_O2 = 2 * OSPLIT2, NJ_LN = 8, NJ_LN2 = 16, NJ_UP = 14, NJ_UP2 = 28, NJ_DN = 8, NJ_LN1 = 8  ;
constexpr uint64_t pk8(int a, int b, int c, int d, int e, int f, int g, int h) {
    return (uint64_t)a | ((uint64_t)b << 8) | ((uint64_t)c << 16) | ((uint64_t)d << 24) | ((uint64_t)e << 32) | ((uint64_t)f << 40) | ((uint64_t)g << 48) | ((uint64_t)h << 56);
}
constexpr uint64_t NJ_C = pk8(32, 16, NJ_O, NJ_LN, NJ_UP, NJ_DN, 0, 0), NJ_F = pk8(32, 16, NJ_O2, NJ_LN2, NJ_UP2, NJ_DN, 0, 0);
constexpr uint64_t TG_C = pk8(2 * NJ_LN1, 64, 32, 2 * NJ_O, 2 * NJ_LN, 2 * NJ_UP, 32, 0), TG_F = pk8(2 * NJ_LN1, 64, 32, 2 * NJ_O2, 2 * NJ_LN2, 2 * NJ_UP2, 32, 0);
constexpr uint64_t NJ_L = pk8(32, 32, 2 * OSPLIT3, NJ_LN2, NJ_UP2, 2 * NJ_DN, 0, 0), TG_L = pk8(2 * NJ_LN1, 64, 64, 4 * OSPLIT3, 2 * NJ_LN2, 2 * NJ_UP2, 32, 0);
__device__ __forceinline__ uint64_t nj_tab(int rb) { return rb < FINE_RB ? NJ_C : (rb < NRB - 1 ? NJ_F : NJ_L); }
__device__ __forceinline__ uint64_t tg_tab(int rb) { return rb < FINE_RB ? TG_C : (rb < NRB - 1 ? TG_F : TG_L); }
__device__ __forceinline__ int o_nk(int rb) { return rb < FINE_RB ? 64 / OSPLIT : (rb < NRB - 1 ? 64 / OSPLIT2 : 64 / OSPLIT3); }
constexpr uint64_t PRIO = pk8(4, 10, 9, 8, 7, 6, 3, 0);
__device__ __forceinline__ int pick_job(int lane, int qmask, int& idx) {
    const int rb = lane & 15, half = lane >> 4;
    const uint64_t nj = nj_tab(rb) >> (8 * half);
    const uint64_t tg = tg_tab(rb) >> (8 * half);
    const unsigned* cp = &g_flags[F_CLAIM + half * 32 + rb];
    const unsigned* dp = &g_flags[half * 32 + rb];
    int gd = 0;
#pragma unroll 1
    while (true) {
        const unsigned c0 = ldg_relaxed32(cp), c1 = ldg_relaxed32(cp + 64), c2 = ldg_relaxed32(cp + 128);
        const unsigned d0 = ldg_relaxed32(dp - (half && rb ? 1 : 0)), d1 = ldg_relaxed32(dp + 64), d2 = ldg_relaxed32(dp + 128);
        const unsigned cl[3] = {c0, c1, c2}, dv[3] = {d0, d1, d2};
        unsigned key = 0xffffu, key2 = 0xffffu;
        bool pre = false;
#pragma unroll
        for (int i = 0; i < 3; i++) {
            const int q = half + 2 * i;
            const bool have = ((qmask >> q) & 1) && cl[i] < (unsigned)((nj >> (16 * i)) & 255);
            bool ready = have && dv[i] >= (unsigned)((tg >> (16 * i)) & 255);
            unsigned pr = (unsigned)((PRIO >> (8 * q)) & 255);
            if (i == 0 && rb <= 1 - half) ready = have;
            if (i == 0 && half && rb >= FINE_RB) pr = 5;
            if (ready) key = min(key, (pr << 8) | (rb << 4) | q);
            if (have) key2 = min(key2, rb >= FINE_RB ? (0x100u | (q << 4) | rb) : (i == 0 ? 0u : 0x1000u));
            pre |= have && i == 0 && !half;
        }
        const bool anypre = __any_sync(~0u, pre);
        if (anypre && (key & 15) == J_QA) key = 0xffffu;
        key = __reduce_min_sync(~0u, key);
        key2 = __reduce_min_sync(~0u, key2);
        if (key2 == 0xffffu) return J_END;
        int pq, prb;
        if (key != 0xffffu) { pq = key & 15; prb = (key >> 4) & 15; }
        else if (key2 >= 0x120u && key2 < 0x1000u) { pq = (key2 >> 4) & 15; prb = key2 & 15; }
        else {
            __nanosleep(IDLE_NS);
            if (++gd > 16 * SPIN_LIMIT) { TIMEOUT(5, 0); return J_END; }
            continue;
        }
        int c = 0;
        if (lane == 0) c = (int)atomicAdd(&g_flags[F_CLAIM + pq * 32 + prb], 1u);
        c = __shfl_sync(~0u, c, 0);
        if (c < (int)((nj_tab(prb) >> (8 * pq)) & 255)) {
            idx = pq * 512 + prb * 32 + c;
            int acq = 0;
            if (pq != J_QA) {
                if (lane == 0 && ld_acquire(&g_flags[pq * 32 + prb]) >= (unsigned)((tg_tab(prb) >> (8 * pq)) & 255)) {
                    asm volatile("fence.proxy.async.global;" ::: "memory");
                    acq = 1 << 24;
                }
            }
            return (pq == J_UP && prb >= FINE_RB ? J_UP2 : pq) | (prb << 8) | (c << 16) | acq;
        }
    }
}
__device__ __forceinline__ int op_row(int rb, int split) {
    return rb < FINE_RB ? split * S_ + rb * 128
                        : (rb < NRB - 1 ? OSPLIT * S_ + (split * (NRB - FINE_RB) + rb - FINE_RB) * 128 : OSPLIT * S_ + (OSPLIT2 * (NRB - FINE_RB) + split) * 128);
}

struct Pipe { uint32_t stage, phase; };
__device__ __forceinline__ void pipe_next(Pipe& p) { if (++p.stage == W_NST) { p.stage = 0; p.phase ^= 1; } }

__device__ __forceinline__ void scheduler(const Params& p, uint32_t sb, int lane) {
    const uint32_t bars = sb + SM_BAR;
    uint32_t ph = 0;
#pragma unroll 1
    while (true) {
        mbar_wait(bars + B_REQ, ph);
        int j = 4095;
        const int jd = pick_job(lane, p.qmask, j);
        if (lane == 0) { sts32(bars + B_NEXT, (uint32_t)jd); sts32(bars + B_NEXT + 4, (uint32_t)j); mbar_arrive(bars + B_RSP); }
        ph ^= 1;
        if (jd == J_END) break;
        __syncwarp();
    }
}

__device__ __forceinline__ void producer(const Params& p, uint32_t sb) {
    Pipe pp{0, 1};
    const uint32_t bars = sb + SM_BAR;
    uint32_t seq = 0, h_seen = 0;
    mbar_arrive(bars + B_REQ);
#pragma unroll 1
    while (true) {
        mbar_wait(bars + B_RSP, seq & 1);
        const int jd = (int)lds32(bars + B_NEXT), j = (int)lds32(bars + B_NEXT + 4);
        int left = (jd & 255) == J_DN ? 15 : ((jd & 255) == J_QA ? (((jd >> 8) & 255) == NRB - 1 ? 10 : 12) : ((jd & 255) == J_O ? o_nk((jd >> 8) & 255) : ((jd & 255) == J_LN ? 1 : 8)));
        left = max(left - PICK_AHEAD, 1);
        TR(j, 1);
        const int type = jd & 255, rb = (jd >> 8) & 255, cb = (jd >> 16) & 255;
        const bool fine = rb >= FINE_RB, acquired = (jd >> 24) & 1;
        bool first = true;
        auto begin_stage = [&](uint32_t bytes) -> uint32_t {
            mbar_wait(bars + B_EMPTY + pp.stage * 8, pp.phase);
            if (first) { sts32(bars + B_RING + (seq & 7) * 4, (uint32_t)jd); sts32(bars + B_RING + 32 + (seq & 7) * 4, (uint32_t)j); first = false; }
            const uint32_t fb = bars + B_FULL + pp.stage * 8;
            if (bytes) mbar_expect_tx(fb, bytes); else mbar_arrive(fb);
            if (--left == 0 && type != J_END) mbar_arrive(bars + B_REQ);
            return fb;
        };
        if (type == J_END || type == J_LN) {
            if (type == J_LN && !(h_seen >> 31)) { wait_flag(F_MOD + 1, 64); h_seen |= 1u << 31; }

            TR(j, 2);
            begin_stage(0); pipe_next(pp);
            seq++;
            if (type == J_END) break;
            continue;
        }
        const CUtensorMap *ta, *tb0, *tb1;
        int k0 = 0, nk = 8, n0 = cb * 256, n1 = n0 + 128, nb = 4, dep = -1;
        unsigned tgt = 0;
        switch (type) {
            case J_KV: ta = &p.tm_h; tb0 = tb1 = cb < 16 ? &p.tm_wk : &p.tm_wv; n0 = (cb & 15) * 256; n1 = n0 + 128; dep = F_H + rb; tgt = 2 * NJ_LN1; break;
            case J_QA: ta = &p.tm_h; tb0 = tb1 = &p.tm_wq; dep = F_H + rb; tgt = 2 * NJ_LN1; if (rb == NRB - 1) { n0 = (cb >> 1) * 256; n1 = n0 + 128; } break;
            case J_O: ta = &p.tm_o; tb0 = tb1 = &p.tm_wo; n0 = (cb & 1) * 256; n1 = n0 + 128; nk = o_nk(rb); k0 = (cb >> 1) * nk * 64;
                      dep = F_O + rb; tgt = rb == NRB - 1 ? 64 : 32; break;
            case J_UP: ta = &p.tm_h2; tb0 = &p.tm_wg; tb1 = &p.tm_wu; n0 = n1 = cb * 128; dep = F_H2 + rb; tgt = 2 * NJ_LN; break;
            case J_UP2: ta = &p.tm_h2; tb0 = &p.tm_wg; tb1 = &p.tm_wu; n0 = n1 = cb * 64; nb = 2; dep = F_H2 + rb; tgt = 2 * NJ_LN2; break;
            default: ta = &p.tm_act; tb0 = tb1 = &p.tm_wd; n0 = cb * 64; nk = 0; break;
        }
        const int m0 = rb * 128;
        if (type == J_DN && rb == NRB - 1) {
            n0 = (cb >> 1) * 64;
            const int mh = m0 + (cb & 1) * 64;
#pragma unroll 1
            for (int kb = 0; kb < 14; kb++) {
                const uint32_t fb = begin_stage(32768);
                const uint32_t st = sb + pp.stage * W_STAGE;
                const int k = kb * 128;
                tma_load2d(st + 32768, tb0, n0, k, fb);
                tma_load2d(st + 40960, tb0, n0, k + 64, fb);
                if (kb == 0) { if (!acquired) { wait_flag(F_ACT + rb, 2 * NJ_UP2); asm volatile("fence.proxy.async.global;" ::: "memory"); } TR(j, 2); }
                tma_load2d(st, ta, k, mh, fb);
                tma_load2d(st + 8192, ta, k + 64, mh, fb);
                pipe_next(pp);
            }
            const uint32_t fb = begin_stage(8192);
            tma_load2d(sb + pp.stage * W_STAGE, &p.tm_x1, n0, mh, fb);
            pipe_next(pp);
            seq++;
            continue;
        }
        if (type == J_DN) {
#pragma unroll 1
            for (int kb = 0; kb < 14; kb++) {
                const uint32_t fb = begin_stage(49152);
                const uint32_t st = sb + pp.stage * W_STAGE;
                const int k = kb * 128;
                tma_load2d(st + 32768, tb0, n0, k, fb);
                tma_load2d(st + 40960, tb0, n0, k + 64, fb);
                if (kb == 0) { if (!acquired) { wait_flag(F_ACT + rb, 2 * (fine ? NJ_UP2 : NJ_UP)); asm volatile("fence.proxy.async.global;" ::: "memory"); } TR(j, 2); }
                tma_load2d(st, ta, k, m0, fb);
                tma_load2d(st + 8192, ta, k, m0 + 64, fb);
                tma_load2d(st + 16384, ta, k + 64, m0, fb);
                tma_load2d(st + 24576, ta, k + 64, m0 + 64, fb);
                pipe_next(pp);
            }
        }
#pragma unroll 1
        for (int kb = 0; kb < nk; kb++) {
            const uint32_t fb = begin_stage(16384 + nb * 8192);
            const uint32_t st = sb + pp.stage * W_STAGE;
            const int k = k0 + kb * 64;
            tma_load2d(st + 16384, tb0, n0, k, fb);
            if (nb == 4) {
                tma_load2d(st + 16384 + 8192, tb0, n0 + 64, k, fb);
                tma_load2d(st + 16384 + 16384, tb1, n1, k, fb);
                tma_load2d(st + 16384 + 24576, tb1, n1 + 64, k, fb);
            } else if (nb == 2) {
                tma_load2d(st + 16384 + 8192, tb1, n1, k, fb);
            }
            if (kb == 0) {
                if (acquired && dep < 16) h_seen |= 1u << dep;
                if (dep >= 0 && !acquired && !(dep < 16 && ((h_seen >> dep) & 1))) {
                    wait_flag(dep, tgt);
                    if (type != J_O) asm volatile("fence.proxy.async.global;" ::: "memory");
                    if (dep < 16) h_seen |= 1u << dep;
                }
                TR(j, 2);
            }
            tma_load2d(st, ta, k, m0, fb);
            tma_load2d(st + 8192, ta, k, m0 + 64, fb);
            pipe_next(pp);
        }
        if (type == J_QA) {
            wait_flag(F_KV + rb, 64);
#pragma unroll 1
            for (int i = 0; i < (rb == NRB - 1 ? 2 : 4); i++) {
                const uint32_t fb = begin_stage(40960);
                const uint32_t st = sb + pp.stage * W_STAGE;
                const int col = (i & 1) * HD_ + (rb == NRB - 1 ? cb : cb * 2 + (i >> 1)) * DH_;
                tma_load2d(st, &p.tm_kv, col, m0, fb);
                tma_load2d(st + 8192, &p.tm_kv, col, m0 + 64, fb);
                tma_load2d(st + 16384, &p.tm_kv, col + 64, m0, fb);
                tma_load2d(st + 24576, &p.tm_kv, col + 64, m0 + 64, fb);
                if (i == 0) { wait_flag(F_MEM + rb, 64); asm volatile("fence.proxy.async.global;" ::: "memory"); }
                tma_load2d(st + 32768, &p.tm_kvm, col, rb * 32, fb);
                tma_load2d(st + 36864, &p.tm_kvm, col + 64, rb * 32, fb);
                pipe_next(pp);
            }
        } else if (type == J_DN) {
            const uint32_t fb = begin_stage(16384);
            const uint32_t st = sb + pp.stage * W_STAGE;
            tma_load2d(st, &p.tm_x1, n0, m0, fb);
            tma_load2d(st + 8192, &p.tm_x1, n0, m0 + 64, fb);
            pipe_next(pp);
        }
        seq++;
    }
}

__device__ __forceinline__ void store_warp(const Params& p, uint32_t sb, int wg, int lane) {
    const uint32_t bars = sb + SM_BAR;
    uint32_t seq = 0;
#pragma unroll 1
    while (true) {
        bar_sync(NB_ST + wg, 160);
        const uint32_t jd = lds32(bars + B_RING + (seq & 7) * 4);
        seq++;
        const int type = jd & 255, rb = (jd >> 8) & 255, cb = (jd >> 16) & 255;
        if (type == J_END) break;
        const uint32_t src = sb + W_STG + wg * 16384;
        const CUtensorMap* tm = nullptr; int n0 = cb * 256, nbox = 4, mrow = rb * 128 + wg * 64, flag = 0;
        switch (type) {
            case J_KV: tm = &p.tm_kv; flag = F_KV + rb; break;
            case J_QA: tm = &p.tm_o; flag = F_O + rb; if (rb == NRB - 1) { n0 = cb * 128; nbox = 2; } break;
            case J_O: tm = &p.tm_op; n0 = (cb & 1) * 256; mrow = op_row(rb, cb >> 1) + wg * 64; flag = F_OP + rb; break;
            case J_LN: flag = F_H2 + rb; nbox = 0; break;
            case J_UP: tm = &p.tm_act; n0 = cb * 128; nbox = 2; flag = F_ACT + rb; break;
            case J_UP2: tm = &p.tm_act; n0 = cb * 64; nbox = 1; flag = F_ACT + rb; break;
            default: tm = &p.tm_out; n0 = cb * 64; nbox = 1; flag = -1;
                     if (rb == NRB - 1) { n0 = (cb >> 1) * 64; mrow = rb * 128 + (cb & 1) * 64; nbox = wg == 0; } break;
        }
        if (nbox == 4) {
            if (lane == 0) {
                tma_store2d(tm, src, n0, mrow);
                tma_store2d(tm, src + 8192, n0 + 64, mrow);
                bulk_commit();
                asm volatile("cp.async.bulk.wait_group.read 0;" ::: "memory");
                mbar_arrive(bars + B_STGFREE + wg * 8);
            }
            __syncwarp();
            bar_sync(NB_ST + wg, 160);
            n0 += 128; nbox = 2;
        }
        if (lane == 0) {
            if (nbox) {
                tma_store2d(tm, src, n0, mrow);
                if (nbox == 2) tma_store2d(tm, src + 8192, n0 + 64, mrow);
                bulk_commit();
                asm volatile("cp.async.bulk.wait_group.read 0;" ::: "memory");
                mbar_arrive(bars + B_STGFREE + wg * 8);
                bulk_wait0();
                if (flag >= 0) asm volatile("red.relaxed.gpu.global.add.u32 [%0], 1;" :: "l"(&g_flags[flag]) : "memory");
            } else {
                mbar_arrive(bars + B_STGFREE + wg * 8);
                if (flag >= 0) red_release(&g_flags[flag], 1);
            }
        }
        __syncwarp();
    }
}

__device__ __forceinline__ float gelu_tanh(float x) {
    const float t = x * fmaf(-0.10294324397f, x * x, -2.30220819814f);
    float r; asm("rcp.approx.ftz.f32 %0, %1;" : "=f"(r) : "f"(1.f + ex2(t)));
    return x * r;
}

#define CTR(i) do {} while (0)

__device__ __forceinline__ void ln2_row(const Params& p, int rb, int r, int lane, bool wait) {
    const int row = rb * 128 + r, nsplit = 64 / o_nk(rb);
    const uint4* xr = (const uint4*)(p.x + (size_t)row * D_);
    const uint4 xa = __ldg(xr + lane), xb = __ldg(xr + 32 + lane);
    uint32_t ga[8], c1[8], sm[8];
    load_mod8(g_mod + 2 * D_, lane, ga);
    load_mod8(g_mod + 4 * D_, lane, c1);
    load_mod8(g_mod + 3 * D_, lane, sm);
    float a[16];
#pragma unroll
    for (int i = 0; i < 16; i++) a[i] = 0.f;
    const uint4* src = (const uint4*)(g_op + (size_t)(op_row(rb, 0) + r) * D_) + lane;
    const int sstride = (op_row(rb, 1) - op_row(rb, 0)) * (D_ / 8);
    if (wait) { if (lane == 0) wait_flag(F_OP + rb, 4 * nsplit); __syncwarp(); }
    uint4 u[2][8];
#pragma unroll
    for (int sp = 0; sp < 4; sp++) { u[0][2 * sp] = __ldcg(src + sp * sstride); u[0][2 * sp + 1] = __ldcg(src + sp * sstride + 32); }
    if (nsplit > 4) {
#pragma unroll
        for (int sp = 0; sp < 4; sp++) { u[1][2 * sp] = __ldcg(src + (4 + sp) * sstride); u[1][2 * sp + 1] = __ldcg(src + (4 + sp) * sstride + 32); }
    }
#pragma unroll 1
    for (int s0 = 0; s0 < nsplit; s0 += 4) {
#pragma unroll
        for (int sp = 0; sp < 8; sp++) {
            float* q = a + (sp & 1) * 8;
            const uint4 w = u[0][sp];
            q[0] += bflo(w.x); q[1] += bfhi(w.x); q[2] += bflo(w.y); q[3] += bfhi(w.y);
            q[4] += bflo(w.z); q[5] += bfhi(w.z); q[6] += bflo(w.w); q[7] += bfhi(w.w);
            u[0][sp] = u[1][sp];
        }
        if (s0 + 8 < nsplit) {
#pragma unroll
            for (int sp = 0; sp < 4; sp++) { u[1][2 * sp] = __ldcg(src + (s0 + 8 + sp) * sstride); u[1][2 * sp + 1] = __ldcg(src + (s0 + 8 + sp) * sstride + 32); }
        }
    }
    const uint32_t xv[8] = {xa.x, xa.y, xa.z, xa.w, xb.x, xb.y, xb.z, xb.w};
    uint32_t v[8], r8[8];
#pragma unroll
    for (int i = 0; i < 8; i++) v[i] = hadd2(xv[i], hmul2(ga[i], pack2(a[2 * i], a[2 * i + 1])));
    uint4* x1r = (uint4*)(g_x1 + (size_t)row * D_);
    x1r[lane] = make_uint4(v[0], v[1], v[2], v[3]); x1r[32 + lane] = make_uint4(v[4], v[5], v[6], v[7]);
    uint32_t mu2; float rden;
    ln_stats(v, mu2, rden);
#pragma unroll
    for (int i = 0; i < 8; i++) c1[i] = hadd2(c1[i], 0x3F803F80u);
    ln_apply(v, mu2, rden, c1, sm, r8);
    uint4* hr = (uint4*)(g_h2 + (size_t)row * D_);
    hr[lane] = make_uint4(r8[0], r8[1], r8[2], r8[3]); hr[32 + lane] = make_uint4(r8[4], r8[5], r8[6], r8[7]);
}

__device__ __forceinline__ void consumer(const Params& p, uint32_t sb, int warp, int lane) {
    const uint32_t bars = sb + SM_BAR;
    const int wg = warp >> 2, wl = warp & 3;
    const uint32_t l7 = lane & 7, l8 = lane >> 3, g = lane >> 2, t = lane & 3;
    Pipe pp{0, 0};
    uint32_t seq = 0, stg_phase = 1;
    const int srow = wl * 16 + l7 + (l8 & 1) * 8;
    const uint32_t stg_base = sb + W_STG + wg * 16384 + srow * 128;
    const uint32_t sx = ((lane >> 4) ^ (srow & 7)) << 4;
#pragma unroll 1
    while (true) {
        mbar_wait(bars + B_FULL + pp.stage * 8, pp.phase);
        const uint32_t jd = lds32(bars + B_RING + (seq & 7) * 4);
        CTR(3);
        seq++;
        const int type = jd & 255, rb = (jd >> 8) & 255, cb = (jd >> 16) & 255;
        if (type == J_END) { mbar_wait(bars + B_STGFREE + wg * 8, stg_phase); bar_arrive(NB_ST + wg, 160); break; }
        if (type == J_LN) {
            __syncwarp();
            if (lane == 0) mbar_arrive(bars + B_EMPTY + pp.stage * 8);
            pipe_next(pp);
            const int nr = rb >= FINE_RB ? 1 : 2;
#pragma unroll 1
            for (int rr = 0; rr < nr; rr++) ln2_row(p, rb, (cb * 8 + warp) * nr + rr, lane, !((jd >> 24) & 1) && rr == 0);
            mbar_wait(bars + B_STGFREE + wg * 8, stg_phase); stg_phase ^= 1;
            CTR(4); CTR(5);
            bar_arrive(NB_ST + wg, 160);
            continue;
        }
        if (type == J_DN || type == J_UP2) {
            float acc[64];
#pragma unroll
            for (int i = 0; i < 64; i++) acc[i] = 0.f;
            const bool ksplit = type == J_DN && rb == NRB - 1;
            if (ksplit) {
#pragma unroll 1
                for (int kb = 0; kb < 14; kb++) {
                    if (kb) mbar_wait(bars + B_FULL + pp.stage * 8, pp.phase);
                    const uint32_t st = sb + pp.stage * W_STAGE;
                    const uint64_t da = mkdesc(st + wg * 8192, 16, 1024), db = mkdesc(st + 32768 + wg * 8192, 8192, 1024);
                    wg_fence();
#pragma unroll
                    for (int ks = 0; ks < 4; ks++) wgmma_n64(acc, da + ks * 2, db + ks * 128);
                    wg_commit();
                    wg_wait0();
                    if (lane == 0) mbar_arrive(bars + B_EMPTY + pp.stage * 8);
                    pipe_next(pp);
                }
                const uint32_t xb = sb + W_STG + 16384 + (wl * 32 + lane) * 16;
                if (wg == 1) {
                    mbar_wait(bars + B_STGFREE + 8, stg_phase);
#pragma unroll
                    for (int i = 0; i < 8; i++)
                        sts128(xb + i * 2048, make_uint4(__float_as_uint(acc[4 * i]), __float_as_uint(acc[4 * i + 1]), __float_as_uint(acc[4 * i + 2]), __float_as_uint(acc[4 * i + 3])));
                }
                bar_sync(NB_M, 256);
                if (wg == 0) {
#pragma unroll
                    for (int i = 0; i < 8; i++) {
                        const uint4 o = lds128(xb + i * 2048);
                        acc[4 * i] += __uint_as_float(o.x); acc[4 * i + 1] += __uint_as_float(o.y); acc[4 * i + 2] += __uint_as_float(o.z); acc[4 * i + 3] += __uint_as_float(o.w);
                    }
                }
                bar_sync(NB_M, 256);
            } else if (type == J_DN) {
#pragma unroll 1
                for (int kb = 0; kb < 14; kb++) {
                    if (kb) mbar_wait(bars + B_FULL + pp.stage * 8, pp.phase);
                    const uint32_t st = sb + pp.stage * W_STAGE;
                    const uint64_t da = mkdesc(st + wg * 8192, 16, 1024), db = mkdesc(st + 32768, 8192, 1024);
                    wg_fence();
#pragma unroll
                    for (int ks = 0; ks < 8; ks++) wgmma_n64(acc, da + (ks >> 2) * 1024 + (ks & 3) * 2, db + ks * 128);
                    wg_commit();
                    wg_wait0();
                    if (lane == 0) mbar_arrive(bars + B_EMPTY + pp.stage * 8);
                    pipe_next(pp);
                }
            } else {
#pragma unroll 1
                for (int kb = 0; kb < 8; kb++) {
                    if (kb) mbar_wait(bars + B_FULL + pp.stage * 8, pp.phase);
                    const uint32_t st = sb + pp.stage * W_STAGE;
                    const uint64_t da = mkdesc(st + wg * 8192, 16, 1024), db = mkdesc(st + 16384, 8192, 1024);
                    wg_fence();
#pragma unroll
                    for (int ks = 0; ks < 4; ks++) wgmma_n128(acc, da + ks * 2, db + ks * 128, 1);
                    wg_commit();
                    wg_wait0();
                    if (lane == 0) mbar_arrive(bars + B_EMPTY + pp.stage * 8);
                    pipe_next(pp);
                }
            }
            CTR(4);
            if (type == J_UP2) {
                mbar_wait(bars + B_STGFREE + wg * 8, stg_phase); stg_phase ^= 1;
#pragma unroll
                for (int j = 0; j < 4; j++) {
                    uint32_t r[4];
#pragma unroll
                    for (int q = 0; q < 4; q++) {
                        const uint32_t gw = pack2(acc[8 * j + 2 * q], acc[8 * j + 2 * q + 1]);
                        const uint32_t uw = pack2(acc[32 + 8 * j + 2 * q], acc[32 + 8 * j + 2 * q + 1]);
                        r[q] = hmul2(pack2(gelu_tanh(bflo(gw)), gelu_tanh(bfhi(gw))), uw);
                    }
                    stsm4(stg_base + (sx ^ (j << 5)), r[0], r[1], r[2], r[3]);
                }
            } else {
                mbar_wait(bars + B_FULL + pp.stage * 8, pp.phase);
                const uint32_t st = sb + pp.stage * W_STAGE;
                mbar_wait(bars + B_STGFREE + wg * 8, stg_phase); stg_phase ^= 1;
                const uint32_t* gb = (const uint32_t*)(g_mod + 5 * D_ + (ksplit ? cb >> 1 : cb) * 64) + t;
                const uint32_t xa = st + (ksplit ? 0 : wg * 8192) + (wl * 16 + g) * 128 + (g << 4) + t * 4;
#pragma unroll
                for (int j = 0; j < 4; j++) {
                    uint32_t r[4];
#pragma unroll
                    for (int q = 0; q < 4; q++) {
                        const int nt = 2 * j + (q >> 1);
                        const uint32_t xw = lds32((xa ^ ((nt & 7) << 4)) + (nt >> 3) * 16384 + (q & 1) * 1024);
                        r[q] = hadd2(xw, hmul2(__ldcg(gb + nt * 4), pack2(acc[8 * j + 2 * q], acc[8 * j + 2 * q + 1])));
                    }
                    stsm4(stg_base + (j >> 2) * 8192 + (sx ^ ((2 * j & 7) << 4)), r[0], r[1], r[2], r[3]);
                }
                __syncwarp();
                if (lane == 0) mbar_arrive(bars + B_EMPTY + pp.stage * 8);
                pipe_next(pp);
            }
            fence_async_smem();
            CTR(5);
            bar_arrive(NB_ST + wg, 160);
            continue;
        }
        float acc[128];
#pragma unroll
        for (int i = 0; i < 128; i++) acc[i] = 0.f;
        const int nk = type == J_O ? o_nk(rb) : 8;
#pragma unroll 1
        for (int kb = 0; kb < nk; kb++) {
            if (kb) mbar_wait(bars + B_FULL + pp.stage * 8, pp.phase);
            const uint32_t st = sb + pp.stage * W_STAGE;
            const uint64_t da = mkdesc(st + wg * 8192, 16, 1024), db = mkdesc(st + 16384, 8192, 1024);
            wg_fence();
#pragma unroll
            for (int ks = 0; ks < 4; ks++) wgmma_n256(acc, da + ks * 2, db + ks * 128, 1);
            wg_commit();
            wg_wait0();
            if (lane == 0) mbar_arrive(bars + B_EMPTY + pp.stage * 8);
            pipe_next(pp);
        }
        CTR(4);
        if (type == J_QA) {
            uint32_t qf[64];
#pragma unroll
            for (int i = 0; i < 64; i++) qf[i] = pack2(acc[2 * i], acc[2 * i + 1]);
            const int sg = warp >> 1, half = warp & 1;
            const float sc = 0.08838834764831845f * 1.4426950408889634f;
            const uint32_t xoff = (sg >> 1) * 8192 + ((sg & 1) * 32 + l7) * 128;
            const uint32_t moff = 32768 + (sg * 8 + l7) * 128;
            const uint32_t kch = (l8 ^ l7) << 4;
            const uint32_t vch = ((l8 & 1) ^ l7) << 4;
            if (rb == NRB - 1 && (cb & 1)) {
#pragma unroll
                for (int i = 0; i < 32; i++) qf[i] = qf[32 + i];
            }
#pragma unroll 1
            for (int hh = rb == NRB - 1; hh < 2; hh++) {
                mbar_wait(bars + B_FULL + pp.stage * 8, pp.phase);
                uint32_t st = sb + pp.stage * W_STAGE;
                float sa[5][4];
#pragma unroll
                for (int n = 0; n < 5; n++) sa[n][0] = sa[n][1] = sa[n][2] = sa[n][3] = 0.f;
#pragma unroll
                for (int i = 0; i < 4; i++) {
                    const uint32_t* q = qf + i * 8;
                    uint32_t kk[5][4];
                    ldsm4(kk[0][0], kk[0][1], kk[0][2], kk[0][3], st + moff + (i >> 1) * 4096 + (kch ^ ((i & 1) * 64)));
#pragma unroll
                    for (int n = 1; n < 5; n++)
                        ldsm4(kk[n][0], kk[n][1], kk[n][2], kk[n][3], st + xoff + (n - 1) * 1024 + (i >> 1) * 16384 + (kch ^ ((i & 1) * 64)));
#pragma unroll
                    for (int n = 0; n < 5; n++) mma16816(sa[n], q[0], q[1], q[2], q[3], kk[n][0], kk[n][1]);
#pragma unroll
                    for (int n = 0; n < 5; n++) mma16816(sa[n], q[4], q[5], q[6], q[7], kk[n][2], kk[n][3]);
                }
                __syncwarp();
                if (lane == 0) mbar_arrive(bars + B_EMPTY + pp.stage * 8);
                pipe_next(pp);
                const int iq0 = half * 16 + g - 2 * t, iq1 = iq0 + 8;
                float m0 = fmaxf(sa[0][0], sa[0][1]), m1 = fmaxf(sa[0][2], sa[0][3]);
#pragma unroll
                for (int n = 1; n < 5; n++) {
#pragma unroll
                    for (int e = 0; e < 2; e++) {
                        const int jx = (n - 1) * 8 + e;
                        if (jx > iq0) sa[n][e] = -3.0e38f;
                        if (jx > iq1) sa[n][2 + e] = -3.0e38f;
                        m0 = fmaxf(m0, sa[n][e]); m1 = fmaxf(m1, sa[n][2 + e]);
                    }
                }
                m0 = fmaxf(m0, __shfl_xor_sync(~0u, m0, 1)); m1 = fmaxf(m1, __shfl_xor_sync(~0u, m1, 1));
                m0 = fmaxf(m0, __shfl_xor_sync(~0u, m0, 2)); m1 = fmaxf(m1, __shfl_xor_sync(~0u, m1, 2));
                m0 *= -sc; m1 *= -sc;
                float l0 = 0.f, l1 = 0.f;
                uint32_t p0[5], p1[5];
#pragma unroll
                for (int n = 0; n < 5; n++) {
                    const float e0 = ex2(fmaf(sa[n][0], sc, m0)), e1 = ex2(fmaf(sa[n][1], sc, m0));
                    const float e2 = ex2(fmaf(sa[n][2], sc, m1)), e3 = ex2(fmaf(sa[n][3], sc, m1));
                    l0 += e0 + e1; l1 += e2 + e3;
                    p0[n] = pack2(e0, e1); p1[n] = pack2(e2, e3);
                }
                l0 += __shfl_xor_sync(~0u, l0, 1); l1 += __shfl_xor_sync(~0u, l1, 1);
                l0 += __shfl_xor_sync(~0u, l0, 2); l1 += __shfl_xor_sync(~0u, l1, 2);
                const float i0 = __fdividef(1.f, l0), i1 = __fdividef(1.f, l1);
                mbar_wait(bars + B_FULL + pp.stage * 8, pp.phase);
                st = sb + pp.stage * W_STAGE;
                mbar_wait(bars + B_STGFREE + wg * 8, stg_phase); stg_phase ^= 1;
#pragma unroll
                for (int i = 0; i < 32; i++) qf[i] = qf[32 + i];
#pragma unroll 1
                for (int bx = 0; bx < 2; bx++) {
                    float o[8][4];
                    uint32_t vm[8], v0[4][4], v1[4][4];
#pragma unroll
                    for (int ep = 0; ep < 4; ep++) {
                        ldsm2t(vm[2 * ep], vm[2 * ep + 1], st + moff + bx * 4096 + (vch ^ (ep << 5)));
                        const uint32_t va = st + xoff + (l8 >> 1) * 1024 + bx * 16384 + (vch ^ (ep << 5));
                        ldsm4t(v0[ep][0], v0[ep][1], v0[ep][2], v0[ep][3], va);
                        ldsm4t(v1[ep][0], v1[ep][1], v1[ep][2], v1[ep][3], va + 2048);
                    }
#pragma unroll
                    for (int n = 0; n < 8; n++) { o[n][0] = o[n][1] = o[n][2] = o[n][3] = 0.f; mma16816(o[n], p0[0], p1[0], p0[1], p1[1], vm[n], v0[n >> 1][n & 1]); }
#pragma unroll
                    for (int n = 0; n < 8; n++) mma16816(o[n], p0[2], p1[2], p0[3], p1[3], v0[n >> 1][2 + (n & 1)], v1[n >> 1][n & 1]);
#pragma unroll
                    for (int n = 0; n < 8; n++) mma1688(o[n], p0[4], p1[4], v1[n >> 1][2 + (n & 1)]);
#pragma unroll
                    for (int ep = 0; ep < 4; ep++)
                        stsm4(stg_base + bx * 8192 + (sx ^ (ep << 5)),
                              pack2(o[2 * ep][0] * i0, o[2 * ep][1] * i0), pack2(o[2 * ep][2] * i1, o[2 * ep][3] * i1),
                              pack2(o[2 * ep + 1][0] * i0, o[2 * ep + 1][1] * i0), pack2(o[2 * ep + 1][2] * i1, o[2 * ep + 1][3] * i1));
                }
                __syncwarp();
                if (lane == 0) mbar_arrive(bars + B_EMPTY + pp.stage * 8);
                pipe_next(pp);
                if (hh == 0) { fence_async_smem(); bar_arrive(NB_ST + wg, 160); }
            }
        } else if (type == J_UP) {
            mbar_wait(bars + B_STGFREE + wg * 8, stg_phase); stg_phase ^= 1;
#pragma unroll
            for (int j = 0; j < 8; j++) {
                uint32_t r[4];
#pragma unroll
                for (int q = 0; q < 4; q++) {
                    const uint32_t gw = pack2(acc[8 * j + 2 * q], acc[8 * j + 2 * q + 1]);
                    const uint32_t uw = pack2(acc[64 + 8 * j + 2 * q], acc[64 + 8 * j + 2 * q + 1]);
                    r[q] = hmul2(pack2(gelu_tanh(bflo(gw)), gelu_tanh(bfhi(gw))), uw);
                }
                stsm4(stg_base + (j >> 2) * 8192 + (sx ^ ((2 * j & 7) << 4)), r[0], r[1], r[2], r[3]);
            }
        } else {
#pragma unroll
            for (int rd = 0; rd < 2; rd++) {
                mbar_wait(bars + B_STGFREE + wg * 8, stg_phase); stg_phase ^= 1;
#pragma unroll
                for (int j = rd * 8; j < rd * 8 + 8; j++)
                    stsm4(stg_base + ((j >> 2) & 1) * 8192 + (sx ^ ((2 * j & 7) << 4)),
                          pack2(acc[8 * j], acc[8 * j + 1]), pack2(acc[8 * j + 2], acc[8 * j + 3]),
                          pack2(acc[8 * j + 4], acc[8 * j + 5]), pack2(acc[8 * j + 6], acc[8 * j + 7]));
                if (rd == 0) { fence_async_smem(); bar_arrive(NB_ST + wg, 160); }
            }
        }
        fence_async_smem();
        CTR(5);
        bar_arrive(NB_ST + wg, 160);
    }
}

__global__ void __launch_bounds__(384, 1) k_work(const __grid_constant__ Params p) {
    extern __shared__ __align__(1024) unsigned char smem_raw[];
    const uint32_t sb = smem_u32(smem_raw);
    if (sb & 1023) __trap();
    const int warp = __shfl_sync(~0u, threadIdx.x >> 5, 0);
    int lane; asm volatile("mov.u32 %0, %%laneid;" : "=r"(lane));
    if (threadIdx.x == 0) {
        const uint32_t bars = sb + SM_BAR;
        for (int i = 0; i < W_NST; i++) { mbar_init(bars + B_FULL + i * 8, 1); mbar_init(bars + B_EMPTY + i * 8, 8); }
        mbar_init(bars + B_STGFREE, 1); mbar_init(bars + B_STGFREE + 8, 1); mbar_init(bars + B_REQ, 1); mbar_init(bars + B_RSP, 1);
        asm volatile("fence.mbarrier_init.release.cluster;" ::: "memory");
    }
    __syncthreads();
    if (warp < 8) {
        asm volatile("setmaxnreg.inc.sync.aligned.u32 224;");
        consumer(p, sb, warp, lane);
    } else {
        asm volatile("setmaxnreg.dec.sync.aligned.u32 56;");
        if (warp == 8) { if (lane == 0) producer(p, sb); }
        else if (warp < 11) store_warp(p, sb, warp - 9, lane);
        else scheduler(p, sb, lane);
        __syncwarp();
        bar_sync(NB_W0, 128);
        if (warp == 8 && p.qmask == 0xff) {
            unsigned last = 0;
            if (lane == 0) { __threadfence(); last = atomicAdd(&g_flags[F_DONE], 1u) == gridDim.x - 1; }
            if (__shfl_sync(~0u, last, 0))
                for (int i = lane; i < F_TOTAL; i += 32) g_flags[i] = 0;
        }
    }
}

typedef CUresult (*EncodeFn)(CUtensorMap*, CUtensorMapDataType, cuuint32_t, void*, const cuuint64_t*, const cuuint64_t*,
                             const cuuint32_t*, const cuuint32_t*, CUtensorMapInterleave, CUtensorMapSwizzle,
                             CUtensorMapL2promotion, CUtensorMapFloatOOBfill);

static void make_map(EncodeFn enc, CUtensorMap* m, const void* ptr, uint64_t rows, uint64_t cols, uint32_t box_rows) {
    cuuint64_t dims[2] = {cols, rows};
    cuuint64_t strides[1] = {cols * 2};
    cuuint32_t box[2] = {64, box_rows};
    cuuint32_t es[2] = {1, 1};
    enc(m, CU_TENSOR_MAP_DATA_TYPE_BFLOAT16, 2, const_cast<void*>(ptr), dims, strides, box, es, CU_TENSOR_MAP_INTERLEAVE_NONE,
        CU_TENSOR_MAP_SWIZZLE_128B, CU_TENSOR_MAP_L2_PROMOTION_L2_256B, CU_TENSOR_MAP_FLOAT_OOB_FILL_NONE);
}
template <typename T> static void* sym_addr(T& sym) { void* p = nullptr; cudaGetSymbolAddress(&p, sym); return p; }

extern "C" void kernel_launch(void* const* d_in, const int* in_sizes, int n_in, void* d_out, int out_size) {
    static Params prm;
    static RecParams rp;
    static int n_sm = 132;
    static bool ready = false;
    static const void* key[14];
    bool same = ready;
    for (int i = 0; i < 13 && same; i++) same = key[i] == d_in[i];
    same = same && key[13] == d_out;
    if (!same) {
        void* fn = nullptr;
        cudaDriverEntryPointQueryResult qr;
        cudaGetDriverEntryPoint("cuTensorMapEncodeTiled", &fn, cudaEnableDefault, &qr);
        EncodeFn enc = (EncodeFn)fn;
        make_map(enc, &prm.tm_h, sym_addr(g_h), S_, D_, 64);
        make_map(enc, &prm.tm_kv, sym_addr(g_kv), S_, 2 * HD_, 64);
        make_map(enc, &prm.tm_kvm, sym_addr(g_kvm), NSEG * 8, 2 * HD_, 32);
        make_map(enc, &prm.tm_o, sym_addr(g_o), S_, HD_, 64);
        make_map(enc, &prm.tm_op, sym_addr(g_op), OP_ROWS, D_, 64);
        make_map(enc, &prm.tm_h2, sym_addr(g_h2), S_, D_, 64);
        make_map(enc, &prm.tm_act, sym_addr(g_act), S_, DF_, 64);
        make_map(enc, &prm.tm_x1, sym_addr(g_x1), S_, D_, 64);
        make_map(enc, &prm.tm_out, d_out, S_, D_, 64);
        make_map(enc, &prm.tm_wq, d_in[2], D_, HD_, 64);
        make_map(enc, &prm.tm_wk, d_in[3], D_, HD_, 64);
        make_map(enc, &prm.tm_wv, d_in[4], D_, HD_, 64);
        make_map(enc, &prm.tm_wo, d_in[5], HD_, D_, 64);
        make_map(enc, &prm.tm_wg, d_in[8], D_, DF_, 64);
        make_map(enc, &prm.tm_wu, d_in[9], D_, DF_, 64);
        make_map(enc, &prm.tm_wd, d_in[10], DF_, D_, 64);
        prm.x = (const bf16*)d_in[0]; prm.c = (const bf16*)d_in[11]; prm.w_mod = (const bf16*)d_in[12];
        rp.mem0 = (const bf16*)d_in[1]; rp.x = prm.x; rp.c = prm.c; rp.w_mod = prm.w_mod;
        rp.wq = (const bf16*)d_in[2]; rp.wk = (const bf16*)d_in[3]; rp.wv = (const bf16*)d_in[4]; rp.wo = (const bf16*)d_in[5];
        cudaDeviceGetAttribute(&n_sm, cudaDevAttrMultiProcessorCount, 0);
        cudaFuncSetAttribute(k_work, cudaFuncAttributeMaxDynamicSharedMemorySize, SMEM_BYTES);
        cudaFuncSetAttribute(k_rec, cudaFuncAttributeMaxDynamicSharedMemorySize, R_SMEM);
        cudaFuncSetAttribute(k_rec, cudaFuncAttributeNonPortableClusterSizeAllowed, 1);
        {
            cudaLaunchConfig_t cfg = {};
            cfg.gridDim = dim3(128); cfg.blockDim = dim3(384); cfg.dynamicSmemBytes = R_SMEM;
            cudaLaunchAttribute at[1];
            at[0].id = cudaLaunchAttributeClusterDimension; at[0].val.clusterDim.x = 16; at[0].val.clusterDim.y = 1; at[0].val.clusterDim.z = 1;
            cfg.attrs = at; cfg.numAttrs = 1;
            int n = 0;
            cudaOccupancyMaxActiveClusters(&n, k_rec, &cfg);
            rp.ncl = n < 4 ? 4 : (n > 8 ? 8 : n);
        }
        for (int i = 0; i < 13; i++) key[i] = d_in[i];
        key[13] = d_out;
        ready = true;
    }
    cudaStream_t st = cudaStreamPerThread;
    auto launch_rec = [&]() {
        cudaLaunchConfig_t cfg = {};
        cfg.gridDim = dim3(16 * rp.ncl); cfg.blockDim = dim3(384); cfg.dynamicSmemBytes = R_SMEM; cfg.stream = st;
        cudaLaunchAttribute at[1];
        at[0].id = cudaLaunchAttributeClusterDimension; at[0].val.clusterDim.x = 16; at[0].val.clusterDim.y = 1; at[0].val.clusterDim.z = 1;
        cfg.attrs = at; cfg.numAttrs = 1;
        cudaLaunchKernelEx(&cfg, k_rec, rp);
    };
    auto launch_work = [&](int qmask, int pdl) {
        prm.qmask = qmask;
        cudaLaunchConfig_t cfg = {};
        cfg.gridDim = dim3(n_sm); cfg.blockDim = dim3(384); cfg.dynamicSmemBytes = SMEM_BYTES; cfg.stream = st;
        cudaLaunchAttribute at[1];
        at[0].id = cudaLaunchAttributeProgrammaticStreamSerialization; at[0].val.programmaticStreamSerializationAllowed = 1;
        cfg.attrs = at; cfg.numAttrs = pdl;
        cudaLaunchKernelEx(&cfg, k_work, prm);
    };
    launch_rec();
    launch_work(0xff, 1);
}
```

```cpp
#include <cuda_runtime.h>
#include <cuda_bf16.h>
#include <cuda.h>
#include <stdint.h>

typedef __nv_bfloat16 bf16;
#define IDLE_NS 150
#define FLAG_NS 20

constexpr int S_ = 2048, D_ = 512, DH_ = 128, HD_ = 4096, NSEG = 64, DF_ = 1792;
constexpr int NRB = 16;
constexpr int OSPLIT = 4;

__device__ __align__(1024) bf16 g_h[S_ * D_];
__device__ __align__(1024) bf16 g_kv[S_ * 2 * HD_];
__device__ __align__(1024) bf16 g_kvm[NSEG * 8 * 2 * HD_];
__device__ __align__(1024) bf16 g_o[S_ * HD_];
#define FINE_RB_ 12
constexpr int FINE_RB = FINE_RB_;
#define OSPLIT2_ 8
constexpr int OSPLIT2 = OSPLIT2_;
constexpr int OSPLIT3 = 16;
constexpr int OP_ROWS = OSPLIT * S_ + OSPLIT2 * (NRB - FINE_RB) * 128 + OSPLIT3 * 128;
__device__ __align__(1024) bf16 g_op[OP_ROWS * D_];
__device__ __align__(1024) bf16 g_x1[S_ * D_];
__device__ __align__(1024) bf16 g_h2[S_ * D_];
__device__ __align__(1024) bf16 g_act[S_ * DF_];
__device__ __align__(1024) bf16 g_mod[6 * D_];
__device__ uint32_t g_Fraw[131072 + 65536 + 2048];
#define g_F ((uint32_t*)(((uint64_t)g_Fraw + 0x7FFFFull) & ~0x7FFFFull))
constexpr int F_H = 0, F_MEM = 32, F_O = 64, F_OP = 96, F_H2 = 128, F_ACT = 160, F_MOD = 192, F_KV = 224, F_CLAIM = 256  ,
              F_SIDE = 512  , F_DONE = 576, F_TOTAL = 608;
__device__ __align__(128) unsigned int g_flags[F_TOTAL];
#define TR(j, i) do {} while (0)

__device__ __forceinline__ uint32_t smem_u32(const void* p) { return (uint32_t)__cvta_generic_to_shared(p); }
__device__ __forceinline__ uint32_t clk32() { uint32_t c; asm volatile("mov.u32 %0, %%clock;" : "=r"(c)); return c; }
__device__ __forceinline__ uint32_t mapa_u32(uint32_t addr, uint32_t rank) {
    uint32_t r; asm volatile("mapa.shared::cluster.u32 %0, %1, %2;" : "=r"(r) : "r"(addr), "r"(rank)); return r;
}
__device__ __forceinline__ void mbar_init(uint32_t bar, uint32_t cnt) {
    asm volatile("mbarrier.init.shared::cta.b64 [%0], %1;" :: "r"(bar), "r"(cnt) : "memory");
}
__device__ __forceinline__ void mbar_expect_tx(uint32_t bar, uint32_t bytes) {
    asm volatile("mbarrier.arrive.expect_tx.shared::cta.b64 _, [%0], %1;" :: "r"(bar), "r"(bytes) : "memory");
}
__device__ __forceinline__ void mbar_arrive(uint32_t bar) {
    asm volatile("mbarrier.arrive.shared::cta.b64 _, [%0];" :: "r"(bar) : "memory");
}
__device__ __forceinline__ bool mbar_try_wait(uint32_t bar, uint32_t parity) {
    uint32_t ok;
    asm volatile("{\n.reg .pred p;\nmbarrier.try_wait.parity.shared::cta.b64 p, [%1], %2;\nselp.u32 %0, 1, 0, p;\n}"
                 : "=r"(ok) : "r"(bar), "r"(parity) : "memory");
    return ok;
}
constexpr int SPIN_LIMIT = 1 << 18;
#define TIMEOUT(code, info) do {} while (0)
__device__ __forceinline__ void mbar_wait(uint32_t bar, uint32_t parity) {
    int g = 0;
#pragma unroll 1
    while (!mbar_try_wait(bar, parity)) { if (++g >= SPIN_LIMIT) { TIMEOUT(0, bar & 255); break; } }
}
__device__ __forceinline__ void bar_sync(int id, int n) { asm volatile("bar.sync %0, %1;" :: "r"(id), "r"(n) : "memory"); }
__device__ __forceinline__ void bar_arrive(int id, int n) { asm volatile("bar.arrive %0, %1;" :: "r"(id), "r"(n) : "memory"); }
__device__ __forceinline__ void st_async_v2(uint32_t addr, float a, float b, uint32_t bar) {
    asm volatile("st.async.weak.shared::cluster.mbarrier::complete_tx::bytes.v2.f32 [%0], {%1,%2}, [%3];"
                 :: "r"(addr), "f"(a), "f"(b), "r"(bar) : "memory");
}
__device__ __forceinline__ void st_async_v4(uint32_t addr, uint4 v, uint32_t bar) {
    asm volatile("st.async.weak.shared::cluster.mbarrier::complete_tx::bytes.v4.b32 [%0], {%1,%2,%3,%4}, [%5];"
                 :: "r"(addr), "r"(v.x), "r"(v.y), "r"(v.z), "r"(v.w), "r"(bar) : "memory");
}
__device__ __forceinline__ void stg_relaxed32(uint32_t* p, uint32_t v) {
    asm volatile("st.relaxed.gpu.global.b32 [%0], %1;" :: "l"(p), "r"(v) : "memory");
}
__device__ __forceinline__ uint32_t ldg_relaxed32(const uint32_t* p) {
    uint32_t v; asm volatile("ld.relaxed.gpu.global.b32 %0, [%1];" : "=r"(v) : "l"(p) : "memory"); return v;
}
__device__ __forceinline__ unsigned int ld_acquire(const unsigned int* p) {
    unsigned int v; asm volatile("ld.acquire.gpu.global.u32 %0, [%1];" : "=r"(v) : "l"(p) : "memory"); return v;
}
__device__ __forceinline__ void red_release(unsigned int* p, unsigned int v) {
    asm volatile("red.release.gpu.global.add.u32 [%0], %1;" :: "l"(p), "r"(v) : "memory");
}
__device__ __forceinline__ void wait_flag(int idx, unsigned int target) {
    const unsigned int* p = &g_flags[idx];
    int g = 0;
#pragma unroll 1
    while (ld_acquire(p) < target) { __nanosleep(FLAG_NS); if (++g >= 64 * SPIN_LIMIT) { TIMEOUT(2, idx); break; } }
}
__device__ __forceinline__ void cp_async16(uint32_t dst, const void* src) {
    asm volatile("cp.async.cg.shared.global [%0], [%1], 16;" :: "r"(dst), "l"(src) : "memory");
}
__device__ __forceinline__ void cp_async_commit() { asm volatile("cp.async.commit_group;" ::: "memory"); }
template <int N> __device__ __forceinline__ void cp_async_wait() { asm volatile("cp.async.wait_group %0;" :: "n"(N) : "memory"); }
__device__ __forceinline__ void ldsm4(uint32_t& r0, uint32_t& r1, uint32_t& r2, uint32_t& r3, uint32_t addr) {
    asm volatile("ldmatrix.sync.aligned.m8n8.x4.shared.b16 {%0,%1,%2,%3}, [%4];" : "=r"(r0), "=r"(r1), "=r"(r2), "=r"(r3) : "r"(addr) : "memory");
}
__device__ __forceinline__ void ldsm4t(uint32_t& r0, uint32_t& r1, uint32_t& r2, uint32_t& r3, uint32_t addr) {
    asm volatile("ldmatrix.sync.aligned.m8n8.x4.trans.shared.b16 {%0,%1,%2,%3}, [%4];" : "=r"(r0), "=r"(r1), "=r"(r2), "=r"(r3) : "r"(addr) : "memory");
}
__device__ __forceinline__ void ldsm2t(uint32_t& r0, uint32_t& r1, uint32_t addr) {
    asm volatile("ldmatrix.sync.aligned.m8n8.x2.trans.shared.b16 {%0,%1}, [%2];" : "=r"(r0), "=r"(r1) : "r"(addr) : "memory");
}
__device__ __forceinline__ void stsm4(uint32_t addr, uint32_t r0, uint32_t r1, uint32_t r2, uint32_t r3) {
    asm volatile("stmatrix.sync.aligned.m8n8.x4.shared.b16 [%0], {%1,%2,%3,%4};" :: "r"(addr), "r"(r0), "r"(r1), "r"(r2), "r"(r3) : "memory");
}
__device__ __forceinline__ void stsm4t(uint32_t addr, uint32_t r0, uint32_t r1, uint32_t r2, uint32_t r3) {
    asm volatile("stmatrix.sync.aligned.m8n8.x4.trans.shared.b16 [%0], {%1,%2,%3,%4};" :: "r"(addr), "r"(r0), "r"(r1), "r"(r2), "r"(r3) : "memory");
}
__device__ __forceinline__ void stsm2t(uint32_t addr, uint32_t r0, uint32_t r1) {
    asm volatile("stmatrix.sync.aligned.m8n8.x2.trans.shared.b16 [%0], {%1,%2};" :: "r"(addr), "r"(r0), "r"(r1) : "memory");
}
__device__ __forceinline__ void mma16816(float* d, uint32_t a0, uint32_t a1, uint32_t a2, uint32_t a3, uint32_t b0, uint32_t b1) {
    asm volatile("mma.sync.aligned.m16n8k16.row.col.f32.bf16.bf16.f32 {%0,%1,%2,%3}, {%4,%5,%6,%7}, {%8,%9}, {%0,%1,%2,%3};"
                 : "+f"(d[0]), "+f"(d[1]), "+f"(d[2]), "+f"(d[3]) : "r"(a0), "r"(a1), "r"(a2), "r"(a3), "r"(b0), "r"(b1));
}
__device__ __forceinline__ void mma1688(float* d, uint32_t a0, uint32_t a1, uint32_t b0) {
    asm volatile("mma.sync.aligned.m16n8k8.row.col.f32.bf16.bf16.f32 {%0,%1,%2,%3}, {%4,%5}, {%6}, {%0,%1,%2,%3};"
                 : "+f"(d[0]), "+f"(d[1]), "+f"(d[2]), "+f"(d[3]) : "r"(a0), "r"(a1), "r"(b0));
}
__device__ __forceinline__ void mma16816h(float* d, uint32_t a0, uint32_t a2, uint32_t b0, uint32_t b1) {
    asm volatile("{\n.reg .b32 ju, jv;\nmma.sync.aligned.m16n8k16.row.col.f32.bf16.bf16.f32 {%0,%1,%2,%3}, {%4,ju,%5,jv}, {%6,%7}, {%0,%1,%2,%3};\n}"
                 : "+f"(d[0]), "+f"(d[1]), "+f"(d[2]), "+f"(d[3]) : "r"(a0), "r"(a2), "r"(b0), "r"(b1));
}
__device__ __forceinline__ void mma1688h(float* d, uint32_t a0, uint32_t b0) {
    asm volatile("{\n.reg .b32 ju;\nmma.sync.aligned.m16n8k8.row.col.f32.bf16.bf16.f32 {%0,%1,%2,%3}, {%4,ju}, {%5}, {%0,%1,%2,%3};\n}"
                 : "+f"(d[0]), "+f"(d[1]), "+f"(d[2]), "+f"(d[3]) : "r"(a0), "r"(b0));
}
__device__ __forceinline__ uint32_t movm(uint32_t a) {
    uint32_t d; asm volatile("movmatrix.sync.aligned.m8n8.trans.b16 %0, %1;" : "=r"(d) : "r"(a)); return d;
}
__device__ __forceinline__ uint32_t pack2(float lo, float hi) {
    uint32_t r; asm("cvt.rn.bf16x2.f32 %0, %1, %2;" : "=r"(r) : "f"(hi), "f"(lo)); return r;
}
__device__ __forceinline__ float bflo(uint32_t w) { return __uint_as_float(w << 16); }
__device__ __forceinline__ float bfhi(uint32_t w) { return __uint_as_float(w & 0xffff0000u); }
__device__ __forceinline__ float rbf(float x) { return __bfloat162float(__float2bfloat16_rn(x)); }
__device__ __forceinline__ float ex2(float x) { float y; asm("ex2.approx.ftz.f32 %0, %1;" : "=f"(y) : "f"(x)); return y; }
__device__ __forceinline__ void sts128(uint32_t addr, uint4 v) {
    asm volatile("st.shared.v4.b32 [%0], {%1,%2,%3,%4};" :: "r"(addr), "r"(v.x), "r"(v.y), "r"(v.z), "r"(v.w) : "memory");
}
__device__ __forceinline__ uint4 lds128(uint32_t addr) {
    uint4 v; asm volatile("ld.shared.v4.b32 {%0,%1,%2,%3}, [%4];" : "=r"(v.x), "=r"(v.y), "=r"(v.z), "=r"(v.w) : "r"(addr) : "memory"); return v;
}
__device__ __forceinline__ float2 lds64f(uint32_t addr) {
    float2 v; asm volatile("ld.shared.v2.f32 {%0,%1}, [%2];" : "=f"(v.x), "=f"(v.y) : "r"(addr) : "memory"); return v;
}
__device__ __forceinline__ float lds32f(uint32_t addr) {
    float v; asm volatile("ld.shared.f32 %0, [%1];" : "=f"(v) : "r"(addr) : "memory"); return v;
}
__device__ __forceinline__ uint32_t lds32(uint32_t addr) {
    uint32_t v; asm volatile("ld.shared.b32 %0, [%1];" : "=r"(v) : "r"(addr) : "memory"); return v;
}
__device__ __forceinline__ void sts32(uint32_t addr, uint32_t v) { asm volatile("st.shared.b32 [%0], %1;" :: "r"(addr), "r"(v) : "memory"); }
__device__ __forceinline__ void sts64f(uint32_t addr, float a, float b) { asm volatile("st.shared.v2.f32 [%0], {%1,%2};" :: "r"(addr), "f"(a), "f"(b) : "memory"); }

__device__ __forceinline__ void tma_load2d(uint32_t dst, const CUtensorMap* tm, int c0, int c1, uint32_t bar) {
    asm volatile("cp.async.bulk.tensor.2d.shared::cluster.global.mbarrier::complete_tx::bytes [%0], [%1, {%3, %4}], [%2];"
                 :: "r"(dst), "l"(tm), "r"(bar), "r"(c0), "r"(c1) : "memory");
}
__device__ __forceinline__ void tma_store2d(const CUtensorMap* tm, uint32_t src, int c0, int c1) {
    asm volatile("cp.async.bulk.tensor.2d.global.shared::cta.bulk_group [%0, {%2, %3}], [%1];"
                 :: "l"(tm), "r"(src), "r"(c0), "r"(c1) : "memory");
}
__device__ __forceinline__ void bulk_commit() { asm volatile("cp.async.bulk.commit_group;" ::: "memory"); }
__device__ __forceinline__ void bulk_wait0() { asm volatile("cp.async.bulk.wait_group 0;" ::: "memory"); }
__device__ __forceinline__ void fence_async_smem() { asm volatile("fence.proxy.async.shared::cta;" ::: "memory"); }
__device__ __forceinline__ void fence_async_all() { asm volatile("fence.proxy.async;" ::: "memory"); }

__device__ __forceinline__ void wg_fence() { asm volatile("wgmma.fence.sync.aligned;" ::: "memory"); }
__device__ __forceinline__ void wg_commit() { asm volatile("wgmma.commit_group.sync.aligned;" ::: "memory"); }
__device__ __forceinline__ void wg_wait0() { asm volatile("wgmma.wait_group.sync.aligned 0;" ::: "memory"); }
__device__ __forceinline__ uint64_t mkdesc(uint32_t saddr, uint32_t lbo, uint32_t sbo) {
    return (uint64_t)((saddr & 0x3FFFF) >> 4) | ((uint64_t)(lbo >> 4) << 16) | ((uint64_t)(sbo >> 4) << 32) | (1ull << 62);
}
#define ACC8(i) "+f"(d[i]), "+f"(d[i + 1]), "+f"(d[i + 2]), "+f"(d[i + 3]), "+f"(d[i + 4]), "+f"(d[i + 5]), "+f"(d[i + 6]), "+f"(d[i + 7])
__device__ __forceinline__ void wgmma_n256(float* d, uint64_t da, uint64_t db, int scale_d) {
    asm volatile(
        "{\n.reg .pred p;\nsetp.ne.b32 p, %130, 0;\n"
        "wgmma.mma_async.sync.aligned.m64n256k16.f32.bf16.bf16 "
        "{%0,%1,%2,%3,%4,%5,%6,%7,%8,%9,%10,%11,%12,%13,%14,%15,%16,%17,%18,%19,%20,%21,%22,%23,%24,%25,%26,%27,%28,%29,%30,%31,"
        "%32,%33,%34,%35,%36,%37,%38,%39,%40,%41,%42,%43,%44,%45,%46,%47,%48,%49,%50,%51,%52,%53,%54,%55,%56,%57,%58,%59,%60,%61,%62,%63,"
        "%64,%65,%66,%67,%68,%69,%70,%71,%72,%73,%74,%75,%76,%77,%78,%79,%80,%81,%82,%83,%84,%85,%86,%87,%88,%89,%90,%91,%92,%93,%94,%95,"
        "%96,%97,%98,%99,%100,%101,%102,%103,%104,%105,%106,%107,%108,%109,%110,%111,%112,%113,%114,%115,%116,%117,%118,%119,%120,%121,%122,%123,%124,%125,%126,%127}, "
        "%128, %129, p, 1, 1, 0, 1;\n}"
        : ACC8(0), ACC8(8), ACC8(16), ACC8(24), ACC8(32), ACC8(40), ACC8(48), ACC8(56),
          ACC8(64), ACC8(72), ACC8(80), ACC8(88), ACC8(96), ACC8(104), ACC8(112), ACC8(120)
        : "l"(da), "l"(db), "r"(scale_d));
}
__device__ __forceinline__ void wgmma_n128(float* d, uint64_t da, uint64_t db, int scale_d) {
    asm volatile(
        "{\n.reg .pred p;\nsetp.ne.b32 p, %66, 0;\n"
        "wgmma.mma_async.sync.aligned.m64n128k16.f32.bf16.bf16 "
        "{%0,%1,%2,%3,%4,%5,%6,%7,%8,%9,%10,%11,%12,%13,%14,%15,%16,%17,%18,%19,%20,%21,%22,%23,%24,%25,%26,%27,%28,%29,%30,%31,"
        "%32,%33,%34,%35,%36,%37,%38,%39,%40,%41,%42,%43,%44,%45,%46,%47,%48,%49,%50,%51,%52,%53,%54,%55,%56,%57,%58,%59,%60,%61,%62,%63}, "
        "%64, %65, p, 1, 1, 0, 1;\n}"
        : ACC8(0), ACC8(8), ACC8(16), ACC8(24), ACC8(32), ACC8(40), ACC8(48), ACC8(56)
        : "l"(da), "l"(db), "r"(scale_d));
}

__device__ __forceinline__ void wgmma_n64(float* d, uint64_t da, uint64_t db) {
    asm volatile(
        "wgmma.mma_async.sync.aligned.m64n64k16.f32.bf16.bf16 "
        "{%0,%1,%2,%3,%4,%5,%6,%7,%8,%9,%10,%11,%12,%13,%14,%15,%16,%17,%18,%19,%20,%21,%22,%23,%24,%25,%26,%27,%28,%29,%30,%31}, "
        "%32, %33, 1, 1, 1, 0, 1;"
        : ACC8(0), ACC8(8), ACC8(16), ACC8(24)
        : "l"(da), "l"(db));
}
__device__ __forceinline__ uint32_t hadd2(uint32_t a, uint32_t b) { uint32_t r; asm("add.rn.bf16x2 %0, %1, %2;" : "=r"(r) : "r"(a), "r"(b)); return r; }
__device__ __forceinline__ uint32_t hsub2(uint32_t a, uint32_t b) { uint32_t r; asm("sub.rn.bf16x2 %0, %1, %2;" : "=r"(r) : "r"(a), "r"(b)); return r; }
__device__ __forceinline__ uint32_t hmul2(uint32_t a, uint32_t b) { uint32_t r; asm("mul.rn.bf16x2 %0, %1, %2;" : "=r"(r) : "r"(a), "r"(b)); return r; }
__device__ __forceinline__ void load_mod8(const bf16* m, int lane, uint32_t* v) {
    const uint4 a = __ldcg((const uint4*)m + lane), b = __ldcg((const uint4*)m + 32 + lane);
    v[0] = a.x; v[1] = a.y; v[2] = a.z; v[3] = a.w; v[4] = b.x; v[5] = b.y; v[6] = b.z; v[7] = b.w;
}
__device__ __forceinline__ void ln_stats(const uint32_t* x, uint32_t& mu2, float& rden) {
    float s = 0.f;
#pragma unroll
    for (int i = 0; i < 8; i++) s += bflo(x[i]) + bfhi(x[i]);
#pragma unroll
    for (int o = 16; o > 0; o >>= 1) s += __shfl_xor_sync(~0u, s, o);
    const float mean = s * (1.f / D_);
    float q = 0.f;
#pragma unroll
    for (int i = 0; i < 8; i++) { const float d0 = bflo(x[i]) - mean, d1 = bfhi(x[i]) - mean; q = fmaf(d0, d0, q); q = fmaf(d1, d1, q); }
#pragma unroll
    for (int o = 16; o > 0; o >>= 1) q += __shfl_xor_sync(~0u, q, o);
    mu2 = pack2(mean, mean);
    rden = __frcp_rn(rbf(__fsqrt_rn(rbf(rbf(q * (1.f / D_)) + 1e-5f))));
}
__device__ __forceinline__ void ln_apply(const uint32_t* x, uint32_t mu2, float rden, const uint32_t* c1, const uint32_t* sm, uint32_t* r) {
#pragma unroll
    for (int i = 0; i < 8; i++) {
        const uint32_t d = hsub2(x[i], mu2);
        r[i] = hadd2(hmul2(pack2(bflo(d) * rden, bfhi(d) * rden), c1[i]), sm[i]);
    }
}

struct __align__(64) Params {
    CUtensorMap tm_h, tm_kv, tm_kvm, tm_o, tm_op, tm_h2, tm_act, tm_x1, tm_out;
    CUtensorMap tm_wq, tm_wk, tm_wv, tm_wo, tm_wg, tm_wu, tm_wd;
    const bf16 *x, *c, *w_mod;
    int qmask;
};

constexpr uint32_t R_WV = 0, R_MEM = 65536  ,
                   R_KX = 69632  , R_VX = R_KX + 8192,
                   R_VMS = R_KX + 32768  , R_OS = R_VMS + 2048  , R_SX = R_OS + 2048  , R_BAR = R_SX + 1536,
                   R_RS = R_BAR + 512  , R_VB = R_RS + 4096  , R_VP = R_VB + 2048  ,
                   R_STG = R_VP + 4096  ,
                   R_TQ = R_STG  , R_TV = R_STG + 53248  , R_QF = R_STG + 77824  ,
                   R_SMEM = R_STG + 98304;
static_assert((R_STG & 1023) == 0 && (R_RS & 511) == 0 && R_QF + 16384 <= R_SMEM, "smem");
constexpr uint32_t RB_Q = R_BAR, RB_V = R_BAR + 8, RB_E = R_BAR + 16, RB_A = R_BAR + 24, RB_ROLE = R_BAR + 32;
constexpr int W_NST = 4;
constexpr uint32_t W_STAGE = 49152, W_STG = W_NST * W_STAGE  , W_END = W_STG + 32768;
constexpr uint32_t SM_BAR = W_END;
constexpr uint32_t SMEM_BYTES = W_END + 1024 + 2048;
constexpr uint32_t B_FULL = 0, B_EMPTY = 32, B_STGFREE = 64, B_REQ = 80, B_RSP = 88, B_NEXT = 96, B_RING = 128;
#define PICK_AHEAD 3

constexpr int NB_S = 11, NB_Y = 1, NB_M = 5, NB_K = 5, NB_B = 2, NB_C = 3, NB_D = 4, NB_W0 = 6  , NB_ST = 9  ;

__device__ __forceinline__ int pos_of_d(int d) {
    const int rem = d & 31;
    return (d & ~31) + ((rem & 7) >> 1) * 8 + (rem & 1) * 4 + (rem >> 3);
}

#define PROF(i) do {} while (0)
#define PROFG(i) do {} while (0)
#define VK0_ 4
constexpr int VK0 = VK0_;
constexpr int NOFF = 8;
#define OFFKS(i) ((i) >> 1)
#define POLL_GAP 110

struct RecParams { const bf16 *mem0, *wq, *wk, *wv, *wo, *x, *c, *w_mod; int ncl, only_pre; };

__device__ __forceinline__ void rec_qk(const RecParams& p, const uint32_t sb, const int cta, const int warp, int lane, const int sel) {
    const int crank = cta & 15, cl = cta >> 4, rank = cta & 1;
    const int wg = warp >> 2, aa = warp & 3;
    uint32_t wa[2][16][4];
    {
        const uint32_t stg = sb + R_STG + wg * 32768;
        const int t128 = aa * 32 + lane;
        const int row = (lane >> 4) * 8 + (lane & 7);
        const int ch = t128 & 7;
        const size_t goff = (size_t)rank * 256 * HD_ + (cta >> 1) * DH_ + ch * 8;
        const bf16* W = (wg == 0 ? p.wq : p.wk) + goff;
#pragma unroll 4
        for (int dd = 0; dd < 16; dd++) {
            const int d = dd * 16 + (t128 >> 3), pp = pos_of_d(d);
            cp_async16(sb + R_WV + wg * 32768 + pp * 128 + ((ch ^ (pp & 7)) << 4), p.wv + goff + wg * 64 + (size_t)d * HD_);
        }
        cp_async_commit();
#pragma unroll 4
        for (int dd = 0; dd < 16; dd++) {
            const int d = dd * 16 + (t128 >> 3), pp = pos_of_d(d);
            cp_async16(stg + pp * 128 + ((ch ^ (pp & 7)) << 4), W + (size_t)d * HD_);
        }
        cp_async_commit();
        {
            const int tok = warp, d0 = lane * 8;
            const uint4 m0 = __ldg((const uint4*)(p.mem0 + tok * D_ + rank * 256 + d0));
            const uint32_t mw[4] = {m0.x, m0.y, m0.z, m0.w};
#pragma unroll
            for (int e = 0; e < 8; e++) {
                const int pp = pos_of_d(d0 + e);
                const unsigned short v = (unsigned short)(mw[e >> 1] >> ((e & 1) * 16));
                asm volatile("st.shared.u16 [%0], %1;" :: "r"(sb + R_MEM + (pp >> 3) * 128 + tok * 16 + (pp & 7) * 2), "h"(v) : "memory");
            }
        }
        cp_async_wait<1>();
        bar_sync(NB_W0 + wg, 128);
        const uint32_t fv = row * 128 + (((2 * aa + ((lane >> 3) & 1)) ^ (row & 7)) << 4);
#pragma unroll
        for (int ks = 0; ks < 16; ks++) ldsm4t(wa[0][ks][0], wa[0][ks][1], wa[0][ks][2], wa[0][ks][3], sb + R_WV + wg * 32768 + fv + ks * 2048);
        bar_sync(NB_W0 + wg, 128);
#pragma unroll
        for (int ks = 0; ks < 16; ks++)
            sts128(sb + R_WV + (warp * 16 + ks) * 512 + lane * 16, make_uint4(wa[0][ks][0], wa[0][ks][1], wa[0][ks][2], wa[0][ks][3]));
        const uint32_t fo = stg + row * 128 + (((4 * (aa & 1) + ((lane >> 3) & 1)) ^ (row & 7)) << 4);
#pragma unroll 1
        for (int m = 0; m < 2; m++) {
            cp_async_wait<0>();
            bar_sync(NB_W0 + wg, 128);
            if ((aa >> 1) == m) {
#pragma unroll
                for (int ks = 0; ks < 16; ks++) {
                    ldsm4t(wa[0][ks][0], wa[0][ks][1], wa[0][ks][2], wa[0][ks][3], fo + ks * 2048);
                    ldsm4t(wa[1][ks][0], wa[1][ks][1], wa[1][ks][2], wa[1][ks][3], (fo ^ 32) + ks * 2048);
                }
            }
            bar_sync(NB_W0 + wg, 128);
            if (m == 0) {
#pragma unroll 4
                for (int dd = 0; dd < 16; dd++) {
                    const int d = dd * 16 + (t128 >> 3), pp = pos_of_d(d);
                    cp_async16(stg + pp * 128 + ((ch ^ (pp & 7)) << 4), W + 64 + (size_t)d * HD_);
                }
                cp_async_commit();
            }
        }
    }
    bar_sync(NB_D, 384);
    const uint32_t tab = sb + R_TQ + wg * 26624 + (aa * 32 + lane) * 16;
    {
        const uint32_t l7 = lane & 7, l8 = lane >> 3, g = lane >> 2, t = lane & 3;
        const uint32_t bq = warp >> 1, tp = warp & 1;
        uint4 v;
        v.x = sb + R_QF + (rank * 8 + warp) * 512 + lane * 16;
        v.y = sb + R_QF + (warp == 5 ? 1024 : 0) + lane * 16;
        v.z = sb + R_KX + ((warp - 1) * 8 + l7) * 128 + ((l8 ^ l7) << 4);
        v.w = sb + R_SX + warp * 256 + lane * 8;
        sts128(tab, v);
        sts128(tab + 2048, make_uint4(sb + lane * 16 + R_MEM, sb + lane * 16 + R_WV + warp * 8192, sb + lane * 16 + R_VP + warp * 512, v.x));
        const uint32_t L = bq * 8 + 2 * tp + (l8 & 1) + 4 * (l8 >> 1);
        const uint32_t d0 = (((crank + ((t >> 1) | (g & 6))) & 7) << 1) | (crank >> 3);
        v.x = sb + R_RS + l7 * 512 + ((L ^ l7) << 4);
        v.y = mapa_u32(sb + R_MEM + ((crank & 7) * 4 + bq) * 128 + (4 * tp + 2 * (t & 1) + (g & 1)) * 16, d0);
        v.z = mapa_u32(sb + RB_A, d0);
        v.w = lane;
        sts128(tab + 4096, v);
        const uint64_t wr = (uint64_t)(g_F + ((crank * 2 + ((crank ^ (crank >> 3) ^ sel) & 1)) * 1024 + warp * 128 + cl * 32 + lane));
        sts128(tab + 6144, make_uint4((uint32_t)wr, (uint32_t)(wr >> 32), (uint32_t)((((cl + 1) & 3) - cl) * 128), (uint32_t)((((cl + 2) & 3) - cl) * 128)));
        sts32(tab + 8192, (uint32_t)((((cl + 3) & 3) - cl) * 128));
#pragma unroll
        for (int i = 0; i < NOFF; i++)
            sts128(tab + 10240 + i * 2048, make_uint4(wa[i & 1][OFFKS(i)][0], wa[i & 1][OFFKS(i)][1], wa[i & 1][OFFKS(i)][2], wa[i & 1][OFFKS(i)][3]));
    }
    bar_sync(NB_D, 384);
    uint4 tb = lds128(tab + 2048);
#pragma unroll 1
    for (int s = 0; s < NSEG; s++) {
        if (s > 0) mbar_wait(sb + RB_A, (s - 1) & 1);
        if (warp == 0) PROF(0);
        uint4 ta;
        const uint32_t par = (s & 1) * 8192;
        {
            float acc[5][4];
#pragma unroll
            for (int c = 0; c < 5; c++) { acc[c][0] = acc[c][1] = acc[c][2] = acc[c][3] = 0.f; }
            uint32_t b[8][4];
            uint4 av[16];
            static_assert(VK0 == 4, "order below assumes the V/O warps cover slices 0,1");
#define QK4(k2) do { \
                mma16816(acc[0], wa[0][2 * (k2)][0], wa[0][2 * (k2)][1], wa[0][2 * (k2)][2], wa[0][2 * (k2)][3], b[k2][0], b[k2][1]); \
                mma16816(acc[1], wa[1][2 * (k2)][0], wa[1][2 * (k2)][1], wa[1][2 * (k2)][2], wa[1][2 * (k2)][3], b[k2][0], b[k2][1]); \
                mma16816(acc[3], wa[0][2 * (k2) + 1][0], wa[0][2 * (k2) + 1][1], wa[0][2 * (k2) + 1][2], wa[0][2 * (k2) + 1][3], b[k2][2], b[k2][3]); \
                mma16816(acc[4], wa[1][2 * (k2) + 1][0], wa[1][2 * (k2) + 1][1], wa[1][2 * (k2) + 1][2], wa[1][2 * (k2) + 1][3], b[k2][2], b[k2][3]); } while (0)
#define V2(k2) do { \
                mma16816(acc[2], av[2 * (k2)].x, av[2 * (k2)].y, av[2 * (k2)].z, av[2 * (k2)].w, b[k2][0], b[k2][1]); \
                mma16816(acv, av[2 * (k2) + 1].x, av[2 * (k2) + 1].y, av[2 * (k2) + 1].z, av[2 * (k2) + 1].w, b[k2][2], b[k2][3]); } while (0)
#define LB(k2) ldsm4(b[k2][0], b[k2][1], b[k2][2], b[k2][3], tb.x + (k2) * 512)
#define LV(k2) do { av[2 * (k2)] = lds128(tb.y + 2 * (k2) * 512); av[2 * (k2) + 1] = lds128(tb.y + (2 * (k2) + 1) * 512); } while (0)
            float acv[4] = {0.f, 0.f, 0.f, 0.f};
            LB(0); LB(1); LB(2); LB(3);
            QK4(0); LB(4); QK4(1); LB(5); LV(2); LV(3); QK4(2); LB(6); QK4(3); LB(7);
            V2(2); V2(3); LV(4); LV(5);
            QK4(4); QK4(5); QK4(6); QK4(7);
            const uint4 f = make_uint4(movm(pack2(acc[0][0] + acc[3][0], acc[0][1] + acc[3][1])), movm(pack2(acc[0][2] + acc[3][2], acc[0][3] + acc[3][3])),
                                       movm(pack2(acc[1][0] + acc[4][0], acc[1][1] + acc[4][1])), movm(pack2(acc[1][2] + acc[4][2], acc[1][3] + acc[4][3])));
            st_async_v4((tb.w + par) ^ (1u << 24), f, (sb + RB_Q) ^ (1u << 24));
            sts128(tb.w + par, f);
            __syncwarp();
            if ((tb.w & 511) == 0) mbar_arrive(sb + RB_Q);
            if (warp == 0) PROF(1);
            if (tb.x == 0) break;
            LV(6); LV(7);
            ta = lds128(tab);
            V2(4); V2(5); V2(6); V2(7);
            sts128(tb.z, make_uint4(__float_as_uint(acc[2][0] + acv[0]), __float_as_uint(acc[2][1] + acv[1]), __float_as_uint(acc[2][2] + acv[2]), __float_as_uint(acc[2][3] + acv[3])));
            bar_arrive(NB_Y, 384);
        }
        if (warp == 0) PROF(14);
        if (warp < 6 && s != NSEG - 1) {
            float sa[4] = {0.f, 0.f, 0.f, 0.f}, sc[4] = {0.f, 0.f, 0.f, 0.f};
            const uint32_t qa = ta.y + par;
            if (warp == 0 || warp == 5) {
                mbar_wait(sb + RB_Q, s & 1);
                const uint4 q0 = lds128(qa), q1 = lds128(qa + 4096), k0 = lds128(qa + 2048), k1 = lds128(qa + 6144);
                const uint4 q2 = lds128(qa + 512), q3 = lds128(qa + 4608), k2 = lds128(qa + 2560), k3 = lds128(qa + 6656);
                mma16816h(sa, hadd2(q0.x, q1.x), hadd2(q0.y, q1.y), hadd2(k0.x, k1.x), hadd2(k0.y, k1.y));
                mma16816h(sc, hadd2(q0.z, q1.z), hadd2(q0.w, q1.w), hadd2(k0.z, k1.z), hadd2(k0.w, k1.w));
                mma16816h(sa, hadd2(q2.x, q3.x), hadd2(q2.y, q3.y), hadd2(k2.x, k3.x), hadd2(k2.y, k3.y));
                mma16816h(sc, hadd2(q2.z, q3.z), hadd2(q2.w, q3.w), hadd2(k2.z, k3.z), hadd2(k2.w, k3.w));
            } else {
                uint32_t k[16];
                const uint32_t kb = ta.z + 2 * par;
                ldsm4(k[0], k[1], k[2], k[3], kb);
                ldsm4(k[4], k[5], k[6], k[7], kb ^ 64);
                ldsm4(k[8], k[9], k[10], k[11], kb + 4096);
                ldsm4(k[12], k[13], k[14], k[15], (kb ^ 64) + 4096);
                mbar_wait(sb + RB_Q, s & 1);
                uint4 q0[4], q1[4];
#pragma unroll
                for (int i = 0; i < 4; i++) { q0[i] = lds128(qa + i * 512); q1[i] = lds128(qa + 4096 + i * 512); }
                float sd[4] = {0.f, 0.f, 0.f, 0.f}, se[4] = {0.f, 0.f, 0.f, 0.f};
                mma16816h(sa, hadd2(q0[0].x, q1[0].x), hadd2(q0[0].y, q1[0].y), k[0], k[1]);
                mma16816h(sc, hadd2(q0[0].z, q1[0].z), hadd2(q0[0].w, q1[0].w), k[2], k[3]);
                mma16816h(sd, hadd2(q0[1].x, q1[1].x), hadd2(q0[1].y, q1[1].y), k[4], k[5]);
                mma16816h(se, hadd2(q0[1].z, q1[1].z), hadd2(q0[1].w, q1[1].w), k[6], k[7]);
                mma16816h(sa, hadd2(q0[2].x, q1[2].x), hadd2(q0[2].y, q1[2].y), k[8], k[9]);
                mma16816h(sc, hadd2(q0[2].z, q1[2].z), hadd2(q0[2].w, q1[2].w), k[10], k[11]);
                mma16816h(sd, hadd2(q0[3].x, q1[3].x), hadd2(q0[3].y, q1[3].y), k[12], k[13]);
                mma16816h(se, hadd2(q0[3].z, q1[3].z), hadd2(q0[3].w, q1[3].w), k[14], k[15]);
                sa[0] += sd[0]; sa[1] += sd[1]; sc[0] += se[0]; sc[1] += se[1];
            }
            const float scl = 0.08838834764831845f * 1.4426950408889634f;
            sts64f(ta.w, (sa[0] + sc[0]) * scl, (sa[1] + sc[1]) * scl);
            bar_arrive(NB_S, 320);
            if (warp == 0) PROF(2);
        } else if (warp == 7) {
            mbar_wait(sb + RB_Q, s & 1);
            if (lane == 0) {
                mbar_expect_tx(sb + RB_Q, 4096);
                if (s > 0) mbar_expect_tx(sb + RB_A, 4096);
            }
            __syncwarp();
        } else if (s > 0 && (s & 3) == 0 && warp == 6) {
            bar_sync(NB_K, 160);
            if (lane == 0) red_release(&g_flags[F_MEM + (s >> 2) - 1], 1);
            __syncwarp();
        }
        if (s == NSEG - 1) {
            const uint4 td = lds128(tab + 6144);
            stg_relaxed32((uint32_t*)(((uint64_t)td.y << 32) | (td.x ^ 0x21000)), 0u);
            break;
        }
        const uint4 tc = lds128(tab + 4096), td = lds128(tab + 6144);
        const uint32_t te = lds32(tab + 8192);
        uint32_t* wr = (uint32_t*)(((uint64_t)td.y << 32) | (td.x ^ ((s & 1) * 0x21000)));
        const uint32_t* r1p = (const uint32_t*)((const char*)wr + (int)td.z);
        const uint32_t* r2p = (const uint32_t*)((const char*)wr + (int)td.w);
        const uint32_t* r3p = (const uint32_t*)((const char*)wr + (int)te);
        const uint32_t tag = ((s >> 1) + 1) & 1;
        mbar_wait(sb + RB_E, s & 1);
        if (warp == 0) PROF(7);
        {
            uint32_t a0, a1, a2, a3;
            ldsm4t(a0, a1, a2, a3, tc.x);
            const uint32_t one = 0x3F803F80u;
            float d0_[4] = {0.f, 0.f, 0.f, 0.f}, d1_[4] = {0.f, 0.f, 0.f, 0.f};
            mma1688(d0_, a0, a1, one);
            mma1688(d1_, a2, a3, one);
            const bool t1 = tc.w & 1, t2 = tc.w & 2;
            const float x = t2 ? (t1 ? d1_[2] : d1_[0]) : (t1 ? d0_[2] : d0_[0]);
            const uint32_t own = (__float_as_uint(x) & ~1u) | tag;
            stg_relaxed32(wr, own);
            const uint32_t tq = clk32();
            if (warp == 0) PROF(8);
            while ((int)(clk32() - tq) < POLL_GAP) {}
            uint32_t f1 = ldg_relaxed32(r1p), f2 = ldg_relaxed32(r2p), f3 = ldg_relaxed32(r3p);
#pragma unroll
            for (int i = 0; i < NOFF; i++) {
                const uint4 f0 = lds128(tab + 10240 + i * 2048);
                wa[i & 1][OFFKS(i)][0] = f0.x; wa[i & 1][OFFKS(i)][1] = f0.y; wa[i & 1][OFFKS(i)][2] = f0.z; wa[i & 1][OFFKS(i)][3] = f0.w;
            }
            tb = lds128(tab + 2048);
            int gg = 0;
#pragma unroll 1
            while (!__all_sync(~0u, (((f1 ^ tag) | (f2 ^ tag) | (f3 ^ tag)) & 1) == 0)) {
                f1 = ldg_relaxed32(r1p); f2 = ldg_relaxed32(r2p); f3 = ldg_relaxed32(r3p);
                if (++gg > 16 * SPIN_LIMIT) { TIMEOUT(3, s); break; }
            }
            if (warp == 0) PROF(9);
            const float v = (__uint_as_float(own) + __uint_as_float(f2)) + (__uint_as_float(f1) + __uint_as_float(f3));
            const bool b8 = tc.w & 8, b16 = tc.w & 16;
            const float recv = __shfl_xor_sync(~0u, v, 8);
            const uint32_t word = b8 ? pack2(recv, v) : pack2(v, recv);
            const uint32_t oth = __shfl_xor_sync(~0u, word, 16);
            const uint32_t wl = b16 ? oth : word, wh = b16 ? word : oth;
            const uint32_t p0 = __shfl_xor_sync(~0u, wl, 2), p1 = __shfl_xor_sync(~0u, wh, 2);
            const uint4 item = t2 ? make_uint4(p0, p1, wl, wh) : make_uint4(wl, wh, p0, p1);
            st_async_v4(tc.y, item, tc.z);
            if (tc.w == 0 && warp == 7) mbar_expect_tx(sb + RB_E, 4096);
            if (warp == 0) PROF(10);
        }
        bar_sync(NB_D, 384);
    }
}

__device__ __forceinline__ void rec_load_tile(uint32_t d, const char* src) {
    cp_async16(d, src);
    cp_async16(d ^ 16, src + 16);
    cp_async16(d + 4096, src + 128);
    cp_async16((d ^ 16) + 4096, src + 128 + 16);
}
__device__ __forceinline__ void rec_store_kvm(uint32_t src, char* dst, int s, int w) {
    dst += (size_t)s * (8 * 2 * HD_ * 2);
    if (w < 2) {
        const uint4 a = lds128(src + (s & 1) * 8192), b = lds128(src + (s & 1) * 8192 + 4096);
        *(uint32_t*)dst = hadd2(a.x, b.x); *(uint32_t*)(dst + 16) = hadd2(a.y, b.y);
        *(uint32_t*)(dst + 32) = hadd2(a.z, b.z); *(uint32_t*)(dst + 48) = hadd2(a.w, b.w);
    } else {
        *(uint4*)dst = lds128(src + (s & 1) * 1024);
    }
}

__device__ __forceinline__ void rec_vo(const RecParams& p, const uint32_t sb, const int cta, const int warp, int lane) {
    const int w = warp - 8, crank = cta & 15, rank = cta & 1;
    uint32_t wo[4][8][4];
    const uint32_t tab = sb + R_TV + (w * 32 + lane) * 16;
    {
        const int t128 = w * 32 + lane;
        const bf16* Wo = p.wo + (size_t)(cta >> 1) * DH_ * D_ + rank * 256;
        const uint32_t stg = sb + R_STG + 2 * 32768;
#pragma unroll
        for (int half = 0; half < 2; half++) {
#pragma unroll 4
            for (int i = t128; i < 2048; i += 128) {
                const int e = i >> 5, ch = i & 31;
                cp_async16(stg + e * 512 + ((ch ^ (e & 7)) << 4), Wo + (size_t)(half * 64 + e) * D_ + ch * 8);
            }
            cp_async_commit();
            cp_async_wait<0>();
            bar_sync(NB_W0 + 2, 128);
#pragma unroll
            for (int j = 0; j < 4; j++)
#pragma unroll
                for (int kk = 0; kk < 4; kk++) {
                    const int e = kk * 16 + (lane >> 4) * 8 + (lane & 7);
                    const int ch = (w * 4 + j) * 2 + ((lane >> 3) & 1);
                    ldsm4t(wo[j][half * 4 + kk][0], wo[j][half * 4 + kk][1], wo[j][half * 4 + kk][2], wo[j][half * 4 + kk][3],
                           stg + e * 512 + ((ch ^ (e & 7)) << 4));
                }
            bar_sync(NB_W0 + 2, 128);
        }
        bar_sync(NB_D, 384);
        const uint32_t l7 = lane & 7, l8 = lane >> 3, g = lane >> 2;
        uint4 v;
        v.x = sb + R_VX + (w >> 1) * 4096 + ((l8 & 1) * 8 + l7) * 128 + (((4 * (w & 1) + (l8 >> 1)) ^ l7) << 4);
        v.y = sb + R_OS + (w >> 1) * 1024 + g * 128 + (((4 * (w & 1)) ^ g) << 4) + (lane & 3) * 4;
        v.z = sb + R_VMS + l7 * 128 + (((4 * (w & 1) + l8) ^ l7) << 4);
        v.w = sb + R_OS + l7 * 128 + ((l8 ^ l7) << 4);
        sts128(tab, v);
        v.x = mapa_u32(sb + R_RS + (crank >> 1) * 512 + ((lane ^ (crank >> 1)) << 4), rank * 8 + w * 2);
        v.y = mapa_u32(sb + RB_E, rank * 8 + w * 2);
        v.z = sb + R_VB + w * 512 + lane * 16;
        v.w = sb + R_SX + lane * 8;
        sts128(tab + 2048, v);
#pragma unroll
        for (int i = 0; i < 8; i++)
            sts128(tab + 4096 + i * 2048, make_uint4(wo[i >> 1][(i & 1) * 4][0], wo[i >> 1][(i & 1) * 4][1], wo[i >> 1][(i & 1) * 4][2], wo[i >> 1][(i & 1) * 4][3]));
        const int row = t128 >> 2, c2 = (lane & 3) * 2, tok = (w & 1) * 4 + (lane >> 3);
        const uint64_t kd = w < 2 ? (uint64_t)(g_kvm + (g * (2 * HD_) + cta * 64 + w * 32 + (lane & 3) * 2))
                                  : (uint64_t)(g_kvm + (tok * (2 * HD_) + HD_ + cta * 64 + (lane & 7) * 8));
        const uint32_t ksrc = w < 2 ? sb + R_QF + (4 + 2 * rank + w) * 512 + lane * 16 : sb + R_VMS + tok * 128 + (((lane & 7) ^ tok) << 4);
        const uint64_t ks = (uint64_t)(g_kv + ((size_t)row * (2 * HD_) + (cta >> 1) * DH_ + c2 * 8));
        const uint32_t dk = sb + R_KX + row * 128 + ((c2 ^ (row & 7)) << 4);
        sts128(tab + 20480, make_uint4((uint32_t)kd, (uint32_t)(kd >> 32), (uint32_t)ks, (uint32_t)(ks >> 32)));
        sts128(tab + 22528, make_uint4(ksrc, dk, lane, sb + lane * 16));
        if (lane == 0) wait_flag(F_KV + 0, 64);
        __syncwarp();
        rec_load_tile(dk, (const char*)ks);
        rec_load_tile(dk + 8192, (const char*)ks + HD_ * 2);
        cp_async_commit();
        cp_async_wait<0>();
    }
    bar_sync(NB_D, 384);
    const uint32_t lane16 = lds32(tab + 22528 + 12);
    uint4 av[8];
#pragma unroll
    for (int i = 0; i < 8; i++) av[i] = lds128(lane16 + R_WV + ((2 * w + (i >> 2)) * 16 + (i & 3)) * 512);
#pragma unroll 1
    for (int s = 0; s < NSEG; s++) {
        {
            if (s > 0) mbar_wait(sb + RB_A, (s - 1) & 1);
            const uint4 tp = lds128(tab + 20480), tq = lds128(tab + 22528);
            if (s > 0) {
                rec_store_kvm(tq.x, (char*)(((uint64_t)tp.y << 32) | tp.x), s - 1, w);
                if ((s & 3) == 0) bar_arrive(NB_K, 160);
            }
            if (s + 1 < NSEG - 1) {
                if (((s + 1) & 3) == 0) { if (tq.z == 0) wait_flag(F_KV + ((s + 1) >> 2), 64); __syncwarp(); }
                const char* src = (const char*)((((uint64_t)tp.w << 32) | tp.z) + (uint64_t)(s + 1) * (32 * 2 * HD_ * 2));
                rec_load_tile(tq.y + ((s + 1) & 1) * 16384, src);
                rec_load_tile(tq.y + ((s + 1) & 1) * 16384 + 8192, src + HD_ * 2);
            }
            cp_async_commit();
        }
        uint4 vb;
        const uint4 ta = lds128(tab), tb = lds128(tab + 2048);
        {
            uint32_t bb[8];
            ldsm4(bb[0], bb[1], bb[2], bb[3], lane16 + R_MEM);
            ldsm4(bb[4], bb[5], bb[6], bb[7], lane16 + R_MEM + 512);
            float vd[4] = {0.f, 0.f, 0.f, 0.f}, ve[4] = {0.f, 0.f, 0.f, 0.f};
#pragma unroll
            for (int i = 0; i < 4; i++) {
                mma16816(vd, av[i].x, av[i].y, av[i].z, av[i].w, bb[2 * i], bb[2 * i + 1]);
                mma16816(ve, av[4 + i].x, av[4 + i].y, av[4 + i].z, av[4 + i].w, bb[2 * i], bb[2 * i + 1]);
            }
            bar_sync(NB_Y, 384);
            const uint4 a = lds128(lane16 + R_VP + w * 1024), b = lds128(lane16 + R_VP + w * 1024 + 512);
            vb = make_uint4(pack2(__uint_as_float(a.x) + vd[0], __uint_as_float(a.y) + vd[1]), pack2(__uint_as_float(a.z) + vd[2], __uint_as_float(a.w) + vd[3]),
                            pack2(__uint_as_float(b.x) + ve[0], __uint_as_float(b.y) + ve[1]), pack2(__uint_as_float(b.z) + ve[2], __uint_as_float(b.w) + ve[3]));
            st_async_v4(tb.z ^ (1u << 24), vb, (sb + RB_V) ^ (1u << 24));
        }
        if (w == 0) PROF(11);
        if (s != NSEG - 1) {
            uint32_t vx[16];
            const uint32_t vxa = ta.x + (s & 1) * 16384;
            ldsm4t(vx[0], vx[1], vx[2], vx[3], vxa);
            ldsm4t(vx[4], vx[5], vx[6], vx[7], vxa ^ 32);
            ldsm4t(vx[8], vx[9], vx[10], vx[11], vxa + 2048);
            ldsm4t(vx[12], vx[13], vx[14], vx[15], (vxa ^ 32) + 2048);
#pragma unroll
            for (int i = 0; i < 4; i++) {
                const uint4 f0 = lds128(tab + 4096 + i * 2048);
                wo[i >> 1][(i & 1) * 4][0] = f0.x; wo[i >> 1][(i & 1) * 4][1] = f0.y; wo[i >> 1][(i & 1) * 4][2] = f0.z; wo[i >> 1][(i & 1) * 4][3] = f0.w;
            }
            mbar_wait(sb + RB_V, s & 1);
            {
                const uint4 o = lds128(tb.z);
                vb = make_uint4(hadd2(vb.x, o.x), hadd2(vb.y, o.y), hadd2(vb.z, o.z), hadd2(vb.w, o.w));
            }
            bar_sync(NB_S, 320);
            if (w == 0) PROF(4);
            float sv[10];
#pragma unroll
            for (int n = 0; n < 5; n++) { const float2 a = lds64f(tb.w + n * 256); sv[2 * n] = a.x; sv[2 * n + 1] = a.y; }
            { const float2 a = lds64f(tb.w + 5 * 256); sv[0] += a.x; sv[1] += a.y; }
            float mx = fmaxf(fmaxf(fmaxf(sv[2], sv[3]), fmaxf(sv[4], sv[5])), fmaxf(fmaxf(sv[6], sv[7]), fmaxf(sv[8], sv[9])));
            mx = fmaxf(mx, fmaxf(sv[0], sv[1]));
            mx = fmaxf(mx, __shfl_xor_sync(~0u, mx, 1));
            mx = fmaxf(mx, __shfl_xor_sync(~0u, mx, 2));
            uint32_t pf[5];
#pragma unroll
            for (int n = 0; n < 5; n++) pf[n] = pack2(ex2(sv[2 * n] - mx), ex2(sv[2 * n + 1] - mx));
            if (w == 0) PROF(12);
            float oa[4][4] = {{0.f, 0.f, 0.f, 0.f}, {0.f, 0.f, 0.f, 0.f}, {0.f, 0.f, 0.f, 0.f}, {0.f, 0.f, 0.f, 0.f}}, sm[4] = {0.f, 0.f, 0.f, 0.f};
            const uint32_t one = 0x3F803F80u;
            mma1688h(sm, pf[0], one);
            mma1688h(oa[0], pf[0], vb.x);
            mma1688h(oa[1], pf[0], vb.y);
            mma1688h(oa[2], pf[0], vb.z);
            mma1688h(oa[3], pf[0], vb.w);
            mma16816h(sm, pf[1], pf[2], one, one);
#pragma unroll
            for (int n = 0; n < 4; n++) mma16816h(oa[n], pf[1], pf[2], vx[2 * n], vx[2 * n + 1]);
            mma16816h(sm, pf[3], pf[4], one, one);
#pragma unroll
            for (int n = 0; n < 4; n++) mma16816h(oa[n], pf[3], pf[4], vx[8 + 2 * n], vx[8 + 2 * n + 1]);
            float inv;
            asm("rcp.approx.ftz.f32 %0, %1;" : "=f"(inv) : "f"(sm[0]));
#pragma unroll
            for (int n = 0; n < 4; n++) sts32(ta.y ^ (n << 4), pack2(oa[n][0] * inv, oa[n][1] * inv));
            bar_sync(NB_C, 128);
            if (w == 0) PROF(5);
            uint32_t ob[16];
            ldsm4(ob[0], ob[1], ob[2], ob[3], ta.w);
            ldsm4(ob[8], ob[9], ob[10], ob[11], ta.w + 1024);
            ldsm4(ob[4], ob[5], ob[6], ob[7], ta.w ^ 64);
            ldsm4(ob[12], ob[13], ob[14], ob[15], (ta.w ^ 64) + 1024);
#pragma unroll
            for (int i = 4; i < 8; i++) {
                const uint4 f0 = lds128(tab + 4096 + i * 2048);
                wo[i >> 1][(i & 1) * 4][0] = f0.x; wo[i >> 1][(i & 1) * 4][1] = f0.y; wo[i >> 1][(i & 1) * 4][2] = f0.z; wo[i >> 1][(i & 1) * 4][3] = f0.w;
            }
#pragma unroll
            for (int jj = 0; jj < 2; jj++) {
                if (jj == 1 && tb.w == 0) break;
                float acc[4][4];
#pragma unroll
                for (int c = 0; c < 4; c++) { acc[c][0] = acc[c][1] = acc[c][2] = acc[c][3] = 0.f; }
#pragma unroll
                for (int k4 = 0; k4 < 4; k4++)
#pragma unroll
                    for (int c = 0; c < 4; c++) {
                        const int tl = jj * 2 + (c >> 1), ks = (c & 1) * 4 + k4;
                        mma16816(acc[c], wo[tl][ks][0], wo[tl][ks][1], wo[tl][ks][2], wo[tl][ks][3], ob[2 * ks], ob[2 * ks + 1]);
                    }
                uint4 v;
                v.x = pack2(acc[0][0] + acc[1][0], acc[0][1] + acc[1][1]);
                v.y = pack2(acc[0][2] + acc[1][2], acc[0][3] + acc[1][3]);
                v.z = pack2(acc[2][0] + acc[3][0], acc[2][1] + acc[3][1]);
                v.w = pack2(acc[2][2] + acc[3][2], acc[2][3] + acc[3][3]);
                st_async_v4(tb.x + (jj << 24), v, tb.y + (jj << 24));
            }
            if (w == 0) PROF(6);
        } else {
            mbar_wait(sb + RB_V, s & 1);
            const uint4 o = lds128(tb.z);
            vb = make_uint4(hadd2(vb.x, o.x), hadd2(vb.y, o.y), hadd2(vb.z, o.z), hadd2(vb.w, o.w));
            mbar_wait(sb + RB_Q, s & 1);
        }
        if ((w >> 1) == rank) stsm4t(ta.z + (s & 1) * 1024, vb.x, vb.y, vb.z, vb.w);
        cp_async_wait<0>();
        bar_sync(NB_C, 128);
        if (s != NSEG - 1) {
            if (w == 0 && lane == 0) mbar_expect_tx(sb + RB_V, 2048);
            bar_arrive(NB_D, 384);
        }
#pragma unroll
        for (int i = 0; i < 8; i++) av[i] = lds128(lane16 + R_WV + ((2 * w + (i >> 2)) * 16 + (i & 3)) * 512);
    }
    {
        const uint4 tp = lds128(tab + 20480), tq = lds128(tab + 22528);
        rec_store_kvm(tq.x, (char*)(((uint64_t)tp.y << 32) | tp.x), NSEG - 1, w);
    }
    bar_sync(NB_C, 128);
    if (w == 0 && lane == 0) red_release(&g_flags[F_MEM + NRB - 1], 1);
}

__global__ void __launch_bounds__(384, 1) k_rec(const RecParams p) {
    extern __shared__ __align__(1024) unsigned char smem_raw[];
    const uint32_t sb = __shfl_sync(~0u, smem_u32(smem_raw), 0);
    const int warp = __shfl_sync(~0u, threadIdx.x >> 5, 0);
    int lane; asm volatile("mov.u32 %0, %%laneid;" : "=r"(lane));
    const int crank = blockIdx.x & 15, slot = blockIdx.x >> 4;
    asm volatile("griddepcontrol.launch_dependents;");
    if (crank == 0 && threadIdx.x == 0) {
        stg_relaxed32(&g_F[65536 + slot * 64], 0u);
        stg_relaxed32(&g_F[65536 + 1024 + slot * 64], 0u);
    }
    if (threadIdx.x == 0) {
        mbar_init(sb + RB_Q, 9); mbar_init(sb + RB_V, 1); mbar_init(sb + RB_E, 1); mbar_init(sb + RB_A, 1); mbar_init(sb + RB_ROLE, 1);
        asm volatile("fence.mbarrier_init.release.cluster;" ::: "memory");
        mbar_expect_tx(sb + RB_Q, 4096);
        mbar_expect_tx(sb + RB_V, 2048);
        mbar_expect_tx(sb + RB_E, 4096);
        mbar_expect_tx(sb + RB_A, 4096);
        mbar_expect_tx(sb + RB_ROLE, 4);
    }
    asm volatile("barrier.cluster.arrive.relaxed.aligned;\nbarrier.cluster.wait.aligned;" ::: "memory");
    unsigned role = 0;
    if (crank == 0 && threadIdx.x == 0 && !p.only_pre) {
        unsigned x = 0;
        int tm[2] = {0x7fffffff, 0x7fffffff};
#pragma unroll 1
        for (int i = 0; i < 6; i++) {
            const uint32_t t0 = clk32();
            x = atomicAdd(&g_F[65536 + (i & 1) * 1024 + slot * 64 + (x >> 31)], 1u);
            if (x != (unsigned)(i >> 1)) sts32(sb + R_BAR + 56, x);
            const int dt = (int)(clk32() - t0);
            if (i >= 2) { if (i & 1) tm[1] = min(tm[1], dt); else tm[0] = min(tm[0], dt); }
        }
        const int side = tm[1] > tm[0];
        const unsigned old = atomicAdd(&g_flags[F_SIDE + side * 32], 1u);
        unsigned c0, c1; int gd = 0;
#pragma unroll 1
        do { c0 = ldg_relaxed32(&g_flags[F_SIDE]); c1 = ldg_relaxed32(&g_flags[F_SIDE + 32]); } while ((int)(c0 + c1) < p.ncl && ++gd < 64 * SPIN_LIMIT);
        const int big = c1 > c0;
        role = side == big ? old : (big ? c1 : c0) + old;
        role |= (big ^ 1) << 8;
    }
    __syncwarp();
    if (crank == 0 && warp == 0 && !p.only_pre) {
        role = __shfl_sync(~0u, role, 0);
        if (lane < 16)
            asm volatile("st.async.weak.shared::cluster.mbarrier::complete_tx::bytes.u32 [%0], %1, [%2];"
                         :: "r"(mapa_u32(sb + R_BAR + 48, lane)), "r"(role), "r"(mapa_u32(sb + RB_ROLE, lane)) : "memory");
    }
    if (warp >= 4) {
        const int w8 = warp - 4, nblk = gridDim.x;
        const int cq = lane & 3, rg = w8 * 8 + (lane >> 2);
        const uint32_t red = sb + R_VP;
        const int row0 = blockIdx.x * 8 + w8;
        const uint4* xr = (const uint4*)(p.x + (size_t)row0 * D_);
        uint4 xa = __ldg(xr + lane), xb = __ldg(xr + 32 + lane);
#pragma unroll 1
        for (int sl = blockIdx.x; sl < 96; sl += nblk) {
            uint4 wv[8];
#pragma unroll
            for (int i = 0; i < 8; i++) wv[i] = __ldg((const uint4*)(p.w_mod + (size_t)(rg * 8 + i) * (6 * D_) + sl * 32 + cq * 8));
            const uint32_t cw = __ldg((const uint32_t*)(p.c + rg * 8) + cq);
            const float cl = bflo(cw), ch = bfhi(cw);
            const uint32_t sw = pack2(__fdividef(cl, 1.f + __expf(-cl)), __fdividef(ch, 1.f + __expf(-ch)));
            float a[8];
#pragma unroll
            for (int i = 0; i < 8; i++) a[i] = 0.f;
#pragma unroll
            for (int i = 0; i < 8; i++) {
                const uint32_t sv = __shfl_sync(~0u, sw, (lane & 28) + (i >> 1));
                const float cv = (i & 1) ? bfhi(sv) : bflo(sv);
                a[0] = fmaf(cv, bflo(wv[i].x), a[0]); a[1] = fmaf(cv, bfhi(wv[i].x), a[1]); a[2] = fmaf(cv, bflo(wv[i].y), a[2]); a[3] = fmaf(cv, bfhi(wv[i].y), a[3]);
                a[4] = fmaf(cv, bflo(wv[i].z), a[4]); a[5] = fmaf(cv, bfhi(wv[i].z), a[5]); a[6] = fmaf(cv, bflo(wv[i].w), a[6]); a[7] = fmaf(cv, bfhi(wv[i].w), a[7]);
            }
#pragma unroll
            for (int i = 0; i < 8; i++) { a[i] += __shfl_xor_sync(~0u, a[i], 4); a[i] += __shfl_xor_sync(~0u, a[i], 8); a[i] += __shfl_xor_sync(~0u, a[i], 16); }
            if (lane < 4) {
                sts128(red + w8 * 128 + lane * 32, make_uint4(__float_as_uint(a[0]), __float_as_uint(a[1]), __float_as_uint(a[2]), __float_as_uint(a[3])));
                sts128(red + w8 * 128 + lane * 32 + 16, make_uint4(__float_as_uint(a[4]), __float_as_uint(a[5]), __float_as_uint(a[6]), __float_as_uint(a[7])));
            }
            bar_sync(NB_B, 256);
            if (w8 == 0) {
                float v = 0.f;
#pragma unroll
                for (int i = 0; i < 8; i++) v += lds32f(red + i * 128 + lane * 4);
                g_mod[sl * 32 + lane] = __float2bfloat16_rn(v);
                __syncwarp();
                if (lane == 0) red_release(&g_flags[F_MOD + (sl >= 32)], 1);
            }
            bar_sync(NB_B, 256);
        }
        uint32_t c1[8], sm[8];
        int row = row0;
#pragma unroll 1
        while (true) {
            const uint32_t v[8] = {xa.x, xa.y, xa.z, xa.w, xb.x, xb.y, xb.z, xb.w};
            uint32_t mu2, r[8]; float rden;
            ln_stats(v, mu2, rden);
            if (row == row0) {
                if (lane == 0) wait_flag(F_MOD, 32);
                __syncwarp();
                load_mod8(g_mod + D_, lane, c1);
                load_mod8(g_mod, lane, sm);
#pragma unroll
                for (int i = 0; i < 8; i++) c1[i] = hadd2(c1[i], 0x3F803F80u);
            } else if (row + 512 < S_) {
                xr = (const uint4*)(p.x + (size_t)(row + 512) * D_); xa = __ldg(xr + lane); xb = __ldg(xr + 32 + lane);
            }
            ln_apply(v, mu2, rden, c1, sm, r);
            uint4* hr = (uint4*)(g_h + (size_t)row * D_);
            hr[lane] = make_uint4(r[0], r[1], r[2], r[3]); hr[32 + lane] = make_uint4(r[4], r[5], r[6], r[7]);
            bar_sync(NB_B, 256);
            if (w8 == (row >> 7 & 7) && lane == 0) red_release(&g_flags[F_H + (row >> 7)], 1);
            __syncwarp();
            if (row == row0) {
                if (!p.only_pre) mbar_wait(sb + RB_ROLE, 0);
                const int cl = p.only_pre ? slot : (int)(lds32(sb + R_BAR + 48) & 255);
                row = cl < 4 ? (nblk + cl * 16 + crank) * 8 + w8 : S_;
                if (row < S_) { xr = (const uint4*)(p.x + (size_t)row * D_); xa = __ldg(xr + lane); xb = __ldg(xr + 32 + lane); }
            } else {
                row += 512;
            }
            if (row >= S_) break;
        }
    }
    if (p.only_pre) return;
    mbar_wait(sb + RB_ROLE, 0);
    const int rolew = __shfl_sync(~0u, lds32(sb + R_BAR + 48), 0);
    const int cl = rolew & 255;
    if (cl >= 4) return;
    const int cta = cl * 16 + crank;
    if (warp < 8) rec_qk(p, sb, cta, warp, lane, rolew >> 8);
    else rec_vo(p, sb, cta, warp, lane);
}

enum { J_KV = 0, J_QA = 1, J_O = 2, J_LN = 3, J_UP = 4, J_DN = 5, J_UP2 = 8, J_END = 9 };
constexpr int NJ_O = 2 * OSPLIT, NJ_O2 = 2 * OSPLIT2, NJ_LN = 8, NJ_LN2 = 16, NJ_UP = 14, NJ_UP2 = 28, NJ_DN = 8, NJ_LN1 = 8  ;
constexpr uint64_t pk8(int a, int b, int c, int d, int e, int f, int g, int h) {
    return (uint64_t)a | ((uint64_t)b << 8) | ((uint64_t)c << 16) | ((uint64_t)d << 24) | ((uint64_t)e << 32) | ((uint64_t)f << 40) | ((uint64_t)g << 48) | ((uint64_t)h << 56);
}
constexpr uint64_t NJ_C = pk8(32, 16, NJ_O, NJ_LN, NJ_UP, NJ_DN, 0, 0), NJ_F = pk8(32, 16, NJ_O2, NJ_LN2, NJ_UP2, NJ_DN, 0, 0);
constexpr uint64_t TG_C = pk8(2 * NJ_LN1, 64, 32, 2 * NJ_O, 2 * NJ_LN, 2 * NJ_UP, 32, 0), TG_F = pk8(2 * NJ_LN1, 64, 32, 2 * NJ_O2, 2 * NJ_LN2, 2 * NJ_UP2, 32, 0);
constexpr uint64_t NJ_L = pk8(32, 32, 2 * OSPLIT3, NJ_LN2, NJ_UP2, 2 * NJ_DN, 0, 0), TG_L = pk8(2 * NJ_LN1, 64, 64, 4 * OSPLIT3, 2 * NJ_LN2, 2 * NJ_UP2, 32, 0);
__device__ __forceinline__ uint64_t nj_tab(int rb) { return rb < FINE_RB ? NJ_C : (rb < NRB - 1 ? NJ_F : NJ_L); }
__device__ __forceinline__ uint64_t tg_tab(int rb) { return rb < FINE_RB ? TG_C : (rb < NRB - 1 ? TG_F : TG_L); }
__device__ __forceinline__ int o_nk(int rb) { return rb < FINE_RB ? 64 / OSPLIT : (rb < NRB - 1 ? 64 / OSPLIT2 : 64 / OSPLIT3); }
constexpr uint64_t PRIO = pk8(4, 10, 9, 8, 7, 6, 3, 0);
__device__ __forceinline__ int pick_job(int lane, int qmask, int& idx) {
    const int rb = lane & 15, half = lane >> 4;
    const uint64_t nj = nj_tab(rb) >> (8 * half);
    const uint64_t tg = tg_tab(rb) >> (8 * half);
    const unsigned* cp = &g_flags[F_CLAIM + half * 32 + rb];
    const unsigned* dp = &g_flags[half * 32 + rb];
    int gd = 0;
#pragma unroll 1
    while (true) {
        const unsigned c0 = ldg_relaxed32(cp), c1 = ldg_relaxed32(cp + 64), c2 = ldg_relaxed32(cp + 128);
        const unsigned d0 = ldg_relaxed32(dp - (half && rb ? 1 : 0)), d1 = ldg_relaxed32(dp + 64), d2 = ldg_relaxed32(dp + 128);
        const unsigned cl[3] = {c0, c1, c2}, dv[3] = {d0, d1, d2};
        unsigned key = 0xffffu, key2 = 0xffffu;
        bool pre = false;
#pragma unroll
        for (int i = 0; i < 3; i++) {
            const int q = half + 2 * i;
            const bool have = ((qmask >> q) & 1) && cl[i] < (unsigned)((nj >> (16 * i)) & 255);
            bool ready = have && dv[i] >= (unsigned)((tg >> (16 * i)) & 255);
            unsigned pr = (unsigned)((PRIO >> (8 * q)) & 255);
            if (i == 0 && rb <= 1 - half) ready = have;
            if (i == 0 && half && rb >= FINE_RB) pr = 5;
            if (ready) key = min(key, (pr << 8) | (rb << 4) | q);
            if (have) key2 = min(key2, rb >= FINE_RB ? (0x100u | (q << 4) | rb) : (i == 0 ? 0u : 0x1000u));
            pre |= have && i == 0 && !half;
        }
        const bool anypre = __any_sync(~0u, pre);
        if (anypre && (key & 15) == J_QA) key = 0xffffu;
        key = __reduce_min_sync(~0u, key);
        key2 = __reduce_min_sync(~0u, key2);
        if (key2 == 0xffffu) return J_END;
        int pq, prb;
        if (key != 0xffffu) { pq = key & 15; prb = (key >> 4) & 15; }
        else if (key2 >= 0x120u && key2 < 0x1000u) { pq = (key2 >> 4) & 15; prb = key2 & 15; }
        else {
            __nanosleep(IDLE_NS);
            if (++gd > 16 * SPIN_LIMIT) { TIMEOUT(5, 0); return J_END; }
            continue;
        }
        int c = 0;
        if (lane == 0) c = (int)atomicAdd(&g_flags[F_CLAIM + pq * 32 + prb], 1u);
        c = __shfl_sync(~0u, c, 0);
        if (c < (int)((nj_tab(prb) >> (8 * pq)) & 255)) {
            idx = pq * 512 + prb * 32 + c;
            int acq = 0;
            if (pq != J_QA) {
                if (lane == 0 && ld_acquire(&g_flags[pq * 32 + prb]) >= (unsigned)((tg_tab(prb) >> (8 * pq)) & 255)) {
                    asm volatile("fence.proxy.async.global;" ::: "memory");
                    acq = 1 << 24;
                }
            }
            return (pq == J_UP && prb >= FINE_RB ? J_UP2 : pq) | (prb << 8) | (c << 16) | acq;
        }
    }
}
__device__ __forceinline__ int op_row(int rb, int split) {
    return rb < FINE_RB ? split * S_ + rb * 128
                        : (rb < NRB - 1 ? OSPLIT * S_ + (split * (NRB - FINE_RB) + rb - FINE_RB) * 128 : OSPLIT * S_ + (OSPLIT2 * (NRB - FINE_RB) + split) * 128);
}

struct Pipe { uint32_t stage, phase; };
__device__ __forceinline__ void pipe_next(Pipe& p) { if (++p.stage == W_NST) { p.stage = 0; p.phase ^= 1; } }

__device__ __forceinline__ void scheduler(const Params& p, uint32_t sb, int lane) {
    const uint32_t bars = sb + SM_BAR;
    uint32_t ph = 0;
#pragma unroll 1
    while (true) {
        mbar_wait(bars + B_REQ, ph);
        int j = 4095;
        const int jd = pick_job(lane, p.qmask, j);
        if (lane == 0) { sts32(bars + B_NEXT, (uint32_t)jd); sts32(bars + B_NEXT + 4, (uint32_t)j); mbar_arrive(bars + B_RSP); }
        ph ^= 1;
        if (jd == J_END) break;
        __syncwarp();
    }
}

__device__ __forceinline__ void producer(const Params& p, uint32_t sb) {
    Pipe pp{0, 1};
    const uint32_t bars = sb + SM_BAR;
    uint32_t seq = 0, h_seen = 0;
    mbar_arrive(bars + B_REQ);
#pragma unroll 1
    while (true) {
        mbar_wait(bars + B_RSP, seq & 1);
        const int jd = (int)lds32(bars + B_NEXT), j = (int)lds32(bars + B_NEXT + 4);
        int left = (jd & 255) == J_DN ? 15 : ((jd & 255) == J_QA ? (((jd >> 8) & 255) == NRB - 1 ? 10 : 12) : ((jd & 255) == J_O ? o_nk((jd >> 8) & 255) : ((jd & 255) == J_LN ? 1 : 8)));
        left = max(left - PICK_AHEAD, 1);
        TR(j, 1);
        const int type = jd & 255, rb = (jd >> 8) & 255, cb = (jd >> 16) & 255;
        const bool fine = rb >= FINE_RB, acquired = (jd >> 24) & 1;
        bool first = true;
        auto begin_stage = [&](uint32_t bytes) -> uint32_t {
            mbar_wait(bars + B_EMPTY + pp.stage * 8, pp.phase);
            if (first) { sts32(bars + B_RING + (seq & 7) * 4, (uint32_t)jd); sts32(bars + B_RING + 32 + (seq & 7) * 4, (uint32_t)j); first = false; }
            const uint32_t fb = bars + B_FULL + pp.stage * 8;
            if (bytes) mbar_expect_tx(fb, bytes); else mbar_arrive(fb);
            if (--left == 0 && type != J_END) mbar_arrive(bars + B_REQ);
            return fb;
        };
        if (type == J_END || type == J_LN) {
            if (type == J_LN && !(h_seen >> 31)) { wait_flag(F_MOD + 1, 64); h_seen |= 1u << 31; }

            TR(j, 2);
            begin_stage(0); pipe_next(pp);
            seq++;
            if (type == J_END) break;
            continue;
        }
        const CUtensorMap *ta, *tb0, *tb1;
        int k0 = 0, nk = 8, n0 = cb * 256, n1 = n0 + 128, nb = 4, dep = -1;
        unsigned tgt = 0;
        switch (type) {
            case J_KV: ta = &p.tm_h; tb0 = tb1 = cb < 16 ? &p.tm_wk : &p.tm_wv; n0 = (cb & 15) * 256; n1 = n0 + 128; dep = F_H + rb; tgt = 2 * NJ_LN1; break;
            case J_QA: ta = &p.tm_h; tb0 = tb1 = &p.tm_wq; dep = F_H + rb; tgt = 2 * NJ_LN1; if (rb == NRB - 1) { n0 = (cb >> 1) * 256; n1 = n0 + 128; } break;
            case J_O: ta = &p.tm_o; tb0 = tb1 = &p.tm_wo; n0 = (cb & 1) * 256; n1 = n0 + 128; nk = o_nk(rb); k0 = (cb >> 1) * nk * 64;
                      dep = F_O + rb; tgt = rb == NRB - 1 ? 64 : 32; break;
            case J_UP: ta = &p.tm_h2; tb0 = &p.tm_wg; tb1 = &p.tm_wu; n0 = n1 = cb * 128; dep = F_H2 + rb; tgt = 2 * NJ_LN; break;
            case J_UP2: ta = &p.tm_h2; tb0 = &p.tm_wg; tb1 = &p.tm_wu; n0 = n1 = cb * 64; nb = 2; dep = F_H2 + rb; tgt = 2 * NJ_LN2; break;
            default: ta = &p.tm_act; tb0 = tb1 = &p.tm_wd; n0 = cb * 64; nk = 0; break;
        }
        const int m0 = rb * 128;
        if (type == J_DN && rb == NRB - 1) {
            n0 = (cb >> 1) * 64;
            const int mh = m0 + (cb & 1) * 64;
#pragma unroll 1
            for (int kb = 0; kb < 14; kb++) {
                const uint32_t fb = begin_stage(32768);
                const uint32_t st = sb + pp.stage * W_STAGE;
                const int k = kb * 128;
                tma_load2d(st + 32768, tb0, n0, k, fb);
                tma_load2d(st + 40960, tb0, n0, k + 64, fb);
                if (kb == 0) { if (!acquired) { wait_flag(F_ACT + rb, 2 * NJ_UP2); asm volatile("fence.proxy.async.global;" ::: "memory"); } TR(j, 2); }
                tma_load2d(st, ta, k, mh, fb);
                tma_load2d(st + 8192, ta, k + 64, mh, fb);
                pipe_next(pp);
            }
            const uint32_t fb = begin_stage(8192);
            tma_load2d(sb + pp.stage * W_STAGE, &p.tm_x1, n0, mh, fb);
            pipe_next(pp);
            seq++;
            continue;
        }
        if (type == J_DN) {
#pragma unroll 1
            for (int kb = 0; kb < 14; kb++) {
                const uint32_t fb = begin_stage(49152);
                const uint32_t st = sb + pp.stage * W_STAGE;
                const int k = kb * 128;
                tma_load2d(st + 32768, tb0, n0, k, fb);
                tma_load2d(st + 40960, tb0, n0, k + 64, fb);
                if (kb == 0) { if (!acquired) { wait_flag(F_ACT + rb, 2 * (fine ? NJ_UP2 : NJ_UP)); asm volatile("fence.proxy.async.global;" ::: "memory"); } TR(j, 2); }
                tma_load2d(st, ta, k, m0, fb);
                tma_load2d(st + 8192, ta, k, m0 + 64, fb);
                tma_load2d(st + 16384, ta, k + 64, m0, fb);
                tma_load2d(st + 24576, ta, k + 64, m0 + 64, fb);
                pipe_next(pp);
            }
        }
#pragma unroll 1
        for (int kb = 0; kb < nk; kb++) {
            const uint32_t fb = begin_stage(16384 + nb * 8192);
            const uint32_t st = sb + pp.stage * W_STAGE;
            const int k = k0 + kb * 64;
            tma_load2d(st + 16384, tb0, n0, k, fb);
            if (nb == 4) {
                tma_load2d(st + 16384 + 8192, tb0, n0 + 64, k, fb);
                tma_load2d(st + 16384 + 16384, tb1, n1, k, fb);
                tma_load2d(st + 16384 + 24576, tb1, n1 + 64, k, fb);
            } else if (nb == 2) {
                tma_load2d(st + 16384 + 8192, tb1, n1, k, fb);
            }
            if (kb == 0) {
                if (acquired && dep < 16) h_seen |= 1u << dep;
                if (dep >= 0 && !acquired && !(dep < 16 && ((h_seen >> dep) & 1))) {
                    wait_flag(dep, tgt);
                    if (type != J_O) asm volatile("fence.proxy.async.global;" ::: "memory");
                    if (dep < 16) h_seen |= 1u << dep;
                }
                TR(j, 2);
            }
            tma_load2d(st, ta, k, m0, fb);
            tma_load2d(st + 8192, ta, k, m0 + 64, fb);
            pipe_next(pp);
        }
        if (type == J_QA) {
            wait_flag(F_KV + rb, 64);
#pragma unroll 1
            for (int i = 0; i < (rb == NRB - 1 ? 2 : 4); i++) {
                const uint32_t fb = begin_stage(40960);
                const uint32_t st = sb + pp.stage * W_STAGE;
                const int col = (i & 1) * HD_ + (rb == NRB - 1 ? cb : cb * 2 + (i >> 1)) * DH_;
                tma_load2d(st, &p.tm_kv, col, m0, fb);
                tma_load2d(st + 8192, &p.tm_kv, col, m0 + 64, fb);
                tma_load2d(st + 16384, &p.tm_kv, col + 64, m0, fb);
                tma_load2d(st + 24576, &p.tm_kv, col + 64, m0 + 64, fb);
                if (i == 0) { wait_flag(F_MEM + rb, 64); asm volatile("fence.proxy.async.global;" ::: "memory"); }
                tma_load2d(st + 32768, &p.tm_kvm, col, rb * 32, fb);
                tma_load2d(st + 36864, &p.tm_kvm, col + 64, rb * 32, fb);
                pipe_next(pp);
            }
        } else if (type == J_DN) {
            const uint32_t fb = begin_stage(16384);
            const uint32_t st = sb + pp.stage * W_STAGE;
            tma_load2d(st, &p.tm_x1, n0, m0, fb);
            tma_load2d(st + 8192, &p.tm_x1, n0, m0 + 64, fb);
            pipe_next(pp);
        }
        seq++;
    }
}

__device__ __forceinline__ void store_warp(const Params& p, uint32_t sb, int wg, int lane) {
    const uint32_t bars = sb + SM_BAR;
    uint32_t seq = 0;
#pragma unroll 1
    while (true) {
        bar_sync(NB_ST + wg, 160);
        const uint32_t jd = lds32(bars + B_RING + (seq & 7) * 4);
        seq++;
        const int type = jd & 255, rb = (jd >> 8) & 255, cb = (jd >> 16) & 255;
        if (type == J_END) break;
        const uint32_t src = sb + W_STG + wg * 16384;
        const CUtensorMap* tm = nullptr; int n0 = cb * 256, nbox = 4, mrow = rb * 128 + wg * 64, flag = 0;
        switch (type) {
            case J_KV: tm = &p.tm_kv; flag = F_KV + rb; break;
            case J_QA: tm = &p.tm_o; flag = F_O + rb; if (rb == NRB - 1) { n0 = cb * 128; nbox = 2; } break;
            case J_O: tm = &p.tm_op; n0 = (cb & 1) * 256; mrow = op_row(rb, cb >> 1) + wg * 64; flag = F_OP + rb; break;
            case J_LN: flag = F_H2 + rb; nbox = 0; break;
            case J_UP: tm = &p.tm_act; n0 = cb * 128; nbox = 2; flag = F_ACT + rb; break;
            case J_UP2: tm = &p.tm_act; n0 = cb * 64; nbox = 1; flag = F_ACT + rb; break;
            default: tm = &p.tm_out; n0 = cb * 64; nbox = 1; flag = -1;
                     if (rb == NRB - 1) { n0 = (cb >> 1) * 64; mrow = rb * 128 + (cb & 1) * 64; nbox = wg == 0; } break;
        }
        if (nbox == 4) {
            if (lane == 0) {
                tma_store2d(tm, src, n0, mrow);
                tma_store2d(tm, src + 8192, n0 + 64, mrow);
                bulk_commit();
                asm volatile("cp.async.bulk.wait_group.read 0;" ::: "memory");
                mbar_arrive(bars + B_STGFREE + wg * 8);
            }
            __syncwarp();
            bar_sync(NB_ST + wg, 160);
            n0 += 128; nbox = 2;
        }
        if (lane == 0) {
            if (nbox) {
                tma_store2d(tm, src, n0, mrow);
                if (nbox == 2) tma_store2d(tm, src + 8192, n0 + 64, mrow);
                bulk_commit();
                asm volatile("cp.async.bulk.wait_group.read 0;" ::: "memory");
                mbar_arrive(bars + B_STGFREE + wg * 8);
                bulk_wait0();
                if (flag >= 0) asm volatile("red.relaxed.gpu.global.add.u32 [%0], 1;" :: "l"(&g_flags[flag]) : "memory");
            } else {
                mbar_arrive(bars + B_STGFREE + wg * 8);
                if (flag >= 0) red_release(&g_flags[flag], 1);
            }
        }
        __syncwarp();
    }
}

__device__ __forceinline__ float gelu_tanh(float x) {
    const float t = x * fmaf(-0.10294324397f, x * x, -2.30220819814f);
    float r; asm("rcp.approx.ftz.f32 %0, %1;" : "=f"(r) : "f"(1.f + ex2(t)));
    return x * r;
}

#define CTR(i) do {} while (0)

__device__ __forceinline__ void ln2_row(const Params& p, int rb, int r, int lane, bool wait) {
    const int row = rb * 128 + r, nsplit = 64 / o_nk(rb);
    const uint4* xr = (const uint4*)(p.x + (size_t)row * D_);
    const uint4 xa = __ldg(xr + lane), xb = __ldg(xr + 32 + lane);
    uint32_t ga[8], c1[8], sm[8];
    load_mod8(g_mod + 2 * D_, lane, ga);
    load_mod8(g_mod + 4 * D_, lane, c1);
    load_mod8(g_mod + 3 * D_, lane, sm);
    float a[16];
#pragma unroll
    for (int i = 0; i < 16; i++) a[i] = 0.f;
    const uint4* src = (const uint4*)(g_op + (size_t)(op_row(rb, 0) + r) * D_) + lane;
    const int sstride = (op_row(rb, 1) - op_row(rb, 0)) * (D_ / 8);
    if (wait) { if (lane == 0) wait_flag(F_OP + rb, 4 * nsplit); __syncwarp(); }
    uint4 u[2][8];
#pragma unroll
    for (int sp = 0; sp < 4; sp++) { u[0][2 * sp] = __ldcg(src + sp * sstride); u[0][2 * sp + 1] = __ldcg(src + sp * sstride + 32); }
    if (nsplit > 4) {
#pragma unroll
        for (int sp = 0; sp < 4; sp++) { u[1][2 * sp] = __ldcg(src + (4 + sp) * sstride); u[1][2 * sp + 1] = __ldcg(src + (4 + sp) * sstride + 32); }
    }
#pragma unroll 1
    for (int s0 = 0; s0 < nsplit; s0 += 4) {
#pragma unroll
        for (int sp = 0; sp < 8; sp++) {
            float* q = a + (sp & 1) * 8;
            const uint4 w = u[0][sp];
            q[0] += bflo(w.x); q[1] += bfhi(w.x); q[2] += bflo(w.y); q[3] += bfhi(w.y);
            q[4] += bflo(w.z); q[5] += bfhi(w.z); q[6] += bflo(w.w); q[7] += bfhi(w.w);
            u[0][sp] = u[1][sp];
        }
        if (s0 + 8 < nsplit) {
#pragma unroll
            for (int sp = 0; sp < 4; sp++) { u[1][2 * sp] = __ldcg(src + (s0 + 8 + sp) * sstride); u[1][2 * sp + 1] = __ldcg(src + (s0 + 8 + sp) * sstride + 32); }
        }
    }
    const uint32_t xv[8] = {xa.x, xa.y, xa.z, xa.w, xb.x, xb.y, xb.z, xb.w};
    uint32_t v[8], r8[8];
#pragma unroll
    for (int i = 0; i < 8; i++) v[i] = hadd2(xv[i], hmul2(ga[i], pack2(a[2 * i], a[2 * i + 1])));
    uint4* x1r = (uint4*)(g_x1 + (size_t)row * D_);
    x1r[lane] = make_uint4(v[0], v[1], v[2], v[3]); x1r[32 + lane] = make_uint4(v[4], v[5], v[6], v[7]);
    uint32_t mu2; float rden;
    ln_stats(v, mu2, rden);
#pragma unroll
    for (int i = 0; i < 8; i++) c1[i] = hadd2(c1[i], 0x3F803F80u);
    ln_apply(v, mu2, rden, c1, sm, r8);
    uint4* hr = (uint4*)(g_h2 + (size_t)row * D_);
    hr[lane] = make_uint4(r8[0], r8[1], r8[2], r8[3]); hr[32 + lane] = make_uint4(r8[4], r8[5], r8[6], r8[7]);
}

__device__ __forceinline__ void consumer(const Params& p, uint32_t sb, int warp, int lane) {
    const uint32_t bars = sb + SM_BAR;
    const int wg = warp >> 2, wl = warp & 3;
    const uint32_t l7 = lane & 7, l8 = lane >> 3, g = lane >> 2, t = lane & 3;
    Pipe pp{0, 0};
    uint32_t seq = 0, stg_phase = 1;
    const int srow = wl * 16 + l7 + (l8 & 1) * 8;
    const uint32_t stg_base = sb + W_STG + wg * 16384 + srow * 128;
    const uint32_t sx = ((lane >> 4) ^ (srow & 7)) << 4;
#pragma unroll 1
    while (true) {
        mbar_wait(bars + B_FULL + pp.stage * 8, pp.phase);
        const uint32_t jd = lds32(bars + B_RING + (seq & 7) * 4);
        CTR(3);
        seq++;
        const int type = jd & 255, rb = (jd >> 8) & 255, cb = (jd >> 16) & 255;
        if (type == J_END) { mbar_wait(bars + B_STGFREE + wg * 8, stg_phase); bar_arrive(NB_ST + wg, 160); break; }
        if (type == J_LN) {
            __syncwarp();
            if (lane == 0) mbar_arrive(bars + B_EMPTY + pp.stage * 8);
            pipe_next(pp);
            const int nr = rb >= FINE_RB ? 1 : 2;
#pragma unroll 1
            for (int rr = 0; rr < nr; rr++) ln2_row(p, rb, (cb * 8 + warp) * nr + rr, lane, !((jd >> 24) & 1) && rr == 0);
            mbar_wait(bars + B_STGFREE + wg * 8, stg_phase); stg_phase ^= 1;
            CTR(4); CTR(5);
            bar_arrive(NB_ST + wg, 160);
            continue;
        }
        if (type == J_DN || type == J_UP2) {
            float acc[64];
#pragma unroll
            for (int i = 0; i < 64; i++) acc[i] = 0.f;
            const bool ksplit = type == J_DN && rb == NRB - 1;
            if (ksplit) {
#pragma unroll 1
                for (int kb = 0; kb < 14; kb++) {
                    if (kb) mbar_wait(bars + B_FULL + pp.stage * 8, pp.phase);
                    const uint32_t st = sb + pp.stage * W_STAGE;
                    const uint64_t da = mkdesc(st + wg * 8192, 16, 1024), db = mkdesc(st + 32768 + wg * 8192, 8192, 1024);
                    wg_fence();
#pragma unroll
                    for (int ks = 0; ks < 4; ks++) wgmma_n64(acc, da + ks * 2, db + ks * 128);
                    wg_commit();
                    wg_wait0();
                    if (lane == 0) mbar_arrive(bars + B_EMPTY + pp.stage * 8);
                    pipe_next(pp);
                }
                const uint32_t xb = sb + W_STG + 16384 + (wl * 32 + lane) * 16;
                if (wg == 1) {
                    mbar_wait(bars + B_STGFREE + 8, stg_phase);
#pragma unroll
                    for (int i = 0; i < 8; i++)
                        sts128(xb + i * 2048, make_uint4(__float_as_uint(acc[4 * i]), __float_as_uint(acc[4 * i + 1]), __float_as_uint(acc[4 * i + 2]), __float_as_uint(acc[4 * i + 3])));
                }
                bar_sync(NB_M, 256);
                if (wg == 0) {
#pragma unroll
                    for (int i = 0; i < 8; i++) {
                        const uint4 o = lds128(xb + i * 2048);
                        acc[4 * i] += __uint_as_float(o.x); acc[4 * i + 1] += __uint_as_float(o.y); acc[4 * i + 2] += __uint_as_float(o.z); acc[4 * i + 3] += __uint_as_float(o.w);
                    }
                }
                bar_sync(NB_M, 256);
            } else if (type == J_DN) {
#pragma unroll 1
                for (int kb = 0; kb < 14; kb++) {
                    if (kb) mbar_wait(bars + B_FULL + pp.stage * 8, pp.phase);
                    const uint32_t st = sb + pp.stage * W_STAGE;
                    const uint64_t da = mkdesc(st + wg * 8192, 16, 1024), db = mkdesc(st + 32768, 8192, 1024);
                    wg_fence();
#pragma unroll
                    for (int ks = 0; ks < 8; ks++) wgmma_n64(acc, da + (ks >> 2) * 1024 + (ks & 3) * 2, db + ks * 128);
                    wg_commit();
                    wg_wait0();
                    if (lane == 0) mbar_arrive(bars + B_EMPTY + pp.stage * 8);
                    pipe_next(pp);
                }
            } else {
#pragma unroll 1
                for (int kb = 0; kb < 8; kb++) {
                    if (kb) mbar_wait(bars + B_FULL + pp.stage * 8, pp.phase);
                    const uint32_t st = sb + pp.stage * W_STAGE;
                    const uint64_t da = mkdesc(st + wg * 8192, 16, 1024), db = mkdesc(st + 16384, 8192, 1024);
                    wg_fence();
#pragma unroll
                    for (int ks = 0; ks < 4; ks++) wgmma_n128(acc, da + ks * 2, db + ks * 128, 1);
                    wg_commit();
                    wg_wait0();
                    if (lane == 0) mbar_arrive(bars + B_EMPTY + pp.stage * 8);
                    pipe_next(pp);
                }
            }
            CTR(4);
            if (type == J_UP2) {
                mbar_wait(bars + B_STGFREE + wg * 8, stg_phase); stg_phase ^= 1;
#pragma unroll
                for (int j = 0; j < 4; j++) {
                    uint32_t r[4];
#pragma unroll
                    for (int q = 0; q < 4; q++) {
                        const uint32_t gw = pack2(acc[8 * j + 2 * q], acc[8 * j + 2 * q + 1]);
                        const uint32_t uw = pack2(acc[32 + 8 * j + 2 * q], acc[32 + 8 * j + 2 * q + 1]);
                        r[q] = hmul2(pack2(gelu_tanh(bflo(gw)), gelu_tanh(bfhi(gw))), uw);
                    }
                    stsm4(stg_base + (sx ^ (j << 5)), r[0], r[1], r[2], r[3]);
                }
            } else {
                mbar_wait(bars + B_FULL + pp.stage * 8, pp.phase);
                const uint32_t st = sb + pp.stage * W_STAGE;
                mbar_wait(bars + B_STGFREE + wg * 8, stg_phase); stg_phase ^= 1;
                const uint32_t* gb = (const uint32_t*)(g_mod + 5 * D_ + (ksplit ? cb >> 1 : cb) * 64) + t;
                const uint32_t xa = st + (ksplit ? 0 : wg * 8192) + (wl * 16 + g) * 128 + (g << 4) + t * 4;
#pragma unroll
                for (int j = 0; j < 4; j++) {
                    uint32_t r[4];
#pragma unroll
                    for (int q = 0; q < 4; q++) {
                        const int nt = 2 * j + (q >> 1);
                        const uint32_t xw = lds32((xa ^ ((nt & 7) << 4)) + (nt >> 3) * 16384 + (q & 1) * 1024);
                        r[q] = hadd2(xw, hmul2(__ldcg(gb + nt * 4), pack2(acc[8 * j + 2 * q], acc[8 * j + 2 * q + 1])));
                    }
                    stsm4(stg_base + (j >> 2) * 8192 + (sx ^ ((2 * j & 7) << 4)), r[0], r[1], r[2], r[3]);
                }
                __syncwarp();
                if (lane == 0) mbar_arrive(bars + B_EMPTY + pp.stage * 8);
                pipe_next(pp);
            }
            fence_async_smem();
            CTR(5);
            bar_arrive(NB_ST + wg, 160);
            continue;
        }
        float acc[128];
#pragma unroll
        for (int i = 0; i < 128; i++) acc[i] = 0.f;
        const int nk = type == J_O ? o_nk(rb) : 8;
#pragma unroll 1
        for (int kb = 0; kb < nk; kb++) {
            if (kb) mbar_wait(bars + B_FULL + pp.stage * 8, pp.phase);
            const uint32_t st = sb + pp.stage * W_STAGE;
            const uint64_t da = mkdesc(st + wg * 8192, 16, 1024), db = mkdesc(st + 16384, 8192, 1024);
            wg_fence();
#pragma unroll
            for (int ks = 0; ks < 4; ks++) wgmma_n256(acc, da + ks * 2, db + ks * 128, 1);
            wg_commit();
            wg_wait0();
            if (lane == 0) mbar_arrive(bars + B_EMPTY + pp.stage * 8);
            pipe_next(pp);
        }
        CTR(4);
        if (type == J_QA) {
            uint32_t qf[64];
#pragma unroll
            for (int i = 0; i < 64; i++) qf[i] = pack2(acc[2 * i], acc[2 * i + 1]);
            const int sg = warp >> 1, half = warp & 1;
            const float sc = 0.08838834764831845f * 1.4426950408889634f;
            const uint32_t xoff = (sg >> 1) * 8192 + ((sg & 1) * 32 + l7) * 128;
            const uint32_t moff = 32768 + (sg * 8 + l7) * 128;
            const uint32_t kch = (l8 ^ l7) << 4;
            const uint32_t vch = ((l8 & 1) ^ l7) << 4;
            if (rb == NRB - 1 && (cb & 1)) {
#pragma unroll
                for (int i = 0; i < 32; i++) qf[i] = qf[32 + i];
            }
#pragma unroll 1
            for (int hh = rb == NRB - 1; hh < 2; hh++) {
                mbar_wait(bars + B_FULL + pp.stage * 8, pp.phase);
                uint32_t st = sb + pp.stage * W_STAGE;
                float sa[5][4];
#pragma unroll
                for (int n = 0; n < 5; n++) sa[n][0] = sa[n][1] = sa[n][2] = sa[n][3] = 0.f;
#pragma unroll
                for (int i = 0; i < 4; i++) {
                    const uint32_t* q = qf + i * 8;
                    uint32_t kk[5][4];
                    ldsm4(kk[0][0], kk[0][1], kk[0][2], kk[0][3], st + moff + (i >> 1) * 4096 + (kch ^ ((i & 1) * 64)));
#pragma unroll
                    for (int n = 1; n < 5; n++)
                        ldsm4(kk[n][0], kk[n][1], kk[n][2], kk[n][3], st + xoff + (n - 1) * 1024 + (i >> 1) * 16384 + (kch ^ ((i & 1) * 64)));
#pragma unroll
                    for (int n = 0; n < 5; n++) mma16816(sa[n], q[0], q[1], q[2], q[3], kk[n][0], kk[n][1]);
#pragma unroll
                    for (int n = 0; n < 5; n++) mma16816(sa[n], q[4], q[5], q[6], q[7], kk[n][2], kk[n][3]);
                }
                __syncwarp();
                if (lane == 0) mbar_arrive(bars + B_EMPTY + pp.stage * 8);
                pipe_next(pp);
                const int iq0 = half * 16 + g - 2 * t, iq1 = iq0 + 8;
                float m0 = fmaxf(sa[0][0], sa[0][1]), m1 = fmaxf(sa[0][2], sa[0][3]);
#pragma unroll
                for (int n = 1; n < 5; n++) {
#pragma unroll
                    for (int e = 0; e < 2; e++) {
                        const int jx = (n - 1) * 8 + e;
                        if (jx > iq0) sa[n][e] = -3.0e38f;
                        if (jx > iq1) sa[n][2 + e] = -3.0e38f;
                        m0 = fmaxf(m0, sa[n][e]); m1 = fmaxf(m1, sa[n][2 + e]);
                    }
                }
                m0 = fmaxf(m0, __shfl_xor_sync(~0u, m0, 1)); m1 = fmaxf(m1, __shfl_xor_sync(~0u, m1, 1));
                m0 = fmaxf(m0, __shfl_xor_sync(~0u, m0, 2)); m1 = fmaxf(m1, __shfl_xor_sync(~0u, m1, 2));
                m0 *= -sc; m1 *= -sc;
                float l0 = 0.f, l1 = 0.f;
                uint32_t p0[5], p1[5];
#pragma unroll
                for (int n = 0; n < 5; n++) {
                    const float e0 = ex2(fmaf(sa[n][0], sc, m0)), e1 = ex2(fmaf(sa[n][1], sc, m0));
                    const float e2 = ex2(fmaf(sa[n][2], sc, m1)), e3 = ex2(fmaf(sa[n][3], sc, m1));
                    l0 += e0 + e1; l1 += e2 + e3;
                    p0[n] = pack2(e0, e1); p1[n] = pack2(e2, e3);
                }
                l0 += __shfl_xor_sync(~0u, l0, 1); l1 += __shfl_xor_sync(~0u, l1, 1);
                l0 += __shfl_xor_sync(~0u, l0, 2); l1 += __shfl_xor_sync(~0u, l1, 2);
                const float i0 = __fdividef(1.f, l0), i1 = __fdividef(1.f, l1);
                mbar_wait(bars + B_FULL + pp.stage * 8, pp.phase);
                st = sb + pp.stage * W_STAGE;
                mbar_wait(bars + B_STGFREE + wg * 8, stg_phase); stg_phase ^= 1;
#pragma unroll
                for (int i = 0; i < 32; i++) qf[i] = qf[32 + i];
#pragma unroll 1
                for (int bx = 0; bx < 2; bx++) {
                    float o[8][4];
                    uint32_t vm[8], v0[4][4], v1[4][4];
#pragma unroll
                    for (int ep = 0; ep < 4; ep++) {
                        ldsm2t(vm[2 * ep], vm[2 * ep + 1], st + moff + bx * 4096 + (vch ^ (ep << 5)));
                        const uint32_t va = st + xoff + (l8 >> 1) * 1024 + bx * 16384 + (vch ^ (ep << 5));
                        ldsm4t(v0[ep][0], v0[ep][1], v0[ep][2], v0[ep][3], va);
                        ldsm4t(v1[ep][0], v1[ep][1], v1[ep][2], v1[ep][3], va + 2048);
                    }
#pragma unroll
                    for (int n = 0; n < 8; n++) { o[n][0] = o[n][1] = o[n][2] = o[n][3] = 0.f; mma16816(o[n], p0[0], p1[0], p0[1], p1[1], vm[n], v0[n >> 1][n & 1]); }
#pragma unroll
                    for (int n = 0; n < 8; n++) mma16816(o[n], p0[2], p1[2], p0[3], p1[3], v0[n >> 1][2 + (n & 1)], v1[n >> 1][n & 1]);
#pragma unroll
                    for (int n = 0; n < 8; n++) mma1688(o[n], p0[4], p1[4], v1[n >> 1][2 + (n & 1)]);
#pragma unroll
                    for (int ep = 0; ep < 4; ep++)
                        stsm4(stg_base + bx * 8192 + (sx ^ (ep << 5)),
                              pack2(o[2 * ep][0] * i0, o[2 * ep][1] * i0), pack2(o[2 * ep][2] * i1, o[2 * ep][3] * i1),
                              pack2(o[2 * ep + 1][0] * i0, o[2 * ep + 1][1] * i0), pack2(o[2 * ep + 1][2] * i1, o[2 * ep + 1][3] * i1));
                }
                __syncwarp();
                if (lane == 0) mbar_arrive(bars + B_EMPTY + pp.stage * 8);
                pipe_next(pp);
                if (hh == 0) { fence_async_smem(); bar_arrive(NB_ST + wg, 160); }
            }
        } else if (type == J_UP) {
            mbar_wait(bars + B_STGFREE + wg * 8, stg_phase); stg_phase ^= 1;
#pragma unroll
            for (int j = 0; j < 8; j++) {
                uint32_t r[4];
#pragma unroll
                for (int q = 0; q < 4; q++) {
                    const uint32_t gw = pack2(acc[8 * j + 2 * q], acc[8 * j + 2 * q + 1]);
                    const uint32_t uw = pack2(acc[64 + 8 * j + 2 * q], acc[64 + 8 * j + 2 * q + 1]);
                    r[q] = hmul2(pack2(gelu_tanh(bflo(gw)), gelu_tanh(bfhi(gw))), uw);
                }
                stsm4(stg_base + (j >> 2) * 8192 + (sx ^ ((2 * j & 7) << 4)), r[0], r[1], r[2], r[3]);
            }
        } else {
#pragma unroll
            for (int rd = 0; rd < 2; rd++) {
                mbar_wait(bars + B_STGFREE + wg * 8, stg_phase); stg_phase ^= 1;
#pragma unroll
                for (int j = rd * 8; j < rd * 8 + 8; j++)
                    stsm4(stg_base + ((j >> 2) & 1) * 8192 + (sx ^ ((2 * j & 7) << 4)),
                          pack2(acc[8 * j], acc[8 * j + 1]), pack2(acc[8 * j + 2], acc[8 * j + 3]),
                          pack2(acc[8 * j + 4], acc[8 * j + 5]), pack2(acc[8 * j + 6], acc[8 * j + 7]));
                if (rd == 0) { fence_async_smem(); bar_arrive(NB_ST + wg, 160); }
            }
        }
        fence_async_smem();
        CTR(5);
        bar_arrive(NB_ST + wg, 160);
    }
}

__global__ void __launch_bounds__(384, 1) k_work(const __grid_constant__ Params p) {
    extern __shared__ __align__(1024) unsigned char smem_raw[];
    const uint32_t sb = smem_u32(smem_raw);
    if (sb & 1023) __trap();
    const int warp = __shfl_sync(~0u, threadIdx.x >> 5, 0);
    int lane; asm volatile("mov.u32 %0, %%laneid;" : "=r"(lane));
    if (threadIdx.x == 0) {
        const uint32_t bars = sb + SM_BAR;
        for (int i = 0; i < W_NST; i++) { mbar_init(bars + B_FULL + i * 8, 1); mbar_init(bars + B_EMPTY + i * 8, 8); }
        mbar_init(bars + B_STGFREE, 1); mbar_init(bars + B_STGFREE + 8, 1); mbar_init(bars + B_REQ, 1); mbar_init(bars + B_RSP, 1);
        asm volatile("fence.mbarrier_init.release.cluster;" ::: "memory");
    }
    __syncthreads();
    if (warp < 8) {
        asm volatile("setmaxnreg.inc.sync.aligned.u32 224;");
        consumer(p, sb, warp, lane);
    } else {
        asm volatile("setmaxnreg.dec.sync.aligned.u32 56;");
        if (warp == 8) { if (lane == 0) producer(p, sb); }
        else if (warp < 11) store_warp(p, sb, warp - 9, lane);
        else scheduler(p, sb, lane);
        __syncwarp();
        bar_sync(NB_W0, 128);
        if (warp == 8 && p.qmask == 0xff) {
            unsigned last = 0;
            if (lane == 0) { __threadfence(); last = atomicAdd(&g_flags[F_DONE], 1u) == gridDim.x - 1; }
            if (__shfl_sync(~0u, last, 0))
                for (int i = lane; i < F_TOTAL; i += 32) g_flags[i] = 0;
        }
    }
}

typedef CUresult (*EncodeFn)(CUtensorMap*, CUtensorMapDataType, cuuint32_t, void*, const cuuint64_t*, const cuuint64_t*,
                             const cuuint32_t*, const cuuint32_t*, CUtensorMapInterleave, CUtensorMapSwizzle,
                             CUtensorMapL2promotion, CUtensorMapFloatOOBfill);

static void make_map(EncodeFn enc, CUtensorMap* m, const void* ptr, uint64_t rows, uint64_t cols, uint32_t box_rows) {
    cuuint64_t dims[2] = {cols, rows};
    cuuint64_t strides[1] = {cols * 2};
    cuuint32_t box[2] = {64, box_rows};
    cuuint32_t es[2] = {1, 1};
    enc(m, CU_TENSOR_MAP_DATA_TYPE_BFLOAT16, 2, const_cast<void*>(ptr), dims, strides, box, es, CU_TENSOR_MAP_INTERLEAVE_NONE,
        CU_TENSOR_MAP_SWIZZLE_128B, CU_TENSOR_MAP_L2_PROMOTION_L2_256B, CU_TENSOR_MAP_FLOAT_OOB_FILL_NONE);
}
template <typename T> static void* sym_addr(T& sym) { void* p = nullptr; cudaGetSymbolAddress(&p, sym); return p; }

extern "C" void kernel_launch(void* const* d_in, const int* in_sizes, int n_in, void* d_out, int out_size) {
    static Params prm;
    static RecParams rp;
    static int n_sm = 132;
    static bool ready = false;
    static const void* key[14];
    bool same = ready;
    for (int i = 0; i < 13 && same; i++) same = key[i] == d_in[i];
    same = same && key[13] == d_out;
    if (!same) {
        void* fn = nullptr;
        cudaDriverEntryPointQueryResult qr;
        cudaGetDriverEntryPoint("cuTensorMapEncodeTiled", &fn, cudaEnableDefault, &qr);
        EncodeFn enc = (EncodeFn)fn;
        make_map(enc, &prm.tm_h, sym_addr(g_h), S_, D_, 64);
        make_map(enc, &prm.tm_kv, sym_addr(g_kv), S_, 2 * HD_, 64);
        make_map(enc, &prm.tm_kvm, sym_addr(g_kvm), NSEG * 8, 2 * HD_, 32);
        make_map(enc, &prm.tm_o, sym_addr(g_o), S_, HD_, 64);
        make_map(enc, &prm.tm_op, sym_addr(g_op), OP_ROWS, D_, 64);
        make_map(enc, &prm.tm_h2, sym_addr(g_h2), S_, D_, 64);
        make_map(enc, &prm.tm_act, sym_addr(g_act), S_, DF_, 64);
        make_map(enc, &prm.tm_x1, sym_addr(g_x1), S_, D_, 64);
        make_map(enc, &prm.tm_out, d_out, S_, D_, 64);
        make_map(enc, &prm.tm_wq, d_in[2], D_, HD_, 64);
        make_map(enc, &prm.tm_wk, d_in[3], D_, HD_, 64);
        make_map(enc, &prm.tm_wv, d_in[4], D_, HD_, 64);
        make_map(enc, &prm.tm_wo, d_in[5], HD_, D_, 64);
        make_map(enc, &prm.tm_wg, d_in[8], D_, DF_, 64);
        make_map(enc, &prm.tm_wu, d_in[9], D_, DF_, 64);
        make_map(enc, &prm.tm_wd, d_in[10], DF_, D_, 64);
        prm.x = (const bf16*)d_in[0]; prm.c = (const bf16*)d_in[11]; prm.w_mod = (const bf16*)d_in[12];
        rp.mem0 = (const bf16*)d_in[1]; rp.x = prm.x; rp.c = prm.c; rp.w_mod = prm.w_mod;
        rp.wq = (const bf16*)d_in[2]; rp.wk = (const bf16*)d_in[3]; rp.wv = (const bf16*)d_in[4]; rp.wo = (const bf16*)d_in[5];
        cudaDeviceGetAttribute(&n_sm, cudaDevAttrMultiProcessorCount, 0);
        cudaFuncSetAttribute(k_work, cudaFuncAttributeMaxDynamicSharedMemorySize, SMEM_BYTES);
        cudaFuncSetAttribute(k_rec, cudaFuncAttributeMaxDynamicSharedMemorySize, R_SMEM);
        cudaFuncSetAttribute(k_rec, cudaFuncAttributeNonPortableClusterSizeAllowed, 1);
        {
            cudaLaunchConfig_t cfg = {};
            cfg.gridDim = dim3(128); cfg.blockDim = dim3(384); cfg.dynamicSmemBytes = R_SMEM;
            cudaLaunchAttribute at[1];
            at[0].id = cudaLaunchAttributeClusterDimension; at[0].val.clusterDim.x = 16; at[0].val.clusterDim.y = 1; at[0].val.clusterDim.z = 1;
            cfg.attrs = at; cfg.numAttrs = 1;
            int n = 0;
            cudaOccupancyMaxActiveClusters(&n, k_rec, &cfg);
            rp.ncl = n < 4 ? 4 : (n > 8 ? 8 : n);
        }
        for (int i = 0; i < 13; i++) key[i] = d_in[i];
        key[13] = d_out;
        ready = true;
    }
    cudaStream_t st = cudaStreamPerThread;
    auto launch_rec = [&]() {
        cudaLaunchConfig_t cfg = {};
        cfg.gridDim = dim3(16 * rp.ncl); cfg.blockDim = dim3(384); cfg.dynamicSmemBytes = R_SMEM; cfg.stream = st;
        cudaLaunchAttribute at[1];
        at[0].id = cudaLaunchAttributeClusterDimension; at[0].val.clusterDim.x = 16; at[0].val.clusterDim.y = 1; at[0].val.clusterDim.z = 1;
        cfg.attrs = at; cfg.numAttrs = 1;
        cudaLaunchKernelEx(&cfg, k_rec, rp);
    };
    auto launch_work = [&](int qmask, int pdl) {
        prm.qmask = qmask;
        cudaLaunchConfig_t cfg = {};
        cfg.gridDim = dim3(n_sm); cfg.blockDim = dim3(384); cfg.dynamicSmemBytes = SMEM_BYTES; cfg.stream = st;
        cudaLaunchAttribute at[1];
        at[0].id = cudaLaunchAttributeProgrammaticStreamSerialization; at[0].val.programmaticStreamSerializationAllowed = 1;
        cfg.attrs = at; cfg.numAttrs = pdl;
        cudaLaunchKernelEx(&cfg, k_work, prm);
    };
    launch_rec();
    launch_work(0xff, 1);
}
```

```cpp
#include <cuda_runtime.h>
#include <cuda_bf16.h>
#include <cuda.h>
#include <stdint.h>

typedef __nv_bfloat16 bf16;
#define IDLE_NS 150
#define FLAG_NS 20

constexpr int S_ = 2048, D_ = 512, DH_ = 128, HD_ = 4096, NSEG = 64, DF_ = 1792;
constexpr int NRB = 16;
constexpr int OSPLIT = 4;

__device__ __align__(1024) bf16 g_h[S_ * D_];
__device__ __align__(1024) bf16 g_kv[S_ * 2 * HD_];
__device__ __align__(1024) bf16 g_kvm[NSEG * 8 * 2 * HD_];
__device__ __align__(1024) bf16 g_o[S_ * HD_];
#define FINE_RB_ 12
constexpr int FINE_RB = FINE_RB_;
#define OSPLIT2_ 8
constexpr int OSPLIT2 = OSPLIT2_;
constexpr int OSPLIT3 = 16;
constexpr int OP_ROWS = OSPLIT * S_ + OSPLIT2 * (NRB - FINE_RB) * 128 + OSPLIT3 * 128;
__device__ __align__(1024) bf16 g_op[OP_ROWS * D_];
__device__ __align__(1024) bf16 g_x1[S_ * D_];
__device__ __align__(1024) bf16 g_h2[S_ * D_];
__device__ __align__(1024) bf16 g_act[S_ * DF_];
__device__ __align__(1024) bf16 g_mod[6 * D_];
__device__ uint32_t g_Fraw[131072 + 65536 + 2048];
#define g_F ((uint32_t*)(((uint64_t)g_Fraw + 0x7FFFFull) & ~0x7FFFFull))
constexpr int F_H = 0, F_MEM = 32, F_O = 64, F_OP = 96, F_H2 = 128, F_ACT = 160, F_MOD = 192, F_KV = 224, F_CLAIM = 256  ,
              F_SIDE = 512  , F_DONE = 576, F_TOTAL = 608;
__device__ __align__(128) unsigned int g_flags[F_TOTAL];
#define TR(j, i) do {} while (0)

__device__ __forceinline__ uint32_t smem_u32(const void* p) { return (uint32_t)__cvta_generic_to_shared(p); }
__device__ __forceinline__ uint32_t clk32() { uint32_t c; asm volatile("mov.u32 %0, %%clock;" : "=r"(c)); return c; }
__device__ __forceinline__ uint32_t mapa_u32(uint32_t addr, uint32_t rank) {
    uint32_t r; asm volatile("mapa.shared::cluster.u32 %0, %1, %2;" : "=r"(r) : "r"(addr), "r"(rank)); return r;
}
__device__ __forceinline__ void mbar_init(uint32_t bar, uint32_t cnt) {
    asm volatile("mbarrier.init.shared::cta.b64 [%0], %1;" :: "r"(bar), "r"(cnt) : "memory");
}
__device__ __forceinline__ void mbar_expect_tx(uint32_t bar, uint32_t bytes) {
    asm volatile("mbarrier.arrive.expect_tx.shared::cta.b64 _, [%0], %1;" :: "r"(bar), "r"(bytes) : "memory");
}
__device__ __forceinline__ void mbar_arrive(uint32_t bar) {
    asm volatile("mbarrier.arrive.shared::cta.b64 _, [%0];" :: "r"(bar) : "memory");
}
__device__ __forceinline__ bool mbar_try_wait(uint32_t bar, uint32_t parity) {
    uint32_t ok;
    asm volatile("{\n.reg .pred p;\nmbarrier.try_wait.parity.shared::cta.b64 p, [%1], %2;\nselp.u32 %0, 1, 0, p;\n}"
                 : "=r"(ok) : "r"(bar), "r"(parity) : "memory");
    return ok;
}
constexpr int SPIN_LIMIT = 1 << 18;
#define TIMEOUT(code, info) do {} while (0)
__device__ __forceinline__ void mbar_wait(uint32_t bar, uint32_t parity) {
    int g = 0;
#pragma unroll 1
    while (!mbar_try_wait(bar, parity)) { if (++g >= SPIN_LIMIT) { TIMEOUT(0, bar & 255); break; } }
}
__device__ __forceinline__ void bar_sync(int id, int n) { asm volatile("bar.sync %0, %1;" :: "r"(id), "r"(n) : "memory"); }
__device__ __forceinline__ void bar_arrive(int id, int n) { asm volatile("bar.arrive %0, %1;" :: "r"(id), "r"(n) : "memory"); }
__device__ __forceinline__ void st_async_v2(uint32_t addr, float a, float b, uint32_t bar) {
    asm volatile("st.async.weak.shared::cluster.mbarrier::complete_tx::bytes.v2.f32 [%0], {%1,%2}, [%3];"
                 :: "r"(addr), "f"(a), "f"(b), "r"(bar) : "memory");
}
__device__ __forceinline__ void st_async_v4(uint32_t addr, uint4 v, uint32_t bar) {
    asm volatile("st.async.weak.shared::cluster.mbarrier::complete_tx::bytes.v4.b32 [%0], {%1,%2,%3,%4}, [%5];"
                 :: "r"(addr), "r"(v.x), "r"(v.y), "r"(v.z), "r"(v.w), "r"(bar) : "memory");
}
__device__ __forceinline__ void stg_relaxed32(uint32_t* p, uint32_t v) {
    asm volatile("st.relaxed.gpu.global.b32 [%0], %1;" :: "l"(p), "r"(v) : "memory");
}
__device__ __forceinline__ uint32_t ldg_relaxed32(const uint32_t* p) {
    uint32_t v; asm volatile("ld.relaxed.gpu.global.b32 %0, [%1];" : "=r"(v) : "l"(p) : "memory"); return v;
}
__device__ __forceinline__ unsigned int ld_acquire(const unsigned int* p) {
    unsigned int v; asm volatile("ld.acquire.gpu.global.u32 %0, [%1];" : "=r"(v) : "l"(p) : "memory"); return v;
}
__device__ __forceinline__ void red_release(unsigned int* p, unsigned int v) {
    asm volatile("red.release.gpu.global.add.u32 [%0], %1;" :: "l"(p), "r"(v) : "memory");
}
__device__ __forceinline__ void wait_flag(int idx, unsigned int target) {
    const unsigned int* p = &g_flags[idx];
    int g = 0;
#pragma unroll 1
    while (ld_acquire(p) < target) { __nanosleep(FLAG_NS); if (++g >= 64 * SPIN_LIMIT) { TIMEOUT(2, idx); break; } }
}
__device__ __forceinline__ void cp_async16(uint32_t dst, const void* src) {
    asm volatile("cp.async.cg.shared.global [%0], [%1], 16;" :: "r"(dst), "l"(src) : "memory");
}
__device__ __forceinline__ void cp_async_commit() { asm volatile("cp.async.commit_group;" ::: "memory"); }
template <int N> __device__ __forceinline__ void cp_async_wait() { asm volatile("cp.async.wait_group %0;" :: "n"(N) : "memory"); }
__device__ __forceinline__ void ldsm4(uint32_t& r0, uint32_t& r1, uint32_t& r2, uint32_t& r3, uint32_t addr) {
    asm volatile("ldmatrix.sync.aligned.m8n8.x4.shared.b16 {%0,%1,%2,%3}, [%4];" : "=r"(r0), "=r"(r1), "=r"(r2), "=r"(r3) : "r"(addr) : "memory");
}
__device__ __forceinline__ void ldsm4t(uint32_t& r0, uint32_t& r1, uint32_t& r2, uint32_t& r3, uint32_t addr) {
    asm volatile("ldmatrix.sync.aligned.m8n8.x4.trans.shared.b16 {%0,%1,%2,%3}, [%4];" : "=r"(r0), "=r"(r1), "=r"(r2), "=r"(r3) : "r"(addr) : "memory");
}
__device__ __forceinline__ void ldsm2t(uint32_t& r0, uint32_t& r1, uint32_t addr) {
    asm volatile("ldmatrix.sync.aligned.m8n8.x2.trans.shared.b16 {%0,%1}, [%2];" : "=r"(r0), "=r"(r1) : "r"(addr) : "memory");
}
__device__ __forceinline__ void stsm4(uint32_t addr, uint32_t r0, uint32_t r1, uint32_t r2, uint32_t r3) {
    asm volatile("stmatrix.sync.aligned.m8n8.x4.shared.b16 [%0], {%1,%2,%3,%4};" :: "r"(addr), "r"(r0), "r"(r1), "r"(r2), "r"(r3) : "memory");
}
__device__ __forceinline__ void stsm4t(uint32_t addr, uint32_t r0, uint32_t r1, uint32_t r2, uint32_t r3) {
    asm volatile("stmatrix.sync.aligned.m8n8.x4.trans.shared.b16 [%0], {%1,%2,%3,%4};" :: "r"(addr), "r"(r0), "r"(r1), "r"(r2), "r"(r3) : "memory");
}
__device__ __forceinline__ void stsm2t(uint32_t addr, uint32_t r0, uint32_t r1) {
    asm volatile("stmatrix.sync.aligned.m8n8.x2.trans.shared.b16 [%0], {%1,%2};" :: "r"(addr), "r"(r0), "r"(r1) : "memory");
}
__device__ __forceinline__ void mma16816(float* d, uint32_t a0, uint32_t a1, uint32_t a2, uint32_t a3, uint32_t b0, uint32_t b1) {
    asm volatile("mma.sync.aligned.m16n8k16.row.col.f32.bf16.bf16.f32 {%0,%1,%2,%3}, {%4,%5,%6,%7}, {%8,%9}, {%0,%1,%2,%3};"
                 : "+f"(d[0]), "+f"(d[1]), "+f"(d[2]), "+f"(d[3]) : "r"(a0), "r"(a1), "r"(a2), "r"(a3), "r"(b0), "r"(b1));
}
__device__ __forceinline__ void mma1688(float* d, uint32_t a0, uint32_t a1, uint32_t b0) {
    asm volatile("mma.sync.aligned.m16n8k8.row.col.f32.bf16.bf16.f32 {%0,%1,%2,%3}, {%4,%5}, {%6}, {%0,%1,%2,%3};"
                 : "+f"(d[0]), "+f"(d[1]), "+f"(d[2]), "+f"(d[3]) : "r"(a0), "r"(a1), "r"(b0));
}
__device__ __forceinline__ void mma16816h(float* d, uint32_t a0, uint32_t a2, uint32_t b0, uint32_t b1) {
    asm volatile("{\n.reg .b32 ju, jv;\nmma.sync.aligned.m16n8k16.row.col.f32.bf16.bf16.f32 {%0,%1,%2,%3}, {%4,ju,%5,jv}, {%6,%7}, {%0,%1,%2,%3};\n}"
                 : "+f"(d[0]), "+f"(d[1]), "+f"(d[2]), "+f"(d[3]) : "r"(a0), "r"(a2), "r"(b0), "r"(b1));
}
__device__ __forceinline__ void mma1688h(float* d, uint32_t a0, uint32_t b0) {
    asm volatile("{\n.reg .b32 ju;\nmma.sync.aligned.m16n8k8.row.col.f32.bf16.bf16.f32 {%0,%1,%2,%3}, {%4,ju}, {%5}, {%0,%1,%2,%3};\n}"
                 : "+f"(d[0]), "+f"(d[1]), "+f"(d[2]), "+f"(d[3]) : "r"(a0), "r"(b0));
}
__device__ __forceinline__ uint32_t movm(uint32_t a) {
    uint32_t d; asm volatile("movmatrix.sync.aligned.m8n8.trans.b16 %0, %1;" : "=r"(d) : "r"(a)); return d;
}
__device__ __forceinline__ uint32_t pack2(float lo, float hi) {
    uint32_t r; asm("cvt.rn.bf16x2.f32 %0, %1, %2;" : "=r"(r) : "f"(hi), "f"(lo)); return r;
}
__device__ __forceinline__ float bflo(uint32_t w) { return __uint_as_float(w << 16); }
__device__ __forceinline__ float bfhi(uint32_t w) { return __uint_as_float(w & 0xffff0000u); }
__device__ __forceinline__ float rbf(float x) { return __bfloat162float(__float2bfloat16_rn(x)); }
__device__ __forceinline__ float ex2(float x) { float y; asm("ex2.approx.ftz.f32 %0, %1;" : "=f"(y) : "f"(x)); return y; }
__device__ __forceinline__ void sts128(uint32_t addr, uint4 v) {
    asm volatile("st.shared.v4.b32 [%0], {%1,%2,%3,%4};" :: "r"(addr), "r"(v.x), "r"(v.y), "r"(v.z), "r"(v.w) : "memory");
}
__device__ __forceinline__ uint4 lds128(uint32_t addr) {
    uint4 v; asm volatile("ld.shared.v4.b32 {%0,%1,%2,%3}, [%4];" : "=r"(v.x), "=r"(v.y), "=r"(v.z), "=r"(v.w) : "r"(addr) : "memory"); return v;
}
__device__ __forceinline__ float2 lds64f(uint32_t addr) {
    float2 v; asm volatile("ld.shared.v2.f32 {%0,%1}, [%2];" : "=f"(v.x), "=f"(v.y) : "r"(addr) : "memory"); return v;
}
__device__ __forceinline__ float lds32f(uint32_t addr) {
    float v; asm volatile("ld.shared.f32 %0, [%1];" : "=f"(v) : "r"(addr) : "memory"); return v;
}
__device__ __forceinline__ uint32_t lds32(uint32_t addr) {
    uint32_t v; asm volatile("ld.shared.b32 %0, [%1];" : "=r"(v) : "r"(addr) : "memory"); return v;
}
__device__ __forceinline__ void sts32(uint32_t addr, uint32_t v) { asm volatile("st.shared.b32 [%0], %1;" :: "r"(addr), "r"(v) : "memory"); }
__device__ __forceinline__ void sts64f(uint32_t addr, float a, float b) { asm volatile("st.shared.v2.f32 [%0], {%1,%2};" :: "r"(addr), "f"(a), "f"(b) : "memory"); }

__device__ __forceinline__ void tma_load2d(uint32_t dst, const CUtensorMap* tm, int c0, int c1, uint32_t bar) {
    asm volatile("cp.async.bulk.tensor.2d.shared::cluster.global.mbarrier::complete_tx::bytes [%0], [%1, {%3, %4}], [%2];"
                 :: "r"(dst), "l"(tm), "r"(bar), "r"(c0), "r"(c1) : "memory");
}
__device__ __forceinline__ void tma_store2d(const CUtensorMap* tm, uint32_t src, int c0, int c1) {
    asm volatile("cp.async.bulk.tensor.2d.global.shared::cta.bulk_group [%0, {%2, %3}], [%1];"
                 :: "l"(tm), "r"(src), "r"(c0), "r"(c1) : "memory");
}
__device__ __forceinline__ void bulk_commit() { asm volatile("cp.async.bulk.commit_group;" ::: "memory"); }
__device__ __forceinline__ void bulk_wait0() { asm volatile("cp.async.bulk.wait_group 0;" ::: "memory"); }
__device__ __forceinline__ void fence_async_smem() { asm volatile("fence.proxy.async.shared::cta;" ::: "memory"); }
__device__ __forceinline__ void fence_async_all() { asm volatile("fence.proxy.async;" ::: "memory"); }

__device__ __forceinline__ void wg_fence() { asm volatile("wgmma.fence.sync.aligned;" ::: "memory"); }
__device__ __forceinline__ void wg_commit() { asm volatile("wgmma.commit_group.sync.aligned;" ::: "memory"); }
__device__ __forceinline__ void wg_wait0() { asm volatile("wgmma.wait_group.sync.aligned 0;" ::: "memory"); }
__device__ __forceinline__ uint64_t mkdesc(uint32_t saddr, uint32_t lbo, uint32_t sbo) {
    return (uint64_t)((saddr & 0x3FFFF) >> 4) | ((uint64_t)(lbo >> 4) << 16) | ((uint64_t)(sbo >> 4) << 32) | (1ull << 62);
}
#define ACC8(i) "+f"(d[i]), "+f"(d[i + 1]), "+f"(d[i + 2]), "+f"(d[i + 3]), "+f"(d[i + 4]), "+f"(d[i + 5]), "+f"(d[i + 6]), "+f"(d[i + 7])
__device__ __forceinline__ void wgmma_n256(float* d, uint64_t da, uint64_t db, int scale_d) {
    asm volatile(
        "{\n.reg .pred p;\nsetp.ne.b32 p, %130, 0;\n"
        "wgmma.mma_async.sync.aligned.m64n256k16.f32.bf16.bf16 "
        "{%0,%1,%2,%3,%4,%5,%6,%7,%8,%9,%10,%11,%12,%13,%14,%15,%16,%17,%18,%19,%20,%21,%22,%23,%24,%25,%26,%27,%28,%29,%30,%31,"
        "%32,%33,%34,%35,%36,%37,%38,%39,%40,%41,%42,%43,%44,%45,%46,%47,%48,%49,%50,%51,%52,%53,%54,%55,%56,%57,%58,%59,%60,%61,%62,%63,"
        "%64,%65,%66,%67,%68,%69,%70,%71,%72,%73,%74,%75,%76,%77,%78,%79,%80,%81,%82,%83,%84,%85,%86,%87,%88,%89,%90,%91,%92,%93,%94,%95,"
        "%96,%97,%98,%99,%100,%101,%102,%103,%104,%105,%106,%107,%108,%109,%110,%111,%112,%113,%114,%115,%116,%117,%118,%119,%120,%121,%122,%123,%124,%125,%126,%127}, "
        "%128, %129, p, 1, 1, 0, 1;\n}"
        : ACC8(0), ACC8(8), ACC8(16), ACC8(24), ACC8(32), ACC8(40), ACC8(48), ACC8(56),
          ACC8(64), ACC8(72), ACC8(80), ACC8(88), ACC8(96), ACC8(104), ACC8(112), ACC8(120)
        : "l"(da), "l"(db), "r"(scale_d));
}
__device__ __forceinline__ void wgmma_n128(float* d, uint64_t da, uint64_t db, int scale_d) {
    asm volatile(
        "{\n.reg .pred p;\nsetp.ne.b32 p, %66, 0;\n"
        "wgmma.mma_async.sync.aligned.m64n128k16.f32.bf16.bf16 "
        "{%0,%1,%2,%3,%4,%5,%6,%7,%8,%9,%10,%11,%12,%13,%14,%15,%16,%17,%18,%19,%20,%21,%22,%23,%24,%25,%26,%27,%28,%29,%30,%31,"
        "%32,%33,%34,%35,%36,%37,%38,%39,%40,%41,%42,%43,%44,%45,%46,%47,%48,%49,%50,%51,%52,%53,%54,%55,%56,%57,%58,%59,%60,%61,%62,%63}, "
        "%64, %65, p, 1, 1, 0, 1;\n}"
        : ACC8(0), ACC8(8), ACC8(16), ACC8(24), ACC8(32), ACC8(40), ACC8(48), ACC8(56)
        : "l"(da), "l"(db), "r"(scale_d));
}

__device__ __forceinline__ void wgmma_n64(float* d, uint64_t da, uint64_t db) {
    asm volatile(
        "wgmma.mma_async.sync.aligned.m64n64k16.f32.bf16.bf16 "
        "{%0,%1,%2,%3,%4,%5,%6,%7,%8,%9,%10,%11,%12,%13,%14,%15,%16,%17,%18,%19,%20,%21,%22,%23,%24,%25,%26,%27,%28,%29,%30,%31}, "
        "%32, %33, 1, 1, 1, 0, 1;"
        : ACC8(0), ACC8(8), ACC8(16), ACC8(24)
        : "l"(da), "l"(db));
}
__device__ __forceinline__ uint32_t hadd2(uint32_t a, uint32_t b) { uint32_t r; asm("add.rn.bf16x2 %0, %1, %2;" : "=r"(r) : "r"(a), "r"(b)); return r; }
__device__ __forceinline__ uint32_t hsub2(uint32_t a, uint32_t b) { uint32_t r; asm("sub.rn.bf16x2 %0, %1, %2;" : "=r"(r) : "r"(a), "r"(b)); return r; }
__device__ __forceinline__ uint32_t hmul2(uint32_t a, uint32_t b) { uint32_t r; asm("mul.rn.bf16x2 %0, %1, %2;" : "=r"(r) : "r"(a), "r"(b)); return r; }
__device__ __forceinline__ void load_mod8(const bf16* m, int lane, uint32_t* v) {
    const uint4 a = __ldcg((const uint4*)m + lane), b = __ldcg((const uint4*)m + 32 + lane);
    v[0] = a.x; v[1] = a.y; v[2] = a.z; v[3] = a.w; v[4] = b.x; v[5] = b.y; v[6] = b.z; v[7] = b.w;
}
__device__ __forceinline__ void ln_stats(const uint32_t* x, uint32_t& mu2, float& rden) {
    float s = 0.f;
#pragma unroll
    for (int i = 0; i < 8; i++) s += bflo(x[i]) + bfhi(x[i]);
#pragma unroll
    for (int o = 16; o > 0; o >>= 1) s += __shfl_xor_sync(~0u, s, o);
    const float mean = s * (1.f / D_);
    float q = 0.f;
#pragma unroll
    for (int i = 0; i < 8; i++) { const float d0 = bflo(x[i]) - mean, d1 = bfhi(x[i]) - mean; q = fmaf(d0, d0, q); q = fmaf(d1, d1, q); }
#pragma unroll
    for (int o = 16; o > 0; o >>= 1) q += __shfl_xor_sync(~0u, q, o);
    mu2 = pack2(mean, mean);
    rden = __frcp_rn(rbf(__fsqrt_rn(rbf(rbf(q * (1.f / D_)) + 1e-5f))));
}
__device__ __forceinline__ void ln_apply(const uint32_t* x, uint32_t mu2, float rden, const uint32_t* c1, const uint32_t* sm, uint32_t* r) {
#pragma unroll
    for (int i = 0; i < 8; i++) {
        const uint32_t d = hsub2(x[i], mu2);
        r[i] = hadd2(hmul2(pack2(bflo(d) * rden, bfhi(d) * rden), c1[i]), sm[i]);
    }
}

struct __align__(64) Params {
    CUtensorMap tm_h, tm_kv, tm_kvm, tm_o, tm_op, tm_h2, tm_act, tm_x1, tm_out;
    CUtensorMap tm_wq, tm_wk, tm_wv, tm_wo, tm_wg, tm_wu, tm_wd;
    const bf16 *x, *c, *w_mod;
    int qmask;
};

constexpr uint32_t R_WV = 0, R_MEM = 65536  ,
                   R_KX = 69632  , R_VX = R_KX + 8192,
                   R_VMS = R_KX + 32768  , R_OS = R_VMS + 2048  , R_SX = R_OS + 2048  , R_BAR = R_SX + 1536,
                   R_RS = R_BAR + 512  , R_VB = R_RS + 4096  , R_VP = R_VB + 2048  ,
                   R_STG = R_VP + 4096  ,
                   R_TQ = R_STG  , R_TV = R_STG + 53248  , R_QF = R_STG + 77824  ,
                   R_SMEM = R_STG + 98304;
static_assert((R_STG & 1023) == 0 && (R_RS & 511) == 0 && R_QF + 16384 <= R_SMEM, "smem");
constexpr uint32_t RB_Q = R_BAR, RB_V = R_BAR + 8, RB_E = R_BAR + 16, RB_A = R_BAR + 24, RB_ROLE = R_BAR + 32, RB_KV = R_BAR + 40  ;
constexpr int W_NST = 4;
constexpr uint32_t W_STAGE = 49152, W_STG = W_NST * W_STAGE  , W_END = W_STG + 32768;
constexpr uint32_t SM_BAR = W_END;
constexpr uint32_t SMEM_BYTES = W_END + 1024 + 2048;
constexpr uint32_t B_FULL = 0, B_EMPTY = 32, B_STGFREE = 64, B_REQ = 80, B_RSP = 88, B_NEXT = 96, B_RING = 128;
#define PICK_AHEAD 3

constexpr int NB_S = 11, NB_Y = 1, NB_M = 5, NB_K = 5, NB_B = 2, NB_C = 3, NB_D = 4, NB_W0 = 6  , NB_ST = 9  ;

__device__ __forceinline__ int pos_of_d(int d) {
    const int rem = d & 31;
    return (d & ~31) + ((rem & 7) >> 1) * 8 + (rem & 1) * 4 + (rem >> 3);
}

#define PROF(i) do {} while (0)
#define PROFG(i) do {} while (0)
#define VK0_ 4
constexpr int VK0 = VK0_;
constexpr int NOFF = 8;
#define OFFKS(i) ((i) >> 1)
#define POLL_GAP 110

struct __align__(64) RecParams { CUtensorMap tm_kv32; const bf16 *mem0, *wq, *wk, *wv, *wo, *x, *c, *w_mod; int ncl, only_pre; };

__device__ __forceinline__ void rec_qk(const RecParams& p, const uint32_t sb, const int cta, const int warp, int lane, const int sel) {
    const int crank = cta & 15, cl = cta >> 4, rank = cta & 1;
    const int wg = warp >> 2, aa = warp & 3;
    uint32_t wa[2][16][4];
    {
        const uint32_t stg = sb + R_STG + wg * 32768;
        const int t128 = aa * 32 + lane;
        const int row = (lane >> 4) * 8 + (lane & 7);
        const int ch = t128 & 7;
        const size_t goff = (size_t)rank * 256 * HD_ + (cta >> 1) * DH_ + ch * 8;
        const bf16* W = (wg == 0 ? p.wq : p.wk) + goff;
#pragma unroll 4
        for (int dd = 0; dd < 16; dd++) {
            const int d = dd * 16 + (t128 >> 3), pp = pos_of_d(d);
            cp_async16(sb + R_WV + wg * 32768 + pp * 128 + ((ch ^ (pp & 7)) << 4), p.wv + goff + wg * 64 + (size_t)d * HD_);
        }
        cp_async_commit();
#pragma unroll 4
        for (int dd = 0; dd < 16; dd++) {
            const int d = dd * 16 + (t128 >> 3), pp = pos_of_d(d);
            cp_async16(stg + pp * 128 + ((ch ^ (pp & 7)) << 4), W + (size_t)d * HD_);
        }
        cp_async_commit();
        {
            const int tok = warp, d0 = lane * 8;
            const uint4 m0 = __ldg((const uint4*)(p.mem0 + tok * D_ + rank * 256 + d0));
            const uint32_t mw[4] = {m0.x, m0.y, m0.z, m0.w};
#pragma unroll
            for (int e = 0; e < 8; e++) {
                const int pp = pos_of_d(d0 + e);
                const unsigned short v = (unsigned short)(mw[e >> 1] >> ((e & 1) * 16));
                asm volatile("st.shared.u16 [%0], %1;" :: "r"(sb + R_MEM + (pp >> 3) * 128 + tok * 16 + (pp & 7) * 2), "h"(v) : "memory");
            }
        }
        cp_async_wait<1>();
        bar_sync(NB_W0 + wg, 128);
        const uint32_t fv = row * 128 + (((2 * aa + ((lane >> 3) & 1)) ^ (row & 7)) << 4);
#pragma unroll
        for (int ks = 0; ks < 16; ks++) ldsm4t(wa[0][ks][0], wa[0][ks][1], wa[0][ks][2], wa[0][ks][3], sb + R_WV + wg * 32768 + fv + ks * 2048);
        bar_sync(NB_W0 + wg, 128);
#pragma unroll
        for (int ks = 0; ks < 16; ks++)
            sts128(sb + R_WV + (warp * 16 + ks) * 512 + lane * 16, make_uint4(wa[0][ks][0], wa[0][ks][1], wa[0][ks][2], wa[0][ks][3]));
        const uint32_t fo = stg + row * 128 + (((4 * (aa & 1) + ((lane >> 3) & 1)) ^ (row & 7)) << 4);
#pragma unroll 1
        for (int m = 0; m < 2; m++) {
            cp_async_wait<0>();
            bar_sync(NB_W0 + wg, 128);
            if ((aa >> 1) == m) {
#pragma unroll
                for (int ks = 0; ks < 16; ks++) {
                    ldsm4t(wa[0][ks][0], wa[0][ks][1], wa[0][ks][2], wa[0][ks][3], fo + ks * 2048);
                    ldsm4t(wa[1][ks][0], wa[1][ks][1], wa[1][ks][2], wa[1][ks][3], (fo ^ 32) + ks * 2048);
                }
            }
            bar_sync(NB_W0 + wg, 128);
            if (m == 0) {
#pragma unroll 4
                for (int dd = 0; dd < 16; dd++) {
                    const int d = dd * 16 + (t128 >> 3), pp = pos_of_d(d);
                    cp_async16(stg + pp * 128 + ((ch ^ (pp & 7)) << 4), W + 64 + (size_t)d * HD_);
                }
                cp_async_commit();
            }
        }
    }
    bar_sync(NB_D, 384);
    const uint32_t tab = sb + R_TQ + wg * 26624 + (aa * 32 + lane) * 16;
    {
        const uint32_t l7 = lane & 7, l8 = lane >> 3, g = lane >> 2, t = lane & 3;
        const uint32_t bq = warp >> 1, tp = warp & 1;
        uint4 v;
        v.x = sb + R_QF + (rank * 8 + warp) * 512 + lane * 16;
        v.y = sb + R_QF + (warp == 5 ? 1024 : 0) + lane * 16;
        v.z = sb + R_KX + ((warp - 1) * 8 + l7) * 128 + ((l8 ^ l7) << 4);
        v.w = sb + R_SX + warp * 256 + lane * 8;
        sts128(tab, v);
        sts128(tab + 2048, make_uint4(sb + lane * 16 + R_MEM, sb + lane * 16 + R_WV + warp * 8192, sb + lane * 16 + R_VP + warp * 512, v.x));
        const uint32_t L = bq * 8 + 2 * tp + (l8 & 1) + 4 * (l8 >> 1);
        const uint32_t d0 = (((crank + ((t >> 1) | (g & 6))) & 7) << 1) | (crank >> 3);
        v.x = sb + R_RS + l7 * 512 + ((L ^ l7) << 4);
        v.y = mapa_u32(sb + R_MEM + ((crank & 7) * 4 + bq) * 128 + (4 * tp + 2 * (t & 1) + (g & 1)) * 16, d0);
        v.z = mapa_u32(sb + RB_A, d0);
        v.w = lane;
        sts128(tab + 4096, v);
        const uint64_t wr = (uint64_t)(g_F + ((crank * 2 + ((crank ^ (crank >> 3) ^ sel) & 1)) * 1024 + warp * 128 + cl * 32 + lane));
        sts128(tab + 6144, make_uint4((uint32_t)wr, (uint32_t)(wr >> 32), (uint32_t)((((cl + 1) & 3) - cl) * 128), (uint32_t)((((cl + 2) & 3) - cl) * 128)));
        sts32(tab + 8192, (uint32_t)((((cl + 3) & 3) - cl) * 128));
#pragma unroll
        for (int i = 0; i < NOFF; i++)
            sts128(tab + 10240 + i * 2048, make_uint4(wa[i & 1][OFFKS(i)][0], wa[i & 1][OFFKS(i)][1], wa[i & 1][OFFKS(i)][2], wa[i & 1][OFFKS(i)][3]));
    }
    bar_sync(NB_D, 384);
    uint4 tb = lds128(tab + 2048);
#pragma unroll 1
    for (int s = 0; s < NSEG; s++) {
        if (s > 0) mbar_wait(sb + RB_A, (s - 1) & 1);
        if (warp == 0) PROF(0);
        uint4 ta;
        const uint32_t par = (s & 1) * 8192;
        {
            float acc[5][4];
#pragma unroll
            for (int c = 0; c < 5; c++) { acc[c][0] = acc[c][1] = acc[c][2] = acc[c][3] = 0.f; }
            uint32_t b[8][4];
            uint4 av[16];
            static_assert(VK0 == 4, "order below assumes the V/O warps cover slices 0,1");
#define QK4(k2) do { \
                mma16816(acc[0], wa[0][2 * (k2)][0], wa[0][2 * (k2)][1], wa[0][2 * (k2)][2], wa[0][2 * (k2)][3], b[k2][0], b[k2][1]); \
                mma16816(acc[1], wa[1][2 * (k2)][0], wa[1][2 * (k2)][1], wa[1][2 * (k2)][2], wa[1][2 * (k2)][3], b[k2][0], b[k2][1]); \
                mma16816(acc[3], wa[0][2 * (k2) + 1][0], wa[0][2 * (k2) + 1][1], wa[0][2 * (k2) + 1][2], wa[0][2 * (k2) + 1][3], b[k2][2], b[k2][3]); \
                mma16816(acc[4], wa[1][2 * (k2) + 1][0], wa[1][2 * (k2) + 1][1], wa[1][2 * (k2) + 1][2], wa[1][2 * (k2) + 1][3], b[k2][2], b[k2][3]); } while (0)
#define V2(k2) do { \
                mma16816(acc[2], av[2 * (k2)].x, av[2 * (k2)].y, av[2 * (k2)].z, av[2 * (k2)].w, b[k2][0], b[k2][1]); \
                mma16816(acv, av[2 * (k2) + 1].x, av[2 * (k2) + 1].y, av[2 * (k2) + 1].z, av[2 * (k2) + 1].w, b[k2][2], b[k2][3]); } while (0)
#define LB(k2) ldsm4(b[k2][0], b[k2][1], b[k2][2], b[k2][3], tb.x + (k2) * 512)
#define LV(k2) do { av[2 * (k2)] = lds128(tb.y + 2 * (k2) * 512); av[2 * (k2) + 1] = lds128(tb.y + (2 * (k2) + 1) * 512); } while (0)
            float acv[4] = {0.f, 0.f, 0.f, 0.f};
            LB(0); LB(1); LB(2); LB(3);
            QK4(0); LB(4); QK4(1); LB(5); LV(2); LV(3); QK4(2); LB(6); QK4(3); LB(7);
            V2(2); V2(3); LV(4); LV(5);
            QK4(4); QK4(5); QK4(6); QK4(7);
            const uint4 f = make_uint4(movm(pack2(acc[0][0] + acc[3][0], acc[0][1] + acc[3][1])), movm(pack2(acc[0][2] + acc[3][2], acc[0][3] + acc[3][3])),
                                       movm(pack2(acc[1][0] + acc[4][0], acc[1][1] + acc[4][1])), movm(pack2(acc[1][2] + acc[4][2], acc[1][3] + acc[4][3])));
            st_async_v4((tb.w + par) ^ (1u << 24), f, (sb + RB_Q) ^ (1u << 24));
            sts128(tb.w + par, f);
            __syncwarp();
            if ((tb.w & 511) == 0) mbar_arrive(sb + RB_Q);
            if (warp == 0) PROF(1);
            if (tb.x == 0) break;
            LV(6); LV(7);
            ta = lds128(tab);
            V2(4); V2(5); V2(6); V2(7);
            sts128(tb.z, make_uint4(__float_as_uint(acc[2][0] + acv[0]), __float_as_uint(acc[2][1] + acv[1]), __float_as_uint(acc[2][2] + acv[2]), __float_as_uint(acc[2][3] + acv[3])));
            bar_arrive(NB_Y, 384);
        }
        if (warp == 0) PROF(14);
        if (warp < 6 && s != NSEG - 1) {
            float sa[4] = {0.f, 0.f, 0.f, 0.f}, sc[4] = {0.f, 0.f, 0.f, 0.f};
            const uint32_t qa = ta.y + par;
            if (warp == 0 || warp == 5) {
                mbar_wait(sb + RB_Q, s & 1);
                const uint4 q0 = lds128(qa), q1 = lds128(qa + 4096), k0 = lds128(qa + 2048), k1 = lds128(qa + 6144);
                const uint4 q2 = lds128(qa + 512), q3 = lds128(qa + 4608), k2 = lds128(qa + 2560), k3 = lds128(qa + 6656);
                mma16816h(sa, hadd2(q0.x, q1.x), hadd2(q0.y, q1.y), hadd2(k0.x, k1.x), hadd2(k0.y, k1.y));
                mma16816h(sc, hadd2(q0.z, q1.z), hadd2(q0.w, q1.w), hadd2(k0.z, k1.z), hadd2(k0.w, k1.w));
                mma16816h(sa, hadd2(q2.x, q3.x), hadd2(q2.y, q3.y), hadd2(k2.x, k3.x), hadd2(k2.y, k3.y));
                mma16816h(sc, hadd2(q2.z, q3.z), hadd2(q2.w, q3.w), hadd2(k2.z, k3.z), hadd2(k2.w, k3.w));
            } else {
                uint32_t k[16];
                const uint32_t kb = ta.z + 2 * par;
                mbar_wait(sb + RB_KV + (s & 1) * 8, (s >> 1) & 1);
                ldsm4(k[0], k[1], k[2], k[3], kb);
                ldsm4(k[4], k[5], k[6], k[7], kb ^ 64);
                ldsm4(k[8], k[9], k[10], k[11], kb + 4096);
                ldsm4(k[12], k[13], k[14], k[15], (kb ^ 64) + 4096);
                mbar_wait(sb + RB_Q, s & 1);
                uint4 q0[4], q1[4];
#pragma unroll
                for (int i = 0; i < 4; i++) { q0[i] = lds128(qa + i * 512); q1[i] = lds128(qa + 4096 + i * 512); }
                float sd[4] = {0.f, 0.f, 0.f, 0.f}, se[4] = {0.f, 0.f, 0.f, 0.f};
                mma16816h(sa, hadd2(q0[0].x, q1[0].x), hadd2(q0[0].y, q1[0].y), k[0], k[1]);
                mma16816h(sc, hadd2(q0[0].z, q1[0].z), hadd2(q0[0].w, q1[0].w), k[2], k[3]);
                mma16816h(sd, hadd2(q0[1].x, q1[1].x), hadd2(q0[1].y, q1[1].y), k[4], k[5]);
                mma16816h(se, hadd2(q0[1].z, q1[1].z), hadd2(q0[1].w, q1[1].w), k[6], k[7]);
                mma16816h(sa, hadd2(q0[2].x, q1[2].x), hadd2(q0[2].y, q1[2].y), k[8], k[9]);
                mma16816h(sc, hadd2(q0[2].z, q1[2].z), hadd2(q0[2].w, q1[2].w), k[10], k[11]);
                mma16816h(sd, hadd2(q0[3].x, q1[3].x), hadd2(q0[3].y, q1[3].y), k[12], k[13]);
                mma16816h(se, hadd2(q0[3].z, q1[3].z), hadd2(q0[3].w, q1[3].w), k[14], k[15]);
                sa[0] += sd[0]; sa[1] += sd[1]; sc[0] += se[0]; sc[1] += se[1];
            }
            const float scl = 0.08838834764831845f * 1.4426950408889634f;
            sts64f(ta.w, (sa[0] + sc[0]) * scl, (sa[1] + sc[1]) * scl);
            bar_arrive(NB_S, 320);
            if (warp == 0) PROF(2);
        } else if (warp == 7) {
            mbar_wait(sb + RB_Q, s & 1);
            if (lane == 0) {
                mbar_expect_tx(sb + RB_Q, 4096);
                if (s > 0) mbar_expect_tx(sb + RB_A, 4096);
            }
            __syncwarp();
        } else if (s > 0 && (s & 3) == 0 && warp == 6) {
            bar_sync(NB_K, 160);
            if (lane == 0) red_release(&g_flags[F_MEM + (s >> 2) - 1], 1);
            __syncwarp();
        }
        if (s == NSEG - 1) {
            const uint4 td = lds128(tab + 6144);
            stg_relaxed32((uint32_t*)(((uint64_t)td.y << 32) | (td.x ^ 0x21000)), 0u);
            break;
        }
        const uint4 tc = lds128(tab + 4096), td = lds128(tab + 6144);
        const uint32_t te = lds32(tab + 8192);
        uint32_t* wr = (uint32_t*)(((uint64_t)td.y << 32) | (td.x ^ ((s & 1) * 0x21000)));
        const uint32_t* r1p = (const uint32_t*)((const char*)wr + (int)td.z);
        const uint32_t* r2p = (const uint32_t*)((const char*)wr + (int)td.w);
        const uint32_t* r3p = (const uint32_t*)((const char*)wr + (int)te);
        const uint32_t tag = ((s >> 1) + 1) & 1;
        mbar_wait(sb + RB_E, s & 1);
        if (warp == 0) PROF(7);
        {
            uint32_t a0, a1, a2, a3;
            ldsm4t(a0, a1, a2, a3, tc.x);
            const uint32_t one = 0x3F803F80u;
            float d0_[4] = {0.f, 0.f, 0.f, 0.f}, d1_[4] = {0.f, 0.f, 0.f, 0.f};
            mma1688(d0_, a0, a1, one);
            mma1688(d1_, a2, a3, one);
            const bool t1 = tc.w & 1, t2 = tc.w & 2;
            const float x = t2 ? (t1 ? d1_[2] : d1_[0]) : (t1 ? d0_[2] : d0_[0]);
            const uint32_t own = (__float_as_uint(x) & ~1u) | tag;
            stg_relaxed32(wr, own);
            const uint32_t tq = clk32();
            if (warp == 0) PROF(8);
            while ((int)(clk32() - tq) < POLL_GAP) {}
            uint32_t f1 = ldg_relaxed32(r1p), f2 = ldg_relaxed32(r2p), f3 = ldg_relaxed32(r3p);
#pragma unroll
            for (int i = 0; i < NOFF; i++) {
                const uint4 f0 = lds128(tab + 10240 + i * 2048);
                wa[i & 1][OFFKS(i)][0] = f0.x; wa[i & 1][OFFKS(i)][1] = f0.y; wa[i & 1][OFFKS(i)][2] = f0.z; wa[i & 1][OFFKS(i)][3] = f0.w;
            }
            tb = lds128(tab + 2048);
            int gg = 0;
#pragma unroll 1
            while (!__all_sync(~0u, (((f1 ^ tag) | (f2 ^ tag) | (f3 ^ tag)) & 1) == 0)) {
                f1 = ldg_relaxed32(r1p); f2 = ldg_relaxed32(r2p); f3 = ldg_relaxed32(r3p);
                if (++gg > 16 * SPIN_LIMIT) { TIMEOUT(3, s); break; }
            }
            if (warp == 0) PROF(9);
            const float v = (__uint_as_float(own) + __uint_as_float(f2)) + (__uint_as_float(f1) + __uint_as_float(f3));
            const bool b8 = tc.w & 8, b16 = tc.w & 16;
            const float recv = __shfl_xor_sync(~0u, v, 8);
            const uint32_t word = b8 ? pack2(recv, v) : pack2(v, recv);
            const uint32_t oth = __shfl_xor_sync(~0u, word, 16);
            const uint32_t wl = b16 ? oth : word, wh = b16 ? word : oth;
            const uint32_t p0 = __shfl_xor_sync(~0u, wl, 2), p1 = __shfl_xor_sync(~0u, wh, 2);
            const uint4 item = t2 ? make_uint4(p0, p1, wl, wh) : make_uint4(wl, wh, p0, p1);
            st_async_v4(tc.y, item, tc.z);
            if (tc.w == 0 && warp == 7) mbar_expect_tx(sb + RB_E, 4096);
            if (warp == 0) PROF(10);
        }
    }
}

__device__ __forceinline__ void rec_load_kv(const RecParams& p, uint32_t sb, int head, int s) {
    const uint32_t bar = sb + RB_KV + (s & 1) * 8, d = sb + R_KX + (s & 1) * 16384;
    mbar_expect_tx(bar, 16384);
    tma_load2d(d, &p.tm_kv32, head * DH_, s * 32, bar);
    tma_load2d(d + 4096, &p.tm_kv32, head * DH_ + 64, s * 32, bar);
    tma_load2d(d + 8192, &p.tm_kv32, HD_ + head * DH_, s * 32, bar);
    tma_load2d(d + 12288, &p.tm_kv32, HD_ + head * DH_ + 64, s * 32, bar);
}
__device__ __forceinline__ void rec_store_kvm(uint32_t src, char* dst, int s, int w) {
    dst += (size_t)s * (8 * 2 * HD_ * 2);
    if (w < 2) {
        const uint4 a = lds128(src + (s & 1) * 8192), b = lds128(src + (s & 1) * 8192 + 4096);
        *(uint32_t*)dst = hadd2(a.x, b.x); *(uint32_t*)(dst + 16) = hadd2(a.y, b.y);
        *(uint32_t*)(dst + 32) = hadd2(a.z, b.z); *(uint32_t*)(dst + 48) = hadd2(a.w, b.w);
    } else {
        *(uint4*)dst = lds128(src + (s & 1) * 1024);
    }
}

__device__ __forceinline__ void rec_vo(const RecParams& p, const uint32_t sb, const int cta, const int warp, int lane) {
    const int w = warp - 8, crank = cta & 15, rank = cta & 1;
    uint32_t wo[4][8][4];
    const uint32_t tab = sb + R_TV + (w * 32 + lane) * 16;
    {
        const int t128 = w * 32 + lane;
        const bf16* Wo = p.wo + (size_t)(cta >> 1) * DH_ * D_ + rank * 256;
        const uint32_t stg = sb + R_STG + 2 * 32768;
#pragma unroll
        for (int half = 0; half < 2; half++) {
#pragma unroll 4
            for (int i = t128; i < 2048; i += 128) {
                const int e = i >> 5, ch = i & 31;
                cp_async16(stg + e * 512 + ((ch ^ (e & 7)) << 4), Wo + (size_t)(half * 64 + e) * D_ + ch * 8);
            }
            cp_async_commit();
            cp_async_wait<0>();
            bar_sync(NB_W0 + 2, 128);
#pragma unroll
            for (int j = 0; j < 4; j++)
#pragma unroll
                for (int kk = 0; kk < 4; kk++) {
                    const int e = kk * 16 + (lane >> 4) * 8 + (lane & 7);
                    const int ch = (w * 4 + j) * 2 + ((lane >> 3) & 1);
                    ldsm4t(wo[j][half * 4 + kk][0], wo[j][half * 4 + kk][1], wo[j][half * 4 + kk][2], wo[j][half * 4 + kk][3],
                           stg + e * 512 + ((ch ^ (e & 7)) << 4));
                }
            bar_sync(NB_W0 + 2, 128);
        }
        bar_sync(NB_D, 384);
        const uint32_t l7 = lane & 7, l8 = lane >> 3, g = lane >> 2;
        uint4 v;
        v.x = sb + R_VX + (w >> 1) * 4096 + ((l8 & 1) * 8 + l7) * 128 + (((4 * (w & 1) + (l8 >> 1)) ^ l7) << 4);
        v.y = sb + R_OS + (w >> 1) * 1024 + g * 128 + (((4 * (w & 1)) ^ g) << 4) + (lane & 3) * 4;
        v.z = sb + R_VMS + l7 * 128 + (((4 * (w & 1) + l8) ^ l7) << 4);
        v.w = sb + R_OS + l7 * 128 + ((l8 ^ l7) << 4);
        sts128(tab, v);
        v.x = mapa_u32(sb + R_RS + (crank >> 1) * 512 + ((lane ^ (crank >> 1)) << 4), rank * 8 + w * 2);
        v.y = mapa_u32(sb + RB_E, rank * 8 + w * 2);
        v.z = sb + R_VB + w * 512 + lane * 16;
        v.w = sb + R_SX + lane * 8;
        sts128(tab + 2048, v);
#pragma unroll
        for (int i = 0; i < 8; i++)
            sts128(tab + 4096 + i * 2048, make_uint4(wo[i >> 1][(i & 1) * 4][0], wo[i >> 1][(i & 1) * 4][1], wo[i >> 1][(i & 1) * 4][2], wo[i >> 1][(i & 1) * 4][3]));
        const int tok = (w & 1) * 4 + (lane >> 3);
        const uint64_t kd = w < 2 ? (uint64_t)(g_kvm + (g * (2 * HD_) + cta * 64 + w * 32 + (lane & 3) * 2))
                                  : (uint64_t)(g_kvm + (tok * (2 * HD_) + HD_ + cta * 64 + (lane & 7) * 8));
        const uint32_t ksrc = w < 2 ? sb + R_QF + (4 + 2 * rank + w) * 512 + lane * 16 : sb + R_VMS + tok * 128 + (((lane & 7) ^ tok) << 4);
        sts128(tab + 20480, make_uint4((uint32_t)kd, (uint32_t)(kd >> 32), ksrc, sb + lane * 16));
        if (t128 == 0) { wait_flag(F_KV + 0, 64); rec_load_kv(p, sb, cta >> 1, 0); mbar_wait(sb + RB_KV, 0); }
        __syncwarp();
    }
    bar_sync(NB_D, 384);
    const uint32_t lane16 = lds32(tab + 20480 + 12);
    uint4 av[8];
#pragma unroll
    for (int i = 0; i < 8; i++) av[i] = lds128(lane16 + R_WV + ((2 * w + (i >> 2)) * 16 + (i & 3)) * 512);
#pragma unroll 1
    for (int s = 0; s < NSEG; s++) {
        {
            if (s > 0) mbar_wait(sb + RB_A, (s - 1) & 1);
            if (s > 0) {
                const uint4 tp = lds128(tab + 20480);
                rec_store_kvm(tp.z, (char*)(((uint64_t)tp.y << 32) | tp.x), s - 1, w);
                if ((s & 3) == 0) bar_arrive(NB_K, 160);
            }
            if (s + 1 < NSEG - 1 && w == 3 && lane16 == sb) {
                if (((s + 1) & 3) == 0) wait_flag(F_KV + ((s + 1) >> 2), 64);
                rec_load_kv(p, sb, cta >> 1, s + 1);
            }
            __syncwarp();
        }
        uint4 vb;
        const uint4 ta = lds128(tab), tb = lds128(tab + 2048);
        {
            uint32_t bb[8];
            ldsm4(bb[0], bb[1], bb[2], bb[3], lane16 + R_MEM);
            ldsm4(bb[4], bb[5], bb[6], bb[7], lane16 + R_MEM + 512);
            float vd[4] = {0.f, 0.f, 0.f, 0.f}, ve[4] = {0.f, 0.f, 0.f, 0.f};
#pragma unroll
            for (int i = 0; i < 4; i++) {
                mma16816(vd, av[i].x, av[i].y, av[i].z, av[i].w, bb[2 * i], bb[2 * i + 1]);
                mma16816(ve, av[4 + i].x, av[4 + i].y, av[4 + i].z, av[4 + i].w, bb[2 * i], bb[2 * i + 1]);
            }
            bar_sync(NB_Y, 384);
            const uint4 a = lds128(lane16 + R_VP + w * 1024), b = lds128(lane16 + R_VP + w * 1024 + 512);
            vb = make_uint4(pack2(__uint_as_float(a.x) + vd[0], __uint_as_float(a.y) + vd[1]), pack2(__uint_as_float(a.z) + vd[2], __uint_as_float(a.w) + vd[3]),
                            pack2(__uint_as_float(b.x) + ve[0], __uint_as_float(b.y) + ve[1]), pack2(__uint_as_float(b.z) + ve[2], __uint_as_float(b.w) + ve[3]));
            st_async_v4(tb.z ^ (1u << 24), vb, (sb + RB_V) ^ (1u << 24));
        }
        if (w == 0) PROF(11);
        if (s != NSEG - 1) {
            uint32_t vx[16];
            const uint32_t vxa = ta.x + (s & 1) * 16384;
            mbar_wait(sb + RB_KV + (s & 1) * 8, (s >> 1) & 1);
            ldsm4t(vx[0], vx[1], vx[2], vx[3], vxa);
            ldsm4t(vx[4], vx[5], vx[6], vx[7], vxa ^ 32);
            ldsm4t(vx[8], vx[9], vx[10], vx[11], vxa + 2048);
            ldsm4t(vx[12], vx[13], vx[14], vx[15], (vxa ^ 32) + 2048);
#pragma unroll
            for (int i = 0; i < 4; i++) {
                const uint4 f0 = lds128(tab + 4096 + i * 2048);
                wo[i >> 1][(i & 1) * 4][0] = f0.x; wo[i >> 1][(i & 1) * 4][1] = f0.y; wo[i >> 1][(i & 1) * 4][2] = f0.z; wo[i >> 1][(i & 1) * 4][3] = f0.w;
            }
            bar_sync(NB_S, 320);
            if (w == 0) PROF(4);
            float sv[10];
#pragma unroll
            for (int n = 0; n < 5; n++) { const float2 a = lds64f(tb.w + n * 256); sv[2 * n] = a.x; sv[2 * n + 1] = a.y; }
            { const float2 a = lds64f(tb.w + 5 * 256); sv[0] += a.x; sv[1] += a.y; }
            float mx = fmaxf(fmaxf(fmaxf(sv[2], sv[3]), fmaxf(sv[4], sv[5])), fmaxf(fmaxf(sv[6], sv[7]), fmaxf(sv[8], sv[9])));
            mx = fmaxf(mx, fmaxf(sv[0], sv[1]));
            mx = fmaxf(mx, __shfl_xor_sync(~0u, mx, 1));
            mx = fmaxf(mx, __shfl_xor_sync(~0u, mx, 2));
            mbar_wait(sb + RB_V, s & 1);
            const uint4 vo = lds128(tb.z);
            uint32_t pf[5];
#pragma unroll
            for (int n = 0; n < 5; n++) pf[n] = pack2(ex2(sv[2 * n] - mx), ex2(sv[2 * n + 1] - mx));
            vb = make_uint4(hadd2(vb.x, vo.x), hadd2(vb.y, vo.y), hadd2(vb.z, vo.z), hadd2(vb.w, vo.w));
            if (w == 0) PROF(12);
            float oa[4][4] = {{0.f, 0.f, 0.f, 0.f}, {0.f, 0.f, 0.f, 0.f}, {0.f, 0.f, 0.f, 0.f}, {0.f, 0.f, 0.f, 0.f}}, sm[4] = {0.f, 0.f, 0.f, 0.f};
            const uint32_t one = 0x3F803F80u;
            mma1688h(sm, pf[0], one);
            mma1688h(oa[0], pf[0], vb.x);
            mma1688h(oa[1], pf[0], vb.y);
            mma1688h(oa[2], pf[0], vb.z);
            mma1688h(oa[3], pf[0], vb.w);
            mma16816h(sm, pf[1], pf[2], one, one);
#pragma unroll
            for (int n = 0; n < 4; n++) mma16816h(oa[n], pf[1], pf[2], vx[2 * n], vx[2 * n + 1]);
            mma16816h(sm, pf[3], pf[4], one, one);
#pragma unroll
            for (int n = 0; n < 4; n++) mma16816h(oa[n], pf[3], pf[4], vx[8 + 2 * n], vx[8 + 2 * n + 1]);
            float inv;
            asm("rcp.approx.ftz.f32 %0, %1;" : "=f"(inv) : "f"(sm[0]));
#pragma unroll
            for (int n = 0; n < 4; n++) sts32(ta.y ^ (n << 4), pack2(oa[n][0] * inv, oa[n][1] * inv));
            bar_sync(NB_C, 128);
            if (w == 0) PROF(5);
            uint32_t ob[16];
            ldsm4(ob[0], ob[1], ob[2], ob[3], ta.w);
            ldsm4(ob[8], ob[9], ob[10], ob[11], ta.w + 1024);
            ldsm4(ob[4], ob[5], ob[6], ob[7], ta.w ^ 64);
            ldsm4(ob[12], ob[13], ob[14], ob[15], (ta.w ^ 64) + 1024);
#pragma unroll
            for (int i = 4; i < 8; i++) {
                const uint4 f0 = lds128(tab + 4096 + i * 2048);
                wo[i >> 1][(i & 1) * 4][0] = f0.x; wo[i >> 1][(i & 1) * 4][1] = f0.y; wo[i >> 1][(i & 1) * 4][2] = f0.z; wo[i >> 1][(i & 1) * 4][3] = f0.w;
            }
#pragma unroll
            for (int jj = 0; jj < 2; jj++) {
                if (jj == 1 && tb.w == 0) break;
                float acc[4][4];
#pragma unroll
                for (int c = 0; c < 4; c++) { acc[c][0] = acc[c][1] = acc[c][2] = acc[c][3] = 0.f; }
#pragma unroll
                for (int k4 = 0; k4 < 4; k4++)
#pragma unroll
                    for (int c = 0; c < 4; c++) {
                        const int tl = jj * 2 + (c >> 1), ks = (c & 1) * 4 + k4;
                        mma16816(acc[c], wo[tl][ks][0], wo[tl][ks][1], wo[tl][ks][2], wo[tl][ks][3], ob[2 * ks], ob[2 * ks + 1]);
                    }
                uint4 v;
                v.x = pack2(acc[0][0] + acc[1][0], acc[0][1] + acc[1][1]);
                v.y = pack2(acc[0][2] + acc[1][2], acc[0][3] + acc[1][3]);
                v.z = pack2(acc[2][0] + acc[3][0], acc[2][1] + acc[3][1]);
                v.w = pack2(acc[2][2] + acc[3][2], acc[2][3] + acc[3][3]);
                st_async_v4(tb.x + (jj << 24), v, tb.y + (jj << 24));
            }
            if (w == 0) PROF(6);
        } else {
            mbar_wait(sb + RB_V, s & 1);
            const uint4 o = lds128(tb.z);
            vb = make_uint4(hadd2(vb.x, o.x), hadd2(vb.y, o.y), hadd2(vb.z, o.z), hadd2(vb.w, o.w));
            mbar_wait(sb + RB_Q, s & 1);
        }
        if ((w >> 1) == rank) stsm4t(ta.z + (s & 1) * 1024, vb.x, vb.y, vb.z, vb.w);
        bar_sync(NB_C, 128);
        if (s != NSEG - 1 && w == 0 && lane16 == sb) mbar_expect_tx(sb + RB_V, 2048);
#pragma unroll
        for (int i = 0; i < 8; i++) av[i] = lds128(lane16 + R_WV + ((2 * w + (i >> 2)) * 16 + (i & 3)) * 512);
    }
    {
        const uint4 tp = lds128(tab + 20480);
        rec_store_kvm(tp.z, (char*)(((uint64_t)tp.y << 32) | tp.x), NSEG - 1, w);
    }
    bar_sync(NB_C, 128);
    if (w == 0 && lane == 0) red_release(&g_flags[F_MEM + NRB - 1], 1);
}

__global__ void __launch_bounds__(384, 1) k_rec(const __grid_constant__ RecParams p) {
    extern __shared__ __align__(1024) unsigned char smem_raw[];
    const uint32_t sb = __shfl_sync(~0u, smem_u32(smem_raw), 0);
    const int warp = __shfl_sync(~0u, threadIdx.x >> 5, 0);
    int lane; asm volatile("mov.u32 %0, %%laneid;" : "=r"(lane));
    const int crank = blockIdx.x & 15, slot = blockIdx.x >> 4;
    asm volatile("griddepcontrol.launch_dependents;");
    if (crank == 0 && threadIdx.x == 0) {
        stg_relaxed32(&g_F[65536 + slot * 64], 0u);
        stg_relaxed32(&g_F[65536 + 1024 + slot * 64], 0u);
    }
    if (threadIdx.x == 0) {
        mbar_init(sb + RB_Q, 9); mbar_init(sb + RB_V, 1); mbar_init(sb + RB_E, 1); mbar_init(sb + RB_A, 1); mbar_init(sb + RB_ROLE, 1);
        mbar_init(sb + RB_KV, 1); mbar_init(sb + RB_KV + 8, 1);
        asm volatile("fence.mbarrier_init.release.cluster;" ::: "memory");
        mbar_expect_tx(sb + RB_Q, 4096);
        mbar_expect_tx(sb + RB_V, 2048);
        mbar_expect_tx(sb + RB_E, 4096);
        mbar_expect_tx(sb + RB_A, 4096);
        mbar_expect_tx(sb + RB_ROLE, 4);
    }
    asm volatile("barrier.cluster.arrive.relaxed.aligned;\nbarrier.cluster.wait.aligned;" ::: "memory");
    unsigned role = 0;
    if (crank == 0 && threadIdx.x == 0 && !p.only_pre) {
        unsigned x = 0;
        int tm[2] = {0x7fffffff, 0x7fffffff};
#pragma unroll 1
        for (int i = 0; i < 6; i++) {
            const uint32_t t0 = clk32();
            x = atomicAdd(&g_F[65536 + (i & 1) * 1024 + slot * 64 + (x >> 31)], 1u);
            if (x != (unsigned)(i >> 1)) sts32(sb + R_BAR + 56, x);
            const int dt = (int)(clk32() - t0);
            if (i >= 2) { if (i & 1) tm[1] = min(tm[1], dt); else tm[0] = min(tm[0], dt); }
        }
        const int side = tm[1] > tm[0];
        const unsigned old = atomicAdd(&g_flags[F_SIDE + side * 32], 1u);
        unsigned c0, c1; int gd = 0;
#pragma unroll 1
        do { c0 = ldg_relaxed32(&g_flags[F_SIDE]); c1 = ldg_relaxed32(&g_flags[F_SIDE + 32]); } while ((int)(c0 + c1) < p.ncl && ++gd < 64 * SPIN_LIMIT);
        const int big = c1 > c0;
        role = side == big ? old : (big ? c1 : c0) + old;
        role |= (big ^ 1) << 8;
    }
    __syncwarp();
    if (crank == 0 && warp == 0 && !p.only_pre) {
        role = __shfl_sync(~0u, role, 0);
        if (lane < 16)
            asm volatile("st.async.weak.shared::cluster.mbarrier::complete_tx::bytes.u32 [%0], %1, [%2];"
                         :: "r"(mapa_u32(sb + R_BAR + 48, lane)), "r"(role), "r"(mapa_u32(sb + RB_ROLE, lane)) : "memory");
    }
    if (warp >= 4) {
        const int w8 = warp - 4, nblk = gridDim.x;
        const int cq = lane & 3, rg = w8 * 8 + (lane >> 2);
        const uint32_t red = sb + R_VP;
        const int row0 = blockIdx.x * 8 + w8;
        const uint4* xr = (const uint4*)(p.x + (size_t)row0 * D_);
        uint4 xa = __ldg(xr + lane), xb = __ldg(xr + 32 + lane);
#pragma unroll 1
        for (int sl = blockIdx.x; sl < 96; sl += nblk) {
            uint4 wv[8];
#pragma unroll
            for (int i = 0; i < 8; i++) wv[i] = __ldg((const uint4*)(p.w_mod + (size_t)(rg * 8 + i) * (6 * D_) + sl * 32 + cq * 8));
            const uint32_t cw = __ldg((const uint32_t*)(p.c + rg * 8) + cq);
            const float cl = bflo(cw), ch = bfhi(cw);
            const uint32_t sw = pack2(__fdividef(cl, 1.f + __expf(-cl)), __fdividef(ch, 1.f + __expf(-ch)));
            float a[8];
#pragma unroll
            for (int i = 0; i < 8; i++) a[i] = 0.f;
#pragma unroll
            for (int i = 0; i < 8; i++) {
                const uint32_t sv = __shfl_sync(~0u, sw, (lane & 28) + (i >> 1));
                const float cv = (i & 1) ? bfhi(sv) : bflo(sv);
                a[0] = fmaf(cv, bflo(wv[i].x), a[0]); a[1] = fmaf(cv, bfhi(wv[i].x), a[1]); a[2] = fmaf(cv, bflo(wv[i].y), a[2]); a[3] = fmaf(cv, bfhi(wv[i].y), a[3]);
                a[4] = fmaf(cv, bflo(wv[i].z), a[4]); a[5] = fmaf(cv, bfhi(wv[i].z), a[5]); a[6] = fmaf(cv, bflo(wv[i].w), a[6]); a[7] = fmaf(cv, bfhi(wv[i].w), a[7]);
            }
#pragma unroll
            for (int i = 0; i < 8; i++) { a[i] += __shfl_xor_sync(~0u, a[i], 4); a[i] += __shfl_xor_sync(~0u, a[i], 8); a[i] += __shfl_xor_sync(~0u, a[i], 16); }
            if (lane < 4) {
                sts128(red + w8 * 128 + lane * 32, make_uint4(__float_as_uint(a[0]), __float_as_uint(a[1]), __float_as_uint(a[2]), __float_as_uint(a[3])));
                sts128(red + w8 * 128 + lane * 32 + 16, make_uint4(__float_as_uint(a[4]), __float_as_uint(a[5]), __float_as_uint(a[6]), __float_as_uint(a[7])));
            }
            bar_sync(NB_B, 256);
            if (w8 == 0) {
                float v = 0.f;
#pragma unroll
                for (int i = 0; i < 8; i++) v += lds32f(red + i * 128 + lane * 4);
                g_mod[sl * 32 + lane] = __float2bfloat16_rn(v);
                __syncwarp();
                if (lane == 0) red_release(&g_flags[F_MOD + (sl >= 32)], 1);
            }
            bar_sync(NB_B, 256);
        }
        uint32_t c1[8], sm[8];
        int row = row0;
#pragma unroll 1
        while (true) {
            const uint32_t v[8] = {xa.x, xa.y, xa.z, xa.w, xb.x, xb.y, xb.z, xb.w};
            uint32_t mu2, r[8]; float rden;
            ln_stats(v, mu2, rden);
            if (row == row0) {
                if (lane == 0) wait_flag(F_MOD, 32);
                __syncwarp();
                load_mod8(g_mod + D_, lane, c1);
                load_mod8(g_mod, lane, sm);
#pragma unroll
                for (int i = 0; i < 8; i++) c1[i] = hadd2(c1[i], 0x3F803F80u);
            } else if (row + 512 < S_) {
                xr = (const uint4*)(p.x + (size_t)(row + 512) * D_); xa = __ldg(xr + lane); xb = __ldg(xr + 32 + lane);
            }
            ln_apply(v, mu2, rden, c1, sm, r);
            uint4* hr = (uint4*)(g_h + (size_t)row * D_);
            hr[lane] = make_uint4(r[0], r[1], r[2], r[3]); hr[32 + lane] = make_uint4(r[4], r[5], r[6], r[7]);
            bar_sync(NB_B, 256);
            if (w8 == (row >> 7 & 7) && lane == 0) red_release(&g_flags[F_H + (row >> 7)], 1);
            __syncwarp();
            if (row == row0) {
                if (!p.only_pre) mbar_wait(sb + RB_ROLE, 0);
                const int cl = p.only_pre ? slot : (int)(lds32(sb + R_BAR + 48) & 255);
                row = cl < 4 ? (nblk + cl * 16 + crank) * 8 + w8 : S_;
                if (row < S_) { xr = (const uint4*)(p.x + (size_t)row * D_); xa = __ldg(xr + lane); xb = __ldg(xr + 32 + lane); }
            } else {
                row += 512;
            }
            if (row >= S_) break;
        }
    }
    if (p.only_pre) return;
    mbar_wait(sb + RB_ROLE, 0);
    const int rolew = __shfl_sync(~0u, lds32(sb + R_BAR + 48), 0);
    const int cl = rolew & 255;
    if (cl >= 4) return;
    const int cta = cl * 16 + crank;
    if (warp < 8) rec_qk(p, sb, cta, warp, lane, rolew >> 8);
    else rec_vo(p, sb, cta, warp, lane);
}

enum { J_KV = 0, J_QA = 1, J_O = 2, J_LN = 3, J_UP = 4, J_DN = 5, J_UP2 = 8, J_END = 9 };
constexpr int NJ_O = 2 * OSPLIT, NJ_O2 = 2 * OSPLIT2, NJ_LN = 8, NJ_LN2 = 16, NJ_UP = 14, NJ_UP2 = 28, NJ_DN = 8, NJ_LN1 = 8  ;
constexpr uint64_t pk8(int a, int b, int c, int d, int e, int f, int g, int h) {
    return (uint64_t)a | ((uint64_t)b << 8) | ((uint64_t)c << 16) | ((uint64_t)d << 24) | ((uint64_t)e << 32) | ((uint64_t)f << 40) | ((uint64_t)g << 48) | ((uint64_t)h << 56);
}
constexpr uint64_t NJ_C = pk8(32, 16, NJ_O, NJ_LN, NJ_UP, NJ_DN, 0, 0), NJ_F = pk8(32, 16, NJ_O2, NJ_LN2, NJ_UP2, NJ_DN, 0, 0);
constexpr uint64_t TG_C = pk8(2 * NJ_LN1, 64, 32, 2 * NJ_O, 2 * NJ_LN, 2 * NJ_UP, 32, 0), TG_F = pk8(2 * NJ_LN1, 64, 32, 2 * NJ_O2, 2 * NJ_LN2, 2 * NJ_UP2, 32, 0);
constexpr uint64_t NJ_L = pk8(32, 32, 2 * OSPLIT3, NJ_LN2, NJ_UP2, 2 * NJ_DN, 0, 0), TG_L = pk8(2 * NJ_LN1, 64, 64, 4 * OSPLIT3, 2 * NJ_LN2, 2 * NJ_UP2, 32, 0);
__device__ __forceinline__ uint64_t nj_tab(int rb) { return rb < FINE_RB ? NJ_C : (rb < NRB - 1 ? NJ_F : NJ_L); }
__device__ __forceinline__ uint64_t tg_tab(int rb) { return rb < FINE_RB ? TG_C : (rb < NRB - 1 ? TG_F : TG_L); }
__device__ __forceinline__ int o_nk(int rb) { return rb < FINE_RB ? 64 / OSPLIT : (rb < NRB - 1 ? 64 / OSPLIT2 : 64 / OSPLIT3); }
constexpr uint64_t PRIO = pk8(4, 10, 9, 8, 7, 6, 3, 0);
__device__ __forceinline__ int pick_job(int lane, int qmask, int& idx) {
    const int rb = lane & 15, half = lane >> 4;
    const uint64_t nj = nj_tab(rb) >> (8 * half);
    const uint64_t tg = tg_tab(rb) >> (8 * half);
    const unsigned* cp = &g_flags[F_CLAIM + half * 32 + rb];
    const unsigned* dp = &g_flags[half * 32 + rb];
    int gd = 0;
#pragma unroll 1
    while (true) {
        const unsigned c0 = ldg_relaxed32(cp), c1 = ldg_relaxed32(cp + 64), c2 = ldg_relaxed32(cp + 128);
        const unsigned d0 = ldg_relaxed32(dp - (half && rb ? 1 : 0)), d1 = ldg_relaxed32(dp + 64), d2 = ldg_relaxed32(dp + 128);
        const unsigned cl[3] = {c0, c1, c2}, dv[3] = {d0, d1, d2};
        unsigned key = 0xffffu, key2 = 0xffffu;
        bool pre = false;
#pragma unroll
        for (int i = 0; i < 3; i++) {
            const int q = half + 2 * i;
            const bool have = ((qmask >> q) & 1) && cl[i] < (unsigned)((nj >> (16 * i)) & 255);
            bool ready = have && dv[i] >= (unsigned)((tg >> (16 * i)) & 255);
            unsigned pr = (unsigned)((PRIO >> (8 * q)) & 255);
            if (i == 0 && rb <= 1 - half) ready = have;
            if (i == 0 && half && rb >= FINE_RB) pr = 5;
            if (ready) key = min(key, (pr << 8) | (rb << 4) | q);
            if (have) key2 = min(key2, rb >= FINE_RB ? (0x100u | (q << 4) | rb) : (i == 0 ? 0u : 0x1000u));
            pre |= have && i == 0 && !half;
        }
        const bool anypre = __any_sync(~0u, pre);
        if (anypre && (key & 15) == J_QA) key = 0xffffu;
        key = __reduce_min_sync(~0u, key);
        key2 = __reduce_min_sync(~0u, key2);
        if (key2 == 0xffffu) return J_END;
        int pq, prb;
        if (key != 0xffffu) { pq = key & 15; prb = (key >> 4) & 15; }
        else if (key2 >= 0x120u && key2 < 0x1000u) { pq = (key2 >> 4) & 15; prb = key2 & 15; }
        else {
            __nanosleep(IDLE_NS);
            if (++gd > 16 * SPIN_LIMIT) { TIMEOUT(5, 0); return J_END; }
            continue;
        }
        int c = 0;
        if (lane == 0) c = (int)atomicAdd(&g_flags[F_CLAIM + pq * 32 + prb], 1u);
        c = __shfl_sync(~0u, c, 0);
        if (c < (int)((nj_tab(prb) >> (8 * pq)) & 255)) {
            idx = pq * 512 + prb * 32 + c;
            int acq = 0;
            if (pq != J_QA) {
                if (lane == 0 && ld_acquire(&g_flags[pq * 32 + prb]) >= (unsigned)((tg_tab(prb) >> (8 * pq)) & 255)) {
                    asm volatile("fence.proxy.async.global;" ::: "memory");
                    acq = 1 << 24;
                }
            }
            return (pq == J_UP && prb >= FINE_RB ? J_UP2 : pq) | (prb << 8) | (c << 16) | acq;
        }
    }
}
__device__ __forceinline__ int op_row(int rb, int split) {
    return rb < FINE_RB ? split * S_ + rb * 128
                        : (rb < NRB - 1 ? OSPLIT * S_ + (split * (NRB - FINE_RB) + rb - FINE_RB) * 128 : OSPLIT * S_ + (OSPLIT2 * (NRB - FINE_RB) + split) * 128);
}

struct Pipe { uint32_t stage, phase; };
__device__ __forceinline__ void pipe_next(Pipe& p) { if (++p.stage == W_NST) { p.stage = 0; p.phase ^= 1; } }

__device__ __forceinline__ void scheduler(const Params& p, uint32_t sb, int lane) {
    const uint32_t bars = sb + SM_BAR;
    uint32_t ph = 0;
#pragma unroll 1
    while (true) {
        mbar_wait(bars + B_REQ, ph);
        int j = 4095;
        const int jd = pick_job(lane, p.qmask, j);
        if (lane == 0) { sts32(bars + B_NEXT, (uint32_t)jd); sts32(bars + B_NEXT + 4, (uint32_t)j); mbar_arrive(bars + B_RSP); }
        ph ^= 1;
        if (jd == J_END) break;
        __syncwarp();
    }
}

__device__ __forceinline__ void producer(const Params& p, uint32_t sb) {
    Pipe pp{0, 1};
    const uint32_t bars = sb + SM_BAR;
    uint32_t seq = 0, h_seen = 0;
    mbar_arrive(bars + B_REQ);
#pragma unroll 1
    while (true) {
        mbar_wait(bars + B_RSP, seq & 1);
        const int jd = (int)lds32(bars + B_NEXT), j = (int)lds32(bars + B_NEXT + 4);
        int left = (jd & 255) == J_DN ? 15 : ((jd & 255) == J_QA ? (((jd >> 8) & 255) == NRB - 1 ? 10 : 12) : ((jd & 255) == J_O ? o_nk((jd >> 8) & 255) : ((jd & 255) == J_LN ? 1 : 8)));
        left = max(left - PICK_AHEAD, 1);
        TR(j, 1);
        const int type = jd & 255, rb = (jd >> 8) & 255, cb = (jd >> 16) & 255;
        const bool fine = rb >= FINE_RB, acquired = (jd >> 24) & 1;
        bool first = true;
        auto begin_stage = [&](uint32_t bytes) -> uint32_t {
            mbar_wait(bars + B_EMPTY + pp.stage * 8, pp.phase);
            if (first) { sts32(bars + B_RING + (seq & 7) * 4, (uint32_t)jd); sts32(bars + B_RING + 32 + (seq & 7) * 4, (uint32_t)j); first = false; }
            const uint32_t fb = bars + B_FULL + pp.stage * 8;
            if (bytes) mbar_expect_tx(fb, bytes); else mbar_arrive(fb);
            if (--left == 0 && type != J_END) mbar_arrive(bars + B_REQ);
            return fb;
        };
        if (type == J_END || type == J_LN) {
            if (type == J_LN && !(h_seen >> 31)) { wait_flag(F_MOD + 1, 64); h_seen |= 1u << 31; }

            TR(j, 2);
            begin_stage(0); pipe_next(pp);
            seq++;
            if (type == J_END) break;
            continue;
        }
        const CUtensorMap *ta, *tb0, *tb1;
        int k0 = 0, nk = 8, n0 = cb * 256, n1 = n0 + 128, nb = 4, dep = -1;
        unsigned tgt = 0;
        switch (type) {
            case J_KV: ta = &p.tm_h; tb0 = tb1 = cb < 16 ? &p.tm_wk : &p.tm_wv; n0 = (cb & 15) * 256; n1 = n0 + 128; dep = F_H + rb; tgt = 2 * NJ_LN1; break;
            case J_QA: ta = &p.tm_h; tb0 = tb1 = &p.tm_wq; dep = F_H + rb; tgt = 2 * NJ_LN1; if (rb == NRB - 1) { n0 = (cb >> 1) * 256; n1 = n0 + 128; } break;
            case J_O: ta = &p.tm_o; tb0 = tb1 = &p.tm_wo; n0 = (cb & 1) * 256; n1 = n0 + 128; nk = o_nk(rb); k0 = (cb >> 1) * nk * 64;
                      dep = F_O + rb; tgt = rb == NRB - 1 ? 64 : 32; break;
            case J_UP: ta = &p.tm_h2; tb0 = &p.tm_wg; tb1 = &p.tm_wu; n0 = n1 = cb * 128; dep = F_H2 + rb; tgt = 2 * NJ_LN; break;
            case J_UP2: ta = &p.tm_h2; tb0 = &p.tm_wg; tb1 = &p.tm_wu; n0 = n1 = cb * 64; nb = 2; dep = F_H2 + rb; tgt = 2 * NJ_LN2; break;
            default: ta = &p.tm_act; tb0 = tb1 = &p.tm_wd; n0 = cb * 64; nk = 0; break;
        }
        const int m0 = rb * 128;
        if (type == J_DN && rb == NRB - 1) {
            n0 = (cb >> 1) * 64;
            const int mh = m0 + (cb & 1) * 64;
#pragma unroll 1
            for (int kb = 0; kb < 14; kb++) {
                const uint32_t fb = begin_stage(32768);
                const uint32_t st = sb + pp.stage * W_STAGE;
                const int k = kb * 128;
                tma_load2d(st + 32768, tb0, n0, k, fb);
                tma_load2d(st + 40960, tb0, n0, k + 64, fb);
                if (kb == 0) { if (!acquired) { wait_flag(F_ACT + rb, 2 * NJ_UP2); asm volatile("fence.proxy.async.global;" ::: "memory"); } TR(j, 2); }
                tma_load2d(st, ta, k, mh, fb);
                tma_load2d(st + 8192, ta, k + 64, mh, fb);
                pipe_next(pp);
            }
            const uint32_t fb = begin_stage(8192);
            tma_load2d(sb + pp.stage * W_STAGE, &p.tm_x1, n0, mh, fb);
            pipe_next(pp);
            seq++;
            continue;
        }
        if (type == J_DN) {
#pragma unroll 1
            for (int kb = 0; kb < 14; kb++) {
                const uint32_t fb = begin_stage(49152);
                const uint32_t st = sb + pp.stage * W_STAGE;
                const int k = kb * 128;
                tma_load2d(st + 32768, tb0, n0, k, fb);
                tma_load2d(st + 40960, tb0, n0, k + 64, fb);
                if (kb == 0) { if (!acquired) { wait_flag(F_ACT + rb, 2 * (fine ? NJ_UP2 : NJ_UP)); asm volatile("fence.proxy.async.global;" ::: "memory"); } TR(j, 2); }
                tma_load2d(st, ta, k, m0, fb);
                tma_load2d(st + 8192, ta, k, m0 + 64, fb);
                tma_load2d(st + 16384, ta, k + 64, m0, fb);
                tma_load2d(st + 24576, ta, k + 64, m0 + 64, fb);
                pipe_next(pp);
            }
        }
#pragma unroll 1
        for (int kb = 0; kb < nk; kb++) {
            const uint32_t fb = begin_stage(16384 + nb * 8192);
            const uint32_t st = sb + pp.stage * W_STAGE;
            const int k = k0 + kb * 64;
            tma_load2d(st + 16384, tb0, n0, k, fb);
            if (nb == 4) {
                tma_load2d(st + 16384 + 8192, tb0, n0 + 64, k, fb);
                tma_load2d(st + 16384 + 16384, tb1, n1, k, fb);
                tma_load2d(st + 16384 + 24576, tb1, n1 + 64, k, fb);
            } else if (nb == 2) {
                tma_load2d(st + 16384 + 8192, tb1, n1, k, fb);
            }
            if (kb == 0) {
                if (acquired && dep < 16) h_seen |= 1u << dep;
                if (dep >= 0 && !acquired && !(dep < 16 && ((h_seen >> dep) & 1))) {
                    wait_flag(dep, tgt);
                    if (type != J_O) asm volatile("fence.proxy.async.global;" ::: "memory");
                    if (dep < 16) h_seen |= 1u << dep;
                }
                TR(j, 2);
            }
            tma_load2d(st, ta, k, m0, fb);
            tma_load2d(st + 8192, ta, k, m0 + 64, fb);
            pipe_next(pp);
        }
        if (type == J_QA) {
            wait_flag(F_KV + rb, 64);
#pragma unroll 1
            for (int i = 0; i < (rb == NRB - 1 ? 2 : 4); i++) {
                const uint32_t fb = begin_stage(40960);
                const uint32_t st = sb + pp.stage * W_STAGE;
                const int col = (i & 1) * HD_ + (rb == NRB - 1 ? cb : cb * 2 + (i >> 1)) * DH_;
                tma_load2d(st, &p.tm_kv, col, m0, fb);
                tma_load2d(st + 8192, &p.tm_kv, col, m0 + 64, fb);
                tma_load2d(st + 16384, &p.tm_kv, col + 64, m0, fb);
                tma_load2d(st + 24576, &p.tm_kv, col + 64, m0 + 64, fb);
                if (i == 0) { wait_flag(F_MEM + rb, 64); asm volatile("fence.proxy.async.global;" ::: "memory"); }
                tma_load2d(st + 32768, &p.tm_kvm, col, rb * 32, fb);
                tma_load2d(st + 36864, &p.tm_kvm, col + 64, rb * 32, fb);
                pipe_next(pp);
            }
        } else if (type == J_DN) {
            const uint32_t fb = begin_stage(16384);
            const uint32_t st = sb + pp.stage * W_STAGE;
            tma_load2d(st, &p.tm_x1, n0, m0, fb);
            tma_load2d(st + 8192, &p.tm_x1, n0, m0 + 64, fb);
            pipe_next(pp);
        }
        seq++;
    }
}

__device__ __forceinline__ void store_warp(const Params& p, uint32_t sb, int wg, int lane) {
    const uint32_t bars = sb + SM_BAR;
    uint32_t seq = 0;
#pragma unroll 1
    while (true) {
        bar_sync(NB_ST + wg, 160);
        const uint32_t jd = lds32(bars + B_RING + (seq & 7) * 4);
        seq++;
        const int type = jd & 255, rb = (jd >> 8) & 255, cb = (jd >> 16) & 255;
        if (type == J_END) break;
        const uint32_t src = sb + W_STG + wg * 16384;
        const CUtensorMap* tm = nullptr; int n0 = cb * 256, nbox = 4, mrow = rb * 128 + wg * 64, flag = 0;
        switch (type) {
            case J_KV: tm = &p.tm_kv; flag = F_KV + rb; break;
            case J_QA: tm = &p.tm_o; flag = F_O + rb; if (rb == NRB - 1) { n0 = cb * 128; nbox = 2; } break;
            case J_O: tm = &p.tm_op; n0 = (cb & 1) * 256; mrow = op_row(rb, cb >> 1) + wg * 64; flag = F_OP + rb; break;
            case J_LN: flag = F_H2 + rb; nbox = 0; break;
            case J_UP: tm = &p.tm_act; n0 = cb * 128; nbox = 2; flag = F_ACT + rb; break;
            case J_UP2: tm = &p.tm_act; n0 = cb * 64; nbox = 1; flag = F_ACT + rb; break;
            default: tm = &p.tm_out; n0 = cb * 64; nbox = 1; flag = -1;
                     if (rb == NRB - 1) { n0 = (cb >> 1) * 64; mrow = rb * 128 + (cb & 1) * 64; nbox = wg == 0; } break;
        }
        if (nbox == 4) {
            if (lane == 0) {
                tma_store2d(tm, src, n0, mrow);
                tma_store2d(tm, src + 8192, n0 + 64, mrow);
                bulk_commit();
                asm volatile("cp.async.bulk.wait_group.read 0;" ::: "memory");
                mbar_arrive(bars + B_STGFREE + wg * 8);
            }
            __syncwarp();
            bar_sync(NB_ST + wg, 160);
            n0 += 128; nbox = 2;
        }
        if (lane == 0) {
            if (nbox) {
                tma_store2d(tm, src, n0, mrow);
                if (nbox == 2) tma_store2d(tm, src + 8192, n0 + 64, mrow);
                bulk_commit();
                asm volatile("cp.async.bulk.wait_group.read 0;" ::: "memory");
                mbar_arrive(bars + B_STGFREE + wg * 8);
                bulk_wait0();
                if (flag >= 0) asm volatile("red.relaxed.gpu.global.add.u32 [%0], 1;" :: "l"(&g_flags[flag]) : "memory");
            } else {
                mbar_arrive(bars + B_STGFREE + wg * 8);
                if (flag >= 0) red_release(&g_flags[flag], 1);
            }
        }
        __syncwarp();
    }
}

__device__ __forceinline__ float gelu_tanh(float x) {
    const float t = x * fmaf(-0.10294324397f, x * x, -2.30220819814f);
    float r; asm("rcp.approx.ftz.f32 %0, %1;" : "=f"(r) : "f"(1.f + ex2(t)));
    return x * r;
}

#define CTR(i) do {} while (0)

__device__ __forceinline__ void ln2_row(const Params& p, int rb, int r, int lane, bool wait) {
    const int row = rb * 128 + r, nsplit = 64 / o_nk(rb);
    const uint4* xr = (const uint4*)(p.x + (size_t)row * D_);
    const uint4 xa = __ldg(xr + lane), xb = __ldg(xr + 32 + lane);
    uint32_t ga[8], c1[8], sm[8];
    load_mod8(g_mod + 2 * D_, lane, ga);
    load_mod8(g_mod + 4 * D_, lane, c1);
    load_mod8(g_mod + 3 * D_, lane, sm);
    float a[16];
#pragma unroll
    for (int i = 0; i < 16; i++) a[i] = 0.f;
    const uint4* src = (const uint4*)(g_op + (size_t)(op_row(rb, 0) + r) * D_) + lane;
    const int sstride = (op_row(rb, 1) - op_row(rb, 0)) * (D_ / 8);
    if (wait) { if (lane == 0) wait_flag(F_OP + rb, 4 * nsplit); __syncwarp(); }
    uint4 u[2][8];
#pragma unroll
    for (int sp = 0; sp < 4; sp++) { u[0][2 * sp] = __ldcg(src + sp * sstride); u[0][2 * sp + 1] = __ldcg(src + sp * sstride + 32); }
    if (nsplit > 4) {
#pragma unroll
        for (int sp = 0; sp < 4; sp++) { u[1][2 * sp] = __ldcg(src + (4 + sp) * sstride); u[1][2 * sp + 1] = __ldcg(src + (4 + sp) * sstride + 32); }
    }
#pragma unroll 1
    for (int s0 = 0; s0 < nsplit; s0 += 4) {
#pragma unroll
        for (int sp = 0; sp < 8; sp++) {
            float* q = a + (sp & 1) * 8;
            const uint4 w = u[0][sp];
            q[0] += bflo(w.x); q[1] += bfhi(w.x); q[2] += bflo(w.y); q[3] += bfhi(w.y);
            q[4] += bflo(w.z); q[5] += bfhi(w.z); q[6] += bflo(w.w); q[7] += bfhi(w.w);
            u[0][sp] = u[1][sp];
        }
        if (s0 + 8 < nsplit) {
#pragma unroll
            for (int sp = 0; sp < 4; sp++) { u[1][2 * sp] = __ldcg(src + (s0 + 8 + sp) * sstride); u[1][2 * sp + 1] = __ldcg(src + (s0 + 8 + sp) * sstride + 32); }
        }
    }
    const uint32_t xv[8] = {xa.x, xa.y, xa.z, xa.w, xb.x, xb.y, xb.z, xb.w};
    uint32_t v[8], r8[8];
#pragma unroll
    for (int i = 0; i < 8; i++) v[i] = hadd2(xv[i], hmul2(ga[i], pack2(a[2 * i], a[2 * i + 1])));
    uint4* x1r = (uint4*)(g_x1 + (size_t)row * D_);
    x1r[lane] = make_uint4(v[0], v[1], v[2], v[3]); x1r[32 + lane] = make_uint4(v[4], v[5], v[6], v[7]);
    uint32_t mu2; float rden;
    ln_stats(v, mu2, rden);
#pragma unroll
    for (int i = 0; i < 8; i++) c1[i] = hadd2(c1[i], 0x3F803F80u);
    ln_apply(v, mu2, rden, c1, sm, r8);
    uint4* hr = (uint4*)(g_h2 + (size_t)row * D_);
    hr[lane] = make_uint4(r8[0], r8[1], r8[2], r8[3]); hr[32 + lane] = make_uint4(r8[4], r8[5], r8[6], r8[7]);
}

__device__ __forceinline__ void consumer(const Params& p, uint32_t sb, int warp, int lane) {
    const uint32_t bars = sb + SM_BAR;
    const int wg = warp >> 2, wl = warp & 3;
    const uint32_t l7 = lane & 7, l8 = lane >> 3, g = lane >> 2, t = lane & 3;
    Pipe pp{0, 0};
    uint32_t seq = 0, stg_phase = 1;
    const int srow = wl * 16 + l7 + (l8 & 1) * 8;
    const uint32_t stg_base = sb + W_STG + wg * 16384 + srow * 128;
    const uint32_t sx = ((lane >> 4) ^ (srow & 7)) << 4;
#pragma unroll 1
    while (true) {
        mbar_wait(bars + B_FULL + pp.stage * 8, pp.phase);
        const uint32_t jd = lds32(bars + B_RING + (seq & 7) * 4);
        CTR(3);
        seq++;
        const int type = jd & 255, rb = (jd >> 8) & 255, cb = (jd >> 16) & 255;
        if (type == J_END) { mbar_wait(bars + B_STGFREE + wg * 8, stg_phase); bar_arrive(NB_ST + wg, 160); break; }
        if (type == J_LN) {
            __syncwarp();
            if (lane == 0) mbar_arrive(bars + B_EMPTY + pp.stage * 8);
            pipe_next(pp);
            const int nr = rb >= FINE_RB ? 1 : 2;
#pragma unroll 1
            for (int rr = 0; rr < nr; rr++) ln2_row(p, rb, (cb * 8 + warp) * nr + rr, lane, !((jd >> 24) & 1) && rr == 0);
            mbar_wait(bars + B_STGFREE + wg * 8, stg_phase); stg_phase ^= 1;
            CTR(4); CTR(5);
            bar_arrive(NB_ST + wg, 160);
            continue;
        }
        if (type == J_DN || type == J_UP2) {
            float acc[64];
#pragma unroll
            for (int i = 0; i < 64; i++) acc[i] = 0.f;
            const bool ksplit = type == J_DN && rb == NRB - 1;
            if (ksplit) {
#pragma unroll 1
                for (int kb = 0; kb < 14; kb++) {
                    if (kb) mbar_wait(bars + B_FULL + pp.stage * 8, pp.phase);
                    const uint32_t st = sb + pp.stage * W_STAGE;
                    const uint64_t da = mkdesc(st + wg * 8192, 16, 1024), db = mkdesc(st + 32768 + wg * 8192, 8192, 1024);
                    wg_fence();
#pragma unroll
                    for (int ks = 0; ks < 4; ks++) wgmma_n64(acc, da + ks * 2, db + ks * 128);
                    wg_commit();
                    wg_wait0();
                    if (lane == 0) mbar_arrive(bars + B_EMPTY + pp.stage * 8);
                    pipe_next(pp);
                }
                const uint32_t xb = sb + W_STG + 16384 + (wl * 32 + lane) * 16;
                if (wg == 1) {
                    mbar_wait(bars + B_STGFREE + 8, stg_phase);
#pragma unroll
                    for (int i = 0; i < 8; i++)
                        sts128(xb + i * 2048, make_uint4(__float_as_uint(acc[4 * i]), __float_as_uint(acc[4 * i + 1]), __float_as_uint(acc[4 * i + 2]), __float_as_uint(acc[4 * i + 3])));
                }
                bar_sync(NB_M, 256);
                if (wg == 0) {
#pragma unroll
                    for (int i = 0; i < 8; i++) {
                        const uint4 o = lds128(xb + i * 2048);
                        acc[4 * i] += __uint_as_float(o.x); acc[4 * i + 1] += __uint_as_float(o.y); acc[4 * i + 2] += __uint_as_float(o.z); acc[4 * i + 3] += __uint_as_float(o.w);
                    }
                }
                bar_sync(NB_M, 256);
            } else if (type == J_DN) {
#pragma unroll 1
                for (int kb = 0; kb < 14; kb++) {
                    if (kb) mbar_wait(bars + B_FULL + pp.stage * 8, pp.phase);
                    const uint32_t st = sb + pp.stage * W_STAGE;
                    const uint64_t da = mkdesc(st + wg * 8192, 16, 1024), db = mkdesc(st + 32768, 8192, 1024);
                    wg_fence();
#pragma unroll
                    for (int ks = 0; ks < 8; ks++) wgmma_n64(acc, da + (ks >> 2) * 1024 + (ks & 3) * 2, db + ks * 128);
                    wg_commit();
                    wg_wait0();
                    if (lane == 0) mbar_arrive(bars + B_EMPTY + pp.stage * 8);
                    pipe_next(pp);
                }
            } else {
#pragma unroll 1
                for (int kb = 0; kb < 8; kb++) {
                    if (kb) mbar_wait(bars + B_FULL + pp.stage * 8, pp.phase);
                    const uint32_t st = sb + pp.stage * W_STAGE;
                    const uint64_t da = mkdesc(st + wg * 8192, 16, 1024), db = mkdesc(st + 16384, 8192, 1024);
                    wg_fence();
#pragma unroll
                    for (int ks = 0; ks < 4; ks++) wgmma_n128(acc, da + ks * 2, db + ks * 128, 1);
                    wg_commit();
                    wg_wait0();
                    if (lane == 0) mbar_arrive(bars + B_EMPTY + pp.stage * 8);
                    pipe_next(pp);
                }
            }
            CTR(4);
            if (type == J_UP2) {
                mbar_wait(bars + B_STGFREE + wg * 8, stg_phase); stg_phase ^= 1;
#pragma unroll
                for (int j = 0; j < 4; j++) {
                    uint32_t r[4];
#pragma unroll
                    for (int q = 0; q < 4; q++) {
                        const uint32_t gw = pack2(acc[8 * j + 2 * q], acc[8 * j + 2 * q + 1]);
                        const uint32_t uw = pack2(acc[32 + 8 * j + 2 * q], acc[32 + 8 * j + 2 * q + 1]);
                        r[q] = hmul2(pack2(gelu_tanh(bflo(gw)), gelu_tanh(bfhi(gw))), uw);
                    }
                    stsm4(stg_base + (sx ^ (j << 5)), r[0], r[1], r[2], r[3]);
                }
            } else {
                mbar_wait(bars + B_FULL + pp.stage * 8, pp.phase);
                const uint32_t st = sb + pp.stage * W_STAGE;
                mbar_wait(bars + B_STGFREE + wg * 8, stg_phase); stg_phase ^= 1;
                const uint32_t* gb = (const uint32_t*)(g_mod + 5 * D_ + (ksplit ? cb >> 1 : cb) * 64) + t;
                const uint32_t xa = st + (ksplit ? 0 : wg * 8192) + (wl * 16 + g) * 128 + (g << 4) + t * 4;
#pragma unroll
                for (int j = 0; j < 4; j++) {
                    uint32_t r[4];
#pragma unroll
                    for (int q = 0; q < 4; q++) {
                        const int nt = 2 * j + (q >> 1);
                        const uint32_t xw = lds32((xa ^ ((nt & 7) << 4)) + (nt >> 3) * 16384 + (q & 1) * 1024);
                        r[q] = hadd2(xw, hmul2(__ldcg(gb + nt * 4), pack2(acc[8 * j + 2 * q], acc[8 * j + 2 * q + 1])));
                    }
                    stsm4(stg_base + (j >> 2) * 8192 + (sx ^ ((2 * j & 7) << 4)), r[0], r[1], r[2], r[3]);
                }
                __syncwarp();
                if (lane == 0) mbar_arrive(bars + B_EMPTY + pp.stage * 8);
                pipe_next(pp);
            }
            fence_async_smem();
            CTR(5);
            bar_arrive(NB_ST + wg, 160);
            continue;
        }
        float acc[128];
#pragma unroll
        for (int i = 0; i < 128; i++) acc[i] = 0.f;
        const int nk = type == J_O ? o_nk(rb) : 8;
#pragma unroll 1
        for (int kb = 0; kb < nk; kb++) {
            if (kb) mbar_wait(bars + B_FULL + pp.stage * 8, pp.phase);
            const uint32_t st = sb + pp.stage * W_STAGE;
            const uint64_t da = mkdesc(st + wg * 8192, 16, 1024), db = mkdesc(st + 16384, 8192, 1024);
            wg_fence();
#pragma unroll
            for (int ks = 0; ks < 4; ks++) wgmma_n256(acc, da + ks * 2, db + ks * 128, 1);
            wg_commit();
            wg_wait0();
            if (lane == 0) mbar_arrive(bars + B_EMPTY + pp.stage * 8);
            pipe_next(pp);
        }
        CTR(4);
        if (type == J_QA) {
            uint32_t qf[64];
#pragma unroll
            for (int i = 0; i < 64; i++) qf[i] = pack2(acc[2 * i], acc[2 * i + 1]);
            const int sg = warp >> 1, half = warp & 1;
            const float sc = 0.08838834764831845f * 1.4426950408889634f;
            const uint32_t xoff = (sg >> 1) * 8192 + ((sg & 1) * 32 + l7) * 128;
            const uint32_t moff = 32768 + (sg * 8 + l7) * 128;
            const uint32_t kch = (l8 ^ l7) << 4;
            const uint32_t vch = ((l8 & 1) ^ l7) << 4;
            if (rb == NRB - 1 && (cb & 1)) {
#pragma unroll
                for (int i = 0; i < 32; i++) qf[i] = qf[32 + i];
            }
#pragma unroll 1
            for (int hh = rb == NRB - 1; hh < 2; hh++) {
                mbar_wait(bars + B_FULL + pp.stage * 8, pp.phase);
                uint32_t st = sb + pp.stage * W_STAGE;
                float sa[5][4];
#pragma unroll
                for (int n = 0; n < 5; n++) sa[n][0] = sa[n][1] = sa[n][2] = sa[n][3] = 0.f;
#pragma unroll
                for (int i = 0; i < 4; i++) {
                    const uint32_t* q = qf + i * 8;
                    uint32_t kk[5][4];
                    ldsm4(kk[0][0], kk[0][1], kk[0][2], kk[0][3], st + moff + (i >> 1) * 4096 + (kch ^ ((i & 1) * 64)));
#pragma unroll
                    for (int n = 1; n < 5; n++)
                        ldsm4(kk[n][0], kk[n][1], kk[n][2], kk[n][3], st + xoff + (n - 1) * 1024 + (i >> 1) * 16384 + (kch ^ ((i & 1) * 64)));
#pragma unroll
                    for (int n = 0; n < 5; n++) mma16816(sa[n], q[0], q[1], q[2], q[3], kk[n][0], kk[n][1]);
#pragma unroll
                    for (int n = 0; n < 5; n++) mma16816(sa[n], q[4], q[5], q[6], q[7], kk[n][2], kk[n][3]);
                }
                __syncwarp();
                if (lane == 0) mbar_arrive(bars + B_EMPTY + pp.stage * 8);
                pipe_next(pp);
                const int iq0 = half * 16 + g - 2 * t, iq1 = iq0 + 8;
                float m0 = fmaxf(sa[0][0], sa[0][1]), m1 = fmaxf(sa[0][2], sa[0][3]);
#pragma unroll
                for (int n = 1; n < 5; n++) {
#pragma unroll
                    for (int e = 0; e < 2; e++) {
                        const int jx = (n - 1) * 8 + e;
                        if (jx > iq0) sa[n][e] = -3.0e38f;
                        if (jx > iq1) sa[n][2 + e] = -3.0e38f;
                        m0 = fmaxf(m0, sa[n][e]); m1 = fmaxf(m1, sa[n][2 + e]);
                    }
                }
                m0 = fmaxf(m0, __shfl_xor_sync(~0u, m0, 1)); m1 = fmaxf(m1, __shfl_xor_sync(~0u, m1, 1));
                m0 = fmaxf(m0, __shfl_xor_sync(~0u, m0, 2)); m1 = fmaxf(m1, __shfl_xor_sync(~0u, m1, 2));
                m0 *= -sc; m1 *= -sc;
                float l0 = 0.f, l1 = 0.f;
                uint32_t p0[5], p1[5];
#pragma unroll
                for (int n = 0; n < 5; n++) {
                    const float e0 = ex2(fmaf(sa[n][0], sc, m0)), e1 = ex2(fmaf(sa[n][1], sc, m0));
                    const float e2 = ex2(fmaf(sa[n][2], sc, m1)), e3 = ex2(fmaf(sa[n][3], sc, m1));
                    l0 += e0 + e1; l1 += e2 + e3;
                    p0[n] = pack2(e0, e1); p1[n] = pack2(e2, e3);
                }
                l0 += __shfl_xor_sync(~0u, l0, 1); l1 += __shfl_xor_sync(~0u, l1, 1);
                l0 += __shfl_xor_sync(~0u, l0, 2); l1 += __shfl_xor_sync(~0u, l1, 2);
                const float i0 = __fdividef(1.f, l0), i1 = __fdividef(1.f, l1);
                mbar_wait(bars + B_FULL + pp.stage * 8, pp.phase);
                st = sb + pp.stage * W_STAGE;
                mbar_wait(bars + B_STGFREE + wg * 8, stg_phase); stg_phase ^= 1;
#pragma unroll
                for (int i = 0; i < 32; i++) qf[i] = qf[32 + i];
#pragma unroll 1
                for (int bx = 0; bx < 2; bx++) {
                    float o[8][4];
                    uint32_t vm[8], v0[4][4], v1[4][4];
#pragma unroll
                    for (int ep = 0; ep < 4; ep++) {
                        ldsm2t(vm[2 * ep], vm[2 * ep + 1], st + moff + bx * 4096 + (vch ^ (ep << 5)));
                        const uint32_t va = st + xoff + (l8 >> 1) * 1024 + bx * 16384 + (vch ^ (ep << 5));
                        ldsm4t(v0[ep][0], v0[ep][1], v0[ep][2], v0[ep][3], va);
                        ldsm4t(v1[ep][0], v1[ep][1], v1[ep][2], v1[ep][3], va + 2048);
                    }
#pragma unroll
                    for (int n = 0; n < 8; n++) { o[n][0] = o[n][1] = o[n][2] = o[n][3] = 0.f; mma16816(o[n], p0[0], p1[0], p0[1], p1[1], vm[n], v0[n >> 1][n & 1]); }
#pragma unroll
                    for (int n = 0; n < 8; n++) mma16816(o[n], p0[2], p1[2], p0[3], p1[3], v0[n >> 1][2 + (n & 1)], v1[n >> 1][n & 1]);
#pragma unroll
                    for (int n = 0; n < 8; n++) mma1688(o[n], p0[4], p1[4], v1[n >> 1][2 + (n & 1)]);
#pragma unroll
                    for (int ep = 0; ep < 4; ep++)
                        stsm4(stg_base + bx * 8192 + (sx ^ (ep << 5)),
                              pack2(o[2 * ep][0] * i0, o[2 * ep][1] * i0), pack2(o[2 * ep][2] * i1, o[2 * ep][3] * i1),
                              pack2(o[2 * ep + 1][0] * i0, o[2 * ep + 1][1] * i0), pack2(o[2 * ep + 1][2] * i1, o[2 * ep + 1][3] * i1));
                }
                __syncwarp();
                if (lane == 0) mbar_arrive(bars + B_EMPTY + pp.stage * 8);
                pipe_next(pp);
                if (hh == 0) { fence_async_smem(); bar_arrive(NB_ST + wg, 160); }
            }
        } else if (type == J_UP) {
            mbar_wait(bars + B_STGFREE + wg * 8, stg_phase); stg_phase ^= 1;
#pragma unroll
            for (int j = 0; j < 8; j++) {
                uint32_t r[4];
#pragma unroll
                for (int q = 0; q < 4; q++) {
                    const uint32_t gw = pack2(acc[8 * j + 2 * q], acc[8 * j + 2 * q + 1]);
                    const uint32_t uw = pack2(acc[64 + 8 * j + 2 * q], acc[64 + 8 * j + 2 * q + 1]);
                    r[q] = hmul2(pack2(gelu_tanh(bflo(gw)), gelu_tanh(bfhi(gw))), uw);
                }
                stsm4(stg_base + (j >> 2) * 8192 + (sx ^ ((2 * j & 7) << 4)), r[0], r[1], r[2], r[3]);
            }
        } else {
#pragma unroll
            for (int rd = 0; rd < 2; rd++) {
                mbar_wait(bars + B_STGFREE + wg * 8, stg_phase); stg_phase ^= 1;
#pragma unroll
                for (int j = rd * 8; j < rd * 8 + 8; j++)
                    stsm4(stg_base + ((j >> 2) & 1) * 8192 + (sx ^ ((2 * j & 7) << 4)),
                          pack2(acc[8 * j], acc[8 * j + 1]), pack2(acc[8 * j + 2], acc[8 * j + 3]),
                          pack2(acc[8 * j + 4], acc[8 * j + 5]), pack2(acc[8 * j + 6], acc[8 * j + 7]));
                if (rd == 0) { fence_async_smem(); bar_arrive(NB_ST + wg, 160); }
            }
        }
        fence_async_smem();
        CTR(5);
        bar_arrive(NB_ST + wg, 160);
    }
}

__global__ void __launch_bounds__(384, 1) k_work(const __grid_constant__ Params p) {
    extern __shared__ __align__(1024) unsigned char smem_raw[];
    const uint32_t sb = smem_u32(smem_raw);
    if (sb & 1023) __trap();
    const int warp = __shfl_sync(~0u, threadIdx.x >> 5, 0);
    int lane; asm volatile("mov.u32 %0, %%laneid;" : "=r"(lane));
    if (threadIdx.x == 0) {
        const uint32_t bars = sb + SM_BAR;
        for (int i = 0; i < W_NST; i++) { mbar_init(bars + B_FULL + i * 8, 1); mbar_init(bars + B_EMPTY + i * 8, 8); }
        mbar_init(bars + B_STGFREE, 1); mbar_init(bars + B_STGFREE + 8, 1); mbar_init(bars + B_REQ, 1); mbar_init(bars + B_RSP, 1);
        asm volatile("fence.mbarrier_init.release.cluster;" ::: "memory");
    }
    __syncthreads();
    if (warp < 8) {
        asm volatile("setmaxnreg.inc.sync.aligned.u32 224;");
        consumer(p, sb, warp, lane);
    } else {
        asm volatile("setmaxnreg.dec.sync.aligned.u32 56;");
        if (warp == 8) { if (lane == 0) producer(p, sb); }
        else if (warp < 11) store_warp(p, sb, warp - 9, lane);
        else scheduler(p, sb, lane);
        __syncwarp();
        bar_sync(NB_W0, 128);
        if (warp == 8 && p.qmask == 0xff) {
            unsigned last = 0;
            if (lane == 0) { __threadfence(); last = atomicAdd(&g_flags[F_DONE], 1u) == gridDim.x - 1; }
            if (__shfl_sync(~0u, last, 0))
                for (int i = lane; i < F_TOTAL; i += 32) g_flags[i] = 0;
        }
    }
}

typedef CUresult (*EncodeFn)(CUtensorMap*, CUtensorMapDataType, cuuint32_t, void*, const cuuint64_t*, const cuuint64_t*,
                             const cuuint32_t*, const cuuint32_t*, CUtensorMapInterleave, CUtensorMapSwizzle,
                             CUtensorMapL2promotion, CUtensorMapFloatOOBfill);

static void make_map(EncodeFn enc, CUtensorMap* m, const void* ptr, uint64_t rows, uint64_t cols, uint32_t box_rows) {
    cuuint64_t dims[2] = {cols, rows};
    cuuint64_t strides[1] = {cols * 2};
    cuuint32_t box[2] = {64, box_rows};
    cuuint32_t es[2] = {1, 1};
    enc(m, CU_TENSOR_MAP_DATA_TYPE_BFLOAT16, 2, const_cast<void*>(ptr), dims, strides, box, es, CU_TENSOR_MAP_INTERLEAVE_NONE,
        CU_TENSOR_MAP_SWIZZLE_128B, CU_TENSOR_MAP_L2_PROMOTION_L2_256B, CU_TENSOR_MAP_FLOAT_OOB_FILL_NONE);
}
template <typename T> static void* sym_addr(T& sym) { void* p = nullptr; cudaGetSymbolAddress(&p, sym); return p; }

extern "C" void kernel_launch(void* const* d_in, const int* in_sizes, int n_in, void* d_out, int out_size) {
    static Params prm;
    static RecParams rp;
    static int n_sm = 132;
    static bool ready = false;
    static const void* key[14];
    bool same = ready;
    for (int i = 0; i < 13 && same; i++) same = key[i] == d_in[i];
    same = same && key[13] == d_out;
    if (!same) {
        void* fn = nullptr;
        cudaDriverEntryPointQueryResult qr;
        cudaGetDriverEntryPoint("cuTensorMapEncodeTiled", &fn, cudaEnableDefault, &qr);
        EncodeFn enc = (EncodeFn)fn;
        make_map(enc, &prm.tm_h, sym_addr(g_h), S_, D_, 64);
        make_map(enc, &prm.tm_kv, sym_addr(g_kv), S_, 2 * HD_, 64);
        make_map(enc, &rp.tm_kv32, sym_addr(g_kv), S_, 2 * HD_, 32);
        make_map(enc, &prm.tm_kvm, sym_addr(g_kvm), NSEG * 8, 2 * HD_, 32);
        make_map(enc, &prm.tm_o, sym_addr(g_o), S_, HD_, 64);
        make_map(enc, &prm.tm_op, sym_addr(g_op), OP_ROWS, D_, 64);
        make_map(enc, &prm.tm_h2, sym_addr(g_h2), S_, D_, 64);
        make_map(enc, &prm.tm_act, sym_addr(g_act), S_, DF_, 64);
        make_map(enc, &prm.tm_x1, sym_addr(g_x1), S_, D_, 64);
        make_map(enc, &prm.tm_out, d_out, S_, D_, 64);
        make_map(enc, &prm.tm_wq, d_in[2], D_, HD_, 64);
        make_map(enc, &prm.tm_wk, d_in[3], D_, HD_, 64);
        make_map(enc, &prm.tm_wv, d_in[4], D_, HD_, 64);
        make_map(enc, &prm.tm_wo, d_in[5], HD_, D_, 64);
        make_map(enc, &prm.tm_wg, d_in[8], D_, DF_, 64);
        make_map(enc, &prm.tm_wu, d_in[9], D_, DF_, 64);
        make_map(enc, &prm.tm_wd, d_in[10], DF_, D_, 64);
        prm.x = (const bf16*)d_in[0]; prm.c = (const bf16*)d_in[11]; prm.w_mod = (const bf16*)d_in[12];
        rp.mem0 = (const bf16*)d_in[1]; rp.x = prm.x; rp.c = prm.c; rp.w_mod = prm.w_mod;
        rp.wq = (const bf16*)d_in[2]; rp.wk = (const bf16*)d_in[3]; rp.wv = (const bf16*)d_in[4]; rp.wo = (const bf16*)d_in[5];
        cudaDeviceGetAttribute(&n_sm, cudaDevAttrMultiProcessorCount, 0);
        cudaFuncSetAttribute(k_work, cudaFuncAttributeMaxDynamicSharedMemorySize, SMEM_BYTES);
        cudaFuncSetAttribute(k_rec, cudaFuncAttributeMaxDynamicSharedMemorySize, R_SMEM);
        cudaFuncSetAttribute(k_rec, cudaFuncAttributeNonPortableClusterSizeAllowed, 1);
        {
            cudaLaunchConfig_t cfg = {};
            cfg.gridDim = dim3(128); cfg.blockDim = dim3(384); cfg.dynamicSmemBytes = R_SMEM;
            cudaLaunchAttribute at[1];
            at[0].id = cudaLaunchAttributeClusterDimension; at[0].val.clusterDim.x = 16; at[0].val.clusterDim.y = 1; at[0].val.clusterDim.z = 1;
            cfg.attrs = at; cfg.numAttrs = 1;
            int n = 0;
            cudaOccupancyMaxActiveClusters(&n, k_rec, &cfg);
            rp.ncl = n < 4 ? 4 : (n > 8 ? 8 : n);
        }
        for (int i = 0; i < 13; i++) key[i] = d_in[i];
        key[13] = d_out;
        ready = true;
    }
    cudaStream_t st = cudaStreamPerThread;
    auto launch_rec = [&]() {
        cudaLaunchConfig_t cfg = {};
        cfg.gridDim = dim3(16 * rp.ncl); cfg.blockDim = dim3(384); cfg.dynamicSmemBytes = R_SMEM; cfg.stream = st;
        cudaLaunchAttribute at[1];
        at[0].id = cudaLaunchAttributeClusterDimension; at[0].val.clusterDim.x = 16; at[0].val.clusterDim.y = 1; at[0].val.clusterDim.z = 1;
        cfg.attrs = at; cfg.numAttrs = 1;
        cudaLaunchKernelEx(&cfg, k_rec, rp);
    };
    auto launch_work = [&](int qmask, int pdl) {
        prm.qmask = qmask;
        cudaLaunchConfig_t cfg = {};
        cfg.gridDim = dim3(n_sm); cfg.blockDim = dim3(384); cfg.dynamicSmemBytes = SMEM_BYTES; cfg.stream = st;
        cudaLaunchAttribute at[1];
        at[0].id = cudaLaunchAttributeProgrammaticStreamSerialization; at[0].val.programmaticStreamSerializationAllowed = 1;
        cfg.attrs = at; cfg.numAttrs = pdl;
        cudaLaunchKernelEx(&cfg, k_work, prm);
    };
    launch_rec();
    launch_work(0xff, 1);
}
```

```cpp
#include <cuda_runtime.h>
#include <cuda_bf16.h>
#include <cuda.h>
#include <stdint.h>

typedef __nv_bfloat16 bf16;
#define IDLE_NS 150
#define FLAG_NS 20

constexpr int S_ = 2048, D_ = 512, DH_ = 128, HD_ = 4096, NSEG = 64, DF_ = 1792;
constexpr int NRB = 16;
constexpr int OSPLIT = 4;

__device__ __align__(1024) bf16 g_h[S_ * D_];
__device__ __align__(1024) bf16 g_kv[S_ * 2 * HD_];
__device__ __align__(1024) bf16 g_kvm[NSEG * 8 * 2 * HD_];
__device__ __align__(1024) bf16 g_o[S_ * HD_];
#define FINE_RB_ 12
constexpr int FINE_RB = FINE_RB_;
#define OSPLIT2_ 8
constexpr int OSPLIT2 = OSPLIT2_;
constexpr int OSPLIT3 = 16;
constexpr int OP_ROWS = OSPLIT * S_ + OSPLIT2 * (NRB - FINE_RB) * 128 + OSPLIT3 * 128;
__device__ __align__(1024) bf16 g_op[OP_ROWS * D_];
__device__ __align__(1024) bf16 g_x1[S_ * D_];
__device__ __align__(1024) bf16 g_h2[S_ * D_];
__device__ __align__(1024) bf16 g_act[S_ * DF_];
__device__ __align__(1024) bf16 g_mod[6 * D_];
__device__ uint32_t g_Fraw[131072 + 65536 + 2048];
#define g_F ((uint32_t*)(((uint64_t)g_Fraw + 0x7FFFFull) & ~0x7FFFFull))
constexpr int F_H = 0, F_MEM = 32, F_O = 64, F_OP = 96, F_H2 = 128, F_ACT = 160, F_MOD = 192, F_KV = 224, F_CLAIM = 256  ,
              F_SIDE = 512  , F_DONE = 576, F_TOTAL = 608;
__device__ __align__(128) unsigned int g_flags[F_TOTAL];
#define TR(j, i) do {} while (0)

__device__ __forceinline__ uint32_t smem_u32(const void* p) { return (uint32_t)__cvta_generic_to_shared(p); }
__device__ __forceinline__ uint32_t clk32() { uint32_t c; asm volatile("mov.u32 %0, %%clock;" : "=r"(c)); return c; }
__device__ __forceinline__ uint32_t mapa_u32(uint32_t addr, uint32_t rank) {
    uint32_t r; asm volatile("mapa.shared::cluster.u32 %0, %1, %2;" : "=r"(r) : "r"(addr), "r"(rank)); return r;
}
__device__ __forceinline__ void mbar_init(uint32_t bar, uint32_t cnt) {
    asm volatile("mbarrier.init.shared::cta.b64 [%0], %1;" :: "r"(bar), "r"(cnt) : "memory");
}
__device__ __forceinline__ void mbar_expect_tx(uint32_t bar, uint32_t bytes) {
    asm volatile("mbarrier.arrive.expect_tx.shared::cta.b64 _, [%0], %1;" :: "r"(bar), "r"(bytes) : "memory");
}
__device__ __forceinline__ void mbar_arrive(uint32_t bar) {
    asm volatile("mbarrier.arrive.shared::cta.b64 _, [%0];" :: "r"(bar) : "memory");
}
__device__ __forceinline__ bool mbar_try_wait(uint32_t bar, uint32_t parity) {
    uint32_t ok;
    asm volatile("{\n.reg .pred p;\nmbarrier.try_wait.parity.shared::cta.b64 p, [%1], %2;\nselp.u32 %0, 1, 0, p;\n}"
                 : "=r"(ok) : "r"(bar), "r"(parity) : "memory");
    return ok;
}
constexpr int SPIN_LIMIT = 1 << 18;
#define TIMEOUT(code, info) do {} while (0)
__device__ __forceinline__ void mbar_wait(uint32_t bar, uint32_t parity) {
    int g = 0;
#pragma unroll 1
    while (!mbar_try_wait(bar, parity)) { if (++g >= SPIN_LIMIT) { TIMEOUT(0, bar & 255); break; } }
}
__device__ __forceinline__ void bar_sync(int id, int n) { asm volatile("bar.sync %0, %1;" :: "r"(id), "r"(n) : "memory"); }
__device__ __forceinline__ void bar_arrive(int id, int n) { asm volatile("bar.arrive %0, %1;" :: "r"(id), "r"(n) : "memory"); }
__device__ __forceinline__ void st_async_v2(uint32_t addr, float a, float b, uint32_t bar) {
    asm volatile("st.async.weak.shared::cluster.mbarrier::complete_tx::bytes.v2.f32 [%0], {%1,%2}, [%3];"
                 :: "r"(addr), "f"(a), "f"(b), "r"(bar) : "memory");
}
__device__ __forceinline__ void st_async_v4(uint32_t addr, uint4 v, uint32_t bar) {
    asm volatile("st.async.weak.shared::cluster.mbarrier::complete_tx::bytes.v4.b32 [%0], {%1,%2,%3,%4}, [%5];"
                 :: "r"(addr), "r"(v.x), "r"(v.y), "r"(v.z), "r"(v.w), "r"(bar) : "memory");
}
__device__ __forceinline__ void stg_relaxed32(uint32_t* p, uint32_t v) {
    asm volatile("st.relaxed.gpu.global.b32 [%0], %1;" :: "l"(p), "r"(v) : "memory");
}
__device__ __forceinline__ uint32_t ldg_relaxed32(const uint32_t* p) {
    uint32_t v; asm volatile("ld.relaxed.gpu.global.b32 %0, [%1];" : "=r"(v) : "l"(p) : "memory"); return v;
}
__device__ __forceinline__ unsigned int ld_acquire(const unsigned int* p) {
    unsigned int v; asm volatile("ld.acquire.gpu.global.u32 %0, [%1];" : "=r"(v) : "l"(p) : "memory"); return v;
}
__device__ __forceinline__ void red_release(unsigned int* p, unsigned int v) {
    asm volatile("red.release.gpu.global.add.u32 [%0], %1;" :: "l"(p), "r"(v) : "memory");
}
__device__ __forceinline__ void wait_flag(int idx, unsigned int target) {
    const unsigned int* p = &g_flags[idx];
    int g = 0;
#pragma unroll 1
    while (ld_acquire(p) < target) { __nanosleep(FLAG_NS); if (++g >= 64 * SPIN_LIMIT) { TIMEOUT(2, idx); break; } }
}
__device__ __forceinline__ void cp_async16(uint32_t dst, const void* src) {
    asm volatile("cp.async.cg.shared.global [%0], [%1], 16;" :: "r"(dst), "l"(src) : "memory");
}
__device__ __forceinline__ void cp_async_commit() { asm volatile("cp.async.commit_group;" ::: "memory"); }
template <int N> __device__ __forceinline__ void cp_async_wait() { asm volatile("cp.async.wait_group %0;" :: "n"(N) : "memory"); }
__device__ __forceinline__ void ldsm4(uint32_t& r0, uint32_t& r1, uint32_t& r2, uint32_t& r3, uint32_t addr) {
    asm volatile("ldmatrix.sync.aligned.m8n8.x4.shared.b16 {%0,%1,%2,%3}, [%4];" : "=r"(r0), "=r"(r1), "=r"(r2), "=r"(r3) : "r"(addr) : "memory");
}
__device__ __forceinline__ void ldsm4t(uint32_t& r0, uint32_t& r1, uint32_t& r2, uint32_t& r3, uint32_t addr) {
    asm volatile("ldmatrix.sync.aligned.m8n8.x4.trans.shared.b16 {%0,%1,%2,%3}, [%4];" : "=r"(r0), "=r"(r1), "=r"(r2), "=r"(r3) : "r"(addr) : "memory");
}
__device__ __forceinline__ void ldsm2t(uint32_t& r0, uint32_t& r1, uint32_t addr) {
    asm volatile("ldmatrix.sync.aligned.m8n8.x2.trans.shared.b16 {%0,%1}, [%2];" : "=r"(r0), "=r"(r1) : "r"(addr) : "memory");
}
__device__ __forceinline__ void stsm4(uint32_t addr, uint32_t r0, uint32_t r1, uint32_t r2, uint32_t r3) {
    asm volatile("stmatrix.sync.aligned.m8n8.x4.shared.b16 [%0], {%1,%2,%3,%4};" :: "r"(addr), "r"(r0), "r"(r1), "r"(r2), "r"(r3) : "memory");
}
__device__ __forceinline__ void stsm4t(uint32_t addr, uint32_t r0, uint32_t r1, uint32_t r2, uint32_t r3) {
    asm volatile("stmatrix.sync.aligned.m8n8.x4.trans.shared.b16 [%0], {%1,%2,%3,%4};" :: "r"(addr), "r"(r0), "r"(r1), "r"(r2), "r"(r3) : "memory");
}
__device__ __forceinline__ void stsm2t(uint32_t addr, uint32_t r0, uint32_t r1) {
    asm volatile("stmatrix.sync.aligned.m8n8.x2.trans.shared.b16 [%0], {%1,%2};" :: "r"(addr), "r"(r0), "r"(r1) : "memory");
}
__device__ __forceinline__ void mma16816(float* d, uint32_t a0, uint32_t a1, uint32_t a2, uint32_t a3, uint32_t b0, uint32_t b1) {
    asm volatile("mma.sync.aligned.m16n8k16.row.col.f32.bf16.bf16.f32 {%0,%1,%2,%3}, {%4,%5,%6,%7}, {%8,%9}, {%0,%1,%2,%3};"
                 : "+f"(d[0]), "+f"(d[1]), "+f"(d[2]), "+f"(d[3]) : "r"(a0), "r"(a1), "r"(a2), "r"(a3), "r"(b0), "r"(b1));
}
__device__ __forceinline__ void mma1688(float* d, uint32_t a0, uint32_t a1, uint32_t b0) {
    asm volatile("mma.sync.aligned.m16n8k8.row.col.f32.bf16.bf16.f32 {%0,%1,%2,%3}, {%4,%5}, {%6}, {%0,%1,%2,%3};"
                 : "+f"(d[0]), "+f"(d[1]), "+f"(d[2]), "+f"(d[3]) : "r"(a0), "r"(a1), "r"(b0));
}
__device__ __forceinline__ void mma16816h(float* d, uint32_t a0, uint32_t a2, uint32_t b0, uint32_t b1) {
    asm volatile("{\n.reg .b32 ju, jv;\nmma.sync.aligned.m16n8k16.row.col.f32.bf16.bf16.f32 {%0,%1,%2,%3}, {%4,ju,%5,jv}, {%6,%7}, {%0,%1,%2,%3};\n}"
                 : "+f"(d[0]), "+f"(d[1]), "+f"(d[2]), "+f"(d[3]) : "r"(a0), "r"(a2), "r"(b0), "r"(b1));
}
__device__ __forceinline__ void mma1688h(float* d, uint32_t a0, uint32_t b0) {
    asm volatile("{\n.reg .b32 ju;\nmma.sync.aligned.m16n8k8.row.col.f32.bf16.bf16.f32 {%0,%1,%2,%3}, {%4,ju}, {%5}, {%0,%1,%2,%3};\n}"
                 : "+f"(d[0]), "+f"(d[1]), "+f"(d[2]), "+f"(d[3]) : "r"(a0), "r"(b0));
}
__device__ __forceinline__ uint32_t movm(uint32_t a) {
    uint32_t d; asm volatile("movmatrix.sync.aligned.m8n8.trans.b16 %0, %1;" : "=r"(d) : "r"(a)); return d;
}
__device__ __forceinline__ uint32_t pack2(float lo, float hi) {
    uint32_t r; asm("cvt.rn.bf16x2.f32 %0, %1, %2;" : "=r"(r) : "f"(hi), "f"(lo)); return r;
}
__device__ __forceinline__ float bflo(uint32_t w) { return __uint_as_float(w << 16); }
__device__ __forceinline__ float bfhi(uint32_t w) { return __uint_as_float(w & 0xffff0000u); }
__device__ __forceinline__ float rbf(float x) { return __bfloat162float(__float2bfloat16_rn(x)); }
__device__ __forceinline__ float ex2(float x) { float y; asm("ex2.approx.ftz.f32 %0, %1;" : "=f"(y) : "f"(x)); return y; }
__device__ __forceinline__ void sts128(uint32_t addr, uint4 v) {
    asm volatile("st.shared.v4.b32 [%0], {%1,%2,%3,%4};" :: "r"(addr), "r"(v.x), "r"(v.y), "r"(v.z), "r"(v.w) : "memory");
}
__device__ __forceinline__ uint4 lds128(uint32_t addr) {
    uint4 v; asm volatile("ld.shared.v4.b32 {%0,%1,%2,%3}, [%4];" : "=r"(v.x), "=r"(v.y), "=r"(v.z), "=r"(v.w) : "r"(addr) : "memory"); return v;
}
__device__ __forceinline__ float2 lds64f(uint32_t addr) {
    float2 v; asm volatile("ld.shared.v2.f32 {%0,%1}, [%2];" : "=f"(v.x), "=f"(v.y) : "r"(addr) : "memory"); return v;
}
__device__ __forceinline__ float lds32f(uint32_t addr) {
    float v; asm volatile("ld.shared.f32 %0, [%1];" : "=f"(v) : "r"(addr) : "memory"); return v;
}
__device__ __forceinline__ uint32_t lds32(uint32_t addr) {
    uint32_t v; asm volatile("ld.shared.b32 %0, [%1];" : "=r"(v) : "r"(addr) : "memory"); return v;
}
__device__ __forceinline__ void sts32(uint32_t addr, uint32_t v) { asm volatile("st.shared.b32 [%0], %1;" :: "r"(addr), "r"(v) : "memory"); }
__device__ __forceinline__ void sts64f(uint32_t addr, float a, float b) { asm volatile("st.shared.v2.f32 [%0], {%1,%2};" :: "r"(addr), "f"(a), "f"(b) : "memory"); }

__device__ __forceinline__ void tma_load2d(uint32_t dst, const CUtensorMap* tm, int c0, int c1, uint32_t bar) {
    asm volatile("cp.async.bulk.tensor.2d.shared::cluster.global.mbarrier::complete_tx::bytes [%0], [%1, {%3, %4}], [%2];"
                 :: "r"(dst), "l"(tm), "r"(bar), "r"(c0), "r"(c1) : "memory");
}
__device__ __forceinline__ void tma_store2d(const CUtensorMap* tm, uint32_t src, int c0, int c1) {
    asm volatile("cp.async.bulk.tensor.2d.global.shared::cta.bulk_group [%0, {%2, %3}], [%1];"
                 :: "l"(tm), "r"(src), "r"(c0), "r"(c1) : "memory");
}
__device__ __forceinline__ void bulk_commit() { asm volatile("cp.async.bulk.commit_group;" ::: "memory"); }
__device__ __forceinline__ void bulk_wait0() { asm volatile("cp.async.bulk.wait_group 0;" ::: "memory"); }
__device__ __forceinline__ void fence_async_smem() { asm volatile("fence.proxy.async.shared::cta;" ::: "memory"); }
__device__ __forceinline__ void fence_async_all() { asm volatile("fence.proxy.async;" ::: "memory"); }

__device__ __forceinline__ void wg_fence() { asm volatile("wgmma.fence.sync.aligned;" ::: "memory"); }
__device__ __forceinline__ void wg_commit() { asm volatile("wgmma.commit_group.sync.aligned;" ::: "memory"); }
__device__ __forceinline__ void wg_wait0() { asm volatile("wgmma.wait_group.sync.aligned 0;" ::: "memory"); }
__device__ __forceinline__ uint64_t mkdesc(uint32_t saddr, uint32_t lbo, uint32_t sbo) {
    return (uint64_t)((saddr & 0x3FFFF) >> 4) | ((uint64_t)(lbo >> 4) << 16) | ((uint64_t)(sbo >> 4) << 32) | (1ull << 62);
}
#define ACC8(i) "+f"(d[i]), "+f"(d[i + 1]), "+f"(d[i + 2]), "+f"(d[i + 3]), "+f"(d[i + 4]), "+f"(d[i + 5]), "+f"(d[i + 6]), "+f"(d[i + 7])
__device__ __forceinline__ void wgmma_n256(float* d, uint64_t da, uint64_t db, int scale_d) {
    asm volatile(
        "{\n.reg .pred p;\nsetp.ne.b32 p, %130, 0;\n"
        "wgmma.mma_async.sync.aligned.m64n256k16.f32.bf16.bf16 "
        "{%0,%1,%2,%3,%4,%5,%6,%7,%8,%9,%10,%11,%12,%13,%14,%15,%16,%17,%18,%19,%20,%21,%22,%23,%24,%25,%26,%27,%28,%29,%30,%31,"
        "%32,%33,%34,%35,%36,%37,%38,%39,%40,%41,%42,%43,%44,%45,%46,%47,%48,%49,%50,%51,%52,%53,%54,%55,%56,%57,%58,%59,%60,%61,%62,%63,"
        "%64,%65,%66,%67,%68,%69,%70,%71,%72,%73,%74,%75,%76,%77,%78,%79,%80,%81,%82,%83,%84,%85,%86,%87,%88,%89,%90,%91,%92,%93,%94,%95,"
        "%96,%97,%98,%99,%100,%101,%102,%103,%104,%105,%106,%107,%108,%109,%110,%111,%112,%113,%114,%115,%116,%117,%118,%119,%120,%121,%122,%123,%124,%125,%126,%127}, "
        "%128, %129, p, 1, 1, 0, 1;\n}"
        : ACC8(0), ACC8(8), ACC8(16), ACC8(24), ACC8(32), ACC8(40), ACC8(48), ACC8(56),
          ACC8(64), ACC8(72), ACC8(80), ACC8(88), ACC8(96), ACC8(104), ACC8(112), ACC8(120)
        : "l"(da), "l"(db), "r"(scale_d));
}
__device__ __forceinline__ void wgmma_n128(float* d, uint64_t da, uint64_t db, int scale_d) {
    asm volatile(
        "{\n.reg .pred p;\nsetp.ne.b32 p, %66, 0;\n"
        "wgmma.mma_async.sync.aligned.m64n128k16.f32.bf16.bf16 "
        "{%0,%1,%2,%3,%4,%5,%6,%7,%8,%9,%10,%11,%12,%13,%14,%15,%16,%17,%18,%19,%20,%21,%22,%23,%24,%25,%26,%27,%28,%29,%30,%31,"
        "%32,%33,%34,%35,%36,%37,%38,%39,%40,%41,%42,%43,%44,%45,%46,%47,%48,%49,%50,%51,%52,%53,%54,%55,%56,%57,%58,%59,%60,%61,%62,%63}, "
        "%64, %65, p, 1, 1, 0, 1;\n}"
        : ACC8(0), ACC8(8), ACC8(16), ACC8(24), ACC8(32), ACC8(40), ACC8(48), ACC8(56)
        : "l"(da), "l"(db), "r"(scale_d));
}

__device__ __forceinline__ void wgmma_n64(float* d, uint64_t da, uint64_t db) {
    asm volatile(
        "wgmma.mma_async.sync.aligned.m64n64k16.f32.bf16.bf16 "
        "{%0,%1,%2,%3,%4,%5,%6,%7,%8,%9,%10,%11,%12,%13,%14,%15,%16,%17,%18,%19,%20,%21,%22,%23,%24,%25,%26,%27,%28,%29,%30,%31}, "
        "%32, %33, 1, 1, 1, 0, 1;"
        : ACC8(0), ACC8(8), ACC8(16), ACC8(24)
        : "l"(da), "l"(db));
}
__device__ __forceinline__ uint32_t hadd2(uint32_t a, uint32_t b) { uint32_t r; asm("add.rn.bf16x2 %0, %1, %2;" : "=r"(r) : "r"(a), "r"(b)); return r; }
__device__ __forceinline__ uint32_t hsub2(uint32_t a, uint32_t b) { uint32_t r; asm("sub.rn.bf16x2 %0, %1, %2;" : "=r"(r) : "r"(a), "r"(b)); return r; }
__device__ __forceinline__ uint32_t hmul2(uint32_t a, uint32_t b) { uint32_t r; asm("mul.rn.bf16x2 %0, %1, %2;" : "=r"(r) : "r"(a), "r"(b)); return r; }
__device__ __forceinline__ void load_mod8(const bf16* m, int lane, uint32_t* v) {
    const uint4 a = __ldcg((const uint4*)m + lane), b = __ldcg((const uint4*)m + 32 + lane);
    v[0] = a.x; v[1] = a.y; v[2] = a.z; v[3] = a.w; v[4] = b.x; v[5] = b.y; v[6] = b.z; v[7] = b.w;
}
__device__ __forceinline__ void ln_stats(const uint32_t* x, uint32_t& mu2, float& rden) {
    float s = 0.f;
#pragma unroll
    for (int i = 0; i < 8; i++) s += bflo(x[i]) + bfhi(x[i]);
#pragma unroll
    for (int o = 16; o > 0; o >>= 1) s += __shfl_xor_sync(~0u, s, o);
    const float mean = s * (1.f / D_);
    float q = 0.f;
#pragma unroll
    for (int i = 0; i < 8; i++) { const float d0 = bflo(x[i]) - mean, d1 = bfhi(x[i]) - mean; q = fmaf(d0, d0, q); q = fmaf(d1, d1, q); }
#pragma unroll
    for (int o = 16; o > 0; o >>= 1) q += __shfl_xor_sync(~0u, q, o);
    mu2 = pack2(mean, mean);
    rden = __frcp_rn(rbf(__fsqrt_rn(rbf(rbf(q * (1.f / D_)) + 1e-5f))));
}
__device__ __forceinline__ void ln_apply(const uint32_t* x, uint32_t mu2, float rden, const uint32_t* c1, const uint32_t* sm, uint32_t* r) {
#pragma unroll
    for (int i = 0; i < 8; i++) {
        const uint32_t d = hsub2(x[i], mu2);
        r[i] = hadd2(hmul2(pack2(bflo(d) * rden, bfhi(d) * rden), c1[i]), sm[i]);
    }
}

struct __align__(64) Params {
    CUtensorMap tm_h, tm_kv, tm_kvm, tm_o, tm_op, tm_h2, tm_act, tm_x1, tm_out;
    CUtensorMap tm_wq, tm_wk, tm_wv, tm_wo, tm_wg, tm_wu, tm_wd;
    const bf16 *x, *c, *w_mod;
    int qmask;
};

constexpr uint32_t R_WV = 0, R_MEM = 65536  ,
                   R_KX = 69632  , R_VX = R_KX + 8192,
                   R_VMS = R_KX + 32768  , R_OS = R_VMS + 2048  , R_SX = R_OS + 2048  , R_BAR = R_SX + 1536,
                   R_RS = R_BAR + 512  , R_VB = R_RS + 4096  , R_VP = R_VB + 2048  ,
                   R_STG = R_VP + 4096  ,
                   R_TQ = R_STG  , R_TV = R_STG + 53248  , R_QF = R_STG + 77824  ,
                   R_SMEM = R_STG + 98304;
static_assert((R_STG & 1023) == 0 && (R_RS & 511) == 0 && R_QF + 16384 <= R_SMEM, "smem");
constexpr uint32_t RB_Q = R_BAR, RB_V = R_BAR + 8, RB_E = R_BAR + 16, RB_A = R_BAR + 24, RB_ROLE = R_BAR + 32, RB_KV = R_BAR + 40  , RB_K = R_BAR + 64;
constexpr int W_NST = 4;
constexpr uint32_t W_STAGE = 49152, W_STG = W_NST * W_STAGE  , W_END = W_STG + 32768;
constexpr uint32_t SM_BAR = W_END;
constexpr uint32_t SMEM_BYTES = W_END + 1024 + 2048;
constexpr uint32_t B_FULL = 0, B_EMPTY = 32, B_STGFREE = 64, B_REQ = 80, B_RSP = 88, B_NEXT = 96, B_RING = 128;
#define PICK_AHEAD 3

constexpr int NB_S = 11, NB_Y = 1, NB_M = 5, NB_K = 5, NB_B = 2, NB_C = 3, NB_D = 4, NB_W0 = 6  , NB_ST = 9  ;

__device__ __forceinline__ int pos_of_d(int d) {
    const int rem = d & 31;
    return (d & ~31) + ((rem & 7) >> 1) * 8 + (rem & 1) * 4 + (rem >> 3);
}

#define PROF(i) do {} while (0)
#define PROFG(i) do {} while (0)
#define VK0_ 4
constexpr int VK0 = VK0_;
constexpr int NOFF = 8;
#define OFFKS(i) ((i) >> 1)
#define POLL_GAP 140

struct __align__(64) RecParams { CUtensorMap tm_kv32; const bf16 *mem0, *wq, *wk, *wv, *wo, *x, *c, *w_mod; int ncl, only_pre; };

__device__ __forceinline__ void rec_qk(const RecParams& p, const uint32_t sb, const int cta, const int warp, int lane, const int sel) {
    const int crank = cta & 15, cl = cta >> 4, rank = cta & 1;
    const int wg = warp >> 2, aa = warp & 3;
    uint32_t wa[2][16][4];
    {
        const uint32_t stg = sb + R_STG + wg * 32768;
        const int t128 = aa * 32 + lane;
        const int row = (lane >> 4) * 8 + (lane & 7);
        const int ch = t128 & 7;
        const size_t goff = (size_t)rank * 256 * HD_ + (cta >> 1) * DH_ + ch * 8;
        const bf16* W = (wg == 0 ? p.wq : p.wk) + goff;
#pragma unroll 4
        for (int dd = 0; dd < 16; dd++) {
            const int d = dd * 16 + (t128 >> 3), pp = pos_of_d(d);
            cp_async16(sb + R_WV + wg * 32768 + pp * 128 + ((ch ^ (pp & 7)) << 4), p.wv + goff + wg * 64 + (size_t)d * HD_);
        }
        cp_async_commit();
#pragma unroll 4
        for (int dd = 0; dd < 16; dd++) {
            const int d = dd * 16 + (t128 >> 3), pp = pos_of_d(d);
            cp_async16(stg + pp * 128 + ((ch ^ (pp & 7)) << 4), W + (size_t)d * HD_);
        }
        cp_async_commit();
        {
            const int tok = warp, d0 = lane * 8;
            const uint4 m0 = __ldg((const uint4*)(p.mem0 + tok * D_ + rank * 256 + d0));
            const uint32_t mw[4] = {m0.x, m0.y, m0.z, m0.w};
#pragma unroll
            for (int e = 0; e < 8; e++) {
                const int pp = pos_of_d(d0 + e);
                const unsigned short v = (unsigned short)(mw[e >> 1] >> ((e & 1) * 16));
                asm volatile("st.shared.u16 [%0], %1;" :: "r"(sb + R_MEM + (pp >> 3) * 128 + tok * 16 + (pp & 7) * 2), "h"(v) : "memory");
            }
        }
        cp_async_wait<1>();
        bar_sync(NB_W0 + wg, 128);
        const uint32_t fv = row * 128 + (((2 * aa + ((lane >> 3) & 1)) ^ (row & 7)) << 4);
#pragma unroll
        for (int ks = 0; ks < 16; ks++) ldsm4t(wa[0][ks][0], wa[0][ks][1], wa[0][ks][2], wa[0][ks][3], sb + R_WV + wg * 32768 + fv + ks * 2048);
        bar_sync(NB_W0 + wg, 128);
#pragma unroll
        for (int ks = 0; ks < 16; ks++)
            sts128(sb + R_WV + (warp * 16 + ks) * 512 + lane * 16, make_uint4(wa[0][ks][0], wa[0][ks][1], wa[0][ks][2], wa[0][ks][3]));
        const uint32_t fo = stg + row * 128 + (((4 * (aa & 1) + ((lane >> 3) & 1)) ^ (row & 7)) << 4);
#pragma unroll 1
        for (int m = 0; m < 2; m++) {
            cp_async_wait<0>();
            bar_sync(NB_W0 + wg, 128);
            if ((aa >> 1) == m) {
#pragma unroll
                for (int ks = 0; ks < 16; ks++) {
                    ldsm4t(wa[0][ks][0], wa[0][ks][1], wa[0][ks][2], wa[0][ks][3], fo + ks * 2048);
                    ldsm4t(wa[1][ks][0], wa[1][ks][1], wa[1][ks][2], wa[1][ks][3], (fo ^ 32) + ks * 2048);
                }
            }
            bar_sync(NB_W0 + wg, 128);
            if (m == 0) {
#pragma unroll 4
                for (int dd = 0; dd < 16; dd++) {
                    const int d = dd * 16 + (t128 >> 3), pp = pos_of_d(d);
                    cp_async16(stg + pp * 128 + ((ch ^ (pp & 7)) << 4), W + 64 + (size_t)d * HD_);
                }
                cp_async_commit();
            }
        }
    }
    bar_sync(NB_D, 384);
    const uint32_t tab = sb + R_TQ + wg * 26624 + (aa * 32 + lane) * 16;
    {
        const uint32_t l7 = lane & 7, l8 = lane >> 3, g = lane >> 2, t = lane & 3;
        const uint32_t bq = warp >> 1, tp = warp & 1;
        uint4 v;
        v.x = sb + R_QF + (rank * 8 + warp) * 512 + lane * 16;
        v.y = sb + R_QF + (warp == 5 ? 1024 : 0) + lane * 16;
        v.z = sb + R_KX + ((warp - 1) * 8 + l7) * 128 + ((l8 ^ l7) << 4);
        v.w = sb + R_SX + warp * 256 + lane * 8;
        sts128(tab, v);
        sts128(tab + 2048, make_uint4(sb + lane * 16 + R_MEM, sb + lane * 16 + R_WV + warp * 8192, sb + lane * 16 + R_VP + warp * 512, v.x));
        const uint32_t L = bq * 8 + 2 * tp + (l8 & 1) + 4 * (l8 >> 1);
        const uint32_t d0 = (((crank + ((t >> 1) | (g & 6))) & 7) << 1) | (crank >> 3);
        v.x = sb + R_RS + l7 * 512 + ((L ^ l7) << 4);
        v.y = mapa_u32(sb + R_MEM + ((crank & 7) * 4 + bq) * 128 + (4 * tp + 2 * (t & 1) + (g & 1)) * 16, d0);
        v.z = mapa_u32(sb + RB_A, d0);
        v.w = lane;
        sts128(tab + 4096, v);
        const uint64_t wr = (uint64_t)(g_F + ((crank * 2 + ((crank ^ (crank >> 3) ^ sel) & 1)) * 1024 + warp * 128 + cl * 32 + lane));
        sts128(tab + 6144, make_uint4((uint32_t)wr, (uint32_t)(wr >> 32), (uint32_t)((((cl + 1) & 3) - cl) * 128), (uint32_t)((((cl + 2) & 3) - cl) * 128)));
        sts32(tab + 8192, (uint32_t)((((cl + 3) & 3) - cl) * 128));
#pragma unroll
        for (int i = 0; i < NOFF; i++)
            sts128(tab + 10240 + i * 2048, make_uint4(wa[i & 1][OFFKS(i)][0], wa[i & 1][OFFKS(i)][1], wa[i & 1][OFFKS(i)][2], wa[i & 1][OFFKS(i)][3]));
    }
    bar_sync(NB_D, 384);
    uint4 tb = lds128(tab + 2048);
    const uint32_t qbar = sb + (wg ? RB_K : RB_Q);
#pragma unroll 1
    for (int s = 0; s < NSEG; s++) {
        if (s > 0) mbar_wait(sb + RB_A, (s - 1) & 1);
        if (warp == 0) PROF(0);
        uint4 ta;
        const uint32_t par = (s & 1) * 8192;
        {
            float acc[5][4];
#pragma unroll
            for (int c = 0; c < 5; c++) { acc[c][0] = acc[c][1] = acc[c][2] = acc[c][3] = 0.f; }
            uint32_t b[8][4];
            uint4 av[16];
            static_assert(VK0 == 4, "order below assumes the V/O warps cover slices 0,1");
#define QK4(k2) do { \
                mma16816(acc[0], wa[0][2 * (k2)][0], wa[0][2 * (k2)][1], wa[0][2 * (k2)][2], wa[0][2 * (k2)][3], b[k2][0], b[k2][1]); \
                mma16816(acc[1], wa[1][2 * (k2)][0], wa[1][2 * (k2)][1], wa[1][2 * (k2)][2], wa[1][2 * (k2)][3], b[k2][0], b[k2][1]); \
                mma16816(acc[3], wa[0][2 * (k2) + 1][0], wa[0][2 * (k2) + 1][1], wa[0][2 * (k2) + 1][2], wa[0][2 * (k2) + 1][3], b[k2][2], b[k2][3]); \
                mma16816(acc[4], wa[1][2 * (k2) + 1][0], wa[1][2 * (k2) + 1][1], wa[1][2 * (k2) + 1][2], wa[1][2 * (k2) + 1][3], b[k2][2], b[k2][3]); } while (0)
#define V2(k2) do { \
                mma16816(acc[2], av[2 * (k2)].x, av[2 * (k2)].y, av[2 * (k2)].z, av[2 * (k2)].w, b[k2][0], b[k2][1]); \
                mma16816(acv, av[2 * (k2) + 1].x, av[2 * (k2) + 1].y, av[2 * (k2) + 1].z, av[2 * (k2) + 1].w, b[k2][2], b[k2][3]); } while (0)
#define LB(k2) ldsm4(b[k2][0], b[k2][1], b[k2][2], b[k2][3], tb.x + (k2) * 512)
#define LV(k2) do { av[2 * (k2)] = lds128(tb.y + 2 * (k2) * 512); av[2 * (k2) + 1] = lds128(tb.y + (2 * (k2) + 1) * 512); } while (0)
            float acv[4] = {0.f, 0.f, 0.f, 0.f};
            LB(0); LB(1); LB(2); LB(3);
            QK4(0); LB(4); QK4(1); LB(5); LV(2); LV(3); QK4(2); LB(6); QK4(3); LB(7);
            V2(2); V2(3); LV(4); LV(5);
            QK4(4); QK4(5); QK4(6); QK4(7);
            const uint4 f = make_uint4(movm(pack2(acc[0][0] + acc[3][0], acc[0][1] + acc[3][1])), movm(pack2(acc[0][2] + acc[3][2], acc[0][3] + acc[3][3])),
                                       movm(pack2(acc[1][0] + acc[4][0], acc[1][1] + acc[4][1])), movm(pack2(acc[1][2] + acc[4][2], acc[1][3] + acc[4][3])));
            st_async_v4((tb.w + par) ^ (1u << 24), f, qbar ^ (1u << 24));
            sts128(tb.w + par, f);
            __syncwarp();
            if ((tb.w & 511) == 0) mbar_arrive(qbar);
            if (warp == 0) PROF(1);
            if (tb.x == 0) break;
            LV(6); LV(7);
            ta = lds128(tab);
            V2(4); V2(5); V2(6); V2(7);
            sts128(tb.z, make_uint4(__float_as_uint(acc[2][0] + acv[0]), __float_as_uint(acc[2][1] + acv[1]), __float_as_uint(acc[2][2] + acv[2]), __float_as_uint(acc[2][3] + acv[3])));
            bar_arrive(NB_Y, 384);
        }
        if (warp == 0) PROF(14);
        if (warp < 6 && s != NSEG - 1) {
            float sa[4] = {0.f, 0.f, 0.f, 0.f}, sc[4] = {0.f, 0.f, 0.f, 0.f};
            const uint32_t qa = ta.y + par;
            if (warp == 0 || warp == 5) {
                mbar_wait(sb + RB_Q, s & 1);
                mbar_wait(sb + RB_K, s & 1);
                const uint4 q0 = lds128(qa), q1 = lds128(qa + 4096), k0 = lds128(qa + 2048), k1 = lds128(qa + 6144);
                const uint4 q2 = lds128(qa + 512), q3 = lds128(qa + 4608), k2 = lds128(qa + 2560), k3 = lds128(qa + 6656);
                mma16816h(sa, hadd2(q0.x, q1.x), hadd2(q0.y, q1.y), hadd2(k0.x, k1.x), hadd2(k0.y, k1.y));
                mma16816h(sc, hadd2(q0.z, q1.z), hadd2(q0.w, q1.w), hadd2(k0.z, k1.z), hadd2(k0.w, k1.w));
                mma16816h(sa, hadd2(q2.x, q3.x), hadd2(q2.y, q3.y), hadd2(k2.x, k3.x), hadd2(k2.y, k3.y));
                mma16816h(sc, hadd2(q2.z, q3.z), hadd2(q2.w, q3.w), hadd2(k2.z, k3.z), hadd2(k2.w, k3.w));
            } else {
                uint32_t k[16];
                const uint32_t kb = ta.z + 2 * par;
                mbar_wait(sb + RB_KV + (s & 1) * 8, (s >> 1) & 1);
                ldsm4(k[0], k[1], k[2], k[3], kb);
                ldsm4(k[4], k[5], k[6], k[7], kb ^ 64);
                ldsm4(k[8], k[9], k[10], k[11], kb + 4096);
                ldsm4(k[12], k[13], k[14], k[15], (kb ^ 64) + 4096);
                mbar_wait(sb + RB_Q, s & 1);
                uint4 q0[4], q1[4];
#pragma unroll
                for (int i = 0; i < 4; i++) { q0[i] = lds128(qa + i * 512); q1[i] = lds128(qa + 4096 + i * 512); }
                float sd[4] = {0.f, 0.f, 0.f, 0.f}, se[4] = {0.f, 0.f, 0.f, 0.f};
                mma16816h(sa, hadd2(q0[0].x, q1[0].x), hadd2(q0[0].y, q1[0].y), k[0], k[1]);
                mma16816h(sc, hadd2(q0[0].z, q1[0].z), hadd2(q0[0].w, q1[0].w), k[2], k[3]);
                mma16816h(sd, hadd2(q0[1].x, q1[1].x), hadd2(q0[1].y, q1[1].y), k[4], k[5]);
                mma16816h(se, hadd2(q0[1].z, q1[1].z), hadd2(q0[1].w, q1[1].w), k[6], k[7]);
                mma16816h(sa, hadd2(q0[2].x, q1[2].x), hadd2(q0[2].y, q1[2].y), k[8], k[9]);
                mma16816h(sc, hadd2(q0[2].z, q1[2].z), hadd2(q0[2].w, q1[2].w), k[10], k[11]);
                mma16816h(sd, hadd2(q0[3].x, q1[3].x), hadd2(q0[3].y, q1[3].y), k[12], k[13]);
                mma16816h(se, hadd2(q0[3].z, q1[3].z), hadd2(q0[3].w, q1[3].w), k[14], k[15]);
                sa[0] += sd[0]; sa[1] += sd[1]; sc[0] += se[0]; sc[1] += se[1];
            }
            const float scl = 0.08838834764831845f * 1.4426950408889634f;
            sts64f(ta.w, (sa[0] + sc[0]) * scl, (sa[1] + sc[1]) * scl);
            bar_arrive(NB_S, 320);
            if (warp == 0) PROF(2);
        } else if (warp == 7) {
            mbar_wait(sb + RB_Q, s & 1);
            mbar_wait(sb + RB_K, s & 1);
            if (lane == 0) {
                mbar_expect_tx(sb + RB_Q, 2048);
                mbar_expect_tx(sb + RB_K, 2048);
                if (s > 0) mbar_expect_tx(sb + RB_A, 4096);
            }
            __syncwarp();
        } else if (s > 0 && (s & 3) == 0 && warp == 6) {
            bar_sync(NB_K, 160);
            if (lane == 0) red_release(&g_flags[F_MEM + (s >> 2) - 1], 1);
            __syncwarp();
        }
        if (s == NSEG - 1) {
            const uint4 td = lds128(tab + 6144);
            stg_relaxed32((uint32_t*)(((uint64_t)td.y << 32) | (td.x ^ 0x21000)), 0u);
            break;
        }
        const uint4 tc = lds128(tab + 4096), td = lds128(tab + 6144);
        const uint32_t te = lds32(tab + 8192);
        uint32_t* wr = (uint32_t*)(((uint64_t)td.y << 32) | (td.x ^ ((s & 1) * 0x21000)));
        const uint32_t* r1p = (const uint32_t*)((const char*)wr + (int)td.z);
        const uint32_t* r2p = (const uint32_t*)((const char*)wr + (int)td.w);
        const uint32_t* r3p = (const uint32_t*)((const char*)wr + (int)te);
        const uint32_t tag = ((s >> 1) + 1) & 1;
        mbar_wait(sb + RB_E, s & 1);
        if (warp == 0) PROF(7);
        {
            uint32_t a0, a1, a2, a3;
            ldsm4t(a0, a1, a2, a3, tc.x);
            const uint32_t one = 0x3F803F80u;
            float d0_[4] = {0.f, 0.f, 0.f, 0.f}, d1_[4] = {0.f, 0.f, 0.f, 0.f};
            mma1688(d0_, a0, a1, one);
            mma1688(d1_, a2, a3, one);
            const bool t1 = tc.w & 1, t2 = tc.w & 2;
            const float x = t2 ? (t1 ? d1_[2] : d1_[0]) : (t1 ? d0_[2] : d0_[0]);
            const uint32_t own = (__float_as_uint(x) & ~1u) | tag;
            stg_relaxed32(wr, own);
            const uint32_t tq = clk32();
            if (warp == 0) PROF(8);
            while ((int)(clk32() - tq) < POLL_GAP) {}
            uint32_t f1 = ldg_relaxed32(r1p), f2 = ldg_relaxed32(r2p), f3 = ldg_relaxed32(r3p);
#pragma unroll
            for (int i = 0; i < NOFF; i++) {
                const uint4 f0 = lds128(tab + 10240 + i * 2048);
                wa[i & 1][OFFKS(i)][0] = f0.x; wa[i & 1][OFFKS(i)][1] = f0.y; wa[i & 1][OFFKS(i)][2] = f0.z; wa[i & 1][OFFKS(i)][3] = f0.w;
            }
            tb = lds128(tab + 2048);
            int gg = 0;
#pragma unroll 1
            while (!__all_sync(~0u, (((f1 ^ tag) | (f2 ^ tag) | (f3 ^ tag)) & 1) == 0)) {
                f1 = ldg_relaxed32(r1p); f2 = ldg_relaxed32(r2p); f3 = ldg_relaxed32(r3p);
                if (++gg > 16 * SPIN_LIMIT) { TIMEOUT(3, s); break; }
            }
            if (warp == 0) PROF(9);
            const float v = (__uint_as_float(own) + __uint_as_float(f2)) + (__uint_as_float(f1) + __uint_as_float(f3));
            const bool b8 = tc.w & 8, b16 = tc.w & 16;
            const float recv = __shfl_xor_sync(~0u, v, 8);
            const uint32_t word = b8 ? pack2(recv, v) : pack2(v, recv);
            const uint32_t oth = __shfl_xor_sync(~0u, word, 16);
            const uint32_t wl = b16 ? oth : word, wh = b16 ? word : oth;
            const uint32_t p0 = __shfl_xor_sync(~0u, wl, 2), p1 = __shfl_xor_sync(~0u, wh, 2);
            const uint4 item = t2 ? make_uint4(p0, p1, wl, wh) : make_uint4(wl, wh, p0, p1);
            st_async_v4(tc.y, item, tc.z);
            if (tc.w == 0 && warp == 7) mbar_expect_tx(sb + RB_E, 4096);
            if (warp == 0) PROF(10);
        }
    }
}

__device__ __forceinline__ void rec_load_kv(const RecParams& p, uint32_t sb, int head, int s) {
    const uint32_t bar = sb + RB_KV + (s & 1) * 8, d = sb + R_KX + (s & 1) * 16384;
    mbar_expect_tx(bar, 16384);
    tma_load2d(d, &p.tm_kv32, head * DH_, s * 32, bar);
    tma_load2d(d + 4096, &p.tm_kv32, head * DH_ + 64, s * 32, bar);
    tma_load2d(d + 8192, &p.tm_kv32, HD_ + head * DH_, s * 32, bar);
    tma_load2d(d + 12288, &p.tm_kv32, HD_ + head * DH_ + 64, s * 32, bar);
}
__device__ __forceinline__ void rec_store_kvm(uint32_t src, char* dst, int s, int w) {
    dst += (size_t)s * (8 * 2 * HD_ * 2);
    if (w < 2) {
        const uint4 a = lds128(src + (s & 1) * 8192), b = lds128(src + (s & 1) * 8192 + 4096);
        *(uint32_t*)dst = hadd2(a.x, b.x); *(uint32_t*)(dst + 16) = hadd2(a.y, b.y);
        *(uint32_t*)(dst + 32) = hadd2(a.z, b.z); *(uint32_t*)(dst + 48) = hadd2(a.w, b.w);
    } else {
        *(uint4*)dst = lds128(src + (s & 1) * 1024);
    }
}

__device__ __forceinline__ void rec_vo(const RecParams& p, const uint32_t sb, const int cta, const int warp, int lane) {
    const int w = warp - 8, crank = cta & 15, rank = cta & 1;
    uint32_t wo[4][8][4];
    const uint32_t tab = sb + R_TV + (w * 32 + lane) * 16;
    {
        const int t128 = w * 32 + lane;
        const bf16* Wo = p.wo + (size_t)(cta >> 1) * DH_ * D_ + rank * 256;
        const uint32_t stg = sb + R_STG + 2 * 32768;
#pragma unroll
        for (int half = 0; half < 2; half++) {
#pragma unroll 4
            for (int i = t128; i < 2048; i += 128) {
                const int e = i >> 5, ch = i & 31;
                cp_async16(stg + e * 512 + ((ch ^ (e & 7)) << 4), Wo + (size_t)(half * 64 + e) * D_ + ch * 8);
            }
            cp_async_commit();
            cp_async_wait<0>();
            bar_sync(NB_W0 + 2, 128);
#pragma unroll
            for (int j = 0; j < 4; j++)
#pragma unroll
                for (int kk = 0; kk < 4; kk++) {
                    const int e = kk * 16 + (lane >> 4) * 8 + (lane & 7);
                    const int ch = (w * 4 + j) * 2 + ((lane >> 3) & 1);
                    ldsm4t(wo[j][half * 4 + kk][0], wo[j][half * 4 + kk][1], wo[j][half * 4 + kk][2], wo[j][half * 4 + kk][3],
                           stg + e * 512 + ((ch ^ (e & 7)) << 4));
                }
            bar_sync(NB_W0 + 2, 128);
        }
        bar_sync(NB_D, 384);
        const uint32_t l7 = lane & 7, l8 = lane >> 3, g = lane >> 2;
        uint4 v;
        v.x = sb + R_VX + (w >> 1) * 4096 + ((l8 & 1) * 8 + l7) * 128 + (((4 * (w & 1) + (l8 >> 1)) ^ l7) << 4);
        v.y = sb + R_OS + (w >> 1) * 1024 + g * 128 + (((4 * (w & 1)) ^ g) << 4) + (lane & 3) * 4;
        v.z = sb + R_VMS + l7 * 128 + (((4 * (w & 1) + l8) ^ l7) << 4);
        v.w = sb + R_OS + l7 * 128 + ((l8 ^ l7) << 4);
        sts128(tab, v);
        v.x = mapa_u32(sb + R_RS + (crank >> 1) * 512 + ((lane ^ (crank >> 1)) << 4), rank * 8 + w * 2);
        v.y = mapa_u32(sb + RB_E, rank * 8 + w * 2);
        v.z = sb + R_VB + w * 512 + lane * 16;
        v.w = sb + R_SX + lane * 8;
        sts128(tab + 2048, v);
#pragma unroll
        for (int i = 0; i < 8; i++)
            sts128(tab + 4096 + i * 2048, make_uint4(wo[i >> 1][(i & 1) * 4][0], wo[i >> 1][(i & 1) * 4][1], wo[i >> 1][(i & 1) * 4][2], wo[i >> 1][(i & 1) * 4][3]));
        const int tok = (w & 1) * 4 + (lane >> 3);
        const uint64_t kd = w < 2 ? (uint64_t)(g_kvm + (g * (2 * HD_) + cta * 64 + w * 32 + (lane & 3) * 2))
                                  : (uint64_t)(g_kvm + (tok * (2 * HD_) + HD_ + cta * 64 + (lane & 7) * 8));
        const uint32_t ksrc = w < 2 ? sb + R_QF + (4 + 2 * rank + w) * 512 + lane * 16 : sb + R_VMS + tok * 128 + (((lane & 7) ^ tok) << 4);
        sts128(tab + 20480, make_uint4((uint32_t)kd, (uint32_t)(kd >> 32), ksrc, sb + lane * 16));
        if (t128 == 0) { wait_flag(F_KV + 0, 64); rec_load_kv(p, sb, cta >> 1, 0); mbar_wait(sb + RB_KV, 0); }
        __syncwarp();
    }
    bar_sync(NB_D, 384);
    const uint32_t lane16 = lds32(tab + 20480 + 12);
    uint4 av[8];
#pragma unroll
    for (int i = 0; i < 8; i++) av[i] = lds128(lane16 + R_WV + ((2 * w + (i >> 2)) * 16 + (i & 3)) * 512);
#pragma unroll 1
    for (int s = 0; s < NSEG; s++) {
        {
            if (s > 0) mbar_wait(sb + RB_A, (s - 1) & 1);
            if (s > 0) {
                const uint4 tp = lds128(tab + 20480);
                rec_store_kvm(tp.z, (char*)(((uint64_t)tp.y << 32) | tp.x), s - 1, w);
                if ((s & 3) == 0) bar_arrive(NB_K, 160);
            }
            if (s + 1 < NSEG - 1 && w == 3 && lane16 == sb) {
                if (((s + 1) & 3) == 0) wait_flag(F_KV + ((s + 1) >> 2), 64);
                rec_load_kv(p, sb, cta >> 1, s + 1);
            }
            __syncwarp();
        }
        uint4 vb;
        const uint4 ta = lds128(tab), tb = lds128(tab + 2048);
        {
            uint32_t bb[8];
            ldsm4(bb[0], bb[1], bb[2], bb[3], lane16 + R_MEM);
            ldsm4(bb[4], bb[5], bb[6], bb[7], lane16 + R_MEM + 512);
            float vd[4] = {0.f, 0.f, 0.f, 0.f}, ve[4] = {0.f, 0.f, 0.f, 0.f};
#pragma unroll
            for (int i = 0; i < 4; i++) {
                mma16816(vd, av[i].x, av[i].y, av[i].z, av[i].w, bb[2 * i], bb[2 * i + 1]);
                mma16816(ve, av[4 + i].x, av[4 + i].y, av[4 + i].z, av[4 + i].w, bb[2 * i], bb[2 * i + 1]);
            }
            bar_sync(NB_Y, 384);
            const uint4 a = lds128(lane16 + R_VP + w * 1024), b = lds128(lane16 + R_VP + w * 1024 + 512);
            vb = make_uint4(pack2(__uint_as_float(a.x) + vd[0], __uint_as_float(a.y) + vd[1]), pack2(__uint_as_float(a.z) + vd[2], __uint_as_float(a.w) + vd[3]),
                            pack2(__uint_as_float(b.x) + ve[0], __uint_as_float(b.y) + ve[1]), pack2(__uint_as_float(b.z) + ve[2], __uint_as_float(b.w) + ve[3]));
            st_async_v4(tb.z ^ (1u << 24), vb, (sb + RB_V) ^ (1u << 24));
        }
        if (w == 0) PROF(11);
        if (s != NSEG - 1) {
            uint32_t vx[16];
            const uint32_t vxa = ta.x + (s & 1) * 16384;
            mbar_wait(sb + RB_KV + (s & 1) * 8, (s >> 1) & 1);
            ldsm4t(vx[0], vx[1], vx[2], vx[3], vxa);
            ldsm4t(vx[4], vx[5], vx[6], vx[7], vxa ^ 32);
            ldsm4t(vx[8], vx[9], vx[10], vx[11], vxa + 2048);
            ldsm4t(vx[12], vx[13], vx[14], vx[15], (vxa ^ 32) + 2048);
#pragma unroll
            for (int i = 0; i < 4; i++) {
                const uint4 f0 = lds128(tab + 4096 + i * 2048);
                wo[i >> 1][(i & 1) * 4][0] = f0.x; wo[i >> 1][(i & 1) * 4][1] = f0.y; wo[i >> 1][(i & 1) * 4][2] = f0.z; wo[i >> 1][(i & 1) * 4][3] = f0.w;
            }
            bar_sync(NB_S, 320);
            if (w == 0) PROF(4);
            float sv[10];
#pragma unroll
            for (int n = 0; n < 5; n++) { const float2 a = lds64f(tb.w + n * 256); sv[2 * n] = a.x; sv[2 * n + 1] = a.y; }
            { const float2 a = lds64f(tb.w + 5 * 256); sv[0] += a.x; sv[1] += a.y; }
            float mx = fmaxf(fmaxf(fmaxf(sv[2], sv[3]), fmaxf(sv[4], sv[5])), fmaxf(fmaxf(sv[6], sv[7]), fmaxf(sv[8], sv[9])));
            mx = fmaxf(mx, fmaxf(sv[0], sv[1]));
            mx = fmaxf(mx, __shfl_xor_sync(~0u, mx, 1));
            mx = fmaxf(mx, __shfl_xor_sync(~0u, mx, 2));
            mbar_wait(sb + RB_V, s & 1);
            const uint4 vo = lds128(tb.z);
            uint32_t pf[5];
#pragma unroll
            for (int n = 0; n < 5; n++) pf[n] = pack2(ex2(sv[2 * n] - mx), ex2(sv[2 * n + 1] - mx));
            vb = make_uint4(hadd2(vb.x, vo.x), hadd2(vb.y, vo.y), hadd2(vb.z, vo.z), hadd2(vb.w, vo.w));
            if (w == 0) PROF(12);
            float oa[4][4] = {{0.f, 0.f, 0.f, 0.f}, {0.f, 0.f, 0.f, 0.f}, {0.f, 0.f, 0.f, 0.f}, {0.f, 0.f, 0.f, 0.f}}, sm[4] = {0.f, 0.f, 0.f, 0.f};
            const uint32_t one = 0x3F803F80u;
            mma1688h(sm, pf[0], one);
            mma1688h(oa[0], pf[0], vb.x);
            mma1688h(oa[1], pf[0], vb.y);
            mma1688h(oa[2], pf[0], vb.z);
            mma1688h(oa[3], pf[0], vb.w);
            mma16816h(sm, pf[1], pf[2], one, one);
#pragma unroll
            for (int n = 0; n < 4; n++) mma16816h(oa[n], pf[1], pf[2], vx[2 * n], vx[2 * n + 1]);
            mma16816h(sm, pf[3], pf[4], one, one);
#pragma unroll
            for (int n = 0; n < 4; n++) mma16816h(oa[n], pf[3], pf[4], vx[8 + 2 * n], vx[8 + 2 * n + 1]);
            float inv;
            asm("rcp.approx.ftz.f32 %0, %1;" : "=f"(inv) : "f"(sm[0]));
#pragma unroll
            for (int n = 0; n < 4; n++) sts32(ta.y ^ (n << 4), pack2(oa[n][0] * inv, oa[n][1] * inv));
            bar_sync(NB_C, 128);
            if (w == 0) PROF(5);
            uint32_t ob[16];
            ldsm4(ob[0], ob[1], ob[2], ob[3], ta.w);
            ldsm4(ob[8], ob[9], ob[10], ob[11], ta.w + 1024);
            ldsm4(ob[4], ob[5], ob[6], ob[7], ta.w ^ 64);
            ldsm4(ob[12], ob[13], ob[14], ob[15], (ta.w ^ 64) + 1024);
#pragma unroll
            for (int i = 4; i < 8; i++) {
                const uint4 f0 = lds128(tab + 4096 + i * 2048);
                wo[i >> 1][(i & 1) * 4][0] = f0.x; wo[i >> 1][(i & 1) * 4][1] = f0.y; wo[i >> 1][(i & 1) * 4][2] = f0.z; wo[i >> 1][(i & 1) * 4][3] = f0.w;
            }
#pragma unroll
            for (int jj = 0; jj < 2; jj++) {
                if (jj == 1 && tb.w == 0) break;
                float acc[4][4];
#pragma unroll
                for (int c = 0; c < 4; c++) { acc[c][0] = acc[c][1] = acc[c][2] = acc[c][3] = 0.f; }
#pragma unroll
                for (int k4 = 0; k4 < 4; k4++)
#pragma unroll
                    for (int c = 0; c < 4; c++) {
                        const int tl = jj * 2 + (c >> 1), ks = (c & 1) * 4 + k4;
                        mma16816(acc[c], wo[tl][ks][0], wo[tl][ks][1], wo[tl][ks][2], wo[tl][ks][3], ob[2 * ks], ob[2 * ks + 1]);
                    }
                uint4 v;
                v.x = pack2(acc[0][0] + acc[1][0], acc[0][1] + acc[1][1]);
                v.y = pack2(acc[0][2] + acc[1][2], acc[0][3] + acc[1][3]);
                v.z = pack2(acc[2][0] + acc[3][0], acc[2][1] + acc[3][1]);
                v.w = pack2(acc[2][2] + acc[3][2], acc[2][3] + acc[3][3]);
                st_async_v4(tb.x + (jj << 24), v, tb.y + (jj << 24));
            }
            if (w == 0) PROF(6);
        } else {
            mbar_wait(sb + RB_V, s & 1);
            const uint4 o = lds128(tb.z);
            vb = make_uint4(hadd2(vb.x, o.x), hadd2(vb.y, o.y), hadd2(vb.z, o.z), hadd2(vb.w, o.w));
            mbar_wait(sb + RB_Q, s & 1);
            mbar_wait(sb + RB_K, s & 1);
        }
        if ((w >> 1) == rank) stsm4t(ta.z + (s & 1) * 1024, vb.x, vb.y, vb.z, vb.w);
        bar_sync(NB_C, 128);
        if (s != NSEG - 1 && w == 0 && lane16 == sb) mbar_expect_tx(sb + RB_V, 2048);
#pragma unroll
        for (int i = 0; i < 8; i++) av[i] = lds128(lane16 + R_WV + ((2 * w + (i >> 2)) * 16 + (i & 3)) * 512);
    }
    {
        const uint4 tp = lds128(tab + 20480);
        rec_store_kvm(tp.z, (char*)(((uint64_t)tp.y << 32) | tp.x), NSEG - 1, w);
    }
    bar_sync(NB_C, 128);
    if (w == 0 && lane == 0) red_release(&g_flags[F_MEM + NRB - 1], 1);
}

__global__ void __launch_bounds__(384, 1) k_rec(const __grid_constant__ RecParams p) {
    extern __shared__ __align__(1024) unsigned char smem_raw[];
    const uint32_t sb = __shfl_sync(~0u, smem_u32(smem_raw), 0);
    const int warp = __shfl_sync(~0u, threadIdx.x >> 5, 0);
    int lane; asm volatile("mov.u32 %0, %%laneid;" : "=r"(lane));
    const int crank = blockIdx.x & 15, slot = blockIdx.x >> 4;
    asm volatile("griddepcontrol.launch_dependents;");
    if (crank == 0 && threadIdx.x == 0) {
        stg_relaxed32(&g_F[65536 + slot * 64], 0u);
        stg_relaxed32(&g_F[65536 + 1024 + slot * 64], 0u);
    }
    if (threadIdx.x == 0) {
        mbar_init(sb + RB_Q, 5); mbar_init(sb + RB_K, 5); mbar_init(sb + RB_V, 1); mbar_init(sb + RB_E, 1); mbar_init(sb + RB_A, 1); mbar_init(sb + RB_ROLE, 1);
        mbar_init(sb + RB_KV, 1); mbar_init(sb + RB_KV + 8, 1);
        asm volatile("fence.mbarrier_init.release.cluster;" ::: "memory");
        mbar_expect_tx(sb + RB_Q, 2048);
        mbar_expect_tx(sb + RB_K, 2048);
        mbar_expect_tx(sb + RB_V, 2048);
        mbar_expect_tx(sb + RB_E, 4096);
        mbar_expect_tx(sb + RB_A, 4096);
        mbar_expect_tx(sb + RB_ROLE, 4);
    }
    asm volatile("barrier.cluster.arrive.relaxed.aligned;\nbarrier.cluster.wait.aligned;" ::: "memory");
    unsigned role = 0;
    if (crank == 0 && threadIdx.x == 0 && !p.only_pre) {
        unsigned x = 0;
        int tm[2] = {0x7fffffff, 0x7fffffff};
#pragma unroll 1
        for (int i = 0; i < 6; i++) {
            const uint32_t t0 = clk32();
            x = atomicAdd(&g_F[65536 + (i & 1) * 1024 + slot * 64 + (x >> 31)], 1u);
            if (x != (unsigned)(i >> 1)) sts32(sb + R_BAR + 80, x);
            const int dt = (int)(clk32() - t0);
            if (i >= 2) { if (i & 1) tm[1] = min(tm[1], dt); else tm[0] = min(tm[0], dt); }
        }
        const int side = tm[1] > tm[0];
        const unsigned old = atomicAdd(&g_flags[F_SIDE + side * 32], 1u);
        unsigned c0, c1; int gd = 0;
#pragma unroll 1
        do { c0 = ldg_relaxed32(&g_flags[F_SIDE]); c1 = ldg_relaxed32(&g_flags[F_SIDE + 32]); } while ((int)(c0 + c1) < p.ncl && ++gd < 64 * SPIN_LIMIT);
        const int big = c1 > c0;
        role = side == big ? old : (big ? c1 : c0) + old;
        role |= (big ^ 1) << 8;
    }
    __syncwarp();
    if (crank == 0 && warp == 0 && !p.only_pre) {
        role = __shfl_sync(~0u, role, 0);
        if (lane < 16)
            asm volatile("st.async.weak.shared::cluster.mbarrier::complete_tx::bytes.u32 [%0], %1, [%2];"
                         :: "r"(mapa_u32(sb + R_BAR + 72, lane)), "r"(role), "r"(mapa_u32(sb + RB_ROLE, lane)) : "memory");
    }
    if (warp >= 4) {
        const int w8 = warp - 4, nblk = gridDim.x;
        const int cq = lane & 3, rg = w8 * 8 + (lane >> 2);
        const uint32_t red = sb + R_VP;
        const int row0 = blockIdx.x * 8 + w8;
        const uint4* xr = (const uint4*)(p.x + (size_t)row0 * D_);
        uint4 xa = __ldg(xr + lane), xb = __ldg(xr + 32 + lane);
#pragma unroll 1
        for (int sl = blockIdx.x; sl < 96; sl += nblk) {
            uint4 wv[8];
#pragma unroll
            for (int i = 0; i < 8; i++) wv[i] = __ldg((const uint4*)(p.w_mod + (size_t)(rg * 8 + i) * (6 * D_) + sl * 32 + cq * 8));
            const uint32_t cw = __ldg((const uint32_t*)(p.c + rg * 8) + cq);
            const float cl = bflo(cw), ch = bfhi(cw);
            const uint32_t sw = pack2(__fdividef(cl, 1.f + __expf(-cl)), __fdividef(ch, 1.f + __expf(-ch)));
            float a[8];
#pragma unroll
            for (int i = 0; i < 8; i++) a[i] = 0.f;
#pragma unroll
            for (int i = 0; i < 8; i++) {
                const uint32_t sv = __shfl_sync(~0u, sw, (lane & 28) + (i >> 1));
                const float cv = (i & 1) ? bfhi(sv) : bflo(sv);
                a[0] = fmaf(cv, bflo(wv[i].x), a[0]); a[1] = fmaf(cv, bfhi(wv[i].x), a[1]); a[2] = fmaf(cv, bflo(wv[i].y), a[2]); a[3] = fmaf(cv, bfhi(wv[i].y), a[3]);
                a[4] = fmaf(cv, bflo(wv[i].z), a[4]); a[5] = fmaf(cv, bfhi(wv[i].z), a[5]); a[6] = fmaf(cv, bflo(wv[i].w), a[6]); a[7] = fmaf(cv, bfhi(wv[i].w), a[7]);
            }
#pragma unroll
            for (int i = 0; i < 8; i++) { a[i] += __shfl_xor_sync(~0u, a[i], 4); a[i] += __shfl_xor_sync(~0u, a[i], 8); a[i] += __shfl_xor_sync(~0u, a[i], 16); }
            if (lane < 4) {
                sts128(red + w8 * 128 + lane * 32, make_uint4(__float_as_uint(a[0]), __float_as_uint(a[1]), __float_as_uint(a[2]), __float_as_uint(a[3])));
                sts128(red + w8 * 128 + lane * 32 + 16, make_uint4(__float_as_uint(a[4]), __float_as_uint(a[5]), __float_as_uint(a[6]), __float_as_uint(a[7])));
            }
            bar_sync(NB_B, 256);
            if (w8 == 0) {
                float v = 0.f;
#pragma unroll
                for (int i = 0; i < 8; i++) v += lds32f(red + i * 128 + lane * 4);
                g_mod[sl * 32 + lane] = __float2bfloat16_rn(v);
                __syncwarp();
                if (lane == 0) red_release(&g_flags[F_MOD + (sl >= 32)], 1);
            }
            bar_sync(NB_B, 256);
        }
        uint32_t c1[8], sm[8];
        int row = row0;
#pragma unroll 1
        while (true) {
            const uint32_t v[8] = {xa.x, xa.y, xa.z, xa.w, xb.x, xb.y, xb.z, xb.w};
            uint32_t mu2, r[8]; float rden;
            ln_stats(v, mu2, rden);
            if (row == row0) {
                if (lane == 0) wait_flag(F_MOD, 32);
                __syncwarp();
                load_mod8(g_mod + D_, lane, c1);
                load_mod8(g_mod, lane, sm);
#pragma unroll
                for (int i = 0; i < 8; i++) c1[i] = hadd2(c1[i], 0x3F803F80u);
            } else if (row + 512 < S_) {
                xr = (const uint4*)(p.x + (size_t)(row + 512) * D_); xa = __ldg(xr + lane); xb = __ldg(xr + 32 + lane);
            }
            ln_apply(v, mu2, rden, c1, sm, r);
            uint4* hr = (uint4*)(g_h + (size_t)row * D_);
            hr[lane] = make_uint4(r[0], r[1], r[2], r[3]); hr[32 + lane] = make_uint4(r[4], r[5], r[6], r[7]);
            bar_sync(NB_B, 256);
            if (w8 == (row >> 7 & 7) && lane == 0) red_release(&g_flags[F_H + (row >> 7)], 1);
            __syncwarp();
            if (row == row0) {
                if (!p.only_pre) mbar_wait(sb + RB_ROLE, 0);
                const int cl = p.only_pre ? slot : (int)(lds32(sb + R_BAR + 72) & 255);
                row = cl < 4 ? (nblk + cl * 16 + crank) * 8 + w8 : S_;
                if (row < S_) { xr = (const uint4*)(p.x + (size_t)row * D_); xa = __ldg(xr + lane); xb = __ldg(xr + 32 + lane); }
            } else {
                row += 512;
            }
            if (row >= S_) break;
        }
    }
    if (p.only_pre) return;
    mbar_wait(sb + RB_ROLE, 0);
    const int rolew = __shfl_sync(~0u, lds32(sb + R_BAR + 72), 0);
    const int cl = rolew & 255;
    if (cl >= 4) return;
    const int cta = cl * 16 + crank;
    if (warp < 8) rec_qk(p, sb, cta, warp, lane, rolew >> 8);
    else rec_vo(p, sb, cta, warp, lane);
}

enum { J_KV = 0, J_QA = 1, J_O = 2, J_LN = 3, J_UP = 4, J_DN = 5, J_UP2 = 8, J_END = 9 };
constexpr int NJ_O = 2 * OSPLIT, NJ_O2 = 2 * OSPLIT2, NJ_LN = 8, NJ_LN2 = 16, NJ_UP = 14, NJ_UP2 = 28, NJ_DN = 8, NJ_LN1 = 8  ;
constexpr uint64_t pk8(int a, int b, int c, int d, int e, int f, int g, int h) {
    return (uint64_t)a | ((uint64_t)b << 8) | ((uint64_t)c << 16) | ((uint64_t)d << 24) | ((uint64_t)e << 32) | ((uint64_t)f << 40) | ((uint64_t)g << 48) | ((uint64_t)h << 56);
}
constexpr uint64_t NJ_C = pk8(32, 16, NJ_O, NJ_LN, NJ_UP, NJ_DN, 0, 0), NJ_F = pk8(32, 16, NJ_O2, NJ_LN2, NJ_UP2, NJ_DN, 0, 0);
constexpr uint64_t TG_C = pk8(2 * NJ_LN1, 64, 32, 2 * NJ_O, 2 * NJ_LN, 2 * NJ_UP, 32, 0), TG_F = pk8(2 * NJ_LN1, 64, 32, 2 * NJ_O2, 2 * NJ_LN2, 2 * NJ_UP2, 32, 0);
constexpr uint64_t NJ_L = pk8(32, 32, 2 * OSPLIT3, NJ_LN2, NJ_UP2, 2 * NJ_DN, 0, 0), TG_L = pk8(2 * NJ_LN1, 64, 64, 4 * OSPLIT3, 2 * NJ_LN2, 2 * NJ_UP2, 32, 0);
__device__ __forceinline__ uint64_t nj_tab(int rb) { return rb < FINE_RB ? NJ_C : (rb < NRB - 1 ? NJ_F : NJ_L); }
__device__ __forceinline__ uint64_t tg_tab(int rb) { return rb < FINE_RB ? TG_C : (rb < NRB - 1 ? TG_F : TG_L); }
__device__ __forceinline__ int o_nk(int rb) { return rb < FINE_RB ? 64 / OSPLIT : (rb < NRB - 1 ? 64 / OSPLIT2 : 64 / OSPLIT3); }
constexpr uint64_t PRIO = pk8(4, 10, 9, 8, 7, 6, 3, 0);
__device__ __forceinline__ int pick_job(int lane, int qmask, int& idx) {
    const int rb = lane & 15, half = lane >> 4;
    const uint64_t nj = nj_tab(rb) >> (8 * half);
    const uint64_t tg = tg_tab(rb) >> (8 * half);
    const unsigned* cp = &g_flags[F_CLAIM + half * 32 + rb];
    const unsigned* dp = &g_flags[half * 32 + rb];
    int gd = 0;
#pragma unroll 1
    while (true) {
        const unsigned c0 = ldg_relaxed32(cp), c1 = ldg_relaxed32(cp + 64), c2 = ldg_relaxed32(cp + 128);
        const unsigned d0 = ldg_relaxed32(dp - (half && rb ? 1 : 0)), d1 = ldg_relaxed32(dp + 64), d2 = ldg_relaxed32(dp + 128);
        const unsigned cl[3] = {c0, c1, c2}, dv[3] = {d0, d1, d2};
        unsigned key = 0xffffu, key2 = 0xffffu;
        bool pre = false;
#pragma unroll
        for (int i = 0; i < 3; i++) {
            const int q = half + 2 * i;
            const bool have = ((qmask >> q) & 1) && cl[i] < (unsigned)((nj >> (16 * i)) & 255);
            bool ready = have && dv[i] >= (unsigned)((tg >> (16 * i)) & 255);
            unsigned pr = (unsigned)((PRIO >> (8 * q)) & 255);
            if (i == 0 && rb <= 1 - half) ready = have;
            if (i == 0 && half && rb >= FINE_RB) pr = 5;
            if (ready) key = min(key, (pr << 8) | (rb << 4) | q);
            if (have) key2 = min(key2, rb >= FINE_RB ? (0x100u | (q << 4) | rb) : (i == 0 ? 0u : 0x1000u));
            pre |= have && i == 0 && !half;
        }
        const bool anypre = __any_sync(~0u, pre);
        if (anypre && (key & 15) == J_QA) key = 0xffffu;
        key = __reduce_min_sync(~0u, key);
        key2 = __reduce_min_sync(~0u, key2);
        if (key2 == 0xffffu) return J_END;
        int pq, prb;
        if (key != 0xffffu) { pq = key & 15; prb = (key >> 4) & 15; }
        else if (key2 >= 0x120u && key2 < 0x1000u) { pq = (key2 >> 4) & 15; prb = key2 & 15; }
        else {
            __nanosleep(IDLE_NS);
            if (++gd > 16 * SPIN_LIMIT) { TIMEOUT(5, 0); return J_END; }
            continue;
        }
        int c = 0;
        if (lane == 0) c = (int)atomicAdd(&g_flags[F_CLAIM + pq * 32 + prb], 1u);
        c = __shfl_sync(~0u, c, 0);
        if (c < (int)((nj_tab(prb) >> (8 * pq)) & 255)) {
            idx = pq * 512 + prb * 32 + c;
            int acq = 0;
            if (pq != J_QA) {
                if (lane == 0 && ld_acquire(&g_flags[pq * 32 + prb]) >= (unsigned)((tg_tab(prb) >> (8 * pq)) & 255)) {
                    asm volatile("fence.proxy.async.global;" ::: "memory");
                    acq = 1 << 24;
                }
            }
            return (pq == J_UP && prb >= FINE_RB ? J_UP2 : pq) | (prb << 8) | (c << 16) | acq;
        }
    }
}
__device__ __forceinline__ int op_row(int rb, int split) {
    return rb < FINE_RB ? split * S_ + rb * 128
                        : (rb < NRB - 1 ? OSPLIT * S_ + (split * (NRB - FINE_RB) + rb - FINE_RB) * 128 : OSPLIT * S_ + (OSPLIT2 * (NRB - FINE_RB) + split) * 128);
}

struct Pipe { uint32_t stage, phase; };
__device__ __forceinline__ void pipe_next(Pipe& p) { if (++p.stage == W_NST) { p.stage = 0; p.phase ^= 1; } }

__device__ __forceinline__ void scheduler(const Params& p, uint32_t sb, int lane) {
    const uint32_t bars = sb + SM_BAR;
    uint32_t ph = 0;
#pragma unroll 1
    while (true) {
        mbar_wait(bars + B_REQ, ph);
        int j = 4095;
        const int jd = pick_job(lane, p.qmask, j);
        if (lane == 0) { sts32(bars + B_NEXT, (uint32_t)jd); sts32(bars + B_NEXT + 4, (uint32_t)j); mbar_arrive(bars + B_RSP); }
        ph ^= 1;
        if (jd == J_END) break;
        __syncwarp();
    }
}

__device__ __forceinline__ void producer(const Params& p, uint32_t sb) {
    Pipe pp{0, 1};
    const uint32_t bars = sb + SM_BAR;
    uint32_t seq = 0, h_seen = 0;
    mbar_arrive(bars + B_REQ);
#pragma unroll 1
    while (true) {
        mbar_wait(bars + B_RSP, seq & 1);
        const int jd = (int)lds32(bars + B_NEXT), j = (int)lds32(bars + B_NEXT + 4);
        int left = (jd & 255) == J_DN ? 15 : ((jd & 255) == J_QA ? (((jd >> 8) & 255) == NRB - 1 ? 10 : 12) : ((jd & 255) == J_O ? o_nk((jd >> 8) & 255) : ((jd & 255) == J_LN ? 1 : 8)));
        left = max(left - PICK_AHEAD, 1);
        TR(j, 1);
        const int type = jd & 255, rb = (jd >> 8) & 255, cb = (jd >> 16) & 255;
        const bool fine = rb >= FINE_RB, acquired = (jd >> 24) & 1;
        bool first = true;
        auto begin_stage = [&](uint32_t bytes) -> uint32_t {
            mbar_wait(bars + B_EMPTY + pp.stage * 8, pp.phase);
            if (first) { sts32(bars + B_RING + (seq & 7) * 4, (uint32_t)jd); sts32(bars + B_RING + 32 + (seq & 7) * 4, (uint32_t)j); first = false; }
            const uint32_t fb = bars + B_FULL + pp.stage * 8;
            if (bytes) mbar_expect_tx(fb, bytes); else mbar_arrive(fb);
            if (--left == 0 && type != J_END) mbar_arrive(bars + B_REQ);
            return fb;
        };
        if (type == J_END || type == J_LN) {
            if (type == J_LN && !(h_seen >> 31)) { wait_flag(F_MOD + 1, 64); h_seen |= 1u << 31; }

            TR(j, 2);
            begin_stage(0); pipe_next(pp);
            seq++;
            if (type == J_END) break;
            continue;
        }
        const CUtensorMap *ta, *tb0, *tb1;
        int k0 = 0, nk = 8, n0 = cb * 256, n1 = n0 + 128, nb = 4, dep = -1;
        unsigned tgt = 0;
        switch (type) {
            case J_KV: ta = &p.tm_h; tb0 = tb1 = cb < 16 ? &p.tm_wk : &p.tm_wv; n0 = (cb & 15) * 256; n1 = n0 + 128; dep = F_H + rb; tgt = 2 * NJ_LN1; break;
            case J_QA: ta = &p.tm_h; tb0 = tb1 = &p.tm_wq; dep = F_H + rb; tgt = 2 * NJ_LN1; if (rb == NRB - 1) { n0 = (cb >> 1) * 256; n1 = n0 + 128; } break;
            case J_O: ta = &p.tm_o; tb0 = tb1 = &p.tm_wo; n0 = (cb & 1) * 256; n1 = n0 + 128; nk = o_nk(rb); k0 = (cb >> 1) * nk * 64;
                      dep = F_O + rb; tgt = rb == NRB - 1 ? 64 : 32; break;
            case J_UP: ta = &p.tm_h2; tb0 = &p.tm_wg; tb1 = &p.tm_wu; n0 = n1 = cb * 128; dep = F_H2 + rb; tgt = 2 * NJ_LN; break;
            case J_UP2: ta = &p.tm_h2; tb0 = &p.tm_wg; tb1 = &p.tm_wu; n0 = n1 = cb * 64; nb = 2; dep = F_H2 + rb; tgt = 2 * NJ_LN2; break;
            default: ta = &p.tm_act; tb0 = tb1 = &p.tm_wd; n0 = cb * 64; nk = 0; break;
        }
        const int m0 = rb * 128;
        if (type == J_DN && rb == NRB - 1) {
            n0 = (cb >> 1) * 64;
            const int mh = m0 + (cb & 1) * 64;
#pragma unroll 1
            for (int kb = 0; kb < 14; kb++) {
                const uint32_t fb = begin_stage(32768);
                const uint32_t st = sb + pp.stage * W_STAGE;
                const int k = kb * 128;
                tma_load2d(st + 32768, tb0, n0, k, fb);
                tma_load2d(st + 40960, tb0, n0, k + 64, fb);
                if (kb == 0) { if (!acquired) { wait_flag(F_ACT + rb, 2 * NJ_UP2); asm volatile("fence.proxy.async.global;" ::: "memory"); } TR(j, 2); }
                tma_load2d(st, ta, k, mh, fb);
                tma_load2d(st + 8192, ta, k + 64, mh, fb);
                pipe_next(pp);
            }
            const uint32_t fb = begin_stage(8192);
            tma_load2d(sb + pp.stage * W_STAGE, &p.tm_x1, n0, mh, fb);
            pipe_next(pp);
            seq++;
            continue;
        }
        if (type == J_DN) {
#pragma unroll 1
            for (int kb = 0; kb < 14; kb++) {
                const uint32_t fb = begin_stage(49152);
                const uint32_t st = sb + pp.stage * W_STAGE;
                const int k = kb * 128;
                tma_load2d(st + 32768, tb0, n0, k, fb);
                tma_load2d(st + 40960, tb0, n0, k + 64, fb);
                if (kb == 0) { if (!acquired) { wait_flag(F_ACT + rb, 2 * (fine ? NJ_UP2 : NJ_UP)); asm volatile("fence.proxy.async.global;" ::: "memory"); } TR(j, 2); }
                tma_load2d(st, ta, k, m0, fb);
                tma_load2d(st + 8192, ta, k, m0 + 64, fb);
                tma_load2d(st + 16384, ta, k + 64, m0, fb);
                tma_load2d(st + 24576, ta, k + 64, m0 + 64, fb);
                pipe_next(pp);
            }
        }
#pragma unroll 1
        for (int kb = 0; kb < nk; kb++) {
            const uint32_t fb = begin_stage(16384 + nb * 8192);
            const uint32_t st = sb + pp.stage * W_STAGE;
            const int k = k0 + kb * 64;
            tma_load2d(st + 16384, tb0, n0, k, fb);
            if (nb == 4) {
                tma_load2d(st + 16384 + 8192, tb0, n0 + 64, k, fb);
                tma_load2d(st + 16384 + 16384, tb1, n1, k, fb);
                tma_load2d(st + 16384 + 24576, tb1, n1 + 64, k, fb);
            } else if (nb == 2) {
                tma_load2d(st + 16384 + 8192, tb1, n1, k, fb);
            }
            if (kb == 0) {
                if (acquired && dep < 16) h_seen |= 1u << dep;
                if (dep >= 0 && !acquired && !(dep < 16 && ((h_seen >> dep) & 1))) {
                    wait_flag(dep, tgt);
                    if (type != J_O) asm volatile("fence.proxy.async.global;" ::: "memory");
                    if (dep < 16) h_seen |= 1u << dep;
                }
                TR(j, 2);
            }
            tma_load2d(st, ta, k, m0, fb);
            tma_load2d(st + 8192, ta, k, m0 + 64, fb);
            pipe_next(pp);
        }
        if (type == J_QA) {
            wait_flag(F_KV + rb, 64);
#pragma unroll 1
            for (int i = 0; i < (rb == NRB - 1 ? 2 : 4); i++) {
                const uint32_t fb = begin_stage(40960);
                const uint32_t st = sb + pp.stage * W_STAGE;
                const int col = (i & 1) * HD_ + (rb == NRB - 1 ? cb : cb * 2 + (i >> 1)) * DH_;
                tma_load2d(st, &p.tm_kv, col, m0, fb);
                tma_load2d(st + 8192, &p.tm_kv, col, m0 + 64, fb);
                tma_load2d(st + 16384, &p.tm_kv, col + 64, m0, fb);
                tma_load2d(st + 24576, &p.tm_kv, col + 64, m0 + 64, fb);
                if (i == 0) { wait_flag(F_MEM + rb, 64); asm volatile("fence.proxy.async.global;" ::: "memory"); }
                tma_load2d(st + 32768, &p.tm_kvm, col, rb * 32, fb);
                tma_load2d(st + 36864, &p.tm_kvm, col + 64, rb * 32, fb);
                pipe_next(pp);
            }
        } else if (type == J_DN) {
            const uint32_t fb = begin_stage(16384);
            const uint32_t st = sb + pp.stage * W_STAGE;
            tma_load2d(st, &p.tm_x1, n0, m0, fb);
            tma_load2d(st + 8192, &p.tm_x1, n0, m0 + 64, fb);
            pipe_next(pp);
        }
        seq++;
    }
}

__device__ __forceinline__ void store_warp(const Params& p, uint32_t sb, int wg, int lane) {
    const uint32_t bars = sb + SM_BAR;
    uint32_t seq = 0;
#pragma unroll 1
    while (true) {
        bar_sync(NB_ST + wg, 160);
        const uint32_t jd = lds32(bars + B_RING + (seq & 7) * 4);
        seq++;
        const int type = jd & 255, rb = (jd >> 8) & 255, cb = (jd >> 16) & 255;
        if (type == J_END) break;
        const uint32_t src = sb + W_STG + wg * 16384;
        const CUtensorMap* tm = nullptr; int n0 = cb * 256, nbox = 4, mrow = rb * 128 + wg * 64, flag = 0;
        switch (type) {
            case J_KV: tm = &p.tm_kv; flag = F_KV + rb; break;
            case J_QA: tm = &p.tm_o; flag = F_O + rb; if (rb == NRB - 1) { n0 = cb * 128; nbox = 2; } break;
            case J_O: tm = &p.tm_op; n0 = (cb & 1) * 256; mrow = op_row(rb, cb >> 1) + wg * 64; flag = F_OP + rb; break;
            case J_LN: flag = F_H2 + rb; nbox = 0; break;
            case J_UP: tm = &p.tm_act; n0 = cb * 128; nbox = 2; flag = F_ACT + rb; break;
            case J_UP2: tm = &p.tm_act; n0 = cb * 64; nbox = 1; flag = F_ACT + rb; break;
            default: tm = &p.tm_out; n0 = cb * 64; nbox = 1; flag = -1;
                     if (rb == NRB - 1) { n0 = (cb >> 1) * 64; mrow = rb * 128 + (cb & 1) * 64; nbox = wg == 0; } break;
        }
        if (nbox == 4) {
            if (lane == 0) {
                tma_store2d(tm, src, n0, mrow);
                tma_store2d(tm, src + 8192, n0 + 64, mrow);
                bulk_commit();
                asm volatile("cp.async.bulk.wait_group.read 0;" ::: "memory");
                mbar_arrive(bars + B_STGFREE + wg * 8);
            }
            __syncwarp();
            bar_sync(NB_ST + wg, 160);
            n0 += 128; nbox = 2;
        }
        if (lane == 0) {
            if (nbox) {
                tma_store2d(tm, src, n0, mrow);
                if (nbox == 2) tma_store2d(tm, src + 8192, n0 + 64, mrow);
                bulk_commit();
                asm volatile("cp.async.bulk.wait_group.read 0;" ::: "memory");
                mbar_arrive(bars + B_STGFREE + wg * 8);
                bulk_wait0();
                if (flag >= 0) asm volatile("red.relaxed.gpu.global.add.u32 [%0], 1;" :: "l"(&g_flags[flag]) : "memory");
            } else {
                mbar_arrive(bars + B_STGFREE + wg * 8);
                if (flag >= 0) red_release(&g_flags[flag], 1);
            }
        }
        __syncwarp();
    }
}

__device__ __forceinline__ float gelu_tanh(float x) {
    const float t = x * fmaf(-0.10294324397f, x * x, -2.30220819814f);
    float r; asm("rcp.approx.ftz.f32 %0, %1;" : "=f"(r) : "f"(1.f + ex2(t)));
    return x * r;
}

#define CTR(i) do {} while (0)

__device__ __forceinline__ void ln2_row(const Params& p, int rb, int r, int lane, bool wait) {
    const int row = rb * 128 + r, nsplit = 64 / o_nk(rb);
    const uint4* xr = (const uint4*)(p.x + (size_t)row * D_);
    const uint4 xa = __ldg(xr + lane), xb = __ldg(xr + 32 + lane);
    uint32_t ga[8], c1[8], sm[8];
    load_mod8(g_mod + 2 * D_, lane, ga);
    load_mod8(g_mod + 4 * D_, lane, c1);
    load_mod8(g_mod + 3 * D_, lane, sm);
    float a[16];
#pragma unroll
    for (int i = 0; i < 16; i++) a[i] = 0.f;
    const uint4* src = (const uint4*)(g_op + (size_t)(op_row(rb, 0) + r) * D_) + lane;
    const int sstride = (op_row(rb, 1) - op_row(rb, 0)) * (D_ / 8);
    if (wait) { if (lane == 0) wait_flag(F_OP + rb, 4 * nsplit); __syncwarp(); }
    uint4 u[2][8];
#pragma unroll
    for (int sp = 0; sp < 4; sp++) { u[0][2 * sp] = __ldcg(src + sp * sstride); u[0][2 * sp + 1] = __ldcg(src + sp * sstride + 32); }
    if (nsplit > 4) {
#pragma unroll
        for (int sp = 0; sp < 4; sp++) { u[1][2 * sp] = __ldcg(src + (4 + sp) * sstride); u[1][2 * sp + 1] = __ldcg(src + (4 + sp) * sstride + 32); }
    }
#pragma unroll 1
    for (int s0 = 0; s0 < nsplit; s0 += 4) {
#pragma unroll
        for (int sp = 0; sp < 8; sp++) {
            float* q = a + (sp & 1) * 8;
            const uint4 w = u[0][sp];
            q[0] += bflo(w.x); q[1] += bfhi(w.x); q[2] += bflo(w.y); q[3] += bfhi(w.y);
            q[4] += bflo(w.z); q[5] += bfhi(w.z); q[6] += bflo(w.w); q[7] += bfhi(w.w);
            u[0][sp] = u[1][sp];
        }
        if (s0 + 8 < nsplit) {
#pragma unroll
            for (int sp = 0; sp < 4; sp++) { u[1][2 * sp] = __ldcg(src + (s0 + 8 + sp) * sstride); u[1][2 * sp + 1] = __ldcg(src + (s0 + 8 + sp) * sstride + 32); }
        }
    }
    const uint32_t xv[8] = {xa.x, xa.y, xa.z, xa.w, xb.x, xb.y, xb.z, xb.w};
    uint32_t v[8], r8[8];
#pragma unroll
    for (int i = 0; i < 8; i++) v[i] = hadd2(xv[i], hmul2(ga[i], pack2(a[2 * i], a[2 * i + 1])));
    uint4* x1r = (uint4*)(g_x1 + (size_t)row * D_);
    x1r[lane] = make_uint4(v[0], v[1], v[2], v[3]); x1r[32 + lane] = make_uint4(v[4], v[5], v[6], v[7]);
    uint32_t mu2; float rden;
    ln_stats(v, mu2, rden);
#pragma unroll
    for (int i = 0; i < 8; i++) c1[i] = hadd2(c1[i], 0x3F803F80u);
    ln_apply(v, mu2, rden, c1, sm, r8);
    uint4* hr = (uint4*)(g_h2 + (size_t)row * D_);
    hr[lane] = make_uint4(r8[0], r8[1], r8[2], r8[3]); hr[32 + lane] = make_uint4(r8[4], r8[5], r8[6], r8[7]);
}

__device__ __forceinline__ void consumer(const Params& p, uint32_t sb, int warp, int lane) {
    const uint32_t bars = sb + SM_BAR;
    const int wg = warp >> 2, wl = warp & 3;
    const uint32_t l7 = lane & 7, l8 = lane >> 3, g = lane >> 2, t = lane & 3;
    Pipe pp{0, 0};
    uint32_t seq = 0, stg_phase = 1;
    const int srow = wl * 16 + l7 + (l8 & 1) * 8;
    const uint32_t stg_base = sb + W_STG + wg * 16384 + srow * 128;
    const uint32_t sx = ((lane >> 4) ^ (srow & 7)) << 4;
#pragma unroll 1
    while (true) {
        mbar_wait(bars + B_FULL + pp.stage * 8, pp.phase);
        const uint32_t jd = lds32(bars + B_RING + (seq & 7) * 4);
        CTR(3);
        seq++;
        const int type = jd & 255, rb = (jd >> 8) & 255, cb = (jd >> 16) & 255;
        if (type == J_END) { mbar_wait(bars + B_STGFREE + wg * 8, stg_phase); bar_arrive(NB_ST + wg, 160); break; }
        if (type == J_LN) {
            __syncwarp();
            if (lane == 0) mbar_arrive(bars + B_EMPTY + pp.stage * 8);
            pipe_next(pp);
            const int nr = rb >= FINE_RB ? 1 : 2;
#pragma unroll 1
            for (int rr = 0; rr < nr; rr++) ln2_row(p, rb, (cb * 8 + warp) * nr + rr, lane, !((jd >> 24) & 1) && rr == 0);
            mbar_wait(bars + B_STGFREE + wg * 8, stg_phase); stg_phase ^= 1;
            CTR(4); CTR(5);
            bar_arrive(NB_ST + wg, 160);
            continue;
        }
        if (type == J_DN || type == J_UP2) {
            float acc[64];
#pragma unroll
            for (int i = 0; i < 64; i++) acc[i] = 0.f;
            const bool ksplit = type == J_DN && rb == NRB - 1;
            if (ksplit) {
#pragma unroll 1
                for (int kb = 0; kb < 14; kb++) {
                    if (kb) mbar_wait(bars + B_FULL + pp.stage * 8, pp.phase);
                    const uint32_t st = sb + pp.stage * W_STAGE;
                    const uint64_t da = mkdesc(st + wg * 8192, 16, 1024), db = mkdesc(st + 32768 + wg * 8192, 8192, 1024);
                    wg_fence();
#pragma unroll
                    for (int ks = 0; ks < 4; ks++) wgmma_n64(acc, da + ks * 2, db + ks * 128);
                    wg_commit();
                    wg_wait0();
                    if (lane == 0) mbar_arrive(bars + B_EMPTY + pp.stage * 8);
                    pipe_next(pp);
                }
                const uint32_t xb = sb + W_STG + 16384 + (wl * 32 + lane) * 16;
                if (wg == 1) {
                    mbar_wait(bars + B_STGFREE + 8, stg_phase);
#pragma unroll
                    for (int i = 0; i < 8; i++)
                        sts128(xb + i * 2048, make_uint4(__float_as_uint(acc[4 * i]), __float_as_uint(acc[4 * i + 1]), __float_as_uint(acc[4 * i + 2]), __float_as_uint(acc[4 * i + 3])));
                }
                bar_sync(NB_M, 256);
                if (wg == 0) {
#pragma unroll
                    for (int i = 0; i < 8; i++) {
                        const uint4 o = lds128(xb + i * 2048);
                        acc[4 * i] += __uint_as_float(o.x); acc[4 * i + 1] += __uint_as_float(o.y); acc[4 * i + 2] += __uint_as_float(o.z); acc[4 * i + 3] += __uint_as_float(o.w);
                    }
                }
                bar_sync(NB_M, 256);
            } else if (type == J_DN) {
#pragma unroll 1
                for (int kb = 0; kb < 14; kb++) {
                    if (kb) mbar_wait(bars + B_FULL + pp.stage * 8, pp.phase);
                    const uint32_t st = sb + pp.stage * W_STAGE;
                    const uint64_t da = mkdesc(st + wg * 8192, 16, 1024), db = mkdesc(st + 32768, 8192, 1024);
                    wg_fence();
#pragma unroll
                    for (int ks = 0; ks < 8; ks++) wgmma_n64(acc, da + (ks >> 2) * 1024 + (ks & 3) * 2, db + ks * 128);
                    wg_commit();
                    wg_wait0();
                    if (lane == 0) mbar_arrive(bars + B_EMPTY + pp.stage * 8);
                    pipe_next(pp);
                }
            } else {
#pragma unroll 1
                for (int kb = 0; kb < 8; kb++) {
                    if (kb) mbar_wait(bars + B_FULL + pp.stage * 8, pp.phase);
                    const uint32_t st = sb + pp.stage * W_STAGE;
                    const uint64_t da = mkdesc(st + wg * 8192, 16, 1024), db = mkdesc(st + 16384, 8192, 1024);
                    wg_fence();
#pragma unroll
                    for (int ks = 0; ks < 4; ks++) wgmma_n128(acc, da + ks * 2, db + ks * 128, 1);
                    wg_commit();
                    wg_wait0();
                    if (lane == 0) mbar_arrive(bars + B_EMPTY + pp.stage * 8);
                    pipe_next(pp);
                }
            }
            CTR(4);
            if (type == J_UP2) {
                mbar_wait(bars + B_STGFREE + wg * 8, stg_phase); stg_phase ^= 1;
#pragma unroll
                for (int j = 0; j < 4; j++) {
                    uint32_t r[4];
#pragma unroll
                    for (int q = 0; q < 4; q++) {
                        const uint32_t gw = pack2(acc[8 * j + 2 * q], acc[8 * j + 2 * q + 1]);
                        const uint32_t uw = pack2(acc[32 + 8 * j + 2 * q], acc[32 + 8 * j + 2 * q + 1]);
                        r[q] = hmul2(pack2(gelu_tanh(bflo(gw)), gelu_tanh(bfhi(gw))), uw);
                    }
                    stsm4(stg_base + (sx ^ (j << 5)), r[0], r[1], r[2], r[3]);
                }
            } else {
                mbar_wait(bars + B_FULL + pp.stage * 8, pp.phase);
                const uint32_t st = sb + pp.stage * W_STAGE;
                mbar_wait(bars + B_STGFREE + wg * 8, stg_phase); stg_phase ^= 1;
                const uint32_t* gb = (const uint32_t*)(g_mod + 5 * D_ + (ksplit ? cb >> 1 : cb) * 64) + t;
                const uint32_t xa = st + (ksplit ? 0 : wg * 8192) + (wl * 16 + g) * 128 + (g << 4) + t * 4;
#pragma unroll
                for (int j = 0; j < 4; j++) {
                    uint32_t r[4];
#pragma unroll
                    for (int q = 0; q < 4; q++) {
                        const int nt = 2 * j + (q >> 1);
                        const uint32_t xw = lds32((xa ^ ((nt & 7) << 4)) + (nt >> 3) * 16384 + (q & 1) * 1024);
                        r[q] = hadd2(xw, hmul2(__ldcg(gb + nt * 4), pack2(acc[8 * j + 2 * q], acc[8 * j + 2 * q + 1])));
                    }
                    stsm4(stg_base + (j >> 2) * 8192 + (sx ^ ((2 * j & 7) << 4)), r[0], r[1], r[2], r[3]);
                }
                __syncwarp();
                if (lane == 0) mbar_arrive(bars + B_EMPTY + pp.stage * 8);
                pipe_next(pp);
            }
            fence_async_smem();
            CTR(5);
            bar_arrive(NB_ST + wg, 160);
            continue;
        }
        float acc[128];
#pragma unroll
        for (int i = 0; i < 128; i++) acc[i] = 0.f;
        const int nk = type == J_O ? o_nk(rb) : 8;
#pragma unroll 1
        for (int kb = 0; kb < nk; kb++) {
            if (kb) mbar_wait(bars + B_FULL + pp.stage * 8, pp.phase);
            const uint32_t st = sb + pp.stage * W_STAGE;
            const uint64_t da = mkdesc(st + wg * 8192, 16, 1024), db = mkdesc(st + 16384, 8192, 1024);
            wg_fence();
#pragma unroll
            for (int ks = 0; ks < 4; ks++) wgmma_n256(acc, da + ks * 2, db + ks * 128, 1);
            wg_commit();
            wg_wait0();
            if (lane == 0) mbar_arrive(bars + B_EMPTY + pp.stage * 8);
            pipe_next(pp);
        }
        CTR(4);
        if (type == J_QA) {
            uint32_t qf[64];
#pragma unroll
            for (int i = 0; i < 64; i++) qf[i] = pack2(acc[2 * i], acc[2 * i + 1]);
            const int sg = warp >> 1, half = warp & 1;
            const float sc = 0.08838834764831845f * 1.4426950408889634f;
            const uint32_t xoff = (sg >> 1) * 8192 + ((sg & 1) * 32 + l7) * 128;
            const uint32_t moff = 32768 + (sg * 8 + l7) * 128;
            const uint32_t kch = (l8 ^ l7) << 4;
            const uint32_t vch = ((l8 & 1) ^ l7) << 4;
            if (rb == NRB - 1 && (cb & 1)) {
#pragma unroll
                for (int i = 0; i < 32; i++) qf[i] = qf[32 + i];
            }
#pragma unroll 1
            for (int hh = rb == NRB - 1; hh < 2; hh++) {
                mbar_wait(bars + B_FULL + pp.stage * 8, pp.phase);
                uint32_t st = sb + pp.stage * W_STAGE;
                float sa[5][4];
#pragma unroll
                for (int n = 0; n < 5; n++) sa[n][0] = sa[n][1] = sa[n][2] = sa[n][3] = 0.f;
#pragma unroll
                for (int i = 0; i < 4; i++) {
                    const uint32_t* q = qf + i * 8;
                    uint32_t kk[5][4];
                    ldsm4(kk[0][0], kk[0][1], kk[0][2], kk[0][3], st + moff + (i >> 1) * 4096 + (kch ^ ((i & 1) * 64)));
#pragma unroll
                    for (int n = 1; n < 5; n++)
                        ldsm4(kk[n][0], kk[n][1], kk[n][2], kk[n][3], st + xoff + (n - 1) * 1024 + (i >> 1) * 16384 + (kch ^ ((i & 1) * 64)));
#pragma unroll
                    for (int n = 0; n < 5; n++) mma16816(sa[n], q[0], q[1], q[2], q[3], kk[n][0], kk[n][1]);
#pragma unroll
                    for (int n = 0; n < 5; n++) mma16816(sa[n], q[4], q[5], q[6], q[7], kk[n][2], kk[n][3]);
                }
                __syncwarp();
                if (lane == 0) mbar_arrive(bars + B_EMPTY + pp.stage * 8);
                pipe_next(pp);
                const int iq0 = half * 16 + g - 2 * t, iq1 = iq0 + 8;
                float m0 = fmaxf(sa[0][0], sa[0][1]), m1 = fmaxf(sa[0][2], sa[0][3]);
#pragma unroll
                for (int n = 1; n < 5; n++) {
#pragma unroll
                    for (int e = 0; e < 2; e++) {
                        const int jx = (n - 1) * 8 + e;
                        if (jx > iq0) sa[n][e] = -3.0e38f;
                        if (jx > iq1) sa[n][2 + e] = -3.0e38f;
                        m0 = fmaxf(m0, sa[n][e]); m1 = fmaxf(m1, sa[n][2 + e]);
                    }
                }
                m0 = fmaxf(m0, __shfl_xor_sync(~0u, m0, 1)); m1 = fmaxf(m1, __shfl_xor_sync(~0u, m1, 1));
                m0 = fmaxf(m0, __shfl_xor_sync(~0u, m0, 2)); m1 = fmaxf(m1, __shfl_xor_sync(~0u, m1, 2));
                m0 *= -sc; m1 *= -sc;
                float l0 = 0.f, l1 = 0.f;
                uint32_t p0[5], p1[5];
#pragma unroll
                for (int n = 0; n < 5; n++) {
                    const float e0 = ex2(fmaf(sa[n][0], sc, m0)), e1 = ex2(fmaf(sa[n][1], sc, m0));
                    const float e2 = ex2(fmaf(sa[n][2], sc, m1)), e3 = ex2(fmaf(sa[n][3], sc, m1));
                    l0 += e0 + e1; l1 += e2 + e3;
                    p0[n] = pack2(e0, e1); p1[n] = pack2(e2, e3);
                }
                l0 += __shfl_xor_sync(~0u, l0, 1); l1 += __shfl_xor_sync(~0u, l1, 1);
                l0 += __shfl_xor_sync(~0u, l0, 2); l1 += __shfl_xor_sync(~0u, l1, 2);
                const float i0 = __fdividef(1.f, l0), i1 = __fdividef(1.f, l1);
                mbar_wait(bars + B_FULL + pp.stage * 8, pp.phase);
                st = sb + pp.stage * W_STAGE;
                mbar_wait(bars + B_STGFREE + wg * 8, stg_phase); stg_phase ^= 1;
#pragma unroll
                for (int i = 0; i < 32; i++) qf[i] = qf[32 + i];
#pragma unroll 1
                for (int bx = 0; bx < 2; bx++) {
                    float o[8][4];
                    uint32_t vm[8], v0[4][4], v1[4][4];
#pragma unroll
                    for (int ep = 0; ep < 4; ep++) {
                        ldsm2t(vm[2 * ep], vm[2 * ep + 1], st + moff + bx * 4096 + (vch ^ (ep << 5)));
                        const uint32_t va = st + xoff + (l8 >> 1) * 1024 + bx * 16384 + (vch ^ (ep << 5));
                        ldsm4t(v0[ep][0], v0[ep][1], v0[ep][2], v0[ep][3], va);
                        ldsm4t(v1[ep][0], v1[ep][1], v1[ep][2], v1[ep][3], va + 2048);
                    }
#pragma unroll
                    for (int n = 0; n < 8; n++) { o[n][0] = o[n][1] = o[n][2] = o[n][3] = 0.f; mma16816(o[n], p0[0], p1[0], p0[1], p1[1], vm[n], v0[n >> 1][n & 1]); }
#pragma unroll
                    for (int n = 0; n < 8; n++) mma16816(o[n], p0[2], p1[2], p0[3], p1[3], v0[n >> 1][2 + (n & 1)], v1[n >> 1][n & 1]);
#pragma unroll
                    for (int n = 0; n < 8; n++) mma1688(o[n], p0[4], p1[4], v1[n >> 1][2 + (n & 1)]);
#pragma unroll
                    for (int ep = 0; ep < 4; ep++)
                        stsm4(stg_base + bx * 8192 + (sx ^ (ep << 5)),
                              pack2(o[2 * ep][0] * i0, o[2 * ep][1] * i0), pack2(o[2 * ep][2] * i1, o[2 * ep][3] * i1),
                              pack2(o[2 * ep + 1][0] * i0, o[2 * ep + 1][1] * i0), pack2(o[2 * ep + 1][2] * i1, o[2 * ep + 1][3] * i1));
                }
                __syncwarp();
                if (lane == 0) mbar_arrive(bars + B_EMPTY + pp.stage * 8);
                pipe_next(pp);
                if (hh == 0) { fence_async_smem(); bar_arrive(NB_ST + wg, 160); }
            }
        } else if (type == J_UP) {
            mbar_wait(bars + B_STGFREE + wg * 8, stg_phase); stg_phase ^= 1;
#pragma unroll
            for (int j = 0; j < 8; j++) {
                uint32_t r[4];
#pragma unroll
                for (int q = 0; q < 4; q++) {
                    const uint32_t gw = pack2(acc[8 * j + 2 * q], acc[8 * j + 2 * q + 1]);
                    const uint32_t uw = pack2(acc[64 + 8 * j + 2 * q], acc[64 + 8 * j + 2 * q + 1]);
                    r[q] = hmul2(pack2(gelu_tanh(bflo(gw)), gelu_tanh(bfhi(gw))), uw);
                }
                stsm4(stg_base + (j >> 2) * 8192 + (sx ^ ((2 * j & 7) << 4)), r[0], r[1], r[2], r[3]);
            }
        } else {
#pragma unroll
            for (int rd = 0; rd < 2; rd++) {
                mbar_wait(bars + B_STGFREE + wg * 8, stg_phase); stg_phase ^= 1;
#pragma unroll
                for (int j = rd * 8; j < rd * 8 + 8; j++)
                    stsm4(stg_base + ((j >> 2) & 1) * 8192 + (sx ^ ((2 * j & 7) << 4)),
                          pack2(acc[8 * j], acc[8 * j + 1]), pack2(acc[8 * j + 2], acc[8 * j + 3]),
                          pack2(acc[8 * j + 4], acc[8 * j + 5]), pack2(acc[8 * j + 6], acc[8 * j + 7]));
                if (rd == 0) { fence_async_smem(); bar_arrive(NB_ST + wg, 160); }
            }
        }
        fence_async_smem();
        CTR(5);
        bar_arrive(NB_ST + wg, 160);
    }
}

__global__ void __launch_bounds__(384, 1) k_work(const __grid_constant__ Params p) {
    extern __shared__ __align__(1024) unsigned char smem_raw[];
    const uint32_t sb = smem_u32(smem_raw);
    if (sb & 1023) __trap();
    const int warp = __shfl_sync(~0u, threadIdx.x >> 5, 0);
    int lane; asm volatile("mov.u32 %0, %%laneid;" : "=r"(lane));
    if (threadIdx.x == 0) {
        const uint32_t bars = sb + SM_BAR;
        for (int i = 0; i < W_NST; i++) { mbar_init(bars + B_FULL + i * 8, 1); mbar_init(bars + B_EMPTY + i * 8, 8); }
        mbar_init(bars + B_STGFREE, 1); mbar_init(bars + B_STGFREE + 8, 1); mbar_init(bars + B_REQ, 1); mbar_init(bars + B_RSP, 1);
        asm volatile("fence.mbarrier_init.release.cluster;" ::: "memory");
    }
    __syncthreads();
    if (warp < 8) {
        asm volatile("setmaxnreg.inc.sync.aligned.u32 224;");
        consumer(p, sb, warp, lane);
    } else {
        asm volatile("setmaxnreg.dec.sync.aligned.u32 56;");
        if (warp == 8) { if (lane == 0) producer(p, sb); }
        else if (warp < 11) store_warp(p, sb, warp - 9, lane);
        else scheduler(p, sb, lane);
        __syncwarp();
        bar_sync(NB_W0, 128);
        if (warp == 8 && p.qmask == 0xff) {
            unsigned last = 0;
            if (lane == 0) { __threadfence(); last = atomicAdd(&g_flags[F_DONE], 1u) == gridDim.x - 1; }
            if (__shfl_sync(~0u, last, 0))
                for (int i = lane; i < F_TOTAL; i += 32) g_flags[i] = 0;
        }
    }
}

typedef CUresult (*EncodeFn)(CUtensorMap*, CUtensorMapDataType, cuuint32_t, void*, const cuuint64_t*, const cuuint64_t*,
                             const cuuint32_t*, const cuuint32_t*, CUtensorMapInterleave, CUtensorMapSwizzle,
                             CUtensorMapL2promotion, CUtensorMapFloatOOBfill);

static void make_map(EncodeFn enc, CUtensorMap* m, const void* ptr, uint64_t rows, uint64_t cols, uint32_t box_rows) {
    cuuint64_t dims[2] = {cols, rows};
    cuuint64_t strides[1] = {cols * 2};
    cuuint32_t box[2] = {64, box_rows};
    cuuint32_t es[2] = {1, 1};
    enc(m, CU_TENSOR_MAP_DATA_TYPE_BFLOAT16, 2, const_cast<void*>(ptr), dims, strides, box, es, CU_TENSOR_MAP_INTERLEAVE_NONE,
        CU_TENSOR_MAP_SWIZZLE_128B, CU_TENSOR_MAP_L2_PROMOTION_L2_256B, CU_TENSOR_MAP_FLOAT_OOB_FILL_NONE);
}
template <typename T> static void* sym_addr(T& sym) { void* p = nullptr; cudaGetSymbolAddress(&p, sym); return p; }

extern "C" void kernel_launch(void* const* d_in, const int* in_sizes, int n_in, void* d_out, int out_size) {
    static Params prm;
    static RecParams rp;
    static int n_sm = 132;
    static bool ready = false;
    static const void* key[14];
    bool same = ready;
    for (int i = 0; i < 13 && same; i++) same = key[i] == d_in[i];
    same = same && key[13] == d_out;
    if (!same) {
        void* fn = nullptr;
        cudaDriverEntryPointQueryResult qr;
        cudaGetDriverEntryPoint("cuTensorMapEncodeTiled", &fn, cudaEnableDefault, &qr);
        EncodeFn enc = (EncodeFn)fn;
        make_map(enc, &prm.tm_h, sym_addr(g_h), S_, D_, 64);
        make_map(enc, &prm.tm_kv, sym_addr(g_kv), S_, 2 * HD_, 64);
        make_map(enc, &rp.tm_kv32, sym_addr(g_kv), S_, 2 * HD_, 32);
        make_map(enc, &prm.tm_kvm, sym_addr(g_kvm), NSEG * 8, 2 * HD_, 32);
        make_map(enc, &prm.tm_o, sym_addr(g_o), S_, HD_, 64);
        make_map(enc, &prm.tm_op, sym_addr(g_op), OP_ROWS, D_, 64);
        make_map(enc, &prm.tm_h2, sym_addr(g_h2), S_, D_, 64);
        make_map(enc, &prm.tm_act, sym_addr(g_act), S_, DF_, 64);
        make_map(enc, &prm.tm_x1, sym_addr(g_x1), S_, D_, 64);
        make_map(enc, &prm.tm_out, d_out, S_, D_, 64);
        make_map(enc, &prm.tm_wq, d_in[2], D_, HD_, 64);
        make_map(enc, &prm.tm_wk, d_in[3], D_, HD_, 64);
        make_map(enc, &prm.tm_wv, d_in[4], D_, HD_, 64);
        make_map(enc, &prm.tm_wo, d_in[5], HD_, D_, 64);
        make_map(enc, &prm.tm_wg, d_in[8], D_, DF_, 64);
        make_map(enc, &prm.tm_wu, d_in[9], D_, DF_, 64);
        make_map(enc, &prm.tm_wd, d_in[10], DF_, D_, 64);
        prm.x = (const bf16*)d_in[0]; prm.c = (const bf16*)d_in[11]; prm.w_mod = (const bf16*)d_in[12];
        rp.mem0 = (const bf16*)d_in[1]; rp.x = prm.x; rp.c = prm.c; rp.w_mod = prm.w_mod;
        rp.wq = (const bf16*)d_in[2]; rp.wk = (const bf16*)d_in[3]; rp.wv = (const bf16*)d_in[4]; rp.wo = (const bf16*)d_in[5];
        cudaDeviceGetAttribute(&n_sm, cudaDevAttrMultiProcessorCount, 0);
        cudaFuncSetAttribute(k_work, cudaFuncAttributeMaxDynamicSharedMemorySize, SMEM_BYTES);
        cudaFuncSetAttribute(k_rec, cudaFuncAttributeMaxDynamicSharedMemorySize, R_SMEM);
        cudaFuncSetAttribute(k_rec, cudaFuncAttributeNonPortableClusterSizeAllowed, 1);
        {
            cudaLaunchConfig_t cfg = {};
            cfg.gridDim = dim3(128); cfg.blockDim = dim3(384); cfg.dynamicSmemBytes = R_SMEM;
            cudaLaunchAttribute at[1];
            at[0].id = cudaLaunchAttributeClusterDimension; at[0].val.clusterDim.x = 16; at[0].val.clusterDim.y = 1; at[0].val.clusterDim.z = 1;
            cfg.attrs = at; cfg.numAttrs = 1;
            int n = 0;
            cudaOccupancyMaxActiveClusters(&n, k_rec, &cfg);
            rp.ncl = n < 4 ? 4 : (n > 8 ? 8 : n);
        }
        for (int i = 0; i < 13; i++) key[i] = d_in[i];
        key[13] = d_out;
        ready = true;
    }
    cudaStream_t st = cudaStreamPerThread;
    auto launch_rec = [&]() {
        cudaLaunchConfig_t cfg = {};
        cfg.gridDim = dim3(16 * rp.ncl); cfg.blockDim = dim3(384); cfg.dynamicSmemBytes = R_SMEM; cfg.stream = st;
        cudaLaunchAttribute at[1];
        at[0].id = cudaLaunchAttributeClusterDimension; at[0].val.clusterDim.x = 16; at[0].val.clusterDim.y = 1; at[0].val.clusterDim.z = 1;
        cfg.attrs = at; cfg.numAttrs = 1;
        cudaLaunchKernelEx(&cfg, k_rec, rp);
    };
    auto launch_work = [&](int qmask, int pdl) {
        prm.qmask = qmask;
        cudaLaunchConfig_t cfg = {};
        cfg.gridDim = dim3(n_sm); cfg.blockDim = dim3(384); cfg.dynamicSmemBytes = SMEM_BYTES; cfg.stream = st;
        cudaLaunchAttribute at[1];
        at[0].id = cudaLaunchAttributeProgrammaticStreamSerialization; at[0].val.programmaticStreamSerializationAllowed = 1;
        cfg.attrs = at; cfg.numAttrs = pdl;
        cudaLaunchKernelEx(&cfg, k_work, prm);
    };
    launch_rec();
    launch_work(0xff, 1);
}
```

```cpp
#include <cuda_runtime.h>
#include <cuda_bf16.h>
#include <cuda.h>
#include <stdint.h>

typedef __nv_bfloat16 bf16;
#define IDLE_NS 150
#define FLAG_NS 20

constexpr int S_ = 2048, D_ = 512, DH_ = 128, HD_ = 4096, NSEG = 64, DF_ = 1792;
constexpr int NRB = 16;
constexpr int OSPLIT = 4;

__device__ __align__(1024) bf16 g_h[S_ * D_];
__device__ __align__(1024) bf16 g_kv[S_ * 2 * HD_];
__device__ __align__(1024) bf16 g_kvm[NSEG * 8 * 2 * HD_];
__device__ __align__(1024) bf16 g_o[S_ * HD_];
#define FINE_RB_ 12
constexpr int FINE_RB = FINE_RB_;
#define OSPLIT2_ 8
constexpr int OSPLIT2 = OSPLIT2_;
constexpr int OSPLIT3 = 16;
constexpr int OP_ROWS = OSPLIT * S_ + OSPLIT2 * (NRB - FINE_RB) * 128 + OSPLIT3 * 128;
__device__ __align__(1024) bf16 g_op[OP_ROWS * D_];
__device__ __align__(1024) bf16 g_x1[S_ * D_];
__device__ __align__(1024) bf16 g_h2[S_ * D_];
__device__ __align__(1024) bf16 g_act[S_ * DF_];
__device__ __align__(1024) bf16 g_mod[6 * D_];
__device__ uint32_t g_Fraw[131072 + 65536 + 2048];
#define g_F ((uint32_t*)(((uint64_t)g_Fraw + 0x7FFFFull) & ~0x7FFFFull))
constexpr int F_H = 0, F_MEM = 32, F_O = 64, F_OP = 96, F_H2 = 128, F_ACT = 160, F_MOD = 192, F_KV = 224, F_CLAIM = 256  ,
              F_SIDE = 512  , F_DONE = 576, F_TOTAL = 608;
__device__ __align__(128) unsigned int g_flags[F_TOTAL];
#define TR(j, i) do {} while (0)

__device__ __forceinline__ uint32_t smem_u32(const void* p) { return (uint32_t)__cvta_generic_to_shared(p); }
__device__ __forceinline__ uint32_t clk32() { uint32_t c; asm volatile("mov.u32 %0, %%clock;" : "=r"(c)); return c; }
__device__ __forceinline__ uint32_t mapa_u32(uint32_t addr, uint32_t rank) {
    uint32_t r; asm volatile("mapa.shared::cluster.u32 %0, %1, %2;" : "=r"(r) : "r"(addr), "r"(rank)); return r;
}
__device__ __forceinline__ void mbar_init(uint32_t bar, uint32_t cnt) {
    asm volatile("mbarrier.init.shared::cta.b64 [%0], %1;" :: "r"(bar), "r"(cnt) : "memory");
}
__device__ __forceinline__ void mbar_expect_tx(uint32_t bar, uint32_t bytes) {
    asm volatile("mbarrier.arrive.expect_tx.shared::cta.b64 _, [%0], %1;" :: "r"(bar), "r"(bytes) : "memory");
}
__device__ __forceinline__ void mbar_arrive(uint32_t bar) {
    asm volatile("mbarrier.arrive.shared::cta.b64 _, [%0];" :: "r"(bar) : "memory");
}
__device__ __forceinline__ bool mbar_try_wait(uint32_t bar, uint32_t parity) {
    uint32_t ok;
    asm volatile("{\n.reg .pred p;\nmbarrier.try_wait.parity.shared::cta.b64 p, [%1], %2;\nselp.u32 %0, 1, 0, p;\n}"
                 : "=r"(ok) : "r"(bar), "r"(parity) : "memory");
    return ok;
}
constexpr int SPIN_LIMIT = 1 << 18;
#define TIMEOUT(code, info) do {} while (0)
__device__ __forceinline__ void mbar_wait(uint32_t bar, uint32_t parity) {
    int g = 0;
#pragma unroll 1
    while (!mbar_try_wait(bar, parity)) { if (++g >= SPIN_LIMIT) { TIMEOUT(0, bar & 255); break; } }
}
__device__ __forceinline__ void bar_sync(int id, int n) { asm volatile("bar.sync %0, %1;" :: "r"(id), "r"(n) : "memory"); }
__device__ __forceinline__ void bar_arrive(int id, int n) { asm volatile("bar.arrive %0, %1;" :: "r"(id), "r"(n) : "memory"); }
__device__ __forceinline__ void st_async_v2(uint32_t addr, float a, float b, uint32_t bar) {
    asm volatile("st.async.weak.shared::cluster.mbarrier::complete_tx::bytes.v2.f32 [%0], {%1,%2}, [%3];"
                 :: "r"(addr), "f"(a), "f"(b), "r"(bar) : "memory");
}
__device__ __forceinline__ void st_async_v4(uint32_t addr, uint4 v, uint32_t bar) {
    asm volatile("st.async.weak.shared::cluster.mbarrier::complete_tx::bytes.v4.b32 [%0], {%1,%2,%3,%4}, [%5];"
                 :: "r"(addr), "r"(v.x), "r"(v.y), "r"(v.z), "r"(v.w), "r"(bar) : "memory");
}
__device__ __forceinline__ void stg_relaxed32(uint32_t* p, uint32_t v) {
    asm volatile("st.relaxed.gpu.global.b32 [%0], %1;" :: "l"(p), "r"(v) : "memory");
}
__device__ __forceinline__ uint32_t ldg_relaxed32(const uint32_t* p) {
    uint32_t v; asm volatile("ld.relaxed.gpu.global.b32 %0, [%1];" : "=r"(v) : "l"(p) : "memory"); return v;
}
__device__ __forceinline__ unsigned int ld_acquire(const unsigned int* p) {
    unsigned int v; asm volatile("ld.acquire.gpu.global.u32 %0, [%1];" : "=r"(v) : "l"(p) : "memory"); return v;
}
__device__ __forceinline__ void red_release(unsigned int* p, unsigned int v) {
    asm volatile("red.release.gpu.global.add.u32 [%0], %1;" :: "l"(p), "r"(v) : "memory");
}
__device__ __forceinline__ void wait_flag(int idx, unsigned int target) {
    const unsigned int* p = &g_flags[idx];
    int g = 0;
#pragma unroll 1
    while (ld_acquire(p) < target) { __nanosleep(FLAG_NS); if (++g >= 64 * SPIN_LIMIT) { TIMEOUT(2, idx); break; } }
}
__device__ __forceinline__ void cp_async16(uint32_t dst, const void* src) {
    asm volatile("cp.async.cg.shared.global [%0], [%1], 16;" :: "r"(dst), "l"(src) : "memory");
}
__device__ __forceinline__ void cp_async_commit() { asm volatile("cp.async.commit_group;" ::: "memory"); }
template <int N> __device__ __forceinline__ void cp_async_wait() { asm volatile("cp.async.wait_group %0;" :: "n"(N) : "memory"); }
__device__ __forceinline__ void ldsm4(uint32_t& r0, uint32_t& r1, uint32_t& r2, uint32_t& r3, uint32_t addr) {
    asm volatile("ldmatrix.sync.aligned.m8n8.x4.shared.b16 {%0,%1,%2,%3}, [%4];" : "=r"(r0), "=r"(r1), "=r"(r2), "=r"(r3) : "r"(addr) : "memory");
}
__device__ __forceinline__ void ldsm4t(uint32_t& r0, uint32_t& r1, uint32_t& r2, uint32_t& r3, uint32_t addr) {
    asm volatile("ldmatrix.sync.aligned.m8n8.x4.trans.shared.b16 {%0,%1,%2,%3}, [%4];" : "=r"(r0), "=r"(r1), "=r"(r2), "=r"(r3) : "r"(addr) : "memory");
}
__device__ __forceinline__ void ldsm2t(uint32_t& r0, uint32_t& r1, uint32_t addr) {
    asm volatile("ldmatrix.sync.aligned.m8n8.x2.trans.shared.b16 {%0,%1}, [%2];" : "=r"(r0), "=r"(r1) : "r"(addr) : "memory");
}
__device__ __forceinline__ void stsm4(uint32_t addr, uint32_t r0, uint32_t r1, uint32_t r2, uint32_t r3) {
    asm volatile("stmatrix.sync.aligned.m8n8.x4.shared.b16 [%0], {%1,%2,%3,%4};" :: "r"(addr), "r"(r0), "r"(r1), "r"(r2), "r"(r3) : "memory");
}
__device__ __forceinline__ void stsm4t(uint32_t addr, uint32_t r0, uint32_t r1, uint32_t r2, uint32_t r3) {
    asm volatile("stmatrix.sync.aligned.m8n8.x4.trans.shared.b16 [%0], {%1,%2,%3,%4};" :: "r"(addr), "r"(r0), "r"(r1), "r"(r2), "r"(r3) : "memory");
}
__device__ __forceinline__ void stsm2t(uint32_t addr, uint32_t r0, uint32_t r1) {
    asm volatile("stmatrix.sync.aligned.m8n8.x2.trans.shared.b16 [%0], {%1,%2};" :: "r"(addr), "r"(r0), "r"(r1) : "memory");
}
__device__ __forceinline__ void mma16816(float* d, uint32_t a0, uint32_t a1, uint32_t a2, uint32_t a3, uint32_t b0, uint32_t b1) {
    asm volatile("mma.sync.aligned.m16n8k16.row.col.f32.bf16.bf16.f32 {%0,%1,%2,%3}, {%4,%5,%6,%7}, {%8,%9}, {%0,%1,%2,%3};"
                 : "+f"(d[0]), "+f"(d[1]), "+f"(d[2]), "+f"(d[3]) : "r"(a0), "r"(a1), "r"(a2), "r"(a3), "r"(b0), "r"(b1));
}
__device__ __forceinline__ void mma1688(float* d, uint32_t a0, uint32_t a1, uint32_t b0) {
    asm volatile("mma.sync.aligned.m16n8k8.row.col.f32.bf16.bf16.f32 {%0,%1,%2,%3}, {%4,%5}, {%6}, {%0,%1,%2,%3};"
                 : "+f"(d[0]), "+f"(d[1]), "+f"(d[2]), "+f"(d[3]) : "r"(a0), "r"(a1), "r"(b0));
}
__device__ __forceinline__ void mma16816h(float* d, uint32_t a0, uint32_t a2, uint32_t b0, uint32_t b1) {
    asm volatile("{\n.reg .b32 ju, jv;\nmma.sync.aligned.m16n8k16.row.col.f32.bf16.bf16.f32 {%0,%1,%2,%3}, {%4,ju,%5,jv}, {%6,%7}, {%0,%1,%2,%3};\n}"
                 : "+f"(d[0]), "+f"(d[1]), "+f"(d[2]), "+f"(d[3]) : "r"(a0), "r"(a2), "r"(b0), "r"(b1));
}
__device__ __forceinline__ void mma1688h(float* d, uint32_t a0, uint32_t b0) {
    asm volatile("{\n.reg .b32 ju;\nmma.sync.aligned.m16n8k8.row.col.f32.bf16.bf16.f32 {%0,%1,%2,%3}, {%4,ju}, {%5}, {%0,%1,%2,%3};\n}"
                 : "+f"(d[0]), "+f"(d[1]), "+f"(d[2]), "+f"(d[3]) : "r"(a0), "r"(b0));
}
__device__ __forceinline__ uint32_t movm(uint32_t a) {
    uint32_t d; asm volatile("movmatrix.sync.aligned.m8n8.trans.b16 %0, %1;" : "=r"(d) : "r"(a)); return d;
}
__device__ __forceinline__ uint32_t pack2(float lo, float hi) {
    uint32_t r; asm("cvt.rn.bf16x2.f32 %0, %1, %2;" : "=r"(r) : "f"(hi), "f"(lo)); return r;
}
__device__ __forceinline__ float bflo(uint32_t w) { return __uint_as_float(w << 16); }
__device__ __forceinline__ float bfhi(uint32_t w) { return __uint_as_float(w & 0xffff0000u); }
__device__ __forceinline__ float rbf(float x) { return __bfloat162float(__float2bfloat16_rn(x)); }
__device__ __forceinline__ float ex2(float x) { float y; asm("ex2.approx.ftz.f32 %0, %1;" : "=f"(y) : "f"(x)); return y; }
__device__ __forceinline__ void sts128(uint32_t addr, uint4 v) {
    asm volatile("st.shared.v4.b32 [%0], {%1,%2,%3,%4};" :: "r"(addr), "r"(v.x), "r"(v.y), "r"(v.z), "r"(v.w) : "memory");
}
__device__ __forceinline__ uint4 lds128(uint32_t addr) {
    uint4 v; asm volatile("ld.shared.v4.b32 {%0,%1,%2,%3}, [%4];" : "=r"(v.x), "=r"(v.y), "=r"(v.z), "=r"(v.w) : "r"(addr) : "memory"); return v;
}
__device__ __forceinline__ float2 lds64f(uint32_t addr) {
    float2 v; asm volatile("ld.shared.v2.f32 {%0,%1}, [%2];" : "=f"(v.x), "=f"(v.y) : "r"(addr) : "memory"); return v;
}
__device__ __forceinline__ float lds32f(uint32_t addr) {
    float v; asm volatile("ld.shared.f32 %0, [%1];" : "=f"(v) : "r"(addr) : "memory"); return v;
}
__device__ __forceinline__ uint32_t lds32(uint32_t addr) {
    uint32_t v; asm volatile("ld.shared.b32 %0, [%1];" : "=r"(v) : "r"(addr) : "memory"); return v;
}
__device__ __forceinline__ void sts32(uint32_t addr, uint32_t v) { asm volatile("st.shared.b32 [%0], %1;" :: "r"(addr), "r"(v) : "memory"); }
__device__ __forceinline__ void sts64f(uint32_t addr, float a, float b) { asm volatile("st.shared.v2.f32 [%0], {%1,%2};" :: "r"(addr), "f"(a), "f"(b) : "memory"); }

__device__ __forceinline__ void tma_load2d(uint32_t dst, const CUtensorMap* tm, int c0, int c1, uint32_t bar) {
    asm volatile("cp.async.bulk.tensor.2d.shared::cluster.global.mbarrier::complete_tx::bytes [%0], [%1, {%3, %4}], [%2];"
                 :: "r"(dst), "l"(tm), "r"(bar), "r"(c0), "r"(c1) : "memory");
}
__device__ __forceinline__ void tma_store2d(const CUtensorMap* tm, uint32_t src, int c0, int c1) {
    asm volatile("cp.async.bulk.tensor.2d.global.shared::cta.bulk_group [%0, {%2, %3}], [%1];"
                 :: "l"(tm), "r"(src), "r"(c0), "r"(c1) : "memory");
}
__device__ __forceinline__ void bulk_commit() { asm volatile("cp.async.bulk.commit_group;" ::: "memory"); }
__device__ __forceinline__ void bulk_wait0() { asm volatile("cp.async.bulk.wait_group 0;" ::: "memory"); }
__device__ __forceinline__ void fence_async_smem() { asm volatile("fence.proxy.async.shared::cta;" ::: "memory"); }
__device__ __forceinline__ void fence_async_all() { asm volatile("fence.proxy.async;" ::: "memory"); }

__device__ __forceinline__ void wg_fence() { asm volatile("wgmma.fence.sync.aligned;" ::: "memory"); }
__device__ __forceinline__ void wg_commit() { asm volatile("wgmma.commit_group.sync.aligned;" ::: "memory"); }
__device__ __forceinline__ void wg_wait0() { asm volatile("wgmma.wait_group.sync.aligned 0;" ::: "memory"); }
__device__ __forceinline__ uint64_t mkdesc(uint32_t saddr, uint32_t lbo, uint32_t sbo) {
    return (uint64_t)((saddr & 0x3FFFF) >> 4) | ((uint64_t)(lbo >> 4) << 16) | ((uint64_t)(sbo >> 4) << 32) | (1ull << 62);
}
#define ACC8(i) "+f"(d[i]), "+f"(d[i + 1]), "+f"(d[i + 2]), "+f"(d[i + 3]), "+f"(d[i + 4]), "+f"(d[i + 5]), "+f"(d[i + 6]), "+f"(d[i + 7])
__device__ __forceinline__ void wgmma_n256(float* d, uint64_t da, uint64_t db, int scale_d) {
    asm volatile(
        "{\n.reg .pred p;\nsetp.ne.b32 p, %130, 0;\n"
        "wgmma.mma_async.sync.aligned.m64n256k16.f32.bf16.bf16 "
        "{%0,%1,%2,%3,%4,%5,%6,%7,%8,%9,%10,%11,%12,%13,%14,%15,%16,%17,%18,%19,%20,%21,%22,%23,%24,%25,%26,%27,%28,%29,%30,%31,"
        "%32,%33,%34,%35,%36,%37,%38,%39,%40,%41,%42,%43,%44,%45,%46,%47,%48,%49,%50,%51,%52,%53,%54,%55,%56,%57,%58,%59,%60,%61,%62,%63,"
        "%64,%65,%66,%67,%68,%69,%70,%71,%72,%73,%74,%75,%76,%77,%78,%79,%80,%81,%82,%83,%84,%85,%86,%87,%88,%89,%90,%91,%92,%93,%94,%95,"
        "%96,%97,%98,%99,%100,%101,%102,%103,%104,%105,%106,%107,%108,%109,%110,%111,%112,%113,%114,%115,%116,%117,%118,%119,%120,%121,%122,%123,%124,%125,%126,%127}, "
        "%128, %129, p, 1, 1, 0, 1;\n}"
        : ACC8(0), ACC8(8), ACC8(16), ACC8(24), ACC8(32), ACC8(40), ACC8(48), ACC8(56),
          ACC8(64), ACC8(72), ACC8(80), ACC8(88), ACC8(96), ACC8(104), ACC8(112), ACC8(120)
        : "l"(da), "l"(db), "r"(scale_d));
}
__device__ __forceinline__ void wgmma_n128(float* d, uint64_t da, uint64_t db, int scale_d) {
    asm volatile(
        "{\n.reg .pred p;\nsetp.ne.b32 p, %66, 0;\n"
        "wgmma.mma_async.sync.aligned.m64n128k16.f32.bf16.bf16 "
        "{%0,%1,%2,%3,%4,%5,%6,%7,%8,%9,%10,%11,%12,%13,%14,%15,%16,%17,%18,%19,%20,%21,%22,%23,%24,%25,%26,%27,%28,%29,%30,%31,"
        "%32,%33,%34,%35,%36,%37,%38,%39,%40,%41,%42,%43,%44,%45,%46,%47,%48,%49,%50,%51,%52,%53,%54,%55,%56,%57,%58,%59,%60,%61,%62,%63}, "
        "%64, %65, p, 1, 1, 0, 1;\n}"
        : ACC8(0), ACC8(8), ACC8(16), ACC8(24), ACC8(32), ACC8(40), ACC8(48), ACC8(56)
        : "l"(da), "l"(db), "r"(scale_d));
}

__device__ __forceinline__ void wgmma_n64(float* d, uint64_t da, uint64_t db) {
    asm volatile(
        "wgmma.mma_async.sync.aligned.m64n64k16.f32.bf16.bf16 "
        "{%0,%1,%2,%3,%4,%5,%6,%7,%8,%9,%10,%11,%12,%13,%14,%15,%16,%17,%18,%19,%20,%21,%22,%23,%24,%25,%26,%27,%28,%29,%30,%31}, "
        "%32, %33, 1, 1, 1, 0, 1;"
        : ACC8(0), ACC8(8), ACC8(16), ACC8(24)
        : "l"(da), "l"(db));
}
__device__ __forceinline__ uint32_t hadd2(uint32_t a, uint32_t b) { uint32_t r; asm("add.rn.bf16x2 %0, %1, %2;" : "=r"(r) : "r"(a), "r"(b)); return r; }
__device__ __forceinline__ uint32_t hsub2(uint32_t a, uint32_t b) { uint32_t r; asm("sub.rn.bf16x2 %0, %1, %2;" : "=r"(r) : "r"(a), "r"(b)); return r; }
__device__ __forceinline__ uint32_t hmul2(uint32_t a, uint32_t b) { uint32_t r; asm("mul.rn.bf16x2 %0, %1, %2;" : "=r"(r) : "r"(a), "r"(b)); return r; }
__device__ __forceinline__ void load_mod8(const bf16* m, int lane, uint32_t* v) {
    const uint4 a = __ldcg((const uint4*)m + lane), b = __ldcg((const uint4*)m + 32 + lane);
    v[0] = a.x; v[1] = a.y; v[2] = a.z; v[3] = a.w; v[4] = b.x; v[5] = b.y; v[6] = b.z; v[7] = b.w;
}
__device__ __forceinline__ void ln_stats(const uint32_t* x, uint32_t& mu2, float& rden) {
    float s = 0.f;
#pragma unroll
    for (int i = 0; i < 8; i++) s += bflo(x[i]) + bfhi(x[i]);
#pragma unroll
    for (int o = 16; o > 0; o >>= 1) s += __shfl_xor_sync(~0u, s, o);
    const float mean = s * (1.f / D_);
    float q = 0.f;
#pragma unroll
    for (int i = 0; i < 8; i++) { const float d0 = bflo(x[i]) - mean, d1 = bfhi(x[i]) - mean; q = fmaf(d0, d0, q); q = fmaf(d1, d1, q); }
#pragma unroll
    for (int o = 16; o > 0; o >>= 1) q += __shfl_xor_sync(~0u, q, o);
    mu2 = pack2(mean, mean);
    rden = __frcp_rn(rbf(__fsqrt_rn(rbf(rbf(q * (1.f / D_)) + 1e-5f))));
}
__device__ __forceinline__ void ln_apply(const uint32_t* x, uint32_t mu2, float rden, const uint32_t* c1, const uint32_t* sm, uint32_t* r) {
#pragma unroll
    for (int i = 0; i < 8; i++) {
        const uint32_t d = hsub2(x[i], mu2);
        r[i] = hadd2(hmul2(pack2(bflo(d) * rden, bfhi(d) * rden), c1[i]), sm[i]);
    }
}

struct __align__(64) Params {
    CUtensorMap tm_h, tm_kv, tm_kvm, tm_o, tm_op, tm_h2, tm_act, tm_x1, tm_out;
    CUtensorMap tm_wq, tm_wk, tm_wv, tm_wo, tm_wg, tm_wu, tm_wd;
    const bf16 *x, *c, *w_mod;
    int qmask;
};

constexpr uint32_t R_WV = 0, R_MEM = 65536  ,
                   R_KX = 69632  , R_VX = R_KX + 8192,
                   R_VMS = R_KX + 32768  , R_OS = R_VMS + 2048  , R_SX = R_OS + 2048  , R_BAR = R_SX + 1536,
                   R_RS = R_BAR + 512  , R_VB = R_RS + 4096  , R_VP = R_VB + 2048  ,
                   R_STG = R_VP + 4096  ,
                   R_TQ = R_STG  , R_TV = R_STG + 53248  , R_QF = R_STG + 77824  ,
                   R_SMEM = R_STG + 98304;
static_assert((R_STG & 1023) == 0 && (R_RS & 511) == 0 && R_QF + 16384 <= R_SMEM, "smem");
constexpr uint32_t RB_Q = R_BAR, RB_V = R_BAR + 8, RB_E = R_BAR + 16, RB_A = R_BAR + 24, RB_ROLE = R_BAR + 32, RB_KV = R_BAR + 40  ;
constexpr int W_NST = 4;
constexpr uint32_t W_STAGE = 49152, W_STG = W_NST * W_STAGE  , W_END = W_STG + 32768;
constexpr uint32_t SM_BAR = W_END;
constexpr uint32_t SMEM_BYTES = W_END + 1024 + 2048;
constexpr uint32_t B_FULL = 0, B_EMPTY = 32, B_STGFREE = 64, B_REQ = 80, B_RSP = 88, B_NEXT = 96, B_RING = 128;
#define PICK_AHEAD 3

constexpr int NB_S = 11, NB_Y = 1, NB_M = 5, NB_K = 5, NB_B = 2, NB_C = 3, NB_D = 4, NB_W0 = 6  , NB_ST = 9  ;

__device__ __forceinline__ int pos_of_d(int d) {
    const int rem = d & 31;
    return (d & ~31) + ((rem & 7) >> 1) * 8 + (rem & 1) * 4 + (rem >> 3);
}

#define PROF(i) do {} while (0)
#define PROFG(i) do {} while (0)
#define VK0_ 4
constexpr int VK0 = VK0_;
constexpr int NOFF = 8;
#define OFFKS(i) ((i) >> 1)
#define POLL_GAP 140

struct __align__(64) RecParams { CUtensorMap tm_kv32; const bf16 *mem0, *wq, *wk, *wv, *wo, *x, *c, *w_mod; int ncl, only_pre; };

__device__ __forceinline__ void rec_qk(const RecParams& p, const uint32_t sb, const int cta, const int warp, int lane, const int sel) {
    const int crank = cta & 15, cl = cta >> 4, rank = cta & 1;
    const int wg = warp >> 2, aa = warp & 3;
    uint32_t wa[2][16][4];
    {
        const uint32_t stg = sb + R_STG + wg * 32768;
        const int t128 = aa * 32 + lane;
        const int row = (lane >> 4) * 8 + (lane & 7);
        const int ch = t128 & 7;
        const size_t goff = (size_t)rank * 256 * HD_ + (cta >> 1) * DH_ + ch * 8;
        const bf16* W = (wg == 0 ? p.wq : p.wk) + goff;
#pragma unroll 4
        for (int dd = 0; dd < 16; dd++) {
            const int d = dd * 16 + (t128 >> 3), pp = pos_of_d(d);
            cp_async16(sb + R_WV + wg * 32768 + pp * 128 + ((ch ^ (pp & 7)) << 4), p.wv + goff + wg * 64 + (size_t)d * HD_);
        }
        cp_async_commit();
#pragma unroll 4
        for (int dd = 0; dd < 16; dd++) {
            const int d = dd * 16 + (t128 >> 3), pp = pos_of_d(d);
            cp_async16(stg + pp * 128 + ((ch ^ (pp & 7)) << 4), W + (size_t)d * HD_);
        }
        cp_async_commit();
        {
            const int tok = warp, d0 = lane * 8;
            const uint4 m0 = __ldg((const uint4*)(p.mem0 + tok * D_ + rank * 256 + d0));
            const uint32_t mw[4] = {m0.x, m0.y, m0.z, m0.w};
#pragma unroll
            for (int e = 0; e < 8; e++) {
                const int pp = pos_of_d(d0 + e);
                const unsigned short v = (unsigned short)(mw[e >> 1] >> ((e & 1) * 16));
                asm volatile("st.shared.u16 [%0], %1;" :: "r"(sb + R_MEM + (pp >> 3) * 128 + tok * 16 + (pp & 7) * 2), "h"(v) : "memory");
            }
        }
        cp_async_wait<1>();
        bar_sync(NB_W0 + wg, 128);
        const uint32_t fv = row * 128 + (((2 * aa + ((lane >> 3) & 1)) ^ (row & 7)) << 4);
#pragma unroll
        for (int ks = 0; ks < 16; ks++) ldsm4t(wa[0][ks][0], wa[0][ks][1], wa[0][ks][2], wa[0][ks][3], sb + R_WV + wg * 32768 + fv + ks * 2048);
        bar_sync(NB_W0 + wg, 128);
#pragma unroll
        for (int ks = 0; ks < 16; ks++)
            sts128(sb + R_WV + (warp * 16 + ks) * 512 + lane * 16, make_uint4(wa[0][ks][0], wa[0][ks][1], wa[0][ks][2], wa[0][ks][3]));
        const uint32_t fo = stg + row * 128 + (((4 * (aa & 1) + ((lane >> 3) & 1)) ^ (row & 7)) << 4);
#pragma unroll 1
        for (int m = 0; m < 2; m++) {
            cp_async_wait<0>();
            bar_sync(NB_W0 + wg, 128);
            if ((aa >> 1) == m) {
#pragma unroll
                for (int ks = 0; ks < 16; ks++) {
                    ldsm4t(wa[0][ks][0], wa[0][ks][1], wa[0][ks][2], wa[0][ks][3], fo + ks * 2048);
                    ldsm4t(wa[1][ks][0], wa[1][ks][1], wa[1][ks][2], wa[1][ks][3], (fo ^ 32) + ks * 2048);
                }
            }
            bar_sync(NB_W0 + wg, 128);
            if (m == 0) {
#pragma unroll 4
                for (int dd = 0; dd < 16; dd++) {
                    const int d = dd * 16 + (t128 >> 3), pp = pos_of_d(d);
                    cp_async16(stg + pp * 128 + ((ch ^ (pp & 7)) << 4), W + 64 + (size_t)d * HD_);
                }
                cp_async_commit();
            }
        }
    }
    bar_sync(NB_D, 384);
    const uint32_t tab = sb + R_TQ + wg * 26624 + (aa * 32 + lane) * 16;
    {
        const uint32_t l7 = lane & 7, l8 = lane >> 3, g = lane >> 2, t = lane & 3;
        const uint32_t bq = warp >> 1, tp = warp & 1;
        uint4 v;
        v.x = sb + R_QF + (rank * 8 + warp) * 512 + lane * 16;
        v.y = sb + R_QF + (warp == 5 ? 1024 : 0) + lane * 16;
        v.z = sb + R_KX + ((warp - 1) * 8 + l7) * 128 + ((l8 ^ l7) << 4);
        v.w = sb + R_SX + warp * 256 + lane * 8;
        sts128(tab, v);
        sts128(tab + 2048, make_uint4(sb + lane * 16 + R_MEM, sb + lane * 16 + R_WV + warp * 8192, sb + lane * 16 + R_VP + warp * 512, v.x));
        const uint32_t L = bq * 8 + 2 * tp + (l8 & 1) + 4 * (l8 >> 1);
        const uint32_t d0 = (((crank + ((t >> 1) | (g & 6))) & 7) << 1) | (crank >> 3);
        v.x = sb + R_RS + l7 * 512 + ((L ^ l7) << 4);
        v.y = mapa_u32(sb + R_MEM + ((crank & 7) * 4 + bq) * 128 + (4 * tp + 2 * (t & 1) + (g & 1)) * 16, d0);
        v.z = mapa_u32(sb + RB_A, d0);
        v.w = lane;
        sts128(tab + 4096, v);
        const uint64_t wr = (uint64_t)(g_F + ((crank * 2 + ((crank ^ (crank >> 3) ^ sel) & 1)) * 1024 + warp * 128 + cl * 32 + lane));
        sts128(tab + 6144, make_uint4((uint32_t)wr, (uint32_t)(wr >> 32), (uint32_t)((((cl + 1) & 3) - cl) * 128), (uint32_t)((((cl + 2) & 3) - cl) * 128)));
        sts32(tab + 8192, (uint32_t)((((cl + 3) & 3) - cl) * 128));
#pragma unroll
        for (int i = 0; i < NOFF; i++)
            sts128(tab + 10240 + i * 2048, make_uint4(wa[i & 1][OFFKS(i)][0], wa[i & 1][OFFKS(i)][1], wa[i & 1][OFFKS(i)][2], wa[i & 1][OFFKS(i)][3]));
    }
    bar_sync(NB_D, 384);
    uint4 tb = lds128(tab + 2048);
#pragma unroll 1
    for (int s = 0; s < NSEG; s++) {
        if (s > 0) mbar_wait(sb + RB_A, (s - 1) & 1);
        if (warp == 0) PROF(0);
        uint4 ta;
        const uint32_t par = (s & 1) * 8192;
        {
            float acc[5][4];
#pragma unroll
            for (int c = 0; c < 5; c++) { acc[c][0] = acc[c][1] = acc[c][2] = acc[c][3] = 0.f; }
            uint32_t b[8][4];
            uint4 av[16];
            static_assert(VK0 == 4, "order below assumes the V/O warps cover slices 0,1");
#define QK4(k2) do { \
                mma16816(acc[0], wa[0][2 * (k2)][0], wa[0][2 * (k2)][1], wa[0][2 * (k2)][2], wa[0][2 * (k2)][3], b[k2][0], b[k2][1]); \
                mma16816(acc[1], wa[1][2 * (k2)][0], wa[1][2 * (k2)][1], wa[1][2 * (k2)][2], wa[1][2 * (k2)][3], b[k2][0], b[k2][1]); \
                mma16816(acc[3], wa[0][2 * (k2) + 1][0], wa[0][2 * (k2) + 1][1], wa[0][2 * (k2) + 1][2], wa[0][2 * (k2) + 1][3], b[k2][2], b[k2][3]); \
                mma16816(acc[4], wa[1][2 * (k2) + 1][0], wa[1][2 * (k2) + 1][1], wa[1][2 * (k2) + 1][2], wa[1][2 * (k2) + 1][3], b[k2][2], b[k2][3]); } while (0)
#define V2(k2) do { \
                mma16816(acc[2], av[2 * (k2)].x, av[2 * (k2)].y, av[2 * (k2)].z, av[2 * (k2)].w, b[k2][0], b[k2][1]); \
                mma16816(acv, av[2 * (k2) + 1].x, av[2 * (k2) + 1].y, av[2 * (k2) + 1].z, av[2 * (k2) + 1].w, b[k2][2], b[k2][3]); } while (0)
#define LB(k2) ldsm4(b[k2][0], b[k2][1], b[k2][2], b[k2][3], tb.x + (k2) * 512)
#define LV(k2) do { av[2 * (k2)] = lds128(tb.y + 2 * (k2) * 512); av[2 * (k2) + 1] = lds128(tb.y + (2 * (k2) + 1) * 512); } while (0)
            float acv[4] = {0.f, 0.f, 0.f, 0.f};
            LB(0); LB(1); LB(2); LB(3);
            QK4(0); LB(4); QK4(1); LB(5); LV(2); LV(3); QK4(2); LB(6); QK4(3); LB(7);
            V2(2); V2(3); LV(4); LV(5);
            QK4(4); QK4(5); QK4(6); QK4(7);
            const uint4 f = make_uint4(movm(pack2(acc[0][0] + acc[3][0], acc[0][1] + acc[3][1])), movm(pack2(acc[0][2] + acc[3][2], acc[0][3] + acc[3][3])),
                                       movm(pack2(acc[1][0] + acc[4][0], acc[1][1] + acc[4][1])), movm(pack2(acc[1][2] + acc[4][2], acc[1][3] + acc[4][3])));
            st_async_v4((tb.w + par) ^ (1u << 24), f, (sb + RB_Q) ^ (1u << 24));
            sts128(tb.w + par, f);
            __syncwarp();
            if ((tb.w & 511) == 0) mbar_arrive(sb + RB_Q);
            if (warp == 0) PROF(1);
            if (tb.x == 0) break;
            LV(6); LV(7);
            ta = lds128(tab);
            V2(4); V2(5); V2(6); V2(7);
            sts128(tb.z, make_uint4(__float_as_uint(acc[2][0] + acv[0]), __float_as_uint(acc[2][1] + acv[1]), __float_as_uint(acc[2][2] + acv[2]), __float_as_uint(acc[2][3] + acv[3])));
            bar_arrive(NB_Y, 384);
        }
        if (warp == 0) PROF(14);
        if (warp < 6 && s != NSEG - 1) {
            float sa[4] = {0.f, 0.f, 0.f, 0.f}, sc[4] = {0.f, 0.f, 0.f, 0.f};
            const uint32_t qa = ta.y + par;
            if (warp == 0 || warp == 5) {
                mbar_wait(sb + RB_Q, s & 1);
                const uint4 q0 = lds128(qa), q1 = lds128(qa + 4096), k0 = lds128(qa + 2048), k1 = lds128(qa + 6144);
                const uint4 q2 = lds128(qa + 512), q3 = lds128(qa + 4608), k2 = lds128(qa + 2560), k3 = lds128(qa + 6656);
                mma16816h(sa, hadd2(q0.x, q1.x), hadd2(q0.y, q1.y), hadd2(k0.x, k1.x), hadd2(k0.y, k1.y));
                mma16816h(sc, hadd2(q0.z, q1.z), hadd2(q0.w, q1.w), hadd2(k0.z, k1.z), hadd2(k0.w, k1.w));
                mma16816h(sa, hadd2(q2.x, q3.x), hadd2(q2.y, q3.y), hadd2(k2.x, k3.x), hadd2(k2.y, k3.y));
                mma16816h(sc, hadd2(q2.z, q3.z), hadd2(q2.w, q3.w), hadd2(k2.z, k3.z), hadd2(k2.w, k3.w));
            } else {
                uint32_t k[16];
                const uint32_t kb = ta.z + 2 * par;
                mbar_wait(sb + RB_KV + (s & 1) * 8, (s >> 1) & 1);
                ldsm4(k[0], k[1], k[2], k[3], kb);
                ldsm4(k[4], k[5], k[6], k[7], kb ^ 64);
                ldsm4(k[8], k[9], k[10], k[11], kb + 4096);
                ldsm4(k[12], k[13], k[14], k[15], (kb ^ 64) + 4096);
                mbar_wait(sb + RB_Q, s & 1);
                uint4 q0[4], q1[4];
#pragma unroll
                for (int i = 0; i < 4; i++) { q0[i] = lds128(qa + i * 512); q1[i] = lds128(qa + 4096 + i * 512); }
                float sd[4] = {0.f, 0.f, 0.f, 0.f}, se[4] = {0.f, 0.f, 0.f, 0.f};
                mma16816h(sa, hadd2(q0[0].x, q1[0].x), hadd2(q0[0].y, q1[0].y), k[0], k[1]);
                mma16816h(sc, hadd2(q0[0].z, q1[0].z), hadd2(q0[0].w, q1[0].w), k[2], k[3]);
                mma16816h(sd, hadd2(q0[1].x, q1[1].x), hadd2(q0[1].y, q1[1].y), k[4], k[5]);
                mma16816h(se, hadd2(q0[1].z, q1[1].z), hadd2(q0[1].w, q1[1].w), k[6], k[7]);
                mma16816h(sa, hadd2(q0[2].x, q1[2].x), hadd2(q0[2].y, q1[2].y), k[8], k[9]);
                mma16816h(sc, hadd2(q0[2].z, q1[2].z), hadd2(q0[2].w, q1[2].w), k[10], k[11]);
                mma16816h(sd, hadd2(q0[3].x, q1[3].x), hadd2(q0[3].y, q1[3].y), k[12], k[13]);
                mma16816h(se, hadd2(q0[3].z, q1[3].z), hadd2(q0[3].w, q1[3].w), k[14], k[15]);
                sa[0] += sd[0]; sa[1] += sd[1]; sc[0] += se[0]; sc[1] += se[1];
            }
            const float scl = 0.08838834764831845f * 1.4426950408889634f;
            sts64f(ta.w, (sa[0] + sc[0]) * scl, (sa[1] + sc[1]) * scl);
            bar_arrive(NB_S, 320);
            if (warp == 0) PROF(2);
        } else if (warp == 7) {
            mbar_wait(sb + RB_Q, s & 1);
            if (lane == 0) {
                mbar_expect_tx(sb + RB_Q, 4096);
                if (s > 0) mbar_expect_tx(sb + RB_A, 4096);
            }
            __syncwarp();
        } else if (s > 0 && (s & 3) == 0 && warp == 6) {
            bar_sync(NB_K, 160);
            if (lane == 0) red_release(&g_flags[F_MEM + (s >> 2) - 1], 1);
            __syncwarp();
        }
        if (s == NSEG - 1) {
            const uint4 td = lds128(tab + 6144);
            stg_relaxed32((uint32_t*)(((uint64_t)td.y << 32) | (td.x ^ 0x21000)), 0u);
            break;
        }
        const uint4 tc = lds128(tab + 4096), td = lds128(tab + 6144);
        const uint32_t te = lds32(tab + 8192);
        uint32_t* wr = (uint32_t*)(((uint64_t)td.y << 32) | (td.x ^ ((s & 1) * 0x21000)));
        const uint32_t* r1p = (const uint32_t*)((const char*)wr + (int)td.z);
        const uint32_t* r2p = (const uint32_t*)((const char*)wr + (int)td.w);
        const uint32_t* r3p = (const uint32_t*)((const char*)wr + (int)te);
        const uint32_t tag = ((s >> 1) + 1) & 1;
        mbar_wait(sb + RB_E, s & 1);
        if (warp == 0) PROF(7);
        {
            uint32_t a0, a1, a2, a3;
            ldsm4t(a0, a1, a2, a3, tc.x);
            const uint32_t one = 0x3F803F80u;
            float d0_[4] = {0.f, 0.f, 0.f, 0.f}, d1_[4] = {0.f, 0.f, 0.f, 0.f};
            mma1688(d0_, a0, a1, one);
            mma1688(d1_, a2, a3, one);
            const bool t1 = tc.w & 1, t2 = tc.w & 2;
            const float x = t2 ? (t1 ? d1_[2] : d1_[0]) : (t1 ? d0_[2] : d0_[0]);
            const uint32_t own = (__float_as_uint(x) & ~1u) | tag;
            stg_relaxed32(wr, own);
            const uint32_t tq = clk32();
            if (warp == 0) PROF(8);
            while ((int)(clk32() - tq) < POLL_GAP) {}
            uint32_t f1 = ldg_relaxed32(r1p), f2 = ldg_relaxed32(r2p), f3 = ldg_relaxed32(r3p);
#pragma unroll
            for (int i = 0; i < NOFF; i++) {
                const uint4 f0 = lds128(tab + 10240 + i * 2048);
                wa[i & 1][OFFKS(i)][0] = f0.x; wa[i & 1][OFFKS(i)][1] = f0.y; wa[i & 1][OFFKS(i)][2] = f0.z; wa[i & 1][OFFKS(i)][3] = f0.w;
            }
            tb = lds128(tab + 2048);
            int gg = 0;
#pragma unroll 1
            while (!__all_sync(~0u, (((f1 ^ tag) | (f2 ^ tag) | (f3 ^ tag)) & 1) == 0)) {
                f1 = ldg_relaxed32(r1p); f2 = ldg_relaxed32(r2p); f3 = ldg_relaxed32(r3p);
                if (++gg > 16 * SPIN_LIMIT) { TIMEOUT(3, s); break; }
            }
            if (warp == 0) PROF(9);
            const float v = (__uint_as_float(own) + __uint_as_float(f2)) + (__uint_as_float(f1) + __uint_as_float(f3));
            const bool b8 = tc.w & 8, b16 = tc.w & 16;
            const float recv = __shfl_xor_sync(~0u, v, 8);
            const uint32_t word = b8 ? pack2(recv, v) : pack2(v, recv);
            const uint32_t oth = __shfl_xor_sync(~0u, word, 16);
            const uint32_t wl = b16 ? oth : word, wh = b16 ? word : oth;
            const uint32_t p0 = __shfl_xor_sync(~0u, wl, 2), p1 = __shfl_xor_sync(~0u, wh, 2);
            const uint4 item = t2 ? make_uint4(p0, p1, wl, wh) : make_uint4(wl, wh, p0, p1);
            st_async_v4(tc.y, item, tc.z);
            if (tc.w == 0 && warp == 7) mbar_expect_tx(sb + RB_E, 4096);
            if (warp == 0) PROF(10);
        }
    }
}

__device__ __forceinline__ void rec_load_kv(const RecParams& p, uint32_t sb, int head, int s) {
    const uint32_t bar = sb + RB_KV + (s & 1) * 8, d = sb + R_KX + (s & 1) * 16384;
    mbar_expect_tx(bar, 16384);
    tma_load2d(d, &p.tm_kv32, head * DH_, s * 32, bar);
    tma_load2d(d + 4096, &p.tm_kv32, head * DH_ + 64, s * 32, bar);
    tma_load2d(d + 8192, &p.tm_kv32, HD_ + head * DH_, s * 32, bar);
    tma_load2d(d + 12288, &p.tm_kv32, HD_ + head * DH_ + 64, s * 32, bar);
}
__device__ __forceinline__ void rec_store_kvm(uint32_t src, char* dst, int s, int w) {
    dst += (size_t)s * (8 * 2 * HD_ * 2);
    if (w < 2) {
        const uint4 a = lds128(src + (s & 1) * 8192), b = lds128(src + (s & 1) * 8192 + 4096);
        *(uint32_t*)dst = hadd2(a.x, b.x); *(uint32_t*)(dst + 16) = hadd2(a.y, b.y);
        *(uint32_t*)(dst + 32) = hadd2(a.z, b.z); *(uint32_t*)(dst + 48) = hadd2(a.w, b.w);
    } else {
        *(uint4*)dst = lds128(src + (s & 1) * 1024);
    }
}

__device__ __forceinline__ void rec_vo(const RecParams& p, const uint32_t sb, const int cta, const int warp, int lane) {
    const int w = warp - 8, crank = cta & 15, rank = cta & 1;
    uint32_t wo[4][8][4];
    const uint32_t tab = sb + R_TV + (w * 32 + lane) * 16;
    {
        const int t128 = w * 32 + lane;
        const bf16* Wo = p.wo + (size_t)(cta >> 1) * DH_ * D_ + rank * 256;
        const uint32_t stg = sb + R_STG + 2 * 32768;
#pragma unroll
        for (int half = 0; half < 2; half++) {
#pragma unroll 4
            for (int i = t128; i < 2048; i += 128) {
                const int e = i >> 5, ch = i & 31;
                cp_async16(stg + e * 512 + ((ch ^ (e & 7)) << 4), Wo + (size_t)(half * 64 + e) * D_ + ch * 8);
            }
            cp_async_commit();
            cp_async_wait<0>();
            bar_sync(NB_W0 + 2, 128);
#pragma unroll
            for (int j = 0; j < 4; j++)
#pragma unroll
                for (int kk = 0; kk < 4; kk++) {
                    const int e = kk * 16 + (lane >> 4) * 8 + (lane & 7);
                    const int ch = (w * 4 + j) * 2 + ((lane >> 3) & 1);
                    ldsm4t(wo[j][half * 4 + kk][0], wo[j][half * 4 + kk][1], wo[j][half * 4 + kk][2], wo[j][half * 4 + kk][3],
                           stg + e * 512 + ((ch ^ (e & 7)) << 4));
                }
            bar_sync(NB_W0 + 2, 128);
        }
        bar_sync(NB_D, 384);
        const uint32_t l7 = lane & 7, l8 = lane >> 3, g = lane >> 2;
        uint4 v;
        v.x = sb + R_VX + (w >> 1) * 4096 + ((l8 & 1) * 8 + l7) * 128 + (((4 * (w & 1) + (l8 >> 1)) ^ l7) << 4);
        v.y = sb + R_OS + (w >> 1) * 1024 + g * 128 + (((4 * (w & 1)) ^ g) << 4) + (lane & 3) * 4;
        v.z = sb + R_VMS + l7 * 128 + (((4 * (w & 1) + l8) ^ l7) << 4);
        v.w = sb + R_OS + l7 * 128 + ((l8 ^ l7) << 4);
        sts128(tab, v);
        v.x = mapa_u32(sb + R_RS + (crank >> 1) * 512 + ((lane ^ (crank >> 1)) << 4), rank * 8 + w * 2);
        v.y = mapa_u32(sb + RB_E, rank * 8 + w * 2);
        v.z = sb + R_VB + w * 512 + lane * 16;
        v.w = sb + R_SX + lane * 8;
        sts128(tab + 2048, v);
#pragma unroll
        for (int i = 0; i < 8; i++)
            sts128(tab + 4096 + i * 2048, make_uint4(wo[i >> 1][(i & 1) * 4][0], wo[i >> 1][(i & 1) * 4][1], wo[i >> 1][(i & 1) * 4][2], wo[i >> 1][(i & 1) * 4][3]));
        const int tok = (w & 1) * 4 + (lane >> 3);
        const uint64_t kd = w < 2 ? (uint64_t)(g_kvm + (g * (2 * HD_) + cta * 64 + w * 32 + (lane & 3) * 2))
                                  : (uint64_t)(g_kvm + (tok * (2 * HD_) + HD_ + cta * 64 + (lane & 7) * 8));
        const uint32_t ksrc = w < 2 ? sb + R_QF + (4 + 2 * rank + w) * 512 + lane * 16 : sb + R_VMS + tok * 128 + (((lane & 7) ^ tok) << 4);
        sts128(tab + 20480, make_uint4((uint32_t)kd, (uint32_t)(kd >> 32), ksrc, sb + lane * 16));
        if (t128 == 0) { wait_flag(F_KV + 0, 64); rec_load_kv(p, sb, cta >> 1, 0); mbar_wait(sb + RB_KV, 0); }
        __syncwarp();
    }
    bar_sync(NB_D, 384);
    const uint32_t lane16 = lds32(tab + 20480 + 12);
    uint4 av[8];
#pragma unroll
    for (int i = 0; i < 8; i++) av[i] = lds128(lane16 + R_WV + ((2 * w + (i >> 2)) * 16 + (i & 3)) * 512);
#pragma unroll 1
    for (int s = 0; s < NSEG; s++) {
        {
            if (s > 0) mbar_wait(sb + RB_A, (s - 1) & 1);
            if (s > 0) {
                const uint4 tp = lds128(tab + 20480);
                rec_store_kvm(tp.z, (char*)(((uint64_t)tp.y << 32) | tp.x), s - 1, w);
                if ((s & 3) == 0) bar_arrive(NB_K, 160);
            }
            if (s + 1 < NSEG - 1 && w == 3 && lane16 == sb) {
                if (((s + 1) & 3) == 0) wait_flag(F_KV + ((s + 1) >> 2), 64);
                rec_load_kv(p, sb, cta >> 1, s + 1);
            }
            __syncwarp();
        }
        uint4 vb;
        const uint4 ta = lds128(tab), tb = lds128(tab + 2048);
        {
            uint32_t bb[8];
            ldsm4(bb[0], bb[1], bb[2], bb[3], lane16 + R_MEM);
            ldsm4(bb[4], bb[5], bb[6], bb[7], lane16 + R_MEM + 512);
            float vd[4] = {0.f, 0.f, 0.f, 0.f}, ve[4] = {0.f, 0.f, 0.f, 0.f};
#pragma unroll
            for (int i = 0; i < 4; i++) {
                mma16816(vd, av[i].x, av[i].y, av[i].z, av[i].w, bb[2 * i], bb[2 * i + 1]);
                mma16816(ve, av[4 + i].x, av[4 + i].y, av[4 + i].z, av[4 + i].w, bb[2 * i], bb[2 * i + 1]);
            }
            bar_sync(NB_Y, 384);
            const uint4 a = lds128(lane16 + R_VP + w * 1024), b = lds128(lane16 + R_VP + w * 1024 + 512);
            vb = make_uint4(pack2(__uint_as_float(a.x) + vd[0], __uint_as_float(a.y) + vd[1]), pack2(__uint_as_float(a.z) + vd[2], __uint_as_float(a.w) + vd[3]),
                            pack2(__uint_as_float(b.x) + ve[0], __uint_as_float(b.y) + ve[1]), pack2(__uint_as_float(b.z) + ve[2], __uint_as_float(b.w) + ve[3]));
            st_async_v4(tb.z ^ (1u << 24), vb, (sb + RB_V) ^ (1u << 24));
        }
        if (w == 0) PROF(11);
        if (s != NSEG - 1) {
            uint32_t vx[16];
            const uint32_t vxa = ta.x + (s & 1) * 16384;
            mbar_wait(sb + RB_KV + (s & 1) * 8, (s >> 1) & 1);
            ldsm4t(vx[0], vx[1], vx[2], vx[3], vxa);
            ldsm4t(vx[4], vx[5], vx[6], vx[7], vxa ^ 32);
            ldsm4t(vx[8], vx[9], vx[10], vx[11], vxa + 2048);
            ldsm4t(vx[12], vx[13], vx[14], vx[15], (vxa ^ 32) + 2048);
#pragma unroll
            for (int i = 0; i < 4; i++) {
                const uint4 f0 = lds128(tab + 4096 + i * 2048);
                wo[i >> 1][(i & 1) * 4][0] = f0.x; wo[i >> 1][(i & 1) * 4][1] = f0.y; wo[i >> 1][(i & 1) * 4][2] = f0.z; wo[i >> 1][(i & 1) * 4][3] = f0.w;
            }
            bar_sync(NB_S, 320);
            if (w == 0) PROF(4);
            float sv[10];
#pragma unroll
            for (int n = 0; n < 5; n++) { const float2 a = lds64f(tb.w + n * 256); sv[2 * n] = a.x; sv[2 * n + 1] = a.y; }
            { const float2 a = lds64f(tb.w + 5 * 256); sv[0] += a.x; sv[1] += a.y; }
            float mx = fmaxf(fmaxf(fmaxf(sv[2], sv[3]), fmaxf(sv[4], sv[5])), fmaxf(fmaxf(sv[6], sv[7]), fmaxf(sv[8], sv[9])));
            mx = fmaxf(mx, fmaxf(sv[0], sv[1]));
            mx = fmaxf(mx, __shfl_xor_sync(~0u, mx, 1));
            mx = fmaxf(mx, __shfl_xor_sync(~0u, mx, 2));
            mbar_wait(sb + RB_V, s & 1);
            const uint4 vo = lds128(tb.z);
            uint32_t pf[5];
#pragma unroll
            for (int n = 0; n < 5; n++) pf[n] = pack2(ex2(sv[2 * n] - mx), ex2(sv[2 * n + 1] - mx));
            vb = make_uint4(hadd2(vb.x, vo.x), hadd2(vb.y, vo.y), hadd2(vb.z, vo.z), hadd2(vb.w, vo.w));
            if (w == 0) PROF(12);
            float oa[4][4] = {{0.f, 0.f, 0.f, 0.f}, {0.f, 0.f, 0.f, 0.f}, {0.f, 0.f, 0.f, 0.f}, {0.f, 0.f, 0.f, 0.f}}, sm[4] = {0.f, 0.f, 0.f, 0.f};
            const uint32_t one = 0x3F803F80u;
            mma1688h(sm, pf[0], one);
            mma1688h(oa[0], pf[0], vb.x);
            mma1688h(oa[1], pf[0], vb.y);
            mma1688h(oa[2], pf[0], vb.z);
            mma1688h(oa[3], pf[0], vb.w);
            mma16816h(sm, pf[1], pf[2], one, one);
#pragma unroll
            for (int n = 0; n < 4; n++) mma16816h(oa[n], pf[1], pf[2], vx[2 * n], vx[2 * n + 1]);
            mma16816h(sm, pf[3], pf[4], one, one);
#pragma unroll
            for (int n = 0; n < 4; n++) mma16816h(oa[n], pf[3], pf[4], vx[8 + 2 * n], vx[8 + 2 * n + 1]);
            float inv;
            asm("rcp.approx.ftz.f32 %0, %1;" : "=f"(inv) : "f"(sm[0]));
#pragma unroll
            for (int n = 0; n < 4; n++) sts32(ta.y ^ (n << 4), pack2(oa[n][0] * inv, oa[n][1] * inv));
            bar_sync(NB_C, 128);
            if (w == 0) PROF(5);
            uint32_t ob[16];
            ldsm4(ob[0], ob[1], ob[2], ob[3], ta.w);
            ldsm4(ob[8], ob[9], ob[10], ob[11], ta.w + 1024);
            ldsm4(ob[4], ob[5], ob[6], ob[7], ta.w ^ 64);
            ldsm4(ob[12], ob[13], ob[14], ob[15], (ta.w ^ 64) + 1024);
#pragma unroll
            for (int i = 4; i < 8; i++) {
                const uint4 f0 = lds128(tab + 4096 + i * 2048);
                wo[i >> 1][(i & 1) * 4][0] = f0.x; wo[i >> 1][(i & 1) * 4][1] = f0.y; wo[i >> 1][(i & 1) * 4][2] = f0.z; wo[i >> 1][(i & 1) * 4][3] = f0.w;
            }
#pragma unroll
            for (int jj = 0; jj < 2; jj++) {
                if (jj == 1 && tb.w == 0) break;
                float acc[4][4];
#pragma unroll
                for (int c = 0; c < 4; c++) { acc[c][0] = acc[c][1] = acc[c][2] = acc[c][3] = 0.f; }
#pragma unroll
                for (int k4 = 0; k4 < 4; k4++)
#pragma unroll
                    for (int c = 0; c < 4; c++) {
                        const int tl = jj * 2 + (c >> 1), ks = (c & 1) * 4 + k4;
                        mma16816(acc[c], wo[tl][ks][0], wo[tl][ks][1], wo[tl][ks][2], wo[tl][ks][3], ob[2 * ks], ob[2 * ks + 1]);
                    }
                uint4 v;
                v.x = pack2(acc[0][0] + acc[1][0], acc[0][1] + acc[1][1]);
                v.y = pack2(acc[0][2] + acc[1][2], acc[0][3] + acc[1][3]);
                v.z = pack2(acc[2][0] + acc[3][0], acc[2][1] + acc[3][1]);
                v.w = pack2(acc[2][2] + acc[3][2], acc[2][3] + acc[3][3]);
                st_async_v4(tb.x + (jj << 24), v, tb.y + (jj << 24));
            }
            if (w == 0) PROF(6);
        } else {
            mbar_wait(sb + RB_V, s & 1);
            const uint4 o = lds128(tb.z);
            vb = make_uint4(hadd2(vb.x, o.x), hadd2(vb.y, o.y), hadd2(vb.z, o.z), hadd2(vb.w, o.w));
            mbar_wait(sb + RB_Q, s & 1);
        }
        if ((w >> 1) == rank) stsm4t(ta.z + (s & 1) * 1024, vb.x, vb.y, vb.z, vb.w);
        bar_sync(NB_C, 128);
        if (s != NSEG - 1 && w == 0 && lane16 == sb) mbar_expect_tx(sb + RB_V, 2048);
#pragma unroll
        for (int i = 0; i < 8; i++) av[i] = lds128(lane16 + R_WV + ((2 * w + (i >> 2)) * 16 + (i & 3)) * 512);
    }
    {
        const uint4 tp = lds128(tab + 20480);
        rec_store_kvm(tp.z, (char*)(((uint64_t)tp.y << 32) | tp.x), NSEG - 1, w);
    }
    bar_sync(NB_C, 128);
    if (w == 0 && lane == 0) red_release(&g_flags[F_MEM + NRB - 1], 1);
}

__global__ void __launch_bounds__(384, 1) k_rec(const __grid_constant__ RecParams p) {
    extern __shared__ __align__(1024) unsigned char smem_raw[];
    const uint32_t sb = __shfl_sync(~0u, smem_u32(smem_raw), 0);
    const int warp = __shfl_sync(~0u, threadIdx.x >> 5, 0);
    int lane; asm volatile("mov.u32 %0, %%laneid;" : "=r"(lane));
    const int crank = blockIdx.x & 15, slot = blockIdx.x >> 4;
    asm volatile("griddepcontrol.launch_dependents;");
    if (crank == 0 && threadIdx.x == 0) {
        stg_relaxed32(&g_F[65536 + slot * 64], 0u);
        stg_relaxed32(&g_F[65536 + 1024 + slot * 64], 0u);
    }
    if (threadIdx.x == 0) {
        mbar_init(sb + RB_Q, 9); mbar_init(sb + RB_V, 1); mbar_init(sb + RB_E, 1); mbar_init(sb + RB_A, 1); mbar_init(sb + RB_ROLE, 1);
        mbar_init(sb + RB_KV, 1); mbar_init(sb + RB_KV + 8, 1);
        asm volatile("fence.mbarrier_init.release.cluster;" ::: "memory");
        mbar_expect_tx(sb + RB_Q, 4096);
        mbar_expect_tx(sb + RB_V, 2048);
        mbar_expect_tx(sb + RB_E, 4096);
        mbar_expect_tx(sb + RB_A, 4096);
        mbar_expect_tx(sb + RB_ROLE, 4);
    }
    asm volatile("barrier.cluster.arrive.relaxed.aligned;\nbarrier.cluster.wait.aligned;" ::: "memory");
    unsigned role = 0;
    if (crank == 0 && threadIdx.x == 0 && !p.only_pre) {
        unsigned x = 0;
        int tm[2] = {0x7fffffff, 0x7fffffff};
#pragma unroll 1
        for (int i = 0; i < 6; i++) {
            const uint32_t t0 = clk32();
            x = atomicAdd(&g_F[65536 + (i & 1) * 1024 + slot * 64 + (x >> 31)], 1u);
            if (x != (unsigned)(i >> 1)) sts32(sb + R_BAR + 56, x);
            const int dt = (int)(clk32() - t0);
            if (i >= 2) { if (i & 1) tm[1] = min(tm[1], dt); else tm[0] = min(tm[0], dt); }
        }
        const int side = tm[1] > tm[0];
        const unsigned old = atomicAdd(&g_flags[F_SIDE + side * 32], 1u);
        unsigned c0, c1; int gd = 0;
#pragma unroll 1
        do { c0 = ldg_relaxed32(&g_flags[F_SIDE]); c1 = ldg_relaxed32(&g_flags[F_SIDE + 32]); } while ((int)(c0 + c1) < p.ncl && ++gd < 64 * SPIN_LIMIT);
        const int big = c1 > c0;
        role = side == big ? old : (big ? c1 : c0) + old;
        role |= (big ^ 1) << 8;
    }
    __syncwarp();
    if (crank == 0 && warp == 0 && !p.only_pre) {
        role = __shfl_sync(~0u, role, 0);
        if (lane < 16)
            asm volatile("st.async.weak.shared::cluster.mbarrier::complete_tx::bytes.u32 [%0], %1, [%2];"
                         :: "r"(mapa_u32(sb + R_BAR + 48, lane)), "r"(role), "r"(mapa_u32(sb + RB_ROLE, lane)) : "memory");
    }
    if (warp >= 4) {
        const int w8 = warp - 4, nblk = gridDim.x;
        const int cq = lane & 3, rg = w8 * 8 + (lane >> 2);
        const uint32_t red = sb + R_VP;
        const int row0 = blockIdx.x * 8 + w8;
        const uint4* xr = (const uint4*)(p.x + (size_t)row0 * D_);
        uint4 xa = __ldg(xr + lane), xb = __ldg(xr + 32 + lane);
#pragma unroll 1
        for (int sl = blockIdx.x; sl < 96; sl += nblk) {
            uint4 wv[8];
#pragma unroll
            for (int i = 0; i < 8; i++) wv[i] = __ldg((const uint4*)(p.w_mod + (size_t)(rg * 8 + i) * (6 * D_) + sl * 32 + cq * 8));
            const uint32_t cw = __ldg((const uint32_t*)(p.c + rg * 8) + cq);
            const float cl = bflo(cw), ch = bfhi(cw);
            const uint32_t sw = pack2(__fdividef(cl, 1.f + __expf(-cl)), __fdividef(ch, 1.f + __expf(-ch)));
            float a[8];
#pragma unroll
            for (int i = 0; i < 8; i++) a[i] = 0.f;
#pragma unroll
            for (int i = 0; i < 8; i++) {
                const uint32_t sv = __shfl_sync(~0u, sw, (lane & 28) + (i >> 1));
                const float cv = (i & 1) ? bfhi(sv) : bflo(sv);
                a[0] = fmaf(cv, bflo(wv[i].x), a[0]); a[1] = fmaf(cv, bfhi(wv[i].x), a[1]); a[2] = fmaf(cv, bflo(wv[i].y), a[2]); a[3] = fmaf(cv, bfhi(wv[i].y), a[3]);
                a[4] = fmaf(cv, bflo(wv[i].z), a[4]); a[5] = fmaf(cv, bfhi(wv[i].z), a[5]); a[6] = fmaf(cv, bflo(wv[i].w), a[6]); a[7] = fmaf(cv, bfhi(wv[i].w), a[7]);
            }
#pragma unroll
            for (int i = 0; i < 8; i++) { a[i] += __shfl_xor_sync(~0u, a[i], 4); a[i] += __shfl_xor_sync(~0u, a[i], 8); a[i] += __shfl_xor_sync(~0u, a[i], 16); }
            if (lane < 4) {
                sts128(red + w8 * 128 + lane * 32, make_uint4(__float_as_uint(a[0]), __float_as_uint(a[1]), __float_as_uint(a[2]), __float_as_uint(a[3])));
                sts128(red + w8 * 128 + lane * 32 + 16, make_uint4(__float_as_uint(a[4]), __float_as_uint(a[5]), __float_as_uint(a[6]), __float_as_uint(a[7])));
            }
            bar_sync(NB_B, 256);
            if (w8 == 0) {
                float v = 0.f;
#pragma unroll
                for (int i = 0; i < 8; i++) v += lds32f(red + i * 128 + lane * 4);
                g_mod[sl * 32 + lane] = __float2bfloat16_rn(v);
                __syncwarp();
                if (lane == 0) red_release(&g_flags[F_MOD + (sl >= 32)], 1);
            }
            bar_sync(NB_B, 256);
        }
        uint32_t c1[8], sm[8];
        int row = row0;
#pragma unroll 1
        while (true) {
            const uint32_t v[8] = {xa.x, xa.y, xa.z, xa.w, xb.x, xb.y, xb.z, xb.w};
            uint32_t mu2, r[8]; float rden;
            ln_stats(v, mu2, rden);
            if (row == row0) {
                if (lane == 0) wait_flag(F_MOD, 32);
                __syncwarp();
                load_mod8(g_mod + D_, lane, c1);
                load_mod8(g_mod, lane, sm);
#pragma unroll
                for (int i = 0; i < 8; i++) c1[i] = hadd2(c1[i], 0x3F803F80u);
            } else if (row + 512 < S_) {
                xr = (const uint4*)(p.x + (size_t)(row + 512) * D_); xa = __ldg(xr + lane); xb = __ldg(xr + 32 + lane);
            }
            ln_apply(v, mu2, rden, c1, sm, r);
            uint4* hr = (uint4*)(g_h + (size_t)row * D_);
            hr[lane] = make_uint4(r[0], r[1], r[2], r[3]); hr[32 + lane] = make_uint4(r[4], r[5], r[6], r[7]);
            bar_sync(NB_B, 256);
            if (w8 == (row >> 7 & 7) && lane == 0) red_release(&g_flags[F_H + (row >> 7)], 1);
            __syncwarp();
            if (row == row0) {
                if (!p.only_pre) mbar_wait(sb + RB_ROLE, 0);
                const int cl = p.only_pre ? slot : (int)(lds32(sb + R_BAR + 48) & 255);
                row = cl < 4 ? (nblk + cl * 16 + crank) * 8 + w8 : S_;
                if (row < S_) { xr = (const uint4*)(p.x + (size_t)row * D_); xa = __ldg(xr + lane); xb = __ldg(xr + 32 + lane); }
            } else {
                row += 512;
            }
            if (row >= S_) break;
        }
    }
    if (p.only_pre) return;
    mbar_wait(sb + RB_ROLE, 0);
    const int rolew = __shfl_sync(~0u, lds32(sb + R_BAR + 48), 0);
    const int cl = rolew & 255;
    if (cl >= 4) return;
    const int cta = cl * 16 + crank;
    if (warp < 8) rec_qk(p, sb, cta, warp, lane, rolew >> 8);
    else rec_vo(p, sb, cta, warp, lane);
}

enum { J_KV = 0, J_QA = 1, J_O = 2, J_LN = 3, J_UP = 4, J_DN = 5, J_UP2 = 8, J_END = 9 };
constexpr int NJ_O = 2 * OSPLIT, NJ_O2 = 2 * OSPLIT2, NJ_LN = 8, NJ_LN2 = 16, NJ_UP = 14, NJ_UP2 = 28, NJ_DN = 8, NJ_LN1 = 8  ;
constexpr uint64_t pk8(int a, int b, int c, int d, int e, int f, int g, int h) {
    return (uint64_t)a | ((uint64_t)b << 8) | ((uint64_t)c << 16) | ((uint64_t)d << 24) | ((uint64_t)e << 32) | ((uint64_t)f << 40) | ((uint64_t)g << 48) | ((uint64_t)h << 56);
}
constexpr uint64_t NJ_C = pk8(32, 16, NJ_O, NJ_LN, NJ_UP, NJ_DN, 0, 0), NJ_F = pk8(32, 16, NJ_O2, NJ_LN2, NJ_UP2, NJ_DN, 0, 0);
constexpr uint64_t TG_C = pk8(2 * NJ_LN1, 64, 32, 2 * NJ_O, 2 * NJ_LN, 2 * NJ_UP, 32, 0), TG_F = pk8(2 * NJ_LN1, 64, 32, 2 * NJ_O2, 2 * NJ_LN2, 2 * NJ_UP2, 32, 0);
constexpr uint64_t NJ_L = pk8(32, 32, 2 * OSPLIT3, NJ_LN2, NJ_UP2, 2 * NJ_DN, 0, 0), TG_L = pk8(2 * NJ_LN1, 64, 64, 4 * OSPLIT3, 2 * NJ_LN2, 2 * NJ_UP2, 32, 0);
__device__ __forceinline__ uint64_t nj_tab(int rb) { return rb < FINE_RB ? NJ_C : (rb < NRB - 1 ? NJ_F : NJ_L); }
__device__ __forceinline__ uint64_t tg_tab(int rb) { return rb < FINE_RB ? TG_C : (rb < NRB - 1 ? TG_F : TG_L); }
__device__ __forceinline__ int o_nk(int rb) { return rb < FINE_RB ? 64 / OSPLIT : (rb < NRB - 1 ? 64 / OSPLIT2 : 64 / OSPLIT3); }
constexpr uint64_t PRIO = pk8(4, 10, 9, 8, 7, 6, 3, 0);
__device__ __forceinline__ int pick_job(int lane, int qmask, int& idx) {
    const int rb = lane & 15, half = lane >> 4;
    const uint64_t nj = nj_tab(rb) >> (8 * half);
    const uint64_t tg = tg_tab(rb) >> (8 * half);
    const unsigned* cp = &g_flags[F_CLAIM + half * 32 + rb];
    const unsigned* dp = &g_flags[half * 32 + rb];
    int gd = 0;
#pragma unroll 1
    while (true) {
        const unsigned c0 = ldg_relaxed32(cp), c1 = ldg_relaxed32(cp + 64), c2 = ldg_relaxed32(cp + 128);
        const unsigned d0 = ldg_relaxed32(dp - (half && rb ? 1 : 0)), d1 = ldg_relaxed32(dp + 64), d2 = ldg_relaxed32(dp + 128);
        const unsigned cl[3] = {c0, c1, c2}, dv[3] = {d0, d1, d2};
        unsigned key = 0xffffu, key2 = 0xffffu;
        bool pre = false;
#pragma unroll
        for (int i = 0; i < 3; i++) {
            const int q = half + 2 * i;
            const bool have = ((qmask >> q) & 1) && cl[i] < (unsigned)((nj >> (16 * i)) & 255);
            bool ready = have && dv[i] >= (unsigned)((tg >> (16 * i)) & 255);
            unsigned pr = (unsigned)((PRIO >> (8 * q)) & 255);
            if (i == 0 && rb <= 1 - half) ready = have;
            if (i == 0 && half && rb >= FINE_RB) pr = 5;
            if (ready) key = min(key, (pr << 8) | (rb << 4) | q);
            if (have) key2 = min(key2, rb >= FINE_RB ? (0x100u | (q << 4) | rb) : (i == 0 ? 0u : 0x1000u));
            pre |= have && i == 0 && !half;
        }
        const bool anypre = __any_sync(~0u, pre);
        if (anypre && (key & 15) == J_QA) key = 0xffffu;
        key = __reduce_min_sync(~0u, key);
        key2 = __reduce_min_sync(~0u, key2);
        if (key2 == 0xffffu) return J_END;
        int pq, prb;
        if (key != 0xffffu) { pq = key & 15; prb = (key >> 4) & 15; }
        else if (key2 >= 0x120u && key2 < 0x1000u) { pq = (key2 >> 4) & 15; prb = key2 & 15; }
        else {
            __nanosleep(IDLE_NS);
            if (++gd > 16 * SPIN_LIMIT) { TIMEOUT(5, 0); return J_END; }
            continue;
        }
        int c = 0;
        if (lane == 0) c = (int)atomicAdd(&g_flags[F_CLAIM + pq * 32 + prb], 1u);
        c = __shfl_sync(~0u, c, 0);
        if (c < (int)((nj_tab(prb) >> (8 * pq)) & 255)) {
            idx = pq * 512 + prb * 32 + c;
            int acq = 0;
            if (pq != J_QA) {
                if (lane == 0 && ld_acquire(&g_flags[pq * 32 + prb]) >= (unsigned)((tg_tab(prb) >> (8 * pq)) & 255)) {
                    asm volatile("fence.proxy.async.global;" ::: "memory");
                    acq = 1 << 24;
                }
            }
            return (pq == J_UP && prb >= FINE_RB ? J_UP2 : pq) | (prb << 8) | (c << 16) | acq;
        }
    }
}
__device__ __forceinline__ int op_row(int rb, int split) {
    return rb < FINE_RB ? split * S_ + rb * 128
                        : (rb < NRB - 1 ? OSPLIT * S_ + (split * (NRB - FINE_RB) + rb - FINE_RB) * 128 : OSPLIT * S_ + (OSPLIT2 * (NRB - FINE_RB) + split) * 128);
}

struct Pipe { uint32_t stage, phase; };
__device__ __forceinline__ void pipe_next(Pipe& p) { if (++p.stage == W_NST) { p.stage = 0; p.phase ^= 1; } }

__device__ __forceinline__ void scheduler(const Params& p, uint32_t sb, int lane) {
    const uint32_t bars = sb + SM_BAR;
    uint32_t ph = 0;
#pragma unroll 1
    while (true) {
        mbar_wait(bars + B_REQ, ph);
        int j = 4095;
        const int jd = pick_job(lane, p.qmask, j);
        if (lane == 0) { sts32(bars + B_NEXT, (uint32_t)jd); sts32(bars + B_NEXT + 4, (uint32_t)j); mbar_arrive(bars + B_RSP); }
        ph ^= 1;
        if (jd == J_END) break;
        __syncwarp();
    }
}

__device__ __forceinline__ void producer(const Params& p, uint32_t sb) {
    Pipe pp{0, 1};
    const uint32_t bars = sb + SM_BAR;
    uint32_t seq = 0, h_seen = 0;
    mbar_arrive(bars + B_REQ);
#pragma unroll 1
    while (true) {
        mbar_wait(bars + B_RSP, seq & 1);
        const int jd = (int)lds32(bars + B_NEXT), j = (int)lds32(bars + B_NEXT + 4);
        int left = (jd & 255) == J_DN ? 15 : ((jd & 255) == J_O ? o_nk((jd >> 8) & 255) : ((jd & 255) == J_LN ? 1 : 8));
        left = (jd & 255) == J_QA ? 9 : max(left - PICK_AHEAD, 1);
        TR(j, 1);
        const int type = jd & 255, rb = (jd >> 8) & 255, cb = (jd >> 16) & 255;
        const bool fine = rb >= FINE_RB, acquired = (jd >> 24) & 1;
        bool first = true;
        auto begin_stage = [&](uint32_t bytes) -> uint32_t {
            mbar_wait(bars + B_EMPTY + pp.stage * 8, pp.phase);
            if (first) { sts32(bars + B_RING + (seq & 7) * 4, (uint32_t)jd); sts32(bars + B_RING + 32 + (seq & 7) * 4, (uint32_t)j); first = false; }
            const uint32_t fb = bars + B_FULL + pp.stage * 8;
            if (bytes) mbar_expect_tx(fb, bytes); else mbar_arrive(fb);
            return fb;
        };
        auto end_stage = [&]() {
            pipe_next(pp);
            if (--left == 0) mbar_arrive(bars + B_REQ);
        };
        if (type == J_END || type == J_LN) {
            if (type == J_LN && !(h_seen >> 31)) { wait_flag(F_MOD + 1, 64); h_seen |= 1u << 31; }

            TR(j, 2);
            begin_stage(0);
            if (type == J_END) break;
            if (!acquired) wait_flag(F_OP + rb, (unsigned)((tg_tab(rb) >> (8 * J_LN)) & 255));
            end_stage();
            seq++;
            continue;
        }
        const CUtensorMap *ta, *tb0, *tb1;
        int k0 = 0, nk = 8, n0 = cb * 256, n1 = n0 + 128, nb = 4, dep = -1;
        unsigned tgt = 0;
        switch (type) {
            case J_KV: ta = &p.tm_h; tb0 = tb1 = cb < 16 ? &p.tm_wk : &p.tm_wv; n0 = (cb & 15) * 256; n1 = n0 + 128; dep = F_H + rb; tgt = 2 * NJ_LN1; break;
            case J_QA: ta = &p.tm_h; tb0 = tb1 = &p.tm_wq; dep = F_H + rb; tgt = 2 * NJ_LN1; if (rb == NRB - 1) { n0 = (cb >> 1) * 256; n1 = n0 + 128; } break;
            case J_O: ta = &p.tm_o; tb0 = tb1 = &p.tm_wo; n0 = (cb & 1) * 256; n1 = n0 + 128; nk = o_nk(rb); k0 = (cb >> 1) * nk * 64;
                      dep = F_O + rb; tgt = rb == NRB - 1 ? 64 : 32; break;
            case J_UP: ta = &p.tm_h2; tb0 = &p.tm_wg; tb1 = &p.tm_wu; n0 = n1 = cb * 128; dep = F_H2 + rb; tgt = 2 * NJ_LN; break;
            case J_UP2: ta = &p.tm_h2; tb0 = &p.tm_wg; tb1 = &p.tm_wu; n0 = n1 = cb * 64; nb = 2; dep = F_H2 + rb; tgt = 2 * NJ_LN2; break;
            default: ta = &p.tm_act; tb0 = tb1 = &p.tm_wd; n0 = cb * 64; nk = 0; break;
        }
        const int m0 = rb * 128;
        if (type == J_DN && rb == NRB - 1) {
            n0 = (cb >> 1) * 64;
            const int mh = m0 + (cb & 1) * 64;
#pragma unroll 1
            for (int kb = 0; kb < 14; kb++) {
                const uint32_t fb = begin_stage(32768);
                const uint32_t st = sb + pp.stage * W_STAGE;
                const int k = kb * 128;
                tma_load2d(st + 32768, tb0, n0, k, fb);
                tma_load2d(st + 40960, tb0, n0, k + 64, fb);
                if (kb == 0) { if (!acquired) { wait_flag(F_ACT + rb, 2 * NJ_UP2); asm volatile("fence.proxy.async.global;" ::: "memory"); } TR(j, 2); }
                tma_load2d(st, ta, k, mh, fb);
                tma_load2d(st + 8192, ta, k + 64, mh, fb);
                end_stage();
            }
            const uint32_t fb = begin_stage(8192);
            tma_load2d(sb + pp.stage * W_STAGE, &p.tm_x1, n0, mh, fb);
            end_stage();
            seq++;
            continue;
        }
        if (type == J_DN) {
#pragma unroll 1
            for (int kb = 0; kb < 14; kb++) {
                const uint32_t fb = begin_stage(49152);
                const uint32_t st = sb + pp.stage * W_STAGE;
                const int k = kb * 128;
                tma_load2d(st + 32768, tb0, n0, k, fb);
                tma_load2d(st + 40960, tb0, n0, k + 64, fb);
                if (kb == 0) { if (!acquired) { wait_flag(F_ACT + rb, 2 * (fine ? NJ_UP2 : NJ_UP)); asm volatile("fence.proxy.async.global;" ::: "memory"); } TR(j, 2); }
                tma_load2d(st, ta, k, m0, fb);
                tma_load2d(st + 8192, ta, k, m0 + 64, fb);
                tma_load2d(st + 16384, ta, k + 64, m0, fb);
                tma_load2d(st + 24576, ta, k + 64, m0 + 64, fb);
                end_stage();
            }
        }
#pragma unroll 1
        for (int kb = 0; kb < nk; kb++) {
            const uint32_t fb = begin_stage(16384 + nb * 8192);
            const uint32_t st = sb + pp.stage * W_STAGE;
            const int k = k0 + kb * 64;
            tma_load2d(st + 16384, tb0, n0, k, fb);
            if (nb == 4) {
                tma_load2d(st + 16384 + 8192, tb0, n0 + 64, k, fb);
                tma_load2d(st + 16384 + 16384, tb1, n1, k, fb);
                tma_load2d(st + 16384 + 24576, tb1, n1 + 64, k, fb);
            } else if (nb == 2) {
                tma_load2d(st + 16384 + 8192, tb1, n1, k, fb);
            }
            if (kb == 0) {
                if (acquired && dep < 16) h_seen |= 1u << dep;
                if (dep >= 0 && !acquired && !(dep < 16 && ((h_seen >> dep) & 1))) {
                    wait_flag(dep, tgt);
                    if (type != J_O) asm volatile("fence.proxy.async.global;" ::: "memory");
                    if (dep < 16) h_seen |= 1u << dep;
                }
                TR(j, 2);
            }
            tma_load2d(st, ta, k, m0, fb);
            tma_load2d(st + 8192, ta, k, m0 + 64, fb);
            end_stage();
        }
        if (type == J_QA) {
            wait_flag(F_KV + rb, 64);
#pragma unroll 1
            for (int i = 0; i < (rb == NRB - 1 ? 2 : 4); i++) {
                const uint32_t fb = begin_stage(40960);
                const uint32_t st = sb + pp.stage * W_STAGE;
                const int col = (i & 1) * HD_ + (rb == NRB - 1 ? cb : cb * 2 + (i >> 1)) * DH_;
                tma_load2d(st, &p.tm_kv, col, m0, fb);
                tma_load2d(st + 8192, &p.tm_kv, col, m0 + 64, fb);
                tma_load2d(st + 16384, &p.tm_kv, col + 64, m0, fb);
                tma_load2d(st + 24576, &p.tm_kv, col + 64, m0 + 64, fb);
                if (i == 0) { wait_flag(F_MEM + rb, 64); asm volatile("fence.proxy.async.global;" ::: "memory"); }
                tma_load2d(st + 32768, &p.tm_kvm, col, rb * 32, fb);
                tma_load2d(st + 36864, &p.tm_kvm, col + 64, rb * 32, fb);
                end_stage();
            }
        } else if (type == J_DN) {
            const uint32_t fb = begin_stage(16384);
            const uint32_t st = sb + pp.stage * W_STAGE;
            tma_load2d(st, &p.tm_x1, n0, m0, fb);
            tma_load2d(st + 8192, &p.tm_x1, n0, m0 + 64, fb);
            end_stage();
        }
        seq++;
    }
}

__device__ __forceinline__ void store_warp(const Params& p, uint32_t sb, int wg, int lane) {
    const uint32_t bars = sb + SM_BAR;
    uint32_t seq = 0;
#pragma unroll 1
    while (true) {
        bar_sync(NB_ST + wg, 160);
        const uint32_t jd = lds32(bars + B_RING + (seq & 7) * 4);
        seq++;
        const int type = jd & 255, rb = (jd >> 8) & 255, cb = (jd >> 16) & 255;
        if (type == J_END) break;
        const uint32_t src = sb + W_STG + wg * 16384;
        const CUtensorMap* tm = nullptr; int n0 = cb * 256, nbox = 4, mrow = rb * 128 + wg * 64, flag = 0;
        switch (type) {
            case J_KV: tm = &p.tm_kv; flag = F_KV + rb; break;
            case J_QA: tm = &p.tm_o; flag = F_O + rb; if (rb == NRB - 1) { n0 = cb * 128; nbox = 2; } break;
            case J_O: tm = &p.tm_op; n0 = (cb & 1) * 256; mrow = op_row(rb, cb >> 1) + wg * 64; flag = F_OP + rb; break;
            case J_LN: flag = F_H2 + rb; nbox = 0; break;
            case J_UP: tm = &p.tm_act; n0 = cb * 128; nbox = 2; flag = F_ACT + rb; break;
            case J_UP2: tm = &p.tm_act; n0 = cb * 64; nbox = 1; flag = F_ACT + rb; break;
            default: tm = &p.tm_out; n0 = cb * 64; nbox = 1; flag = -1;
                     if (rb == NRB - 1) { n0 = (cb >> 1) * 64; mrow = rb * 128 + (cb & 1) * 64; nbox = wg == 0; } break;
        }
        if (nbox == 4) {
            if (lane == 0) {
                tma_store2d(tm, src, n0, mrow);
                tma_store2d(tm, src + 8192, n0 + 64, mrow);
                bulk_commit();
                asm volatile("cp.async.bulk.wait_group.read 0;" ::: "memory");
                mbar_arrive(bars + B_STGFREE + wg * 8);
            }
            __syncwarp();
            bar_sync(NB_ST + wg, 160);
            n0 += 128; nbox = 2;
        }
        if (lane == 0) {
            if (nbox) {
                tma_store2d(tm, src, n0, mrow);
                if (nbox == 2) tma_store2d(tm, src + 8192, n0 + 64, mrow);
                bulk_commit();
                asm volatile("cp.async.bulk.wait_group.read 0;" ::: "memory");
                mbar_arrive(bars + B_STGFREE + wg * 8);
                bulk_wait0();
                if (flag >= 0) asm volatile("red.relaxed.gpu.global.add.u32 [%0], 1;" :: "l"(&g_flags[flag]) : "memory");
            } else {
                mbar_arrive(bars + B_STGFREE + wg * 8);
                if (flag >= 0) red_release(&g_flags[flag], 1);
            }
        }
        __syncwarp();
    }
}

__device__ __forceinline__ float gelu_tanh(float x) {
    const float t = x * fmaf(-0.10294324397f, x * x, -2.30220819814f);
    float r; asm("rcp.approx.ftz.f32 %0, %1;" : "=f"(r) : "f"(1.f + ex2(t)));
    return x * r;
}

#define CTR(i) do {} while (0)

__device__ __forceinline__ void ln2_row(const Params& p, int rb, int r, int lane, bool wait) {
    const int row = rb * 128 + r, nsplit = 64 / o_nk(rb);
    const uint4* xr = (const uint4*)(p.x + (size_t)row * D_);
    const uint4 xa = __ldg(xr + lane), xb = __ldg(xr + 32 + lane);
    uint32_t ga[8], c1[8], sm[8];
    load_mod8(g_mod + 2 * D_, lane, ga);
    load_mod8(g_mod + 4 * D_, lane, c1);
    load_mod8(g_mod + 3 * D_, lane, sm);
    float a[16];
#pragma unroll
    for (int i = 0; i < 16; i++) a[i] = 0.f;
    const uint4* src = (const uint4*)(g_op + (size_t)(op_row(rb, 0) + r) * D_) + lane;
    const int sstride = (op_row(rb, 1) - op_row(rb, 0)) * (D_ / 8);
    if (wait) { if (lane == 0) wait_flag(F_OP + rb, 4 * nsplit); __syncwarp(); }
    uint4 u[2][8];
#pragma unroll
    for (int sp = 0; sp < 4; sp++) { u[0][2 * sp] = __ldcg(src + sp * sstride); u[0][2 * sp + 1] = __ldcg(src + sp * sstride + 32); }
    if (nsplit > 4) {
#pragma unroll
        for (int sp = 0; sp < 4; sp++) { u[1][2 * sp] = __ldcg(src + (4 + sp) * sstride); u[1][2 * sp + 1] = __ldcg(src + (4 + sp) * sstride + 32); }
    }
#pragma unroll 1
    for (int s0 = 0; s0 < nsplit; s0 += 4) {
#pragma unroll
        for (int sp = 0; sp < 8; sp++) {
            float* q = a + (sp & 1) * 8;
            const uint4 w = u[0][sp];
            q[0] += bflo(w.x); q[1] += bfhi(w.x); q[2] += bflo(w.y); q[3] += bfhi(w.y);
            q[4] += bflo(w.z); q[5] += bfhi(w.z); q[6] += bflo(w.w); q[7] += bfhi(w.w);
            u[0][sp] = u[1][sp];
        }
        if (s0 + 8 < nsplit) {
#pragma unroll
            for (int sp = 0; sp < 4; sp++) { u[1][2 * sp] = __ldcg(src + (s0 + 8 + sp) * sstride); u[1][2 * sp + 1] = __ldcg(src + (s0 + 8 + sp) * sstride + 32); }
        }
    }
    const uint32_t xv[8] = {xa.x, xa.y, xa.z, xa.w, xb.x, xb.y, xb.z, xb.w};
    uint32_t v[8], r8[8];
#pragma unroll
    for (int i = 0; i < 8; i++) v[i] = hadd2(xv[i], hmul2(ga[i], pack2(a[2 * i], a[2 * i + 1])));
    uint4* x1r = (uint4*)(g_x1 + (size_t)row * D_);
    x1r[lane] = make_uint4(v[0], v[1], v[2], v[3]); x1r[32 + lane] = make_uint4(v[4], v[5], v[6], v[7]);
    uint32_t mu2; float rden;
    ln_stats(v, mu2, rden);
#pragma unroll
    for (int i = 0; i < 8; i++) c1[i] = hadd2(c1[i], 0x3F803F80u);
    ln_apply(v, mu2, rden, c1, sm, r8);
    uint4* hr = (uint4*)(g_h2 + (size_t)row * D_);
    hr[lane] = make_uint4(r8[0], r8[1], r8[2], r8[3]); hr[32 + lane] = make_uint4(r8[4], r8[5], r8[6], r8[7]);
}

__device__ __forceinline__ void consumer(const Params& p, uint32_t sb, int warp, int lane) {
    const uint32_t bars = sb + SM_BAR;
    const int wg = warp >> 2, wl = warp & 3;
    const uint32_t l7 = lane & 7, l8 = lane >> 3, g = lane >> 2, t = lane & 3;
    Pipe pp{0, 0};
    uint32_t seq = 0, stg_phase = 1;
    const int srow = wl * 16 + l7 + (l8 & 1) * 8;
    const uint32_t stg_base = sb + W_STG + wg * 16384 + srow * 128;
    const uint32_t sx = ((lane >> 4) ^ (srow & 7)) << 4;
#pragma unroll 1
    while (true) {
        mbar_wait(bars + B_FULL + pp.stage * 8, pp.phase);
        const uint32_t jd = lds32(bars + B_RING + (seq & 7) * 4);
        CTR(3);
        seq++;
        const int type = jd & 255, rb = (jd >> 8) & 255, cb = (jd >> 16) & 255;
        if (type == J_END) { mbar_wait(bars + B_STGFREE + wg * 8, stg_phase); bar_arrive(NB_ST + wg, 160); break; }
        if (type == J_LN) {
            __syncwarp();
            if (lane == 0) mbar_arrive(bars + B_EMPTY + pp.stage * 8);
            pipe_next(pp);
            const int nr = rb >= FINE_RB ? 1 : 2;
#pragma unroll 1
            for (int rr = 0; rr < nr; rr++) ln2_row(p, rb, (cb * 8 + warp) * nr + rr, lane, !((jd >> 24) & 1) && rr == 0);
            mbar_wait(bars + B_STGFREE + wg * 8, stg_phase); stg_phase ^= 1;
            CTR(4); CTR(5);
            bar_arrive(NB_ST + wg, 160);
            continue;
        }
        if (type == J_DN || type == J_UP2) {
            float acc[64];
#pragma unroll
            for (int i = 0; i < 64; i++) acc[i] = 0.f;
            const bool ksplit = type == J_DN && rb == NRB - 1;
            if (ksplit) {
#pragma unroll 1
                for (int kb = 0; kb < 14; kb++) {
                    if (kb) mbar_wait(bars + B_FULL + pp.stage * 8, pp.phase);
                    const uint32_t st = sb + pp.stage * W_STAGE;
                    const uint64_t da = mkdesc(st + wg * 8192, 16, 1024), db = mkdesc(st + 32768 + wg * 8192, 8192, 1024);
                    wg_fence();
#pragma unroll
                    for (int ks = 0; ks < 4; ks++) wgmma_n64(acc, da + ks * 2, db + ks * 128);
                    wg_commit();
                    wg_wait0();
                    if (lane == 0) mbar_arrive(bars + B_EMPTY + pp.stage * 8);
                    pipe_next(pp);
                }
                const uint32_t xb = sb + W_STG + 16384 + (wl * 32 + lane) * 16;
                if (wg == 1) {
                    mbar_wait(bars + B_STGFREE + 8, stg_phase);
#pragma unroll
                    for (int i = 0; i < 8; i++)
                        sts128(xb + i * 2048, make_uint4(__float_as_uint(acc[4 * i]), __float_as_uint(acc[4 * i + 1]), __float_as_uint(acc[4 * i + 2]), __float_as_uint(acc[4 * i + 3])));
                }
                bar_sync(NB_M, 256);
                if (wg == 0) {
#pragma unroll
                    for (int i = 0; i < 8; i++) {
                        const uint4 o = lds128(xb + i * 2048);
                        acc[4 * i] += __uint_as_float(o.x); acc[4 * i + 1] += __uint_as_float(o.y); acc[4 * i + 2] += __uint_as_float(o.z); acc[4 * i + 3] += __uint_as_float(o.w);
                    }
                }
                bar_sync(NB_M, 256);
            } else if (type == J_DN) {
#pragma unroll 1
                for (int kb = 0; kb < 14; kb++) {
                    if (kb) mbar_wait(bars + B_FULL + pp.stage * 8, pp.phase);
                    const uint32_t st = sb + pp.stage * W_STAGE;
                    const uint64_t da = mkdesc(st + wg * 8192, 16, 1024), db = mkdesc(st + 32768, 8192, 1024);
                    wg_fence();
#pragma unroll
                    for (int ks = 0; ks < 8; ks++) wgmma_n64(acc, da + (ks >> 2) * 1024 + (ks & 3) * 2, db + ks * 128);
                    wg_commit();
                    wg_wait0();
                    if (lane == 0) mbar_arrive(bars + B_EMPTY + pp.stage * 8);
                    pipe_next(pp);
                }
            } else {
#pragma unroll 1
                for (int kb = 0; kb < 8; kb++) {
                    if (kb) mbar_wait(bars + B_FULL + pp.stage * 8, pp.phase);
                    const uint32_t st = sb + pp.stage * W_STAGE;
                    const uint64_t da = mkdesc(st + wg * 8192, 16, 1024), db = mkdesc(st + 16384, 8192, 1024);
                    wg_fence();
#pragma unroll
                    for (int ks = 0; ks < 4; ks++) wgmma_n128(acc, da + ks * 2, db + ks * 128, 1);
                    wg_commit();
                    wg_wait0();
                    if (lane == 0) mbar_arrive(bars + B_EMPTY + pp.stage * 8);
                    pipe_next(pp);
                }
            }
            CTR(4);
            if (type == J_UP2) {
                mbar_wait(bars + B_STGFREE + wg * 8, stg_phase); stg_phase ^= 1;
#pragma unroll
                for (int j = 0; j < 4; j++) {
                    uint32_t r[4];
#pragma unroll
                    for (int q = 0; q < 4; q++) {
                        const uint32_t gw = pack2(acc[8 * j + 2 * q], acc[8 * j + 2 * q + 1]);
                        const uint32_t uw = pack2(acc[32 + 8 * j + 2 * q], acc[32 + 8 * j + 2 * q + 1]);
                        r[q] = hmul2(pack2(gelu_tanh(bflo(gw)), gelu_tanh(bfhi(gw))), uw);
                    }
                    stsm4(stg_base + (sx ^ (j << 5)), r[0], r[1], r[2], r[3]);
                }
            } else {
                mbar_wait(bars + B_FULL + pp.stage * 8, pp.phase);
                const uint32_t st = sb + pp.stage * W_STAGE;
                mbar_wait(bars + B_STGFREE + wg * 8, stg_phase); stg_phase ^= 1;
                const uint32_t* gb = (const uint32_t*)(g_mod + 5 * D_ + (ksplit ? cb >> 1 : cb) * 64) + t;
                const uint32_t xa = st + (ksplit ? 0 : wg * 8192) + (wl * 16 + g) * 128 + (g << 4) + t * 4;
#pragma unroll
                for (int j = 0; j < 4; j++) {
                    uint32_t r[4];
#pragma unroll
                    for (int q = 0; q < 4; q++) {
                        const int nt = 2 * j + (q >> 1);
                        const uint32_t xw = lds32((xa ^ ((nt & 7) << 4)) + (nt >> 3) * 16384 + (q & 1) * 1024);
                        r[q] = hadd2(xw, hmul2(__ldcg(gb + nt * 4), pack2(acc[8 * j + 2 * q], acc[8 * j + 2 * q + 1])));
                    }
                    stsm4(stg_base + (j >> 2) * 8192 + (sx ^ ((2 * j & 7) << 4)), r[0], r[1], r[2], r[3]);
                }
                __syncwarp();
                if (lane == 0) mbar_arrive(bars + B_EMPTY + pp.stage * 8);
                pipe_next(pp);
            }
            fence_async_smem();
            CTR(5);
            bar_arrive(NB_ST + wg, 160);
            continue;
        }
        float acc[128];
#pragma unroll
        for (int i = 0; i < 128; i++) acc[i] = 0.f;
        const int nk = type == J_O ? o_nk(rb) : 8;
#pragma unroll 1
        for (int kb = 0; kb < nk; kb++) {
            if (kb) mbar_wait(bars + B_FULL + pp.stage * 8, pp.phase);
            const uint32_t st = sb + pp.stage * W_STAGE;
            const uint64_t da = mkdesc(st + wg * 8192, 16, 1024), db = mkdesc(st + 16384, 8192, 1024);
            wg_fence();
#pragma unroll
            for (int ks = 0; ks < 4; ks++) wgmma_n256(acc, da + ks * 2, db + ks * 128, 1);
            wg_commit();
            wg_wait0();
            if (lane == 0) mbar_arrive(bars + B_EMPTY + pp.stage * 8);
            pipe_next(pp);
        }
        CTR(4);
        if (type == J_QA) {
            uint32_t qf[64];
#pragma unroll
            for (int i = 0; i < 64; i++) qf[i] = pack2(acc[2 * i], acc[2 * i + 1]);
            const int sg = warp >> 1, half = warp & 1;
            const float sc = 0.08838834764831845f * 1.4426950408889634f;
            const uint32_t xoff = (sg >> 1) * 8192 + ((sg & 1) * 32 + l7) * 128;
            const uint32_t moff = 32768 + (sg * 8 + l7) * 128;
            const uint32_t kch = (l8 ^ l7) << 4;
            const uint32_t vch = ((l8 & 1) ^ l7) << 4;
            if (rb == NRB - 1 && (cb & 1)) {
#pragma unroll
                for (int i = 0; i < 32; i++) qf[i] = qf[32 + i];
            }
#pragma unroll 1
            for (int hh = rb == NRB - 1; hh < 2; hh++) {
                mbar_wait(bars + B_FULL + pp.stage * 8, pp.phase);
                uint32_t st = sb + pp.stage * W_STAGE;
                float sa[5][4];
#pragma unroll
                for (int n = 0; n < 5; n++) sa[n][0] = sa[n][1] = sa[n][2] = sa[n][3] = 0.f;
#pragma unroll
                for (int i = 0; i < 4; i++) {
                    const uint32_t* q = qf + i * 8;
                    uint32_t kk[5][4];
                    ldsm4(kk[0][0], kk[0][1], kk[0][2], kk[0][3], st + moff + (i >> 1) * 4096 + (kch ^ ((i & 1) * 64)));
#pragma unroll
                    for (int n = 1; n < 5; n++)
                        ldsm4(kk[n][0], kk[n][1], kk[n][2], kk[n][3], st + xoff + (n - 1) * 1024 + (i >> 1) * 16384 + (kch ^ ((i & 1) * 64)));
#pragma unroll
                    for (int n = 0; n < 5; n++) mma16816(sa[n], q[0], q[1], q[2], q[3], kk[n][0], kk[n][1]);
#pragma unroll
                    for (int n = 0; n < 5; n++) mma16816(sa[n], q[4], q[5], q[6], q[7], kk[n][2], kk[n][3]);
                }
                __syncwarp();
                if (lane == 0) mbar_arrive(bars + B_EMPTY + pp.stage * 8);
                pipe_next(pp);
                const int iq0 = half * 16 + g - 2 * t, iq1 = iq0 + 8;
                float m0 = fmaxf(sa[0][0], sa[0][1]), m1 = fmaxf(sa[0][2], sa[0][3]);
#pragma unroll
                for (int n = 1; n < 5; n++) {
#pragma unroll
                    for (int e = 0; e < 2; e++) {
                        const int jx = (n - 1) * 8 + e;
                        if (jx > iq0) sa[n][e] = -3.0e38f;
                        if (jx > iq1) sa[n][2 + e] = -3.0e38f;
                        m0 = fmaxf(m0, sa[n][e]); m1 = fmaxf(m1, sa[n][2 + e]);
                    }
                }
                m0 = fmaxf(m0, __shfl_xor_sync(~0u, m0, 1)); m1 = fmaxf(m1, __shfl_xor_sync(~0u, m1, 1));
                m0 = fmaxf(m0, __shfl_xor_sync(~0u, m0, 2)); m1 = fmaxf(m1, __shfl_xor_sync(~0u, m1, 2));
                m0 *= -sc; m1 *= -sc;
                float l0 = 0.f, l1 = 0.f;
                uint32_t p0[5], p1[5];
#pragma unroll
                for (int n = 0; n < 5; n++) {
                    const float e0 = ex2(fmaf(sa[n][0], sc, m0)), e1 = ex2(fmaf(sa[n][1], sc, m0));
                    const float e2 = ex2(fmaf(sa[n][2], sc, m1)), e3 = ex2(fmaf(sa[n][3], sc, m1));
                    l0 += e0 + e1; l1 += e2 + e3;
                    p0[n] = pack2(e0, e1); p1[n] = pack2(e2, e3);
                }
                l0 += __shfl_xor_sync(~0u, l0, 1); l1 += __shfl_xor_sync(~0u, l1, 1);
                l0 += __shfl_xor_sync(~0u, l0, 2); l1 += __shfl_xor_sync(~0u, l1, 2);
                const float i0 = __fdividef(1.f, l0), i1 = __fdividef(1.f, l1);
                mbar_wait(bars + B_FULL + pp.stage * 8, pp.phase);
                st = sb + pp.stage * W_STAGE;
                mbar_wait(bars + B_STGFREE + wg * 8, stg_phase); stg_phase ^= 1;
#pragma unroll
                for (int i = 0; i < 32; i++) qf[i] = qf[32 + i];
#pragma unroll 1
                for (int bx = 0; bx < 2; bx++) {
                    float o[8][4];
                    uint32_t vm[8], v0[4][4], v1[4][4];
#pragma unroll
                    for (int ep = 0; ep < 4; ep++) {
                        ldsm2t(vm[2 * ep], vm[2 * ep + 1], st + moff + bx * 4096 + (vch ^ (ep << 5)));
                        const uint32_t va = st + xoff + (l8 >> 1) * 1024 + bx * 16384 + (vch ^ (ep << 5));
                        ldsm4t(v0[ep][0], v0[ep][1], v0[ep][2], v0[ep][3], va);
                        ldsm4t(v1[ep][0], v1[ep][1], v1[ep][2], v1[ep][3], va + 2048);
                    }
#pragma unroll
                    for (int n = 0; n < 8; n++) { o[n][0] = o[n][1] = o[n][2] = o[n][3] = 0.f; mma16816(o[n], p0[0], p1[0], p0[1], p1[1], vm[n], v0[n >> 1][n & 1]); }
#pragma unroll
                    for (int n = 0; n < 8; n++) mma16816(o[n], p0[2], p1[2], p0[3], p1[3], v0[n >> 1][2 + (n & 1)], v1[n >> 1][n & 1]);
#pragma unroll
                    for (int n = 0; n < 8; n++) mma1688(o[n], p0[4], p1[4], v1[n >> 1][2 + (n & 1)]);
#pragma unroll
                    for (int ep = 0; ep < 4; ep++)
                        stsm4(stg_base + bx * 8192 + (sx ^ (ep << 5)),
                              pack2(o[2 * ep][0] * i0, o[2 * ep][1] * i0), pack2(o[2 * ep][2] * i1, o[2 * ep][3] * i1),
                              pack2(o[2 * ep + 1][0] * i0, o[2 * ep + 1][1] * i0), pack2(o[2 * ep + 1][2] * i1, o[2 * ep + 1][3] * i1));
                }
                __syncwarp();
                if (lane == 0) mbar_arrive(bars + B_EMPTY + pp.stage * 8);
                pipe_next(pp);
                if (hh == 0) { fence_async_smem(); bar_arrive(NB_ST + wg, 160); }
            }
        } else if (type == J_UP) {
            mbar_wait(bars + B_STGFREE + wg * 8, stg_phase); stg_phase ^= 1;
#pragma unroll
            for (int j = 0; j < 8; j++) {
                uint32_t r[4];
#pragma unroll
                for (int q = 0; q < 4; q++) {
                    const uint32_t gw = pack2(acc[8 * j + 2 * q], acc[8 * j + 2 * q + 1]);
                    const uint32_t uw = pack2(acc[64 + 8 * j + 2 * q], acc[64 + 8 * j + 2 * q + 1]);
                    r[q] = hmul2(pack2(gelu_tanh(bflo(gw)), gelu_tanh(bfhi(gw))), uw);
                }
                stsm4(stg_base + (j >> 2) * 8192 + (sx ^ ((2 * j & 7) << 4)), r[0], r[1], r[2], r[3]);
            }
        } else {
#pragma unroll
            for (int rd = 0; rd < 2; rd++) {
                mbar_wait(bars + B_STGFREE + wg * 8, stg_phase); stg_phase ^= 1;
#pragma unroll
                for (int j = rd * 8; j < rd * 8 + 8; j++)
                    stsm4(stg_base + ((j >> 2) & 1) * 8192 + (sx ^ ((2 * j & 7) << 4)),
                          pack2(acc[8 * j], acc[8 * j + 1]), pack2(acc[8 * j + 2], acc[8 * j + 3]),
                          pack2(acc[8 * j + 4], acc[8 * j + 5]), pack2(acc[8 * j + 6], acc[8 * j + 7]));
                if (rd == 0) { fence_async_smem(); bar_arrive(NB_ST + wg, 160); }
            }
        }
        fence_async_smem();
        CTR(5);
        bar_arrive(NB_ST + wg, 160);
    }
}

__global__ void __launch_bounds__(384, 1) k_work(const __grid_constant__ Params p) {
    extern __shared__ __align__(1024) unsigned char smem_raw[];
    const uint32_t sb = smem_u32(smem_raw);
    if (sb & 1023) __trap();
    const int warp = __shfl_sync(~0u, threadIdx.x >> 5, 0);
    int lane; asm volatile("mov.u32 %0, %%laneid;" : "=r"(lane));
    if (threadIdx.x == 0) {
        const uint32_t bars = sb + SM_BAR;
        for (int i = 0; i < W_NST; i++) { mbar_init(bars + B_FULL + i * 8, 1); mbar_init(bars + B_EMPTY + i * 8, 8); }
        mbar_init(bars + B_STGFREE, 1); mbar_init(bars + B_STGFREE + 8, 1); mbar_init(bars + B_REQ, 1); mbar_init(bars + B_RSP, 1);
        asm volatile("fence.mbarrier_init.release.cluster;" ::: "memory");
    }
    __syncthreads();
    if (warp < 8) {
        asm volatile("setmaxnreg.inc.sync.aligned.u32 224;");
        consumer(p, sb, warp, lane);
    } else {
        asm volatile("setmaxnreg.dec.sync.aligned.u32 56;");
        if (warp == 8) { if (lane == 0) producer(p, sb); }
        else if (warp < 11) store_warp(p, sb, warp - 9, lane);
        else scheduler(p, sb, lane);
        __syncwarp();
        bar_sync(NB_W0, 128);
        if (warp == 8 && p.qmask == 0xff) {
            unsigned last = 0;
            if (lane == 0) { __threadfence(); last = atomicAdd(&g_flags[F_DONE], 1u) == gridDim.x - 1; }
            if (__shfl_sync(~0u, last, 0))
                for (int i = lane; i < F_TOTAL; i += 32) g_flags[i] = 0;
        }
    }
}

typedef CUresult (*EncodeFn)(CUtensorMap*, CUtensorMapDataType, cuuint32_t, void*, const cuuint64_t*, const cuuint64_t*,
                             const cuuint32_t*, const cuuint32_t*, CUtensorMapInterleave, CUtensorMapSwizzle,
                             CUtensorMapL2promotion, CUtensorMapFloatOOBfill);

static void make_map(EncodeFn enc, CUtensorMap* m, const void* ptr, uint64_t rows, uint64_t cols, uint32_t box_rows) {
    cuuint64_t dims[2] = {cols, rows};
    cuuint64_t strides[1] = {cols * 2};
    cuuint32_t box[2] = {64, box_rows};
    cuuint32_t es[2] = {1, 1};
    enc(m, CU_TENSOR_MAP_DATA_TYPE_BFLOAT16, 2, const_cast<void*>(ptr), dims, strides, box, es, CU_TENSOR_MAP_INTERLEAVE_NONE,
        CU_TENSOR_MAP_SWIZZLE_128B, CU_TENSOR_MAP_L2_PROMOTION_L2_256B, CU_TENSOR_MAP_FLOAT_OOB_FILL_NONE);
}
template <typename T> static void* sym_addr(T& sym) { void* p = nullptr; cudaGetSymbolAddress(&p, sym); return p; }

extern "C" void kernel_launch(void* const* d_in, const int* in_sizes, int n_in, void* d_out, int out_size) {
    static Params prm;
    static RecParams rp;
    static int n_sm = 132;
    static bool ready = false;
    static const void* key[14];
    bool same = ready;
    for (int i = 0; i < 13 && same; i++) same = key[i] == d_in[i];
    same = same && key[13] == d_out;
    if (!same) {
        void* fn = nullptr;
        cudaDriverEntryPointQueryResult qr;
        cudaGetDriverEntryPoint("cuTensorMapEncodeTiled", &fn, cudaEnableDefault, &qr);
        EncodeFn enc = (EncodeFn)fn;
        make_map(enc, &prm.tm_h, sym_addr(g_h), S_, D_, 64);
        make_map(enc, &prm.tm_kv, sym_addr(g_kv), S_, 2 * HD_, 64);
        make_map(enc, &rp.tm_kv32, sym_addr(g_kv), S_, 2 * HD_, 32);
        make_map(enc, &prm.tm_kvm, sym_addr(g_kvm), NSEG * 8, 2 * HD_, 32);
        make_map(enc, &prm.tm_o, sym_addr(g_o), S_, HD_, 64);
        make_map(enc, &prm.tm_op, sym_addr(g_op), OP_ROWS, D_, 64);
        make_map(enc, &prm.tm_h2, sym_addr(g_h2), S_, D_, 64);
        make_map(enc, &prm.tm_act, sym_addr(g_act), S_, DF_, 64);
        make_map(enc, &prm.tm_x1, sym_addr(g_x1), S_, D_, 64);
        make_map(enc, &prm.tm_out, d_out, S_, D_, 64);
        make_map(enc, &prm.tm_wq, d_in[2], D_, HD_, 64);
        make_map(enc, &prm.tm_wk, d_in[3], D_, HD_, 64);
        make_map(enc, &prm.tm_wv, d_in[4], D_, HD_, 64);
        make_map(enc, &prm.tm_wo, d_in[5], HD_, D_, 64);
        make_map(enc, &prm.tm_wg, d_in[8], D_, DF_, 64);
        make_map(enc, &prm.tm_wu, d_in[9], D_, DF_, 64);
        make_map(enc, &prm.tm_wd, d_in[10], DF_, D_, 64);
        prm.x = (const bf16*)d_in[0]; prm.c = (const bf16*)d_in[11]; prm.w_mod = (const bf16*)d_in[12];
        rp.mem0 = (const bf16*)d_in[1]; rp.x = prm.x; rp.c = prm.c; rp.w_mod = prm.w_mod;
        rp.wq = (const bf16*)d_in[2]; rp.wk = (const bf16*)d_in[3]; rp.wv = (const bf16*)d_in[4]; rp.wo = (const bf16*)d_in[5];
        cudaDeviceGetAttribute(&n_sm, cudaDevAttrMultiProcessorCount, 0);
        cudaFuncSetAttribute(k_work, cudaFuncAttributeMaxDynamicSharedMemorySize, SMEM_BYTES);
        cudaFuncSetAttribute(k_rec, cudaFuncAttributeMaxDynamicSharedMemorySize, R_SMEM);
        cudaFuncSetAttribute(k_rec, cudaFuncAttributeNonPortableClusterSizeAllowed, 1);
        {
            cudaLaunchConfig_t cfg = {};
            cfg.gridDim = dim3(128); cfg.blockDim = dim3(384); cfg.dynamicSmemBytes = R_SMEM;
            cudaLaunchAttribute at[1];
            at[0].id = cudaLaunchAttributeClusterDimension; at[0].val.clusterDim.x = 16; at[0].val.clusterDim.y = 1; at[0].val.clusterDim.z = 1;
            cfg.attrs = at; cfg.numAttrs = 1;
            int n = 0;
            cudaOccupancyMaxActiveClusters(&n, k_rec, &cfg);
            rp.ncl = n < 4 ? 4 : (n > 8 ? 8 : n);
        }
        for (int i = 0; i < 13; i++) key[i] = d_in[i];
        key[13] = d_out;
        ready = true;
    }
    cudaStream_t st = cudaStreamPerThread;
    auto launch_rec = [&]() {
        cudaLaunchConfig_t cfg = {};
        cfg.gridDim = dim3(16 * rp.ncl); cfg.blockDim = dim3(384); cfg.dynamicSmemBytes = R_SMEM; cfg.stream = st;
        cudaLaunchAttribute at[1];
        at[0].id = cudaLaunchAttributeClusterDimension; at[0].val.clusterDim.x = 16; at[0].val.clusterDim.y = 1; at[0].val.clusterDim.z = 1;
        cfg.attrs = at; cfg.numAttrs = 1;
        cudaLaunchKernelEx(&cfg, k_rec, rp);
    };
    auto launch_work = [&](int qmask, int pdl) {
        prm.qmask = qmask;
        cudaLaunchConfig_t cfg = {};
        cfg.gridDim = dim3(n_sm); cfg.blockDim = dim3(384); cfg.dynamicSmemBytes = SMEM_BYTES; cfg.stream = st;
        cudaLaunchAttribute at[1];
        at[0].id = cudaLaunchAttributeProgrammaticStreamSerialization; at[0].val.programmaticStreamSerializationAllowed = 1;
        cfg.attrs = at; cfg.numAttrs = pdl;
        cudaLaunchKernelEx(&cfg, k_work, prm);
    };
    launch_rec();
    launch_work(0xff, 1);
}
```

```cpp
#include <cuda_runtime.h>
#include <cuda_bf16.h>
#include <cuda.h>
#include <stdint.h>

typedef __nv_bfloat16 bf16;
#define IDLE_NS 150
#define FLAG_NS 20

constexpr int S_ = 2048, D_ = 512, DH_ = 128, HD_ = 4096, NSEG = 64, DF_ = 1792;
constexpr int NRB = 16;
constexpr int OSPLIT = 4;

__device__ __align__(1024) bf16 g_h[S_ * D_];
__device__ __align__(1024) bf16 g_kv[S_ * 2 * HD_];
__device__ __align__(1024) bf16 g_kvm[NSEG * 8 * 2 * HD_];
__device__ __align__(1024) bf16 g_o[S_ * HD_];
#define FINE_RB_ 12
constexpr int FINE_RB = FINE_RB_;
#define OSPLIT2_ 8
constexpr int OSPLIT2 = OSPLIT2_;
constexpr int OSPLIT3 = 16;
constexpr int OP_ROWS = OSPLIT * S_ + OSPLIT2 * (NRB - FINE_RB) * 128 + OSPLIT3 * 128;
__device__ __align__(1024) bf16 g_op[OP_ROWS * D_];
__device__ __align__(1024) bf16 g_x1[S_ * D_];
__device__ __align__(1024) bf16 g_h2[S_ * D_];
__device__ __align__(1024) bf16 g_act[S_ * DF_];
__device__ __align__(1024) bf16 g_mod[6 * D_];
__device__ uint32_t g_Fraw[131072 + 65536 + 2048];
#define g_F ((uint32_t*)(((uint64_t)g_Fraw + 0x7FFFFull) & ~0x7FFFFull))
constexpr int F_H = 0, F_MEM = 32, F_O = 64, F_OP = 96, F_H2 = 128, F_ACT = 160, F_MOD = 192, F_KV = 224, F_CLAIM = 256  ,
              F_SIDE = 512  , F_DONE = 576, F_TOTAL = 608;
__device__ __align__(128) unsigned int g_flags[F_TOTAL];
#define TR(j, i) do {} while (0)

__device__ __forceinline__ uint32_t smem_u32(const void* p) { return (uint32_t)__cvta_generic_to_shared(p); }
__device__ __forceinline__ uint32_t clk32() { uint32_t c; asm volatile("mov.u32 %0, %%clock;" : "=r"(c)); return c; }
__device__ __forceinline__ uint32_t mapa_u32(uint32_t addr, uint32_t rank) {
    uint32_t r; asm volatile("mapa.shared::cluster.u32 %0, %1, %2;" : "=r"(r) : "r"(addr), "r"(rank)); return r;
}
__device__ __forceinline__ void mbar_init(uint32_t bar, uint32_t cnt) {
    asm volatile("mbarrier.init.shared::cta.b64 [%0], %1;" :: "r"(bar), "r"(cnt) : "memory");
}
__device__ __forceinline__ void mbar_expect_tx(uint32_t bar, uint32_t bytes) {
    asm volatile("mbarrier.arrive.expect_tx.shared::cta.b64 _, [%0], %1;" :: "r"(bar), "r"(bytes) : "memory");
}
__device__ __forceinline__ void mbar_arrive(uint32_t bar) {
    asm volatile("mbarrier.arrive.shared::cta.b64 _, [%0];" :: "r"(bar) : "memory");
}
__device__ __forceinline__ bool mbar_try_wait(uint32_t bar, uint32_t parity) {
    uint32_t ok;
    asm volatile("{\n.reg .pred p;\nmbarrier.try_wait.parity.shared::cta.b64 p, [%1], %2;\nselp.u32 %0, 1, 0, p;\n}"
                 : "=r"(ok) : "r"(bar), "r"(parity) : "memory");
    return ok;
}
constexpr int SPIN_LIMIT = 1 << 18;
#define TIMEOUT(code, info) do {} while (0)
__device__ __forceinline__ void mbar_wait(uint32_t bar, uint32_t parity) {
    int g = 0;
#pragma unroll 1
    while (!mbar_try_wait(bar, parity)) { if (++g >= SPIN_LIMIT) { TIMEOUT(0, bar & 255); break; } }
}
__device__ __forceinline__ void bar_sync(int id, int n) { asm volatile("bar.sync %0, %1;" :: "r"(id), "r"(n) : "memory"); }
__device__ __forceinline__ void bar_arrive(int id, int n) { asm volatile("bar.arrive %0, %1;" :: "r"(id), "r"(n) : "memory"); }
__device__ __forceinline__ void st_async_v4(uint32_t addr, uint4 v, uint32_t bar) {
    asm volatile("st.async.weak.shared::cluster.mbarrier::complete_tx::bytes.v4.b32 [%0], {%1,%2,%3,%4}, [%5];"
                 :: "r"(addr), "r"(v.x), "r"(v.y), "r"(v.z), "r"(v.w), "r"(bar) : "memory");
}
__device__ __forceinline__ void stg_relaxed32(uint32_t* p, uint32_t v) {
    asm volatile("st.relaxed.gpu.global.b32 [%0], %1;" :: "l"(p), "r"(v) : "memory");
}
__device__ __forceinline__ uint32_t ldg_relaxed32(const uint32_t* p) {
    uint32_t v; asm volatile("ld.relaxed.gpu.global.b32 %0, [%1];" : "=r"(v) : "l"(p) : "memory"); return v;
}
__device__ __forceinline__ unsigned int ld_acquire(const unsigned int* p) {
    unsigned int v; asm volatile("ld.acquire.gpu.global.u32 %0, [%1];" : "=r"(v) : "l"(p) : "memory"); return v;
}
__device__ __forceinline__ void red_release(unsigned int* p, unsigned int v) {
    asm volatile("red.release.gpu.global.add.u32 [%0], %1;" :: "l"(p), "r"(v) : "memory");
}
__device__ __forceinline__ void wait_flag(int idx, unsigned int target) {
    const unsigned int* p = &g_flags[idx];
    int g = 0;
#pragma unroll 1
    while (ld_acquire(p) < target) { __nanosleep(FLAG_NS); if (++g >= 64 * SPIN_LIMIT) { TIMEOUT(2, idx); break; } }
}
__device__ __forceinline__ void cp_async16(uint32_t dst, const void* src) {
    asm volatile("cp.async.cg.shared.global [%0], [%1], 16;" :: "r"(dst), "l"(src) : "memory");
}
__device__ __forceinline__ void cp_async_commit() { asm volatile("cp.async.commit_group;" ::: "memory"); }
template <int N> __device__ __forceinline__ void cp_async_wait() { asm volatile("cp.async.wait_group %0;" :: "n"(N) : "memory"); }
__device__ __forceinline__ void ldsm4(uint32_t& r0, uint32_t& r1, uint32_t& r2, uint32_t& r3, uint32_t addr) {
    asm volatile("ldmatrix.sync.aligned.m8n8.x4.shared.b16 {%0,%1,%2,%3}, [%4];" : "=r"(r0), "=r"(r1), "=r"(r2), "=r"(r3) : "r"(addr) : "memory");
}
__device__ __forceinline__ void ldsm4t(uint32_t& r0, uint32_t& r1, uint32_t& r2, uint32_t& r3, uint32_t addr) {
    asm volatile("ldmatrix.sync.aligned.m8n8.x4.trans.shared.b16 {%0,%1,%2,%3}, [%4];" : "=r"(r0), "=r"(r1), "=r"(r2), "=r"(r3) : "r"(addr) : "memory");
}
__device__ __forceinline__ void ldsm2t(uint32_t& r0, uint32_t& r1, uint32_t addr) {
    asm volatile("ldmatrix.sync.aligned.m8n8.x2.trans.shared.b16 {%0,%1}, [%2];" : "=r"(r0), "=r"(r1) : "r"(addr) : "memory");
}
__device__ __forceinline__ void stsm4(uint32_t addr, uint32_t r0, uint32_t r1, uint32_t r2, uint32_t r3) {
    asm volatile("stmatrix.sync.aligned.m8n8.x4.shared.b16 [%0], {%1,%2,%3,%4};" :: "r"(addr), "r"(r0), "r"(r1), "r"(r2), "r"(r3) : "memory");
}
__device__ __forceinline__ void stsm4t(uint32_t addr, uint32_t r0, uint32_t r1, uint32_t r2, uint32_t r3) {
    asm volatile("stmatrix.sync.aligned.m8n8.x4.trans.shared.b16 [%0], {%1,%2,%3,%4};" :: "r"(addr), "r"(r0), "r"(r1), "r"(r2), "r"(r3) : "memory");
}
__device__ __forceinline__ void mma16816(float* d, uint32_t a0, uint32_t a1, uint32_t a2, uint32_t a3, uint32_t b0, uint32_t b1) {
    asm volatile("mma.sync.aligned.m16n8k16.row.col.f32.bf16.bf16.f32 {%0,%1,%2,%3}, {%4,%5,%6,%7}, {%8,%9}, {%0,%1,%2,%3};"
                 : "+f"(d[0]), "+f"(d[1]), "+f"(d[2]), "+f"(d[3]) : "r"(a0), "r"(a1), "r"(a2), "r"(a3), "r"(b0), "r"(b1));
}
__device__ __forceinline__ void mma1688(float* d, uint32_t a0, uint32_t a1, uint32_t b0) {
    asm volatile("mma.sync.aligned.m16n8k8.row.col.f32.bf16.bf16.f32 {%0,%1,%2,%3}, {%4,%5}, {%6}, {%0,%1,%2,%3};"
                 : "+f"(d[0]), "+f"(d[1]), "+f"(d[2]), "+f"(d[3]) : "r"(a0), "r"(a1), "r"(b0));
}
__device__ __forceinline__ void mma16816h(float* d, uint32_t a0, uint32_t a2, uint32_t b0, uint32_t b1) {
    asm volatile("{\n.reg .b32 ju, jv;\nmma.sync.aligned.m16n8k16.row.col.f32.bf16.bf16.f32 {%0,%1,%2,%3}, {%4,ju,%5,jv}, {%6,%7}, {%0,%1,%2,%3};\n}"
                 : "+f"(d[0]), "+f"(d[1]), "+f"(d[2]), "+f"(d[3]) : "r"(a0), "r"(a2), "r"(b0), "r"(b1));
}
__device__ __forceinline__ void mma1688h(float* d, uint32_t a0, uint32_t b0) {
    asm volatile("{\n.reg .b32 ju;\nmma.sync.aligned.m16n8k8.row.col.f32.bf16.bf16.f32 {%0,%1,%2,%3}, {%4,ju}, {%5}, {%0,%1,%2,%3};\n}"
                 : "+f"(d[0]), "+f"(d[1]), "+f"(d[2]), "+f"(d[3]) : "r"(a0), "r"(b0));
}
__device__ __forceinline__ uint32_t movm(uint32_t a) {
    uint32_t d; asm volatile("movmatrix.sync.aligned.m8n8.trans.b16 %0, %1;" : "=r"(d) : "r"(a)); return d;
}
__device__ __forceinline__ uint32_t pack2(float lo, float hi) {
    uint32_t r; asm("cvt.rn.bf16x2.f32 %0, %1, %2;" : "=r"(r) : "f"(hi), "f"(lo)); return r;
}
__device__ __forceinline__ float bflo(uint32_t w) { return __uint_as_float(w << 16); }
__device__ __forceinline__ float bfhi(uint32_t w) { return __uint_as_float(w & 0xffff0000u); }
__device__ __forceinline__ float rbf(float x) { return __bfloat162float(__float2bfloat16_rn(x)); }
__device__ __forceinline__ float ex2(float x) { float y; asm("ex2.approx.ftz.f32 %0, %1;" : "=f"(y) : "f"(x)); return y; }
__device__ __forceinline__ void sts128(uint32_t addr, uint4 v) {
    asm volatile("st.shared.v4.b32 [%0], {%1,%2,%3,%4};" :: "r"(addr), "r"(v.x), "r"(v.y), "r"(v.z), "r"(v.w) : "memory");
}
__device__ __forceinline__ uint4 lds128(uint32_t addr) {
    uint4 v; asm volatile("ld.shared.v4.b32 {%0,%1,%2,%3}, [%4];" : "=r"(v.x), "=r"(v.y), "=r"(v.z), "=r"(v.w) : "r"(addr) : "memory"); return v;
}
__device__ __forceinline__ float2 lds64f(uint32_t addr) {
    float2 v; asm volatile("ld.shared.v2.f32 {%0,%1}, [%2];" : "=f"(v.x), "=f"(v.y) : "r"(addr) : "memory"); return v;
}
__device__ __forceinline__ float lds32f(uint32_t addr) {
    float v; asm volatile("ld.shared.f32 %0, [%1];" : "=f"(v) : "r"(addr) : "memory"); return v;
}
__device__ __forceinline__ uint32_t lds32(uint32_t addr) {
    uint32_t v; asm volatile("ld.shared.b32 %0, [%1];" : "=r"(v) : "r"(addr) : "memory"); return v;
}
__device__ __forceinline__ void sts32(uint32_t addr, uint32_t v) { asm volatile("st.shared.b32 [%0], %1;" :: "r"(addr), "r"(v) : "memory"); }
__device__ __forceinline__ void sts64f(uint32_t addr, float a, float b) { asm volatile("st.shared.v2.f32 [%0], {%1,%2};" :: "r"(addr), "f"(a), "f"(b) : "memory"); }

__device__ __forceinline__ void tma_load2d(uint32_t dst, const CUtensorMap* tm, int c0, int c1, uint32_t bar) {
    asm volatile("cp.async.bulk.tensor.2d.shared::cluster.global.mbarrier::complete_tx::bytes [%0], [%1, {%3, %4}], [%2];"
                 :: "r"(dst), "l"(tm), "r"(bar), "r"(c0), "r"(c1) : "memory");
}
__device__ __forceinline__ void tma_store2d(const CUtensorMap* tm, uint32_t src, int c0, int c1) {
    asm volatile("cp.async.bulk.tensor.2d.global.shared::cta.bulk_group [%0, {%2, %3}], [%1];"
                 :: "l"(tm), "r"(src), "r"(c0), "r"(c1) : "memory");
}
__device__ __forceinline__ void bulk_commit() { asm volatile("cp.async.bulk.commit_group;" ::: "memory"); }
__device__ __forceinline__ void bulk_wait0() { asm volatile("cp.async.bulk.wait_group 0;" ::: "memory"); }
__device__ __forceinline__ void fence_async_smem() { asm volatile("fence.proxy.async.shared::cta;" ::: "memory"); }

__device__ __forceinline__ void wg_fence() { asm volatile("wgmma.fence.sync.aligned;" ::: "memory"); }
__device__ __forceinline__ void wg_commit() { asm volatile("wgmma.commit_group.sync.aligned;" ::: "memory"); }
__device__ __forceinline__ void wg_wait0() { asm volatile("wgmma.wait_group.sync.aligned 0;" ::: "memory"); }
__device__ __forceinline__ uint64_t mkdesc(uint32_t saddr, uint32_t lbo, uint32_t sbo) {
    return (uint64_t)((saddr & 0x3FFFF) >> 4) | ((uint64_t)(lbo >> 4) << 16) | ((uint64_t)(sbo >> 4) << 32) | (1ull << 62);
}
#define ACC8(i) "+f"(d[i]), "+f"(d[i + 1]), "+f"(d[i + 2]), "+f"(d[i + 3]), "+f"(d[i + 4]), "+f"(d[i + 5]), "+f"(d[i + 6]), "+f"(d[i + 7])
__device__ __forceinline__ void wgmma_n256(float* d, uint64_t da, uint64_t db, int scale_d) {
    asm volatile(
        "{\n.reg .pred p;\nsetp.ne.b32 p, %130, 0;\n"
        "wgmma.mma_async.sync.aligned.m64n256k16.f32.bf16.bf16 "
        "{%0,%1,%2,%3,%4,%5,%6,%7,%8,%9,%10,%11,%12,%13,%14,%15,%16,%17,%18,%19,%20,%21,%22,%23,%24,%25,%26,%27,%28,%29,%30,%31,"
        "%32,%33,%34,%35,%36,%37,%38,%39,%40,%41,%42,%43,%44,%45,%46,%47,%48,%49,%50,%51,%52,%53,%54,%55,%56,%57,%58,%59,%60,%61,%62,%63,"
        "%64,%65,%66,%67,%68,%69,%70,%71,%72,%73,%74,%75,%76,%77,%78,%79,%80,%81,%82,%83,%84,%85,%86,%87,%88,%89,%90,%91,%92,%93,%94,%95,"
        "%96,%97,%98,%99,%100,%101,%102,%103,%104,%105,%106,%107,%108,%109,%110,%111,%112,%113,%114,%115,%116,%117,%118,%119,%120,%121,%122,%123,%124,%125,%126,%127}, "
        "%128, %129, p, 1, 1, 0, 1;\n}"
        : ACC8(0), ACC8(8), ACC8(16), ACC8(24), ACC8(32), ACC8(40), ACC8(48), ACC8(56),
          ACC8(64), ACC8(72), ACC8(80), ACC8(88), ACC8(96), ACC8(104), ACC8(112), ACC8(120)
        : "l"(da), "l"(db), "r"(scale_d));
}
__device__ __forceinline__ void wgmma_n128(float* d, uint64_t da, uint64_t db, int scale_d) {
    asm volatile(
        "{\n.reg .pred p;\nsetp.ne.b32 p, %66, 0;\n"
        "wgmma.mma_async.sync.aligned.m64n128k16.f32.bf16.bf16 "
        "{%0,%1,%2,%3,%4,%5,%6,%7,%8,%9,%10,%11,%12,%13,%14,%15,%16,%17,%18,%19,%20,%21,%22,%23,%24,%25,%26,%27,%28,%29,%30,%31,"
        "%32,%33,%34,%35,%36,%37,%38,%39,%40,%41,%42,%43,%44,%45,%46,%47,%48,%49,%50,%51,%52,%53,%54,%55,%56,%57,%58,%59,%60,%61,%62,%63}, "
        "%64, %65, p, 1, 1, 0, 1;\n}"
        : ACC8(0), ACC8(8), ACC8(16), ACC8(24), ACC8(32), ACC8(40), ACC8(48), ACC8(56)
        : "l"(da), "l"(db), "r"(scale_d));
}

__device__ __forceinline__ void wgmma_n64(float* d, uint64_t da, uint64_t db) {
    asm volatile(
        "wgmma.mma_async.sync.aligned.m64n64k16.f32.bf16.bf16 "
        "{%0,%1,%2,%3,%4,%5,%6,%7,%8,%9,%10,%11,%12,%13,%14,%15,%16,%17,%18,%19,%20,%21,%22,%23,%24,%25,%26,%27,%28,%29,%30,%31}, "
        "%32, %33, 1, 1, 1, 0, 1;"
        : ACC8(0), ACC8(8), ACC8(16), ACC8(24)
        : "l"(da), "l"(db));
}
__device__ __forceinline__ uint32_t hadd2(uint32_t a, uint32_t b) { uint32_t r; asm("add.rn.bf16x2 %0, %1, %2;" : "=r"(r) : "r"(a), "r"(b)); return r; }
__device__ __forceinline__ uint32_t hsub2(uint32_t a, uint32_t b) { uint32_t r; asm("sub.rn.bf16x2 %0, %1, %2;" : "=r"(r) : "r"(a), "r"(b)); return r; }
__device__ __forceinline__ uint32_t hmul2(uint32_t a, uint32_t b) { uint32_t r; asm("mul.rn.bf16x2 %0, %1, %2;" : "=r"(r) : "r"(a), "r"(b)); return r; }
__device__ __forceinline__ void load_mod8(const bf16* m, int lane, uint32_t* v) {
    const uint4 a = __ldcg((const uint4*)m + lane), b = __ldcg((const uint4*)m + 32 + lane);
    v[0] = a.x; v[1] = a.y; v[2] = a.z; v[3] = a.w; v[4] = b.x; v[5] = b.y; v[6] = b.z; v[7] = b.w;
}
__device__ __forceinline__ void ln_stats(const uint32_t* x, uint32_t& mu2, float& rden) {
    float s = 0.f;
#pragma unroll
    for (int i = 0; i < 8; i++) s += bflo(x[i]) + bfhi(x[i]);
#pragma unroll
    for (int o = 16; o > 0; o >>= 1) s += __shfl_xor_sync(~0u, s, o);
    const float mean = s * (1.f / D_);
    float q = 0.f;
#pragma unroll
    for (int i = 0; i < 8; i++) { const float d0 = bflo(x[i]) - mean, d1 = bfhi(x[i]) - mean; q = fmaf(d0, d0, q); q = fmaf(d1, d1, q); }
#pragma unroll
    for (int o = 16; o > 0; o >>= 1) q += __shfl_xor_sync(~0u, q, o);
    mu2 = pack2(mean, mean);
    rden = __frcp_rn(rbf(__fsqrt_rn(rbf(rbf(q * (1.f / D_)) + 1e-5f))));
}
__device__ __forceinline__ void ln_apply(const uint32_t* x, uint32_t mu2, float rden, const uint32_t* c1, const uint32_t* sm, uint32_t* r) {
#pragma unroll
    for (int i = 0; i < 8; i++) {
        const uint32_t d = hsub2(x[i], mu2);
        r[i] = hadd2(hmul2(pack2(bflo(d) * rden, bfhi(d) * rden), c1[i]), sm[i]);
    }
}

struct __align__(64) Params {
    CUtensorMap tm_h, tm_kv, tm_kvm, tm_o, tm_op, tm_h2, tm_act, tm_x1, tm_out;
    CUtensorMap tm_wq, tm_wk, tm_wv, tm_wo, tm_wg, tm_wu, tm_wd;
    const bf16 *x, *c, *w_mod;
    int qmask;
};

constexpr uint32_t R_WV = 0, R_MEM = 65536  ,
                   R_KX = 69632  , R_VX = R_KX + 8192,
                   R_VMS = R_KX + 32768  , R_OS = R_VMS + 2048  , R_SX = R_OS + 2048  , R_BAR = R_SX + 1536,
                   R_RS = R_BAR + 512  , R_VB = R_RS + 4096  , R_VP = R_VB + 2048  ,
                   R_STG = R_VP + 4096  ,
                   R_TQ = R_STG  , R_TV = R_STG + 53248  , R_QF = R_STG + 77824  ,
                   R_SMEM = R_STG + 98304;
static_assert((R_STG & 1023) == 0 && (R_RS & 511) == 0 && R_QF + 16384 <= R_SMEM, "smem");
constexpr uint32_t RB_Q = R_BAR, RB_V = R_BAR + 8, RB_E = R_BAR + 16, RB_A = R_BAR + 24, RB_ROLE = R_BAR + 32, RB_KV = R_BAR + 40  ;
constexpr int W_NST = 4;
constexpr uint32_t W_STAGE = 49152, W_STG = W_NST * W_STAGE  , W_END = W_STG + 32768;
constexpr uint32_t SM_BAR = W_END;
constexpr uint32_t SMEM_BYTES = W_END + 1024 + 2048;
constexpr uint32_t B_FULL = 0, B_EMPTY = 32, B_STGFREE = 64, B_REQ = 80, B_RSP = 88, B_NEXT = 96, B_RING = 128;
#define PICK_AHEAD 3

constexpr int NB_S = 11, NB_Y = 1, NB_M = 5, NB_K = 5, NB_B = 2, NB_C = 3, NB_D = 4, NB_W0 = 6  , NB_ST = 9  ;

__device__ __forceinline__ int pos_of_d(int d) {
    const int rem = d & 31;
    return (d & ~31) + ((rem & 7) >> 1) * 8 + (rem & 1) * 4 + (rem >> 3);
}

#define PROF(i) do {} while (0)
#define VK0_ 4
constexpr int VK0 = VK0_;
constexpr int NOFF = 8;
#define OFFKS(i) ((i) >> 1)
#define POLL_GAP 140

struct __align__(64) RecParams { CUtensorMap tm_kv32; const bf16 *mem0, *wq, *wk, *wv, *wo, *x, *c, *w_mod; int ncl, only_pre; };

__device__ __forceinline__ void rec_qk(const RecParams& p, const uint32_t sb, const int cta, const int warp, int lane, const int sel) {
    const int crank = cta & 15, cl = cta >> 4, rank = cta & 1;
    const int wg = warp >> 2, aa = warp & 3;
    uint32_t wa[2][16][4];
    {
        const uint32_t stg = sb + R_STG + wg * 32768;
        const int t128 = aa * 32 + lane;
        const int row = (lane >> 4) * 8 + (lane & 7);
        const int ch = t128 & 7;
        const size_t goff = (size_t)rank * 256 * HD_ + (cta >> 1) * DH_ + ch * 8;
        const bf16* W = (wg == 0 ? p.wq : p.wk) + goff;
#pragma unroll 4
        for (int dd = 0; dd < 16; dd++) {
            const int d = dd * 16 + (t128 >> 3), pp = pos_of_d(d);
            cp_async16(sb + R_WV + wg * 32768 + pp * 128 + ((ch ^ (pp & 7)) << 4), p.wv + goff + wg * 64 + (size_t)d * HD_);
        }
        cp_async_commit();
#pragma unroll 4
        for (int dd = 0; dd < 16; dd++) {
            const int d = dd * 16 + (t128 >> 3), pp = pos_of_d(d);
            cp_async16(stg + pp * 128 + ((ch ^ (pp & 7)) << 4), W + (size_t)d * HD_);
        }
        cp_async_commit();
        {
            const int tok = warp, d0 = lane * 8;
            const uint4 m0 = __ldg((const uint4*)(p.mem0 + tok * D_ + rank * 256 + d0));
            const uint32_t mw[4] = {m0.x, m0.y, m0.z, m0.w};
#pragma unroll
            for (int e = 0; e < 8; e++) {
                const int pp = pos_of_d(d0 + e);
                const unsigned short v = (unsigned short)(mw[e >> 1] >> ((e & 1) * 16));
                asm volatile("st.shared.u16 [%0], %1;" :: "r"(sb + R_MEM + (pp >> 3) * 128 + tok * 16 + (pp & 7) * 2), "h"(v) : "memory");
            }
        }
        cp_async_wait<1>();
        bar_sync(NB_W0 + wg, 128);
        const uint32_t fv = row * 128 + (((2 * aa + ((lane >> 3) & 1)) ^ (row & 7)) << 4);
#pragma unroll
        for (int ks = 0; ks < 16; ks++) ldsm4t(wa[0][ks][0], wa[0][ks][1], wa[0][ks][2], wa[0][ks][3], sb + R_WV + wg * 32768 + fv + ks * 2048);
        bar_sync(NB_W0 + wg, 128);
#pragma unroll
        for (int ks = 0; ks < 16; ks++)
            sts128(sb + R_WV + (warp * 16 + ks) * 512 + lane * 16, make_uint4(wa[0][ks][0], wa[0][ks][1], wa[0][ks][2], wa[0][ks][3]));
        const uint32_t fo = stg + row * 128 + (((4 * (aa & 1) + ((lane >> 3) & 1)) ^ (row & 7)) << 4);
#pragma unroll 1
        for (int m = 0; m < 2; m++) {
            cp_async_wait<0>();
            bar_sync(NB_W0 + wg, 128);
            if ((aa >> 1) == m) {
#pragma unroll
                for (int ks = 0; ks < 16; ks++) {
                    ldsm4t(wa[0][ks][0], wa[0][ks][1], wa[0][ks][2], wa[0][ks][3], fo + ks * 2048);
                    ldsm4t(wa[1][ks][0], wa[1][ks][1], wa[1][ks][2], wa[1][ks][3], (fo ^ 32) + ks * 2048);
                }
            }
            bar_sync(NB_W0 + wg, 128);
            if (m == 0) {
#pragma unroll 4
                for (int dd = 0; dd < 16; dd++) {
                    const int d = dd * 16 + (t128 >> 3), pp = pos_of_d(d);
                    cp_async16(stg + pp * 128 + ((ch ^ (pp & 7)) << 4), W + 64 + (size_t)d * HD_);
                }
                cp_async_commit();
            }
        }
    }
    bar_sync(NB_D, 384);
    const uint32_t tab = sb + R_TQ + wg * 26624 + (aa * 32 + lane) * 16;
    {
        const uint32_t l7 = lane & 7, l8 = lane >> 3, g = lane >> 2, t = lane & 3;
        const uint32_t bq = warp >> 1, tp = warp & 1;
        uint4 v;
        v.x = sb + R_QF + (rank * 8 + warp) * 512 + lane * 16;
        v.y = sb + R_QF + (warp == 5 ? 1024 : 0) + lane * 16;
        v.z = sb + R_KX + ((warp - 1) * 8 + l7) * 128 + ((l8 ^ l7) << 4);
        v.w = sb + R_SX + warp * 256 + lane * 8;
        sts128(tab, v);
        sts128(tab + 2048, make_uint4(sb + lane * 16 + R_MEM, sb + lane * 16 + R_WV + warp * 8192, sb + lane * 16 + R_VP + warp * 512, v.x));
        const uint32_t L = bq * 8 + 2 * tp + (l8 & 1) + 4 * (l8 >> 1);
        const uint32_t d0 = (((crank + ((t >> 1) | (g & 6))) & 7) << 1) | (crank >> 3);
        v.x = sb + R_RS + l7 * 512 + ((L ^ l7) << 4);
        v.y = mapa_u32(sb + R_MEM + ((crank & 7) * 4 + bq) * 128 + (4 * tp + 2 * (t & 1) + (g & 1)) * 16, d0);
        v.z = mapa_u32(sb + RB_A, d0);
        v.w = lane;
        sts128(tab + 4096, v);
        const uint64_t wr = (uint64_t)(g_F + ((crank * 2 + ((crank ^ (crank >> 3) ^ sel) & 1)) * 1024 + warp * 128 + cl * 32 + lane));
        sts128(tab + 6144, make_uint4((uint32_t)wr, (uint32_t)(wr >> 32), (uint32_t)((((cl + 1) & 3) - cl) * 128), (uint32_t)((((cl + 2) & 3) - cl) * 128)));
        sts32(tab + 8192, (uint32_t)((((cl + 3) & 3) - cl) * 128));
#pragma unroll
        for (int i = 0; i < NOFF; i++)
            sts128(tab + 10240 + i * 2048, make_uint4(wa[i & 1][OFFKS(i)][0], wa[i & 1][OFFKS(i)][1], wa[i & 1][OFFKS(i)][2], wa[i & 1][OFFKS(i)][3]));
    }
    bar_sync(NB_D, 384);
    uint4 tb = lds128(tab + 2048);
#pragma unroll 1
    for (int s = 0; s < NSEG; s++) {
        if (s > 0) mbar_wait(sb + RB_A, (s - 1) & 1);
        if (warp == 0) PROF(0);
        uint4 ta;
        const uint32_t par = (s & 1) * 8192;
        {
            float acc[5][4];
#pragma unroll
            for (int c = 0; c < 5; c++) { acc[c][0] = acc[c][1] = acc[c][2] = acc[c][3] = 0.f; }
            uint32_t b[8][4];
            uint4 av[16];
            static_assert(VK0 == 4, "order below assumes the V/O warps cover slices 0,1");
#define QK4(k2) do { \
                mma16816(acc[0], wa[0][2 * (k2)][0], wa[0][2 * (k2)][1], wa[0][2 * (k2)][2], wa[0][2 * (k2)][3], b[k2][0], b[k2][1]); \
                mma16816(acc[1], wa[1][2 * (k2)][0], wa[1][2 * (k2)][1], wa[1][2 * (k2)][2], wa[1][2 * (k2)][3], b[k2][0], b[k2][1]); \
                mma16816(acc[3], wa[0][2 * (k2) + 1][0], wa[0][2 * (k2) + 1][1], wa[0][2 * (k2) + 1][2], wa[0][2 * (k2) + 1][3], b[k2][2], b[k2][3]); \
                mma16816(acc[4], wa[1][2 * (k2) + 1][0], wa[1][2 * (k2) + 1][1], wa[1][2 * (k2) + 1][2], wa[1][2 * (k2) + 1][3], b[k2][2], b[k2][3]); } while (0)
#define V2(k2) do { \
                mma16816(acc[2], av[2 * (k2)].x, av[2 * (k2)].y, av[2 * (k2)].z, av[2 * (k2)].w, b[k2][0], b[k2][1]); \
                mma16816(acv, av[2 * (k2) + 1].x, av[2 * (k2) + 1].y, av[2 * (k2) + 1].z, av[2 * (k2) + 1].w, b[k2][2], b[k2][3]); } while (0)
#define LB(k2) ldsm4(b[k2][0], b[k2][1], b[k2][2], b[k2][3], tb.x + (k2) * 512)
#define LV(k2) do { av[2 * (k2)] = lds128(tb.y + 2 * (k2) * 512); av[2 * (k2) + 1] = lds128(tb.y + (2 * (k2) + 1) * 512); } while (0)
            float acv[4] = {0.f, 0.f, 0.f, 0.f};
            LB(0); LB(1); LB(2); LB(3);
            QK4(0); LB(4); QK4(1); LB(5); LV(2); LV(3); QK4(2); LB(6); QK4(3); LB(7);
            V2(2); V2(3); LV(4); LV(5);
            QK4(4); QK4(5); QK4(6); QK4(7);
            const uint4 f = make_uint4(movm(pack2(acc[0][0] + acc[3][0], acc[0][1] + acc[3][1])), movm(pack2(acc[0][2] + acc[3][2], acc[0][3] + acc[3][3])),
                                       movm(pack2(acc[1][0] + acc[4][0], acc[1][1] + acc[4][1])), movm(pack2(acc[1][2] + acc[4][2], acc[1][3] + acc[4][3])));
            st_async_v4((tb.w + par) ^ (1u << 24), f, (sb + RB_Q) ^ (1u << 24));
            sts128(tb.w + par, f);
            __syncwarp();
            if ((tb.w & 511) == 0) mbar_arrive(sb + RB_Q);
            if (warp == 0) PROF(1);
            if (tb.x == 0) break;
            LV(6); LV(7);
            ta = lds128(tab);
            V2(4); V2(5); V2(6); V2(7);
            sts128(tb.z, make_uint4(__float_as_uint(acc[2][0] + acv[0]), __float_as_uint(acc[2][1] + acv[1]), __float_as_uint(acc[2][2] + acv[2]), __float_as_uint(acc[2][3] + acv[3])));
            bar_arrive(NB_Y, 384);
        }
        if (warp == 0) PROF(14);
        if (warp < 6 && s != NSEG - 1) {
            float sa[4] = {0.f, 0.f, 0.f, 0.f}, sc[4] = {0.f, 0.f, 0.f, 0.f};
            const uint32_t qa = ta.y + par;
            if (warp == 0 || warp == 5) {
                mbar_wait(sb + RB_Q, s & 1);
                const uint4 q0 = lds128(qa), q1 = lds128(qa + 4096), k0 = lds128(qa + 2048), k1 = lds128(qa + 6144);
                const uint4 q2 = lds128(qa + 512), q3 = lds128(qa + 4608), k2 = lds128(qa + 2560), k3 = lds128(qa + 6656);
                mma16816h(sa, hadd2(q0.x, q1.x), hadd2(q0.y, q1.y), hadd2(k0.x, k1.x), hadd2(k0.y, k1.y));
                mma16816h(sc, hadd2(q0.z, q1.z), hadd2(q0.w, q1.w), hadd2(k0.z, k1.z), hadd2(k0.w, k1.w));
                mma16816h(sa, hadd2(q2.x, q3.x), hadd2(q2.y, q3.y), hadd2(k2.x, k3.x), hadd2(k2.y, k3.y));
                mma16816h(sc, hadd2(q2.z, q3.z), hadd2(q2.w, q3.w), hadd2(k2.z, k3.z), hadd2(k2.w, k3.w));
            } else {
                uint32_t k[16];
                const uint32_t kb = ta.z + 2 * par;
                mbar_wait(sb + RB_KV + (s & 1) * 8, (s >> 1) & 1);
                ldsm4(k[0], k[1], k[2], k[3], kb);
                ldsm4(k[4], k[5], k[6], k[7], kb ^ 64);
                ldsm4(k[8], k[9], k[10], k[11], kb + 4096);
                ldsm4(k[12], k[13], k[14], k[15], (kb ^ 64) + 4096);
                mbar_wait(sb + RB_Q, s & 1);
                uint4 q0[4], q1[4];
#pragma unroll
                for (int i = 0; i < 4; i++) { q0[i] = lds128(qa + i * 512); q1[i] = lds128(qa + 4096 + i * 512); }
                float sd[4] = {0.f, 0.f, 0.f, 0.f}, se[4] = {0.f, 0.f, 0.f, 0.f};
                mma16816h(sa, hadd2(q0[0].x, q1[0].x), hadd2(q0[0].y, q1[0].y), k[0], k[1]);
                mma16816h(sc, hadd2(q0[0].z, q1[0].z), hadd2(q0[0].w, q1[0].w), k[2], k[3]);
                mma16816h(sd, hadd2(q0[1].x, q1[1].x), hadd2(q0[1].y, q1[1].y), k[4], k[5]);
                mma16816h(se, hadd2(q0[1].z, q1[1].z), hadd2(q0[1].w, q1[1].w), k[6], k[7]);
                mma16816h(sa, hadd2(q0[2].x, q1[2].x), hadd2(q0[2].y, q1[2].y), k[8], k[9]);
                mma16816h(sc, hadd2(q0[2].z, q1[2].z), hadd2(q0[2].w, q1[2].w), k[10], k[11]);
                mma16816h(sd, hadd2(q0[3].x, q1[3].x), hadd2(q0[3].y, q1[3].y), k[12], k[13]);
                mma16816h(se, hadd2(q0[3].z, q1[3].z), hadd2(q0[3].w, q1[3].w), k[14], k[15]);
                sa[0] += sd[0]; sa[1] += sd[1]; sc[0] += se[0]; sc[1] += se[1];
            }
            const float scl = 0.08838834764831845f * 1.4426950408889634f;
            sts64f(ta.w, (sa[0] + sc[0]) * scl, (sa[1] + sc[1]) * scl);
            bar_arrive(NB_S, 320);
            if (warp == 0) PROF(2);
        } else if (warp == 7) {
            mbar_wait(sb + RB_Q, s & 1);
            if (lane == 0) {
                mbar_expect_tx(sb + RB_Q, 4096);
                if (s > 0) mbar_expect_tx(sb + RB_A, 4096);
            }
            __syncwarp();
        } else if (s > 0 && (s & 3) == 0 && warp == 6) {
            bar_sync(NB_K, 160);
            if (lane == 0) red_release(&g_flags[F_MEM + (s >> 2) - 1], 1);
            __syncwarp();
        }
        if (s == NSEG - 1) {
            const uint4 td = lds128(tab + 6144);
            stg_relaxed32((uint32_t*)(((uint64_t)td.y << 32) | (td.x ^ 0x21000)), 0u);
            break;
        }
        const uint4 tc = lds128(tab + 4096), td = lds128(tab + 6144);
        const uint32_t te = lds32(tab + 8192);
        uint32_t* wr = (uint32_t*)(((uint64_t)td.y << 32) | (td.x ^ ((s & 1) * 0x21000)));
        const uint32_t* r1p = (const uint32_t*)((const char*)wr + (int)td.z);
        const uint32_t* r2p = (const uint32_t*)((const char*)wr + (int)td.w);
        const uint32_t* r3p = (const uint32_t*)((const char*)wr + (int)te);
        const uint32_t tag = ((s >> 1) + 1) & 1;
        mbar_wait(sb + RB_E, s & 1);
        if (warp == 0) PROF(7);
        {
            uint32_t a0, a1, a2, a3;
            ldsm4t(a0, a1, a2, a3, tc.x);
            const uint32_t one = 0x3F803F80u;
            float d0_[4] = {0.f, 0.f, 0.f, 0.f}, d1_[4] = {0.f, 0.f, 0.f, 0.f};
            mma1688(d0_, a0, a1, one);
            mma1688(d1_, a2, a3, one);
            const bool t1 = tc.w & 1, t2 = tc.w & 2;
            const float x = t2 ? (t1 ? d1_[2] : d1_[0]) : (t1 ? d0_[2] : d0_[0]);
            const uint32_t own = (__float_as_uint(x) & ~1u) | tag;
            stg_relaxed32(wr, own);
            const uint32_t tq = clk32();
            if (warp == 0) PROF(8);
            while ((int)(clk32() - tq) < POLL_GAP) {}
            uint32_t f1 = ldg_relaxed32(r1p), f2 = ldg_relaxed32(r2p), f3 = ldg_relaxed32(r3p);
#pragma unroll
            for (int i = 0; i < NOFF; i++) {
                const uint4 f0 = lds128(tab + 10240 + i * 2048);
                wa[i & 1][OFFKS(i)][0] = f0.x; wa[i & 1][OFFKS(i)][1] = f0.y; wa[i & 1][OFFKS(i)][2] = f0.z; wa[i & 1][OFFKS(i)][3] = f0.w;
            }
            tb = lds128(tab + 2048);
            int gg = 0;
#pragma unroll 1
            while (!__all_sync(~0u, (((f1 ^ tag) | (f2 ^ tag) | (f3 ^ tag)) & 1) == 0)) {
                f1 = ldg_relaxed32(r1p); f2 = ldg_relaxed32(r2p); f3 = ldg_relaxed32(r3p);
                if (++gg > 16 * SPIN_LIMIT) { TIMEOUT(3, s); break; }
            }
            if (warp == 0) PROF(9);
            const float v = (__uint_as_float(own) + __uint_as_float(f2)) + (__uint_as_float(f1) + __uint_as_float(f3));
            const bool b8 = tc.w & 8, b16 = tc.w & 16;
            const float recv = __shfl_xor_sync(~0u, v, 8);
            const uint32_t word = b8 ? pack2(recv, v) : pack2(v, recv);
            const uint32_t oth = __shfl_xor_sync(~0u, word, 16);
            const uint32_t wl = b16 ? oth : word, wh = b16 ? word : oth;
            const uint32_t p0 = __shfl_xor_sync(~0u, wl, 2), p1 = __shfl_xor_sync(~0u, wh, 2);
            const uint4 item = t2 ? make_uint4(p0, p1, wl, wh) : make_uint4(wl, wh, p0, p1);
            st_async_v4(tc.y, item, tc.z);
            if (tc.w == 0 && warp == 7) mbar_expect_tx(sb + RB_E, 4096);
            if (warp == 0) PROF(10);
        }
    }
}

__device__ __forceinline__ void rec_load_kv(const RecParams& p, uint32_t sb, int head, int s) {
    const uint32_t bar = sb + RB_KV + (s & 1) * 8, d = sb + R_KX + (s & 1) * 16384;
    mbar_expect_tx(bar, 16384);
    tma_load2d(d, &p.tm_kv32, head * DH_, s * 32, bar);
    tma_load2d(d + 4096, &p.tm_kv32, head * DH_ + 64, s * 32, bar);
    tma_load2d(d + 8192, &p.tm_kv32, HD_ + head * DH_, s * 32, bar);
    tma_load2d(d + 12288, &p.tm_kv32, HD_ + head * DH_ + 64, s * 32, bar);
}
__device__ __forceinline__ void rec_store_kvm(uint32_t src, char* dst, int s, int w) {
    dst += (size_t)s * (8 * 2 * HD_ * 2);
    if (w < 2) {
        const uint4 a = lds128(src + (s & 1) * 8192), b = lds128(src + (s & 1) * 8192 + 4096);
        *(uint32_t*)dst = hadd2(a.x, b.x); *(uint32_t*)(dst + 16) = hadd2(a.y, b.y);
        *(uint32_t*)(dst + 32) = hadd2(a.z, b.z); *(uint32_t*)(dst + 48) = hadd2(a.w, b.w);
    } else {
        *(uint4*)dst = lds128(src + (s & 1) * 1024);
    }
}

__device__ __forceinline__ void rec_vo(const RecParams& p, const uint32_t sb, const int cta, const int warp, int lane) {
    const int w = warp - 8, crank = cta & 15, rank = cta & 1;
    uint32_t wo[4][8][4];
    const uint32_t tab = sb + R_TV + (w * 32 + lane) * 16;
    {
        const int t128 = w * 32 + lane;
        const bf16* Wo = p.wo + (size_t)(cta >> 1) * DH_ * D_ + rank * 256;
        const uint32_t stg = sb + R_STG + 2 * 32768;
#pragma unroll
        for (int half = 0; half < 2; half++) {
#pragma unroll 4
            for (int i = t128; i < 2048; i += 128) {
                const int e = i >> 5, ch = i & 31;
                cp_async16(stg + e * 512 + ((ch ^ (e & 7)) << 4), Wo + (size_t)(half * 64 + e) * D_ + ch * 8);
            }
            cp_async_commit();
            cp_async_wait<0>();
            bar_sync(NB_W0 + 2, 128);
#pragma unroll
            for (int j = 0; j < 4; j++)
#pragma unroll
                for (int kk = 0; kk < 4; kk++) {
                    const int e = kk * 16 + (lane >> 4) * 8 + (lane & 7);
                    const int ch = (w * 4 + j) * 2 + ((lane >> 3) & 1);
                    ldsm4t(wo[j][half * 4 + kk][0], wo[j][half * 4 + kk][1], wo[j][half * 4 + kk][2], wo[j][half * 4 + kk][3],
                           stg + e * 512 + ((ch ^ (e & 7)) << 4));
                }
            bar_sync(NB_W0 + 2, 128);
        }
        bar_sync(NB_D, 384);
        const uint32_t l7 = lane & 7, l8 = lane >> 3, g = lane >> 2;
        uint4 v;
        v.x = sb + R_VX + (w >> 1) * 4096 + ((l8 & 1) * 8 + l7) * 128 + (((4 * (w & 1) + (l8 >> 1)) ^ l7) << 4);
        v.y = sb + R_OS + (w >> 1) * 1024 + g * 128 + (((4 * (w & 1)) ^ g) << 4) + (lane & 3) * 4;
        v.z = sb + R_VMS + l7 * 128 + (((4 * (w & 1) + l8) ^ l7) << 4);
        v.w = sb + R_OS + l7 * 128 + ((l8 ^ l7) << 4);
        sts128(tab, v);
        v.x = mapa_u32(sb + R_RS + (crank >> 1) * 512 + ((lane ^ (crank >> 1)) << 4), rank * 8 + w * 2);
        v.y = mapa_u32(sb + RB_E, rank * 8 + w * 2);
        v.z = sb + R_VB + w * 512 + lane * 16;
        v.w = sb + R_SX + lane * 8;
        sts128(tab + 2048, v);
#pragma unroll
        for (int i = 0; i < 8; i++)
            sts128(tab + 4096 + i * 2048, make_uint4(wo[i >> 1][(i & 1) * 4][0], wo[i >> 1][(i & 1) * 4][1], wo[i >> 1][(i & 1) * 4][2], wo[i >> 1][(i & 1) * 4][3]));
        const int tok = (w & 1) * 4 + (lane >> 3);
        const uint64_t kd = w < 2 ? (uint64_t)(g_kvm + (g * (2 * HD_) + cta * 64 + w * 32 + (lane & 3) * 2))
                                  : (uint64_t)(g_kvm + (tok * (2 * HD_) + HD_ + cta * 64 + (lane & 7) * 8));
        const uint32_t ksrc = w < 2 ? sb + R_QF + (4 + 2 * rank + w) * 512 + lane * 16 : sb + R_VMS + tok * 128 + (((lane & 7) ^ tok) << 4);
        sts128(tab + 20480, make_uint4((uint32_t)kd, (uint32_t)(kd >> 32), ksrc, sb + lane * 16));
        if (t128 == 0) { wait_flag(F_KV + 0, 64); rec_load_kv(p, sb, cta >> 1, 0); mbar_wait(sb + RB_KV, 0); }
        __syncwarp();
    }
    bar_sync(NB_D, 384);
    const uint32_t lane16 = lds32(tab + 20480 + 12);
    uint4 av[8];
#pragma unroll
    for (int i = 0; i < 8; i++) av[i] = lds128(lane16 + R_WV + ((2 * w + (i >> 2)) * 16 + (i & 3)) * 512);
#pragma unroll 1
    for (int s = 0; s < NSEG; s++) {
        {
            if (s > 0) mbar_wait(sb + RB_A, (s - 1) & 1);
            if (s > 0) {
                const uint4 tp = lds128(tab + 20480);
                rec_store_kvm(tp.z, (char*)(((uint64_t)tp.y << 32) | tp.x), s - 1, w);
                if ((s & 3) == 0) bar_arrive(NB_K, 160);
            }
            if (s + 1 < NSEG - 1 && w == 3 && lane16 == sb) {
                if (((s + 1) & 3) == 0) wait_flag(F_KV + ((s + 1) >> 2), 64);
                rec_load_kv(p, sb, cta >> 1, s + 1);
            }
            __syncwarp();
        }
        uint4 vb;
        const uint4 ta = lds128(tab), tb = lds128(tab + 2048);
        {
            uint32_t bb[8];
            ldsm4(bb[0], bb[1], bb[2], bb[3], lane16 + R_MEM);
            ldsm4(bb[4], bb[5], bb[6], bb[7], lane16 + R_MEM + 512);
            float vd[4] = {0.f, 0.f, 0.f, 0.f}, ve[4] = {0.f, 0.f, 0.f, 0.f};
#pragma unroll
            for (int i = 0; i < 4; i++) {
                mma16816(vd, av[i].x, av[i].y, av[i].z, av[i].w, bb[2 * i], bb[2 * i + 1]);
                mma16816(ve, av[4 + i].x, av[4 + i].y, av[4 + i].z, av[4 + i].w, bb[2 * i], bb[2 * i + 1]);
            }
            bar_sync(NB_Y, 384);
            const uint4 a = lds128(lane16 + R_VP + w * 1024), b = lds128(lane16 + R_VP + w * 1024 + 512);
            vb = make_uint4(pack2(__uint_as_float(a.x) + vd[0], __uint_as_float(a.y) + vd[1]), pack2(__uint_as_float(a.z) + vd[2], __uint_as_float(a.w) + vd[3]),
                            pack2(__uint_as_float(b.x) + ve[0], __uint_as_float(b.y) + ve[1]), pack2(__uint_as_float(b.z) + ve[2], __uint_as_float(b.w) + ve[3]));
            st_async_v4(tb.z ^ (1u << 24), vb, (sb + RB_V) ^ (1u << 24));
        }
        if (w == 0) PROF(11);
        if (s != NSEG - 1) {
            uint32_t vx[16];
            const uint32_t vxa = ta.x + (s & 1) * 16384;
            mbar_wait(sb + RB_KV + (s & 1) * 8, (s >> 1) & 1);
            ldsm4t(vx[0], vx[1], vx[2], vx[3], vxa);
            ldsm4t(vx[4], vx[5], vx[6], vx[7], vxa ^ 32);
            ldsm4t(vx[8], vx[9], vx[10], vx[11], vxa + 2048);
            ldsm4t(vx[12], vx[13], vx[14], vx[15], (vxa ^ 32) + 2048);
#pragma unroll
            for (int i = 0; i < 4; i++) {
                const uint4 f0 = lds128(tab + 4096 + i * 2048);
                wo[i >> 1][(i & 1) * 4][0] = f0.x; wo[i >> 1][(i & 1) * 4][1] = f0.y; wo[i >> 1][(i & 1) * 4][2] = f0.z; wo[i >> 1][(i & 1) * 4][3] = f0.w;
            }
            bar_sync(NB_S, 320);
            if (w == 0) PROF(4);
            float sv[10];
#pragma unroll
            for (int n = 0; n < 5; n++) { const float2 a = lds64f(tb.w + n * 256); sv[2 * n] = a.x; sv[2 * n + 1] = a.y; }
            { const float2 a = lds64f(tb.w + 5 * 256); sv[0] += a.x; sv[1] += a.y; }
            float mx = fmaxf(fmaxf(fmaxf(sv[2], sv[3]), fmaxf(sv[4], sv[5])), fmaxf(fmaxf(sv[6], sv[7]), fmaxf(sv[8], sv[9])));
            mx = fmaxf(mx, fmaxf(sv[0], sv[1]));
            mx = fmaxf(mx, __shfl_xor_sync(~0u, mx, 1));
            mx = fmaxf(mx, __shfl_xor_sync(~0u, mx, 2));
            mbar_wait(sb + RB_V, s & 1);
            const uint4 vo = lds128(tb.z);
            uint32_t pf[5];
#pragma unroll
            for (int n = 0; n < 5; n++) pf[n] = pack2(ex2(sv[2 * n] - mx), ex2(sv[2 * n + 1] - mx));
            vb = make_uint4(hadd2(vb.x, vo.x), hadd2(vb.y, vo.y), hadd2(vb.z, vo.z), hadd2(vb.w, vo.w));
            if (w == 0) PROF(12);
            float oa[4][4] = {{0.f, 0.f, 0.f, 0.f}, {0.f, 0.f, 0.f, 0.f}, {0.f, 0.f, 0.f, 0.f}, {0.f, 0.f, 0.f, 0.f}}, sm[4] = {0.f, 0.f, 0.f, 0.f};
            const uint32_t one = 0x3F803F80u;
            mma1688h(sm, pf[0], one);
            mma1688h(oa[0], pf[0], vb.x);
            mma1688h(oa[1], pf[0], vb.y);
            mma1688h(oa[2], pf[0], vb.z);
            mma1688h(oa[3], pf[0], vb.w);
            mma16816h(sm, pf[1], pf[2], one, one);
#pragma unroll
            for (int n = 0; n < 4; n++) mma16816h(oa[n], pf[1], pf[2], vx[2 * n], vx[2 * n + 1]);
            mma16816h(sm, pf[3], pf[4], one, one);
#pragma unroll
            for (int n = 0; n < 4; n++) mma16816h(oa[n], pf[3], pf[4], vx[8 + 2 * n], vx[8 + 2 * n + 1]);
            float inv;
            asm("rcp.approx.ftz.f32 %0, %1;" : "=f"(inv) : "f"(sm[0]));
#pragma unroll
            for (int n = 0; n < 4; n++) sts32(ta.y ^ (n << 4), pack2(oa[n][0] * inv, oa[n][1] * inv));
            bar_sync(NB_C, 128);
            if (w == 0) PROF(5);
            uint32_t ob[16];
            ldsm4(ob[0], ob[1], ob[2], ob[3], ta.w);
            ldsm4(ob[8], ob[9], ob[10], ob[11], ta.w + 1024);
            ldsm4(ob[4], ob[5], ob[6], ob[7], ta.w ^ 64);
            ldsm4(ob[12], ob[13], ob[14], ob[15], (ta.w ^ 64) + 1024);
#pragma unroll
            for (int i = 4; i < 8; i++) {
                const uint4 f0 = lds128(tab + 4096 + i * 2048);
                wo[i >> 1][(i & 1) * 4][0] = f0.x; wo[i >> 1][(i & 1) * 4][1] = f0.y; wo[i >> 1][(i & 1) * 4][2] = f0.z; wo[i >> 1][(i & 1) * 4][3] = f0.w;
            }
#pragma unroll
            for (int jj = 0; jj < 2; jj++) {
                if (jj == 1 && tb.w == 0) break;
                float acc[4][4];
#pragma unroll
                for (int c = 0; c < 4; c++) { acc[c][0] = acc[c][1] = acc[c][2] = acc[c][3] = 0.f; }
#pragma unroll
                for (int k4 = 0; k4 < 4; k4++)
#pragma unroll
                    for (int c = 0; c < 4; c++) {
                        const int tl = jj * 2 + (c >> 1), ks = (c & 1) * 4 + k4;
                        mma16816(acc[c], wo[tl][ks][0], wo[tl][ks][1], wo[tl][ks][2], wo[tl][ks][3], ob[2 * ks], ob[2 * ks + 1]);
                    }
                uint4 v;
                v.x = pack2(acc[0][0] + acc[1][0], acc[0][1] + acc[1][1]);
                v.y = pack2(acc[0][2] + acc[1][2], acc[0][3] + acc[1][3]);
                v.z = pack2(acc[2][0] + acc[3][0], acc[2][1] + acc[3][1]);
                v.w = pack2(acc[2][2] + acc[3][2], acc[2][3] + acc[3][3]);
                st_async_v4(tb.x + (jj << 24), v, tb.y + (jj << 24));
            }
            if (w == 0) PROF(6);
        } else {
            mbar_wait(sb + RB_V, s & 1);
            const uint4 o = lds128(tb.z);
            vb = make_uint4(hadd2(vb.x, o.x), hadd2(vb.y, o.y), hadd2(vb.z, o.z), hadd2(vb.w, o.w));
            mbar_wait(sb + RB_Q, s & 1);
        }
        if ((w >> 1) == rank) stsm4t(ta.z + (s & 1) * 1024, vb.x, vb.y, vb.z, vb.w);
        bar_sync(NB_C, 128);
        if (s != NSEG - 1 && w == 0 && lane16 == sb) mbar_expect_tx(sb + RB_V, 2048);
#pragma unroll
        for (int i = 0; i < 8; i++) av[i] = lds128(lane16 + R_WV + ((2 * w + (i >> 2)) * 16 + (i & 3)) * 512);
    }
    {
        const uint4 tp = lds128(tab + 20480);
        rec_store_kvm(tp.z, (char*)(((uint64_t)tp.y << 32) | tp.x), NSEG - 1, w);
    }
    bar_sync(NB_C, 128);
    if (w == 0 && lane == 0) red_release(&g_flags[F_MEM + NRB - 1], 1);
}

__global__ void __launch_bounds__(384, 1) k_rec(const __grid_constant__ RecParams p) {
    extern __shared__ __align__(1024) unsigned char smem_raw[];
    const uint32_t sb = __shfl_sync(~0u, smem_u32(smem_raw), 0);
    const int warp = __shfl_sync(~0u, threadIdx.x >> 5, 0);
    int lane; asm volatile("mov.u32 %0, %%laneid;" : "=r"(lane));
    const int crank = blockIdx.x & 15, slot = blockIdx.x >> 4;
    asm volatile("griddepcontrol.launch_dependents;");
    if (crank == 0 && threadIdx.x == 0) {
        stg_relaxed32(&g_F[65536 + slot * 64], 0u);
        stg_relaxed32(&g_F[65536 + 1024 + slot * 64], 0u);
    }
    if (threadIdx.x == 0) {
        mbar_init(sb + RB_Q, 9); mbar_init(sb + RB_V, 1); mbar_init(sb + RB_E, 1); mbar_init(sb + RB_A, 1); mbar_init(sb + RB_ROLE, 1);
        mbar_init(sb + RB_KV, 1); mbar_init(sb + RB_KV + 8, 1);
        asm volatile("fence.mbarrier_init.release.cluster;" ::: "memory");
        mbar_expect_tx(sb + RB_Q, 4096);
        mbar_expect_tx(sb + RB_V, 2048);
        mbar_expect_tx(sb + RB_E, 4096);
        mbar_expect_tx(sb + RB_A, 4096);
        mbar_expect_tx(sb + RB_ROLE, 4);
    }
    asm volatile("barrier.cluster.arrive.relaxed.aligned;\nbarrier.cluster.wait.aligned;" ::: "memory");
    unsigned role = 0;
    if (crank == 0 && threadIdx.x == 0 && !p.only_pre) {
        unsigned x = 0;
        int tm[2] = {0x7fffffff, 0x7fffffff};
#pragma unroll 1
        for (int i = 0; i < 6; i++) {
            const uint32_t t0 = clk32();
            x = atomicAdd(&g_F[65536 + (i & 1) * 1024 + slot * 64 + (x >> 31)], 1u);
            if (x != (unsigned)(i >> 1)) sts32(sb + R_BAR + 56, x);
            const int dt = (int)(clk32() - t0);
            if (i >= 2) { if (i & 1) tm[1] = min(tm[1], dt); else tm[0] = min(tm[0], dt); }
        }
        const int side = tm[1] > tm[0];
        const unsigned old = atomicAdd(&g_flags[F_SIDE + side * 32], 1u);
        unsigned c0, c1; int gd = 0;
#pragma unroll 1
        do { c0 = ldg_relaxed32(&g_flags[F_SIDE]); c1 = ldg_relaxed32(&g_flags[F_SIDE + 32]); } while ((int)(c0 + c1) < p.ncl && ++gd < 64 * SPIN_LIMIT);
        const int big = c1 > c0;
        role = side == big ? old : (big ? c1 : c0) + old;
        role |= (big ^ 1) << 8;
    }
    __syncwarp();
    if (crank == 0 && warp == 0 && !p.only_pre) {
        role = __shfl_sync(~0u, role, 0);
        if (lane < 16)
            asm volatile("st.async.weak.shared::cluster.mbarrier::complete_tx::bytes.u32 [%0], %1, [%2];"
                         :: "r"(mapa_u32(sb + R_BAR + 48, lane)), "r"(role), "r"(mapa_u32(sb + RB_ROLE, lane)) : "memory");
    }
    if (warp >= 4) {
        const int w8 = warp - 4, nblk = gridDim.x;
        const int cq = lane & 3, rg = w8 * 8 + (lane >> 2);
        const uint32_t red = sb + R_VP;
        const int row0 = blockIdx.x * 8 + w8;
        const uint4* xr = (const uint4*)(p.x + (size_t)row0 * D_);
        uint4 xa = __ldg(xr + lane), xb = __ldg(xr + 32 + lane);
#pragma unroll 1
        for (int sl = blockIdx.x; sl < 96; sl += nblk) {
            uint4 wv[8];
#pragma unroll
            for (int i = 0; i < 8; i++) wv[i] = __ldg((const uint4*)(p.w_mod + (size_t)(rg * 8 + i) * (6 * D_) + sl * 32 + cq * 8));
            const uint32_t cw = __ldg((const uint32_t*)(p.c + rg * 8) + cq);
            const float cl = bflo(cw), ch = bfhi(cw);
            const uint32_t sw = pack2(__fdividef(cl, 1.f + __expf(-cl)), __fdividef(ch, 1.f + __expf(-ch)));
            float a[8];
#pragma unroll
            for (int i = 0; i < 8; i++) a[i] = 0.f;
#pragma unroll
            for (int i = 0; i < 8; i++) {
                const uint32_t sv = __shfl_sync(~0u, sw, (lane & 28) + (i >> 1));
                const float cv = (i & 1) ? bfhi(sv) : bflo(sv);
                a[0] = fmaf(cv, bflo(wv[i].x), a[0]); a[1] = fmaf(cv, bfhi(wv[i].x), a[1]); a[2] = fmaf(cv, bflo(wv[i].y), a[2]); a[3] = fmaf(cv, bfhi(wv[i].y), a[3]);
                a[4] = fmaf(cv, bflo(wv[i].z), a[4]); a[5] = fmaf(cv, bfhi(wv[i].z), a[5]); a[6] = fmaf(cv, bflo(wv[i].w), a[6]); a[7] = fmaf(cv, bfhi(wv[i].w), a[7]);
            }
#pragma unroll
            for (int i = 0; i < 8; i++) { a[i] += __shfl_xor_sync(~0u, a[i], 4); a[i] += __shfl_xor_sync(~0u, a[i], 8); a[i] += __shfl_xor_sync(~0u, a[i], 16); }
            if (lane < 4) {
                sts128(red + w8 * 128 + lane * 32, make_uint4(__float_as_uint(a[0]), __float_as_uint(a[1]), __float_as_uint(a[2]), __float_as_uint(a[3])));
                sts128(red + w8 * 128 + lane * 32 + 16, make_uint4(__float_as_uint(a[4]), __float_as_uint(a[5]), __float_as_uint(a[6]), __float_as_uint(a[7])));
            }
            bar_sync(NB_B, 256);
            if (w8 == 0) {
                float v = 0.f;
#pragma unroll
                for (int i = 0; i < 8; i++) v += lds32f(red + i * 128 + lane * 4);
                g_mod[sl * 32 + lane] = __float2bfloat16_rn(v);
                __syncwarp();
                if (lane == 0) red_release(&g_flags[F_MOD + (sl >= 32)], 1);
            }
            bar_sync(NB_B, 256);
        }
        uint32_t c1[8], sm[8];
        int row = row0;
#pragma unroll 1
        while (true) {
            const uint32_t v[8] = {xa.x, xa.y, xa.z, xa.w, xb.x, xb.y, xb.z, xb.w};
            uint32_t mu2, r[8]; float rden;
            ln_stats(v, mu2, rden);
            if (row == row0) {
                if (lane == 0) wait_flag(F_MOD, 32);
                __syncwarp();
                load_mod8(g_mod + D_, lane, c1);
                load_mod8(g_mod, lane, sm);
#pragma unroll
                for (int i = 0; i < 8; i++) c1[i] = hadd2(c1[i], 0x3F803F80u);
            } else if (row + 512 < S_) {
                xr = (const uint4*)(p.x + (size_t)(row + 512) * D_); xa = __ldg(xr + lane); xb = __ldg(xr + 32 + lane);
            }
            ln_apply(v, mu2, rden, c1, sm, r);
            uint4* hr = (uint4*)(g_h + (size_t)row * D_);
            hr[lane] = make_uint4(r[0], r[1], r[2], r[3]); hr[32 + lane] = make_uint4(r[4], r[5], r[6], r[7]);
            bar_sync(NB_B, 256);
            if (w8 == (row >> 7 & 7) && lane == 0) red_release(&g_flags[F_H + (row >> 7)], 1);
            __syncwarp();
            if (row == row0) {
                if (!p.only_pre) mbar_wait(sb + RB_ROLE, 0);
                const int cl = p.only_pre ? slot : (int)(lds32(sb + R_BAR + 48) & 255);
                row = cl < 4 ? (nblk + cl * 16 + crank) * 8 + w8 : S_;
                if (row < S_) { xr = (const uint4*)(p.x + (size_t)row * D_); xa = __ldg(xr + lane); xb = __ldg(xr + 32 + lane); }
            } else {
                row += 512;
            }
            if (row >= S_) break;
        }
    }
    if (p.only_pre) return;
    mbar_wait(sb + RB_ROLE, 0);
    const int rolew = __shfl_sync(~0u, lds32(sb + R_BAR + 48), 0);
    const int cl = rolew & 255;
    if (cl >= 4) return;
    const int cta = cl * 16 + crank;
    if (warp < 8) rec_qk(p, sb, cta, warp, lane, rolew >> 8);
    else rec_vo(p, sb, cta, warp, lane);
}

enum { J_KV = 0, J_QA = 1, J_O = 2, J_LN = 3, J_UP = 4, J_DN = 5, J_UP2 = 8, J_END = 9 };
constexpr int NJ_O = 2 * OSPLIT, NJ_O2 = 2 * OSPLIT2, NJ_LN = 8, NJ_LN2 = 16, NJ_UP = 14, NJ_UP2 = 28, NJ_DN = 8, NJ_LN1 = 8  ;
constexpr uint64_t pk8(int a, int b, int c, int d, int e, int f, int g, int h) {
    return (uint64_t)a | ((uint64_t)b << 8) | ((uint64_t)c << 16) | ((uint64_t)d << 24) | ((uint64_t)e << 32) | ((uint64_t)f << 40) | ((uint64_t)g << 48) | ((uint64_t)h << 56);
}
constexpr uint64_t NJ_C = pk8(32, 16, NJ_O, NJ_LN, NJ_UP, NJ_DN, 0, 0), NJ_F = pk8(32, 16, NJ_O2, NJ_LN2, NJ_UP2, NJ_DN, 0, 0);
constexpr uint64_t TG_C = pk8(2 * NJ_LN1, 64, 32, 2 * NJ_O, 2 * NJ_LN, 2 * NJ_UP, 32, 0), TG_F = pk8(2 * NJ_LN1, 64, 32, 2 * NJ_O2, 2 * NJ_LN2, 2 * NJ_UP2, 32, 0);
constexpr uint64_t NJ_L = pk8(32, 32, 2 * OSPLIT3, NJ_LN2, NJ_UP2, 2 * NJ_DN, 0, 0), TG_L = pk8(2 * NJ_LN1, 64, 64, 4 * OSPLIT3, 2 * NJ_LN2, 2 * NJ_UP2, 32, 0);
__device__ __forceinline__ uint64_t nj_tab(int rb) { return rb < FINE_RB ? NJ_C : (rb < NRB - 1 ? NJ_F : NJ_L); }
__device__ __forceinline__ uint64_t tg_tab(int rb) { return rb < FINE_RB ? TG_C : (rb < NRB - 1 ? TG_F : TG_L); }
__device__ __forceinline__ int o_nk(int rb) { return rb < FINE_RB ? 64 / OSPLIT : (rb < NRB - 1 ? 64 / OSPLIT2 : 64 / OSPLIT3); }
constexpr uint64_t PRIO = pk8(4, 10, 9, 8, 7, 6, 3, 0);
__device__ __forceinline__ int pick_job(int lane, int qmask, int& idx) {
    const int rb = lane & 15, half = lane >> 4;
    const uint64_t nj = nj_tab(rb) >> (8 * half);
    const uint64_t tg = tg_tab(rb) >> (8 * half);
    const unsigned* cp = &g_flags[F_CLAIM + half * 32 + rb];
    const unsigned* dp = &g_flags[half * 32 + rb];
    int gd = 0;
#pragma unroll 1
    while (true) {
        const unsigned c0 = ldg_relaxed32(cp), c1 = ldg_relaxed32(cp + 64), c2 = ldg_relaxed32(cp + 128);
        const unsigned d0 = ldg_relaxed32(dp - (half && rb ? 1 : 0)), d1 = ldg_relaxed32(dp + 64), d2 = ldg_relaxed32(dp + 128);
        const unsigned cl[3] = {c0, c1, c2}, dv[3] = {d0, d1, d2};
        unsigned key = 0xffffu, key2 = 0xffffu;
        bool pre = false;
#pragma unroll
        for (int i = 0; i < 3; i++) {
            const int q = half + 2 * i;
            const bool have = ((qmask >> q) & 1) && cl[i] < (unsigned)((nj >> (16 * i)) & 255);
            bool ready = have && dv[i] >= (unsigned)((tg >> (16 * i)) & 255);
            unsigned pr = (unsigned)((PRIO >> (8 * q)) & 255);
            if (i == 0 && rb <= 1 - half) ready = have;
            if (i == 0 && half && rb >= FINE_RB) pr = 5;
            if (ready) key = min(key, (pr << 8) | (rb << 4) | q);
            if (have) key2 = min(key2, rb >= FINE_RB ? (0x100u | (q << 4) | rb) : (i == 0 ? 0u : 0x1000u));
            pre |= have && i == 0 && !half;
        }
        const bool anypre = __any_sync(~0u, pre);
        if (anypre && (key & 15) == J_QA) key = 0xffffu;
        key = __reduce_min_sync(~0u, key);
        key2 = __reduce_min_sync(~0u, key2);
        if (key2 == 0xffffu) return J_END;
        int pq, prb;
        if (key != 0xffffu) { pq = key & 15; prb = (key >> 4) & 15; }
        else if (key2 >= 0x120u && key2 < 0x1000u) { pq = (key2 >> 4) & 15; prb = key2 & 15; }
        else {
            __nanosleep(IDLE_NS);
            if (++gd > 16 * SPIN_LIMIT) { TIMEOUT(5, 0); return J_END; }
            continue;
        }
        int c = 0;
        if (lane == 0) c = (int)atomicAdd(&g_flags[F_CLAIM + pq * 32 + prb], 1u);
        c = __shfl_sync(~0u, c, 0);
        if (c < (int)((nj_tab(prb) >> (8 * pq)) & 255)) {
            idx = pq * 512 + prb * 32 + c;
            int acq = 0;
            if (pq != J_QA) {
                if (lane == 0 && ld_acquire(&g_flags[pq * 32 + prb]) >= (unsigned)((tg_tab(prb) >> (8 * pq)) & 255)) {
                    asm volatile("fence.proxy.async.global;" ::: "memory");
                    acq = 1 << 24;
                }
            }
            return (pq == J_UP && prb >= FINE_RB ? J_UP2 : pq) | (prb << 8) | (c << 16) | acq;
        }
    }
}
__device__ __forceinline__ int op_row(int rb, int split) {
    return rb < FINE_RB ? split * S_ + rb * 128
                        : (rb < NRB - 1 ? OSPLIT * S_ + (split * (NRB - FINE_RB) + rb - FINE_RB) * 128 : OSPLIT * S_ + (OSPLIT2 * (NRB - FINE_RB) + split) * 128);
}

struct Pipe { uint32_t stage, phase; };
__device__ __forceinline__ void pipe_next(Pipe& p) { if (++p.stage == W_NST) { p.stage = 0; p.phase ^= 1; } }

__device__ __forceinline__ void scheduler(const Params& p, uint32_t sb, int lane) {
    const uint32_t bars = sb + SM_BAR;
    uint32_t ph = 0;
#pragma unroll 1
    while (true) {
        mbar_wait(bars + B_REQ, ph);
        int j = 4095;
        const int jd = pick_job(lane, p.qmask, j);
        if (lane == 0) { sts32(bars + B_NEXT, (uint32_t)jd); sts32(bars + B_NEXT + 4, (uint32_t)j); mbar_arrive(bars + B_RSP); }
        ph ^= 1;
        if (jd == J_END) break;
        __syncwarp();
    }
}

__device__ __forceinline__ void producer(const Params& p, uint32_t sb) {
    Pipe pp{0, 1};
    const uint32_t bars = sb + SM_BAR;
    uint32_t seq = 0, h_seen = 0;
    mbar_arrive(bars + B_REQ);
#pragma unroll 1
    while (true) {
        mbar_wait(bars + B_RSP, seq & 1);
        const int jd = (int)lds32(bars + B_NEXT), j = (int)lds32(bars + B_NEXT + 4);
        int left = (jd & 255) == J_DN ? 15 : ((jd & 255) == J_O ? o_nk((jd >> 8) & 255) : ((jd & 255) == J_LN ? 1 : 8));
        left = (jd & 255) == J_QA ? 9 : max(left - PICK_AHEAD, 1);
        TR(j, 1);
        const int type = jd & 255, rb = (jd >> 8) & 255, cb = (jd >> 16) & 255;
        const bool fine = rb >= FINE_RB, acquired = (jd >> 24) & 1;
        bool first = true;
        auto begin_stage = [&](uint32_t bytes) -> uint32_t {
            mbar_wait(bars + B_EMPTY + pp.stage * 8, pp.phase);
            if (first) { sts32(bars + B_RING + (seq & 7) * 4, (uint32_t)jd); sts32(bars + B_RING + 32 + (seq & 7) * 4, (uint32_t)j); first = false; }
            const uint32_t fb = bars + B_FULL + pp.stage * 8;
            if (bytes) mbar_expect_tx(fb, bytes); else mbar_arrive(fb);
            return fb;
        };
        auto end_stage = [&]() {
            pipe_next(pp);
            if (--left == 0) mbar_arrive(bars + B_REQ);
        };
        if (type == J_END || type == J_LN) {
            if (type == J_LN && !(h_seen >> 31)) { wait_flag(F_MOD + 1, 64); h_seen |= 1u << 31; }

            TR(j, 2);
            begin_stage(0);
            if (type == J_END) break;
            if (!acquired) wait_flag(F_OP + rb, (unsigned)((tg_tab(rb) >> (8 * J_LN)) & 255));
            end_stage();
            seq++;
            continue;
        }
        const CUtensorMap *ta, *tb0, *tb1;
        int k0 = 0, nk = 8, n0 = cb * 256, n1 = n0 + 128, nb = 4, dep = -1;
        unsigned tgt = 0;
        switch (type) {
            case J_KV: ta = &p.tm_h; tb0 = tb1 = cb < 16 ? &p.tm_wk : &p.tm_wv; n0 = (cb & 15) * 256; n1 = n0 + 128; dep = F_H + rb; tgt = 2 * NJ_LN1; break;
            case J_QA: ta = &p.tm_h; tb0 = tb1 = &p.tm_wq; dep = F_H + rb; tgt = 2 * NJ_LN1; if (rb == NRB - 1) { n0 = (cb >> 1) * 256; n1 = n0 + 128; } break;
            case J_O: ta = &p.tm_o; tb0 = tb1 = &p.tm_wo; n0 = (cb & 1) * 256; n1 = n0 + 128; nk = o_nk(rb); k0 = (cb >> 1) * nk * 64;
                      dep = F_O + rb; tgt = rb == NRB - 1 ? 64 : 32; break;
            case J_UP: ta = &p.tm_h2; tb0 = &p.tm_wg; tb1 = &p.tm_wu; n0 = n1 = cb * 128; dep = F_H2 + rb; tgt = 2 * NJ_LN; break;
            case J_UP2: ta = &p.tm_h2; tb0 = &p.tm_wg; tb1 = &p.tm_wu; n0 = n1 = cb * 64; nb = 2; dep = F_H2 + rb; tgt = 2 * NJ_LN2; break;
            default: ta = &p.tm_act; tb0 = tb1 = &p.tm_wd; n0 = cb * 64; nk = 0; break;
        }
        const int m0 = rb * 128;
        if (type == J_DN && rb == NRB - 1) {
            n0 = (cb >> 1) * 64;
            const int mh = m0 + (cb & 1) * 64;
#pragma unroll 1
            for (int kb = 0; kb < 14; kb++) {
                const uint32_t fb = begin_stage(32768);
                const uint32_t st = sb + pp.stage * W_STAGE;
                const int k = kb * 128;
                tma_load2d(st + 32768, tb0, n0, k, fb);
                tma_load2d(st + 40960, tb0, n0, k + 64, fb);
                if (kb == 0) { if (!acquired) { wait_flag(F_ACT + rb, 2 * NJ_UP2); asm volatile("fence.proxy.async.global;" ::: "memory"); } TR(j, 2); }
                tma_load2d(st, ta, k, mh, fb);
                tma_load2d(st + 8192, ta, k + 64, mh, fb);
                end_stage();
            }
            const uint32_t fb = begin_stage(8192);
            tma_load2d(sb + pp.stage * W_STAGE, &p.tm_x1, n0, mh, fb);
            end_stage();
            seq++;
            continue;
        }
        if (type == J_DN) {
#pragma unroll 1
            for (int kb = 0; kb < 14; kb++) {
                const uint32_t fb = begin_stage(49152);
                const uint32_t st = sb + pp.stage * W_STAGE;
                const int k = kb * 128;
                tma_load2d(st + 32768, tb0, n0, k, fb);
                tma_load2d(st + 40960, tb0, n0, k + 64, fb);
                if (kb == 0) { if (!acquired) { wait_flag(F_ACT + rb, 2 * (fine ? NJ_UP2 : NJ_UP)); asm volatile("fence.proxy.async.global;" ::: "memory"); } TR(j, 2); }
                tma_load2d(st, ta, k, m0, fb);
                tma_load2d(st + 8192, ta, k, m0 + 64, fb);
                tma_load2d(st + 16384, ta, k + 64, m0, fb);
                tma_load2d(st + 24576, ta, k + 64, m0 + 64, fb);
                end_stage();
            }
        }
#pragma unroll 1
        for (int kb = 0; kb < nk; kb++) {
            const uint32_t fb = begin_stage(16384 + nb * 8192);
            const uint32_t st = sb + pp.stage * W_STAGE;
            const int k = k0 + kb * 64;
            tma_load2d(st + 16384, tb0, n0, k, fb);
            if (nb == 4) {
                tma_load2d(st + 16384 + 8192, tb0, n0 + 64, k, fb);
                tma_load2d(st + 16384 + 16384, tb1, n1, k, fb);
                tma_load2d(st + 16384 + 24576, tb1, n1 + 64, k, fb);
            } else if (nb == 2) {
                tma_load2d(st + 16384 + 8192, tb1, n1, k, fb);
            }
            if (kb == 0) {
                if (acquired && dep < 16) h_seen |= 1u << dep;
                if (dep >= 0 && !acquired && !(dep < 16 && ((h_seen >> dep) & 1))) {
                    wait_flag(dep, tgt);
                    if (type != J_O) asm volatile("fence.proxy.async.global;" ::: "memory");
                    if (dep < 16) h_seen |= 1u << dep;
                }
                TR(j, 2);
            }
            tma_load2d(st, ta, k, m0, fb);
            tma_load2d(st + 8192, ta, k, m0 + 64, fb);
            end_stage();
        }
        if (type == J_QA) {
            wait_flag(F_KV + rb, 64);
#pragma unroll 1
            for (int i = 0; i < (rb == NRB - 1 ? 2 : 4); i++) {
                const uint32_t fb = begin_stage(40960);
                const uint32_t st = sb + pp.stage * W_STAGE;
                const int col = (i & 1) * HD_ + (rb == NRB - 1 ? cb : cb * 2 + (i >> 1)) * DH_;
                tma_load2d(st, &p.tm_kv, col, m0, fb);
                tma_load2d(st + 8192, &p.tm_kv, col, m0 + 64, fb);
                tma_load2d(st + 16384, &p.tm_kv, col + 64, m0, fb);
                tma_load2d(st + 24576, &p.tm_kv, col + 64, m0 + 64, fb);
                if (i == 0) { wait_flag(F_MEM + rb, 64); asm volatile("fence.proxy.async.global;" ::: "memory"); }
                tma_load2d(st + 32768, &p.tm_kvm, col, rb * 32, fb);
                tma_load2d(st + 36864, &p.tm_kvm, col + 64, rb * 32, fb);
                end_stage();
            }
        } else if (type == J_DN) {
            const uint32_t fb = begin_stage(16384);
            const uint32_t st = sb + pp.stage * W_STAGE;
            tma_load2d(st, &p.tm_x1, n0, m0, fb);
            tma_load2d(st + 8192, &p.tm_x1, n0, m0 + 64, fb);
            end_stage();
        }
        seq++;
    }
}

__device__ __forceinline__ void store_warp(const Params& p, uint32_t sb, int wg, int lane) {
    const uint32_t bars = sb + SM_BAR;
    uint32_t seq = 0;
#pragma unroll 1
    while (true) {
        bar_sync(NB_ST + wg, 160);
        const uint32_t jd = lds32(bars + B_RING + (seq & 7) * 4);
        seq++;
        const int type = jd & 255, rb = (jd >> 8) & 255, cb = (jd >> 16) & 255;
        if (type == J_END) break;
        const uint32_t src = sb + W_STG + wg * 16384;
        const CUtensorMap* tm = nullptr; int n0 = cb * 256, nbox = 4, mrow = rb * 128 + wg * 64, flag = 0;
        switch (type) {
            case J_KV: tm = &p.tm_kv; flag = F_KV + rb; break;
            case J_QA: tm = &p.tm_o; flag = F_O + rb; if (rb == NRB - 1) { n0 = cb * 128; nbox = 2; } break;
            case J_O: tm = &p.tm_op; n0 = (cb & 1) * 256; mrow = op_row(rb, cb >> 1) + wg * 64; flag = F_OP + rb; break;
            case J_LN: flag = F_H2 + rb; nbox = 0; break;
            case J_UP: tm = &p.tm_act; n0 = cb * 128; nbox = 2; flag = F_ACT + rb; break;
            case J_UP2: tm = &p.tm_act; n0 = cb * 64; nbox = 1; flag = F_ACT + rb; break;
            default: tm = &p.tm_out; n0 = cb * 64; nbox = 1; flag = -1;
                     if (rb == NRB - 1) { n0 = (cb >> 1) * 64; mrow = rb * 128 + (cb & 1) * 64; nbox = wg == 0; } break;
        }
        if (nbox == 4) {
            if (lane == 0) {
                tma_store2d(tm, src, n0, mrow);
                tma_store2d(tm, src + 8192, n0 + 64, mrow);
                bulk_commit();
                asm volatile("cp.async.bulk.wait_group.read 0;" ::: "memory");
                mbar_arrive(bars + B_STGFREE + wg * 8);
            }
            __syncwarp();
            bar_sync(NB_ST + wg, 160);
            n0 += 128; nbox = 2;
        }
        if (lane == 0) {
            if (nbox) {
                tma_store2d(tm, src, n0, mrow);
                if (nbox == 2) tma_store2d(tm, src + 8192, n0 + 64, mrow);
                bulk_commit();
                asm volatile("cp.async.bulk.wait_group.read 0;" ::: "memory");
                mbar_arrive(bars + B_STGFREE + wg * 8);
                bulk_wait0();
                if (flag >= 0) asm volatile("red.relaxed.gpu.global.add.u32 [%0], 1;" :: "l"(&g_flags[flag]) : "memory");
            } else {
                mbar_arrive(bars + B_STGFREE + wg * 8);
                if (flag >= 0) red_release(&g_flags[flag], 1);
            }
        }
        __syncwarp();
    }
}

__device__ __forceinline__ float gelu_tanh(float x) {
    const float t = x * fmaf(-0.10294324397f, x * x, -2.30220819814f);
    float r; asm("rcp.approx.ftz.f32 %0, %1;" : "=f"(r) : "f"(1.f + ex2(t)));
    return x * r;
}

#define CTR(i) do {} while (0)

__device__ __forceinline__ void ln2_row(const Params& p, int rb, int r, int lane, bool wait) {
    const int row = rb * 128 + r, nsplit = 64 / o_nk(rb);
    const uint4* xr = (const uint4*)(p.x + (size_t)row * D_);
    const uint4 xa = __ldg(xr + lane), xb = __ldg(xr + 32 + lane);
    uint32_t ga[8], c1[8], sm[8];
    load_mod8(g_mod + 2 * D_, lane, ga);
    load_mod8(g_mod + 4 * D_, lane, c1);
    load_mod8(g_mod + 3 * D_, lane, sm);
    float a[16];
#pragma unroll
    for (int i = 0; i < 16; i++) a[i] = 0.f;
    const uint4* src = (const uint4*)(g_op + (size_t)(op_row(rb, 0) + r) * D_) + lane;
    const int sstride = (op_row(rb, 1) - op_row(rb, 0)) * (D_ / 8);
    if (wait) { if (lane == 0) wait_flag(F_OP + rb, 4 * nsplit); __syncwarp(); }
    uint4 u[2][8];
#pragma unroll
    for (int sp = 0; sp < 4; sp++) { u[0][2 * sp] = __ldcg(src + sp * sstride); u[0][2 * sp + 1] = __ldcg(src + sp * sstride + 32); }
    if (nsplit > 4) {
#pragma unroll
        for (int sp = 0; sp < 4; sp++) { u[1][2 * sp] = __ldcg(src + (4 + sp) * sstride); u[1][2 * sp + 1] = __ldcg(src + (4 + sp) * sstride + 32); }
    }
#pragma unroll 1
    for (int s0 = 0; s0 < nsplit; s0 += 4) {
#pragma unroll
        for (int sp = 0; sp < 8; sp++) {
            float* q = a + (sp & 1) * 8;
            const uint4 w = u[0][sp];
            q[0] += bflo(w.x); q[1] += bfhi(w.x); q[2] += bflo(w.y); q[3] += bfhi(w.y);
            q[4] += bflo(w.z); q[5] += bfhi(w.z); q[6] += bflo(w.w); q[7] += bfhi(w.w);
            u[0][sp] = u[1][sp];
        }
        if (s0 + 8 < nsplit) {
#pragma unroll
            for (int sp = 0; sp < 4; sp++) { u[1][2 * sp] = __ldcg(src + (s0 + 8 + sp) * sstride); u[1][2 * sp + 1] = __ldcg(src + (s0 + 8 + sp) * sstride + 32); }
        }
    }
    const uint32_t xv[8] = {xa.x, xa.y, xa.z, xa.w, xb.x, xb.y, xb.z, xb.w};
    uint32_t v[8], r8[8];
#pragma unroll
    for (int i = 0; i < 8; i++) v[i] = hadd2(xv[i], hmul2(ga[i], pack2(a[2 * i], a[2 * i + 1])));
    uint4* x1r = (uint4*)(g_x1 + (size_t)row * D_);
    x1r[lane] = make_uint4(v[0], v[1], v[2], v[3]); x1r[32 + lane] = make_uint4(v[4], v[5], v[6], v[7]);
    uint32_t mu2; float rden;
    ln_stats(v, mu2, rden);
#pragma unroll
    for (int i = 0; i < 8; i++) c1[i] = hadd2(c1[i], 0x3F803F80u);
    ln_apply(v, mu2, rden, c1, sm, r8);
    uint4* hr = (uint4*)(g_h2 + (size_t)row * D_);
    hr[lane] = make_uint4(r8[0], r8[1], r8[2], r8[3]); hr[32 + lane] = make_uint4(r8[4], r8[5], r8[6], r8[7]);
}

__device__ __forceinline__ void consumer(const Params& p, uint32_t sb, int warp, int lane) {
    const uint32_t bars = sb + SM_BAR;
    const int wg = warp >> 2, wl = warp & 3;
    const uint32_t l7 = lane & 7, l8 = lane >> 3, g = lane >> 2, t = lane & 3;
    Pipe pp{0, 0};
    uint32_t seq = 0, stg_phase = 1;
    const int srow = wl * 16 + l7 + (l8 & 1) * 8;
    const uint32_t stg_base = sb + W_STG + wg * 16384 + srow * 128;
    const uint32_t sx = ((lane >> 4) ^ (srow & 7)) << 4;
#pragma unroll 1
    while (true) {
        mbar_wait(bars + B_FULL + pp.stage * 8, pp.phase);
        const uint32_t jd = lds32(bars + B_RING + (seq & 7) * 4);
        CTR(3);
        seq++;
        const int type = jd & 255, rb = (jd >> 8) & 255, cb = (jd >> 16) & 255;
        if (type == J_END) { mbar_wait(bars + B_STGFREE + wg * 8, stg_phase); bar_arrive(NB_ST + wg, 160); break; }
        if (type == J_LN) {
            __syncwarp();
            if (lane == 0) mbar_arrive(bars + B_EMPTY + pp.stage * 8);
            pipe_next(pp);
            const int nr = rb >= FINE_RB ? 1 : 2;
#pragma unroll 1
            for (int rr = 0; rr < nr; rr++) ln2_row(p, rb, (cb * 8 + warp) * nr + rr, lane, !((jd >> 24) & 1) && rr == 0);
            mbar_wait(bars + B_STGFREE + wg * 8, stg_phase); stg_phase ^= 1;
            CTR(4); CTR(5);
            bar_arrive(NB_ST + wg, 160);
            continue;
        }
        if (type == J_DN || type == J_UP2) {
            float acc[64];
#pragma unroll
            for (int i = 0; i < 64; i++) acc[i] = 0.f;
            const bool ksplit = type == J_DN && rb == NRB - 1;
            if (ksplit) {
#pragma unroll 1
                for (int kb = 0; kb < 14; kb++) {
                    if (kb) mbar_wait(bars + B_FULL + pp.stage * 8, pp.phase);
                    const uint32_t st = sb + pp.stage * W_STAGE;
                    const uint64_t da = mkdesc(st + wg * 8192, 16, 1024), db = mkdesc(st + 32768 + wg * 8192, 8192, 1024);
                    wg_fence();
#pragma unroll
                    for (int ks = 0; ks < 4; ks++) wgmma_n64(acc, da + ks * 2, db + ks * 128);
                    wg_commit();
                    wg_wait0();
                    if (lane == 0) mbar_arrive(bars + B_EMPTY + pp.stage * 8);
                    pipe_next(pp);
                }
                const uint32_t xb = sb + W_STG + 16384 + (wl * 32 + lane) * 16;
                if (wg == 1) {
                    mbar_wait(bars + B_STGFREE + 8, stg_phase);
#pragma unroll
                    for (int i = 0; i < 8; i++)
                        sts128(xb + i * 2048, make_uint4(__float_as_uint(acc[4 * i]), __float_as_uint(acc[4 * i + 1]), __float_as_uint(acc[4 * i + 2]), __float_as_uint(acc[4 * i + 3])));
                }
                bar_sync(NB_M, 256);
                if (wg == 0) {
#pragma unroll
                    for (int i = 0; i < 8; i++) {
                        const uint4 o = lds128(xb + i * 2048);
                        acc[4 * i] += __uint_as_float(o.x); acc[4 * i + 1] += __uint_as_float(o.y); acc[4 * i + 2] += __uint_as_float(o.z); acc[4 * i + 3] += __uint_as_float(o.w);
                    }
                }
                bar_sync(NB_M, 256);
            } else if (type == J_DN) {
#pragma unroll 1
                for (int kb = 0; kb < 14; kb++) {
                    if (kb) mbar_wait(bars + B_FULL + pp.stage * 8, pp.phase);
                    const uint32_t st = sb + pp.stage * W_STAGE;
                    const uint64_t da = mkdesc(st + wg * 8192, 16, 1024), db = mkdesc(st + 32768, 8192, 1024);
                    wg_fence();
#pragma unroll
                    for (int ks = 0; ks < 8; ks++) wgmma_n64(acc, da + (ks >> 2) * 1024 + (ks & 3) * 2, db + ks * 128);
                    wg_commit();
                    wg_wait0();
                    if (lane == 0) mbar_arrive(bars + B_EMPTY + pp.stage * 8);
                    pipe_next(pp);
                }
            } else {
#pragma unroll 1
                for (int kb = 0; kb < 8; kb++) {
                    if (kb) mbar_wait(bars + B_FULL + pp.stage * 8, pp.phase);
                    const uint32_t st = sb + pp.stage * W_STAGE;
                    const uint64_t da = mkdesc(st + wg * 8192, 16, 1024), db = mkdesc(st + 16384, 8192, 1024);
                    wg_fence();
#pragma unroll
                    for (int ks = 0; ks < 4; ks++) wgmma_n128(acc, da + ks * 2, db + ks * 128, 1);
                    wg_commit();
                    wg_wait0();
                    if (lane == 0) mbar_arrive(bars + B_EMPTY + pp.stage * 8);
                    pipe_next(pp);
                }
            }
            CTR(4);
            if (type == J_UP2) {
                mbar_wait(bars + B_STGFREE + wg * 8, stg_phase); stg_phase ^= 1;
#pragma unroll
                for (int j = 0; j < 4; j++) {
                    uint32_t r[4];
#pragma unroll
                    for (int q = 0; q < 4; q++) {
                        const uint32_t gw = pack2(acc[8 * j + 2 * q], acc[8 * j + 2 * q + 1]);
                        const uint32_t uw = pack2(acc[32 + 8 * j + 2 * q], acc[32 + 8 * j + 2 * q + 1]);
                        r[q] = hmul2(pack2(gelu_tanh(bflo(gw)), gelu_tanh(bfhi(gw))), uw);
                    }
                    stsm4(stg_base + (sx ^ (j << 5)), r[0], r[1], r[2], r[3]);
                }
            } else {
                mbar_wait(bars + B_FULL + pp.stage * 8, pp.phase);
                const uint32_t st = sb + pp.stage * W_STAGE;
                mbar_wait(bars + B_STGFREE + wg * 8, stg_phase); stg_phase ^= 1;
                const uint32_t* gb = (const uint32_t*)(g_mod + 5 * D_ + (ksplit ? cb >> 1 : cb) * 64) + t;
                const uint32_t xa = st + (ksplit ? 0 : wg * 8192) + (wl * 16 + g) * 128 + (g << 4) + t * 4;
#pragma unroll
                for (int j = 0; j < 4; j++) {
                    uint32_t r[4];
#pragma unroll
                    for (int q = 0; q < 4; q++) {
                        const int nt = 2 * j + (q >> 1);
                        const uint32_t xw = lds32((xa ^ ((nt & 7) << 4)) + (nt >> 3) * 16384 + (q & 1) * 1024);
                        r[q] = hadd2(xw, hmul2(__ldcg(gb + nt * 4), pack2(acc[8 * j + 2 * q], acc[8 * j + 2 * q + 1])));
                    }
                    stsm4(stg_base + (j >> 2) * 8192 + (sx ^ ((2 * j & 7) << 4)), r[0], r[1], r[2], r[3]);
                }
                __syncwarp();
                if (lane == 0) mbar_arrive(bars + B_EMPTY + pp.stage * 8);
                pipe_next(pp);
            }
            fence_async_smem();
            CTR(5);
            bar_arrive(NB_ST + wg, 160);
            continue;
        }
        float acc[128];
#pragma unroll
        for (int i = 0; i < 128; i++) acc[i] = 0.f;
        const int nk = type == J_O ? o_nk(rb) : 8;
#pragma unroll 1
        for (int kb = 0; kb < nk; kb++) {
            if (kb) mbar_wait(bars + B_FULL + pp.stage * 8, pp.phase);
            const uint32_t st = sb + pp.stage * W_STAGE;
            const uint64_t da = mkdesc(st + wg * 8192, 16, 1024), db = mkdesc(st + 16384, 8192, 1024);
            wg_fence();
#pragma unroll
            for (int ks = 0; ks < 4; ks++) wgmma_n256(acc, da + ks * 2, db + ks * 128, 1);
            wg_commit();
            wg_wait0();
            if (lane == 0) mbar_arrive(bars + B_EMPTY + pp.stage * 8);
            pipe_next(pp);
        }
        CTR(4);
        if (type == J_QA) {
            uint32_t qf[64];
#pragma unroll
            for (int i = 0; i < 64; i++) qf[i] = pack2(acc[2 * i], acc[2 * i + 1]);
            const int sg = warp >> 1, half = warp & 1;
            const float sc = 0.08838834764831845f * 1.4426950408889634f;
            const uint32_t xoff = (sg >> 1) * 8192 + ((sg & 1) * 32 + l7) * 128;
            const uint32_t moff = 32768 + (sg * 8 + l7) * 128;
            const uint32_t kch = (l8 ^ l7) << 4;
            const uint32_t vch = ((l8 & 1) ^ l7) << 4;
            if (rb == NRB - 1 && (cb & 1)) {
#pragma unroll
                for (int i = 0; i < 32; i++) qf[i] = qf[32 + i];
            }
#pragma unroll 1
            for (int hh = rb == NRB - 1; hh < 2; hh++) {
                mbar_wait(bars + B_FULL + pp.stage * 8, pp.phase);
                uint32_t st = sb + pp.stage * W_STAGE;
                float sa[5][4];
#pragma unroll
                for (int n = 0; n < 5; n++) sa[n][0] = sa[n][1] = sa[n][2] = sa[n][3] = 0.f;
#pragma unroll
                for (int i = 0; i < 4; i++) {
                    const uint32_t* q = qf + i * 8;
                    uint32_t kk[5][4];
                    ldsm4(kk[0][0], kk[0][1], kk[0][2], kk[0][3], st + moff + (i >> 1) * 4096 + (kch ^ ((i & 1) * 64)));
#pragma unroll
                    for (int n = 1; n < 5; n++)
                        ldsm4(kk[n][0], kk[n][1], kk[n][2], kk[n][3], st + xoff + (n - 1) * 1024 + (i >> 1) * 16384 + (kch ^ ((i & 1) * 64)));
#pragma unroll
                    for (int n = 0; n < 5; n++) mma16816(sa[n], q[0], q[1], q[2], q[3], kk[n][0], kk[n][1]);
#pragma unroll
                    for (int n = 0; n < 5; n++) mma16816(sa[n], q[4], q[5], q[6], q[7], kk[n][2], kk[n][3]);
                }
                __syncwarp();
                if (lane == 0) mbar_arrive(bars + B_EMPTY + pp.stage * 8);
                pipe_next(pp);
                const int iq0 = half * 16 + g - 2 * t, iq1 = iq0 + 8;
                float m0 = fmaxf(sa[0][0], sa[0][1]), m1 = fmaxf(sa[0][2], sa[0][3]);
#pragma unroll
                for (int n = 1; n < 5; n++) {
#pragma unroll
                    for (int e = 0; e < 2; e++) {
                        const int jx = (n - 1) * 8 + e;
                        if (jx > iq0) sa[n][e] = -3.0e38f;
                        if (jx > iq1) sa[n][2 + e] = -3.0e38f;
                        m0 = fmaxf(m0, sa[n][e]); m1 = fmaxf(m1, sa[n][2 + e]);
                    }
                }
                m0 = fmaxf(m0, __shfl_xor_sync(~0u, m0, 1)); m1 = fmaxf(m1, __shfl_xor_sync(~0u, m1, 1));
                m0 = fmaxf(m0, __shfl_xor_sync(~0u, m0, 2)); m1 = fmaxf(m1, __shfl_xor_sync(~0u, m1, 2));
                m0 *= -sc; m1 *= -sc;
                float l0 = 0.f, l1 = 0.f;
                uint32_t p0[5], p1[5];
#pragma unroll
                for (int n = 0; n < 5; n++) {
                    const float e0 = ex2(fmaf(sa[n][0], sc, m0)), e1 = ex2(fmaf(sa[n][1], sc, m0));
                    const float e2 = ex2(fmaf(sa[n][2], sc, m1)), e3 = ex2(fmaf(sa[n][3], sc, m1));
                    l0 += e0 + e1; l1 += e2 + e3;
                    p0[n] = pack2(e0, e1); p1[n] = pack2(e2, e3);
                }
                l0 += __shfl_xor_sync(~0u, l0, 1); l1 += __shfl_xor_sync(~0u, l1, 1);
                l0 += __shfl_xor_sync(~0u, l0, 2); l1 += __shfl_xor_sync(~0u, l1, 2);
                const float i0 = __fdividef(1.f, l0), i1 = __fdividef(1.f, l1);
                mbar_wait(bars + B_FULL + pp.stage * 8, pp.phase);
                st = sb + pp.stage * W_STAGE;
                mbar_wait(bars + B_STGFREE + wg * 8, stg_phase); stg_phase ^= 1;
#pragma unroll
                for (int i = 0; i < 32; i++) qf[i] = qf[32 + i];
#pragma unroll 1
                for (int bx = 0; bx < 2; bx++) {
                    float o[8][4];
                    uint32_t vm[8], v0[4][4], v1[4][4];
#pragma unroll
                    for (int ep = 0; ep < 4; ep++) {
                        ldsm2t(vm[2 * ep], vm[2 * ep + 1], st + moff + bx * 4096 + (vch ^ (ep << 5)));
                        const uint32_t va = st + xoff + (l8 >> 1) * 1024 + bx * 16384 + (vch ^ (ep << 5));
                        ldsm4t(v0[ep][0], v0[ep][1], v0[ep][2], v0[ep][3], va);
                        ldsm4t(v1[ep][0], v1[ep][1], v1[ep][2], v1[ep][3], va + 2048);
                    }
#pragma unroll
                    for (int n = 0; n < 8; n++) { o[n][0] = o[n][1] = o[n][2] = o[n][3] = 0.f; mma16816(o[n], p0[0], p1[0], p0[1], p1[1], vm[n], v0[n >> 1][n & 1]); }
#pragma unroll
                    for (int n = 0; n < 8; n++) mma16816(o[n], p0[2], p1[2], p0[3], p1[3], v0[n >> 1][2 + (n & 1)], v1[n >> 1][n & 1]);
#pragma unroll
                    for (int n = 0; n < 8; n++) mma1688(o[n], p0[4], p1[4], v1[n >> 1][2 + (n & 1)]);
#pragma unroll
                    for (int ep = 0; ep < 4; ep++)
                        stsm4(stg_base + bx * 8192 + (sx ^ (ep << 5)),
                              pack2(o[2 * ep][0] * i0, o[2 * ep][1] * i0), pack2(o[2 * ep][2] * i1, o[2 * ep][3] * i1),
                              pack2(o[2 * ep + 1][0] * i0, o[2 * ep + 1][1] * i0), pack2(o[2 * ep + 1][2] * i1, o[2 * ep + 1][3] * i1));
                }
                __syncwarp();
                if (lane == 0) mbar_arrive(bars + B_EMPTY + pp.stage * 8);
                pipe_next(pp);
                if (hh == 0) { fence_async_smem(); bar_arrive(NB_ST + wg, 160); }
            }
        } else if (type == J_UP) {
            mbar_wait(bars + B_STGFREE + wg * 8, stg_phase); stg_phase ^= 1;
#pragma unroll
            for (int j = 0; j < 8; j++) {
                uint32_t r[4];
#pragma unroll
                for (int q = 0; q < 4; q++) {
                    const uint32_t gw = pack2(acc[8 * j + 2 * q], acc[8 * j + 2 * q + 1]);
                    const uint32_t uw = pack2(acc[64 + 8 * j + 2 * q], acc[64 + 8 * j + 2 * q + 1]);
                    r[q] = hmul2(pack2(gelu_tanh(bflo(gw)), gelu_tanh(bfhi(gw))), uw);
                }
                stsm4(stg_base + (j >> 2) * 8192 + (sx ^ ((2 * j & 7) << 4)), r[0], r[1], r[2], r[3]);
            }
        } else {
#pragma unroll
            for (int rd = 0; rd < 2; rd++) {
                mbar_wait(bars + B_STGFREE + wg * 8, stg_phase); stg_phase ^= 1;
#pragma unroll
                for (int j = rd * 8; j < rd * 8 + 8; j++)
                    stsm4(stg_base + ((j >> 2) & 1) * 8192 + (sx ^ ((2 * j & 7) << 4)),
                          pack2(acc[8 * j], acc[8 * j + 1]), pack2(acc[8 * j + 2], acc[8 * j + 3]),
                          pack2(acc[8 * j + 4], acc[8 * j + 5]), pack2(acc[8 * j + 6], acc[8 * j + 7]));
                if (rd == 0) { fence_async_smem(); bar_arrive(NB_ST + wg, 160); }
            }
        }
        fence_async_smem();
        CTR(5);
        bar_arrive(NB_ST + wg, 160);
    }
}

__global__ void __launch_bounds__(384, 1) k_work(const __grid_constant__ Params p) {
    extern __shared__ __align__(1024) unsigned char smem_raw[];
    const uint32_t sb = smem_u32(smem_raw);
    if (sb & 1023) __trap();
    const int warp = __shfl_sync(~0u, threadIdx.x >> 5, 0);
    int lane; asm volatile("mov.u32 %0, %%laneid;" : "=r"(lane));
    if (threadIdx.x == 0) {
        const uint32_t bars = sb + SM_BAR;
        for (int i = 0; i < W_NST; i++) { mbar_init(bars + B_FULL + i * 8, 1); mbar_init(bars + B_EMPTY + i * 8, 8); }
        mbar_init(bars + B_STGFREE, 1); mbar_init(bars + B_STGFREE + 8, 1); mbar_init(bars + B_REQ, 1); mbar_init(bars + B_RSP, 1);
        asm volatile("fence.mbarrier_init.release.cluster;" ::: "memory");
    }
    __syncthreads();
    if (warp < 8) {
        asm volatile("setmaxnreg.inc.sync.aligned.u32 224;");
        consumer(p, sb, warp, lane);
    } else {
        asm volatile("setmaxnreg.dec.sync.aligned.u32 56;");
        if (warp == 8) { if (lane == 0) producer(p, sb); }
        else if (warp < 11) store_warp(p, sb, warp - 9, lane);
        else scheduler(p, sb, lane);
        __syncwarp();
        bar_sync(NB_W0, 128);
        if (warp == 8 && p.qmask == 0xff) {
            unsigned last = 0;
            if (lane == 0) { __threadfence(); last = atomicAdd(&g_flags[F_DONE], 1u) == gridDim.x - 1; }
            if (__shfl_sync(~0u, last, 0))
                for (int i = lane; i < F_TOTAL; i += 32) g_flags[i] = 0;
        }
    }
}

typedef CUresult (*EncodeFn)(CUtensorMap*, CUtensorMapDataType, cuuint32_t, void*, const cuuint64_t*, const cuuint64_t*,
                             const cuuint32_t*, const cuuint32_t*, CUtensorMapInterleave, CUtensorMapSwizzle,
                             CUtensorMapL2promotion, CUtensorMapFloatOOBfill);

static void make_map(EncodeFn enc, CUtensorMap* m, const void* ptr, uint64_t rows, uint64_t cols, uint32_t box_rows) {
    cuuint64_t dims[2] = {cols, rows};
    cuuint64_t strides[1] = {cols * 2};
    cuuint32_t box[2] = {64, box_rows};
    cuuint32_t es[2] = {1, 1};
    enc(m, CU_TENSOR_MAP_DATA_TYPE_BFLOAT16, 2, const_cast<void*>(ptr), dims, strides, box, es, CU_TENSOR_MAP_INTERLEAVE_NONE,
        CU_TENSOR_MAP_SWIZZLE_128B, CU_TENSOR_MAP_L2_PROMOTION_L2_256B, CU_TENSOR_MAP_FLOAT_OOB_FILL_NONE);
}
template <typename T> static void* sym_addr(T& sym) { void* p = nullptr; cudaGetSymbolAddress(&p, sym); return p; }

extern "C" void kernel_launch(void* const* d_in, const int* in_sizes, int n_in, void* d_out, int out_size) {
    static Params prm;
    static RecParams rp;
    static int n_sm = 132;
    static bool ready = false;
    static const void* key[14];
    bool same = ready;
    for (int i = 0; i < 13 && same; i++) same = key[i] == d_in[i];
    same = same && key[13] == d_out;
    if (!same) {
        void* fn = nullptr;
        cudaDriverEntryPointQueryResult qr;
        cudaGetDriverEntryPoint("cuTensorMapEncodeTiled", &fn, cudaEnableDefault, &qr);
        EncodeFn enc = (EncodeFn)fn;
        make_map(enc, &prm.tm_h, sym_addr(g_h), S_, D_, 64);
        make_map(enc, &prm.tm_kv, sym_addr(g_kv), S_, 2 * HD_, 64);
        make_map(enc, &rp.tm_kv32, sym_addr(g_kv), S_, 2 * HD_, 32);
        make_map(enc, &prm.tm_kvm, sym_addr(g_kvm), NSEG * 8, 2 * HD_, 32);
        make_map(enc, &prm.tm_o, sym_addr(g_o), S_, HD_, 64);
        make_map(enc, &prm.tm_op, sym_addr(g_op), OP_ROWS, D_, 64);
        make_map(enc, &prm.tm_h2, sym_addr(g_h2), S_, D_, 64);
        make_map(enc, &prm.tm_act, sym_addr(g_act), S_, DF_, 64);
        make_map(enc, &prm.tm_x1, sym_addr(g_x1), S_, D_, 64);
        make_map(enc, &prm.tm_out, d_out, S_, D_, 64);
        make_map(enc, &prm.tm_wq, d_in[2], D_, HD_, 64);
        make_map(enc, &prm.tm_wk, d_in[3], D_, HD_, 64);
        make_map(enc, &prm.tm_wv, d_in[4], D_, HD_, 64);
        make_map(enc, &prm.tm_wo, d_in[5], HD_, D_, 64);
        make_map(enc, &prm.tm_wg, d_in[8], D_, DF_, 64);
        make_map(enc, &prm.tm_wu, d_in[9], D_, DF_, 64);
        make_map(enc, &prm.tm_wd, d_in[10], DF_, D_, 64);
        prm.x = (const bf16*)d_in[0]; prm.c = (const bf16*)d_in[11]; prm.w_mod = (const bf16*)d_in[12];
        rp.mem0 = (const bf16*)d_in[1]; rp.x = prm.x; rp.c = prm.c; rp.w_mod = prm.w_mod;
        rp.wq = (const bf16*)d_in[2]; rp.wk = (const bf16*)d_in[3]; rp.wv = (const bf16*)d_in[4]; rp.wo = (const bf16*)d_in[5];
        cudaDeviceGetAttribute(&n_sm, cudaDevAttrMultiProcessorCount, 0);
        cudaFuncSetAttribute(k_work, cudaFuncAttributeMaxDynamicSharedMemorySize, SMEM_BYTES);
        cudaFuncSetAttribute(k_rec, cudaFuncAttributeMaxDynamicSharedMemorySize, R_SMEM);
        cudaFuncSetAttribute(k_rec, cudaFuncAttributeNonPortableClusterSizeAllowed, 1);
        {
            cudaLaunchConfig_t cfg = {};
            cfg.gridDim = dim3(128); cfg.blockDim = dim3(384); cfg.dynamicSmemBytes = R_SMEM;
            cudaLaunchAttribute at[1];
            at[0].id = cudaLaunchAttributeClusterDimension; at[0].val.clusterDim.x = 16; at[0].val.clusterDim.y = 1; at[0].val.clusterDim.z = 1;
            cfg.attrs = at; cfg.numAttrs = 1;
            int n = 0;
            cudaOccupancyMaxActiveClusters(&n, k_rec, &cfg);
            rp.ncl = n < 4 ? 4 : (n > 8 ? 8 : n);
        }
        for (int i = 0; i < 13; i++) key[i] = d_in[i];
        key[13] = d_out;
        ready = true;
    }
    cudaStream_t st = cudaStreamPerThread;
    auto launch_rec = [&]() {
        cudaLaunchConfig_t cfg = {};
        cfg.gridDim = dim3(16 * rp.ncl); cfg.blockDim = dim3(384); cfg.dynamicSmemBytes = R_SMEM; cfg.stream = st;
        cudaLaunchAttribute at[1];
        at[0].id = cudaLaunchAttributeClusterDimension; at[0].val.clusterDim.x = 16; at[0].val.clusterDim.y = 1; at[0].val.clusterDim.z = 1;
        cfg.attrs = at; cfg.numAttrs = 1;
        cudaLaunchKernelEx(&cfg, k_rec, rp);
    };
    auto launch_work = [&](int qmask, int pdl) {
        prm.qmask = qmask;
        cudaLaunchConfig_t cfg = {};
        cfg.gridDim = dim3(n_sm); cfg.blockDim = dim3(384); cfg.dynamicSmemBytes = SMEM_BYTES; cfg.stream = st;
        cudaLaunchAttribute at[1];
        at[0].id = cudaLaunchAttributeProgrammaticStreamSerialization; at[0].val.programmaticStreamSerializationAllowed = 1;
        cfg.attrs = at; cfg.numAttrs = pdl;
        cudaLaunchKernelEx(&cfg, k_work, prm);
    };
    launch_rec();
    launch_work(0xff, 1);
}
```

```cpp
#include <cuda_runtime.h>
#include <cuda_bf16.h>
#include <cuda.h>
#include <stdint.h>

typedef __nv_bfloat16 bf16;
#define IDLE_NS 150
#define FLAG_NS 20

constexpr int S_ = 2048, D_ = 512, DH_ = 128, HD_ = 4096, NSEG = 64, DF_ = 1792;
constexpr int NRB = 16;
constexpr int OSPLIT = 4;

__device__ __align__(1024) bf16 g_h[S_ * D_];
__device__ __align__(1024) bf16 g_kv[S_ * 2 * HD_];
__device__ __align__(1024) bf16 g_kvm[NSEG * 8 * 2 * HD_];
__device__ __align__(1024) bf16 g_o[S_ * HD_];
#define FINE_RB_ 12
constexpr int FINE_RB = FINE_RB_;
#define OSPLIT2_ 8
constexpr int OSPLIT2 = OSPLIT2_;
constexpr int OSPLIT3 = 16;
constexpr int OP_ROWS = OSPLIT * S_ + OSPLIT2 * (NRB - FINE_RB) * 128 + OSPLIT3 * 128;
__device__ __align__(1024) bf16 g_op[OP_ROWS * D_];
__device__ __align__(1024) bf16 g_x1[S_ * D_];
__device__ __align__(1024) bf16 g_h2[S_ * D_];
__device__ __align__(1024) bf16 g_act[S_ * DF_];
__device__ __align__(1024) bf16 g_mod[6 * D_];
__device__ uint32_t g_Fraw[131072 + 65536 + 2048];
#define g_F ((uint32_t*)(((uint64_t)g_Fraw + 0x7FFFFull) & ~0x7FFFFull))
constexpr int F_H = 0, F_MEM = 32, F_O = 64, F_OP = 96, F_H2 = 128, F_ACT = 160, F_MOD = 192, F_KV = 224, F_CLAIM = 256  ,
              F_SIDE = 512  , F_DONE = 576, F_TOTAL = 608;
__device__ __align__(128) unsigned int g_flags[F_TOTAL];
#define TR(j, i) do {} while (0)

__device__ __forceinline__ uint32_t smem_u32(const void* p) { return (uint32_t)__cvta_generic_to_shared(p); }
__device__ __forceinline__ uint32_t clk32() { uint32_t c; asm volatile("mov.u32 %0, %%clock;" : "=r"(c)); return c; }
__device__ __forceinline__ uint32_t mapa_u32(uint32_t addr, uint32_t rank) {
    uint32_t r; asm volatile("mapa.shared::cluster.u32 %0, %1, %2;" : "=r"(r) : "r"(addr), "r"(rank)); return r;
}
__device__ __forceinline__ void mbar_init(uint32_t bar, uint32_t cnt) {
    asm volatile("mbarrier.init.shared::cta.b64 [%0], %1;" :: "r"(bar), "r"(cnt) : "memory");
}
__device__ __forceinline__ void mbar_expect_tx(uint32_t bar, uint32_t bytes) {
    asm volatile("mbarrier.arrive.expect_tx.shared::cta.b64 _, [%0], %1;" :: "r"(bar), "r"(bytes) : "memory");
}
__device__ __forceinline__ void mbar_arrive(uint32_t bar) {
    asm volatile("mbarrier.arrive.shared::cta.b64 _, [%0];" :: "r"(bar) : "memory");
}
__device__ __forceinline__ bool mbar_try_wait(uint32_t bar, uint32_t parity) {
    uint32_t ok;
    asm volatile("{\n.reg .pred p;\nmbarrier.try_wait.parity.shared::cta.b64 p, [%1], %2;\nselp.u32 %0, 1, 0, p;\n}"
                 : "=r"(ok) : "r"(bar), "r"(parity) : "memory");
    return ok;
}
constexpr int SPIN_LIMIT = 1 << 18;
#define TIMEOUT(code, info) do {} while (0)
__device__ __forceinline__ void mbar_wait(uint32_t bar, uint32_t parity) {
    int g = 0;
#pragma unroll 1
    while (!mbar_try_wait(bar, parity)) { if (++g >= SPIN_LIMIT) { TIMEOUT(0, bar & 255); break; } }
}
__device__ __forceinline__ void mbar_wait_sleep(uint32_t bar, uint32_t parity) {
    int g = 0;
    uint32_t ok;
#pragma unroll 1
    do {
        asm volatile("{\n.reg .pred p;\nmbarrier.try_wait.parity.shared::cta.b64 p, [%1], %2, %3;\nselp.u32 %0, 1, 0, p;\n}"
                     : "=r"(ok) : "r"(bar), "r"(parity), "r"(4000u) : "memory");
    } while (!ok && ++g < SPIN_LIMIT);
}
__device__ __forceinline__ void bar_sync(int id, int n) { asm volatile("bar.sync %0, %1;" :: "r"(id), "r"(n) : "memory"); }
__device__ __forceinline__ void bar_arrive(int id, int n) { asm volatile("bar.arrive %0, %1;" :: "r"(id), "r"(n) : "memory"); }
__device__ __forceinline__ void st_async_v4(uint32_t addr, uint4 v, uint32_t bar) {
    asm volatile("st.async.weak.shared::cluster.mbarrier::complete_tx::bytes.v4.b32 [%0], {%1,%2,%3,%4}, [%5];"
                 :: "r"(addr), "r"(v.x), "r"(v.y), "r"(v.z), "r"(v.w), "r"(bar) : "memory");
}
__device__ __forceinline__ void stg_relaxed32(uint32_t* p, uint32_t v) {
    asm volatile("st.relaxed.gpu.global.b32 [%0], %1;" :: "l"(p), "r"(v) : "memory");
}
__device__ __forceinline__ uint32_t ldg_relaxed32(const uint32_t* p) {
    uint32_t v; asm volatile("ld.relaxed.gpu.global.b32 %0, [%1];" : "=r"(v) : "l"(p) : "memory"); return v;
}
__device__ __forceinline__ unsigned int ld_acquire(const unsigned int* p) {
    unsigned int v; asm volatile("ld.acquire.gpu.global.u32 %0, [%1];" : "=r"(v) : "l"(p) : "memory"); return v;
}
__device__ __forceinline__ void red_release(unsigned int* p, unsigned int v) {
    asm volatile("red.release.gpu.global.add.u32 [%0], %1;" :: "l"(p), "r"(v) : "memory");
}
__device__ __forceinline__ void wait_flag(int idx, unsigned int target) {
    const unsigned int* p = &g_flags[idx];
    int g = 0;
#pragma unroll 1
    while (ld_acquire(p) < target) { __nanosleep(FLAG_NS); if (++g >= 64 * SPIN_LIMIT) { TIMEOUT(2, idx); break; } }
}
__device__ __forceinline__ void cp_async16(uint32_t dst, const void* src) {
    asm volatile("cp.async.cg.shared.global [%0], [%1], 16;" :: "r"(dst), "l"(src) : "memory");
}
__device__ __forceinline__ void cp_async_commit() { asm volatile("cp.async.commit_group;" ::: "memory"); }
template <int N> __device__ __forceinline__ void cp_async_wait() { asm volatile("cp.async.wait_group %0;" :: "n"(N) : "memory"); }
__device__ __forceinline__ void ldsm4(uint32_t& r0, uint32_t& r1, uint32_t& r2, uint32_t& r3, uint32_t addr) {
    asm volatile("ldmatrix.sync.aligned.m8n8.x4.shared.b16 {%0,%1,%2,%3}, [%4];" : "=r"(r0), "=r"(r1), "=r"(r2), "=r"(r3) : "r"(addr) : "memory");
}
__device__ __forceinline__ void ldsm4t(uint32_t& r0, uint32_t& r1, uint32_t& r2, uint32_t& r3, uint32_t addr) {
    asm volatile("ldmatrix.sync.aligned.m8n8.x4.trans.shared.b16 {%0,%1,%2,%3}, [%4];" : "=r"(r0), "=r"(r1), "=r"(r2), "=r"(r3) : "r"(addr) : "memory");
}
__device__ __forceinline__ void ldsm2t(uint32_t& r0, uint32_t& r1, uint32_t addr) {
    asm volatile("ldmatrix.sync.aligned.m8n8.x2.trans.shared.b16 {%0,%1}, [%2];" : "=r"(r0), "=r"(r1) : "r"(addr) : "memory");
}
__device__ __forceinline__ void stsm4(uint32_t addr, uint32_t r0, uint32_t r1, uint32_t r2, uint32_t r3) {
    asm volatile("stmatrix.sync.aligned.m8n8.x4.shared.b16 [%0], {%1,%2,%3,%4};" :: "r"(addr), "r"(r0), "r"(r1), "r"(r2), "r"(r3) : "memory");
}
__device__ __forceinline__ void stsm4t(uint32_t addr, uint32_t r0, uint32_t r1, uint32_t r2, uint32_t r3) {
    asm volatile("stmatrix.sync.aligned.m8n8.x4.trans.shared.b16 [%0], {%1,%2,%3,%4};" :: "r"(addr), "r"(r0), "r"(r1), "r"(r2), "r"(r3) : "memory");
}
__device__ __forceinline__ void mma16816(float* d, uint32_t a0, uint32_t a1, uint32_t a2, uint32_t a3, uint32_t b0, uint32_t b1) {
    asm volatile("mma.sync.aligned.m16n8k16.row.col.f32.bf16.bf16.f32 {%0,%1,%2,%3}, {%4,%5,%6,%7}, {%8,%9}, {%0,%1,%2,%3};"
                 : "+f"(d[0]), "+f"(d[1]), "+f"(d[2]), "+f"(d[3]) : "r"(a0), "r"(a1), "r"(a2), "r"(a3), "r"(b0), "r"(b1));
}
__device__ __forceinline__ void mma1688(float* d, uint32_t a0, uint32_t a1, uint32_t b0) {
    asm volatile("mma.sync.aligned.m16n8k8.row.col.f32.bf16.bf16.f32 {%0,%1,%2,%3}, {%4,%5}, {%6}, {%0,%1,%2,%3};"
                 : "+f"(d[0]), "+f"(d[1]), "+f"(d[2]), "+f"(d[3]) : "r"(a0), "r"(a1), "r"(b0));
}
__device__ __forceinline__ void mma16816h(float* d, uint32_t a0, uint32_t a2, uint32_t b0, uint32_t b1) {
    asm volatile("{\n.reg .b32 ju, jv;\nmma.sync.aligned.m16n8k16.row.col.f32.bf16.bf16.f32 {%0,%1,%2,%3}, {%4,ju,%5,jv}, {%6,%7}, {%0,%1,%2,%3};\n}"
                 : "+f"(d[0]), "+f"(d[1]), "+f"(d[2]), "+f"(d[3]) : "r"(a0), "r"(a2), "r"(b0), "r"(b1));
}
__device__ __forceinline__ void mma1688h(float* d, uint32_t a0, uint32_t b0) {
    asm volatile("{\n.reg .b32 ju;\nmma.sync.aligned.m16n8k8.row.col.f32.bf16.bf16.f32 {%0,%1,%2,%3}, {%4,ju}, {%5}, {%0,%1,%2,%3};\n}"
                 : "+f"(d[0]), "+f"(d[1]), "+f"(d[2]), "+f"(d[3]) : "r"(a0), "r"(b0));
}
__device__ __forceinline__ uint32_t movm(uint32_t a) {
    uint32_t d; asm volatile("movmatrix.sync.aligned.m8n8.trans.b16 %0, %1;" : "=r"(d) : "r"(a)); return d;
}
__device__ __forceinline__ uint32_t pack2(float lo, float hi) {
    uint32_t r; asm("cvt.rn.bf16x2.f32 %0, %1, %2;" : "=r"(r) : "f"(hi), "f"(lo)); return r;
}
__device__ __forceinline__ float bflo(uint32_t w) { return __uint_as_float(w << 16); }
__device__ __forceinline__ float bfhi(uint32_t w) { return __uint_as_float(w & 0xffff0000u); }
__device__ __forceinline__ float rbf(float x) { return __bfloat162float(__float2bfloat16_rn(x)); }
__device__ __forceinline__ float ex2(float x) { float y; asm("ex2.approx.ftz.f32 %0, %1;" : "=f"(y) : "f"(x)); return y; }
__device__ __forceinline__ void sts128(uint32_t addr, uint4 v) {
    asm volatile("st.shared.v4.b32 [%0], {%1,%2,%3,%4};" :: "r"(addr), "r"(v.x), "r"(v.y), "r"(v.z), "r"(v.w) : "memory");
}
__device__ __forceinline__ uint4 lds128(uint32_t addr) {
    uint4 v; asm volatile("ld.shared.v4.b32 {%0,%1,%2,%3}, [%4];" : "=r"(v.x), "=r"(v.y), "=r"(v.z), "=r"(v.w) : "r"(addr) : "memory"); return v;
}
__device__ __forceinline__ float2 lds64f(uint32_t addr) {
    float2 v; asm volatile("ld.shared.v2.f32 {%0,%1}, [%2];" : "=f"(v.x), "=f"(v.y) : "r"(addr) : "memory"); return v;
}
__device__ __forceinline__ float lds32f(uint32_t addr) {
    float v; asm volatile("ld.shared.f32 %0, [%1];" : "=f"(v) : "r"(addr) : "memory"); return v;
}
__device__ __forceinline__ uint32_t lds32(uint32_t addr) {
    uint32_t v; asm volatile("ld.shared.b32 %0, [%1];" : "=r"(v) : "r"(addr) : "memory"); return v;
}
__device__ __forceinline__ void sts32(uint32_t addr, uint32_t v) { asm volatile("st.shared.b32 [%0], %1;" :: "r"(addr), "r"(v) : "memory"); }
__device__ __forceinline__ void sts64f(uint32_t addr, float a, float b) { asm volatile("st.shared.v2.f32 [%0], {%1,%2};" :: "r"(addr), "f"(a), "f"(b) : "memory"); }

__device__ __forceinline__ void tma_load2d(uint32_t dst, const CUtensorMap* tm, int c0, int c1, uint32_t bar) {
    asm volatile("cp.async.bulk.tensor.2d.shared::cluster.global.mbarrier::complete_tx::bytes [%0], [%1, {%3, %4}], [%2];"
                 :: "r"(dst), "l"(tm), "r"(bar), "r"(c0), "r"(c1) : "memory");
}
__device__ __forceinline__ void tma_store2d(const CUtensorMap* tm, uint32_t src, int c0, int c1) {
    asm volatile("cp.async.bulk.tensor.2d.global.shared::cta.bulk_group [%0, {%2, %3}], [%1];"
                 :: "l"(tm), "r"(src), "r"(c0), "r"(c1) : "memory");
}
__device__ __forceinline__ void bulk_commit() { asm volatile("cp.async.bulk.commit_group;" ::: "memory"); }
__device__ __forceinline__ void bulk_wait0() { asm volatile("cp.async.bulk.wait_group 0;" ::: "memory"); }
__device__ __forceinline__ void fence_async_smem() { asm volatile("fence.proxy.async.shared::cta;" ::: "memory"); }

__device__ __forceinline__ void wg_fence() { asm volatile("wgmma.fence.sync.aligned;" ::: "memory"); }
__device__ __forceinline__ void wg_commit() { asm volatile("wgmma.commit_group.sync.aligned;" ::: "memory"); }
__device__ __forceinline__ void wg_wait0() { asm volatile("wgmma.wait_group.sync.aligned 0;" ::: "memory"); }
__device__ __forceinline__ uint64_t mkdesc(uint32_t saddr, uint32_t lbo, uint32_t sbo) {
    return (uint64_t)((saddr & 0x3FFFF) >> 4) | ((uint64_t)(lbo >> 4) << 16) | ((uint64_t)(sbo >> 4) << 32) | (1ull << 62);
}
#define ACC8(i) "+f"(d[i]), "+f"(d[i + 1]), "+f"(d[i + 2]), "+f"(d[i + 3]), "+f"(d[i + 4]), "+f"(d[i + 5]), "+f"(d[i + 6]), "+f"(d[i + 7])
__device__ __forceinline__ void wgmma_n256(float* d, uint64_t da, uint64_t db, int scale_d) {
    asm volatile(
        "{\n.reg .pred p;\nsetp.ne.b32 p, %130, 0;\n"
        "wgmma.mma_async.sync.aligned.m64n256k16.f32.bf16.bf16 "
        "{%0,%1,%2,%3,%4,%5,%6,%7,%8,%9,%10,%11,%12,%13,%14,%15,%16,%17,%18,%19,%20,%21,%22,%23,%24,%25,%26,%27,%28,%29,%30,%31,"
        "%32,%33,%34,%35,%36,%37,%38,%39,%40,%41,%42,%43,%44,%45,%46,%47,%48,%49,%50,%51,%52,%53,%54,%55,%56,%57,%58,%59,%60,%61,%62,%63,"
        "%64,%65,%66,%67,%68,%69,%70,%71,%72,%73,%74,%75,%76,%77,%78,%79,%80,%81,%82,%83,%84,%85,%86,%87,%88,%89,%90,%91,%92,%93,%94,%95,"
        "%96,%97,%98,%99,%100,%101,%102,%103,%104,%105,%106,%107,%108,%109,%110,%111,%112,%113,%114,%115,%116,%117,%118,%119,%120,%121,%122,%123,%124,%125,%126,%127}, "
        "%128, %129, p, 1, 1, 0, 1;\n}"
        : ACC8(0), ACC8(8), ACC8(16), ACC8(24), ACC8(32), ACC8(40), ACC8(48), ACC8(56),
          ACC8(64), ACC8(72), ACC8(80), ACC8(88), ACC8(96), ACC8(104), ACC8(112), ACC8(120)
        : "l"(da), "l"(db), "r"(scale_d));
}
__device__ __forceinline__ void wgmma_n128(float* d, uint64_t da, uint64_t db, int scale_d) {
    asm volatile(
        "{\n.reg .pred p;\nsetp.ne.b32 p, %66, 0;\n"
        "wgmma.mma_async.sync.aligned.m64n128k16.f32.bf16.bf16 "
        "{%0,%1,%2,%3,%4,%5,%6,%7,%8,%9,%10,%11,%12,%13,%14,%15,%16,%17,%18,%19,%20,%21,%22,%23,%24,%25,%26,%27,%28,%29,%30,%31,"
        "%32,%33,%34,%35,%36,%37,%38,%39,%40,%41,%42,%43,%44,%45,%46,%47,%48,%49,%50,%51,%52,%53,%54,%55,%56,%57,%58,%59,%60,%61,%62,%63}, "
        "%64, %65, p, 1, 1, 0, 1;\n}"
        : ACC8(0), ACC8(8), ACC8(16), ACC8(24), ACC8(32), ACC8(40), ACC8(48), ACC8(56)
        : "l"(da), "l"(db), "r"(scale_d));
}

__device__ __forceinline__ void wgmma_n64(float* d, uint64_t da, uint64_t db) {
    asm volatile(
        "wgmma.mma_async.sync.aligned.m64n64k16.f32.bf16.bf16 "
        "{%0,%1,%2,%3,%4,%5,%6,%7,%8,%9,%10,%11,%12,%13,%14,%15,%16,%17,%18,%19,%20,%21,%22,%23,%24,%25,%26,%27,%28,%29,%30,%31}, "
        "%32, %33, 1, 1, 1, 0, 1;"
        : ACC8(0), ACC8(8), ACC8(16), ACC8(24)
        : "l"(da), "l"(db));
}
__device__ __forceinline__ uint32_t hadd2(uint32_t a, uint32_t b) { uint32_t r; asm("add.rn.bf16x2 %0, %1, %2;" : "=r"(r) : "r"(a), "r"(b)); return r; }
__device__ __forceinline__ uint32_t hsub2(uint32_t a, uint32_t b) { uint32_t r; asm("sub.rn.bf16x2 %0, %1, %2;" : "=r"(r) : "r"(a), "r"(b)); return r; }
__device__ __forceinline__ uint32_t hmul2(uint32_t a, uint32_t b) { uint32_t r; asm("mul.rn.bf16x2 %0, %1, %2;" : "=r"(r) : "r"(a), "r"(b)); return r; }
__device__ __forceinline__ void load_mod8(const bf16* m, int lane, uint32_t* v) {
    const uint4 a = __ldcg((const uint4*)m + lane), b = __ldcg((const uint4*)m + 32 + lane);
    v[0] = a.x; v[1] = a.y; v[2] = a.z; v[3] = a.w; v[4] = b.x; v[5] = b.y; v[6] = b.z; v[7] = b.w;
}
__device__ __forceinline__ void ln_stats(const uint32_t* x, uint32_t& mu2, float& rden) {
    float s = 0.f;
#pragma unroll
    for (int i = 0; i < 8; i++) s += bflo(x[i]) + bfhi(x[i]);
#pragma unroll
    for (int o = 16; o > 0; o >>= 1) s += __shfl_xor_sync(~0u, s, o);
    const float mean = s * (1.f / D_);
    float q = 0.f;
#pragma unroll
    for (int i = 0; i < 8; i++) { const float d0 = bflo(x[i]) - mean, d1 = bfhi(x[i]) - mean; q = fmaf(d0, d0, q); q = fmaf(d1, d1, q); }
#pragma unroll
    for (int o = 16; o > 0; o >>= 1) q += __shfl_xor_sync(~0u, q, o);
    mu2 = pack2(mean, mean);
    rden = __frcp_rn(rbf(__fsqrt_rn(rbf(rbf(q * (1.f / D_)) + 1e-5f))));
}
__device__ __forceinline__ void ln_apply(const uint32_t* x, uint32_t mu2, float rden, const uint32_t* c1, const uint32_t* sm, uint32_t* r) {
#pragma unroll
    for (int i = 0; i < 8; i++) {
        const uint32_t d = hsub2(x[i], mu2);
        r[i] = hadd2(hmul2(pack2(bflo(d) * rden, bfhi(d) * rden), c1[i]), sm[i]);
    }
}

struct __align__(64) Params {
    CUtensorMap tm_h, tm_kv, tm_kvm, tm_o, tm_op, tm_h2, tm_act, tm_x1, tm_out;
    CUtensorMap tm_wq, tm_wk, tm_wv, tm_wo, tm_wg, tm_wu, tm_wd;
    const bf16 *x, *c, *w_mod;
    int qmask;
};

constexpr uint32_t R_WV = 0, R_MEM = 65536  ,
                   R_KX = 69632  , R_VX = R_KX + 8192,
                   R_VMS = R_KX + 32768  , R_OS = R_VMS + 2048  , R_SX = R_OS + 2048  , R_BAR = R_SX + 1536,
                   R_RS = R_BAR + 512  , R_VB = R_RS + 4096  , R_VP = R_VB + 2048  ,
                   R_STG = R_VP + 4096  ,
                   R_TQ = R_STG  , R_TV = R_STG + 53248  , R_QF = R_STG + 77824  ,
                   R_SMEM = R_STG + 98304;
static_assert((R_STG & 1023) == 0 && (R_RS & 511) == 0 && R_QF + 16384 <= R_SMEM, "smem");
constexpr uint32_t RB_Q = R_BAR, RB_V = R_BAR + 8, RB_E = R_BAR + 16, RB_A = R_BAR + 24, RB_ROLE = R_BAR + 32, RB_KV = R_BAR + 40  ;
constexpr int W_NST = 4;
constexpr uint32_t W_STAGE = 49152, W_STG = W_NST * W_STAGE  , W_END = W_STG + 32768;
constexpr uint32_t SM_BAR = W_END;
constexpr uint32_t SMEM_BYTES = W_END + 1024 + 2048;
constexpr uint32_t B_FULL = 0, B_EMPTY = 32, B_STGFREE = 64, B_REQ = 80, B_RSP = 88, B_NEXT = 96, B_RING = 128;
#define PICK_AHEAD 3

constexpr int NB_S = 11, NB_Y = 1, NB_M = 5, NB_K = 5, NB_B = 2, NB_C = 3, NB_D = 4, NB_W0 = 6  , NB_ST = 9  ;

__device__ __forceinline__ int pos_of_d(int d) {
    const int rem = d & 31;
    return (d & ~31) + ((rem & 7) >> 1) * 8 + (rem & 1) * 4 + (rem >> 3);
}

#define PROF(i) do {} while (0)
#define VK0_ 4
constexpr int VK0 = VK0_;
constexpr int NOFF = 8;
#define OFFKS(i) ((i) >> 1)
#define POLL_GAP 140

struct __align__(64) RecParams { CUtensorMap tm_kv32; const bf16 *mem0, *wq, *wk, *wv, *wo, *x, *c, *w_mod; int ncl, only_pre; };

__device__ __forceinline__ void rec_qk(const RecParams& p, const uint32_t sb, const int cta, const int warp, int lane, const int sel) {
    const int crank = cta & 15, cl = cta >> 4, rank = cta & 1;
    const int wg = warp >> 2, aa = warp & 3;
    uint32_t wa[2][16][4];
    {
        const uint32_t stg = sb + R_STG + wg * 32768;
        const int t128 = aa * 32 + lane;
        const int row = (lane >> 4) * 8 + (lane & 7);
        const int ch = t128 & 7;
        const size_t goff = (size_t)rank * 256 * HD_ + (cta >> 1) * DH_ + ch * 8;
        const bf16* W = (wg == 0 ? p.wq : p.wk) + goff;
#pragma unroll 4
        for (int dd = 0; dd < 16; dd++) {
            const int d = dd * 16 + (t128 >> 3), pp = pos_of_d(d);
            cp_async16(sb + R_WV + wg * 32768 + pp * 128 + ((ch ^ (pp & 7)) << 4), p.wv + goff + wg * 64 + (size_t)d * HD_);
        }
        cp_async_commit();
#pragma unroll 4
        for (int dd = 0; dd < 16; dd++) {
            const int d = dd * 16 + (t128 >> 3), pp = pos_of_d(d);
            cp_async16(stg + pp * 128 + ((ch ^ (pp & 7)) << 4), W + (size_t)d * HD_);
        }
        cp_async_commit();
        {
            const int tok = warp, d0 = lane * 8;
            const uint4 m0 = __ldg((const uint4*)(p.mem0 + tok * D_ + rank * 256 + d0));
            const uint32_t mw[4] = {m0.x, m0.y, m0.z, m0.w};
#pragma unroll
            for (int e = 0; e < 8; e++) {
                const int pp = pos_of_d(d0 + e);
                const unsigned short v = (unsigned short)(mw[e >> 1] >> ((e & 1) * 16));
                asm volatile("st.shared.u16 [%0], %1;" :: "r"(sb + R_MEM + (pp >> 3) * 128 + tok * 16 + (pp & 7) * 2), "h"(v) : "memory");
            }
        }
        cp_async_wait<1>();
        bar_sync(NB_W0 + wg, 128);
        const uint32_t fv = row * 128 + (((2 * aa + ((lane >> 3) & 1)) ^ (row & 7)) << 4);
#pragma unroll
        for (int ks = 0; ks < 16; ks++) ldsm4t(wa[0][ks][0], wa[0][ks][1], wa[0][ks][2], wa[0][ks][3], sb + R_WV + wg * 32768 + fv + ks * 2048);
        bar_sync(NB_W0 + wg, 128);
#pragma unroll
        for (int ks = 0; ks < 16; ks++)
            sts128(sb + R_WV + (warp * 16 + ks) * 512 + lane * 16, make_uint4(wa[0][ks][0], wa[0][ks][1], wa[0][ks][2], wa[0][ks][3]));
        const uint32_t fo = stg + row * 128 + (((4 * (aa & 1) + ((lane >> 3) & 1)) ^ (row & 7)) << 4);
#pragma unroll 1
        for (int m = 0; m < 2; m++) {
            cp_async_wait<0>();
            bar_sync(NB_W0 + wg, 128);
            if ((aa >> 1) == m) {
#pragma unroll
                for (int ks = 0; ks < 16; ks++) {
                    ldsm4t(wa[0][ks][0], wa[0][ks][1], wa[0][ks][2], wa[0][ks][3], fo + ks * 2048);
                    ldsm4t(wa[1][ks][0], wa[1][ks][1], wa[1][ks][2], wa[1][ks][3], (fo ^ 32) + ks * 2048);
                }
            }
            bar_sync(NB_W0 + wg, 128);
            if (m == 0) {
#pragma unroll 4
                for (int dd = 0; dd < 16; dd++) {
                    const int d = dd * 16 + (t128 >> 3), pp = pos_of_d(d);
                    cp_async16(stg + pp * 128 + ((ch ^ (pp & 7)) << 4), W + 64 + (size_t)d * HD_);
                }
                cp_async_commit();
            }
        }
    }
    bar_sync(NB_D, 384);
    const uint32_t tab = sb + R_TQ + wg * 26624 + (aa * 32 + lane) * 16;
    {
        const uint32_t l7 = lane & 7, l8 = lane >> 3, g = lane >> 2, t = lane & 3;
        const uint32_t bq = warp >> 1, tp = warp & 1;
        uint4 v;
        v.x = sb + R_QF + (rank * 8 + warp) * 512 + lane * 16;
        v.y = sb + R_QF + (warp == 5 ? 1024 : 0) + lane * 16;
        v.z = sb + R_KX + ((warp - 1) * 8 + l7) * 128 + ((l8 ^ l7) << 4);
        v.w = sb + R_SX + warp * 256 + lane * 8;
        sts128(tab, v);
        sts128(tab + 2048, make_uint4(sb + lane * 16 + R_MEM, sb + lane * 16 + R_WV + warp * 8192, sb + lane * 16 + R_VP + warp * 512, v.x));
        const uint32_t L = bq * 8 + 2 * tp + (l8 & 1) + 4 * (l8 >> 1);
        const uint32_t d0 = (((crank + ((t >> 1) | (g & 6))) & 7) << 1) | (crank >> 3);
        v.x = sb + R_RS + l7 * 512 + ((L ^ l7) << 4);
        v.y = mapa_u32(sb + R_MEM + ((crank & 7) * 4 + bq) * 128 + (4 * tp + 2 * (t & 1) + (g & 1)) * 16, d0);
        v.z = mapa_u32(sb + RB_A, d0);
        v.w = lane;
        sts128(tab + 4096, v);
        const uint64_t wr = (uint64_t)(g_F + ((crank * 2 + ((crank ^ (crank >> 3) ^ sel) & 1)) * 1024 + warp * 128 + cl * 32 + lane));
        sts128(tab + 6144, make_uint4((uint32_t)wr, (uint32_t)(wr >> 32), (uint32_t)((((cl + 1) & 3) - cl) * 128), (uint32_t)((((cl + 2) & 3) - cl) * 128)));
        sts32(tab + 8192, (uint32_t)((((cl + 3) & 3) - cl) * 128));
#pragma unroll
        for (int i = 0; i < NOFF; i++)
            sts128(tab + 10240 + i * 2048, make_uint4(wa[i & 1][OFFKS(i)][0], wa[i & 1][OFFKS(i)][1], wa[i & 1][OFFKS(i)][2], wa[i & 1][OFFKS(i)][3]));
    }
    bar_sync(NB_D, 384);
    uint4 tb = lds128(tab + 2048);
#pragma unroll 1
    for (int s = 0; s < NSEG; s++) {
        if (s > 0) mbar_wait(sb + RB_A, (s - 1) & 1);
        if (warp == 0) PROF(0);
        uint4 ta;
        const uint32_t par = (s & 1) * 8192;
        {
            float acc[5][4];
#pragma unroll
            for (int c = 0; c < 5; c++) { acc[c][0] = acc[c][1] = acc[c][2] = acc[c][3] = 0.f; }
            uint32_t b[8][4];
            uint4 av[16];
            static_assert(VK0 == 4, "order below assumes the V/O warps cover slices 0,1");
#define QK4(k2) do { \
                mma16816(acc[0], wa[0][2 * (k2)][0], wa[0][2 * (k2)][1], wa[0][2 * (k2)][2], wa[0][2 * (k2)][3], b[k2][0], b[k2][1]); \
                mma16816(acc[1], wa[1][2 * (k2)][0], wa[1][2 * (k2)][1], wa[1][2 * (k2)][2], wa[1][2 * (k2)][3], b[k2][0], b[k2][1]); \
                mma16816(acc[3], wa[0][2 * (k2) + 1][0], wa[0][2 * (k2) + 1][1], wa[0][2 * (k2) + 1][2], wa[0][2 * (k2) + 1][3], b[k2][2], b[k2][3]); \
                mma16816(acc[4], wa[1][2 * (k2) + 1][0], wa[1][2 * (k2) + 1][1], wa[1][2 * (k2) + 1][2], wa[1][2 * (k2) + 1][3], b[k2][2], b[k2][3]); } while (0)
#define V2(k2) do { \
                mma16816(acc[2], av[2 * (k2)].x, av[2 * (k2)].y, av[2 * (k2)].z, av[2 * (k2)].w, b[k2][0], b[k2][1]); \
                mma16816(acv, av[2 * (k2) + 1].x, av[2 * (k2) + 1].y, av[2 * (k2) + 1].z, av[2 * (k2) + 1].w, b[k2][2], b[k2][3]); } while (0)
#define LB(k2) ldsm4(b[k2][0], b[k2][1], b[k2][2], b[k2][3], tb.x + (k2) * 512)
#define LV(k2) do { av[2 * (k2)] = lds128(tb.y + 2 * (k2) * 512); av[2 * (k2) + 1] = lds128(tb.y + (2 * (k2) + 1) * 512); } while (0)
            float acv[4] = {0.f, 0.f, 0.f, 0.f};
            LB(0); LB(1); LB(2); LB(3);
            QK4(0); LB(4); QK4(1); LB(5); LV(2); LV(3); QK4(2); LB(6); QK4(3); LB(7);
            V2(2); V2(3); LV(4); LV(5);
            QK4(4); QK4(5); QK4(6); QK4(7);
            const uint4 f = make_uint4(movm(pack2(acc[0][0] + acc[3][0], acc[0][1] + acc[3][1])), movm(pack2(acc[0][2] + acc[3][2], acc[0][3] + acc[3][3])),
                                       movm(pack2(acc[1][0] + acc[4][0], acc[1][1] + acc[4][1])), movm(pack2(acc[1][2] + acc[4][2], acc[1][3] + acc[4][3])));
            st_async_v4((tb.w + par) ^ (1u << 24), f, (sb + RB_Q) ^ (1u << 24));
            sts128(tb.w + par, f);
            __syncwarp();
            if ((tb.w & 511) == 0) mbar_arrive(sb + RB_Q);
            if (warp == 0) PROF(1);
            if (tb.x == 0) break;
            LV(6); LV(7);
            ta = lds128(tab);
            V2(4); V2(5); V2(6); V2(7);
            sts128(tb.z, make_uint4(__float_as_uint(acc[2][0] + acv[0]), __float_as_uint(acc[2][1] + acv[1]), __float_as_uint(acc[2][2] + acv[2]), __float_as_uint(acc[2][3] + acv[3])));
            bar_arrive(NB_Y, 384);
        }
        if (warp == 0) PROF(14);
        if (warp < 6 && s != NSEG - 1) {
            float sa[4] = {0.f, 0.f, 0.f, 0.f}, sc[4] = {0.f, 0.f, 0.f, 0.f};
            const uint32_t qa = ta.y + par;
            if (warp == 0 || warp == 5) {
                mbar_wait(sb + RB_Q, s & 1);
                const uint4 q0 = lds128(qa), q1 = lds128(qa + 4096), k0 = lds128(qa + 2048), k1 = lds128(qa + 6144);
                const uint4 q2 = lds128(qa + 512), q3 = lds128(qa + 4608), k2 = lds128(qa + 2560), k3 = lds128(qa + 6656);
                mma16816h(sa, hadd2(q0.x, q1.x), hadd2(q0.y, q1.y), hadd2(k0.x, k1.x), hadd2(k0.y, k1.y));
                mma16816h(sc, hadd2(q0.z, q1.z), hadd2(q0.w, q1.w), hadd2(k0.z, k1.z), hadd2(k0.w, k1.w));
                mma16816h(sa, hadd2(q2.x, q3.x), hadd2(q2.y, q3.y), hadd2(k2.x, k3.x), hadd2(k2.y, k3.y));
                mma16816h(sc, hadd2(q2.z, q3.z), hadd2(q2.w, q3.w), hadd2(k2.z, k3.z), hadd2(k2.w, k3.w));
            } else {
                uint32_t k[16];
                const uint32_t kb = ta.z + 2 * par;
                mbar_wait(sb + RB_KV + (s & 1) * 8, (s >> 1) & 1);
                ldsm4(k[0], k[1], k[2], k[3], kb);
                ldsm4(k[4], k[5], k[6], k[7], kb ^ 64);
                ldsm4(k[8], k[9], k[10], k[11], kb + 4096);
                ldsm4(k[12], k[13], k[14], k[15], (kb ^ 64) + 4096);
                mbar_wait(sb + RB_Q, s & 1);
                uint4 q0[4], q1[4];
#pragma unroll
                for (int i = 0; i < 4; i++) { q0[i] = lds128(qa + i * 512); q1[i] = lds128(qa + 4096 + i * 512); }
                float sd[4] = {0.f, 0.f, 0.f, 0.f}, se[4] = {0.f, 0.f, 0.f, 0.f};
                mma16816h(sa, hadd2(q0[0].x, q1[0].x), hadd2(q0[0].y, q1[0].y), k[0], k[1]);
                mma16816h(sc, hadd2(q0[0].z, q1[0].z), hadd2(q0[0].w, q1[0].w), k[2], k[3]);
                mma16816h(sd, hadd2(q0[1].x, q1[1].x), hadd2(q0[1].y, q1[1].y), k[4], k[5]);
                mma16816h(se, hadd2(q0[1].z, q1[1].z), hadd2(q0[1].w, q1[1].w), k[6], k[7]);
                mma16816h(sa, hadd2(q0[2].x, q1[2].x), hadd2(q0[2].y, q1[2].y), k[8], k[9]);
                mma16816h(sc, hadd2(q0[2].z, q1[2].z), hadd2(q0[2].w, q1[2].w), k[10], k[11]);
                mma16816h(sd, hadd2(q0[3].x, q1[3].x), hadd2(q0[3].y, q1[3].y), k[12], k[13]);
                mma16816h(se, hadd2(q0[3].z, q1[3].z), hadd2(q0[3].w, q1[3].w), k[14], k[15]);
                sa[0] += sd[0]; sa[1] += sd[1]; sc[0] += se[0]; sc[1] += se[1];
            }
            const float scl = 0.08838834764831845f * 1.4426950408889634f;
            sts64f(ta.w, (sa[0] + sc[0]) * scl, (sa[1] + sc[1]) * scl);
            bar_arrive(NB_S, 320);
            if (warp == 0) PROF(2);
        } else if (warp == 7) {
            mbar_wait(sb + RB_Q, s & 1);
            if (lane == 0) {
                mbar_expect_tx(sb + RB_Q, 4096);
                if (s > 0) mbar_expect_tx(sb + RB_A, 4096);
            }
            __syncwarp();
        } else if (s > 0 && (s & 3) == 0 && warp == 6) {
            bar_sync(NB_K, 160);
            if (lane == 0) red_release(&g_flags[F_MEM + (s >> 2) - 1], 1);
            __syncwarp();
        }
        if (s == NSEG - 1) {
            const uint4 td = lds128(tab + 6144);
            stg_relaxed32((uint32_t*)(((uint64_t)td.y << 32) | (td.x ^ 0x21000)), 0u);
            break;
        }
        const uint4 tc = lds128(tab + 4096), td = lds128(tab + 6144);
        const uint32_t te = lds32(tab + 8192);
        uint32_t* wr = (uint32_t*)(((uint64_t)td.y << 32) | (td.x ^ ((s & 1) * 0x21000)));
        const uint32_t* r1p = (const uint32_t*)((const char*)wr + (int)td.z);
        const uint32_t* r2p = (const uint32_t*)((const char*)wr + (int)td.w);
        const uint32_t* r3p = (const uint32_t*)((const char*)wr + (int)te);
        const uint32_t tag = ((s >> 1) + 1) & 1;
        mbar_wait(sb + RB_E, s & 1);
        if (warp == 0) PROF(7);
        {
            uint32_t a0, a1, a2, a3;
            ldsm4t(a0, a1, a2, a3, tc.x);
            const uint32_t one = 0x3F803F80u;
            float d0_[4] = {0.f, 0.f, 0.f, 0.f}, d1_[4] = {0.f, 0.f, 0.f, 0.f};
            mma1688(d0_, a0, a1, one);
            mma1688(d1_, a2, a3, one);
            const bool t1 = tc.w & 1, t2 = tc.w & 2;
            const float x = t2 ? (t1 ? d1_[2] : d1_[0]) : (t1 ? d0_[2] : d0_[0]);
            const uint32_t own = (__float_as_uint(x) & ~1u) | tag;
            stg_relaxed32(wr, own);
            const uint32_t tq = clk32();
            if (warp == 0) PROF(8);
            while ((int)(clk32() - tq) < POLL_GAP) {}
            uint32_t f1 = ldg_relaxed32(r1p), f2 = ldg_relaxed32(r2p), f3 = ldg_relaxed32(r3p);
#pragma unroll
            for (int i = 0; i < NOFF; i++) {
                const uint4 f0 = lds128(tab + 10240 + i * 2048);
                wa[i & 1][OFFKS(i)][0] = f0.x; wa[i & 1][OFFKS(i)][1] = f0.y; wa[i & 1][OFFKS(i)][2] = f0.z; wa[i & 1][OFFKS(i)][3] = f0.w;
            }
            tb = lds128(tab + 2048);
            int gg = 0;
#pragma unroll 1
            while (!__all_sync(~0u, (((f1 ^ tag) | (f2 ^ tag) | (f3 ^ tag)) & 1) == 0)) {
                f1 = ldg_relaxed32(r1p); f2 = ldg_relaxed32(r2p); f3 = ldg_relaxed32(r3p);
                if (++gg > 16 * SPIN_LIMIT) { TIMEOUT(3, s); break; }
            }
            if (warp == 0) PROF(9);
            const float v = (__uint_as_float(own) + __uint_as_float(f2)) + (__uint_as_float(f1) + __uint_as_float(f3));
            const bool b8 = tc.w & 8, b16 = tc.w & 16;
            const float recv = __shfl_xor_sync(~0u, v, 8);
            const uint32_t word = b8 ? pack2(recv, v) : pack2(v, recv);
            const uint32_t oth = __shfl_xor_sync(~0u, word, 16);
            const uint32_t wl = b16 ? oth : word, wh = b16 ? word : oth;
            const uint32_t p0 = __shfl_xor_sync(~0u, wl, 2), p1 = __shfl_xor_sync(~0u, wh, 2);
            const uint4 item = t2 ? make_uint4(p0, p1, wl, wh) : make_uint4(wl, wh, p0, p1);
            st_async_v4(tc.y, item, tc.z);
            if (tc.w == 0 && warp == 7) mbar_expect_tx(sb + RB_E, 4096);
            if (warp == 0) PROF(10);
        }
    }
}

__device__ __forceinline__ void rec_load_kv(const RecParams& p, uint32_t sb, int head, int s) {
    const uint32_t bar = sb + RB_KV + (s & 1) * 8, d = sb + R_KX + (s & 1) * 16384;
    mbar_expect_tx(bar, 16384);
    tma_load2d(d, &p.tm_kv32, head * DH_, s * 32, bar);
    tma_load2d(d + 4096, &p.tm_kv32, head * DH_ + 64, s * 32, bar);
    tma_load2d(d + 8192, &p.tm_kv32, HD_ + head * DH_, s * 32, bar);
    tma_load2d(d + 12288, &p.tm_kv32, HD_ + head * DH_ + 64, s * 32, bar);
}
__device__ __forceinline__ void rec_store_kvm(uint32_t src, char* dst, int s, int w) {
    dst += (size_t)s * (8 * 2 * HD_ * 2);
    if (w < 2) {
        const uint4 a = lds128(src + (s & 1) * 8192), b = lds128(src + (s & 1) * 8192 + 4096);
        *(uint32_t*)dst = hadd2(a.x, b.x); *(uint32_t*)(dst + 16) = hadd2(a.y, b.y);
        *(uint32_t*)(dst + 32) = hadd2(a.z, b.z); *(uint32_t*)(dst + 48) = hadd2(a.w, b.w);
    } else {
        *(uint4*)dst = lds128(src + (s & 1) * 1024);
    }
}

__device__ __forceinline__ void rec_vo(const RecParams& p, const uint32_t sb, const int cta, const int warp, int lane) {
    const int w = warp - 8, crank = cta & 15, rank = cta & 1;
    uint32_t wo[4][8][4];
    const uint32_t tab = sb + R_TV + (w * 32 + lane) * 16;
    {
        const int t128 = w * 32 + lane;
        const bf16* Wo = p.wo + (size_t)(cta >> 1) * DH_ * D_ + rank * 256;
        const uint32_t stg = sb + R_STG + 2 * 32768;
#pragma unroll
        for (int half = 0; half < 2; half++) {
#pragma unroll 4
            for (int i = t128; i < 2048; i += 128) {
                const int e = i >> 5, ch = i & 31;
                cp_async16(stg + e * 512 + ((ch ^ (e & 7)) << 4), Wo + (size_t)(half * 64 + e) * D_ + ch * 8);
            }
            cp_async_commit();
            cp_async_wait<0>();
            bar_sync(NB_W0 + 2, 128);
#pragma unroll
            for (int j = 0; j < 4; j++)
#pragma unroll
                for (int kk = 0; kk < 4; kk++) {
                    const int e = kk * 16 + (lane >> 4) * 8 + (lane & 7);
                    const int ch = (w * 4 + j) * 2 + ((lane >> 3) & 1);
                    ldsm4t(wo[j][half * 4 + kk][0], wo[j][half * 4 + kk][1], wo[j][half * 4 + kk][2], wo[j][half * 4 + kk][3],
                           stg + e * 512 + ((ch ^ (e & 7)) << 4));
                }
            bar_sync(NB_W0 + 2, 128);
        }
        bar_sync(NB_D, 384);
        const uint32_t l7 = lane & 7, l8 = lane >> 3, g = lane >> 2;
        uint4 v;
        v.x = sb + R_VX + (w >> 1) * 4096 + ((l8 & 1) * 8 + l7) * 128 + (((4 * (w & 1) + (l8 >> 1)) ^ l7) << 4);
        v.y = sb + R_OS + (w >> 1) * 1024 + g * 128 + (((4 * (w & 1)) ^ g) << 4) + (lane & 3) * 4;
        v.z = sb + R_VMS + l7 * 128 + (((4 * (w & 1) + l8) ^ l7) << 4);
        v.w = sb + R_OS + l7 * 128 + ((l8 ^ l7) << 4);
        sts128(tab, v);
        v.x = mapa_u32(sb + R_RS + (crank >> 1) * 512 + ((lane ^ (crank >> 1)) << 4), rank * 8 + w * 2);
        v.y = mapa_u32(sb + RB_E, rank * 8 + w * 2);
        v.z = sb + R_VB + w * 512 + lane * 16;
        v.w = sb + R_SX + lane * 8;
        sts128(tab + 2048, v);
#pragma unroll
        for (int i = 0; i < 8; i++)
            sts128(tab + 4096 + i * 2048, make_uint4(wo[i >> 1][(i & 1) * 4][0], wo[i >> 1][(i & 1) * 4][1], wo[i >> 1][(i & 1) * 4][2], wo[i >> 1][(i & 1) * 4][3]));
        const int tok = (w & 1) * 4 + (lane >> 3);
        const uint64_t kd = w < 2 ? (uint64_t)(g_kvm + (g * (2 * HD_) + cta * 64 + w * 32 + (lane & 3) * 2))
                                  : (uint64_t)(g_kvm + (tok * (2 * HD_) + HD_ + cta * 64 + (lane & 7) * 8));
        const uint32_t ksrc = w < 2 ? sb + R_QF + (4 + 2 * rank + w) * 512 + lane * 16 : sb + R_VMS + tok * 128 + (((lane & 7) ^ tok) << 4);
        sts128(tab + 20480, make_uint4((uint32_t)kd, (uint32_t)(kd >> 32), ksrc, sb + lane * 16));
        if (t128 == 0) { wait_flag(F_KV + 0, 64); rec_load_kv(p, sb, cta >> 1, 0); mbar_wait(sb + RB_KV, 0); }
        __syncwarp();
    }
    bar_sync(NB_D, 384);
    const uint32_t lane16 = lds32(tab + 20480 + 12);
    uint4 av[8];
#pragma unroll
    for (int i = 0; i < 8; i++) av[i] = lds128(lane16 + R_WV + ((2 * w + (i >> 2)) * 16 + (i & 3)) * 512);
#pragma unroll 1
    for (int s = 0; s < NSEG; s++) {
        {
            if (s > 0) mbar_wait(sb + RB_A, (s - 1) & 1);
            if (s > 0) {
                const uint4 tp = lds128(tab + 20480);
                rec_store_kvm(tp.z, (char*)(((uint64_t)tp.y << 32) | tp.x), s - 1, w);
                if ((s & 3) == 0) bar_arrive(NB_K, 160);
            }
            if (s + 1 < NSEG - 1 && w == 3 && lane16 == sb) {
                if (((s + 1) & 3) == 0) wait_flag(F_KV + ((s + 1) >> 2), 64);
                rec_load_kv(p, sb, cta >> 1, s + 1);
            }
            __syncwarp();
        }
        uint4 vb;
        const uint4 ta = lds128(tab), tb = lds128(tab + 2048);
        {
            uint32_t bb[8];
            ldsm4(bb[0], bb[1], bb[2], bb[3], lane16 + R_MEM);
            ldsm4(bb[4], bb[5], bb[6], bb[7], lane16 + R_MEM + 512);
            float vd[4] = {0.f, 0.f, 0.f, 0.f}, ve[4] = {0.f, 0.f, 0.f, 0.f};
#pragma unroll
            for (int i = 0; i < 4; i++) {
                mma16816(vd, av[i].x, av[i].y, av[i].z, av[i].w, bb[2 * i], bb[2 * i + 1]);
                mma16816(ve, av[4 + i].x, av[4 + i].y, av[4 + i].z, av[4 + i].w, bb[2 * i], bb[2 * i + 1]);
            }
            bar_sync(NB_Y, 384);
            const uint4 a = lds128(lane16 + R_VP + w * 1024), b = lds128(lane16 + R_VP + w * 1024 + 512);
            vb = make_uint4(pack2(__uint_as_float(a.x) + vd[0], __uint_as_float(a.y) + vd[1]), pack2(__uint_as_float(a.z) + vd[2], __uint_as_float(a.w) + vd[3]),
                            pack2(__uint_as_float(b.x) + ve[0], __uint_as_float(b.y) + ve[1]), pack2(__uint_as_float(b.z) + ve[2], __uint_as_float(b.w) + ve[3]));
            st_async_v4(tb.z ^ (1u << 24), vb, (sb + RB_V) ^ (1u << 24));
        }
        if (w == 0) PROF(11);
        if (s != NSEG - 1) {
            uint32_t vx[16];
            const uint32_t vxa = ta.x + (s & 1) * 16384;
            mbar_wait(sb + RB_KV + (s & 1) * 8, (s >> 1) & 1);
            ldsm4t(vx[0], vx[1], vx[2], vx[3], vxa);
            ldsm4t(vx[4], vx[5], vx[6], vx[7], vxa ^ 32);
            ldsm4t(vx[8], vx[9], vx[10], vx[11], vxa + 2048);
            ldsm4t(vx[12], vx[13], vx[14], vx[15], (vxa ^ 32) + 2048);
#pragma unroll
            for (int i = 0; i < 4; i++) {
                const uint4 f0 = lds128(tab + 4096 + i * 2048);
                wo[i >> 1][(i & 1) * 4][0] = f0.x; wo[i >> 1][(i & 1) * 4][1] = f0.y; wo[i >> 1][(i & 1) * 4][2] = f0.z; wo[i >> 1][(i & 1) * 4][3] = f0.w;
            }
            bar_sync(NB_S, 320);
            if (w == 0) PROF(4);
            float sv[10];
#pragma unroll
            for (int n = 0; n < 5; n++) { const float2 a = lds64f(tb.w + n * 256); sv[2 * n] = a.x; sv[2 * n + 1] = a.y; }
            { const float2 a = lds64f(tb.w + 5 * 256); sv[0] += a.x; sv[1] += a.y; }
            float mx = fmaxf(fmaxf(fmaxf(sv[2], sv[3]), fmaxf(sv[4], sv[5])), fmaxf(fmaxf(sv[6], sv[7]), fmaxf(sv[8], sv[9])));
            mx = fmaxf(mx, fmaxf(sv[0], sv[1]));
            mx = fmaxf(mx, __shfl_xor_sync(~0u, mx, 1));
            mx = fmaxf(mx, __shfl_xor_sync(~0u, mx, 2));
            mbar_wait(sb + RB_V, s & 1);
            const uint4 vo = lds128(tb.z);
            uint32_t pf[5];
#pragma unroll
            for (int n = 0; n < 5; n++) pf[n] = pack2(ex2(sv[2 * n] - mx), ex2(sv[2 * n + 1] - mx));
            vb = make_uint4(hadd2(vb.x, vo.x), hadd2(vb.y, vo.y), hadd2(vb.z, vo.z), hadd2(vb.w, vo.w));
            if (w == 0) PROF(12);
            float oa[4][4] = {{0.f, 0.f, 0.f, 0.f}, {0.f, 0.f, 0.f, 0.f}, {0.f, 0.f, 0.f, 0.f}, {0.f, 0.f, 0.f, 0.f}}, sm[4] = {0.f, 0.f, 0.f, 0.f};
            const uint32_t one = 0x3F803F80u;
            mma1688h(sm, pf[0], one);
            mma1688h(oa[0], pf[0], vb.x);
            mma1688h(oa[1], pf[0], vb.y);
            mma1688h(oa[2], pf[0], vb.z);
            mma1688h(oa[3], pf[0], vb.w);
            mma16816h(sm, pf[1], pf[2], one, one);
#pragma unroll
            for (int n = 0; n < 4; n++) mma16816h(oa[n], pf[1], pf[2], vx[2 * n], vx[2 * n + 1]);
            mma16816h(sm, pf[3], pf[4], one, one);
#pragma unroll
            for (int n = 0; n < 4; n++) mma16816h(oa[n], pf[3], pf[4], vx[8 + 2 * n], vx[8 + 2 * n + 1]);
            float inv;
            asm("rcp.approx.ftz.f32 %0, %1;" : "=f"(inv) : "f"(sm[0]));
#pragma unroll
            for (int n = 0; n < 4; n++) sts32(ta.y ^ (n << 4), pack2(oa[n][0] * inv, oa[n][1] * inv));
            bar_sync(NB_C, 128);
            if (w == 0) PROF(5);
            uint32_t ob[16];
            ldsm4(ob[0], ob[1], ob[2], ob[3], ta.w);
            ldsm4(ob[8], ob[9], ob[10], ob[11], ta.w + 1024);
            ldsm4(ob[4], ob[5], ob[6], ob[7], ta.w ^ 64);
            ldsm4(ob[12], ob[13], ob[14], ob[15], (ta.w ^ 64) + 1024);
#pragma unroll
            for (int i = 4; i < 8; i++) {
                const uint4 f0 = lds128(tab + 4096 + i * 2048);
                wo[i >> 1][(i & 1) * 4][0] = f0.x; wo[i >> 1][(i & 1) * 4][1] = f0.y; wo[i >> 1][(i & 1) * 4][2] = f0.z; wo[i >> 1][(i & 1) * 4][3] = f0.w;
            }
#pragma unroll
            for (int jj = 0; jj < 2; jj++) {
                if (jj == 1 && tb.w == 0) break;
                float acc[4][4];
#pragma unroll
                for (int c = 0; c < 4; c++) { acc[c][0] = acc[c][1] = acc[c][2] = acc[c][3] = 0.f; }
#pragma unroll
                for (int k4 = 0; k4 < 4; k4++)
#pragma unroll
                    for (int c = 0; c < 4; c++) {
                        const int tl = jj * 2 + (c >> 1), ks = (c & 1) * 4 + k4;
                        mma16816(acc[c], wo[tl][ks][0], wo[tl][ks][1], wo[tl][ks][2], wo[tl][ks][3], ob[2 * ks], ob[2 * ks + 1]);
                    }
                uint4 v;
                v.x = pack2(acc[0][0] + acc[1][0], acc[0][1] + acc[1][1]);
                v.y = pack2(acc[0][2] + acc[1][2], acc[0][3] + acc[1][3]);
                v.z = pack2(acc[2][0] + acc[3][0], acc[2][1] + acc[3][1]);
                v.w = pack2(acc[2][2] + acc[3][2], acc[2][3] + acc[3][3]);
                st_async_v4(tb.x + (jj << 24), v, tb.y + (jj << 24));
            }
            if (w == 0) PROF(6);
        } else {
            mbar_wait(sb + RB_V, s & 1);
            const uint4 o = lds128(tb.z);
            vb = make_uint4(hadd2(vb.x, o.x), hadd2(vb.y, o.y), hadd2(vb.z, o.z), hadd2(vb.w, o.w));
            mbar_wait(sb + RB_Q, s & 1);
        }
        if ((w >> 1) == rank) stsm4t(ta.z + (s & 1) * 1024, vb.x, vb.y, vb.z, vb.w);
        bar_sync(NB_C, 128);
        if (s != NSEG - 1 && w == 0 && lane16 == sb) mbar_expect_tx(sb + RB_V, 2048);
#pragma unroll
        for (int i = 0; i < 8; i++) av[i] = lds128(lane16 + R_WV + ((2 * w + (i >> 2)) * 16 + (i & 3)) * 512);
    }
    {
        const uint4 tp = lds128(tab + 20480);
        rec_store_kvm(tp.z, (char*)(((uint64_t)tp.y << 32) | tp.x), NSEG - 1, w);
    }
    bar_sync(NB_C, 128);
    if (w == 0 && lane == 0) red_release(&g_flags[F_MEM + NRB - 1], 1);
}

__global__ void __launch_bounds__(384, 1) k_rec(const __grid_constant__ RecParams p) {
    extern __shared__ __align__(1024) unsigned char smem_raw[];
    const uint32_t sb = __shfl_sync(~0u, smem_u32(smem_raw), 0);
    const int warp = __shfl_sync(~0u, threadIdx.x >> 5, 0);
    int lane; asm volatile("mov.u32 %0, %%laneid;" : "=r"(lane));
    const int crank = blockIdx.x & 15, slot = blockIdx.x >> 4;
    asm volatile("griddepcontrol.launch_dependents;");
    if (crank == 0 && threadIdx.x == 0) {
        stg_relaxed32(&g_F[65536 + slot * 64], 0u);
        stg_relaxed32(&g_F[65536 + 1024 + slot * 64], 0u);
    }
    if (threadIdx.x == 0) {
        mbar_init(sb + RB_Q, 9); mbar_init(sb + RB_V, 1); mbar_init(sb + RB_E, 1); mbar_init(sb + RB_A, 1); mbar_init(sb + RB_ROLE, 1);
        mbar_init(sb + RB_KV, 1); mbar_init(sb + RB_KV + 8, 1);
        asm volatile("fence.mbarrier_init.release.cluster;" ::: "memory");
        mbar_expect_tx(sb + RB_Q, 4096);
        mbar_expect_tx(sb + RB_V, 2048);
        mbar_expect_tx(sb + RB_E, 4096);
        mbar_expect_tx(sb + RB_A, 4096);
        mbar_expect_tx(sb + RB_ROLE, 4);
    }
    asm volatile("barrier.cluster.arrive.relaxed.aligned;\nbarrier.cluster.wait.aligned;" ::: "memory");
    unsigned role = 0;
    if (crank == 0 && threadIdx.x == 0 && !p.only_pre) {
        unsigned x = 0;
        int tm[2] = {0x7fffffff, 0x7fffffff};
#pragma unroll 1
        for (int i = 0; i < 6; i++) {
            const uint32_t t0 = clk32();
            x = atomicAdd(&g_F[65536 + (i & 1) * 1024 + slot * 64 + (x >> 31)], 1u);
            if (x != (unsigned)(i >> 1)) sts32(sb + R_BAR + 56, x);
            const int dt = (int)(clk32() - t0);
            if (i >= 2) { if (i & 1) tm[1] = min(tm[1], dt); else tm[0] = min(tm[0], dt); }
        }
        const int side = tm[1] > tm[0];
        const unsigned old = atomicAdd(&g_flags[F_SIDE + side * 32], 1u);
        unsigned c0, c1; int gd = 0;
#pragma unroll 1
        do { c0 = ldg_relaxed32(&g_flags[F_SIDE]); c1 = ldg_relaxed32(&g_flags[F_SIDE + 32]); } while ((int)(c0 + c1) < p.ncl && ++gd < 64 * SPIN_LIMIT);
        const int big = c1 > c0;
        role = side == big ? old : (big ? c1 : c0) + old;
        role |= (big ^ 1) << 8;
    }
    __syncwarp();
    if (crank == 0 && warp == 0 && !p.only_pre) {
        role = __shfl_sync(~0u, role, 0);
        if (lane < 16)
            asm volatile("st.async.weak.shared::cluster.mbarrier::complete_tx::bytes.u32 [%0], %1, [%2];"
                         :: "r"(mapa_u32(sb + R_BAR + 48, lane)), "r"(role), "r"(mapa_u32(sb + RB_ROLE, lane)) : "memory");
    }
    if (warp >= 4) {
        const int w8 = warp - 4, nblk = gridDim.x;
        const int cq = lane & 3, rg = w8 * 8 + (lane >> 2);
        const uint32_t red = sb + R_VP;
        const int row0 = blockIdx.x * 8 + w8;
        const uint4* xr = (const uint4*)(p.x + (size_t)row0 * D_);
        uint4 xa = __ldg(xr + lane), xb = __ldg(xr + 32 + lane);
#pragma unroll 1
        for (int sl = blockIdx.x; sl < 96; sl += nblk) {
            uint4 wv[8];
#pragma unroll
            for (int i = 0; i < 8; i++) wv[i] = __ldg((const uint4*)(p.w_mod + (size_t)(rg * 8 + i) * (6 * D_) + sl * 32 + cq * 8));
            const uint32_t cw = __ldg((const uint32_t*)(p.c + rg * 8) + cq);
            const float cl = bflo(cw), ch = bfhi(cw);
            const uint32_t sw = pack2(__fdividef(cl, 1.f + __expf(-cl)), __fdividef(ch, 1.f + __expf(-ch)));
            float a[8];
#pragma unroll
            for (int i = 0; i < 8; i++) a[i] = 0.f;
#pragma unroll
            for (int i = 0; i < 8; i++) {
                const uint32_t sv = __shfl_sync(~0u, sw, (lane & 28) + (i >> 1));
                const float cv = (i & 1) ? bfhi(sv) : bflo(sv);
                a[0] = fmaf(cv, bflo(wv[i].x), a[0]); a[1] = fmaf(cv, bfhi(wv[i].x), a[1]); a[2] = fmaf(cv, bflo(wv[i].y), a[2]); a[3] = fmaf(cv, bfhi(wv[i].y), a[3]);
                a[4] = fmaf(cv, bflo(wv[i].z), a[4]); a[5] = fmaf(cv, bfhi(wv[i].z), a[5]); a[6] = fmaf(cv, bflo(wv[i].w), a[6]); a[7] = fmaf(cv, bfhi(wv[i].w), a[7]);
            }
#pragma unroll
            for (int i = 0; i < 8; i++) { a[i] += __shfl_xor_sync(~0u, a[i], 4); a[i] += __shfl_xor_sync(~0u, a[i], 8); a[i] += __shfl_xor_sync(~0u, a[i], 16); }
            if (lane < 4) {
                sts128(red + w8 * 128 + lane * 32, make_uint4(__float_as_uint(a[0]), __float_as_uint(a[1]), __float_as_uint(a[2]), __float_as_uint(a[3])));
                sts128(red + w8 * 128 + lane * 32 + 16, make_uint4(__float_as_uint(a[4]), __float_as_uint(a[5]), __float_as_uint(a[6]), __float_as_uint(a[7])));
            }
            bar_sync(NB_B, 256);
            if (w8 == 0) {
                float v = 0.f;
#pragma unroll
                for (int i = 0; i < 8; i++) v += lds32f(red + i * 128 + lane * 4);
                g_mod[sl * 32 + lane] = __float2bfloat16_rn(v);
                __syncwarp();
                if (lane == 0) red_release(&g_flags[F_MOD + (sl >= 32)], 1);
            }
            bar_sync(NB_B, 256);
        }
        uint32_t c1[8], sm[8];
        int row = row0;
#pragma unroll 1
        while (true) {
            const uint32_t v[8] = {xa.x, xa.y, xa.z, xa.w, xb.x, xb.y, xb.z, xb.w};
            uint32_t mu2, r[8]; float rden;
            ln_stats(v, mu2, rden);
            if (row == row0) {
                if (lane == 0) wait_flag(F_MOD, 32);
                __syncwarp();
                load_mod8(g_mod + D_, lane, c1);
                load_mod8(g_mod, lane, sm);
#pragma unroll
                for (int i = 0; i < 8; i++) c1[i] = hadd2(c1[i], 0x3F803F80u);
            } else if (row + 512 < S_) {
                xr = (const uint4*)(p.x + (size_t)(row + 512) * D_); xa = __ldg(xr + lane); xb = __ldg(xr + 32 + lane);
            }
            ln_apply(v, mu2, rden, c1, sm, r);
            uint4* hr = (uint4*)(g_h + (size_t)row * D_);
            hr[lane] = make_uint4(r[0], r[1], r[2], r[3]); hr[32 + lane] = make_uint4(r[4], r[5], r[6], r[7]);
            bar_sync(NB_B, 256);
            if (w8 == (row >> 7 & 7) && lane == 0) red_release(&g_flags[F_H + (row >> 7)], 1);
            __syncwarp();
            if (row == row0) {
                if (!p.only_pre) mbar_wait(sb + RB_ROLE, 0);
                const int cl = p.only_pre ? slot : (int)(lds32(sb + R_BAR + 48) & 255);
                row = cl < 4 ? (nblk + cl * 16 + crank) * 8 + w8 : S_;
                if (row < S_) { xr = (const uint4*)(p.x + (size_t)row * D_); xa = __ldg(xr + lane); xb = __ldg(xr + 32 + lane); }
            } else {
                row += 512;
            }
            if (row >= S_) break;
        }
    }
    if (p.only_pre) return;
    mbar_wait(sb + RB_ROLE, 0);
    const int rolew = __shfl_sync(~0u, lds32(sb + R_BAR + 48), 0);
    const int cl = rolew & 255;
    if (cl >= 4) return;
    const int cta = cl * 16 + crank;
    if (warp < 8) rec_qk(p, sb, cta, warp, lane, rolew >> 8);
    else rec_vo(p, sb, cta, warp, lane);
}

#define MBW mbar_wait
enum { J_KV = 0, J_QA = 1, J_O = 2, J_LN = 3, J_UP = 4, J_DN = 5, J_UP2 = 8, J_END = 9 };
constexpr int NJ_O = 2 * OSPLIT, NJ_O2 = 2 * OSPLIT2, NJ_LN = 8, NJ_LN2 = 16, NJ_UP = 14, NJ_UP2 = 28, NJ_DN = 8, NJ_LN1 = 8  ;
constexpr uint64_t pk8(int a, int b, int c, int d, int e, int f, int g, int h) {
    return (uint64_t)a | ((uint64_t)b << 8) | ((uint64_t)c << 16) | ((uint64_t)d << 24) | ((uint64_t)e << 32) | ((uint64_t)f << 40) | ((uint64_t)g << 48) | ((uint64_t)h << 56);
}
constexpr uint64_t NJ_C = pk8(32, 16, NJ_O, NJ_LN, NJ_UP, NJ_DN, 0, 0), NJ_F = pk8(32, 16, NJ_O2, NJ_LN2, NJ_UP2, NJ_DN, 0, 0);
constexpr uint64_t TG_C = pk8(2 * NJ_LN1, 64, 32, 2 * NJ_O, 2 * NJ_LN, 2 * NJ_UP, 32, 0), TG_F = pk8(2 * NJ_LN1, 64, 32, 2 * NJ_O2, 2 * NJ_LN2, 2 * NJ_UP2, 32, 0);
constexpr uint64_t NJ_L = pk8(32, 32, 2 * OSPLIT3, NJ_LN2, NJ_UP2, 2 * NJ_DN, 0, 0), TG_L = pk8(2 * NJ_LN1, 64, 64, 4 * OSPLIT3, 2 * NJ_LN2, 2 * NJ_UP2, 32, 0);
__device__ __forceinline__ uint64_t nj_tab(int rb) { return rb < FINE_RB ? NJ_C : (rb < NRB - 1 ? NJ_F : NJ_L); }
__device__ __forceinline__ uint64_t tg_tab(int rb) { return rb < FINE_RB ? TG_C : (rb < NRB - 1 ? TG_F : TG_L); }
__device__ __forceinline__ int o_nk(int rb) { return rb < FINE_RB ? 64 / OSPLIT : (rb < NRB - 1 ? 64 / OSPLIT2 : 64 / OSPLIT3); }
constexpr uint64_t PRIO = pk8(4, 10, 9, 8, 7, 6, 3, 0);
__device__ __forceinline__ int pick_job(int lane, int qmask, int& idx) {
    const int rb = lane & 15, half = lane >> 4;
    const uint64_t nj = nj_tab(rb) >> (8 * half);
    const uint64_t tg = tg_tab(rb) >> (8 * half);
    const unsigned* cp = &g_flags[F_CLAIM + half * 32 + rb];
    const unsigned* dp = &g_flags[half * 32 + rb];
    int gd = 0;
#pragma unroll 1
    while (true) {
        const unsigned c0 = ldg_relaxed32(cp), c1 = ldg_relaxed32(cp + 64), c2 = ldg_relaxed32(cp + 128);
        const unsigned d0 = ldg_relaxed32(dp - (half && rb ? 1 : 0)), d1 = ldg_relaxed32(dp + 64), d2 = ldg_relaxed32(dp + 128);
        const unsigned cl[3] = {c0, c1, c2}, dv[3] = {d0, d1, d2};
        unsigned key = 0xffffu, key2 = 0xffffu;
        bool pre = false;
#pragma unroll
        for (int i = 0; i < 3; i++) {
            const int q = half + 2 * i;
            const bool have = ((qmask >> q) & 1) && cl[i] < (unsigned)((nj >> (16 * i)) & 255);
            bool ready = have && dv[i] >= (unsigned)((tg >> (16 * i)) & 255);
            unsigned pr = (unsigned)((PRIO >> (8 * q)) & 255);
            if (i == 0 && rb <= 1 - half) ready = have;
            if (i == 0 && half && rb >= FINE_RB) pr = 5;
            if (ready) key = min(key, (pr << 8) | (rb << 4) | q);
            if (have) key2 = min(key2, rb >= FINE_RB ? (0x100u | (q << 4) | rb) : (i == 0 ? 0u : 0x1000u));
            pre |= have && i == 0 && !half;
        }
        const bool anypre = __any_sync(~0u, pre);
        if (anypre && (key & 15) == J_QA) key = 0xffffu;
        key = __reduce_min_sync(~0u, key);
        key2 = __reduce_min_sync(~0u, key2);
        if (key2 == 0xffffu) return J_END;
        int pq, prb;
        if (key != 0xffffu) { pq = key & 15; prb = (key >> 4) & 15; }
        else if (key2 >= 0x120u && key2 < 0x1000u) { pq = (key2 >> 4) & 15; prb = key2 & 15; }
        else {
            __nanosleep(IDLE_NS);
            if (++gd > 16 * SPIN_LIMIT) { TIMEOUT(5, 0); return J_END; }
            continue;
        }
        int c = 0;
        if (lane == 0) c = (int)atomicAdd(&g_flags[F_CLAIM + pq * 32 + prb], 1u);
        c = __shfl_sync(~0u, c, 0);
        if (c < (int)((nj_tab(prb) >> (8 * pq)) & 255)) {
            idx = pq * 512 + prb * 32 + c;
            int acq = 0;
            if (pq != J_QA) {
                if (lane == 0 && ld_acquire(&g_flags[pq * 32 + prb]) >= (unsigned)((tg_tab(prb) >> (8 * pq)) & 255)) {
                    asm volatile("fence.proxy.async.global;" ::: "memory");
                    acq = 1 << 24;
                }
            }
            return (pq == J_UP && prb >= FINE_RB ? J_UP2 : pq) | (prb << 8) | (c << 16) | acq;
        }
    }
}
__device__ __forceinline__ int op_row(int rb, int split) {
    return rb < FINE_RB ? split * S_ + rb * 128
                        : (rb < NRB - 1 ? OSPLIT * S_ + (split * (NRB - FINE_RB) + rb - FINE_RB) * 128 : OSPLIT * S_ + (OSPLIT2 * (NRB - FINE_RB) + split) * 128);
}

struct Pipe { uint32_t stage, phase; };
__device__ __forceinline__ void pipe_next(Pipe& p) { if (++p.stage == W_NST) { p.stage = 0; p.phase ^= 1; } }

__device__ __forceinline__ void scheduler(const Params& p, uint32_t sb, int lane) {
    const uint32_t bars = sb + SM_BAR;
    uint32_t ph = 0;
#pragma unroll 1
    while (true) {
        MBW(bars + B_REQ, ph);
        int j = 4095;
        const int jd = pick_job(lane, p.qmask, j);
        if (lane == 0) { sts32(bars + B_NEXT, (uint32_t)jd); sts32(bars + B_NEXT + 4, (uint32_t)j); mbar_arrive(bars + B_RSP); }
        ph ^= 1;
        if (jd == J_END) break;
        __syncwarp();
    }
}

__device__ __forceinline__ void producer(const Params& p, uint32_t sb) {
    Pipe pp{0, 1};
    const uint32_t bars = sb + SM_BAR;
    uint32_t seq = 0, h_seen = 0;
    mbar_arrive(bars + B_REQ);
#pragma unroll 1
    while (true) {
        MBW(bars + B_RSP, seq & 1);
        const int jd = (int)lds32(bars + B_NEXT), j = (int)lds32(bars + B_NEXT + 4);
        int left = (jd & 255) == J_DN ? 15 : ((jd & 255) == J_O ? o_nk((jd >> 8) & 255) : ((jd & 255) == J_LN ? 1 : 8));
        left = (jd & 255) == J_QA ? 9 : max(left - PICK_AHEAD, 1);
        TR(j, 1);
        const int type = jd & 255, rb = (jd >> 8) & 255, cb = (jd >> 16) & 255;
        const bool fine = rb >= FINE_RB, acquired = (jd >> 24) & 1;
        bool first = true;
        auto begin_stage = [&](uint32_t bytes) -> uint32_t {
            MBW(bars + B_EMPTY + pp.stage * 8, pp.phase);
            if (first) { sts32(bars + B_RING + (seq & 7) * 4, (uint32_t)jd); sts32(bars + B_RING + 32 + (seq & 7) * 4, (uint32_t)j); first = false; }
            const uint32_t fb = bars + B_FULL + pp.stage * 8;
            if (bytes) mbar_expect_tx(fb, bytes); else mbar_arrive(fb);
            return fb;
        };
        auto end_stage = [&]() {
            pipe_next(pp);
            if (--left == 0) mbar_arrive(bars + B_REQ);
        };
        if (type == J_END || type == J_LN) {
            if (type == J_LN && !(h_seen >> 31)) { wait_flag(F_MOD + 1, 64); h_seen |= 1u << 31; }

            TR(j, 2);
            begin_stage(0);
            if (type == J_END) break;
            if (!acquired) wait_flag(F_OP + rb, (unsigned)((tg_tab(rb) >> (8 * J_LN)) & 255));
            end_stage();
            seq++;
            continue;
        }
        const CUtensorMap *ta, *tb0, *tb1;
        int k0 = 0, nk = 8, n0 = cb * 256, n1 = n0 + 128, nb = 4, dep = -1;
        unsigned tgt = 0;
        switch (type) {
            case J_KV: ta = &p.tm_h; tb0 = tb1 = cb < 16 ? &p.tm_wk : &p.tm_wv; n0 = (cb & 15) * 256; n1 = n0 + 128; dep = F_H + rb; tgt = 2 * NJ_LN1; break;
            case J_QA: ta = &p.tm_h; tb0 = tb1 = &p.tm_wq; dep = F_H + rb; tgt = 2 * NJ_LN1; if (rb == NRB - 1) { n0 = (cb >> 1) * 256; n1 = n0 + 128; } break;
            case J_O: ta = &p.tm_o; tb0 = tb1 = &p.tm_wo; n0 = (cb & 1) * 256; n1 = n0 + 128; nk = o_nk(rb); k0 = (cb >> 1) * nk * 64;
                      dep = F_O + rb; tgt = rb == NRB - 1 ? 64 : 32; break;
            case J_UP: ta = &p.tm_h2; tb0 = &p.tm_wg; tb1 = &p.tm_wu; n0 = n1 = cb * 128; dep = F_H2 + rb; tgt = 2 * NJ_LN; break;
            case J_UP2: ta = &p.tm_h2; tb0 = &p.tm_wg; tb1 = &p.tm_wu; n0 = n1 = cb * 64; nb = 2; dep = F_H2 + rb; tgt = 2 * NJ_LN2; break;
            default: ta = &p.tm_act; tb0 = tb1 = &p.tm_wd; n0 = cb * 64; nk = 0; break;
        }
        const int m0 = rb * 128;
        if (type == J_DN && rb == NRB - 1) {
            n0 = (cb >> 1) * 64;
            const int mh = m0 + (cb & 1) * 64;
#pragma unroll 1
            for (int kb = 0; kb < 14; kb++) {
                const uint32_t fb = begin_stage(32768);
                const uint32_t st = sb + pp.stage * W_STAGE;
                const int k = kb * 128;
                tma_load2d(st + 32768, tb0, n0, k, fb);
                tma_load2d(st + 40960, tb0, n0, k + 64, fb);
                if (kb == 0) { if (!acquired) { wait_flag(F_ACT + rb, 2 * NJ_UP2); asm volatile("fence.proxy.async.global;" ::: "memory"); } TR(j, 2); }
                tma_load2d(st, ta, k, mh, fb);
                tma_load2d(st + 8192, ta, k + 64, mh, fb);
                end_stage();
            }
            const uint32_t fb = begin_stage(8192);
            tma_load2d(sb + pp.stage * W_STAGE, &p.tm_x1, n0, mh, fb);
            end_stage();
            seq++;
            continue;
        }
        if (type == J_DN) {
#pragma unroll 1
            for (int kb = 0; kb < 14; kb++) {
                const uint32_t fb = begin_stage(49152);
                const uint32_t st = sb + pp.stage * W_STAGE;
                const int k = kb * 128;
                tma_load2d(st + 32768, tb0, n0, k, fb);
                tma_load2d(st + 40960, tb0, n0, k + 64, fb);
                if (kb == 0) { if (!acquired) { wait_flag(F_ACT + rb, 2 * (fine ? NJ_UP2 : NJ_UP)); asm volatile("fence.proxy.async.global;" ::: "memory"); } TR(j, 2); }
                tma_load2d(st, ta, k, m0, fb);
                tma_load2d(st + 8192, ta, k, m0 + 64, fb);
                tma_load2d(st + 16384, ta, k + 64, m0, fb);
                tma_load2d(st + 24576, ta, k + 64, m0 + 64, fb);
                end_stage();
            }
        }
#pragma unroll 1
        for (int kb = 0; kb < nk; kb++) {
            const uint32_t fb = begin_stage(16384 + nb * 8192);
            const uint32_t st = sb + pp.stage * W_STAGE;
            const int k = k0 + kb * 64;
            tma_load2d(st + 16384, tb0, n0, k, fb);
            if (nb == 4) {
                tma_load2d(st + 16384 + 8192, tb0, n0 + 64, k, fb);
                tma_load2d(st + 16384 + 16384, tb1, n1, k, fb);
                tma_load2d(st + 16384 + 24576, tb1, n1 + 64, k, fb);
            } else if (nb == 2) {
                tma_load2d(st + 16384 + 8192, tb1, n1, k, fb);
            }
            if (kb == 0) {
                if (acquired && dep < 16) h_seen |= 1u << dep;
                if (dep >= 0 && !acquired && !(dep < 16 && ((h_seen >> dep) & 1))) {
                    wait_flag(dep, tgt);
                    if (type != J_O) asm volatile("fence.proxy.async.global;" ::: "memory");
                    if (dep < 16) h_seen |= 1u << dep;
                }
                TR(j, 2);
            }
            tma_load2d(st, ta, k, m0, fb);
            tma_load2d(st + 8192, ta, k, m0 + 64, fb);
            end_stage();
        }
        if (type == J_QA) {
            wait_flag(F_KV + rb, 64);
#pragma unroll 1
            for (int i = 0; i < (rb == NRB - 1 ? 2 : 4); i++) {
                const uint32_t fb = begin_stage(40960);
                const uint32_t st = sb + pp.stage * W_STAGE;
                const int col = (i & 1) * HD_ + (rb == NRB - 1 ? cb : cb * 2 + (i >> 1)) * DH_;
                tma_load2d(st, &p.tm_kv, col, m0, fb);
                tma_load2d(st + 8192, &p.tm_kv, col, m0 + 64, fb);
                tma_load2d(st + 16384, &p.tm_kv, col + 64, m0, fb);
                tma_load2d(st + 24576, &p.tm_kv, col + 64, m0 + 64, fb);
                if (i == 0) { wait_flag(F_MEM + rb, 64); asm volatile("fence.proxy.async.global;" ::: "memory"); }
                tma_load2d(st + 32768, &p.tm_kvm, col, rb * 32, fb);
                tma_load2d(st + 36864, &p.tm_kvm, col + 64, rb * 32, fb);
                end_stage();
            }
        } else if (type == J_DN) {
            const uint32_t fb = begin_stage(16384);
            const uint32_t st = sb + pp.stage * W_STAGE;
            tma_load2d(st, &p.tm_x1, n0, m0, fb);
            tma_load2d(st + 8192, &p.tm_x1, n0, m0 + 64, fb);
            end_stage();
        }
        seq++;
    }
}

__device__ __forceinline__ void store_warp(const Params& p, uint32_t sb, int wg, int lane) {
    const uint32_t bars = sb + SM_BAR;
    uint32_t seq = 0;
#pragma unroll 1
    while (true) {
        bar_sync(NB_ST + wg, 160);
        const uint32_t jd = lds32(bars + B_RING + (seq & 7) * 4);
        seq++;
        const int type = jd & 255, rb = (jd >> 8) & 255, cb = (jd >> 16) & 255;
        if (type == J_END) break;
        const uint32_t src = sb + W_STG + wg * 16384;
        const CUtensorMap* tm = nullptr; int n0 = cb * 256, nbox = 4, mrow = rb * 128 + wg * 64, flag = 0;
        switch (type) {
            case J_KV: tm = &p.tm_kv; flag = F_KV + rb; break;
            case J_QA: tm = &p.tm_o; flag = F_O + rb; if (rb == NRB - 1) { n0 = cb * 128; nbox = 2; } break;
            case J_O: tm = &p.tm_op; n0 = (cb & 1) * 256; mrow = op_row(rb, cb >> 1) + wg * 64; flag = F_OP + rb; break;
            case J_LN: flag = F_H2 + rb; nbox = 0; break;
            case J_UP: tm = &p.tm_act; n0 = cb * 128; nbox = 2; flag = F_ACT + rb; break;
            case J_UP2: tm = &p.tm_act; n0 = cb * 64; nbox = 1; flag = F_ACT + rb; break;
            default: tm = &p.tm_out; n0 = cb * 64; nbox = 1; flag = -1;
                     if (rb == NRB - 1) { n0 = (cb >> 1) * 64; mrow = rb * 128 + (cb & 1) * 64; nbox = wg == 0; } break;
        }
        if (nbox == 4) {
            if (lane == 0) {
                tma_store2d(tm, src, n0, mrow);
                tma_store2d(tm, src + 8192, n0 + 64, mrow);
                bulk_commit();
                asm volatile("cp.async.bulk.wait_group.read 0;" ::: "memory");
                mbar_arrive(bars + B_STGFREE + wg * 8);
            }
            __syncwarp();
            bar_sync(NB_ST + wg, 160);
            n0 += 128; nbox = 2;
        }
        if (lane == 0) {
            if (nbox) {
                tma_store2d(tm, src, n0, mrow);
                if (nbox == 2) tma_store2d(tm, src + 8192, n0 + 64, mrow);
                bulk_commit();
                asm volatile("cp.async.bulk.wait_group.read 0;" ::: "memory");
                mbar_arrive(bars + B_STGFREE + wg * 8);
                bulk_wait0();
                if (flag >= 0) asm volatile("red.relaxed.gpu.global.add.u32 [%0], 1;" :: "l"(&g_flags[flag]) : "memory");
            } else {
                mbar_arrive(bars + B_STGFREE + wg * 8);
                if (flag >= 0) red_release(&g_flags[flag], 1);
            }
        }
        __syncwarp();
    }
}

__device__ __forceinline__ float gelu_tanh(float x) {
    const float t = x * fmaf(-0.10294324397f, x * x, -2.30220819814f);
    float r; asm("rcp.approx.ftz.f32 %0, %1;" : "=f"(r) : "f"(1.f + ex2(t)));
    return x * r;
}

#define CTR(i) do {} while (0)

__device__ __forceinline__ void ln2_row(const Params& p, int rb, int r, int lane, bool wait) {
    const int row = rb * 128 + r, nsplit = 64 / o_nk(rb);
    const uint4* xr = (const uint4*)(p.x + (size_t)row * D_);
    const uint4 xa = __ldg(xr + lane), xb = __ldg(xr + 32 + lane);
    uint32_t ga[8], c1[8], sm[8];
    load_mod8(g_mod + 2 * D_, lane, ga);
    load_mod8(g_mod + 4 * D_, lane, c1);
    load_mod8(g_mod + 3 * D_, lane, sm);
    float a[16];
#pragma unroll
    for (int i = 0; i < 16; i++) a[i] = 0.f;
    const uint4* src = (const uint4*)(g_op + (size_t)(op_row(rb, 0) + r) * D_) + lane;
    const int sstride = (op_row(rb, 1) - op_row(rb, 0)) * (D_ / 8);
    if (wait) { if (lane == 0) wait_flag(F_OP + rb, 4 * nsplit); __syncwarp(); }
    uint4 u[2][8];
#pragma unroll
    for (int sp = 0; sp < 4; sp++) { u[0][2 * sp] = __ldcg(src + sp * sstride); u[0][2 * sp + 1] = __ldcg(src + sp * sstride + 32); }
    if (nsplit > 4) {
#pragma unroll
        for (int sp = 0; sp < 4; sp++) { u[1][2 * sp] = __ldcg(src + (4 + sp) * sstride); u[1][2 * sp + 1] = __ldcg(src + (4 + sp) * sstride + 32); }
    }
#pragma unroll 1
    for (int s0 = 0; s0 < nsplit; s0 += 4) {
#pragma unroll
        for (int sp = 0; sp < 8; sp++) {
            float* q = a + (sp & 1) * 8;
            const uint4 w = u[0][sp];
            q[0] += bflo(w.x); q[1] += bfhi(w.x); q[2] += bflo(w.y); q[3] += bfhi(w.y);
            q[4] += bflo(w.z); q[5] += bfhi(w.z); q[6] += bflo(w.w); q[7] += bfhi(w.w);
            u[0][sp] = u[1][sp];
        }
        if (s0 + 8 < nsplit) {
#pragma unroll
            for (int sp = 0; sp < 4; sp++) { u[1][2 * sp] = __ldcg(src + (s0 + 8 + sp) * sstride); u[1][2 * sp + 1] = __ldcg(src + (s0 + 8 + sp) * sstride + 32); }
        }
    }
    const uint32_t xv[8] = {xa.x, xa.y, xa.z, xa.w, xb.x, xb.y, xb.z, xb.w};
    uint32_t v[8], r8[8];
#pragma unroll
    for (int i = 0; i < 8; i++) v[i] = hadd2(xv[i], hmul2(ga[i], pack2(a[2 * i], a[2 * i + 1])));
    uint4* x1r = (uint4*)(g_x1 + (size_t)row * D_);
    x1r[lane] = make_uint4(v[0], v[1], v[2], v[3]); x1r[32 + lane] = make_uint4(v[4], v[5], v[6], v[7]);
    uint32_t mu2; float rden;
    ln_stats(v, mu2, rden);
#pragma unroll
    for (int i = 0; i < 8; i++) c1[i] = hadd2(c1[i], 0x3F803F80u);
    ln_apply(v, mu2, rden, c1, sm, r8);
    uint4* hr = (uint4*)(g_h2 + (size_t)row * D_);
    hr[lane] = make_uint4(r8[0], r8[1], r8[2], r8[3]); hr[32 + lane] = make_uint4(r8[4], r8[5], r8[6], r8[7]);
}

__device__ __forceinline__ void consumer(const Params& p, uint32_t sb, int warp, int lane) {
    const uint32_t bars = sb + SM_BAR;
    const int wg = warp >> 2, wl = warp & 3;
    const uint32_t l7 = lane & 7, l8 = lane >> 3, g = lane >> 2, t = lane & 3;
    Pipe pp{0, 0};
    uint32_t seq = 0, stg_phase = 1;
    const int srow = wl * 16 + l7 + (l8 & 1) * 8;
    const uint32_t stg_base = sb + W_STG + wg * 16384 + srow * 128;
    const uint32_t sx = ((lane >> 4) ^ (srow & 7)) << 4;
#pragma unroll 1
    while (true) {
        MBW(bars + B_FULL + pp.stage * 8, pp.phase);
        const uint32_t jd = lds32(bars + B_RING + (seq & 7) * 4);
        CTR(3);
        seq++;
        const int type = jd & 255, rb = (jd >> 8) & 255, cb = (jd >> 16) & 255;
        if (type == J_END) { MBW(bars + B_STGFREE + wg * 8, stg_phase); bar_arrive(NB_ST + wg, 160); break; }
        if (type == J_LN) {
            __syncwarp();
            if (lane == 0) mbar_arrive(bars + B_EMPTY + pp.stage * 8);
            pipe_next(pp);
            const int nr = rb >= FINE_RB ? 1 : 2;
#pragma unroll 1
            for (int rr = 0; rr < nr; rr++) ln2_row(p, rb, (cb * 8 + warp) * nr + rr, lane, !((jd >> 24) & 1) && rr == 0);
            MBW(bars + B_STGFREE + wg * 8, stg_phase); stg_phase ^= 1;
            CTR(4); CTR(5);
            bar_arrive(NB_ST + wg, 160);
            continue;
        }
        if (type == J_DN || type == J_UP2) {
            float acc[64];
#pragma unroll
            for (int i = 0; i < 64; i++) acc[i] = 0.f;
            const bool ksplit = type == J_DN && rb == NRB - 1;
            if (ksplit) {
#pragma unroll 1
                for (int kb = 0; kb < 14; kb++) {
                    if (kb) MBW(bars + B_FULL + pp.stage * 8, pp.phase);
                    const uint32_t st = sb + pp.stage * W_STAGE;
                    const uint64_t da = mkdesc(st + wg * 8192, 16, 1024), db = mkdesc(st + 32768 + wg * 8192, 8192, 1024);
                    wg_fence();
#pragma unroll
                    for (int ks = 0; ks < 4; ks++) wgmma_n64(acc, da + ks * 2, db + ks * 128);
                    wg_commit();
                    wg_wait0();
                    if (lane == 0) mbar_arrive(bars + B_EMPTY + pp.stage * 8);
                    pipe_next(pp);
                }
                const uint32_t xb = sb + W_STG + 16384 + (wl * 32 + lane) * 16;
                if (wg == 1) {
                    MBW(bars + B_STGFREE + 8, stg_phase);
#pragma unroll
                    for (int i = 0; i < 8; i++)
                        sts128(xb + i * 2048, make_uint4(__float_as_uint(acc[4 * i]), __float_as_uint(acc[4 * i + 1]), __float_as_uint(acc[4 * i + 2]), __float_as_uint(acc[4 * i + 3])));
                }
                bar_sync(NB_M, 256);
                if (wg == 0) {
#pragma unroll
                    for (int i = 0; i < 8; i++) {
                        const uint4 o = lds128(xb + i * 2048);
                        acc[4 * i] += __uint_as_float(o.x); acc[4 * i + 1] += __uint_as_float(o.y); acc[4 * i + 2] += __uint_as_float(o.z); acc[4 * i + 3] += __uint_as_float(o.w);
                    }
                }
                bar_sync(NB_M, 256);
            } else if (type == J_DN) {
#pragma unroll 1
                for (int kb = 0; kb < 14; kb++) {
                    if (kb) MBW(bars + B_FULL + pp.stage * 8, pp.phase);
                    const uint32_t st = sb + pp.stage * W_STAGE;
                    const uint64_t da = mkdesc(st + wg * 8192, 16, 1024), db = mkdesc(st + 32768, 8192, 1024);
                    wg_fence();
#pragma unroll
                    for (int ks = 0; ks < 8; ks++) wgmma_n64(acc, da + (ks >> 2) * 1024 + (ks & 3) * 2, db + ks * 128);
                    wg_commit();
                    wg_wait0();
                    if (lane == 0) mbar_arrive(bars + B_EMPTY + pp.stage * 8);
                    pipe_next(pp);
                }
            } else {
#pragma unroll 1
                for (int kb = 0; kb < 8; kb++) {
                    if (kb) MBW(bars + B_FULL + pp.stage * 8, pp.phase);
                    const uint32_t st = sb + pp.stage * W_STAGE;
                    const uint64_t da = mkdesc(st + wg * 8192, 16, 1024), db = mkdesc(st + 16384, 8192, 1024);
                    wg_fence();
#pragma unroll
                    for (int ks = 0; ks < 4; ks++) wgmma_n128(acc, da + ks * 2, db + ks * 128, 1);
                    wg_commit();
                    wg_wait0();
                    if (lane == 0) mbar_arrive(bars + B_EMPTY + pp.stage * 8);
                    pipe_next(pp);
                }
            }
            CTR(4);
            if (type == J_UP2) {
                MBW(bars + B_STGFREE + wg * 8, stg_phase); stg_phase ^= 1;
#pragma unroll
                for (int j = 0; j < 4; j++) {
                    uint32_t r[4];
#pragma unroll
                    for (int q = 0; q < 4; q++) {
                        const uint32_t gw = pack2(acc[8 * j + 2 * q], acc[8 * j + 2 * q + 1]);
                        const uint32_t uw = pack2(acc[32 + 8 * j + 2 * q], acc[32 + 8 * j + 2 * q + 1]);
                        r[q] = hmul2(pack2(gelu_tanh(bflo(gw)), gelu_tanh(bfhi(gw))), uw);
                    }
                    stsm4(stg_base + (sx ^ (j << 5)), r[0], r[1], r[2], r[3]);
                }
            } else {
                MBW(bars + B_FULL + pp.stage * 8, pp.phase);
                const uint32_t st = sb + pp.stage * W_STAGE;
                MBW(bars + B_STGFREE + wg * 8, stg_phase); stg_phase ^= 1;
                const uint32_t* gb = (const uint32_t*)(g_mod + 5 * D_ + (ksplit ? cb >> 1 : cb) * 64) + t;
                const uint32_t xa = st + (ksplit ? 0 : wg * 8192) + (wl * 16 + g) * 128 + (g << 4) + t * 4;
#pragma unroll
                for (int j = 0; j < 4; j++) {
                    uint32_t r[4];
#pragma unroll
                    for (int q = 0; q < 4; q++) {
                        const int nt = 2 * j + (q >> 1);
                        const uint32_t xw = lds32((xa ^ ((nt & 7) << 4)) + (nt >> 3) * 16384 + (q & 1) * 1024);
                        r[q] = hadd2(xw, hmul2(__ldcg(gb + nt * 4), pack2(acc[8 * j + 2 * q], acc[8 * j + 2 * q + 1])));
                    }
                    stsm4(stg_base + (j >> 2) * 8192 + (sx ^ ((2 * j & 7) << 4)), r[0], r[1], r[2], r[3]);
                }
                __syncwarp();
                if (lane == 0) mbar_arrive(bars + B_EMPTY + pp.stage * 8);
                pipe_next(pp);
            }
            fence_async_smem();
            CTR(5);
            bar_arrive(NB_ST + wg, 160);
            continue;
        }
        float acc[128];
#pragma unroll
        for (int i = 0; i < 128; i++) acc[i] = 0.f;
        const int nk = type == J_O ? o_nk(rb) : 8;
#pragma unroll 1
        for (int kb = 0; kb < nk; kb++) {
            if (kb) MBW(bars + B_FULL + pp.stage * 8, pp.phase);
            const uint32_t st = sb + pp.stage * W_STAGE;
            const uint64_t da = mkdesc(st + wg * 8192, 16, 1024), db = mkdesc(st + 16384, 8192, 1024);
            wg_fence();
#pragma unroll
            for (int ks = 0; ks < 4; ks++) wgmma_n256(acc, da + ks * 2, db + ks * 128, 1);
            wg_commit();
            wg_wait0();
            if (lane == 0) mbar_arrive(bars + B_EMPTY + pp.stage * 8);
            pipe_next(pp);
        }
        CTR(4);
        if (type == J_QA) {
            uint32_t qf[64];
#pragma unroll
            for (int i = 0; i < 64; i++) qf[i] = pack2(acc[2 * i], acc[2 * i + 1]);
            const int sg = warp >> 1, half = warp & 1;
            const float sc = 0.08838834764831845f * 1.4426950408889634f;
            const uint32_t xoff = (sg >> 1) * 8192 + ((sg & 1) * 32 + l7) * 128;
            const uint32_t moff = 32768 + (sg * 8 + l7) * 128;
            const uint32_t kch = (l8 ^ l7) << 4;
            const uint32_t vch = ((l8 & 1) ^ l7) << 4;
            if (rb == NRB - 1 && (cb & 1)) {
#pragma unroll
                for (int i = 0; i < 32; i++) qf[i] = qf[32 + i];
            }
#pragma unroll 1
            for (int hh = rb == NRB - 1; hh < 2; hh++) {
                MBW(bars + B_FULL + pp.stage * 8, pp.phase);
                uint32_t st = sb + pp.stage * W_STAGE;
                float sa[5][4];
#pragma unroll
                for (int n = 0; n < 5; n++) sa[n][0] = sa[n][1] = sa[n][2] = sa[n][3] = 0.f;
#pragma unroll
                for (int i = 0; i < 4; i++) {
                    const uint32_t* q = qf + i * 8;
                    uint32_t kk[5][4];
                    ldsm4(kk[0][0], kk[0][1], kk[0][2], kk[0][3], st + moff + (i >> 1) * 4096 + (kch ^ ((i & 1) * 64)));
#pragma unroll
                    for (int n = 1; n < 5; n++)
                        ldsm4(kk[n][0], kk[n][1], kk[n][2], kk[n][3], st + xoff + (n - 1) * 1024 + (i >> 1) * 16384 + (kch ^ ((i & 1) * 64)));
#pragma unroll
                    for (int n = 0; n < 5; n++) mma16816(sa[n], q[0], q[1], q[2], q[3], kk[n][0], kk[n][1]);
#pragma unroll
                    for (int n = 0; n < 5; n++) mma16816(sa[n], q[4], q[5], q[6], q[7], kk[n][2], kk[n][3]);
                }
                __syncwarp();
                if (lane == 0) mbar_arrive(bars + B_EMPTY + pp.stage * 8);
                pipe_next(pp);
                const int iq0 = half * 16 + g - 2 * t, iq1 = iq0 + 8;
                float m0 = fmaxf(sa[0][0], sa[0][1]), m1 = fmaxf(sa[0][2], sa[0][3]);
#pragma unroll
                for (int n = 1; n < 5; n++) {
#pragma unroll
                    for (int e = 0; e < 2; e++) {
                        const int jx = (n - 1) * 8 + e;
                        if (jx > iq0) sa[n][e] = -3.0e38f;
                        if (jx > iq1) sa[n][2 + e] = -3.0e38f;
                        m0 = fmaxf(m0, sa[n][e]); m1 = fmaxf(m1, sa[n][2 + e]);
                    }
                }
                m0 = fmaxf(m0, __shfl_xor_sync(~0u, m0, 1)); m1 = fmaxf(m1, __shfl_xor_sync(~0u, m1, 1));
                m0 = fmaxf(m0, __shfl_xor_sync(~0u, m0, 2)); m1 = fmaxf(m1, __shfl_xor_sync(~0u, m1, 2));
                m0 *= -sc; m1 *= -sc;
                float l0 = 0.f, l1 = 0.f;
                uint32_t p0[5], p1[5];
#pragma unroll
                for (int n = 0; n < 5; n++) {
                    const float e0 = ex2(fmaf(sa[n][0], sc, m0)), e1 = ex2(fmaf(sa[n][1], sc, m0));
                    const float e2 = ex2(fmaf(sa[n][2], sc, m1)), e3 = ex2(fmaf(sa[n][3], sc, m1));
                    l0 += e0 + e1; l1 += e2 + e3;
                    p0[n] = pack2(e0, e1); p1[n] = pack2(e2, e3);
                }
                l0 += __shfl_xor_sync(~0u, l0, 1); l1 += __shfl_xor_sync(~0u, l1, 1);
                l0 += __shfl_xor_sync(~0u, l0, 2); l1 += __shfl_xor_sync(~0u, l1, 2);
                const float i0 = __fdividef(1.f, l0), i1 = __fdividef(1.f, l1);
                MBW(bars + B_FULL + pp.stage * 8, pp.phase);
                st = sb + pp.stage * W_STAGE;
                MBW(bars + B_STGFREE + wg * 8, stg_phase); stg_phase ^= 1;
#pragma unroll
                for (int i = 0; i < 32; i++) qf[i] = qf[32 + i];
#pragma unroll 1
                for (int bx = 0; bx < 2; bx++) {
                    float o[8][4];
                    uint32_t vm[8], v0[4][4], v1[4][4];
#pragma unroll
                    for (int ep = 0; ep < 4; ep++) {
                        ldsm2t(vm[2 * ep], vm[2 * ep + 1], st + moff + bx * 4096 + (vch ^ (ep << 5)));
                        const uint32_t va = st + xoff + (l8 >> 1) * 1024 + bx * 16384 + (vch ^ (ep << 5));
                        ldsm4t(v0[ep][0], v0[ep][1], v0[ep][2], v0[ep][3], va);
                        ldsm4t(v1[ep][0], v1[ep][1], v1[ep][2], v1[ep][3], va + 2048);
                    }
#pragma unroll
                    for (int n = 0; n < 8; n++) { o[n][0] = o[n][1] = o[n][2] = o[n][3] = 0.f; mma16816(o[n], p0[0], p1[0], p0[1], p1[1], vm[n], v0[n >> 1][n & 1]); }
#pragma unroll
                    for (int n = 0; n < 8; n++) mma16816(o[n], p0[2], p1[2], p0[3], p1[3], v0[n >> 1][2 + (n & 1)], v1[n >> 1][n & 1]);
#pragma unroll
                    for (int n = 0; n < 8; n++) mma1688(o[n], p0[4], p1[4], v1[n >> 1][2 + (n & 1)]);
#pragma unroll
                    for (int ep = 0; ep < 4; ep++)
                        stsm4(stg_base + bx * 8192 + (sx ^ (ep << 5)),
                              pack2(o[2 * ep][0] * i0, o[2 * ep][1] * i0), pack2(o[2 * ep][2] * i1, o[2 * ep][3] * i1),
                              pack2(o[2 * ep + 1][0] * i0, o[2 * ep + 1][1] * i0), pack2(o[2 * ep + 1][2] * i1, o[2 * ep + 1][3] * i1));
                }
                __syncwarp();
                if (lane == 0) mbar_arrive(bars + B_EMPTY + pp.stage * 8);
                pipe_next(pp);
                if (hh == 0) { fence_async_smem(); bar_arrive(NB_ST + wg, 160); }
            }
        } else if (type == J_UP) {
            MBW(bars + B_STGFREE + wg * 8, stg_phase); stg_phase ^= 1;
#pragma unroll
            for (int j = 0; j < 8; j++) {
                uint32_t r[4];
#pragma unroll
                for (int q = 0; q < 4; q++) {
                    const uint32_t gw = pack2(acc[8 * j + 2 * q], acc[8 * j + 2 * q + 1]);
                    const uint32_t uw = pack2(acc[64 + 8 * j + 2 * q], acc[64 + 8 * j + 2 * q + 1]);
                    r[q] = hmul2(pack2(gelu_tanh(bflo(gw)), gelu_tanh(bfhi(gw))), uw);
                }
                stsm4(stg_base + (j >> 2) * 8192 + (sx ^ ((2 * j & 7) << 4)), r[0], r[1], r[2], r[3]);
            }
        } else {
#pragma unroll
            for (int rd = 0; rd < 2; rd++) {
                MBW(bars + B_STGFREE + wg * 8, stg_phase); stg_phase ^= 1;
#pragma unroll
                for (int j = rd * 8; j < rd * 8 + 8; j++)
                    stsm4(stg_base + ((j >> 2) & 1) * 8192 + (sx ^ ((2 * j & 7) << 4)),
                          pack2(acc[8 * j], acc[8 * j + 1]), pack2(acc[8 * j + 2], acc[8 * j + 3]),
                          pack2(acc[8 * j + 4], acc[8 * j + 5]), pack2(acc[8 * j + 6], acc[8 * j + 7]));
                if (rd == 0) { fence_async_smem(); bar_arrive(NB_ST + wg, 160); }
            }
        }
        fence_async_smem();
        CTR(5);
        bar_arrive(NB_ST + wg, 160);
    }
}

__global__ void __launch_bounds__(384, 1) k_work(const __grid_constant__ Params p) {
    extern __shared__ __align__(1024) unsigned char smem_raw[];
    const uint32_t sb = smem_u32(smem_raw);
    if (sb & 1023) __trap();
    const int warp = __shfl_sync(~0u, threadIdx.x >> 5, 0);
    int lane; asm volatile("mov.u32 %0, %%laneid;" : "=r"(lane));
    if (threadIdx.x == 0) {
        const uint32_t bars = sb + SM_BAR;
        for (int i = 0; i < W_NST; i++) { mbar_init(bars + B_FULL + i * 8, 1); mbar_init(bars + B_EMPTY + i * 8, 8); }
        mbar_init(bars + B_STGFREE, 1); mbar_init(bars + B_STGFREE + 8, 1); mbar_init(bars + B_REQ, 1); mbar_init(bars + B_RSP, 1);
        asm volatile("fence.mbarrier_init.release.cluster;" ::: "memory");
    }
    __syncthreads();
    if (warp < 8) {
        asm volatile("setmaxnreg.inc.sync.aligned.u32 224;");
        consumer(p, sb, warp, lane);
    } else {
        asm volatile("setmaxnreg.dec.sync.aligned.u32 56;");
        if (warp == 8) { if (lane == 0) producer(p, sb); }
        else if (warp < 11) store_warp(p, sb, warp - 9, lane);
        else scheduler(p, sb, lane);
        __syncwarp();
        bar_sync(NB_W0, 128);
        if (warp == 8 && p.qmask == 0xff) {
            unsigned last = 0;
            if (lane == 0) { __threadfence(); last = atomicAdd(&g_flags[F_DONE], 1u) == gridDim.x - 1; }
            if (__shfl_sync(~0u, last, 0))
                for (int i = lane; i < F_TOTAL; i += 32) g_flags[i] = 0;
        }
    }
}

typedef CUresult (*EncodeFn)(CUtensorMap*, CUtensorMapDataType, cuuint32_t, void*, const cuuint64_t*, const cuuint64_t*,
                             const cuuint32_t*, const cuuint32_t*, CUtensorMapInterleave, CUtensorMapSwizzle,
                             CUtensorMapL2promotion, CUtensorMapFloatOOBfill);

static void make_map(EncodeFn enc, CUtensorMap* m, const void* ptr, uint64_t rows, uint64_t cols, uint32_t box_rows) {
    cuuint64_t dims[2] = {cols, rows};
    cuuint64_t strides[1] = {cols * 2};
    cuuint32_t box[2] = {64, box_rows};
    cuuint32_t es[2] = {1, 1};
    enc(m, CU_TENSOR_MAP_DATA_TYPE_BFLOAT16, 2, const_cast<void*>(ptr), dims, strides, box, es, CU_TENSOR_MAP_INTERLEAVE_NONE,
        CU_TENSOR_MAP_SWIZZLE_128B, CU_TENSOR_MAP_L2_PROMOTION_L2_256B, CU_TENSOR_MAP_FLOAT_OOB_FILL_NONE);
}
template <typename T> static void* sym_addr(T& sym) { void* p = nullptr; cudaGetSymbolAddress(&p, sym); return p; }

extern "C" void kernel_launch(void* const* d_in, const int* in_sizes, int n_in, void* d_out, int out_size) {
    static Params prm;
    static RecParams rp;
    static int n_sm = 132;
    static bool ready = false;
    static const void* key[14];
    bool same = ready;
    for (int i = 0; i < 13 && same; i++) same = key[i] == d_in[i];
    same = same && key[13] == d_out;
    if (!same) {
        void* fn = nullptr;
        cudaDriverEntryPointQueryResult qr;
        cudaGetDriverEntryPoint("cuTensorMapEncodeTiled", &fn, cudaEnableDefault, &qr);
        EncodeFn enc = (EncodeFn)fn;
        make_map(enc, &prm.tm_h, sym_addr(g_h), S_, D_, 64);
        make_map(enc, &prm.tm_kv, sym_addr(g_kv), S_, 2 * HD_, 64);
        make_map(enc, &rp.tm_kv32, sym_addr(g_kv), S_, 2 * HD_, 32);
        make_map(enc, &prm.tm_kvm, sym_addr(g_kvm), NSEG * 8, 2 * HD_, 32);
        make_map(enc, &prm.tm_o, sym_addr(g_o), S_, HD_, 64);
        make_map(enc, &prm.tm_op, sym_addr(g_op), OP_ROWS, D_, 64);
        make_map(enc, &prm.tm_h2, sym_addr(g_h2), S_, D_, 64);
        make_map(enc, &prm.tm_act, sym_addr(g_act), S_, DF_, 64);
        make_map(enc, &prm.tm_x1, sym_addr(g_x1), S_, D_, 64);
        make_map(enc, &prm.tm_out, d_out, S_, D_, 64);
        make_map(enc, &prm.tm_wq, d_in[2], D_, HD_, 64);
        make_map(enc, &prm.tm_wk, d_in[3], D_, HD_, 64);
        make_map(enc, &prm.tm_wv, d_in[4], D_, HD_, 64);
        make_map(enc, &prm.tm_wo, d_in[5], HD_, D_, 64);
        make_map(enc, &prm.tm_wg, d_in[8], D_, DF_, 64);
        make_map(enc, &prm.tm_wu, d_in[9], D_, DF_, 64);
        make_map(enc, &prm.tm_wd, d_in[10], DF_, D_, 64);
        prm.x = (const bf16*)d_in[0]; prm.c = (const bf16*)d_in[11]; prm.w_mod = (const bf16*)d_in[12];
        rp.mem0 = (const bf16*)d_in[1]; rp.x = prm.x; rp.c = prm.c; rp.w_mod = prm.w_mod;
        rp.wq = (const bf16*)d_in[2]; rp.wk = (const bf16*)d_in[3]; rp.wv = (const bf16*)d_in[4]; rp.wo = (const bf16*)d_in[5];
        cudaDeviceGetAttribute(&n_sm, cudaDevAttrMultiProcessorCount, 0);
        cudaFuncSetAttribute(k_work, cudaFuncAttributeMaxDynamicSharedMemorySize, SMEM_BYTES);
        cudaFuncSetAttribute(k_rec, cudaFuncAttributeMaxDynamicSharedMemorySize, R_SMEM);
        cudaFuncSetAttribute(k_rec, cudaFuncAttributeNonPortableClusterSizeAllowed, 1);
        {
            cudaLaunchConfig_t cfg = {};
            cfg.gridDim = dim3(128); cfg.blockDim = dim3(384); cfg.dynamicSmemBytes = R_SMEM;
            cudaLaunchAttribute at[1];
            at[0].id = cudaLaunchAttributeClusterDimension; at[0].val.clusterDim.x = 16; at[0].val.clusterDim.y = 1; at[0].val.clusterDim.z = 1;
            cfg.attrs = at; cfg.numAttrs = 1;
            int n = 0;
            cudaOccupancyMaxActiveClusters(&n, k_rec, &cfg);
            rp.ncl = n < 4 ? 4 : (n > 8 ? 8 : n);
        }
        for (int i = 0; i < 13; i++) key[i] = d_in[i];
        key[13] = d_out;
        ready = true;
    }
    cudaStream_t st = cudaStreamPerThread;
    auto launch_rec = [&]() {
        cudaLaunchConfig_t cfg = {};
        cfg.gridDim = dim3(16 * rp.ncl); cfg.blockDim = dim3(384); cfg.dynamicSmemBytes = R_SMEM; cfg.stream = st;
        cudaLaunchAttribute at[1];
        at[0].id = cudaLaunchAttributeClusterDimension; at[0].val.clusterDim.x = 16; at[0].val.clusterDim.y = 1; at[0].val.clusterDim.z = 1;
        cfg.attrs = at; cfg.numAttrs = 1;
        cudaLaunchKernelEx(&cfg, k_rec, rp);
    };
    auto launch_work = [&](int qmask, int pdl) {
        prm.qmask = qmask;
        cudaLaunchConfig_t cfg = {};
        cfg.gridDim = dim3(n_sm); cfg.blockDim = dim3(384); cfg.dynamicSmemBytes = SMEM_BYTES; cfg.stream = st;
        cudaLaunchAttribute at[1];
        at[0].id = cudaLaunchAttributeProgrammaticStreamSerialization; at[0].val.programmaticStreamSerializationAllowed = 1;
        cfg.attrs = at; cfg.numAttrs = pdl;
        cudaLaunchKernelEx(&cfg, k_work, prm);
    };
    launch_rec();
    launch_work(0xff, 1);
}
```
